```python
import torch

def _softmax(x, axis=-1):
    return torch.softmax(x, dim=axis)
def _gelu(x):
    return torch.nn.functional.gelu(x, approximate="tanh")
def _silu(x):
    return torch.nn.functional.silu(x)
def _sigmoid(x):
    return torch.sigmoid(x)
def _layernorm(x, axis=-1, eps=1e-5):
    m = x.mean(dim=axis, keepdim=True)
    v = x.var(dim=axis, keepdim=True, unbiased=False)
    return (x - m) / torch.sqrt(v + eps)
def _scatter_add(tgt, idx, src, axis=0):
    return tgt.clone().index_add_(axis, idx, src)
def _segment_sum(src, seg, n):
    out = torch.zeros((n,) + src.shape[1:], dtype=src.dtype)
    return out.index_add_(0, seg, src)
def _pad(x, pw):
    flat = tuple(v for pair in reversed(pw) for v in pair)
    return torch.nn.functional.pad(x, flat)

kernel_name = 'standalone__modern_conv_block_convnext_v2__vision'

def setup_inputs():

    _w = (lambda a: (lambda t: t.to(torch.bfloat16) if t.is_floating_point() else t)(torch.as_tensor(a)))
    H = W = 512
    C = 96
    K = 3
    return {
        "x": _w((lambda *s: torch.randn(*s, dtype=torch.bfloat16) * 0.05)(1, H, W, C)),
        "dw": _w((lambda *s: torch.randn(*s, dtype=torch.bfloat16) * 0.05)(K, K, C)),
        "w1": _w((lambda *s: torch.randn(*s, dtype=torch.bfloat16) * 0.05)(C, 4 * C)),
        "w2": _w((lambda *s: torch.randn(*s, dtype=torch.bfloat16) * 0.05)(4 * C, C)),
        "grn_gamma": _w((lambda *s: torch.randn(*s, dtype=torch.bfloat16) * 0.05)(4 * C)),
        "grn_beta": _w((lambda *s: torch.randn(*s, dtype=torch.bfloat16) * 0.05)(4 * C)),
    }

def reference(x, dw, w1, w2, grn_gamma, grn_beta):
    B, H, W, C = x.shape
    K = dw.shape[0]
    pad = K // 2
    xp = _pad(x, ((0,0),(pad,pad),(pad,pad),(0,0)))
    out = torch.zeros_like(x)
    for i in range(K):
        for j in range(K):
            out = out + xp[:, i:i+H, j:j+W, :] * dw[i, j][None, None, None, :]
    h = _layernorm(out, axis=-1)
    h = torch.einsum('bhwc,ce->bhwe', h, w1)
    h = _gelu(h)
    gx = torch.sqrt((h * h).sum(axis=(1, 2), keepdims=True) + 1e-6)
    nx = gx / (gx.mean(axis=-1, keepdims=True) + 1e-6)
    h = grn_gamma * (h * nx) + grn_beta + h
    h = torch.einsum('bhwe,ec->bhwc', h, w2)
    return x + h
```

```cpp
#include <cuda.h>
#include <cuda_runtime.h>
#include <cuda_bf16.h>
#include <stdint.h>

namespace {

constexpr int IMG_W = 512, CH = 96, EX = 384;
constexpr int TILE_PX = 64;
constexpr int ROWS_PER_CTA = 32;
constexpr int NUM_CTAS = 128;
constexpr int STEPS = ROWS_PER_CTA + 2;
constexpr int ROW_BYTES = IMG_W * CH * 2;

#define FORCE_EXACT 0
#define PREGS 200
#define CREGS 104
constexpr int PRODUCER_REGS = PREGS, CONSUMER_REGS = CREGS, EVEN_REGS = 128;

constexpr int XHALF_BYTES = 34 * 192;
constexpr int XHALF_B = XHALF_BYTES + 64;
constexpr int XROW_BYTES = XHALF_B + XHALF_BYTES + 64;
constexpr int L2_AHEAD = 2;
constexpr int NX = 3;
constexpr int TILE_BYTES = TILE_PX * 192;
constexpr int NY1 = 3;

constexpr uint32_t sb = 1024;
constexpr int SM_W1 = 0;
constexpr int SM_W2 = 73728;
constexpr int SM_RING = 147456;
constexpr int SM_Y1 = SM_RING;
constexpr int SM_X = SM_Y1 + NY1 * TILE_BYTES;
constexpr int SM_XS = SM_RING;
constexpr int SM_Y2 = SM_XS + 4 * TILE_BYTES;
constexpr int SM_STAT = SM_X + NX * XROW_BYTES;
constexpr int STAT_SLOT = TILE_PX * 8;
constexpr int SM_SEL = SM_STAT + NX * STAT_SLOT;
constexpr int SM_BIAS = SM_SEL + 512;
constexpr int SM_BPART = SM_BIAS + 384;
constexpr int SM_GAMMA = SM_BPART + 96 * 4;
constexpr int SM_BETA = SM_GAMMA + EX * 2;
constexpr int SM_RED = SM_BETA + EX * 2;
constexpr int SM_BAR = SM_RED + 16;
constexpr int SM_TOTAL = SM_BAR + 20 * 8;
static_assert(SM_Y2 + 2 * TILE_BYTES <= SM_STAT && SM_Y2 >= SM_X, "pass-2 y slots live in the pass-1 x ring");
static_assert(SM_TOTAL <= 232448, "smem budget");
static_assert(SM_STAT % 128 == 0 && SM_BIAS % 16 == 0 && SM_BAR % 8 == 0 && SM_X % 128 == 0, "alignment");

constexpr int BAR_XFULL = 0, BAR_Y1FULL = 3, BAR_Y1EMPTY = 6, BAR_Y2FULL = 9, BAR_XSFULL = 13, BAR_W1 = 17, BAR_W2 = 18,
              BAR_READY = 19;
static_assert(NX == NY1, "both rings are walked with one index");
constexpr int RED_EPOCH = 0, RED_W2MAX = 2;

constexpr float GELU_A = 0.32920349f;
constexpr uint32_t GELU_C_H2 = 0x40D940D9u;
constexpr float INV_2A = 1.0f / (2.0f * GELU_A);

constexpr uint32_t TAP_SCALE_BF2 = 0x2B802B80u;
constexpr float LN_EPS_SCALED = 1e-5f * 0x1p-80f;
constexpr float RSTD_SCALE = GELU_A * 0x1p-112f;

__device__ float g_sums[2][2][EX];
__device__ unsigned int g_count[2];
__device__ uint4 g_zero_row[66 * 192 / 16];

#define TS(k)

#define SPLITS 3
#define FENCE_HEAD(k) "{\n.reg .pred p;\n.reg .u32 t;\nsetp.ne.u32 p, %" #k ", 0;\n@p bra.uni GO;\nSTAY:\nld.volatile.shared.u32 t, [%" #k "];\n"
#define FENCE_TAIL "setp.ne.u32 p, t, 0;\n@p bra.uni STAY;\nGO:\n}\n"
template <int N> __device__ __forceinline__ void sched_fence(uint32_t* r, uint32_t key);
template <> __device__ __forceinline__ void sched_fence<2>(uint32_t* r, uint32_t key) {
    asm volatile(FENCE_HEAD(2) "mov.b32 %0, t;\nmov.b32 %1, t;\n" FENCE_TAIL
                 : "+r"(r[0]), "+r"(r[1]) : "r"(key) : "memory");
}
template <> __device__ __forceinline__ void sched_fence<4>(uint32_t* r, uint32_t key) {
    asm volatile(FENCE_HEAD(4) "mov.b32 %0, t;\nmov.b32 %1, t;\nmov.b32 %2, t;\nmov.b32 %3, t;\n" FENCE_TAIL
                 : "+r"(r[0]), "+r"(r[1]), "+r"(r[2]), "+r"(r[3]) : "r"(key) : "memory");
}
template <> __device__ __forceinline__ void sched_fence<6>(uint32_t* r, uint32_t key) {
    asm volatile(FENCE_HEAD(6) "mov.b32 %0, t;\nmov.b32 %1, t;\nmov.b32 %2, t;\nmov.b32 %3, t;\nmov.b32 %4, t;\nmov.b32 %5, t;\n" FENCE_TAIL
                 : "+r"(r[0]), "+r"(r[1]), "+r"(r[2]), "+r"(r[3]), "+r"(r[4]), "+r"(r[5]) : "r"(key) : "memory");
}
template <> __device__ __forceinline__ void sched_fence<8>(uint32_t* r, uint32_t key) {
    asm volatile(FENCE_HEAD(8) "mov.b32 %0, t;\nmov.b32 %1, t;\nmov.b32 %2, t;\nmov.b32 %3, t;\nmov.b32 %4, t;\nmov.b32 %5, t;\nmov.b32 %6, t;\nmov.b32 %7, t;\n" FENCE_TAIL
                 : "+r"(r[0]), "+r"(r[1]), "+r"(r[2]), "+r"(r[3]), "+r"(r[4]), "+r"(r[5]), "+r"(r[6]), "+r"(r[7]) : "r"(key) : "memory");
}
template <> __device__ __forceinline__ void sched_fence<10>(uint32_t* r, uint32_t key) {
    asm volatile(FENCE_HEAD(10) "mov.b32 %0, t;\nmov.b32 %1, t;\nmov.b32 %2, t;\nmov.b32 %3, t;\nmov.b32 %4, t;\nmov.b32 %5, t;\nmov.b32 %6, t;\nmov.b32 %7, t;\nmov.b32 %8, t;\nmov.b32 %9, t;\n" FENCE_TAIL
                 : "+r"(r[0]), "+r"(r[1]), "+r"(r[2]), "+r"(r[3]), "+r"(r[4]), "+r"(r[5]), "+r"(r[6]), "+r"(r[7]), "+r"(r[8]), "+r"(r[9]) : "r"(key) : "memory");
}
template <> __device__ __forceinline__ void sched_fence<12>(uint32_t* r, uint32_t key) {
    asm volatile(FENCE_HEAD(12) "mov.b32 %0, t;\nmov.b32 %1, t;\nmov.b32 %2, t;\nmov.b32 %3, t;\nmov.b32 %4, t;\nmov.b32 %5, t;\nmov.b32 %6, t;\nmov.b32 %7, t;\nmov.b32 %8, t;\nmov.b32 %9, t;\nmov.b32 %10, t;\nmov.b32 %11, t;\n" FENCE_TAIL
                 : "+r"(r[0]), "+r"(r[1]), "+r"(r[2]), "+r"(r[3]), "+r"(r[4]), "+r"(r[5]), "+r"(r[6]), "+r"(r[7]), "+r"(r[8]), "+r"(r[9]), "+r"(r[10]), "+r"(r[11]) : "r"(key) : "memory");
}
template <> __device__ __forceinline__ void sched_fence<24>(uint32_t* r, uint32_t key) {
    asm volatile(FENCE_HEAD(24) "mov.b32 %0, t;\nmov.b32 %1, t;\nmov.b32 %2, t;\nmov.b32 %3, t;\nmov.b32 %4, t;\nmov.b32 %5, t;\nmov.b32 %6, t;\nmov.b32 %7, t;\nmov.b32 %8, t;\nmov.b32 %9, t;\nmov.b32 %10, t;\nmov.b32 %11, t;\nmov.b32 %12, t;\nmov.b32 %13, t;\nmov.b32 %14, t;\nmov.b32 %15, t;\nmov.b32 %16, t;\nmov.b32 %17, t;\nmov.b32 %18, t;\nmov.b32 %19, t;\nmov.b32 %20, t;\nmov.b32 %21, t;\nmov.b32 %22, t;\nmov.b32 %23, t;\n" FENCE_TAIL
                 : "+r"(r[0]), "+r"(r[1]), "+r"(r[2]), "+r"(r[3]), "+r"(r[4]), "+r"(r[5]), "+r"(r[6]), "+r"(r[7]), "+r"(r[8]), "+r"(r[9]), "+r"(r[10]), "+r"(r[11]), "+r"(r[12]), "+r"(r[13]), "+r"(r[14]), "+r"(r[15]), "+r"(r[16]), "+r"(r[17]), "+r"(r[18]), "+r"(r[19]), "+r"(r[20]), "+r"(r[21]), "+r"(r[22]), "+r"(r[23]) : "r"(key) : "memory");
}
#define SPLIT(k, r) do { if ((SPLITS >> (k)) & 1) sched_fence<sizeof(r) / 4>(r, prm.ydesc); } while (0)

__device__ __forceinline__ void mbar_init(uint32_t bar, uint32_t count) {
    asm volatile("mbarrier.init.shared::cta.b64 [%0], %1;" ::"r"(bar), "r"(count) : "memory");
}
__device__ __forceinline__ void mbar_arrive_if(uint32_t bar, bool pred) {
    asm volatile("{\n.reg .pred p;\nsetp.ne.u32 p, %1, 0;\n@p mbarrier.arrive.shared::cta.b64 _, [%0];\n}\n"
                 ::"r"(bar), "r"((uint32_t)pred) : "memory");
}
__device__ __forceinline__ void mbar_wait(uint32_t bar, uint32_t parity) {
    asm volatile(
        "{\n.reg .pred p;\n.reg .u32 n;\n"
        "mbarrier.try_wait.parity.shared::cta.b64 p, [%0], %1;\n"
        "@p bra.uni WAIT_DONE;\n"
        "mov.u32 n, 0;\n"
        "WAIT_LOOP:\n"
        "mbarrier.try_wait.parity.shared::cta.b64 p, [%0], %1;\n"
        "@p bra.uni WAIT_DONE;\n"
        "mbarrier.try_wait.parity.shared::cta.b64 p, [%0], %1;\n"
        "@p bra.uni WAIT_DONE;\n"
        "mbarrier.try_wait.parity.shared::cta.b64 p, [%0], %1;\n"
        "@p bra.uni WAIT_DONE;\n"
        "add.u32 n, n, 1;\nsetp.lt.u32 p, n, 0x40000;\n"
        "@p bra.uni WAIT_LOOP;\n"
        "trap;\n"
        "WAIT_DONE:\n}\n"
        ::"r"(bar), "r"(parity) : "memory");
}
template <int PARITY> __device__ __forceinline__ void mbar_wait_c(uint32_t bar) {
    asm volatile(
        "{\n.reg .pred p;\n.reg .u32 n;\n"
        "mbarrier.try_wait.parity.shared::cta.b64 p, [%0], %1;\n"
        "@p bra.uni WAIT_DONE;\n"
        "mov.u32 n, 0;\n"
        "WAIT_LOOP:\n"
        "mbarrier.try_wait.parity.shared::cta.b64 p, [%0], %1;\n"
        "@p bra.uni WAIT_DONE;\n"
        "mbarrier.try_wait.parity.shared::cta.b64 p, [%0], %1;\n"
        "@p bra.uni WAIT_DONE;\n"
        "mbarrier.try_wait.parity.shared::cta.b64 p, [%0], %1;\n"
        "@p bra.uni WAIT_DONE;\n"
        "add.u32 n, n, 1;\nsetp.lt.u32 p, n, 0x40000;\n"
        "@p bra.uni WAIT_LOOP;\n"
        "trap;\n"
        "WAIT_DONE:\n}\n"
        ::"r"(bar), "n"(PARITY) : "memory");
}
__device__ __forceinline__ bool mbar_probe(uint32_t bar, uint32_t parity) {
    uint32_t ok;
    asm volatile("{\n.reg .pred p;\nmbarrier.test_wait.parity.shared::cta.b64 p, [%1], %2;\nselp.u32 %0, 1, 0, p;\n}\n"
                 : "=r"(ok) : "r"(bar), "r"(parity) : "memory");
    return ok;
}
__device__ __forceinline__ void mbar_wait2(uint32_t bar0, uint32_t parity0, uint32_t bar1, uint32_t parity1) {
    asm volatile(
        "{\n.reg .pred p, q;\n.reg .u32 n;\n"
        "mbarrier.try_wait.parity.shared::cta.b64 p, [%0], %1;\n"
        "mbarrier.try_wait.parity.shared::cta.b64 q, [%2], %3;\n"
        "and.pred p, p, q;\n"
        "@p bra.uni WAIT_DONE;\n"
        "mov.u32 n, 0;\n"
        "WAIT_LOOP:\n"
        "mbarrier.try_wait.parity.shared::cta.b64 p, [%0], %1;\n"
        "mbarrier.try_wait.parity.shared::cta.b64 q, [%2], %3;\n"
        "and.pred p, p, q;\n"
        "@p bra.uni WAIT_DONE;\n"
        "add.u32 n, n, 1;\nsetp.lt.u32 p, n, 0x80000;\n"
        "@p bra.uni WAIT_LOOP;\n"
        "trap;\n"
        "WAIT_DONE:\n}\n"
        ::"r"(bar0), "r"(parity0), "r"(bar1), "r"(parity1) : "memory");
}
#define ELECTED(body) "{\n.reg .pred p;\nelect.sync _|p, 0xffffffff;\n" body "}\n"
__device__ __forceinline__ void expect_tx(uint32_t bar, uint32_t bytes) {
    asm volatile(ELECTED("@p mbarrier.arrive.expect_tx.shared::cta.b64 _, [%0], %1;\n") ::"r"(bar), "r"(bytes) : "memory");
}
__device__ __forceinline__ void arrive_n(uint32_t bar, uint32_t count) {
    asm volatile(ELECTED("@p mbarrier.arrive.shared::cta.b64 _, [%0], %1;\n") ::"r"(bar), "r"(count) : "memory");
}
__device__ __forceinline__ void bulk_load(uint32_t dst, const void* src, uint32_t bytes, uint32_t bar) {
    asm volatile(ELECTED("@p cp.async.bulk.shared::cluster.global.mbarrier::complete_tx::bytes [%0], [%1], %2, [%3];\n")
                 ::"r"(dst), "l"(src), "r"(bytes), "r"(bar) : "memory");
}
__device__ __forceinline__ void bulk_store(void* dst, uint32_t src, uint32_t bytes) {
    asm volatile(ELECTED("@p cp.async.bulk.global.shared::cta.bulk_group [%0], [%1], %2;\n@p cp.async.bulk.commit_group;\n")
                 ::"l"(dst), "r"(src), "r"(bytes) : "memory");
}
__device__ __forceinline__ void bulk_prefetch(const void* src, uint32_t bytes) {
    asm volatile(ELECTED("@p cp.async.bulk.prefetch.L2.global [%0], %1;\n") ::"l"(src), "r"(bytes) : "memory");
}
__device__ __forceinline__ void tma_load_2d(uint32_t dst, const CUtensorMap* map, int c0, int c1, uint32_t bar) {
    asm volatile(ELECTED("@p cp.async.bulk.tensor.2d.shared::cluster.global.mbarrier::complete_tx::bytes [%0], [%1, {%2, %3}], [%4];\n")
                 ::"r"(dst), "l"(map), "r"(c0), "r"(c1), "r"(bar) : "memory");
}
template <int N> __device__ __forceinline__ void bulk_wait_read() {
    asm volatile("cp.async.bulk.wait_group.read %0;" ::"n"(N) : "memory");
}
__device__ __forceinline__ void bulk_wait_all() { asm volatile("cp.async.bulk.wait_group 0;" ::: "memory"); }
__device__ __forceinline__ void fence_async_smem() { asm volatile("fence.proxy.async.shared::cta;" ::: "memory"); }
__device__ __forceinline__ void named_sync(int id, int n) { asm volatile("bar.sync %0, %1;" ::"r"(id), "r"(n) : "memory"); }

__device__ __forceinline__ void lds64(uint32_t (&v)[2], uint32_t addr) {
    asm volatile("ld.shared.v2.b32 {%0,%1}, [%2];" : "=r"(v[0]), "=r"(v[1]) : "r"(addr));
}
__device__ __forceinline__ void sts64(uint32_t addr, uint32_t a, uint32_t b) {
    asm volatile("st.shared.v2.b32 [%0], {%1,%2};" ::"r"(addr), "r"(a), "r"(b) : "memory");
}
__device__ __forceinline__ void sts128(uint32_t addr, uint32_t a, uint32_t b, uint32_t c, uint32_t d) {
    asm volatile("st.shared.v4.b32 [%0], {%1,%2,%3,%4};" ::"r"(addr), "r"(a), "r"(b), "r"(c), "r"(d) : "memory");
}
__device__ __forceinline__ void ldsm4(uint32_t* r, uint32_t addr) {
    asm volatile("ldmatrix.sync.aligned.m8n8.x4.shared.b16 {%0,%1,%2,%3}, [%4];"
                 : "=r"(r[0]), "=r"(r[1]), "=r"(r[2]), "=r"(r[3]) : "r"(addr) : "memory");
}
__device__ __forceinline__ void ldsm4_t(uint32_t* r, uint32_t addr) {
    asm volatile("ldmatrix.sync.aligned.m8n8.x4.trans.shared.b16 {%0,%1,%2,%3}, [%4];"
                 : "=r"(r[0]), "=r"(r[1]), "=r"(r[2]), "=r"(r[3]) : "r"(addr) : "memory");
}
__device__ __forceinline__ void lds128(uint32_t* v, uint32_t addr) {
    asm volatile("ld.shared.v4.b32 {%0,%1,%2,%3}, [%4];"
                 : "=r"(v[0]), "=r"(v[1]), "=r"(v[2]), "=r"(v[3]) : "r"(addr) : "memory");
}
__device__ __forceinline__ uint32_t lds32(uint32_t addr) {
    uint32_t v; asm volatile("ld.shared.b32 %0, [%1];" : "=r"(v) : "r"(addr) : "memory"); return v;
}
__device__ __forceinline__ void sts32(uint32_t addr, uint32_t v) {
    asm volatile("st.shared.b32 [%0], %1;" ::"r"(addr), "r"(v) : "memory");
}

__device__ __forceinline__ uint32_t bf2_fma(uint32_t a, uint32_t b, uint32_t c) {
    uint32_t d; asm("fma.rn.bf16x2 %0, %1, %2, %3;" : "=r"(d) : "r"(a), "r"(b), "r"(c)); return d;
}
__device__ __forceinline__ uint32_t bf2_mul(uint32_t a, uint32_t b) {
    uint32_t d; asm("mul.rn.bf16x2 %0, %1, %2;" : "=r"(d) : "r"(a), "r"(b)); return d;
}
__device__ __forceinline__ uint32_t bf2_add(uint32_t a, uint32_t b) {
    uint32_t d; asm("add.rn.bf16x2 %0, %1, %2;" : "=r"(d) : "r"(a), "r"(b)); return d;
}
__device__ __forceinline__ uint32_t bf2_affine(uint32_t a, uint32_t sm) {
    uint32_t d;
    asm("{\n.reg .b16 l, h;\n.reg .b32 r, m;\nmov.b32 {l, h}, %2;\nmov.b32 r, {l, l};\nmov.b32 m, {h, h};\n"
        "fma.rn.bf16x2 %0, %1, r, m;\n}\n" : "=r"(d) : "r"(a), "r"(sm));
    return d;
}
__device__ __forceinline__ uint32_t bf2_rebias_h2(uint32_t v) { return (v & 0x7fff7fffu) * 7u + v; }
__device__ __forceinline__ uint32_t h2_fma(uint32_t a, uint32_t b, uint32_t c) {
    uint32_t d; asm("fma.rn.f16x2 %0, %1, %2, %3;" : "=r"(d) : "r"(a), "r"(b), "r"(c)); return d;
}
__device__ __forceinline__ uint32_t h2_mul(uint32_t a, uint32_t b) {
    uint32_t d; asm("mul.rn.f16x2 %0, %1, %2;" : "=r"(d) : "r"(a), "r"(b)); return d;
}
__device__ __forceinline__ uint32_t h2_tanh(uint32_t a) {
    uint32_t d; asm("tanh.approx.f16x2 %0, %1;" : "=r"(d) : "r"(a)); return d;
}
__device__ __forceinline__ float bf_lo(uint32_t v) { return __uint_as_float(v << 16); }
__device__ __forceinline__ float bf_hi(uint32_t v) { return __uint_as_float(v & 0xffff0000u); }
__device__ __forceinline__ uint32_t pack_h2(float lo, float hi) {
    uint32_t d; asm("cvt.rn.f16x2.f32 %0, %1, %2;" : "=r"(d) : "f"(hi), "f"(lo)); return d;
}
__device__ __forceinline__ uint32_t pack_bf2(float lo, float hi) {
    uint32_t d; asm("cvt.rn.bf16x2.f32 %0, %1, %2;" : "=r"(d) : "f"(hi), "f"(lo)); return d;
}
__device__ __forceinline__ void h2_unpack(uint32_t v, float& lo, float& hi) {
    asm("{\n.reg .b16 l, h;\nmov.b32 {l, h}, %2;\ncvt.f32.f16 %0, l;\ncvt.f32.f16 %1, h;\n}\n" : "=f"(lo), "=f"(hi) : "r"(v));
}
__device__ __forceinline__ uint32_t bf2_to_h2(uint32_t v) { return pack_h2(bf_lo(v), bf_hi(v)); }

__device__ __forceinline__ uint32_t gelu2(uint32_t z) {
    uint32_t p = h2_fma(z, z, GELU_C_H2);
    uint32_t t = h2_tanh(h2_mul(z, p));
    return h2_fma(z, t, z);
}

__device__ __forceinline__ void wg_fence() { asm volatile("wgmma.fence.sync.aligned;" ::: "memory"); }
__device__ __forceinline__ void wg_commit() { asm volatile("wgmma.commit_group.sync.aligned;" ::: "memory"); }
template <int N> __device__ __forceinline__ void wg_wait() {
    asm volatile("wgmma.wait_group.sync.aligned %0;" ::"n"(N) : "memory");
}
template <int N> __device__ __forceinline__ void pin(uint32_t (&r)[N]) {
#pragma unroll
    for (int i = 0; i < N; i++) asm volatile("" : "+r"(r[i])::"memory");
}
constexpr uint32_t desc_lo(uint32_t addr, uint32_t lbo) { return ((addr & 0x3FFFF) >> 4) | ((lbo >> 4) << 16); }
template <uint32_t SBO, uint32_t SWZ> __device__ __forceinline__ uint64_t desc(uint32_t lo, uint32_t bytes) {
    return (((uint64_t)((SBO >> 4) | (SWZ << 30)) << 32) | lo) + (bytes >> 4);
}
__device__ __forceinline__ uint32_t fresh_tid() {
    uint32_t v; asm volatile("mov.u32 %0, %%tid.x;" : "=r"(v));
    return v;
}
template <uint32_t V> __device__ __forceinline__ uint32_t loop_init() {
    uint32_t v; asm volatile("mov.u32 %0, %1;" : "=r"(v) : "n"(V)); return v;
}
__device__ __forceinline__ int fresh_warp() {
    int v; asm volatile("shfl.sync.idx.b32 %0, %1, 0, 0x1f, 0xffffffff;" : "=r"(v) : "r"(fresh_tid() >> 5)); return v;
}
__device__ __forceinline__ uint32_t fresh_cta() {
    uint32_t v; asm volatile("mov.u32 %0, %%ctaid.x;" : "=r"(v)); return v;
}
__device__ __forceinline__ float rsqrt_fast(float v) { float r; asm("rsqrt.approx.ftz.f32 %0, %1;" : "=f"(r) : "f"(v)); return r; }
__device__ __forceinline__ float sqrt_fast(float v) { float r; asm("sqrt.approx.f32 %0, %1;" : "=f"(r) : "f"(v)); return r; }

template <int TB>
__device__ __forceinline__ void wgmma_n64_h_set(uint32_t (&d)[16], const uint32_t* a, uint64_t desc) {
    asm volatile(
        "{\n.reg .pred p;\nsetp.ne.b32 p, 0, 0;\n"
        "wgmma.mma_async.sync.aligned.m64n64k16.f16.f16.f16 "
        "{%0,%1,%2,%3,%4,%5,%6,%7,%8,%9,%10,%11,%12,%13,%14,%15}, {%16,%17,%18,%19}, %20, p, 1, 1, %21;\n}\n"
        : "=r"(d[0]), "=r"(d[1]), "=r"(d[2]), "=r"(d[3]), "=r"(d[4]), "=r"(d[5]), "=r"(d[6]), "=r"(d[7]), "=r"(d[8]), "=r"(d[9]), "=r"(d[10]), "=r"(d[11]), "=r"(d[12]), "=r"(d[13]), "=r"(d[14]), "=r"(d[15])
        : "r"(a[0]), "r"(a[1]), "r"(a[2]), "r"(a[3]), "l"(desc), "n"(TB));
}
template <int TB>
__device__ __forceinline__ void wgmma_n64_h_acc(uint32_t (&d)[16], const uint32_t* a, uint64_t desc) {
    asm volatile(
        "{\n.reg .pred p;\nsetp.ne.b32 p, 1, 0;\n"
        "wgmma.mma_async.sync.aligned.m64n64k16.f16.f16.f16 "
        "{%0,%1,%2,%3,%4,%5,%6,%7,%8,%9,%10,%11,%12,%13,%14,%15}, {%16,%17,%18,%19}, %20, p, 1, 1, %21;\n}\n"
        : "+r"(d[0]), "+r"(d[1]), "+r"(d[2]), "+r"(d[3]), "+r"(d[4]), "+r"(d[5]), "+r"(d[6]), "+r"(d[7]), "+r"(d[8]), "+r"(d[9]), "+r"(d[10]), "+r"(d[11]), "+r"(d[12]), "+r"(d[13]), "+r"(d[14]), "+r"(d[15])
        : "r"(a[0]), "r"(a[1]), "r"(a[2]), "r"(a[3]), "l"(desc), "n"(TB));
}
__device__ __forceinline__ void wgmma_n64_h_acc_ss(uint32_t (&d)[16], uint64_t adesc, uint64_t desc) {
    asm volatile(
        "{\n.reg .pred p;\nsetp.ne.b32 p, 1, 0;\n"
        "wgmma.mma_async.sync.aligned.m64n64k16.f16.f16.f16 "
        "{%0,%1,%2,%3,%4,%5,%6,%7,%8,%9,%10,%11,%12,%13,%14,%15}, %16, %17, p, 1, 1, 1, 0;\n}\n"
        : "+r"(d[0]), "+r"(d[1]), "+r"(d[2]), "+r"(d[3]), "+r"(d[4]), "+r"(d[5]), "+r"(d[6]), "+r"(d[7]), "+r"(d[8]), "+r"(d[9]), "+r"(d[10]), "+r"(d[11]), "+r"(d[12]), "+r"(d[13]), "+r"(d[14]), "+r"(d[15])
        : "l"(adesc), "l"(desc));
}
__device__ __forceinline__ void wgmma_n96_h_acc(uint32_t (&d)[24], const uint32_t* a, uint64_t desc) {
    asm volatile(
        "{\n.reg .pred p;\nsetp.ne.b32 p, 1, 0;\n"
        "wgmma.mma_async.sync.aligned.m64n96k16.f16.f16.f16 "
        "{%0,%1,%2,%3,%4,%5,%6,%7,%8,%9,%10,%11,%12,%13,%14,%15,%16,%17,%18,%19,%20,%21,%22,%23}, {%24,%25,%26,%27}, %28, p, 1, 1, 1;\n}\n"
        : "+r"(d[0]), "+r"(d[1]), "+r"(d[2]), "+r"(d[3]), "+r"(d[4]), "+r"(d[5]), "+r"(d[6]), "+r"(d[7]), "+r"(d[8]), "+r"(d[9]), "+r"(d[10]), "+r"(d[11]), "+r"(d[12]), "+r"(d[13]), "+r"(d[14]), "+r"(d[15]), "+r"(d[16]), "+r"(d[17]), "+r"(d[18]), "+r"(d[19]), "+r"(d[20]), "+r"(d[21]), "+r"(d[22]), "+r"(d[23])
        : "r"(a[0]), "r"(a[1]), "r"(a[2]), "r"(a[3]), "l"(desc));
}

template <int ACC>
__device__ __forceinline__ void wgmma_n8(float (&d)[4], uint32_t a0, uint32_t a1, uint32_t a2, uint32_t a3, uint64_t desc) {
    if (ACC)
        asm volatile("{\n.reg .pred p;\nsetp.ne.b32 p, 1, 0;\n"
                     "wgmma.mma_async.sync.aligned.m64n8k16.f32.bf16.bf16 {%0,%1,%2,%3}, {%4,%5,%6,%7}, %8, p, 1, 1, 0;\n}\n"
                     : "+f"(d[0]), "+f"(d[1]), "+f"(d[2]), "+f"(d[3]) : "r"(a0), "r"(a1), "r"(a2), "r"(a3), "l"(desc));
    else
        asm volatile("{\n.reg .pred p;\nsetp.ne.b32 p, 0, 0;\n"
                     "wgmma.mma_async.sync.aligned.m64n8k16.f32.bf16.bf16 {%0,%1,%2,%3}, {%4,%5,%6,%7}, %8, p, 1, 1, 0;\n}\n"
                     : "=f"(d[0]), "=f"(d[1]), "=f"(d[2]), "=f"(d[3]) : "r"(a0), "r"(a1), "r"(a2), "r"(a3), "l"(desc));
}

struct Params {
    CUtensorMap w2_map;
    const __nv_bfloat16* x;
    const __nv_bfloat16* dw;
    const __nv_bfloat16* w1;
    const __nv_bfloat16* gamma;
    const __nv_bfloat16* beta;
    __nv_bfloat16* out;
    uint32_t w1desc, w2desc, ydesc, seldesc;
};

__device__ __forceinline__ uint32_t cta_tile0(uint32_t cta) {
    return (cta >> 3) * (ROWS_PER_CTA * ROW_BYTES) + (cta & 7) * TILE_BYTES;
}

struct Producer {
    uint32_t w[9][6];
    uint32_t xoff[2];
    uint32_t yoff[2][2];
    uint32_t stat, own;
    int lane, warp;
};

struct RowCopy {
    const char* x0;
    char* y0;
    uint32_t cut0, cut1;
    int first, last;
};
__device__ __forceinline__ RowCopy row_copy(const Params& prm) {
    const uint32_t cta = fresh_cta(), strip = cta & 7, t0 = cta_tile0(cta);
    RowCopy r;
    r.x0 = (const char*)prm.x + t0 - ROW_BYTES - 192;
    r.y0 = (char*)prm.out + t0;
    r.cut0 = strip == 0 ? 192 : 0;
    r.cut1 = strip == 7 ? 192 : 0;
    r.first = cta < 8 ? 1 : 0;
    r.last = cta >= NUM_CTAS - 8 ? STEPS - 2 : STEPS - 1;
    return r;
}
__device__ __forceinline__ void issue_row_load(const RowCopy& r, int i, uint32_t slot) {
    const char* src = (i >= r.first && i <= r.last) ? r.x0 + (uint32_t)i * ROW_BYTES : (const char*)g_zero_row;
    const uint32_t bar = sb + SM_BAR + (BAR_XFULL + slot) * 8, dst = sb + SM_X + slot * XROW_BYTES;
    expect_tx(bar, XHALF_BYTES - r.cut0);
    bulk_load(dst + r.cut0, src + r.cut0, XHALF_BYTES - r.cut0, bar);
    expect_tx(bar, XHALF_BYTES - r.cut1);
    bulk_load(dst + XHALF_B, src + 32 * 192, XHALF_BYTES - r.cut1, bar);
}

__device__ __forceinline__ float quad_sum(float v) {
    v += __shfl_xor_sync(0xffffffffu, v, 1);
    v += __shfl_xor_sync(0xffffffffu, v, 2);
    return v;
}

__device__ __forceinline__ void load_x(uint32_t (&v)[6][6], const Producer& c, uint32_t row) {
#pragma unroll
    for (int k = 0; k < 6; k++) {
        asm volatile("ld.shared.v4.b32 {%0,%1,%2,%3}, [%4];"
                     : "=r"(v[k][0]), "=r"(v[k][1]), "=r"(v[k][2]), "=r"(v[k][3]) : "r"(row + c.xoff[0] + k * 192));
        asm volatile("ld.shared.v2.b32 {%0,%1}, [%2];" : "=r"(v[k][4]), "=r"(v[k][5]) : "r"(row + c.xoff[1] + k * 192));
    }
}
template <int DY, int STRIDE>
__device__ __forceinline__ void conv_row(uint32_t (&dst)[24], const uint32_t* src, const uint32_t (&v)[6][6], const Producer& c) {
#pragma unroll
    for (int o = 0; o < 4; o++)
#pragma unroll
        for (int u = 0; u < 6; u++)
            dst[o * 6 + u] = bf2_fma(v[o + 2][u], c.w[3 * DY + 2][u], bf2_fma(v[o + 1][u], c.w[3 * DY + 1][u],
                             bf2_fma(v[o][u], c.w[3 * DY][u], STRIDE ? src[o * 6 + u] : src[2 * o + 1])));
}
__device__ __forceinline__ void start_sums(float (&d)[4], const uint32_t (&A)[24], const uint32_t (&q)[4], uint32_t sel) {
    wg_fence();
#pragma unroll
    for (int k = 0; k < 6; k++) {
        const int r = (k / 3) * 12 + (k % 3) * 2;
        if (k == 0) wgmma_n8<0>(d, A[r], A[r + 6], A[r + 1], A[r + 7], desc<128, 0>(sel, 0));
        else wgmma_n8<1>(d, A[r], A[r + 6], A[r + 1], A[r + 7], desc<128, 0>(sel, (k / 3) * 128));
    }
    wgmma_n8<1>(d, q[0], q[1], q[2], q[3], desc<128, 0>(sel + (8 << 16), 256));
    wg_commit();
}
__device__ __forceinline__ void finish_sums(float (&d)[4], int lane, float& sum, float& sq) {
    wg_wait<0>();
    asm volatile("" : "+f"(d[0]), "+f"(d[1]), "+f"(d[2]), "+f"(d[3])::"memory");
    sum = (lane & 1) ? d[2] : d[0];
    sq = (lane & 1) ? d[3] : d[1];
    sum += __shfl_xor_sync(0xffffffffu, sum, 4);
    sq += __shfl_xor_sync(0xffffffffu, sq, 4);
}

__device__ __forceinline__ void produce(const Producer& c, const Params& prm) {
    uint32_t A[24], B[24], C[24];
    const RowCopy rc = row_copy(prm);
    uint32_t st[8];
    uint32_t v[6][6];
    float d[4];
    {
        uint32_t ws[6], q[4] = {};
#pragma unroll
        for (int u = 0; u < 6; u++) {
            ws[u] = c.w[0][u];
#pragma unroll
            for (int t = 1; t < 9; t++) ws[u] = bf2_add(ws[u], c.w[t][u]);
        }
        mbar_wait_c<0>(sb + SM_BAR + (BAR_XFULL + rc.first) * 8);
        load_x(v, c, sb + SM_X + rc.first * XROW_BYTES);
#pragma unroll
        for (int r = 0; r < 24; r++) A[r] = bf2_mul(v[r / 6 + 1][r % 6], ws[r % 6]);
        start_sums(d, A, q, prm.seldesc);
        float e, sq;
        finish_sums(d, c.lane, e, sq);
        e *= -1.0f / CH;
#pragma unroll
        for (int k = 0; k < NX; k++) sts32(c.own + k * STAT_SLOT + 4, pack_bf2(e, e));
        __syncwarp();
        lds128(st, c.stat);
        lds128(st + 4, c.stat + 16);
#pragma unroll
        for (int r = 0; r < 24; r++) C[r] = 0;
    }
#pragma unroll 1
    for (int i = loop_init<0>();; i++) {
        mbar_wait_c<0>(sb + SM_BAR + (BAR_XFULL + i) * 8);
        load_x(v, c, sb + SM_X + i * XROW_BYTES);
        fence_async_smem();
        __syncwarp();
        mbar_arrive_if(sb + SM_BAR + (BAR_Y1FULL + i) * 8, c.lane == 0);
        if (c.warp == i) {
            mbar_wait_c<0>(sb + SM_BAR + (BAR_Y1FULL + i) * 8);
            issue_row_load(rc, i + NX, i);
        }
        if (i == 2) break;
        conv_row<1, 1>(B, C, v, c);
        conv_row<0, 0>(C, st, v, c);
    }
    if (c.warp == 3) {
        expect_tx(sb + SM_BAR + BAR_W2 * 8, CH * EX * 2 + EX * 4);
        bulk_load(sb + SM_GAMMA, prm.gamma, EX * 2, sb + SM_BAR + BAR_W2 * 8);
        bulk_load(sb + SM_BETA, prm.beta, EX * 2, sb + SM_BAR + BAR_W2 * 8);
#pragma unroll
        for (int k = 0; k < 6; k++)
            tma_load_2d(sb + SM_W2 + k * 12288, &prm.w2_map, 32 * (k >> 1), 192 * (k & 1), sb + SM_BAR + BAR_W2 * 8);
    }
    uint32_t slot = loop_init<0>(), phase = loop_init<1>();
#pragma unroll 1
    for (int t = loop_init<0>(); t < ROWS_PER_CTA; t++) {
        uint32_t q[4];
        conv_row<2, 1>(A, B, v, c);
#pragma unroll
        for (int r = 0; r < 24; r++) q[r / 6] = r % 6 == 0 ? bf2_mul(A[r], A[r]) : bf2_fma(A[r], A[r], q[r / 6]);
        start_sums(d, A, q, prm.seldesc);
        SPLIT(0, C);
        conv_row<1, 1>(B, C, v, c);
        const uint32_t so = slot * STAT_SLOT;
        const float used = bf_hi(lds32(c.own + so + 4));
        SPLIT(1, B);
        float sum, sq;
        finish_sums(d, c.lane, sum, sq);
        conv_row<0, 0>(C, st, v, c);
        const float mean = sum * (1.0f / CH);
        const float var = fmaxf(fmaf(sq, 1.0f / CH, -mean * mean), 0.0f);
        const float rs = rsqrt_fast(var + LN_EPS_SCALED) * RSTD_SCALE;
        sts64(c.own + so, pack_bf2(rs, -mean * rs), pack_bf2(used - mean, used - mean));
        __syncwarp();
        pin(C);
        lds128(st, c.stat + so);
        lds128(st + 4, c.stat + so + 16);
        mbar_wait2(sb + SM_BAR + (BAR_Y1EMPTY + slot) * 8, phase, sb + SM_BAR + (BAR_XFULL + slot) * 8,
                   t == ROWS_PER_CTA - 1 ? phase ^ 1 : phase);
        load_x(v, c, sb + SM_X + slot * XROW_BYTES);
        const uint32_t yb = sb + SM_Y1 + slot * TILE_BYTES;
#pragma unroll
        for (int r = 0; r < 24; r++) A[r] = bf2_affine(A[r], st[2 * (r / 6)]);
        SPLIT(2, A);
#pragma unroll
        for (int o = 0; o < 4; o++) {
            uint32_t y[6];
#pragma unroll
            for (int u = 0; u < 6; u++) y[u] = bf2_rebias_h2(A[o * 6 + u]);
            sts128(yb + c.yoff[0][o & 1] + (o >> 1) * 2048, y[0], y[1], y[2], y[3]);
            sts64(yb + c.yoff[1][o & 1] + (o >> 1) * 1024, y[4], y[5]);
        }
        fence_async_smem();
        __syncwarp();
        mbar_arrive_if(sb + SM_BAR + (BAR_Y1FULL + slot) * 8, c.lane == 0);
        if (++slot == NX) { slot = 0; phase ^= 1; }
    }
    mbar_arrive_if(sb + SM_BAR + (BAR_Y1FULL + ROWS_PER_CTA % NX) * 8, c.lane == 0);
}

struct Duty {
    const char* g;
    uint32_t s, bytes;
    int end, zero;
};
__device__ __forceinline__ Duty make_duty(const Params& prm, int wg, int w) {
    const RowCopy rc = row_copy(prm);
    Duty d;
    d.g = (w == 2 ? rc.y0 : rc.x0 + 2 * NX * ROW_BYTES + (w == 0 ? rc.cut0 : w == 1 ? 32 * 192 : 192 + L2_AHEAD * ROW_BYTES)) +
          (uint32_t)wg * ROW_BYTES;
    d.s = w == 2 ? sb + SM_Y1 + wg * TILE_BYTES : sb + SM_X + wg * XROW_BYTES + (w == 0 ? rc.cut0 : XHALF_B);
    d.bytes = w >= 2 ? TILE_BYTES : XHALF_BYTES - (w == 0 ? rc.cut0 : rc.cut1);
    d.end = w == 2 ? ROWS_PER_CTA : w < 2 ? STEPS - 2 * NX : rc.last + 1 - 2 * NX - L2_AHEAD;
    d.zero = rc.last + 1 - 2 * NX;
    return d;
}
__device__ __forceinline__ void run_duty(Duty& d, int n, int wg, int w) {
    if (n < d.end) {
        if (w < 2) {
            const uint32_t bar = sb + SM_BAR + (BAR_XFULL + wg) * 8;
            expect_tx(bar, d.bytes);
            bulk_load(d.s, n == d.zero ? (const char*)g_zero_row : d.g, d.bytes, bar);
        } else if (w == 2) {
            bulk_store((char*)d.g, d.s, TILE_BYTES);
        } else {
            bulk_prefetch(d.g, TILE_BYTES);
        }
    }
    d.g += NX * ROW_BYTES;
}

template <int M, bool LAST_SMEM = true>
__device__ __forceinline__ void gemm1_t(uint32_t (&d)[16], const uint32_t* wa, uint32_t yd, uint32_t wd) {
    wg_fence();
    wgmma_n64_h_set<0>(d, wa, desc<1024, 1>(yd, 0));
#pragma unroll
    for (int kk = 1; kk < (LAST_SMEM ? 5 : 6); kk++)
        wgmma_n64_h_acc<0>(d, wa + kk * 4, kk < 4 ? desc<1024, 1>(yd, kk * 32) : desc<512, 2>(yd, 8192 + (kk - 4) * 32));
    if (LAST_SMEM) wgmma_n64_h_acc_ss(d, desc<1024, 1>(wd, M * 12288), desc<512, 2>(yd, 8192 + 32));
    wg_commit();
}

#define GTAIL 0
__device__ __forceinline__ void gelu_sumsq_h(uint32_t (&d)[16], uint32_t (&q)[2], uint32_t key) {
#pragma unroll
    for (int r = 0; r < 16; r++) {
        if (GTAIL && r == 16 - GTAIL) sched_fence<GTAIL ? GTAIL : 2>(d + r, key);
        const uint32_t gv = gelu2(d[r]);
        q[r & 1] = h2_fma(gv, gv, q[r & 1]);
    }
}
__device__ __forceinline__ void flush_sumsq(uint32_t (&q)[2], float (&acc)[2]) {
#pragma unroll
    for (int h = 0; h < 2; h++) {
        float lo, hi;
        h2_unpack(q[h], lo, hi);
        acc[h] += lo + hi;
        q[h] = 0;
    }
}
__device__ __forceinline__ void gelu_sumsq_f(const uint32_t (&d)[16], float (&acc)[2]) {
#pragma unroll
    for (int r = 0; r < 16; r++) {
        float lo, hi;
        h2_unpack(gelu2(d[r]), lo, hi);
        acc[r & 1] = fmaf(lo, lo, acc[r & 1]);
        acc[r & 1] = fmaf(hi, hi, acc[r & 1]);
    }
}
__device__ __forceinline__ void load_w1t(uint32_t (&wa)[2][24], int wg, int w, int lane) {
#pragma unroll
    for (int m = 0; m < 2; m++)
#pragma unroll
        for (int kk = 0; kk < 5; kk++) {
            const int q = lane >> 3, c = 16 * kk + 8 * (q >> 1) + (lane & 7), ck = 2 * w + (q & 1);
            ldsm4_t(wa[m] + kk * 4, sb + SM_W1 + (2 * wg + m) * 12288 + c * 128 + ((ck ^ (c & 7)) * 16));
        }
}
__device__ __forceinline__ void publish_sums(const float (&acc)[2][2], float* sums, unsigned int* counter, int wg, int w, int lane) {
#pragma unroll
    for (int m = 0; m < 2; m++)
#pragma unroll
        for (int h = 0; h < 2; h++) {
            const float v = quad_sum(acc[m][h]);
            if ((lane & 3) == 0) atomicAdd(sums + 64 * (2 * wg + m) + 16 * w + (lane >> 2) + 8 * h, v);
        }
    named_sync(1, 384);
    if (fresh_tid() == 0) asm volatile("red.release.gpu.global.add.u32 [%0], 1;" ::"l"(counter) : "memory");
}
__device__ __forceinline__ void grid_wait(const unsigned int* counter, unsigned int target) {
    if (fresh_tid() == 0) {
        unsigned int v, spins = 0;
        do {
            asm volatile("ld.acquire.gpu.global.u32 %0, [%1];" : "=r"(v) : "l"(counter) : "memory");
            if (++spins > (1u << 22)) __trap();
        } while ((int)(v - target) < 0);
    }
    __syncthreads();
}

__device__ __forceinline__ void gemm1(uint32_t (&z)[16], const uint32_t (&a)[24], uint32_t w1d, int j) {
    wg_fence();
    wgmma_n64_h_set<1>(z, a, desc<1024, 1>(w1d, j * 12288));
#pragma unroll
    for (int kk = 1; kk < 6; kk++) wgmma_n64_h_acc<1>(z, a + kk * 4, desc<1024, 1>(w1d, j * 12288 + kk * 2048));
    wg_commit();
}
__device__ __forceinline__ void unpack_offsets(uint32_t (&o)[2], uint32_t packed) {
    asm volatile("and.b32 %0, %2, 0xffff;\nshr.u32 %1, %2, 16;" : "=r"(o[0]), "=r"(o[1]) : "r"(packed));
}
__device__ __forceinline__ void load_a(uint32_t (&a)[24], uint32_t wg, uint32_t offs) {
    uint32_t o[2];
    unpack_offsets(o, offs);
#pragma unroll
    for (int kk = 0; kk < 6; kk++) ldsm4(a + kk * 4, sb + SM_Y2 + (wg & 1) * TILE_BYTES + (o[kk >> 2] ^ ((kk & 3) * 32)));
}
__device__ __forceinline__ void init_bias(uint32_t (&o)[24], uint32_t addr) {
#pragma unroll
    for (int j = 0; j < 6; j++) lds128(o + 4 * j, addr + j * 64);
}

struct Pass2 {
    uint32_t wg;
    uint32_t off;
    uint32_t a_offs, xs_offs, bias_addr, out_scale;
    bool lead;
    uint32_t a[24], z[3][16], o[24];
};

__device__ __forceinline__ void refill_y(const Pass2& c, const Params& prm, int n, uint32_t off) {
    const uint32_t bars = sb + SM_BAR;
    fence_async_smem();
    named_sync(2 + c.wg, 128);
    if (c.lead && 4 * n + c.wg + 2 < ROWS_PER_CTA) {
        expect_tx(bars + (BAR_Y2FULL + (c.wg ^ 2)) * 8, TILE_BYTES);
        bulk_load(sb + SM_Y2 + (c.wg & 1) * TILE_BYTES, (const char*)prm.out + (off - 2 * ROW_BYTES), TILE_BYTES,
                  bars + (BAR_Y2FULL + (c.wg ^ 2)) * 8);
    }
}

__device__ __forceinline__ void start_first_tile(Pass2& c, const Params& prm) {
    const uint32_t bars = sb + SM_BAR;
    mbar_wait_c<0>(bars + (BAR_Y2FULL + c.wg) * 8);
    load_a(c.a, c.wg, c.a_offs);
    gemm1(c.z[0], c.a, prm.w1desc, 0);
    refill_y(c, prm, 0, c.off);
}

__device__ __forceinline__ void pass2_tile(Pass2& c, const Params& prm, int n) {
    const uint32_t xs = sb + SM_XS + c.wg * TILE_BYTES, xsfull = sb + SM_BAR + (BAR_XSFULL + c.wg) * 8;
#pragma unroll
    for (int j = 0; j < 6; j++) {
        uint32_t (&zc)[16] = c.z[j % 3];
        uint32_t (&zn)[16] = c.z[(j + 1) % 3];
        if (j == 0) wg_wait<0>(); else wg_wait<1>();
        pin(zc);
        if (j == 5) {
            pin(c.a);
            mbar_wait(sb + SM_BAR + (BAR_Y2FULL + c.wg) * 8, min(n + 1, ROWS_PER_CTA / 4 - 1) & 1);
            load_a(c.a, c.wg, c.a_offs);
        }
        const int jn = (j + 1) % 6;
#pragma unroll
        for (int sl = 0; sl < 4; sl++) {
#pragma unroll
            for (int r = 0; r < 4; r++) zc[sl * 4 + r] = gelu2(zc[sl * 4 + r]);
            wg_fence();
            wgmma_n96_h_acc(c.o, zc + sl * 4, desc<512, 2>(prm.w2desc, (j * 4 + sl) * 1024));
            if (sl < 2) {
#pragma unroll
                for (int kk = sl * 3; kk < sl * 3 + 3; kk++) {
                    if (kk == 0) wgmma_n64_h_set<1>(zn, c.a, desc<1024, 1>(prm.w1desc, jn * 12288));
                    else wgmma_n64_h_acc<1>(zn, c.a + kk * 4, desc<1024, 1>(prm.w1desc, jn * 12288 + kk * 2048));
                }
            }
            if (sl == 1) wg_commit();
        }
        wg_commit();
        if (j == 5) refill_y(c, prm, n + 1, c.off - 4 * ROW_BYTES);
        if (j == 1 && c.lead) {
            bulk_wait_read<0>();
            expect_tx(xsfull, TILE_BYTES);
            bulk_load(xs, (const char*)prm.x + c.off, TILE_BYTES, xsfull);
        }
    }
    wg_wait<0>();
    pin(c.o); pin(c.z[0]);
    mbar_wait(xsfull, n & 1);
    uint32_t xo[2];
    unpack_offsets(xo, c.xs_offs);
#pragma unroll
    for (int h = 0; h < 2; h++)
#pragma unroll
        for (int a = 0; a < 3; a++) {
            const uint32_t addr = xs + xo[h] + a * 64;
            uint32_t v[4];
            lds128(v, addr);
#pragma unroll
            for (int b = 0; b < 4; b++) {
                float lo, hi;
                h2_unpack(c.o[a * 8 + b * 2 + h], lo, hi);
                v[b] = bf2_fma(pack_bf2(lo, hi), c.out_scale, v[b]);
            }
            sts128(addr, v[0], v[1], v[2], v[3]);
        }
    init_bias(c.o, c.bias_addr);
    fence_async_smem();
    named_sync(2 + c.wg, 128);
    if (c.lead) bulk_store((char*)prm.out + c.off, xs, TILE_BYTES);
    c.off -= 4 * ROW_BYTES;
}

__device__ __forceinline__ float warp_sum(float v) {
#pragma unroll
    for (int s = 16; s >= 1; s >>= 1) v += __shfl_xor_sync(0xffffffffu, v, s);
    return v;
}
__device__ __forceinline__ float pow2f(int e) { return __uint_as_float((uint32_t)(e + 127) << 23); }
__device__ __forceinline__ int clamped_exponent(float v) {
    return min(max((int)((__float_as_uint(v) >> 23) & 0xff) - 127, -40), 40);
}

__device__ __forceinline__ void scan_w2(const Params& prm) {
    const uint32_t tid = fresh_tid() & 127, t = tid & 3;
    uint32_t be[48];
    mbar_wait_c<0>(sb + SM_BAR + BAR_W2 * 8);
#pragma unroll
    for (int k = 0; k < 48; k++) be[k] = lds32(sb + SM_BETA + (4 * k + t) * 4);
    float d[48];
#pragma unroll
    for (int k = 0; k < 48; k++) d[k] = 0.0f;
    wg_fence();
#pragma unroll
    for (int ks = 0; ks < 24; ks++)
        asm volatile(
            "{\n.reg .pred p;\nsetp.ne.b32 p, 1, 0;\n"
            "wgmma.mma_async.sync.aligned.m64n96k16.f32.bf16.bf16 {%0,%1,%2,%3,%4,%5,%6,%7,%8,%9,%10,%11,%12,%13,%14,%15,%16,%17,%18,%19,%20,%21,%22,%23,%24,%25,%26,%27,%28,%29,%30,%31,%32,%33,%34,%35,%36,%37,%38,%39,%40,%41,%42,%43,%44,%45,%46,%47}, {%48,%48,%49,%49}, %50, p, 1, 1, 1;\n}\n"
            : "+f"(d[0]), "+f"(d[1]), "+f"(d[2]), "+f"(d[3]), "+f"(d[4]), "+f"(d[5]), "+f"(d[6]), "+f"(d[7]), "+f"(d[8]), "+f"(d[9]), "+f"(d[10]), "+f"(d[11]), "+f"(d[12]), "+f"(d[13]), "+f"(d[14]), "+f"(d[15]), "+f"(d[16]), "+f"(d[17]), "+f"(d[18]), "+f"(d[19]), "+f"(d[20]), "+f"(d[21]), "+f"(d[22]), "+f"(d[23]), "+f"(d[24]), "+f"(d[25]), "+f"(d[26]), "+f"(d[27]), "+f"(d[28]), "+f"(d[29]), "+f"(d[30]), "+f"(d[31]), "+f"(d[32]), "+f"(d[33]), "+f"(d[34]), "+f"(d[35]), "+f"(d[36]), "+f"(d[37]), "+f"(d[38]), "+f"(d[39]), "+f"(d[40]), "+f"(d[41]), "+f"(d[42]), "+f"(d[43]), "+f"(d[44]), "+f"(d[45]), "+f"(d[46]), "+f"(d[47])
            : "r"(be[2 * ks]), "r"(be[2 * ks + 1]), "l"(desc<512, 2>(prm.w2desc, ks * 1024)));
    wg_commit();
    uint32_t mx = 0;
#pragma unroll 4
    for (int k = 0; k < 36; k++) {
        uint32_t v[4];
        lds128(v, sb + SM_W2 + tid * 16 + k * 2048);
#pragma unroll
        for (int b = 0; b < 4; b++) asm("max.xorsign.abs.bf16x2 %0, %0, %1;" : "+r"(mx) : "r"(v[b]));
    }
    mx &= 0x7fff7fffu;
    mx = __reduce_max_sync(0xffffffffu, max(mx << 16, mx & 0xffff0000u));
    if ((tid & 31) == 0) asm volatile("red.shared.max.u32 [%0], %1;" ::"r"(sb + SM_RED + RED_W2MAX * 4), "r"(mx) : "memory");
    wg_wait<0>();
#pragma unroll
    for (int k = 0; k < 48; k++) asm volatile("" : "+f"(d[k])::"memory");
    if (tid < 4) {
#pragma unroll
        for (int jb = 0; jb < 12; jb++)
            sts64(sb + SM_BPART + (8 * jb + 2 * t) * 4, __float_as_uint(d[4 * jb]), __float_as_uint(d[4 * jb + 1]));
    }
}
__device__ __forceinline__ void fetch_w2_row(uint32_t (&u)[12][4], uint32_t row, uint32_t sw, uint32_t nrm2) {
#pragma unroll
    for (int a = 0; a < 3; a++) {
        uint32_t v[4][4];
#pragma unroll
        for (int k = 0; k < 4; k++) lds128(v[k], row + a * 24576 + ((k * 16) ^ sw));
#pragma unroll
        for (int b = 0; b < 4; b++)
#pragma unroll
            for (int k = 0; k < 4; k++) u[a * 4 + b][k] = bf2_to_h2(bf2_mul(v[k][b], nrm2));
    }
}

__device__ __forceinline__ bool grn_stats(float ss, float gm, float bt, float& gx, float& inv, int& eb) {
    const int warp = fresh_warp();
    gx = sqrt_fast(fmaf(ss, INV_2A * INV_2A, 1e-6f));
    const float rt = sqrt_fast(ss + 1.0f) * INV_2A;
    const float r[3] = {warp_sum(gx), warp_sum(rt + bt), warp_sum(rt * fabsf(gm) * gx)};
    if ((fresh_tid() & 31) == 0 && warp < 12) {
#pragma unroll
        for (int k = 0; k < 3; k++) sts32(sb + SM_STAT + (k * 12 + warp) * 4, __float_as_uint(r[k]));
    }
    const bool bad = __syncthreads_or(!(ss >= 16.0f && ss < 1e30f));
    float tot[3];
#pragma unroll
    for (int k = 0; k < 3; k++) {
        uint32_t v[12];
#pragma unroll
        for (int q = 0; q < 3; q++) lds128(v + 4 * q, sb + SM_STAT + k * 48 + q * 16);
        float p[4];
#pragma unroll
        for (int q = 0; q < 4; q++) p[q] = __uint_as_float(v[q]) + __uint_as_float(v[q + 4]) + __uint_as_float(v[q + 8]);
        tot[k] = (p[0] + p[1]) + (p[2] + p[3]);
    }
    inv = __fdividef(1.0f, fmaf(tot[0], 1.0f / EX, 1e-6f));
    eb = clamped_exponent(fmaf(tot[2], inv, tot[1])) - 13;
    return bad;
}

__device__ __forceinline__ float exact_sums(const Params& prm, int e) {
    const int lane = fresh_tid() & 31, warp = fresh_warp(), wg = warp >> 2;
    const uint32_t epoch = lds32(sb + SM_RED + (RED_EPOCH + 1) * 4), bar = sb + SM_BAR + BAR_W1 * 8;
    if (wg < 3) {
        uint32_t wa[2][24], d[2][16];
        float acc[2][2] = {};
        const uint32_t yd = prm.ydesc, wd = prm.w1desc + ((2 * wg * 12288 + 5 * 2048) >> 4);
        load_w1t(wa, wg, warp & 3, lane);
#pragma unroll 1
        for (int n = 0; n < ROWS_PER_CTA; n++) {
            if (warp == 0) {
                expect_tx(bar, TILE_BYTES);
                bulk_load(sb + SM_Y1, (const char*)prm.out + cta_tile0(fresh_cta()) + n * ROW_BYTES, TILE_BYTES, bar);
            }
            mbar_wait(bar, (n + 1) & 1);
            gemm1_t<0>(d[0], wa[0], yd, wd);
            gemm1_t<1>(d[1], wa[1], yd, wd);
            wg_wait<0>();
            pin(d[0]); pin(d[1]);
            gelu_sumsq_f(d[0], acc[0]);
            gelu_sumsq_f(d[1], acc[1]);
            named_sync(1, 384);
        }
        publish_sums(acc, g_sums[1][epoch & 1], &g_count[1], wg, warp & 3, lane);
    }
    grid_wait(&g_count[1], (epoch + 1) * NUM_CTAS);
    return __ldcg(g_sums[1][epoch & 1] + e);
}

__global__ void __launch_bounds__(512, 1) convnext_kernel(const __grid_constant__ Params prm) {
    extern __shared__ __align__(1024) uint8_t smem[];
    if ((uint32_t)__cvta_generic_to_shared(smem) != sb) __trap();
    if (fresh_tid() < 32) TS(0);
    if (fresh_warp() == 0) {
        const RowCopy rc = row_copy(prm);
        if (fresh_tid() == 0) {
            mbar_init(sb + SM_BAR + BAR_XFULL * 8, 2);
            fence_async_smem();
        }
        __syncwarp();
        issue_row_load(rc, 0, 0);
        if (fresh_tid() == 0) {
#pragma unroll
            for (int k = 1; k <= BAR_W2; k++)
                mbar_init(sb + SM_BAR + k * 8, k < BAR_Y1FULL ? 2 : k < BAR_Y1EMPTY ? 4 : k < BAR_Y2FULL ? 12 : 1);
            mbar_init(sb + SM_BAR + BAR_READY * 8, 16);
            sts32(sb + SM_RED + RED_W2MAX * 4, 0);
            fence_async_smem();
        }
        __syncwarp();
#pragma unroll
        for (int s = 1; s <= NX; s++) {
            if (s == 1 + rc.first) {
                expect_tx(sb + SM_BAR + BAR_W1 * 8, CH * EX * 2);
#pragma unroll
                for (int k = 0; k < 3; k++)
                    bulk_load(sb + SM_W1 + k * 24576, (const char*)prm.w1 + k * 24576, 24576, sb + SM_BAR + BAR_W1 * 8);
            }
            if (s < NX) issue_row_load(rc, s, s);
        }
    }
    Producer pc;
    if (fresh_warp() >= 12) {
        const char* dw = (const char*)prm.dw + (fresh_tid() & 7) * 8;
#pragma unroll
        for (int tap = 0; tap < 9; tap++) {
            asm volatile("ld.global.nc.v4.b32 {%0,%1,%2,%3}, [%4];"
                         : "=r"(pc.w[tap][0]), "=r"(pc.w[tap][1]), "=r"(pc.w[tap][2]), "=r"(pc.w[tap][3])
                         : "l"(dw + (fresh_tid() & 7) * 8 + tap * CH * 2));
            asm volatile("ld.global.nc.v2.b32 {%0,%1}, [%2];"
                         : "=r"(pc.w[tap][4]), "=r"(pc.w[tap][5]) : "l"(dw + tap * CH * 2 + 128));
        }
    }
    if (fresh_tid() >= 96 && fresh_tid() < 128) {
        const uint32_t k = fresh_tid() - 96, n = k & 7, one = (n & 5) == ((k & 8) >> 1) + (k >> 4) ? 0x3f803f80u : 0u;
        sts128(sb + SM_SEL + k * 16, one, one, one, one);
        fence_async_smem();
    }
    if (fresh_tid() >= 32 && fresh_tid() < 32 + NX * 12 && ((blockIdx.x + 1) & 7) < 2) {
        const int k = fresh_tid() - 32;
        sts128(sb + SM_X + (k / 12) * XROW_BYTES + ((blockIdx.x & 7) == 0 ? 0 : XHALF_B + 33 * 192) + (k % 12) * 16, 0, 0, 0, 0);
    }
    __syncthreads();
    if (fresh_tid() < 32) TS(16);

    if (fresh_warp() >= 12) {
        TS(17);
        asm volatile("setmaxnreg.inc.sync.aligned.u32 %0;" ::"n"(PRODUCER_REGS));
        TS(18);
        const int w = fresh_warp() & 3, lane = fresh_tid() & 31;
        const int j = lane & 7, hb = (lane >> 3) & 1, base = 4 * (2 * w + (lane >> 4));
        pc.lane = lane; pc.warp = w;
        pc.xoff[0] = hb * XHALF_B + base * 192 + j * 16;
        pc.xoff[1] = hb * XHALF_B + base * 192 + 128 + j * 8;
        const int grp = 4 * w + (lane >> 3);
#pragma unroll
        for (int o = 0; o < 2; o++) {
            const int row = (grp & 7) + 8 * (o ^ hb) + 32 * (grp >> 3);
            pc.yoff[0][o] = row * 128 + ((j ^ (row & 7)) * 16);
            pc.yoff[1][o] = 8192 + row * 64 + (((j >> 1) ^ ((row >> 1) & 3)) * 16) + (j & 1) * 8;
        }
        pc.stat = sb + SM_STAT + grp * 32;
        pc.own = pc.stat + (lane & 3) * 8;
#pragma unroll
        for (int tap = 0; tap < 9; tap++)
#pragma unroll
            for (int u = 0; u < 6; u++) pc.w[tap][u] = bf2_mul(pc.w[tap][u], TAP_SCALE_BF2);
        TS(8);
        produce(pc, prm);
        TS(9);
        scan_w2(prm);
        TS(22);
        asm volatile("setmaxnreg.dec.sync.aligned.u32 %0;" ::"n"(EVEN_REGS));
    } else {
        asm volatile("setmaxnreg.dec.sync.aligned.u32 %0;" ::"n"(CONSUMER_REGS));
        if (fresh_tid() - 160 < 2) {
            const uint32_t k = fresh_tid() - 160;
            unsigned int cnt;
            asm volatile("ld.relaxed.gpu.global.u32 %0, [%1];" : "=r"(cnt) : "l"(&g_count[k]) : "memory");
            sts32(sb + SM_RED + (RED_EPOCH + k) * 4, cnt / NUM_CTAS);
        }
        __syncwarp();
        if (fresh_tid() < 32) TS(19);
        {
            const int tid = fresh_tid(), c0 = tid / 48, ec = tid % 48;
            const uint32_t dst = sb + SM_W1 + (ec >> 3) * 12288 + c0 * 128 + (((ec & 7) ^ (c0 & 7)) * 16);
            uint32_t v[12][4];
            mbar_wait_c<0>(sb + SM_BAR + BAR_W1 * 8);
            if (fresh_tid() < 32) TS(20);
#pragma unroll
            for (int it = 0; it < 12; it++) lds128(v[it], sb + SM_W1 + tid * 16 + it * 6144);
#pragma unroll
            for (int it = 0; it < 12; it++)
#pragma unroll
                for (int k = 0; k < 4; k++) v[it][k] = bf2_to_h2(v[it][k]);
#pragma unroll
            for (int it = 0; it < 12; it++) pin(v[it]);
            named_sync(1, 384);
#pragma unroll
            for (int it = 0; it < 12; it++) sts128(dst + it * 1024, v[it][0], v[it][1], v[it][2], v[it][3]);
            if (fresh_cta() < 2) g_sums[fresh_cta()][(lds32(sb + SM_RED + (RED_EPOCH + fresh_cta()) * 4) & 1) ^ 1][tid] = 0.0f;
            fence_async_smem();
            named_sync(1, 384);
            if (fresh_tid() < 32) TS(21);
        }

        const int tid = fresh_tid(), lane = tid & 31, wg = fresh_warp() >> 2, w = fresh_warp() & 3;
        uint32_t wa[2][24], d[2][16], q[2][2] = {};
        float acc[2][2] = {};
        load_w1t(wa, wg, w, lane);
        Duty duty = make_duty(prm, wg, w);
        if (wg == 0) TS(1);
        mbar_wait_c<0>(sb + SM_BAR + BAR_Y1FULL * 8);
        mbar_wait_c<1>(sb + SM_BAR + BAR_Y1FULL * 8);
        if (wg == 0) TS(2);
        uint32_t yd = prm.ydesc;
        const uint32_t wd = prm.w1desc + ((2 * wg * 12288 + 5 * 2048) >> 4);
        gemm1_t<0>(d[0], wa[0], yd, wd);
        uint32_t slot = loop_init<0>(), phase = loop_init<1>();
#pragma unroll 1
        for (int n = loop_init<0>(); n < ROWS_PER_CTA; n++) {
            if (wg == slot) {
                run_duty(duty, n, wg, w);
                flush_sumsq(q[0], acc[0]);
                flush_sumsq(q[1], acc[1]);
            }
            wg_wait<0>();
            pin(d[0]);
            gemm1_t<1>(d[1], wa[1], yd, wd);
            const uint32_t release = sb + SM_BAR + (BAR_Y1EMPTY + slot) * 8;
            if (++slot == NY1) { slot = 0; phase ^= 1; }
            yd = prm.ydesc + slot * (TILE_BYTES >> 4);
            gelu_sumsq_h(d[0], q[0], prm.ydesc);
            mbar_wait(sb + SM_BAR + (BAR_Y1FULL + slot) * 8, phase);
            wg_wait<0>();
            pin(d[1]);
            bulk_wait_read<0>();
            mbar_arrive_if(release, lane == 0);
            gemm1_t<0>(d[0], wa[0], yd, wd);
            gelu_sumsq_h(d[1], q[1], prm.ydesc);
        }
        flush_sumsq(q[0], acc[0]);
        flush_sumsq(q[1], acc[1]);
        wg_wait<0>();
        pin(d[0]);
        publish_sums(acc, g_sums[0][lds32(sb + SM_RED + RED_EPOCH * 4) & 1], &g_count[0], wg, w, lane);
        bulk_wait_all();
        if (wg == 0) TS(3);
        asm volatile("setmaxnreg.inc.sync.aligned.u32 %0;" ::"n"(EVEN_REGS));
    }

    uint32_t out_scale;
    {
        const int tid = fresh_tid(), lane = tid & 31, warp = fresh_warp(), e = min(tid, EX - 1);
        const uint32_t epoch = lds32(sb + SM_RED + RED_EPOCH * 4);
        __syncthreads();
        uint16_t gm16, bt16;
        asm volatile("ld.shared.u16 %0, [%1];" : "=h"(gm16) : "r"(sb + SM_GAMMA + e * 2) : "memory");
        asm volatile("ld.shared.u16 %0, [%1];" : "=h"(bt16) : "r"(sb + SM_BETA + e * 2) : "memory");
        const float gm = bf_lo(gm16), bt = fabsf(bf_lo(bt16));
        if (warp == 13) {
            const uint32_t last = cta_tile0(fresh_cta()) + (ROWS_PER_CTA - 1) * ROW_BYTES;
            for (int k = 0; k < 2; k++) {
                expect_tx(sb + SM_BAR + (BAR_Y2FULL + k) * 8, TILE_BYTES);
                bulk_load(sb + SM_Y2 + k * TILE_BYTES, (const char*)prm.out + (last - k * ROW_BYTES), TILE_BYTES,
                          sb + SM_BAR + (BAR_Y2FULL + k) * 8);
            }
        }
        const uint32_t w2row = sb + SM_W2 + e * 64, sw = ((e >> 1) & 3) * 16;
        const int ew = clamped_exponent(__uint_as_float(lds32(sb + SM_RED + RED_W2MAX * 4)));
        const uint32_t nrm2 = pack_bf2(pow2f(-ew), pow2f(-ew));
        uint32_t u[12][4], b[4];
        fetch_w2_row(u, w2row, sw, nrm2);
        const int jj = min(lane >> 2, 5);
        lds128(b, sb + SM_BPART + (32 * (jj >> 1) + 8 * (lane & 3) + 4 * (jj & 1)) * 4);
        grid_wait(&g_count[0], (epoch + 1) * NUM_CTAS);
        if (warp == 0) TS(4);
        float gx, inv;
        int eb;
        if (grn_stats(__ldcg(g_sums[0][epoch & 1] + e), gm, bt, gx, inv, eb) || FORCE_EXACT) {
            grn_stats(exact_sums(prm, e), gm, bt, gx, inv, eb);
            fetch_w2_row(u, w2row, sw, nrm2);
        }
        const float up = pow2f(ew + eb);
        out_scale = pack_bf2(up, up);
        if (warp < 12) {
            const float sc = fmaf(gm, gx * inv, 1.0f) * INV_2A * pow2f(-eb);
            const uint32_t s2 = pack_h2(sc, sc);
#pragma unroll
            for (int k = 0; k < 12; k++)
                sts128(w2row + (k >> 2) * 24576 + (((k & 3) * 16) ^ sw), h2_mul(u[k][0], s2), h2_mul(u[k][1], s2),
                       h2_mul(u[k][2], s2), h2_mul(u[k][3], s2));
        } else if (warp == 12 && lane < 24) {
            const float dn = pow2f(-(ew + eb));
            const uint32_t p0 = pack_h2(__uint_as_float(b[0]) * dn, __uint_as_float(b[1]) * dn);
            const uint32_t p1 = pack_h2(__uint_as_float(b[2]) * dn, __uint_as_float(b[3]) * dn);
            sts128(sb + SM_BIAS + lane * 16, p0, p0, p1, p1);
        }
        fence_async_smem();
        __syncwarp();
        mbar_arrive_if(sb + SM_BAR + BAR_READY * 8, lane == 0);
    }

    {
        Pass2 c;
        const int tid = fresh_tid(), lane = tid & 31, wg = fresh_warp() >> 2, w = fresh_warp() & 3;
        const int arow = 16 * w + (lane & 15);
        c.wg = wg;
        c.off = cta_tile0(fresh_cta()) + (ROWS_PER_CTA - 1 - wg) * ROW_BYTES;
        c.a_offs = (arow * 128 + (((lane >> 4) ^ (arow & 7)) * 16)) |
                   (8192 + arow * 64 + (((lane >> 4) ^ ((arow >> 1) & 3)) * 16)) << 16;
        const int g = lane >> 2, px = 33 * (g & 1) + 4 * (g >> 1) + 16 * (w >> 1) + 2 * (w & 1);
        c.xs_offs = (px * 192 + (lane & 3) * 16) | ((px ^ 1) * 192 + (lane & 3) * 16) << 16;
        c.bias_addr = sb + SM_BIAS + (lane & 3) * 16;
        c.out_scale = out_scale;
        c.lead = w == 0;
        if (wg == 0) TS(5);
        start_first_tile(c, prm);
        mbar_wait_c<0>(sb + SM_BAR + BAR_READY * 8);
        init_bias(c.o, c.bias_addr);
#pragma unroll 1
        for (int n = loop_init<0>(); n < ROWS_PER_CTA / 4; n++) pass2_tile(c, prm, n);
        bulk_wait_all();
        if (wg == 0) TS(6);
        if (wg == 3) TS(7);
    }
}

}

extern "C" void kernel_launch(void* const* d_in, const int* in_sizes, int n_in, void* d_out, int out_size) {
    (void)in_sizes; (void)n_in; (void)out_size;
    typedef CUresult (*EncodeFn)(CUtensorMap*, CUtensorMapDataType, cuuint32_t, void*, const cuuint64_t*, const cuuint64_t*,
                                 const cuuint32_t*, const cuuint32_t*, CUtensorMapInterleave, CUtensorMapSwizzle,
                                 CUtensorMapL2promotion, CUtensorMapFloatOOBfill);
    void* fn = nullptr;
    cudaDriverEntryPointQueryResult status;
    cudaGetDriverEntryPoint("cuTensorMapEncodeTiled", &fn, cudaEnableDefault, &status);
    const EncodeFn encode = (EncodeFn)fn;
    const cuuint32_t ones[2] = {1, 1};

    Params p;
    {
        const cuuint64_t dims[2] = {CH, EX}, strides[1] = {CH * 2};
        const cuuint32_t box[2] = {32, 192};
        encode(&p.w2_map, CU_TENSOR_MAP_DATA_TYPE_BFLOAT16, 2, d_in[3], dims, strides, box, ones,
               CU_TENSOR_MAP_INTERLEAVE_NONE, CU_TENSOR_MAP_SWIZZLE_64B, CU_TENSOR_MAP_L2_PROMOTION_NONE,
               CU_TENSOR_MAP_FLOAT_OOB_FILL_NONE);
    }
    p.x = (const __nv_bfloat16*)d_in[0];
    p.dw = (const __nv_bfloat16*)d_in[1];
    p.w1 = (const __nv_bfloat16*)d_in[2];
    p.gamma = (const __nv_bfloat16*)d_in[4];
    p.beta = (const __nv_bfloat16*)d_in[5];
    p.out = (__nv_bfloat16*)d_out;
    p.w1desc = desc_lo(sb + SM_W1, 12288);
    p.w2desc = desc_lo(sb + SM_W2, 24576);
    p.ydesc = desc_lo(sb + SM_Y1, 16);
    p.seldesc = desc_lo(sb + SM_SEL, 0);
    cudaFuncSetAttribute(convnext_kernel, cudaFuncAttributeMaxDynamicSharedMemorySize, SM_TOTAL);
    convnext_kernel<<<NUM_CTAS, 512, SM_TOTAL>>>(p);
}
```

```cpp
#include <cuda.h>
#include <cuda_runtime.h>
#include <cuda_bf16.h>
#include <stdint.h>

namespace {

constexpr int IMG_W = 512, CH = 96, EX = 384;
constexpr int TILE_PX = 64;
constexpr int ROWS_PER_CTA = 32;
constexpr int NUM_CTAS = 128;
constexpr int STEPS = ROWS_PER_CTA + 2;
constexpr int ROW_BYTES = IMG_W * CH * 2;

#define FORCE_EXACT 0
#define PREGS 200
#define CREGS 104
constexpr int PRODUCER_REGS = PREGS, CONSUMER_REGS = CREGS, EVEN_REGS = 128;

constexpr int XHALF_BYTES = 34 * 192;
constexpr int XHALF_B = XHALF_BYTES + 64;
constexpr int XROW_BYTES = XHALF_B + XHALF_BYTES + 64;
constexpr int L2_AHEAD = 2;
constexpr int NX = 3;
constexpr int TILE_BYTES = TILE_PX * 192;
constexpr int NY1 = 3;

constexpr uint32_t sb = 1024;
constexpr int SM_W1 = 0;
constexpr int SM_W2 = 73728;
constexpr int SM_RING = 147456;
constexpr int SLOT_BYTES = 26624;
constexpr int SM_Y1 = SM_RING;
constexpr int SM_X = SM_Y1 + TILE_BYTES;
constexpr int SM_STAT = SM_X + XROW_BYTES;
constexpr int SM_XFULL = SM_STAT + TILE_PX * 8, SM_Y1FULL = SM_XFULL + 8, SM_Y1EMPTY = SM_XFULL + 16;
constexpr int SM_XS = SM_RING;
constexpr int SM_Y2 = SM_XS + 4 * TILE_BYTES;
constexpr int SM_SEL = SM_RING + NX * SLOT_BYTES;
constexpr int SM_BIAS = SM_SEL + 512;
constexpr int SM_BPART = SM_BIAS + 384;
constexpr int SM_GAMMA = SM_BPART + 96 * 4;
constexpr int SM_BETA = SM_GAMMA + EX * 2;
constexpr int SM_RED = SM_BETA + EX * 2;
constexpr int SM_BAR = SM_RED + 16;
constexpr int SM_TOTAL = SM_BAR + 11 * 8;
static_assert(SM_Y1EMPTY + 8 <= SM_RING + SLOT_BYTES && SM_Y2 + 2 * TILE_BYTES <= SM_SEL, "ring layout");
static_assert(SM_TOTAL <= 232448, "smem budget");
static_assert(SM_STAT % 128 == 0 && SM_BIAS % 16 == 0 && SM_BAR % 8 == 0 && SLOT_BYTES % 1024 == 0, "alignment");

constexpr int BAR_Y2FULL = 0, BAR_XSFULL = 4, BAR_W1 = 8, BAR_W2 = 9, BAR_READY = 10;
static_assert(NX == NY1, "both rings are walked with one index");
constexpr int RED_EPOCH = 0, RED_W2MAX = 2;

constexpr float GELU_A = 0.32920349f;
constexpr uint32_t GELU_C_H2 = 0x40D940D9u;
constexpr float INV_2A = 1.0f / (2.0f * GELU_A);

constexpr uint32_t TAP_SCALE_BF2 = 0x2B802B80u;
constexpr float LN_EPS_SCALED = 1e-5f * 0x1p-80f;
constexpr float RSTD_SCALE = GELU_A * 0x1p-112f;

__device__ float g_sums[2][2][EX];
__device__ unsigned int g_count[2];
__device__ uint4 g_zero_row[66 * 192 / 16];

#define TS(k)

#define SPLITS 2
#define FENCE_HEAD(k) "{\n.reg .pred p;\n.reg .u32 t;\nsetp.ne.u32 p, %" #k ", 0;\n@p bra.uni GO;\nSTAY:\nld.volatile.shared.u32 t, [%" #k "];\n"
#define FENCE_TAIL "setp.ne.u32 p, t, 0;\n@p bra.uni STAY;\nGO:\n}\n"
template <int N> __device__ __forceinline__ void sched_fence(uint32_t* r, uint32_t key);
template <> __device__ __forceinline__ void sched_fence<2>(uint32_t* r, uint32_t key) {
    asm volatile(FENCE_HEAD(2) "mov.b32 %0, t;\nmov.b32 %1, t;\n" FENCE_TAIL
                 : "+r"(r[0]), "+r"(r[1]) : "r"(key) : "memory");
}
template <> __device__ __forceinline__ void sched_fence<4>(uint32_t* r, uint32_t key) {
    asm volatile(FENCE_HEAD(4) "mov.b32 %0, t;\nmov.b32 %1, t;\nmov.b32 %2, t;\nmov.b32 %3, t;\n" FENCE_TAIL
                 : "+r"(r[0]), "+r"(r[1]), "+r"(r[2]), "+r"(r[3]) : "r"(key) : "memory");
}
template <> __device__ __forceinline__ void sched_fence<6>(uint32_t* r, uint32_t key) {
    asm volatile(FENCE_HEAD(6) "mov.b32 %0, t;\nmov.b32 %1, t;\nmov.b32 %2, t;\nmov.b32 %3, t;\nmov.b32 %4, t;\nmov.b32 %5, t;\n" FENCE_TAIL
                 : "+r"(r[0]), "+r"(r[1]), "+r"(r[2]), "+r"(r[3]), "+r"(r[4]), "+r"(r[5]) : "r"(key) : "memory");
}
template <> __device__ __forceinline__ void sched_fence<8>(uint32_t* r, uint32_t key) {
    asm volatile(FENCE_HEAD(8) "mov.b32 %0, t;\nmov.b32 %1, t;\nmov.b32 %2, t;\nmov.b32 %3, t;\nmov.b32 %4, t;\nmov.b32 %5, t;\nmov.b32 %6, t;\nmov.b32 %7, t;\n" FENCE_TAIL
                 : "+r"(r[0]), "+r"(r[1]), "+r"(r[2]), "+r"(r[3]), "+r"(r[4]), "+r"(r[5]), "+r"(r[6]), "+r"(r[7]) : "r"(key) : "memory");
}
template <> __device__ __forceinline__ void sched_fence<10>(uint32_t* r, uint32_t key) {
    asm volatile(FENCE_HEAD(10) "mov.b32 %0, t;\nmov.b32 %1, t;\nmov.b32 %2, t;\nmov.b32 %3, t;\nmov.b32 %4, t;\nmov.b32 %5, t;\nmov.b32 %6, t;\nmov.b32 %7, t;\nmov.b32 %8, t;\nmov.b32 %9, t;\n" FENCE_TAIL
                 : "+r"(r[0]), "+r"(r[1]), "+r"(r[2]), "+r"(r[3]), "+r"(r[4]), "+r"(r[5]), "+r"(r[6]), "+r"(r[7]), "+r"(r[8]), "+r"(r[9]) : "r"(key) : "memory");
}
template <> __device__ __forceinline__ void sched_fence<12>(uint32_t* r, uint32_t key) {
    asm volatile(FENCE_HEAD(12) "mov.b32 %0, t;\nmov.b32 %1, t;\nmov.b32 %2, t;\nmov.b32 %3, t;\nmov.b32 %4, t;\nmov.b32 %5, t;\nmov.b32 %6, t;\nmov.b32 %7, t;\nmov.b32 %8, t;\nmov.b32 %9, t;\nmov.b32 %10, t;\nmov.b32 %11, t;\n" FENCE_TAIL
                 : "+r"(r[0]), "+r"(r[1]), "+r"(r[2]), "+r"(r[3]), "+r"(r[4]), "+r"(r[5]), "+r"(r[6]), "+r"(r[7]), "+r"(r[8]), "+r"(r[9]), "+r"(r[10]), "+r"(r[11]) : "r"(key) : "memory");
}
template <> __device__ __forceinline__ void sched_fence<24>(uint32_t* r, uint32_t key) {
    asm volatile(FENCE_HEAD(24) "mov.b32 %0, t;\nmov.b32 %1, t;\nmov.b32 %2, t;\nmov.b32 %3, t;\nmov.b32 %4, t;\nmov.b32 %5, t;\nmov.b32 %6, t;\nmov.b32 %7, t;\nmov.b32 %8, t;\nmov.b32 %9, t;\nmov.b32 %10, t;\nmov.b32 %11, t;\nmov.b32 %12, t;\nmov.b32 %13, t;\nmov.b32 %14, t;\nmov.b32 %15, t;\nmov.b32 %16, t;\nmov.b32 %17, t;\nmov.b32 %18, t;\nmov.b32 %19, t;\nmov.b32 %20, t;\nmov.b32 %21, t;\nmov.b32 %22, t;\nmov.b32 %23, t;\n" FENCE_TAIL
                 : "+r"(r[0]), "+r"(r[1]), "+r"(r[2]), "+r"(r[3]), "+r"(r[4]), "+r"(r[5]), "+r"(r[6]), "+r"(r[7]), "+r"(r[8]), "+r"(r[9]), "+r"(r[10]), "+r"(r[11]), "+r"(r[12]), "+r"(r[13]), "+r"(r[14]), "+r"(r[15]), "+r"(r[16]), "+r"(r[17]), "+r"(r[18]), "+r"(r[19]), "+r"(r[20]), "+r"(r[21]), "+r"(r[22]), "+r"(r[23]) : "r"(key) : "memory");
}
#define SPLIT(k, r) do { if ((SPLITS >> (k)) & 1) sched_fence<sizeof(r) / 4>(r, prm.ydesc); } while (0)

__device__ __forceinline__ void mbar_init(uint32_t bar, uint32_t count) {
    asm volatile("mbarrier.init.shared::cta.b64 [%0], %1;" ::"r"(bar), "r"(count) : "memory");
}
__device__ __forceinline__ void mbar_arrive_if(uint32_t bar, bool pred) {
    asm volatile("{\n.reg .pred p;\nsetp.ne.u32 p, %1, 0;\n@p mbarrier.arrive.shared::cta.b64 _, [%0];\n}\n"
                 ::"r"(bar), "r"((uint32_t)pred) : "memory");
}
__device__ __forceinline__ void mbar_wait(uint32_t bar, uint32_t parity) {
    asm volatile(
        "{\n.reg .pred p;\n.reg .u32 n;\n"
        "mbarrier.try_wait.parity.shared::cta.b64 p, [%0], %1;\n"
        "@p bra.uni WAIT_DONE;\n"
        "mov.u32 n, 0;\n"
        "WAIT_LOOP:\n"
        "mbarrier.try_wait.parity.shared::cta.b64 p, [%0], %1;\n"
        "@p bra.uni WAIT_DONE;\n"
        "mbarrier.try_wait.parity.shared::cta.b64 p, [%0], %1;\n"
        "@p bra.uni WAIT_DONE;\n"
        "mbarrier.try_wait.parity.shared::cta.b64 p, [%0], %1;\n"
        "@p bra.uni WAIT_DONE;\n"
        "add.u32 n, n, 1;\nsetp.lt.u32 p, n, 0x40000;\n"
        "@p bra.uni WAIT_LOOP;\n"
        "trap;\n"
        "WAIT_DONE:\n}\n"
        ::"r"(bar), "r"(parity) : "memory");
}
template <int PARITY> __device__ __forceinline__ void mbar_wait_c(uint32_t bar) {
    asm volatile(
        "{\n.reg .pred p;\n.reg .u32 n;\n"
        "mbarrier.try_wait.parity.shared::cta.b64 p, [%0], %1;\n"
        "@p bra.uni WAIT_DONE;\n"
        "mov.u32 n, 0;\n"
        "WAIT_LOOP:\n"
        "mbarrier.try_wait.parity.shared::cta.b64 p, [%0], %1;\n"
        "@p bra.uni WAIT_DONE;\n"
        "mbarrier.try_wait.parity.shared::cta.b64 p, [%0], %1;\n"
        "@p bra.uni WAIT_DONE;\n"
        "mbarrier.try_wait.parity.shared::cta.b64 p, [%0], %1;\n"
        "@p bra.uni WAIT_DONE;\n"
        "add.u32 n, n, 1;\nsetp.lt.u32 p, n, 0x40000;\n"
        "@p bra.uni WAIT_LOOP;\n"
        "trap;\n"
        "WAIT_DONE:\n}\n"
        ::"r"(bar), "n"(PARITY) : "memory");
}
__device__ __forceinline__ bool mbar_probe(uint32_t bar, uint32_t parity) {
    uint32_t ok;
    asm volatile("{\n.reg .pred p;\nmbarrier.test_wait.parity.shared::cta.b64 p, [%1], %2;\nselp.u32 %0, 1, 0, p;\n}\n"
                 : "=r"(ok) : "r"(bar), "r"(parity) : "memory");
    return ok;
}
__device__ __forceinline__ void mbar_wait2(uint32_t bar0, uint32_t parity0, uint32_t bar1, uint32_t parity1) {
    asm volatile(
        "{\n.reg .pred p, q;\n.reg .u32 n;\n"
        "mbarrier.try_wait.parity.shared::cta.b64 p, [%0], %1;\n"
        "mbarrier.try_wait.parity.shared::cta.b64 q, [%2], %3;\n"
        "and.pred p, p, q;\n"
        "@p bra.uni WAIT_DONE;\n"
        "mov.u32 n, 0;\n"
        "WAIT_LOOP:\n"
        "mbarrier.try_wait.parity.shared::cta.b64 p, [%0], %1;\n"
        "mbarrier.try_wait.parity.shared::cta.b64 q, [%2], %3;\n"
        "and.pred p, p, q;\n"
        "@p bra.uni WAIT_DONE;\n"
        "add.u32 n, n, 1;\nsetp.lt.u32 p, n, 0x80000;\n"
        "@p bra.uni WAIT_LOOP;\n"
        "trap;\n"
        "WAIT_DONE:\n}\n"
        ::"r"(bar0), "r"(parity0), "r"(bar1), "r"(parity1) : "memory");
}
#define ELECTED(body) "{\n.reg .pred p;\nelect.sync _|p, 0xffffffff;\n" body "}\n"
__device__ __forceinline__ void expect_tx(uint32_t bar, uint32_t bytes) {
    asm volatile(ELECTED("@p mbarrier.arrive.expect_tx.shared::cta.b64 _, [%0], %1;\n") ::"r"(bar), "r"(bytes) : "memory");
}
__device__ __forceinline__ void arrive_n(uint32_t bar, uint32_t count) {
    asm volatile(ELECTED("@p mbarrier.arrive.shared::cta.b64 _, [%0], %1;\n") ::"r"(bar), "r"(count) : "memory");
}
__device__ __forceinline__ void bulk_load(uint32_t dst, const void* src, uint32_t bytes, uint32_t bar) {
    asm volatile(ELECTED("@p cp.async.bulk.shared::cluster.global.mbarrier::complete_tx::bytes [%0], [%1], %2, [%3];\n")
                 ::"r"(dst), "l"(src), "r"(bytes), "r"(bar) : "memory");
}
__device__ __forceinline__ void bulk_store(void* dst, uint32_t src, uint32_t bytes) {
    asm volatile(ELECTED("@p cp.async.bulk.global.shared::cta.bulk_group [%0], [%1], %2;\n@p cp.async.bulk.commit_group;\n")
                 ::"l"(dst), "r"(src), "r"(bytes) : "memory");
}
__device__ __forceinline__ void bulk_prefetch(const void* src, uint32_t bytes) {
    asm volatile(ELECTED("@p cp.async.bulk.prefetch.L2.global [%0], %1;\n") ::"l"(src), "r"(bytes) : "memory");
}
__device__ __forceinline__ void tma_load_2d(uint32_t dst, const CUtensorMap* map, int c0, int c1, uint32_t bar) {
    asm volatile(ELECTED("@p cp.async.bulk.tensor.2d.shared::cluster.global.mbarrier::complete_tx::bytes [%0], [%1, {%2, %3}], [%4];\n")
                 ::"r"(dst), "l"(map), "r"(c0), "r"(c1), "r"(bar) : "memory");
}
template <int N> __device__ __forceinline__ void bulk_wait_read() {
    asm volatile("cp.async.bulk.wait_group.read %0;" ::"n"(N) : "memory");
}
__device__ __forceinline__ void bulk_wait_all() { asm volatile("cp.async.bulk.wait_group 0;" ::: "memory"); }
__device__ __forceinline__ void fence_async_smem() { asm volatile("fence.proxy.async.shared::cta;" ::: "memory"); }
__device__ __forceinline__ void named_sync(int id, int n) { asm volatile("bar.sync %0, %1;" ::"r"(id), "r"(n) : "memory"); }

__device__ __forceinline__ void lds64(uint32_t (&v)[2], uint32_t addr) {
    asm volatile("ld.shared.v2.b32 {%0,%1}, [%2];" : "=r"(v[0]), "=r"(v[1]) : "r"(addr));
}
__device__ __forceinline__ void sts64(uint32_t addr, uint32_t a, uint32_t b) {
    asm volatile("st.shared.v2.b32 [%0], {%1,%2};" ::"r"(addr), "r"(a), "r"(b) : "memory");
}
__device__ __forceinline__ void sts128(uint32_t addr, uint32_t a, uint32_t b, uint32_t c, uint32_t d) {
    asm volatile("st.shared.v4.b32 [%0], {%1,%2,%3,%4};" ::"r"(addr), "r"(a), "r"(b), "r"(c), "r"(d) : "memory");
}
__device__ __forceinline__ void ldsm4(uint32_t* r, uint32_t addr) {
    asm volatile("ldmatrix.sync.aligned.m8n8.x4.shared.b16 {%0,%1,%2,%3}, [%4];"
                 : "=r"(r[0]), "=r"(r[1]), "=r"(r[2]), "=r"(r[3]) : "r"(addr) : "memory");
}
__device__ __forceinline__ void ldsm4_t(uint32_t* r, uint32_t addr) {
    asm volatile("ldmatrix.sync.aligned.m8n8.x4.trans.shared.b16 {%0,%1,%2,%3}, [%4];"
                 : "=r"(r[0]), "=r"(r[1]), "=r"(r[2]), "=r"(r[3]) : "r"(addr) : "memory");
}
__device__ __forceinline__ void lds128(uint32_t* v, uint32_t addr) {
    asm volatile("ld.shared.v4.b32 {%0,%1,%2,%3}, [%4];"
                 : "=r"(v[0]), "=r"(v[1]), "=r"(v[2]), "=r"(v[3]) : "r"(addr) : "memory");
}
__device__ __forceinline__ uint32_t lds32(uint32_t addr) {
    uint32_t v; asm volatile("ld.shared.b32 %0, [%1];" : "=r"(v) : "r"(addr) : "memory"); return v;
}
__device__ __forceinline__ void sts32(uint32_t addr, uint32_t v) {
    asm volatile("st.shared.b32 [%0], %1;" ::"r"(addr), "r"(v) : "memory");
}

__device__ __forceinline__ uint32_t bf2_fma(uint32_t a, uint32_t b, uint32_t c) {
    uint32_t d; asm("fma.rn.bf16x2 %0, %1, %2, %3;" : "=r"(d) : "r"(a), "r"(b), "r"(c)); return d;
}
__device__ __forceinline__ uint32_t bf2_mul(uint32_t a, uint32_t b) {
    uint32_t d; asm("mul.rn.bf16x2 %0, %1, %2;" : "=r"(d) : "r"(a), "r"(b)); return d;
}
__device__ __forceinline__ uint32_t bf2_add(uint32_t a, uint32_t b) {
    uint32_t d; asm("add.rn.bf16x2 %0, %1, %2;" : "=r"(d) : "r"(a), "r"(b)); return d;
}
__device__ __forceinline__ uint32_t bf2_fma_hi(uint32_t a, uint32_t b, uint32_t c) {
    uint32_t d;
    asm("{\n.reg .b16 l, h;\n.reg .b32 m;\nmov.b32 {l, h}, %3;\nmov.b32 m, {h, h};\nfma.rn.bf16x2 %0, %1, %2, m;\n}\n"
        : "=r"(d) : "r"(a), "r"(b), "r"(c));
    return d;
}
__device__ __forceinline__ uint32_t bf2_affine(uint32_t a, uint32_t sm) {
    uint32_t d;
    asm("{\n.reg .b16 l, h;\n.reg .b32 r, m;\nmov.b32 {l, h}, %2;\nmov.b32 r, {l, l};\nmov.b32 m, {h, h};\n"
        "fma.rn.bf16x2 %0, %1, r, m;\n}\n" : "=r"(d) : "r"(a), "r"(sm));
    return d;
}
__device__ __forceinline__ uint32_t bf2_rebias_h2(uint32_t v) { return (v & 0x7fff7fffu) * 7u + v; }
__device__ __forceinline__ uint32_t h2_fma(uint32_t a, uint32_t b, uint32_t c) {
    uint32_t d; asm("fma.rn.f16x2 %0, %1, %2, %3;" : "=r"(d) : "r"(a), "r"(b), "r"(c)); return d;
}
__device__ __forceinline__ uint32_t h2_mul(uint32_t a, uint32_t b) {
    uint32_t d; asm("mul.rn.f16x2 %0, %1, %2;" : "=r"(d) : "r"(a), "r"(b)); return d;
}
__device__ __forceinline__ uint32_t h2_tanh(uint32_t a) {
    uint32_t d; asm("tanh.approx.f16x2 %0, %1;" : "=r"(d) : "r"(a)); return d;
}
__device__ __forceinline__ float bf_lo(uint32_t v) { return __uint_as_float(v << 16); }
__device__ __forceinline__ float bf_hi(uint32_t v) { return __uint_as_float(v & 0xffff0000u); }
__device__ __forceinline__ uint32_t pack_h2(float lo, float hi) {
    uint32_t d; asm("cvt.rn.f16x2.f32 %0, %1, %2;" : "=r"(d) : "f"(hi), "f"(lo)); return d;
}
__device__ __forceinline__ uint32_t pack_bf2(float lo, float hi) {
    uint32_t d; asm("cvt.rn.bf16x2.f32 %0, %1, %2;" : "=r"(d) : "f"(hi), "f"(lo)); return d;
}
__device__ __forceinline__ void h2_unpack(uint32_t v, float& lo, float& hi) {
    asm("{\n.reg .b16 l, h;\nmov.b32 {l, h}, %2;\ncvt.f32.f16 %0, l;\ncvt.f32.f16 %1, h;\n}\n" : "=f"(lo), "=f"(hi) : "r"(v));
}
__device__ __forceinline__ uint32_t bf2_to_h2(uint32_t v) { return pack_h2(bf_lo(v), bf_hi(v)); }

__device__ __forceinline__ uint32_t gelu2(uint32_t z) {
    uint32_t p = h2_fma(z, z, GELU_C_H2);
    uint32_t t = h2_tanh(h2_mul(z, p));
    return h2_fma(z, t, z);
}

__device__ __forceinline__ void wg_fence() { asm volatile("wgmma.fence.sync.aligned;" ::: "memory"); }
__device__ __forceinline__ void wg_commit() { asm volatile("wgmma.commit_group.sync.aligned;" ::: "memory"); }
template <int N> __device__ __forceinline__ void wg_wait() {
    asm volatile("wgmma.wait_group.sync.aligned %0;" ::"n"(N) : "memory");
}
template <int N> __device__ __forceinline__ void pin(uint32_t (&r)[N]) {
#pragma unroll
    for (int i = 0; i < N; i++) asm volatile("" : "+r"(r[i])::"memory");
}
constexpr uint32_t desc_lo(uint32_t addr, uint32_t lbo) { return ((addr & 0x3FFFF) >> 4) | ((lbo >> 4) << 16); }
template <uint32_t SBO, uint32_t SWZ> __device__ __forceinline__ uint64_t desc(uint32_t lo, uint32_t bytes) {
    return (((uint64_t)((SBO >> 4) | (SWZ << 30)) << 32) | lo) + (bytes >> 4);
}
__device__ __forceinline__ uint32_t fresh_tid() {
    uint32_t v; asm volatile("mov.u32 %0, %%tid.x;" : "=r"(v));
    return v;
}
template <uint32_t V> __device__ __forceinline__ uint32_t loop_init() {
    uint32_t v; asm volatile("mov.u32 %0, %1;" : "=r"(v) : "n"(V)); return v;
}
__device__ __forceinline__ int fresh_warp() {
    int v; asm volatile("shfl.sync.idx.b32 %0, %1, 0, 0x1f, 0xffffffff;" : "=r"(v) : "r"(fresh_tid() >> 5)); return v;
}
__device__ __forceinline__ uint32_t fresh_cta() {
    uint32_t v; asm volatile("mov.u32 %0, %%ctaid.x;" : "=r"(v)); return v;
}
__device__ __forceinline__ float rsqrt_fast(float v) { float r; asm("rsqrt.approx.ftz.f32 %0, %1;" : "=f"(r) : "f"(v)); return r; }
__device__ __forceinline__ float sqrt_fast(float v) { float r; asm("sqrt.approx.f32 %0, %1;" : "=f"(r) : "f"(v)); return r; }

template <int TB>
__device__ __forceinline__ void wgmma_n64_h_set(uint32_t (&d)[16], const uint32_t* a, uint64_t desc) {
    asm volatile(
        "{\n.reg .pred p;\nsetp.ne.b32 p, 0, 0;\n"
        "wgmma.mma_async.sync.aligned.m64n64k16.f16.f16.f16 "
        "{%0,%1,%2,%3,%4,%5,%6,%7,%8,%9,%10,%11,%12,%13,%14,%15}, {%16,%17,%18,%19}, %20, p, 1, 1, %21;\n}\n"
        : "=r"(d[0]), "=r"(d[1]), "=r"(d[2]), "=r"(d[3]), "=r"(d[4]), "=r"(d[5]), "=r"(d[6]), "=r"(d[7]), "=r"(d[8]), "=r"(d[9]), "=r"(d[10]), "=r"(d[11]), "=r"(d[12]), "=r"(d[13]), "=r"(d[14]), "=r"(d[15])
        : "r"(a[0]), "r"(a[1]), "r"(a[2]), "r"(a[3]), "l"(desc), "n"(TB));
}
template <int TB>
__device__ __forceinline__ void wgmma_n64_h_acc(uint32_t (&d)[16], const uint32_t* a, uint64_t desc) {
    asm volatile(
        "{\n.reg .pred p;\nsetp.ne.b32 p, 1, 0;\n"
        "wgmma.mma_async.sync.aligned.m64n64k16.f16.f16.f16 "
        "{%0,%1,%2,%3,%4,%5,%6,%7,%8,%9,%10,%11,%12,%13,%14,%15}, {%16,%17,%18,%19}, %20, p, 1, 1, %21;\n}\n"
        : "+r"(d[0]), "+r"(d[1]), "+r"(d[2]), "+r"(d[3]), "+r"(d[4]), "+r"(d[5]), "+r"(d[6]), "+r"(d[7]), "+r"(d[8]), "+r"(d[9]), "+r"(d[10]), "+r"(d[11]), "+r"(d[12]), "+r"(d[13]), "+r"(d[14]), "+r"(d[15])
        : "r"(a[0]), "r"(a[1]), "r"(a[2]), "r"(a[3]), "l"(desc), "n"(TB));
}
__device__ __forceinline__ void wgmma_n64_h_acc_ss(uint32_t (&d)[16], uint64_t adesc, uint64_t desc) {
    asm volatile(
        "{\n.reg .pred p;\nsetp.ne.b32 p, 1, 0;\n"
        "wgmma.mma_async.sync.aligned.m64n64k16.f16.f16.f16 "
        "{%0,%1,%2,%3,%4,%5,%6,%7,%8,%9,%10,%11,%12,%13,%14,%15}, %16, %17, p, 1, 1, 1, 0;\n}\n"
        : "+r"(d[0]), "+r"(d[1]), "+r"(d[2]), "+r"(d[3]), "+r"(d[4]), "+r"(d[5]), "+r"(d[6]), "+r"(d[7]), "+r"(d[8]), "+r"(d[9]), "+r"(d[10]), "+r"(d[11]), "+r"(d[12]), "+r"(d[13]), "+r"(d[14]), "+r"(d[15])
        : "l"(adesc), "l"(desc));
}
__device__ __forceinline__ void wgmma_n96_h_acc(uint32_t (&d)[24], const uint32_t* a, uint64_t desc) {
    asm volatile(
        "{\n.reg .pred p;\nsetp.ne.b32 p, 1, 0;\n"
        "wgmma.mma_async.sync.aligned.m64n96k16.f16.f16.f16 "
        "{%0,%1,%2,%3,%4,%5,%6,%7,%8,%9,%10,%11,%12,%13,%14,%15,%16,%17,%18,%19,%20,%21,%22,%23}, {%24,%25,%26,%27}, %28, p, 1, 1, 1;\n}\n"
        : "+r"(d[0]), "+r"(d[1]), "+r"(d[2]), "+r"(d[3]), "+r"(d[4]), "+r"(d[5]), "+r"(d[6]), "+r"(d[7]), "+r"(d[8]), "+r"(d[9]), "+r"(d[10]), "+r"(d[11]), "+r"(d[12]), "+r"(d[13]), "+r"(d[14]), "+r"(d[15]), "+r"(d[16]), "+r"(d[17]), "+r"(d[18]), "+r"(d[19]), "+r"(d[20]), "+r"(d[21]), "+r"(d[22]), "+r"(d[23])
        : "r"(a[0]), "r"(a[1]), "r"(a[2]), "r"(a[3]), "l"(desc));
}

template <int ACC>
__device__ __forceinline__ void wgmma_n8(float (&d)[4], uint32_t a0, uint32_t a1, uint32_t a2, uint32_t a3, uint64_t desc) {
    if (ACC)
        asm volatile("{\n.reg .pred p;\nsetp.ne.b32 p, 1, 0;\n"
                     "wgmma.mma_async.sync.aligned.m64n8k16.f32.bf16.bf16 {%0,%1,%2,%3}, {%4,%5,%6,%7}, %8, p, 1, 1, 0;\n}\n"
                     : "+f"(d[0]), "+f"(d[1]), "+f"(d[2]), "+f"(d[3]) : "r"(a0), "r"(a1), "r"(a2), "r"(a3), "l"(desc));
    else
        asm volatile("{\n.reg .pred p;\nsetp.ne.b32 p, 0, 0;\n"
                     "wgmma.mma_async.sync.aligned.m64n8k16.f32.bf16.bf16 {%0,%1,%2,%3}, {%4,%5,%6,%7}, %8, p, 1, 1, 0;\n}\n"
                     : "=f"(d[0]), "=f"(d[1]), "=f"(d[2]), "=f"(d[3]) : "r"(a0), "r"(a1), "r"(a2), "r"(a3), "l"(desc));
}

struct Params {
    CUtensorMap w2_map;
    const __nv_bfloat16* x;
    const __nv_bfloat16* dw;
    const __nv_bfloat16* w1;
    const __nv_bfloat16* gamma;
    const __nv_bfloat16* beta;
    __nv_bfloat16* out;
    uint64_t sel[3];
    uint32_t w1desc, w2desc, ydesc;
};

__device__ __forceinline__ uint32_t cta_tile0(uint32_t cta) {
    return (cta >> 3) * (ROWS_PER_CTA * ROW_BYTES) + (cta & 7) * TILE_BYTES;
}

struct Producer {
    uint32_t w[9][6];
    uint32_t xoff[2];
    uint32_t yoff[2][2];
    uint32_t stat, own;
    int lane, warp;
};

struct RowCopy {
    const char* x0;
    char* y0;
    uint32_t cut0, cut1;
    int first, last;
};
__device__ __forceinline__ RowCopy row_copy(const Params& prm) {
    const uint32_t cta = fresh_cta(), strip = cta & 7, t0 = cta_tile0(cta);
    RowCopy r;
    r.x0 = (const char*)prm.x + t0 - ROW_BYTES - 192;
    r.y0 = (char*)prm.out + t0;
    r.cut0 = strip == 0 ? 192 : 0;
    r.cut1 = strip == 7 ? 192 : 0;
    r.first = cta < 8 ? 1 : 0;
    r.last = cta >= NUM_CTAS - 8 ? STEPS - 2 : STEPS - 1;
    return r;
}
__device__ __forceinline__ void issue_row_load(const RowCopy& r, int i, uint32_t slot) {
    const char* src = (i >= r.first && i <= r.last) ? r.x0 + (uint32_t)i * ROW_BYTES : (const char*)g_zero_row;
    const uint32_t bar = sb + SM_XFULL + slot * SLOT_BYTES, dst = sb + SM_X + slot * SLOT_BYTES;
    expect_tx(bar, XHALF_BYTES - r.cut0);
    bulk_load(dst + r.cut0, src + r.cut0, XHALF_BYTES - r.cut0, bar);
    expect_tx(bar, XHALF_BYTES - r.cut1);
    bulk_load(dst + XHALF_B, src + 32 * 192, XHALF_BYTES - r.cut1, bar);
}

__device__ __forceinline__ float quad_sum(float v) {
    v += __shfl_xor_sync(0xffffffffu, v, 1);
    v += __shfl_xor_sync(0xffffffffu, v, 2);
    return v;
}

__device__ __forceinline__ void load_x(uint32_t (&v)[6][6], const Producer& c, uint32_t row) {
#pragma unroll
    for (int k = 0; k < 6; k++) {
        asm volatile("ld.shared.v4.b32 {%0,%1,%2,%3}, [%4];"
                     : "=r"(v[k][0]), "=r"(v[k][1]), "=r"(v[k][2]), "=r"(v[k][3]) : "r"(row + c.xoff[0] + k * 192));
        asm volatile("ld.shared.v2.b32 {%0,%1}, [%2];" : "=r"(v[k][4]), "=r"(v[k][5]) : "r"(row + c.xoff[1] + k * 192));
    }
}
template <int DY, int STRIDE>
__device__ __forceinline__ void conv_row(uint32_t (&dst)[24], const uint32_t* src, const uint32_t (&v)[6][6], const Producer& c) {
#pragma unroll
    for (int o = 0; o < 4; o++)
#pragma unroll
        for (int u = 0; u < 6; u++)
            dst[o * 6 + u] = bf2_fma(v[o + 2][u], c.w[3 * DY + 2][u], bf2_fma(v[o + 1][u], c.w[3 * DY + 1][u],
                             STRIDE ? bf2_fma(v[o][u], c.w[3 * DY][u], src[o * 6 + u])
                                    : bf2_fma_hi(v[o][u], c.w[3 * DY][u], src[2 * o + 1])));
}
__device__ __forceinline__ void start_sums(float (&d)[4], const uint32_t (&A)[24], const uint32_t (&q)[4], const Params& prm) {
    wg_fence();
#pragma unroll
    for (int k = 0; k < 6; k++) {
        const int r = (k / 3) * 12 + (k % 3) * 2;
        if (k == 0) wgmma_n8<0>(d, A[r], A[r + 6], A[r + 1], A[r + 7], prm.sel[0]);
        else wgmma_n8<1>(d, A[r], A[r + 6], A[r + 1], A[r + 7], prm.sel[k / 3]);
    }
    wgmma_n8<1>(d, q[0], q[1], q[2], q[3], prm.sel[2]);
    wg_commit();
}
__device__ __forceinline__ void finish_sums(float (&d)[4], int lane, float& sum, float& sq) {
    wg_wait<0>();
    asm volatile("" : "+f"(d[0]), "+f"(d[1]), "+f"(d[2]), "+f"(d[3])::"memory");
    sum = (lane & 1) ? d[2] : d[0];
    sq = (lane & 1) ? d[3] : d[1];
    sum += __shfl_xor_sync(0xffffffffu, sum, 4);
    sq += __shfl_xor_sync(0xffffffffu, sq, 4);
}

__device__ __forceinline__ void produce(const Producer& c, const Params& prm) {
    uint32_t A[24], B[24], C[24];
    const RowCopy rc = row_copy(prm);
    uint32_t st[8];
    uint32_t v[6][6];
    float d[4];
    {
        uint32_t ws[6], q[4] = {};
#pragma unroll
        for (int u = 0; u < 6; u++) {
            ws[u] = c.w[0][u];
#pragma unroll
            for (int t = 1; t < 9; t++) ws[u] = bf2_add(ws[u], c.w[t][u]);
        }
        mbar_wait_c<0>(sb + SM_XFULL + rc.first * SLOT_BYTES);
        load_x(v, c, sb + SM_X + rc.first * SLOT_BYTES);
#pragma unroll
        for (int r = 0; r < 24; r++) A[r] = bf2_mul(v[r / 6 + 1][r % 6], ws[r % 6]);
        start_sums(d, A, q, prm);
        float e, sq;
        finish_sums(d, c.lane, e, sq);
        e *= -1.0f / CH;
#pragma unroll
        for (int k = 0; k < NX; k++) sts32(c.own + k * SLOT_BYTES + 4, __float_as_uint(e));
        __syncwarp();
        lds128(st, c.stat);
        lds128(st + 4, c.stat + 16);
#pragma unroll
        for (int r = 0; r < 24; r++) C[r] = 0;
    }
#pragma unroll 1
    for (int i = loop_init<0>();; i++) {
        mbar_wait_c<0>(sb + SM_XFULL + i * SLOT_BYTES);
        load_x(v, c, sb + SM_X + i * SLOT_BYTES);
        fence_async_smem();
        if (c.warp == i) {
            named_sync(6 + i, 128);
            issue_row_load(rc, i + NX, i);
        } else {
            asm volatile("bar.arrive %0, 128;" ::"r"(6 + i) : "memory");
        }
        if (i == 2) break;
        conv_row<1, 1>(B, C, v, c);
        conv_row<0, 0>(C, st, v, c);
    }
    if (c.warp == 3) {
        expect_tx(sb + SM_BAR + BAR_W2 * 8, CH * EX * 2 + EX * 4);
        bulk_load(sb + SM_GAMMA, prm.gamma, EX * 2, sb + SM_BAR + BAR_W2 * 8);
        bulk_load(sb + SM_BETA, prm.beta, EX * 2, sb + SM_BAR + BAR_W2 * 8);
#pragma unroll
        for (int k = 0; k < 6; k++)
            tma_load_2d(sb + SM_W2 + k * 12288, &prm.w2_map, 32 * (k >> 1), 192 * (k & 1), sb + SM_BAR + BAR_W2 * 8);
    }
    uint32_t so = loop_init<0>(), phase = loop_init<1>();
#pragma unroll 1
    for (int t = loop_init<0>(); t < ROWS_PER_CTA; t++) {
        uint32_t q[4];
        conv_row<2, 1>(A, B, v, c);
#pragma unroll
        for (int r = 0; r < 24; r++) q[r / 6] = r % 6 == 0 ? bf2_mul(A[r], A[r]) : bf2_fma(A[r], A[r], q[r / 6]);
        start_sums(d, A, q, prm);
        SPLIT(0, C);
        conv_row<1, 1>(B, C, v, c);
        const float used = __uint_as_float(lds32(c.own + so + 4));
        SPLIT(1, B);
        float sum, sq;
        finish_sums(d, c.lane, sum, sq);
        conv_row<0, 0>(C, st, v, c);
        const float mean = sum * (1.0f / CH);
        const float var = fmaf(sq, 1.0f / CH, fmaf(-mean, mean, LN_EPS_SCALED));
        const float rs = rsqrt_fast(fmaxf(var, LN_EPS_SCALED)) * RSTD_SCALE;
        sts64(c.own + so, pack_bf2(rs, -mean * rs), __float_as_uint(used - mean));
        __syncwarp();
        pin(C);
        lds128(st, c.stat + so);
        lds128(st + 4, c.stat + so + 16);
        mbar_wait2(sb + SM_Y1EMPTY + so, phase, sb + SM_XFULL + so, phase);
        load_x(v, c, sb + SM_X + so);
        const uint32_t yb = sb + SM_Y1 + so;
#pragma unroll
        for (int r = 0; r < 24; r++) A[r] = bf2_affine(A[r], st[2 * (r / 6)]);
        SPLIT(2, A);
#pragma unroll
        for (int o = 0; o < 4; o++) {
            uint32_t y[6];
#pragma unroll
            for (int u = 0; u < 6; u++) y[u] = bf2_rebias_h2(A[o * 6 + u]);
            sts128(yb + c.yoff[0][o & 1] + (o >> 1) * 2048, y[0], y[1], y[2], y[3]);
            sts64(yb + c.yoff[1][o & 1] + (o >> 1) * 1024, y[4], y[5]);
        }
        fence_async_smem();
        __syncwarp();
        mbar_arrive_if(sb + SM_Y1FULL + so, c.lane == 0);
        if ((so += SLOT_BYTES) == NX * SLOT_BYTES) { so = 0; phase ^= 1; }
    }
    mbar_arrive_if(sb + SM_Y1FULL + ROWS_PER_CTA % NX * SLOT_BYTES, c.lane == 0);
}

struct Duty {
    const char* g;
    uint32_t s, bytes;
    int end, zero;
};
__device__ __forceinline__ Duty make_duty(const Params& prm, int wg, int w) {
    const RowCopy rc = row_copy(prm);
    Duty d;
    d.g = (w == 2 ? rc.y0 : rc.x0 + 2 * NX * ROW_BYTES + (w == 0 ? rc.cut0 : w == 1 ? 32 * 192 : 192 + L2_AHEAD * ROW_BYTES)) +
          (uint32_t)wg * ROW_BYTES;
    d.s = wg * SLOT_BYTES + (w == 2 ? sb + SM_Y1 : sb + SM_X + (w == 0 ? rc.cut0 : XHALF_B));
    d.bytes = w >= 2 ? TILE_BYTES : XHALF_BYTES - (w == 0 ? rc.cut0 : rc.cut1);
    d.end = w == 2 ? ROWS_PER_CTA : w < 2 ? STEPS + 1 - 2 * NX : rc.last + 1 - 2 * NX - L2_AHEAD;
    d.zero = rc.last + 1 - 2 * NX;
    return d;
}
__device__ __forceinline__ void run_duty(Duty& d, int n, int wg, int w) {
    if (n < d.end) {
        if (w < 2) {
            const uint32_t bar = sb + SM_XFULL + wg * SLOT_BYTES;
            expect_tx(bar, d.bytes);
            bulk_load(d.s, n >= d.zero ? (const char*)g_zero_row : d.g, d.bytes, bar);
        } else if (w == 2) {
            bulk_store((char*)d.g, d.s, TILE_BYTES);
        } else {
            bulk_prefetch(d.g, TILE_BYTES);
        }
    }
    d.g += NX * ROW_BYTES;
}

template <int M, bool LAST_SMEM = true>
__device__ __forceinline__ void gemm1_t(uint32_t (&d)[16], const uint32_t* wa, uint32_t yd, uint32_t wd) {
    wg_fence();
    wgmma_n64_h_set<0>(d, wa, desc<1024, 1>(yd, 0));
#pragma unroll
    for (int kk = 1; kk < (LAST_SMEM ? 5 : 6); kk++)
        wgmma_n64_h_acc<0>(d, wa + kk * 4, kk < 4 ? desc<1024, 1>(yd, kk * 32) : desc<512, 2>(yd, 8192 + (kk - 4) * 32));
    if (LAST_SMEM) wgmma_n64_h_acc_ss(d, desc<1024, 1>(wd, M * 12288), desc<512, 2>(yd, 8192 + 32));
    wg_commit();
}

#define GTAIL 0
__device__ __forceinline__ void gelu_sumsq_h(uint32_t (&d)[16], uint32_t (&q)[2], uint32_t key) {
#pragma unroll
    for (int r = 0; r < 16; r++) {
        if (GTAIL && r == 16 - GTAIL) sched_fence<GTAIL ? GTAIL : 2>(d + r, key);
        const uint32_t gv = gelu2(d[r]);
        q[r & 1] = h2_fma(gv, gv, q[r & 1]);
    }
}
__device__ __forceinline__ void flush_sumsq(uint32_t (&q)[2], float (&acc)[2]) {
#pragma unroll
    for (int h = 0; h < 2; h++) {
        float lo, hi;
        h2_unpack(q[h], lo, hi);
        acc[h] += lo + hi;
        q[h] = 0;
    }
}
__device__ __forceinline__ void gelu_sumsq_f(const uint32_t (&d)[16], float (&acc)[2]) {
#pragma unroll
    for (int r = 0; r < 16; r++) {
        float lo, hi;
        h2_unpack(gelu2(d[r]), lo, hi);
        acc[r & 1] = fmaf(lo, lo, acc[r & 1]);
        acc[r & 1] = fmaf(hi, hi, acc[r & 1]);
    }
}
__device__ __forceinline__ void load_w1t(uint32_t (&wa)[2][24], int wg, int w, int lane) {
#pragma unroll
    for (int m = 0; m < 2; m++)
#pragma unroll
        for (int kk = 0; kk < 5; kk++) {
            const int q = lane >> 3, c = 16 * kk + 8 * (q >> 1) + (lane & 7), ck = 2 * w + (q & 1);
            ldsm4_t(wa[m] + kk * 4, sb + SM_W1 + (2 * wg + m) * 12288 + c * 128 + ((ck ^ (c & 7)) * 16));
        }
}
__device__ __forceinline__ void publish_sums(const float (&acc)[2][2], float* sums, unsigned int* counter, int wg, int w, int lane) {
#pragma unroll
    for (int m = 0; m < 2; m++)
#pragma unroll
        for (int h = 0; h < 2; h++) {
            const float v = quad_sum(acc[m][h]);
            if ((lane & 3) == 0) atomicAdd(sums + 64 * (2 * wg + m) + 16 * w + (lane >> 2) + 8 * h, v);
        }
    named_sync(1, 384);
    if (fresh_tid() == 0) asm volatile("red.release.gpu.global.add.u32 [%0], 1;" ::"l"(counter) : "memory");
}
__device__ __forceinline__ void grid_wait(const unsigned int* counter, unsigned int target) {
    if (fresh_tid() == 0) {
        unsigned int v, spins = 0;
        do {
            asm volatile("ld.acquire.gpu.global.u32 %0, [%1];" : "=r"(v) : "l"(counter) : "memory");
            if (++spins > (1u << 22)) __trap();
        } while ((int)(v - target) < 0);
    }
    __syncthreads();
}

__device__ __forceinline__ void gemm1(uint32_t (&z)[16], const uint32_t (&a)[24], uint32_t w1d, int j) {
    wg_fence();
    wgmma_n64_h_set<1>(z, a, desc<1024, 1>(w1d, j * 12288));
#pragma unroll
    for (int kk = 1; kk < 6; kk++) wgmma_n64_h_acc<1>(z, a + kk * 4, desc<1024, 1>(w1d, j * 12288 + kk * 2048));
    wg_commit();
}
__device__ __forceinline__ void unpack_offsets(uint32_t (&o)[2], uint32_t packed) {
    asm volatile("and.b32 %0, %2, 0xffff;\nshr.u32 %1, %2, 16;" : "=r"(o[0]), "=r"(o[1]) : "r"(packed));
}
__device__ __forceinline__ void load_a(uint32_t (&a)[24], uint32_t wg, uint32_t offs) {
    uint32_t o[2];
    unpack_offsets(o, offs);
#pragma unroll
    for (int kk = 0; kk < 6; kk++) ldsm4(a + kk * 4, sb + SM_Y2 + (wg & 1) * TILE_BYTES + (o[kk >> 2] ^ ((kk & 3) * 32)));
}
__device__ __forceinline__ void init_bias(uint32_t (&o)[24], uint32_t addr) {
#pragma unroll
    for (int j = 0; j < 6; j++) lds128(o + 4 * j, addr + j * 64);
}

struct Pass2 {
    uint32_t wg;
    uint32_t off;
    uint32_t a_offs, xs_offs, bias_addr, out_scale;
    bool lead;
    uint32_t a[24], z[3][16], o[24];
};

__device__ __forceinline__ void refill_y(const Pass2& c, const Params& prm, int n, uint32_t off) {
    const uint32_t bars = sb + SM_BAR;
    fence_async_smem();
    named_sync(2 + c.wg, 128);
    if (c.lead && 4 * n + c.wg + 2 < ROWS_PER_CTA) {
        expect_tx(bars + (BAR_Y2FULL + (c.wg ^ 2)) * 8, TILE_BYTES);
        bulk_load(sb + SM_Y2 + (c.wg & 1) * TILE_BYTES, (const char*)prm.out + (off - 2 * ROW_BYTES), TILE_BYTES,
                  bars + (BAR_Y2FULL + (c.wg ^ 2)) * 8);
    }
}

__device__ __forceinline__ void start_first_tile(Pass2& c, const Params& prm) {
    const uint32_t bars = sb + SM_BAR;
    mbar_wait_c<0>(bars + (BAR_Y2FULL + c.wg) * 8);
    load_a(c.a, c.wg, c.a_offs);
    gemm1(c.z[0], c.a, prm.w1desc, 0);
    refill_y(c, prm, 0, c.off);
}

__device__ __forceinline__ void pass2_tile(Pass2& c, const Params& prm, int n) {
    const uint32_t xs = sb + SM_XS + c.wg * TILE_BYTES, xsfull = sb + SM_BAR + (BAR_XSFULL + c.wg) * 8;
#pragma unroll
    for (int j = 0; j < 6; j++) {
        uint32_t (&zc)[16] = c.z[j % 3];
        uint32_t (&zn)[16] = c.z[(j + 1) % 3];
        if (j == 0) wg_wait<0>(); else wg_wait<1>();
        pin(zc);
        if (j == 5) {
            pin(c.a);
            mbar_wait(sb + SM_BAR + (BAR_Y2FULL + c.wg) * 8, min(n + 1, ROWS_PER_CTA / 4 - 1) & 1);
            load_a(c.a, c.wg, c.a_offs);
        }
        const int jn = (j + 1) % 6;
#pragma unroll
        for (int sl = 0; sl < 4; sl++) {
#pragma unroll
            for (int r = 0; r < 4; r++) zc[sl * 4 + r] = gelu2(zc[sl * 4 + r]);
            wg_fence();
            wgmma_n96_h_acc(c.o, zc + sl * 4, desc<512, 2>(prm.w2desc, (j * 4 + sl) * 1024));
            if (sl < 2) {
#pragma unroll
                for (int kk = sl * 3; kk < sl * 3 + 3; kk++) {
                    if (kk == 0) wgmma_n64_h_set<1>(zn, c.a, desc<1024, 1>(prm.w1desc, jn * 12288));
                    else wgmma_n64_h_acc<1>(zn, c.a + kk * 4, desc<1024, 1>(prm.w1desc, jn * 12288 + kk * 2048));
                }
            }
            if (sl == 1) wg_commit();
        }
        wg_commit();
        if (j == 5) refill_y(c, prm, n + 1, c.off - 4 * ROW_BYTES);
        if (j == 1 && c.lead) {
            bulk_wait_read<0>();
            expect_tx(xsfull, TILE_BYTES);
            bulk_load(xs, (const char*)prm.x + c.off, TILE_BYTES, xsfull);
        }
    }
    wg_wait<0>();
    pin(c.o); pin(c.z[0]);
    mbar_wait(xsfull, n & 1);
    uint32_t xo[2];
    unpack_offsets(xo, c.xs_offs);
#pragma unroll
    for (int h = 0; h < 2; h++)
#pragma unroll
        for (int a = 0; a < 3; a++) {
            const uint32_t addr = xs + xo[h] + a * 64;
            uint32_t v[4];
            lds128(v, addr);
#pragma unroll
            for (int b = 0; b < 4; b++) {
                float lo, hi;
                h2_unpack(c.o[a * 8 + b * 2 + h], lo, hi);
                v[b] = bf2_fma(pack_bf2(lo, hi), c.out_scale, v[b]);
            }
            sts128(addr, v[0], v[1], v[2], v[3]);
        }
    init_bias(c.o, c.bias_addr);
    fence_async_smem();
    named_sync(2 + c.wg, 128);
    if (c.lead) bulk_store((char*)prm.out + c.off, xs, TILE_BYTES);
    c.off -= 4 * ROW_BYTES;
}

__device__ __forceinline__ float warp_sum(float v) {
#pragma unroll
    for (int s = 16; s >= 1; s >>= 1) v += __shfl_xor_sync(0xffffffffu, v, s);
    return v;
}
__device__ __forceinline__ float pow2f(int e) { return __uint_as_float((uint32_t)(e + 127) << 23); }
__device__ __forceinline__ int clamped_exponent(float v) {
    return min(max((int)((__float_as_uint(v) >> 23) & 0xff) - 127, -40), 40);
}

__device__ __forceinline__ void scan_w2(const Params& prm) {
    const uint32_t tid = fresh_tid() & 127, t = tid & 3;
    uint32_t be[48];
    mbar_wait_c<0>(sb + SM_BAR + BAR_W2 * 8);
#pragma unroll
    for (int k = 0; k < 48; k++) be[k] = lds32(sb + SM_BETA + (4 * k + t) * 4);
    float d[48];
#pragma unroll
    for (int k = 0; k < 48; k++) d[k] = 0.0f;
    wg_fence();
#pragma unroll
    for (int ks = 0; ks < 24; ks++)
        asm volatile(
            "{\n.reg .pred p;\nsetp.ne.b32 p, 1, 0;\n"
            "wgmma.mma_async.sync.aligned.m64n96k16.f32.bf16.bf16 {%0,%1,%2,%3,%4,%5,%6,%7,%8,%9,%10,%11,%12,%13,%14,%15,%16,%17,%18,%19,%20,%21,%22,%23,%24,%25,%26,%27,%28,%29,%30,%31,%32,%33,%34,%35,%36,%37,%38,%39,%40,%41,%42,%43,%44,%45,%46,%47}, {%48,%48,%49,%49}, %50, p, 1, 1, 1;\n}\n"
            : "+f"(d[0]), "+f"(d[1]), "+f"(d[2]), "+f"(d[3]), "+f"(d[4]), "+f"(d[5]), "+f"(d[6]), "+f"(d[7]), "+f"(d[8]), "+f"(d[9]), "+f"(d[10]), "+f"(d[11]), "+f"(d[12]), "+f"(d[13]), "+f"(d[14]), "+f"(d[15]), "+f"(d[16]), "+f"(d[17]), "+f"(d[18]), "+f"(d[19]), "+f"(d[20]), "+f"(d[21]), "+f"(d[22]), "+f"(d[23]), "+f"(d[24]), "+f"(d[25]), "+f"(d[26]), "+f"(d[27]), "+f"(d[28]), "+f"(d[29]), "+f"(d[30]), "+f"(d[31]), "+f"(d[32]), "+f"(d[33]), "+f"(d[34]), "+f"(d[35]), "+f"(d[36]), "+f"(d[37]), "+f"(d[38]), "+f"(d[39]), "+f"(d[40]), "+f"(d[41]), "+f"(d[42]), "+f"(d[43]), "+f"(d[44]), "+f"(d[45]), "+f"(d[46]), "+f"(d[47])
            : "r"(be[2 * ks]), "r"(be[2 * ks + 1]), "l"(desc<512, 2>(prm.w2desc, ks * 1024)));
    wg_commit();
    uint32_t mx = 0;
#pragma unroll 4
    for (int k = 0; k < 36; k++) {
        uint32_t v[4];
        lds128(v, sb + SM_W2 + tid * 16 + k * 2048);
#pragma unroll
        for (int b = 0; b < 4; b++) asm("max.xorsign.abs.bf16x2 %0, %0, %1;" : "+r"(mx) : "r"(v[b]));
    }
    mx &= 0x7fff7fffu;
    mx = __reduce_max_sync(0xffffffffu, max(mx << 16, mx & 0xffff0000u));
    if ((tid & 31) == 0) asm volatile("red.shared.max.u32 [%0], %1;" ::"r"(sb + SM_RED + RED_W2MAX * 4), "r"(mx) : "memory");
    wg_wait<0>();
#pragma unroll
    for (int k = 0; k < 48; k++) asm volatile("" : "+f"(d[k])::"memory");
    if (tid < 4) {
#pragma unroll
        for (int jb = 0; jb < 12; jb++)
            sts64(sb + SM_BPART + (8 * jb + 2 * t) * 4, __float_as_uint(d[4 * jb]), __float_as_uint(d[4 * jb + 1]));
    }
}
__device__ __forceinline__ void fetch_w2_row(uint32_t (&u)[12][4], uint32_t row, uint32_t sw, uint32_t nrm2) {
#pragma unroll
    for (int a = 0; a < 3; a++) {
        uint32_t v[4][4];
#pragma unroll
        for (int k = 0; k < 4; k++) lds128(v[k], row + a * 24576 + ((k * 16) ^ sw));
#pragma unroll
        for (int b = 0; b < 4; b++)
#pragma unroll
            for (int k = 0; k < 4; k++) u[a * 4 + b][k] = bf2_to_h2(bf2_mul(v[k][b], nrm2));
    }
}

__device__ __forceinline__ bool grn_stats(float ss, float gm, float bt, float& gx, float& inv, int& eb) {
    const int warp = fresh_warp();
    gx = sqrt_fast(fmaf(ss, INV_2A * INV_2A, 1e-6f));
    const float rt = sqrt_fast(ss + 1.0f) * INV_2A;
    const float r[3] = {warp_sum(gx), warp_sum(rt + bt), warp_sum(rt * fabsf(gm) * gx)};
    if ((fresh_tid() & 31) == 0 && warp < 12) {
#pragma unroll
        for (int k = 0; k < 3; k++) sts32(sb + SM_SEL + (k * 12 + warp) * 4, __float_as_uint(r[k]));
    }
    const bool bad = __syncthreads_or(!(ss >= 16.0f && ss < 1e30f));
    float tot[3];
#pragma unroll
    for (int k = 0; k < 3; k++) {
        uint32_t v[12];
#pragma unroll
        for (int q = 0; q < 3; q++) lds128(v + 4 * q, sb + SM_SEL + k * 48 + q * 16);
        float p[4];
#pragma unroll
        for (int q = 0; q < 4; q++) p[q] = __uint_as_float(v[q]) + __uint_as_float(v[q + 4]) + __uint_as_float(v[q + 8]);
        tot[k] = (p[0] + p[1]) + (p[2] + p[3]);
    }
    inv = __fdividef(1.0f, fmaf(tot[0], 1.0f / EX, 1e-6f));
    eb = clamped_exponent(fmaf(tot[2], inv, tot[1])) - 13;
    return bad;
}

__device__ __forceinline__ float exact_sums(const Params& prm, int e) {
    const int lane = fresh_tid() & 31, warp = fresh_warp(), wg = warp >> 2;
    const uint32_t epoch = lds32(sb + SM_RED + (RED_EPOCH + 1) * 4), bar = sb + SM_BAR + BAR_W1 * 8;
    if (wg < 3) {
        uint32_t wa[2][24], d[2][16];
        float acc[2][2] = {};
        const uint32_t yd = prm.ydesc, wd = prm.w1desc + ((2 * wg * 12288 + 5 * 2048) >> 4);
        load_w1t(wa, wg, warp & 3, lane);
#pragma unroll 1
        for (int n = 0; n < ROWS_PER_CTA; n++) {
            if (warp == 0) {
                expect_tx(bar, TILE_BYTES);
                bulk_load(sb + SM_Y1, (const char*)prm.out + cta_tile0(fresh_cta()) + n * ROW_BYTES, TILE_BYTES, bar);
            }
            mbar_wait(bar, (n + 1) & 1);
            gemm1_t<0>(d[0], wa[0], yd, wd);
            gemm1_t<1>(d[1], wa[1], yd, wd);
            wg_wait<0>();
            pin(d[0]); pin(d[1]);
            gelu_sumsq_f(d[0], acc[0]);
            gelu_sumsq_f(d[1], acc[1]);
            named_sync(1, 384);
        }
        publish_sums(acc, g_sums[1][epoch & 1], &g_count[1], wg, warp & 3, lane);
    }
    grid_wait(&g_count[1], (epoch + 1) * NUM_CTAS);
    return __ldcg(g_sums[1][epoch & 1] + e);
}

__global__ void __launch_bounds__(512, 1) convnext_kernel(const __grid_constant__ Params prm) {
    extern __shared__ __align__(1024) uint8_t smem[];
    if ((uint32_t)__cvta_generic_to_shared(smem) != sb) __trap();
    if (fresh_tid() < 32) TS(0);
    if (fresh_warp() == 0) {
        const RowCopy rc = row_copy(prm);
        if (fresh_tid() == 0) {
            mbar_init(sb + SM_XFULL, 2);
            fence_async_smem();
        }
        __syncwarp();
        issue_row_load(rc, 0, 0);
        if (fresh_tid() == 0) {
#pragma unroll
            for (int k = 0; k < NX; k++) {
                if (k) mbar_init(sb + SM_XFULL + k * SLOT_BYTES, 2);
                mbar_init(sb + SM_Y1FULL + k * SLOT_BYTES, 4);
                mbar_init(sb + SM_Y1EMPTY + k * SLOT_BYTES, 12);
            }
#pragma unroll
            for (int k = 0; k <= BAR_W2; k++) mbar_init(sb + SM_BAR + k * 8, 1);
            mbar_init(sb + SM_BAR + BAR_READY * 8, 16);
            sts32(sb + SM_RED + RED_W2MAX * 4, 0);
            fence_async_smem();
        }
        __syncwarp();
#pragma unroll
        for (int s = 1; s <= NX; s++) {
            if (s == 1 + rc.first) {
                expect_tx(sb + SM_BAR + BAR_W1 * 8, CH * EX * 2);
#pragma unroll
                for (int k = 0; k < 3; k++)
                    bulk_load(sb + SM_W1 + k * 24576, (const char*)prm.w1 + k * 24576, 24576, sb + SM_BAR + BAR_W1 * 8);
            }
            if (s < NX) issue_row_load(rc, s, s);
        }
    }
    Producer pc;
    if (fresh_warp() >= 12) {
        const char* dw = (const char*)prm.dw + (fresh_tid() & 7) * 8;
#pragma unroll
        for (int tap = 0; tap < 9; tap++) {
            asm volatile("ld.global.nc.v4.b32 {%0,%1,%2,%3}, [%4];"
                         : "=r"(pc.w[tap][0]), "=r"(pc.w[tap][1]), "=r"(pc.w[tap][2]), "=r"(pc.w[tap][3])
                         : "l"(dw + (fresh_tid() & 7) * 8 + tap * CH * 2));
            asm volatile("ld.global.nc.v2.b32 {%0,%1}, [%2];"
                         : "=r"(pc.w[tap][4]), "=r"(pc.w[tap][5]) : "l"(dw + tap * CH * 2 + 128));
        }
    }
    if (fresh_tid() >= 96 && fresh_tid() < 128) {
        const uint32_t k = fresh_tid() - 96, n = k & 7, one = (n & 5) == ((k & 8) >> 1) + (k >> 4) ? 0x3f803f80u : 0u;
        sts128(sb + SM_SEL + k * 16, one, one, one, one);
        fence_async_smem();
    }
    if (fresh_tid() >= 32 && fresh_tid() < 32 + NX * 12 && ((blockIdx.x + 1) & 7) < 2) {
        const int k = fresh_tid() - 32;
        sts128(sb + SM_X + (k / 12) * SLOT_BYTES + ((blockIdx.x & 7) == 0 ? 0 : XHALF_B + 33 * 192) + (k % 12) * 16, 0, 0, 0, 0);
    }
    __syncthreads();
    if (fresh_tid() < 32) TS(16);

    if (fresh_warp() >= 12) {
        TS(17);
        asm volatile("setmaxnreg.inc.sync.aligned.u32 %0;" ::"n"(PRODUCER_REGS));
        TS(18);
        const int w = fresh_warp() & 3, lane = fresh_tid() & 31;
        const int j = lane & 7, hb = (lane >> 3) & 1, base = 4 * (2 * w + (lane >> 4));
        pc.lane = lane; pc.warp = w;
        pc.xoff[0] = hb * XHALF_B + base * 192 + j * 16;
        pc.xoff[1] = hb * XHALF_B + base * 192 + 128 + j * 8;
        const int grp = 4 * w + (lane >> 3);
#pragma unroll
        for (int o = 0; o < 2; o++) {
            const int row = (grp & 7) + 8 * (o ^ hb) + 32 * (grp >> 3);
            pc.yoff[0][o] = row * 128 + ((j ^ (row & 7)) * 16);
            pc.yoff[1][o] = 8192 + row * 64 + (((j >> 1) ^ ((row >> 1) & 3)) * 16) + (j & 1) * 8;
        }
        pc.stat = sb + SM_STAT + grp * 32;
        pc.own = pc.stat + (lane & 3) * 8;
#pragma unroll
        for (int tap = 0; tap < 9; tap++)
#pragma unroll
            for (int u = 0; u < 6; u++) pc.w[tap][u] = bf2_mul(pc.w[tap][u], TAP_SCALE_BF2);
        TS(8);
        produce(pc, prm);
        TS(9);
        scan_w2(prm);
        TS(22);
        asm volatile("setmaxnreg.dec.sync.aligned.u32 %0;" ::"n"(EVEN_REGS));
    } else {
        asm volatile("setmaxnreg.dec.sync.aligned.u32 %0;" ::"n"(CONSUMER_REGS));
        if (fresh_tid() - 160 < 2) {
            const uint32_t k = fresh_tid() - 160;
            unsigned int cnt;
            asm volatile("ld.relaxed.gpu.global.u32 %0, [%1];" : "=r"(cnt) : "l"(&g_count[k]) : "memory");
            sts32(sb + SM_RED + (RED_EPOCH + k) * 4, cnt / NUM_CTAS);
        }
        __syncwarp();
        if (fresh_tid() < 32) TS(19);
        {
            const int tid = fresh_tid(), c0 = tid / 48, ec = tid % 48;
            const uint32_t dst = sb + SM_W1 + (ec >> 3) * 12288 + c0 * 128 + (((ec & 7) ^ (c0 & 7)) * 16);
            uint32_t v[12][4];
            mbar_wait_c<0>(sb + SM_BAR + BAR_W1 * 8);
            if (fresh_tid() < 32) TS(20);
#pragma unroll
            for (int it = 0; it < 12; it++) lds128(v[it], sb + SM_W1 + tid * 16 + it * 6144);
#pragma unroll
            for (int it = 0; it < 12; it++)
#pragma unroll
                for (int k = 0; k < 4; k++) v[it][k] = bf2_to_h2(v[it][k]);
#pragma unroll
            for (int it = 0; it < 12; it++) pin(v[it]);
            named_sync(1, 384);
#pragma unroll
            for (int it = 0; it < 12; it++) sts128(dst + it * 1024, v[it][0], v[it][1], v[it][2], v[it][3]);
            if (fresh_cta() < 2) g_sums[fresh_cta()][(lds32(sb + SM_RED + (RED_EPOCH + fresh_cta()) * 4) & 1) ^ 1][tid] = 0.0f;
            fence_async_smem();
            named_sync(1, 384);
            if (fresh_tid() < 32) TS(21);
        }

        const int tid = fresh_tid(), lane = tid & 31, wg = fresh_warp() >> 2, w = fresh_warp() & 3;
        uint32_t wa[2][24], d[2][16], q[2][2] = {};
        float acc[2][2] = {};
        load_w1t(wa, wg, w, lane);
        Duty duty = make_duty(prm, wg, w);
        if (wg == 0) TS(1);
        mbar_wait_c<0>(sb + SM_Y1FULL);
        if (wg == 0) TS(2);
        uint32_t yd = prm.ydesc;
        const uint32_t wd = prm.w1desc + ((2 * wg * 12288 + 5 * 2048) >> 4);
        gemm1_t<0>(d[0], wa[0], yd, wd);
        uint32_t so = loop_init<0>(), phase = loop_init<0>();
#pragma unroll 1
        for (int n = loop_init<0>(); n < ROWS_PER_CTA; n++) {
            if (wg * SLOT_BYTES == so) {
                run_duty(duty, n, wg, w);
                flush_sumsq(q[0], acc[0]);
                flush_sumsq(q[1], acc[1]);
            }
            wg_wait<0>();
            pin(d[0]);
            gemm1_t<1>(d[1], wa[1], yd, wd);
            const uint32_t release = sb + SM_Y1EMPTY + so;
            if ((so += SLOT_BYTES) == NX * SLOT_BYTES) { so = 0; phase ^= 1; }
            yd = prm.ydesc + (so >> 4);
            gelu_sumsq_h(d[0], q[0], prm.ydesc);
            mbar_wait(sb + SM_Y1FULL + so, phase);
            wg_wait<0>();
            pin(d[1]);
            bulk_wait_read<0>();
            mbar_arrive_if(release, lane == 0);
            gemm1_t<0>(d[0], wa[0], yd, wd);
            gelu_sumsq_h(d[1], q[1], prm.ydesc);
        }
        flush_sumsq(q[0], acc[0]);
        flush_sumsq(q[1], acc[1]);
        wg_wait<0>();
        pin(d[0]);
        publish_sums(acc, g_sums[0][lds32(sb + SM_RED + RED_EPOCH * 4) & 1], &g_count[0], wg, w, lane);
        bulk_wait_all();
        if (wg == 0) TS(3);
        asm volatile("setmaxnreg.inc.sync.aligned.u32 %0;" ::"n"(EVEN_REGS));
    }

    uint32_t out_scale;
    {
        const int tid = fresh_tid(), lane = tid & 31, warp = fresh_warp(), e = min(tid, EX - 1);
        const uint32_t epoch = lds32(sb + SM_RED + RED_EPOCH * 4);
        __syncthreads();
        uint16_t gm16, bt16;
        asm volatile("ld.shared.u16 %0, [%1];" : "=h"(gm16) : "r"(sb + SM_GAMMA + e * 2) : "memory");
        asm volatile("ld.shared.u16 %0, [%1];" : "=h"(bt16) : "r"(sb + SM_BETA + e * 2) : "memory");
        const float gm = bf_lo(gm16), bt = fabsf(bf_lo(bt16));
        if (warp == 13) {
            const uint32_t last = cta_tile0(fresh_cta()) + (ROWS_PER_CTA - 1) * ROW_BYTES;
            for (int k = 0; k < 2; k++) {
                expect_tx(sb + SM_BAR + (BAR_Y2FULL + k) * 8, TILE_BYTES);
                bulk_load(sb + SM_Y2 + k * TILE_BYTES, (const char*)prm.out + (last - k * ROW_BYTES), TILE_BYTES,
                          sb + SM_BAR + (BAR_Y2FULL + k) * 8);
            }
        }
        const uint32_t w2row = sb + SM_W2 + e * 64, sw = ((e >> 1) & 3) * 16;
        const int ew = clamped_exponent(__uint_as_float(lds32(sb + SM_RED + RED_W2MAX * 4)));
        const uint32_t nrm2 = pack_bf2(pow2f(-ew), pow2f(-ew));
        uint32_t u[12][4], b[4];
        fetch_w2_row(u, w2row, sw, nrm2);
        const int jj = min(lane >> 2, 5);
        lds128(b, sb + SM_BPART + (32 * (jj >> 1) + 8 * (lane & 3) + 4 * (jj & 1)) * 4);
        grid_wait(&g_count[0], (epoch + 1) * NUM_CTAS);
        if (warp == 0) TS(4);
        float gx, inv;
        int eb;
        if (grn_stats(__ldcg(g_sums[0][epoch & 1] + e), gm, bt, gx, inv, eb) || FORCE_EXACT) {
            grn_stats(exact_sums(prm, e), gm, bt, gx, inv, eb);
            fetch_w2_row(u, w2row, sw, nrm2);
        }
        const float up = pow2f(ew + eb);
        out_scale = pack_bf2(up, up);
        if (warp < 12) {
            const float sc = fmaf(gm, gx * inv, 1.0f) * INV_2A * pow2f(-eb);
            const uint32_t s2 = pack_h2(sc, sc);
#pragma unroll
            for (int k = 0; k < 12; k++)
                sts128(w2row + (k >> 2) * 24576 + (((k & 3) * 16) ^ sw), h2_mul(u[k][0], s2), h2_mul(u[k][1], s2),
                       h2_mul(u[k][2], s2), h2_mul(u[k][3], s2));
        } else if (warp == 12 && lane < 24) {
            const float dn = pow2f(-(ew + eb));
            const uint32_t p0 = pack_h2(__uint_as_float(b[0]) * dn, __uint_as_float(b[1]) * dn);
            const uint32_t p1 = pack_h2(__uint_as_float(b[2]) * dn, __uint_as_float(b[3]) * dn);
            sts128(sb + SM_BIAS + lane * 16, p0, p0, p1, p1);
        }
        fence_async_smem();
        __syncwarp();
        mbar_arrive_if(sb + SM_BAR + BAR_READY * 8, lane == 0);
    }

    {
        Pass2 c;
        const int tid = fresh_tid(), lane = tid & 31, wg = fresh_warp() >> 2, w = fresh_warp() & 3;
        const int arow = 16 * w + (lane & 15);
        c.wg = wg;
        c.off = cta_tile0(fresh_cta()) + (ROWS_PER_CTA - 1 - wg) * ROW_BYTES;
        c.a_offs = (arow * 128 + (((lane >> 4) ^ (arow & 7)) * 16)) |
                   (8192 + arow * 64 + (((lane >> 4) ^ ((arow >> 1) & 3)) * 16)) << 16;
        const int g = lane >> 2, px = 33 * (g & 1) + 4 * (g >> 1) + 16 * (w >> 1) + 2 * (w & 1);
        c.xs_offs = (px * 192 + (lane & 3) * 16) | ((px ^ 1) * 192 + (lane & 3) * 16) << 16;
        c.bias_addr = sb + SM_BIAS + (lane & 3) * 16;
        c.out_scale = out_scale;
        c.lead = w == 0;
        if (wg == 0) TS(5);
        start_first_tile(c, prm);
        mbar_wait_c<0>(sb + SM_BAR + BAR_READY * 8);
        init_bias(c.o, c.bias_addr);
#pragma unroll 1
        for (int n = loop_init<0>(); n < ROWS_PER_CTA / 4; n++) pass2_tile(c, prm, n);
        bulk_wait_all();
        if (wg == 0) TS(6);
        if (wg == 3) TS(7);
    }
}

}

extern "C" void kernel_launch(void* const* d_in, const int* in_sizes, int n_in, void* d_out, int out_size) {
    (void)in_sizes; (void)n_in; (void)out_size;
    typedef CUresult (*EncodeFn)(CUtensorMap*, CUtensorMapDataType, cuuint32_t, void*, const cuuint64_t*, const cuuint64_t*,
                                 const cuuint32_t*, const cuuint32_t*, CUtensorMapInterleave, CUtensorMapSwizzle,
                                 CUtensorMapL2promotion, CUtensorMapFloatOOBfill);
    void* fn = nullptr;
    cudaDriverEntryPointQueryResult status;
    cudaGetDriverEntryPoint("cuTensorMapEncodeTiled", &fn, cudaEnableDefault, &status);
    const EncodeFn encode = (EncodeFn)fn;
    const cuuint32_t ones[2] = {1, 1};

    Params p;
    {
        const cuuint64_t dims[2] = {CH, EX}, strides[1] = {CH * 2};
        const cuuint32_t box[2] = {32, 192};
        encode(&p.w2_map, CU_TENSOR_MAP_DATA_TYPE_BFLOAT16, 2, d_in[3], dims, strides, box, ones,
               CU_TENSOR_MAP_INTERLEAVE_NONE, CU_TENSOR_MAP_SWIZZLE_64B, CU_TENSOR_MAP_L2_PROMOTION_NONE,
               CU_TENSOR_MAP_FLOAT_OOB_FILL_NONE);
    }
    p.x = (const __nv_bfloat16*)d_in[0];
    p.dw = (const __nv_bfloat16*)d_in[1];
    p.w1 = (const __nv_bfloat16*)d_in[2];
    p.gamma = (const __nv_bfloat16*)d_in[4];
    p.beta = (const __nv_bfloat16*)d_in[5];
    p.out = (__nv_bfloat16*)d_out;
    p.w1desc = desc_lo(sb + SM_W1, 12288);
    p.w2desc = desc_lo(sb + SM_W2, 24576);
    p.ydesc = desc_lo(sb + SM_Y1, 16);
    for (int k = 0; k < 3; k++) p.sel[k] = (8ull << 32) | desc_lo(sb + SM_SEL + k * 128, k == 2 ? 128 : 0);
    cudaFuncSetAttribute(convnext_kernel, cudaFuncAttributeMaxDynamicSharedMemorySize, SM_TOTAL);
    convnext_kernel<<<NUM_CTAS, 512, SM_TOTAL>>>(p);
}
```

```cpp
#include <cuda.h>
#include <cuda_runtime.h>
#include <cuda_bf16.h>
#include <stdint.h>

namespace {

constexpr int IMG_W = 512, CH = 96, EX = 384;
constexpr int TILE_PX = 64;
constexpr int ROWS_PER_CTA = 32;
constexpr int NUM_CTAS = 128;
constexpr int STEPS = ROWS_PER_CTA + 2;
constexpr int ROW_BYTES = IMG_W * CH * 2;

#define FORCE_EXACT 0
#define PREGS 200
#define CREGS 104
constexpr int PRODUCER_REGS = PREGS, CONSUMER_REGS = CREGS, EVEN_REGS = 128;

constexpr int XHALF_BYTES = 34 * 192;
constexpr int XHALF_B = XHALF_BYTES + 64;
constexpr int XROW_BYTES = XHALF_B + XHALF_BYTES + 64;
constexpr int L2_AHEAD = 2;
constexpr int NX = 3;
constexpr int TILE_BYTES = TILE_PX * 192;
constexpr int NY1 = 3;

constexpr uint32_t sb = 1024;
constexpr int SM_W1 = 0;
constexpr int SM_W2 = 73728;
constexpr int SM_RING = 147456;
constexpr int SLOT_BYTES = 26624;
constexpr int SM_Y1 = SM_RING;
constexpr int SM_X = SM_Y1 + TILE_BYTES;
constexpr int SM_STAT = SM_X + XROW_BYTES;
constexpr int SM_XFULL = SM_STAT + TILE_PX * 8, SM_Y1FULL = SM_XFULL + 8, SM_Y1EMPTY = SM_XFULL + 16;
constexpr int SM_XS = SM_RING;
constexpr int SM_Y2 = SM_XS + 4 * TILE_BYTES;
constexpr int SM_SEL = SM_RING + NX * SLOT_BYTES;
constexpr int SM_BIAS = SM_SEL + 512;
constexpr int SM_BPART = SM_BIAS + 384;
constexpr int SM_GAMMA = SM_BPART + 96 * 4;
constexpr int SM_BETA = SM_GAMMA + EX * 2;
constexpr int SM_RED = SM_BETA + EX * 2;
constexpr int SM_BAR = SM_RED + 16;
constexpr int SM_TOTAL = SM_BAR + 11 * 8;
static_assert(SM_Y1EMPTY + 8 <= SM_RING + SLOT_BYTES && SM_Y2 + 2 * TILE_BYTES <= SM_SEL, "ring layout");
static_assert(SM_TOTAL <= 232448, "smem budget");
static_assert(SM_STAT % 128 == 0 && SM_BIAS % 16 == 0 && SM_BAR % 8 == 0 && SLOT_BYTES % 1024 == 0, "alignment");

constexpr int BAR_Y2FULL = 0, BAR_XSFULL = 4, BAR_W1 = 8, BAR_W2 = 9, BAR_READY = 10;
static_assert(NX == NY1, "both rings are walked with one index");
constexpr int RED_EPOCH = 0, RED_W2MAX = 2;

constexpr float GELU_A = 0.32920349f;
constexpr uint32_t GELU_C_H2 = 0x40D940D9u;
constexpr float INV_2A = 1.0f / (2.0f * GELU_A);

constexpr uint32_t TAP_SCALE_BF2 = 0x2B802B80u;
constexpr float LN_EPS_SCALED = 1e-5f * 0x1p-80f;
constexpr float RSTD_SCALE = GELU_A * 0x1p-112f;

__device__ float g_sums[2][2][EX];
__device__ unsigned int g_count[2];
__device__ uint4 g_zero_row[66 * 192 / 16];

#define TS(k)
#define ASM_TS
#define ASM_TRC

#define SPLITS 2
#define FENCE_HEAD(k) "{\n.reg .pred p;\n.reg .u32 t;\nsetp.ne.u32 p, %" #k ", 0;\n@p bra.uni GO;\nSTAY:\nld.volatile.shared.u32 t, [%" #k "];\n"
#define FENCE_TAIL "setp.ne.u32 p, t, 0;\n@p bra.uni STAY;\nGO:\n}\n"
template <int N> __device__ __forceinline__ void sched_fence(uint32_t* r, uint32_t key);
template <> __device__ __forceinline__ void sched_fence<2>(uint32_t* r, uint32_t key) {
    asm volatile(FENCE_HEAD(2) "mov.b32 %0, t;\nmov.b32 %1, t;\n" FENCE_TAIL
                 : "+r"(r[0]), "+r"(r[1]) : "r"(key) : "memory");
}
template <> __device__ __forceinline__ void sched_fence<4>(uint32_t* r, uint32_t key) {
    asm volatile(FENCE_HEAD(4) "mov.b32 %0, t;\nmov.b32 %1, t;\nmov.b32 %2, t;\nmov.b32 %3, t;\n" FENCE_TAIL
                 : "+r"(r[0]), "+r"(r[1]), "+r"(r[2]), "+r"(r[3]) : "r"(key) : "memory");
}
template <> __device__ __forceinline__ void sched_fence<6>(uint32_t* r, uint32_t key) {
    asm volatile(FENCE_HEAD(6) "mov.b32 %0, t;\nmov.b32 %1, t;\nmov.b32 %2, t;\nmov.b32 %3, t;\nmov.b32 %4, t;\nmov.b32 %5, t;\n" FENCE_TAIL
                 : "+r"(r[0]), "+r"(r[1]), "+r"(r[2]), "+r"(r[3]), "+r"(r[4]), "+r"(r[5]) : "r"(key) : "memory");
}
template <> __device__ __forceinline__ void sched_fence<8>(uint32_t* r, uint32_t key) {
    asm volatile(FENCE_HEAD(8) "mov.b32 %0, t;\nmov.b32 %1, t;\nmov.b32 %2, t;\nmov.b32 %3, t;\nmov.b32 %4, t;\nmov.b32 %5, t;\nmov.b32 %6, t;\nmov.b32 %7, t;\n" FENCE_TAIL
                 : "+r"(r[0]), "+r"(r[1]), "+r"(r[2]), "+r"(r[3]), "+r"(r[4]), "+r"(r[5]), "+r"(r[6]), "+r"(r[7]) : "r"(key) : "memory");
}
template <> __device__ __forceinline__ void sched_fence<10>(uint32_t* r, uint32_t key) {
    asm volatile(FENCE_HEAD(10) "mov.b32 %0, t;\nmov.b32 %1, t;\nmov.b32 %2, t;\nmov.b32 %3, t;\nmov.b32 %4, t;\nmov.b32 %5, t;\nmov.b32 %6, t;\nmov.b32 %7, t;\nmov.b32 %8, t;\nmov.b32 %9, t;\n" FENCE_TAIL
                 : "+r"(r[0]), "+r"(r[1]), "+r"(r[2]), "+r"(r[3]), "+r"(r[4]), "+r"(r[5]), "+r"(r[6]), "+r"(r[7]), "+r"(r[8]), "+r"(r[9]) : "r"(key) : "memory");
}
template <> __device__ __forceinline__ void sched_fence<12>(uint32_t* r, uint32_t key) {
    asm volatile(FENCE_HEAD(12) "mov.b32 %0, t;\nmov.b32 %1, t;\nmov.b32 %2, t;\nmov.b32 %3, t;\nmov.b32 %4, t;\nmov.b32 %5, t;\nmov.b32 %6, t;\nmov.b32 %7, t;\nmov.b32 %8, t;\nmov.b32 %9, t;\nmov.b32 %10, t;\nmov.b32 %11, t;\n" FENCE_TAIL
                 : "+r"(r[0]), "+r"(r[1]), "+r"(r[2]), "+r"(r[3]), "+r"(r[4]), "+r"(r[5]), "+r"(r[6]), "+r"(r[7]), "+r"(r[8]), "+r"(r[9]), "+r"(r[10]), "+r"(r[11]) : "r"(key) : "memory");
}
template <> __device__ __forceinline__ void sched_fence<24>(uint32_t* r, uint32_t key) {
    asm volatile(FENCE_HEAD(24) "mov.b32 %0, t;\nmov.b32 %1, t;\nmov.b32 %2, t;\nmov.b32 %3, t;\nmov.b32 %4, t;\nmov.b32 %5, t;\nmov.b32 %6, t;\nmov.b32 %7, t;\nmov.b32 %8, t;\nmov.b32 %9, t;\nmov.b32 %10, t;\nmov.b32 %11, t;\nmov.b32 %12, t;\nmov.b32 %13, t;\nmov.b32 %14, t;\nmov.b32 %15, t;\nmov.b32 %16, t;\nmov.b32 %17, t;\nmov.b32 %18, t;\nmov.b32 %19, t;\nmov.b32 %20, t;\nmov.b32 %21, t;\nmov.b32 %22, t;\nmov.b32 %23, t;\n" FENCE_TAIL
                 : "+r"(r[0]), "+r"(r[1]), "+r"(r[2]), "+r"(r[3]), "+r"(r[4]), "+r"(r[5]), "+r"(r[6]), "+r"(r[7]), "+r"(r[8]), "+r"(r[9]), "+r"(r[10]), "+r"(r[11]), "+r"(r[12]), "+r"(r[13]), "+r"(r[14]), "+r"(r[15]), "+r"(r[16]), "+r"(r[17]), "+r"(r[18]), "+r"(r[19]), "+r"(r[20]), "+r"(r[21]), "+r"(r[22]), "+r"(r[23]) : "r"(key) : "memory");
}
#define SPLIT(k, r) do { if ((SPLITS >> (k)) & 1) sched_fence<sizeof(r) / 4>(r, prm.ydesc); } while (0)

__device__ __forceinline__ void mbar_init(uint32_t bar, uint32_t count) {
    asm volatile("mbarrier.init.shared::cta.b64 [%0], %1;" ::"r"(bar), "r"(count) : "memory");
}
__device__ __forceinline__ void mbar_arrive_if(uint32_t bar, bool pred) {
    asm volatile("{\n.reg .pred p;\nsetp.ne.u32 p, %1, 0;\n@p mbarrier.arrive.shared::cta.b64 _, [%0];\n}\n"
                 ::"r"(bar), "r"((uint32_t)pred) : "memory");
}
__device__ __forceinline__ void mbar_wait(uint32_t bar, uint32_t parity) {
    asm volatile(
        "{\n.reg .pred p;\n.reg .u32 n;\n"
        "mbarrier.try_wait.parity.shared::cta.b64 p, [%0], %1;\n"
        "@p bra.uni WAIT_DONE;\n"
        "mov.u32 n, 0;\n"
        "WAIT_LOOP:\n"
        "mbarrier.try_wait.parity.shared::cta.b64 p, [%0], %1;\n"
        "@p bra.uni WAIT_DONE;\n"
        "mbarrier.try_wait.parity.shared::cta.b64 p, [%0], %1;\n"
        "@p bra.uni WAIT_DONE;\n"
        "mbarrier.try_wait.parity.shared::cta.b64 p, [%0], %1;\n"
        "@p bra.uni WAIT_DONE;\n"
        "add.u32 n, n, 1;\nsetp.lt.u32 p, n, 0x40000;\n"
        "@p bra.uni WAIT_LOOP;\n"
        "trap;\n"
        "WAIT_DONE:\n}\n"
        ::"r"(bar), "r"(parity) : "memory");
}
template <int PARITY> __device__ __forceinline__ void mbar_wait_c(uint32_t bar) {
    asm volatile(
        "{\n.reg .pred p;\n.reg .u32 n;\n"
        "mbarrier.try_wait.parity.shared::cta.b64 p, [%0], %1;\n"
        "@p bra.uni WAIT_DONE;\n"
        "mov.u32 n, 0;\n"
        "WAIT_LOOP:\n"
        "mbarrier.try_wait.parity.shared::cta.b64 p, [%0], %1;\n"
        "@p bra.uni WAIT_DONE;\n"
        "mbarrier.try_wait.parity.shared::cta.b64 p, [%0], %1;\n"
        "@p bra.uni WAIT_DONE;\n"
        "mbarrier.try_wait.parity.shared::cta.b64 p, [%0], %1;\n"
        "@p bra.uni WAIT_DONE;\n"
        "add.u32 n, n, 1;\nsetp.lt.u32 p, n, 0x40000;\n"
        "@p bra.uni WAIT_LOOP;\n"
        "trap;\n"
        "WAIT_DONE:\n}\n"
        ::"r"(bar), "n"(PARITY) : "memory");
}
__device__ __forceinline__ bool mbar_probe(uint32_t bar, uint32_t parity) {
    uint32_t ok;
    asm volatile("{\n.reg .pred p;\nmbarrier.test_wait.parity.shared::cta.b64 p, [%1], %2;\nselp.u32 %0, 1, 0, p;\n}\n"
                 : "=r"(ok) : "r"(bar), "r"(parity) : "memory");
    return ok;
}
__device__ __forceinline__ void mbar_wait2(uint32_t bar0, uint32_t parity0, uint32_t bar1, uint32_t parity1) {
    asm volatile(
        "{\n.reg .pred p, q;\n.reg .u32 n;\n"
        "mbarrier.try_wait.parity.shared::cta.b64 p, [%0], %1;\n"
        "mbarrier.try_wait.parity.shared::cta.b64 q, [%2], %3;\n"
        "and.pred p, p, q;\n"
        "@p bra.uni WAIT_DONE;\n"
        "mov.u32 n, 0;\n"
        "WAIT_LOOP:\n"
        "mbarrier.try_wait.parity.shared::cta.b64 p, [%0], %1;\n"
        "mbarrier.try_wait.parity.shared::cta.b64 q, [%2], %3;\n"
        "and.pred p, p, q;\n"
        "@p bra.uni WAIT_DONE;\n"
        "add.u32 n, n, 1;\nsetp.lt.u32 p, n, 0x80000;\n"
        "@p bra.uni WAIT_LOOP;\n"
        "trap;\n"
        "WAIT_DONE:\n}\n"
        ::"r"(bar0), "r"(parity0), "r"(bar1), "r"(parity1) : "memory");
}
#define ELECTED(body) "{\n.reg .pred p;\nelect.sync _|p, 0xffffffff;\n" body "}\n"
__device__ __forceinline__ void expect_tx(uint32_t bar, uint32_t bytes) {
    asm volatile(ELECTED("@p mbarrier.arrive.expect_tx.shared::cta.b64 _, [%0], %1;\n") ::"r"(bar), "r"(bytes) : "memory");
}
__device__ __forceinline__ void arrive_n(uint32_t bar, uint32_t count) {
    asm volatile(ELECTED("@p mbarrier.arrive.shared::cta.b64 _, [%0], %1;\n") ::"r"(bar), "r"(count) : "memory");
}
__device__ __forceinline__ void bulk_load(uint32_t dst, const void* src, uint32_t bytes, uint32_t bar) {
    asm volatile(ELECTED("@p cp.async.bulk.shared::cluster.global.mbarrier::complete_tx::bytes [%0], [%1], %2, [%3];\n")
                 ::"r"(dst), "l"(src), "r"(bytes), "r"(bar) : "memory");
}
__device__ __forceinline__ void bulk_store(void* dst, uint32_t src, uint32_t bytes) {
    asm volatile(ELECTED("@p cp.async.bulk.global.shared::cta.bulk_group [%0], [%1], %2;\n@p cp.async.bulk.commit_group;\n")
                 ::"l"(dst), "r"(src), "r"(bytes) : "memory");
}
__device__ __forceinline__ void bulk_prefetch(const void* src, uint32_t bytes) {
    asm volatile(ELECTED("@p cp.async.bulk.prefetch.L2.global [%0], %1;\n") ::"l"(src), "r"(bytes) : "memory");
}
__device__ __forceinline__ void tma_load_2d(uint32_t dst, const CUtensorMap* map, int c0, int c1, uint32_t bar) {
    asm volatile(ELECTED("@p cp.async.bulk.tensor.2d.shared::cluster.global.mbarrier::complete_tx::bytes [%0], [%1, {%2, %3}], [%4];\n")
                 ::"r"(dst), "l"(map), "r"(c0), "r"(c1), "r"(bar) : "memory");
}
template <int N> __device__ __forceinline__ void bulk_wait_read() {
    asm volatile("cp.async.bulk.wait_group.read %0;" ::"n"(N) : "memory");
}
__device__ __forceinline__ void bulk_wait_all() { asm volatile("cp.async.bulk.wait_group 0;" ::: "memory"); }
__device__ __forceinline__ void fence_async_smem() { asm volatile("fence.proxy.async.shared::cta;" ::: "memory"); }
__device__ __forceinline__ void named_sync(int id, int n) { asm volatile("bar.sync %0, %1;" ::"r"(id), "r"(n) : "memory"); }

__device__ __forceinline__ void lds64(uint32_t (&v)[2], uint32_t addr) {
    asm volatile("ld.shared.v2.b32 {%0,%1}, [%2];" : "=r"(v[0]), "=r"(v[1]) : "r"(addr));
}
__device__ __forceinline__ void sts64(uint32_t addr, uint32_t a, uint32_t b) {
    asm volatile("st.shared.v2.b32 [%0], {%1,%2};" ::"r"(addr), "r"(a), "r"(b) : "memory");
}
__device__ __forceinline__ void sts128(uint32_t addr, uint32_t a, uint32_t b, uint32_t c, uint32_t d) {
    asm volatile("st.shared.v4.b32 [%0], {%1,%2,%3,%4};" ::"r"(addr), "r"(a), "r"(b), "r"(c), "r"(d) : "memory");
}
__device__ __forceinline__ void ldsm4(uint32_t* r, uint32_t addr) {
    asm volatile("ldmatrix.sync.aligned.m8n8.x4.shared.b16 {%0,%1,%2,%3}, [%4];"
                 : "=r"(r[0]), "=r"(r[1]), "=r"(r[2]), "=r"(r[3]) : "r"(addr) : "memory");
}
__device__ __forceinline__ void ldsm4_t(uint32_t* r, uint32_t addr) {
    asm volatile("ldmatrix.sync.aligned.m8n8.x4.trans.shared.b16 {%0,%1,%2,%3}, [%4];"
                 : "=r"(r[0]), "=r"(r[1]), "=r"(r[2]), "=r"(r[3]) : "r"(addr) : "memory");
}
__device__ __forceinline__ void lds128(uint32_t* v, uint32_t addr) {
    asm volatile("ld.shared.v4.b32 {%0,%1,%2,%3}, [%4];"
                 : "=r"(v[0]), "=r"(v[1]), "=r"(v[2]), "=r"(v[3]) : "r"(addr) : "memory");
}
__device__ __forceinline__ uint32_t lds32(uint32_t addr) {
    uint32_t v; asm volatile("ld.shared.b32 %0, [%1];" : "=r"(v) : "r"(addr) : "memory"); return v;
}
__device__ __forceinline__ void sts32(uint32_t addr, uint32_t v) {
    asm volatile("st.shared.b32 [%0], %1;" ::"r"(addr), "r"(v) : "memory");
}

__device__ __forceinline__ uint32_t bf2_fma(uint32_t a, uint32_t b, uint32_t c) {
    uint32_t d; asm("fma.rn.bf16x2 %0, %1, %2, %3;" : "=r"(d) : "r"(a), "r"(b), "r"(c)); return d;
}
__device__ __forceinline__ uint32_t bf2_mul(uint32_t a, uint32_t b) {
    uint32_t d; asm("mul.rn.bf16x2 %0, %1, %2;" : "=r"(d) : "r"(a), "r"(b)); return d;
}
__device__ __forceinline__ uint32_t bf2_add(uint32_t a, uint32_t b) {
    uint32_t d; asm("add.rn.bf16x2 %0, %1, %2;" : "=r"(d) : "r"(a), "r"(b)); return d;
}
__device__ __forceinline__ uint32_t bf2_fma_hi(uint32_t a, uint32_t b, uint32_t c) {
    uint32_t d;
    asm("{\n.reg .b16 l, h;\n.reg .b32 m;\nmov.b32 {l, h}, %3;\nmov.b32 m, {h, h};\nfma.rn.bf16x2 %0, %1, %2, m;\n}\n"
        : "=r"(d) : "r"(a), "r"(b), "r"(c));
    return d;
}
__device__ __forceinline__ uint32_t bf2_affine(uint32_t a, uint32_t sm) {
    uint32_t d;
    asm("{\n.reg .b16 l, h;\n.reg .b32 r, m;\nmov.b32 {l, h}, %2;\nmov.b32 r, {l, l};\nmov.b32 m, {h, h};\n"
        "fma.rn.bf16x2 %0, %1, r, m;\n}\n" : "=r"(d) : "r"(a), "r"(sm));
    return d;
}
__device__ __forceinline__ uint32_t bf2_rebias_h2(uint32_t v) { return (v & 0x7fff7fffu) * 7u + v; }
__device__ __forceinline__ uint32_t h2_fma(uint32_t a, uint32_t b, uint32_t c) {
    uint32_t d; asm("fma.rn.f16x2 %0, %1, %2, %3;" : "=r"(d) : "r"(a), "r"(b), "r"(c)); return d;
}
__device__ __forceinline__ uint32_t h2_mul(uint32_t a, uint32_t b) {
    uint32_t d; asm("mul.rn.f16x2 %0, %1, %2;" : "=r"(d) : "r"(a), "r"(b)); return d;
}
__device__ __forceinline__ uint32_t h2_tanh(uint32_t a) {
    uint32_t d; asm("tanh.approx.f16x2 %0, %1;" : "=r"(d) : "r"(a)); return d;
}
__device__ __forceinline__ float bf_lo(uint32_t v) { return __uint_as_float(v << 16); }
__device__ __forceinline__ float bf_hi(uint32_t v) { return __uint_as_float(v & 0xffff0000u); }
__device__ __forceinline__ uint32_t pack_h2(float lo, float hi) {
    uint32_t d; asm("cvt.rn.f16x2.f32 %0, %1, %2;" : "=r"(d) : "f"(hi), "f"(lo)); return d;
}
__device__ __forceinline__ uint32_t pack_bf2(float lo, float hi) {
    uint32_t d; asm("cvt.rn.bf16x2.f32 %0, %1, %2;" : "=r"(d) : "f"(hi), "f"(lo)); return d;
}
__device__ __forceinline__ void h2_unpack(uint32_t v, float& lo, float& hi) {
    asm("{\n.reg .b16 l, h;\nmov.b32 {l, h}, %2;\ncvt.f32.f16 %0, l;\ncvt.f32.f16 %1, h;\n}\n" : "=f"(lo), "=f"(hi) : "r"(v));
}
__device__ __forceinline__ uint32_t bf2_to_h2(uint32_t v) { return pack_h2(bf_lo(v), bf_hi(v)); }

__device__ __forceinline__ uint32_t gelu2(uint32_t z) {
    uint32_t p = h2_fma(z, z, GELU_C_H2);
    uint32_t t = h2_tanh(h2_mul(z, p));
    return h2_fma(z, t, z);
}

__device__ __forceinline__ void wg_fence() { asm volatile("wgmma.fence.sync.aligned;" ::: "memory"); }
__device__ __forceinline__ void wg_commit() { asm volatile("wgmma.commit_group.sync.aligned;" ::: "memory"); }
template <int N> __device__ __forceinline__ void wg_wait() {
    asm volatile("wgmma.wait_group.sync.aligned %0;" ::"n"(N) : "memory");
}
template <int N> __device__ __forceinline__ void pin(uint32_t (&r)[N]) {
#pragma unroll
    for (int i = 0; i < N; i++) asm volatile("" : "+r"(r[i])::"memory");
}
constexpr uint32_t desc_lo(uint32_t addr, uint32_t lbo) { return ((addr & 0x3FFFF) >> 4) | ((lbo >> 4) << 16); }
template <uint32_t SBO, uint32_t SWZ> __device__ __forceinline__ uint64_t desc(uint32_t lo, uint32_t bytes) {
    return (((uint64_t)((SBO >> 4) | (SWZ << 30)) << 32) | lo) + (bytes >> 4);
}
__device__ __forceinline__ uint32_t fresh_tid() {
    uint32_t v; asm volatile("mov.u32 %0, %%tid.x;" : "=r"(v));
    return v;
}
template <uint32_t V> __device__ __forceinline__ uint32_t loop_init() {
    uint32_t v; asm volatile("mov.u32 %0, %1;" : "=r"(v) : "n"(V)); return v;
}
__device__ __forceinline__ int fresh_warp() {
    int v; asm volatile("shfl.sync.idx.b32 %0, %1, 0, 0x1f, 0xffffffff;" : "=r"(v) : "r"(fresh_tid() >> 5)); return v;
}
__device__ __forceinline__ uint32_t fresh_cta() {
    uint32_t v; asm volatile("mov.u32 %0, %%ctaid.x;" : "=r"(v)); return v;
}
__device__ __forceinline__ float rsqrt_fast(float v) { float r; asm("rsqrt.approx.ftz.f32 %0, %1;" : "=f"(r) : "f"(v)); return r; }
__device__ __forceinline__ float sqrt_fast(float v) { float r; asm("sqrt.approx.f32 %0, %1;" : "=f"(r) : "f"(v)); return r; }

template <int TB>
__device__ __forceinline__ void wgmma_n64_h_set(uint32_t (&d)[16], const uint32_t* a, uint64_t desc) {
    asm volatile(
        "{\n.reg .pred p;\nsetp.ne.b32 p, 0, 0;\n"
        "wgmma.mma_async.sync.aligned.m64n64k16.f16.f16.f16 "
        "{%0,%1,%2,%3,%4,%5,%6,%7,%8,%9,%10,%11,%12,%13,%14,%15}, {%16,%17,%18,%19}, %20, p, 1, 1, %21;\n}\n"
        : "=r"(d[0]), "=r"(d[1]), "=r"(d[2]), "=r"(d[3]), "=r"(d[4]), "=r"(d[5]), "=r"(d[6]), "=r"(d[7]), "=r"(d[8]), "=r"(d[9]), "=r"(d[10]), "=r"(d[11]), "=r"(d[12]), "=r"(d[13]), "=r"(d[14]), "=r"(d[15])
        : "r"(a[0]), "r"(a[1]), "r"(a[2]), "r"(a[3]), "l"(desc), "n"(TB));
}
template <int TB>
__device__ __forceinline__ void wgmma_n64_h_acc(uint32_t (&d)[16], const uint32_t* a, uint64_t desc) {
    asm volatile(
        "{\n.reg .pred p;\nsetp.ne.b32 p, 1, 0;\n"
        "wgmma.mma_async.sync.aligned.m64n64k16.f16.f16.f16 "
        "{%0,%1,%2,%3,%4,%5,%6,%7,%8,%9,%10,%11,%12,%13,%14,%15}, {%16,%17,%18,%19}, %20, p, 1, 1, %21;\n}\n"
        : "+r"(d[0]), "+r"(d[1]), "+r"(d[2]), "+r"(d[3]), "+r"(d[4]), "+r"(d[5]), "+r"(d[6]), "+r"(d[7]), "+r"(d[8]), "+r"(d[9]), "+r"(d[10]), "+r"(d[11]), "+r"(d[12]), "+r"(d[13]), "+r"(d[14]), "+r"(d[15])
        : "r"(a[0]), "r"(a[1]), "r"(a[2]), "r"(a[3]), "l"(desc), "n"(TB));
}
__device__ __forceinline__ void wgmma_n64_h_acc_ss(uint32_t (&d)[16], uint64_t adesc, uint64_t desc) {
    asm volatile(
        "{\n.reg .pred p;\nsetp.ne.b32 p, 1, 0;\n"
        "wgmma.mma_async.sync.aligned.m64n64k16.f16.f16.f16 "
        "{%0,%1,%2,%3,%4,%5,%6,%7,%8,%9,%10,%11,%12,%13,%14,%15}, %16, %17, p, 1, 1, 1, 0;\n}\n"
        : "+r"(d[0]), "+r"(d[1]), "+r"(d[2]), "+r"(d[3]), "+r"(d[4]), "+r"(d[5]), "+r"(d[6]), "+r"(d[7]), "+r"(d[8]), "+r"(d[9]), "+r"(d[10]), "+r"(d[11]), "+r"(d[12]), "+r"(d[13]), "+r"(d[14]), "+r"(d[15])
        : "l"(adesc), "l"(desc));
}
__device__ __forceinline__ void wgmma_n96_h_acc(uint32_t (&d)[24], const uint32_t* a, uint64_t desc) {
    asm volatile(
        "{\n.reg .pred p;\nsetp.ne.b32 p, 1, 0;\n"
        "wgmma.mma_async.sync.aligned.m64n96k16.f16.f16.f16 "
        "{%0,%1,%2,%3,%4,%5,%6,%7,%8,%9,%10,%11,%12,%13,%14,%15,%16,%17,%18,%19,%20,%21,%22,%23}, {%24,%25,%26,%27}, %28, p, 1, 1, 1;\n}\n"
        : "+r"(d[0]), "+r"(d[1]), "+r"(d[2]), "+r"(d[3]), "+r"(d[4]), "+r"(d[5]), "+r"(d[6]), "+r"(d[7]), "+r"(d[8]), "+r"(d[9]), "+r"(d[10]), "+r"(d[11]), "+r"(d[12]), "+r"(d[13]), "+r"(d[14]), "+r"(d[15]), "+r"(d[16]), "+r"(d[17]), "+r"(d[18]), "+r"(d[19]), "+r"(d[20]), "+r"(d[21]), "+r"(d[22]), "+r"(d[23])
        : "r"(a[0]), "r"(a[1]), "r"(a[2]), "r"(a[3]), "l"(desc));
}

template <int ACC>
__device__ __forceinline__ void wgmma_n8(float (&d)[4], uint32_t a0, uint32_t a1, uint32_t a2, uint32_t a3, uint64_t desc) {
    if (ACC)
        asm volatile("{\n.reg .pred p;\nsetp.ne.b32 p, 1, 0;\n"
                     "wgmma.mma_async.sync.aligned.m64n8k16.f32.bf16.bf16 {%0,%1,%2,%3}, {%4,%5,%6,%7}, %8, p, 1, 1, 0;\n}\n"
                     : "+f"(d[0]), "+f"(d[1]), "+f"(d[2]), "+f"(d[3]) : "r"(a0), "r"(a1), "r"(a2), "r"(a3), "l"(desc));
    else
        asm volatile("{\n.reg .pred p;\nsetp.ne.b32 p, 0, 0;\n"
                     "wgmma.mma_async.sync.aligned.m64n8k16.f32.bf16.bf16 {%0,%1,%2,%3}, {%4,%5,%6,%7}, %8, p, 1, 1, 0;\n}\n"
                     : "=f"(d[0]), "=f"(d[1]), "=f"(d[2]), "=f"(d[3]) : "r"(a0), "r"(a1), "r"(a2), "r"(a3), "l"(desc));
}

struct Params {
    CUtensorMap w2_map;
    const __nv_bfloat16* x;
    const __nv_bfloat16* dw;
    const __nv_bfloat16* w1;
    const __nv_bfloat16* gamma;
    const __nv_bfloat16* beta;
    __nv_bfloat16* out;
    uint64_t sel[3];
    uint32_t w1desc, w2desc, ydesc;
};

__device__ __forceinline__ uint32_t cta_tile0(uint32_t cta) {
    return (cta >> 3) * (ROWS_PER_CTA * ROW_BYTES) + (cta & 7) * TILE_BYTES;
}

struct Producer {
    uint32_t w[9][6];
    uint32_t xoff[2];
    uint32_t yoff[2][2];
    uint32_t stat, own;
    int lane, warp;
};

struct RowCopy {
    const char* x0;
    char* y0;
    uint32_t cut0, cut1;
    int first, last;
};
__device__ __forceinline__ RowCopy row_copy(const Params& prm) {
    const uint32_t cta = fresh_cta(), strip = cta & 7, t0 = cta_tile0(cta);
    RowCopy r;
    r.x0 = (const char*)prm.x + t0 - ROW_BYTES - 192;
    r.y0 = (char*)prm.out + t0;
    r.cut0 = strip == 0 ? 192 : 0;
    r.cut1 = strip == 7 ? 192 : 0;
    r.first = cta < 8 ? 1 : 0;
    r.last = cta >= NUM_CTAS - 8 ? STEPS - 2 : STEPS - 1;
    return r;
}
__device__ __forceinline__ void issue_row_load(const RowCopy& r, int i, uint32_t slot) {
    const char* src = (i >= r.first && i <= r.last) ? r.x0 + (uint32_t)i * ROW_BYTES : (const char*)g_zero_row;
    const uint32_t bar = sb + SM_XFULL + slot * SLOT_BYTES, dst = sb + SM_X + slot * SLOT_BYTES;
    expect_tx(bar, XHALF_BYTES - r.cut0);
    bulk_load(dst + r.cut0, src + r.cut0, XHALF_BYTES - r.cut0, bar);
    expect_tx(bar, XHALF_BYTES - r.cut1);
    bulk_load(dst + XHALF_B, src + 32 * 192, XHALF_BYTES - r.cut1, bar);
}

__device__ __forceinline__ float quad_sum(float v) {
    v += __shfl_xor_sync(0xffffffffu, v, 1);
    v += __shfl_xor_sync(0xffffffffu, v, 2);
    return v;
}

__device__ __forceinline__ void load_x(uint32_t (&v)[6][6], const Producer& c, uint32_t row) {
#pragma unroll
    for (int k = 0; k < 6; k++) {
        asm volatile("ld.shared.v4.b32 {%0,%1,%2,%3}, [%4];"
                     : "=r"(v[k][0]), "=r"(v[k][1]), "=r"(v[k][2]), "=r"(v[k][3]) : "r"(row + c.xoff[0] + k * 192));
        asm volatile("ld.shared.v2.b32 {%0,%1}, [%2];" : "=r"(v[k][4]), "=r"(v[k][5]) : "r"(row + c.xoff[1] + k * 192));
    }
}
template <int DY, int STRIDE>
__device__ __forceinline__ void conv_row(uint32_t (&dst)[24], const uint32_t* src, const uint32_t (&v)[6][6], const Producer& c) {
#pragma unroll
    for (int o = 0; o < 4; o++)
#pragma unroll
        for (int u = 0; u < 6; u++)
            dst[o * 6 + u] = bf2_fma(v[o + 2][u], c.w[3 * DY + 2][u], bf2_fma(v[o + 1][u], c.w[3 * DY + 1][u],
                             STRIDE ? bf2_fma(v[o][u], c.w[3 * DY][u], src[o * 6 + u])
                                    : bf2_fma_hi(v[o][u], c.w[3 * DY][u], src[2 * o + 1])));
}
__device__ __forceinline__ void start_sums(float (&d)[4], const uint32_t (&A)[24], const uint32_t (&q)[4], const Params& prm) {
    wg_fence();
#pragma unroll
    for (int k = 0; k < 6; k++) {
        const int r = (k / 3) * 12 + (k % 3) * 2;
        if (k == 0) wgmma_n8<0>(d, A[r], A[r + 6], A[r + 1], A[r + 7], prm.sel[0]);
        else wgmma_n8<1>(d, A[r], A[r + 6], A[r + 1], A[r + 7], prm.sel[k / 3]);
    }
    wgmma_n8<1>(d, q[0], q[1], q[2], q[3], prm.sel[2]);
    wg_commit();
}
__device__ __forceinline__ void finish_sums(float (&d)[4], int lane, float& sum, float& sq) {
    wg_wait<0>();
    asm volatile("" : "+f"(d[0]), "+f"(d[1]), "+f"(d[2]), "+f"(d[3])::"memory");
    sum = (lane & 1) ? d[2] : d[0];
    sq = (lane & 1) ? d[3] : d[1];
    sum += __shfl_xor_sync(0xffffffffu, sum, 4);
    sq += __shfl_xor_sync(0xffffffffu, sq, 4);
}

__device__ __forceinline__ void produce(const Producer& c, const Params& prm) {
    uint32_t A[24], B[24], C[24];
    const RowCopy rc = row_copy(prm);
    uint32_t st[8];
    uint32_t v[6][6];
    float d[4];
    {
        uint32_t ws[6], q[4] = {};
#pragma unroll
        for (int u = 0; u < 6; u++) {
            ws[u] = c.w[0][u];
#pragma unroll
            for (int t = 1; t < 9; t++) ws[u] = bf2_add(ws[u], c.w[t][u]);
        }
        mbar_wait_c<0>(sb + SM_XFULL + rc.first * SLOT_BYTES);
        load_x(v, c, sb + SM_X + rc.first * SLOT_BYTES);
#pragma unroll
        for (int r = 0; r < 24; r++) A[r] = bf2_mul(v[r / 6 + 1][r % 6], ws[r % 6]);
        start_sums(d, A, q, prm);
        float e, sq;
        finish_sums(d, c.lane, e, sq);
        e *= -1.0f / CH;
#pragma unroll
        for (int k = 0; k < NX; k++) sts32(c.own + k * SLOT_BYTES + 4, __float_as_uint(e));
        __syncwarp();
        lds128(st, c.stat);
        lds128(st + 4, c.stat + 16);
#pragma unroll
        for (int r = 0; r < 24; r++) C[r] = 0;
    }
#pragma unroll 1
    for (int i = loop_init<0>();; i++) {
        mbar_wait_c<0>(sb + SM_XFULL + i * SLOT_BYTES);
        load_x(v, c, sb + SM_X + i * SLOT_BYTES);
        fence_async_smem();
        if (c.warp == i) {
            named_sync(6 + i, 128);
            issue_row_load(rc, i + NX, i);
        } else {
            asm volatile("bar.arrive %0, 128;" ::"r"(6 + i) : "memory");
        }
        if (i == 2) break;
        conv_row<1, 1>(B, C, v, c);
        conv_row<0, 0>(C, st, v, c);
    }
    if (c.warp == 3) {
        expect_tx(sb + SM_BAR + BAR_W2 * 8, CH * EX * 2 + EX * 4);
        bulk_load(sb + SM_GAMMA, prm.gamma, EX * 2, sb + SM_BAR + BAR_W2 * 8);
        bulk_load(sb + SM_BETA, prm.beta, EX * 2, sb + SM_BAR + BAR_W2 * 8);
#pragma unroll
        for (int k = 0; k < 6; k++)
            tma_load_2d(sb + SM_W2 + k * 12288, &prm.w2_map, 32 * (k >> 1), 192 * (k & 1), sb + SM_BAR + BAR_W2 * 8);
    }
    uint32_t so = loop_init<0>(), phase = loop_init<1>();
#pragma unroll 1
    for (int t = loop_init<0>(); t < ROWS_PER_CTA; t++) {
        uint32_t q[4];
        conv_row<2, 1>(A, B, v, c);
#pragma unroll
        for (int r = 0; r < 24; r++) q[r / 6] = r % 6 == 0 ? bf2_mul(A[r], A[r]) : bf2_fma(A[r], A[r], q[r / 6]);
        start_sums(d, A, q, prm);
        SPLIT(0, C);
        conv_row<1, 1>(B, C, v, c);
        const float used = __uint_as_float(lds32(c.own + so + 4));
        SPLIT(1, B);
        float sum, sq;
        finish_sums(d, c.lane, sum, sq);
        conv_row<0, 0>(C, st, v, c);
        const float mean = sum * (1.0f / CH);
        const float var = fmaf(sq, 1.0f / CH, fmaf(-mean, mean, LN_EPS_SCALED));
        const float rs = rsqrt_fast(fmaxf(var, LN_EPS_SCALED)) * RSTD_SCALE;
        sts64(c.own + so, pack_bf2(rs, -mean * rs), __float_as_uint(used - mean));
        __syncwarp();
        pin(C);
        lds128(st, c.stat + so);
        lds128(st + 4, c.stat + so + 16);
        mbar_wait2(sb + SM_Y1EMPTY + so, phase, sb + SM_XFULL + so, phase);
        load_x(v, c, sb + SM_X + so);
        const uint32_t yb = sb + SM_Y1 + so;
#pragma unroll
        for (int r = 0; r < 24; r++) A[r] = bf2_affine(A[r], st[2 * (r / 6)]);
        SPLIT(2, A);
#pragma unroll
        for (int o = 0; o < 4; o++) {
            uint32_t y[6];
#pragma unroll
            for (int u = 0; u < 6; u++) y[u] = bf2_rebias_h2(A[o * 6 + u]);
            sts128(yb + c.yoff[0][o & 1] + (o >> 1) * 2048, y[0], y[1], y[2], y[3]);
            sts64(yb + c.yoff[1][o & 1] + (o >> 1) * 1024, y[4], y[5]);
        }
        fence_async_smem();
        __syncwarp();
        mbar_arrive_if(sb + SM_Y1FULL + so, c.lane == 0);
        if ((so += SLOT_BYTES) == NX * SLOT_BYTES) { so = 0; phase ^= 1; }
    }
    mbar_arrive_if(sb + SM_Y1FULL + ROWS_PER_CTA % NX * SLOT_BYTES, c.lane == 0);
}

struct Duty {
    const char* g;
    uint32_t s, bytes;
    int end, zero;
};
__device__ __forceinline__ Duty make_duty(const Params& prm, int wg, int w) {
    const RowCopy rc = row_copy(prm);
    Duty d;
    d.g = (w == 2 ? rc.y0 : rc.x0 + 2 * NX * ROW_BYTES + (w == 0 ? rc.cut0 : w == 1 ? 32 * 192 : 192 + L2_AHEAD * ROW_BYTES)) +
          (uint32_t)wg * ROW_BYTES;
    d.s = wg * SLOT_BYTES + (w == 2 ? sb + SM_Y1 : sb + SM_X + (w == 0 ? rc.cut0 : XHALF_B));
    d.bytes = w >= 2 ? TILE_BYTES : XHALF_BYTES - (w == 0 ? rc.cut0 : rc.cut1);
    d.end = w == 2 ? ROWS_PER_CTA : w < 2 ? STEPS + 1 - 2 * NX : rc.last + 1 - 2 * NX - L2_AHEAD;
    d.zero = rc.last + 1 - 2 * NX;
    return d;
}

static_assert(sb + SM_Y1FULL == 174472 && sb + SM_Y1EMPTY == 174480 && sb + SM_XFULL == 174464 && SLOT_BYTES == 26624, "layout");
__device__ __forceinline__ void consume(float (&acc)[2][2], uint32_t w1t, uint32_t yd, uint32_t wd, uint32_t own_slot, const Duty& d,
                                        uint32_t role, uint32_t lane) {
    asm volatile(
        "{\n"
        ".reg .b32 z<32>, w<44>, p<2>, a<4>, lo<4>, hi<4>, t<2>, g<2>, q<4>, n, so, sp, ph, c, tt, cnt;\n"
        ".reg .b16 xl, xh, xr;\n"
        ".reg .f32 f0, f1;\n"
        ".reg .b64 ds<6>, wd, gp, src;\n"
        ".reg .pred pt, pf, pr, pw, pl, pe;\n"
        "setp.ne.b32 pt, 1, 0; setp.ne.b32 pf, 0, 0; setp.eq.u32 pl, %15, 0;\n"
        "mov.b32 c, 0x40D940D9;\n"
        "ldmatrix.sync.aligned.m8n8.x4.trans.shared.b16 {w0,w1,w2,w3}, [%4+0];\n"
        "ldmatrix.sync.aligned.m8n8.x4.trans.shared.b16 {w4,w5,w6,w7}, [%4+2048];\n"
        "ldmatrix.sync.aligned.m8n8.x4.trans.shared.b16 {w8,w9,w10,w11}, [%4+4096];\n"
        "ldmatrix.sync.aligned.m8n8.x4.trans.shared.b16 {w12,w13,w14,w15}, [%4+6144];\n"
        "ldmatrix.sync.aligned.m8n8.x4.trans.shared.b16 {w16,w17,w18,w19}, [%4+8192];\n"
        "ldmatrix.sync.aligned.m8n8.x4.trans.shared.b16 {w20,w21,w22,w23}, [%4+10240];\n"
        "ldmatrix.sync.aligned.m8n8.x4.trans.shared.b16 {w24,w25,w26,w27}, [%4+12288];\n"
        "ldmatrix.sync.aligned.m8n8.x4.trans.shared.b16 {w28,w29,w30,w31}, [%4+14336];\n"
        "ldmatrix.sync.aligned.m8n8.x4.trans.shared.b16 {w32,w33,w34,w35}, [%4+16384];\n"
        "ldmatrix.sync.aligned.m8n8.x4.trans.shared.b16 {w36,w37,w38,w39}, [%4+18432];\n"
        "ldmatrix.sync.aligned.m8n8.x4.trans.shared.b16 {w40,w41,w42,w43}, [%4+20480];\n"
        "mov.b32 p0, 0; mov.b32 p1, 0; mov.b32 t0, 0; mov.b32 t1, 0; mov.b32 g0, 0; mov.b32 g1, 0; mov.b32 a0, 0; mov.b32 a1, 0; mov.b32 lo0, 0; mov.b32 lo1, 0; mov.b32 hi0, 0; mov.b32 hi1, 0; mov.b32 q0, 0; mov.b32 q1, 0; mov.b32 q2, 0; mov.b32 q3, 0;\n"
        "mov.b32 z16, 0; mov.b32 z17, 0; mov.b32 z18, 0; mov.b32 z19, 0; mov.b32 z20, 0; mov.b32 z21, 0; mov.b32 z22, 0; mov.b32 z23, 0; mov.b32 z24, 0; mov.b32 z25, 0; mov.b32 z26, 0; mov.b32 z27, 0; mov.b32 z28, 0; mov.b32 z29, 0; mov.b32 z30, 0; mov.b32 z31, 0;\n"
        "mov.f32 %0, 0f00000000; mov.f32 %1, 0f00000000; mov.f32 %2, 0f00000000; mov.f32 %3, 0f00000000;\n"
        "mov.u32 n, 0; mov.u32 so, 0; mov.u32 sp, 0; mov.u32 ph, 0; mov.b64 gp, %8; mov.b64 wd, {%6, 0x40000040};\n"
        "shr.u32 tt, so, 4; add.u32 tt, tt, %5; mov.b64 ds0, {tt, 0x40000040}; mov.b64 ds4, {tt, 0x80000020};\n"
        "add.s64 ds1, ds0, 2; add.s64 ds2, ds0, 4; add.s64 ds3, ds0, 6; add.s64 ds5, ds4, 514; add.s64 ds4, ds4, 512;\n"
        "mbarrier.try_wait.parity.shared::cta.b64 pw, [so+174472], ph;\n"
        "@!pw bra.uni SPIN0;\n"
        "BACK0:\n"
        ASM_TS
        "wgmma.fence.sync.aligned;\n"
        "wgmma.mma_async.sync.aligned.m64n64k16.f16.f16.f16 {z0,z1,z2,z3,z4,z5,z6,z7,z8,z9,z10,z11,z12,z13,z14,z15}, {w0,w1,w2,w3}, ds0, pf, 1, 1, 0;\n"
        "wgmma.mma_async.sync.aligned.m64n64k16.f16.f16.f16 {z0,z1,z2,z3,z4,z5,z6,z7,z8,z9,z10,z11,z12,z13,z14,z15}, {w4,w5,w6,w7}, ds1, pt, 1, 1, 0;\n"
        "wgmma.mma_async.sync.aligned.m64n64k16.f16.f16.f16 {z0,z1,z2,z3,z4,z5,z6,z7,z8,z9,z10,z11,z12,z13,z14,z15}, {w8,w9,w10,w11}, ds2, pt, 1, 1, 0;\n"
        "wgmma.mma_async.sync.aligned.m64n64k16.f16.f16.f16 {z0,z1,z2,z3,z4,z5,z6,z7,z8,z9,z10,z11,z12,z13,z14,z15}, {w12,w13,w14,w15}, ds3, pt, 1, 1, 0;\n"
        "wgmma.mma_async.sync.aligned.m64n64k16.f16.f16.f16 {z0,z1,z2,z3,z4,z5,z6,z7,z8,z9,z10,z11,z12,z13,z14,z15}, {w16,w17,w18,w19}, ds4, pt, 1, 1, 0;\n"
        "wgmma.mma_async.sync.aligned.m64n64k16.f16.f16.f16 {z0,z1,z2,z3,z4,z5,z6,z7,z8,z9,z10,z11,z12,z13,z14,z15}, {w20,w21,w22,w23}, ds5, pt, 1, 1, 0;\n"
        "wgmma.commit_group.sync.aligned;\n"
        "LOOP:\n"
        ASM_TRC
        "setp.eq.u32 pr, so, %7;\n"
        "@pr bra.uni DUTY;\n"
        "TOP:\n"
        "wgmma.wait_group.sync.aligned 0;\n"
        "mov.b32 {xl, xh}, a0; tanh.approx.f16 xr, xl; cvt.u32.u16 lo0, xr; tanh.approx.f16 xr, xh; cvt.u32.u16 hi0, xr; fma.rn.f16x2 p0, z0, z0, c; mul.rn.f16x2 a1, z31, p1; fma.rn.f16x2 q3, g1, g1, q3; fma.rn.f16x2 g0, z28, t0, z28; prmt.b32 t1, lo1, hi1, 0x5410;\n"
        "B31:\n"
        "mov.b32 {xl, xh}, a1; tanh.approx.f16 xr, xl; cvt.u32.u16 lo1, xr; tanh.approx.f16 xr, xh; cvt.u32.u16 hi1, xr; fma.rn.f16x2 p1, z1, z1, c; mul.rn.f16x2 a0, z0, p0; fma.rn.f16x2 q2, g0, g0, q2; fma.rn.f16x2 g1, z29, t1, z29; prmt.b32 t0, lo0, hi0, 0x5410;\n"
        "B0:\n"
        "mov.b32 {xl, xh}, a0; tanh.approx.f16 xr, xl; cvt.u32.u16 lo0, xr; tanh.approx.f16 xr, xh; cvt.u32.u16 hi0, xr; fma.rn.f16x2 p0, z2, z2, c; mul.rn.f16x2 a1, z1, p1; fma.rn.f16x2 q3, g1, g1, q3; fma.rn.f16x2 g0, z30, t0, z30; prmt.b32 t1, lo1, hi1, 0x5410;\n"
        "B1:\n"
        "mov.b32 {xl, xh}, a1; tanh.approx.f16 xr, xl; cvt.u32.u16 lo1, xr; tanh.approx.f16 xr, xh; cvt.u32.u16 hi1, xr; fma.rn.f16x2 p1, z3, z3, c; mul.rn.f16x2 a0, z2, p0; fma.rn.f16x2 q2, g0, g0, q2; fma.rn.f16x2 g1, z31, t1, z31; prmt.b32 t0, lo0, hi0, 0x5410;\n"
        "B2:\n"
        "wgmma.fence.sync.aligned;\n"
        "wgmma.mma_async.sync.aligned.m64n64k16.f16.f16.f16 {z16,z17,z18,z19,z20,z21,z22,z23,z24,z25,z26,z27,z28,z29,z30,z31}, {w24,w25,w26,w27}, ds0, pf, 1, 1, 0;\n"
        "wgmma.mma_async.sync.aligned.m64n64k16.f16.f16.f16 {z16,z17,z18,z19,z20,z21,z22,z23,z24,z25,z26,z27,z28,z29,z30,z31}, {w28,w29,w30,w31}, ds1, pt, 1, 1, 0;\n"
        "wgmma.mma_async.sync.aligned.m64n64k16.f16.f16.f16 {z16,z17,z18,z19,z20,z21,z22,z23,z24,z25,z26,z27,z28,z29,z30,z31}, {w32,w33,w34,w35}, ds2, pt, 1, 1, 0;\n"
        "mov.b32 {xl, xh}, a0; tanh.approx.f16 xr, xl; cvt.u32.u16 lo0, xr; tanh.approx.f16 xr, xh; cvt.u32.u16 hi0, xr; fma.rn.f16x2 p0, z4, z4, c; mul.rn.f16x2 a1, z3, p1; fma.rn.f16x2 q3, g1, g1, q3; fma.rn.f16x2 g0, z0, t0, z0; prmt.b32 t1, lo1, hi1, 0x5410;\n"
        "B3:\n"
        "mov.b32 {xl, xh}, a1; tanh.approx.f16 xr, xl; cvt.u32.u16 lo1, xr; tanh.approx.f16 xr, xh; cvt.u32.u16 hi1, xr; fma.rn.f16x2 p1, z5, z5, c; mul.rn.f16x2 a0, z4, p0; fma.rn.f16x2 q0, g0, g0, q0; fma.rn.f16x2 g1, z1, t1, z1; prmt.b32 t0, lo0, hi0, 0x5410;\n"
        "B4:\n"
        "mov.b32 {xl, xh}, a0; tanh.approx.f16 xr, xl; cvt.u32.u16 lo0, xr; tanh.approx.f16 xr, xh; cvt.u32.u16 hi0, xr; fma.rn.f16x2 p0, z6, z6, c; mul.rn.f16x2 a1, z5, p1; fma.rn.f16x2 q1, g1, g1, q1; fma.rn.f16x2 g0, z2, t0, z2; prmt.b32 t1, lo1, hi1, 0x5410;\n"
        "B5:\n"
        "wgmma.mma_async.sync.aligned.m64n64k16.f16.f16.f16 {z16,z17,z18,z19,z20,z21,z22,z23,z24,z25,z26,z27,z28,z29,z30,z31}, {w36,w37,w38,w39}, ds3, pt, 1, 1, 0;\n"
        "wgmma.mma_async.sync.aligned.m64n64k16.f16.f16.f16 {z16,z17,z18,z19,z20,z21,z22,z23,z24,z25,z26,z27,z28,z29,z30,z31}, {w40,w41,w42,w43}, ds4, pt, 1, 1, 0;\n"
        "wgmma.mma_async.sync.aligned.m64n64k16.f16.f16.f16 {z16,z17,z18,z19,z20,z21,z22,z23,z24,z25,z26,z27,z28,z29,z30,z31}, wd, ds5, pt, 1, 1, 1, 0;\n"
        "wgmma.commit_group.sync.aligned;\n"
        "mov.b32 {xl, xh}, a1; tanh.approx.f16 xr, xl; cvt.u32.u16 lo1, xr; tanh.approx.f16 xr, xh; cvt.u32.u16 hi1, xr; fma.rn.f16x2 p1, z7, z7, c; mul.rn.f16x2 a0, z6, p0; fma.rn.f16x2 q0, g0, g0, q0; fma.rn.f16x2 g1, z3, t1, z3; prmt.b32 t0, lo0, hi0, 0x5410;\n"
        "B6:\n"
        "mov.u32 sp, so; add.u32 so, so, 26624; setp.eq.u32 pr, so, 79872; selp.u32 so, 0, so, pr; selp.u32 tt, 1, 0, pr; xor.b32 ph, ph, tt;\n"
        "mov.b32 {xl, xh}, a0; tanh.approx.f16 xr, xl; cvt.u32.u16 lo0, xr; tanh.approx.f16 xr, xh; cvt.u32.u16 hi0, xr; fma.rn.f16x2 p0, z8, z8, c; mul.rn.f16x2 a1, z7, p1; fma.rn.f16x2 q1, g1, g1, q1; fma.rn.f16x2 g0, z4, t0, z4; prmt.b32 t1, lo1, hi1, 0x5410;\n"
        "B7:\n"
        "shr.u32 tt, so, 4; add.u32 tt, tt, %5; mov.b64 ds0, {tt, 0x40000040}; mov.b64 ds4, {tt, 0x80000020};\n"
        "add.s64 ds1, ds0, 2; add.s64 ds2, ds0, 4; add.s64 ds3, ds0, 6; add.s64 ds5, ds4, 514; add.s64 ds4, ds4, 512;\n"
        "mov.b32 {xl, xh}, a1; tanh.approx.f16 xr, xl; cvt.u32.u16 lo1, xr; tanh.approx.f16 xr, xh; cvt.u32.u16 hi1, xr; fma.rn.f16x2 p1, z9, z9, c; mul.rn.f16x2 a0, z8, p0; fma.rn.f16x2 q0, g0, g0, q0; fma.rn.f16x2 g1, z5, t1, z5; prmt.b32 t0, lo0, hi0, 0x5410;\n"
        "B8:\n"
        "mov.b32 {xl, xh}, a0; tanh.approx.f16 xr, xl; cvt.u32.u16 lo0, xr; tanh.approx.f16 xr, xh; cvt.u32.u16 hi0, xr; fma.rn.f16x2 p0, z10, z10, c; mul.rn.f16x2 a1, z9, p1; fma.rn.f16x2 q1, g1, g1, q1; fma.rn.f16x2 g0, z6, t0, z6; prmt.b32 t1, lo1, hi1, 0x5410;\n"
        "B9:\n"
        "mov.b32 {xl, xh}, a1; tanh.approx.f16 xr, xl; cvt.u32.u16 lo1, xr; tanh.approx.f16 xr, xh; cvt.u32.u16 hi1, xr; fma.rn.f16x2 p1, z11, z11, c; mul.rn.f16x2 a0, z10, p0; fma.rn.f16x2 q0, g0, g0, q0; fma.rn.f16x2 g1, z7, t1, z7; prmt.b32 t0, lo0, hi0, 0x5410;\n"
        "B10:\n"
        "mov.b32 {xl, xh}, a0; tanh.approx.f16 xr, xl; cvt.u32.u16 lo0, xr; tanh.approx.f16 xr, xh; cvt.u32.u16 hi0, xr; fma.rn.f16x2 p0, z12, z12, c; mul.rn.f16x2 a1, z11, p1; fma.rn.f16x2 q1, g1, g1, q1; fma.rn.f16x2 g0, z8, t0, z8; prmt.b32 t1, lo1, hi1, 0x5410;\n"
        "B11:\n"
        "mov.b32 {xl, xh}, a1; tanh.approx.f16 xr, xl; cvt.u32.u16 lo1, xr; tanh.approx.f16 xr, xh; cvt.u32.u16 hi1, xr; fma.rn.f16x2 p1, z13, z13, c; mul.rn.f16x2 a0, z12, p0; fma.rn.f16x2 q0, g0, g0, q0; fma.rn.f16x2 g1, z9, t1, z9; prmt.b32 t0, lo0, hi0, 0x5410;\n"
        "B12:\n"
        "mov.b32 {xl, xh}, a0; tanh.approx.f16 xr, xl; cvt.u32.u16 lo0, xr; tanh.approx.f16 xr, xh; cvt.u32.u16 hi0, xr; fma.rn.f16x2 p0, z14, z14, c; mul.rn.f16x2 a1, z13, p1; fma.rn.f16x2 q1, g1, g1, q1; fma.rn.f16x2 g0, z10, t0, z10; prmt.b32 t1, lo1, hi1, 0x5410;\n"
        "B13:\n"
        "mov.b32 {xl, xh}, a1; tanh.approx.f16 xr, xl; cvt.u32.u16 lo1, xr; tanh.approx.f16 xr, xh; cvt.u32.u16 hi1, xr; fma.rn.f16x2 p1, z15, z15, c; mul.rn.f16x2 a0, z14, p0; fma.rn.f16x2 q0, g0, g0, q0; fma.rn.f16x2 g1, z11, t1, z11; prmt.b32 t0, lo0, hi0, 0x5410;\n"
        "B14:\n"
        "wgmma.wait_group.sync.aligned 0;\n"
        "cp.async.bulk.wait_group.read 0;\n"
        "@pl mbarrier.arrive.shared::cta.b64 _, [sp+174480];\n"
        "mov.b32 {xl, xh}, a0; tanh.approx.f16 xr, xl; cvt.u32.u16 lo0, xr; tanh.approx.f16 xr, xh; cvt.u32.u16 hi0, xr; fma.rn.f16x2 p0, z16, z16, c; mul.rn.f16x2 a1, z15, p1; fma.rn.f16x2 q1, g1, g1, q1; fma.rn.f16x2 g0, z12, t0, z12; prmt.b32 t1, lo1, hi1, 0x5410;\n"
        "B15:\n"
        "mbarrier.try_wait.parity.shared::cta.b64 pw, [so+174472], ph;\n"
        "mov.b32 {xl, xh}, a1; tanh.approx.f16 xr, xl; cvt.u32.u16 lo1, xr; tanh.approx.f16 xr, xh; cvt.u32.u16 hi1, xr; fma.rn.f16x2 p1, z17, z17, c; mul.rn.f16x2 a0, z16, p0; fma.rn.f16x2 q0, g0, g0, q0; fma.rn.f16x2 g1, z13, t1, z13; prmt.b32 t0, lo0, hi0, 0x5410;\n"
        "B16:\n"
        "mov.b32 {xl, xh}, a0; tanh.approx.f16 xr, xl; cvt.u32.u16 lo0, xr; tanh.approx.f16 xr, xh; cvt.u32.u16 hi0, xr; fma.rn.f16x2 p0, z18, z18, c; mul.rn.f16x2 a1, z17, p1; fma.rn.f16x2 q1, g1, g1, q1; fma.rn.f16x2 g0, z14, t0, z14; prmt.b32 t1, lo1, hi1, 0x5410;\n"
        "B17:\n"
        "mov.b32 {xl, xh}, a1; tanh.approx.f16 xr, xl; cvt.u32.u16 lo1, xr; tanh.approx.f16 xr, xh; cvt.u32.u16 hi1, xr; fma.rn.f16x2 p1, z19, z19, c; mul.rn.f16x2 a0, z18, p0; fma.rn.f16x2 q0, g0, g0, q0; fma.rn.f16x2 g1, z15, t1, z15; prmt.b32 t0, lo0, hi0, 0x5410;\n"
        "B18:\n"
        "@!pw bra.uni SPIN;\n"
        "BACK:\n"
        "wgmma.fence.sync.aligned;\n"
        "wgmma.mma_async.sync.aligned.m64n64k16.f16.f16.f16 {z0,z1,z2,z3,z4,z5,z6,z7,z8,z9,z10,z11,z12,z13,z14,z15}, {w0,w1,w2,w3}, ds0, pf, 1, 1, 0;\n"
        "wgmma.mma_async.sync.aligned.m64n64k16.f16.f16.f16 {z0,z1,z2,z3,z4,z5,z6,z7,z8,z9,z10,z11,z12,z13,z14,z15}, {w4,w5,w6,w7}, ds1, pt, 1, 1, 0;\n"
        "wgmma.mma_async.sync.aligned.m64n64k16.f16.f16.f16 {z0,z1,z2,z3,z4,z5,z6,z7,z8,z9,z10,z11,z12,z13,z14,z15}, {w8,w9,w10,w11}, ds2, pt, 1, 1, 0;\n"
        "mov.b32 {xl, xh}, a0; tanh.approx.f16 xr, xl; cvt.u32.u16 lo0, xr; tanh.approx.f16 xr, xh; cvt.u32.u16 hi0, xr; fma.rn.f16x2 p0, z20, z20, c; mul.rn.f16x2 a1, z19, p1; fma.rn.f16x2 q1, g1, g1, q1; fma.rn.f16x2 g0, z16, t0, z16; prmt.b32 t1, lo1, hi1, 0x5410;\n"
        "B19:\n"
        "mov.b32 {xl, xh}, a1; tanh.approx.f16 xr, xl; cvt.u32.u16 lo1, xr; tanh.approx.f16 xr, xh; cvt.u32.u16 hi1, xr; fma.rn.f16x2 p1, z21, z21, c; mul.rn.f16x2 a0, z20, p0; fma.rn.f16x2 q2, g0, g0, q2; fma.rn.f16x2 g1, z17, t1, z17; prmt.b32 t0, lo0, hi0, 0x5410;\n"
        "B20:\n"
        "mov.b32 {xl, xh}, a0; tanh.approx.f16 xr, xl; cvt.u32.u16 lo0, xr; tanh.approx.f16 xr, xh; cvt.u32.u16 hi0, xr; fma.rn.f16x2 p0, z22, z22, c; mul.rn.f16x2 a1, z21, p1; fma.rn.f16x2 q3, g1, g1, q3; fma.rn.f16x2 g0, z18, t0, z18; prmt.b32 t1, lo1, hi1, 0x5410;\n"
        "B21:\n"
        "wgmma.mma_async.sync.aligned.m64n64k16.f16.f16.f16 {z0,z1,z2,z3,z4,z5,z6,z7,z8,z9,z10,z11,z12,z13,z14,z15}, {w12,w13,w14,w15}, ds3, pt, 1, 1, 0;\n"
        "wgmma.mma_async.sync.aligned.m64n64k16.f16.f16.f16 {z0,z1,z2,z3,z4,z5,z6,z7,z8,z9,z10,z11,z12,z13,z14,z15}, {w16,w17,w18,w19}, ds4, pt, 1, 1, 0;\n"
        "wgmma.mma_async.sync.aligned.m64n64k16.f16.f16.f16 {z0,z1,z2,z3,z4,z5,z6,z7,z8,z9,z10,z11,z12,z13,z14,z15}, {w20,w21,w22,w23}, ds5, pt, 1, 1, 0;\n"
        "wgmma.commit_group.sync.aligned;\n"
        "mov.b32 {xl, xh}, a1; tanh.approx.f16 xr, xl; cvt.u32.u16 lo1, xr; tanh.approx.f16 xr, xh; cvt.u32.u16 hi1, xr; fma.rn.f16x2 p1, z23, z23, c; mul.rn.f16x2 a0, z22, p0; fma.rn.f16x2 q2, g0, g0, q2; fma.rn.f16x2 g1, z19, t1, z19; prmt.b32 t0, lo0, hi0, 0x5410;\n"
        "B22:\n"
        "mov.b32 {xl, xh}, a0; tanh.approx.f16 xr, xl; cvt.u32.u16 lo0, xr; tanh.approx.f16 xr, xh; cvt.u32.u16 hi0, xr; fma.rn.f16x2 p0, z24, z24, c; mul.rn.f16x2 a1, z23, p1; fma.rn.f16x2 q3, g1, g1, q3; fma.rn.f16x2 g0, z20, t0, z20; prmt.b32 t1, lo1, hi1, 0x5410;\n"
        "B23:\n"
        "mov.b32 {xl, xh}, a1; tanh.approx.f16 xr, xl; cvt.u32.u16 lo1, xr; tanh.approx.f16 xr, xh; cvt.u32.u16 hi1, xr; fma.rn.f16x2 p1, z25, z25, c; mul.rn.f16x2 a0, z24, p0; fma.rn.f16x2 q2, g0, g0, q2; fma.rn.f16x2 g1, z21, t1, z21; prmt.b32 t0, lo0, hi0, 0x5410;\n"
        "B24:\n"
        "mov.b32 {xl, xh}, a0; tanh.approx.f16 xr, xl; cvt.u32.u16 lo0, xr; tanh.approx.f16 xr, xh; cvt.u32.u16 hi0, xr; fma.rn.f16x2 p0, z26, z26, c; mul.rn.f16x2 a1, z25, p1; fma.rn.f16x2 q3, g1, g1, q3; fma.rn.f16x2 g0, z22, t0, z22; prmt.b32 t1, lo1, hi1, 0x5410;\n"
        "B25:\n"
        "mov.b32 {xl, xh}, a1; tanh.approx.f16 xr, xl; cvt.u32.u16 lo1, xr; tanh.approx.f16 xr, xh; cvt.u32.u16 hi1, xr; fma.rn.f16x2 p1, z27, z27, c; mul.rn.f16x2 a0, z26, p0; fma.rn.f16x2 q2, g0, g0, q2; fma.rn.f16x2 g1, z23, t1, z23; prmt.b32 t0, lo0, hi0, 0x5410;\n"
        "B26:\n"
        "mov.b32 {xl, xh}, a0; tanh.approx.f16 xr, xl; cvt.u32.u16 lo0, xr; tanh.approx.f16 xr, xh; cvt.u32.u16 hi0, xr; fma.rn.f16x2 p0, z28, z28, c; mul.rn.f16x2 a1, z27, p1; fma.rn.f16x2 q3, g1, g1, q3; fma.rn.f16x2 g0, z24, t0, z24; prmt.b32 t1, lo1, hi1, 0x5410;\n"
        "B27:\n"
        "add.u32 n, n, 1; setp.lt.u32 pe, n, 32;\n"
        "mov.b32 {xl, xh}, a1; tanh.approx.f16 xr, xl; cvt.u32.u16 lo1, xr; tanh.approx.f16 xr, xh; cvt.u32.u16 hi1, xr; fma.rn.f16x2 p1, z29, z29, c; mul.rn.f16x2 a0, z28, p0; fma.rn.f16x2 q2, g0, g0, q2; fma.rn.f16x2 g1, z25, t1, z25; prmt.b32 t0, lo0, hi0, 0x5410;\n"
        "B28:\n"
        "mov.b32 {xl, xh}, a0; tanh.approx.f16 xr, xl; cvt.u32.u16 lo0, xr; tanh.approx.f16 xr, xh; cvt.u32.u16 hi0, xr; fma.rn.f16x2 p0, z30, z30, c; mul.rn.f16x2 a1, z29, p1; fma.rn.f16x2 q3, g1, g1, q3; fma.rn.f16x2 g0, z26, t0, z26; prmt.b32 t1, lo1, hi1, 0x5410;\n"
        "B29:\n"
        "mov.b32 {xl, xh}, a1; tanh.approx.f16 xr, xl; cvt.u32.u16 lo1, xr; tanh.approx.f16 xr, xh; cvt.u32.u16 hi1, xr; fma.rn.f16x2 p1, z31, z31, c; mul.rn.f16x2 a0, z30, p0; fma.rn.f16x2 q2, g0, g0, q2; fma.rn.f16x2 g1, z27, t1, z27; prmt.b32 t0, lo0, hi0, 0x5410;\n"
        "@pe bra.uni LOOP;\n"
        "bra.uni DONE;\n"
        "SPIN0: mov.u32 cnt, 0;\n"
        "SPIN0L:\n"
        "mbarrier.try_wait.parity.shared::cta.b64 pw, [so+174472], ph;\n"
        "@pw bra.uni BACK0;\n"
        "add.u32 cnt, cnt, 1; setp.lt.u32 pw, cnt, 0x100000;\n"
        "@pw bra.uni SPIN0L;\n"
        "trap;\n"
        "SPIN: mov.u32 cnt, 0;\n"
        "SPINL:\n"
        "mbarrier.try_wait.parity.shared::cta.b64 pw, [so+174472], ph;\n"
        "@pw bra.uni BACK;\n"
        "add.u32 cnt, cnt, 1; setp.lt.u32 pw, cnt, 0x100000;\n"
        "@pw bra.uni SPINL;\n"
        "trap;\n"
        "DUTY:\n"
        "setp.ge.s32 pr, n, %11;\n"
        "@pr bra.uni FLUSH;\n"
        "setp.ge.u32 pr, %13, 2;\n"
        "@pr bra.uni ROLE2;\n"
        "setp.ge.s32 pr, n, %12; selp.b64 src, %14, gp, pr; add.u32 tt, %7, 174464;\n"
        "elect.sync _|pr, 0xffffffff;\n"
        "@pr mbarrier.arrive.expect_tx.shared::cta.b64 _, [tt], %10;\n"
        "@pr cp.async.bulk.shared::cluster.global.mbarrier::complete_tx::bytes [%9], [src], %10, [tt];\n"
        "bra.uni FLUSH;\n"
        "ROLE2:\n"
        "setp.eq.u32 pr, %13, 3;\n"
        "@pr bra.uni ROLE3;\n"
        "elect.sync _|pr, 0xffffffff;\n"
        "@pr cp.async.bulk.global.shared::cta.bulk_group [gp], [%9], 12288;\n"
        "@pr cp.async.bulk.commit_group;\n"
        "bra.uni FLUSH;\n"
        "ROLE3:\n"
        "elect.sync _|pr, 0xffffffff;\n"
        "@pr cp.async.bulk.prefetch.L2.global [gp], 12288;\n"
        "FLUSH:\n"
        "add.s64 gp, gp, 294912;\n"
        "mov.b32 {xl, xh}, q0; cvt.f32.f16 f0, xl; cvt.f32.f16 f1, xh; add.f32 f0, f0, f1; add.f32 %0, %0, f0; mov.b32 q0, 0;\n"
        "mov.b32 {xl, xh}, q1; cvt.f32.f16 f0, xl; cvt.f32.f16 f1, xh; add.f32 f0, f0, f1; add.f32 %1, %1, f0; mov.b32 q1, 0;\n"
        "mov.b32 {xl, xh}, q2; cvt.f32.f16 f0, xl; cvt.f32.f16 f1, xh; add.f32 f0, f0, f1; add.f32 %2, %2, f0; mov.b32 q2, 0;\n"
        "mov.b32 {xl, xh}, q3; cvt.f32.f16 f0, xl; cvt.f32.f16 f1, xh; add.f32 f0, f0, f1; add.f32 %3, %3, f0; mov.b32 q3, 0;\n"
        "setp.ne.u32 pr, %5, 0;\n"
        "@pr bra.uni TOP;\n"
        "wgmma.wait_group.sync.aligned 0;\n"
        "wgmma.fence.sync.aligned;\n"
        "setp.eq.u32 pr, n, 1000; @pr bra.uni B31;\n"
        "setp.eq.u32 pr, n, 1001; @pr bra.uni B0;\n"
        "setp.eq.u32 pr, n, 1002; @pr bra.uni B1;\n"
        "setp.eq.u32 pr, n, 1003; @pr bra.uni B2;\n"
        "setp.eq.u32 pr, n, 1004; @pr bra.uni B3;\n"
        "setp.eq.u32 pr, n, 1005; @pr bra.uni B4;\n"
        "setp.eq.u32 pr, n, 1006; @pr bra.uni B5;\n"
        "setp.eq.u32 pr, n, 1007; @pr bra.uni B6;\n"
        "setp.eq.u32 pr, n, 1008; @pr bra.uni B7;\n"
        "setp.eq.u32 pr, n, 1009; @pr bra.uni B8;\n"
        "setp.eq.u32 pr, n, 1010; @pr bra.uni B9;\n"
        "setp.eq.u32 pr, n, 1011; @pr bra.uni B10;\n"
        "setp.eq.u32 pr, n, 1012; @pr bra.uni B11;\n"
        "setp.eq.u32 pr, n, 1013; @pr bra.uni B12;\n"
        "setp.eq.u32 pr, n, 1014; @pr bra.uni B13;\n"
        "setp.eq.u32 pr, n, 1015; @pr bra.uni B14;\n"
        "setp.eq.u32 pr, n, 1016; @pr bra.uni B15;\n"
        "setp.eq.u32 pr, n, 1017; @pr bra.uni B16;\n"
        "setp.eq.u32 pr, n, 1018; @pr bra.uni B17;\n"
        "setp.eq.u32 pr, n, 1019; @pr bra.uni B18;\n"
        "setp.eq.u32 pr, n, 1020; @pr bra.uni B19;\n"
        "setp.eq.u32 pr, n, 1021; @pr bra.uni B20;\n"
        "setp.eq.u32 pr, n, 1022; @pr bra.uni B21;\n"
        "setp.eq.u32 pr, n, 1023; @pr bra.uni B22;\n"
        "setp.eq.u32 pr, n, 1024; @pr bra.uni B23;\n"
        "setp.eq.u32 pr, n, 1025; @pr bra.uni B24;\n"
        "setp.eq.u32 pr, n, 1026; @pr bra.uni B25;\n"
        "setp.eq.u32 pr, n, 1027; @pr bra.uni B26;\n"
        "setp.eq.u32 pr, n, 1028; @pr bra.uni B27;\n"
        "setp.eq.u32 pr, n, 1029; @pr bra.uni B28;\n"
        "setp.eq.u32 pr, n, 1030; @pr bra.uni B29;\n"
        "trap;\n"
        "DONE:\n"
        "mov.b32 {xl, xh}, a0; tanh.approx.f16 xr, xl; cvt.u32.u16 lo0, xr; tanh.approx.f16 xr, xh; cvt.u32.u16 hi0, xr; mul.rn.f16x2 a1, z31, p1; fma.rn.f16x2 q3, g1, g1, q3; fma.rn.f16x2 g0, z28, t0, z28; prmt.b32 t1, lo1, hi1, 0x5410;\n"
        "mov.b32 {xl, xh}, a1; tanh.approx.f16 xr, xl; cvt.u32.u16 lo1, xr; tanh.approx.f16 xr, xh; cvt.u32.u16 hi1, xr; fma.rn.f16x2 q2, g0, g0, q2; fma.rn.f16x2 g1, z29, t1, z29; prmt.b32 t0, lo0, hi0, 0x5410;\n"
        "fma.rn.f16x2 q3, g1, g1, q3; fma.rn.f16x2 g0, z30, t0, z30; prmt.b32 t1, lo1, hi1, 0x5410;\n"
        "fma.rn.f16x2 q2, g0, g0, q2; fma.rn.f16x2 g1, z31, t1, z31;\n"
        "fma.rn.f16x2 q3, g1, g1, q3;\n"
        "mov.b32 {xl, xh}, q0; cvt.f32.f16 f0, xl; cvt.f32.f16 f1, xh; add.f32 f0, f0, f1; add.f32 %0, %0, f0; mov.b32 q0, 0;\n"
        "mov.b32 {xl, xh}, q1; cvt.f32.f16 f0, xl; cvt.f32.f16 f1, xh; add.f32 f0, f0, f1; add.f32 %1, %1, f0; mov.b32 q1, 0;\n"
        "mov.b32 {xl, xh}, q2; cvt.f32.f16 f0, xl; cvt.f32.f16 f1, xh; add.f32 f0, f0, f1; add.f32 %2, %2, f0; mov.b32 q2, 0;\n"
        "mov.b32 {xl, xh}, q3; cvt.f32.f16 f0, xl; cvt.f32.f16 f1, xh; add.f32 f0, f0, f1; add.f32 %3, %3, f0; mov.b32 q3, 0;\n"
        "wgmma.wait_group.sync.aligned 0;\n"
        "}\n"
        : "=f"(acc[0][0]), "=f"(acc[0][1]), "=f"(acc[1][0]), "=f"(acc[1][1])
        : "r"(w1t), "r"(yd), "r"(wd), "r"(own_slot), "l"(d.g), "r"(d.s), "r"(d.bytes), "r"(d.end), "r"(d.zero), "r"(role),
          "l"(g_zero_row), "r"(lane)
        : "memory");
}
template <int M, bool LAST_SMEM = true>
__device__ __forceinline__ void gemm1_t(uint32_t (&d)[16], const uint32_t* wa, uint32_t yd, uint32_t wd) {
    wg_fence();
    wgmma_n64_h_set<0>(d, wa, desc<1024, 1>(yd, 0));
#pragma unroll
    for (int kk = 1; kk < (LAST_SMEM ? 5 : 6); kk++)
        wgmma_n64_h_acc<0>(d, wa + kk * 4, kk < 4 ? desc<1024, 1>(yd, kk * 32) : desc<512, 2>(yd, 8192 + (kk - 4) * 32));
    if (LAST_SMEM) wgmma_n64_h_acc_ss(d, desc<1024, 1>(wd, M * 12288), desc<512, 2>(yd, 8192 + 32));
    wg_commit();
}

#define GTAIL 0
__device__ __forceinline__ void gelu_sumsq_h(uint32_t (&d)[16], uint32_t (&q)[2], uint32_t key) {
#pragma unroll
    for (int r = 0; r < 16; r++) {
        if (GTAIL && r == 16 - GTAIL) sched_fence<GTAIL ? GTAIL : 2>(d + r, key);
        const uint32_t gv = gelu2(d[r]);
        q[r & 1] = h2_fma(gv, gv, q[r & 1]);
    }
}
__device__ __forceinline__ void flush_sumsq(uint32_t (&q)[2], float (&acc)[2]) {
#pragma unroll
    for (int h = 0; h < 2; h++) {
        float lo, hi;
        h2_unpack(q[h], lo, hi);
        acc[h] += lo + hi;
        q[h] = 0;
    }
}
__device__ __forceinline__ void gelu_sumsq_f(const uint32_t (&d)[16], float (&acc)[2]) {
#pragma unroll
    for (int r = 0; r < 16; r++) {
        float lo, hi;
        h2_unpack(gelu2(d[r]), lo, hi);
        acc[r & 1] = fmaf(lo, lo, acc[r & 1]);
        acc[r & 1] = fmaf(hi, hi, acc[r & 1]);
    }
}
__device__ __forceinline__ void load_w1t(uint32_t (&wa)[2][24], int wg, int w, int lane) {
#pragma unroll
    for (int m = 0; m < 2; m++)
#pragma unroll
        for (int kk = 0; kk < 5; kk++) {
            const int q = lane >> 3, c = 16 * kk + 8 * (q >> 1) + (lane & 7), ck = 2 * w + (q & 1);
            ldsm4_t(wa[m] + kk * 4, sb + SM_W1 + (2 * wg + m) * 12288 + c * 128 + ((ck ^ (c & 7)) * 16));
        }
}
__device__ __forceinline__ void publish_sums(const float (&acc)[2][2], float* sums, unsigned int* counter, int wg, int w, int lane) {
#pragma unroll
    for (int m = 0; m < 2; m++)
#pragma unroll
        for (int h = 0; h < 2; h++) {
            const float v = quad_sum(acc[m][h]);
            if ((lane & 3) == 0) atomicAdd(sums + 64 * (2 * wg + m) + 16 * w + (lane >> 2) + 8 * h, v);
        }
    named_sync(1, 384);
    if (fresh_tid() == 0) asm volatile("red.release.gpu.global.add.u32 [%0], 1;" ::"l"(counter) : "memory");
}
__device__ __forceinline__ void grid_wait(const unsigned int* counter, unsigned int target) {
    if (fresh_tid() == 0) {
        unsigned int v, spins = 0;
        do {
            asm volatile("ld.acquire.gpu.global.u32 %0, [%1];" : "=r"(v) : "l"(counter) : "memory");
            if (++spins > (1u << 22)) __trap();
        } while ((int)(v - target) < 0);
    }
    __syncthreads();
}

__device__ __forceinline__ void gemm1(uint32_t (&z)[16], const uint32_t (&a)[24], uint32_t w1d, int j) {
    wg_fence();
    wgmma_n64_h_set<1>(z, a, desc<1024, 1>(w1d, j * 12288));
#pragma unroll
    for (int kk = 1; kk < 6; kk++) wgmma_n64_h_acc<1>(z, a + kk * 4, desc<1024, 1>(w1d, j * 12288 + kk * 2048));
    wg_commit();
}
__device__ __forceinline__ void unpack_offsets(uint32_t (&o)[2], uint32_t packed) {
    asm volatile("and.b32 %0, %2, 0xffff;\nshr.u32 %1, %2, 16;" : "=r"(o[0]), "=r"(o[1]) : "r"(packed));
}
__device__ __forceinline__ void load_a(uint32_t (&a)[24], uint32_t wg, uint32_t offs) {
    uint32_t o[2];
    unpack_offsets(o, offs);
#pragma unroll
    for (int kk = 0; kk < 6; kk++) ldsm4(a + kk * 4, sb + SM_Y2 + (wg & 1) * TILE_BYTES + (o[kk >> 2] ^ ((kk & 3) * 32)));
}
__device__ __forceinline__ void init_bias(uint32_t (&o)[24], uint32_t addr) {
#pragma unroll
    for (int j = 0; j < 6; j++) lds128(o + 4 * j, addr + j * 64);
}

struct Pass2 {
    uint32_t wg;
    uint32_t off;
    uint32_t a_offs, xs_offs, bias_addr, out_scale;
    bool lead;
    uint32_t a[24], z[3][16], o[24];
};

__device__ __forceinline__ void refill_y(const Pass2& c, const Params& prm, int n, uint32_t off) {
    const uint32_t bars = sb + SM_BAR;
    fence_async_smem();
    named_sync(2 + c.wg, 128);
    if (c.lead && 4 * n + c.wg + 2 < ROWS_PER_CTA) {
        expect_tx(bars + (BAR_Y2FULL + (c.wg ^ 2)) * 8, TILE_BYTES);
        bulk_load(sb + SM_Y2 + (c.wg & 1) * TILE_BYTES, (const char*)prm.out + (off - 2 * ROW_BYTES), TILE_BYTES,
                  bars + (BAR_Y2FULL + (c.wg ^ 2)) * 8);
    }
}

__device__ __forceinline__ void start_first_tile(Pass2& c, const Params& prm) {
    const uint32_t bars = sb + SM_BAR;
    mbar_wait_c<0>(bars + (BAR_Y2FULL + c.wg) * 8);
    load_a(c.a, c.wg, c.a_offs);
    gemm1(c.z[0], c.a, prm.w1desc, 0);
    refill_y(c, prm, 0, c.off);
}

__device__ __forceinline__ void pass2_tile(Pass2& c, const Params& prm, int n) {
    const uint32_t xs = sb + SM_XS + c.wg * TILE_BYTES, xsfull = sb + SM_BAR + (BAR_XSFULL + c.wg) * 8;
#pragma unroll
    for (int j = 0; j < 6; j++) {
        uint32_t (&zc)[16] = c.z[j % 3];
        uint32_t (&zn)[16] = c.z[(j + 1) % 3];
        if (j == 0) wg_wait<0>(); else wg_wait<1>();
        pin(zc);
        if (j == 5) {
            pin(c.a);
            mbar_wait(sb + SM_BAR + (BAR_Y2FULL + c.wg) * 8, min(n + 1, ROWS_PER_CTA / 4 - 1) & 1);
            load_a(c.a, c.wg, c.a_offs);
        }
        const int jn = (j + 1) % 6;
#pragma unroll
        for (int sl = 0; sl < 4; sl++) {
#pragma unroll
            for (int r = 0; r < 4; r++) zc[sl * 4 + r] = gelu2(zc[sl * 4 + r]);
            wg_fence();
            wgmma_n96_h_acc(c.o, zc + sl * 4, desc<512, 2>(prm.w2desc, (j * 4 + sl) * 1024));
            if (sl < 2) {
#pragma unroll
                for (int kk = sl * 3; kk < sl * 3 + 3; kk++) {
                    if (kk == 0) wgmma_n64_h_set<1>(zn, c.a, desc<1024, 1>(prm.w1desc, jn * 12288));
                    else wgmma_n64_h_acc<1>(zn, c.a + kk * 4, desc<1024, 1>(prm.w1desc, jn * 12288 + kk * 2048));
                }
            }
            if (sl == 1) wg_commit();
        }
        wg_commit();
        if (j == 5) refill_y(c, prm, n + 1, c.off - 4 * ROW_BYTES);
        if (j == 1 && c.lead) {
            bulk_wait_read<0>();
            expect_tx(xsfull, TILE_BYTES);
            bulk_load(xs, (const char*)prm.x + c.off, TILE_BYTES, xsfull);
        }
    }
    wg_wait<0>();
    pin(c.o); pin(c.z[0]);
    mbar_wait(xsfull, n & 1);
    uint32_t xo[2];
    unpack_offsets(xo, c.xs_offs);
#pragma unroll
    for (int h = 0; h < 2; h++)
#pragma unroll
        for (int a = 0; a < 3; a++) {
            const uint32_t addr = xs + xo[h] + a * 64;
            uint32_t v[4];
            lds128(v, addr);
#pragma unroll
            for (int b = 0; b < 4; b++) {
                float lo, hi;
                h2_unpack(c.o[a * 8 + b * 2 + h], lo, hi);
                v[b] = bf2_fma(pack_bf2(lo, hi), c.out_scale, v[b]);
            }
            sts128(addr, v[0], v[1], v[2], v[3]);
        }
    init_bias(c.o, c.bias_addr);
    fence_async_smem();
    named_sync(2 + c.wg, 128);
    if (c.lead) bulk_store((char*)prm.out + c.off, xs, TILE_BYTES);
    c.off -= 4 * ROW_BYTES;
}

__device__ __forceinline__ float warp_sum(float v) {
#pragma unroll
    for (int s = 16; s >= 1; s >>= 1) v += __shfl_xor_sync(0xffffffffu, v, s);
    return v;
}
__device__ __forceinline__ float pow2f(int e) { return __uint_as_float((uint32_t)(e + 127) << 23); }
__device__ __forceinline__ int clamped_exponent(float v) {
    return min(max((int)((__float_as_uint(v) >> 23) & 0xff) - 127, -40), 40);
}

__device__ __forceinline__ void scan_w2(const Params& prm) {
    const uint32_t tid = fresh_tid() & 127, t = tid & 3;
    uint32_t be[48];
    mbar_wait_c<0>(sb + SM_BAR + BAR_W2 * 8);
#pragma unroll
    for (int k = 0; k < 48; k++) be[k] = lds32(sb + SM_BETA + (4 * k + t) * 4);
    float d[48];
#pragma unroll
    for (int k = 0; k < 48; k++) d[k] = 0.0f;
    wg_fence();
#pragma unroll
    for (int ks = 0; ks < 24; ks++)
        asm volatile(
            "{\n.reg .pred p;\nsetp.ne.b32 p, 1, 0;\n"
            "wgmma.mma_async.sync.aligned.m64n96k16.f32.bf16.bf16 {%0,%1,%2,%3,%4,%5,%6,%7,%8,%9,%10,%11,%12,%13,%14,%15,%16,%17,%18,%19,%20,%21,%22,%23,%24,%25,%26,%27,%28,%29,%30,%31,%32,%33,%34,%35,%36,%37,%38,%39,%40,%41,%42,%43,%44,%45,%46,%47}, {%48,%48,%49,%49}, %50, p, 1, 1, 1;\n}\n"
            : "+f"(d[0]), "+f"(d[1]), "+f"(d[2]), "+f"(d[3]), "+f"(d[4]), "+f"(d[5]), "+f"(d[6]), "+f"(d[7]), "+f"(d[8]), "+f"(d[9]), "+f"(d[10]), "+f"(d[11]), "+f"(d[12]), "+f"(d[13]), "+f"(d[14]), "+f"(d[15]), "+f"(d[16]), "+f"(d[17]), "+f"(d[18]), "+f"(d[19]), "+f"(d[20]), "+f"(d[21]), "+f"(d[22]), "+f"(d[23]), "+f"(d[24]), "+f"(d[25]), "+f"(d[26]), "+f"(d[27]), "+f"(d[28]), "+f"(d[29]), "+f"(d[30]), "+f"(d[31]), "+f"(d[32]), "+f"(d[33]), "+f"(d[34]), "+f"(d[35]), "+f"(d[36]), "+f"(d[37]), "+f"(d[38]), "+f"(d[39]), "+f"(d[40]), "+f"(d[41]), "+f"(d[42]), "+f"(d[43]), "+f"(d[44]), "+f"(d[45]), "+f"(d[46]), "+f"(d[47])
            : "r"(be[2 * ks]), "r"(be[2 * ks + 1]), "l"(desc<512, 2>(prm.w2desc, ks * 1024)));
    wg_commit();
    uint32_t mx = 0;
#pragma unroll 4
    for (int k = 0; k < 36; k++) {
        uint32_t v[4];
        lds128(v, sb + SM_W2 + tid * 16 + k * 2048);
#pragma unroll
        for (int b = 0; b < 4; b++) asm("max.xorsign.abs.bf16x2 %0, %0, %1;" : "+r"(mx) : "r"(v[b]));
    }
    mx &= 0x7fff7fffu;
    mx = __reduce_max_sync(0xffffffffu, max(mx << 16, mx & 0xffff0000u));
    if ((tid & 31) == 0) asm volatile("red.shared.max.u32 [%0], %1;" ::"r"(sb + SM_RED + RED_W2MAX * 4), "r"(mx) : "memory");
    wg_wait<0>();
#pragma unroll
    for (int k = 0; k < 48; k++) asm volatile("" : "+f"(d[k])::"memory");
    if (tid < 4) {
#pragma unroll
        for (int jb = 0; jb < 12; jb++)
            sts64(sb + SM_BPART + (8 * jb + 2 * t) * 4, __float_as_uint(d[4 * jb]), __float_as_uint(d[4 * jb + 1]));
    }
}
__device__ __forceinline__ void fetch_w2_row(uint32_t (&u)[12][4], uint32_t row, uint32_t sw, uint32_t nrm2) {
#pragma unroll
    for (int a = 0; a < 3; a++) {
        uint32_t v[4][4];
#pragma unroll
        for (int k = 0; k < 4; k++) lds128(v[k], row + a * 24576 + ((k * 16) ^ sw));
#pragma unroll
        for (int b = 0; b < 4; b++)
#pragma unroll
            for (int k = 0; k < 4; k++) u[a * 4 + b][k] = bf2_to_h2(bf2_mul(v[k][b], nrm2));
    }
}

__device__ __forceinline__ bool grn_stats(float ss, float gm, float bt, float& gx, float& inv, int& eb) {
    const int warp = fresh_warp();
    gx = sqrt_fast(fmaf(ss, INV_2A * INV_2A, 1e-6f));
    const float rt = sqrt_fast(ss + 1.0f) * INV_2A;
    const float r[3] = {warp_sum(gx), warp_sum(rt + bt), warp_sum(rt * fabsf(gm) * gx)};
    if ((fresh_tid() & 31) == 0 && warp < 12) {
#pragma unroll
        for (int k = 0; k < 3; k++) sts32(sb + SM_SEL + (k * 12 + warp) * 4, __float_as_uint(r[k]));
    }
    const bool bad = __syncthreads_or(!(ss >= 16.0f && ss < 1e30f));
    float tot[3];
#pragma unroll
    for (int k = 0; k < 3; k++) {
        uint32_t v[12];
#pragma unroll
        for (int q = 0; q < 3; q++) lds128(v + 4 * q, sb + SM_SEL + k * 48 + q * 16);
        float p[4];
#pragma unroll
        for (int q = 0; q < 4; q++) p[q] = __uint_as_float(v[q]) + __uint_as_float(v[q + 4]) + __uint_as_float(v[q + 8]);
        tot[k] = (p[0] + p[1]) + (p[2] + p[3]);
    }
    inv = __fdividef(1.0f, fmaf(tot[0], 1.0f / EX, 1e-6f));
    eb = clamped_exponent(fmaf(tot[2], inv, tot[1])) - 13;
    return bad;
}

__device__ __forceinline__ float exact_sums(const Params& prm, int e) {
    const int lane = fresh_tid() & 31, warp = fresh_warp(), wg = warp >> 2;
    const uint32_t epoch = lds32(sb + SM_RED + (RED_EPOCH + 1) * 4), bar = sb + SM_BAR + BAR_W1 * 8;
    if (wg < 3) {
        uint32_t wa[2][24], d[2][16];
        float acc[2][2] = {};
        const uint32_t yd = prm.ydesc, wd = prm.w1desc + ((2 * wg * 12288 + 5 * 2048) >> 4);
        load_w1t(wa, wg, warp & 3, lane);
#pragma unroll 1
        for (int n = 0; n < ROWS_PER_CTA; n++) {
            if (warp == 0) {
                expect_tx(bar, TILE_BYTES);
                bulk_load(sb + SM_Y1, (const char*)prm.out + cta_tile0(fresh_cta()) + n * ROW_BYTES, TILE_BYTES, bar);
            }
            mbar_wait(bar, (n + 1) & 1);
            gemm1_t<0>(d[0], wa[0], yd, wd);
            gemm1_t<1>(d[1], wa[1], yd, wd);
            wg_wait<0>();
            pin(d[0]); pin(d[1]);
            gelu_sumsq_f(d[0], acc[0]);
            gelu_sumsq_f(d[1], acc[1]);
            named_sync(1, 384);
        }
        publish_sums(acc, g_sums[1][epoch & 1], &g_count[1], wg, warp & 3, lane);
    }
    grid_wait(&g_count[1], (epoch + 1) * NUM_CTAS);
    return __ldcg(g_sums[1][epoch & 1] + e);
}

__global__ void __launch_bounds__(512, 1) convnext_kernel(const __grid_constant__ Params prm) {
    extern __shared__ __align__(1024) uint8_t smem[];
    if ((uint32_t)__cvta_generic_to_shared(smem) != sb) __trap();
    if (fresh_tid() < 32) TS(0);
    if (fresh_warp() == 0) {
        const RowCopy rc = row_copy(prm);
        if (fresh_tid() == 0) {
            mbar_init(sb + SM_XFULL, 2);
            fence_async_smem();
        }
        __syncwarp();
        issue_row_load(rc, 0, 0);
        if (fresh_tid() == 0) {
#pragma unroll
            for (int k = 0; k < NX; k++) {
                if (k) mbar_init(sb + SM_XFULL + k * SLOT_BYTES, 2);
                mbar_init(sb + SM_Y1FULL + k * SLOT_BYTES, 4);
                mbar_init(sb + SM_Y1EMPTY + k * SLOT_BYTES, 12);
            }
#pragma unroll
            for (int k = 0; k <= BAR_W2; k++) mbar_init(sb + SM_BAR + k * 8, 1);
            mbar_init(sb + SM_BAR + BAR_READY * 8, 16);
            sts32(sb + SM_RED + RED_W2MAX * 4, 0);
            fence_async_smem();
        }
        __syncwarp();
#pragma unroll
        for (int s = 1; s <= NX; s++) {
            if (s == 1 + rc.first) {
                expect_tx(sb + SM_BAR + BAR_W1 * 8, CH * EX * 2);
#pragma unroll
                for (int k = 0; k < 3; k++)
                    bulk_load(sb + SM_W1 + k * 24576, (const char*)prm.w1 + k * 24576, 24576, sb + SM_BAR + BAR_W1 * 8);
            }
            if (s < NX) issue_row_load(rc, s, s);
        }
    }
    Producer pc;
    if (fresh_warp() >= 12) {
        const char* dw = (const char*)prm.dw + (fresh_tid() & 7) * 8;
#pragma unroll
        for (int tap = 0; tap < 9; tap++) {
            asm volatile("ld.global.nc.v4.b32 {%0,%1,%2,%3}, [%4];"
                         : "=r"(pc.w[tap][0]), "=r"(pc.w[tap][1]), "=r"(pc.w[tap][2]), "=r"(pc.w[tap][3])
                         : "l"(dw + (fresh_tid() & 7) * 8 + tap * CH * 2));
            asm volatile("ld.global.nc.v2.b32 {%0,%1}, [%2];"
                         : "=r"(pc.w[tap][4]), "=r"(pc.w[tap][5]) : "l"(dw + tap * CH * 2 + 128));
        }
    }
    if (fresh_tid() >= 96 && fresh_tid() < 128) {
        const uint32_t k = fresh_tid() - 96, n = k & 7, one = (n & 5) == ((k & 8) >> 1) + (k >> 4) ? 0x3f803f80u : 0u;
        sts128(sb + SM_SEL + k * 16, one, one, one, one);
        fence_async_smem();
    }
    if (fresh_tid() >= 32 && fresh_tid() < 32 + NX * 12 && ((blockIdx.x + 1) & 7) < 2) {
        const int k = fresh_tid() - 32;
        sts128(sb + SM_X + (k / 12) * SLOT_BYTES + ((blockIdx.x & 7) == 0 ? 0 : XHALF_B + 33 * 192) + (k % 12) * 16, 0, 0, 0, 0);
    }
    __syncthreads();
    if (fresh_tid() < 32) TS(16);

    if (fresh_warp() >= 12) {
        TS(17);
        asm volatile("setmaxnreg.inc.sync.aligned.u32 %0;" ::"n"(PRODUCER_REGS));
        TS(18);
        const int w = fresh_warp() & 3, lane = fresh_tid() & 31;
        const int j = lane & 7, hb = (lane >> 3) & 1, base = 4 * (2 * w + (lane >> 4));
        pc.lane = lane; pc.warp = w;
        pc.xoff[0] = hb * XHALF_B + base * 192 + j * 16;
        pc.xoff[1] = hb * XHALF_B + base * 192 + 128 + j * 8;
        const int grp = 4 * w + (lane >> 3);
#pragma unroll
        for (int o = 0; o < 2; o++) {
            const int row = (grp & 7) + 8 * (o ^ hb) + 32 * (grp >> 3);
            pc.yoff[0][o] = row * 128 + ((j ^ (row & 7)) * 16);
            pc.yoff[1][o] = 8192 + row * 64 + (((j >> 1) ^ ((row >> 1) & 3)) * 16) + (j & 1) * 8;
        }
        pc.stat = sb + SM_STAT + grp * 32;
        pc.own = pc.stat + (lane & 3) * 8;
#pragma unroll
        for (int tap = 0; tap < 9; tap++)
#pragma unroll
            for (int u = 0; u < 6; u++) pc.w[tap][u] = bf2_mul(pc.w[tap][u], TAP_SCALE_BF2);
        TS(8);
        produce(pc, prm);
        TS(9);
        scan_w2(prm);
        TS(22);
        asm volatile("setmaxnreg.dec.sync.aligned.u32 %0;" ::"n"(EVEN_REGS));
    } else {
        asm volatile("setmaxnreg.dec.sync.aligned.u32 %0;" ::"n"(CONSUMER_REGS));
        if (fresh_tid() - 160 < 2) {
            const uint32_t k = fresh_tid() - 160;
            unsigned int cnt;
            asm volatile("ld.relaxed.gpu.global.u32 %0, [%1];" : "=r"(cnt) : "l"(&g_count[k]) : "memory");
            sts32(sb + SM_RED + (RED_EPOCH + k) * 4, cnt / NUM_CTAS);
        }
        __syncwarp();
        if (fresh_tid() < 32) TS(19);
        {
            const int tid = fresh_tid(), c0 = tid / 48, ec = tid % 48;
            const uint32_t dst = sb + SM_W1 + (ec >> 3) * 12288 + c0 * 128 + (((ec & 7) ^ (c0 & 7)) * 16);
            uint32_t v[12][4];
            mbar_wait_c<0>(sb + SM_BAR + BAR_W1 * 8);
            if (fresh_tid() < 32) TS(20);
#pragma unroll
            for (int it = 0; it < 12; it++) lds128(v[it], sb + SM_W1 + tid * 16 + it * 6144);
#pragma unroll
            for (int it = 0; it < 12; it++)
#pragma unroll
                for (int k = 0; k < 4; k++) v[it][k] = bf2_to_h2(v[it][k]);
#pragma unroll
            for (int it = 0; it < 12; it++) pin(v[it]);
            named_sync(1, 384);
#pragma unroll
            for (int it = 0; it < 12; it++) sts128(dst + it * 1024, v[it][0], v[it][1], v[it][2], v[it][3]);
            if (fresh_cta() < 2) g_sums[fresh_cta()][(lds32(sb + SM_RED + (RED_EPOCH + fresh_cta()) * 4) & 1) ^ 1][tid] = 0.0f;
            fence_async_smem();
            named_sync(1, 384);
            if (fresh_tid() < 32) TS(21);
        }

        const int tid = fresh_tid(), lane = tid & 31, wg = fresh_warp() >> 2, w = fresh_warp() & 3;
        float acc[2][2];
        const int c = 8 * (lane >> 4) + (lane & 7), ck = 2 * w + ((lane >> 3) & 1);
        if (wg == 0) TS(1);
        consume(acc, sb + SM_W1 + 2 * wg * 12288 + c * 128 + ((ck ^ (c & 7)) * 16), prm.ydesc,
                prm.w1desc + (((2 * wg + 1) * 12288 + 5 * 2048) >> 4), wg * SLOT_BYTES, make_duty(prm, wg, w), w, lane);
        publish_sums(acc, g_sums[0][lds32(sb + SM_RED + RED_EPOCH * 4) & 1], &g_count[0], wg, w, lane);
        bulk_wait_all();
        if (wg == 0) TS(3);
        asm volatile("setmaxnreg.inc.sync.aligned.u32 %0;" ::"n"(EVEN_REGS));
    }

    uint32_t out_scale;
    {
        const int tid = fresh_tid(), lane = tid & 31, warp = fresh_warp(), e = min(tid, EX - 1);
        const uint32_t epoch = lds32(sb + SM_RED + RED_EPOCH * 4);
        __syncthreads();
        uint16_t gm16, bt16;
        asm volatile("ld.shared.u16 %0, [%1];" : "=h"(gm16) : "r"(sb + SM_GAMMA + e * 2) : "memory");
        asm volatile("ld.shared.u16 %0, [%1];" : "=h"(bt16) : "r"(sb + SM_BETA + e * 2) : "memory");
        const float gm = bf_lo(gm16), bt = fabsf(bf_lo(bt16));
        if (warp == 13) {
            const uint32_t last = cta_tile0(fresh_cta()) + (ROWS_PER_CTA - 1) * ROW_BYTES;
            for (int k = 0; k < 2; k++) {
                expect_tx(sb + SM_BAR + (BAR_Y2FULL + k) * 8, TILE_BYTES);
                bulk_load(sb + SM_Y2 + k * TILE_BYTES, (const char*)prm.out + (last - k * ROW_BYTES), TILE_BYTES,
                          sb + SM_BAR + (BAR_Y2FULL + k) * 8);
            }
        }
        const uint32_t w2row = sb + SM_W2 + e * 64, sw = ((e >> 1) & 3) * 16;
        const int ew = clamped_exponent(__uint_as_float(lds32(sb + SM_RED + RED_W2MAX * 4)));
        const uint32_t nrm2 = pack_bf2(pow2f(-ew), pow2f(-ew));
        uint32_t u[12][4], b[4];
        fetch_w2_row(u, w2row, sw, nrm2);
        const int jj = min(lane >> 2, 5);
        lds128(b, sb + SM_BPART + (32 * (jj >> 1) + 8 * (lane & 3) + 4 * (jj & 1)) * 4);
        grid_wait(&g_count[0], (epoch + 1) * NUM_CTAS);
        if (warp == 0) TS(4);
        float gx, inv;
        int eb;
        if (grn_stats(__ldcg(g_sums[0][epoch & 1] + e), gm, bt, gx, inv, eb) || FORCE_EXACT) {
            grn_stats(exact_sums(prm, e), gm, bt, gx, inv, eb);
            fetch_w2_row(u, w2row, sw, nrm2);
        }
        const float up = pow2f(ew + eb);
        out_scale = pack_bf2(up, up);
        if (warp < 12) {
            const float sc = fmaf(gm, gx * inv, 1.0f) * INV_2A * pow2f(-eb);
            const uint32_t s2 = pack_h2(sc, sc);
#pragma unroll
            for (int k = 0; k < 12; k++)
                sts128(w2row + (k >> 2) * 24576 + (((k & 3) * 16) ^ sw), h2_mul(u[k][0], s2), h2_mul(u[k][1], s2),
                       h2_mul(u[k][2], s2), h2_mul(u[k][3], s2));
        } else if (warp == 12 && lane < 24) {
            const float dn = pow2f(-(ew + eb));
            const uint32_t p0 = pack_h2(__uint_as_float(b[0]) * dn, __uint_as_float(b[1]) * dn);
            const uint32_t p1 = pack_h2(__uint_as_float(b[2]) * dn, __uint_as_float(b[3]) * dn);
            sts128(sb + SM_BIAS + lane * 16, p0, p0, p1, p1);
        }
        fence_async_smem();
        __syncwarp();
        mbar_arrive_if(sb + SM_BAR + BAR_READY * 8, lane == 0);
    }

    {
        Pass2 c;
        const int tid = fresh_tid(), lane = tid & 31, wg = fresh_warp() >> 2, w = fresh_warp() & 3;
        const int arow = 16 * w + (lane & 15);
        c.wg = wg;
        c.off = cta_tile0(fresh_cta()) + (ROWS_PER_CTA - 1 - wg) * ROW_BYTES;
        c.a_offs = (arow * 128 + (((lane >> 4) ^ (arow & 7)) * 16)) |
                   (8192 + arow * 64 + (((lane >> 4) ^ ((arow >> 1) & 3)) * 16)) << 16;
        const int g = lane >> 2, px = 33 * (g & 1) + 4 * (g >> 1) + 16 * (w >> 1) + 2 * (w & 1);
        c.xs_offs = (px * 192 + (lane & 3) * 16) | ((px ^ 1) * 192 + (lane & 3) * 16) << 16;
        c.bias_addr = sb + SM_BIAS + (lane & 3) * 16;
        c.out_scale = out_scale;
        c.lead = w == 0;
        if (wg == 0) TS(5);
        start_first_tile(c, prm);
        mbar_wait_c<0>(sb + SM_BAR + BAR_READY * 8);
        init_bias(c.o, c.bias_addr);
#pragma unroll 1
        for (int n = loop_init<0>(); n < ROWS_PER_CTA / 4; n++) pass2_tile(c, prm, n);
        bulk_wait_all();
        if (wg == 0) TS(6);
        if (wg == 3) TS(7);
    }
}

}

extern "C" void kernel_launch(void* const* d_in, const int* in_sizes, int n_in, void* d_out, int out_size) {
    (void)in_sizes; (void)n_in; (void)out_size;
    typedef CUresult (*EncodeFn)(CUtensorMap*, CUtensorMapDataType, cuuint32_t, void*, const cuuint64_t*, const cuuint64_t*,
                                 const cuuint32_t*, const cuuint32_t*, CUtensorMapInterleave, CUtensorMapSwizzle,
                                 CUtensorMapL2promotion, CUtensorMapFloatOOBfill);
    void* fn = nullptr;
    cudaDriverEntryPointQueryResult status;
    cudaGetDriverEntryPoint("cuTensorMapEncodeTiled", &fn, cudaEnableDefault, &status);
    const EncodeFn encode = (EncodeFn)fn;
    const cuuint32_t ones[2] = {1, 1};

    Params p;
    {
        const cuuint64_t dims[2] = {CH, EX}, strides[1] = {CH * 2};
        const cuuint32_t box[2] = {32, 192};
        encode(&p.w2_map, CU_TENSOR_MAP_DATA_TYPE_BFLOAT16, 2, d_in[3], dims, strides, box, ones,
               CU_TENSOR_MAP_INTERLEAVE_NONE, CU_TENSOR_MAP_SWIZZLE_64B, CU_TENSOR_MAP_L2_PROMOTION_NONE,
               CU_TENSOR_MAP_FLOAT_OOB_FILL_NONE);
    }
    p.x = (const __nv_bfloat16*)d_in[0];
    p.dw = (const __nv_bfloat16*)d_in[1];
    p.w1 = (const __nv_bfloat16*)d_in[2];
    p.gamma = (const __nv_bfloat16*)d_in[4];
    p.beta = (const __nv_bfloat16*)d_in[5];
    p.out = (__nv_bfloat16*)d_out;
    p.w1desc = desc_lo(sb + SM_W1, 12288);
    p.w2desc = desc_lo(sb + SM_W2, 24576);
    p.ydesc = desc_lo(sb + SM_Y1, 16);
    for (int k = 0; k < 3; k++) p.sel[k] = (8ull << 32) | desc_lo(sb + SM_SEL + k * 128, k == 2 ? 128 : 0);
    cudaFuncSetAttribute(convnext_kernel, cudaFuncAttributeMaxDynamicSharedMemorySize, SM_TOTAL);
    convnext_kernel<<<NUM_CTAS, 512, SM_TOTAL>>>(p);
}
```

```cpp
#include <cuda.h>
#include <cuda_runtime.h>
#include <cuda_bf16.h>
#include <stdint.h>

namespace {

constexpr int IMG_W = 512, CH = 96, EX = 384;
constexpr int TILE_PX = 64;
constexpr int ROWS_PER_CTA = 32;
constexpr int NUM_CTAS = 128;
constexpr int STEPS = ROWS_PER_CTA + 2;
constexpr int ROW_BYTES = IMG_W * CH * 2;

#define FORCE_EXACT 0
#define PREGS 200
#define CREGS 104
constexpr int PRODUCER_REGS = PREGS, CONSUMER_REGS = CREGS, EVEN_REGS = 128;

constexpr int XHALF_BYTES = 34 * 192;
constexpr int XHALF_B = XHALF_BYTES + 64;
constexpr int XROW_BYTES = XHALF_B + XHALF_BYTES + 64;
constexpr int L2_AHEAD = 2;
constexpr int NX = 3;
constexpr int TILE_BYTES = TILE_PX * 192;
constexpr int NY1 = 3;

constexpr uint32_t sb = 1024;
constexpr int SM_W1 = 0;
constexpr int SM_W2 = 73728;
constexpr int SM_RING = 147456;
constexpr int SLOT_BYTES = 26624;
constexpr int SM_Y1 = SM_RING;
constexpr int SM_X = SM_Y1 + TILE_BYTES;
constexpr int SM_STAT = SM_X + XROW_BYTES;
constexpr int SM_XFULL = SM_STAT + TILE_PX * 8, SM_Y1FULL = SM_XFULL + 8, SM_Y1EMPTY = SM_XFULL + 16;
constexpr int SM_Y2 = SM_X, SM_SPARE = SM_X + 2 * SLOT_BYTES;
constexpr int SM_SEL = SM_RING + NX * SLOT_BYTES;
constexpr int SM_BIAS = SM_SEL + 512;
constexpr int SM_GAMMA = SM_BIAS + 384;
constexpr int SM_BETA = SM_GAMMA + EX * 2;
constexpr int SM_RED = SM_BETA + EX * 2;
constexpr int SM_BAR = SM_RED + 16;
constexpr int SM_TOTAL = SM_BAR + 11 * 8;
static_assert(SM_Y1EMPTY + 8 <= SM_RING + SLOT_BYTES && XROW_BYTES >= TILE_BYTES && SM_X % 1024 == 0, "ring layout");
static_assert(SM_TOTAL <= 232448, "smem budget");
static_assert(SM_STAT % 128 == 0 && SM_BIAS % 16 == 0 && SM_BAR % 8 == 0 && SLOT_BYTES % 1024 == 0, "alignment");

constexpr int BAR_Y2FULL = 0, BAR_XSFULL = 4, BAR_W1 = 8, BAR_W2 = 9, BAR_DUMMY = 10;
static_assert(NX == NY1, "both rings are walked with one index");
constexpr int RED_EPOCH = 0;

constexpr float GELU_A = 0.32920349f;
constexpr uint32_t GELU_C_H2 = 0x40D940D9u;
constexpr float INV_2A = 1.0f / (2.0f * GELU_A);
constexpr uint32_t W2_MASK = 0xfff8fff8u;
constexpr float W2_CENTRE = 1.0023f;

constexpr uint32_t TAP_SCALE_BF2 = 0x2B802B80u;
constexpr float LN_EPS_SCALED = 1e-5f * 0x1p-80f;
constexpr float RSTD_SCALE = GELU_A * 0x1p-112f;

__device__ unsigned long long g_acc[2][EX / 4 * 32];
__device__ unsigned long long g_bias[CH];
__device__ float g_sums[2][EX];
__device__ unsigned int g_count[2];
constexpr float ACC_LIMIT = 0x1p30f;
__device__ uint4 g_zero_row[66 * 192 / 16];

#define TS(k)
#define ASM_TS
#define ASM_TRC(it, k)

#define SPLITS 2
#define FENCE_HEAD(k) "{\n.reg .pred p;\n.reg .u32 t;\nsetp.ne.u32 p, %" #k ", 0;\n@p bra.uni GO;\nSTAY:\nld.volatile.shared.u32 t, [%" #k "];\n"
#define FENCE_TAIL "setp.ne.u32 p, t, 0;\n@p bra.uni STAY;\nGO:\n}\n"
template <int N> __device__ __forceinline__ void sched_fence(uint32_t* r, uint32_t key);
template <> __device__ __forceinline__ void sched_fence<2>(uint32_t* r, uint32_t key) {
    asm volatile(FENCE_HEAD(2) "mov.b32 %0, t;\nmov.b32 %1, t;\n" FENCE_TAIL
                 : "+r"(r[0]), "+r"(r[1]) : "r"(key) : "memory");
}
template <> __device__ __forceinline__ void sched_fence<4>(uint32_t* r, uint32_t key) {
    asm volatile(FENCE_HEAD(4) "mov.b32 %0, t;\nmov.b32 %1, t;\nmov.b32 %2, t;\nmov.b32 %3, t;\n" FENCE_TAIL
                 : "+r"(r[0]), "+r"(r[1]), "+r"(r[2]), "+r"(r[3]) : "r"(key) : "memory");
}
template <> __device__ __forceinline__ void sched_fence<6>(uint32_t* r, uint32_t key) {
    asm volatile(FENCE_HEAD(6) "mov.b32 %0, t;\nmov.b32 %1, t;\nmov.b32 %2, t;\nmov.b32 %3, t;\nmov.b32 %4, t;\nmov.b32 %5, t;\n" FENCE_TAIL
                 : "+r"(r[0]), "+r"(r[1]), "+r"(r[2]), "+r"(r[3]), "+r"(r[4]), "+r"(r[5]) : "r"(key) : "memory");
}
template <> __device__ __forceinline__ void sched_fence<8>(uint32_t* r, uint32_t key) {
    asm volatile(FENCE_HEAD(8) "mov.b32 %0, t;\nmov.b32 %1, t;\nmov.b32 %2, t;\nmov.b32 %3, t;\nmov.b32 %4, t;\nmov.b32 %5, t;\nmov.b32 %6, t;\nmov.b32 %7, t;\n" FENCE_TAIL
                 : "+r"(r[0]), "+r"(r[1]), "+r"(r[2]), "+r"(r[3]), "+r"(r[4]), "+r"(r[5]), "+r"(r[6]), "+r"(r[7]) : "r"(key) : "memory");
}
template <> __device__ __forceinline__ void sched_fence<10>(uint32_t* r, uint32_t key) {
    asm volatile(FENCE_HEAD(10) "mov.b32 %0, t;\nmov.b32 %1, t;\nmov.b32 %2, t;\nmov.b32 %3, t;\nmov.b32 %4, t;\nmov.b32 %5, t;\nmov.b32 %6, t;\nmov.b32 %7, t;\nmov.b32 %8, t;\nmov.b32 %9, t;\n" FENCE_TAIL
                 : "+r"(r[0]), "+r"(r[1]), "+r"(r[2]), "+r"(r[3]), "+r"(r[4]), "+r"(r[5]), "+r"(r[6]), "+r"(r[7]), "+r"(r[8]), "+r"(r[9]) : "r"(key) : "memory");
}
template <> __device__ __forceinline__ void sched_fence<12>(uint32_t* r, uint32_t key) {
    asm volatile(FENCE_HEAD(12) "mov.b32 %0, t;\nmov.b32 %1, t;\nmov.b32 %2, t;\nmov.b32 %3, t;\nmov.b32 %4, t;\nmov.b32 %5, t;\nmov.b32 %6, t;\nmov.b32 %7, t;\nmov.b32 %8, t;\nmov.b32 %9, t;\nmov.b32 %10, t;\nmov.b32 %11, t;\n" FENCE_TAIL
                 : "+r"(r[0]), "+r"(r[1]), "+r"(r[2]), "+r"(r[3]), "+r"(r[4]), "+r"(r[5]), "+r"(r[6]), "+r"(r[7]), "+r"(r[8]), "+r"(r[9]), "+r"(r[10]), "+r"(r[11]) : "r"(key) : "memory");
}
template <> __device__ __forceinline__ void sched_fence<24>(uint32_t* r, uint32_t key) {
    asm volatile(FENCE_HEAD(24) "mov.b32 %0, t;\nmov.b32 %1, t;\nmov.b32 %2, t;\nmov.b32 %3, t;\nmov.b32 %4, t;\nmov.b32 %5, t;\nmov.b32 %6, t;\nmov.b32 %7, t;\nmov.b32 %8, t;\nmov.b32 %9, t;\nmov.b32 %10, t;\nmov.b32 %11, t;\nmov.b32 %12, t;\nmov.b32 %13, t;\nmov.b32 %14, t;\nmov.b32 %15, t;\nmov.b32 %16, t;\nmov.b32 %17, t;\nmov.b32 %18, t;\nmov.b32 %19, t;\nmov.b32 %20, t;\nmov.b32 %21, t;\nmov.b32 %22, t;\nmov.b32 %23, t;\n" FENCE_TAIL
                 : "+r"(r[0]), "+r"(r[1]), "+r"(r[2]), "+r"(r[3]), "+r"(r[4]), "+r"(r[5]), "+r"(r[6]), "+r"(r[7]), "+r"(r[8]), "+r"(r[9]), "+r"(r[10]), "+r"(r[11]), "+r"(r[12]), "+r"(r[13]), "+r"(r[14]), "+r"(r[15]), "+r"(r[16]), "+r"(r[17]), "+r"(r[18]), "+r"(r[19]), "+r"(r[20]), "+r"(r[21]), "+r"(r[22]), "+r"(r[23]) : "r"(key) : "memory");
}
#define SPLIT(k, r) do { if ((SPLITS >> (k)) & 1) sched_fence<sizeof(r) / 4>(r, prm.ydesc); } while (0)

__device__ __forceinline__ void mbar_init(uint32_t bar, uint32_t count) {
    asm volatile("mbarrier.init.shared::cta.b64 [%0], %1;" ::"r"(bar), "r"(count) : "memory");
}
__device__ __forceinline__ void mbar_arrive_if(uint32_t bar, bool pred) {
    asm volatile("{\n.reg .pred p;\nsetp.ne.u32 p, %1, 0;\n@p mbarrier.arrive.shared::cta.b64 _, [%0];\n}\n"
                 ::"r"(bar), "r"((uint32_t)pred) : "memory");
}
__device__ __forceinline__ void mbar_wait(uint32_t bar, uint32_t parity) {
    asm volatile(
        "{\n.reg .pred p;\n.reg .u32 n;\n"
        "mbarrier.try_wait.parity.shared::cta.b64 p, [%0], %1;\n"
        "@p bra.uni WAIT_DONE;\n"
        "mov.u32 n, 0;\n"
        "WAIT_LOOP:\n"
        "mbarrier.try_wait.parity.shared::cta.b64 p, [%0], %1;\n"
        "@p bra.uni WAIT_DONE;\n"
        "mbarrier.try_wait.parity.shared::cta.b64 p, [%0], %1;\n"
        "@p bra.uni WAIT_DONE;\n"
        "mbarrier.try_wait.parity.shared::cta.b64 p, [%0], %1;\n"
        "@p bra.uni WAIT_DONE;\n"
        "add.u32 n, n, 1;\nsetp.lt.u32 p, n, 0x40000;\n"
        "@p bra.uni WAIT_LOOP;\n"
        "trap;\n"
        "WAIT_DONE:\n}\n"
        ::"r"(bar), "r"(parity) : "memory");
}
template <int PARITY> __device__ __forceinline__ void mbar_wait_c(uint32_t bar) {
    asm volatile(
        "{\n.reg .pred p;\n.reg .u32 n;\n"
        "mbarrier.try_wait.parity.shared::cta.b64 p, [%0], %1;\n"
        "@p bra.uni WAIT_DONE;\n"
        "mov.u32 n, 0;\n"
        "WAIT_LOOP:\n"
        "mbarrier.try_wait.parity.shared::cta.b64 p, [%0], %1;\n"
        "@p bra.uni WAIT_DONE;\n"
        "mbarrier.try_wait.parity.shared::cta.b64 p, [%0], %1;\n"
        "@p bra.uni WAIT_DONE;\n"
        "mbarrier.try_wait.parity.shared::cta.b64 p, [%0], %1;\n"
        "@p bra.uni WAIT_DONE;\n"
        "add.u32 n, n, 1;\nsetp.lt.u32 p, n, 0x40000;\n"
        "@p bra.uni WAIT_LOOP;\n"
        "trap;\n"
        "WAIT_DONE:\n}\n"
        ::"r"(bar), "n"(PARITY) : "memory");
}
__device__ __forceinline__ bool mbar_probe(uint32_t bar, uint32_t parity) {
    uint32_t ok;
    asm volatile("{\n.reg .pred p;\nmbarrier.test_wait.parity.shared::cta.b64 p, [%1], %2;\nselp.u32 %0, 1, 0, p;\n}\n"
                 : "=r"(ok) : "r"(bar), "r"(parity) : "memory");
    return ok;
}
__device__ __forceinline__ void mbar_wait2(uint32_t bar0, uint32_t parity0, uint32_t bar1, uint32_t parity1) {
    asm volatile(
        "{\n.reg .pred p, q;\n.reg .u32 n;\n"
        "mbarrier.try_wait.parity.shared::cta.b64 p, [%0], %1;\n"
        "mbarrier.try_wait.parity.shared::cta.b64 q, [%2], %3;\n"
        "and.pred p, p, q;\n"
        "@p bra.uni WAIT_DONE;\n"
        "mov.u32 n, 0;\n"
        "WAIT_LOOP:\n"
        "mbarrier.try_wait.parity.shared::cta.b64 p, [%0], %1;\n"
        "mbarrier.try_wait.parity.shared::cta.b64 q, [%2], %3;\n"
        "and.pred p, p, q;\n"
        "@p bra.uni WAIT_DONE;\n"
        "add.u32 n, n, 1;\nsetp.lt.u32 p, n, 0x80000;\n"
        "@p bra.uni WAIT_LOOP;\n"
        "trap;\n"
        "WAIT_DONE:\n}\n"
        ::"r"(bar0), "r"(parity0), "r"(bar1), "r"(parity1) : "memory");
}
#define ELECTED(body) "{\n.reg .pred p;\nelect.sync _|p, 0xffffffff;\n" body "}\n"
__device__ __forceinline__ void expect_tx(uint32_t bar, uint32_t bytes) {
    asm volatile(ELECTED("@p mbarrier.arrive.expect_tx.shared::cta.b64 _, [%0], %1;\n") ::"r"(bar), "r"(bytes) : "memory");
}
__device__ __forceinline__ void arrive_n(uint32_t bar, uint32_t count) {
    asm volatile(ELECTED("@p mbarrier.arrive.shared::cta.b64 _, [%0], %1;\n") ::"r"(bar), "r"(count) : "memory");
}
__device__ __forceinline__ void bulk_load(uint32_t dst, const void* src, uint32_t bytes, uint32_t bar) {
    asm volatile(ELECTED("@p cp.async.bulk.shared::cluster.global.mbarrier::complete_tx::bytes [%0], [%1], %2, [%3];\n")
                 ::"r"(dst), "l"(src), "r"(bytes), "r"(bar) : "memory");
}
__device__ __forceinline__ void bulk_store(void* dst, uint32_t src, uint32_t bytes) {
    asm volatile(ELECTED("@p cp.async.bulk.global.shared::cta.bulk_group [%0], [%1], %2;\n@p cp.async.bulk.commit_group;\n")
                 ::"l"(dst), "r"(src), "r"(bytes) : "memory");
}
__device__ __forceinline__ void bulk_prefetch(const void* src, uint32_t bytes) {
    asm volatile(ELECTED("@p cp.async.bulk.prefetch.L2.global [%0], %1;\n") ::"l"(src), "r"(bytes) : "memory");
}
__device__ __forceinline__ void tma_load_2d(uint32_t dst, const CUtensorMap* map, int c0, int c1, uint32_t bar) {
    asm volatile(ELECTED("@p cp.async.bulk.tensor.2d.shared::cluster.global.mbarrier::complete_tx::bytes [%0], [%1, {%2, %3}], [%4];\n")
                 ::"r"(dst), "l"(map), "r"(c0), "r"(c1), "r"(bar) : "memory");
}
template <int N> __device__ __forceinline__ void bulk_wait_read() {
    asm volatile("cp.async.bulk.wait_group.read %0;" ::"n"(N) : "memory");
}
__device__ __forceinline__ void bulk_wait_all() { asm volatile("cp.async.bulk.wait_group 0;" ::: "memory"); }
__device__ __forceinline__ void fence_async_smem() { asm volatile("fence.proxy.async.shared::cta;" ::: "memory"); }
__device__ __forceinline__ void named_sync(int id, int n) { asm volatile("bar.sync %0, %1;" ::"r"(id), "r"(n) : "memory"); }

__device__ __forceinline__ void lds64(uint32_t (&v)[2], uint32_t addr) {
    asm volatile("ld.shared.v2.b32 {%0,%1}, [%2];" : "=r"(v[0]), "=r"(v[1]) : "r"(addr));
}
__device__ __forceinline__ void sts64(uint32_t addr, uint32_t a, uint32_t b) {
    asm volatile("st.shared.v2.b32 [%0], {%1,%2};" ::"r"(addr), "r"(a), "r"(b) : "memory");
}
__device__ __forceinline__ void sts128(uint32_t addr, uint32_t a, uint32_t b, uint32_t c, uint32_t d) {
    asm volatile("st.shared.v4.b32 [%0], {%1,%2,%3,%4};" ::"r"(addr), "r"(a), "r"(b), "r"(c), "r"(d) : "memory");
}
__device__ __forceinline__ void ldsm4(uint32_t* r, uint32_t addr) {
    asm volatile("ldmatrix.sync.aligned.m8n8.x4.shared.b16 {%0,%1,%2,%3}, [%4];"
                 : "=r"(r[0]), "=r"(r[1]), "=r"(r[2]), "=r"(r[3]) : "r"(addr) : "memory");
}
__device__ __forceinline__ void ldsm4_t(uint32_t* r, uint32_t addr) {
    asm volatile("ldmatrix.sync.aligned.m8n8.x4.trans.shared.b16 {%0,%1,%2,%3}, [%4];"
                 : "=r"(r[0]), "=r"(r[1]), "=r"(r[2]), "=r"(r[3]) : "r"(addr) : "memory");
}
__device__ __forceinline__ void lds128(uint32_t* v, uint32_t addr) {
    asm volatile("ld.shared.v4.b32 {%0,%1,%2,%3}, [%4];"
                 : "=r"(v[0]), "=r"(v[1]), "=r"(v[2]), "=r"(v[3]) : "r"(addr) : "memory");
}
__device__ __forceinline__ uint32_t lds32(uint32_t addr) {
    uint32_t v; asm volatile("ld.shared.b32 %0, [%1];" : "=r"(v) : "r"(addr) : "memory"); return v;
}
__device__ __forceinline__ void sts32(uint32_t addr, uint32_t v) {
    asm volatile("st.shared.b32 [%0], %1;" ::"r"(addr), "r"(v) : "memory");
}

__device__ __forceinline__ uint32_t bf2_fma(uint32_t a, uint32_t b, uint32_t c) {
    uint32_t d; asm("fma.rn.bf16x2 %0, %1, %2, %3;" : "=r"(d) : "r"(a), "r"(b), "r"(c)); return d;
}
__device__ __forceinline__ uint32_t bf2_mul(uint32_t a, uint32_t b) {
    uint32_t d; asm("mul.rn.bf16x2 %0, %1, %2;" : "=r"(d) : "r"(a), "r"(b)); return d;
}
__device__ __forceinline__ uint32_t bf2_add(uint32_t a, uint32_t b) {
    uint32_t d; asm("add.rn.bf16x2 %0, %1, %2;" : "=r"(d) : "r"(a), "r"(b)); return d;
}
__device__ __forceinline__ uint32_t h2_fma(uint32_t a, uint32_t b, uint32_t c) {
    uint32_t d; asm("fma.rn.f16x2 %0, %1, %2, %3;" : "=r"(d) : "r"(a), "r"(b), "r"(c)); return d;
}
__device__ __forceinline__ uint32_t h2_mul(uint32_t a, uint32_t b) {
    uint32_t d; asm("mul.rn.f16x2 %0, %1, %2;" : "=r"(d) : "r"(a), "r"(b)); return d;
}
__device__ __forceinline__ uint32_t h2_tanh(uint32_t a) {
    uint32_t d; asm("tanh.approx.f16x2 %0, %1;" : "=r"(d) : "r"(a)); return d;
}
__device__ __forceinline__ float bf_lo(uint32_t v) { return __uint_as_float(v << 16); }
__device__ __forceinline__ float bf_hi(uint32_t v) { return __uint_as_float(v & 0xffff0000u); }
__device__ __forceinline__ uint32_t pack_h2(float lo, float hi) {
    uint32_t d; asm("cvt.rn.f16x2.f32 %0, %1, %2;" : "=r"(d) : "f"(hi), "f"(lo)); return d;
}
__device__ __forceinline__ uint32_t pack_bf2(float lo, float hi) {
    uint32_t d; asm("cvt.rn.bf16x2.f32 %0, %1, %2;" : "=r"(d) : "f"(hi), "f"(lo)); return d;
}
__device__ __forceinline__ void h2_unpack(uint32_t v, float& lo, float& hi) {
    asm("{\n.reg .b16 l, h;\nmov.b32 {l, h}, %2;\ncvt.f32.f16 %0, l;\ncvt.f32.f16 %1, h;\n}\n" : "=f"(lo), "=f"(hi) : "r"(v));
}
__device__ __forceinline__ uint32_t bf2_to_h2(uint32_t v) { return pack_h2(bf_lo(v), bf_hi(v)); }

__device__ __forceinline__ uint32_t gelu2(uint32_t z) {
    uint32_t p = h2_fma(z, z, GELU_C_H2);
    uint32_t t = h2_tanh(h2_mul(z, p));
    return h2_fma(z, t, z);
}

__device__ __forceinline__ void wg_fence() { asm volatile("wgmma.fence.sync.aligned;" ::: "memory"); }
__device__ __forceinline__ void wg_commit() { asm volatile("wgmma.commit_group.sync.aligned;" ::: "memory"); }
template <int N> __device__ __forceinline__ void wg_wait() {
    asm volatile("wgmma.wait_group.sync.aligned %0;" ::"n"(N) : "memory");
}
template <int N> __device__ __forceinline__ void pin(uint32_t (&r)[N]) {
#pragma unroll
    for (int i = 0; i < N; i++) asm volatile("" : "+r"(r[i])::"memory");
}
constexpr uint32_t desc_lo(uint32_t addr, uint32_t lbo) { return ((addr & 0x3FFFF) >> 4) | ((lbo >> 4) << 16); }
template <uint32_t SBO, uint32_t SWZ> __device__ __forceinline__ uint64_t desc(uint32_t lo, uint32_t bytes) {
    return (((uint64_t)((SBO >> 4) | (SWZ << 30)) << 32) | lo) + (bytes >> 4);
}
__device__ __forceinline__ uint32_t fresh_tid() {
    uint32_t v; asm volatile("mov.u32 %0, %%tid.x;" : "=r"(v));
    return v;
}
template <uint32_t V> __device__ __forceinline__ uint32_t loop_init() {
    uint32_t v; asm volatile("mov.u32 %0, %1;" : "=r"(v) : "n"(V)); return v;
}
__device__ __forceinline__ int fresh_warp() {
    int v; asm volatile("shfl.sync.idx.b32 %0, %1, 0, 0x1f, 0xffffffff;" : "=r"(v) : "r"(fresh_tid() >> 5)); return v;
}
__device__ __forceinline__ uint32_t fresh_cta() {
    uint32_t v; asm volatile("mov.u32 %0, %%ctaid.x;" : "=r"(v)); return v;
}
__device__ __forceinline__ float rsqrt_fast(float v) { float r; asm("rsqrt.approx.ftz.f32 %0, %1;" : "=f"(r) : "f"(v)); return r; }
__device__ __forceinline__ float sqrt_fast(float v) { float r; asm("sqrt.approx.f32 %0, %1;" : "=f"(r) : "f"(v)); return r; }

template <int TB>
__device__ __forceinline__ void wgmma_n64_h_set(uint32_t (&d)[16], const uint32_t* a, uint64_t desc) {
    asm volatile(
        "{\n.reg .pred p;\nsetp.ne.b32 p, 0, 0;\n"
        "wgmma.mma_async.sync.aligned.m64n64k16.f16.f16.f16 "
        "{%0,%1,%2,%3,%4,%5,%6,%7,%8,%9,%10,%11,%12,%13,%14,%15}, {%16,%17,%18,%19}, %20, p, 1, 1, %21;\n}\n"
        : "=r"(d[0]), "=r"(d[1]), "=r"(d[2]), "=r"(d[3]), "=r"(d[4]), "=r"(d[5]), "=r"(d[6]), "=r"(d[7]), "=r"(d[8]), "=r"(d[9]), "=r"(d[10]), "=r"(d[11]), "=r"(d[12]), "=r"(d[13]), "=r"(d[14]), "=r"(d[15])
        : "r"(a[0]), "r"(a[1]), "r"(a[2]), "r"(a[3]), "l"(desc), "n"(TB));
}
template <int TB>
__device__ __forceinline__ void wgmma_n64_h_acc(uint32_t (&d)[16], const uint32_t* a, uint64_t desc) {
    asm volatile(
        "{\n.reg .pred p;\nsetp.ne.b32 p, 1, 0;\n"
        "wgmma.mma_async.sync.aligned.m64n64k16.f16.f16.f16 "
        "{%0,%1,%2,%3,%4,%5,%6,%7,%8,%9,%10,%11,%12,%13,%14,%15}, {%16,%17,%18,%19}, %20, p, 1, 1, %21;\n}\n"
        : "+r"(d[0]), "+r"(d[1]), "+r"(d[2]), "+r"(d[3]), "+r"(d[4]), "+r"(d[5]), "+r"(d[6]), "+r"(d[7]), "+r"(d[8]), "+r"(d[9]), "+r"(d[10]), "+r"(d[11]), "+r"(d[12]), "+r"(d[13]), "+r"(d[14]), "+r"(d[15])
        : "r"(a[0]), "r"(a[1]), "r"(a[2]), "r"(a[3]), "l"(desc), "n"(TB));
}
__device__ __forceinline__ void wgmma_n64_h_acc_ss(uint32_t (&d)[16], uint64_t adesc, uint64_t desc) {
    asm volatile(
        "{\n.reg .pred p;\nsetp.ne.b32 p, 1, 0;\n"
        "wgmma.mma_async.sync.aligned.m64n64k16.f16.f16.f16 "
        "{%0,%1,%2,%3,%4,%5,%6,%7,%8,%9,%10,%11,%12,%13,%14,%15}, %16, %17, p, 1, 1, 1, 0;\n}\n"
        : "+r"(d[0]), "+r"(d[1]), "+r"(d[2]), "+r"(d[3]), "+r"(d[4]), "+r"(d[5]), "+r"(d[6]), "+r"(d[7]), "+r"(d[8]), "+r"(d[9]), "+r"(d[10]), "+r"(d[11]), "+r"(d[12]), "+r"(d[13]), "+r"(d[14]), "+r"(d[15])
        : "l"(adesc), "l"(desc));
}
__device__ __forceinline__ void wgmma_n96_h_acc(uint32_t (&d)[24], const uint32_t* a, uint64_t desc) {
    asm volatile(
        "{\n.reg .pred p;\nsetp.ne.b32 p, 1, 0;\n"
        "wgmma.mma_async.sync.aligned.m64n96k16.f16.f16.f16 "
        "{%0,%1,%2,%3,%4,%5,%6,%7,%8,%9,%10,%11,%12,%13,%14,%15,%16,%17,%18,%19,%20,%21,%22,%23}, {%24,%25,%26,%27}, %28, p, 1, 1, 1;\n}\n"
        : "+r"(d[0]), "+r"(d[1]), "+r"(d[2]), "+r"(d[3]), "+r"(d[4]), "+r"(d[5]), "+r"(d[6]), "+r"(d[7]), "+r"(d[8]), "+r"(d[9]), "+r"(d[10]), "+r"(d[11]), "+r"(d[12]), "+r"(d[13]), "+r"(d[14]), "+r"(d[15]), "+r"(d[16]), "+r"(d[17]), "+r"(d[18]), "+r"(d[19]), "+r"(d[20]), "+r"(d[21]), "+r"(d[22]), "+r"(d[23])
        : "r"(a[0]), "r"(a[1]), "r"(a[2]), "r"(a[3]), "l"(desc));
}

template <int ACC>
__device__ __forceinline__ void wgmma_n8(float (&d)[4], uint32_t a0, uint32_t a1, uint32_t a2, uint32_t a3, uint64_t desc) {
    if (ACC)
        asm volatile("{\n.reg .pred p;\nsetp.ne.b32 p, 1, 0;\n"
                     "wgmma.mma_async.sync.aligned.m64n8k16.f32.bf16.bf16 {%0,%1,%2,%3}, {%4,%5,%6,%7}, %8, p, 1, 1, 0;\n}\n"
                     : "+f"(d[0]), "+f"(d[1]), "+f"(d[2]), "+f"(d[3]) : "r"(a0), "r"(a1), "r"(a2), "r"(a3), "l"(desc));
    else
        asm volatile("{\n.reg .pred p;\nsetp.ne.b32 p, 0, 0;\n"
                     "wgmma.mma_async.sync.aligned.m64n8k16.f32.bf16.bf16 {%0,%1,%2,%3}, {%4,%5,%6,%7}, %8, p, 1, 1, 0;\n}\n"
                     : "=f"(d[0]), "=f"(d[1]), "=f"(d[2]), "=f"(d[3]) : "r"(a0), "r"(a1), "r"(a2), "r"(a3), "l"(desc));
}

struct Params {
    CUtensorMap w2_map;
    const __nv_bfloat16* x;
    const __nv_bfloat16* dw;
    const __nv_bfloat16* w1;
    const __nv_bfloat16* gamma;
    const __nv_bfloat16* beta;
    __nv_bfloat16* out;
    uint64_t sel[3];
    uint32_t w1desc, w2desc, ydesc;
};

__device__ __forceinline__ uint32_t cta_tile0(uint32_t cta) {
    return (cta >> 3) * (ROWS_PER_CTA * ROW_BYTES) + (cta & 7) * TILE_BYTES;
}

struct Producer {
    uint32_t w[9][6];
    uint32_t xoff[2];
    uint32_t yoff[2][2];
    uint32_t stat, own;
    int lane, warp;
};

struct RowCopy {
    const char* x0;
    char* y0;
    uint32_t cut0, cut1;
    int first, last;
};
__device__ __forceinline__ RowCopy row_copy(const Params& prm) {
    const uint32_t cta = fresh_cta(), strip = cta & 7, t0 = cta_tile0(cta);
    RowCopy r;
    r.x0 = (const char*)prm.x + t0 - ROW_BYTES - 192;
    r.y0 = (char*)prm.out + t0;
    r.cut0 = strip == 0 ? 192 : 0;
    r.cut1 = strip == 7 ? 192 : 0;
    r.first = cta < 8 ? 1 : 0;
    r.last = cta >= NUM_CTAS - 8 ? STEPS - 2 : STEPS - 1;
    return r;
}
__device__ __forceinline__ void issue_row_load(const RowCopy& r, int i, uint32_t slot) {
    const char* src = (i >= r.first && i <= r.last) ? r.x0 + (uint32_t)i * ROW_BYTES : (const char*)g_zero_row;
    const uint32_t bar = sb + SM_XFULL + slot * SLOT_BYTES, dst = sb + SM_X + slot * SLOT_BYTES;
    expect_tx(bar, XHALF_BYTES - r.cut0);
    bulk_load(dst + r.cut0, src + r.cut0, XHALF_BYTES - r.cut0, bar);
    expect_tx(bar, XHALF_BYTES - r.cut1);
    bulk_load(dst + XHALF_B, src + 32 * 192, XHALF_BYTES - r.cut1, bar);
}

__device__ __forceinline__ float quad_sum(float v) {
    v += __shfl_xor_sync(0xffffffffu, v, 1);
    v += __shfl_xor_sync(0xffffffffu, v, 2);
    return v;
}

__device__ __forceinline__ void load_x(uint32_t (&v)[6][6], const Producer& c, uint32_t row) {
#pragma unroll
    for (int k = 0; k < 6; k++) {
        asm volatile("ld.shared.v4.b32 {%0,%1,%2,%3}, [%4];"
                     : "=r"(v[k][0]), "=r"(v[k][1]), "=r"(v[k][2]), "=r"(v[k][3]) : "r"(row + c.xoff[0] + k * 192));
        asm volatile("ld.shared.v2.b32 {%0,%1}, [%2];" : "=r"(v[k][4]), "=r"(v[k][5]) : "r"(row + c.xoff[1] + k * 192));
    }
}
template <int DY, int STRIDE>
__device__ __forceinline__ void conv_row(uint32_t (&dst)[24], const uint32_t* src, const uint32_t (&v)[6][6], const Producer& c) {
#pragma unroll
    for (int o = 0; o < 4; o++)
#pragma unroll
        for (int u = 0; u < 6; u++)
            dst[o * 6 + u] = bf2_fma(v[o + 2][u], c.w[3 * DY + 2][u], bf2_fma(v[o + 1][u], c.w[3 * DY + 1][u],
                             bf2_fma(v[o][u], c.w[3 * DY][u], STRIDE ? src[o * 6 + u] : src[2 * o + 1])));
}
__device__ __forceinline__ void start_sums(float (&d)[4], const uint32_t (&A)[24], const uint32_t (&q)[4], const Params& prm) {
    wg_fence();
#pragma unroll
    for (int k = 0; k < 6; k++) {
        const int r = (k / 3) * 12 + (k % 3) * 2;
        if (k == 0) wgmma_n8<0>(d, A[r], A[r + 6], A[r + 1], A[r + 7], prm.sel[0]);
        else wgmma_n8<1>(d, A[r], A[r + 6], A[r + 1], A[r + 7], prm.sel[k / 3]);
    }
    wgmma_n8<1>(d, q[0], q[1], q[2], q[3], prm.sel[2]);
    wg_commit();
}
__device__ __forceinline__ void finish_sums(float (&d)[4], int lane, float& sum, float& sq) {
    wg_wait<0>();
    asm volatile("" : "+f"(d[0]), "+f"(d[1]), "+f"(d[2]), "+f"(d[3])::"memory");
    sum = (lane & 1) ? d[2] : d[0];
    sq = (lane & 1) ? d[3] : d[1];
    sum += __shfl_xor_sync(0xffffffffu, sum, 4);
    sq += __shfl_xor_sync(0xffffffffu, sq, 4);
}

#define HAND_OVER(name, base, r) asm volatile("mov.b32 " name "%6, %0; mov.b32 " name "%7, %1; mov.b32 " name "%8, %2;\n" \
    "mov.b32 " name "%9, %3; mov.b32 " name "%10, %4; mov.b32 " name "%11, %5;" ::"r"((r)[0]), "r"((r)[1]), "r"((r)[2]), \
    "r"((r)[3]), "r"((r)[4]), "r"((r)[5]), "n"(base), "n"(base + 1), "n"(base + 2), "n"(base + 3), "n"(base + 4), "n"(base + 5))
template <int K> __device__ __forceinline__ void hand_over(const Producer& c, const uint32_t (&B)[24], const uint32_t (&C)[24],
                                                           const uint32_t (&v)[6][6]) {
    HAND_OVER("pw", K * 6, c.w[K]);
    if (K < 6) HAND_OVER("pv", K * 6, v[K % 6]);
    if (K < 4) { HAND_OVER("pb", K * 6, B + K % 4 * 6); HAND_OVER("pc", K * 6, C + K % 4 * 6); }
    if constexpr (K < 8) hand_over<K + 1>(c, B, C, v);
}
static_assert(sb + SM_BAR + BAR_DUMMY * 8 == 230880, "layout");
__device__ __forceinline__ void produce_tiles(const Producer& c, const Params& prm) {
    asm volatile(
        "{\n"
        ".reg .b32 pa<24>, pq<4>, m<6>, y<6>, rr, mm, t, so, sp, ph, ad, tt, cnt;\n"
        ".reg .b16 xl, xh;\n"
        ".reg .f32 d<4>, us, s0, s1, f0, f1;\n"
        ".reg .pred pt, pf, pr, pw, px, pl, po, pe;\n"
        "setp.ne.b32 pt, 1, 0; setp.ne.b32 pf, 0, 0; setp.eq.u32 pl, %8, 0; and.b32 tt, %8, 1; setp.ne.u32 po, tt, 0;\n"
        "mov.u32 t, 0; mov.u32 so, 0; mov.u32 sp, 56408; mov.u32 ph, 1;\n"
        "LOOP:\n"
        ASM_TRC("t", 0)
        "setp.eq.u32 pr, %12, 0;\n"
        "@pr bra.uni RARE;\n"
        "fence.proxy.async.shared::cta;\n"
        "@pl mbarrier.arrive.shared::cta.b64 _, [sp+174472];\n"
        "fma.rn.bf16x2 pa0, pv0, pw36, pb0; fma.rn.bf16x2 pa1, pv1, pw37, pb1; fma.rn.bf16x2 pa2, pv2, pw38, pb2; fma.rn.bf16x2 pa3, pv3, pw39, pb3; fma.rn.bf16x2 pa4, pv4, pw40, pb4; fma.rn.bf16x2 pa5, pv5, pw41, pb5;\n"
        "fma.rn.bf16x2 pa6, pv6, pw36, pb6; fma.rn.bf16x2 pa7, pv7, pw37, pb7; fma.rn.bf16x2 pa8, pv8, pw38, pb8; fma.rn.bf16x2 pa9, pv9, pw39, pb9; fma.rn.bf16x2 pa10, pv10, pw40, pb10; fma.rn.bf16x2 pa11, pv11, pw41, pb11;\n"
        "fma.rn.bf16x2 pa12, pv12, pw36, pb12; fma.rn.bf16x2 pa13, pv13, pw37, pb13; fma.rn.bf16x2 pa14, pv14, pw38, pb14; fma.rn.bf16x2 pa15, pv15, pw39, pb15; fma.rn.bf16x2 pa16, pv16, pw40, pb16; fma.rn.bf16x2 pa17, pv17, pw41, pb17;\n"
        "fma.rn.bf16x2 pa18, pv18, pw36, pb18; fma.rn.bf16x2 pa19, pv19, pw37, pb19; fma.rn.bf16x2 pa20, pv20, pw38, pb20; fma.rn.bf16x2 pa21, pv21, pw39, pb21; fma.rn.bf16x2 pa22, pv22, pw40, pb22; fma.rn.bf16x2 pa23, pv23, pw41, pb23;\n"
        "fma.rn.bf16x2 pa0, pv6, pw42, pa0; fma.rn.bf16x2 pa1, pv7, pw43, pa1; fma.rn.bf16x2 pa2, pv8, pw44, pa2; fma.rn.bf16x2 pa3, pv9, pw45, pa3; fma.rn.bf16x2 pa4, pv10, pw46, pa4; fma.rn.bf16x2 pa5, pv11, pw47, pa5;\n"
        "fma.rn.bf16x2 pa6, pv12, pw42, pa6; fma.rn.bf16x2 pa7, pv13, pw43, pa7; fma.rn.bf16x2 pa8, pv14, pw44, pa8; fma.rn.bf16x2 pa9, pv15, pw45, pa9; fma.rn.bf16x2 pa10, pv16, pw46, pa10; fma.rn.bf16x2 pa11, pv17, pw47, pa11;\n"
        "fma.rn.bf16x2 pa12, pv18, pw42, pa12; fma.rn.bf16x2 pa13, pv19, pw43, pa13; fma.rn.bf16x2 pa14, pv20, pw44, pa14; fma.rn.bf16x2 pa15, pv21, pw45, pa15; fma.rn.bf16x2 pa16, pv22, pw46, pa16; fma.rn.bf16x2 pa17, pv23, pw47, pa17;\n"
        "fma.rn.bf16x2 pa18, pv24, pw42, pa18; fma.rn.bf16x2 pa19, pv25, pw43, pa19; fma.rn.bf16x2 pa20, pv26, pw44, pa20; fma.rn.bf16x2 pa21, pv27, pw45, pa21; fma.rn.bf16x2 pa22, pv28, pw46, pa22; fma.rn.bf16x2 pa23, pv29, pw47, pa23;\n"
        "fma.rn.bf16x2 pa0, pv12, pw48, pa0; fma.rn.bf16x2 pa1, pv13, pw49, pa1; fma.rn.bf16x2 pa2, pv14, pw50, pa2; fma.rn.bf16x2 pa3, pv15, pw51, pa3; fma.rn.bf16x2 pa4, pv16, pw52, pa4; fma.rn.bf16x2 pa5, pv17, pw53, pa5;\n"
        "fma.rn.bf16x2 pa6, pv18, pw48, pa6; fma.rn.bf16x2 pa7, pv19, pw49, pa7; fma.rn.bf16x2 pa8, pv20, pw50, pa8; fma.rn.bf16x2 pa9, pv21, pw51, pa9; fma.rn.bf16x2 pa10, pv22, pw52, pa10; fma.rn.bf16x2 pa11, pv23, pw53, pa11;\n"
        "fma.rn.bf16x2 pa12, pv24, pw48, pa12; fma.rn.bf16x2 pa13, pv25, pw49, pa13; fma.rn.bf16x2 pa14, pv26, pw50, pa14; fma.rn.bf16x2 pa15, pv27, pw51, pa15; fma.rn.bf16x2 pa16, pv28, pw52, pa16; fma.rn.bf16x2 pa17, pv29, pw53, pa17;\n"
        "fma.rn.bf16x2 pa18, pv30, pw48, pa18; fma.rn.bf16x2 pa19, pv31, pw49, pa19; fma.rn.bf16x2 pa20, pv32, pw50, pa20; fma.rn.bf16x2 pa21, pv33, pw51, pa21; fma.rn.bf16x2 pa22, pv34, pw52, pa22; fma.rn.bf16x2 pa23, pv35, pw53, pa23;\n"
        "mul.rn.bf16x2 pq0, pa0, pa0; fma.rn.bf16x2 pq0, pa1, pa1, pq0; fma.rn.bf16x2 pq0, pa2, pa2, pq0; fma.rn.bf16x2 pq0, pa3, pa3, pq0; fma.rn.bf16x2 pq0, pa4, pa4, pq0; fma.rn.bf16x2 pq0, pa5, pa5, pq0;\n"
        "mul.rn.bf16x2 pq1, pa6, pa6; fma.rn.bf16x2 pq1, pa7, pa7, pq1; fma.rn.bf16x2 pq1, pa8, pa8, pq1; fma.rn.bf16x2 pq1, pa9, pa9, pq1; fma.rn.bf16x2 pq1, pa10, pa10, pq1; fma.rn.bf16x2 pq1, pa11, pa11, pq1;\n"
        "mul.rn.bf16x2 pq2, pa12, pa12; fma.rn.bf16x2 pq2, pa13, pa13, pq2; fma.rn.bf16x2 pq2, pa14, pa14, pq2; fma.rn.bf16x2 pq2, pa15, pa15, pq2; fma.rn.bf16x2 pq2, pa16, pa16, pq2; fma.rn.bf16x2 pq2, pa17, pa17, pq2;\n"
        "mul.rn.bf16x2 pq3, pa18, pa18; fma.rn.bf16x2 pq3, pa19, pa19, pq3; fma.rn.bf16x2 pq3, pa20, pa20, pq3; fma.rn.bf16x2 pq3, pa21, pa21, pq3; fma.rn.bf16x2 pq3, pa22, pa22, pq3; fma.rn.bf16x2 pq3, pa23, pa23, pq3;\n"
        "B0:\n"
        "wgmma.fence.sync.aligned;\n"
        "wgmma.mma_async.sync.aligned.m64n8k16.f32.bf16.bf16 {d0,d1,d2,d3}, {pa0,pa6,pa1,pa7}, %9, pf, 1, 1, 0;\n"
        "wgmma.mma_async.sync.aligned.m64n8k16.f32.bf16.bf16 {d0,d1,d2,d3}, {pa2,pa8,pa3,pa9}, %9, pt, 1, 1, 0;\n"
        "wgmma.mma_async.sync.aligned.m64n8k16.f32.bf16.bf16 {d0,d1,d2,d3}, {pa4,pa10,pa5,pa11}, %9, pt, 1, 1, 0;\n"
        "wgmma.mma_async.sync.aligned.m64n8k16.f32.bf16.bf16 {d0,d1,d2,d3}, {pa12,pa18,pa13,pa19}, %10, pt, 1, 1, 0;\n"
        "wgmma.mma_async.sync.aligned.m64n8k16.f32.bf16.bf16 {d0,d1,d2,d3}, {pa14,pa20,pa15,pa21}, %10, pt, 1, 1, 0;\n"
        "wgmma.mma_async.sync.aligned.m64n8k16.f32.bf16.bf16 {d0,d1,d2,d3}, {pa16,pa22,pa17,pa23}, %10, pt, 1, 1, 0;\n"
        "wgmma.mma_async.sync.aligned.m64n8k16.f32.bf16.bf16 {d0,d1,d2,d3}, {pq0,pq1,pq2,pq3}, %11, pt, 1, 1, 0;\n"
        "wgmma.commit_group.sync.aligned;\n"
        "add.u32 ad, %7, so; ld.shared.f32 us, [ad+4];\n"
        "fma.rn.bf16x2 pb0, pv0, pw18, pc0; fma.rn.bf16x2 pb1, pv1, pw19, pc1; fma.rn.bf16x2 pb2, pv2, pw20, pc2; fma.rn.bf16x2 pb3, pv3, pw21, pc3; fma.rn.bf16x2 pb4, pv4, pw22, pc4; fma.rn.bf16x2 pb5, pv5, pw23, pc5;\n"
        "fma.rn.bf16x2 pb6, pv6, pw18, pc6; fma.rn.bf16x2 pb7, pv7, pw19, pc7; fma.rn.bf16x2 pb8, pv8, pw20, pc8; fma.rn.bf16x2 pb9, pv9, pw21, pc9; fma.rn.bf16x2 pb10, pv10, pw22, pc10; fma.rn.bf16x2 pb11, pv11, pw23, pc11;\n"
        "fma.rn.bf16x2 pb0, pv6, pw24, pb0; fma.rn.bf16x2 pb1, pv7, pw25, pb1; fma.rn.bf16x2 pb2, pv8, pw26, pb2; fma.rn.bf16x2 pb3, pv9, pw27, pb3; fma.rn.bf16x2 pb4, pv10, pw28, pb4; fma.rn.bf16x2 pb5, pv11, pw29, pb5;\n"
        "fma.rn.bf16x2 pb6, pv12, pw24, pb6; fma.rn.bf16x2 pb7, pv13, pw25, pb7; fma.rn.bf16x2 pb8, pv14, pw26, pb8; fma.rn.bf16x2 pb9, pv15, pw27, pb9; fma.rn.bf16x2 pb10, pv16, pw28, pb10; fma.rn.bf16x2 pb11, pv17, pw29, pb11;\n"
        "fma.rn.bf16x2 pb0, pv12, pw30, pb0; fma.rn.bf16x2 pb1, pv13, pw31, pb1; fma.rn.bf16x2 pb2, pv14, pw32, pb2; fma.rn.bf16x2 pb3, pv15, pw33, pb3; fma.rn.bf16x2 pb4, pv16, pw34, pb4; fma.rn.bf16x2 pb5, pv17, pw35, pb5;\n"
        "fma.rn.bf16x2 pb6, pv18, pw30, pb6; fma.rn.bf16x2 pb7, pv19, pw31, pb7; fma.rn.bf16x2 pb8, pv20, pw32, pb8; fma.rn.bf16x2 pb9, pv21, pw33, pb9; fma.rn.bf16x2 pb10, pv22, pw34, pb10; fma.rn.bf16x2 pb11, pv23, pw35, pb11;\n"
        "B1:\n"
        "fma.rn.bf16x2 pb12, pv12, pw18, pc12; fma.rn.bf16x2 pb13, pv13, pw19, pc13; fma.rn.bf16x2 pb14, pv14, pw20, pc14; fma.rn.bf16x2 pb15, pv15, pw21, pc15; fma.rn.bf16x2 pb16, pv16, pw22, pc16; fma.rn.bf16x2 pb17, pv17, pw23, pc17;\n"
        "fma.rn.bf16x2 pb18, pv18, pw18, pc18; fma.rn.bf16x2 pb19, pv19, pw19, pc19; fma.rn.bf16x2 pb20, pv20, pw20, pc20; fma.rn.bf16x2 pb21, pv21, pw21, pc21; fma.rn.bf16x2 pb22, pv22, pw22, pc22; fma.rn.bf16x2 pb23, pv23, pw23, pc23;\n"
        "fma.rn.bf16x2 pb12, pv18, pw24, pb12; fma.rn.bf16x2 pb13, pv19, pw25, pb13; fma.rn.bf16x2 pb14, pv20, pw26, pb14; fma.rn.bf16x2 pb15, pv21, pw27, pb15; fma.rn.bf16x2 pb16, pv22, pw28, pb16; fma.rn.bf16x2 pb17, pv23, pw29, pb17;\n"
        "fma.rn.bf16x2 pb18, pv24, pw24, pb18; fma.rn.bf16x2 pb19, pv25, pw25, pb19; fma.rn.bf16x2 pb20, pv26, pw26, pb20; fma.rn.bf16x2 pb21, pv27, pw27, pb21; fma.rn.bf16x2 pb22, pv28, pw28, pb22; fma.rn.bf16x2 pb23, pv29, pw29, pb23;\n"
        "fma.rn.bf16x2 pb12, pv24, pw30, pb12; fma.rn.bf16x2 pb13, pv25, pw31, pb13; fma.rn.bf16x2 pb14, pv26, pw32, pb14; fma.rn.bf16x2 pb15, pv27, pw33, pb15; fma.rn.bf16x2 pb16, pv28, pw34, pb16; fma.rn.bf16x2 pb17, pv29, pw35, pb17;\n"
        "fma.rn.bf16x2 pb18, pv30, pw30, pb18; fma.rn.bf16x2 pb19, pv31, pw31, pb19; fma.rn.bf16x2 pb20, pv32, pw32, pb20; fma.rn.bf16x2 pb21, pv33, pw33, pb21; fma.rn.bf16x2 pb22, pv34, pw34, pb22; fma.rn.bf16x2 pb23, pv35, pw35, pb23;\n"
        "C0:\n"
        "wgmma.wait_group.sync.aligned 0;\n"
        "selp.f32 s0, d2, d0, po; selp.f32 s1, d3, d1, po;\n"
        "shfl.sync.bfly.b32 f0, s0, 4, 0x1f, 0xffffffff; shfl.sync.bfly.b32 f1, s1, 4, 0x1f, 0xffffffff;\n"
        "fma.rn.bf16x2 pc0, pv0, pw0, ps1; fma.rn.bf16x2 pc1, pv1, pw1, ps1; fma.rn.bf16x2 pc2, pv2, pw2, ps1; fma.rn.bf16x2 pc3, pv3, pw3, ps1; fma.rn.bf16x2 pc4, pv4, pw4, ps1; fma.rn.bf16x2 pc5, pv5, pw5, ps1;\n"
        "fma.rn.bf16x2 pc6, pv6, pw0, ps3; fma.rn.bf16x2 pc7, pv7, pw1, ps3; fma.rn.bf16x2 pc8, pv8, pw2, ps3; fma.rn.bf16x2 pc9, pv9, pw3, ps3; fma.rn.bf16x2 pc10, pv10, pw4, ps3; fma.rn.bf16x2 pc11, pv11, pw5, ps3;\n"
        "fma.rn.bf16x2 pc12, pv12, pw0, ps5; fma.rn.bf16x2 pc13, pv13, pw1, ps5; fma.rn.bf16x2 pc14, pv14, pw2, ps5; fma.rn.bf16x2 pc15, pv15, pw3, ps5; fma.rn.bf16x2 pc16, pv16, pw4, ps5; fma.rn.bf16x2 pc17, pv17, pw5, ps5;\n"
        "fma.rn.bf16x2 pc18, pv18, pw0, ps7; fma.rn.bf16x2 pc19, pv19, pw1, ps7; fma.rn.bf16x2 pc20, pv20, pw2, ps7; fma.rn.bf16x2 pc21, pv21, pw3, ps7; fma.rn.bf16x2 pc22, pv22, pw4, ps7; fma.rn.bf16x2 pc23, pv23, pw5, ps7;\n"
        "fma.rn.bf16x2 pc0, pv6, pw6, pc0; fma.rn.bf16x2 pc1, pv7, pw7, pc1; fma.rn.bf16x2 pc2, pv8, pw8, pc2; fma.rn.bf16x2 pc3, pv9, pw9, pc3; fma.rn.bf16x2 pc4, pv10, pw10, pc4; fma.rn.bf16x2 pc5, pv11, pw11, pc5;\n"
        "fma.rn.bf16x2 pc6, pv12, pw6, pc6; fma.rn.bf16x2 pc7, pv13, pw7, pc7; fma.rn.bf16x2 pc8, pv14, pw8, pc8; fma.rn.bf16x2 pc9, pv15, pw9, pc9; fma.rn.bf16x2 pc10, pv16, pw10, pc10; fma.rn.bf16x2 pc11, pv17, pw11, pc11;\n"
        "fma.rn.bf16x2 pc12, pv18, pw6, pc12; fma.rn.bf16x2 pc13, pv19, pw7, pc13; fma.rn.bf16x2 pc14, pv20, pw8, pc14; fma.rn.bf16x2 pc15, pv21, pw9, pc15; fma.rn.bf16x2 pc16, pv22, pw10, pc16; fma.rn.bf16x2 pc17, pv23, pw11, pc17;\n"
        "fma.rn.bf16x2 pc18, pv24, pw6, pc18; fma.rn.bf16x2 pc19, pv25, pw7, pc19; fma.rn.bf16x2 pc20, pv26, pw8, pc20; fma.rn.bf16x2 pc21, pv27, pw9, pc21; fma.rn.bf16x2 pc22, pv28, pw10, pc22; fma.rn.bf16x2 pc23, pv29, pw11, pc23;\n"
        "fma.rn.bf16x2 pc0, pv12, pw12, pc0; fma.rn.bf16x2 pc1, pv13, pw13, pc1; fma.rn.bf16x2 pc2, pv14, pw14, pc2; fma.rn.bf16x2 pc3, pv15, pw15, pc3; fma.rn.bf16x2 pc4, pv16, pw16, pc4; fma.rn.bf16x2 pc5, pv17, pw17, pc5;\n"
        "fma.rn.bf16x2 pc6, pv18, pw12, pc6; fma.rn.bf16x2 pc7, pv19, pw13, pc7; fma.rn.bf16x2 pc8, pv20, pw14, pc8; fma.rn.bf16x2 pc9, pv21, pw15, pc9; fma.rn.bf16x2 pc10, pv22, pw16, pc10; fma.rn.bf16x2 pc11, pv23, pw17, pc11;\n"
        "fma.rn.bf16x2 pc12, pv24, pw12, pc12; fma.rn.bf16x2 pc13, pv25, pw13, pc13; fma.rn.bf16x2 pc14, pv26, pw14, pc14; fma.rn.bf16x2 pc15, pv27, pw15, pc15; fma.rn.bf16x2 pc16, pv28, pw16, pc16; fma.rn.bf16x2 pc17, pv29, pw17, pc17;\n"
        "fma.rn.bf16x2 pc18, pv30, pw12, pc18; fma.rn.bf16x2 pc19, pv31, pw13, pc19; fma.rn.bf16x2 pc20, pv32, pw14, pc20; fma.rn.bf16x2 pc21, pv33, pw15, pc21; fma.rn.bf16x2 pc22, pv34, pw16, pc22; fma.rn.bf16x2 pc23, pv35, pw17, pc23;\n"
        "add.f32 s0, s0, f0; add.f32 s1, s1, f1; mul.f32 s0, s0, 0fBC2AAAAB;\n"
        "neg.f32 f0, s0; fma.rn.f32 f0, f0, s0, %13; fma.rn.f32 f0, s1, 0f3C2AAAAB, f0; max.f32 f0, f0, %13;\n"
        "rsqrt.approx.ftz.f32 f0, f0; mul.f32 f0, f0, %14; mul.f32 f1, s0, f0; cvt.rn.bf16x2.f32 tt, f1, f0; add.f32 us, us, s0; cvt.rn.bf16x2.f32 mm, us, us;\n"
        "add.u32 ad, %7, so; st.shared.v2.b32 [ad], {tt, mm};\n"
        "add.u32 ad, %6, so; ld.shared.v4.b32 {ps0,ps1,ps2,ps3}, [ad]; ld.shared.v4.b32 {ps4,ps5,ps6,ps7}, [ad+16];\n"
        "mbarrier.try_wait.parity.shared::cta.b64 pw, [so+174480], ph;\n"
        "mbarrier.try_wait.parity.shared::cta.b64 px, [so+174464], ph;\n"
        "and.pred pw, pw, px;\n"
        "N0:\n"
        "@!pw bra.uni SPIN;\n"
        "BACK:\n"
        "add.u32 ad, %0, so; ld.shared.v4.b32 {pv0,pv1,pv2,pv3}, [ad+0];\n"
        "add.u32 ad, %1, so; ld.shared.v2.b32 {pv4,pv5}, [ad+0];\n"
        "add.u32 ad, %0, so; ld.shared.v4.b32 {pv6,pv7,pv8,pv9}, [ad+192];\n"
        "add.u32 ad, %1, so; ld.shared.v2.b32 {pv10,pv11}, [ad+192];\n"
        "mov.b32 {xl, xh}, ps0; mov.b32 rr, {xl, xl}; mov.b32 mm, {xh, xh}; fma.rn.bf16x2 pa0, pa0, rr, mm; fma.rn.bf16x2 pa1, pa1, rr, mm; fma.rn.bf16x2 pa2, pa2, rr, mm; fma.rn.bf16x2 pa3, pa3, rr, mm; fma.rn.bf16x2 pa4, pa4, rr, mm; fma.rn.bf16x2 pa5, pa5, rr, mm;\n"
        "and.b32 m0, pa0, 0x7fff7fff; and.b32 m1, pa1, 0x7fff7fff; and.b32 m2, pa2, 0x7fff7fff; and.b32 m3, pa3, 0x7fff7fff; and.b32 m4, pa4, 0x7fff7fff; and.b32 m5, pa5, 0x7fff7fff;\n"
        "mad.lo.u32 y0, m0, 7, pa0; mad.lo.u32 y1, m1, 7, pa1; mad.lo.u32 y2, m2, 7, pa2; mad.lo.u32 y3, m3, 7, pa3; mad.lo.u32 y4, m4, 7, pa4; mad.lo.u32 y5, m5, 7, pa5;\n"
        "add.u32 ad, %2, so; st.shared.v4.b32 [ad+0], {y0,y1,y2,y3};\n"
        "add.u32 ad, %4, so; st.shared.v2.b32 [ad+0], {y4,y5};\n"
        "N1:\n"
        "add.u32 ad, %0, so; ld.shared.v4.b32 {pv12,pv13,pv14,pv15}, [ad+384];\n"
        "add.u32 ad, %1, so; ld.shared.v2.b32 {pv16,pv17}, [ad+384];\n"
        "add.u32 ad, %0, so; ld.shared.v4.b32 {pv18,pv19,pv20,pv21}, [ad+576];\n"
        "add.u32 ad, %1, so; ld.shared.v2.b32 {pv22,pv23}, [ad+576];\n"
        "mov.b32 {xl, xh}, ps2; mov.b32 rr, {xl, xl}; mov.b32 mm, {xh, xh}; fma.rn.bf16x2 pa6, pa6, rr, mm; fma.rn.bf16x2 pa7, pa7, rr, mm; fma.rn.bf16x2 pa8, pa8, rr, mm; fma.rn.bf16x2 pa9, pa9, rr, mm; fma.rn.bf16x2 pa10, pa10, rr, mm; fma.rn.bf16x2 pa11, pa11, rr, mm;\n"
        "and.b32 m0, pa6, 0x7fff7fff; and.b32 m1, pa7, 0x7fff7fff; and.b32 m2, pa8, 0x7fff7fff; and.b32 m3, pa9, 0x7fff7fff; and.b32 m4, pa10, 0x7fff7fff; and.b32 m5, pa11, 0x7fff7fff;\n"
        "mad.lo.u32 y0, m0, 7, pa6; mad.lo.u32 y1, m1, 7, pa7; mad.lo.u32 y2, m2, 7, pa8; mad.lo.u32 y3, m3, 7, pa9; mad.lo.u32 y4, m4, 7, pa10; mad.lo.u32 y5, m5, 7, pa11;\n"
        "add.u32 ad, %3, so; st.shared.v4.b32 [ad+0], {y0,y1,y2,y3};\n"
        "add.u32 ad, %5, so; st.shared.v2.b32 [ad+0], {y4,y5};\n"
        "N2:\n"
        "add.u32 ad, %0, so; ld.shared.v4.b32 {pv24,pv25,pv26,pv27}, [ad+768];\n"
        "add.u32 ad, %1, so; ld.shared.v2.b32 {pv28,pv29}, [ad+768];\n"
        "mov.b32 {xl, xh}, ps4; mov.b32 rr, {xl, xl}; mov.b32 mm, {xh, xh}; fma.rn.bf16x2 pa12, pa12, rr, mm; fma.rn.bf16x2 pa13, pa13, rr, mm; fma.rn.bf16x2 pa14, pa14, rr, mm; fma.rn.bf16x2 pa15, pa15, rr, mm; fma.rn.bf16x2 pa16, pa16, rr, mm; fma.rn.bf16x2 pa17, pa17, rr, mm;\n"
        "and.b32 m0, pa12, 0x7fff7fff; and.b32 m1, pa13, 0x7fff7fff; and.b32 m2, pa14, 0x7fff7fff; and.b32 m3, pa15, 0x7fff7fff; and.b32 m4, pa16, 0x7fff7fff; and.b32 m5, pa17, 0x7fff7fff;\n"
        "mad.lo.u32 y0, m0, 7, pa12; mad.lo.u32 y1, m1, 7, pa13; mad.lo.u32 y2, m2, 7, pa14; mad.lo.u32 y3, m3, 7, pa15; mad.lo.u32 y4, m4, 7, pa16; mad.lo.u32 y5, m5, 7, pa17;\n"
        "add.u32 ad, %2, so; st.shared.v4.b32 [ad+2048], {y0,y1,y2,y3};\n"
        "add.u32 ad, %4, so; st.shared.v2.b32 [ad+1024], {y4,y5};\n"
        "N3:\n"
        "add.u32 ad, %0, so; ld.shared.v4.b32 {pv30,pv31,pv32,pv33}, [ad+960];\n"
        "add.u32 ad, %1, so; ld.shared.v2.b32 {pv34,pv35}, [ad+960];\n"
        "mov.b32 {xl, xh}, ps6; mov.b32 rr, {xl, xl}; mov.b32 mm, {xh, xh}; fma.rn.bf16x2 pa18, pa18, rr, mm; fma.rn.bf16x2 pa19, pa19, rr, mm; fma.rn.bf16x2 pa20, pa20, rr, mm; fma.rn.bf16x2 pa21, pa21, rr, mm; fma.rn.bf16x2 pa22, pa22, rr, mm; fma.rn.bf16x2 pa23, pa23, rr, mm;\n"
        "and.b32 m0, pa18, 0x7fff7fff; and.b32 m1, pa19, 0x7fff7fff; and.b32 m2, pa20, 0x7fff7fff; and.b32 m3, pa21, 0x7fff7fff; and.b32 m4, pa22, 0x7fff7fff; and.b32 m5, pa23, 0x7fff7fff;\n"
        "mad.lo.u32 y0, m0, 7, pa18; mad.lo.u32 y1, m1, 7, pa19; mad.lo.u32 y2, m2, 7, pa20; mad.lo.u32 y3, m3, 7, pa21; mad.lo.u32 y4, m4, 7, pa22; mad.lo.u32 y5, m5, 7, pa23;\n"
        "add.u32 ad, %3, so; st.shared.v4.b32 [ad+2048], {y0,y1,y2,y3};\n"
        "add.u32 ad, %5, so; st.shared.v2.b32 [ad+1024], {y4,y5};\n"
        "mov.u32 sp, so; add.u32 so, so, 26624; setp.eq.u32 pr, so, 79872; selp.u32 so, 0, so, pr; selp.u32 tt, 1, 0, pr; xor.b32 ph, ph, tt;\n"
        "add.u32 t, t, 1; setp.lt.u32 pe, t, 32;\n"
        "@pe bra.uni LOOP;\n"
        "bra.uni DONE;\n"
        "SPIN: mov.u32 cnt, 0;\n"
        ASM_TRC("t", 1)
        "SPINL:\n"
        "mbarrier.try_wait.parity.shared::cta.b64 pw, [so+174480], ph;\n"
        "mbarrier.try_wait.parity.shared::cta.b64 px, [so+174464], ph;\n"
        "and.pred pw, pw, px;\n"
        "@pw bra.uni BACK;\n"
        "add.u32 cnt, cnt, 1; setp.lt.u32 pw, cnt, 0x100000;\n"
        "@pw bra.uni SPINL;\n"
        "trap;\n"
        "RARE:\n"
        "ld.volatile.shared.u32 tt, [%6];\n"
        "mov.b32 pa0, tt; mov.b32 pa1, tt; mov.b32 pa2, tt; mov.b32 pa3, tt; mov.b32 pa4, tt; mov.b32 pa5, tt; mov.b32 pa6, tt; mov.b32 pa7, tt; mov.b32 pa8, tt; mov.b32 pa9, tt; mov.b32 pa10, tt; mov.b32 pa11, tt;\n"
        "mov.b32 pa12, tt; mov.b32 pa13, tt; mov.b32 pa14, tt; mov.b32 pa15, tt; mov.b32 pa16, tt; mov.b32 pa17, tt; mov.b32 pa18, tt; mov.b32 pa19, tt; mov.b32 pa20, tt; mov.b32 pa21, tt; mov.b32 pa22, tt; mov.b32 pa23, tt;\n"
        "mov.b32 pb0, tt; mov.b32 pb1, tt; mov.b32 pb2, tt; mov.b32 pb3, tt; mov.b32 pb4, tt; mov.b32 pb5, tt; mov.b32 pb6, tt; mov.b32 pb7, tt; mov.b32 pb8, tt; mov.b32 pb9, tt; mov.b32 pb10, tt; mov.b32 pb11, tt;\n"
        "mov.b32 pb12, tt; mov.b32 pb13, tt; mov.b32 pb14, tt; mov.b32 pb15, tt; mov.b32 pb16, tt; mov.b32 pb17, tt; mov.b32 pb18, tt; mov.b32 pb19, tt; mov.b32 pb20, tt; mov.b32 pb21, tt; mov.b32 pb22, tt; mov.b32 pb23, tt;\n"
        "mov.b32 pc0, tt; mov.b32 pc1, tt; mov.b32 pc2, tt; mov.b32 pc3, tt; mov.b32 pc4, tt; mov.b32 pc5, tt; mov.b32 pc6, tt; mov.b32 pc7, tt; mov.b32 pc8, tt; mov.b32 pc9, tt; mov.b32 pc10, tt; mov.b32 pc11, tt;\n"
        "mov.b32 pc12, tt; mov.b32 pc13, tt; mov.b32 pc14, tt; mov.b32 pc15, tt; mov.b32 pc16, tt; mov.b32 pc17, tt; mov.b32 pc18, tt; mov.b32 pc19, tt; mov.b32 pc20, tt; mov.b32 pc21, tt; mov.b32 pc22, tt; mov.b32 pc23, tt;\n"
        "mov.b32 pv0, tt; mov.b32 pv1, tt; mov.b32 pv2, tt; mov.b32 pv3, tt; mov.b32 pv4, tt; mov.b32 pv5, tt; mov.b32 pv6, tt; mov.b32 pv7, tt; mov.b32 pv8, tt; mov.b32 pv9, tt; mov.b32 pv10, tt; mov.b32 pv11, tt;\n"
        "mov.b32 pv12, tt; mov.b32 pv13, tt; mov.b32 pv14, tt; mov.b32 pv15, tt; mov.b32 pv16, tt; mov.b32 pv17, tt; mov.b32 pv18, tt; mov.b32 pv19, tt; mov.b32 pv20, tt; mov.b32 pv21, tt; mov.b32 pv22, tt; mov.b32 pv23, tt;\n"
        "mov.b32 pv24, tt; mov.b32 pv25, tt; mov.b32 pv26, tt; mov.b32 pv27, tt; mov.b32 pv28, tt; mov.b32 pv29, tt; mov.b32 pv30, tt; mov.b32 pv31, tt; mov.b32 pv32, tt; mov.b32 pv33, tt; mov.b32 pv34, tt; mov.b32 pv35, tt;\n"
        "mov.b32 ps0, tt; mov.b32 ps1, tt; mov.b32 ps2, tt; mov.b32 ps3, tt; mov.b32 ps4, tt; mov.b32 ps5, tt; mov.b32 ps6, tt; mov.b32 ps7, tt; mov.b32 pq0, tt; mov.b32 pq1, tt; mov.b32 pq2, tt; mov.b32 pq3, tt;\n"
        "mov.b32 m0, tt; mov.b32 m1, tt; mov.b32 m2, tt; mov.b32 m3, tt; mov.b32 m4, tt; mov.b32 m5, tt; mov.b32 y0, tt; mov.b32 y1, tt; mov.b32 y2, tt; mov.b32 y3, tt; mov.b32 y4, tt; mov.b32 y5, tt;\n"
        "mov.b32 us, tt; setp.ne.u32 pw, t, 7;\n"
        "wgmma.fence.sync.aligned;\n"
        "setp.eq.u32 pr, t, 1000; @pr bra.uni B0;\n"
        "setp.eq.u32 pr, t, 1001; @pr bra.uni B1;\n"
        "setp.eq.u32 pr, t, 1002; @pr bra.uni C0;\n"
        "setp.eq.u32 pr, t, 1003; @pr bra.uni N0;\n"
        "setp.eq.u32 pr, t, 1004; @pr bra.uni N1;\n"
        "setp.eq.u32 pr, t, 1005; @pr bra.uni N2;\n"
        "setp.eq.u32 pr, t, 1006; @pr bra.uni N3;\n"
        "trap;\n"
        "DONE:\n"
        ASM_TRC("t", 0)
        "fence.proxy.async.shared::cta;\n"
        "@pl mbarrier.arrive.shared::cta.b64 _, [sp+174472];\n"
        "}\n"
        :: "r"(sb + SM_X + c.xoff[0]), "r"(sb + SM_X + c.xoff[1]), "r"(sb + SM_Y1 + c.yoff[0][0]), "r"(sb + SM_Y1 + c.yoff[0][1]),
           "r"(sb + SM_Y1 + c.yoff[1][0]), "r"(sb + SM_Y1 + c.yoff[1][1]), "r"(c.stat), "r"(c.own), "r"(c.lane),
           "l"(prm.sel[0]), "l"(prm.sel[1]), "l"(prm.sel[2]), "r"(prm.ydesc), "f"(LN_EPS_SCALED), "f"(RSTD_SCALE)
        : "memory");
}

__device__ __forceinline__ void produce(const Producer& c, const Params& prm) {
    uint32_t A[24], B[24], C[24];
    const RowCopy rc = row_copy(prm);
    uint32_t st[8];
    uint32_t v[6][6];
    float d[4];
    {
        uint32_t ws[6], q[4] = {};
#pragma unroll
        for (int u = 0; u < 6; u++) {
            ws[u] = c.w[0][u];
#pragma unroll
            for (int t = 1; t < 9; t++) ws[u] = bf2_add(ws[u], c.w[t][u]);
        }
        mbar_wait_c<0>(sb + SM_XFULL + rc.first * SLOT_BYTES);
        load_x(v, c, sb + SM_X + rc.first * SLOT_BYTES);
#pragma unroll
        for (int r = 0; r < 24; r++) A[r] = bf2_mul(v[r / 6 + 1][r % 6], ws[r % 6]);
        start_sums(d, A, q, prm);
        float e, sq;
        finish_sums(d, c.lane, e, sq);
        e *= -1.0f / CH;
#pragma unroll
        for (int k = 0; k < NX; k++) sts32(c.own + k * SLOT_BYTES + 4, pack_bf2(e, e));
        __syncwarp();
        lds128(st, c.stat);
        lds128(st + 4, c.stat + 16);
#pragma unroll
        for (int r = 0; r < 24; r++) C[r] = 0;
    }
#pragma unroll 1
    for (int i = loop_init<0>();; i++) {
        mbar_wait_c<0>(sb + SM_XFULL + i * SLOT_BYTES);
        load_x(v, c, sb + SM_X + i * SLOT_BYTES);
        fence_async_smem();
        if (c.warp == i) {
            named_sync(6 + i, 128);
            issue_row_load(rc, i + NX, i);
        } else {
            asm volatile("bar.arrive %0, 128;" ::"r"(6 + i) : "memory");
        }
        if (i == 2) break;
        conv_row<1, 1>(B, C, v, c);
        conv_row<0, 0>(C, st, v, c);
    }
    if (c.warp == 3) {
        expect_tx(sb + SM_BAR + BAR_W2 * 8, CH * EX * 2 + EX * 4);
        bulk_load(sb + SM_GAMMA, prm.gamma, EX * 2, sb + SM_BAR + BAR_W2 * 8);
        bulk_load(sb + SM_BETA, prm.beta, EX * 2, sb + SM_BAR + BAR_W2 * 8);
#pragma unroll
        for (int k = 0; k < 6; k++)
            tma_load_2d(sb + SM_W2 + k * 12288, &prm.w2_map, 32 * (k >> 1), 192 * (k & 1), sb + SM_BAR + BAR_W2 * 8);
    }
    asm volatile(".reg .b32 pw<54>, pb<24>, pc<24>, pv<36>, ps<8>;");
    hand_over<0>(c, B, C, v);
    asm volatile("mov.b32 ps1, %0; mov.b32 ps3, %1; mov.b32 ps5, %2; mov.b32 ps7, %3;" ::"r"(st[1]), "r"(st[3]), "r"(st[5]), "r"(st[7]));
    produce_tiles(c, prm);
    mbar_arrive_if(sb + SM_Y1FULL + ROWS_PER_CTA % NX * SLOT_BYTES, c.lane == 0);
}

struct Duty {
    const char* g;
    uint32_t s, bytes;
    int end, zero;
};
__device__ __forceinline__ Duty make_duty(const Params& prm, int wg, int w) {
    const RowCopy rc = row_copy(prm);
    Duty d;
    d.g = (w == 2 ? rc.y0 : rc.x0 + 2 * NX * ROW_BYTES + (w == 0 ? rc.cut0 : w == 1 ? 32 * 192 : 192 + L2_AHEAD * ROW_BYTES)) +
          (uint32_t)wg * ROW_BYTES;
    d.s = wg * SLOT_BYTES + (w == 2 ? sb + SM_Y1 : sb + SM_X + (w == 0 ? rc.cut0 : XHALF_B));
    d.bytes = w >= 2 ? TILE_BYTES : XHALF_BYTES - (w == 0 ? rc.cut0 : rc.cut1);
    d.end = w == 2 ? ROWS_PER_CTA : w < 2 ? STEPS + 1 - 2 * NX : rc.last + 1 - 2 * NX - L2_AHEAD;
    d.zero = rc.last + 1 - 2 * NX;
    return d;
}

static_assert(sb + SM_Y1FULL == 174472 && sb + SM_Y1EMPTY == 174480 && sb + SM_XFULL == 174464 && SLOT_BYTES == 26624, "layout");
__device__ __forceinline__ void consume(float (&acc)[2][2], uint32_t w1t, uint32_t yd, uint32_t wd, uint32_t own_slot, const Duty& d,
                                        uint32_t role, uint32_t lane) {
    asm volatile(
        "{\n"
        ".reg .b32 z<32>, w<44>, p<2>, a<4>, lo<4>, hi<4>, t<2>, g<2>, q<4>, n, so, sp, ph, c, tt, cnt;\n"
        ".reg .b16 xl, xh, xr;\n"
        ".reg .f32 f0, f1;\n"
        ".reg .b64 ds<6>, wd, gp, src;\n"
        ".reg .pred pt, pf, pr, pw, pl, pe;\n"
        "setp.ne.b32 pt, 1, 0; setp.ne.b32 pf, 0, 0; setp.eq.u32 pl, %15, 0;\n"
        "mov.b32 c, 0x40D940D9;\n"
        "ldmatrix.sync.aligned.m8n8.x4.trans.shared.b16 {w0,w1,w2,w3}, [%4+0];\n"
        "ldmatrix.sync.aligned.m8n8.x4.trans.shared.b16 {w4,w5,w6,w7}, [%4+2048];\n"
        "ldmatrix.sync.aligned.m8n8.x4.trans.shared.b16 {w8,w9,w10,w11}, [%4+4096];\n"
        "ldmatrix.sync.aligned.m8n8.x4.trans.shared.b16 {w12,w13,w14,w15}, [%4+6144];\n"
        "ldmatrix.sync.aligned.m8n8.x4.trans.shared.b16 {w16,w17,w18,w19}, [%4+8192];\n"
        "ldmatrix.sync.aligned.m8n8.x4.trans.shared.b16 {w20,w21,w22,w23}, [%4+10240];\n"
        "ldmatrix.sync.aligned.m8n8.x4.trans.shared.b16 {w24,w25,w26,w27}, [%4+12288];\n"
        "ldmatrix.sync.aligned.m8n8.x4.trans.shared.b16 {w28,w29,w30,w31}, [%4+14336];\n"
        "ldmatrix.sync.aligned.m8n8.x4.trans.shared.b16 {w32,w33,w34,w35}, [%4+16384];\n"
        "ldmatrix.sync.aligned.m8n8.x4.trans.shared.b16 {w36,w37,w38,w39}, [%4+18432];\n"
        "ldmatrix.sync.aligned.m8n8.x4.trans.shared.b16 {w40,w41,w42,w43}, [%4+20480];\n"
        "mov.b32 p0, 0; mov.b32 p1, 0; mov.b32 t0, 0; mov.b32 t1, 0; mov.b32 g0, 0; mov.b32 g1, 0; mov.b32 a0, 0; mov.b32 a1, 0; mov.b32 lo0, 0; mov.b32 lo1, 0; mov.b32 hi0, 0; mov.b32 hi1, 0; mov.b32 q0, 0; mov.b32 q1, 0; mov.b32 q2, 0; mov.b32 q3, 0;\n"
        "mov.b32 z16, 0; mov.b32 z17, 0; mov.b32 z18, 0; mov.b32 z19, 0; mov.b32 z20, 0; mov.b32 z21, 0; mov.b32 z22, 0; mov.b32 z23, 0; mov.b32 z24, 0; mov.b32 z25, 0; mov.b32 z26, 0; mov.b32 z27, 0; mov.b32 z28, 0; mov.b32 z29, 0; mov.b32 z30, 0; mov.b32 z31, 0;\n"
        "mov.f32 %0, 0f00000000; mov.f32 %1, 0f00000000; mov.f32 %2, 0f00000000; mov.f32 %3, 0f00000000;\n"
        "mov.u32 n, 0; mov.u32 so, 0; mov.u32 sp, 0; mov.u32 ph, 0; mov.b64 gp, %8; mov.b64 wd, {%6, 0x40000040};\n"
        "shr.u32 tt, so, 4; add.u32 tt, tt, %5; mov.b64 ds0, {tt, 0x40000040}; mov.b64 ds4, {tt, 0x80000020};\n"
        "add.s64 ds1, ds0, 2; add.s64 ds2, ds0, 4; add.s64 ds3, ds0, 6; add.s64 ds5, ds4, 514; add.s64 ds4, ds4, 512;\n"
        "mbarrier.try_wait.parity.shared::cta.b64 pw, [so+174472], ph;\n"
        "@!pw bra.uni SPIN0;\n"
        "BACK0:\n"
        ASM_TS
        "wgmma.fence.sync.aligned;\n"
        "wgmma.mma_async.sync.aligned.m64n64k16.f16.f16.f16 {z0,z1,z2,z3,z4,z5,z6,z7,z8,z9,z10,z11,z12,z13,z14,z15}, {w0,w1,w2,w3}, ds0, pf, 1, 1, 0;\n"
        "wgmma.mma_async.sync.aligned.m64n64k16.f16.f16.f16 {z0,z1,z2,z3,z4,z5,z6,z7,z8,z9,z10,z11,z12,z13,z14,z15}, {w4,w5,w6,w7}, ds1, pt, 1, 1, 0;\n"
        "wgmma.mma_async.sync.aligned.m64n64k16.f16.f16.f16 {z0,z1,z2,z3,z4,z5,z6,z7,z8,z9,z10,z11,z12,z13,z14,z15}, {w8,w9,w10,w11}, ds2, pt, 1, 1, 0;\n"
        "wgmma.mma_async.sync.aligned.m64n64k16.f16.f16.f16 {z0,z1,z2,z3,z4,z5,z6,z7,z8,z9,z10,z11,z12,z13,z14,z15}, {w12,w13,w14,w15}, ds3, pt, 1, 1, 0;\n"
        "wgmma.mma_async.sync.aligned.m64n64k16.f16.f16.f16 {z0,z1,z2,z3,z4,z5,z6,z7,z8,z9,z10,z11,z12,z13,z14,z15}, {w16,w17,w18,w19}, ds4, pt, 1, 1, 0;\n"
        "wgmma.mma_async.sync.aligned.m64n64k16.f16.f16.f16 {z0,z1,z2,z3,z4,z5,z6,z7,z8,z9,z10,z11,z12,z13,z14,z15}, {w20,w21,w22,w23}, ds5, pt, 1, 1, 0;\n"
        "wgmma.commit_group.sync.aligned;\n"
        "LOOP:\n"
        ASM_TRC("n", 0)
        "setp.eq.u32 pr, so, %7;\n"
        "@pr bra.uni DUTY;\n"
        "TOP:\n"
        "wgmma.wait_group.sync.aligned 0;\n"
        "mov.b32 {xl, xh}, a0; tanh.approx.f16 xr, xl; cvt.u32.u16 lo0, xr; tanh.approx.f16 xr, xh; cvt.u32.u16 hi0, xr; fma.rn.f16x2 p0, z0, z0, c; mul.rn.f16x2 a1, z31, p1; fma.rn.f16x2 q3, g1, g1, q3; fma.rn.f16x2 g0, z28, t0, z28; prmt.b32 t1, lo1, hi1, 0x5410;\n"
        "B31:\n"
        "mov.b32 {xl, xh}, a1; tanh.approx.f16 xr, xl; cvt.u32.u16 lo1, xr; tanh.approx.f16 xr, xh; cvt.u32.u16 hi1, xr; fma.rn.f16x2 p1, z1, z1, c; mul.rn.f16x2 a0, z0, p0; fma.rn.f16x2 q2, g0, g0, q2; fma.rn.f16x2 g1, z29, t1, z29; prmt.b32 t0, lo0, hi0, 0x5410;\n"
        "B0:\n"
        "mov.b32 {xl, xh}, a0; tanh.approx.f16 xr, xl; cvt.u32.u16 lo0, xr; tanh.approx.f16 xr, xh; cvt.u32.u16 hi0, xr; fma.rn.f16x2 p0, z2, z2, c; mul.rn.f16x2 a1, z1, p1; fma.rn.f16x2 q3, g1, g1, q3; fma.rn.f16x2 g0, z30, t0, z30; prmt.b32 t1, lo1, hi1, 0x5410;\n"
        "B1:\n"
        "mov.b32 {xl, xh}, a1; tanh.approx.f16 xr, xl; cvt.u32.u16 lo1, xr; tanh.approx.f16 xr, xh; cvt.u32.u16 hi1, xr; fma.rn.f16x2 p1, z3, z3, c; mul.rn.f16x2 a0, z2, p0; fma.rn.f16x2 q2, g0, g0, q2; fma.rn.f16x2 g1, z31, t1, z31; prmt.b32 t0, lo0, hi0, 0x5410;\n"
        "B2:\n"
        "wgmma.fence.sync.aligned;\n"
        "wgmma.mma_async.sync.aligned.m64n64k16.f16.f16.f16 {z16,z17,z18,z19,z20,z21,z22,z23,z24,z25,z26,z27,z28,z29,z30,z31}, {w24,w25,w26,w27}, ds0, pf, 1, 1, 0;\n"
        "wgmma.mma_async.sync.aligned.m64n64k16.f16.f16.f16 {z16,z17,z18,z19,z20,z21,z22,z23,z24,z25,z26,z27,z28,z29,z30,z31}, {w28,w29,w30,w31}, ds1, pt, 1, 1, 0;\n"
        "wgmma.mma_async.sync.aligned.m64n64k16.f16.f16.f16 {z16,z17,z18,z19,z20,z21,z22,z23,z24,z25,z26,z27,z28,z29,z30,z31}, {w32,w33,w34,w35}, ds2, pt, 1, 1, 0;\n"
        "mov.b32 {xl, xh}, a0; tanh.approx.f16 xr, xl; cvt.u32.u16 lo0, xr; tanh.approx.f16 xr, xh; cvt.u32.u16 hi0, xr; fma.rn.f16x2 p0, z4, z4, c; mul.rn.f16x2 a1, z3, p1; fma.rn.f16x2 q3, g1, g1, q3; fma.rn.f16x2 g0, z0, t0, z0; prmt.b32 t1, lo1, hi1, 0x5410;\n"
        "B3:\n"
        "mov.b32 {xl, xh}, a1; tanh.approx.f16 xr, xl; cvt.u32.u16 lo1, xr; tanh.approx.f16 xr, xh; cvt.u32.u16 hi1, xr; fma.rn.f16x2 p1, z5, z5, c; mul.rn.f16x2 a0, z4, p0; fma.rn.f16x2 q0, g0, g0, q0; fma.rn.f16x2 g1, z1, t1, z1; prmt.b32 t0, lo0, hi0, 0x5410;\n"
        "B4:\n"
        "mov.b32 {xl, xh}, a0; tanh.approx.f16 xr, xl; cvt.u32.u16 lo0, xr; tanh.approx.f16 xr, xh; cvt.u32.u16 hi0, xr; fma.rn.f16x2 p0, z6, z6, c; mul.rn.f16x2 a1, z5, p1; fma.rn.f16x2 q1, g1, g1, q1; fma.rn.f16x2 g0, z2, t0, z2; prmt.b32 t1, lo1, hi1, 0x5410;\n"
        "B5:\n"
        "wgmma.mma_async.sync.aligned.m64n64k16.f16.f16.f16 {z16,z17,z18,z19,z20,z21,z22,z23,z24,z25,z26,z27,z28,z29,z30,z31}, {w36,w37,w38,w39}, ds3, pt, 1, 1, 0;\n"
        "wgmma.mma_async.sync.aligned.m64n64k16.f16.f16.f16 {z16,z17,z18,z19,z20,z21,z22,z23,z24,z25,z26,z27,z28,z29,z30,z31}, {w40,w41,w42,w43}, ds4, pt, 1, 1, 0;\n"
        "wgmma.mma_async.sync.aligned.m64n64k16.f16.f16.f16 {z16,z17,z18,z19,z20,z21,z22,z23,z24,z25,z26,z27,z28,z29,z30,z31}, wd, ds5, pt, 1, 1, 1, 0;\n"
        "wgmma.commit_group.sync.aligned;\n"
        "mov.b32 {xl, xh}, a1; tanh.approx.f16 xr, xl; cvt.u32.u16 lo1, xr; tanh.approx.f16 xr, xh; cvt.u32.u16 hi1, xr; fma.rn.f16x2 p1, z7, z7, c; mul.rn.f16x2 a0, z6, p0; fma.rn.f16x2 q0, g0, g0, q0; fma.rn.f16x2 g1, z3, t1, z3; prmt.b32 t0, lo0, hi0, 0x5410;\n"
        "B6:\n"
        "mov.u32 sp, so; add.u32 so, so, 26624; setp.eq.u32 pr, so, 79872; selp.u32 so, 0, so, pr; selp.u32 tt, 1, 0, pr; xor.b32 ph, ph, tt;\n"
        "mov.b32 {xl, xh}, a0; tanh.approx.f16 xr, xl; cvt.u32.u16 lo0, xr; tanh.approx.f16 xr, xh; cvt.u32.u16 hi0, xr; fma.rn.f16x2 p0, z8, z8, c; mul.rn.f16x2 a1, z7, p1; fma.rn.f16x2 q1, g1, g1, q1; fma.rn.f16x2 g0, z4, t0, z4; prmt.b32 t1, lo1, hi1, 0x5410;\n"
        "B7:\n"
        "shr.u32 tt, so, 4; add.u32 tt, tt, %5; mov.b64 ds0, {tt, 0x40000040}; mov.b64 ds4, {tt, 0x80000020};\n"
        "add.s64 ds1, ds0, 2; add.s64 ds2, ds0, 4; add.s64 ds3, ds0, 6; add.s64 ds5, ds4, 514; add.s64 ds4, ds4, 512;\n"
        "mov.b32 {xl, xh}, a1; tanh.approx.f16 xr, xl; cvt.u32.u16 lo1, xr; tanh.approx.f16 xr, xh; cvt.u32.u16 hi1, xr; fma.rn.f16x2 p1, z9, z9, c; mul.rn.f16x2 a0, z8, p0; fma.rn.f16x2 q0, g0, g0, q0; fma.rn.f16x2 g1, z5, t1, z5; prmt.b32 t0, lo0, hi0, 0x5410;\n"
        "B8:\n"
        "mov.b32 {xl, xh}, a0; tanh.approx.f16 xr, xl; cvt.u32.u16 lo0, xr; tanh.approx.f16 xr, xh; cvt.u32.u16 hi0, xr; fma.rn.f16x2 p0, z10, z10, c; mul.rn.f16x2 a1, z9, p1; fma.rn.f16x2 q1, g1, g1, q1; fma.rn.f16x2 g0, z6, t0, z6; prmt.b32 t1, lo1, hi1, 0x5410;\n"
        "B9:\n"
        "mov.b32 {xl, xh}, a1; tanh.approx.f16 xr, xl; cvt.u32.u16 lo1, xr; tanh.approx.f16 xr, xh; cvt.u32.u16 hi1, xr; fma.rn.f16x2 p1, z11, z11, c; mul.rn.f16x2 a0, z10, p0; fma.rn.f16x2 q0, g0, g0, q0; fma.rn.f16x2 g1, z7, t1, z7; prmt.b32 t0, lo0, hi0, 0x5410;\n"
        "B10:\n"
        "mov.b32 {xl, xh}, a0; tanh.approx.f16 xr, xl; cvt.u32.u16 lo0, xr; tanh.approx.f16 xr, xh; cvt.u32.u16 hi0, xr; fma.rn.f16x2 p0, z12, z12, c; mul.rn.f16x2 a1, z11, p1; fma.rn.f16x2 q1, g1, g1, q1; fma.rn.f16x2 g0, z8, t0, z8; prmt.b32 t1, lo1, hi1, 0x5410;\n"
        "B11:\n"
        "mov.b32 {xl, xh}, a1; tanh.approx.f16 xr, xl; cvt.u32.u16 lo1, xr; tanh.approx.f16 xr, xh; cvt.u32.u16 hi1, xr; fma.rn.f16x2 p1, z13, z13, c; mul.rn.f16x2 a0, z12, p0; fma.rn.f16x2 q0, g0, g0, q0; fma.rn.f16x2 g1, z9, t1, z9; prmt.b32 t0, lo0, hi0, 0x5410;\n"
        "B12:\n"
        "mov.b32 {xl, xh}, a0; tanh.approx.f16 xr, xl; cvt.u32.u16 lo0, xr; tanh.approx.f16 xr, xh; cvt.u32.u16 hi0, xr; fma.rn.f16x2 p0, z14, z14, c; mul.rn.f16x2 a1, z13, p1; fma.rn.f16x2 q1, g1, g1, q1; fma.rn.f16x2 g0, z10, t0, z10; prmt.b32 t1, lo1, hi1, 0x5410;\n"
        "B13:\n"
        "mov.b32 {xl, xh}, a1; tanh.approx.f16 xr, xl; cvt.u32.u16 lo1, xr; tanh.approx.f16 xr, xh; cvt.u32.u16 hi1, xr; fma.rn.f16x2 p1, z15, z15, c; mul.rn.f16x2 a0, z14, p0; fma.rn.f16x2 q0, g0, g0, q0; fma.rn.f16x2 g1, z11, t1, z11; prmt.b32 t0, lo0, hi0, 0x5410;\n"
        "B14:\n"
        "wgmma.wait_group.sync.aligned 0;\n"
        "cp.async.bulk.wait_group.read 0;\n"
        "@pl mbarrier.arrive.shared::cta.b64 _, [sp+174480];\n"
        "mov.b32 {xl, xh}, a0; tanh.approx.f16 xr, xl; cvt.u32.u16 lo0, xr; tanh.approx.f16 xr, xh; cvt.u32.u16 hi0, xr; fma.rn.f16x2 p0, z16, z16, c; mul.rn.f16x2 a1, z15, p1; fma.rn.f16x2 q1, g1, g1, q1; fma.rn.f16x2 g0, z12, t0, z12; prmt.b32 t1, lo1, hi1, 0x5410;\n"
        "B15:\n"
        "mbarrier.try_wait.parity.shared::cta.b64 pw, [so+174472], ph;\n"
        "mov.b32 {xl, xh}, a1; tanh.approx.f16 xr, xl; cvt.u32.u16 lo1, xr; tanh.approx.f16 xr, xh; cvt.u32.u16 hi1, xr; fma.rn.f16x2 p1, z17, z17, c; mul.rn.f16x2 a0, z16, p0; fma.rn.f16x2 q0, g0, g0, q0; fma.rn.f16x2 g1, z13, t1, z13; prmt.b32 t0, lo0, hi0, 0x5410;\n"
        "B16:\n"
        "mov.b32 {xl, xh}, a0; tanh.approx.f16 xr, xl; cvt.u32.u16 lo0, xr; tanh.approx.f16 xr, xh; cvt.u32.u16 hi0, xr; fma.rn.f16x2 p0, z18, z18, c; mul.rn.f16x2 a1, z17, p1; fma.rn.f16x2 q1, g1, g1, q1; fma.rn.f16x2 g0, z14, t0, z14; prmt.b32 t1, lo1, hi1, 0x5410;\n"
        "B17:\n"
        "mov.b32 {xl, xh}, a1; tanh.approx.f16 xr, xl; cvt.u32.u16 lo1, xr; tanh.approx.f16 xr, xh; cvt.u32.u16 hi1, xr; fma.rn.f16x2 p1, z19, z19, c; mul.rn.f16x2 a0, z18, p0; fma.rn.f16x2 q0, g0, g0, q0; fma.rn.f16x2 g1, z15, t1, z15; prmt.b32 t0, lo0, hi0, 0x5410;\n"
        "B18:\n"
        "@!pw bra.uni SPIN;\n"
        "BACK:\n"
        "wgmma.fence.sync.aligned;\n"
        "wgmma.mma_async.sync.aligned.m64n64k16.f16.f16.f16 {z0,z1,z2,z3,z4,z5,z6,z7,z8,z9,z10,z11,z12,z13,z14,z15}, {w0,w1,w2,w3}, ds0, pf, 1, 1, 0;\n"
        "wgmma.mma_async.sync.aligned.m64n64k16.f16.f16.f16 {z0,z1,z2,z3,z4,z5,z6,z7,z8,z9,z10,z11,z12,z13,z14,z15}, {w4,w5,w6,w7}, ds1, pt, 1, 1, 0;\n"
        "wgmma.mma_async.sync.aligned.m64n64k16.f16.f16.f16 {z0,z1,z2,z3,z4,z5,z6,z7,z8,z9,z10,z11,z12,z13,z14,z15}, {w8,w9,w10,w11}, ds2, pt, 1, 1, 0;\n"
        "mov.b32 {xl, xh}, a0; tanh.approx.f16 xr, xl; cvt.u32.u16 lo0, xr; tanh.approx.f16 xr, xh; cvt.u32.u16 hi0, xr; fma.rn.f16x2 p0, z20, z20, c; mul.rn.f16x2 a1, z19, p1; fma.rn.f16x2 q1, g1, g1, q1; fma.rn.f16x2 g0, z16, t0, z16; prmt.b32 t1, lo1, hi1, 0x5410;\n"
        "B19:\n"
        "mov.b32 {xl, xh}, a1; tanh.approx.f16 xr, xl; cvt.u32.u16 lo1, xr; tanh.approx.f16 xr, xh; cvt.u32.u16 hi1, xr; fma.rn.f16x2 p1, z21, z21, c; mul.rn.f16x2 a0, z20, p0; fma.rn.f16x2 q2, g0, g0, q2; fma.rn.f16x2 g1, z17, t1, z17; prmt.b32 t0, lo0, hi0, 0x5410;\n"
        "B20:\n"
        "mov.b32 {xl, xh}, a0; tanh.approx.f16 xr, xl; cvt.u32.u16 lo0, xr; tanh.approx.f16 xr, xh; cvt.u32.u16 hi0, xr; fma.rn.f16x2 p0, z22, z22, c; mul.rn.f16x2 a1, z21, p1; fma.rn.f16x2 q3, g1, g1, q3; fma.rn.f16x2 g0, z18, t0, z18; prmt.b32 t1, lo1, hi1, 0x5410;\n"
        "B21:\n"
        "wgmma.mma_async.sync.aligned.m64n64k16.f16.f16.f16 {z0,z1,z2,z3,z4,z5,z6,z7,z8,z9,z10,z11,z12,z13,z14,z15}, {w12,w13,w14,w15}, ds3, pt, 1, 1, 0;\n"
        "wgmma.mma_async.sync.aligned.m64n64k16.f16.f16.f16 {z0,z1,z2,z3,z4,z5,z6,z7,z8,z9,z10,z11,z12,z13,z14,z15}, {w16,w17,w18,w19}, ds4, pt, 1, 1, 0;\n"
        "wgmma.mma_async.sync.aligned.m64n64k16.f16.f16.f16 {z0,z1,z2,z3,z4,z5,z6,z7,z8,z9,z10,z11,z12,z13,z14,z15}, {w20,w21,w22,w23}, ds5, pt, 1, 1, 0;\n"
        "wgmma.commit_group.sync.aligned;\n"
        "mov.b32 {xl, xh}, a1; tanh.approx.f16 xr, xl; cvt.u32.u16 lo1, xr; tanh.approx.f16 xr, xh; cvt.u32.u16 hi1, xr; fma.rn.f16x2 p1, z23, z23, c; mul.rn.f16x2 a0, z22, p0; fma.rn.f16x2 q2, g0, g0, q2; fma.rn.f16x2 g1, z19, t1, z19; prmt.b32 t0, lo0, hi0, 0x5410;\n"
        "B22:\n"
        "mov.b32 {xl, xh}, a0; tanh.approx.f16 xr, xl; cvt.u32.u16 lo0, xr; tanh.approx.f16 xr, xh; cvt.u32.u16 hi0, xr; fma.rn.f16x2 p0, z24, z24, c; mul.rn.f16x2 a1, z23, p1; fma.rn.f16x2 q3, g1, g1, q3; fma.rn.f16x2 g0, z20, t0, z20; prmt.b32 t1, lo1, hi1, 0x5410;\n"
        "B23:\n"
        "mov.b32 {xl, xh}, a1; tanh.approx.f16 xr, xl; cvt.u32.u16 lo1, xr; tanh.approx.f16 xr, xh; cvt.u32.u16 hi1, xr; fma.rn.f16x2 p1, z25, z25, c; mul.rn.f16x2 a0, z24, p0; fma.rn.f16x2 q2, g0, g0, q2; fma.rn.f16x2 g1, z21, t1, z21; prmt.b32 t0, lo0, hi0, 0x5410;\n"
        "B24:\n"
        "mov.b32 {xl, xh}, a0; tanh.approx.f16 xr, xl; cvt.u32.u16 lo0, xr; tanh.approx.f16 xr, xh; cvt.u32.u16 hi0, xr; fma.rn.f16x2 p0, z26, z26, c; mul.rn.f16x2 a1, z25, p1; fma.rn.f16x2 q3, g1, g1, q3; fma.rn.f16x2 g0, z22, t0, z22; prmt.b32 t1, lo1, hi1, 0x5410;\n"
        "B25:\n"
        "mov.b32 {xl, xh}, a1; tanh.approx.f16 xr, xl; cvt.u32.u16 lo1, xr; tanh.approx.f16 xr, xh; cvt.u32.u16 hi1, xr; fma.rn.f16x2 p1, z27, z27, c; mul.rn.f16x2 a0, z26, p0; fma.rn.f16x2 q2, g0, g0, q2; fma.rn.f16x2 g1, z23, t1, z23; prmt.b32 t0, lo0, hi0, 0x5410;\n"
        "B26:\n"
        "mov.b32 {xl, xh}, a0; tanh.approx.f16 xr, xl; cvt.u32.u16 lo0, xr; tanh.approx.f16 xr, xh; cvt.u32.u16 hi0, xr; fma.rn.f16x2 p0, z28, z28, c; mul.rn.f16x2 a1, z27, p1; fma.rn.f16x2 q3, g1, g1, q3; fma.rn.f16x2 g0, z24, t0, z24; prmt.b32 t1, lo1, hi1, 0x5410;\n"
        "B27:\n"
        "add.u32 n, n, 1; setp.lt.u32 pe, n, 32;\n"
        "mov.b32 {xl, xh}, a1; tanh.approx.f16 xr, xl; cvt.u32.u16 lo1, xr; tanh.approx.f16 xr, xh; cvt.u32.u16 hi1, xr; fma.rn.f16x2 p1, z29, z29, c; mul.rn.f16x2 a0, z28, p0; fma.rn.f16x2 q2, g0, g0, q2; fma.rn.f16x2 g1, z25, t1, z25; prmt.b32 t0, lo0, hi0, 0x5410;\n"
        "B28:\n"
        "mov.b32 {xl, xh}, a0; tanh.approx.f16 xr, xl; cvt.u32.u16 lo0, xr; tanh.approx.f16 xr, xh; cvt.u32.u16 hi0, xr; fma.rn.f16x2 p0, z30, z30, c; mul.rn.f16x2 a1, z29, p1; fma.rn.f16x2 q3, g1, g1, q3; fma.rn.f16x2 g0, z26, t0, z26; prmt.b32 t1, lo1, hi1, 0x5410;\n"
        "B29:\n"
        "mov.b32 {xl, xh}, a1; tanh.approx.f16 xr, xl; cvt.u32.u16 lo1, xr; tanh.approx.f16 xr, xh; cvt.u32.u16 hi1, xr; fma.rn.f16x2 p1, z31, z31, c; mul.rn.f16x2 a0, z30, p0; fma.rn.f16x2 q2, g0, g0, q2; fma.rn.f16x2 g1, z27, t1, z27; prmt.b32 t0, lo0, hi0, 0x5410;\n"
        "@pe bra.uni LOOP;\n"
        "bra.uni DONE;\n"
        "SPIN0: mov.u32 cnt, 0;\n"
        ASM_TRC("n", 1)
        "SPIN0L:\n"
        "mbarrier.try_wait.parity.shared::cta.b64 pw, [so+174472], ph;\n"
        "@pw bra.uni BACK0;\n"
        "add.u32 cnt, cnt, 1; setp.lt.u32 pw, cnt, 0x100000;\n"
        "@pw bra.uni SPIN0L;\n"
        "trap;\n"
        "SPIN: mov.u32 cnt, 0;\n"
        ASM_TRC("n", 1)
        "SPINL:\n"
        "mbarrier.try_wait.parity.shared::cta.b64 pw, [so+174472], ph;\n"
        "@pw bra.uni BACK;\n"
        "add.u32 cnt, cnt, 1; setp.lt.u32 pw, cnt, 0x100000;\n"
        "@pw bra.uni SPINL;\n"
        "trap;\n"
        "DUTY:\n"
        "setp.ge.s32 pr, n, %11;\n"
        "@pr bra.uni FLUSH;\n"
        "setp.ge.u32 pr, %13, 2;\n"
        "@pr bra.uni ROLE2;\n"
        "setp.ge.s32 pr, n, %12; selp.b64 src, %14, gp, pr; add.u32 tt, %7, 174464;\n"
        "elect.sync _|pr, 0xffffffff;\n"
        "@pr mbarrier.arrive.expect_tx.shared::cta.b64 _, [tt], %10;\n"
        "@pr cp.async.bulk.shared::cluster.global.mbarrier::complete_tx::bytes [%9], [src], %10, [tt];\n"
        "bra.uni FLUSH;\n"
        "ROLE2:\n"
        "setp.eq.u32 pr, %13, 3;\n"
        "@pr bra.uni ROLE3;\n"
        "elect.sync _|pr, 0xffffffff;\n"
        "@pr cp.async.bulk.global.shared::cta.bulk_group [gp], [%9], 12288;\n"
        "@pr cp.async.bulk.commit_group;\n"
        "bra.uni FLUSH;\n"
        "ROLE3:\n"
        "elect.sync _|pr, 0xffffffff;\n"
        "@pr cp.async.bulk.prefetch.L2.global [gp], 12288;\n"
        "FLUSH:\n"
        "add.s64 gp, gp, 294912;\n"
        "mov.b32 {xl, xh}, q0; cvt.f32.f16 f0, xl; cvt.f32.f16 f1, xh; add.f32 f0, f0, f1; add.f32 %0, %0, f0; mov.b32 q0, 0;\n"
        "mov.b32 {xl, xh}, q1; cvt.f32.f16 f0, xl; cvt.f32.f16 f1, xh; add.f32 f0, f0, f1; add.f32 %1, %1, f0; mov.b32 q1, 0;\n"
        "mov.b32 {xl, xh}, q2; cvt.f32.f16 f0, xl; cvt.f32.f16 f1, xh; add.f32 f0, f0, f1; add.f32 %2, %2, f0; mov.b32 q2, 0;\n"
        "mov.b32 {xl, xh}, q3; cvt.f32.f16 f0, xl; cvt.f32.f16 f1, xh; add.f32 f0, f0, f1; add.f32 %3, %3, f0; mov.b32 q3, 0;\n"
        "setp.ne.u32 pr, %5, 0;\n"
        "@pr bra.uni TOP;\n"
        "wgmma.wait_group.sync.aligned 0;\n"
        "wgmma.fence.sync.aligned;\n"
        "setp.eq.u32 pr, n, 1000; @pr bra.uni B31;\n"
        "setp.eq.u32 pr, n, 1001; @pr bra.uni B0;\n"
        "setp.eq.u32 pr, n, 1002; @pr bra.uni B1;\n"
        "setp.eq.u32 pr, n, 1003; @pr bra.uni B2;\n"
        "setp.eq.u32 pr, n, 1004; @pr bra.uni B3;\n"
        "setp.eq.u32 pr, n, 1005; @pr bra.uni B4;\n"
        "setp.eq.u32 pr, n, 1006; @pr bra.uni B5;\n"
        "setp.eq.u32 pr, n, 1007; @pr bra.uni B6;\n"
        "setp.eq.u32 pr, n, 1008; @pr bra.uni B7;\n"
        "setp.eq.u32 pr, n, 1009; @pr bra.uni B8;\n"
        "setp.eq.u32 pr, n, 1010; @pr bra.uni B9;\n"
        "setp.eq.u32 pr, n, 1011; @pr bra.uni B10;\n"
        "setp.eq.u32 pr, n, 1012; @pr bra.uni B11;\n"
        "setp.eq.u32 pr, n, 1013; @pr bra.uni B12;\n"
        "setp.eq.u32 pr, n, 1014; @pr bra.uni B13;\n"
        "setp.eq.u32 pr, n, 1015; @pr bra.uni B14;\n"
        "setp.eq.u32 pr, n, 1016; @pr bra.uni B15;\n"
        "setp.eq.u32 pr, n, 1017; @pr bra.uni B16;\n"
        "setp.eq.u32 pr, n, 1018; @pr bra.uni B17;\n"
        "setp.eq.u32 pr, n, 1019; @pr bra.uni B18;\n"
        "setp.eq.u32 pr, n, 1020; @pr bra.uni B19;\n"
        "setp.eq.u32 pr, n, 1021; @pr bra.uni B20;\n"
        "setp.eq.u32 pr, n, 1022; @pr bra.uni B21;\n"
        "setp.eq.u32 pr, n, 1023; @pr bra.uni B22;\n"
        "setp.eq.u32 pr, n, 1024; @pr bra.uni B23;\n"
        "setp.eq.u32 pr, n, 1025; @pr bra.uni B24;\n"
        "setp.eq.u32 pr, n, 1026; @pr bra.uni B25;\n"
        "setp.eq.u32 pr, n, 1027; @pr bra.uni B26;\n"
        "setp.eq.u32 pr, n, 1028; @pr bra.uni B27;\n"
        "setp.eq.u32 pr, n, 1029; @pr bra.uni B28;\n"
        "setp.eq.u32 pr, n, 1030; @pr bra.uni B29;\n"
        "trap;\n"
        "DONE:\n"
        ASM_TRC("n", 0)
        "mov.b32 {xl, xh}, a0; tanh.approx.f16 xr, xl; cvt.u32.u16 lo0, xr; tanh.approx.f16 xr, xh; cvt.u32.u16 hi0, xr; mul.rn.f16x2 a1, z31, p1; fma.rn.f16x2 q3, g1, g1, q3; fma.rn.f16x2 g0, z28, t0, z28; prmt.b32 t1, lo1, hi1, 0x5410;\n"
        "mov.b32 {xl, xh}, a1; tanh.approx.f16 xr, xl; cvt.u32.u16 lo1, xr; tanh.approx.f16 xr, xh; cvt.u32.u16 hi1, xr; fma.rn.f16x2 q2, g0, g0, q2; fma.rn.f16x2 g1, z29, t1, z29; prmt.b32 t0, lo0, hi0, 0x5410;\n"
        "fma.rn.f16x2 q3, g1, g1, q3; fma.rn.f16x2 g0, z30, t0, z30; prmt.b32 t1, lo1, hi1, 0x5410;\n"
        "fma.rn.f16x2 q2, g0, g0, q2; fma.rn.f16x2 g1, z31, t1, z31;\n"
        "fma.rn.f16x2 q3, g1, g1, q3;\n"
        "mov.b32 {xl, xh}, q0; cvt.f32.f16 f0, xl; cvt.f32.f16 f1, xh; add.f32 f0, f0, f1; add.f32 %0, %0, f0; mov.b32 q0, 0;\n"
        "mov.b32 {xl, xh}, q1; cvt.f32.f16 f0, xl; cvt.f32.f16 f1, xh; add.f32 f0, f0, f1; add.f32 %1, %1, f0; mov.b32 q1, 0;\n"
        "mov.b32 {xl, xh}, q2; cvt.f32.f16 f0, xl; cvt.f32.f16 f1, xh; add.f32 f0, f0, f1; add.f32 %2, %2, f0; mov.b32 q2, 0;\n"
        "mov.b32 {xl, xh}, q3; cvt.f32.f16 f0, xl; cvt.f32.f16 f1, xh; add.f32 f0, f0, f1; add.f32 %3, %3, f0; mov.b32 q3, 0;\n"
        "wgmma.wait_group.sync.aligned 0;\n"
        "}\n"
        : "=f"(acc[0][0]), "=f"(acc[0][1]), "=f"(acc[1][0]), "=f"(acc[1][1])
        : "r"(w1t), "r"(yd), "r"(wd), "r"(own_slot), "l"(d.g), "r"(d.s), "r"(d.bytes), "r"(d.end), "r"(d.zero), "r"(role),
          "l"(g_zero_row), "r"(lane)
        : "memory");
}
template <int M, bool LAST_SMEM = true>
__device__ __forceinline__ void gemm1_t(uint32_t (&d)[16], const uint32_t* wa, uint32_t yd, uint32_t wd) {
    wg_fence();
    wgmma_n64_h_set<0>(d, wa, desc<1024, 1>(yd, 0));
#pragma unroll
    for (int kk = 1; kk < (LAST_SMEM ? 5 : 6); kk++)
        wgmma_n64_h_acc<0>(d, wa + kk * 4, kk < 4 ? desc<1024, 1>(yd, kk * 32) : desc<512, 2>(yd, 8192 + (kk - 4) * 32));
    if (LAST_SMEM) wgmma_n64_h_acc_ss(d, desc<1024, 1>(wd, M * 12288), desc<512, 2>(yd, 8192 + 32));
    wg_commit();
}

#define GTAIL 0
__device__ __forceinline__ void gelu_sumsq_h(uint32_t (&d)[16], uint32_t (&q)[2], uint32_t key) {
#pragma unroll
    for (int r = 0; r < 16; r++) {
        if (GTAIL && r == 16 - GTAIL) sched_fence<GTAIL ? GTAIL : 2>(d + r, key);
        const uint32_t gv = gelu2(d[r]);
        q[r & 1] = h2_fma(gv, gv, q[r & 1]);
    }
}
__device__ __forceinline__ void flush_sumsq(uint32_t (&q)[2], float (&acc)[2]) {
#pragma unroll
    for (int h = 0; h < 2; h++) {
        float lo, hi;
        h2_unpack(q[h], lo, hi);
        acc[h] += lo + hi;
        q[h] = 0;
    }
}
__device__ __forceinline__ void gelu_sumsq_f(const uint32_t (&d)[16], float (&acc)[2]) {
#pragma unroll
    for (int r = 0; r < 16; r++) {
        float lo, hi;
        h2_unpack(gelu2(d[r]), lo, hi);
        acc[r & 1] = fmaf(lo, lo, acc[r & 1]);
        acc[r & 1] = fmaf(hi, hi, acc[r & 1]);
    }
}
__device__ __forceinline__ void load_w1t(uint32_t (&wa)[2][24], int wg, int w, int lane) {
#pragma unroll
    for (int m = 0; m < 2; m++)
#pragma unroll
        for (int kk = 0; kk < 5; kk++) {
            const int q = lane >> 3, c = 16 * kk + 8 * (q >> 1) + (lane & 7), ck = 2 * w + (q & 1);
            ldsm4_t(wa[m] + kk * 4, sb + SM_W1 + (2 * wg + m) * 12288 + c * 128 + ((ck ^ (c & 7)) * 16));
        }
}
__device__ __forceinline__ unsigned long long* acc_word(uint32_t epoch, uint32_t e) {
    return &g_acc[epoch & 1][(e >> 2) * 32 + (e & 3)];
}
__device__ __forceinline__ void publish_fast(const float (&acc)[2][2], uint32_t epoch, int wg, int w, int lane) {
    const bool m = lane & 2, h = lane & 1;
    const float a = (m ? acc[1][0] : acc[0][0]) + __shfl_xor_sync(0xffffffffu, m ? acc[0][0] : acc[1][0], 2);
    const float b = (m ? acc[1][1] : acc[0][1]) + __shfl_xor_sync(0xffffffffu, m ? acc[0][1] : acc[1][1], 2);
    const float v = (h ? b : a) + __shfl_xor_sync(0xffffffffu, h ? a : b, 1);
    const unsigned long long q = (__float2ull_rn(fminf(v, ACC_LIMIT) * 0x1p16f) << 8) + 1;
    asm volatile("red.relaxed.gpu.global.add.u64 [%0], %1;"
                 ::"l"(acc_word(epoch, 128 * wg + 32 * (lane & 2) + 16 * w + (lane >> 2) + 8 * (lane & 1))), "l"(q) : "memory");
}
__device__ __forceinline__ void publish_sums(const float (&acc)[2][2], float* sums, unsigned int* counter, int wg, int w, int lane) {
#pragma unroll
    for (int m = 0; m < 2; m++)
#pragma unroll
        for (int h = 0; h < 2; h++) {
            const float v = quad_sum(acc[m][h]);
            if ((lane & 3) == 0) atomicAdd(sums + 64 * (2 * wg + m) + 16 * w + (lane >> 2) + 8 * h, v);
        }
    named_sync(1, 384);
    if (fresh_tid() == 0) asm volatile("red.release.gpu.global.add.u32 [%0], 1;" ::"l"(counter) : "memory");
}
__device__ __forceinline__ void grid_wait(const unsigned int* counter, unsigned int target) {
    if (fresh_tid() == 0) {
        unsigned int v, spins = 0;
        do {
            asm volatile("ld.acquire.gpu.global.u32 %0, [%1];" : "=r"(v) : "l"(counter) : "memory");
            if (++spins > (1u << 22)) __trap();
        } while ((int)(v - target) < 0);
    }
    __syncthreads();
}

__device__ __forceinline__ void gemm1(uint32_t (&z)[16], const uint32_t (&a)[24], uint32_t w1d, int j) {
    wg_fence();
    wgmma_n64_h_set<1>(z, a, desc<1024, 1>(w1d, j * 12288));
#pragma unroll
    for (int kk = 1; kk < 6; kk++) wgmma_n64_h_acc<1>(z, a + kk * 4, desc<1024, 1>(w1d, j * 12288 + kk * 2048));
    wg_commit();
}
__device__ __forceinline__ void unpack_offsets(uint32_t (&o)[2], uint32_t packed) {
    asm volatile("and.b32 %0, %2, 0xffff;\nshr.u32 %1, %2, 16;" : "=r"(o[0]), "=r"(o[1]) : "r"(packed));
}
__device__ __forceinline__ void load_a(uint32_t (&a)[24], uint32_t tile, uint32_t offs) {
    uint32_t o[2];
    unpack_offsets(o, offs);
#pragma unroll
    for (int kk = 0; kk < 6; kk++) ldsm4(a + kk * 4, tile + (o[kk >> 2] ^ ((kk & 3) * 32)));
}
__device__ __forceinline__ void init_bias(uint32_t (&o)[24], uint32_t addr) {
#pragma unroll
    for (int j = 0; j < 6; j++) lds128(o + 4 * j, addr + j * 64);
}

struct Pass2 {
    uint32_t wg;
    uint32_t off;
    uint32_t xs;
    uint32_t a_offs, xs_offs, bias_addr, out_scale;
    bool lead;
    uint32_t a[24], z[3][16], o[24];
};

__device__ __forceinline__ void refill_y(const Pass2& c, const Params& prm, bool more, uint32_t off) {
    const uint32_t bars = sb + SM_BAR;
    fence_async_smem();
    named_sync(2 + c.wg, 128);
    if (c.lead && more) {
        expect_tx(bars + (BAR_Y2FULL + (c.wg ^ 2)) * 8, TILE_BYTES);
        bulk_load(sb + SM_Y2 + (c.wg & 1) * SLOT_BYTES, (const char*)prm.out + (off - 2 * ROW_BYTES), TILE_BYTES,
                  bars + (BAR_Y2FULL + (c.wg ^ 2)) * 8);
    }
}

__device__ __forceinline__ void start_first_tile(Pass2& c, const Params& prm) {
    if (c.wg == 3) mbar_wait_c<0>(sb + SM_BAR + (BAR_Y2FULL + 3) * 8);
    load_a(c.a, c.wg == 3 ? sb + SM_Y2 + SLOT_BYTES : c.xs, c.a_offs);
    gemm1(c.z[0], c.a, prm.w1desc, 0);
}

__device__ __forceinline__ void pass2_tile(Pass2& c, const Params& prm, int n) {
    const uint32_t xs = c.xs, xsfull = sb + SM_BAR + (BAR_XSFULL + c.wg) * 8;
#pragma unroll
    for (int j = 0; j < 6; j++) {
        uint32_t (&zc)[16] = c.z[j % 3];
        uint32_t (&zn)[16] = c.z[(j + 1) % 3];
        if (j == 0) wg_wait<0>(); else wg_wait<1>();
        pin(zc);
        if (j == 5) {
            pin(c.a);
            mbar_wait(sb + SM_BAR + (BAR_Y2FULL + c.wg) * 8, min(n + 1, ROWS_PER_CTA / 4 - 1) & 1);
            load_a(c.a, sb + SM_Y2 + (c.wg & 1) * SLOT_BYTES, c.a_offs);
        }
        const int jn = (j + 1) % 6;
#pragma unroll
        for (int sl = 0; sl < 4; sl++) {
#pragma unroll
            for (int r = 0; r < 4; r++) zc[sl * 4 + r] = gelu2(zc[sl * 4 + r]);
            wg_fence();
            wgmma_n96_h_acc(c.o, zc + sl * 4, desc<512, 2>(prm.w2desc, (j * 4 + sl) * 1024));
            if (sl < 2) {
#pragma unroll
                for (int kk = sl * 3; kk < sl * 3 + 3; kk++) {
                    if (kk == 0) wgmma_n64_h_set<1>(zn, c.a, desc<1024, 1>(prm.w1desc, jn * 12288));
                    else wgmma_n64_h_acc<1>(zn, c.a + kk * 4, desc<1024, 1>(prm.w1desc, jn * 12288 + kk * 2048));
                }
            }
            if (sl == 1) wg_commit();
        }
        wg_commit();
        if (j == 5) refill_y(c, prm, 4 * n + c.wg + 6 < ROWS_PER_CTA, c.off - 4 * ROW_BYTES);
        if (j == 1 && c.lead) {
            bulk_wait_read<0>();
            expect_tx(xsfull, TILE_BYTES);
            bulk_load(xs, (const char*)prm.x + c.off, TILE_BYTES, xsfull);
        }
    }
    wg_wait<0>();
    pin(c.o); pin(c.z[0]);
    mbar_wait(xsfull, n & 1);
    uint32_t xo[2];
    unpack_offsets(xo, c.xs_offs);
#pragma unroll
    for (int h = 0; h < 2; h++)
#pragma unroll
        for (int a = 0; a < 3; a++) {
            const uint32_t addr = xs + xo[h] + a * 64;
            uint32_t v[4];
            lds128(v, addr);
#pragma unroll
            for (int b = 0; b < 4; b++) {
                float lo, hi;
                h2_unpack(c.o[a * 8 + b * 2 + h], lo, hi);
                v[b] = bf2_fma(pack_bf2(lo, hi), c.out_scale, v[b]);
            }
            sts128(addr, v[0], v[1], v[2], v[3]);
        }
    init_bias(c.o, c.bias_addr);
    fence_async_smem();
    named_sync(2 + c.wg, 128);
    if (c.lead) bulk_store((char*)prm.out + c.off, xs, TILE_BYTES);
    c.off -= 4 * ROW_BYTES;
}

__device__ __forceinline__ float warp_sum(float v) {
#pragma unroll
    for (int s = 16; s >= 1; s >>= 1) v += __shfl_xor_sync(0xffffffffu, v, s);
    return v;
}
__device__ __forceinline__ float pow2f(int e) { return __uint_as_float((uint32_t)(e + 127) << 23); }
__device__ __forceinline__ int exponent_of(float v) { return (int)(__float_as_uint(v) >> 23) - 127; }
__device__ __forceinline__ float lds_bf16(uint32_t addr) {
    uint16_t v; asm volatile("ld.shared.u16 %0, [%1];" : "=h"(v) : "r"(addr) : "memory"); return bf_lo(v);
}

__device__ __forceinline__ void publish_bias(uint32_t c, uint32_t tag) {
    const uint32_t lane = fresh_tid() & 31;
    const uint32_t col = sb + SM_W2 + (c >> 5) * 24576 + lane * 64 + ((((c >> 3) ^ (lane >> 1)) & 3) * 16) + (c & 7) * 2;
    float v = 0.0f;
#pragma unroll
    for (int k = 0; k < EX / 32; k++) v = fmaf(lds_bf16(col + k * 2048), lds_bf16(sb + SM_BETA + lane * 2 + k * 64), v);
    v = warp_sum(v);
    if (lane == 0) asm volatile("st.relaxed.gpu.global.v2.b32 [%0], {%1, %2};" ::"l"(g_bias + c), "f"(v), "r"(tag) : "memory");
}
__device__ __forceinline__ float fetch_w2_row(uint32_t (&u)[12][4], uint32_t row, uint32_t sw) {
    uint32_t mx = 0x2B802B80u;
#pragma unroll
    for (int a = 0; a < 3; a++)
#pragma unroll
        for (int k = 0; k < 4; k++) {
            asm volatile("ld.shared.v4.b32 {%0,%1,%2,%3}, [%4];"
                         : "=r"(u[a * 4][k]), "=r"(u[a * 4 + 1][k]), "=r"(u[a * 4 + 2][k]), "=r"(u[a * 4 + 3][k])
                         : "r"(row + a * 24576 + ((k * 16) ^ sw)) : "memory");
#pragma unroll
            for (int b = 0; b < 4; b++) asm("max.xorsign.abs.bf16x2 %0, %0, %1;" : "+r"(mx) : "r"(u[a * 4 + b][k]));
        }
    const float top = fmaxf(fabsf(bf_lo(mx)), fabsf(bf_hi(mx)));
    const float nrm = pow2f(-min(exponent_of(top), 21)) * 0x1p-112f;
    const uint32_t nrm2 = pack_bf2(nrm, nrm);
#pragma unroll
    for (int k = 0; k < 48; k++) {
        const uint32_t v = bf2_mul(u[k >> 2][k & 3], nrm2);
        u[k >> 2][k & 3] = (v & 0x7fff7fffu) * 7u + v;
    }
    return top;
}

__device__ __forceinline__ bool grn_stats(float ss, float gm, float bt, float top, float& gx, float& inv, int& eo) {
    const int warp = fresh_warp();
    gx = sqrt_fast(fmaf(ss, INV_2A * INV_2A, 1e-6f));
    const float rt = sqrt_fast(ss + 1.0f) * INV_2A * top;
    const float r[3] = {warp_sum(gx), warp_sum(fmaf(bt, top, rt)), warp_sum(rt * fabsf(gm) * gx)};
    if ((fresh_tid() & 31) == 0 && warp < 12) {
#pragma unroll
        for (int k = 0; k < 3; k++) sts32(sb + SM_SEL + (k * 12 + warp) * 4, __float_as_uint(r[k]));
    }
    const bool bad = __syncthreads_or(!(ss >= 16.0f && ss < ACC_LIMIT));
    float tot[3];
#pragma unroll
    for (int k = 0; k < 3; k++) {
        uint32_t v[12];
#pragma unroll
        for (int q = 0; q < 3; q++) lds128(v + 4 * q, sb + SM_SEL + k * 48 + q * 16);
        float p[4];
#pragma unroll
        for (int q = 0; q < 4; q++) p[q] = __uint_as_float(v[q]) + __uint_as_float(v[q + 4]) + __uint_as_float(v[q + 8]);
        tot[k] = (p[0] + p[1]) + (p[2] + p[3]);
    }
    inv = __fdividef(1.0f, fmaf(tot[0], 1.0f / EX, 1e-6f));
    eo = min(exponent_of(fmaf(tot[2], inv, tot[1])), 94) - 14;
    return bad;
}

__device__ __forceinline__ float exact_sums(const Params& prm, int e) {
    const int lane = fresh_tid() & 31, warp = fresh_warp(), wg = warp >> 2;
    const uint32_t epoch = lds32(sb + SM_RED + (RED_EPOCH + 1) * 4), bar = sb + SM_BAR + BAR_W1 * 8;
    if (wg < 3) {
        uint32_t wa[2][24], d[2][16];
        float acc[2][2] = {};
        const uint32_t yd = prm.ydesc + ((SM_SPARE - SM_Y1) >> 4), wd = prm.w1desc + ((2 * wg * 12288 + 5 * 2048) >> 4);
        load_w1t(wa, wg, warp & 3, lane);
#pragma unroll 1
        for (int n = 0; n < ROWS_PER_CTA; n++) {
            if (warp == 0) {
                expect_tx(bar, TILE_BYTES);
                bulk_load(sb + SM_SPARE, (const char*)prm.out + cta_tile0(fresh_cta()) + n * ROW_BYTES, TILE_BYTES, bar);
            }
            mbar_wait(bar, (n + 1) & 1);
            gemm1_t<0>(d[0], wa[0], yd, wd);
            gemm1_t<1>(d[1], wa[1], yd, wd);
            wg_wait<0>();
            pin(d[0]); pin(d[1]);
            gelu_sumsq_f(d[0], acc[0]);
            gelu_sumsq_f(d[1], acc[1]);
            named_sync(1, 384);
        }
        publish_sums(acc, g_sums[epoch & 1], &g_count[1], wg, warp & 3, lane);
    }
    grid_wait(&g_count[1], (epoch + 1) * NUM_CTAS);
    return __ldcg(g_sums[epoch & 1] + e);
}

__global__ void __launch_bounds__(512, 1) convnext_kernel(const __grid_constant__ Params prm) {
    extern __shared__ __align__(1024) uint8_t smem[];
    if ((uint32_t)__cvta_generic_to_shared(smem) != sb) __trap();
    if (fresh_tid() < 32) TS(0);
    if (fresh_warp() == 0) {
        const RowCopy rc = row_copy(prm);
        if (fresh_tid() == 0) {
            mbar_init(sb + SM_XFULL, 2);
            fence_async_smem();
        }
        __syncwarp();
        issue_row_load(rc, 0, 0);
        if (fresh_tid() == 0) {
#pragma unroll
            for (int k = 0; k < NX; k++) {
                if (k) mbar_init(sb + SM_XFULL + k * SLOT_BYTES, 2);
                mbar_init(sb + SM_Y1FULL + k * SLOT_BYTES, 4);
                mbar_init(sb + SM_Y1EMPTY + k * SLOT_BYTES, 12);
            }
#pragma unroll
            for (int k = 0; k <= BAR_W2; k++) mbar_init(sb + SM_BAR + k * 8, 1);
            mbar_init(sb + SM_BAR + BAR_DUMMY * 8, 16);
#pragma unroll
            for (int k = 0; k < 3; k++) mbar_arrive_if(sb + SM_BAR + (BAR_Y2FULL + k) * 8, true);
            fence_async_smem();
        }
        __syncwarp();
#pragma unroll
        for (int s = 1; s <= NX; s++) {
            if (s == 1 + rc.first) {
                expect_tx(sb + SM_BAR + BAR_W1 * 8, CH * EX * 2);
#pragma unroll
                for (int k = 0; k < 3; k++)
                    bulk_load(sb + SM_W1 + k * 24576, (const char*)prm.w1 + k * 24576, 24576, sb + SM_BAR + BAR_W1 * 8);
            }
            if (s < NX) issue_row_load(rc, s, s);
        }
    }
    Producer pc;
    if (fresh_warp() >= 12) {
        const char* dw = (const char*)prm.dw + (fresh_tid() & 7) * 8;
#pragma unroll
        for (int tap = 0; tap < 9; tap++) {
            asm volatile("ld.global.nc.v4.b32 {%0,%1,%2,%3}, [%4];"
                         : "=r"(pc.w[tap][0]), "=r"(pc.w[tap][1]), "=r"(pc.w[tap][2]), "=r"(pc.w[tap][3])
                         : "l"(dw + (fresh_tid() & 7) * 8 + tap * CH * 2));
            asm volatile("ld.global.nc.v2.b32 {%0,%1}, [%2];"
                         : "=r"(pc.w[tap][4]), "=r"(pc.w[tap][5]) : "l"(dw + tap * CH * 2 + 128));
        }
    }
    if (fresh_tid() >= 96 && fresh_tid() < 128) {
        const uint32_t k = fresh_tid() - 96, n = k & 7, one = (n & 5) == ((k & 8) >> 1) + (k >> 4) ? 0x3f803f80u : 0u;
        sts128(sb + SM_SEL + k * 16, one, one, one, one);
        fence_async_smem();
    }
    if (fresh_tid() >= 32 && fresh_tid() < 32 + NX * 12 && ((blockIdx.x + 1) & 7) < 2) {
        const int k = fresh_tid() - 32;
        sts128(sb + SM_X + (k / 12) * SLOT_BYTES + ((blockIdx.x & 7) == 0 ? 0 : XHALF_B + 33 * 192) + (k % 12) * 16, 0, 0, 0, 0);
    }
    __syncthreads();
    if (fresh_tid() < 32) TS(16);

    if (fresh_warp() >= 12) {
        TS(17);
        asm volatile("setmaxnreg.inc.sync.aligned.u32 %0;" ::"n"(PRODUCER_REGS));
        TS(18);
        const int w = fresh_warp() & 3, lane = fresh_tid() & 31;
        const int j = lane & 7, hb = (lane >> 3) & 1, base = 4 * (2 * w + (lane >> 4));
        pc.lane = lane; pc.warp = w;
        pc.xoff[0] = hb * XHALF_B + base * 192 + j * 16;
        pc.xoff[1] = hb * XHALF_B + base * 192 + 128 + j * 8;
        const int grp = 4 * w + (lane >> 3);
#pragma unroll
        for (int o = 0; o < 2; o++) {
            const int row = (grp & 7) + 8 * (o ^ hb) + 32 * (grp >> 3);
            pc.yoff[0][o] = row * 128 + ((j ^ (row & 7)) * 16);
            pc.yoff[1][o] = 8192 + row * 64 + (((j >> 1) ^ ((row >> 1) & 3)) * 16) + (j & 1) * 8;
        }
        pc.stat = sb + SM_STAT + grp * 32;
        pc.own = pc.stat + (lane & 3) * 8;
#pragma unroll
        for (int tap = 0; tap < 9; tap++)
#pragma unroll
            for (int u = 0; u < 6; u++) pc.w[tap][u] = bf2_mul(pc.w[tap][u], TAP_SCALE_BF2);
        TS(8);
        produce(pc, prm);
        TS(9);
        if (w == 0) {
            mbar_wait_c<0>(sb + SM_BAR + BAR_W2 * 8);
            if (fresh_cta() < CH) publish_bias(fresh_cta(), lds32(sb + SM_RED + RED_EPOCH * 4) + 1);
        }
        TS(22);
        asm volatile("setmaxnreg.dec.sync.aligned.u32 %0;" ::"n"(EVEN_REGS));
    } else {
        asm volatile("setmaxnreg.dec.sync.aligned.u32 %0;" ::"n"(CONSUMER_REGS));
        if (fresh_tid() - 160 < 2) {
            const uint32_t k = fresh_tid() - 160;
            unsigned int cnt;
            asm volatile("ld.relaxed.gpu.global.u32 %0, [%1];" : "=r"(cnt) : "l"(&g_count[k]) : "memory");
            sts32(sb + SM_RED + (RED_EPOCH + k) * 4, k ? cnt / NUM_CTAS : cnt);
        }
        __syncwarp();
        if (fresh_tid() < 32) TS(19);
        {
            const int tid = fresh_tid(), c0 = tid / 48, ec = tid % 48;
            const uint32_t dst = sb + SM_W1 + (ec >> 3) * 12288 + c0 * 128 + (((ec & 7) ^ (c0 & 7)) * 16);
            uint32_t v[12][4];
            mbar_wait_c<0>(sb + SM_BAR + BAR_W1 * 8);
            if (fresh_tid() < 32) TS(20);
#pragma unroll
            for (int it = 0; it < 12; it++) lds128(v[it], sb + SM_W1 + tid * 16 + it * 6144);
#pragma unroll
            for (int it = 0; it < 12; it++)
#pragma unroll
                for (int k = 0; k < 4; k++) v[it][k] = bf2_to_h2(v[it][k]);
#pragma unroll
            for (int it = 0; it < 12; it++) pin(v[it]);
            named_sync(1, 384);
#pragma unroll
            for (int it = 0; it < 12; it++) sts128(dst + it * 1024, v[it][0], v[it][1], v[it][2], v[it][3]);
            if (fresh_cta() == 0) *acc_word(lds32(sb + SM_RED + RED_EPOCH * 4) + 1, tid) = 0;
            if (fresh_cta() == 1) g_sums[(lds32(sb + SM_RED + (RED_EPOCH + 1) * 4) & 1) ^ 1][tid] = 0.0f;
            fence_async_smem();
            named_sync(1, 384);
            if (fresh_tid() < 32) TS(21);
        }

        const int tid = fresh_tid(), lane = tid & 31, wg = fresh_warp() >> 2, w = fresh_warp() & 3;
        float acc[2][2];
        const int c = 8 * (lane >> 4) + (lane & 7), ck = 2 * w + ((lane >> 3) & 1);
        if (wg == 0) TS(1);
        consume(acc, sb + SM_W1 + 2 * wg * 12288 + c * 128 + ((ck ^ (c & 7)) * 16), prm.ydesc,
                prm.w1desc + (((2 * wg + 1) * 12288 + 5 * 2048) >> 4), wg * SLOT_BYTES, make_duty(prm, wg, w), w, lane);
        publish_fast(acc, lds32(sb + SM_RED + RED_EPOCH * 4), wg, w, lane);
        bulk_wait_all();
        if (wg == 0) TS(3);
        asm volatile("setmaxnreg.inc.sync.aligned.u32 %0;" ::"n"(EVEN_REGS));
    }

    {
        Pass2 c;
        const int tid = fresh_tid(), lane = tid & 31, warp = fresh_warp(), wg = warp >> 2, w = warp & 3, e = min(tid, EX - 1);
        const int arow = 16 * w + (lane & 15);
        c.wg = wg;
        c.off = cta_tile0(fresh_cta()) + (ROWS_PER_CTA - 1 - wg) * ROW_BYTES;
        c.xs = wg == 3 ? sb + SM_SPARE : sb + SM_Y1 + (wg == 2 ? 2 : 1 - wg) * SLOT_BYTES;
        static_assert((ROWS_PER_CTA - 1) % NX == 1, "slot of the last tile");
        c.a_offs = (arow * 128 + (((lane >> 4) ^ (arow & 7)) * 16)) |
                   (8192 + arow * 64 + (((lane >> 4) ^ ((arow >> 1) & 3)) * 16)) << 16;
        const int g = lane >> 2, px = 33 * (g & 1) + 4 * (g >> 1) + 16 * (w >> 1) + 2 * (w & 1);
        c.xs_offs = (px * 192 + (lane & 3) * 16) | ((px ^ 1) * 192 + (lane & 3) * 16) << 16;
        c.bias_addr = sb + SM_BIAS + (lane & 3) * 16;
        c.lead = w == 0;
        const uint32_t epoch = lds32(sb + SM_RED + RED_EPOCH * 4);
        __syncthreads();
        if (warp == 13) {
#pragma unroll
            for (int k = 0; k < 2; k++) {
                const uint32_t bar = sb + SM_BAR + (BAR_Y2FULL + (k ? 0 : 3)) * 8;
                expect_tx(bar, TILE_BYTES);
                bulk_load(sb + SM_Y2 + (1 - k) * SLOT_BYTES, (const char*)prm.out + (c.off - k * ROW_BYTES), TILE_BYTES, bar);
            }
        }
        start_first_tile(c, prm);
        const float gm = lds_bf16(sb + SM_GAMMA + e * 2), bt = fabsf(lds_bf16(sb + SM_BETA + e * 2));
        const uint32_t w2row = sb + SM_W2 + e * 64, sw = ((e >> 1) & 3) * 16;
        uint32_t u[12][4];
        float top = 0.0f, ss = 16.0f;
        unsigned int spins = 0;
        if (wg < 3) top = fetch_w2_row(u, w2row, sw);
        wg_wait<0>();
        pin(c.z[0]); pin(c.a);
        if (wg < 3) {
            unsigned long long v;
            do {
                asm volatile("ld.relaxed.gpu.global.u64 %0, [%1];" : "=l"(v) : "l"(acc_word(epoch, e)) : "memory");
                if (++spins > (1u << 22)) __trap();
            } while ((v & 255) != NUM_CTAS);
            ss = __ull2float_rn(v >> 8) * 0x1p-16f;
        } else if (w == 0) {
            const int jj = min(lane >> 2, 5);
            const unsigned long long* src = g_bias + 32 * (jj >> 1) + 8 * (lane & 3) + 4 * (jj & 1);
            do {
#pragma unroll
                for (int k = 0; k < 4; k++)
                    asm volatile("ld.relaxed.gpu.global.v2.b32 {%0, %1}, [%2];" : "=r"(u[0][k]), "=r"(u[1][k]) : "l"(src + k) : "memory");
                if (++spins > (1u << 22)) __trap();
            } while (u[1][0] != epoch + 1 || u[1][1] != epoch + 1 || u[1][2] != epoch + 1 || u[1][3] != epoch + 1);
        }
        __syncwarp();
        if (warp == 0) TS(4);
        float gx, inv;
        int eo;
        if (grn_stats(ss, gm, bt, top, gx, inv, eo) || FORCE_EXACT) {
            const uint32_t b[4] = {u[0][0], u[0][1], u[0][2], u[0][3]};
            grn_stats(exact_sums(prm, e), gm, bt, top, gx, inv, eo);
            start_first_tile(c, prm);
            fetch_w2_row(u, w2row, sw);
            if (wg == 3) { u[0][0] = b[0]; u[0][1] = b[1]; u[0][2] = b[2]; u[0][3] = b[3]; }
            wg_wait<0>();
            pin(c.z[0]); pin(c.a);
            __syncthreads();
        }
        if (tid == 416 && fresh_cta() == 0) g_count[0] = epoch + 1;
        const float up = pow2f(eo);
        c.out_scale = pack_bf2(up, up);
        if (wg < 3) {
            const float sc = fmaf(gm, gx * inv, 1.0f) * (INV_2A * W2_CENTRE) * pow2f(min(exponent_of(top), 21) - eo);
            const uint32_t s2 = pack_h2(sc, sc);
#pragma unroll
            for (int k = 0; k < 12; k++)
                sts128(w2row + (k >> 2) * 24576 + (((k & 3) * 16) ^ sw), h2_mul(u[k][0], s2) & W2_MASK, h2_mul(u[k][1], s2) & W2_MASK,
                       h2_mul(u[k][2], s2) & W2_MASK, h2_mul(u[k][3], s2) & W2_MASK);
        } else if (w == 0 && lane < 24) {
            const float dn = pow2f(-eo);
            const uint32_t p0 = pack_h2(__uint_as_float(u[0][0]) * dn, __uint_as_float(u[0][1]) * dn);
            const uint32_t p1 = pack_h2(__uint_as_float(u[0][2]) * dn, __uint_as_float(u[0][3]) * dn);
            sts128(sb + SM_BIAS + lane * 16, p0, p0, p1, p1);
        }
        fence_async_smem();
        __syncthreads();

        if (wg == 0) TS(5);
        if (warp == 13) {
            expect_tx(sb + SM_BAR + (BAR_Y2FULL + 1) * 8, TILE_BYTES);
            bulk_load(sb + SM_Y2 + SLOT_BYTES, (const char*)prm.out + (c.off - 2 * ROW_BYTES), TILE_BYTES, sb + SM_BAR + (BAR_Y2FULL + 1) * 8);
        }
        init_bias(c.o, c.bias_addr);
#pragma unroll 1
        for (int n = loop_init<0>(); n < ROWS_PER_CTA / 4; n++) pass2_tile(c, prm, n);
        bulk_wait_all();
        if (wg == 0) TS(6);
        if (wg == 3) TS(7);
    }
}

}

extern "C" void kernel_launch(void* const* d_in, const int* in_sizes, int n_in, void* d_out, int out_size) {
    (void)in_sizes; (void)n_in; (void)out_size;
    typedef CUresult (*EncodeFn)(CUtensorMap*, CUtensorMapDataType, cuuint32_t, void*, const cuuint64_t*, const cuuint64_t*,
                                 const cuuint32_t*, const cuuint32_t*, CUtensorMapInterleave, CUtensorMapSwizzle,
                                 CUtensorMapL2promotion, CUtensorMapFloatOOBfill);
    void* fn = nullptr;
    cudaDriverEntryPointQueryResult status;
    cudaGetDriverEntryPoint("cuTensorMapEncodeTiled", &fn, cudaEnableDefault, &status);
    const EncodeFn encode = (EncodeFn)fn;
    const cuuint32_t ones[2] = {1, 1};

    Params p;
    {
        const cuuint64_t dims[2] = {CH, EX}, strides[1] = {CH * 2};
        const cuuint32_t box[2] = {32, 192};
        encode(&p.w2_map, CU_TENSOR_MAP_DATA_TYPE_BFLOAT16, 2, d_in[3], dims, strides, box, ones,
               CU_TENSOR_MAP_INTERLEAVE_NONE, CU_TENSOR_MAP_SWIZZLE_64B, CU_TENSOR_MAP_L2_PROMOTION_NONE,
               CU_TENSOR_MAP_FLOAT_OOB_FILL_NONE);
    }
    p.x = (const __nv_bfloat16*)d_in[0];
    p.dw = (const __nv_bfloat16*)d_in[1];
    p.w1 = (const __nv_bfloat16*)d_in[2];
    p.gamma = (const __nv_bfloat16*)d_in[4];
    p.beta = (const __nv_bfloat16*)d_in[5];
    p.out = (__nv_bfloat16*)d_out;
    p.w1desc = desc_lo(sb + SM_W1, 12288);
    p.w2desc = desc_lo(sb + SM_W2, 24576);
    p.ydesc = desc_lo(sb + SM_Y1, 16);
    for (int k = 0; k < 3; k++) p.sel[k] = (8ull << 32) | desc_lo(sb + SM_SEL + k * 128, k == 2 ? 128 : 0);
    constexpr int smem_bytes = SM_TOTAL;
    cudaFuncSetAttribute(convnext_kernel, cudaFuncAttributeMaxDynamicSharedMemorySize, smem_bytes);
    convnext_kernel<<<NUM_CTAS, 512, smem_bytes>>>(p);
}
```

```cpp
#include <cuda.h>
#include <cuda_runtime.h>
#include <cuda_bf16.h>
#include <stdint.h>

namespace {

constexpr int IMG_W = 512, CH = 96, EX = 384;
constexpr int TILE_PX = 64;
constexpr int ROWS_PER_CTA = 32;
constexpr int NUM_CTAS = 128;
constexpr int STEPS = ROWS_PER_CTA + 2;
constexpr int ROW_BYTES = IMG_W * CH * 2;

#define FORCE_EXACT 0
#define PREGS 200
#define CREGS 104
constexpr int PRODUCER_REGS = PREGS, CONSUMER_REGS = CREGS, EVEN_REGS = 128;

constexpr int XHALF_BYTES = 34 * 192;
constexpr int XHALF_B = XHALF_BYTES + 64;
constexpr int XROW_BYTES = XHALF_B + XHALF_BYTES + 64;
constexpr int L2_AHEAD = 2;
constexpr int NX = 3;
constexpr int TILE_BYTES = TILE_PX * 192;
constexpr int NY1 = 3;

constexpr uint32_t sb = 1024;
constexpr int SM_W1 = 0;
constexpr int SM_W2 = 73728;
constexpr int SM_RING = 147456;
constexpr int SLOT_BYTES = 26624;
constexpr int SM_Y1 = SM_RING;
constexpr int SM_X = SM_Y1 + TILE_BYTES;
constexpr int SM_STAT = SM_X + XROW_BYTES;
constexpr int SM_XFULL = SM_STAT + TILE_PX * 16, SM_Y1FULL = SM_XFULL + 8, SM_Y1EMPTY = SM_XFULL + 16;
constexpr int SM_Y2 = SM_X, SM_SPARE = SM_X + 2 * SLOT_BYTES;
constexpr int SM_SEL = SM_RING + NX * SLOT_BYTES;
constexpr int SM_BIAS = SM_SEL + 512;
constexpr int SM_GAMMA = SM_BIAS + 384;
constexpr int SM_BETA = SM_GAMMA + EX * 2;
constexpr int SM_RED = SM_BETA + EX * 2;
constexpr int SM_BAR = SM_RED + 16;
constexpr int SM_TOTAL = SM_BAR + 11 * 8;
static_assert(SM_Y1EMPTY + 8 <= SM_RING + SLOT_BYTES && XROW_BYTES >= TILE_BYTES && SM_X % 1024 == 0, "ring layout");
static_assert(SM_TOTAL <= 232448, "smem budget");
static_assert(SM_STAT % 128 == 0 && SM_BIAS % 16 == 0 && SM_BAR % 8 == 0 && SLOT_BYTES % 1024 == 0, "alignment");

constexpr int BAR_Y2FULL = 0, BAR_XSFULL = 4, BAR_W1 = 8, BAR_W2 = 9, BAR_DUMMY = 10;
static_assert(NX == NY1, "both rings are walked with one index");
constexpr int RED_EPOCH = 0;

constexpr float GELU_A = 0.32920349f;
constexpr uint32_t GELU_C_H2 = 0x40D940D9u;
constexpr float INV_2A = 1.0f / (2.0f * GELU_A);

constexpr uint32_t TAP_SCALE_BF2 = 0x2B802B80u;
constexpr float LN_EPS_SCALED = 1e-5f * 0x1p-80f;
constexpr float RSTD_SCALE = GELU_A * 0x1p-112f;

__device__ unsigned long long g_acc[2][EX / 4 * 32];
__device__ unsigned long long g_bias[CH];
__device__ float g_sums[2][EX];
__device__ unsigned int g_count[2];
constexpr float ACC_LIMIT = 0x1p30f;
__device__ uint4 g_zero_row[66 * 192 / 16];

#define TS(k)
#define ASM_TS
#define MARK(k)
#define ASM_TRC(it, k)

#define SPLITS 2
#define FENCE_HEAD(k) "{\n.reg .pred p;\n.reg .u32 t;\nsetp.ne.u32 p, %" #k ", 0;\n@p bra.uni GO;\nSTAY:\nld.volatile.shared.u32 t, [%" #k "];\n"
#define FENCE_TAIL "setp.ne.u32 p, t, 0;\n@p bra.uni STAY;\nGO:\n}\n"
template <int N> __device__ __forceinline__ void sched_fence(uint32_t* r, uint32_t key);
template <> __device__ __forceinline__ void sched_fence<2>(uint32_t* r, uint32_t key) {
    asm volatile(FENCE_HEAD(2) "mov.b32 %0, t;\nmov.b32 %1, t;\n" FENCE_TAIL
                 : "+r"(r[0]), "+r"(r[1]) : "r"(key) : "memory");
}
template <> __device__ __forceinline__ void sched_fence<4>(uint32_t* r, uint32_t key) {
    asm volatile(FENCE_HEAD(4) "mov.b32 %0, t;\nmov.b32 %1, t;\nmov.b32 %2, t;\nmov.b32 %3, t;\n" FENCE_TAIL
                 : "+r"(r[0]), "+r"(r[1]), "+r"(r[2]), "+r"(r[3]) : "r"(key) : "memory");
}
template <> __device__ __forceinline__ void sched_fence<6>(uint32_t* r, uint32_t key) {
    asm volatile(FENCE_HEAD(6) "mov.b32 %0, t;\nmov.b32 %1, t;\nmov.b32 %2, t;\nmov.b32 %3, t;\nmov.b32 %4, t;\nmov.b32 %5, t;\n" FENCE_TAIL
                 : "+r"(r[0]), "+r"(r[1]), "+r"(r[2]), "+r"(r[3]), "+r"(r[4]), "+r"(r[5]) : "r"(key) : "memory");
}
template <> __device__ __forceinline__ void sched_fence<8>(uint32_t* r, uint32_t key) {
    asm volatile(FENCE_HEAD(8) "mov.b32 %0, t;\nmov.b32 %1, t;\nmov.b32 %2, t;\nmov.b32 %3, t;\nmov.b32 %4, t;\nmov.b32 %5, t;\nmov.b32 %6, t;\nmov.b32 %7, t;\n" FENCE_TAIL
                 : "+r"(r[0]), "+r"(r[1]), "+r"(r[2]), "+r"(r[3]), "+r"(r[4]), "+r"(r[5]), "+r"(r[6]), "+r"(r[7]) : "r"(key) : "memory");
}
template <> __device__ __forceinline__ void sched_fence<10>(uint32_t* r, uint32_t key) {
    asm volatile(FENCE_HEAD(10) "mov.b32 %0, t;\nmov.b32 %1, t;\nmov.b32 %2, t;\nmov.b32 %3, t;\nmov.b32 %4, t;\nmov.b32 %5, t;\nmov.b32 %6, t;\nmov.b32 %7, t;\nmov.b32 %8, t;\nmov.b32 %9, t;\n" FENCE_TAIL
                 : "+r"(r[0]), "+r"(r[1]), "+r"(r[2]), "+r"(r[3]), "+r"(r[4]), "+r"(r[5]), "+r"(r[6]), "+r"(r[7]), "+r"(r[8]), "+r"(r[9]) : "r"(key) : "memory");
}
template <> __device__ __forceinline__ void sched_fence<12>(uint32_t* r, uint32_t key) {
    asm volatile(FENCE_HEAD(12) "mov.b32 %0, t;\nmov.b32 %1, t;\nmov.b32 %2, t;\nmov.b32 %3, t;\nmov.b32 %4, t;\nmov.b32 %5, t;\nmov.b32 %6, t;\nmov.b32 %7, t;\nmov.b32 %8, t;\nmov.b32 %9, t;\nmov.b32 %10, t;\nmov.b32 %11, t;\n" FENCE_TAIL
                 : "+r"(r[0]), "+r"(r[1]), "+r"(r[2]), "+r"(r[3]), "+r"(r[4]), "+r"(r[5]), "+r"(r[6]), "+r"(r[7]), "+r"(r[8]), "+r"(r[9]), "+r"(r[10]), "+r"(r[11]) : "r"(key) : "memory");
}
template <> __device__ __forceinline__ void sched_fence<24>(uint32_t* r, uint32_t key) {
    asm volatile(FENCE_HEAD(24) "mov.b32 %0, t;\nmov.b32 %1, t;\nmov.b32 %2, t;\nmov.b32 %3, t;\nmov.b32 %4, t;\nmov.b32 %5, t;\nmov.b32 %6, t;\nmov.b32 %7, t;\nmov.b32 %8, t;\nmov.b32 %9, t;\nmov.b32 %10, t;\nmov.b32 %11, t;\nmov.b32 %12, t;\nmov.b32 %13, t;\nmov.b32 %14, t;\nmov.b32 %15, t;\nmov.b32 %16, t;\nmov.b32 %17, t;\nmov.b32 %18, t;\nmov.b32 %19, t;\nmov.b32 %20, t;\nmov.b32 %21, t;\nmov.b32 %22, t;\nmov.b32 %23, t;\n" FENCE_TAIL
                 : "+r"(r[0]), "+r"(r[1]), "+r"(r[2]), "+r"(r[3]), "+r"(r[4]), "+r"(r[5]), "+r"(r[6]), "+r"(r[7]), "+r"(r[8]), "+r"(r[9]), "+r"(r[10]), "+r"(r[11]), "+r"(r[12]), "+r"(r[13]), "+r"(r[14]), "+r"(r[15]), "+r"(r[16]), "+r"(r[17]), "+r"(r[18]), "+r"(r[19]), "+r"(r[20]), "+r"(r[21]), "+r"(r[22]), "+r"(r[23]) : "r"(key) : "memory");
}
#define SPLIT(k, r) do { if ((SPLITS >> (k)) & 1) sched_fence<sizeof(r) / 4>(r, prm.ydesc); } while (0)

__device__ __forceinline__ void mbar_init(uint32_t bar, uint32_t count) {
    asm volatile("mbarrier.init.shared::cta.b64 [%0], %1;" ::"r"(bar), "r"(count) : "memory");
}
__device__ __forceinline__ void mbar_arrive_if(uint32_t bar, bool pred) {
    asm volatile("{\n.reg .pred p;\nsetp.ne.u32 p, %1, 0;\n@p mbarrier.arrive.shared::cta.b64 _, [%0];\n}\n"
                 ::"r"(bar), "r"((uint32_t)pred) : "memory");
}
__device__ __forceinline__ void mbar_wait(uint32_t bar, uint32_t parity) {
    asm volatile(
        "{\n.reg .pred p;\n.reg .u32 n;\n"
        "mbarrier.try_wait.parity.shared::cta.b64 p, [%0], %1;\n"
        "@p bra.uni WAIT_DONE;\n"
        "mov.u32 n, 0;\n"
        "WAIT_LOOP:\n"
        "mbarrier.try_wait.parity.shared::cta.b64 p, [%0], %1;\n"
        "@p bra.uni WAIT_DONE;\n"
        "mbarrier.try_wait.parity.shared::cta.b64 p, [%0], %1;\n"
        "@p bra.uni WAIT_DONE;\n"
        "mbarrier.try_wait.parity.shared::cta.b64 p, [%0], %1;\n"
        "@p bra.uni WAIT_DONE;\n"
        "add.u32 n, n, 1;\nsetp.lt.u32 p, n, 0x40000;\n"
        "@p bra.uni WAIT_LOOP;\n"
        "trap;\n"
        "WAIT_DONE:\n}\n"
        ::"r"(bar), "r"(parity) : "memory");
}
template <int PARITY> __device__ __forceinline__ void mbar_wait_c(uint32_t bar) {
    asm volatile(
        "{\n.reg .pred p;\n.reg .u32 n;\n"
        "mbarrier.try_wait.parity.shared::cta.b64 p, [%0], %1;\n"
        "@p bra.uni WAIT_DONE;\n"
        "mov.u32 n, 0;\n"
        "WAIT_LOOP:\n"
        "mbarrier.try_wait.parity.shared::cta.b64 p, [%0], %1;\n"
        "@p bra.uni WAIT_DONE;\n"
        "mbarrier.try_wait.parity.shared::cta.b64 p, [%0], %1;\n"
        "@p bra.uni WAIT_DONE;\n"
        "mbarrier.try_wait.parity.shared::cta.b64 p, [%0], %1;\n"
        "@p bra.uni WAIT_DONE;\n"
        "add.u32 n, n, 1;\nsetp.lt.u32 p, n, 0x40000;\n"
        "@p bra.uni WAIT_LOOP;\n"
        "trap;\n"
        "WAIT_DONE:\n}\n"
        ::"r"(bar), "n"(PARITY) : "memory");
}
__device__ __forceinline__ bool mbar_probe(uint32_t bar, uint32_t parity) {
    uint32_t ok;
    asm volatile("{\n.reg .pred p;\nmbarrier.test_wait.parity.shared::cta.b64 p, [%1], %2;\nselp.u32 %0, 1, 0, p;\n}\n"
                 : "=r"(ok) : "r"(bar), "r"(parity) : "memory");
    return ok;
}
__device__ __forceinline__ void mbar_wait2(uint32_t bar0, uint32_t parity0, uint32_t bar1, uint32_t parity1) {
    asm volatile(
        "{\n.reg .pred p, q;\n.reg .u32 n;\n"
        "mbarrier.try_wait.parity.shared::cta.b64 p, [%0], %1;\n"
        "mbarrier.try_wait.parity.shared::cta.b64 q, [%2], %3;\n"
        "and.pred p, p, q;\n"
        "@p bra.uni WAIT_DONE;\n"
        "mov.u32 n, 0;\n"
        "WAIT_LOOP:\n"
        "mbarrier.try_wait.parity.shared::cta.b64 p, [%0], %1;\n"
        "mbarrier.try_wait.parity.shared::cta.b64 q, [%2], %3;\n"
        "and.pred p, p, q;\n"
        "@p bra.uni WAIT_DONE;\n"
        "add.u32 n, n, 1;\nsetp.lt.u32 p, n, 0x80000;\n"
        "@p bra.uni WAIT_LOOP;\n"
        "trap;\n"
        "WAIT_DONE:\n}\n"
        ::"r"(bar0), "r"(parity0), "r"(bar1), "r"(parity1) : "memory");
}
#define ELECTED(body) "{\n.reg .pred p;\nelect.sync _|p, 0xffffffff;\n" body "}\n"
__device__ __forceinline__ void expect_tx(uint32_t bar, uint32_t bytes) {
    asm volatile(ELECTED("@p mbarrier.arrive.expect_tx.shared::cta.b64 _, [%0], %1;\n") ::"r"(bar), "r"(bytes) : "memory");
}
__device__ __forceinline__ void arrive_n(uint32_t bar, uint32_t count) {
    asm volatile(ELECTED("@p mbarrier.arrive.shared::cta.b64 _, [%0], %1;\n") ::"r"(bar), "r"(count) : "memory");
}
__device__ __forceinline__ void bulk_load(uint32_t dst, const void* src, uint32_t bytes, uint32_t bar) {
    asm volatile(ELECTED("@p cp.async.bulk.shared::cluster.global.mbarrier::complete_tx::bytes [%0], [%1], %2, [%3];\n")
                 ::"r"(dst), "l"(src), "r"(bytes), "r"(bar) : "memory");
}
__device__ __forceinline__ void bulk_store(void* dst, uint32_t src, uint32_t bytes) {
    asm volatile(ELECTED("@p cp.async.bulk.global.shared::cta.bulk_group [%0], [%1], %2;\n@p cp.async.bulk.commit_group;\n")
                 ::"l"(dst), "r"(src), "r"(bytes) : "memory");
}
__device__ __forceinline__ void bulk_prefetch(const void* src, uint32_t bytes) {
    asm volatile(ELECTED("@p cp.async.bulk.prefetch.L2.global [%0], %1;\n") ::"l"(src), "r"(bytes) : "memory");
}
__device__ __forceinline__ void tma_load_2d(uint32_t dst, const CUtensorMap* map, int c0, int c1, uint32_t bar) {
    asm volatile(ELECTED("@p cp.async.bulk.tensor.2d.shared::cluster.global.mbarrier::complete_tx::bytes [%0], [%1, {%2, %3}], [%4];\n")
                 ::"r"(dst), "l"(map), "r"(c0), "r"(c1), "r"(bar) : "memory");
}
template <int N> __device__ __forceinline__ void bulk_wait_read() {
    asm volatile("cp.async.bulk.wait_group.read %0;" ::"n"(N) : "memory");
}
__device__ __forceinline__ void bulk_wait_all() { asm volatile("cp.async.bulk.wait_group 0;" ::: "memory"); }
__device__ __forceinline__ void fence_async_smem() { asm volatile("fence.proxy.async.shared::cta;" ::: "memory"); }
__device__ __forceinline__ void named_sync(int id, int n) { asm volatile("bar.sync %0, %1;" ::"r"(id), "r"(n) : "memory"); }

__device__ __forceinline__ void lds64(uint32_t (&v)[2], uint32_t addr) {
    asm volatile("ld.shared.v2.b32 {%0,%1}, [%2];" : "=r"(v[0]), "=r"(v[1]) : "r"(addr));
}
__device__ __forceinline__ void sts64(uint32_t addr, uint32_t a, uint32_t b) {
    asm volatile("st.shared.v2.b32 [%0], {%1,%2};" ::"r"(addr), "r"(a), "r"(b) : "memory");
}
__device__ __forceinline__ void sts128(uint32_t addr, uint32_t a, uint32_t b, uint32_t c, uint32_t d) {
    asm volatile("st.shared.v4.b32 [%0], {%1,%2,%3,%4};" ::"r"(addr), "r"(a), "r"(b), "r"(c), "r"(d) : "memory");
}
__device__ __forceinline__ void ldsm4(uint32_t* r, uint32_t addr) {
    asm volatile("ldmatrix.sync.aligned.m8n8.x4.shared.b16 {%0,%1,%2,%3}, [%4];"
                 : "=r"(r[0]), "=r"(r[1]), "=r"(r[2]), "=r"(r[3]) : "r"(addr) : "memory");
}
__device__ __forceinline__ void ldsm4_t(uint32_t* r, uint32_t addr) {
    asm volatile("ldmatrix.sync.aligned.m8n8.x4.trans.shared.b16 {%0,%1,%2,%3}, [%4];"
                 : "=r"(r[0]), "=r"(r[1]), "=r"(r[2]), "=r"(r[3]) : "r"(addr) : "memory");
}
__device__ __forceinline__ void lds128(uint32_t* v, uint32_t addr) {
    asm volatile("ld.shared.v4.b32 {%0,%1,%2,%3}, [%4];"
                 : "=r"(v[0]), "=r"(v[1]), "=r"(v[2]), "=r"(v[3]) : "r"(addr) : "memory");
}
__device__ __forceinline__ uint32_t lds32(uint32_t addr) {
    uint32_t v; asm volatile("ld.shared.b32 %0, [%1];" : "=r"(v) : "r"(addr) : "memory"); return v;
}
__device__ __forceinline__ void sts32(uint32_t addr, uint32_t v) {
    asm volatile("st.shared.b32 [%0], %1;" ::"r"(addr), "r"(v) : "memory");
}

__device__ __forceinline__ uint32_t bf2_fma(uint32_t a, uint32_t b, uint32_t c) {
    uint32_t d; asm("fma.rn.bf16x2 %0, %1, %2, %3;" : "=r"(d) : "r"(a), "r"(b), "r"(c)); return d;
}
__device__ __forceinline__ uint32_t bf2_mul(uint32_t a, uint32_t b) {
    uint32_t d; asm("mul.rn.bf16x2 %0, %1, %2;" : "=r"(d) : "r"(a), "r"(b)); return d;
}
__device__ __forceinline__ uint32_t bf2_add(uint32_t a, uint32_t b) {
    uint32_t d; asm("add.rn.bf16x2 %0, %1, %2;" : "=r"(d) : "r"(a), "r"(b)); return d;
}
__device__ __forceinline__ uint32_t h2_fma(uint32_t a, uint32_t b, uint32_t c) {
    uint32_t d; asm("fma.rn.f16x2 %0, %1, %2, %3;" : "=r"(d) : "r"(a), "r"(b), "r"(c)); return d;
}
__device__ __forceinline__ uint32_t h2_mul(uint32_t a, uint32_t b) {
    uint32_t d; asm("mul.rn.f16x2 %0, %1, %2;" : "=r"(d) : "r"(a), "r"(b)); return d;
}
__device__ __forceinline__ uint32_t h2_tanh(uint32_t a) {
    uint32_t d; asm("tanh.approx.f16x2 %0, %1;" : "=r"(d) : "r"(a)); return d;
}
__device__ __forceinline__ float bf_lo(uint32_t v) { return __uint_as_float(v << 16); }
__device__ __forceinline__ float bf_hi(uint32_t v) { return __uint_as_float(v & 0xffff0000u); }
__device__ __forceinline__ uint32_t pack_h2(float lo, float hi) {
    uint32_t d; asm("cvt.rn.f16x2.f32 %0, %1, %2;" : "=r"(d) : "f"(hi), "f"(lo)); return d;
}
__device__ __forceinline__ uint32_t pack_bf2(float lo, float hi) {
    uint32_t d; asm("cvt.rn.bf16x2.f32 %0, %1, %2;" : "=r"(d) : "f"(hi), "f"(lo)); return d;
}
__device__ __forceinline__ void h2_unpack(uint32_t v, float& lo, float& hi) {
    asm("{\n.reg .b16 l, h;\nmov.b32 {l, h}, %2;\ncvt.f32.f16 %0, l;\ncvt.f32.f16 %1, h;\n}\n" : "=f"(lo), "=f"(hi) : "r"(v));
}
__device__ __forceinline__ uint32_t bf2_to_h2(uint32_t v) { return pack_h2(bf_lo(v), bf_hi(v)); }

__device__ __forceinline__ uint32_t gelu2(uint32_t z) {
    uint32_t p = h2_fma(z, z, GELU_C_H2);
    uint32_t t = h2_tanh(h2_mul(z, p));
    return h2_fma(z, t, z);
}

__device__ __forceinline__ void wg_fence() { asm volatile("wgmma.fence.sync.aligned;" ::: "memory"); }
__device__ __forceinline__ void wg_commit() { asm volatile("wgmma.commit_group.sync.aligned;" ::: "memory"); }
template <int N> __device__ __forceinline__ void wg_wait() {
    asm volatile("wgmma.wait_group.sync.aligned %0;" ::"n"(N) : "memory");
}
template <int N> __device__ __forceinline__ void pin(uint32_t (&r)[N]) {
#pragma unroll
    for (int i = 0; i < N; i++) asm volatile("" : "+r"(r[i])::"memory");
}
constexpr uint32_t desc_lo(uint32_t addr, uint32_t lbo) { return ((addr & 0x3FFFF) >> 4) | ((lbo >> 4) << 16); }
template <uint32_t SBO, uint32_t SWZ> __device__ __forceinline__ uint64_t desc(uint32_t lo, uint32_t bytes) {
    return (((uint64_t)((SBO >> 4) | (SWZ << 30)) << 32) | lo) + (bytes >> 4);
}
__device__ __forceinline__ uint32_t fresh_tid() {
    uint32_t v; asm volatile("mov.u32 %0, %%tid.x;" : "=r"(v));
    return v;
}
template <uint32_t V> __device__ __forceinline__ uint32_t loop_init() {
    uint32_t v; asm volatile("mov.u32 %0, %1;" : "=r"(v) : "n"(V)); return v;
}
__device__ __forceinline__ int fresh_warp() {
    int v; asm volatile("shfl.sync.idx.b32 %0, %1, 0, 0x1f, 0xffffffff;" : "=r"(v) : "r"(fresh_tid() >> 5)); return v;
}
__device__ __forceinline__ uint32_t fresh_cta() {
    uint32_t v; asm volatile("mov.u32 %0, %%ctaid.x;" : "=r"(v)); return v;
}
__device__ __forceinline__ float rsqrt_fast(float v) { float r; asm("rsqrt.approx.ftz.f32 %0, %1;" : "=f"(r) : "f"(v)); return r; }
__device__ __forceinline__ float sqrt_fast(float v) { float r; asm("sqrt.approx.f32 %0, %1;" : "=f"(r) : "f"(v)); return r; }

template <int TB>
__device__ __forceinline__ void wgmma_n64_h_set(uint32_t (&d)[16], const uint32_t* a, uint64_t desc) {
    asm volatile(
        "{\n.reg .pred p;\nsetp.ne.b32 p, 0, 0;\n"
        "wgmma.mma_async.sync.aligned.m64n64k16.f16.f16.f16 "
        "{%0,%1,%2,%3,%4,%5,%6,%7,%8,%9,%10,%11,%12,%13,%14,%15}, {%16,%17,%18,%19}, %20, p, 1, 1, %21;\n}\n"
        : "=r"(d[0]), "=r"(d[1]), "=r"(d[2]), "=r"(d[3]), "=r"(d[4]), "=r"(d[5]), "=r"(d[6]), "=r"(d[7]), "=r"(d[8]), "=r"(d[9]), "=r"(d[10]), "=r"(d[11]), "=r"(d[12]), "=r"(d[13]), "=r"(d[14]), "=r"(d[15])
        : "r"(a[0]), "r"(a[1]), "r"(a[2]), "r"(a[3]), "l"(desc), "n"(TB));
}
template <int TB>
__device__ __forceinline__ void wgmma_n64_h_acc(uint32_t (&d)[16], const uint32_t* a, uint64_t desc) {
    asm volatile(
        "{\n.reg .pred p;\nsetp.ne.b32 p, 1, 0;\n"
        "wgmma.mma_async.sync.aligned.m64n64k16.f16.f16.f16 "
        "{%0,%1,%2,%3,%4,%5,%6,%7,%8,%9,%10,%11,%12,%13,%14,%15}, {%16,%17,%18,%19}, %20, p, 1, 1, %21;\n}\n"
        : "+r"(d[0]), "+r"(d[1]), "+r"(d[2]), "+r"(d[3]), "+r"(d[4]), "+r"(d[5]), "+r"(d[6]), "+r"(d[7]), "+r"(d[8]), "+r"(d[9]), "+r"(d[10]), "+r"(d[11]), "+r"(d[12]), "+r"(d[13]), "+r"(d[14]), "+r"(d[15])
        : "r"(a[0]), "r"(a[1]), "r"(a[2]), "r"(a[3]), "l"(desc), "n"(TB));
}
__device__ __forceinline__ void wgmma_n64_h_acc_ss(uint32_t (&d)[16], uint64_t adesc, uint64_t desc) {
    asm volatile(
        "{\n.reg .pred p;\nsetp.ne.b32 p, 1, 0;\n"
        "wgmma.mma_async.sync.aligned.m64n64k16.f16.f16.f16 "
        "{%0,%1,%2,%3,%4,%5,%6,%7,%8,%9,%10,%11,%12,%13,%14,%15}, %16, %17, p, 1, 1, 1, 0;\n}\n"
        : "+r"(d[0]), "+r"(d[1]), "+r"(d[2]), "+r"(d[3]), "+r"(d[4]), "+r"(d[5]), "+r"(d[6]), "+r"(d[7]), "+r"(d[8]), "+r"(d[9]), "+r"(d[10]), "+r"(d[11]), "+r"(d[12]), "+r"(d[13]), "+r"(d[14]), "+r"(d[15])
        : "l"(adesc), "l"(desc));
}
__device__ __forceinline__ void wgmma_n96_h_acc(uint32_t (&d)[24], const uint32_t* a, uint64_t desc) {
    asm volatile(
        "{\n.reg .pred p;\nsetp.ne.b32 p, 1, 0;\n"
        "wgmma.mma_async.sync.aligned.m64n96k16.f16.f16.f16 "
        "{%0,%1,%2,%3,%4,%5,%6,%7,%8,%9,%10,%11,%12,%13,%14,%15,%16,%17,%18,%19,%20,%21,%22,%23}, {%24,%25,%26,%27}, %28, p, 1, 1, 1;\n}\n"
        : "+r"(d[0]), "+r"(d[1]), "+r"(d[2]), "+r"(d[3]), "+r"(d[4]), "+r"(d[5]), "+r"(d[6]), "+r"(d[7]), "+r"(d[8]), "+r"(d[9]), "+r"(d[10]), "+r"(d[11]), "+r"(d[12]), "+r"(d[13]), "+r"(d[14]), "+r"(d[15]), "+r"(d[16]), "+r"(d[17]), "+r"(d[18]), "+r"(d[19]), "+r"(d[20]), "+r"(d[21]), "+r"(d[22]), "+r"(d[23])
        : "r"(a[0]), "r"(a[1]), "r"(a[2]), "r"(a[3]), "l"(desc));
}

template <int ACC>
__device__ __forceinline__ void wgmma_n8(float (&d)[4], uint32_t a0, uint32_t a1, uint32_t a2, uint32_t a3, uint64_t desc) {
    if (ACC)
        asm volatile("{\n.reg .pred p;\nsetp.ne.b32 p, 1, 0;\n"
                     "wgmma.mma_async.sync.aligned.m64n8k16.f32.bf16.bf16 {%0,%1,%2,%3}, {%4,%5,%6,%7}, %8, p, 1, 1, 0;\n}\n"
                     : "+f"(d[0]), "+f"(d[1]), "+f"(d[2]), "+f"(d[3]) : "r"(a0), "r"(a1), "r"(a2), "r"(a3), "l"(desc));
    else
        asm volatile("{\n.reg .pred p;\nsetp.ne.b32 p, 0, 0;\n"
                     "wgmma.mma_async.sync.aligned.m64n8k16.f32.bf16.bf16 {%0,%1,%2,%3}, {%4,%5,%6,%7}, %8, p, 1, 1, 0;\n}\n"
                     : "=f"(d[0]), "=f"(d[1]), "=f"(d[2]), "=f"(d[3]) : "r"(a0), "r"(a1), "r"(a2), "r"(a3), "l"(desc));
}

struct Params {
    CUtensorMap w2_map;
    const __nv_bfloat16* x;
    const __nv_bfloat16* dw;
    const __nv_bfloat16* w1;
    const __nv_bfloat16* gamma;
    const __nv_bfloat16* beta;
    __nv_bfloat16* out;
    uint64_t sel[3];
    uint32_t w1desc, w2desc, ydesc;
};

__device__ __forceinline__ uint32_t cta_tile0(uint32_t cta) {
    return (cta >> 3) * (ROWS_PER_CTA * ROW_BYTES) + (cta & 7) * TILE_BYTES;
}

struct Producer {
    uint32_t w[9][6];
    uint32_t xoff[2];
    uint32_t yoff[2][2];
    uint32_t stat, own;
    int lane, warp;
};

struct RowCopy {
    const char* x0;
    char* y0;
    uint32_t cut0, cut1;
    int first, last;
};
__device__ __forceinline__ RowCopy row_copy(const Params& prm) {
    const uint32_t cta = fresh_cta(), strip = cta & 7, t0 = cta_tile0(cta);
    RowCopy r;
    r.x0 = (const char*)prm.x + t0 - ROW_BYTES - 192;
    r.y0 = (char*)prm.out + t0;
    r.cut0 = strip == 0 ? 192 : 0;
    r.cut1 = strip == 7 ? 192 : 0;
    r.first = cta < 8 ? 1 : 0;
    r.last = cta >= NUM_CTAS - 8 ? STEPS - 2 : STEPS - 1;
    return r;
}
__device__ __forceinline__ void issue_row_load(const RowCopy& r, int i, uint32_t slot) {
    const char* src = (i >= r.first && i <= r.last) ? r.x0 + (uint32_t)i * ROW_BYTES : (const char*)g_zero_row;
    const uint32_t bar = sb + SM_XFULL + slot * SLOT_BYTES, dst = sb + SM_X + slot * SLOT_BYTES;
    expect_tx(bar, XHALF_BYTES - r.cut0);
    bulk_load(dst + r.cut0, src + r.cut0, XHALF_BYTES - r.cut0, bar);
    expect_tx(bar, XHALF_BYTES - r.cut1);
    bulk_load(dst + XHALF_B, src + 32 * 192, XHALF_BYTES - r.cut1, bar);
}

__device__ __forceinline__ float quad_sum(float v) {
    v += __shfl_xor_sync(0xffffffffu, v, 1);
    v += __shfl_xor_sync(0xffffffffu, v, 2);
    return v;
}

__device__ __forceinline__ void load_x(uint32_t (&v)[6][6], const Producer& c, uint32_t row) {
#pragma unroll
    for (int k = 0; k < 6; k++) {
        asm volatile("ld.shared.v4.b32 {%0,%1,%2,%3}, [%4];"
                     : "=r"(v[k][0]), "=r"(v[k][1]), "=r"(v[k][2]), "=r"(v[k][3]) : "r"(row + c.xoff[0] + k * 192));
        asm volatile("ld.shared.v2.b32 {%0,%1}, [%2];" : "=r"(v[k][4]), "=r"(v[k][5]) : "r"(row + c.xoff[1] + k * 192));
    }
}
template <int DY, int STRIDE>
__device__ __forceinline__ void conv_row(uint32_t (&dst)[24], const uint32_t* src, const uint32_t (&v)[6][6], const Producer& c) {
#pragma unroll
    for (int o = 0; o < 4; o++)
#pragma unroll
        for (int u = 0; u < 6; u++)
            dst[o * 6 + u] = bf2_fma(v[o + 2][u], c.w[3 * DY + 2][u], bf2_fma(v[o + 1][u], c.w[3 * DY + 1][u],
                             bf2_fma(v[o][u], c.w[3 * DY][u], STRIDE ? src[o * 6 + u] : src[2 * o + 1])));
}
__device__ __forceinline__ void start_sums(float (&d)[4], const uint32_t (&A)[24], const uint32_t (&q)[4], const Params& prm) {
    wg_fence();
#pragma unroll
    for (int k = 0; k < 6; k++) {
        const int r = (k / 3) * 12 + (k % 3) * 2;
        if (k == 0) wgmma_n8<0>(d, A[r], A[r + 6], A[r + 1], A[r + 7], prm.sel[0]);
        else wgmma_n8<1>(d, A[r], A[r + 6], A[r + 1], A[r + 7], prm.sel[k / 3]);
    }
    wgmma_n8<1>(d, q[0], q[1], q[2], q[3], prm.sel[2]);
    wg_commit();
}
__device__ __forceinline__ void finish_sums(float (&d)[4], int lane, float& sum, float& sq) {
    wg_wait<0>();
    asm volatile("" : "+f"(d[0]), "+f"(d[1]), "+f"(d[2]), "+f"(d[3])::"memory");
    sum = (lane & 1) ? d[2] : d[0];
    sq = (lane & 1) ? d[3] : d[1];
    sum += __shfl_xor_sync(0xffffffffu, sum, 4);
    sq += __shfl_xor_sync(0xffffffffu, sq, 4);
}

#define HAND_OVER(name, base, r) asm volatile("mov.b32 " name "%6, %0; mov.b32 " name "%7, %1; mov.b32 " name "%8, %2;\n" \
    "mov.b32 " name "%9, %3; mov.b32 " name "%10, %4; mov.b32 " name "%11, %5;" ::"r"((r)[0]), "r"((r)[1]), "r"((r)[2]), \
    "r"((r)[3]), "r"((r)[4]), "r"((r)[5]), "n"(base), "n"(base + 1), "n"(base + 2), "n"(base + 3), "n"(base + 4), "n"(base + 5))
template <int K> __device__ __forceinline__ void hand_over(const Producer& c, const uint32_t (&B)[24], const uint32_t (&C)[24],
                                                           const uint32_t (&v)[6][6]) {
    HAND_OVER("pw", K * 6, c.w[K]);
    if (K < 6) HAND_OVER("pv", K * 6, v[K % 6]);
    if (K < 4) { HAND_OVER("pb", K * 6, B + K % 4 * 6); HAND_OVER("pc", K * 6, C + K % 4 * 6); }
    if constexpr (K < 8) hand_over<K + 1>(c, B, C, v);
}
static_assert(sb + SM_BAR + BAR_DUMMY * 8 == 230880, "layout");
__device__ __forceinline__ void produce_tiles(const Producer& c, const Params& prm) {
    asm volatile(
        "{\n"
        ".reg .b32 pa<24>, pq<4>, m<6>, y<6>, rr, mm, t, so, sp, ph, ad, tt, cnt;\n"
        ".reg .b16 xl, xh;\n"
        ".reg .f32 d<4>, us, s0, s1, f0, f1, kq;\n"
        ".reg .pred pt, pf, pr, pw, px, pl, po, pe;\n"
        "setp.ne.b32 pt, 1, 0; setp.ne.b32 pf, 0, 0; setp.eq.u32 pl, %8, 0; and.b32 tt, %8, 1; setp.ne.u32 po, tt, 0;\n"
        "and.b32 tt, %8, 4; setp.ne.u32 pr, tt, 0; selp.f32 kq, 0f3F802D41, 0f3F7FA57E, pr;\n"
        "mov.u32 t, 0; mov.u32 so, 0; mov.u32 sp, 55896; mov.u32 ph, 1;\n"
        "LOOP:\n"
        ASM_TRC("t", 0)
        "setp.eq.u32 pr, %12, 0;\n"
        "@pr bra.uni RARE;\n"
        "fence.proxy.async.shared::cta;\n"
        "@pl mbarrier.arrive.shared::cta.b64 _, [sp+174984];\n"
        "fma.rn.bf16x2 pa0, pv0, pw36, pb0; fma.rn.bf16x2 pa1, pv1, pw37, pb1; fma.rn.bf16x2 pa2, pv2, pw38, pb2; fma.rn.bf16x2 pa3, pv3, pw39, pb3; fma.rn.bf16x2 pa4, pv4, pw40, pb4; fma.rn.bf16x2 pa5, pv5, pw41, pb5;\n"
        "fma.rn.bf16x2 pa6, pv6, pw36, pb6; fma.rn.bf16x2 pa7, pv7, pw37, pb7; fma.rn.bf16x2 pa8, pv8, pw38, pb8; fma.rn.bf16x2 pa9, pv9, pw39, pb9; fma.rn.bf16x2 pa10, pv10, pw40, pb10; fma.rn.bf16x2 pa11, pv11, pw41, pb11;\n"
        "fma.rn.bf16x2 pa12, pv12, pw36, pb12; fma.rn.bf16x2 pa13, pv13, pw37, pb13; fma.rn.bf16x2 pa14, pv14, pw38, pb14; fma.rn.bf16x2 pa15, pv15, pw39, pb15; fma.rn.bf16x2 pa16, pv16, pw40, pb16; fma.rn.bf16x2 pa17, pv17, pw41, pb17;\n"
        "fma.rn.bf16x2 pa18, pv18, pw36, pb18; fma.rn.bf16x2 pa19, pv19, pw37, pb19; fma.rn.bf16x2 pa20, pv20, pw38, pb20; fma.rn.bf16x2 pa21, pv21, pw39, pb21; fma.rn.bf16x2 pa22, pv22, pw40, pb22; fma.rn.bf16x2 pa23, pv23, pw41, pb23;\n"
        "fma.rn.bf16x2 pa0, pv6, pw42, pa0; fma.rn.bf16x2 pa1, pv7, pw43, pa1; fma.rn.bf16x2 pa2, pv8, pw44, pa2; fma.rn.bf16x2 pa3, pv9, pw45, pa3; fma.rn.bf16x2 pa4, pv10, pw46, pa4; fma.rn.bf16x2 pa5, pv11, pw47, pa5;\n"
        "fma.rn.bf16x2 pa6, pv12, pw42, pa6; fma.rn.bf16x2 pa7, pv13, pw43, pa7; fma.rn.bf16x2 pa8, pv14, pw44, pa8; fma.rn.bf16x2 pa9, pv15, pw45, pa9; fma.rn.bf16x2 pa10, pv16, pw46, pa10; fma.rn.bf16x2 pa11, pv17, pw47, pa11;\n"
        "fma.rn.bf16x2 pa12, pv18, pw42, pa12; fma.rn.bf16x2 pa13, pv19, pw43, pa13; fma.rn.bf16x2 pa14, pv20, pw44, pa14; fma.rn.bf16x2 pa15, pv21, pw45, pa15; fma.rn.bf16x2 pa16, pv22, pw46, pa16; fma.rn.bf16x2 pa17, pv23, pw47, pa17;\n"
        "fma.rn.bf16x2 pa18, pv24, pw42, pa18; fma.rn.bf16x2 pa19, pv25, pw43, pa19; fma.rn.bf16x2 pa20, pv26, pw44, pa20; fma.rn.bf16x2 pa21, pv27, pw45, pa21; fma.rn.bf16x2 pa22, pv28, pw46, pa22; fma.rn.bf16x2 pa23, pv29, pw47, pa23;\n"
        "fma.rn.bf16x2 pa0, pv12, pw48, pa0; fma.rn.bf16x2 pa1, pv13, pw49, pa1; fma.rn.bf16x2 pa2, pv14, pw50, pa2; fma.rn.bf16x2 pa3, pv15, pw51, pa3; fma.rn.bf16x2 pa4, pv16, pw52, pa4; fma.rn.bf16x2 pa5, pv17, pw53, pa5;\n"
        "fma.rn.bf16x2 pa6, pv18, pw48, pa6; fma.rn.bf16x2 pa7, pv19, pw49, pa7; fma.rn.bf16x2 pa8, pv20, pw50, pa8; fma.rn.bf16x2 pa9, pv21, pw51, pa9; fma.rn.bf16x2 pa10, pv22, pw52, pa10; fma.rn.bf16x2 pa11, pv23, pw53, pa11;\n"
        "fma.rn.bf16x2 pa12, pv24, pw48, pa12; fma.rn.bf16x2 pa13, pv25, pw49, pa13; fma.rn.bf16x2 pa14, pv26, pw50, pa14; fma.rn.bf16x2 pa15, pv27, pw51, pa15; fma.rn.bf16x2 pa16, pv28, pw52, pa16; fma.rn.bf16x2 pa17, pv29, pw53, pa17;\n"
        "fma.rn.bf16x2 pa18, pv30, pw48, pa18; fma.rn.bf16x2 pa19, pv31, pw49, pa19; fma.rn.bf16x2 pa20, pv32, pw50, pa20; fma.rn.bf16x2 pa21, pv33, pw51, pa21; fma.rn.bf16x2 pa22, pv34, pw52, pa22; fma.rn.bf16x2 pa23, pv35, pw53, pa23;\n"
        "mul.rn.bf16x2 pq0, pa0, pa0; fma.rn.bf16x2 pq0, pa1, pa1, pq0; fma.rn.bf16x2 pq0, pa2, pa2, pq0; fma.rn.bf16x2 pq0, pa3, pa3, pq0; fma.rn.bf16x2 pq0, pa4, pa4, pq0; fma.rn.bf16x2 pq0, pa5, pa5, pq0;\n"
        "mul.rn.bf16x2 pq1, pa6, pa6; fma.rn.bf16x2 pq1, pa7, pa7, pq1; fma.rn.bf16x2 pq1, pa8, pa8, pq1; fma.rn.bf16x2 pq1, pa9, pa9, pq1; fma.rn.bf16x2 pq1, pa10, pa10, pq1; fma.rn.bf16x2 pq1, pa11, pa11, pq1;\n"
        "mul.rn.bf16x2 pq2, pa12, pa12; fma.rn.bf16x2 pq2, pa13, pa13, pq2; fma.rn.bf16x2 pq2, pa14, pa14, pq2; fma.rn.bf16x2 pq2, pa15, pa15, pq2; fma.rn.bf16x2 pq2, pa16, pa16, pq2; fma.rn.bf16x2 pq2, pa17, pa17, pq2;\n"
        "mul.rn.bf16x2 pq3, pa18, pa18; fma.rn.bf16x2 pq3, pa19, pa19, pq3; fma.rn.bf16x2 pq3, pa20, pa20, pq3; fma.rn.bf16x2 pq3, pa21, pa21, pq3; fma.rn.bf16x2 pq3, pa22, pa22, pq3; fma.rn.bf16x2 pq3, pa23, pa23, pq3;\n"
        "B0:\n"
        "wgmma.fence.sync.aligned;\n"
        "wgmma.mma_async.sync.aligned.m64n8k16.f32.bf16.bf16 {d0,d1,d2,d3}, {pa0,pa6,pa1,pa7}, %9, pf, 1, 1, 0;\n"
        "wgmma.mma_async.sync.aligned.m64n8k16.f32.bf16.bf16 {d0,d1,d2,d3}, {pa2,pa8,pa3,pa9}, %9, pt, 1, 1, 0;\n"
        "wgmma.mma_async.sync.aligned.m64n8k16.f32.bf16.bf16 {d0,d1,d2,d3}, {pa4,pa10,pa5,pa11}, %9, pt, 1, 1, 0;\n"
        "wgmma.mma_async.sync.aligned.m64n8k16.f32.bf16.bf16 {d0,d1,d2,d3}, {pa12,pa18,pa13,pa19}, %10, pt, 1, 1, 0;\n"
        "wgmma.mma_async.sync.aligned.m64n8k16.f32.bf16.bf16 {d0,d1,d2,d3}, {pa14,pa20,pa15,pa21}, %10, pt, 1, 1, 0;\n"
        "wgmma.mma_async.sync.aligned.m64n8k16.f32.bf16.bf16 {d0,d1,d2,d3}, {pa16,pa22,pa17,pa23}, %10, pt, 1, 1, 0;\n"
        "wgmma.mma_async.sync.aligned.m64n8k16.f32.bf16.bf16 {d0,d1,d2,d3}, {pq0,pq1,pq2,pq3}, %11, pt, 1, 1, 0;\n"
        "wgmma.commit_group.sync.aligned;\n"
        "add.u32 ad, %7, so; ld.shared.f32 us, [ad+4];\n"
        "fma.rn.bf16x2 pb0, pv0, pw18, pc0; fma.rn.bf16x2 pb1, pv1, pw19, pc1; fma.rn.bf16x2 pb2, pv2, pw20, pc2; fma.rn.bf16x2 pb3, pv3, pw21, pc3; fma.rn.bf16x2 pb4, pv4, pw22, pc4; fma.rn.bf16x2 pb5, pv5, pw23, pc5;\n"
        "fma.rn.bf16x2 pb6, pv6, pw18, pc6; fma.rn.bf16x2 pb7, pv7, pw19, pc7; fma.rn.bf16x2 pb8, pv8, pw20, pc8; fma.rn.bf16x2 pb9, pv9, pw21, pc9; fma.rn.bf16x2 pb10, pv10, pw22, pc10; fma.rn.bf16x2 pb11, pv11, pw23, pc11;\n"
        "fma.rn.bf16x2 pb0, pv6, pw24, pb0; fma.rn.bf16x2 pb1, pv7, pw25, pb1; fma.rn.bf16x2 pb2, pv8, pw26, pb2; fma.rn.bf16x2 pb3, pv9, pw27, pb3; fma.rn.bf16x2 pb4, pv10, pw28, pb4; fma.rn.bf16x2 pb5, pv11, pw29, pb5;\n"
        "fma.rn.bf16x2 pb6, pv12, pw24, pb6; fma.rn.bf16x2 pb7, pv13, pw25, pb7; fma.rn.bf16x2 pb8, pv14, pw26, pb8; fma.rn.bf16x2 pb9, pv15, pw27, pb9; fma.rn.bf16x2 pb10, pv16, pw28, pb10; fma.rn.bf16x2 pb11, pv17, pw29, pb11;\n"
        "fma.rn.bf16x2 pb0, pv12, pw30, pb0; fma.rn.bf16x2 pb1, pv13, pw31, pb1; fma.rn.bf16x2 pb2, pv14, pw32, pb2; fma.rn.bf16x2 pb3, pv15, pw33, pb3; fma.rn.bf16x2 pb4, pv16, pw34, pb4; fma.rn.bf16x2 pb5, pv17, pw35, pb5;\n"
        "fma.rn.bf16x2 pb6, pv18, pw30, pb6; fma.rn.bf16x2 pb7, pv19, pw31, pb7; fma.rn.bf16x2 pb8, pv20, pw32, pb8; fma.rn.bf16x2 pb9, pv21, pw33, pb9; fma.rn.bf16x2 pb10, pv22, pw34, pb10; fma.rn.bf16x2 pb11, pv23, pw35, pb11;\n"
        "B1:\n"
        "fma.rn.bf16x2 pb12, pv12, pw18, pc12; fma.rn.bf16x2 pb13, pv13, pw19, pc13; fma.rn.bf16x2 pb14, pv14, pw20, pc14; fma.rn.bf16x2 pb15, pv15, pw21, pc15; fma.rn.bf16x2 pb16, pv16, pw22, pc16; fma.rn.bf16x2 pb17, pv17, pw23, pc17;\n"
        "fma.rn.bf16x2 pb18, pv18, pw18, pc18; fma.rn.bf16x2 pb19, pv19, pw19, pc19; fma.rn.bf16x2 pb20, pv20, pw20, pc20; fma.rn.bf16x2 pb21, pv21, pw21, pc21; fma.rn.bf16x2 pb22, pv22, pw22, pc22; fma.rn.bf16x2 pb23, pv23, pw23, pc23;\n"
        "fma.rn.bf16x2 pb12, pv18, pw24, pb12; fma.rn.bf16x2 pb13, pv19, pw25, pb13; fma.rn.bf16x2 pb14, pv20, pw26, pb14; fma.rn.bf16x2 pb15, pv21, pw27, pb15; fma.rn.bf16x2 pb16, pv22, pw28, pb16; fma.rn.bf16x2 pb17, pv23, pw29, pb17;\n"
        "fma.rn.bf16x2 pb18, pv24, pw24, pb18; fma.rn.bf16x2 pb19, pv25, pw25, pb19; fma.rn.bf16x2 pb20, pv26, pw26, pb20; fma.rn.bf16x2 pb21, pv27, pw27, pb21; fma.rn.bf16x2 pb22, pv28, pw28, pb22; fma.rn.bf16x2 pb23, pv29, pw29, pb23;\n"
        "fma.rn.bf16x2 pb12, pv24, pw30, pb12; fma.rn.bf16x2 pb13, pv25, pw31, pb13; fma.rn.bf16x2 pb14, pv26, pw32, pb14; fma.rn.bf16x2 pb15, pv27, pw33, pb15; fma.rn.bf16x2 pb16, pv28, pw34, pb16; fma.rn.bf16x2 pb17, pv29, pw35, pb17;\n"
        "fma.rn.bf16x2 pb18, pv30, pw30, pb18; fma.rn.bf16x2 pb19, pv31, pw31, pb19; fma.rn.bf16x2 pb20, pv32, pw32, pb20; fma.rn.bf16x2 pb21, pv33, pw33, pb21; fma.rn.bf16x2 pb22, pv34, pw34, pb22; fma.rn.bf16x2 pb23, pv35, pw35, pb23;\n"
        "C0:\n"
        "wgmma.wait_group.sync.aligned 0;\n"
        "selp.f32 s0, d2, d0, po; selp.f32 s1, d3, d1, po;\n"
        "shfl.sync.bfly.b32 f0, s0, 4, 0x1f, 0xffffffff; shfl.sync.bfly.b32 f1, s1, 4, 0x1f, 0xffffffff;\n"
        "fma.rn.bf16x2 pc0, pv0, pw0, ps1; fma.rn.bf16x2 pc1, pv1, pw1, ps1; fma.rn.bf16x2 pc2, pv2, pw2, ps1; fma.rn.bf16x2 pc3, pv3, pw3, ps1; fma.rn.bf16x2 pc4, pv4, pw4, ps1; fma.rn.bf16x2 pc5, pv5, pw5, ps1;\n"
        "fma.rn.bf16x2 pc6, pv6, pw0, ps3; fma.rn.bf16x2 pc7, pv7, pw1, ps3; fma.rn.bf16x2 pc8, pv8, pw2, ps3; fma.rn.bf16x2 pc9, pv9, pw3, ps3; fma.rn.bf16x2 pc10, pv10, pw4, ps3; fma.rn.bf16x2 pc11, pv11, pw5, ps3;\n"
        "fma.rn.bf16x2 pc12, pv12, pw0, ps5; fma.rn.bf16x2 pc13, pv13, pw1, ps5; fma.rn.bf16x2 pc14, pv14, pw2, ps5; fma.rn.bf16x2 pc15, pv15, pw3, ps5; fma.rn.bf16x2 pc16, pv16, pw4, ps5; fma.rn.bf16x2 pc17, pv17, pw5, ps5;\n"
        "fma.rn.bf16x2 pc18, pv18, pw0, ps7; fma.rn.bf16x2 pc19, pv19, pw1, ps7; fma.rn.bf16x2 pc20, pv20, pw2, ps7; fma.rn.bf16x2 pc21, pv21, pw3, ps7; fma.rn.bf16x2 pc22, pv22, pw4, ps7; fma.rn.bf16x2 pc23, pv23, pw5, ps7;\n"
        "fma.rn.bf16x2 pc0, pv6, pw6, pc0; fma.rn.bf16x2 pc1, pv7, pw7, pc1; fma.rn.bf16x2 pc2, pv8, pw8, pc2; fma.rn.bf16x2 pc3, pv9, pw9, pc3; fma.rn.bf16x2 pc4, pv10, pw10, pc4; fma.rn.bf16x2 pc5, pv11, pw11, pc5;\n"
        "fma.rn.bf16x2 pc6, pv12, pw6, pc6; fma.rn.bf16x2 pc7, pv13, pw7, pc7; fma.rn.bf16x2 pc8, pv14, pw8, pc8; fma.rn.bf16x2 pc9, pv15, pw9, pc9; fma.rn.bf16x2 pc10, pv16, pw10, pc10; fma.rn.bf16x2 pc11, pv17, pw11, pc11;\n"
        "fma.rn.bf16x2 pc12, pv18, pw6, pc12; fma.rn.bf16x2 pc13, pv19, pw7, pc13; fma.rn.bf16x2 pc14, pv20, pw8, pc14; fma.rn.bf16x2 pc15, pv21, pw9, pc15; fma.rn.bf16x2 pc16, pv22, pw10, pc16; fma.rn.bf16x2 pc17, pv23, pw11, pc17;\n"
        "fma.rn.bf16x2 pc18, pv24, pw6, pc18; fma.rn.bf16x2 pc19, pv25, pw7, pc19; fma.rn.bf16x2 pc20, pv26, pw8, pc20; fma.rn.bf16x2 pc21, pv27, pw9, pc21; fma.rn.bf16x2 pc22, pv28, pw10, pc22; fma.rn.bf16x2 pc23, pv29, pw11, pc23;\n"
        "fma.rn.bf16x2 pc0, pv12, pw12, pc0; fma.rn.bf16x2 pc1, pv13, pw13, pc1; fma.rn.bf16x2 pc2, pv14, pw14, pc2; fma.rn.bf16x2 pc3, pv15, pw15, pc3; fma.rn.bf16x2 pc4, pv16, pw16, pc4; fma.rn.bf16x2 pc5, pv17, pw17, pc5;\n"
        "fma.rn.bf16x2 pc6, pv18, pw12, pc6; fma.rn.bf16x2 pc7, pv19, pw13, pc7; fma.rn.bf16x2 pc8, pv20, pw14, pc8; fma.rn.bf16x2 pc9, pv21, pw15, pc9; fma.rn.bf16x2 pc10, pv22, pw16, pc10; fma.rn.bf16x2 pc11, pv23, pw17, pc11;\n"
        "fma.rn.bf16x2 pc12, pv24, pw12, pc12; fma.rn.bf16x2 pc13, pv25, pw13, pc13; fma.rn.bf16x2 pc14, pv26, pw14, pc14; fma.rn.bf16x2 pc15, pv27, pw15, pc15; fma.rn.bf16x2 pc16, pv28, pw16, pc16; fma.rn.bf16x2 pc17, pv29, pw17, pc17;\n"
        "fma.rn.bf16x2 pc18, pv30, pw12, pc18; fma.rn.bf16x2 pc19, pv31, pw13, pc19; fma.rn.bf16x2 pc20, pv32, pw14, pc20; fma.rn.bf16x2 pc21, pv33, pw15, pc21; fma.rn.bf16x2 pc22, pv34, pw16, pc22; fma.rn.bf16x2 pc23, pv35, pw17, pc23;\n"
        "add.f32 s0, s0, f0; add.f32 s1, s1, f1; mul.f32 s0, s0, 0fBC2AAAAB;\n"
        "neg.f32 f0, s0; fma.rn.f32 f0, f0, s0, %13; fma.rn.f32 f0, s1, 0f3C2AAAAB, f0; max.f32 f0, f0, %13;\n"
        "rsqrt.approx.ftz.f32 f0, f0; mul.f32 f0, f0, %14; cvt.rn.bf16x2.f32 tt, f0, 0f00000000; mov.b32 f0, tt;\n"
        "mul.f32 f1, s0, kq; mul.f32 f1, f1, f0; cvt.rn.bf16x2.f32 tt, f1, f0; add.f32 us, us, s0; cvt.rn.bf16x2.f32 mm, us, us;\n"
        "add.u32 ad, %7, so; st.shared.v2.b32 [ad], {tt, mm};\n"
        "add.u32 ad, %6, so; ld.shared.v4.b32 {ps0,ps1,ps2,ps3}, [ad]; ld.shared.v4.b32 {ps4,ps5,ps6,ps7}, [ad+16];\n"
        "mbarrier.try_wait.parity.shared::cta.b64 pw, [so+174992], ph;\n"
        "mbarrier.try_wait.parity.shared::cta.b64 px, [so+174976], ph;\n"
        "and.pred pw, pw, px;\n"
        "N0:\n"
        "@!pw bra.uni SPIN;\n"
        "BACK:\n"
        "add.u32 ad, %0, so; ld.shared.v4.b32 {pv0,pv1,pv2,pv3}, [ad+0];\n"
        "add.u32 ad, %1, so; ld.shared.v2.b32 {pv4,pv5}, [ad+0];\n"
        "add.u32 ad, %0, so; ld.shared.v4.b32 {pv6,pv7,pv8,pv9}, [ad+192];\n"
        "add.u32 ad, %1, so; ld.shared.v2.b32 {pv10,pv11}, [ad+192];\n"
        "mov.b32 {xl, xh}, ps0; mov.b32 rr, {xl, xl}; mov.b32 mm, {xh, xh}; fma.rn.bf16x2 pa0, pa0, rr, mm; fma.rn.bf16x2 pa1, pa1, rr, mm; fma.rn.bf16x2 pa2, pa2, rr, mm; fma.rn.bf16x2 pa3, pa3, rr, mm; fma.rn.bf16x2 pa4, pa4, rr, mm; fma.rn.bf16x2 pa5, pa5, rr, mm;\n"
        "and.b32 m0, pa0, 0x7fff7fff; and.b32 m1, pa1, 0x7fff7fff; and.b32 m2, pa2, 0x7fff7fff; and.b32 m3, pa3, 0x7fff7fff; and.b32 m4, pa4, 0x7fff7fff; and.b32 m5, pa5, 0x7fff7fff;\n"
        "mad.lo.u32 y0, m0, 7, pa0; mad.lo.u32 y1, m1, 7, pa1; mad.lo.u32 y2, m2, 7, pa2; mad.lo.u32 y3, m3, 7, pa3; mad.lo.u32 y4, m4, 7, pa4; mad.lo.u32 y5, m5, 7, pa5;\n"
        "add.u32 ad, %2, so; st.shared.v4.b32 [ad+0], {y0,y1,y2,y3};\n"
        "add.u32 ad, %4, so; st.shared.v2.b32 [ad+0], {y4,y5};\n"
        "N1:\n"
        "add.u32 ad, %0, so; ld.shared.v4.b32 {pv12,pv13,pv14,pv15}, [ad+384];\n"
        "add.u32 ad, %1, so; ld.shared.v2.b32 {pv16,pv17}, [ad+384];\n"
        "add.u32 ad, %0, so; ld.shared.v4.b32 {pv18,pv19,pv20,pv21}, [ad+576];\n"
        "add.u32 ad, %1, so; ld.shared.v2.b32 {pv22,pv23}, [ad+576];\n"
        "mov.b32 {xl, xh}, ps2; mov.b32 rr, {xl, xl}; mov.b32 mm, {xh, xh}; fma.rn.bf16x2 pa6, pa6, rr, mm; fma.rn.bf16x2 pa7, pa7, rr, mm; fma.rn.bf16x2 pa8, pa8, rr, mm; fma.rn.bf16x2 pa9, pa9, rr, mm; fma.rn.bf16x2 pa10, pa10, rr, mm; fma.rn.bf16x2 pa11, pa11, rr, mm;\n"
        "and.b32 m0, pa6, 0x7fff7fff; and.b32 m1, pa7, 0x7fff7fff; and.b32 m2, pa8, 0x7fff7fff; and.b32 m3, pa9, 0x7fff7fff; and.b32 m4, pa10, 0x7fff7fff; and.b32 m5, pa11, 0x7fff7fff;\n"
        "mad.lo.u32 y0, m0, 7, pa6; mad.lo.u32 y1, m1, 7, pa7; mad.lo.u32 y2, m2, 7, pa8; mad.lo.u32 y3, m3, 7, pa9; mad.lo.u32 y4, m4, 7, pa10; mad.lo.u32 y5, m5, 7, pa11;\n"
        "add.u32 ad, %3, so; st.shared.v4.b32 [ad+0], {y0,y1,y2,y3};\n"
        "add.u32 ad, %5, so; st.shared.v2.b32 [ad+0], {y4,y5};\n"
        "N2:\n"
        "add.u32 ad, %0, so; ld.shared.v4.b32 {pv24,pv25,pv26,pv27}, [ad+768];\n"
        "add.u32 ad, %1, so; ld.shared.v2.b32 {pv28,pv29}, [ad+768];\n"
        "mov.b32 {xl, xh}, ps4; mov.b32 rr, {xl, xl}; mov.b32 mm, {xh, xh}; fma.rn.bf16x2 pa12, pa12, rr, mm; fma.rn.bf16x2 pa13, pa13, rr, mm; fma.rn.bf16x2 pa14, pa14, rr, mm; fma.rn.bf16x2 pa15, pa15, rr, mm; fma.rn.bf16x2 pa16, pa16, rr, mm; fma.rn.bf16x2 pa17, pa17, rr, mm;\n"
        "and.b32 m0, pa12, 0x7fff7fff; and.b32 m1, pa13, 0x7fff7fff; and.b32 m2, pa14, 0x7fff7fff; and.b32 m3, pa15, 0x7fff7fff; and.b32 m4, pa16, 0x7fff7fff; and.b32 m5, pa17, 0x7fff7fff;\n"
        "mad.lo.u32 y0, m0, 7, pa12; mad.lo.u32 y1, m1, 7, pa13; mad.lo.u32 y2, m2, 7, pa14; mad.lo.u32 y3, m3, 7, pa15; mad.lo.u32 y4, m4, 7, pa16; mad.lo.u32 y5, m5, 7, pa17;\n"
        "add.u32 ad, %2, so; st.shared.v4.b32 [ad+2048], {y0,y1,y2,y3};\n"
        "add.u32 ad, %4, so; st.shared.v2.b32 [ad+1024], {y4,y5};\n"
        "N3:\n"
        "add.u32 ad, %0, so; ld.shared.v4.b32 {pv30,pv31,pv32,pv33}, [ad+960];\n"
        "add.u32 ad, %1, so; ld.shared.v2.b32 {pv34,pv35}, [ad+960];\n"
        "mov.b32 {xl, xh}, ps6; mov.b32 rr, {xl, xl}; mov.b32 mm, {xh, xh}; fma.rn.bf16x2 pa18, pa18, rr, mm; fma.rn.bf16x2 pa19, pa19, rr, mm; fma.rn.bf16x2 pa20, pa20, rr, mm; fma.rn.bf16x2 pa21, pa21, rr, mm; fma.rn.bf16x2 pa22, pa22, rr, mm; fma.rn.bf16x2 pa23, pa23, rr, mm;\n"
        "and.b32 m0, pa18, 0x7fff7fff; and.b32 m1, pa19, 0x7fff7fff; and.b32 m2, pa20, 0x7fff7fff; and.b32 m3, pa21, 0x7fff7fff; and.b32 m4, pa22, 0x7fff7fff; and.b32 m5, pa23, 0x7fff7fff;\n"
        "mad.lo.u32 y0, m0, 7, pa18; mad.lo.u32 y1, m1, 7, pa19; mad.lo.u32 y2, m2, 7, pa20; mad.lo.u32 y3, m3, 7, pa21; mad.lo.u32 y4, m4, 7, pa22; mad.lo.u32 y5, m5, 7, pa23;\n"
        "add.u32 ad, %3, so; st.shared.v4.b32 [ad+2048], {y0,y1,y2,y3};\n"
        "add.u32 ad, %5, so; st.shared.v2.b32 [ad+1024], {y4,y5};\n"
        "mov.u32 sp, so; add.u32 so, so, 26624; setp.eq.u32 pr, so, 79872; selp.u32 so, 0, so, pr; selp.u32 tt, 1, 0, pr; xor.b32 ph, ph, tt;\n"
        "add.u32 t, t, 1; setp.lt.u32 pe, t, 32;\n"
        "@pe bra.uni LOOP;\n"
        "bra.uni DONE;\n"
        "SPIN: mov.u32 cnt, 0;\n"
        ASM_TRC("t", 1)
        "SPINL:\n"
        "mbarrier.try_wait.parity.shared::cta.b64 pw, [so+174992], ph;\n"
        "mbarrier.try_wait.parity.shared::cta.b64 px, [so+174976], ph;\n"
        "and.pred pw, pw, px;\n"
        "@pw bra.uni BACK;\n"
        "add.u32 cnt, cnt, 1; setp.lt.u32 pw, cnt, 0x100000;\n"
        "@pw bra.uni SPINL;\n"
        "trap;\n"
        "RARE:\n"
        "ld.volatile.shared.u32 tt, [%6];\n"
        "mov.b32 pa0, tt; mov.b32 pa1, tt; mov.b32 pa2, tt; mov.b32 pa3, tt; mov.b32 pa4, tt; mov.b32 pa5, tt; mov.b32 pa6, tt; mov.b32 pa7, tt; mov.b32 pa8, tt; mov.b32 pa9, tt; mov.b32 pa10, tt; mov.b32 pa11, tt;\n"
        "mov.b32 pa12, tt; mov.b32 pa13, tt; mov.b32 pa14, tt; mov.b32 pa15, tt; mov.b32 pa16, tt; mov.b32 pa17, tt; mov.b32 pa18, tt; mov.b32 pa19, tt; mov.b32 pa20, tt; mov.b32 pa21, tt; mov.b32 pa22, tt; mov.b32 pa23, tt;\n"
        "mov.b32 pb0, tt; mov.b32 pb1, tt; mov.b32 pb2, tt; mov.b32 pb3, tt; mov.b32 pb4, tt; mov.b32 pb5, tt; mov.b32 pb6, tt; mov.b32 pb7, tt; mov.b32 pb8, tt; mov.b32 pb9, tt; mov.b32 pb10, tt; mov.b32 pb11, tt;\n"
        "mov.b32 pb12, tt; mov.b32 pb13, tt; mov.b32 pb14, tt; mov.b32 pb15, tt; mov.b32 pb16, tt; mov.b32 pb17, tt; mov.b32 pb18, tt; mov.b32 pb19, tt; mov.b32 pb20, tt; mov.b32 pb21, tt; mov.b32 pb22, tt; mov.b32 pb23, tt;\n"
        "mov.b32 pc0, tt; mov.b32 pc1, tt; mov.b32 pc2, tt; mov.b32 pc3, tt; mov.b32 pc4, tt; mov.b32 pc5, tt; mov.b32 pc6, tt; mov.b32 pc7, tt; mov.b32 pc8, tt; mov.b32 pc9, tt; mov.b32 pc10, tt; mov.b32 pc11, tt;\n"
        "mov.b32 pc12, tt; mov.b32 pc13, tt; mov.b32 pc14, tt; mov.b32 pc15, tt; mov.b32 pc16, tt; mov.b32 pc17, tt; mov.b32 pc18, tt; mov.b32 pc19, tt; mov.b32 pc20, tt; mov.b32 pc21, tt; mov.b32 pc22, tt; mov.b32 pc23, tt;\n"
        "mov.b32 pv0, tt; mov.b32 pv1, tt; mov.b32 pv2, tt; mov.b32 pv3, tt; mov.b32 pv4, tt; mov.b32 pv5, tt; mov.b32 pv6, tt; mov.b32 pv7, tt; mov.b32 pv8, tt; mov.b32 pv9, tt; mov.b32 pv10, tt; mov.b32 pv11, tt;\n"
        "mov.b32 pv12, tt; mov.b32 pv13, tt; mov.b32 pv14, tt; mov.b32 pv15, tt; mov.b32 pv16, tt; mov.b32 pv17, tt; mov.b32 pv18, tt; mov.b32 pv19, tt; mov.b32 pv20, tt; mov.b32 pv21, tt; mov.b32 pv22, tt; mov.b32 pv23, tt;\n"
        "mov.b32 pv24, tt; mov.b32 pv25, tt; mov.b32 pv26, tt; mov.b32 pv27, tt; mov.b32 pv28, tt; mov.b32 pv29, tt; mov.b32 pv30, tt; mov.b32 pv31, tt; mov.b32 pv32, tt; mov.b32 pv33, tt; mov.b32 pv34, tt; mov.b32 pv35, tt;\n"
        "mov.b32 ps0, tt; mov.b32 ps1, tt; mov.b32 ps2, tt; mov.b32 ps3, tt; mov.b32 ps4, tt; mov.b32 ps5, tt; mov.b32 ps6, tt; mov.b32 ps7, tt; mov.b32 pq0, tt; mov.b32 pq1, tt; mov.b32 pq2, tt; mov.b32 pq3, tt;\n"
        "mov.b32 m0, tt; mov.b32 m1, tt; mov.b32 m2, tt; mov.b32 m3, tt; mov.b32 m4, tt; mov.b32 m5, tt; mov.b32 y0, tt; mov.b32 y1, tt; mov.b32 y2, tt; mov.b32 y3, tt; mov.b32 y4, tt; mov.b32 y5, tt;\n"
        "mov.b32 us, tt; setp.ne.u32 pw, t, 7;\n"
        "wgmma.fence.sync.aligned;\n"
        "setp.eq.u32 pr, t, 1000; @pr bra.uni B0;\n"
        "setp.eq.u32 pr, t, 1001; @pr bra.uni B1;\n"
        "setp.eq.u32 pr, t, 1002; @pr bra.uni C0;\n"
        "setp.eq.u32 pr, t, 1003; @pr bra.uni N0;\n"
        "setp.eq.u32 pr, t, 1004; @pr bra.uni N1;\n"
        "setp.eq.u32 pr, t, 1005; @pr bra.uni N2;\n"
        "setp.eq.u32 pr, t, 1006; @pr bra.uni N3;\n"
        "trap;\n"
        "DONE:\n"
        ASM_TRC("t", 0)
        "fence.proxy.async.shared::cta;\n"
        "@pl mbarrier.arrive.shared::cta.b64 _, [sp+174984];\n"
        "}\n"
        :: "r"(sb + SM_X + c.xoff[0]), "r"(sb + SM_X + c.xoff[1]), "r"(sb + SM_Y1 + c.yoff[0][0]), "r"(sb + SM_Y1 + c.yoff[0][1]),
           "r"(sb + SM_Y1 + c.yoff[1][0]), "r"(sb + SM_Y1 + c.yoff[1][1]), "r"(c.stat), "r"(c.own), "r"(c.lane),
           "l"(prm.sel[0]), "l"(prm.sel[1]), "l"(prm.sel[2]), "r"(prm.ydesc), "f"(LN_EPS_SCALED), "f"(RSTD_SCALE)
        : "memory");
}

__device__ __forceinline__ void produce(const Producer& c, const Params& prm) {
    uint32_t A[24], B[24], C[24];
    const RowCopy rc = row_copy(prm);
    uint32_t st[8];
    uint32_t v[6][6];
    float d[4];
    {
        uint32_t ws[6], q[4] = {};
#pragma unroll
        for (int u = 0; u < 6; u++) {
            ws[u] = c.w[0][u];
#pragma unroll
            for (int t = 1; t < 9; t++) ws[u] = bf2_add(ws[u], c.w[t][u]);
        }
        mbar_wait_c<0>(sb + SM_XFULL + rc.first * SLOT_BYTES);
        load_x(v, c, sb + SM_X + rc.first * SLOT_BYTES);
#pragma unroll
        for (int r = 0; r < 24; r++) A[r] = bf2_mul(v[r / 6 + 1][r % 6], ws[r % 6]);
        start_sums(d, A, q, prm);
        float e, sq;
        finish_sums(d, c.lane, e, sq);
        e *= -1.0f / CH;
#pragma unroll
        for (int k = 0; k < NX; k++) sts32(c.own + k * SLOT_BYTES + 4, pack_bf2(e, e));
        __syncwarp();
        lds128(st, c.stat);
        lds128(st + 4, c.stat + 16);
#pragma unroll
        for (int r = 0; r < 24; r++) C[r] = 0;
    }
#pragma unroll 1
    for (int i = loop_init<0>();; i++) {
        mbar_wait_c<0>(sb + SM_XFULL + i * SLOT_BYTES);
        load_x(v, c, sb + SM_X + i * SLOT_BYTES);
        fence_async_smem();
        if (c.warp == i) {
            named_sync(6 + i, 128);
            issue_row_load(rc, i + NX, i);
        } else {
            asm volatile("bar.arrive %0, 128;" ::"r"(6 + i) : "memory");
        }
        if (i == 2) break;
        conv_row<1, 1>(B, C, v, c);
        conv_row<0, 0>(C, st, v, c);
    }
    if (c.warp == 3) {
        expect_tx(sb + SM_BAR + BAR_W2 * 8, CH * EX * 2 + EX * 4);
        bulk_load(sb + SM_GAMMA, prm.gamma, EX * 2, sb + SM_BAR + BAR_W2 * 8);
        bulk_load(sb + SM_BETA, prm.beta, EX * 2, sb + SM_BAR + BAR_W2 * 8);
#pragma unroll
        for (int k = 0; k < 6; k++)
            tma_load_2d(sb + SM_W2 + k * 12288, &prm.w2_map, 32 * (k >> 1), 192 * (k & 1), sb + SM_BAR + BAR_W2 * 8);
    }
    asm volatile(".reg .b32 pw<54>, pb<24>, pc<24>, pv<36>, ps<8>;");
    hand_over<0>(c, B, C, v);
    asm volatile("mov.b32 ps1, %0; mov.b32 ps3, %1; mov.b32 ps5, %2; mov.b32 ps7, %3;" ::"r"(st[1]), "r"(st[3]), "r"(st[5]), "r"(st[7]));
    produce_tiles(c, prm);
    mbar_arrive_if(sb + SM_Y1FULL + ROWS_PER_CTA % NX * SLOT_BYTES, c.lane == 0);
}

struct Duty {
    const char* g;
    uint32_t s, bytes;
    int end, zero;
};
__device__ __forceinline__ Duty make_duty(const Params& prm, int wg, int w) {
    const RowCopy rc = row_copy(prm);
    Duty d;
    d.g = (w == 2 ? rc.y0 : rc.x0 + 2 * NX * ROW_BYTES + (w == 0 ? rc.cut0 : w == 1 ? 32 * 192 : 192 + L2_AHEAD * ROW_BYTES)) +
          (uint32_t)wg * ROW_BYTES;
    d.s = wg * SLOT_BYTES + (w == 2 ? sb + SM_Y1 : sb + SM_X + (w == 0 ? rc.cut0 : XHALF_B));
    d.bytes = w >= 2 ? TILE_BYTES : XHALF_BYTES - (w == 0 ? rc.cut0 : rc.cut1);
    d.end = w == 2 ? ROWS_PER_CTA : w < 2 ? STEPS + 1 - 2 * NX : rc.last + 1 - 2 * NX - L2_AHEAD;
    d.zero = rc.last + 1 - 2 * NX;
    return d;
}

static_assert(sb + SM_Y1FULL == 174984 && sb + SM_Y1EMPTY == 174992 && sb + SM_XFULL == 174976 && SLOT_BYTES == 26624, "layout");
__device__ __forceinline__ void consume(float (&acc)[2][2], uint32_t w1t, uint32_t yd, uint32_t wd, uint32_t own_slot, const Duty& d,
                                        uint32_t role, uint32_t lane) {
    asm volatile(
        "{\n"
        ".reg .b32 z<32>, w<44>, p<2>, a<4>, lo<4>, hi<4>, t<2>, g<2>, q<4>, n, so, sp, ph, c, tt, cnt;\n"
        ".reg .b16 xl, xh, xr;\n"
        ".reg .f32 f0, f1;\n"
        ".reg .b64 ds<6>, wd, gp, src;\n"
        ".reg .pred pt, pf, pr, pw, pl, pe;\n"
        "setp.ne.b32 pt, 1, 0; setp.ne.b32 pf, 0, 0; setp.eq.u32 pl, %15, 0;\n"
        "mov.b32 c, 0x40D940D9;\n"
        "ldmatrix.sync.aligned.m8n8.x4.trans.shared.b16 {w0,w1,w2,w3}, [%4+0];\n"
        "ldmatrix.sync.aligned.m8n8.x4.trans.shared.b16 {w4,w5,w6,w7}, [%4+2048];\n"
        "ldmatrix.sync.aligned.m8n8.x4.trans.shared.b16 {w8,w9,w10,w11}, [%4+4096];\n"
        "ldmatrix.sync.aligned.m8n8.x4.trans.shared.b16 {w12,w13,w14,w15}, [%4+6144];\n"
        "ldmatrix.sync.aligned.m8n8.x4.trans.shared.b16 {w16,w17,w18,w19}, [%4+8192];\n"
        "ldmatrix.sync.aligned.m8n8.x4.trans.shared.b16 {w20,w21,w22,w23}, [%4+10240];\n"
        "ldmatrix.sync.aligned.m8n8.x4.trans.shared.b16 {w24,w25,w26,w27}, [%4+12288];\n"
        "ldmatrix.sync.aligned.m8n8.x4.trans.shared.b16 {w28,w29,w30,w31}, [%4+14336];\n"
        "ldmatrix.sync.aligned.m8n8.x4.trans.shared.b16 {w32,w33,w34,w35}, [%4+16384];\n"
        "ldmatrix.sync.aligned.m8n8.x4.trans.shared.b16 {w36,w37,w38,w39}, [%4+18432];\n"
        "ldmatrix.sync.aligned.m8n8.x4.trans.shared.b16 {w40,w41,w42,w43}, [%4+20480];\n"
        "mov.b32 p0, 0; mov.b32 p1, 0; mov.b32 t0, 0; mov.b32 t1, 0; mov.b32 g0, 0; mov.b32 g1, 0; mov.b32 a0, 0; mov.b32 a1, 0; mov.b32 lo0, 0; mov.b32 lo1, 0; mov.b32 hi0, 0; mov.b32 hi1, 0; mov.b32 q0, 0; mov.b32 q1, 0; mov.b32 q2, 0; mov.b32 q3, 0;\n"
        "mov.b32 z16, 0; mov.b32 z17, 0; mov.b32 z18, 0; mov.b32 z19, 0; mov.b32 z20, 0; mov.b32 z21, 0; mov.b32 z22, 0; mov.b32 z23, 0; mov.b32 z24, 0; mov.b32 z25, 0; mov.b32 z26, 0; mov.b32 z27, 0; mov.b32 z28, 0; mov.b32 z29, 0; mov.b32 z30, 0; mov.b32 z31, 0;\n"
        "mov.f32 %0, 0f00000000; mov.f32 %1, 0f00000000; mov.f32 %2, 0f00000000; mov.f32 %3, 0f00000000;\n"
        "mov.u32 n, 0; mov.u32 so, 0; mov.u32 sp, 0; mov.u32 ph, 0; mov.b64 gp, %8; mov.b64 wd, {%6, 0x40000040};\n"
        "shr.u32 tt, so, 4; add.u32 tt, tt, %5; mov.b64 ds0, {tt, 0x40000040}; mov.b64 ds4, {tt, 0x80000020};\n"
        "add.s64 ds1, ds0, 2; add.s64 ds2, ds0, 4; add.s64 ds3, ds0, 6; add.s64 ds5, ds4, 514; add.s64 ds4, ds4, 512;\n"
        "mbarrier.try_wait.parity.shared::cta.b64 pw, [so+174984], ph;\n"
        "@!pw bra.uni SPIN0;\n"
        "BACK0:\n"
        ASM_TS
        "wgmma.fence.sync.aligned;\n"
        "wgmma.mma_async.sync.aligned.m64n64k16.f16.f16.f16 {z0,z1,z2,z3,z4,z5,z6,z7,z8,z9,z10,z11,z12,z13,z14,z15}, {w0,w1,w2,w3}, ds0, pf, 1, 1, 0;\n"
        "wgmma.mma_async.sync.aligned.m64n64k16.f16.f16.f16 {z0,z1,z2,z3,z4,z5,z6,z7,z8,z9,z10,z11,z12,z13,z14,z15}, {w4,w5,w6,w7}, ds1, pt, 1, 1, 0;\n"
        "wgmma.mma_async.sync.aligned.m64n64k16.f16.f16.f16 {z0,z1,z2,z3,z4,z5,z6,z7,z8,z9,z10,z11,z12,z13,z14,z15}, {w8,w9,w10,w11}, ds2, pt, 1, 1, 0;\n"
        "wgmma.mma_async.sync.aligned.m64n64k16.f16.f16.f16 {z0,z1,z2,z3,z4,z5,z6,z7,z8,z9,z10,z11,z12,z13,z14,z15}, {w12,w13,w14,w15}, ds3, pt, 1, 1, 0;\n"
        "wgmma.mma_async.sync.aligned.m64n64k16.f16.f16.f16 {z0,z1,z2,z3,z4,z5,z6,z7,z8,z9,z10,z11,z12,z13,z14,z15}, {w16,w17,w18,w19}, ds4, pt, 1, 1, 0;\n"
        "wgmma.mma_async.sync.aligned.m64n64k16.f16.f16.f16 {z0,z1,z2,z3,z4,z5,z6,z7,z8,z9,z10,z11,z12,z13,z14,z15}, {w20,w21,w22,w23}, ds5, pt, 1, 1, 0;\n"
        "wgmma.commit_group.sync.aligned;\n"
        "LOOP:\n"
        ASM_TRC("n", 0)
        "setp.eq.u32 pr, so, %7;\n"
        "@pr bra.uni DUTY;\n"
        "TOP:\n"
        "wgmma.wait_group.sync.aligned 0;\n"
        "mov.b32 {xl, xh}, a0; tanh.approx.f16 xr, xl; cvt.u32.u16 lo0, xr; tanh.approx.f16 xr, xh; cvt.u32.u16 hi0, xr; fma.rn.f16x2 p0, z0, z0, c; mul.rn.f16x2 a1, z31, p1; fma.rn.f16x2 q3, g1, g1, q3; fma.rn.f16x2 g0, z28, t0, z28; prmt.b32 t1, lo1, hi1, 0x5410;\n"
        "B31:\n"
        "mov.b32 {xl, xh}, a1; tanh.approx.f16 xr, xl; cvt.u32.u16 lo1, xr; tanh.approx.f16 xr, xh; cvt.u32.u16 hi1, xr; fma.rn.f16x2 p1, z1, z1, c; mul.rn.f16x2 a0, z0, p0; fma.rn.f16x2 q2, g0, g0, q2; fma.rn.f16x2 g1, z29, t1, z29; prmt.b32 t0, lo0, hi0, 0x5410;\n"
        "B0:\n"
        "mov.b32 {xl, xh}, a0; tanh.approx.f16 xr, xl; cvt.u32.u16 lo0, xr; tanh.approx.f16 xr, xh; cvt.u32.u16 hi0, xr; fma.rn.f16x2 p0, z2, z2, c; mul.rn.f16x2 a1, z1, p1; fma.rn.f16x2 q3, g1, g1, q3; fma.rn.f16x2 g0, z30, t0, z30; prmt.b32 t1, lo1, hi1, 0x5410;\n"
        "B1:\n"
        "mov.b32 {xl, xh}, a1; tanh.approx.f16 xr, xl; cvt.u32.u16 lo1, xr; tanh.approx.f16 xr, xh; cvt.u32.u16 hi1, xr; fma.rn.f16x2 p1, z3, z3, c; mul.rn.f16x2 a0, z2, p0; fma.rn.f16x2 q2, g0, g0, q2; fma.rn.f16x2 g1, z31, t1, z31; prmt.b32 t0, lo0, hi0, 0x5410;\n"
        "B2:\n"
        "wgmma.fence.sync.aligned;\n"
        "wgmma.mma_async.sync.aligned.m64n64k16.f16.f16.f16 {z16,z17,z18,z19,z20,z21,z22,z23,z24,z25,z26,z27,z28,z29,z30,z31}, {w24,w25,w26,w27}, ds0, pf, 1, 1, 0;\n"
        "wgmma.mma_async.sync.aligned.m64n64k16.f16.f16.f16 {z16,z17,z18,z19,z20,z21,z22,z23,z24,z25,z26,z27,z28,z29,z30,z31}, {w28,w29,w30,w31}, ds1, pt, 1, 1, 0;\n"
        "wgmma.mma_async.sync.aligned.m64n64k16.f16.f16.f16 {z16,z17,z18,z19,z20,z21,z22,z23,z24,z25,z26,z27,z28,z29,z30,z31}, {w32,w33,w34,w35}, ds2, pt, 1, 1, 0;\n"
        "mov.b32 {xl, xh}, a0; tanh.approx.f16 xr, xl; cvt.u32.u16 lo0, xr; tanh.approx.f16 xr, xh; cvt.u32.u16 hi0, xr; fma.rn.f16x2 p0, z4, z4, c; mul.rn.f16x2 a1, z3, p1; fma.rn.f16x2 q3, g1, g1, q3; fma.rn.f16x2 g0, z0, t0, z0; prmt.b32 t1, lo1, hi1, 0x5410;\n"
        "B3:\n"
        "mov.b32 {xl, xh}, a1; tanh.approx.f16 xr, xl; cvt.u32.u16 lo1, xr; tanh.approx.f16 xr, xh; cvt.u32.u16 hi1, xr; fma.rn.f16x2 p1, z5, z5, c; mul.rn.f16x2 a0, z4, p0; fma.rn.f16x2 q0, g0, g0, q0; fma.rn.f16x2 g1, z1, t1, z1; prmt.b32 t0, lo0, hi0, 0x5410;\n"
        "B4:\n"
        "mov.b32 {xl, xh}, a0; tanh.approx.f16 xr, xl; cvt.u32.u16 lo0, xr; tanh.approx.f16 xr, xh; cvt.u32.u16 hi0, xr; fma.rn.f16x2 p0, z6, z6, c; mul.rn.f16x2 a1, z5, p1; fma.rn.f16x2 q1, g1, g1, q1; fma.rn.f16x2 g0, z2, t0, z2; prmt.b32 t1, lo1, hi1, 0x5410;\n"
        "B5:\n"
        "wgmma.mma_async.sync.aligned.m64n64k16.f16.f16.f16 {z16,z17,z18,z19,z20,z21,z22,z23,z24,z25,z26,z27,z28,z29,z30,z31}, {w36,w37,w38,w39}, ds3, pt, 1, 1, 0;\n"
        "wgmma.mma_async.sync.aligned.m64n64k16.f16.f16.f16 {z16,z17,z18,z19,z20,z21,z22,z23,z24,z25,z26,z27,z28,z29,z30,z31}, {w40,w41,w42,w43}, ds4, pt, 1, 1, 0;\n"
        "wgmma.mma_async.sync.aligned.m64n64k16.f16.f16.f16 {z16,z17,z18,z19,z20,z21,z22,z23,z24,z25,z26,z27,z28,z29,z30,z31}, wd, ds5, pt, 1, 1, 1, 0;\n"
        "wgmma.commit_group.sync.aligned;\n"
        "mov.b32 {xl, xh}, a1; tanh.approx.f16 xr, xl; cvt.u32.u16 lo1, xr; tanh.approx.f16 xr, xh; cvt.u32.u16 hi1, xr; fma.rn.f16x2 p1, z7, z7, c; mul.rn.f16x2 a0, z6, p0; fma.rn.f16x2 q0, g0, g0, q0; fma.rn.f16x2 g1, z3, t1, z3; prmt.b32 t0, lo0, hi0, 0x5410;\n"
        "B6:\n"
        "mov.u32 sp, so; add.u32 so, so, 26624; setp.eq.u32 pr, so, 79872; selp.u32 so, 0, so, pr; selp.u32 tt, 1, 0, pr; xor.b32 ph, ph, tt;\n"
        "mov.b32 {xl, xh}, a0; tanh.approx.f16 xr, xl; cvt.u32.u16 lo0, xr; tanh.approx.f16 xr, xh; cvt.u32.u16 hi0, xr; fma.rn.f16x2 p0, z8, z8, c; mul.rn.f16x2 a1, z7, p1; fma.rn.f16x2 q1, g1, g1, q1; fma.rn.f16x2 g0, z4, t0, z4; prmt.b32 t1, lo1, hi1, 0x5410;\n"
        "B7:\n"
        "shr.u32 tt, so, 4; add.u32 tt, tt, %5; mov.b64 ds0, {tt, 0x40000040}; mov.b64 ds4, {tt, 0x80000020};\n"
        "add.s64 ds1, ds0, 2; add.s64 ds2, ds0, 4; add.s64 ds3, ds0, 6; add.s64 ds5, ds4, 514; add.s64 ds4, ds4, 512;\n"
        "mov.b32 {xl, xh}, a1; tanh.approx.f16 xr, xl; cvt.u32.u16 lo1, xr; tanh.approx.f16 xr, xh; cvt.u32.u16 hi1, xr; fma.rn.f16x2 p1, z9, z9, c; mul.rn.f16x2 a0, z8, p0; fma.rn.f16x2 q0, g0, g0, q0; fma.rn.f16x2 g1, z5, t1, z5; prmt.b32 t0, lo0, hi0, 0x5410;\n"
        "B8:\n"
        "mov.b32 {xl, xh}, a0; tanh.approx.f16 xr, xl; cvt.u32.u16 lo0, xr; tanh.approx.f16 xr, xh; cvt.u32.u16 hi0, xr; fma.rn.f16x2 p0, z10, z10, c; mul.rn.f16x2 a1, z9, p1; fma.rn.f16x2 q1, g1, g1, q1; fma.rn.f16x2 g0, z6, t0, z6; prmt.b32 t1, lo1, hi1, 0x5410;\n"
        "B9:\n"
        "mov.b32 {xl, xh}, a1; tanh.approx.f16 xr, xl; cvt.u32.u16 lo1, xr; tanh.approx.f16 xr, xh; cvt.u32.u16 hi1, xr; fma.rn.f16x2 p1, z11, z11, c; mul.rn.f16x2 a0, z10, p0; fma.rn.f16x2 q0, g0, g0, q0; fma.rn.f16x2 g1, z7, t1, z7; prmt.b32 t0, lo0, hi0, 0x5410;\n"
        "B10:\n"
        "mov.b32 {xl, xh}, a0; tanh.approx.f16 xr, xl; cvt.u32.u16 lo0, xr; tanh.approx.f16 xr, xh; cvt.u32.u16 hi0, xr; fma.rn.f16x2 p0, z12, z12, c; mul.rn.f16x2 a1, z11, p1; fma.rn.f16x2 q1, g1, g1, q1; fma.rn.f16x2 g0, z8, t0, z8; prmt.b32 t1, lo1, hi1, 0x5410;\n"
        "B11:\n"
        "mov.b32 {xl, xh}, a1; tanh.approx.f16 xr, xl; cvt.u32.u16 lo1, xr; tanh.approx.f16 xr, xh; cvt.u32.u16 hi1, xr; fma.rn.f16x2 p1, z13, z13, c; mul.rn.f16x2 a0, z12, p0; fma.rn.f16x2 q0, g0, g0, q0; fma.rn.f16x2 g1, z9, t1, z9; prmt.b32 t0, lo0, hi0, 0x5410;\n"
        "B12:\n"
        "mov.b32 {xl, xh}, a0; tanh.approx.f16 xr, xl; cvt.u32.u16 lo0, xr; tanh.approx.f16 xr, xh; cvt.u32.u16 hi0, xr; fma.rn.f16x2 p0, z14, z14, c; mul.rn.f16x2 a1, z13, p1; fma.rn.f16x2 q1, g1, g1, q1; fma.rn.f16x2 g0, z10, t0, z10; prmt.b32 t1, lo1, hi1, 0x5410;\n"
        "B13:\n"
        "mov.b32 {xl, xh}, a1; tanh.approx.f16 xr, xl; cvt.u32.u16 lo1, xr; tanh.approx.f16 xr, xh; cvt.u32.u16 hi1, xr; fma.rn.f16x2 p1, z15, z15, c; mul.rn.f16x2 a0, z14, p0; fma.rn.f16x2 q0, g0, g0, q0; fma.rn.f16x2 g1, z11, t1, z11; prmt.b32 t0, lo0, hi0, 0x5410;\n"
        "B14:\n"
        "wgmma.wait_group.sync.aligned 0;\n"
        "cp.async.bulk.wait_group.read 0;\n"
        "@pl mbarrier.arrive.shared::cta.b64 _, [sp+174992];\n"
        "mov.b32 {xl, xh}, a0; tanh.approx.f16 xr, xl; cvt.u32.u16 lo0, xr; tanh.approx.f16 xr, xh; cvt.u32.u16 hi0, xr; fma.rn.f16x2 p0, z16, z16, c; mul.rn.f16x2 a1, z15, p1; fma.rn.f16x2 q1, g1, g1, q1; fma.rn.f16x2 g0, z12, t0, z12; prmt.b32 t1, lo1, hi1, 0x5410;\n"
        "B15:\n"
        "mbarrier.try_wait.parity.shared::cta.b64 pw, [so+174984], ph;\n"
        "mov.b32 {xl, xh}, a1; tanh.approx.f16 xr, xl; cvt.u32.u16 lo1, xr; tanh.approx.f16 xr, xh; cvt.u32.u16 hi1, xr; fma.rn.f16x2 p1, z17, z17, c; mul.rn.f16x2 a0, z16, p0; fma.rn.f16x2 q0, g0, g0, q0; fma.rn.f16x2 g1, z13, t1, z13; prmt.b32 t0, lo0, hi0, 0x5410;\n"
        "B16:\n"
        "mov.b32 {xl, xh}, a0; tanh.approx.f16 xr, xl; cvt.u32.u16 lo0, xr; tanh.approx.f16 xr, xh; cvt.u32.u16 hi0, xr; fma.rn.f16x2 p0, z18, z18, c; mul.rn.f16x2 a1, z17, p1; fma.rn.f16x2 q1, g1, g1, q1; fma.rn.f16x2 g0, z14, t0, z14; prmt.b32 t1, lo1, hi1, 0x5410;\n"
        "B17:\n"
        "mov.b32 {xl, xh}, a1; tanh.approx.f16 xr, xl; cvt.u32.u16 lo1, xr; tanh.approx.f16 xr, xh; cvt.u32.u16 hi1, xr; fma.rn.f16x2 p1, z19, z19, c; mul.rn.f16x2 a0, z18, p0; fma.rn.f16x2 q0, g0, g0, q0; fma.rn.f16x2 g1, z15, t1, z15; prmt.b32 t0, lo0, hi0, 0x5410;\n"
        "B18:\n"
        "@!pw bra.uni SPIN;\n"
        "BACK:\n"
        "wgmma.fence.sync.aligned;\n"
        "wgmma.mma_async.sync.aligned.m64n64k16.f16.f16.f16 {z0,z1,z2,z3,z4,z5,z6,z7,z8,z9,z10,z11,z12,z13,z14,z15}, {w0,w1,w2,w3}, ds0, pf, 1, 1, 0;\n"
        "wgmma.mma_async.sync.aligned.m64n64k16.f16.f16.f16 {z0,z1,z2,z3,z4,z5,z6,z7,z8,z9,z10,z11,z12,z13,z14,z15}, {w4,w5,w6,w7}, ds1, pt, 1, 1, 0;\n"
        "wgmma.mma_async.sync.aligned.m64n64k16.f16.f16.f16 {z0,z1,z2,z3,z4,z5,z6,z7,z8,z9,z10,z11,z12,z13,z14,z15}, {w8,w9,w10,w11}, ds2, pt, 1, 1, 0;\n"
        "mov.b32 {xl, xh}, a0; tanh.approx.f16 xr, xl; cvt.u32.u16 lo0, xr; tanh.approx.f16 xr, xh; cvt.u32.u16 hi0, xr; fma.rn.f16x2 p0, z20, z20, c; mul.rn.f16x2 a1, z19, p1; fma.rn.f16x2 q1, g1, g1, q1; fma.rn.f16x2 g0, z16, t0, z16; prmt.b32 t1, lo1, hi1, 0x5410;\n"
        "B19:\n"
        "mov.b32 {xl, xh}, a1; tanh.approx.f16 xr, xl; cvt.u32.u16 lo1, xr; tanh.approx.f16 xr, xh; cvt.u32.u16 hi1, xr; fma.rn.f16x2 p1, z21, z21, c; mul.rn.f16x2 a0, z20, p0; fma.rn.f16x2 q2, g0, g0, q2; fma.rn.f16x2 g1, z17, t1, z17; prmt.b32 t0, lo0, hi0, 0x5410;\n"
        "B20:\n"
        "mov.b32 {xl, xh}, a0; tanh.approx.f16 xr, xl; cvt.u32.u16 lo0, xr; tanh.approx.f16 xr, xh; cvt.u32.u16 hi0, xr; fma.rn.f16x2 p0, z22, z22, c; mul.rn.f16x2 a1, z21, p1; fma.rn.f16x2 q3, g1, g1, q3; fma.rn.f16x2 g0, z18, t0, z18; prmt.b32 t1, lo1, hi1, 0x5410;\n"
        "B21:\n"
        "wgmma.mma_async.sync.aligned.m64n64k16.f16.f16.f16 {z0,z1,z2,z3,z4,z5,z6,z7,z8,z9,z10,z11,z12,z13,z14,z15}, {w12,w13,w14,w15}, ds3, pt, 1, 1, 0;\n"
        "wgmma.mma_async.sync.aligned.m64n64k16.f16.f16.f16 {z0,z1,z2,z3,z4,z5,z6,z7,z8,z9,z10,z11,z12,z13,z14,z15}, {w16,w17,w18,w19}, ds4, pt, 1, 1, 0;\n"
        "wgmma.mma_async.sync.aligned.m64n64k16.f16.f16.f16 {z0,z1,z2,z3,z4,z5,z6,z7,z8,z9,z10,z11,z12,z13,z14,z15}, {w20,w21,w22,w23}, ds5, pt, 1, 1, 0;\n"
        "wgmma.commit_group.sync.aligned;\n"
        "mov.b32 {xl, xh}, a1; tanh.approx.f16 xr, xl; cvt.u32.u16 lo1, xr; tanh.approx.f16 xr, xh; cvt.u32.u16 hi1, xr; fma.rn.f16x2 p1, z23, z23, c; mul.rn.f16x2 a0, z22, p0; fma.rn.f16x2 q2, g0, g0, q2; fma.rn.f16x2 g1, z19, t1, z19; prmt.b32 t0, lo0, hi0, 0x5410;\n"
        "B22:\n"
        "mov.b32 {xl, xh}, a0; tanh.approx.f16 xr, xl; cvt.u32.u16 lo0, xr; tanh.approx.f16 xr, xh; cvt.u32.u16 hi0, xr; fma.rn.f16x2 p0, z24, z24, c; mul.rn.f16x2 a1, z23, p1; fma.rn.f16x2 q3, g1, g1, q3; fma.rn.f16x2 g0, z20, t0, z20; prmt.b32 t1, lo1, hi1, 0x5410;\n"
        "B23:\n"
        "mov.b32 {xl, xh}, a1; tanh.approx.f16 xr, xl; cvt.u32.u16 lo1, xr; tanh.approx.f16 xr, xh; cvt.u32.u16 hi1, xr; fma.rn.f16x2 p1, z25, z25, c; mul.rn.f16x2 a0, z24, p0; fma.rn.f16x2 q2, g0, g0, q2; fma.rn.f16x2 g1, z21, t1, z21; prmt.b32 t0, lo0, hi0, 0x5410;\n"
        "B24:\n"
        "mov.b32 {xl, xh}, a0; tanh.approx.f16 xr, xl; cvt.u32.u16 lo0, xr; tanh.approx.f16 xr, xh; cvt.u32.u16 hi0, xr; fma.rn.f16x2 p0, z26, z26, c; mul.rn.f16x2 a1, z25, p1; fma.rn.f16x2 q3, g1, g1, q3; fma.rn.f16x2 g0, z22, t0, z22; prmt.b32 t1, lo1, hi1, 0x5410;\n"
        "B25:\n"
        "mov.b32 {xl, xh}, a1; tanh.approx.f16 xr, xl; cvt.u32.u16 lo1, xr; tanh.approx.f16 xr, xh; cvt.u32.u16 hi1, xr; fma.rn.f16x2 p1, z27, z27, c; mul.rn.f16x2 a0, z26, p0; fma.rn.f16x2 q2, g0, g0, q2; fma.rn.f16x2 g1, z23, t1, z23; prmt.b32 t0, lo0, hi0, 0x5410;\n"
        "B26:\n"
        "mov.b32 {xl, xh}, a0; tanh.approx.f16 xr, xl; cvt.u32.u16 lo0, xr; tanh.approx.f16 xr, xh; cvt.u32.u16 hi0, xr; fma.rn.f16x2 p0, z28, z28, c; mul.rn.f16x2 a1, z27, p1; fma.rn.f16x2 q3, g1, g1, q3; fma.rn.f16x2 g0, z24, t0, z24; prmt.b32 t1, lo1, hi1, 0x5410;\n"
        "B27:\n"
        "add.u32 n, n, 1; setp.lt.u32 pe, n, 32;\n"
        "mov.b32 {xl, xh}, a1; tanh.approx.f16 xr, xl; cvt.u32.u16 lo1, xr; tanh.approx.f16 xr, xh; cvt.u32.u16 hi1, xr; fma.rn.f16x2 p1, z29, z29, c; mul.rn.f16x2 a0, z28, p0; fma.rn.f16x2 q2, g0, g0, q2; fma.rn.f16x2 g1, z25, t1, z25; prmt.b32 t0, lo0, hi0, 0x5410;\n"
        "B28:\n"
        "mov.b32 {xl, xh}, a0; tanh.approx.f16 xr, xl; cvt.u32.u16 lo0, xr; tanh.approx.f16 xr, xh; cvt.u32.u16 hi0, xr; fma.rn.f16x2 p0, z30, z30, c; mul.rn.f16x2 a1, z29, p1; fma.rn.f16x2 q3, g1, g1, q3; fma.rn.f16x2 g0, z26, t0, z26; prmt.b32 t1, lo1, hi1, 0x5410;\n"
        "B29:\n"
        "mov.b32 {xl, xh}, a1; tanh.approx.f16 xr, xl; cvt.u32.u16 lo1, xr; tanh.approx.f16 xr, xh; cvt.u32.u16 hi1, xr; fma.rn.f16x2 p1, z31, z31, c; mul.rn.f16x2 a0, z30, p0; fma.rn.f16x2 q2, g0, g0, q2; fma.rn.f16x2 g1, z27, t1, z27; prmt.b32 t0, lo0, hi0, 0x5410;\n"
        "@pe bra.uni LOOP;\n"
        "bra.uni DONE;\n"
        "SPIN0: mov.u32 cnt, 0;\n"
        ASM_TRC("n", 1)
        "SPIN0L:\n"
        "mbarrier.try_wait.parity.shared::cta.b64 pw, [so+174984], ph;\n"
        "@pw bra.uni BACK0;\n"
        "add.u32 cnt, cnt, 1; setp.lt.u32 pw, cnt, 0x100000;\n"
        "@pw bra.uni SPIN0L;\n"
        "trap;\n"
        "SPIN: mov.u32 cnt, 0;\n"
        ASM_TRC("n", 1)
        "SPINL:\n"
        "mbarrier.try_wait.parity.shared::cta.b64 pw, [so+174984], ph;\n"
        "@pw bra.uni BACK;\n"
        "add.u32 cnt, cnt, 1; setp.lt.u32 pw, cnt, 0x100000;\n"
        "@pw bra.uni SPINL;\n"
        "trap;\n"
        "DUTY:\n"
        "setp.ge.s32 pr, n, %11;\n"
        "@pr bra.uni FLUSH;\n"
        "setp.ge.u32 pr, %13, 2;\n"
        "@pr bra.uni ROLE2;\n"
        "setp.ge.s32 pr, n, %12; selp.b64 src, %14, gp, pr; add.u32 tt, %7, 174976;\n"
        "elect.sync _|pr, 0xffffffff;\n"
        "@pr mbarrier.arrive.expect_tx.shared::cta.b64 _, [tt], %10;\n"
        "@pr cp.async.bulk.shared::cluster.global.mbarrier::complete_tx::bytes [%9], [src], %10, [tt];\n"
        "bra.uni FLUSH;\n"
        "ROLE2:\n"
        "setp.eq.u32 pr, %13, 3;\n"
        "@pr bra.uni ROLE3;\n"
        "elect.sync _|pr, 0xffffffff;\n"
        "@pr cp.async.bulk.global.shared::cta.bulk_group [gp], [%9], 12288;\n"
        "@pr cp.async.bulk.commit_group;\n"
        "bra.uni FLUSH;\n"
        "ROLE3:\n"
        "elect.sync _|pr, 0xffffffff;\n"
        "@pr cp.async.bulk.prefetch.L2.global [gp], 12288;\n"
        "FLUSH:\n"
        "add.s64 gp, gp, 294912;\n"
        "mov.b32 {xl, xh}, q0; cvt.f32.f16 f0, xl; cvt.f32.f16 f1, xh; add.f32 f0, f0, f1; add.f32 %0, %0, f0; mov.b32 q0, 0;\n"
        "mov.b32 {xl, xh}, q1; cvt.f32.f16 f0, xl; cvt.f32.f16 f1, xh; add.f32 f0, f0, f1; add.f32 %1, %1, f0; mov.b32 q1, 0;\n"
        "mov.b32 {xl, xh}, q2; cvt.f32.f16 f0, xl; cvt.f32.f16 f1, xh; add.f32 f0, f0, f1; add.f32 %2, %2, f0; mov.b32 q2, 0;\n"
        "mov.b32 {xl, xh}, q3; cvt.f32.f16 f0, xl; cvt.f32.f16 f1, xh; add.f32 f0, f0, f1; add.f32 %3, %3, f0; mov.b32 q3, 0;\n"
        "setp.ne.u32 pr, %5, 0;\n"
        "@pr bra.uni TOP;\n"
        "wgmma.wait_group.sync.aligned 0;\n"
        "wgmma.fence.sync.aligned;\n"
        "setp.eq.u32 pr, n, 1000; @pr bra.uni B31;\n"
        "setp.eq.u32 pr, n, 1001; @pr bra.uni B0;\n"
        "setp.eq.u32 pr, n, 1002; @pr bra.uni B1;\n"
        "setp.eq.u32 pr, n, 1003; @pr bra.uni B2;\n"
        "setp.eq.u32 pr, n, 1004; @pr bra.uni B3;\n"
        "setp.eq.u32 pr, n, 1005; @pr bra.uni B4;\n"
        "setp.eq.u32 pr, n, 1006; @pr bra.uni B5;\n"
        "setp.eq.u32 pr, n, 1007; @pr bra.uni B6;\n"
        "setp.eq.u32 pr, n, 1008; @pr bra.uni B7;\n"
        "setp.eq.u32 pr, n, 1009; @pr bra.uni B8;\n"
        "setp.eq.u32 pr, n, 1010; @pr bra.uni B9;\n"
        "setp.eq.u32 pr, n, 1011; @pr bra.uni B10;\n"
        "setp.eq.u32 pr, n, 1012; @pr bra.uni B11;\n"
        "setp.eq.u32 pr, n, 1013; @pr bra.uni B12;\n"
        "setp.eq.u32 pr, n, 1014; @pr bra.uni B13;\n"
        "setp.eq.u32 pr, n, 1015; @pr bra.uni B14;\n"
        "setp.eq.u32 pr, n, 1016; @pr bra.uni B15;\n"
        "setp.eq.u32 pr, n, 1017; @pr bra.uni B16;\n"
        "setp.eq.u32 pr, n, 1018; @pr bra.uni B17;\n"
        "setp.eq.u32 pr, n, 1019; @pr bra.uni B18;\n"
        "setp.eq.u32 pr, n, 1020; @pr bra.uni B19;\n"
        "setp.eq.u32 pr, n, 1021; @pr bra.uni B20;\n"
        "setp.eq.u32 pr, n, 1022; @pr bra.uni B21;\n"
        "setp.eq.u32 pr, n, 1023; @pr bra.uni B22;\n"
        "setp.eq.u32 pr, n, 1024; @pr bra.uni B23;\n"
        "setp.eq.u32 pr, n, 1025; @pr bra.uni B24;\n"
        "setp.eq.u32 pr, n, 1026; @pr bra.uni B25;\n"
        "setp.eq.u32 pr, n, 1027; @pr bra.uni B26;\n"
        "setp.eq.u32 pr, n, 1028; @pr bra.uni B27;\n"
        "setp.eq.u32 pr, n, 1029; @pr bra.uni B28;\n"
        "setp.eq.u32 pr, n, 1030; @pr bra.uni B29;\n"
        "trap;\n"
        "DONE:\n"
        ASM_TRC("n", 0)
        "mov.b32 {xl, xh}, a0; tanh.approx.f16 xr, xl; cvt.u32.u16 lo0, xr; tanh.approx.f16 xr, xh; cvt.u32.u16 hi0, xr; mul.rn.f16x2 a1, z31, p1; fma.rn.f16x2 q3, g1, g1, q3; fma.rn.f16x2 g0, z28, t0, z28; prmt.b32 t1, lo1, hi1, 0x5410;\n"
        "mov.b32 {xl, xh}, a1; tanh.approx.f16 xr, xl; cvt.u32.u16 lo1, xr; tanh.approx.f16 xr, xh; cvt.u32.u16 hi1, xr; fma.rn.f16x2 q2, g0, g0, q2; fma.rn.f16x2 g1, z29, t1, z29; prmt.b32 t0, lo0, hi0, 0x5410;\n"
        "fma.rn.f16x2 q3, g1, g1, q3; fma.rn.f16x2 g0, z30, t0, z30; prmt.b32 t1, lo1, hi1, 0x5410;\n"
        "fma.rn.f16x2 q2, g0, g0, q2; fma.rn.f16x2 g1, z31, t1, z31;\n"
        "fma.rn.f16x2 q3, g1, g1, q3;\n"
        "mov.b32 {xl, xh}, q0; cvt.f32.f16 f0, xl; cvt.f32.f16 f1, xh; add.f32 f0, f0, f1; add.f32 %0, %0, f0; mov.b32 q0, 0;\n"
        "mov.b32 {xl, xh}, q1; cvt.f32.f16 f0, xl; cvt.f32.f16 f1, xh; add.f32 f0, f0, f1; add.f32 %1, %1, f0; mov.b32 q1, 0;\n"
        "mov.b32 {xl, xh}, q2; cvt.f32.f16 f0, xl; cvt.f32.f16 f1, xh; add.f32 f0, f0, f1; add.f32 %2, %2, f0; mov.b32 q2, 0;\n"
        "mov.b32 {xl, xh}, q3; cvt.f32.f16 f0, xl; cvt.f32.f16 f1, xh; add.f32 f0, f0, f1; add.f32 %3, %3, f0; mov.b32 q3, 0;\n"
        "wgmma.wait_group.sync.aligned 0;\n"
        "}\n"
        : "=f"(acc[0][0]), "=f"(acc[0][1]), "=f"(acc[1][0]), "=f"(acc[1][1])
        : "r"(w1t), "r"(yd), "r"(wd), "r"(own_slot), "l"(d.g), "r"(d.s), "r"(d.bytes), "r"(d.end), "r"(d.zero), "r"(role),
          "l"(g_zero_row), "r"(lane)
        : "memory");
}
template <int M, bool LAST_SMEM = true>
__device__ __forceinline__ void gemm1_t(uint32_t (&d)[16], const uint32_t* wa, uint32_t yd, uint32_t wd) {
    wg_fence();
    wgmma_n64_h_set<0>(d, wa, desc<1024, 1>(yd, 0));
#pragma unroll
    for (int kk = 1; kk < (LAST_SMEM ? 5 : 6); kk++)
        wgmma_n64_h_acc<0>(d, wa + kk * 4, kk < 4 ? desc<1024, 1>(yd, kk * 32) : desc<512, 2>(yd, 8192 + (kk - 4) * 32));
    if (LAST_SMEM) wgmma_n64_h_acc_ss(d, desc<1024, 1>(wd, M * 12288), desc<512, 2>(yd, 8192 + 32));
    wg_commit();
}

#define GTAIL 0
__device__ __forceinline__ void gelu_sumsq_h(uint32_t (&d)[16], uint32_t (&q)[2], uint32_t key) {
#pragma unroll
    for (int r = 0; r < 16; r++) {
        if (GTAIL && r == 16 - GTAIL) sched_fence<GTAIL ? GTAIL : 2>(d + r, key);
        const uint32_t gv = gelu2(d[r]);
        q[r & 1] = h2_fma(gv, gv, q[r & 1]);
    }
}
__device__ __forceinline__ void flush_sumsq(uint32_t (&q)[2], float (&acc)[2]) {
#pragma unroll
    for (int h = 0; h < 2; h++) {
        float lo, hi;
        h2_unpack(q[h], lo, hi);
        acc[h] += lo + hi;
        q[h] = 0;
    }
}
__device__ __forceinline__ void gelu_sumsq_f(const uint32_t (&d)[16], float (&acc)[2]) {
#pragma unroll
    for (int r = 0; r < 16; r++) {
        float lo, hi;
        h2_unpack(gelu2(d[r]), lo, hi);
        acc[r & 1] = fmaf(lo, lo, acc[r & 1]);
        acc[r & 1] = fmaf(hi, hi, acc[r & 1]);
    }
}
__device__ __forceinline__ void load_w1t(uint32_t (&wa)[2][24], int wg, int w, int lane) {
#pragma unroll
    for (int m = 0; m < 2; m++)
#pragma unroll
        for (int kk = 0; kk < 5; kk++) {
            const int q = lane >> 3, c = 16 * kk + 8 * (q >> 1) + (lane & 7), ck = 2 * w + (q & 1);
            ldsm4_t(wa[m] + kk * 4, sb + SM_W1 + (2 * wg + m) * 12288 + c * 128 + ((ck ^ (c & 7)) * 16));
        }
}
__device__ __forceinline__ unsigned long long* acc_word(uint32_t epoch, uint32_t e) {
    return &g_acc[epoch & 1][(e >> 2) * 32 + (e & 3)];
}
__device__ __forceinline__ void publish_fast(const float (&acc)[2][2], uint32_t epoch, int wg, int w, int lane) {
    const bool m = lane & 2, h = lane & 1;
    const float a = (m ? acc[1][0] : acc[0][0]) + __shfl_xor_sync(0xffffffffu, m ? acc[0][0] : acc[1][0], 2);
    const float b = (m ? acc[1][1] : acc[0][1]) + __shfl_xor_sync(0xffffffffu, m ? acc[0][1] : acc[1][1], 2);
    const float v = (h ? b : a) + __shfl_xor_sync(0xffffffffu, h ? a : b, 1);
    const unsigned long long q = (__float2ull_rn(fminf(v, ACC_LIMIT) * 0x1p16f) << 8) + 1;
    asm volatile("red.relaxed.gpu.global.add.u64 [%0], %1;"
                 ::"l"(acc_word(epoch, 128 * wg + 32 * (lane & 2) + 16 * w + (lane >> 2) + 8 * (lane & 1))), "l"(q) : "memory");
}
__device__ __forceinline__ float collect_fast(const unsigned long long* word) {
    unsigned long long v;
    asm volatile(
        "{\n.reg .pred p;\n.reg .u32 n, lo, hi;\nmov.u32 n, 0;\n"
        "POLL:\nld.relaxed.gpu.global.u64 %0, [%1];\nmov.b64 {lo, hi}, %0;\nand.b32 lo, lo, 255;\n"
        "setp.eq.u32 p, lo, %2;\nvote.sync.all.pred p, p, 0xffffffff;\n@p bra.uni POLL_DONE;\n"
        "add.u32 n, n, 1;\nsetp.lt.u32 p, n, 0x400000;\n@p bra.uni POLL;\ntrap;\nPOLL_DONE:\n}\n"
        : "=l"(v) : "l"(word), "n"(NUM_CTAS) : "memory");
    return __ull2float_rn(v >> 8) * 0x1p-16f;
}
__device__ __forceinline__ void publish_sums(const float (&acc)[2][2], float* sums, unsigned int* counter, int wg, int w, int lane) {
#pragma unroll
    for (int m = 0; m < 2; m++)
#pragma unroll
        for (int h = 0; h < 2; h++) {
            const float v = quad_sum(acc[m][h]);
            if ((lane & 3) == 0) atomicAdd(sums + 64 * (2 * wg + m) + 16 * w + (lane >> 2) + 8 * h, v);
        }
    named_sync(1, 384);
    if (fresh_tid() == 0) asm volatile("red.release.gpu.global.add.u32 [%0], 1;" ::"l"(counter) : "memory");
}
__device__ __forceinline__ void grid_wait(const unsigned int* counter, unsigned int target) {
    if (fresh_tid() == 0) {
        unsigned int v, spins = 0;
        do {
            asm volatile("ld.acquire.gpu.global.u32 %0, [%1];" : "=r"(v) : "l"(counter) : "memory");
            if (++spins > (1u << 22)) __trap();
        } while ((int)(v - target) < 0);
    }
    __syncthreads();
}

__device__ __forceinline__ void gemm1(uint32_t (&z)[16], const uint32_t (&a)[24], uint32_t w1d, int j) {
    wg_fence();
    wgmma_n64_h_set<1>(z, a, desc<1024, 1>(w1d, j * 12288));
#pragma unroll
    for (int kk = 1; kk < 6; kk++) wgmma_n64_h_acc<1>(z, a + kk * 4, desc<1024, 1>(w1d, j * 12288 + kk * 2048));
    wg_commit();
}
__device__ __forceinline__ void unpack_offsets(uint32_t (&o)[2], uint32_t packed) {
    asm volatile("and.b32 %0, %2, 0xffff;\nshr.u32 %1, %2, 16;" : "=r"(o[0]), "=r"(o[1]) : "r"(packed));
}
__device__ __forceinline__ void load_a(uint32_t (&a)[24], uint32_t tile, uint32_t offs) {
    uint32_t o[2];
    unpack_offsets(o, offs);
#pragma unroll
    for (int kk = 0; kk < 6; kk++) ldsm4(a + kk * 4, tile + (o[kk >> 2] ^ ((kk & 3) * 32)));
}
__device__ __forceinline__ void init_bias(uint32_t (&o)[24], uint32_t addr) {
#pragma unroll
    for (int j = 0; j < 6; j++) lds128(o + 4 * j, addr + j * 64);
}

struct Pass2 {
    uint32_t wg;
    uint32_t off;
    uint32_t xs;
    uint32_t a_offs, xs_offs, bias_addr, out_scale;
    bool lead;
    uint32_t a[24], z[3][16], o[24];
};

__device__ __forceinline__ void refill_y(const Pass2& c, const Params& prm, bool more, uint32_t off) {
    const uint32_t bars = sb + SM_BAR;
    fence_async_smem();
    named_sync(2 + c.wg, 128);
    if (c.lead && more) {
        expect_tx(bars + (BAR_Y2FULL + (c.wg ^ 2)) * 8, TILE_BYTES);
        bulk_load(sb + SM_Y2 + (c.wg & 1) * SLOT_BYTES, (const char*)prm.out + (off - 2 * ROW_BYTES), TILE_BYTES,
                  bars + (BAR_Y2FULL + (c.wg ^ 2)) * 8);
    }
}

__device__ __forceinline__ void start_first_tile(Pass2& c, const Params& prm) {
    if (c.wg == 3) mbar_wait_c<0>(sb + SM_BAR + (BAR_Y2FULL + 3) * 8);
    load_a(c.a, c.wg == 3 ? sb + SM_Y2 + SLOT_BYTES : c.xs, c.a_offs);
    gemm1(c.z[0], c.a, prm.w1desc, 0);
}

__device__ __forceinline__ void pass2_tile(Pass2& c, const Params& prm, int n) {
    const uint32_t xs = c.xs, xsfull = sb + SM_BAR + (BAR_XSFULL + c.wg) * 8;
#pragma unroll
    for (int j = 0; j < 6; j++) {
        uint32_t (&zc)[16] = c.z[j % 3];
        uint32_t (&zn)[16] = c.z[(j + 1) % 3];
        if (j == 0) wg_wait<0>(); else wg_wait<1>();
        pin(zc);
        if (j == 5) {
            pin(c.a);
            mbar_wait(sb + SM_BAR + (BAR_Y2FULL + c.wg) * 8, min(n + 1, ROWS_PER_CTA / 4 - 1) & 1);
            load_a(c.a, sb + SM_Y2 + (c.wg & 1) * SLOT_BYTES, c.a_offs);
        }
        const int jn = (j + 1) % 6;
#pragma unroll
        for (int sl = 0; sl < 4; sl++) {
#pragma unroll
            for (int r = 0; r < 4; r++) zc[sl * 4 + r] = gelu2(zc[sl * 4 + r]);
            wg_fence();
            wgmma_n96_h_acc(c.o, zc + sl * 4, desc<512, 2>(prm.w2desc, (j * 4 + sl) * 1024));
            if (sl < 2) {
#pragma unroll
                for (int kk = sl * 3; kk < sl * 3 + 3; kk++) {
                    if (kk == 0) wgmma_n64_h_set<1>(zn, c.a, desc<1024, 1>(prm.w1desc, jn * 12288));
                    else wgmma_n64_h_acc<1>(zn, c.a + kk * 4, desc<1024, 1>(prm.w1desc, jn * 12288 + kk * 2048));
                }
            }
            if (sl == 1) wg_commit();
        }
        wg_commit();
        if (j == 5) refill_y(c, prm, 4 * n + c.wg + 6 < ROWS_PER_CTA, c.off - 4 * ROW_BYTES);
        if (j == 1 && c.lead) {
            bulk_wait_read<0>();
            expect_tx(xsfull, TILE_BYTES);
            bulk_load(xs, (const char*)prm.x + c.off, TILE_BYTES, xsfull);
        }
    }
    wg_wait<0>();
    pin(c.o); pin(c.z[0]);
    mbar_wait(xsfull, n & 1);
    uint32_t xo[2];
    unpack_offsets(xo, c.xs_offs);
#pragma unroll
    for (int h = 0; h < 2; h++)
#pragma unroll
        for (int a = 0; a < 3; a++) {
            const uint32_t addr = xs + xo[h] + a * 64;
            uint32_t v[4];
            lds128(v, addr);
#pragma unroll
            for (int b = 0; b < 4; b++) {
                float lo, hi;
                h2_unpack(c.o[a * 8 + b * 2 + h], lo, hi);
                v[b] = bf2_fma(pack_bf2(lo, hi), c.out_scale, v[b]);
            }
            sts128(addr, v[0], v[1], v[2], v[3]);
        }
    init_bias(c.o, c.bias_addr);
    fence_async_smem();
    named_sync(2 + c.wg, 128);
    if (c.lead) bulk_store((char*)prm.out + c.off, xs, TILE_BYTES);
    if (n < 2) MARK(11 + n);
    c.off -= 4 * ROW_BYTES;
}

__device__ __forceinline__ float warp_sum(float v) {
#pragma unroll
    for (int s = 16; s >= 1; s >>= 1) v += __shfl_xor_sync(0xffffffffu, v, s);
    return v;
}
__device__ __forceinline__ float pow2f(int e) { return __uint_as_float((uint32_t)(e + 127) << 23); }
__device__ __forceinline__ int exponent_of(float v) { return (int)(__float_as_uint(v) >> 23) - 127; }
__device__ __forceinline__ float lds_bf16(uint32_t addr) {
    uint16_t v; asm volatile("ld.shared.u16 %0, [%1];" : "=h"(v) : "r"(addr) : "memory"); return bf_lo(v);
}

__device__ __forceinline__ void publish_bias(uint32_t c, uint32_t tag) {
    const uint32_t lane = fresh_tid() & 31;
    const uint32_t col = sb + SM_W2 + (c >> 5) * 24576 + lane * 64 + ((((c >> 3) ^ (lane >> 1)) & 3) * 16) + (c & 7) * 2;
    float v = 0.0f;
#pragma unroll
    for (int k = 0; k < EX / 32; k++) v = fmaf(lds_bf16(col + k * 2048), lds_bf16(sb + SM_BETA + lane * 2 + k * 64), v);
    v = warp_sum(v);
    if (lane == 0) asm volatile("st.relaxed.gpu.global.v2.b32 [%0], {%1, %2};" ::"l"(g_bias + c), "f"(v), "r"(tag) : "memory");
}
__device__ __forceinline__ void collect_bias(uint32_t tag) {
    const uint32_t lane = fresh_tid() & 31;
    if (lane < 24) {
        const unsigned long long* src = g_bias + 32 * (lane >> 3) + 8 * (lane & 3) + (lane & 4);
        uint32_t v[4], t[4], spins = 0;
        for (;;) {
#pragma unroll
            for (int k = 0; k < 4; k++)
                asm volatile("ld.relaxed.gpu.global.v2.b32 {%0, %1}, [%2];" : "=r"(v[k]), "=r"(t[k]) : "l"(src + k) : "memory");
            if (t[0] == tag && t[1] == tag && t[2] == tag && t[3] == tag) break;
            if (++spins > (1u << 22)) __trap();
        }
        sts128(sb + SM_BIAS + lane * 16, v[0], v[1], v[2], v[3]);
    }
    __syncwarp();
}
__device__ __forceinline__ float fetch_w2_row(uint32_t (&u)[12][4], uint32_t row, uint32_t sw) {
    uint32_t mx[4] = {};
#pragma unroll
    for (int a = 0; a < 3; a++)
#pragma unroll
        for (int k = 0; k < 4; k++) {
            asm volatile("ld.shared.v4.b32 {%0,%1,%2,%3}, [%4];"
                         : "=r"(u[a * 4][k]), "=r"(u[a * 4 + 1][k]), "=r"(u[a * 4 + 2][k]), "=r"(u[a * 4 + 3][k])
                         : "r"(row + a * 24576 + ((k * 16) ^ sw)) : "memory");
#pragma unroll
            for (int b = 0; b < 4; b++) asm("max.xorsign.abs.bf16x2 %0, %0, %1;" : "+r"(mx[b]) : "r"(u[a * 4 + b][k]));
        }
#pragma unroll
    for (int b = 1; b < 4; b++) asm("max.xorsign.abs.bf16x2 %0, %0, %1;" : "+r"(mx[0]) : "r"(mx[b]));
    return fmaxf(fabsf(bf_lo(mx[0])), fabsf(bf_hi(mx[0])));
}

__device__ __forceinline__ bool grn_stats(float ss, float gm, float bt, float top, float& gx, float& inv, int& eo) {
    const int warp = fresh_warp();
    gx = sqrt_fast(fmaf(ss, INV_2A * INV_2A, 1e-6f));
    const float rt = sqrt_fast(ss + 1.0f) * INV_2A * top;
    const float r[3] = {warp_sum(gx), warp_sum(fmaf(bt, top, rt)), warp_sum(rt * fabsf(gm) * gx)};
    if ((fresh_tid() & 31) == 0 && warp < 12) {
#pragma unroll
        for (int k = 0; k < 3; k++) sts32(sb + SM_SEL + (k * 12 + warp) * 4, __float_as_uint(r[k]));
    }
    MARK(6);
    const bool bad = __syncthreads_or(!(ss >= 16.0f && ss < ACC_LIMIT));
    MARK(7);
    float tot[3];
#pragma unroll
    for (int k = 0; k < 3; k++) {
        uint32_t v[12];
#pragma unroll
        for (int q = 0; q < 3; q++) lds128(v + 4 * q, sb + SM_SEL + k * 48 + q * 16);
        float p[4];
#pragma unroll
        for (int q = 0; q < 4; q++) p[q] = __uint_as_float(v[q]) + __uint_as_float(v[q + 4]) + __uint_as_float(v[q + 8]);
        tot[k] = (p[0] + p[1]) + (p[2] + p[3]);
    }
    inv = __fdividef(1.0f, fmaf(tot[0], 1.0f / EX, 1e-6f));
    eo = min(max(exponent_of(fmaf(tot[2], inv, tot[1])), -90), 126) - 14;
    return bad;
}

__device__ __forceinline__ float exact_sums(const Params& prm, int e) {
    const int lane = fresh_tid() & 31, warp = fresh_warp(), wg = warp >> 2;
    const uint32_t epoch = lds32(sb + SM_RED + (RED_EPOCH + 1) * 4), bar = sb + SM_BAR + BAR_W1 * 8;
    if (wg < 3) {
        uint32_t wa[2][24], d[2][16];
        float acc[2][2] = {};
        const uint32_t yd = prm.ydesc + ((SM_SPARE - SM_Y1) >> 4), wd = prm.w1desc + ((2 * wg * 12288 + 5 * 2048) >> 4);
        load_w1t(wa, wg, warp & 3, lane);
#pragma unroll 1
        for (int n = 0; n < ROWS_PER_CTA; n++) {
            if (warp == 0) {
                expect_tx(bar, TILE_BYTES);
                bulk_load(sb + SM_SPARE, (const char*)prm.out + cta_tile0(fresh_cta()) + n * ROW_BYTES, TILE_BYTES, bar);
            }
            mbar_wait(bar, (n + 1) & 1);
            gemm1_t<0>(d[0], wa[0], yd, wd);
            gemm1_t<1>(d[1], wa[1], yd, wd);
            wg_wait<0>();
            pin(d[0]); pin(d[1]);
            gelu_sumsq_f(d[0], acc[0]);
            gelu_sumsq_f(d[1], acc[1]);
            named_sync(1, 384);
        }
        publish_sums(acc, g_sums[epoch & 1], &g_count[1], wg, warp & 3, lane);
    }
    grid_wait(&g_count[1], (epoch + 1) * NUM_CTAS);
    return __ldcg(g_sums[epoch & 1] + e);
}

__global__ void __launch_bounds__(512, 1) convnext_kernel(const __grid_constant__ Params prm) {
    extern __shared__ __align__(1024) uint8_t smem[];
    if ((uint32_t)__cvta_generic_to_shared(smem) != sb) __trap();
    if (fresh_tid() < 32) TS(0);
    if (fresh_warp() == 0) {
        const RowCopy rc = row_copy(prm);
        if (fresh_tid() == 0) {
            mbar_init(sb + SM_XFULL, 2);
            fence_async_smem();
        }
        __syncwarp();
        issue_row_load(rc, 0, 0);
        if (fresh_tid() == 0) {
#pragma unroll
            for (int k = 0; k < NX; k++) {
                if (k) mbar_init(sb + SM_XFULL + k * SLOT_BYTES, 2);
                mbar_init(sb + SM_Y1FULL + k * SLOT_BYTES, 4);
                mbar_init(sb + SM_Y1EMPTY + k * SLOT_BYTES, 12);
            }
#pragma unroll
            for (int k = 0; k <= BAR_W2; k++) mbar_init(sb + SM_BAR + k * 8, 1);
            mbar_init(sb + SM_BAR + BAR_DUMMY * 8, 16);
#pragma unroll
            for (int k = 0; k < 3; k++) mbar_arrive_if(sb + SM_BAR + (BAR_Y2FULL + k) * 8, true);
            fence_async_smem();
        }
        __syncwarp();
#pragma unroll
        for (int s = 1; s <= NX; s++) {
            if (s == 1 + rc.first) {
                expect_tx(sb + SM_BAR + BAR_W1 * 8, CH * EX * 2);
#pragma unroll
                for (int k = 0; k < 3; k++)
                    bulk_load(sb + SM_W1 + k * 24576, (const char*)prm.w1 + k * 24576, 24576, sb + SM_BAR + BAR_W1 * 8);
            }
            if (s < NX) issue_row_load(rc, s, s);
        }
    }
    Producer pc;
    if (fresh_warp() >= 12) {
        const char* dw = (const char*)prm.dw + (fresh_tid() & 7) * 8;
#pragma unroll
        for (int tap = 0; tap < 9; tap++) {
            asm volatile("ld.global.nc.v4.b32 {%0,%1,%2,%3}, [%4];"
                         : "=r"(pc.w[tap][0]), "=r"(pc.w[tap][1]), "=r"(pc.w[tap][2]), "=r"(pc.w[tap][3])
                         : "l"(dw + (fresh_tid() & 7) * 8 + tap * CH * 2));
            asm volatile("ld.global.nc.v2.b32 {%0,%1}, [%2];"
                         : "=r"(pc.w[tap][4]), "=r"(pc.w[tap][5]) : "l"(dw + tap * CH * 2 + 128));
        }
    }
    if (fresh_tid() >= 96 && fresh_tid() < 128) {
        const uint32_t k = fresh_tid() - 96, n = k & 7, one = (n & 5) == ((k & 8) >> 1) + (k >> 4) ? 0x3f803f80u : 0u;
        sts128(sb + SM_SEL + k * 16, one, one, one, one);
        fence_async_smem();
    }
    if (fresh_tid() >= 32 && fresh_tid() < 32 + NX * 12 && ((blockIdx.x + 1) & 7) < 2) {
        const int k = fresh_tid() - 32;
        sts128(sb + SM_X + (k / 12) * SLOT_BYTES + ((blockIdx.x & 7) == 0 ? 0 : XHALF_B + 33 * 192) + (k % 12) * 16, 0, 0, 0, 0);
    }
    __syncthreads();
    if (fresh_tid() < 32) TS(16);

    if (fresh_warp() >= 12) {
        TS(17);
        asm volatile("setmaxnreg.inc.sync.aligned.u32 %0;" ::"n"(PRODUCER_REGS));
        TS(18);
        const int w = fresh_warp() & 3, lane = fresh_tid() & 31;
        const int j = lane & 7, hb = (lane >> 3) & 1, base = 4 * (2 * w + (lane >> 4));
        pc.lane = lane; pc.warp = w;
        pc.xoff[0] = hb * XHALF_B + base * 192 + j * 16;
        pc.xoff[1] = hb * XHALF_B + base * 192 + 128 + j * 8;
        const int grp = 4 * w + (lane >> 3);
#pragma unroll
        for (int o = 0; o < 2; o++) {
            const int row = (grp & 7) + 8 * (o ^ hb) + 32 * (grp >> 3);
            pc.yoff[0][o] = row * 128 + ((j ^ (row & 7)) * 16);
            pc.yoff[1][o] = 8192 + row * 64 + (((j >> 1) ^ ((row >> 1) & 3)) * 16) + (j & 1) * 8;
        }
        pc.stat = sb + SM_STAT + (8 * w + (lane >> 2)) * 32;
        pc.own = pc.stat + (lane & 3) * 8;
#pragma unroll
        for (int tap = 0; tap < 9; tap++)
#pragma unroll
            for (int u = 0; u < 6; u++) pc.w[tap][u] = bf2_mul(pc.w[tap][u], TAP_SCALE_BF2);
        TS(8);
        produce(pc, prm);
        TS(9);
        TS(22);
        asm volatile("setmaxnreg.dec.sync.aligned.u32 %0;" ::"n"(EVEN_REGS));
        if (fresh_warp() == 12) {
            mbar_wait_c<0>(sb + SM_BAR + BAR_W2 * 8);
            if (fresh_cta() < CH) publish_bias(fresh_cta(), lds32(sb + SM_RED + RED_EPOCH * 4) + 1);
        }
    } else {
        asm volatile("setmaxnreg.dec.sync.aligned.u32 %0;" ::"n"(CONSUMER_REGS));
        if (fresh_tid() - 160 < 2) {
            const uint32_t k = fresh_tid() - 160;
            unsigned int cnt;
            asm volatile("ld.relaxed.gpu.global.u32 %0, [%1];" : "=r"(cnt) : "l"(&g_count[k]) : "memory");
            sts32(sb + SM_RED + (RED_EPOCH + k) * 4, k ? cnt / NUM_CTAS : cnt);
        }
        __syncwarp();
        if (fresh_tid() < 32) TS(19);
        {
            const int tid = fresh_tid(), c0 = tid / 48, ec = tid % 48;
            const uint32_t dst = sb + SM_W1 + (ec >> 3) * 12288 + c0 * 128 + (((ec & 7) ^ (c0 & 7)) * 16);
            uint32_t v[12][4];
            mbar_wait_c<0>(sb + SM_BAR + BAR_W1 * 8);
            if (fresh_tid() < 32) TS(20);
#pragma unroll
            for (int it = 0; it < 12; it++) lds128(v[it], sb + SM_W1 + tid * 16 + it * 6144);
#pragma unroll
            for (int it = 0; it < 12; it++)
#pragma unroll
                for (int k = 0; k < 4; k++) v[it][k] = bf2_to_h2(v[it][k]);
#pragma unroll
            for (int it = 0; it < 12; it++) pin(v[it]);
            named_sync(1, 384);
#pragma unroll
            for (int it = 0; it < 12; it++) sts128(dst + it * 1024, v[it][0], v[it][1], v[it][2], v[it][3]);
            if (fresh_cta() == 0) *acc_word(lds32(sb + SM_RED + RED_EPOCH * 4) + 1, tid) = 0;
            if (fresh_cta() == 1) g_sums[(lds32(sb + SM_RED + (RED_EPOCH + 1) * 4) & 1) ^ 1][tid] = 0.0f;
            fence_async_smem();
            named_sync(1, 384);
            if (fresh_tid() < 32) TS(21);
        }

        const int tid = fresh_tid(), lane = tid & 31, wg = fresh_warp() >> 2, w = fresh_warp() & 3;
        float acc[2][2];
        const int c = 8 * (lane >> 4) + (lane & 7), ck = 2 * w + ((lane >> 3) & 1);
        if (wg == 0) TS(1);
        consume(acc, sb + SM_W1 + 2 * wg * 12288 + c * 128 + ((ck ^ (c & 7)) * 16), prm.ydesc,
                prm.w1desc + (((2 * wg + 1) * 12288 + 5 * 2048) >> 4), wg * SLOT_BYTES, make_duty(prm, wg, w), w, lane);
        publish_fast(acc, lds32(sb + SM_RED + RED_EPOCH * 4), wg, w, lane);
        MARK(0);
        bulk_wait_all();
        if (wg == 0) TS(3);
        asm volatile("setmaxnreg.inc.sync.aligned.u32 %0;" ::"n"(EVEN_REGS));
    }

    {
        Pass2 c;
        const int tid = fresh_tid(), lane = tid & 31, warp = fresh_warp(), wg = warp >> 2, w = warp & 3, e = min(tid, EX - 1);
        const int arow = 16 * w + (lane & 15);
        c.wg = wg;
        c.off = cta_tile0(fresh_cta()) + (ROWS_PER_CTA - 1 - wg) * ROW_BYTES;
        c.xs = wg == 3 ? sb + SM_SPARE : sb + SM_Y1 + (wg == 2 ? 2 : 1 - wg) * SLOT_BYTES;
        static_assert((ROWS_PER_CTA - 1) % NX == 1, "slot of the last tile");
        c.a_offs = (arow * 128 + (((lane >> 4) ^ (arow & 7)) * 16)) |
                   (8192 + arow * 64 + (((lane >> 4) ^ ((arow >> 1) & 3)) * 16)) << 16;
        const int g = lane >> 2, px = 33 * (g & 1) + 4 * (g >> 1) + 16 * (w >> 1) + 2 * (w & 1);
        c.xs_offs = (px * 192 + (lane & 3) * 16) | ((px ^ 1) * 192 + (lane & 3) * 16) << 16;
        c.bias_addr = sb + SM_BIAS + (lane & 3) * 16;
        c.lead = w == 0;
        const uint32_t epoch = lds32(sb + SM_RED + RED_EPOCH * 4);
        MARK(1);
        if (warp == 2 || warp == 6) {
            const uint32_t bar = sb + SM_BAR + (BAR_Y2FULL + 3 * wg) * 8;
            expect_tx(bar, TILE_BYTES);
            bulk_load(sb + SM_Y2 + wg * SLOT_BYTES, (const char*)prm.out + (c.off - (4 - 2 * wg) * ROW_BYTES), TILE_BYTES, bar);
        }
        mbar_wait_c<0>(sb + SM_BAR + BAR_W2 * 8);
        const float gm = lds_bf16(sb + SM_GAMMA + e * 2), bt = fabsf(lds_bf16(sb + SM_BETA + e * 2));
        const uint32_t w2row = sb + SM_W2 + e * 64, sw = ((e >> 1) & 3) * 16;
        uint32_t u[12][4];
        float top = 0.0f, ss = 16.0f;
        if (wg < 3) top = fetch_w2_row(u, w2row, sw);
        if (warp == 12) collect_bias(epoch + 1);
        MARK(3);
        start_first_tile(c, prm);
        MARK(4);
        if (wg < 3) ss = collect_fast(acc_word(epoch, e));
        if (warp == 0) TS(4);
        MARK(5);
        float gx, inv;
        int eo;
        if (grn_stats(ss, gm, bt, top, gx, inv, eo) || FORCE_EXACT) {
            wg_wait<0>();
            pin(c.z[0]); pin(c.a);
            grn_stats(exact_sums(prm, e), gm, bt, top, gx, inv, eo);
            fetch_w2_row(u, w2row, sw);
            start_first_tile(c, prm);
            __syncthreads();
        }
        MARK(8);
        if (tid == 416 && fresh_cta() == 0) g_count[0] = epoch + 1;
        const float up = pow2f(eo), dn = pow2f(-eo);
        c.out_scale = pack_bf2(up, up);
        if (wg < 3) {
            float sc = fmaf(gm, gx * inv, 1.0f) * INV_2A;
            if (eo > 6) {
                const uint32_t dn2 = pack_bf2(dn, dn);
#pragma unroll
                for (int k = 0; k < 48; k++) u[k >> 2][k & 3] = bf2_mul(u[k >> 2][k & 3], dn2);
            } else {
                sc *= dn;
            }
            const uint32_t s2 = pack_bf2(sc * 0x1p-112f, sc * 0x1p-112f);
#pragma unroll
            for (int k = 0; k < 12; k++) {
                uint32_t v[4];
#pragma unroll
                for (int b = 0; b < 4; b++) {
                    v[b] = bf2_mul(u[k][b], s2);
                    v[b] += (v[b] & 0x7fff7fffu) * 7u;
                }
                sts128(w2row + (k >> 2) * 24576 + (((k & 3) * 16) ^ sw), v[0], v[1], v[2], v[3]);
            }
        } else if (w == 0 && lane < 24) {
            uint32_t b[4];
            lds128(b, sb + SM_BIAS + lane * 16);
            const uint32_t p0 = pack_h2(__uint_as_float(b[0]) * dn, __uint_as_float(b[1]) * dn);
            const uint32_t p1 = pack_h2(__uint_as_float(b[2]) * dn, __uint_as_float(b[3]) * dn);
            sts128(sb + SM_BIAS + lane * 16, p0, p0, p1, p1);
        }
        MARK(9);
        fence_async_smem();
        __syncthreads();
        MARK(10);

        if (wg == 0) TS(5);
        if (warp == 13) {
            expect_tx(sb + SM_BAR + (BAR_Y2FULL + 1) * 8, TILE_BYTES);
            bulk_load(sb + SM_Y2 + SLOT_BYTES, (const char*)prm.out + (c.off - 2 * ROW_BYTES), TILE_BYTES, sb + SM_BAR + (BAR_Y2FULL + 1) * 8);
        }
        init_bias(c.o, c.bias_addr);
#pragma unroll 1
        for (int n = loop_init<0>(); n < ROWS_PER_CTA / 4; n++) pass2_tile(c, prm, n);
        bulk_wait_all();
        if (wg == 0) TS(6);
        if (wg == 3) TS(7);
    }
}

}

extern "C" void kernel_launch(void* const* d_in, const int* in_sizes, int n_in, void* d_out, int out_size) {
    (void)in_sizes; (void)n_in; (void)out_size;
    typedef CUresult (*EncodeFn)(CUtensorMap*, CUtensorMapDataType, cuuint32_t, void*, const cuuint64_t*, const cuuint64_t*,
                                 const cuuint32_t*, const cuuint32_t*, CUtensorMapInterleave, CUtensorMapSwizzle,
                                 CUtensorMapL2promotion, CUtensorMapFloatOOBfill);
    void* fn = nullptr;
    cudaDriverEntryPointQueryResult status;
    cudaGetDriverEntryPoint("cuTensorMapEncodeTiled", &fn, cudaEnableDefault, &status);
    const EncodeFn encode = (EncodeFn)fn;
    const cuuint32_t ones[2] = {1, 1};

    Params p;
    {
        const cuuint64_t dims[2] = {CH, EX}, strides[1] = {CH * 2};
        const cuuint32_t box[2] = {32, 192};
        encode(&p.w2_map, CU_TENSOR_MAP_DATA_TYPE_BFLOAT16, 2, d_in[3], dims, strides, box, ones,
               CU_TENSOR_MAP_INTERLEAVE_NONE, CU_TENSOR_MAP_SWIZZLE_64B, CU_TENSOR_MAP_L2_PROMOTION_NONE,
               CU_TENSOR_MAP_FLOAT_OOB_FILL_NONE);
    }
    p.x = (const __nv_bfloat16*)d_in[0];
    p.dw = (const __nv_bfloat16*)d_in[1];
    p.w1 = (const __nv_bfloat16*)d_in[2];
    p.gamma = (const __nv_bfloat16*)d_in[4];
    p.beta = (const __nv_bfloat16*)d_in[5];
    p.out = (__nv_bfloat16*)d_out;
    p.w1desc = desc_lo(sb + SM_W1, 12288);
    p.w2desc = desc_lo(sb + SM_W2, 24576);
    p.ydesc = desc_lo(sb + SM_Y1, 16);
    for (int k = 0; k < 3; k++) p.sel[k] = (8ull << 32) | desc_lo(sb + SM_SEL + k * 128, k == 2 ? 128 : 0);
    constexpr int smem_bytes = SM_TOTAL;
    cudaFuncSetAttribute(convnext_kernel, cudaFuncAttributeMaxDynamicSharedMemorySize, smem_bytes);
    convnext_kernel<<<NUM_CTAS, 512, smem_bytes>>>(p);
}
```

```cpp
#include <cuda.h>
#include <cuda_runtime.h>
#include <cuda_bf16.h>
#include <stdint.h>

namespace {

constexpr int IMG_W = 512, CH = 96, EX = 384;
constexpr int TILE_PX = 64;
constexpr int ROWS_PER_CTA = 32;
constexpr int NUM_CTAS = 128;
constexpr int STEPS = ROWS_PER_CTA + 2;
constexpr int ROW_BYTES = IMG_W * CH * 2;

#define FORCE_EXACT 0
#define PREGS 200
#define CREGS 104
constexpr int PRODUCER_REGS = PREGS, CONSUMER_REGS = CREGS, EVEN_REGS = 128;

constexpr int XHALF_BYTES = 34 * 192;
constexpr int XHALF_B = XHALF_BYTES + 64;
constexpr int XROW_BYTES = XHALF_B + XHALF_BYTES + 64;
constexpr int L2_AHEAD = 2;
constexpr int NX = 3;
constexpr int TILE_BYTES = TILE_PX * 192;
constexpr int NY1 = 3;

constexpr uint32_t sb = 1024;
constexpr int SM_W1 = 0;
constexpr int SM_W2 = 73728;
constexpr int SM_RING = 147456;
constexpr int SLOT_BYTES = 26624;
constexpr int SM_Y1 = SM_RING;
constexpr int SM_X = SM_Y1 + TILE_BYTES;
constexpr int SM_STAT = SM_X + XROW_BYTES;
constexpr int SM_XFULL = SM_STAT + TILE_PX * 16, SM_Y1FULL = SM_XFULL + 8, SM_Y1EMPTY = SM_XFULL + 16;
constexpr int SM_BUF3 = SM_X + SLOT_BYTES, SM_SPARE = SM_X;
constexpr int SM_SEL = SM_RING + NX * SLOT_BYTES;
constexpr int SM_BIAS = SM_SEL + 512;
constexpr int SM_GAMMA = SM_BIAS + 384;
constexpr int SM_BETA = SM_GAMMA + EX * 2;
constexpr int SM_RED = SM_BETA + EX * 2;
constexpr int SM_BAR = SM_RED + 16;
constexpr int SM_TOTAL = SM_BAR + 51 * 8;
static_assert(SM_Y1EMPTY + 8 <= SM_RING + SLOT_BYTES && XROW_BYTES >= TILE_BYTES && SM_X % 1024 == 0, "ring layout");
static_assert(SM_TOTAL <= 232448, "smem budget");
static_assert(SM_STAT % 128 == 0 && SM_BIAS % 16 == 0 && SM_BAR % 8 == 0 && SLOT_BYTES % 1024 == 0, "alignment");

constexpr int BAR_Y2FULL = 0, BAR_XSFULL = 4, BAR_W1 = 8, BAR_W2 = 9, BAR_DUMMY = 10, BAR_TURN = 11;
static_assert(NX == NY1, "both rings are walked with one index");
constexpr int RED_EPOCH = 0;

constexpr float GELU_A = 0.32920349f;
constexpr uint32_t GELU_C_H2 = 0x40D940D9u;
constexpr float INV_2A = 1.0f / (2.0f * GELU_A);

constexpr uint32_t TAP_SCALE_BF2 = 0x2B802B80u;
constexpr float LN_EPS_SCALED = 1e-5f * 0x1p-80f;
constexpr float RSTD_SCALE = GELU_A * 0x1p-112f;

__device__ unsigned long long g_acc[2][EX / 4 * 32];
__device__ unsigned long long g_bias[CH];
__device__ float g_sums[2][EX];
__device__ unsigned int g_count[2];
constexpr float ACC_LIMIT = 0x1p30f;
__device__ uint4 g_zero_row[66 * 192 / 16];

#define TS(k)
#define ASM_TS
#define MARK(k)
#define ASM_MARK
#define ASM_TRC(it, k)

#define SPLITS 2
#define FENCE_HEAD(k) "{\n.reg .pred p;\n.reg .u32 t;\nsetp.ne.u32 p, %" #k ", 0;\n@p bra.uni GO;\nSTAY:\nld.volatile.shared.u32 t, [%" #k "];\n"
#define FENCE_TAIL "setp.ne.u32 p, t, 0;\n@p bra.uni STAY;\nGO:\n}\n"
template <int N> __device__ __forceinline__ void sched_fence(uint32_t* r, uint32_t key);
template <> __device__ __forceinline__ void sched_fence<2>(uint32_t* r, uint32_t key) {
    asm volatile(FENCE_HEAD(2) "mov.b32 %0, t;\nmov.b32 %1, t;\n" FENCE_TAIL
                 : "+r"(r[0]), "+r"(r[1]) : "r"(key) : "memory");
}
template <> __device__ __forceinline__ void sched_fence<4>(uint32_t* r, uint32_t key) {
    asm volatile(FENCE_HEAD(4) "mov.b32 %0, t;\nmov.b32 %1, t;\nmov.b32 %2, t;\nmov.b32 %3, t;\n" FENCE_TAIL
                 : "+r"(r[0]), "+r"(r[1]), "+r"(r[2]), "+r"(r[3]) : "r"(key) : "memory");
}
template <> __device__ __forceinline__ void sched_fence<6>(uint32_t* r, uint32_t key) {
    asm volatile(FENCE_HEAD(6) "mov.b32 %0, t;\nmov.b32 %1, t;\nmov.b32 %2, t;\nmov.b32 %3, t;\nmov.b32 %4, t;\nmov.b32 %5, t;\n" FENCE_TAIL
                 : "+r"(r[0]), "+r"(r[1]), "+r"(r[2]), "+r"(r[3]), "+r"(r[4]), "+r"(r[5]) : "r"(key) : "memory");
}
template <> __device__ __forceinline__ void sched_fence<8>(uint32_t* r, uint32_t key) {
    asm volatile(FENCE_HEAD(8) "mov.b32 %0, t;\nmov.b32 %1, t;\nmov.b32 %2, t;\nmov.b32 %3, t;\nmov.b32 %4, t;\nmov.b32 %5, t;\nmov.b32 %6, t;\nmov.b32 %7, t;\n" FENCE_TAIL
                 : "+r"(r[0]), "+r"(r[1]), "+r"(r[2]), "+r"(r[3]), "+r"(r[4]), "+r"(r[5]), "+r"(r[6]), "+r"(r[7]) : "r"(key) : "memory");
}
template <> __device__ __forceinline__ void sched_fence<10>(uint32_t* r, uint32_t key) {
    asm volatile(FENCE_HEAD(10) "mov.b32 %0, t;\nmov.b32 %1, t;\nmov.b32 %2, t;\nmov.b32 %3, t;\nmov.b32 %4, t;\nmov.b32 %5, t;\nmov.b32 %6, t;\nmov.b32 %7, t;\nmov.b32 %8, t;\nmov.b32 %9, t;\n" FENCE_TAIL
                 : "+r"(r[0]), "+r"(r[1]), "+r"(r[2]), "+r"(r[3]), "+r"(r[4]), "+r"(r[5]), "+r"(r[6]), "+r"(r[7]), "+r"(r[8]), "+r"(r[9]) : "r"(key) : "memory");
}
template <> __device__ __forceinline__ void sched_fence<12>(uint32_t* r, uint32_t key) {
    asm volatile(FENCE_HEAD(12) "mov.b32 %0, t;\nmov.b32 %1, t;\nmov.b32 %2, t;\nmov.b32 %3, t;\nmov.b32 %4, t;\nmov.b32 %5, t;\nmov.b32 %6, t;\nmov.b32 %7, t;\nmov.b32 %8, t;\nmov.b32 %9, t;\nmov.b32 %10, t;\nmov.b32 %11, t;\n" FENCE_TAIL
                 : "+r"(r[0]), "+r"(r[1]), "+r"(r[2]), "+r"(r[3]), "+r"(r[4]), "+r"(r[5]), "+r"(r[6]), "+r"(r[7]), "+r"(r[8]), "+r"(r[9]), "+r"(r[10]), "+r"(r[11]) : "r"(key) : "memory");
}
template <> __device__ __forceinline__ void sched_fence<24>(uint32_t* r, uint32_t key) {
    asm volatile(FENCE_HEAD(24) "mov.b32 %0, t;\nmov.b32 %1, t;\nmov.b32 %2, t;\nmov.b32 %3, t;\nmov.b32 %4, t;\nmov.b32 %5, t;\nmov.b32 %6, t;\nmov.b32 %7, t;\nmov.b32 %8, t;\nmov.b32 %9, t;\nmov.b32 %10, t;\nmov.b32 %11, t;\nmov.b32 %12, t;\nmov.b32 %13, t;\nmov.b32 %14, t;\nmov.b32 %15, t;\nmov.b32 %16, t;\nmov.b32 %17, t;\nmov.b32 %18, t;\nmov.b32 %19, t;\nmov.b32 %20, t;\nmov.b32 %21, t;\nmov.b32 %22, t;\nmov.b32 %23, t;\n" FENCE_TAIL
                 : "+r"(r[0]), "+r"(r[1]), "+r"(r[2]), "+r"(r[3]), "+r"(r[4]), "+r"(r[5]), "+r"(r[6]), "+r"(r[7]), "+r"(r[8]), "+r"(r[9]), "+r"(r[10]), "+r"(r[11]), "+r"(r[12]), "+r"(r[13]), "+r"(r[14]), "+r"(r[15]), "+r"(r[16]), "+r"(r[17]), "+r"(r[18]), "+r"(r[19]), "+r"(r[20]), "+r"(r[21]), "+r"(r[22]), "+r"(r[23]) : "r"(key) : "memory");
}
#define SPLIT(k, r) do { if ((SPLITS >> (k)) & 1) sched_fence<sizeof(r) / 4>(r, prm.ydesc); } while (0)

__device__ __forceinline__ void mbar_init(uint32_t bar, uint32_t count) {
    asm volatile("mbarrier.init.shared::cta.b64 [%0], %1;" ::"r"(bar), "r"(count) : "memory");
}
__device__ __forceinline__ void mbar_arrive_if(uint32_t bar, bool pred) {
    asm volatile("{\n.reg .pred p;\nsetp.ne.u32 p, %1, 0;\n@p mbarrier.arrive.shared::cta.b64 _, [%0];\n}\n"
                 ::"r"(bar), "r"((uint32_t)pred) : "memory");
}
__device__ __forceinline__ void mbar_wait(uint32_t bar, uint32_t parity) {
    asm volatile(
        "{\n.reg .pred p;\n.reg .u32 n;\n"
        "mbarrier.try_wait.parity.shared::cta.b64 p, [%0], %1;\n"
        "@p bra.uni WAIT_DONE;\n"
        "mov.u32 n, 0;\n"
        "WAIT_LOOP:\n"
        "mbarrier.try_wait.parity.shared::cta.b64 p, [%0], %1;\n"
        "@p bra.uni WAIT_DONE;\n"
        "mbarrier.try_wait.parity.shared::cta.b64 p, [%0], %1;\n"
        "@p bra.uni WAIT_DONE;\n"
        "mbarrier.try_wait.parity.shared::cta.b64 p, [%0], %1;\n"
        "@p bra.uni WAIT_DONE;\n"
        "add.u32 n, n, 1;\nsetp.lt.u32 p, n, 0x40000;\n"
        "@p bra.uni WAIT_LOOP;\n"
        "trap;\n"
        "WAIT_DONE:\n}\n"
        ::"r"(bar), "r"(parity) : "memory");
}
template <int PARITY> __device__ __forceinline__ void mbar_wait_c(uint32_t bar) {
    asm volatile(
        "{\n.reg .pred p;\n.reg .u32 n;\n"
        "mbarrier.try_wait.parity.shared::cta.b64 p, [%0], %1;\n"
        "@p bra.uni WAIT_DONE;\n"
        "mov.u32 n, 0;\n"
        "WAIT_LOOP:\n"
        "mbarrier.try_wait.parity.shared::cta.b64 p, [%0], %1;\n"
        "@p bra.uni WAIT_DONE;\n"
        "mbarrier.try_wait.parity.shared::cta.b64 p, [%0], %1;\n"
        "@p bra.uni WAIT_DONE;\n"
        "mbarrier.try_wait.parity.shared::cta.b64 p, [%0], %1;\n"
        "@p bra.uni WAIT_DONE;\n"
        "add.u32 n, n, 1;\nsetp.lt.u32 p, n, 0x40000;\n"
        "@p bra.uni WAIT_LOOP;\n"
        "trap;\n"
        "WAIT_DONE:\n}\n"
        ::"r"(bar), "n"(PARITY) : "memory");
}
__device__ __forceinline__ bool mbar_probe(uint32_t bar, uint32_t parity) {
    uint32_t ok;
    asm volatile("{\n.reg .pred p;\nmbarrier.test_wait.parity.shared::cta.b64 p, [%1], %2;\nselp.u32 %0, 1, 0, p;\n}\n"
                 : "=r"(ok) : "r"(bar), "r"(parity) : "memory");
    return ok;
}
__device__ __forceinline__ void mbar_wait2(uint32_t bar0, uint32_t parity0, uint32_t bar1, uint32_t parity1) {
    asm volatile(
        "{\n.reg .pred p, q;\n.reg .u32 n;\n"
        "mbarrier.try_wait.parity.shared::cta.b64 p, [%0], %1;\n"
        "mbarrier.try_wait.parity.shared::cta.b64 q, [%2], %3;\n"
        "and.pred p, p, q;\n"
        "@p bra.uni WAIT_DONE;\n"
        "mov.u32 n, 0;\n"
        "WAIT_LOOP:\n"
        "mbarrier.try_wait.parity.shared::cta.b64 p, [%0], %1;\n"
        "mbarrier.try_wait.parity.shared::cta.b64 q, [%2], %3;\n"
        "and.pred p, p, q;\n"
        "@p bra.uni WAIT_DONE;\n"
        "add.u32 n, n, 1;\nsetp.lt.u32 p, n, 0x80000;\n"
        "@p bra.uni WAIT_LOOP;\n"
        "trap;\n"
        "WAIT_DONE:\n}\n"
        ::"r"(bar0), "r"(parity0), "r"(bar1), "r"(parity1) : "memory");
}
#define ELECTED(body) "{\n.reg .pred p;\nelect.sync _|p, 0xffffffff;\n" body "}\n"
__device__ __forceinline__ void expect_tx(uint32_t bar, uint32_t bytes) {
    asm volatile(ELECTED("@p mbarrier.arrive.expect_tx.shared::cta.b64 _, [%0], %1;\n") ::"r"(bar), "r"(bytes) : "memory");
}
__device__ __forceinline__ void arrive_n(uint32_t bar, uint32_t count) {
    asm volatile(ELECTED("@p mbarrier.arrive.shared::cta.b64 _, [%0], %1;\n") ::"r"(bar), "r"(count) : "memory");
}
__device__ __forceinline__ void bulk_load(uint32_t dst, const void* src, uint32_t bytes, uint32_t bar) {
    asm volatile(ELECTED("@p cp.async.bulk.shared::cluster.global.mbarrier::complete_tx::bytes [%0], [%1], %2, [%3];\n")
                 ::"r"(dst), "l"(src), "r"(bytes), "r"(bar) : "memory");
}
__device__ __forceinline__ void bulk_store(void* dst, uint32_t src, uint32_t bytes) {
    asm volatile(ELECTED("@p cp.async.bulk.global.shared::cta.bulk_group [%0], [%1], %2;\n@p cp.async.bulk.commit_group;\n")
                 ::"l"(dst), "r"(src), "r"(bytes) : "memory");
}
__device__ __forceinline__ void bulk_prefetch(const void* src, uint32_t bytes) {
    asm volatile(ELECTED("@p cp.async.bulk.prefetch.L2.global [%0], %1;\n") ::"l"(src), "r"(bytes) : "memory");
}
__device__ __forceinline__ void tma_load_2d(uint32_t dst, const CUtensorMap* map, int c0, int c1, uint32_t bar) {
    asm volatile(ELECTED("@p cp.async.bulk.tensor.2d.shared::cluster.global.mbarrier::complete_tx::bytes [%0], [%1, {%2, %3}], [%4];\n")
                 ::"r"(dst), "l"(map), "r"(c0), "r"(c1), "r"(bar) : "memory");
}
template <int N> __device__ __forceinline__ void bulk_wait_read() {
    asm volatile("cp.async.bulk.wait_group.read %0;" ::"n"(N) : "memory");
}
__device__ __forceinline__ void bulk_wait_all() { asm volatile("cp.async.bulk.wait_group 0;" ::: "memory"); }
__device__ __forceinline__ void fence_async_smem() { asm volatile("fence.proxy.async.shared::cta;" ::: "memory"); }
__device__ __forceinline__ void named_sync(int id, int n) { asm volatile("bar.sync %0, %1;" ::"r"(id), "r"(n) : "memory"); }

__device__ __forceinline__ void lds64(uint32_t (&v)[2], uint32_t addr) {
    asm volatile("ld.shared.v2.b32 {%0,%1}, [%2];" : "=r"(v[0]), "=r"(v[1]) : "r"(addr));
}
__device__ __forceinline__ void sts64(uint32_t addr, uint32_t a, uint32_t b) {
    asm volatile("st.shared.v2.b32 [%0], {%1,%2};" ::"r"(addr), "r"(a), "r"(b) : "memory");
}
__device__ __forceinline__ void sts128(uint32_t addr, uint32_t a, uint32_t b, uint32_t c, uint32_t d) {
    asm volatile("st.shared.v4.b32 [%0], {%1,%2,%3,%4};" ::"r"(addr), "r"(a), "r"(b), "r"(c), "r"(d) : "memory");
}
__device__ __forceinline__ void ldsm4(uint32_t* r, uint32_t addr) {
    asm volatile("ldmatrix.sync.aligned.m8n8.x4.shared.b16 {%0,%1,%2,%3}, [%4];"
                 : "=r"(r[0]), "=r"(r[1]), "=r"(r[2]), "=r"(r[3]) : "r"(addr) : "memory");
}
__device__ __forceinline__ void ldsm4_t(uint32_t* r, uint32_t addr) {
    asm volatile("ldmatrix.sync.aligned.m8n8.x4.trans.shared.b16 {%0,%1,%2,%3}, [%4];"
                 : "=r"(r[0]), "=r"(r[1]), "=r"(r[2]), "=r"(r[3]) : "r"(addr) : "memory");
}
__device__ __forceinline__ void lds128(uint32_t* v, uint32_t addr) {
    asm volatile("ld.shared.v4.b32 {%0,%1,%2,%3}, [%4];"
                 : "=r"(v[0]), "=r"(v[1]), "=r"(v[2]), "=r"(v[3]) : "r"(addr) : "memory");
}
__device__ __forceinline__ uint32_t lds32(uint32_t addr) {
    uint32_t v; asm volatile("ld.shared.b32 %0, [%1];" : "=r"(v) : "r"(addr) : "memory"); return v;
}
__device__ __forceinline__ void sts32(uint32_t addr, uint32_t v) {
    asm volatile("st.shared.b32 [%0], %1;" ::"r"(addr), "r"(v) : "memory");
}

__device__ __forceinline__ uint32_t bf2_fma(uint32_t a, uint32_t b, uint32_t c) {
    uint32_t d; asm("fma.rn.bf16x2 %0, %1, %2, %3;" : "=r"(d) : "r"(a), "r"(b), "r"(c)); return d;
}
__device__ __forceinline__ uint32_t bf2_mul(uint32_t a, uint32_t b) {
    uint32_t d; asm("mul.rn.bf16x2 %0, %1, %2;" : "=r"(d) : "r"(a), "r"(b)); return d;
}
__device__ __forceinline__ uint32_t bf2_add(uint32_t a, uint32_t b) {
    uint32_t d; asm("add.rn.bf16x2 %0, %1, %2;" : "=r"(d) : "r"(a), "r"(b)); return d;
}
__device__ __forceinline__ uint32_t h2_fma(uint32_t a, uint32_t b, uint32_t c) {
    uint32_t d; asm("fma.rn.f16x2 %0, %1, %2, %3;" : "=r"(d) : "r"(a), "r"(b), "r"(c)); return d;
}
__device__ __forceinline__ uint32_t h2_mul(uint32_t a, uint32_t b) {
    uint32_t d; asm("mul.rn.f16x2 %0, %1, %2;" : "=r"(d) : "r"(a), "r"(b)); return d;
}
__device__ __forceinline__ uint32_t h2_tanh(uint32_t a) {
    uint32_t d; asm("tanh.approx.f16x2 %0, %1;" : "=r"(d) : "r"(a)); return d;
}
__device__ __forceinline__ float bf_lo(uint32_t v) { return __uint_as_float(v << 16); }
__device__ __forceinline__ float bf_hi(uint32_t v) { return __uint_as_float(v & 0xffff0000u); }
__device__ __forceinline__ uint32_t pack_h2(float lo, float hi) {
    uint32_t d; asm("cvt.rn.f16x2.f32 %0, %1, %2;" : "=r"(d) : "f"(hi), "f"(lo)); return d;
}
__device__ __forceinline__ uint32_t pack_bf2(float lo, float hi) {
    uint32_t d; asm("cvt.rn.bf16x2.f32 %0, %1, %2;" : "=r"(d) : "f"(hi), "f"(lo)); return d;
}
__device__ __forceinline__ void h2_unpack(uint32_t v, float& lo, float& hi) {
    asm("{\n.reg .b16 l, h;\nmov.b32 {l, h}, %2;\ncvt.f32.f16 %0, l;\ncvt.f32.f16 %1, h;\n}\n" : "=f"(lo), "=f"(hi) : "r"(v));
}
__device__ __forceinline__ uint32_t bf2_to_h2(uint32_t v) { return pack_h2(bf_lo(v), bf_hi(v)); }

__device__ __forceinline__ uint32_t gelu2(uint32_t z) {
    uint32_t p = h2_fma(z, z, GELU_C_H2);
    uint32_t t = h2_tanh(h2_mul(z, p));
    return h2_fma(z, t, z);
}

__device__ __forceinline__ void wg_fence() { asm volatile("wgmma.fence.sync.aligned;" ::: "memory"); }
__device__ __forceinline__ void wg_commit() { asm volatile("wgmma.commit_group.sync.aligned;" ::: "memory"); }
template <int N> __device__ __forceinline__ void wg_wait() {
    asm volatile("wgmma.wait_group.sync.aligned %0;" ::"n"(N) : "memory");
}
template <int N> __device__ __forceinline__ void pin(uint32_t (&r)[N]) {
#pragma unroll
    for (int i = 0; i < N; i++) asm volatile("" : "+r"(r[i])::"memory");
}
constexpr uint32_t desc_lo(uint32_t addr, uint32_t lbo) { return ((addr & 0x3FFFF) >> 4) | ((lbo >> 4) << 16); }
template <uint32_t SBO, uint32_t SWZ> __device__ __forceinline__ uint64_t desc(uint32_t lo, uint32_t bytes) {
    return (((uint64_t)((SBO >> 4) | (SWZ << 30)) << 32) | lo) + (bytes >> 4);
}
__device__ __forceinline__ uint32_t fresh_tid() {
    uint32_t v; asm volatile("mov.u32 %0, %%tid.x;" : "=r"(v));
    return v;
}
template <uint32_t V> __device__ __forceinline__ uint32_t loop_init() {
    uint32_t v; asm volatile("mov.u32 %0, %1;" : "=r"(v) : "n"(V)); return v;
}
__device__ __forceinline__ int fresh_warp() {
    int v; asm volatile("shfl.sync.idx.b32 %0, %1, 0, 0x1f, 0xffffffff;" : "=r"(v) : "r"(fresh_tid() >> 5)); return v;
}
__device__ __forceinline__ uint32_t fresh_cta() {
    uint32_t v; asm volatile("mov.u32 %0, %%ctaid.x;" : "=r"(v)); return v;
}
__device__ __forceinline__ float rsqrt_fast(float v) { float r; asm("rsqrt.approx.ftz.f32 %0, %1;" : "=f"(r) : "f"(v)); return r; }
__device__ __forceinline__ float sqrt_fast(float v) { float r; asm("sqrt.approx.f32 %0, %1;" : "=f"(r) : "f"(v)); return r; }

template <int TB>
__device__ __forceinline__ void wgmma_n64_h_set(uint32_t (&d)[16], const uint32_t* a, uint64_t desc) {
    asm volatile(
        "{\n.reg .pred p;\nsetp.ne.b32 p, 0, 0;\n"
        "wgmma.mma_async.sync.aligned.m64n64k16.f16.f16.f16 "
        "{%0,%1,%2,%3,%4,%5,%6,%7,%8,%9,%10,%11,%12,%13,%14,%15}, {%16,%17,%18,%19}, %20, p, 1, 1, %21;\n}\n"
        : "=r"(d[0]), "=r"(d[1]), "=r"(d[2]), "=r"(d[3]), "=r"(d[4]), "=r"(d[5]), "=r"(d[6]), "=r"(d[7]), "=r"(d[8]), "=r"(d[9]), "=r"(d[10]), "=r"(d[11]), "=r"(d[12]), "=r"(d[13]), "=r"(d[14]), "=r"(d[15])
        : "r"(a[0]), "r"(a[1]), "r"(a[2]), "r"(a[3]), "l"(desc), "n"(TB));
}
template <int TB>
__device__ __forceinline__ void wgmma_n64_h_acc(uint32_t (&d)[16], const uint32_t* a, uint64_t desc) {
    asm volatile(
        "{\n.reg .pred p;\nsetp.ne.b32 p, 1, 0;\n"
        "wgmma.mma_async.sync.aligned.m64n64k16.f16.f16.f16 "
        "{%0,%1,%2,%3,%4,%5,%6,%7,%8,%9,%10,%11,%12,%13,%14,%15}, {%16,%17,%18,%19}, %20, p, 1, 1, %21;\n}\n"
        : "+r"(d[0]), "+r"(d[1]), "+r"(d[2]), "+r"(d[3]), "+r"(d[4]), "+r"(d[5]), "+r"(d[6]), "+r"(d[7]), "+r"(d[8]), "+r"(d[9]), "+r"(d[10]), "+r"(d[11]), "+r"(d[12]), "+r"(d[13]), "+r"(d[14]), "+r"(d[15])
        : "r"(a[0]), "r"(a[1]), "r"(a[2]), "r"(a[3]), "l"(desc), "n"(TB));
}
__device__ __forceinline__ void wgmma_n64_h_acc_ss(uint32_t (&d)[16], uint64_t adesc, uint64_t desc) {
    asm volatile(
        "{\n.reg .pred p;\nsetp.ne.b32 p, 1, 0;\n"
        "wgmma.mma_async.sync.aligned.m64n64k16.f16.f16.f16 "
        "{%0,%1,%2,%3,%4,%5,%6,%7,%8,%9,%10,%11,%12,%13,%14,%15}, %16, %17, p, 1, 1, 1, 0;\n}\n"
        : "+r"(d[0]), "+r"(d[1]), "+r"(d[2]), "+r"(d[3]), "+r"(d[4]), "+r"(d[5]), "+r"(d[6]), "+r"(d[7]), "+r"(d[8]), "+r"(d[9]), "+r"(d[10]), "+r"(d[11]), "+r"(d[12]), "+r"(d[13]), "+r"(d[14]), "+r"(d[15])
        : "l"(adesc), "l"(desc));
}
__device__ __forceinline__ void wgmma_n96_h_acc(uint32_t (&d)[24], const uint32_t* a, uint64_t desc) {
    asm volatile(
        "{\n.reg .pred p;\nsetp.ne.b32 p, 1, 0;\n"
        "wgmma.mma_async.sync.aligned.m64n96k16.f16.f16.f16 "
        "{%0,%1,%2,%3,%4,%5,%6,%7,%8,%9,%10,%11,%12,%13,%14,%15,%16,%17,%18,%19,%20,%21,%22,%23}, {%24,%25,%26,%27}, %28, p, 1, 1, 1;\n}\n"
        : "+r"(d[0]), "+r"(d[1]), "+r"(d[2]), "+r"(d[3]), "+r"(d[4]), "+r"(d[5]), "+r"(d[6]), "+r"(d[7]), "+r"(d[8]), "+r"(d[9]), "+r"(d[10]), "+r"(d[11]), "+r"(d[12]), "+r"(d[13]), "+r"(d[14]), "+r"(d[15]), "+r"(d[16]), "+r"(d[17]), "+r"(d[18]), "+r"(d[19]), "+r"(d[20]), "+r"(d[21]), "+r"(d[22]), "+r"(d[23])
        : "r"(a[0]), "r"(a[1]), "r"(a[2]), "r"(a[3]), "l"(desc));
}

template <int ACC>
__device__ __forceinline__ void wgmma_n8(float (&d)[4], uint32_t a0, uint32_t a1, uint32_t a2, uint32_t a3, uint64_t desc) {
    if (ACC)
        asm volatile("{\n.reg .pred p;\nsetp.ne.b32 p, 1, 0;\n"
                     "wgmma.mma_async.sync.aligned.m64n8k16.f32.bf16.bf16 {%0,%1,%2,%3}, {%4,%5,%6,%7}, %8, p, 1, 1, 0;\n}\n"
                     : "+f"(d[0]), "+f"(d[1]), "+f"(d[2]), "+f"(d[3]) : "r"(a0), "r"(a1), "r"(a2), "r"(a3), "l"(desc));
    else
        asm volatile("{\n.reg .pred p;\nsetp.ne.b32 p, 0, 0;\n"
                     "wgmma.mma_async.sync.aligned.m64n8k16.f32.bf16.bf16 {%0,%1,%2,%3}, {%4,%5,%6,%7}, %8, p, 1, 1, 0;\n}\n"
                     : "=f"(d[0]), "=f"(d[1]), "=f"(d[2]), "=f"(d[3]) : "r"(a0), "r"(a1), "r"(a2), "r"(a3), "l"(desc));
}

struct Params {
    CUtensorMap w2_map;
    const __nv_bfloat16* x;
    const __nv_bfloat16* dw;
    const __nv_bfloat16* w1;
    const __nv_bfloat16* gamma;
    const __nv_bfloat16* beta;
    __nv_bfloat16* out;
    uint64_t sel[3];
    uint32_t w1desc, w2desc, ydesc;
};

__device__ __forceinline__ uint32_t cta_tile0(uint32_t cta) {
    return (cta >> 3) * (ROWS_PER_CTA * ROW_BYTES) + (cta & 7) * TILE_BYTES;
}

struct Producer {
    uint32_t w[9][6];
    uint32_t xoff[2];
    uint32_t yoff[2][2];
    uint32_t stat, own;
    int lane, warp;
};

struct RowCopy {
    const char* x0;
    char* y0;
    uint32_t cut0, cut1;
    int first, last;
};
__device__ __forceinline__ RowCopy row_copy(const Params& prm) {
    const uint32_t cta = fresh_cta(), strip = cta & 7, t0 = cta_tile0(cta);
    RowCopy r;
    r.x0 = (const char*)prm.x + t0 - ROW_BYTES - 192;
    r.y0 = (char*)prm.out + t0;
    r.cut0 = strip == 0 ? 192 : 0;
    r.cut1 = strip == 7 ? 192 : 0;
    r.first = cta < 8 ? 1 : 0;
    r.last = cta >= NUM_CTAS - 8 ? STEPS - 2 : STEPS - 1;
    return r;
}
__device__ __forceinline__ void issue_row_load(const RowCopy& r, int i, uint32_t slot) {
    const char* src = (i >= r.first && i <= r.last) ? r.x0 + (uint32_t)i * ROW_BYTES : (const char*)g_zero_row;
    const uint32_t bar = sb + SM_XFULL + slot * SLOT_BYTES, dst = sb + SM_X + slot * SLOT_BYTES;
    expect_tx(bar, XHALF_BYTES - r.cut0);
    bulk_load(dst + r.cut0, src + r.cut0, XHALF_BYTES - r.cut0, bar);
    expect_tx(bar, XHALF_BYTES - r.cut1);
    bulk_load(dst + XHALF_B, src + 32 * 192, XHALF_BYTES - r.cut1, bar);
}

__device__ __forceinline__ float quad_sum(float v) {
    v += __shfl_xor_sync(0xffffffffu, v, 1);
    v += __shfl_xor_sync(0xffffffffu, v, 2);
    return v;
}

__device__ __forceinline__ void load_x(uint32_t (&v)[6][6], const Producer& c, uint32_t row) {
#pragma unroll
    for (int k = 0; k < 6; k++) {
        asm volatile("ld.shared.v4.b32 {%0,%1,%2,%3}, [%4];"
                     : "=r"(v[k][0]), "=r"(v[k][1]), "=r"(v[k][2]), "=r"(v[k][3]) : "r"(row + c.xoff[0] + k * 192));
        asm volatile("ld.shared.v2.b32 {%0,%1}, [%2];" : "=r"(v[k][4]), "=r"(v[k][5]) : "r"(row + c.xoff[1] + k * 192));
    }
}
template <int DY, int STRIDE>
__device__ __forceinline__ void conv_row(uint32_t (&dst)[24], const uint32_t* src, const uint32_t (&v)[6][6], const Producer& c) {
#pragma unroll
    for (int o = 0; o < 4; o++)
#pragma unroll
        for (int u = 0; u < 6; u++)
            dst[o * 6 + u] = bf2_fma(v[o + 2][u], c.w[3 * DY + 2][u], bf2_fma(v[o + 1][u], c.w[3 * DY + 1][u],
                             bf2_fma(v[o][u], c.w[3 * DY][u], STRIDE ? src[o * 6 + u] : src[2 * o + 1])));
}
__device__ __forceinline__ void start_sums(float (&d)[4], const uint32_t (&A)[24], const uint32_t (&q)[4], const Params& prm) {
    wg_fence();
#pragma unroll
    for (int k = 0; k < 6; k++) {
        const int r = (k / 3) * 12 + (k % 3) * 2;
        if (k == 0) wgmma_n8<0>(d, A[r], A[r + 6], A[r + 1], A[r + 7], prm.sel[0]);
        else wgmma_n8<1>(d, A[r], A[r + 6], A[r + 1], A[r + 7], prm.sel[k / 3]);
    }
    wgmma_n8<1>(d, q[0], q[1], q[2], q[3], prm.sel[2]);
    wg_commit();
}
__device__ __forceinline__ void finish_sums(float (&d)[4], int lane, float& sum, float& sq) {
    wg_wait<0>();
    asm volatile("" : "+f"(d[0]), "+f"(d[1]), "+f"(d[2]), "+f"(d[3])::"memory");
    sum = (lane & 1) ? d[2] : d[0];
    sq = (lane & 1) ? d[3] : d[1];
    sum += __shfl_xor_sync(0xffffffffu, sum, 4);
    sq += __shfl_xor_sync(0xffffffffu, sq, 4);
}

#define HAND_OVER(name, base, r) asm volatile("mov.b32 " name "%6, %0; mov.b32 " name "%7, %1; mov.b32 " name "%8, %2;\n" \
    "mov.b32 " name "%9, %3; mov.b32 " name "%10, %4; mov.b32 " name "%11, %5;" ::"r"((r)[0]), "r"((r)[1]), "r"((r)[2]), \
    "r"((r)[3]), "r"((r)[4]), "r"((r)[5]), "n"(base), "n"(base + 1), "n"(base + 2), "n"(base + 3), "n"(base + 4), "n"(base + 5))
template <int K> __device__ __forceinline__ void hand_over(const Producer& c, const uint32_t (&B)[24], const uint32_t (&C)[24],
                                                           const uint32_t (&v)[6][6]) {
    HAND_OVER("pw", K * 6, c.w[K]);
    if (K < 6) HAND_OVER("pv", K * 6, v[K % 6]);
    if (K < 4) { HAND_OVER("pb", K * 6, B + K % 4 * 6); HAND_OVER("pc", K * 6, C + K % 4 * 6); }
    if constexpr (K < 8) hand_over<K + 1>(c, B, C, v);
}
static_assert(sb + SM_BAR + BAR_DUMMY * 8 == 230880, "layout");
__device__ __forceinline__ void produce_tiles(const Producer& c, const Params& prm) {
    asm volatile(
        "{\n"
        ".reg .b32 pa<24>, pq<4>, m<6>, y<6>, rr, mm, t, so, sp, ph, ad, tt, cnt;\n"
        ".reg .b16 xl, xh;\n"
        ".reg .f32 d<4>, us, s0, s1, f0, f1, kq;\n"
        ".reg .pred pt, pf, pr, pw, px, pl, po, pe;\n"
        "setp.ne.b32 pt, 1, 0; setp.ne.b32 pf, 0, 0; setp.eq.u32 pl, %8, 0; and.b32 tt, %8, 1; setp.ne.u32 po, tt, 0;\n"
        "and.b32 tt, %8, 4; setp.ne.u32 pr, tt, 0; selp.f32 kq, 0f3F802D41, 0f3F7FA57E, pr;\n"
        "mov.u32 t, 0; mov.u32 so, 0; mov.u32 sp, 55896; mov.u32 ph, 1;\n"
        "LOOP:\n"
        ASM_TRC("t", 0)
        "setp.eq.u32 pr, %12, 0;\n"
        "@pr bra.uni RARE;\n"
        "fence.proxy.async.shared::cta;\n"
        "@pl mbarrier.arrive.shared::cta.b64 _, [sp+174984];\n"
        "fma.rn.bf16x2 pa0, pv0, pw36, pb0; fma.rn.bf16x2 pa1, pv1, pw37, pb1; fma.rn.bf16x2 pa2, pv2, pw38, pb2; fma.rn.bf16x2 pa3, pv3, pw39, pb3; fma.rn.bf16x2 pa4, pv4, pw40, pb4; fma.rn.bf16x2 pa5, pv5, pw41, pb5;\n"
        "fma.rn.bf16x2 pa6, pv6, pw36, pb6; fma.rn.bf16x2 pa7, pv7, pw37, pb7; fma.rn.bf16x2 pa8, pv8, pw38, pb8; fma.rn.bf16x2 pa9, pv9, pw39, pb9; fma.rn.bf16x2 pa10, pv10, pw40, pb10; fma.rn.bf16x2 pa11, pv11, pw41, pb11;\n"
        "fma.rn.bf16x2 pa12, pv12, pw36, pb12; fma.rn.bf16x2 pa13, pv13, pw37, pb13; fma.rn.bf16x2 pa14, pv14, pw38, pb14; fma.rn.bf16x2 pa15, pv15, pw39, pb15; fma.rn.bf16x2 pa16, pv16, pw40, pb16; fma.rn.bf16x2 pa17, pv17, pw41, pb17;\n"
        "fma.rn.bf16x2 pa18, pv18, pw36, pb18; fma.rn.bf16x2 pa19, pv19, pw37, pb19; fma.rn.bf16x2 pa20, pv20, pw38, pb20; fma.rn.bf16x2 pa21, pv21, pw39, pb21; fma.rn.bf16x2 pa22, pv22, pw40, pb22; fma.rn.bf16x2 pa23, pv23, pw41, pb23;\n"
        "fma.rn.bf16x2 pa0, pv6, pw42, pa0; fma.rn.bf16x2 pa1, pv7, pw43, pa1; fma.rn.bf16x2 pa2, pv8, pw44, pa2; fma.rn.bf16x2 pa3, pv9, pw45, pa3; fma.rn.bf16x2 pa4, pv10, pw46, pa4; fma.rn.bf16x2 pa5, pv11, pw47, pa5;\n"
        "fma.rn.bf16x2 pa6, pv12, pw42, pa6; fma.rn.bf16x2 pa7, pv13, pw43, pa7; fma.rn.bf16x2 pa8, pv14, pw44, pa8; fma.rn.bf16x2 pa9, pv15, pw45, pa9; fma.rn.bf16x2 pa10, pv16, pw46, pa10; fma.rn.bf16x2 pa11, pv17, pw47, pa11;\n"
        "fma.rn.bf16x2 pa12, pv18, pw42, pa12; fma.rn.bf16x2 pa13, pv19, pw43, pa13; fma.rn.bf16x2 pa14, pv20, pw44, pa14; fma.rn.bf16x2 pa15, pv21, pw45, pa15; fma.rn.bf16x2 pa16, pv22, pw46, pa16; fma.rn.bf16x2 pa17, pv23, pw47, pa17;\n"
        "fma.rn.bf16x2 pa18, pv24, pw42, pa18; fma.rn.bf16x2 pa19, pv25, pw43, pa19; fma.rn.bf16x2 pa20, pv26, pw44, pa20; fma.rn.bf16x2 pa21, pv27, pw45, pa21; fma.rn.bf16x2 pa22, pv28, pw46, pa22; fma.rn.bf16x2 pa23, pv29, pw47, pa23;\n"
        "fma.rn.bf16x2 pa0, pv12, pw48, pa0; fma.rn.bf16x2 pa1, pv13, pw49, pa1; fma.rn.bf16x2 pa2, pv14, pw50, pa2; fma.rn.bf16x2 pa3, pv15, pw51, pa3; fma.rn.bf16x2 pa4, pv16, pw52, pa4; fma.rn.bf16x2 pa5, pv17, pw53, pa5;\n"
        "fma.rn.bf16x2 pa6, pv18, pw48, pa6; fma.rn.bf16x2 pa7, pv19, pw49, pa7; fma.rn.bf16x2 pa8, pv20, pw50, pa8; fma.rn.bf16x2 pa9, pv21, pw51, pa9; fma.rn.bf16x2 pa10, pv22, pw52, pa10; fma.rn.bf16x2 pa11, pv23, pw53, pa11;\n"
        "fma.rn.bf16x2 pa12, pv24, pw48, pa12; fma.rn.bf16x2 pa13, pv25, pw49, pa13; fma.rn.bf16x2 pa14, pv26, pw50, pa14; fma.rn.bf16x2 pa15, pv27, pw51, pa15; fma.rn.bf16x2 pa16, pv28, pw52, pa16; fma.rn.bf16x2 pa17, pv29, pw53, pa17;\n"
        "fma.rn.bf16x2 pa18, pv30, pw48, pa18; fma.rn.bf16x2 pa19, pv31, pw49, pa19; fma.rn.bf16x2 pa20, pv32, pw50, pa20; fma.rn.bf16x2 pa21, pv33, pw51, pa21; fma.rn.bf16x2 pa22, pv34, pw52, pa22; fma.rn.bf16x2 pa23, pv35, pw53, pa23;\n"
        "mul.rn.bf16x2 pq0, pa0, pa0; fma.rn.bf16x2 pq0, pa1, pa1, pq0; fma.rn.bf16x2 pq0, pa2, pa2, pq0; fma.rn.bf16x2 pq0, pa3, pa3, pq0; fma.rn.bf16x2 pq0, pa4, pa4, pq0; fma.rn.bf16x2 pq0, pa5, pa5, pq0;\n"
        "mul.rn.bf16x2 pq1, pa6, pa6; fma.rn.bf16x2 pq1, pa7, pa7, pq1; fma.rn.bf16x2 pq1, pa8, pa8, pq1; fma.rn.bf16x2 pq1, pa9, pa9, pq1; fma.rn.bf16x2 pq1, pa10, pa10, pq1; fma.rn.bf16x2 pq1, pa11, pa11, pq1;\n"
        "mul.rn.bf16x2 pq2, pa12, pa12; fma.rn.bf16x2 pq2, pa13, pa13, pq2; fma.rn.bf16x2 pq2, pa14, pa14, pq2; fma.rn.bf16x2 pq2, pa15, pa15, pq2; fma.rn.bf16x2 pq2, pa16, pa16, pq2; fma.rn.bf16x2 pq2, pa17, pa17, pq2;\n"
        "mul.rn.bf16x2 pq3, pa18, pa18; fma.rn.bf16x2 pq3, pa19, pa19, pq3; fma.rn.bf16x2 pq3, pa20, pa20, pq3; fma.rn.bf16x2 pq3, pa21, pa21, pq3; fma.rn.bf16x2 pq3, pa22, pa22, pq3; fma.rn.bf16x2 pq3, pa23, pa23, pq3;\n"
        "B0:\n"
        "wgmma.fence.sync.aligned;\n"
        "wgmma.mma_async.sync.aligned.m64n8k16.f32.bf16.bf16 {d0,d1,d2,d3}, {pa0,pa6,pa1,pa7}, %9, pf, 1, 1, 0;\n"
        "wgmma.mma_async.sync.aligned.m64n8k16.f32.bf16.bf16 {d0,d1,d2,d3}, {pa2,pa8,pa3,pa9}, %9, pt, 1, 1, 0;\n"
        "wgmma.mma_async.sync.aligned.m64n8k16.f32.bf16.bf16 {d0,d1,d2,d3}, {pa4,pa10,pa5,pa11}, %9, pt, 1, 1, 0;\n"
        "wgmma.mma_async.sync.aligned.m64n8k16.f32.bf16.bf16 {d0,d1,d2,d3}, {pa12,pa18,pa13,pa19}, %10, pt, 1, 1, 0;\n"
        "wgmma.mma_async.sync.aligned.m64n8k16.f32.bf16.bf16 {d0,d1,d2,d3}, {pa14,pa20,pa15,pa21}, %10, pt, 1, 1, 0;\n"
        "wgmma.mma_async.sync.aligned.m64n8k16.f32.bf16.bf16 {d0,d1,d2,d3}, {pa16,pa22,pa17,pa23}, %10, pt, 1, 1, 0;\n"
        "wgmma.mma_async.sync.aligned.m64n8k16.f32.bf16.bf16 {d0,d1,d2,d3}, {pq0,pq1,pq2,pq3}, %11, pt, 1, 1, 0;\n"
        "wgmma.commit_group.sync.aligned;\n"
        "add.u32 ad, %7, so; ld.shared.f32 us, [ad+4];\n"
        "fma.rn.bf16x2 pb0, pv0, pw18, pc0; fma.rn.bf16x2 pb1, pv1, pw19, pc1; fma.rn.bf16x2 pb2, pv2, pw20, pc2; fma.rn.bf16x2 pb3, pv3, pw21, pc3; fma.rn.bf16x2 pb4, pv4, pw22, pc4; fma.rn.bf16x2 pb5, pv5, pw23, pc5;\n"
        "fma.rn.bf16x2 pb6, pv6, pw18, pc6; fma.rn.bf16x2 pb7, pv7, pw19, pc7; fma.rn.bf16x2 pb8, pv8, pw20, pc8; fma.rn.bf16x2 pb9, pv9, pw21, pc9; fma.rn.bf16x2 pb10, pv10, pw22, pc10; fma.rn.bf16x2 pb11, pv11, pw23, pc11;\n"
        "fma.rn.bf16x2 pb0, pv6, pw24, pb0; fma.rn.bf16x2 pb1, pv7, pw25, pb1; fma.rn.bf16x2 pb2, pv8, pw26, pb2; fma.rn.bf16x2 pb3, pv9, pw27, pb3; fma.rn.bf16x2 pb4, pv10, pw28, pb4; fma.rn.bf16x2 pb5, pv11, pw29, pb5;\n"
        "fma.rn.bf16x2 pb6, pv12, pw24, pb6; fma.rn.bf16x2 pb7, pv13, pw25, pb7; fma.rn.bf16x2 pb8, pv14, pw26, pb8; fma.rn.bf16x2 pb9, pv15, pw27, pb9; fma.rn.bf16x2 pb10, pv16, pw28, pb10; fma.rn.bf16x2 pb11, pv17, pw29, pb11;\n"
        "fma.rn.bf16x2 pb0, pv12, pw30, pb0; fma.rn.bf16x2 pb1, pv13, pw31, pb1; fma.rn.bf16x2 pb2, pv14, pw32, pb2; fma.rn.bf16x2 pb3, pv15, pw33, pb3; fma.rn.bf16x2 pb4, pv16, pw34, pb4; fma.rn.bf16x2 pb5, pv17, pw35, pb5;\n"
        "fma.rn.bf16x2 pb6, pv18, pw30, pb6; fma.rn.bf16x2 pb7, pv19, pw31, pb7; fma.rn.bf16x2 pb8, pv20, pw32, pb8; fma.rn.bf16x2 pb9, pv21, pw33, pb9; fma.rn.bf16x2 pb10, pv22, pw34, pb10; fma.rn.bf16x2 pb11, pv23, pw35, pb11;\n"
        "B1:\n"
        "fma.rn.bf16x2 pb12, pv12, pw18, pc12; fma.rn.bf16x2 pb13, pv13, pw19, pc13; fma.rn.bf16x2 pb14, pv14, pw20, pc14; fma.rn.bf16x2 pb15, pv15, pw21, pc15; fma.rn.bf16x2 pb16, pv16, pw22, pc16; fma.rn.bf16x2 pb17, pv17, pw23, pc17;\n"
        "fma.rn.bf16x2 pb18, pv18, pw18, pc18; fma.rn.bf16x2 pb19, pv19, pw19, pc19; fma.rn.bf16x2 pb20, pv20, pw20, pc20; fma.rn.bf16x2 pb21, pv21, pw21, pc21; fma.rn.bf16x2 pb22, pv22, pw22, pc22; fma.rn.bf16x2 pb23, pv23, pw23, pc23;\n"
        "fma.rn.bf16x2 pb12, pv18, pw24, pb12; fma.rn.bf16x2 pb13, pv19, pw25, pb13; fma.rn.bf16x2 pb14, pv20, pw26, pb14; fma.rn.bf16x2 pb15, pv21, pw27, pb15; fma.rn.bf16x2 pb16, pv22, pw28, pb16; fma.rn.bf16x2 pb17, pv23, pw29, pb17;\n"
        "fma.rn.bf16x2 pb18, pv24, pw24, pb18; fma.rn.bf16x2 pb19, pv25, pw25, pb19; fma.rn.bf16x2 pb20, pv26, pw26, pb20; fma.rn.bf16x2 pb21, pv27, pw27, pb21; fma.rn.bf16x2 pb22, pv28, pw28, pb22; fma.rn.bf16x2 pb23, pv29, pw29, pb23;\n"
        "fma.rn.bf16x2 pb12, pv24, pw30, pb12; fma.rn.bf16x2 pb13, pv25, pw31, pb13; fma.rn.bf16x2 pb14, pv26, pw32, pb14; fma.rn.bf16x2 pb15, pv27, pw33, pb15; fma.rn.bf16x2 pb16, pv28, pw34, pb16; fma.rn.bf16x2 pb17, pv29, pw35, pb17;\n"
        "fma.rn.bf16x2 pb18, pv30, pw30, pb18; fma.rn.bf16x2 pb19, pv31, pw31, pb19; fma.rn.bf16x2 pb20, pv32, pw32, pb20; fma.rn.bf16x2 pb21, pv33, pw33, pb21; fma.rn.bf16x2 pb22, pv34, pw34, pb22; fma.rn.bf16x2 pb23, pv35, pw35, pb23;\n"
        "C0:\n"
        "wgmma.wait_group.sync.aligned 0;\n"
        "selp.f32 s0, d2, d0, po; selp.f32 s1, d3, d1, po;\n"
        "shfl.sync.bfly.b32 f0, s0, 4, 0x1f, 0xffffffff; shfl.sync.bfly.b32 f1, s1, 4, 0x1f, 0xffffffff;\n"
        "fma.rn.bf16x2 pc0, pv0, pw0, ps1; fma.rn.bf16x2 pc1, pv1, pw1, ps1; fma.rn.bf16x2 pc2, pv2, pw2, ps1; fma.rn.bf16x2 pc3, pv3, pw3, ps1; fma.rn.bf16x2 pc4, pv4, pw4, ps1; fma.rn.bf16x2 pc5, pv5, pw5, ps1;\n"
        "fma.rn.bf16x2 pc6, pv6, pw0, ps3; fma.rn.bf16x2 pc7, pv7, pw1, ps3; fma.rn.bf16x2 pc8, pv8, pw2, ps3; fma.rn.bf16x2 pc9, pv9, pw3, ps3; fma.rn.bf16x2 pc10, pv10, pw4, ps3; fma.rn.bf16x2 pc11, pv11, pw5, ps3;\n"
        "fma.rn.bf16x2 pc12, pv12, pw0, ps5; fma.rn.bf16x2 pc13, pv13, pw1, ps5; fma.rn.bf16x2 pc14, pv14, pw2, ps5; fma.rn.bf16x2 pc15, pv15, pw3, ps5; fma.rn.bf16x2 pc16, pv16, pw4, ps5; fma.rn.bf16x2 pc17, pv17, pw5, ps5;\n"
        "fma.rn.bf16x2 pc18, pv18, pw0, ps7; fma.rn.bf16x2 pc19, pv19, pw1, ps7; fma.rn.bf16x2 pc20, pv20, pw2, ps7; fma.rn.bf16x2 pc21, pv21, pw3, ps7; fma.rn.bf16x2 pc22, pv22, pw4, ps7; fma.rn.bf16x2 pc23, pv23, pw5, ps7;\n"
        "fma.rn.bf16x2 pc0, pv6, pw6, pc0; fma.rn.bf16x2 pc1, pv7, pw7, pc1; fma.rn.bf16x2 pc2, pv8, pw8, pc2; fma.rn.bf16x2 pc3, pv9, pw9, pc3; fma.rn.bf16x2 pc4, pv10, pw10, pc4; fma.rn.bf16x2 pc5, pv11, pw11, pc5;\n"
        "fma.rn.bf16x2 pc6, pv12, pw6, pc6; fma.rn.bf16x2 pc7, pv13, pw7, pc7; fma.rn.bf16x2 pc8, pv14, pw8, pc8; fma.rn.bf16x2 pc9, pv15, pw9, pc9; fma.rn.bf16x2 pc10, pv16, pw10, pc10; fma.rn.bf16x2 pc11, pv17, pw11, pc11;\n"
        "fma.rn.bf16x2 pc12, pv18, pw6, pc12; fma.rn.bf16x2 pc13, pv19, pw7, pc13; fma.rn.bf16x2 pc14, pv20, pw8, pc14; fma.rn.bf16x2 pc15, pv21, pw9, pc15; fma.rn.bf16x2 pc16, pv22, pw10, pc16; fma.rn.bf16x2 pc17, pv23, pw11, pc17;\n"
        "fma.rn.bf16x2 pc18, pv24, pw6, pc18; fma.rn.bf16x2 pc19, pv25, pw7, pc19; fma.rn.bf16x2 pc20, pv26, pw8, pc20; fma.rn.bf16x2 pc21, pv27, pw9, pc21; fma.rn.bf16x2 pc22, pv28, pw10, pc22; fma.rn.bf16x2 pc23, pv29, pw11, pc23;\n"
        "fma.rn.bf16x2 pc0, pv12, pw12, pc0; fma.rn.bf16x2 pc1, pv13, pw13, pc1; fma.rn.bf16x2 pc2, pv14, pw14, pc2; fma.rn.bf16x2 pc3, pv15, pw15, pc3; fma.rn.bf16x2 pc4, pv16, pw16, pc4; fma.rn.bf16x2 pc5, pv17, pw17, pc5;\n"
        "fma.rn.bf16x2 pc6, pv18, pw12, pc6; fma.rn.bf16x2 pc7, pv19, pw13, pc7; fma.rn.bf16x2 pc8, pv20, pw14, pc8; fma.rn.bf16x2 pc9, pv21, pw15, pc9; fma.rn.bf16x2 pc10, pv22, pw16, pc10; fma.rn.bf16x2 pc11, pv23, pw17, pc11;\n"
        "fma.rn.bf16x2 pc12, pv24, pw12, pc12; fma.rn.bf16x2 pc13, pv25, pw13, pc13; fma.rn.bf16x2 pc14, pv26, pw14, pc14; fma.rn.bf16x2 pc15, pv27, pw15, pc15; fma.rn.bf16x2 pc16, pv28, pw16, pc16; fma.rn.bf16x2 pc17, pv29, pw17, pc17;\n"
        "fma.rn.bf16x2 pc18, pv30, pw12, pc18; fma.rn.bf16x2 pc19, pv31, pw13, pc19; fma.rn.bf16x2 pc20, pv32, pw14, pc20; fma.rn.bf16x2 pc21, pv33, pw15, pc21; fma.rn.bf16x2 pc22, pv34, pw16, pc22; fma.rn.bf16x2 pc23, pv35, pw17, pc23;\n"
        "add.f32 s0, s0, f0; add.f32 s1, s1, f1; mul.f32 s0, s0, 0fBC2AAAAB;\n"
        "neg.f32 f0, s0; fma.rn.f32 f0, f0, s0, %13; fma.rn.f32 f0, s1, 0f3C2AAAAB, f0; max.f32 f0, f0, %13;\n"
        "rsqrt.approx.ftz.f32 f0, f0; mul.f32 f0, f0, %14; cvt.rn.bf16x2.f32 tt, f0, 0f00000000; mov.b32 f0, tt;\n"
        "mul.f32 f1, s0, kq; mul.f32 f1, f1, f0; cvt.rn.bf16x2.f32 tt, f1, f0; add.f32 us, us, s0; cvt.rn.bf16x2.f32 mm, us, us;\n"
        "add.u32 ad, %7, so; st.shared.v2.b32 [ad], {tt, mm};\n"
        "add.u32 ad, %6, so; ld.shared.v4.b32 {ps0,ps1,ps2,ps3}, [ad]; ld.shared.v4.b32 {ps4,ps5,ps6,ps7}, [ad+16];\n"
        "mbarrier.try_wait.parity.shared::cta.b64 pw, [so+174992], ph;\n"
        "mbarrier.try_wait.parity.shared::cta.b64 px, [so+174976], ph;\n"
        "and.pred pw, pw, px;\n"
        "N0:\n"
        "@!pw bra.uni SPIN;\n"
        "BACK:\n"
        "add.u32 ad, %0, so; ld.shared.v4.b32 {pv0,pv1,pv2,pv3}, [ad+0];\n"
        "add.u32 ad, %1, so; ld.shared.v2.b32 {pv4,pv5}, [ad+0];\n"
        "add.u32 ad, %0, so; ld.shared.v4.b32 {pv6,pv7,pv8,pv9}, [ad+192];\n"
        "add.u32 ad, %1, so; ld.shared.v2.b32 {pv10,pv11}, [ad+192];\n"
        "mov.b32 {xl, xh}, ps0; mov.b32 rr, {xl, xl}; mov.b32 mm, {xh, xh}; fma.rn.bf16x2 pa0, pa0, rr, mm; fma.rn.bf16x2 pa1, pa1, rr, mm; fma.rn.bf16x2 pa2, pa2, rr, mm; fma.rn.bf16x2 pa3, pa3, rr, mm; fma.rn.bf16x2 pa4, pa4, rr, mm; fma.rn.bf16x2 pa5, pa5, rr, mm;\n"
        "and.b32 m0, pa0, 0x7fff7fff; and.b32 m1, pa1, 0x7fff7fff; and.b32 m2, pa2, 0x7fff7fff; and.b32 m3, pa3, 0x7fff7fff; and.b32 m4, pa4, 0x7fff7fff; and.b32 m5, pa5, 0x7fff7fff;\n"
        "mad.lo.u32 y0, m0, 7, pa0; mad.lo.u32 y1, m1, 7, pa1; mad.lo.u32 y2, m2, 7, pa2; mad.lo.u32 y3, m3, 7, pa3; mad.lo.u32 y4, m4, 7, pa4; mad.lo.u32 y5, m5, 7, pa5;\n"
        "add.u32 ad, %2, so; st.shared.v4.b32 [ad+0], {y0,y1,y2,y3};\n"
        "add.u32 ad, %4, so; st.shared.v2.b32 [ad+0], {y4,y5};\n"
        "N1:\n"
        "add.u32 ad, %0, so; ld.shared.v4.b32 {pv12,pv13,pv14,pv15}, [ad+384];\n"
        "add.u32 ad, %1, so; ld.shared.v2.b32 {pv16,pv17}, [ad+384];\n"
        "add.u32 ad, %0, so; ld.shared.v4.b32 {pv18,pv19,pv20,pv21}, [ad+576];\n"
        "add.u32 ad, %1, so; ld.shared.v2.b32 {pv22,pv23}, [ad+576];\n"
        "mov.b32 {xl, xh}, ps2; mov.b32 rr, {xl, xl}; mov.b32 mm, {xh, xh}; fma.rn.bf16x2 pa6, pa6, rr, mm; fma.rn.bf16x2 pa7, pa7, rr, mm; fma.rn.bf16x2 pa8, pa8, rr, mm; fma.rn.bf16x2 pa9, pa9, rr, mm; fma.rn.bf16x2 pa10, pa10, rr, mm; fma.rn.bf16x2 pa11, pa11, rr, mm;\n"
        "and.b32 m0, pa6, 0x7fff7fff; and.b32 m1, pa7, 0x7fff7fff; and.b32 m2, pa8, 0x7fff7fff; and.b32 m3, pa9, 0x7fff7fff; and.b32 m4, pa10, 0x7fff7fff; and.b32 m5, pa11, 0x7fff7fff;\n"
        "mad.lo.u32 y0, m0, 7, pa6; mad.lo.u32 y1, m1, 7, pa7; mad.lo.u32 y2, m2, 7, pa8; mad.lo.u32 y3, m3, 7, pa9; mad.lo.u32 y4, m4, 7, pa10; mad.lo.u32 y5, m5, 7, pa11;\n"
        "add.u32 ad, %3, so; st.shared.v4.b32 [ad+0], {y0,y1,y2,y3};\n"
        "add.u32 ad, %5, so; st.shared.v2.b32 [ad+0], {y4,y5};\n"
        "N2:\n"
        "add.u32 ad, %0, so; ld.shared.v4.b32 {pv24,pv25,pv26,pv27}, [ad+768];\n"
        "add.u32 ad, %1, so; ld.shared.v2.b32 {pv28,pv29}, [ad+768];\n"
        "mov.b32 {xl, xh}, ps4; mov.b32 rr, {xl, xl}; mov.b32 mm, {xh, xh}; fma.rn.bf16x2 pa12, pa12, rr, mm; fma.rn.bf16x2 pa13, pa13, rr, mm; fma.rn.bf16x2 pa14, pa14, rr, mm; fma.rn.bf16x2 pa15, pa15, rr, mm; fma.rn.bf16x2 pa16, pa16, rr, mm; fma.rn.bf16x2 pa17, pa17, rr, mm;\n"
        "and.b32 m0, pa12, 0x7fff7fff; and.b32 m1, pa13, 0x7fff7fff; and.b32 m2, pa14, 0x7fff7fff; and.b32 m3, pa15, 0x7fff7fff; and.b32 m4, pa16, 0x7fff7fff; and.b32 m5, pa17, 0x7fff7fff;\n"
        "mad.lo.u32 y0, m0, 7, pa12; mad.lo.u32 y1, m1, 7, pa13; mad.lo.u32 y2, m2, 7, pa14; mad.lo.u32 y3, m3, 7, pa15; mad.lo.u32 y4, m4, 7, pa16; mad.lo.u32 y5, m5, 7, pa17;\n"
        "add.u32 ad, %2, so; st.shared.v4.b32 [ad+2048], {y0,y1,y2,y3};\n"
        "add.u32 ad, %4, so; st.shared.v2.b32 [ad+1024], {y4,y5};\n"
        "N3:\n"
        "add.u32 ad, %0, so; ld.shared.v4.b32 {pv30,pv31,pv32,pv33}, [ad+960];\n"
        "add.u32 ad, %1, so; ld.shared.v2.b32 {pv34,pv35}, [ad+960];\n"
        "mov.b32 {xl, xh}, ps6; mov.b32 rr, {xl, xl}; mov.b32 mm, {xh, xh}; fma.rn.bf16x2 pa18, pa18, rr, mm; fma.rn.bf16x2 pa19, pa19, rr, mm; fma.rn.bf16x2 pa20, pa20, rr, mm; fma.rn.bf16x2 pa21, pa21, rr, mm; fma.rn.bf16x2 pa22, pa22, rr, mm; fma.rn.bf16x2 pa23, pa23, rr, mm;\n"
        "and.b32 m0, pa18, 0x7fff7fff; and.b32 m1, pa19, 0x7fff7fff; and.b32 m2, pa20, 0x7fff7fff; and.b32 m3, pa21, 0x7fff7fff; and.b32 m4, pa22, 0x7fff7fff; and.b32 m5, pa23, 0x7fff7fff;\n"
        "mad.lo.u32 y0, m0, 7, pa18; mad.lo.u32 y1, m1, 7, pa19; mad.lo.u32 y2, m2, 7, pa20; mad.lo.u32 y3, m3, 7, pa21; mad.lo.u32 y4, m4, 7, pa22; mad.lo.u32 y5, m5, 7, pa23;\n"
        "add.u32 ad, %3, so; st.shared.v4.b32 [ad+2048], {y0,y1,y2,y3};\n"
        "add.u32 ad, %5, so; st.shared.v2.b32 [ad+1024], {y4,y5};\n"
        "mov.u32 sp, so; add.u32 so, so, 26624; setp.eq.u32 pr, so, 79872; selp.u32 so, 0, so, pr; selp.u32 tt, 1, 0, pr; xor.b32 ph, ph, tt;\n"
        "add.u32 t, t, 1; setp.lt.u32 pe, t, 32;\n"
        "@pe bra.uni LOOP;\n"
        "bra.uni DONE;\n"
        "SPIN: mov.u32 cnt, 0;\n"
        ASM_TRC("t", 1)
        "SPINL:\n"
        "mbarrier.try_wait.parity.shared::cta.b64 pw, [so+174992], ph;\n"
        "mbarrier.try_wait.parity.shared::cta.b64 px, [so+174976], ph;\n"
        "and.pred pw, pw, px;\n"
        "@pw bra.uni BACK;\n"
        "add.u32 cnt, cnt, 1; setp.lt.u32 pw, cnt, 0x100000;\n"
        "@pw bra.uni SPINL;\n"
        "trap;\n"
        "RARE:\n"
        "ld.volatile.shared.u32 tt, [%6];\n"
        "mov.b32 pa0, tt; mov.b32 pa1, tt; mov.b32 pa2, tt; mov.b32 pa3, tt; mov.b32 pa4, tt; mov.b32 pa5, tt; mov.b32 pa6, tt; mov.b32 pa7, tt; mov.b32 pa8, tt; mov.b32 pa9, tt; mov.b32 pa10, tt; mov.b32 pa11, tt;\n"
        "mov.b32 pa12, tt; mov.b32 pa13, tt; mov.b32 pa14, tt; mov.b32 pa15, tt; mov.b32 pa16, tt; mov.b32 pa17, tt; mov.b32 pa18, tt; mov.b32 pa19, tt; mov.b32 pa20, tt; mov.b32 pa21, tt; mov.b32 pa22, tt; mov.b32 pa23, tt;\n"
        "mov.b32 pb0, tt; mov.b32 pb1, tt; mov.b32 pb2, tt; mov.b32 pb3, tt; mov.b32 pb4, tt; mov.b32 pb5, tt; mov.b32 pb6, tt; mov.b32 pb7, tt; mov.b32 pb8, tt; mov.b32 pb9, tt; mov.b32 pb10, tt; mov.b32 pb11, tt;\n"
        "mov.b32 pb12, tt; mov.b32 pb13, tt; mov.b32 pb14, tt; mov.b32 pb15, tt; mov.b32 pb16, tt; mov.b32 pb17, tt; mov.b32 pb18, tt; mov.b32 pb19, tt; mov.b32 pb20, tt; mov.b32 pb21, tt; mov.b32 pb22, tt; mov.b32 pb23, tt;\n"
        "mov.b32 pc0, tt; mov.b32 pc1, tt; mov.b32 pc2, tt; mov.b32 pc3, tt; mov.b32 pc4, tt; mov.b32 pc5, tt; mov.b32 pc6, tt; mov.b32 pc7, tt; mov.b32 pc8, tt; mov.b32 pc9, tt; mov.b32 pc10, tt; mov.b32 pc11, tt;\n"
        "mov.b32 pc12, tt; mov.b32 pc13, tt; mov.b32 pc14, tt; mov.b32 pc15, tt; mov.b32 pc16, tt; mov.b32 pc17, tt; mov.b32 pc18, tt; mov.b32 pc19, tt; mov.b32 pc20, tt; mov.b32 pc21, tt; mov.b32 pc22, tt; mov.b32 pc23, tt;\n"
        "mov.b32 pv0, tt; mov.b32 pv1, tt; mov.b32 pv2, tt; mov.b32 pv3, tt; mov.b32 pv4, tt; mov.b32 pv5, tt; mov.b32 pv6, tt; mov.b32 pv7, tt; mov.b32 pv8, tt; mov.b32 pv9, tt; mov.b32 pv10, tt; mov.b32 pv11, tt;\n"
        "mov.b32 pv12, tt; mov.b32 pv13, tt; mov.b32 pv14, tt; mov.b32 pv15, tt; mov.b32 pv16, tt; mov.b32 pv17, tt; mov.b32 pv18, tt; mov.b32 pv19, tt; mov.b32 pv20, tt; mov.b32 pv21, tt; mov.b32 pv22, tt; mov.b32 pv23, tt;\n"
        "mov.b32 pv24, tt; mov.b32 pv25, tt; mov.b32 pv26, tt; mov.b32 pv27, tt; mov.b32 pv28, tt; mov.b32 pv29, tt; mov.b32 pv30, tt; mov.b32 pv31, tt; mov.b32 pv32, tt; mov.b32 pv33, tt; mov.b32 pv34, tt; mov.b32 pv35, tt;\n"
        "mov.b32 ps0, tt; mov.b32 ps1, tt; mov.b32 ps2, tt; mov.b32 ps3, tt; mov.b32 ps4, tt; mov.b32 ps5, tt; mov.b32 ps6, tt; mov.b32 ps7, tt; mov.b32 pq0, tt; mov.b32 pq1, tt; mov.b32 pq2, tt; mov.b32 pq3, tt;\n"
        "mov.b32 m0, tt; mov.b32 m1, tt; mov.b32 m2, tt; mov.b32 m3, tt; mov.b32 m4, tt; mov.b32 m5, tt; mov.b32 y0, tt; mov.b32 y1, tt; mov.b32 y2, tt; mov.b32 y3, tt; mov.b32 y4, tt; mov.b32 y5, tt;\n"
        "mov.b32 us, tt; setp.ne.u32 pw, t, 7;\n"
        "wgmma.fence.sync.aligned;\n"
        "setp.eq.u32 pr, t, 1000; @pr bra.uni B0;\n"
        "setp.eq.u32 pr, t, 1001; @pr bra.uni B1;\n"
        "setp.eq.u32 pr, t, 1002; @pr bra.uni C0;\n"
        "setp.eq.u32 pr, t, 1003; @pr bra.uni N0;\n"
        "setp.eq.u32 pr, t, 1004; @pr bra.uni N1;\n"
        "setp.eq.u32 pr, t, 1005; @pr bra.uni N2;\n"
        "setp.eq.u32 pr, t, 1006; @pr bra.uni N3;\n"
        "trap;\n"
        "DONE:\n"
        ASM_TRC("t", 0)
        "fence.proxy.async.shared::cta;\n"
        "@pl mbarrier.arrive.shared::cta.b64 _, [sp+174984];\n"
        "}\n"
        :: "r"(sb + SM_X + c.xoff[0]), "r"(sb + SM_X + c.xoff[1]), "r"(sb + SM_Y1 + c.yoff[0][0]), "r"(sb + SM_Y1 + c.yoff[0][1]),
           "r"(sb + SM_Y1 + c.yoff[1][0]), "r"(sb + SM_Y1 + c.yoff[1][1]), "r"(c.stat), "r"(c.own), "r"(c.lane),
           "l"(prm.sel[0]), "l"(prm.sel[1]), "l"(prm.sel[2]), "r"(prm.ydesc), "f"(LN_EPS_SCALED), "f"(RSTD_SCALE)
        : "memory");
}

__device__ __forceinline__ void produce(const Producer& c, const Params& prm) {
    uint32_t A[24], B[24], C[24];
    const RowCopy rc = row_copy(prm);
    uint32_t st[8];
    uint32_t v[6][6];
    float d[4];
    {
        uint32_t ws[6], q[4] = {};
#pragma unroll
        for (int u = 0; u < 6; u++) {
            ws[u] = c.w[0][u];
#pragma unroll
            for (int t = 1; t < 9; t++) ws[u] = bf2_add(ws[u], c.w[t][u]);
        }
        mbar_wait_c<0>(sb + SM_XFULL + rc.first * SLOT_BYTES);
        load_x(v, c, sb + SM_X + rc.first * SLOT_BYTES);
#pragma unroll
        for (int r = 0; r < 24; r++) A[r] = bf2_mul(v[r / 6 + 1][r % 6], ws[r % 6]);
        start_sums(d, A, q, prm);
        float e, sq;
        finish_sums(d, c.lane, e, sq);
        e *= -1.0f / CH;
#pragma unroll
        for (int k = 0; k < NX; k++) sts32(c.own + k * SLOT_BYTES + 4, pack_bf2(e, e));
        __syncwarp();
        lds128(st, c.stat);
        lds128(st + 4, c.stat + 16);
#pragma unroll
        for (int r = 0; r < 24; r++) C[r] = 0;
    }
#pragma unroll 1
    for (int i = loop_init<0>();; i++) {
        mbar_wait_c<0>(sb + SM_XFULL + i * SLOT_BYTES);
        load_x(v, c, sb + SM_X + i * SLOT_BYTES);
        fence_async_smem();
        if (c.warp == i) {
            named_sync(6 + i, 128);
            issue_row_load(rc, i + NX, i);
        } else {
            asm volatile("bar.arrive %0, 128;" ::"r"(6 + i) : "memory");
        }
        if (i == 2) break;
        conv_row<1, 1>(B, C, v, c);
        conv_row<0, 0>(C, st, v, c);
    }
    if (c.warp == 3) {
        expect_tx(sb + SM_BAR + BAR_W2 * 8, CH * EX * 2 + EX * 4);
        bulk_load(sb + SM_GAMMA, prm.gamma, EX * 2, sb + SM_BAR + BAR_W2 * 8);
        bulk_load(sb + SM_BETA, prm.beta, EX * 2, sb + SM_BAR + BAR_W2 * 8);
#pragma unroll
        for (int k = 0; k < 6; k++)
            tma_load_2d(sb + SM_W2 + k * 12288, &prm.w2_map, 32 * (k >> 1), 192 * (k & 1), sb + SM_BAR + BAR_W2 * 8);
    }
    asm volatile(".reg .b32 pw<54>, pb<24>, pc<24>, pv<36>, ps<8>;");
    hand_over<0>(c, B, C, v);
    asm volatile("mov.b32 ps1, %0; mov.b32 ps3, %1; mov.b32 ps5, %2; mov.b32 ps7, %3;" ::"r"(st[1]), "r"(st[3]), "r"(st[5]), "r"(st[7]));
    produce_tiles(c, prm);
    mbar_arrive_if(sb + SM_Y1FULL + ROWS_PER_CTA % NX * SLOT_BYTES, c.lane == 0);
}

struct Duty {
    const char* g;
    uint32_t s, bytes;
    int end, zero;
};
__device__ __forceinline__ Duty make_duty(const Params& prm, int wg, int w) {
    const RowCopy rc = row_copy(prm);
    Duty d;
    d.g = (w == 2 ? rc.y0 : rc.x0 + 2 * NX * ROW_BYTES + (w == 0 ? rc.cut0 : w == 1 ? 32 * 192 : 192 + L2_AHEAD * ROW_BYTES)) +
          (uint32_t)wg * ROW_BYTES;
    d.s = wg * SLOT_BYTES + (w == 2 ? sb + SM_Y1 : sb + SM_X + (w == 0 ? rc.cut0 : XHALF_B));
    d.bytes = w >= 2 ? TILE_BYTES : XHALF_BYTES - (w == 0 ? rc.cut0 : rc.cut1);
    d.end = w == 2 ? ROWS_PER_CTA : w < 2 ? STEPS + 1 - 2 * NX : rc.last + 1 - 2 * NX - L2_AHEAD;
    d.zero = rc.last + 1 - 2 * NX;
    return d;
}

static_assert(sb + SM_Y1FULL == 174984 && sb + SM_Y1EMPTY == 174992 && sb + SM_XFULL == 174976 && SLOT_BYTES == 26624, "layout");
__device__ __forceinline__ void consume(float (&acc)[2][2], uint32_t w1t, uint32_t yd, uint32_t wd, uint32_t own_slot, const Duty& d,
                                        uint32_t role, uint32_t lane) {
    asm volatile(
        "{\n"
        ".reg .b32 z<32>, w<44>, p<2>, a<4>, lo<4>, hi<4>, t<2>, g<2>, q<4>, n, so, sp, ph, c, tt, cnt;\n"
        ".reg .b16 xl, xh, xr;\n"
        ".reg .f32 f0, f1;\n"
        ".reg .b64 ds<6>, wd, gp, src;\n"
        ".reg .pred pt, pf, pr, pw, pl, pe;\n"
        "setp.ne.b32 pt, 1, 0; setp.ne.b32 pf, 0, 0; setp.eq.u32 pl, %15, 0;\n"
        "mov.b32 c, 0x40D940D9;\n"
        "ldmatrix.sync.aligned.m8n8.x4.trans.shared.b16 {w0,w1,w2,w3}, [%4+0];\n"
        "ldmatrix.sync.aligned.m8n8.x4.trans.shared.b16 {w4,w5,w6,w7}, [%4+2048];\n"
        "ldmatrix.sync.aligned.m8n8.x4.trans.shared.b16 {w8,w9,w10,w11}, [%4+4096];\n"
        "ldmatrix.sync.aligned.m8n8.x4.trans.shared.b16 {w12,w13,w14,w15}, [%4+6144];\n"
        "ldmatrix.sync.aligned.m8n8.x4.trans.shared.b16 {w16,w17,w18,w19}, [%4+8192];\n"
        "ldmatrix.sync.aligned.m8n8.x4.trans.shared.b16 {w20,w21,w22,w23}, [%4+10240];\n"
        "ldmatrix.sync.aligned.m8n8.x4.trans.shared.b16 {w24,w25,w26,w27}, [%4+12288];\n"
        "ldmatrix.sync.aligned.m8n8.x4.trans.shared.b16 {w28,w29,w30,w31}, [%4+14336];\n"
        "ldmatrix.sync.aligned.m8n8.x4.trans.shared.b16 {w32,w33,w34,w35}, [%4+16384];\n"
        "ldmatrix.sync.aligned.m8n8.x4.trans.shared.b16 {w36,w37,w38,w39}, [%4+18432];\n"
        "ldmatrix.sync.aligned.m8n8.x4.trans.shared.b16 {w40,w41,w42,w43}, [%4+20480];\n"
        "mov.b32 p0, 0; mov.b32 p1, 0; mov.b32 t0, 0; mov.b32 t1, 0; mov.b32 g0, 0; mov.b32 g1, 0; mov.b32 a0, 0; mov.b32 a1, 0; mov.b32 lo0, 0; mov.b32 lo1, 0; mov.b32 hi0, 0; mov.b32 hi1, 0; mov.b32 q0, 0; mov.b32 q1, 0; mov.b32 q2, 0; mov.b32 q3, 0;\n"
        "mov.b32 z16, 0; mov.b32 z17, 0; mov.b32 z18, 0; mov.b32 z19, 0; mov.b32 z20, 0; mov.b32 z21, 0; mov.b32 z22, 0; mov.b32 z23, 0; mov.b32 z24, 0; mov.b32 z25, 0; mov.b32 z26, 0; mov.b32 z27, 0; mov.b32 z28, 0; mov.b32 z29, 0; mov.b32 z30, 0; mov.b32 z31, 0;\n"
        "mov.f32 %0, 0f00000000; mov.f32 %1, 0f00000000; mov.f32 %2, 0f00000000; mov.f32 %3, 0f00000000;\n"
        "mov.u32 n, 0; mov.u32 so, 0; mov.u32 sp, 0; mov.u32 ph, 0; mov.b64 gp, %8; mov.b64 wd, {%6, 0x40000040};\n"
        "shr.u32 tt, so, 4; add.u32 tt, tt, %5; mov.b64 ds0, {tt, 0x40000040}; mov.b64 ds4, {tt, 0x80000020};\n"
        "add.s64 ds1, ds0, 2; add.s64 ds2, ds0, 4; add.s64 ds3, ds0, 6; add.s64 ds5, ds4, 514; add.s64 ds4, ds4, 512;\n"
        "mbarrier.try_wait.parity.shared::cta.b64 pw, [so+174984], ph;\n"
        "@!pw bra.uni SPIN0;\n"
        "BACK0:\n"
        ASM_TS
        "wgmma.fence.sync.aligned;\n"
        "wgmma.mma_async.sync.aligned.m64n64k16.f16.f16.f16 {z0,z1,z2,z3,z4,z5,z6,z7,z8,z9,z10,z11,z12,z13,z14,z15}, {w0,w1,w2,w3}, ds0, pf, 1, 1, 0;\n"
        "wgmma.mma_async.sync.aligned.m64n64k16.f16.f16.f16 {z0,z1,z2,z3,z4,z5,z6,z7,z8,z9,z10,z11,z12,z13,z14,z15}, {w4,w5,w6,w7}, ds1, pt, 1, 1, 0;\n"
        "wgmma.mma_async.sync.aligned.m64n64k16.f16.f16.f16 {z0,z1,z2,z3,z4,z5,z6,z7,z8,z9,z10,z11,z12,z13,z14,z15}, {w8,w9,w10,w11}, ds2, pt, 1, 1, 0;\n"
        "wgmma.mma_async.sync.aligned.m64n64k16.f16.f16.f16 {z0,z1,z2,z3,z4,z5,z6,z7,z8,z9,z10,z11,z12,z13,z14,z15}, {w12,w13,w14,w15}, ds3, pt, 1, 1, 0;\n"
        "wgmma.mma_async.sync.aligned.m64n64k16.f16.f16.f16 {z0,z1,z2,z3,z4,z5,z6,z7,z8,z9,z10,z11,z12,z13,z14,z15}, {w16,w17,w18,w19}, ds4, pt, 1, 1, 0;\n"
        "wgmma.mma_async.sync.aligned.m64n64k16.f16.f16.f16 {z0,z1,z2,z3,z4,z5,z6,z7,z8,z9,z10,z11,z12,z13,z14,z15}, {w20,w21,w22,w23}, ds5, pt, 1, 1, 0;\n"
        "wgmma.commit_group.sync.aligned;\n"
        "LOOP:\n"
        ASM_TRC("n", 0)
        "setp.eq.u32 pr, so, %7;\n"
        "@pr bra.uni DUTY;\n"
        "TOP:\n"
        "wgmma.wait_group.sync.aligned 0;\n"
        "mov.b32 {xl, xh}, a0; tanh.approx.f16 xr, xl; cvt.u32.u16 lo0, xr; tanh.approx.f16 xr, xh; cvt.u32.u16 hi0, xr; fma.rn.f16x2 p0, z0, z0, c; mul.rn.f16x2 a1, z31, p1; fma.rn.f16x2 q3, g1, g1, q3; fma.rn.f16x2 g0, z28, t0, z28; prmt.b32 t1, lo1, hi1, 0x5410;\n"
        "B31:\n"
        "mov.b32 {xl, xh}, a1; tanh.approx.f16 xr, xl; cvt.u32.u16 lo1, xr; tanh.approx.f16 xr, xh; cvt.u32.u16 hi1, xr; fma.rn.f16x2 p1, z1, z1, c; mul.rn.f16x2 a0, z0, p0; fma.rn.f16x2 q2, g0, g0, q2; fma.rn.f16x2 g1, z29, t1, z29; prmt.b32 t0, lo0, hi0, 0x5410;\n"
        "B0:\n"
        "mov.b32 {xl, xh}, a0; tanh.approx.f16 xr, xl; cvt.u32.u16 lo0, xr; tanh.approx.f16 xr, xh; cvt.u32.u16 hi0, xr; fma.rn.f16x2 p0, z2, z2, c; mul.rn.f16x2 a1, z1, p1; fma.rn.f16x2 q3, g1, g1, q3; fma.rn.f16x2 g0, z30, t0, z30; prmt.b32 t1, lo1, hi1, 0x5410;\n"
        "B1:\n"
        "mov.b32 {xl, xh}, a1; tanh.approx.f16 xr, xl; cvt.u32.u16 lo1, xr; tanh.approx.f16 xr, xh; cvt.u32.u16 hi1, xr; fma.rn.f16x2 p1, z3, z3, c; mul.rn.f16x2 a0, z2, p0; fma.rn.f16x2 q2, g0, g0, q2; fma.rn.f16x2 g1, z31, t1, z31; prmt.b32 t0, lo0, hi0, 0x5410;\n"
        "B2:\n"
        "wgmma.fence.sync.aligned;\n"
        "wgmma.mma_async.sync.aligned.m64n64k16.f16.f16.f16 {z16,z17,z18,z19,z20,z21,z22,z23,z24,z25,z26,z27,z28,z29,z30,z31}, {w24,w25,w26,w27}, ds0, pf, 1, 1, 0;\n"
        "wgmma.mma_async.sync.aligned.m64n64k16.f16.f16.f16 {z16,z17,z18,z19,z20,z21,z22,z23,z24,z25,z26,z27,z28,z29,z30,z31}, {w28,w29,w30,w31}, ds1, pt, 1, 1, 0;\n"
        "wgmma.mma_async.sync.aligned.m64n64k16.f16.f16.f16 {z16,z17,z18,z19,z20,z21,z22,z23,z24,z25,z26,z27,z28,z29,z30,z31}, {w32,w33,w34,w35}, ds2, pt, 1, 1, 0;\n"
        "mov.b32 {xl, xh}, a0; tanh.approx.f16 xr, xl; cvt.u32.u16 lo0, xr; tanh.approx.f16 xr, xh; cvt.u32.u16 hi0, xr; fma.rn.f16x2 p0, z4, z4, c; mul.rn.f16x2 a1, z3, p1; fma.rn.f16x2 q3, g1, g1, q3; fma.rn.f16x2 g0, z0, t0, z0; prmt.b32 t1, lo1, hi1, 0x5410;\n"
        "B3:\n"
        "mov.b32 {xl, xh}, a1; tanh.approx.f16 xr, xl; cvt.u32.u16 lo1, xr; tanh.approx.f16 xr, xh; cvt.u32.u16 hi1, xr; fma.rn.f16x2 p1, z5, z5, c; mul.rn.f16x2 a0, z4, p0; fma.rn.f16x2 q0, g0, g0, q0; fma.rn.f16x2 g1, z1, t1, z1; prmt.b32 t0, lo0, hi0, 0x5410;\n"
        "B4:\n"
        "mov.b32 {xl, xh}, a0; tanh.approx.f16 xr, xl; cvt.u32.u16 lo0, xr; tanh.approx.f16 xr, xh; cvt.u32.u16 hi0, xr; fma.rn.f16x2 p0, z6, z6, c; mul.rn.f16x2 a1, z5, p1; fma.rn.f16x2 q1, g1, g1, q1; fma.rn.f16x2 g0, z2, t0, z2; prmt.b32 t1, lo1, hi1, 0x5410;\n"
        "B5:\n"
        "wgmma.mma_async.sync.aligned.m64n64k16.f16.f16.f16 {z16,z17,z18,z19,z20,z21,z22,z23,z24,z25,z26,z27,z28,z29,z30,z31}, {w36,w37,w38,w39}, ds3, pt, 1, 1, 0;\n"
        "wgmma.mma_async.sync.aligned.m64n64k16.f16.f16.f16 {z16,z17,z18,z19,z20,z21,z22,z23,z24,z25,z26,z27,z28,z29,z30,z31}, {w40,w41,w42,w43}, ds4, pt, 1, 1, 0;\n"
        "wgmma.mma_async.sync.aligned.m64n64k16.f16.f16.f16 {z16,z17,z18,z19,z20,z21,z22,z23,z24,z25,z26,z27,z28,z29,z30,z31}, wd, ds5, pt, 1, 1, 1, 0;\n"
        "wgmma.commit_group.sync.aligned;\n"
        "mov.b32 {xl, xh}, a1; tanh.approx.f16 xr, xl; cvt.u32.u16 lo1, xr; tanh.approx.f16 xr, xh; cvt.u32.u16 hi1, xr; fma.rn.f16x2 p1, z7, z7, c; mul.rn.f16x2 a0, z6, p0; fma.rn.f16x2 q0, g0, g0, q0; fma.rn.f16x2 g1, z3, t1, z3; prmt.b32 t0, lo0, hi0, 0x5410;\n"
        "B6:\n"
        "mov.u32 sp, so; add.u32 so, so, 26624; setp.eq.u32 pr, so, 79872; selp.u32 so, 0, so, pr; selp.u32 tt, 1, 0, pr; xor.b32 ph, ph, tt;\n"
        "mov.b32 {xl, xh}, a0; tanh.approx.f16 xr, xl; cvt.u32.u16 lo0, xr; tanh.approx.f16 xr, xh; cvt.u32.u16 hi0, xr; fma.rn.f16x2 p0, z8, z8, c; mul.rn.f16x2 a1, z7, p1; fma.rn.f16x2 q1, g1, g1, q1; fma.rn.f16x2 g0, z4, t0, z4; prmt.b32 t1, lo1, hi1, 0x5410;\n"
        "B7:\n"
        "shr.u32 tt, so, 4; add.u32 tt, tt, %5; mov.b64 ds0, {tt, 0x40000040}; mov.b64 ds4, {tt, 0x80000020};\n"
        "add.s64 ds1, ds0, 2; add.s64 ds2, ds0, 4; add.s64 ds3, ds0, 6; add.s64 ds5, ds4, 514; add.s64 ds4, ds4, 512;\n"
        "mov.b32 {xl, xh}, a1; tanh.approx.f16 xr, xl; cvt.u32.u16 lo1, xr; tanh.approx.f16 xr, xh; cvt.u32.u16 hi1, xr; fma.rn.f16x2 p1, z9, z9, c; mul.rn.f16x2 a0, z8, p0; fma.rn.f16x2 q0, g0, g0, q0; fma.rn.f16x2 g1, z5, t1, z5; prmt.b32 t0, lo0, hi0, 0x5410;\n"
        "B8:\n"
        "mov.b32 {xl, xh}, a0; tanh.approx.f16 xr, xl; cvt.u32.u16 lo0, xr; tanh.approx.f16 xr, xh; cvt.u32.u16 hi0, xr; fma.rn.f16x2 p0, z10, z10, c; mul.rn.f16x2 a1, z9, p1; fma.rn.f16x2 q1, g1, g1, q1; fma.rn.f16x2 g0, z6, t0, z6; prmt.b32 t1, lo1, hi1, 0x5410;\n"
        "B9:\n"
        "mov.b32 {xl, xh}, a1; tanh.approx.f16 xr, xl; cvt.u32.u16 lo1, xr; tanh.approx.f16 xr, xh; cvt.u32.u16 hi1, xr; fma.rn.f16x2 p1, z11, z11, c; mul.rn.f16x2 a0, z10, p0; fma.rn.f16x2 q0, g0, g0, q0; fma.rn.f16x2 g1, z7, t1, z7; prmt.b32 t0, lo0, hi0, 0x5410;\n"
        "B10:\n"
        "mov.b32 {xl, xh}, a0; tanh.approx.f16 xr, xl; cvt.u32.u16 lo0, xr; tanh.approx.f16 xr, xh; cvt.u32.u16 hi0, xr; fma.rn.f16x2 p0, z12, z12, c; mul.rn.f16x2 a1, z11, p1; fma.rn.f16x2 q1, g1, g1, q1; fma.rn.f16x2 g0, z8, t0, z8; prmt.b32 t1, lo1, hi1, 0x5410;\n"
        "B11:\n"
        "mov.b32 {xl, xh}, a1; tanh.approx.f16 xr, xl; cvt.u32.u16 lo1, xr; tanh.approx.f16 xr, xh; cvt.u32.u16 hi1, xr; fma.rn.f16x2 p1, z13, z13, c; mul.rn.f16x2 a0, z12, p0; fma.rn.f16x2 q0, g0, g0, q0; fma.rn.f16x2 g1, z9, t1, z9; prmt.b32 t0, lo0, hi0, 0x5410;\n"
        "B12:\n"
        "mov.b32 {xl, xh}, a0; tanh.approx.f16 xr, xl; cvt.u32.u16 lo0, xr; tanh.approx.f16 xr, xh; cvt.u32.u16 hi0, xr; fma.rn.f16x2 p0, z14, z14, c; mul.rn.f16x2 a1, z13, p1; fma.rn.f16x2 q1, g1, g1, q1; fma.rn.f16x2 g0, z10, t0, z10; prmt.b32 t1, lo1, hi1, 0x5410;\n"
        "B13:\n"
        "mov.b32 {xl, xh}, a1; tanh.approx.f16 xr, xl; cvt.u32.u16 lo1, xr; tanh.approx.f16 xr, xh; cvt.u32.u16 hi1, xr; fma.rn.f16x2 p1, z15, z15, c; mul.rn.f16x2 a0, z14, p0; fma.rn.f16x2 q0, g0, g0, q0; fma.rn.f16x2 g1, z11, t1, z11; prmt.b32 t0, lo0, hi0, 0x5410;\n"
        "B14:\n"
        "wgmma.wait_group.sync.aligned 0;\n"
        "cp.async.bulk.wait_group.read 0;\n"
        "@pl mbarrier.arrive.shared::cta.b64 _, [sp+174992];\n"
        "mov.b32 {xl, xh}, a0; tanh.approx.f16 xr, xl; cvt.u32.u16 lo0, xr; tanh.approx.f16 xr, xh; cvt.u32.u16 hi0, xr; fma.rn.f16x2 p0, z16, z16, c; mul.rn.f16x2 a1, z15, p1; fma.rn.f16x2 q1, g1, g1, q1; fma.rn.f16x2 g0, z12, t0, z12; prmt.b32 t1, lo1, hi1, 0x5410;\n"
        "B15:\n"
        "mbarrier.try_wait.parity.shared::cta.b64 pw, [so+174984], ph;\n"
        "mov.b32 {xl, xh}, a1; tanh.approx.f16 xr, xl; cvt.u32.u16 lo1, xr; tanh.approx.f16 xr, xh; cvt.u32.u16 hi1, xr; fma.rn.f16x2 p1, z17, z17, c; mul.rn.f16x2 a0, z16, p0; fma.rn.f16x2 q0, g0, g0, q0; fma.rn.f16x2 g1, z13, t1, z13; prmt.b32 t0, lo0, hi0, 0x5410;\n"
        "B16:\n"
        "mov.b32 {xl, xh}, a0; tanh.approx.f16 xr, xl; cvt.u32.u16 lo0, xr; tanh.approx.f16 xr, xh; cvt.u32.u16 hi0, xr; fma.rn.f16x2 p0, z18, z18, c; mul.rn.f16x2 a1, z17, p1; fma.rn.f16x2 q1, g1, g1, q1; fma.rn.f16x2 g0, z14, t0, z14; prmt.b32 t1, lo1, hi1, 0x5410;\n"
        "B17:\n"
        "mov.b32 {xl, xh}, a1; tanh.approx.f16 xr, xl; cvt.u32.u16 lo1, xr; tanh.approx.f16 xr, xh; cvt.u32.u16 hi1, xr; fma.rn.f16x2 p1, z19, z19, c; mul.rn.f16x2 a0, z18, p0; fma.rn.f16x2 q0, g0, g0, q0; fma.rn.f16x2 g1, z15, t1, z15; prmt.b32 t0, lo0, hi0, 0x5410;\n"
        "B18:\n"
        "@!pw bra.uni SPIN;\n"
        "BACK:\n"
        "wgmma.fence.sync.aligned;\n"
        "wgmma.mma_async.sync.aligned.m64n64k16.f16.f16.f16 {z0,z1,z2,z3,z4,z5,z6,z7,z8,z9,z10,z11,z12,z13,z14,z15}, {w0,w1,w2,w3}, ds0, pf, 1, 1, 0;\n"
        "wgmma.mma_async.sync.aligned.m64n64k16.f16.f16.f16 {z0,z1,z2,z3,z4,z5,z6,z7,z8,z9,z10,z11,z12,z13,z14,z15}, {w4,w5,w6,w7}, ds1, pt, 1, 1, 0;\n"
        "wgmma.mma_async.sync.aligned.m64n64k16.f16.f16.f16 {z0,z1,z2,z3,z4,z5,z6,z7,z8,z9,z10,z11,z12,z13,z14,z15}, {w8,w9,w10,w11}, ds2, pt, 1, 1, 0;\n"
        "mov.b32 {xl, xh}, a0; tanh.approx.f16 xr, xl; cvt.u32.u16 lo0, xr; tanh.approx.f16 xr, xh; cvt.u32.u16 hi0, xr; fma.rn.f16x2 p0, z20, z20, c; mul.rn.f16x2 a1, z19, p1; fma.rn.f16x2 q1, g1, g1, q1; fma.rn.f16x2 g0, z16, t0, z16; prmt.b32 t1, lo1, hi1, 0x5410;\n"
        "B19:\n"
        "mov.b32 {xl, xh}, a1; tanh.approx.f16 xr, xl; cvt.u32.u16 lo1, xr; tanh.approx.f16 xr, xh; cvt.u32.u16 hi1, xr; fma.rn.f16x2 p1, z21, z21, c; mul.rn.f16x2 a0, z20, p0; fma.rn.f16x2 q2, g0, g0, q2; fma.rn.f16x2 g1, z17, t1, z17; prmt.b32 t0, lo0, hi0, 0x5410;\n"
        "B20:\n"
        "mov.b32 {xl, xh}, a0; tanh.approx.f16 xr, xl; cvt.u32.u16 lo0, xr; tanh.approx.f16 xr, xh; cvt.u32.u16 hi0, xr; fma.rn.f16x2 p0, z22, z22, c; mul.rn.f16x2 a1, z21, p1; fma.rn.f16x2 q3, g1, g1, q3; fma.rn.f16x2 g0, z18, t0, z18; prmt.b32 t1, lo1, hi1, 0x5410;\n"
        "B21:\n"
        "wgmma.mma_async.sync.aligned.m64n64k16.f16.f16.f16 {z0,z1,z2,z3,z4,z5,z6,z7,z8,z9,z10,z11,z12,z13,z14,z15}, {w12,w13,w14,w15}, ds3, pt, 1, 1, 0;\n"
        "wgmma.mma_async.sync.aligned.m64n64k16.f16.f16.f16 {z0,z1,z2,z3,z4,z5,z6,z7,z8,z9,z10,z11,z12,z13,z14,z15}, {w16,w17,w18,w19}, ds4, pt, 1, 1, 0;\n"
        "wgmma.mma_async.sync.aligned.m64n64k16.f16.f16.f16 {z0,z1,z2,z3,z4,z5,z6,z7,z8,z9,z10,z11,z12,z13,z14,z15}, {w20,w21,w22,w23}, ds5, pt, 1, 1, 0;\n"
        "wgmma.commit_group.sync.aligned;\n"
        "mov.b32 {xl, xh}, a1; tanh.approx.f16 xr, xl; cvt.u32.u16 lo1, xr; tanh.approx.f16 xr, xh; cvt.u32.u16 hi1, xr; fma.rn.f16x2 p1, z23, z23, c; mul.rn.f16x2 a0, z22, p0; fma.rn.f16x2 q2, g0, g0, q2; fma.rn.f16x2 g1, z19, t1, z19; prmt.b32 t0, lo0, hi0, 0x5410;\n"
        "B22:\n"
        "mov.b32 {xl, xh}, a0; tanh.approx.f16 xr, xl; cvt.u32.u16 lo0, xr; tanh.approx.f16 xr, xh; cvt.u32.u16 hi0, xr; fma.rn.f16x2 p0, z24, z24, c; mul.rn.f16x2 a1, z23, p1; fma.rn.f16x2 q3, g1, g1, q3; fma.rn.f16x2 g0, z20, t0, z20; prmt.b32 t1, lo1, hi1, 0x5410;\n"
        "B23:\n"
        "mov.b32 {xl, xh}, a1; tanh.approx.f16 xr, xl; cvt.u32.u16 lo1, xr; tanh.approx.f16 xr, xh; cvt.u32.u16 hi1, xr; fma.rn.f16x2 p1, z25, z25, c; mul.rn.f16x2 a0, z24, p0; fma.rn.f16x2 q2, g0, g0, q2; fma.rn.f16x2 g1, z21, t1, z21; prmt.b32 t0, lo0, hi0, 0x5410;\n"
        "B24:\n"
        "mov.b32 {xl, xh}, a0; tanh.approx.f16 xr, xl; cvt.u32.u16 lo0, xr; tanh.approx.f16 xr, xh; cvt.u32.u16 hi0, xr; fma.rn.f16x2 p0, z26, z26, c; mul.rn.f16x2 a1, z25, p1; fma.rn.f16x2 q3, g1, g1, q3; fma.rn.f16x2 g0, z22, t0, z22; prmt.b32 t1, lo1, hi1, 0x5410;\n"
        "B25:\n"
        "mov.b32 {xl, xh}, a1; tanh.approx.f16 xr, xl; cvt.u32.u16 lo1, xr; tanh.approx.f16 xr, xh; cvt.u32.u16 hi1, xr; fma.rn.f16x2 p1, z27, z27, c; mul.rn.f16x2 a0, z26, p0; fma.rn.f16x2 q2, g0, g0, q2; fma.rn.f16x2 g1, z23, t1, z23; prmt.b32 t0, lo0, hi0, 0x5410;\n"
        "B26:\n"
        "mov.b32 {xl, xh}, a0; tanh.approx.f16 xr, xl; cvt.u32.u16 lo0, xr; tanh.approx.f16 xr, xh; cvt.u32.u16 hi0, xr; fma.rn.f16x2 p0, z28, z28, c; mul.rn.f16x2 a1, z27, p1; fma.rn.f16x2 q3, g1, g1, q3; fma.rn.f16x2 g0, z24, t0, z24; prmt.b32 t1, lo1, hi1, 0x5410;\n"
        "B27:\n"
        "add.u32 n, n, 1; setp.lt.u32 pe, n, 32;\n"
        "mov.b32 {xl, xh}, a1; tanh.approx.f16 xr, xl; cvt.u32.u16 lo1, xr; tanh.approx.f16 xr, xh; cvt.u32.u16 hi1, xr; fma.rn.f16x2 p1, z29, z29, c; mul.rn.f16x2 a0, z28, p0; fma.rn.f16x2 q2, g0, g0, q2; fma.rn.f16x2 g1, z25, t1, z25; prmt.b32 t0, lo0, hi0, 0x5410;\n"
        "B28:\n"
        "mov.b32 {xl, xh}, a0; tanh.approx.f16 xr, xl; cvt.u32.u16 lo0, xr; tanh.approx.f16 xr, xh; cvt.u32.u16 hi0, xr; fma.rn.f16x2 p0, z30, z30, c; mul.rn.f16x2 a1, z29, p1; fma.rn.f16x2 q3, g1, g1, q3; fma.rn.f16x2 g0, z26, t0, z26; prmt.b32 t1, lo1, hi1, 0x5410;\n"
        "B29:\n"
        "mov.b32 {xl, xh}, a1; tanh.approx.f16 xr, xl; cvt.u32.u16 lo1, xr; tanh.approx.f16 xr, xh; cvt.u32.u16 hi1, xr; fma.rn.f16x2 p1, z31, z31, c; mul.rn.f16x2 a0, z30, p0; fma.rn.f16x2 q2, g0, g0, q2; fma.rn.f16x2 g1, z27, t1, z27; prmt.b32 t0, lo0, hi0, 0x5410;\n"
        "@pe bra.uni LOOP;\n"
        "bra.uni DONE;\n"
        "SPIN0: mov.u32 cnt, 0;\n"
        ASM_TRC("n", 1)
        "SPIN0L:\n"
        "mbarrier.try_wait.parity.shared::cta.b64 pw, [so+174984], ph;\n"
        "@pw bra.uni BACK0;\n"
        "add.u32 cnt, cnt, 1; setp.lt.u32 pw, cnt, 0x100000;\n"
        "@pw bra.uni SPIN0L;\n"
        "trap;\n"
        "SPIN: mov.u32 cnt, 0;\n"
        ASM_TRC("n", 1)
        "SPINL:\n"
        "mbarrier.try_wait.parity.shared::cta.b64 pw, [so+174984], ph;\n"
        "@pw bra.uni BACK;\n"
        "add.u32 cnt, cnt, 1; setp.lt.u32 pw, cnt, 0x100000;\n"
        "@pw bra.uni SPINL;\n"
        "trap;\n"
        "DUTY:\n"
        "setp.ge.s32 pr, n, %11;\n"
        "@pr bra.uni FLUSH;\n"
        "setp.ge.u32 pr, %13, 2;\n"
        "@pr bra.uni ROLE2;\n"
        "setp.ge.s32 pr, n, %12; selp.b64 src, %14, gp, pr; add.u32 tt, %7, 174976;\n"
        "elect.sync _|pr, 0xffffffff;\n"
        "@pr mbarrier.arrive.expect_tx.shared::cta.b64 _, [tt], %10;\n"
        "@pr cp.async.bulk.shared::cluster.global.mbarrier::complete_tx::bytes [%9], [src], %10, [tt];\n"
        "bra.uni FLUSH;\n"
        "ROLE2:\n"
        "setp.eq.u32 pr, %13, 3;\n"
        "@pr bra.uni ROLE3;\n"
        "elect.sync _|pr, 0xffffffff;\n"
        "@pr cp.async.bulk.global.shared::cta.bulk_group [gp], [%9], 12288;\n"
        "@pr cp.async.bulk.commit_group;\n"
        "bra.uni FLUSH;\n"
        "ROLE3:\n"
        "elect.sync _|pr, 0xffffffff;\n"
        "@pr cp.async.bulk.prefetch.L2.global [gp], 12288;\n"
        "FLUSH:\n"
        "add.s64 gp, gp, 294912;\n"
        "mov.b32 {xl, xh}, q0; cvt.f32.f16 f0, xl; cvt.f32.f16 f1, xh; add.f32 f0, f0, f1; add.f32 %0, %0, f0; mov.b32 q0, 0;\n"
        "mov.b32 {xl, xh}, q1; cvt.f32.f16 f0, xl; cvt.f32.f16 f1, xh; add.f32 f0, f0, f1; add.f32 %1, %1, f0; mov.b32 q1, 0;\n"
        "mov.b32 {xl, xh}, q2; cvt.f32.f16 f0, xl; cvt.f32.f16 f1, xh; add.f32 f0, f0, f1; add.f32 %2, %2, f0; mov.b32 q2, 0;\n"
        "mov.b32 {xl, xh}, q3; cvt.f32.f16 f0, xl; cvt.f32.f16 f1, xh; add.f32 f0, f0, f1; add.f32 %3, %3, f0; mov.b32 q3, 0;\n"
        "setp.ne.u32 pr, %5, 0;\n"
        "@pr bra.uni TOP;\n"
        "wgmma.wait_group.sync.aligned 0;\n"
        "wgmma.fence.sync.aligned;\n"
        "setp.eq.u32 pr, n, 1000; @pr bra.uni B31;\n"
        "setp.eq.u32 pr, n, 1001; @pr bra.uni B0;\n"
        "setp.eq.u32 pr, n, 1002; @pr bra.uni B1;\n"
        "setp.eq.u32 pr, n, 1003; @pr bra.uni B2;\n"
        "setp.eq.u32 pr, n, 1004; @pr bra.uni B3;\n"
        "setp.eq.u32 pr, n, 1005; @pr bra.uni B4;\n"
        "setp.eq.u32 pr, n, 1006; @pr bra.uni B5;\n"
        "setp.eq.u32 pr, n, 1007; @pr bra.uni B6;\n"
        "setp.eq.u32 pr, n, 1008; @pr bra.uni B7;\n"
        "setp.eq.u32 pr, n, 1009; @pr bra.uni B8;\n"
        "setp.eq.u32 pr, n, 1010; @pr bra.uni B9;\n"
        "setp.eq.u32 pr, n, 1011; @pr bra.uni B10;\n"
        "setp.eq.u32 pr, n, 1012; @pr bra.uni B11;\n"
        "setp.eq.u32 pr, n, 1013; @pr bra.uni B12;\n"
        "setp.eq.u32 pr, n, 1014; @pr bra.uni B13;\n"
        "setp.eq.u32 pr, n, 1015; @pr bra.uni B14;\n"
        "setp.eq.u32 pr, n, 1016; @pr bra.uni B15;\n"
        "setp.eq.u32 pr, n, 1017; @pr bra.uni B16;\n"
        "setp.eq.u32 pr, n, 1018; @pr bra.uni B17;\n"
        "setp.eq.u32 pr, n, 1019; @pr bra.uni B18;\n"
        "setp.eq.u32 pr, n, 1020; @pr bra.uni B19;\n"
        "setp.eq.u32 pr, n, 1021; @pr bra.uni B20;\n"
        "setp.eq.u32 pr, n, 1022; @pr bra.uni B21;\n"
        "setp.eq.u32 pr, n, 1023; @pr bra.uni B22;\n"
        "setp.eq.u32 pr, n, 1024; @pr bra.uni B23;\n"
        "setp.eq.u32 pr, n, 1025; @pr bra.uni B24;\n"
        "setp.eq.u32 pr, n, 1026; @pr bra.uni B25;\n"
        "setp.eq.u32 pr, n, 1027; @pr bra.uni B26;\n"
        "setp.eq.u32 pr, n, 1028; @pr bra.uni B27;\n"
        "setp.eq.u32 pr, n, 1029; @pr bra.uni B28;\n"
        "setp.eq.u32 pr, n, 1030; @pr bra.uni B29;\n"
        "trap;\n"
        "DONE:\n"
        ASM_TRC("n", 0)
        "mov.b32 {xl, xh}, a0; tanh.approx.f16 xr, xl; cvt.u32.u16 lo0, xr; tanh.approx.f16 xr, xh; cvt.u32.u16 hi0, xr; mul.rn.f16x2 a1, z31, p1; fma.rn.f16x2 q3, g1, g1, q3; fma.rn.f16x2 g0, z28, t0, z28; prmt.b32 t1, lo1, hi1, 0x5410;\n"
        "mov.b32 {xl, xh}, a1; tanh.approx.f16 xr, xl; cvt.u32.u16 lo1, xr; tanh.approx.f16 xr, xh; cvt.u32.u16 hi1, xr; fma.rn.f16x2 q2, g0, g0, q2; fma.rn.f16x2 g1, z29, t1, z29; prmt.b32 t0, lo0, hi0, 0x5410;\n"
        "fma.rn.f16x2 q3, g1, g1, q3; fma.rn.f16x2 g0, z30, t0, z30; prmt.b32 t1, lo1, hi1, 0x5410;\n"
        "fma.rn.f16x2 q2, g0, g0, q2; fma.rn.f16x2 g1, z31, t1, z31;\n"
        "fma.rn.f16x2 q3, g1, g1, q3;\n"
        "mov.b32 {xl, xh}, q0; cvt.f32.f16 f0, xl; cvt.f32.f16 f1, xh; add.f32 f0, f0, f1; add.f32 %0, %0, f0; mov.b32 q0, 0;\n"
        "mov.b32 {xl, xh}, q1; cvt.f32.f16 f0, xl; cvt.f32.f16 f1, xh; add.f32 f0, f0, f1; add.f32 %1, %1, f0; mov.b32 q1, 0;\n"
        "mov.b32 {xl, xh}, q2; cvt.f32.f16 f0, xl; cvt.f32.f16 f1, xh; add.f32 f0, f0, f1; add.f32 %2, %2, f0; mov.b32 q2, 0;\n"
        "mov.b32 {xl, xh}, q3; cvt.f32.f16 f0, xl; cvt.f32.f16 f1, xh; add.f32 f0, f0, f1; add.f32 %3, %3, f0; mov.b32 q3, 0;\n"
        "wgmma.wait_group.sync.aligned 0;\n"
        "}\n"
        : "=f"(acc[0][0]), "=f"(acc[0][1]), "=f"(acc[1][0]), "=f"(acc[1][1])
        : "r"(w1t), "r"(yd), "r"(wd), "r"(own_slot), "l"(d.g), "r"(d.s), "r"(d.bytes), "r"(d.end), "r"(d.zero), "r"(role),
          "l"(g_zero_row), "r"(lane)
        : "memory");
}
template <int M, bool LAST_SMEM = true>
__device__ __forceinline__ void gemm1_t(uint32_t (&d)[16], const uint32_t* wa, uint32_t yd, uint32_t wd) {
    wg_fence();
    wgmma_n64_h_set<0>(d, wa, desc<1024, 1>(yd, 0));
#pragma unroll
    for (int kk = 1; kk < (LAST_SMEM ? 5 : 6); kk++)
        wgmma_n64_h_acc<0>(d, wa + kk * 4, kk < 4 ? desc<1024, 1>(yd, kk * 32) : desc<512, 2>(yd, 8192 + (kk - 4) * 32));
    if (LAST_SMEM) wgmma_n64_h_acc_ss(d, desc<1024, 1>(wd, M * 12288), desc<512, 2>(yd, 8192 + 32));
    wg_commit();
}

#define GTAIL 0
__device__ __forceinline__ void gelu_sumsq_h(uint32_t (&d)[16], uint32_t (&q)[2], uint32_t key) {
#pragma unroll
    for (int r = 0; r < 16; r++) {
        if (GTAIL && r == 16 - GTAIL) sched_fence<GTAIL ? GTAIL : 2>(d + r, key);
        const uint32_t gv = gelu2(d[r]);
        q[r & 1] = h2_fma(gv, gv, q[r & 1]);
    }
}
__device__ __forceinline__ void flush_sumsq(uint32_t (&q)[2], float (&acc)[2]) {
#pragma unroll
    for (int h = 0; h < 2; h++) {
        float lo, hi;
        h2_unpack(q[h], lo, hi);
        acc[h] += lo + hi;
        q[h] = 0;
    }
}
__device__ __forceinline__ void gelu_sumsq_f(const uint32_t (&d)[16], float (&acc)[2]) {
#pragma unroll
    for (int r = 0; r < 16; r++) {
        float lo, hi;
        h2_unpack(gelu2(d[r]), lo, hi);
        acc[r & 1] = fmaf(lo, lo, acc[r & 1]);
        acc[r & 1] = fmaf(hi, hi, acc[r & 1]);
    }
}
__device__ __forceinline__ void load_w1t(uint32_t (&wa)[2][24], int wg, int w, int lane) {
#pragma unroll
    for (int m = 0; m < 2; m++)
#pragma unroll
        for (int kk = 0; kk < 5; kk++) {
            const int q = lane >> 3, c = 16 * kk + 8 * (q >> 1) + (lane & 7), ck = 2 * w + (q & 1);
            ldsm4_t(wa[m] + kk * 4, sb + SM_W1 + (2 * wg + m) * 12288 + c * 128 + ((ck ^ (c & 7)) * 16));
        }
}
__device__ __forceinline__ unsigned long long* acc_word(uint32_t epoch, uint32_t e) {
    return &g_acc[epoch & 1][(e >> 2) * 32 + (e & 3)];
}
__device__ __forceinline__ void publish_fast(const float (&acc)[2][2], uint32_t epoch, int wg, int w, int lane) {
    const bool m = lane & 2, h = lane & 1;
    const float a = (m ? acc[1][0] : acc[0][0]) + __shfl_xor_sync(0xffffffffu, m ? acc[0][0] : acc[1][0], 2);
    const float b = (m ? acc[1][1] : acc[0][1]) + __shfl_xor_sync(0xffffffffu, m ? acc[0][1] : acc[1][1], 2);
    const float v = (h ? b : a) + __shfl_xor_sync(0xffffffffu, h ? a : b, 1);
    const unsigned long long q = (__float2ull_rn(fminf(v, ACC_LIMIT) * 0x1p16f) << 8) + 1;
    asm volatile("red.relaxed.gpu.global.add.u64 [%0], %1;"
                 ::"l"(acc_word(epoch, 128 * wg + 32 * (lane & 2) + 16 * w + (lane >> 2) + 8 * (lane & 1))), "l"(q) : "memory");
}
__device__ __forceinline__ float collect_fast(const unsigned long long* word) {
    unsigned long long v;
    asm volatile(
        "{\n.reg .pred p;\n.reg .u32 n, lo, hi;\nmov.u32 n, 0;\n"
        "POLL:\nld.relaxed.gpu.global.u64 %0, [%1];\nmov.b64 {lo, hi}, %0;\nand.b32 lo, lo, 255;\n"
        "setp.eq.u32 p, lo, %2;\nvote.sync.all.pred p, p, 0xffffffff;\n@p bra.uni POLL_DONE;\n"
        "add.u32 n, n, 1;\nsetp.lt.u32 p, n, 0x400000;\n@p bra.uni POLL;\ntrap;\nPOLL_DONE:\n}\n"
        : "=l"(v) : "l"(word), "n"(NUM_CTAS) : "memory");
    return __ull2float_rn(v >> 8) * 0x1p-16f;
}
__device__ __forceinline__ void publish_sums(const float (&acc)[2][2], float* sums, unsigned int* counter, int wg, int w, int lane) {
#pragma unroll
    for (int m = 0; m < 2; m++)
#pragma unroll
        for (int h = 0; h < 2; h++) {
            const float v = quad_sum(acc[m][h]);
            if ((lane & 3) == 0) atomicAdd(sums + 64 * (2 * wg + m) + 16 * w + (lane >> 2) + 8 * h, v);
        }
    named_sync(1, 384);
    if (fresh_tid() == 0) asm volatile("red.release.gpu.global.add.u32 [%0], 1;" ::"l"(counter) : "memory");
}
__device__ __forceinline__ void grid_wait(const unsigned int* counter, unsigned int target) {
    if (fresh_tid() == 0) {
        unsigned int v, spins = 0;
        do {
            asm volatile("ld.acquire.gpu.global.u32 %0, [%1];" : "=r"(v) : "l"(counter) : "memory");
            if (++spins > (1u << 22)) __trap();
        } while ((int)(v - target) < 0);
    }
    __syncthreads();
}

struct Pass2 {
    uint32_t wg;
    uint32_t off;
    uint32_t xs;
    uint32_t a_offs, xs_offs, bias_addr, out_scale;
    uint32_t w;
};

static_assert(sb + SM_BAR + BAR_Y2FULL * 8 == 230800 && sb + SM_BAR + BAR_XSFULL * 8 == 230832, "layout");
__device__ __forceinline__ void first_gemm(uint32_t tile, uint32_t offs, uint32_t w1d) {
    asm volatile(
        "{\n"
        ".reg .b32 t<2>, ad;\n"
        ".reg .b64 w1d, dt;\n"
        ".reg .pred pt, pf;\n"
        "setp.ne.b32 pt, 1, 0; setp.ne.b32 pf, 0, 0; mov.b64 w1d, {%2, 0x40000040};\n"
        "and.b32 t0, %1, 0xffff; shr.u32 t1, %1, 16;\n"
        "xor.b32 ad, t0, 0; add.u32 ad, ad, %0; ldmatrix.sync.aligned.m8n8.x4.shared.b16 {qa0,qa1,qa2,qa3}, [ad];\n"
        "xor.b32 ad, t0, 32; add.u32 ad, ad, %0; ldmatrix.sync.aligned.m8n8.x4.shared.b16 {qa4,qa5,qa6,qa7}, [ad];\n"
        "xor.b32 ad, t0, 64; add.u32 ad, ad, %0; ldmatrix.sync.aligned.m8n8.x4.shared.b16 {qa8,qa9,qa10,qa11}, [ad];\n"
        "xor.b32 ad, t0, 96; add.u32 ad, ad, %0; ldmatrix.sync.aligned.m8n8.x4.shared.b16 {qa12,qa13,qa14,qa15}, [ad];\n"
        "xor.b32 ad, t1, 0; add.u32 ad, ad, %0; ldmatrix.sync.aligned.m8n8.x4.shared.b16 {qa16,qa17,qa18,qa19}, [ad];\n"
        "xor.b32 ad, t1, 32; add.u32 ad, ad, %0; ldmatrix.sync.aligned.m8n8.x4.shared.b16 {qa20,qa21,qa22,qa23}, [ad];\n"
        "wgmma.fence.sync.aligned;\n"
        "add.s64 dt, w1d, 0; wgmma.mma_async.sync.aligned.m64n64k16.f16.f16.f16 {qz0,qz1,qz2,qz3,qz4,qz5,qz6,qz7,qz8,qz9,qz10,qz11,qz12,qz13,qz14,qz15}, {qa0,qa1,qa2,qa3}, dt, pf, 1, 1, 1;\n"
        "add.s64 dt, w1d, 128; wgmma.mma_async.sync.aligned.m64n64k16.f16.f16.f16 {qz0,qz1,qz2,qz3,qz4,qz5,qz6,qz7,qz8,qz9,qz10,qz11,qz12,qz13,qz14,qz15}, {qa4,qa5,qa6,qa7}, dt, pt, 1, 1, 1;\n"
        "add.s64 dt, w1d, 256; wgmma.mma_async.sync.aligned.m64n64k16.f16.f16.f16 {qz0,qz1,qz2,qz3,qz4,qz5,qz6,qz7,qz8,qz9,qz10,qz11,qz12,qz13,qz14,qz15}, {qa8,qa9,qa10,qa11}, dt, pt, 1, 1, 1;\n"
        "add.s64 dt, w1d, 384; wgmma.mma_async.sync.aligned.m64n64k16.f16.f16.f16 {qz0,qz1,qz2,qz3,qz4,qz5,qz6,qz7,qz8,qz9,qz10,qz11,qz12,qz13,qz14,qz15}, {qa12,qa13,qa14,qa15}, dt, pt, 1, 1, 1;\n"
        "add.s64 dt, w1d, 512; wgmma.mma_async.sync.aligned.m64n64k16.f16.f16.f16 {qz0,qz1,qz2,qz3,qz4,qz5,qz6,qz7,qz8,qz9,qz10,qz11,qz12,qz13,qz14,qz15}, {qa16,qa17,qa18,qa19}, dt, pt, 1, 1, 1;\n"
        "add.s64 dt, w1d, 640; wgmma.mma_async.sync.aligned.m64n64k16.f16.f16.f16 {qz0,qz1,qz2,qz3,qz4,qz5,qz6,qz7,qz8,qz9,qz10,qz11,qz12,qz13,qz14,qz15}, {qa20,qa21,qa22,qa23}, dt, pt, 1, 1, 1;\n"
        "wgmma.commit_group.sync.aligned;\n"
        "}\n"
        :: "r"(tile), "r"(offs), "r"(w1d) : "memory");
}
__device__ __forceinline__ void pass2_tiles(const Pass2& c, const Params& prm) {
    asm volatile(
        "{\n"
        ".reg .b32 o<24>, g<16>, p<2>, a<2>, lo<2>, hi<2>, h<2>, v<8>, n, off, c, tt, ad, cnt, ybar, xbar, tbar, tpar, id;\n"
        ".reg .b16 xl, xh, xr;\n"
        ".reg .f32 f0, f1;\n"
        ".reg .b64 w1d, w2d, dt, gp, pol;\n"
        ".reg .pred pt, pf, pr, pw, pl, pk, pm, pz, pn;\n"
        "setp.ne.b32 pt, 1, 0; setp.ne.b32 pf, 0, 0; setp.eq.u32 pl, %9, 0; setp.eq.u32 pk, %9, 0; setp.eq.u32 pz, %0, 0;\n"
        "mov.b32 c, 0x40D940D9;\n"
        "mov.b64 w1d, {%0, 0x40000040}; mov.b64 w2d, {%1, 0x80000020};\n"
        "mad.lo.u32 ybar, %2, 8, 230800; mad.lo.u32 xbar, %2, 8, 230832; add.u32 id, %2, 2;\n"
        "xor.b32 tt, %2, 0; mad.lo.u32 tbar, tt, 64, 230888; setp.eq.u32 pr, tt, 0; selp.u32 tpar, 1, 0, pr; mov.u32 tt, %laneid; setp.eq.u32 pn, tt, 0;\n"
        "mov.u32 n, -1; add.u32 off, %3, 393216; mov.pred pm, pt; mov.b64 pol, 0x12F0000000000000;\n"
        "wgmma.wait_group.sync.aligned 0;\n"
        "ld.shared.v4.b32 {o0,o1,o2,o3}, [%7+0];\n"
        "ld.shared.v4.b32 {o4,o5,o6,o7}, [%7+64];\n"
        "ld.shared.v4.b32 {o8,o9,o10,o11}, [%7+128];\n"
        "ld.shared.v4.b32 {o12,o13,o14,o15}, [%7+192];\n"
        "ld.shared.v4.b32 {o16,o17,o18,o19}, [%7+256];\n"
        "ld.shared.v4.b32 {o20,o21,o22,o23}, [%7+320];\n"
        "fma.rn.f16x2 p0, qz0, qz0, c;\n"
        "fma.rn.f16x2 p1, qz1, qz1, c; mul.rn.f16x2 a0, qz0, p0;\n"
        "mov.b32 {xl, xh}, a0; tanh.approx.f16 xr, xl; cvt.u32.u16 lo0, xr; tanh.approx.f16 xr, xh; cvt.u32.u16 hi0, xr; fma.rn.f16x2 p0, qz2, qz2, c; mul.rn.f16x2 a1, qz1, p1;\n"
        "mov.b32 {xl, xh}, a1; tanh.approx.f16 xr, xl; cvt.u32.u16 lo1, xr; tanh.approx.f16 xr, xh; cvt.u32.u16 hi1, xr; fma.rn.f16x2 p1, qz3, qz3, c; mul.rn.f16x2 a0, qz2, p0; prmt.b32 h0, lo0, hi0, 0x5410;\n"
        "mov.b32 {xl, xh}, a0; tanh.approx.f16 xr, xl; cvt.u32.u16 lo0, xr; tanh.approx.f16 xr, xh; cvt.u32.u16 hi0, xr; fma.rn.f16x2 p0, qz4, qz4, c; mul.rn.f16x2 a1, qz3, p1; fma.rn.f16x2 g0, qz0, h0, qz0; prmt.b32 h1, lo1, hi1, 0x5410;\n"
        "mov.b32 {xl, xh}, a1; tanh.approx.f16 xr, xl; cvt.u32.u16 lo1, xr; tanh.approx.f16 xr, xh; cvt.u32.u16 hi1, xr; fma.rn.f16x2 p1, qz5, qz5, c; mul.rn.f16x2 a0, qz4, p0; fma.rn.f16x2 g1, qz1, h1, qz1; prmt.b32 h0, lo0, hi0, 0x5410;\n"
        "mov.b32 {xl, xh}, a0; tanh.approx.f16 xr, xl; cvt.u32.u16 lo0, xr; tanh.approx.f16 xr, xh; cvt.u32.u16 hi0, xr; fma.rn.f16x2 p0, qz6, qz6, c; mul.rn.f16x2 a1, qz5, p1; fma.rn.f16x2 g2, qz2, h0, qz2; prmt.b32 h1, lo1, hi1, 0x5410;\n"
        "mov.b32 {xl, xh}, a1; tanh.approx.f16 xr, xl; cvt.u32.u16 lo1, xr; tanh.approx.f16 xr, xh; cvt.u32.u16 hi1, xr; fma.rn.f16x2 p1, qz7, qz7, c; mul.rn.f16x2 a0, qz6, p0; fma.rn.f16x2 g3, qz3, h1, qz3; prmt.b32 h0, lo0, hi0, 0x5410;\n"
        "mov.b32 v0, 0; mov.b32 v1, 0; mov.b32 v2, 0; mov.b32 v3, 0; mov.b32 v4, 0; mov.b32 v5, 0; mov.b32 v6, 0; mov.b32 v7, 0;\n"
        "LOOP:\n"
        "@!pm bra.uni SKIP0;\n"
        "wgmma.fence.sync.aligned;\n"
        "add.s64 dt, w1d, 768; wgmma.mma_async.sync.aligned.m64n64k16.f16.f16.f16 {qz16,qz17,qz18,qz19,qz20,qz21,qz22,qz23,qz24,qz25,qz26,qz27,qz28,qz29,qz30,qz31}, {qa0,qa1,qa2,qa3}, dt, pf, 1, 1, 1;\n"
        "add.s64 dt, w1d, 896; wgmma.mma_async.sync.aligned.m64n64k16.f16.f16.f16 {qz16,qz17,qz18,qz19,qz20,qz21,qz22,qz23,qz24,qz25,qz26,qz27,qz28,qz29,qz30,qz31}, {qa4,qa5,qa6,qa7}, dt, pt, 1, 1, 1;\n"
        "add.s64 dt, w1d, 1024; wgmma.mma_async.sync.aligned.m64n64k16.f16.f16.f16 {qz16,qz17,qz18,qz19,qz20,qz21,qz22,qz23,qz24,qz25,qz26,qz27,qz28,qz29,qz30,qz31}, {qa8,qa9,qa10,qa11}, dt, pt, 1, 1, 1;\n"
        "add.s64 dt, w1d, 1152; wgmma.mma_async.sync.aligned.m64n64k16.f16.f16.f16 {qz16,qz17,qz18,qz19,qz20,qz21,qz22,qz23,qz24,qz25,qz26,qz27,qz28,qz29,qz30,qz31}, {qa12,qa13,qa14,qa15}, dt, pt, 1, 1, 1;\n"
        "add.s64 dt, w1d, 1280; wgmma.mma_async.sync.aligned.m64n64k16.f16.f16.f16 {qz16,qz17,qz18,qz19,qz20,qz21,qz22,qz23,qz24,qz25,qz26,qz27,qz28,qz29,qz30,qz31}, {qa16,qa17,qa18,qa19}, dt, pt, 1, 1, 1;\n"
        "add.s64 dt, w1d, 1408; wgmma.mma_async.sync.aligned.m64n64k16.f16.f16.f16 {qz16,qz17,qz18,qz19,qz20,qz21,qz22,qz23,qz24,qz25,qz26,qz27,qz28,qz29,qz30,qz31}, {qa20,qa21,qa22,qa23}, dt, pt, 1, 1, 1;\n"
        "SKIP0:\n"
        "wgmma.fence.sync.aligned;\n"
        "wgmma.commit_group.sync.aligned;\n"
        "setp.lt.s32 pr, n, 0;\n"
        "@pr bra.uni FIRST;\n"
        "and.b32 tt, n, 1; mbarrier.try_wait.parity.shared::cta.b64 pw, [xbar], tt;\n"
        "@!pw bra.uni SPINX;\n"
        "BACKX:\n"
        "and.b32 ad, %6, 0xffff; add.u32 ad, ad, %4; ld.shared.v4.b32 {v0,v1,v2,v3}, [ad+0];\n"
        "shr.u32 ad, %6, 16; add.u32 ad, ad, %4; ld.shared.v4.b32 {v4,v5,v6,v7}, [ad+0];\n"
        "mov.b32 {xl, xh}, o0; cvt.f32.f16 f0, xl; cvt.f32.f16 f1, xh; cvt.rn.bf16x2.f32 tt, f1, f0; fma.rn.bf16x2 v0, tt, %8, v0;\n"
        "mov.b32 {xl, xh}, o2; cvt.f32.f16 f0, xl; cvt.f32.f16 f1, xh; cvt.rn.bf16x2.f32 tt, f1, f0; fma.rn.bf16x2 v1, tt, %8, v1;\n"
        "mov.b32 {xl, xh}, o4; cvt.f32.f16 f0, xl; cvt.f32.f16 f1, xh; cvt.rn.bf16x2.f32 tt, f1, f0; fma.rn.bf16x2 v2, tt, %8, v2;\n"
        "mov.b32 {xl, xh}, o6; cvt.f32.f16 f0, xl; cvt.f32.f16 f1, xh; cvt.rn.bf16x2.f32 tt, f1, f0; fma.rn.bf16x2 v3, tt, %8, v3;\n"
        "and.b32 ad, %6, 0xffff; add.u32 ad, ad, %4; st.shared.v4.b32 [ad+0], {v0,v1,v2,v3};\n"
        "and.b32 ad, %6, 0xffff; add.u32 ad, ad, %4; ld.shared.v4.b32 {v0,v1,v2,v3}, [ad+64];\n"
        "mov.b32 {xl, xh}, o1; cvt.f32.f16 f0, xl; cvt.f32.f16 f1, xh; cvt.rn.bf16x2.f32 tt, f1, f0; fma.rn.bf16x2 v4, tt, %8, v4;\n"
        "mov.b32 {xl, xh}, o3; cvt.f32.f16 f0, xl; cvt.f32.f16 f1, xh; cvt.rn.bf16x2.f32 tt, f1, f0; fma.rn.bf16x2 v5, tt, %8, v5;\n"
        "mov.b32 {xl, xh}, o5; cvt.f32.f16 f0, xl; cvt.f32.f16 f1, xh; cvt.rn.bf16x2.f32 tt, f1, f0; fma.rn.bf16x2 v6, tt, %8, v6;\n"
        "mov.b32 {xl, xh}, o7; cvt.f32.f16 f0, xl; cvt.f32.f16 f1, xh; cvt.rn.bf16x2.f32 tt, f1, f0; fma.rn.bf16x2 v7, tt, %8, v7;\n"
        "shr.u32 ad, %6, 16; add.u32 ad, ad, %4; st.shared.v4.b32 [ad+0], {v4,v5,v6,v7};\n"
        "shr.u32 ad, %6, 16; add.u32 ad, ad, %4; ld.shared.v4.b32 {v4,v5,v6,v7}, [ad+64];\n"
        "ld.shared.v4.b32 {o0,o1,o2,o3}, [%7+0];\n"
        "ld.shared.v4.b32 {o4,o5,o6,o7}, [%7+64];\n"
        "mov.b32 {xl, xh}, o8; cvt.f32.f16 f0, xl; cvt.f32.f16 f1, xh; cvt.rn.bf16x2.f32 tt, f1, f0; fma.rn.bf16x2 v0, tt, %8, v0;\n"
        "mov.b32 {xl, xh}, o10; cvt.f32.f16 f0, xl; cvt.f32.f16 f1, xh; cvt.rn.bf16x2.f32 tt, f1, f0; fma.rn.bf16x2 v1, tt, %8, v1;\n"
        "mov.b32 {xl, xh}, o12; cvt.f32.f16 f0, xl; cvt.f32.f16 f1, xh; cvt.rn.bf16x2.f32 tt, f1, f0; fma.rn.bf16x2 v2, tt, %8, v2;\n"
        "mov.b32 {xl, xh}, o14; cvt.f32.f16 f0, xl; cvt.f32.f16 f1, xh; cvt.rn.bf16x2.f32 tt, f1, f0; fma.rn.bf16x2 v3, tt, %8, v3;\n"
        "and.b32 ad, %6, 0xffff; add.u32 ad, ad, %4; st.shared.v4.b32 [ad+64], {v0,v1,v2,v3};\n"
        "and.b32 ad, %6, 0xffff; add.u32 ad, ad, %4; ld.shared.v4.b32 {v0,v1,v2,v3}, [ad+128];\n"
        "mov.b32 {xl, xh}, o9; cvt.f32.f16 f0, xl; cvt.f32.f16 f1, xh; cvt.rn.bf16x2.f32 tt, f1, f0; fma.rn.bf16x2 v4, tt, %8, v4;\n"
        "mov.b32 {xl, xh}, o11; cvt.f32.f16 f0, xl; cvt.f32.f16 f1, xh; cvt.rn.bf16x2.f32 tt, f1, f0; fma.rn.bf16x2 v5, tt, %8, v5;\n"
        "mov.b32 {xl, xh}, o13; cvt.f32.f16 f0, xl; cvt.f32.f16 f1, xh; cvt.rn.bf16x2.f32 tt, f1, f0; fma.rn.bf16x2 v6, tt, %8, v6;\n"
        "mov.b32 {xl, xh}, o15; cvt.f32.f16 f0, xl; cvt.f32.f16 f1, xh; cvt.rn.bf16x2.f32 tt, f1, f0; fma.rn.bf16x2 v7, tt, %8, v7;\n"
        "shr.u32 ad, %6, 16; add.u32 ad, ad, %4; st.shared.v4.b32 [ad+64], {v4,v5,v6,v7};\n"
        "shr.u32 ad, %6, 16; add.u32 ad, ad, %4; ld.shared.v4.b32 {v4,v5,v6,v7}, [ad+128];\n"
        "ld.shared.v4.b32 {o8,o9,o10,o11}, [%7+128];\n"
        "ld.shared.v4.b32 {o12,o13,o14,o15}, [%7+192];\n"
        "mov.b32 {xl, xh}, o16; cvt.f32.f16 f0, xl; cvt.f32.f16 f1, xh; cvt.rn.bf16x2.f32 tt, f1, f0; fma.rn.bf16x2 v0, tt, %8, v0;\n"
        "mov.b32 {xl, xh}, o18; cvt.f32.f16 f0, xl; cvt.f32.f16 f1, xh; cvt.rn.bf16x2.f32 tt, f1, f0; fma.rn.bf16x2 v1, tt, %8, v1;\n"
        "mov.b32 {xl, xh}, o20; cvt.f32.f16 f0, xl; cvt.f32.f16 f1, xh; cvt.rn.bf16x2.f32 tt, f1, f0; fma.rn.bf16x2 v2, tt, %8, v2;\n"
        "mov.b32 {xl, xh}, o22; cvt.f32.f16 f0, xl; cvt.f32.f16 f1, xh; cvt.rn.bf16x2.f32 tt, f1, f0; fma.rn.bf16x2 v3, tt, %8, v3;\n"
        "and.b32 ad, %6, 0xffff; add.u32 ad, ad, %4; st.shared.v4.b32 [ad+128], {v0,v1,v2,v3};\n"
        "mov.b32 {xl, xh}, o17; cvt.f32.f16 f0, xl; cvt.f32.f16 f1, xh; cvt.rn.bf16x2.f32 tt, f1, f0; fma.rn.bf16x2 v4, tt, %8, v4;\n"
        "mov.b32 {xl, xh}, o19; cvt.f32.f16 f0, xl; cvt.f32.f16 f1, xh; cvt.rn.bf16x2.f32 tt, f1, f0; fma.rn.bf16x2 v5, tt, %8, v5;\n"
        "mov.b32 {xl, xh}, o21; cvt.f32.f16 f0, xl; cvt.f32.f16 f1, xh; cvt.rn.bf16x2.f32 tt, f1, f0; fma.rn.bf16x2 v6, tt, %8, v6;\n"
        "mov.b32 {xl, xh}, o23; cvt.f32.f16 f0, xl; cvt.f32.f16 f1, xh; cvt.rn.bf16x2.f32 tt, f1, f0; fma.rn.bf16x2 v7, tt, %8, v7;\n"
        "shr.u32 ad, %6, 16; add.u32 ad, ad, %4; st.shared.v4.b32 [ad+128], {v4,v5,v6,v7};\n"
        "ld.shared.v4.b32 {o16,o17,o18,o19}, [%7+256];\n"
        "ld.shared.v4.b32 {o20,o21,o22,o23}, [%7+320];\n"
        "FIRST:\n"
        "@pz bra.uni B8;\n"
        "mov.b32 {xl, xh}, a0; tanh.approx.f16 xr, xl; cvt.u32.u16 lo0, xr; tanh.approx.f16 xr, xh; cvt.u32.u16 hi0, xr; fma.rn.f16x2 p0, qz8, qz8, c; mul.rn.f16x2 a1, qz7, p1; fma.rn.f16x2 g4, qz4, h0, qz4; prmt.b32 h1, lo1, hi1, 0x5410;\n"
        "mov.b32 {xl, xh}, a1; tanh.approx.f16 xr, xl; cvt.u32.u16 lo1, xr; tanh.approx.f16 xr, xh; cvt.u32.u16 hi1, xr; fma.rn.f16x2 p1, qz9, qz9, c; mul.rn.f16x2 a0, qz8, p0; fma.rn.f16x2 g5, qz5, h1, qz5; prmt.b32 h0, lo0, hi0, 0x5410;\n"
        "B8:\n"
        "fence.proxy.async.shared::cta;\n"
        "add.u32 tt, id, 4;\n"
        "@pl bra.uni STORE;\n"
        "bar.arrive tt, 128;\n"
        "STOREB:\n"
        ASM_MARK
        "@!pm bra.uni DONE;\n"
        "add.s32 n, n, 1; sub.u32 off, off, 393216; setp.lt.s32 pm, n, 7;\n"
        "@pz bra.uni B10;\n"
        "mov.b32 {xl, xh}, a0; tanh.approx.f16 xr, xl; cvt.u32.u16 lo0, xr; tanh.approx.f16 xr, xh; cvt.u32.u16 hi0, xr; fma.rn.f16x2 p0, qz10, qz10, c; mul.rn.f16x2 a1, qz9, p1; fma.rn.f16x2 g6, qz6, h0, qz6; prmt.b32 h1, lo1, hi1, 0x5410;\n"
        "mov.b32 {xl, xh}, a1; tanh.approx.f16 xr, xl; cvt.u32.u16 lo1, xr; tanh.approx.f16 xr, xh; cvt.u32.u16 hi1, xr; fma.rn.f16x2 p1, qz11, qz11, c; mul.rn.f16x2 a0, qz10, p0; fma.rn.f16x2 g7, qz7, h1, qz7; prmt.b32 h0, lo0, hi0, 0x5410;\n"
        "B10:\n"
        "wgmma.fence.sync.aligned;\n"
        "add.s64 dt, w2d, 0; wgmma.mma_async.sync.aligned.m64n96k16.f16.f16.f16 {o0,o1,o2,o3,o4,o5,o6,o7,o8,o9,o10,o11,o12,o13,o14,o15,o16,o17,o18,o19,o20,o21,o22,o23}, {g0,g1,g2,g3}, dt, pt, 1, 1, 1;\n"
        "add.s64 dt, w2d, 64; wgmma.mma_async.sync.aligned.m64n96k16.f16.f16.f16 {o0,o1,o2,o3,o4,o5,o6,o7,o8,o9,o10,o11,o12,o13,o14,o15,o16,o17,o18,o19,o20,o21,o22,o23}, {g4,g5,g6,g7}, dt, pt, 1, 1, 1;\n"
        "wgmma.commit_group.sync.aligned;\n"
        "@pz bra.uni B14;\n"
        "mov.b32 {xl, xh}, a0; tanh.approx.f16 xr, xl; cvt.u32.u16 lo0, xr; tanh.approx.f16 xr, xh; cvt.u32.u16 hi0, xr; fma.rn.f16x2 p0, qz12, qz12, c; mul.rn.f16x2 a1, qz11, p1; fma.rn.f16x2 g8, qz8, h0, qz8; prmt.b32 h1, lo1, hi1, 0x5410;\n"
        "mov.b32 {xl, xh}, a1; tanh.approx.f16 xr, xl; cvt.u32.u16 lo1, xr; tanh.approx.f16 xr, xh; cvt.u32.u16 hi1, xr; fma.rn.f16x2 p1, qz13, qz13, c; mul.rn.f16x2 a0, qz12, p0; fma.rn.f16x2 g9, qz9, h1, qz9; prmt.b32 h0, lo0, hi0, 0x5410;\n"
        "mov.b32 {xl, xh}, a0; tanh.approx.f16 xr, xl; cvt.u32.u16 lo0, xr; tanh.approx.f16 xr, xh; cvt.u32.u16 hi0, xr; fma.rn.f16x2 p0, qz14, qz14, c; mul.rn.f16x2 a1, qz13, p1; fma.rn.f16x2 g10, qz10, h0, qz10; prmt.b32 h1, lo1, hi1, 0x5410;\n"
        "mov.b32 {xl, xh}, a1; tanh.approx.f16 xr, xl; cvt.u32.u16 lo1, xr; tanh.approx.f16 xr, xh; cvt.u32.u16 hi1, xr; fma.rn.f16x2 p1, qz15, qz15, c; mul.rn.f16x2 a0, qz14, p0; fma.rn.f16x2 g11, qz11, h1, qz11; prmt.b32 h0, lo0, hi0, 0x5410;\n"
        "B14:\n"
        "wgmma.wait_group.sync.aligned 1;\n"
        "wgmma.fence.sync.aligned;\n"
        "add.s64 dt, w2d, 128; wgmma.mma_async.sync.aligned.m64n96k16.f16.f16.f16 {o0,o1,o2,o3,o4,o5,o6,o7,o8,o9,o10,o11,o12,o13,o14,o15,o16,o17,o18,o19,o20,o21,o22,o23}, {g8,g9,g10,g11}, dt, pt, 1, 1, 1;\n"
        "wgmma.commit_group.sync.aligned;\n"
        "@pz bra.uni B18;\n"
        "mov.b32 {xl, xh}, a0; tanh.approx.f16 xr, xl; cvt.u32.u16 lo0, xr; tanh.approx.f16 xr, xh; cvt.u32.u16 hi0, xr; fma.rn.f16x2 p0, qz16, qz16, c; mul.rn.f16x2 a1, qz15, p1; fma.rn.f16x2 g12, qz12, h0, qz12; prmt.b32 h1, lo1, hi1, 0x5410;\n"
        "mov.b32 {xl, xh}, a1; tanh.approx.f16 xr, xl; cvt.u32.u16 lo1, xr; tanh.approx.f16 xr, xh; cvt.u32.u16 hi1, xr; fma.rn.f16x2 p1, qz17, qz17, c; mul.rn.f16x2 a0, qz16, p0; fma.rn.f16x2 g13, qz13, h1, qz13; prmt.b32 h0, lo0, hi0, 0x5410;\n"
        "mov.b32 {xl, xh}, a0; tanh.approx.f16 xr, xl; cvt.u32.u16 lo0, xr; tanh.approx.f16 xr, xh; cvt.u32.u16 hi0, xr; fma.rn.f16x2 p0, qz18, qz18, c; mul.rn.f16x2 a1, qz17, p1; fma.rn.f16x2 g14, qz14, h0, qz14; prmt.b32 h1, lo1, hi1, 0x5410;\n"
        "mov.b32 {xl, xh}, a1; tanh.approx.f16 xr, xl; cvt.u32.u16 lo1, xr; tanh.approx.f16 xr, xh; cvt.u32.u16 hi1, xr; fma.rn.f16x2 p1, qz19, qz19, c; mul.rn.f16x2 a0, qz18, p0; fma.rn.f16x2 g15, qz15, h1, qz15; prmt.b32 h0, lo0, hi0, 0x5410;\n"
        "B18:\n"
        "wgmma.wait_group.sync.aligned 1;\n"
        "mad.lo.u32 tt, n, 8, tbar; mbarrier.try_wait.parity.shared::cta.b64 pw, [tt], tpar;\n"
        "@!pw bra.uni SPINT;\n"
        "BACKT:\n"
        "wgmma.fence.sync.aligned;\n"
        "add.s64 dt, w2d, 192; wgmma.mma_async.sync.aligned.m64n96k16.f16.f16.f16 {o0,o1,o2,o3,o4,o5,o6,o7,o8,o9,o10,o11,o12,o13,o14,o15,o16,o17,o18,o19,o20,o21,o22,o23}, {g12,g13,g14,g15}, dt, pt, 1, 1, 1;\n"
        "add.s64 dt, w1d, 1536; wgmma.mma_async.sync.aligned.m64n64k16.f16.f16.f16 {qz0,qz1,qz2,qz3,qz4,qz5,qz6,qz7,qz8,qz9,qz10,qz11,qz12,qz13,qz14,qz15}, {qa0,qa1,qa2,qa3}, dt, pf, 1, 1, 1;\n"
        "add.s64 dt, w1d, 1664; wgmma.mma_async.sync.aligned.m64n64k16.f16.f16.f16 {qz0,qz1,qz2,qz3,qz4,qz5,qz6,qz7,qz8,qz9,qz10,qz11,qz12,qz13,qz14,qz15}, {qa4,qa5,qa6,qa7}, dt, pt, 1, 1, 1;\n"
        "add.s64 dt, w1d, 1792; wgmma.mma_async.sync.aligned.m64n64k16.f16.f16.f16 {qz0,qz1,qz2,qz3,qz4,qz5,qz6,qz7,qz8,qz9,qz10,qz11,qz12,qz13,qz14,qz15}, {qa8,qa9,qa10,qa11}, dt, pt, 1, 1, 1;\n"
        "wgmma.commit_group.sync.aligned;\n"
        "@pl bra.uni YLOAD;\n"
        "YLOADB:\n"
        "@pz bra.uni B22;\n"
        "mov.b32 {xl, xh}, a0; tanh.approx.f16 xr, xl; cvt.u32.u16 lo0, xr; tanh.approx.f16 xr, xh; cvt.u32.u16 hi0, xr; fma.rn.f16x2 p0, qz20, qz20, c; mul.rn.f16x2 a1, qz19, p1; fma.rn.f16x2 g0, qz16, h0, qz16; prmt.b32 h1, lo1, hi1, 0x5410;\n"
        "mov.b32 {xl, xh}, a1; tanh.approx.f16 xr, xl; cvt.u32.u16 lo1, xr; tanh.approx.f16 xr, xh; cvt.u32.u16 hi1, xr; fma.rn.f16x2 p1, qz21, qz21, c; mul.rn.f16x2 a0, qz20, p0; fma.rn.f16x2 g1, qz17, h1, qz17; prmt.b32 h0, lo0, hi0, 0x5410;\n"
        "mov.b32 {xl, xh}, a0; tanh.approx.f16 xr, xl; cvt.u32.u16 lo0, xr; tanh.approx.f16 xr, xh; cvt.u32.u16 hi0, xr; fma.rn.f16x2 p0, qz22, qz22, c; mul.rn.f16x2 a1, qz21, p1; fma.rn.f16x2 g2, qz18, h0, qz18; prmt.b32 h1, lo1, hi1, 0x5410;\n"
        "mov.b32 {xl, xh}, a1; tanh.approx.f16 xr, xl; cvt.u32.u16 lo1, xr; tanh.approx.f16 xr, xh; cvt.u32.u16 hi1, xr; fma.rn.f16x2 p1, qz23, qz23, c; mul.rn.f16x2 a0, qz22, p0; fma.rn.f16x2 g3, qz19, h1, qz19; prmt.b32 h0, lo0, hi0, 0x5410;\n"
        "B22:\n"
        "wgmma.fence.sync.aligned;\n"
        "add.s64 dt, w2d, 256; wgmma.mma_async.sync.aligned.m64n96k16.f16.f16.f16 {o0,o1,o2,o3,o4,o5,o6,o7,o8,o9,o10,o11,o12,o13,o14,o15,o16,o17,o18,o19,o20,o21,o22,o23}, {g0,g1,g2,g3}, dt, pt, 1, 1, 1;\n"
        "add.s64 dt, w1d, 1920; wgmma.mma_async.sync.aligned.m64n64k16.f16.f16.f16 {qz0,qz1,qz2,qz3,qz4,qz5,qz6,qz7,qz8,qz9,qz10,qz11,qz12,qz13,qz14,qz15}, {qa12,qa13,qa14,qa15}, dt, pt, 1, 1, 1;\n"
        "add.s64 dt, w1d, 2048; wgmma.mma_async.sync.aligned.m64n64k16.f16.f16.f16 {qz0,qz1,qz2,qz3,qz4,qz5,qz6,qz7,qz8,qz9,qz10,qz11,qz12,qz13,qz14,qz15}, {qa16,qa17,qa18,qa19}, dt, pt, 1, 1, 1;\n"
        "add.s64 dt, w1d, 2176; wgmma.mma_async.sync.aligned.m64n64k16.f16.f16.f16 {qz0,qz1,qz2,qz3,qz4,qz5,qz6,qz7,qz8,qz9,qz10,qz11,qz12,qz13,qz14,qz15}, {qa20,qa21,qa22,qa23}, dt, pt, 1, 1, 1;\n"
        "wgmma.commit_group.sync.aligned;\n"
        "@pz bra.uni B26;\n"
        "mov.b32 {xl, xh}, a0; tanh.approx.f16 xr, xl; cvt.u32.u16 lo0, xr; tanh.approx.f16 xr, xh; cvt.u32.u16 hi0, xr; fma.rn.f16x2 p0, qz24, qz24, c; mul.rn.f16x2 a1, qz23, p1; fma.rn.f16x2 g4, qz20, h0, qz20; prmt.b32 h1, lo1, hi1, 0x5410;\n"
        "mov.b32 {xl, xh}, a1; tanh.approx.f16 xr, xl; cvt.u32.u16 lo1, xr; tanh.approx.f16 xr, xh; cvt.u32.u16 hi1, xr; fma.rn.f16x2 p1, qz25, qz25, c; mul.rn.f16x2 a0, qz24, p0; fma.rn.f16x2 g5, qz21, h1, qz21; prmt.b32 h0, lo0, hi0, 0x5410;\n"
        "mov.b32 {xl, xh}, a0; tanh.approx.f16 xr, xl; cvt.u32.u16 lo0, xr; tanh.approx.f16 xr, xh; cvt.u32.u16 hi0, xr; fma.rn.f16x2 p0, qz26, qz26, c; mul.rn.f16x2 a1, qz25, p1; fma.rn.f16x2 g6, qz22, h0, qz22; prmt.b32 h1, lo1, hi1, 0x5410;\n"
        "mov.b32 {xl, xh}, a1; tanh.approx.f16 xr, xl; cvt.u32.u16 lo1, xr; tanh.approx.f16 xr, xh; cvt.u32.u16 hi1, xr; fma.rn.f16x2 p1, qz27, qz27, c; mul.rn.f16x2 a0, qz26, p0; fma.rn.f16x2 g7, qz23, h1, qz23; prmt.b32 h0, lo0, hi0, 0x5410;\n"
        "B26:\n"
        "wgmma.wait_group.sync.aligned 2;\n"
        "wgmma.fence.sync.aligned;\n"
        "add.s64 dt, w2d, 320; wgmma.mma_async.sync.aligned.m64n96k16.f16.f16.f16 {o0,o1,o2,o3,o4,o5,o6,o7,o8,o9,o10,o11,o12,o13,o14,o15,o16,o17,o18,o19,o20,o21,o22,o23}, {g4,g5,g6,g7}, dt, pt, 1, 1, 1;\n"
        "wgmma.commit_group.sync.aligned;\n"
        "@pz bra.uni B30;\n"
        "mov.b32 {xl, xh}, a0; tanh.approx.f16 xr, xl; cvt.u32.u16 lo0, xr; tanh.approx.f16 xr, xh; cvt.u32.u16 hi0, xr; fma.rn.f16x2 p0, qz28, qz28, c; mul.rn.f16x2 a1, qz27, p1; fma.rn.f16x2 g8, qz24, h0, qz24; prmt.b32 h1, lo1, hi1, 0x5410;\n"
        "mov.b32 {xl, xh}, a1; tanh.approx.f16 xr, xl; cvt.u32.u16 lo1, xr; tanh.approx.f16 xr, xh; cvt.u32.u16 hi1, xr; fma.rn.f16x2 p1, qz29, qz29, c; mul.rn.f16x2 a0, qz28, p0; fma.rn.f16x2 g9, qz25, h1, qz25; prmt.b32 h0, lo0, hi0, 0x5410;\n"
        "mov.b32 {xl, xh}, a0; tanh.approx.f16 xr, xl; cvt.u32.u16 lo0, xr; tanh.approx.f16 xr, xh; cvt.u32.u16 hi0, xr; fma.rn.f16x2 p0, qz30, qz30, c; mul.rn.f16x2 a1, qz29, p1; fma.rn.f16x2 g10, qz26, h0, qz26; prmt.b32 h1, lo1, hi1, 0x5410;\n"
        "mov.b32 {xl, xh}, a1; tanh.approx.f16 xr, xl; cvt.u32.u16 lo1, xr; tanh.approx.f16 xr, xh; cvt.u32.u16 hi1, xr; fma.rn.f16x2 p1, qz31, qz31, c; mul.rn.f16x2 a0, qz30, p0; fma.rn.f16x2 g11, qz27, h1, qz27; prmt.b32 h0, lo0, hi0, 0x5410;\n"
        "B30:\n"
        "wgmma.wait_group.sync.aligned 1;\n"
        "wgmma.fence.sync.aligned;\n"
        "add.s64 dt, w2d, 384; wgmma.mma_async.sync.aligned.m64n96k16.f16.f16.f16 {o0,o1,o2,o3,o4,o5,o6,o7,o8,o9,o10,o11,o12,o13,o14,o15,o16,o17,o18,o19,o20,o21,o22,o23}, {g8,g9,g10,g11}, dt, pt, 1, 1, 1;\n"
        "wgmma.commit_group.sync.aligned;\n"
        "@pz bra.uni B34;\n"
        "mov.b32 {xl, xh}, a0; tanh.approx.f16 xr, xl; cvt.u32.u16 lo0, xr; tanh.approx.f16 xr, xh; cvt.u32.u16 hi0, xr; fma.rn.f16x2 p0, qz0, qz0, c; mul.rn.f16x2 a1, qz31, p1; fma.rn.f16x2 g12, qz28, h0, qz28; prmt.b32 h1, lo1, hi1, 0x5410;\n"
        "mov.b32 {xl, xh}, a1; tanh.approx.f16 xr, xl; cvt.u32.u16 lo1, xr; tanh.approx.f16 xr, xh; cvt.u32.u16 hi1, xr; fma.rn.f16x2 p1, qz1, qz1, c; mul.rn.f16x2 a0, qz0, p0; fma.rn.f16x2 g13, qz29, h1, qz29; prmt.b32 h0, lo0, hi0, 0x5410;\n"
        "mov.b32 {xl, xh}, a0; tanh.approx.f16 xr, xl; cvt.u32.u16 lo0, xr; tanh.approx.f16 xr, xh; cvt.u32.u16 hi0, xr; fma.rn.f16x2 p0, qz2, qz2, c; mul.rn.f16x2 a1, qz1, p1; fma.rn.f16x2 g14, qz30, h0, qz30; prmt.b32 h1, lo1, hi1, 0x5410;\n"
        "mov.b32 {xl, xh}, a1; tanh.approx.f16 xr, xl; cvt.u32.u16 lo1, xr; tanh.approx.f16 xr, xh; cvt.u32.u16 hi1, xr; fma.rn.f16x2 p1, qz3, qz3, c; mul.rn.f16x2 a0, qz2, p0; fma.rn.f16x2 g15, qz31, h1, qz31; prmt.b32 h0, lo0, hi0, 0x5410;\n"
        "B34:\n"
        "wgmma.fence.sync.aligned;\n"
        "add.s64 dt, w2d, 448; wgmma.mma_async.sync.aligned.m64n96k16.f16.f16.f16 {o0,o1,o2,o3,o4,o5,o6,o7,o8,o9,o10,o11,o12,o13,o14,o15,o16,o17,o18,o19,o20,o21,o22,o23}, {g12,g13,g14,g15}, dt, pt, 1, 1, 1;\n"
        "add.s64 dt, w1d, 2304; wgmma.mma_async.sync.aligned.m64n64k16.f16.f16.f16 {qz16,qz17,qz18,qz19,qz20,qz21,qz22,qz23,qz24,qz25,qz26,qz27,qz28,qz29,qz30,qz31}, {qa0,qa1,qa2,qa3}, dt, pf, 1, 1, 1;\n"
        "add.s64 dt, w1d, 2432; wgmma.mma_async.sync.aligned.m64n64k16.f16.f16.f16 {qz16,qz17,qz18,qz19,qz20,qz21,qz22,qz23,qz24,qz25,qz26,qz27,qz28,qz29,qz30,qz31}, {qa4,qa5,qa6,qa7}, dt, pt, 1, 1, 1;\n"
        "add.s64 dt, w1d, 2560; wgmma.mma_async.sync.aligned.m64n64k16.f16.f16.f16 {qz16,qz17,qz18,qz19,qz20,qz21,qz22,qz23,qz24,qz25,qz26,qz27,qz28,qz29,qz30,qz31}, {qa8,qa9,qa10,qa11}, dt, pt, 1, 1, 1;\n"
        "wgmma.commit_group.sync.aligned;\n"
        "@pz bra.uni B38;\n"
        "mov.b32 {xl, xh}, a0; tanh.approx.f16 xr, xl; cvt.u32.u16 lo0, xr; tanh.approx.f16 xr, xh; cvt.u32.u16 hi0, xr; fma.rn.f16x2 p0, qz4, qz4, c; mul.rn.f16x2 a1, qz3, p1; fma.rn.f16x2 g0, qz0, h0, qz0; prmt.b32 h1, lo1, hi1, 0x5410;\n"
        "mov.b32 {xl, xh}, a1; tanh.approx.f16 xr, xl; cvt.u32.u16 lo1, xr; tanh.approx.f16 xr, xh; cvt.u32.u16 hi1, xr; fma.rn.f16x2 p1, qz5, qz5, c; mul.rn.f16x2 a0, qz4, p0; fma.rn.f16x2 g1, qz1, h1, qz1; prmt.b32 h0, lo0, hi0, 0x5410;\n"
        "mov.b32 {xl, xh}, a0; tanh.approx.f16 xr, xl; cvt.u32.u16 lo0, xr; tanh.approx.f16 xr, xh; cvt.u32.u16 hi0, xr; fma.rn.f16x2 p0, qz6, qz6, c; mul.rn.f16x2 a1, qz5, p1; fma.rn.f16x2 g2, qz2, h0, qz2; prmt.b32 h1, lo1, hi1, 0x5410;\n"
        "mov.b32 {xl, xh}, a1; tanh.approx.f16 xr, xl; cvt.u32.u16 lo1, xr; tanh.approx.f16 xr, xh; cvt.u32.u16 hi1, xr; fma.rn.f16x2 p1, qz7, qz7, c; mul.rn.f16x2 a0, qz6, p0; fma.rn.f16x2 g3, qz3, h1, qz3; prmt.b32 h0, lo0, hi0, 0x5410;\n"
        "B38:\n"
        "wgmma.wait_group.sync.aligned 2;\n"
        "wgmma.fence.sync.aligned;\n"
        "add.s64 dt, w2d, 512; wgmma.mma_async.sync.aligned.m64n96k16.f16.f16.f16 {o0,o1,o2,o3,o4,o5,o6,o7,o8,o9,o10,o11,o12,o13,o14,o15,o16,o17,o18,o19,o20,o21,o22,o23}, {g0,g1,g2,g3}, dt, pt, 1, 1, 1;\n"
        "add.s64 dt, w1d, 2688; wgmma.mma_async.sync.aligned.m64n64k16.f16.f16.f16 {qz16,qz17,qz18,qz19,qz20,qz21,qz22,qz23,qz24,qz25,qz26,qz27,qz28,qz29,qz30,qz31}, {qa12,qa13,qa14,qa15}, dt, pt, 1, 1, 1;\n"
        "add.s64 dt, w1d, 2816; wgmma.mma_async.sync.aligned.m64n64k16.f16.f16.f16 {qz16,qz17,qz18,qz19,qz20,qz21,qz22,qz23,qz24,qz25,qz26,qz27,qz28,qz29,qz30,qz31}, {qa16,qa17,qa18,qa19}, dt, pt, 1, 1, 1;\n"
        "add.s64 dt, w1d, 2944; wgmma.mma_async.sync.aligned.m64n64k16.f16.f16.f16 {qz16,qz17,qz18,qz19,qz20,qz21,qz22,qz23,qz24,qz25,qz26,qz27,qz28,qz29,qz30,qz31}, {qa20,qa21,qa22,qa23}, dt, pt, 1, 1, 1;\n"
        "wgmma.commit_group.sync.aligned;\n"
        "@pz bra.uni B42;\n"
        "mov.b32 {xl, xh}, a0; tanh.approx.f16 xr, xl; cvt.u32.u16 lo0, xr; tanh.approx.f16 xr, xh; cvt.u32.u16 hi0, xr; fma.rn.f16x2 p0, qz8, qz8, c; mul.rn.f16x2 a1, qz7, p1; fma.rn.f16x2 g4, qz4, h0, qz4; prmt.b32 h1, lo1, hi1, 0x5410;\n"
        "mov.b32 {xl, xh}, a1; tanh.approx.f16 xr, xl; cvt.u32.u16 lo1, xr; tanh.approx.f16 xr, xh; cvt.u32.u16 hi1, xr; fma.rn.f16x2 p1, qz9, qz9, c; mul.rn.f16x2 a0, qz8, p0; fma.rn.f16x2 g5, qz5, h1, qz5; prmt.b32 h0, lo0, hi0, 0x5410;\n"
        "mov.b32 {xl, xh}, a0; tanh.approx.f16 xr, xl; cvt.u32.u16 lo0, xr; tanh.approx.f16 xr, xh; cvt.u32.u16 hi0, xr; fma.rn.f16x2 p0, qz10, qz10, c; mul.rn.f16x2 a1, qz9, p1; fma.rn.f16x2 g6, qz6, h0, qz6; prmt.b32 h1, lo1, hi1, 0x5410;\n"
        "mov.b32 {xl, xh}, a1; tanh.approx.f16 xr, xl; cvt.u32.u16 lo1, xr; tanh.approx.f16 xr, xh; cvt.u32.u16 hi1, xr; fma.rn.f16x2 p1, qz11, qz11, c; mul.rn.f16x2 a0, qz10, p0; fma.rn.f16x2 g7, qz7, h1, qz7; prmt.b32 h0, lo0, hi0, 0x5410;\n"
        "B42:\n"
        "wgmma.wait_group.sync.aligned 2;\n"
        "wgmma.fence.sync.aligned;\n"
        "add.s64 dt, w2d, 576; wgmma.mma_async.sync.aligned.m64n96k16.f16.f16.f16 {o0,o1,o2,o3,o4,o5,o6,o7,o8,o9,o10,o11,o12,o13,o14,o15,o16,o17,o18,o19,o20,o21,o22,o23}, {g4,g5,g6,g7}, dt, pt, 1, 1, 1;\n"
        "wgmma.commit_group.sync.aligned;\n"
        "mad.lo.u32 tt, n, 8, tbar;\n"
        "@pn mbarrier.arrive.shared::cta.b64 _, [tt+64];\n"
        "@pz bra.uni B46;\n"
        "mov.b32 {xl, xh}, a0; tanh.approx.f16 xr, xl; cvt.u32.u16 lo0, xr; tanh.approx.f16 xr, xh; cvt.u32.u16 hi0, xr; fma.rn.f16x2 p0, qz12, qz12, c; mul.rn.f16x2 a1, qz11, p1; fma.rn.f16x2 g8, qz8, h0, qz8; prmt.b32 h1, lo1, hi1, 0x5410;\n"
        "mov.b32 {xl, xh}, a1; tanh.approx.f16 xr, xl; cvt.u32.u16 lo1, xr; tanh.approx.f16 xr, xh; cvt.u32.u16 hi1, xr; fma.rn.f16x2 p1, qz13, qz13, c; mul.rn.f16x2 a0, qz12, p0; fma.rn.f16x2 g9, qz9, h1, qz9; prmt.b32 h0, lo0, hi0, 0x5410;\n"
        "mov.b32 {xl, xh}, a0; tanh.approx.f16 xr, xl; cvt.u32.u16 lo0, xr; tanh.approx.f16 xr, xh; cvt.u32.u16 hi0, xr; fma.rn.f16x2 p0, qz14, qz14, c; mul.rn.f16x2 a1, qz13, p1; fma.rn.f16x2 g10, qz10, h0, qz10; prmt.b32 h1, lo1, hi1, 0x5410;\n"
        "mov.b32 {xl, xh}, a1; tanh.approx.f16 xr, xl; cvt.u32.u16 lo1, xr; tanh.approx.f16 xr, xh; cvt.u32.u16 hi1, xr; fma.rn.f16x2 p1, qz15, qz15, c; mul.rn.f16x2 a0, qz14, p0; fma.rn.f16x2 g11, qz11, h1, qz11; prmt.b32 h0, lo0, hi0, 0x5410;\n"
        "B46:\n"
        "wgmma.wait_group.sync.aligned 1;\n"
        "wgmma.fence.sync.aligned;\n"
        "add.s64 dt, w2d, 640; wgmma.mma_async.sync.aligned.m64n96k16.f16.f16.f16 {o0,o1,o2,o3,o4,o5,o6,o7,o8,o9,o10,o11,o12,o13,o14,o15,o16,o17,o18,o19,o20,o21,o22,o23}, {g8,g9,g10,g11}, dt, pt, 1, 1, 1;\n"
        "wgmma.commit_group.sync.aligned;\n"
        "@pz bra.uni B50;\n"
        "mov.b32 {xl, xh}, a0; tanh.approx.f16 xr, xl; cvt.u32.u16 lo0, xr; tanh.approx.f16 xr, xh; cvt.u32.u16 hi0, xr; fma.rn.f16x2 p0, qz16, qz16, c; mul.rn.f16x2 a1, qz15, p1; fma.rn.f16x2 g12, qz12, h0, qz12; prmt.b32 h1, lo1, hi1, 0x5410;\n"
        "mov.b32 {xl, xh}, a1; tanh.approx.f16 xr, xl; cvt.u32.u16 lo1, xr; tanh.approx.f16 xr, xh; cvt.u32.u16 hi1, xr; fma.rn.f16x2 p1, qz17, qz17, c; mul.rn.f16x2 a0, qz16, p0; fma.rn.f16x2 g13, qz13, h1, qz13; prmt.b32 h0, lo0, hi0, 0x5410;\n"
        "mov.b32 {xl, xh}, a0; tanh.approx.f16 xr, xl; cvt.u32.u16 lo0, xr; tanh.approx.f16 xr, xh; cvt.u32.u16 hi0, xr; fma.rn.f16x2 p0, qz18, qz18, c; mul.rn.f16x2 a1, qz17, p1; fma.rn.f16x2 g14, qz14, h0, qz14; prmt.b32 h1, lo1, hi1, 0x5410;\n"
        "mov.b32 {xl, xh}, a1; tanh.approx.f16 xr, xl; cvt.u32.u16 lo1, xr; tanh.approx.f16 xr, xh; cvt.u32.u16 hi1, xr; fma.rn.f16x2 p1, qz19, qz19, c; mul.rn.f16x2 a0, qz18, p0; fma.rn.f16x2 g15, qz15, h1, qz15; prmt.b32 h0, lo0, hi0, 0x5410;\n"
        "B50:\n"
        "wgmma.fence.sync.aligned;\n"
        "add.s64 dt, w2d, 704; wgmma.mma_async.sync.aligned.m64n96k16.f16.f16.f16 {o0,o1,o2,o3,o4,o5,o6,o7,o8,o9,o10,o11,o12,o13,o14,o15,o16,o17,o18,o19,o20,o21,o22,o23}, {g12,g13,g14,g15}, dt, pt, 1, 1, 1;\n"
        "add.s64 dt, w1d, 3072; wgmma.mma_async.sync.aligned.m64n64k16.f16.f16.f16 {qz0,qz1,qz2,qz3,qz4,qz5,qz6,qz7,qz8,qz9,qz10,qz11,qz12,qz13,qz14,qz15}, {qa0,qa1,qa2,qa3}, dt, pf, 1, 1, 1;\n"
        "add.s64 dt, w1d, 3200; wgmma.mma_async.sync.aligned.m64n64k16.f16.f16.f16 {qz0,qz1,qz2,qz3,qz4,qz5,qz6,qz7,qz8,qz9,qz10,qz11,qz12,qz13,qz14,qz15}, {qa4,qa5,qa6,qa7}, dt, pt, 1, 1, 1;\n"
        "add.s64 dt, w1d, 3328; wgmma.mma_async.sync.aligned.m64n64k16.f16.f16.f16 {qz0,qz1,qz2,qz3,qz4,qz5,qz6,qz7,qz8,qz9,qz10,qz11,qz12,qz13,qz14,qz15}, {qa8,qa9,qa10,qa11}, dt, pt, 1, 1, 1;\n"
        "wgmma.commit_group.sync.aligned;\n"
        "@pz bra.uni B54;\n"
        "mov.b32 {xl, xh}, a0; tanh.approx.f16 xr, xl; cvt.u32.u16 lo0, xr; tanh.approx.f16 xr, xh; cvt.u32.u16 hi0, xr; fma.rn.f16x2 p0, qz20, qz20, c; mul.rn.f16x2 a1, qz19, p1; fma.rn.f16x2 g0, qz16, h0, qz16; prmt.b32 h1, lo1, hi1, 0x5410;\n"
        "mov.b32 {xl, xh}, a1; tanh.approx.f16 xr, xl; cvt.u32.u16 lo1, xr; tanh.approx.f16 xr, xh; cvt.u32.u16 hi1, xr; fma.rn.f16x2 p1, qz21, qz21, c; mul.rn.f16x2 a0, qz20, p0; fma.rn.f16x2 g1, qz17, h1, qz17; prmt.b32 h0, lo0, hi0, 0x5410;\n"
        "mov.b32 {xl, xh}, a0; tanh.approx.f16 xr, xl; cvt.u32.u16 lo0, xr; tanh.approx.f16 xr, xh; cvt.u32.u16 hi0, xr; fma.rn.f16x2 p0, qz22, qz22, c; mul.rn.f16x2 a1, qz21, p1; fma.rn.f16x2 g2, qz18, h0, qz18; prmt.b32 h1, lo1, hi1, 0x5410;\n"
        "mov.b32 {xl, xh}, a1; tanh.approx.f16 xr, xl; cvt.u32.u16 lo1, xr; tanh.approx.f16 xr, xh; cvt.u32.u16 hi1, xr; fma.rn.f16x2 p1, qz23, qz23, c; mul.rn.f16x2 a0, qz22, p0; fma.rn.f16x2 g3, qz19, h1, qz19; prmt.b32 h0, lo0, hi0, 0x5410;\n"
        "B54:\n"
        "wgmma.wait_group.sync.aligned 2;\n"
        "wgmma.fence.sync.aligned;\n"
        "add.s64 dt, w2d, 768; wgmma.mma_async.sync.aligned.m64n96k16.f16.f16.f16 {o0,o1,o2,o3,o4,o5,o6,o7,o8,o9,o10,o11,o12,o13,o14,o15,o16,o17,o18,o19,o20,o21,o22,o23}, {g0,g1,g2,g3}, dt, pt, 1, 1, 1;\n"
        "add.s64 dt, w1d, 3456; wgmma.mma_async.sync.aligned.m64n64k16.f16.f16.f16 {qz0,qz1,qz2,qz3,qz4,qz5,qz6,qz7,qz8,qz9,qz10,qz11,qz12,qz13,qz14,qz15}, {qa12,qa13,qa14,qa15}, dt, pt, 1, 1, 1;\n"
        "add.s64 dt, w1d, 3584; wgmma.mma_async.sync.aligned.m64n64k16.f16.f16.f16 {qz0,qz1,qz2,qz3,qz4,qz5,qz6,qz7,qz8,qz9,qz10,qz11,qz12,qz13,qz14,qz15}, {qa16,qa17,qa18,qa19}, dt, pt, 1, 1, 1;\n"
        "add.s64 dt, w1d, 3712; wgmma.mma_async.sync.aligned.m64n64k16.f16.f16.f16 {qz0,qz1,qz2,qz3,qz4,qz5,qz6,qz7,qz8,qz9,qz10,qz11,qz12,qz13,qz14,qz15}, {qa20,qa21,qa22,qa23}, dt, pt, 1, 1, 1;\n"
        "wgmma.commit_group.sync.aligned;\n"
        "@pz bra.uni B58;\n"
        "mov.b32 {xl, xh}, a0; tanh.approx.f16 xr, xl; cvt.u32.u16 lo0, xr; tanh.approx.f16 xr, xh; cvt.u32.u16 hi0, xr; fma.rn.f16x2 p0, qz24, qz24, c; mul.rn.f16x2 a1, qz23, p1; fma.rn.f16x2 g4, qz20, h0, qz20; prmt.b32 h1, lo1, hi1, 0x5410;\n"
        "mov.b32 {xl, xh}, a1; tanh.approx.f16 xr, xl; cvt.u32.u16 lo1, xr; tanh.approx.f16 xr, xh; cvt.u32.u16 hi1, xr; fma.rn.f16x2 p1, qz25, qz25, c; mul.rn.f16x2 a0, qz24, p0; fma.rn.f16x2 g5, qz21, h1, qz21; prmt.b32 h0, lo0, hi0, 0x5410;\n"
        "mov.b32 {xl, xh}, a0; tanh.approx.f16 xr, xl; cvt.u32.u16 lo0, xr; tanh.approx.f16 xr, xh; cvt.u32.u16 hi0, xr; fma.rn.f16x2 p0, qz26, qz26, c; mul.rn.f16x2 a1, qz25, p1; fma.rn.f16x2 g6, qz22, h0, qz22; prmt.b32 h1, lo1, hi1, 0x5410;\n"
        "mov.b32 {xl, xh}, a1; tanh.approx.f16 xr, xl; cvt.u32.u16 lo1, xr; tanh.approx.f16 xr, xh; cvt.u32.u16 hi1, xr; fma.rn.f16x2 p1, qz27, qz27, c; mul.rn.f16x2 a0, qz26, p0; fma.rn.f16x2 g7, qz23, h1, qz23; prmt.b32 h0, lo0, hi0, 0x5410;\n"
        "B58:\n"
        "wgmma.wait_group.sync.aligned 2;\n"
        "wgmma.fence.sync.aligned;\n"
        "add.s64 dt, w2d, 832; wgmma.mma_async.sync.aligned.m64n96k16.f16.f16.f16 {o0,o1,o2,o3,o4,o5,o6,o7,o8,o9,o10,o11,o12,o13,o14,o15,o16,o17,o18,o19,o20,o21,o22,o23}, {g4,g5,g6,g7}, dt, pt, 1, 1, 1;\n"
        "wgmma.commit_group.sync.aligned;\n"
        "@pz bra.uni B62;\n"
        "mov.b32 {xl, xh}, a0; tanh.approx.f16 xr, xl; cvt.u32.u16 lo0, xr; tanh.approx.f16 xr, xh; cvt.u32.u16 hi0, xr; fma.rn.f16x2 p0, qz28, qz28, c; mul.rn.f16x2 a1, qz27, p1; fma.rn.f16x2 g8, qz24, h0, qz24; prmt.b32 h1, lo1, hi1, 0x5410;\n"
        "mov.b32 {xl, xh}, a1; tanh.approx.f16 xr, xl; cvt.u32.u16 lo1, xr; tanh.approx.f16 xr, xh; cvt.u32.u16 hi1, xr; fma.rn.f16x2 p1, qz29, qz29, c; mul.rn.f16x2 a0, qz28, p0; fma.rn.f16x2 g9, qz25, h1, qz25; prmt.b32 h0, lo0, hi0, 0x5410;\n"
        "mov.b32 {xl, xh}, a0; tanh.approx.f16 xr, xl; cvt.u32.u16 lo0, xr; tanh.approx.f16 xr, xh; cvt.u32.u16 hi0, xr; fma.rn.f16x2 p0, qz30, qz30, c; mul.rn.f16x2 a1, qz29, p1; fma.rn.f16x2 g10, qz26, h0, qz26; prmt.b32 h1, lo1, hi1, 0x5410;\n"
        "mov.b32 {xl, xh}, a1; tanh.approx.f16 xr, xl; cvt.u32.u16 lo1, xr; tanh.approx.f16 xr, xh; cvt.u32.u16 hi1, xr; fma.rn.f16x2 p1, qz31, qz31, c; mul.rn.f16x2 a0, qz30, p0; fma.rn.f16x2 g11, qz27, h1, qz27; prmt.b32 h0, lo0, hi0, 0x5410;\n"
        "B62:\n"
        "wgmma.wait_group.sync.aligned 1;\n"
        "wgmma.fence.sync.aligned;\n"
        "add.s64 dt, w2d, 896; wgmma.mma_async.sync.aligned.m64n96k16.f16.f16.f16 {o0,o1,o2,o3,o4,o5,o6,o7,o8,o9,o10,o11,o12,o13,o14,o15,o16,o17,o18,o19,o20,o21,o22,o23}, {g8,g9,g10,g11}, dt, pt, 1, 1, 1;\n"
        "wgmma.commit_group.sync.aligned;\n"
        "@pz bra.uni B66;\n"
        "mov.b32 {xl, xh}, a0; tanh.approx.f16 xr, xl; cvt.u32.u16 lo0, xr; tanh.approx.f16 xr, xh; cvt.u32.u16 hi0, xr; fma.rn.f16x2 p0, qz0, qz0, c; mul.rn.f16x2 a1, qz31, p1; fma.rn.f16x2 g12, qz28, h0, qz28; prmt.b32 h1, lo1, hi1, 0x5410;\n"
        "mov.b32 {xl, xh}, a1; tanh.approx.f16 xr, xl; cvt.u32.u16 lo1, xr; tanh.approx.f16 xr, xh; cvt.u32.u16 hi1, xr; fma.rn.f16x2 p1, qz1, qz1, c; mul.rn.f16x2 a0, qz0, p0; fma.rn.f16x2 g13, qz29, h1, qz29; prmt.b32 h0, lo0, hi0, 0x5410;\n"
        "mov.b32 {xl, xh}, a0; tanh.approx.f16 xr, xl; cvt.u32.u16 lo0, xr; tanh.approx.f16 xr, xh; cvt.u32.u16 hi0, xr; fma.rn.f16x2 p0, qz2, qz2, c; mul.rn.f16x2 a1, qz1, p1; fma.rn.f16x2 g14, qz30, h0, qz30; prmt.b32 h1, lo1, hi1, 0x5410;\n"
        "mov.b32 {xl, xh}, a1; tanh.approx.f16 xr, xl; cvt.u32.u16 lo1, xr; tanh.approx.f16 xr, xh; cvt.u32.u16 hi1, xr; fma.rn.f16x2 p1, qz3, qz3, c; mul.rn.f16x2 a0, qz2, p0; fma.rn.f16x2 g15, qz31, h1, qz31; prmt.b32 h0, lo0, hi0, 0x5410;\n"
        "B66:\n"
        "wgmma.fence.sync.aligned;\n"
        "add.s64 dt, w2d, 960; wgmma.mma_async.sync.aligned.m64n96k16.f16.f16.f16 {o0,o1,o2,o3,o4,o5,o6,o7,o8,o9,o10,o11,o12,o13,o14,o15,o16,o17,o18,o19,o20,o21,o22,o23}, {g12,g13,g14,g15}, dt, pt, 1, 1, 1;\n"
        "add.s64 dt, w1d, 3840; wgmma.mma_async.sync.aligned.m64n64k16.f16.f16.f16 {qz16,qz17,qz18,qz19,qz20,qz21,qz22,qz23,qz24,qz25,qz26,qz27,qz28,qz29,qz30,qz31}, {qa0,qa1,qa2,qa3}, dt, pf, 1, 1, 1;\n"
        "add.s64 dt, w1d, 3968; wgmma.mma_async.sync.aligned.m64n64k16.f16.f16.f16 {qz16,qz17,qz18,qz19,qz20,qz21,qz22,qz23,qz24,qz25,qz26,qz27,qz28,qz29,qz30,qz31}, {qa4,qa5,qa6,qa7}, dt, pt, 1, 1, 1;\n"
        "add.s64 dt, w1d, 4096; wgmma.mma_async.sync.aligned.m64n64k16.f16.f16.f16 {qz16,qz17,qz18,qz19,qz20,qz21,qz22,qz23,qz24,qz25,qz26,qz27,qz28,qz29,qz30,qz31}, {qa8,qa9,qa10,qa11}, dt, pt, 1, 1, 1;\n"
        "wgmma.commit_group.sync.aligned;\n"
        "@pz bra.uni B70;\n"
        "mov.b32 {xl, xh}, a0; tanh.approx.f16 xr, xl; cvt.u32.u16 lo0, xr; tanh.approx.f16 xr, xh; cvt.u32.u16 hi0, xr; fma.rn.f16x2 p0, qz4, qz4, c; mul.rn.f16x2 a1, qz3, p1; fma.rn.f16x2 g0, qz0, h0, qz0; prmt.b32 h1, lo1, hi1, 0x5410;\n"
        "mov.b32 {xl, xh}, a1; tanh.approx.f16 xr, xl; cvt.u32.u16 lo1, xr; tanh.approx.f16 xr, xh; cvt.u32.u16 hi1, xr; fma.rn.f16x2 p1, qz5, qz5, c; mul.rn.f16x2 a0, qz4, p0; fma.rn.f16x2 g1, qz1, h1, qz1; prmt.b32 h0, lo0, hi0, 0x5410;\n"
        "mov.b32 {xl, xh}, a0; tanh.approx.f16 xr, xl; cvt.u32.u16 lo0, xr; tanh.approx.f16 xr, xh; cvt.u32.u16 hi0, xr; fma.rn.f16x2 p0, qz6, qz6, c; mul.rn.f16x2 a1, qz5, p1; fma.rn.f16x2 g2, qz2, h0, qz2; prmt.b32 h1, lo1, hi1, 0x5410;\n"
        "mov.b32 {xl, xh}, a1; tanh.approx.f16 xr, xl; cvt.u32.u16 lo1, xr; tanh.approx.f16 xr, xh; cvt.u32.u16 hi1, xr; fma.rn.f16x2 p1, qz7, qz7, c; mul.rn.f16x2 a0, qz6, p0; fma.rn.f16x2 g3, qz3, h1, qz3; prmt.b32 h0, lo0, hi0, 0x5410;\n"
        "B70:\n"
        "wgmma.wait_group.sync.aligned 2;\n"
        "wgmma.fence.sync.aligned;\n"
        "add.s64 dt, w2d, 1024; wgmma.mma_async.sync.aligned.m64n96k16.f16.f16.f16 {o0,o1,o2,o3,o4,o5,o6,o7,o8,o9,o10,o11,o12,o13,o14,o15,o16,o17,o18,o19,o20,o21,o22,o23}, {g0,g1,g2,g3}, dt, pt, 1, 1, 1;\n"
        "add.s64 dt, w1d, 4224; wgmma.mma_async.sync.aligned.m64n64k16.f16.f16.f16 {qz16,qz17,qz18,qz19,qz20,qz21,qz22,qz23,qz24,qz25,qz26,qz27,qz28,qz29,qz30,qz31}, {qa12,qa13,qa14,qa15}, dt, pt, 1, 1, 1;\n"
        "add.s64 dt, w1d, 4352; wgmma.mma_async.sync.aligned.m64n64k16.f16.f16.f16 {qz16,qz17,qz18,qz19,qz20,qz21,qz22,qz23,qz24,qz25,qz26,qz27,qz28,qz29,qz30,qz31}, {qa16,qa17,qa18,qa19}, dt, pt, 1, 1, 1;\n"
        "add.s64 dt, w1d, 4480; wgmma.mma_async.sync.aligned.m64n64k16.f16.f16.f16 {qz16,qz17,qz18,qz19,qz20,qz21,qz22,qz23,qz24,qz25,qz26,qz27,qz28,qz29,qz30,qz31}, {qa20,qa21,qa22,qa23}, dt, pt, 1, 1, 1;\n"
        "wgmma.commit_group.sync.aligned;\n"
        "@pz bra.uni B74;\n"
        "mov.b32 {xl, xh}, a0; tanh.approx.f16 xr, xl; cvt.u32.u16 lo0, xr; tanh.approx.f16 xr, xh; cvt.u32.u16 hi0, xr; fma.rn.f16x2 p0, qz8, qz8, c; mul.rn.f16x2 a1, qz7, p1; fma.rn.f16x2 g4, qz4, h0, qz4; prmt.b32 h1, lo1, hi1, 0x5410;\n"
        "mov.b32 {xl, xh}, a1; tanh.approx.f16 xr, xl; cvt.u32.u16 lo1, xr; tanh.approx.f16 xr, xh; cvt.u32.u16 hi1, xr; fma.rn.f16x2 p1, qz9, qz9, c; mul.rn.f16x2 a0, qz8, p0; fma.rn.f16x2 g5, qz5, h1, qz5; prmt.b32 h0, lo0, hi0, 0x5410;\n"
        "mov.b32 {xl, xh}, a0; tanh.approx.f16 xr, xl; cvt.u32.u16 lo0, xr; tanh.approx.f16 xr, xh; cvt.u32.u16 hi0, xr; fma.rn.f16x2 p0, qz10, qz10, c; mul.rn.f16x2 a1, qz9, p1; fma.rn.f16x2 g6, qz6, h0, qz6; prmt.b32 h1, lo1, hi1, 0x5410;\n"
        "mov.b32 {xl, xh}, a1; tanh.approx.f16 xr, xl; cvt.u32.u16 lo1, xr; tanh.approx.f16 xr, xh; cvt.u32.u16 hi1, xr; fma.rn.f16x2 p1, qz11, qz11, c; mul.rn.f16x2 a0, qz10, p0; fma.rn.f16x2 g7, qz7, h1, qz7; prmt.b32 h0, lo0, hi0, 0x5410;\n"
        "B74:\n"
        "wgmma.wait_group.sync.aligned 2;\n"
        "wgmma.fence.sync.aligned;\n"
        "add.s64 dt, w2d, 1088; wgmma.mma_async.sync.aligned.m64n96k16.f16.f16.f16 {o0,o1,o2,o3,o4,o5,o6,o7,o8,o9,o10,o11,o12,o13,o14,o15,o16,o17,o18,o19,o20,o21,o22,o23}, {g4,g5,g6,g7}, dt, pt, 1, 1, 1;\n"
        "wgmma.commit_group.sync.aligned;\n"
        "@pz bra.uni B78;\n"
        "mov.b32 {xl, xh}, a0; tanh.approx.f16 xr, xl; cvt.u32.u16 lo0, xr; tanh.approx.f16 xr, xh; cvt.u32.u16 hi0, xr; fma.rn.f16x2 p0, qz12, qz12, c; mul.rn.f16x2 a1, qz11, p1; fma.rn.f16x2 g8, qz8, h0, qz8; prmt.b32 h1, lo1, hi1, 0x5410;\n"
        "mov.b32 {xl, xh}, a1; tanh.approx.f16 xr, xl; cvt.u32.u16 lo1, xr; tanh.approx.f16 xr, xh; cvt.u32.u16 hi1, xr; fma.rn.f16x2 p1, qz13, qz13, c; mul.rn.f16x2 a0, qz12, p0; fma.rn.f16x2 g9, qz9, h1, qz9; prmt.b32 h0, lo0, hi0, 0x5410;\n"
        "mov.b32 {xl, xh}, a0; tanh.approx.f16 xr, xl; cvt.u32.u16 lo0, xr; tanh.approx.f16 xr, xh; cvt.u32.u16 hi0, xr; fma.rn.f16x2 p0, qz14, qz14, c; mul.rn.f16x2 a1, qz13, p1; fma.rn.f16x2 g10, qz10, h0, qz10; prmt.b32 h1, lo1, hi1, 0x5410;\n"
        "mov.b32 {xl, xh}, a1; tanh.approx.f16 xr, xl; cvt.u32.u16 lo1, xr; tanh.approx.f16 xr, xh; cvt.u32.u16 hi1, xr; fma.rn.f16x2 p1, qz15, qz15, c; mul.rn.f16x2 a0, qz14, p0; fma.rn.f16x2 g11, qz11, h1, qz11; prmt.b32 h0, lo0, hi0, 0x5410;\n"
        "B78:\n"
        "wgmma.wait_group.sync.aligned 1;\n"
        "wgmma.fence.sync.aligned;\n"
        "add.s64 dt, w2d, 1152; wgmma.mma_async.sync.aligned.m64n96k16.f16.f16.f16 {o0,o1,o2,o3,o4,o5,o6,o7,o8,o9,o10,o11,o12,o13,o14,o15,o16,o17,o18,o19,o20,o21,o22,o23}, {g8,g9,g10,g11}, dt, pt, 1, 1, 1;\n"
        "wgmma.commit_group.sync.aligned;\n"
        "@!pm bra.uni BACKY;\n"
        "add.u32 tt, n, 1; and.b32 tt, tt, 1; mbarrier.try_wait.parity.shared::cta.b64 pw, [ybar], tt;\n"
        "@!pw bra.uni SPINY;\n"
        "BACKY:\n"
        "@pz bra.uni B80;\n"
        "and.b32 ad, %5, 0xffff; xor.b32 ad, ad, 0; add.u32 ad, ad, %4; ldmatrix.sync.aligned.m8n8.x4.shared.b16 {qa0,qa1,qa2,qa3}, [ad];\n"
        "and.b32 ad, %5, 0xffff; xor.b32 ad, ad, 32; add.u32 ad, ad, %4; ldmatrix.sync.aligned.m8n8.x4.shared.b16 {qa4,qa5,qa6,qa7}, [ad];\n"
        "and.b32 ad, %5, 0xffff; xor.b32 ad, ad, 64; add.u32 ad, ad, %4; ldmatrix.sync.aligned.m8n8.x4.shared.b16 {qa8,qa9,qa10,qa11}, [ad];\n"
        "and.b32 ad, %5, 0xffff; xor.b32 ad, ad, 96; add.u32 ad, ad, %4; ldmatrix.sync.aligned.m8n8.x4.shared.b16 {qa12,qa13,qa14,qa15}, [ad];\n"
        "shr.u32 ad, %5, 16; xor.b32 ad, ad, 0; add.u32 ad, ad, %4; ldmatrix.sync.aligned.m8n8.x4.shared.b16 {qa16,qa17,qa18,qa19}, [ad];\n"
        "shr.u32 ad, %5, 16; xor.b32 ad, ad, 32; add.u32 ad, ad, %4; ldmatrix.sync.aligned.m8n8.x4.shared.b16 {qa20,qa21,qa22,qa23}, [ad];\n"
        "mov.b32 {xl, xh}, a0; tanh.approx.f16 xr, xl; cvt.u32.u16 lo0, xr; tanh.approx.f16 xr, xh; cvt.u32.u16 hi0, xr; fma.rn.f16x2 p0, qz16, qz16, c; mul.rn.f16x2 a1, qz15, p1; fma.rn.f16x2 g12, qz12, h0, qz12; prmt.b32 h1, lo1, hi1, 0x5410;\n"
        "mov.b32 {xl, xh}, a1; tanh.approx.f16 xr, xl; cvt.u32.u16 lo1, xr; tanh.approx.f16 xr, xh; cvt.u32.u16 hi1, xr; fma.rn.f16x2 p1, qz17, qz17, c; mul.rn.f16x2 a0, qz16, p0; fma.rn.f16x2 g13, qz13, h1, qz13; prmt.b32 h0, lo0, hi0, 0x5410;\n"
        "B80:\n"
        "fence.proxy.async.shared::cta;\n"
        "add.u32 tt, id, 0;\n"
        "@pk bra.uni XLOAD;\n"
        "bar.arrive tt, 128;\n"
        "XLOADB:\n"
        "@pz bra.uni B82;\n"
        "mov.b32 {xl, xh}, a0; tanh.approx.f16 xr, xl; cvt.u32.u16 lo0, xr; tanh.approx.f16 xr, xh; cvt.u32.u16 hi0, xr; fma.rn.f16x2 p0, qz18, qz18, c; mul.rn.f16x2 a1, qz17, p1; fma.rn.f16x2 g14, qz14, h0, qz14; prmt.b32 h1, lo1, hi1, 0x5410;\n"
        "mov.b32 {xl, xh}, a1; tanh.approx.f16 xr, xl; cvt.u32.u16 lo1, xr; tanh.approx.f16 xr, xh; cvt.u32.u16 hi1, xr; fma.rn.f16x2 p1, qz19, qz19, c; mul.rn.f16x2 a0, qz18, p0; fma.rn.f16x2 g15, qz15, h1, qz15; prmt.b32 h0, lo0, hi0, 0x5410;\n"
        "B82:\n"
        "wgmma.fence.sync.aligned;\n"
        "add.s64 dt, w2d, 1216; wgmma.mma_async.sync.aligned.m64n96k16.f16.f16.f16 {o0,o1,o2,o3,o4,o5,o6,o7,o8,o9,o10,o11,o12,o13,o14,o15,o16,o17,o18,o19,o20,o21,o22,o23}, {g12,g13,g14,g15}, dt, pt, 1, 1, 1;\n"
        "wgmma.commit_group.sync.aligned;\n"
        "@!pm bra.uni SKIP1;\n"
        "wgmma.fence.sync.aligned;\n"
        "add.s64 dt, w1d, 0; wgmma.mma_async.sync.aligned.m64n64k16.f16.f16.f16 {qz0,qz1,qz2,qz3,qz4,qz5,qz6,qz7,qz8,qz9,qz10,qz11,qz12,qz13,qz14,qz15}, {qa0,qa1,qa2,qa3}, dt, pf, 1, 1, 1;\n"
        "add.s64 dt, w1d, 128; wgmma.mma_async.sync.aligned.m64n64k16.f16.f16.f16 {qz0,qz1,qz2,qz3,qz4,qz5,qz6,qz7,qz8,qz9,qz10,qz11,qz12,qz13,qz14,qz15}, {qa4,qa5,qa6,qa7}, dt, pt, 1, 1, 1;\n"
        "add.s64 dt, w1d, 256; wgmma.mma_async.sync.aligned.m64n64k16.f16.f16.f16 {qz0,qz1,qz2,qz3,qz4,qz5,qz6,qz7,qz8,qz9,qz10,qz11,qz12,qz13,qz14,qz15}, {qa8,qa9,qa10,qa11}, dt, pt, 1, 1, 1;\n"
        "SKIP1:\n"
        "@pz bra.uni B86;\n"
        "mov.b32 {xl, xh}, a0; tanh.approx.f16 xr, xl; cvt.u32.u16 lo0, xr; tanh.approx.f16 xr, xh; cvt.u32.u16 hi0, xr; fma.rn.f16x2 p0, qz20, qz20, c; mul.rn.f16x2 a1, qz19, p1; fma.rn.f16x2 g0, qz16, h0, qz16; prmt.b32 h1, lo1, hi1, 0x5410;\n"
        "mov.b32 {xl, xh}, a1; tanh.approx.f16 xr, xl; cvt.u32.u16 lo1, xr; tanh.approx.f16 xr, xh; cvt.u32.u16 hi1, xr; fma.rn.f16x2 p1, qz21, qz21, c; mul.rn.f16x2 a0, qz20, p0; fma.rn.f16x2 g1, qz17, h1, qz17; prmt.b32 h0, lo0, hi0, 0x5410;\n"
        "mov.b32 {xl, xh}, a0; tanh.approx.f16 xr, xl; cvt.u32.u16 lo0, xr; tanh.approx.f16 xr, xh; cvt.u32.u16 hi0, xr; fma.rn.f16x2 p0, qz22, qz22, c; mul.rn.f16x2 a1, qz21, p1; fma.rn.f16x2 g2, qz18, h0, qz18; prmt.b32 h1, lo1, hi1, 0x5410;\n"
        "mov.b32 {xl, xh}, a1; tanh.approx.f16 xr, xl; cvt.u32.u16 lo1, xr; tanh.approx.f16 xr, xh; cvt.u32.u16 hi1, xr; fma.rn.f16x2 p1, qz23, qz23, c; mul.rn.f16x2 a0, qz22, p0; fma.rn.f16x2 g3, qz19, h1, qz19; prmt.b32 h0, lo0, hi0, 0x5410;\n"
        "B86:\n"
        "wgmma.wait_group.sync.aligned 2;\n"
        "wgmma.fence.sync.aligned;\n"
        "add.s64 dt, w2d, 1280; wgmma.mma_async.sync.aligned.m64n96k16.f16.f16.f16 {o0,o1,o2,o3,o4,o5,o6,o7,o8,o9,o10,o11,o12,o13,o14,o15,o16,o17,o18,o19,o20,o21,o22,o23}, {g0,g1,g2,g3}, dt, pt, 1, 1, 1;\n"
        "wgmma.commit_group.sync.aligned;\n"
        "@!pm bra.uni SKIP2;\n"
        "wgmma.fence.sync.aligned;\n"
        "add.s64 dt, w1d, 384; wgmma.mma_async.sync.aligned.m64n64k16.f16.f16.f16 {qz0,qz1,qz2,qz3,qz4,qz5,qz6,qz7,qz8,qz9,qz10,qz11,qz12,qz13,qz14,qz15}, {qa12,qa13,qa14,qa15}, dt, pt, 1, 1, 1;\n"
        "add.s64 dt, w1d, 512; wgmma.mma_async.sync.aligned.m64n64k16.f16.f16.f16 {qz0,qz1,qz2,qz3,qz4,qz5,qz6,qz7,qz8,qz9,qz10,qz11,qz12,qz13,qz14,qz15}, {qa16,qa17,qa18,qa19}, dt, pt, 1, 1, 1;\n"
        "add.s64 dt, w1d, 640; wgmma.mma_async.sync.aligned.m64n64k16.f16.f16.f16 {qz0,qz1,qz2,qz3,qz4,qz5,qz6,qz7,qz8,qz9,qz10,qz11,qz12,qz13,qz14,qz15}, {qa20,qa21,qa22,qa23}, dt, pt, 1, 1, 1;\n"
        "SKIP2:\n"
        "wgmma.fence.sync.aligned;\n"
        "wgmma.commit_group.sync.aligned;\n"
        "@pz bra.uni B90;\n"
        "mov.b32 {xl, xh}, a0; tanh.approx.f16 xr, xl; cvt.u32.u16 lo0, xr; tanh.approx.f16 xr, xh; cvt.u32.u16 hi0, xr; fma.rn.f16x2 p0, qz24, qz24, c; mul.rn.f16x2 a1, qz23, p1; fma.rn.f16x2 g4, qz20, h0, qz20; prmt.b32 h1, lo1, hi1, 0x5410;\n"
        "mov.b32 {xl, xh}, a1; tanh.approx.f16 xr, xl; cvt.u32.u16 lo1, xr; tanh.approx.f16 xr, xh; cvt.u32.u16 hi1, xr; fma.rn.f16x2 p1, qz25, qz25, c; mul.rn.f16x2 a0, qz24, p0; fma.rn.f16x2 g5, qz21, h1, qz21; prmt.b32 h0, lo0, hi0, 0x5410;\n"
        "mov.b32 {xl, xh}, a0; tanh.approx.f16 xr, xl; cvt.u32.u16 lo0, xr; tanh.approx.f16 xr, xh; cvt.u32.u16 hi0, xr; fma.rn.f16x2 p0, qz26, qz26, c; mul.rn.f16x2 a1, qz25, p1; fma.rn.f16x2 g6, qz22, h0, qz22; prmt.b32 h1, lo1, hi1, 0x5410;\n"
        "mov.b32 {xl, xh}, a1; tanh.approx.f16 xr, xl; cvt.u32.u16 lo1, xr; tanh.approx.f16 xr, xh; cvt.u32.u16 hi1, xr; fma.rn.f16x2 p1, qz27, qz27, c; mul.rn.f16x2 a0, qz26, p0; fma.rn.f16x2 g7, qz23, h1, qz23; prmt.b32 h0, lo0, hi0, 0x5410;\n"
        "B90:\n"
        "wgmma.wait_group.sync.aligned 3;\n"
        "wgmma.fence.sync.aligned;\n"
        "add.s64 dt, w2d, 1344; wgmma.mma_async.sync.aligned.m64n96k16.f16.f16.f16 {o0,o1,o2,o3,o4,o5,o6,o7,o8,o9,o10,o11,o12,o13,o14,o15,o16,o17,o18,o19,o20,o21,o22,o23}, {g4,g5,g6,g7}, dt, pt, 1, 1, 1;\n"
        "wgmma.commit_group.sync.aligned;\n"
        "@pz bra.uni B94;\n"
        "mov.b32 {xl, xh}, a0; tanh.approx.f16 xr, xl; cvt.u32.u16 lo0, xr; tanh.approx.f16 xr, xh; cvt.u32.u16 hi0, xr; fma.rn.f16x2 p0, qz28, qz28, c; mul.rn.f16x2 a1, qz27, p1; fma.rn.f16x2 g8, qz24, h0, qz24; prmt.b32 h1, lo1, hi1, 0x5410;\n"
        "mov.b32 {xl, xh}, a1; tanh.approx.f16 xr, xl; cvt.u32.u16 lo1, xr; tanh.approx.f16 xr, xh; cvt.u32.u16 hi1, xr; fma.rn.f16x2 p1, qz29, qz29, c; mul.rn.f16x2 a0, qz28, p0; fma.rn.f16x2 g9, qz25, h1, qz25; prmt.b32 h0, lo0, hi0, 0x5410;\n"
        "mov.b32 {xl, xh}, a0; tanh.approx.f16 xr, xl; cvt.u32.u16 lo0, xr; tanh.approx.f16 xr, xh; cvt.u32.u16 hi0, xr; fma.rn.f16x2 p0, qz30, qz30, c; mul.rn.f16x2 a1, qz29, p1; fma.rn.f16x2 g10, qz26, h0, qz26; prmt.b32 h1, lo1, hi1, 0x5410;\n"
        "mov.b32 {xl, xh}, a1; tanh.approx.f16 xr, xl; cvt.u32.u16 lo1, xr; tanh.approx.f16 xr, xh; cvt.u32.u16 hi1, xr; fma.rn.f16x2 p1, qz31, qz31, c; mul.rn.f16x2 a0, qz30, p0; fma.rn.f16x2 g11, qz27, h1, qz27; prmt.b32 h0, lo0, hi0, 0x5410;\n"
        "B94:\n"
        "wgmma.wait_group.sync.aligned 1;\n"
        "wgmma.fence.sync.aligned;\n"
        "add.s64 dt, w2d, 1408; wgmma.mma_async.sync.aligned.m64n96k16.f16.f16.f16 {o0,o1,o2,o3,o4,o5,o6,o7,o8,o9,o10,o11,o12,o13,o14,o15,o16,o17,o18,o19,o20,o21,o22,o23}, {g8,g9,g10,g11}, dt, pt, 1, 1, 1;\n"
        "wgmma.commit_group.sync.aligned;\n"
        "@pz bra.uni B2;\n"
        "mov.b32 {xl, xh}, a0; tanh.approx.f16 xr, xl; cvt.u32.u16 lo0, xr; tanh.approx.f16 xr, xh; cvt.u32.u16 hi0, xr; fma.rn.f16x2 p0, qz0, qz0, c; mul.rn.f16x2 a1, qz31, p1; fma.rn.f16x2 g12, qz28, h0, qz28; prmt.b32 h1, lo1, hi1, 0x5410;\n"
        "mov.b32 {xl, xh}, a1; tanh.approx.f16 xr, xl; cvt.u32.u16 lo1, xr; tanh.approx.f16 xr, xh; cvt.u32.u16 hi1, xr; fma.rn.f16x2 p1, qz1, qz1, c; mul.rn.f16x2 a0, qz0, p0; fma.rn.f16x2 g13, qz29, h1, qz29; prmt.b32 h0, lo0, hi0, 0x5410;\n"
        "mov.b32 {xl, xh}, a0; tanh.approx.f16 xr, xl; cvt.u32.u16 lo0, xr; tanh.approx.f16 xr, xh; cvt.u32.u16 hi0, xr; fma.rn.f16x2 p0, qz2, qz2, c; mul.rn.f16x2 a1, qz1, p1; fma.rn.f16x2 g14, qz30, h0, qz30; prmt.b32 h1, lo1, hi1, 0x5410;\n"
        "mov.b32 {xl, xh}, a1; tanh.approx.f16 xr, xl; cvt.u32.u16 lo1, xr; tanh.approx.f16 xr, xh; cvt.u32.u16 hi1, xr; fma.rn.f16x2 p1, qz3, qz3, c; mul.rn.f16x2 a0, qz2, p0; fma.rn.f16x2 g15, qz31, h1, qz31; prmt.b32 h0, lo0, hi0, 0x5410;\n"
        "B2:\n"
        "wgmma.fence.sync.aligned;\n"
        "add.s64 dt, w2d, 1472; wgmma.mma_async.sync.aligned.m64n96k16.f16.f16.f16 {o0,o1,o2,o3,o4,o5,o6,o7,o8,o9,o10,o11,o12,o13,o14,o15,o16,o17,o18,o19,o20,o21,o22,o23}, {g12,g13,g14,g15}, dt, pt, 1, 1, 1;\n"
        "wgmma.commit_group.sync.aligned;\n"
        "@pz bra.uni BE;\n"
        "mov.b32 {xl, xh}, a0; tanh.approx.f16 xr, xl; cvt.u32.u16 lo0, xr; tanh.approx.f16 xr, xh; cvt.u32.u16 hi0, xr; fma.rn.f16x2 p0, qz4, qz4, c; mul.rn.f16x2 a1, qz3, p1; fma.rn.f16x2 g0, qz0, h0, qz0; prmt.b32 h1, lo1, hi1, 0x5410;\n"
        "mov.b32 {xl, xh}, a1; tanh.approx.f16 xr, xl; cvt.u32.u16 lo1, xr; tanh.approx.f16 xr, xh; cvt.u32.u16 hi1, xr; fma.rn.f16x2 p1, qz5, qz5, c; mul.rn.f16x2 a0, qz4, p0; fma.rn.f16x2 g1, qz1, h1, qz1; prmt.b32 h0, lo0, hi0, 0x5410;\n"
        "mov.b32 {xl, xh}, a0; tanh.approx.f16 xr, xl; cvt.u32.u16 lo0, xr; tanh.approx.f16 xr, xh; cvt.u32.u16 hi0, xr; fma.rn.f16x2 p0, qz6, qz6, c; mul.rn.f16x2 a1, qz5, p1; fma.rn.f16x2 g2, qz2, h0, qz2; prmt.b32 h1, lo1, hi1, 0x5410;\n"
        "mov.b32 {xl, xh}, a1; tanh.approx.f16 xr, xl; cvt.u32.u16 lo1, xr; tanh.approx.f16 xr, xh; cvt.u32.u16 hi1, xr; fma.rn.f16x2 p1, qz7, qz7, c; mul.rn.f16x2 a0, qz6, p0; fma.rn.f16x2 g3, qz3, h1, qz3; prmt.b32 h0, lo0, hi0, 0x5410;\n"
        "BE:\n"
        "wgmma.wait_group.sync.aligned 0;\n"
        "bra.uni LOOP;\n"
        "STORE:\n"
        "bar.sync tt, 128;\n"
        "setp.lt.s32 pr, n, 0;\n"
        "@pr bra.uni STOREB;\n"
        "cvt.u64.u32 gp, off; add.s64 gp, gp, %11;\n"
        "elect.sync _|pr, 0xffffffff;\n"
        "@pr cp.async.bulk.global.shared::cta.bulk_group [gp], [%4], 12288;\n"
        "@pr cp.async.bulk.commit_group;\n"
        "bra.uni STOREB;\n"
        "YLOAD:\n"
        "@!pm bra.uni YLOADP;\n"
        "cp.async.bulk.wait_group.read 0;\n"
        "sub.u32 ad, off, 393216; cvt.u64.u32 gp, ad; add.s64 gp, gp, %11;\n"
        "elect.sync _|pr, 0xffffffff;\n"
        "@pr mbarrier.arrive.expect_tx.shared::cta.b64 _, [ybar], 12288;\n"
        "@pr cp.async.bulk.shared::cluster.global.mbarrier::complete_tx::bytes [%4], [gp], 12288, [ybar];\n"
        "YLOADP:\n"
        "cvt.u64.u32 gp, off; add.s64 gp, gp, %10;\n"
        "elect.sync _|pr, 0xffffffff;\n"
        "@pr cp.async.bulk.prefetch.L2.global.L2::cache_hint [gp], 12288, pol;\n"
        "bra.uni YLOADB;\n"
        "XLOAD:\n"
        "bar.sync tt, 128;\n"
        "cp.async.bulk.wait_group.read 0;\n"
        "cvt.u64.u32 gp, off; add.s64 gp, gp, %10;\n"
        "elect.sync _|pr, 0xffffffff;\n"
        "@pr mbarrier.arrive.expect_tx.shared::cta.b64 _, [xbar], 12288;\n"
        "@pr cp.async.bulk.shared::cluster.global.mbarrier::complete_tx::bytes.L2::cache_hint [%4], [gp], 12288, [xbar], pol;\n"
        "bra.uni XLOADB;\n"
        "SPINY: mov.u32 cnt, 0;\n"
        "SPINYL:\n"
        "add.u32 tt, n, 1; and.b32 tt, tt, 1; mbarrier.try_wait.parity.shared::cta.b64 pw, [ybar], tt;\n"
        "@pw bra.uni BACKY;\n"
        "add.u32 cnt, cnt, 1; setp.lt.u32 pw, cnt, 0x100000;\n"
        "@pw bra.uni SPINYL;\n"
        "trap;\n"
        "SPINX: mov.u32 cnt, 0;\n"
        "SPINXL:\n"
        "and.b32 tt, n, 1; mbarrier.try_wait.parity.shared::cta.b64 pw, [xbar], tt;\n"
        "@pw bra.uni BACKX;\n"
        "add.u32 cnt, cnt, 1; setp.lt.u32 pw, cnt, 0x100000;\n"
        "@pw bra.uni SPINXL;\n"
        "trap;\n"
        "SPINT: mov.u32 cnt, 0;\n"
        "SPINTL:\n"
        "mad.lo.u32 tt, n, 8, tbar; mbarrier.try_wait.parity.shared::cta.b64 pw, [tt], tpar;\n"
        "@pw bra.uni BACKT;\n"
        "add.u32 cnt, cnt, 1; setp.lt.u32 pw, cnt, 0x100000;\n"
        "@pw bra.uni SPINTL;\n"
        "trap;\n"
        "DONE:\n"
        "wgmma.wait_group.sync.aligned 0;\n"
        "}\n"
        :: "r"(prm.w1desc), "r"(prm.w2desc), "r"(c.wg), "r"(c.off), "r"(c.xs), "r"(c.a_offs), "r"(c.xs_offs), "r"(c.bias_addr),
           "r"(c.out_scale), "r"(c.w), "l"(prm.x), "l"(prm.out)
        : "memory");
}

__device__ __forceinline__ void start_first_tile(const Pass2& c, const Params& prm) {
    if (c.wg == 3) mbar_wait_c<0>(sb + SM_BAR + (BAR_Y2FULL + 3) * 8);
    first_gemm(c.xs, c.a_offs, prm.w1desc);
}

__device__ __forceinline__ float warp_sum(float v) {
#pragma unroll
    for (int s = 16; s >= 1; s >>= 1) v += __shfl_xor_sync(0xffffffffu, v, s);
    return v;
}
__device__ __forceinline__ float pow2f(int e) { return __uint_as_float((uint32_t)(e + 127) << 23); }
__device__ __forceinline__ int exponent_of(float v) { return (int)(__float_as_uint(v) >> 23) - 127; }
__device__ __forceinline__ float lds_bf16(uint32_t addr) {
    uint16_t v; asm volatile("ld.shared.u16 %0, [%1];" : "=h"(v) : "r"(addr) : "memory"); return bf_lo(v);
}

__device__ __forceinline__ void publish_bias(uint32_t c, uint32_t tag) {
    const uint32_t lane = fresh_tid() & 31;
    const uint32_t col = sb + SM_W2 + (c >> 5) * 24576 + lane * 64 + ((((c >> 3) ^ (lane >> 1)) & 3) * 16) + (c & 7) * 2;
    float v = 0.0f;
#pragma unroll
    for (int k = 0; k < EX / 32; k++) v = fmaf(lds_bf16(col + k * 2048), lds_bf16(sb + SM_BETA + lane * 2 + k * 64), v);
    v = warp_sum(v);
    if (lane == 0) asm volatile("st.relaxed.gpu.global.v2.b32 [%0], {%1, %2};" ::"l"(g_bias + c), "f"(v), "r"(tag) : "memory");
}
__device__ __forceinline__ void collect_bias(uint32_t tag) {
    const uint32_t lane = fresh_tid() & 31;
    if (lane < 24) {
        const unsigned long long* src = g_bias + 32 * (lane >> 3) + 8 * (lane & 3) + (lane & 4);
        uint32_t v[4], t[4], spins = 0;
        for (;;) {
#pragma unroll
            for (int k = 0; k < 4; k++)
                asm volatile("ld.relaxed.gpu.global.v2.b32 {%0, %1}, [%2];" : "=r"(v[k]), "=r"(t[k]) : "l"(src + k) : "memory");
            if (t[0] == tag && t[1] == tag && t[2] == tag && t[3] == tag) break;
            if (++spins > (1u << 22)) __trap();
        }
        sts128(sb + SM_BIAS + lane * 16, v[0], v[1], v[2], v[3]);
    }
    __syncwarp();
}
__device__ __forceinline__ float fetch_w2_row(uint32_t (&u)[12][4], uint32_t row, uint32_t sw) {
    uint32_t mx[4] = {};
#pragma unroll
    for (int a = 0; a < 3; a++)
#pragma unroll
        for (int k = 0; k < 4; k++) {
            asm volatile("ld.shared.v4.b32 {%0,%1,%2,%3}, [%4];"
                         : "=r"(u[a * 4][k]), "=r"(u[a * 4 + 1][k]), "=r"(u[a * 4 + 2][k]), "=r"(u[a * 4 + 3][k])
                         : "r"(row + a * 24576 + ((k * 16) ^ sw)) : "memory");
#pragma unroll
            for (int b = 0; b < 4; b++) asm("max.xorsign.abs.bf16x2 %0, %0, %1;" : "+r"(mx[b]) : "r"(u[a * 4 + b][k]));
        }
#pragma unroll
    for (int b = 1; b < 4; b++) asm("max.xorsign.abs.bf16x2 %0, %0, %1;" : "+r"(mx[0]) : "r"(mx[b]));
    return fmaxf(fabsf(bf_lo(mx[0])), fabsf(bf_hi(mx[0])));
}

__device__ __forceinline__ bool grn_stats(float ss, float gm, float bt, float top, float& gx, float& inv, int& eo) {
    const int warp = fresh_warp();
    gx = sqrt_fast(fmaf(ss, INV_2A * INV_2A, 1e-6f));
    const float rt = sqrt_fast(ss + 1.0f) * INV_2A * top;
    const float r[3] = {warp_sum(gx), warp_sum(fmaf(bt, top, rt)), warp_sum(rt * fabsf(gm) * gx)};
    if ((fresh_tid() & 31) == 0 && warp < 12) {
#pragma unroll
        for (int k = 0; k < 3; k++) sts32(sb + SM_SEL + (k * 12 + warp) * 4, __float_as_uint(r[k]));
    }
    MARK(6);
    const bool bad = __syncthreads_or(!(ss >= 16.0f && ss < ACC_LIMIT));
    MARK(7);
    float tot[3];
#pragma unroll
    for (int k = 0; k < 3; k++) {
        uint32_t v[12];
#pragma unroll
        for (int q = 0; q < 3; q++) lds128(v + 4 * q, sb + SM_SEL + k * 48 + q * 16);
        float p[4];
#pragma unroll
        for (int q = 0; q < 4; q++) p[q] = __uint_as_float(v[q]) + __uint_as_float(v[q + 4]) + __uint_as_float(v[q + 8]);
        tot[k] = (p[0] + p[1]) + (p[2] + p[3]);
    }
    inv = __fdividef(1.0f, fmaf(tot[0], 1.0f / EX, 1e-6f));
    eo = min(max(exponent_of(fmaf(tot[2], inv, tot[1])), -90), 126) - 14;
    return bad;
}

__device__ __forceinline__ float exact_sums(const Params& prm, int e) {
    const int lane = fresh_tid() & 31, warp = fresh_warp(), wg = warp >> 2;
    const uint32_t epoch = lds32(sb + SM_RED + (RED_EPOCH + 1) * 4), bar = sb + SM_BAR + BAR_W1 * 8;
    if (wg < 3) {
        uint32_t wa[2][24], d[2][16];
        float acc[2][2] = {};
        const uint32_t yd = prm.ydesc + ((SM_SPARE - SM_Y1) >> 4), wd = prm.w1desc + ((2 * wg * 12288 + 5 * 2048) >> 4);
        load_w1t(wa, wg, warp & 3, lane);
#pragma unroll 1
        for (int n = 0; n < ROWS_PER_CTA; n++) {
            if (warp == 0) {
                expect_tx(bar, TILE_BYTES);
                bulk_load(sb + SM_SPARE, (const char*)prm.out + cta_tile0(fresh_cta()) + n * ROW_BYTES, TILE_BYTES, bar);
            }
            mbar_wait(bar, (n + 1) & 1);
            gemm1_t<0>(d[0], wa[0], yd, wd);
            gemm1_t<1>(d[1], wa[1], yd, wd);
            wg_wait<0>();
            pin(d[0]); pin(d[1]);
            gelu_sumsq_f(d[0], acc[0]);
            gelu_sumsq_f(d[1], acc[1]);
            named_sync(1, 384);
        }
        publish_sums(acc, g_sums[epoch & 1], &g_count[1], wg, warp & 3, lane);
    }
    grid_wait(&g_count[1], (epoch + 1) * NUM_CTAS);
    return __ldcg(g_sums[epoch & 1] + e);
}

__global__ void __launch_bounds__(512, 1) convnext_kernel(const __grid_constant__ Params prm) {
    extern __shared__ __align__(1024) uint8_t smem[];
    if ((uint32_t)__cvta_generic_to_shared(smem) != sb) __trap();
    if (fresh_tid() < 32) TS(0);
    if (fresh_warp() == 0) {
        const RowCopy rc = row_copy(prm);
        if (fresh_tid() == 0) {
            mbar_init(sb + SM_XFULL, 2);
            fence_async_smem();
        }
        __syncwarp();
        issue_row_load(rc, 0, 0);
        if (fresh_tid() == 0) {
#pragma unroll
            for (int k = 0; k < NX; k++) {
                if (k) mbar_init(sb + SM_XFULL + k * SLOT_BYTES, 2);
                mbar_init(sb + SM_Y1FULL + k * SLOT_BYTES, 4);
                mbar_init(sb + SM_Y1EMPTY + k * SLOT_BYTES, 12);
            }
#pragma unroll
            for (int k = 0; k <= BAR_W2; k++) mbar_init(sb + SM_BAR + k * 8, 1);
            mbar_init(sb + SM_BAR + BAR_DUMMY * 8, 16);
#pragma unroll
            for (int k = 0; k < 3; k++) mbar_arrive_if(sb + SM_BAR + (BAR_Y2FULL + k) * 8, true);
            fence_async_smem();
        }
        __syncwarp();
#pragma unroll
        for (int s = 1; s <= NX; s++) {
            if (s == 1 + rc.first) {
                expect_tx(sb + SM_BAR + BAR_W1 * 8, CH * EX * 2);
#pragma unroll
                for (int k = 0; k < 3; k++)
                    bulk_load(sb + SM_W1 + k * 24576, (const char*)prm.w1 + k * 24576, 24576, sb + SM_BAR + BAR_W1 * 8);
            }
            if (s < NX) issue_row_load(rc, s, s);
        }
    }
    Producer pc;
    if (fresh_warp() >= 12) {
        const char* dw = (const char*)prm.dw + (fresh_tid() & 7) * 8;
#pragma unroll
        for (int tap = 0; tap < 9; tap++) {
            asm volatile("ld.global.nc.v4.b32 {%0,%1,%2,%3}, [%4];"
                         : "=r"(pc.w[tap][0]), "=r"(pc.w[tap][1]), "=r"(pc.w[tap][2]), "=r"(pc.w[tap][3])
                         : "l"(dw + (fresh_tid() & 7) * 8 + tap * CH * 2));
            asm volatile("ld.global.nc.v2.b32 {%0,%1}, [%2];"
                         : "=r"(pc.w[tap][4]), "=r"(pc.w[tap][5]) : "l"(dw + tap * CH * 2 + 128));
        }
    }
    if (fresh_tid() - 128 < 40) mbar_init(sb + SM_BAR + BAR_TURN * 8 + (fresh_tid() - 128) * 8, 4);
    if (fresh_tid() >= 96 && fresh_tid() < 128) {
        const uint32_t k = fresh_tid() - 96, n = k & 7, one = (n & 5) == ((k & 8) >> 1) + (k >> 4) ? 0x3f803f80u : 0u;
        sts128(sb + SM_SEL + k * 16, one, one, one, one);
        fence_async_smem();
    }
    if (fresh_tid() >= 32 && fresh_tid() < 32 + NX * 12 && ((blockIdx.x + 1) & 7) < 2) {
        const int k = fresh_tid() - 32;
        sts128(sb + SM_X + (k / 12) * SLOT_BYTES + ((blockIdx.x & 7) == 0 ? 0 : XHALF_B + 33 * 192) + (k % 12) * 16, 0, 0, 0, 0);
    }
    __syncthreads();
    if (fresh_tid() < 32) TS(16);

    if (fresh_warp() >= 12) {
        TS(17);
        asm volatile("setmaxnreg.inc.sync.aligned.u32 %0;" ::"n"(PRODUCER_REGS));
        TS(18);
        const int w = fresh_warp() & 3, lane = fresh_tid() & 31;
        const int j = lane & 7, hb = (lane >> 3) & 1, base = 4 * (2 * w + (lane >> 4));
        pc.lane = lane; pc.warp = w;
        pc.xoff[0] = hb * XHALF_B + base * 192 + j * 16;
        pc.xoff[1] = hb * XHALF_B + base * 192 + 128 + j * 8;
        const int grp = 4 * w + (lane >> 3);
#pragma unroll
        for (int o = 0; o < 2; o++) {
            const int row = (grp & 7) + 8 * (o ^ hb) + 32 * (grp >> 3);
            pc.yoff[0][o] = row * 128 + ((j ^ (row & 7)) * 16);
            pc.yoff[1][o] = 8192 + row * 64 + (((j >> 1) ^ ((row >> 1) & 3)) * 16) + (j & 1) * 8;
        }
        pc.stat = sb + SM_STAT + (8 * w + (lane >> 2)) * 32;
        pc.own = pc.stat + (lane & 3) * 8;
#pragma unroll
        for (int tap = 0; tap < 9; tap++)
#pragma unroll
            for (int u = 0; u < 6; u++) pc.w[tap][u] = bf2_mul(pc.w[tap][u], TAP_SCALE_BF2);
        TS(8);
        produce(pc, prm);
        TS(9);
        TS(22);
        asm volatile("setmaxnreg.dec.sync.aligned.u32 %0;" ::"n"(EVEN_REGS));
        if (fresh_warp() == 12) {
            mbar_wait_c<0>(sb + SM_BAR + BAR_W2 * 8);
            if (fresh_cta() < CH) publish_bias(fresh_cta(), lds32(sb + SM_RED + RED_EPOCH * 4) + 1);
        }
    } else {
        asm volatile("setmaxnreg.dec.sync.aligned.u32 %0;" ::"n"(CONSUMER_REGS));
        if (fresh_tid() - 160 < 2) {
            const uint32_t k = fresh_tid() - 160;
            unsigned int cnt;
            asm volatile("ld.relaxed.gpu.global.u32 %0, [%1];" : "=r"(cnt) : "l"(&g_count[k]) : "memory");
            sts32(sb + SM_RED + (RED_EPOCH + k) * 4, k ? cnt / NUM_CTAS : cnt);
        }
        __syncwarp();
        if (fresh_tid() < 32) TS(19);
        {
            const int tid = fresh_tid(), c0 = tid / 48, ec = tid % 48;
            const uint32_t dst = sb + SM_W1 + (ec >> 3) * 12288 + c0 * 128 + (((ec & 7) ^ (c0 & 7)) * 16);
            uint32_t v[12][4];
            mbar_wait_c<0>(sb + SM_BAR + BAR_W1 * 8);
            if (fresh_tid() < 32) TS(20);
#pragma unroll
            for (int it = 0; it < 12; it++) lds128(v[it], sb + SM_W1 + tid * 16 + it * 6144);
#pragma unroll
            for (int it = 0; it < 12; it++)
#pragma unroll
                for (int k = 0; k < 4; k++) v[it][k] = bf2_to_h2(v[it][k]);
#pragma unroll
            for (int it = 0; it < 12; it++) pin(v[it]);
            named_sync(1, 384);
#pragma unroll
            for (int it = 0; it < 12; it++) sts128(dst + it * 1024, v[it][0], v[it][1], v[it][2], v[it][3]);
            if (fresh_cta() == 0) *acc_word(lds32(sb + SM_RED + RED_EPOCH * 4) + 1, tid) = 0;
            if (fresh_cta() == 1) g_sums[(lds32(sb + SM_RED + (RED_EPOCH + 1) * 4) & 1) ^ 1][tid] = 0.0f;
            fence_async_smem();
            named_sync(1, 384);
            if (fresh_tid() < 32) TS(21);
        }

        const int tid = fresh_tid(), lane = tid & 31, wg = fresh_warp() >> 2, w = fresh_warp() & 3;
        float acc[2][2];
        const int c = 8 * (lane >> 4) + (lane & 7), ck = 2 * w + ((lane >> 3) & 1);
        if (wg == 0) TS(1);
        consume(acc, sb + SM_W1 + 2 * wg * 12288 + c * 128 + ((ck ^ (c & 7)) * 16), prm.ydesc,
                prm.w1desc + (((2 * wg + 1) * 12288 + 5 * 2048) >> 4), wg * SLOT_BYTES, make_duty(prm, wg, w), w, lane);
        publish_fast(acc, lds32(sb + SM_RED + RED_EPOCH * 4), wg, w, lane);
        MARK(0);
        bulk_wait_all();
        if (wg == 0) TS(3);
        asm volatile("setmaxnreg.inc.sync.aligned.u32 %0;" ::"n"(EVEN_REGS));
    }

    {
        asm volatile(".reg .b32 qa<24>, qz<32>;");
        Pass2 c;
        const int tid = fresh_tid(), lane = tid & 31, warp = fresh_warp(), wg = warp >> 2, w = warp & 3, e = min(tid, EX - 1);
        const int arow = 16 * w + (lane & 15);
        c.wg = wg;
        c.off = cta_tile0(fresh_cta()) + (ROWS_PER_CTA - 1 - wg) * ROW_BYTES;
        c.xs = wg == 3 ? sb + SM_BUF3 : sb + SM_Y1 + (wg == 2 ? 2 : 1 - wg) * SLOT_BYTES;
        static_assert((ROWS_PER_CTA - 1) % NX == 1, "slot of the last tile");
        c.a_offs = (arow * 128 + (((lane >> 4) ^ (arow & 7)) * 16)) |
                   (8192 + arow * 64 + (((lane >> 4) ^ ((arow >> 1) & 3)) * 16)) << 16;
        const int g = lane >> 2, px = 33 * (g & 1) + 4 * (g >> 1) + 16 * (w >> 1) + 2 * (w & 1);
        c.xs_offs = (px * 192 + (lane & 3) * 16) | ((px ^ 1) * 192 + (lane & 3) * 16) << 16;
        c.bias_addr = sb + SM_BIAS + (lane & 3) * 16;
        c.w = w;
        const uint32_t epoch = lds32(sb + SM_RED + RED_EPOCH * 4);
        MARK(1);
        if (warp == 6) {
            const uint32_t bar = sb + SM_BAR + (BAR_Y2FULL + 3) * 8;
            expect_tx(bar, TILE_BYTES);
            bulk_load(sb + SM_BUF3, (const char*)prm.out + (c.off - 2 * ROW_BYTES), TILE_BYTES, bar);
        }
        mbar_wait_c<0>(sb + SM_BAR + BAR_W2 * 8);
        const float gm = lds_bf16(sb + SM_GAMMA + e * 2), bt = fabsf(lds_bf16(sb + SM_BETA + e * 2));
        const uint32_t w2row = sb + SM_W2 + e * 64, sw = ((e >> 1) & 3) * 16;
        uint32_t u[12][4];
        float top = 0.0f, ss = 16.0f;
        if (wg < 3) top = fetch_w2_row(u, w2row, sw);
        if (warp == 12) collect_bias(epoch + 1);
        MARK(3);
        start_first_tile(c, prm);
        MARK(4);
        if (wg < 3) ss = collect_fast(acc_word(epoch, e));
        if (warp == 0) TS(4);
        MARK(5);
        float gx, inv;
        int eo;
        if (grn_stats(ss, gm, bt, top, gx, inv, eo) || FORCE_EXACT) {
            wg_wait<0>();
            grn_stats(exact_sums(prm, e), gm, bt, top, gx, inv, eo);
            fetch_w2_row(u, w2row, sw);
            start_first_tile(c, prm);
            __syncthreads();
        }
        MARK(8);
        if (tid == 416 && fresh_cta() == 0) g_count[0] = epoch + 1;
        const float up = pow2f(eo), dn = pow2f(-eo);
        c.out_scale = pack_bf2(up, up);
        if (wg < 3) {
            float sc = fmaf(gm, gx * inv, 1.0f) * INV_2A;
            if (eo > 6) {
                const uint32_t dn2 = pack_bf2(dn, dn);
#pragma unroll
                for (int k = 0; k < 48; k++) u[k >> 2][k & 3] = bf2_mul(u[k >> 2][k & 3], dn2);
            } else {
                sc *= dn;
            }
            const uint32_t s2 = pack_bf2(sc * 0x1p-112f, sc * 0x1p-112f);
#pragma unroll
            for (int k = 0; k < 12; k++) {
                uint32_t v[4];
#pragma unroll
                for (int b = 0; b < 4; b++) {
                    v[b] = bf2_mul(u[k][b], s2);
                    v[b] += (v[b] & 0x7fff7fffu) * 7u;
                }
                sts128(w2row + (k >> 2) * 24576 + (((k & 3) * 16) ^ sw), v[0], v[1], v[2], v[3]);
            }
        } else if (w == 0 && lane < 24) {
            uint32_t b[4];
            lds128(b, sb + SM_BIAS + lane * 16);
            const uint32_t p0 = pack_h2(__uint_as_float(b[0]) * dn, __uint_as_float(b[1]) * dn);
            const uint32_t p1 = pack_h2(__uint_as_float(b[2]) * dn, __uint_as_float(b[3]) * dn);
            sts128(sb + SM_BIAS + lane * 16, p0, p0, p1, p1);
        }
        MARK(9);
        fence_async_smem();
        __syncthreads();
        MARK(10);

        if (wg == 0) TS(5);
        pass2_tiles(c, prm);
        bulk_wait_all();
        MARK(13);
    }
}

}

extern "C" void kernel_launch(void* const* d_in, const int* in_sizes, int n_in, void* d_out, int out_size) {
    (void)in_sizes; (void)n_in; (void)out_size;
    typedef CUresult (*EncodeFn)(CUtensorMap*, CUtensorMapDataType, cuuint32_t, void*, const cuuint64_t*, const cuuint64_t*,
                                 const cuuint32_t*, const cuuint32_t*, CUtensorMapInterleave, CUtensorMapSwizzle,
                                 CUtensorMapL2promotion, CUtensorMapFloatOOBfill);
    void* fn = nullptr;
    cudaDriverEntryPointQueryResult status;
    cudaGetDriverEntryPoint("cuTensorMapEncodeTiled", &fn, cudaEnableDefault, &status);
    const EncodeFn encode = (EncodeFn)fn;
    const cuuint32_t ones[2] = {1, 1};

    Params p;
    {
        const cuuint64_t dims[2] = {CH, EX}, strides[1] = {CH * 2};
        const cuuint32_t box[2] = {32, 192};
        encode(&p.w2_map, CU_TENSOR_MAP_DATA_TYPE_BFLOAT16, 2, d_in[3], dims, strides, box, ones,
               CU_TENSOR_MAP_INTERLEAVE_NONE, CU_TENSOR_MAP_SWIZZLE_64B, CU_TENSOR_MAP_L2_PROMOTION_NONE,
               CU_TENSOR_MAP_FLOAT_OOB_FILL_NONE);
    }
    p.x = (const __nv_bfloat16*)d_in[0];
    p.dw = (const __nv_bfloat16*)d_in[1];
    p.w1 = (const __nv_bfloat16*)d_in[2];
    p.gamma = (const __nv_bfloat16*)d_in[4];
    p.beta = (const __nv_bfloat16*)d_in[5];
    p.out = (__nv_bfloat16*)d_out;
    p.w1desc = desc_lo(sb + SM_W1, 12288);
    p.w2desc = desc_lo(sb + SM_W2, 24576);
    p.ydesc = desc_lo(sb + SM_Y1, 16);
    for (int k = 0; k < 3; k++) p.sel[k] = (8ull << 32) | desc_lo(sb + SM_SEL + k * 128, k == 2 ? 128 : 0);
    constexpr int smem_bytes = SM_TOTAL;
    cudaFuncSetAttribute(convnext_kernel, cudaFuncAttributeMaxDynamicSharedMemorySize, smem_bytes);
    convnext_kernel<<<NUM_CTAS, 512, smem_bytes>>>(p);
}
```

```cpp
#include <cuda.h>
#include <cuda_runtime.h>
#include <cuda_bf16.h>
#include <stdint.h>

namespace {

constexpr int IMG_W = 512, CH = 96, EX = 384;
constexpr int TILE_PX = 64;
constexpr int ROWS_PER_CTA = 32;
constexpr int NUM_CTAS = 128;
constexpr int STEPS = ROWS_PER_CTA + 2;
constexpr int ROW_BYTES = IMG_W * CH * 2;

#define FORCE_EXACT 0
#define HOLD 1
#define ROT 0
#define PRE 9
#define W1POS 3
#define PREGS 200
#define CREGS 104
constexpr int PRODUCER_REGS = PREGS, CONSUMER_REGS = CREGS, EVEN_REGS = 128;

constexpr int XHALF_BYTES = 34 * 192;
constexpr int XHALF_B = XHALF_BYTES + 64;
constexpr int XROW_BYTES = XHALF_B + XHALF_BYTES + 64;
constexpr int L2_AHEAD = 2;
constexpr int NX = 3;
constexpr int TILE_BYTES = TILE_PX * 192;
constexpr int NY1 = 3;

constexpr uint32_t sb = 1024;
constexpr int SM_W1 = 0;
constexpr int SM_W2 = 73728;
constexpr int SM_RING = 147456;
constexpr int SLOT_BYTES = 26624;
constexpr int SM_Y1 = SM_RING;
constexpr int SM_X = SM_Y1 + TILE_BYTES;
constexpr int SM_STAT = SM_X + XROW_BYTES;
constexpr int SM_XFULL = SM_STAT + TILE_PX * 16, SM_Y1FULL = SM_XFULL + 8, SM_Y1EMPTY = SM_XFULL + 16;
constexpr int SM_BUF3 = SM_X + SLOT_BYTES, SM_SPARE = SM_X;
constexpr int SM_SEL = SM_RING + NX * SLOT_BYTES;
constexpr int SM_BIAS = SM_SEL + 512;
constexpr int SM_GAMMA = SM_BIAS + 384;
constexpr int SM_BETA = SM_GAMMA + EX * 2;
constexpr int SM_RED = SM_BETA + EX * 2;
constexpr int SM_BAR = SM_RED + 16;
constexpr int BAR_Y2FULL = 0, BAR_XSFULL = 4, BAR_W1 = 8, BAR_W2 = 9, BAR_DUMMY = 10, BAR_TURN = 11, BAR_COUNT = 51;
constexpr int SM_TOTAL = SM_BAR + BAR_COUNT * 8;
static_assert(SM_Y1EMPTY + 8 <= SM_RING + SLOT_BYTES && XROW_BYTES >= TILE_BYTES && SM_X % 1024 == 0, "ring layout");
static_assert(SM_TOTAL <= 232448, "smem budget");
static_assert(SM_STAT % 128 == 0 && SM_BIAS % 16 == 0 && SM_BAR % 8 == 0 && SLOT_BYTES % 1024 == 0, "alignment");

static_assert(NX == NY1, "both rings are walked with one index");
constexpr int RED_EPOCH = 0;

constexpr float GELU_A = 0.32920349f;
constexpr uint32_t GELU_C_H2 = 0x40D940D9u;
constexpr float INV_2A = 1.0f / (2.0f * GELU_A);

constexpr uint32_t TAP_SCALE_BF2 = 0x2B802B80u;
constexpr float LN_EPS_SCALED = 1e-5f * 0x1p-80f;
constexpr float RSTD_SCALE = GELU_A * 0x1p-112f;

struct Scratch {
    unsigned long long acc[2][EX / 4 * 32];
    unsigned long long bias[CH];
    float sums[2][EX];
    uint4 zero_row[66 * 192 / 16];
    unsigned int count[2];
};
__device__ __align__(256) Scratch g_scratch;
constexpr float ACC_LIMIT = 0x1p30f;

#define TS(k)
#define ASM_TS
#define MARK(k)
#define SMARK(k)
#define ASM_MARK
#define ASM_SMARK
#define ASM_TRC(it, k)

#define SPLITS 2
#define FENCE_HEAD(k) "{\n.reg .pred p;\n.reg .u32 t;\nsetp.ne.u32 p, %" #k ", 0;\n@p bra.uni GO;\nSTAY:\nld.volatile.shared.u32 t, [%" #k "];\n"
#define FENCE_TAIL "setp.ne.u32 p, t, 0;\n@p bra.uni STAY;\nGO:\n}\n"
template <int N> __device__ __forceinline__ void sched_fence(uint32_t* r, uint32_t key);
template <> __device__ __forceinline__ void sched_fence<2>(uint32_t* r, uint32_t key) {
    asm volatile(FENCE_HEAD(2) "mov.b32 %0, t;\nmov.b32 %1, t;\n" FENCE_TAIL
                 : "+r"(r[0]), "+r"(r[1]) : "r"(key) : "memory");
}
template <> __device__ __forceinline__ void sched_fence<4>(uint32_t* r, uint32_t key) {
    asm volatile(FENCE_HEAD(4) "mov.b32 %0, t;\nmov.b32 %1, t;\nmov.b32 %2, t;\nmov.b32 %3, t;\n" FENCE_TAIL
                 : "+r"(r[0]), "+r"(r[1]), "+r"(r[2]), "+r"(r[3]) : "r"(key) : "memory");
}
template <> __device__ __forceinline__ void sched_fence<6>(uint32_t* r, uint32_t key) {
    asm volatile(FENCE_HEAD(6) "mov.b32 %0, t;\nmov.b32 %1, t;\nmov.b32 %2, t;\nmov.b32 %3, t;\nmov.b32 %4, t;\nmov.b32 %5, t;\n" FENCE_TAIL
                 : "+r"(r[0]), "+r"(r[1]), "+r"(r[2]), "+r"(r[3]), "+r"(r[4]), "+r"(r[5]) : "r"(key) : "memory");
}
template <> __device__ __forceinline__ void sched_fence<8>(uint32_t* r, uint32_t key) {
    asm volatile(FENCE_HEAD(8) "mov.b32 %0, t;\nmov.b32 %1, t;\nmov.b32 %2, t;\nmov.b32 %3, t;\nmov.b32 %4, t;\nmov.b32 %5, t;\nmov.b32 %6, t;\nmov.b32 %7, t;\n" FENCE_TAIL
                 : "+r"(r[0]), "+r"(r[1]), "+r"(r[2]), "+r"(r[3]), "+r"(r[4]), "+r"(r[5]), "+r"(r[6]), "+r"(r[7]) : "r"(key) : "memory");
}
template <> __device__ __forceinline__ void sched_fence<10>(uint32_t* r, uint32_t key) {
    asm volatile(FENCE_HEAD(10) "mov.b32 %0, t;\nmov.b32 %1, t;\nmov.b32 %2, t;\nmov.b32 %3, t;\nmov.b32 %4, t;\nmov.b32 %5, t;\nmov.b32 %6, t;\nmov.b32 %7, t;\nmov.b32 %8, t;\nmov.b32 %9, t;\n" FENCE_TAIL
                 : "+r"(r[0]), "+r"(r[1]), "+r"(r[2]), "+r"(r[3]), "+r"(r[4]), "+r"(r[5]), "+r"(r[6]), "+r"(r[7]), "+r"(r[8]), "+r"(r[9]) : "r"(key) : "memory");
}
template <> __device__ __forceinline__ void sched_fence<12>(uint32_t* r, uint32_t key) {
    asm volatile(FENCE_HEAD(12) "mov.b32 %0, t;\nmov.b32 %1, t;\nmov.b32 %2, t;\nmov.b32 %3, t;\nmov.b32 %4, t;\nmov.b32 %5, t;\nmov.b32 %6, t;\nmov.b32 %7, t;\nmov.b32 %8, t;\nmov.b32 %9, t;\nmov.b32 %10, t;\nmov.b32 %11, t;\n" FENCE_TAIL
                 : "+r"(r[0]), "+r"(r[1]), "+r"(r[2]), "+r"(r[3]), "+r"(r[4]), "+r"(r[5]), "+r"(r[6]), "+r"(r[7]), "+r"(r[8]), "+r"(r[9]), "+r"(r[10]), "+r"(r[11]) : "r"(key) : "memory");
}
template <> __device__ __forceinline__ void sched_fence<24>(uint32_t* r, uint32_t key) {
    asm volatile(FENCE_HEAD(24) "mov.b32 %0, t;\nmov.b32 %1, t;\nmov.b32 %2, t;\nmov.b32 %3, t;\nmov.b32 %4, t;\nmov.b32 %5, t;\nmov.b32 %6, t;\nmov.b32 %7, t;\nmov.b32 %8, t;\nmov.b32 %9, t;\nmov.b32 %10, t;\nmov.b32 %11, t;\nmov.b32 %12, t;\nmov.b32 %13, t;\nmov.b32 %14, t;\nmov.b32 %15, t;\nmov.b32 %16, t;\nmov.b32 %17, t;\nmov.b32 %18, t;\nmov.b32 %19, t;\nmov.b32 %20, t;\nmov.b32 %21, t;\nmov.b32 %22, t;\nmov.b32 %23, t;\n" FENCE_TAIL
                 : "+r"(r[0]), "+r"(r[1]), "+r"(r[2]), "+r"(r[3]), "+r"(r[4]), "+r"(r[5]), "+r"(r[6]), "+r"(r[7]), "+r"(r[8]), "+r"(r[9]), "+r"(r[10]), "+r"(r[11]), "+r"(r[12]), "+r"(r[13]), "+r"(r[14]), "+r"(r[15]), "+r"(r[16]), "+r"(r[17]), "+r"(r[18]), "+r"(r[19]), "+r"(r[20]), "+r"(r[21]), "+r"(r[22]), "+r"(r[23]) : "r"(key) : "memory");
}
#define SPLIT(k, r) do { if ((SPLITS >> (k)) & 1) sched_fence<sizeof(r) / 4>(r, prm.ydesc); } while (0)

__device__ __forceinline__ void mbar_init(uint32_t bar, uint32_t count) {
    asm volatile("mbarrier.init.shared::cta.b64 [%0], %1;" ::"r"(bar), "r"(count) : "memory");
}
__device__ __forceinline__ void mbar_arrive_if(uint32_t bar, bool pred) {
    asm volatile("{\n.reg .pred p;\nsetp.ne.u32 p, %1, 0;\n@p mbarrier.arrive.shared::cta.b64 _, [%0];\n}\n"
                 ::"r"(bar), "r"((uint32_t)pred) : "memory");
}
__device__ __forceinline__ void mbar_wait(uint32_t bar, uint32_t parity) {
    asm volatile(
        "{\n.reg .pred p;\n.reg .u32 n;\n"
        "mbarrier.try_wait.parity.shared::cta.b64 p, [%0], %1;\n"
        "@p bra.uni WAIT_DONE;\n"
        "mov.u32 n, 0;\n"
        "WAIT_LOOP:\n"
        "mbarrier.try_wait.parity.shared::cta.b64 p, [%0], %1;\n"
        "@p bra.uni WAIT_DONE;\n"
        "mbarrier.try_wait.parity.shared::cta.b64 p, [%0], %1;\n"
        "@p bra.uni WAIT_DONE;\n"
        "mbarrier.try_wait.parity.shared::cta.b64 p, [%0], %1;\n"
        "@p bra.uni WAIT_DONE;\n"
        "add.u32 n, n, 1;\nsetp.lt.u32 p, n, 0x40000;\n"
        "@p bra.uni WAIT_LOOP;\n"
        "trap;\n"
        "WAIT_DONE:\n}\n"
        ::"r"(bar), "r"(parity) : "memory");
}
template <int PARITY> __device__ __forceinline__ void mbar_wait_c(uint32_t bar) {
    asm volatile(
        "{\n.reg .pred p;\n.reg .u32 n;\n"
        "mbarrier.try_wait.parity.shared::cta.b64 p, [%0], %1;\n"
        "@p bra.uni WAIT_DONE;\n"
        "mov.u32 n, 0;\n"
        "WAIT_LOOP:\n"
        "mbarrier.try_wait.parity.shared::cta.b64 p, [%0], %1;\n"
        "@p bra.uni WAIT_DONE;\n"
        "mbarrier.try_wait.parity.shared::cta.b64 p, [%0], %1;\n"
        "@p bra.uni WAIT_DONE;\n"
        "mbarrier.try_wait.parity.shared::cta.b64 p, [%0], %1;\n"
        "@p bra.uni WAIT_DONE;\n"
        "add.u32 n, n, 1;\nsetp.lt.u32 p, n, 0x40000;\n"
        "@p bra.uni WAIT_LOOP;\n"
        "trap;\n"
        "WAIT_DONE:\n}\n"
        ::"r"(bar), "n"(PARITY) : "memory");
}
__device__ __forceinline__ bool mbar_probe(uint32_t bar, uint32_t parity) {
    uint32_t ok;
    asm volatile("{\n.reg .pred p;\nmbarrier.test_wait.parity.shared::cta.b64 p, [%1], %2;\nselp.u32 %0, 1, 0, p;\n}\n"
                 : "=r"(ok) : "r"(bar), "r"(parity) : "memory");
    return ok;
}
__device__ __forceinline__ void mbar_wait2(uint32_t bar0, uint32_t parity0, uint32_t bar1, uint32_t parity1) {
    asm volatile(
        "{\n.reg .pred p, q;\n.reg .u32 n;\n"
        "mbarrier.try_wait.parity.shared::cta.b64 p, [%0], %1;\n"
        "mbarrier.try_wait.parity.shared::cta.b64 q, [%2], %3;\n"
        "and.pred p, p, q;\n"
        "@p bra.uni WAIT_DONE;\n"
        "mov.u32 n, 0;\n"
        "WAIT_LOOP:\n"
        "mbarrier.try_wait.parity.shared::cta.b64 p, [%0], %1;\n"
        "mbarrier.try_wait.parity.shared::cta.b64 q, [%2], %3;\n"
        "and.pred p, p, q;\n"
        "@p bra.uni WAIT_DONE;\n"
        "add.u32 n, n, 1;\nsetp.lt.u32 p, n, 0x80000;\n"
        "@p bra.uni WAIT_LOOP;\n"
        "trap;\n"
        "WAIT_DONE:\n}\n"
        ::"r"(bar0), "r"(parity0), "r"(bar1), "r"(parity1) : "memory");
}
#define ELECTED(body) "{\n.reg .pred p;\nelect.sync _|p, 0xffffffff;\n" body "}\n"
__device__ __forceinline__ void expect_tx(uint32_t bar, uint32_t bytes) {
    asm volatile(ELECTED("@p mbarrier.arrive.expect_tx.shared::cta.b64 _, [%0], %1;\n") ::"r"(bar), "r"(bytes) : "memory");
}
__device__ __forceinline__ void arrive_n(uint32_t bar, uint32_t count) {
    asm volatile(ELECTED("@p mbarrier.arrive.shared::cta.b64 _, [%0], %1;\n") ::"r"(bar), "r"(count) : "memory");
}
__device__ __forceinline__ void bulk_load(uint32_t dst, const void* src, uint32_t bytes, uint32_t bar) {
    asm volatile(ELECTED("@p cp.async.bulk.shared::cluster.global.mbarrier::complete_tx::bytes [%0], [%1], %2, [%3];\n")
                 ::"r"(dst), "l"(src), "r"(bytes), "r"(bar) : "memory");
}
__device__ __forceinline__ void bulk_store(void* dst, uint32_t src, uint32_t bytes) {
    asm volatile(ELECTED("@p cp.async.bulk.global.shared::cta.bulk_group [%0], [%1], %2;\n@p cp.async.bulk.commit_group;\n")
                 ::"l"(dst), "r"(src), "r"(bytes) : "memory");
}
__device__ __forceinline__ void bulk_prefetch(const void* src, uint32_t bytes) {
    asm volatile(ELECTED("@p cp.async.bulk.prefetch.L2.global [%0], %1;\n") ::"l"(src), "r"(bytes) : "memory");
}
__device__ __forceinline__ void tma_load_2d(uint32_t dst, const CUtensorMap* map, int c0, int c1, uint32_t bar) {
    asm volatile(ELECTED("@p cp.async.bulk.tensor.2d.shared::cluster.global.mbarrier::complete_tx::bytes [%0], [%1, {%2, %3}], [%4];\n")
                 ::"r"(dst), "l"(map), "r"(c0), "r"(c1), "r"(bar) : "memory");
}
template <int N> __device__ __forceinline__ void bulk_wait_read() {
    asm volatile("cp.async.bulk.wait_group.read %0;" ::"n"(N) : "memory");
}
__device__ __forceinline__ void bulk_wait_all() { asm volatile("cp.async.bulk.wait_group 0;" ::: "memory"); }
__device__ __forceinline__ void fence_async_smem() { asm volatile("fence.proxy.async.shared::cta;" ::: "memory"); }
__device__ __forceinline__ void named_sync(int id, int n) { asm volatile("bar.sync %0, %1;" ::"r"(id), "r"(n) : "memory"); }

__device__ __forceinline__ void lds64(uint32_t (&v)[2], uint32_t addr) {
    asm volatile("ld.shared.v2.b32 {%0,%1}, [%2];" : "=r"(v[0]), "=r"(v[1]) : "r"(addr));
}
__device__ __forceinline__ void sts64(uint32_t addr, uint32_t a, uint32_t b) {
    asm volatile("st.shared.v2.b32 [%0], {%1,%2};" ::"r"(addr), "r"(a), "r"(b) : "memory");
}
__device__ __forceinline__ void sts128(uint32_t addr, uint32_t a, uint32_t b, uint32_t c, uint32_t d) {
    asm volatile("st.shared.v4.b32 [%0], {%1,%2,%3,%4};" ::"r"(addr), "r"(a), "r"(b), "r"(c), "r"(d) : "memory");
}
__device__ __forceinline__ void ldsm4(uint32_t* r, uint32_t addr) {
    asm volatile("ldmatrix.sync.aligned.m8n8.x4.shared.b16 {%0,%1,%2,%3}, [%4];"
                 : "=r"(r[0]), "=r"(r[1]), "=r"(r[2]), "=r"(r[3]) : "r"(addr) : "memory");
}
__device__ __forceinline__ void ldsm4_t(uint32_t* r, uint32_t addr) {
    asm volatile("ldmatrix.sync.aligned.m8n8.x4.trans.shared.b16 {%0,%1,%2,%3}, [%4];"
                 : "=r"(r[0]), "=r"(r[1]), "=r"(r[2]), "=r"(r[3]) : "r"(addr) : "memory");
}
__device__ __forceinline__ void lds128(uint32_t* v, uint32_t addr) {
    asm volatile("ld.shared.v4.b32 {%0,%1,%2,%3}, [%4];"
                 : "=r"(v[0]), "=r"(v[1]), "=r"(v[2]), "=r"(v[3]) : "r"(addr) : "memory");
}
__device__ __forceinline__ uint32_t lds32(uint32_t addr) {
    uint32_t v; asm volatile("ld.shared.b32 %0, [%1];" : "=r"(v) : "r"(addr) : "memory"); return v;
}
__device__ __forceinline__ void sts32(uint32_t addr, uint32_t v) {
    asm volatile("st.shared.b32 [%0], %1;" ::"r"(addr), "r"(v) : "memory");
}

__device__ __forceinline__ uint32_t bf2_fma(uint32_t a, uint32_t b, uint32_t c) {
    uint32_t d; asm("fma.rn.bf16x2 %0, %1, %2, %3;" : "=r"(d) : "r"(a), "r"(b), "r"(c)); return d;
}
__device__ __forceinline__ uint32_t bf2_mul(uint32_t a, uint32_t b) {
    uint32_t d; asm("mul.rn.bf16x2 %0, %1, %2;" : "=r"(d) : "r"(a), "r"(b)); return d;
}
__device__ __forceinline__ uint32_t bf2_add(uint32_t a, uint32_t b) {
    uint32_t d; asm("add.rn.bf16x2 %0, %1, %2;" : "=r"(d) : "r"(a), "r"(b)); return d;
}
__device__ __forceinline__ uint32_t h2_fma(uint32_t a, uint32_t b, uint32_t c) {
    uint32_t d; asm("fma.rn.f16x2 %0, %1, %2, %3;" : "=r"(d) : "r"(a), "r"(b), "r"(c)); return d;
}
__device__ __forceinline__ uint32_t h2_mul(uint32_t a, uint32_t b) {
    uint32_t d; asm("mul.rn.f16x2 %0, %1, %2;" : "=r"(d) : "r"(a), "r"(b)); return d;
}
__device__ __forceinline__ uint32_t h2_tanh(uint32_t a) {
    uint32_t d; asm("tanh.approx.f16x2 %0, %1;" : "=r"(d) : "r"(a)); return d;
}
__device__ __forceinline__ float bf_lo(uint32_t v) { return __uint_as_float(v << 16); }
__device__ __forceinline__ float bf_hi(uint32_t v) { return __uint_as_float(v & 0xffff0000u); }
__device__ __forceinline__ uint32_t pack_h2(float lo, float hi) {
    uint32_t d; asm("cvt.rn.f16x2.f32 %0, %1, %2;" : "=r"(d) : "f"(hi), "f"(lo)); return d;
}
__device__ __forceinline__ uint32_t pack_bf2(float lo, float hi) {
    uint32_t d; asm("cvt.rn.bf16x2.f32 %0, %1, %2;" : "=r"(d) : "f"(hi), "f"(lo)); return d;
}
__device__ __forceinline__ void h2_unpack(uint32_t v, float& lo, float& hi) {
    asm("{\n.reg .b16 l, h;\nmov.b32 {l, h}, %2;\ncvt.f32.f16 %0, l;\ncvt.f32.f16 %1, h;\n}\n" : "=f"(lo), "=f"(hi) : "r"(v));
}
__device__ __forceinline__ uint32_t bf2_to_h2(uint32_t v) { return pack_h2(bf_lo(v), bf_hi(v)); }

__device__ __forceinline__ uint32_t gelu2(uint32_t z) {
    uint32_t p = h2_fma(z, z, GELU_C_H2);
    uint32_t t = h2_tanh(h2_mul(z, p));
    return h2_fma(z, t, z);
}

__device__ __forceinline__ void wg_fence() { asm volatile("wgmma.fence.sync.aligned;" ::: "memory"); }
__device__ __forceinline__ void wg_commit() { asm volatile("wgmma.commit_group.sync.aligned;" ::: "memory"); }
template <int N> __device__ __forceinline__ void wg_wait() {
    asm volatile("wgmma.wait_group.sync.aligned %0;" ::"n"(N) : "memory");
}
template <int N> __device__ __forceinline__ void pin(uint32_t (&r)[N]) {
#pragma unroll
    for (int i = 0; i < N; i++) asm volatile("" : "+r"(r[i])::"memory");
}
constexpr uint32_t desc_lo(uint32_t addr, uint32_t lbo) { return ((addr & 0x3FFFF) >> 4) | ((lbo >> 4) << 16); }
template <uint32_t SBO, uint32_t SWZ> __device__ __forceinline__ uint64_t desc(uint32_t lo, uint32_t bytes) {
    return (((uint64_t)((SBO >> 4) | (SWZ << 30)) << 32) | lo) + (bytes >> 4);
}
__device__ __forceinline__ uint32_t fresh_tid() {
    uint32_t v; asm volatile("mov.u32 %0, %%tid.x;" : "=r"(v));
    return v;
}
template <uint32_t V> __device__ __forceinline__ uint32_t loop_init() {
    uint32_t v; asm volatile("mov.u32 %0, %1;" : "=r"(v) : "n"(V)); return v;
}
__device__ __forceinline__ int fresh_warp() {
    int v; asm volatile("shfl.sync.idx.b32 %0, %1, 0, 0x1f, 0xffffffff;" : "=r"(v) : "r"(fresh_tid() >> 5)); return v;
}
__device__ __forceinline__ uint32_t fresh_cta() {
    uint32_t v; asm volatile("mov.u32 %0, %%ctaid.x;" : "=r"(v)); return v;
}
__device__ __forceinline__ float rsqrt_fast(float v) { float r; asm("rsqrt.approx.ftz.f32 %0, %1;" : "=f"(r) : "f"(v)); return r; }
__device__ __forceinline__ float sqrt_fast(float v) { float r; asm("sqrt.approx.f32 %0, %1;" : "=f"(r) : "f"(v)); return r; }

template <int TB>
__device__ __forceinline__ void wgmma_n64_h_set(uint32_t (&d)[16], const uint32_t* a, uint64_t desc) {
    asm volatile(
        "{\n.reg .pred p;\nsetp.ne.b32 p, 0, 0;\n"
        "wgmma.mma_async.sync.aligned.m64n64k16.f16.f16.f16 "
        "{%0,%1,%2,%3,%4,%5,%6,%7,%8,%9,%10,%11,%12,%13,%14,%15}, {%16,%17,%18,%19}, %20, p, 1, 1, %21;\n}\n"
        : "=r"(d[0]), "=r"(d[1]), "=r"(d[2]), "=r"(d[3]), "=r"(d[4]), "=r"(d[5]), "=r"(d[6]), "=r"(d[7]), "=r"(d[8]), "=r"(d[9]), "=r"(d[10]), "=r"(d[11]), "=r"(d[12]), "=r"(d[13]), "=r"(d[14]), "=r"(d[15])
        : "r"(a[0]), "r"(a[1]), "r"(a[2]), "r"(a[3]), "l"(desc), "n"(TB));
}
template <int TB>
__device__ __forceinline__ void wgmma_n64_h_acc(uint32_t (&d)[16], const uint32_t* a, uint64_t desc) {
    asm volatile(
        "{\n.reg .pred p;\nsetp.ne.b32 p, 1, 0;\n"
        "wgmma.mma_async.sync.aligned.m64n64k16.f16.f16.f16 "
        "{%0,%1,%2,%3,%4,%5,%6,%7,%8,%9,%10,%11,%12,%13,%14,%15}, {%16,%17,%18,%19}, %20, p, 1, 1, %21;\n}\n"
        : "+r"(d[0]), "+r"(d[1]), "+r"(d[2]), "+r"(d[3]), "+r"(d[4]), "+r"(d[5]), "+r"(d[6]), "+r"(d[7]), "+r"(d[8]), "+r"(d[9]), "+r"(d[10]), "+r"(d[11]), "+r"(d[12]), "+r"(d[13]), "+r"(d[14]), "+r"(d[15])
        : "r"(a[0]), "r"(a[1]), "r"(a[2]), "r"(a[3]), "l"(desc), "n"(TB));
}
__device__ __forceinline__ void wgmma_n64_h_acc_ss(uint32_t (&d)[16], uint64_t adesc, uint64_t desc) {
    asm volatile(
        "{\n.reg .pred p;\nsetp.ne.b32 p, 1, 0;\n"
        "wgmma.mma_async.sync.aligned.m64n64k16.f16.f16.f16 "
        "{%0,%1,%2,%3,%4,%5,%6,%7,%8,%9,%10,%11,%12,%13,%14,%15}, %16, %17, p, 1, 1, 1, 0;\n}\n"
        : "+r"(d[0]), "+r"(d[1]), "+r"(d[2]), "+r"(d[3]), "+r"(d[4]), "+r"(d[5]), "+r"(d[6]), "+r"(d[7]), "+r"(d[8]), "+r"(d[9]), "+r"(d[10]), "+r"(d[11]), "+r"(d[12]), "+r"(d[13]), "+r"(d[14]), "+r"(d[15])
        : "l"(adesc), "l"(desc));
}
__device__ __forceinline__ void wgmma_n96_h_acc(uint32_t (&d)[24], const uint32_t* a, uint64_t desc) {
    asm volatile(
        "{\n.reg .pred p;\nsetp.ne.b32 p, 1, 0;\n"
        "wgmma.mma_async.sync.aligned.m64n96k16.f16.f16.f16 "
        "{%0,%1,%2,%3,%4,%5,%6,%7,%8,%9,%10,%11,%12,%13,%14,%15,%16,%17,%18,%19,%20,%21,%22,%23}, {%24,%25,%26,%27}, %28, p, 1, 1, 1;\n}\n"
        : "+r"(d[0]), "+r"(d[1]), "+r"(d[2]), "+r"(d[3]), "+r"(d[4]), "+r"(d[5]), "+r"(d[6]), "+r"(d[7]), "+r"(d[8]), "+r"(d[9]), "+r"(d[10]), "+r"(d[11]), "+r"(d[12]), "+r"(d[13]), "+r"(d[14]), "+r"(d[15]), "+r"(d[16]), "+r"(d[17]), "+r"(d[18]), "+r"(d[19]), "+r"(d[20]), "+r"(d[21]), "+r"(d[22]), "+r"(d[23])
        : "r"(a[0]), "r"(a[1]), "r"(a[2]), "r"(a[3]), "l"(desc));
}

struct Params {
    CUtensorMap w1_map, w2_map;
    const __nv_bfloat16* x;
    const __nv_bfloat16* dw;
    const __nv_bfloat16* w1;
    const __nv_bfloat16* gamma;
    const __nv_bfloat16* beta;
    __nv_bfloat16* out;
    Scratch* g;
    uint64_t sel[3];
    uint32_t w1desc, w2desc, ydesc;
};

__device__ __forceinline__ int cta_stride(uint32_t cta) { return cta & 8 ? ROW_BYTES : -ROW_BYTES; }
__device__ __forceinline__ uint32_t cta_tile0(uint32_t cta) {
    return ((cta >> 3) * ROWS_PER_CTA + (cta & 8 ? 0 : ROWS_PER_CTA - 1)) * ROW_BYTES + (cta & 7) * TILE_BYTES;
}

struct Producer {
    uint32_t w[9][6];
    uint32_t xoff[2];
    uint32_t yoff[2][2];
    uint32_t stat, own;
    int lane, warp;
};

struct RowCopy {
    const char* x0;
    char* y0;
    const char* zeros;
    uint32_t cut0, cut1;
    int stride, last;
};
__device__ __forceinline__ RowCopy row_copy(const Params& prm) {
    const uint32_t cta = fresh_cta(), strip = cta & 7, t0 = cta_tile0(cta);
    RowCopy r;
    r.stride = cta_stride(cta);
    r.x0 = (const char*)prm.x + (t0 - r.stride) - 192;
    r.y0 = (char*)prm.out + t0;
    r.zeros = (const char*)prm.g->zero_row;
    r.cut0 = strip == 0 ? 192 : 0;
    r.cut1 = strip == 7 ? 192 : 0;
    r.last = cta - 8 >= NUM_CTAS - 16 ? STEPS - 2 : STEPS - 1;
    return r;
}
__device__ __forceinline__ void issue_row_load(const RowCopy& r, int i, uint32_t slot) {
    const char* src = r.x0 + i * r.stride;
    const uint32_t bar = sb + SM_XFULL + slot * SLOT_BYTES, dst = sb + SM_X + slot * SLOT_BYTES;
    expect_tx(bar, XHALF_BYTES - r.cut0);
    bulk_load(dst + r.cut0, src + r.cut0, XHALF_BYTES - r.cut0, bar);
    expect_tx(bar, XHALF_BYTES - r.cut1);
    bulk_load(dst + XHALF_B, src + 32 * 192, XHALF_BYTES - r.cut1, bar);
}

__device__ __forceinline__ float quad_sum(float v) {
    v += __shfl_xor_sync(0xffffffffu, v, 1);
    v += __shfl_xor_sync(0xffffffffu, v, 2);
    return v;
}

__device__ __forceinline__ void load_x(uint32_t (&v)[6][6], const Producer& c, uint32_t row) {
#pragma unroll
    for (int k = 0; k < 6; k++) {
        asm volatile("ld.shared.v4.b32 {%0,%1,%2,%3}, [%4];"
                     : "=r"(v[k][0]), "=r"(v[k][1]), "=r"(v[k][2]), "=r"(v[k][3]) : "r"(row + c.xoff[0] + k * 192));
        asm volatile("ld.shared.v2.b32 {%0,%1}, [%2];" : "=r"(v[k][4]), "=r"(v[k][5]) : "r"(row + c.xoff[1] + k * 192));
    }
}
template <int DY, int STRIDE>
__device__ __forceinline__ void conv_row(uint32_t (&dst)[24], const uint32_t* src, const uint32_t (&v)[6][6], const Producer& c) {
#pragma unroll
    for (int o = 0; o < 4; o++)
#pragma unroll
        for (int u = 0; u < 6; u++)
            dst[o * 6 + u] = bf2_fma(v[o + 2][u], c.w[3 * DY + 2][u], bf2_fma(v[o + 1][u], c.w[3 * DY + 1][u],
                             bf2_fma(v[o][u], c.w[3 * DY][u], STRIDE ? src[o * 6 + u] : src[2 * o + 1])));
}
#define HAND_OVER(name, base, r) asm volatile("mov.b32 " name "%6, %0; mov.b32 " name "%7, %1; mov.b32 " name "%8, %2;\n" \
    "mov.b32 " name "%9, %3; mov.b32 " name "%10, %4; mov.b32 " name "%11, %5;" ::"r"((r)[0]), "r"((r)[1]), "r"((r)[2]), \
    "r"((r)[3]), "r"((r)[4]), "r"((r)[5]), "n"(base), "n"(base + 1), "n"(base + 2), "n"(base + 3), "n"(base + 4), "n"(base + 5))
template <int K> __device__ __forceinline__ void hand_over(const Producer& c, const uint32_t (&B)[24], const uint32_t (&C)[24],
                                                           const uint32_t (&v)[6][6]) {
    HAND_OVER("pw", K * 6, c.w[K]);
    if (K < 6) HAND_OVER("pv", K * 6, v[K % 6]);
    if (K < 4) { HAND_OVER("pb", K * 6, B + K % 4 * 6); HAND_OVER("pc", K * 6, C + K % 4 * 6); }
    if constexpr (K < 8) hand_over<K + 1>(c, B, C, v);
}
static_assert(sb + SM_BAR + BAR_DUMMY * 8 == 230880, "layout");
__device__ __forceinline__ void produce_tiles(const Producer& c, const Params& prm) {
    asm volatile(
        "{\n"
        ".reg .b32 pa<24>, pq<4>, m<6>, y<6>, rr, mm, t, so, sp, ph, ad, tt, cnt;\n"
        ".reg .b16 xl, xh;\n"
        ".reg .f32 d<4>, us, s0, s1, f0, f1, kq;\n"
        ".reg .pred pt, pf, pr, pw, px, pl, po, pe;\n"
        "setp.ne.b32 pt, 1, 0; setp.ne.b32 pf, 0, 0; setp.eq.u32 pl, %8, 0; and.b32 tt, %8, 1; setp.ne.u32 po, tt, 0;\n"
        "and.b32 tt, %8, 4; setp.ne.u32 pr, tt, 0; selp.f32 kq, 0f3F802D41, 0f3F7FA57E, pr;\n"
        "mov.u32 t, 0; mov.u32 so, 0; mov.u32 sp, 55896; mov.u32 ph, 1;\n"
        "LOOP:\n"
        ASM_TRC("t", 0)
        "setp.eq.u32 pr, %12, 0;\n"
        "@pr bra.uni RARE;\n"
        "fence.proxy.async.shared::cta;\n"
        "@pl mbarrier.arrive.shared::cta.b64 _, [sp+174984];\n"
        "fma.rn.bf16x2 pa0, pv0, pw36, pb0; fma.rn.bf16x2 pa1, pv1, pw37, pb1; fma.rn.bf16x2 pa2, pv2, pw38, pb2; fma.rn.bf16x2 pa3, pv3, pw39, pb3; fma.rn.bf16x2 pa4, pv4, pw40, pb4; fma.rn.bf16x2 pa5, pv5, pw41, pb5;\n"
        "fma.rn.bf16x2 pa6, pv6, pw36, pb6; fma.rn.bf16x2 pa7, pv7, pw37, pb7; fma.rn.bf16x2 pa8, pv8, pw38, pb8; fma.rn.bf16x2 pa9, pv9, pw39, pb9; fma.rn.bf16x2 pa10, pv10, pw40, pb10; fma.rn.bf16x2 pa11, pv11, pw41, pb11;\n"
        "fma.rn.bf16x2 pa12, pv12, pw36, pb12; fma.rn.bf16x2 pa13, pv13, pw37, pb13; fma.rn.bf16x2 pa14, pv14, pw38, pb14; fma.rn.bf16x2 pa15, pv15, pw39, pb15; fma.rn.bf16x2 pa16, pv16, pw40, pb16; fma.rn.bf16x2 pa17, pv17, pw41, pb17;\n"
        "fma.rn.bf16x2 pa18, pv18, pw36, pb18; fma.rn.bf16x2 pa19, pv19, pw37, pb19; fma.rn.bf16x2 pa20, pv20, pw38, pb20; fma.rn.bf16x2 pa21, pv21, pw39, pb21; fma.rn.bf16x2 pa22, pv22, pw40, pb22; fma.rn.bf16x2 pa23, pv23, pw41, pb23;\n"
        "fma.rn.bf16x2 pa0, pv6, pw42, pa0; fma.rn.bf16x2 pa1, pv7, pw43, pa1; fma.rn.bf16x2 pa2, pv8, pw44, pa2; fma.rn.bf16x2 pa3, pv9, pw45, pa3; fma.rn.bf16x2 pa4, pv10, pw46, pa4; fma.rn.bf16x2 pa5, pv11, pw47, pa5;\n"
        "fma.rn.bf16x2 pa6, pv12, pw42, pa6; fma.rn.bf16x2 pa7, pv13, pw43, pa7; fma.rn.bf16x2 pa8, pv14, pw44, pa8; fma.rn.bf16x2 pa9, pv15, pw45, pa9; fma.rn.bf16x2 pa10, pv16, pw46, pa10; fma.rn.bf16x2 pa11, pv17, pw47, pa11;\n"
        "fma.rn.bf16x2 pa12, pv18, pw42, pa12; fma.rn.bf16x2 pa13, pv19, pw43, pa13; fma.rn.bf16x2 pa14, pv20, pw44, pa14; fma.rn.bf16x2 pa15, pv21, pw45, pa15; fma.rn.bf16x2 pa16, pv22, pw46, pa16; fma.rn.bf16x2 pa17, pv23, pw47, pa17;\n"
        "fma.rn.bf16x2 pa18, pv24, pw42, pa18; fma.rn.bf16x2 pa19, pv25, pw43, pa19; fma.rn.bf16x2 pa20, pv26, pw44, pa20; fma.rn.bf16x2 pa21, pv27, pw45, pa21; fma.rn.bf16x2 pa22, pv28, pw46, pa22; fma.rn.bf16x2 pa23, pv29, pw47, pa23;\n"
        "fma.rn.bf16x2 pa0, pv12, pw48, pa0; fma.rn.bf16x2 pa1, pv13, pw49, pa1; fma.rn.bf16x2 pa2, pv14, pw50, pa2; fma.rn.bf16x2 pa3, pv15, pw51, pa3; fma.rn.bf16x2 pa4, pv16, pw52, pa4; fma.rn.bf16x2 pa5, pv17, pw53, pa5;\n"
        "fma.rn.bf16x2 pa6, pv18, pw48, pa6; fma.rn.bf16x2 pa7, pv19, pw49, pa7; fma.rn.bf16x2 pa8, pv20, pw50, pa8; fma.rn.bf16x2 pa9, pv21, pw51, pa9; fma.rn.bf16x2 pa10, pv22, pw52, pa10; fma.rn.bf16x2 pa11, pv23, pw53, pa11;\n"
        "fma.rn.bf16x2 pa12, pv24, pw48, pa12; fma.rn.bf16x2 pa13, pv25, pw49, pa13; fma.rn.bf16x2 pa14, pv26, pw50, pa14; fma.rn.bf16x2 pa15, pv27, pw51, pa15; fma.rn.bf16x2 pa16, pv28, pw52, pa16; fma.rn.bf16x2 pa17, pv29, pw53, pa17;\n"
        "fma.rn.bf16x2 pa18, pv30, pw48, pa18; fma.rn.bf16x2 pa19, pv31, pw49, pa19; fma.rn.bf16x2 pa20, pv32, pw50, pa20; fma.rn.bf16x2 pa21, pv33, pw51, pa21; fma.rn.bf16x2 pa22, pv34, pw52, pa22; fma.rn.bf16x2 pa23, pv35, pw53, pa23;\n"
        "mul.rn.bf16x2 pq0, pa0, pa0; fma.rn.bf16x2 pq0, pa1, pa1, pq0; fma.rn.bf16x2 pq0, pa2, pa2, pq0; fma.rn.bf16x2 pq0, pa3, pa3, pq0; fma.rn.bf16x2 pq0, pa4, pa4, pq0; fma.rn.bf16x2 pq0, pa5, pa5, pq0;\n"
        "mul.rn.bf16x2 pq1, pa6, pa6; fma.rn.bf16x2 pq1, pa7, pa7, pq1; fma.rn.bf16x2 pq1, pa8, pa8, pq1; fma.rn.bf16x2 pq1, pa9, pa9, pq1; fma.rn.bf16x2 pq1, pa10, pa10, pq1; fma.rn.bf16x2 pq1, pa11, pa11, pq1;\n"
        "mul.rn.bf16x2 pq2, pa12, pa12; fma.rn.bf16x2 pq2, pa13, pa13, pq2; fma.rn.bf16x2 pq2, pa14, pa14, pq2; fma.rn.bf16x2 pq2, pa15, pa15, pq2; fma.rn.bf16x2 pq2, pa16, pa16, pq2; fma.rn.bf16x2 pq2, pa17, pa17, pq2;\n"
        "mul.rn.bf16x2 pq3, pa18, pa18; fma.rn.bf16x2 pq3, pa19, pa19, pq3; fma.rn.bf16x2 pq3, pa20, pa20, pq3; fma.rn.bf16x2 pq3, pa21, pa21, pq3; fma.rn.bf16x2 pq3, pa22, pa22, pq3; fma.rn.bf16x2 pq3, pa23, pa23, pq3;\n"
        "B0:\n"
        "wgmma.fence.sync.aligned;\n"
        "wgmma.mma_async.sync.aligned.m64n8k16.f32.bf16.bf16 {d0,d1,d2,d3}, {pa0,pa6,pa1,pa7}, %9, pf, 1, 1, 0;\n"
        "wgmma.mma_async.sync.aligned.m64n8k16.f32.bf16.bf16 {d0,d1,d2,d3}, {pa2,pa8,pa3,pa9}, %9, pt, 1, 1, 0;\n"
        "wgmma.mma_async.sync.aligned.m64n8k16.f32.bf16.bf16 {d0,d1,d2,d3}, {pa4,pa10,pa5,pa11}, %9, pt, 1, 1, 0;\n"
        "wgmma.mma_async.sync.aligned.m64n8k16.f32.bf16.bf16 {d0,d1,d2,d3}, {pa12,pa18,pa13,pa19}, %10, pt, 1, 1, 0;\n"
        "wgmma.mma_async.sync.aligned.m64n8k16.f32.bf16.bf16 {d0,d1,d2,d3}, {pa14,pa20,pa15,pa21}, %10, pt, 1, 1, 0;\n"
        "wgmma.mma_async.sync.aligned.m64n8k16.f32.bf16.bf16 {d0,d1,d2,d3}, {pa16,pa22,pa17,pa23}, %10, pt, 1, 1, 0;\n"
        "wgmma.mma_async.sync.aligned.m64n8k16.f32.bf16.bf16 {d0,d1,d2,d3}, {pq0,pq1,pq2,pq3}, %11, pt, 1, 1, 0;\n"
        "wgmma.commit_group.sync.aligned;\n"
        "add.u32 ad, %7, so; ld.shared.f32 us, [ad+4];\n"
        "fma.rn.bf16x2 pb0, pv0, pw18, pc0; fma.rn.bf16x2 pb1, pv1, pw19, pc1; fma.rn.bf16x2 pb2, pv2, pw20, pc2; fma.rn.bf16x2 pb3, pv3, pw21, pc3; fma.rn.bf16x2 pb4, pv4, pw22, pc4; fma.rn.bf16x2 pb5, pv5, pw23, pc5;\n"
        "fma.rn.bf16x2 pb6, pv6, pw18, pc6; fma.rn.bf16x2 pb7, pv7, pw19, pc7; fma.rn.bf16x2 pb8, pv8, pw20, pc8; fma.rn.bf16x2 pb9, pv9, pw21, pc9; fma.rn.bf16x2 pb10, pv10, pw22, pc10; fma.rn.bf16x2 pb11, pv11, pw23, pc11;\n"
        "fma.rn.bf16x2 pb0, pv6, pw24, pb0; fma.rn.bf16x2 pb1, pv7, pw25, pb1; fma.rn.bf16x2 pb2, pv8, pw26, pb2; fma.rn.bf16x2 pb3, pv9, pw27, pb3; fma.rn.bf16x2 pb4, pv10, pw28, pb4; fma.rn.bf16x2 pb5, pv11, pw29, pb5;\n"
        "fma.rn.bf16x2 pb6, pv12, pw24, pb6; fma.rn.bf16x2 pb7, pv13, pw25, pb7; fma.rn.bf16x2 pb8, pv14, pw26, pb8; fma.rn.bf16x2 pb9, pv15, pw27, pb9; fma.rn.bf16x2 pb10, pv16, pw28, pb10; fma.rn.bf16x2 pb11, pv17, pw29, pb11;\n"
        "fma.rn.bf16x2 pb0, pv12, pw30, pb0; fma.rn.bf16x2 pb1, pv13, pw31, pb1; fma.rn.bf16x2 pb2, pv14, pw32, pb2; fma.rn.bf16x2 pb3, pv15, pw33, pb3; fma.rn.bf16x2 pb4, pv16, pw34, pb4; fma.rn.bf16x2 pb5, pv17, pw35, pb5;\n"
        "fma.rn.bf16x2 pb6, pv18, pw30, pb6; fma.rn.bf16x2 pb7, pv19, pw31, pb7; fma.rn.bf16x2 pb8, pv20, pw32, pb8; fma.rn.bf16x2 pb9, pv21, pw33, pb9; fma.rn.bf16x2 pb10, pv22, pw34, pb10; fma.rn.bf16x2 pb11, pv23, pw35, pb11;\n"
        "B1:\n"
        "fma.rn.bf16x2 pb12, pv12, pw18, pc12; fma.rn.bf16x2 pb13, pv13, pw19, pc13; fma.rn.bf16x2 pb14, pv14, pw20, pc14; fma.rn.bf16x2 pb15, pv15, pw21, pc15; fma.rn.bf16x2 pb16, pv16, pw22, pc16; fma.rn.bf16x2 pb17, pv17, pw23, pc17;\n"
        "fma.rn.bf16x2 pb18, pv18, pw18, pc18; fma.rn.bf16x2 pb19, pv19, pw19, pc19; fma.rn.bf16x2 pb20, pv20, pw20, pc20; fma.rn.bf16x2 pb21, pv21, pw21, pc21; fma.rn.bf16x2 pb22, pv22, pw22, pc22; fma.rn.bf16x2 pb23, pv23, pw23, pc23;\n"
        "fma.rn.bf16x2 pb12, pv18, pw24, pb12; fma.rn.bf16x2 pb13, pv19, pw25, pb13; fma.rn.bf16x2 pb14, pv20, pw26, pb14; fma.rn.bf16x2 pb15, pv21, pw27, pb15; fma.rn.bf16x2 pb16, pv22, pw28, pb16; fma.rn.bf16x2 pb17, pv23, pw29, pb17;\n"
        "fma.rn.bf16x2 pb18, pv24, pw24, pb18; fma.rn.bf16x2 pb19, pv25, pw25, pb19; fma.rn.bf16x2 pb20, pv26, pw26, pb20; fma.rn.bf16x2 pb21, pv27, pw27, pb21; fma.rn.bf16x2 pb22, pv28, pw28, pb22; fma.rn.bf16x2 pb23, pv29, pw29, pb23;\n"
        "fma.rn.bf16x2 pb12, pv24, pw30, pb12; fma.rn.bf16x2 pb13, pv25, pw31, pb13; fma.rn.bf16x2 pb14, pv26, pw32, pb14; fma.rn.bf16x2 pb15, pv27, pw33, pb15; fma.rn.bf16x2 pb16, pv28, pw34, pb16; fma.rn.bf16x2 pb17, pv29, pw35, pb17;\n"
        "fma.rn.bf16x2 pb18, pv30, pw30, pb18; fma.rn.bf16x2 pb19, pv31, pw31, pb19; fma.rn.bf16x2 pb20, pv32, pw32, pb20; fma.rn.bf16x2 pb21, pv33, pw33, pb21; fma.rn.bf16x2 pb22, pv34, pw34, pb22; fma.rn.bf16x2 pb23, pv35, pw35, pb23;\n"
        "C0:\n"
        "wgmma.wait_group.sync.aligned 0;\n"
        "selp.f32 s0, d2, d0, po; selp.f32 s1, d3, d1, po;\n"
        "shfl.sync.bfly.b32 f0, s0, 4, 0x1f, 0xffffffff; shfl.sync.bfly.b32 f1, s1, 4, 0x1f, 0xffffffff;\n"
        "fma.rn.bf16x2 pc0, pv0, pw0, ps1; fma.rn.bf16x2 pc1, pv1, pw1, ps1; fma.rn.bf16x2 pc2, pv2, pw2, ps1; fma.rn.bf16x2 pc3, pv3, pw3, ps1; fma.rn.bf16x2 pc4, pv4, pw4, ps1; fma.rn.bf16x2 pc5, pv5, pw5, ps1;\n"
        "fma.rn.bf16x2 pc6, pv6, pw0, ps3; fma.rn.bf16x2 pc7, pv7, pw1, ps3; fma.rn.bf16x2 pc8, pv8, pw2, ps3; fma.rn.bf16x2 pc9, pv9, pw3, ps3; fma.rn.bf16x2 pc10, pv10, pw4, ps3; fma.rn.bf16x2 pc11, pv11, pw5, ps3;\n"
        "fma.rn.bf16x2 pc12, pv12, pw0, ps5; fma.rn.bf16x2 pc13, pv13, pw1, ps5; fma.rn.bf16x2 pc14, pv14, pw2, ps5; fma.rn.bf16x2 pc15, pv15, pw3, ps5; fma.rn.bf16x2 pc16, pv16, pw4, ps5; fma.rn.bf16x2 pc17, pv17, pw5, ps5;\n"
        "fma.rn.bf16x2 pc18, pv18, pw0, ps7; fma.rn.bf16x2 pc19, pv19, pw1, ps7; fma.rn.bf16x2 pc20, pv20, pw2, ps7; fma.rn.bf16x2 pc21, pv21, pw3, ps7; fma.rn.bf16x2 pc22, pv22, pw4, ps7; fma.rn.bf16x2 pc23, pv23, pw5, ps7;\n"
        "fma.rn.bf16x2 pc0, pv6, pw6, pc0; fma.rn.bf16x2 pc1, pv7, pw7, pc1; fma.rn.bf16x2 pc2, pv8, pw8, pc2; fma.rn.bf16x2 pc3, pv9, pw9, pc3; fma.rn.bf16x2 pc4, pv10, pw10, pc4; fma.rn.bf16x2 pc5, pv11, pw11, pc5;\n"
        "fma.rn.bf16x2 pc6, pv12, pw6, pc6; fma.rn.bf16x2 pc7, pv13, pw7, pc7; fma.rn.bf16x2 pc8, pv14, pw8, pc8; fma.rn.bf16x2 pc9, pv15, pw9, pc9; fma.rn.bf16x2 pc10, pv16, pw10, pc10; fma.rn.bf16x2 pc11, pv17, pw11, pc11;\n"
        "fma.rn.bf16x2 pc12, pv18, pw6, pc12; fma.rn.bf16x2 pc13, pv19, pw7, pc13; fma.rn.bf16x2 pc14, pv20, pw8, pc14; fma.rn.bf16x2 pc15, pv21, pw9, pc15; fma.rn.bf16x2 pc16, pv22, pw10, pc16; fma.rn.bf16x2 pc17, pv23, pw11, pc17;\n"
        "fma.rn.bf16x2 pc18, pv24, pw6, pc18; fma.rn.bf16x2 pc19, pv25, pw7, pc19; fma.rn.bf16x2 pc20, pv26, pw8, pc20; fma.rn.bf16x2 pc21, pv27, pw9, pc21; fma.rn.bf16x2 pc22, pv28, pw10, pc22; fma.rn.bf16x2 pc23, pv29, pw11, pc23;\n"
        "fma.rn.bf16x2 pc0, pv12, pw12, pc0; fma.rn.bf16x2 pc1, pv13, pw13, pc1; fma.rn.bf16x2 pc2, pv14, pw14, pc2; fma.rn.bf16x2 pc3, pv15, pw15, pc3; fma.rn.bf16x2 pc4, pv16, pw16, pc4; fma.rn.bf16x2 pc5, pv17, pw17, pc5;\n"
        "fma.rn.bf16x2 pc6, pv18, pw12, pc6; fma.rn.bf16x2 pc7, pv19, pw13, pc7; fma.rn.bf16x2 pc8, pv20, pw14, pc8; fma.rn.bf16x2 pc9, pv21, pw15, pc9; fma.rn.bf16x2 pc10, pv22, pw16, pc10; fma.rn.bf16x2 pc11, pv23, pw17, pc11;\n"
        "fma.rn.bf16x2 pc12, pv24, pw12, pc12; fma.rn.bf16x2 pc13, pv25, pw13, pc13; fma.rn.bf16x2 pc14, pv26, pw14, pc14; fma.rn.bf16x2 pc15, pv27, pw15, pc15; fma.rn.bf16x2 pc16, pv28, pw16, pc16; fma.rn.bf16x2 pc17, pv29, pw17, pc17;\n"
        "fma.rn.bf16x2 pc18, pv30, pw12, pc18; fma.rn.bf16x2 pc19, pv31, pw13, pc19; fma.rn.bf16x2 pc20, pv32, pw14, pc20; fma.rn.bf16x2 pc21, pv33, pw15, pc21; fma.rn.bf16x2 pc22, pv34, pw16, pc22; fma.rn.bf16x2 pc23, pv35, pw17, pc23;\n"
        "add.f32 s0, s0, f0; add.f32 s1, s1, f1; mul.f32 s0, s0, 0fBC2AAAAB;\n"
        "neg.f32 f0, s0; fma.rn.f32 f0, f0, s0, %13; fma.rn.f32 f0, s1, 0f3C2AAAAB, f0; max.f32 f0, f0, %13;\n"
        "rsqrt.approx.ftz.f32 f0, f0; mul.f32 f0, f0, %14; cvt.rn.bf16x2.f32 tt, f0, 0f00000000; mov.b32 f0, tt;\n"
        "mul.f32 f1, s0, kq; mul.f32 f1, f1, f0; cvt.rn.bf16x2.f32 tt, f1, f0; add.f32 us, us, s0; cvt.rn.bf16x2.f32 mm, us, us;\n"
        "add.u32 ad, %7, so; st.shared.v2.b32 [ad], {tt, mm};\n"
        "add.u32 ad, %6, so; ld.shared.v4.b32 {ps0,ps1,ps2,ps3}, [ad]; ld.shared.v4.b32 {ps4,ps5,ps6,ps7}, [ad+16];\n"
        "mbarrier.try_wait.parity.shared::cta.b64 pw, [so+174992], ph;\n"
        "mbarrier.try_wait.parity.shared::cta.b64 px, [so+174976], ph;\n"
        "and.pred pw, pw, px;\n"
        "N0:\n"
        "@!pw bra.uni SPIN;\n"
        "BACK:\n"
        "add.u32 ad, %0, so; ld.shared.v4.b32 {pv0,pv1,pv2,pv3}, [ad+0];\n"
        "add.u32 ad, %1, so; ld.shared.v2.b32 {pv4,pv5}, [ad+0];\n"
        "add.u32 ad, %0, so; ld.shared.v4.b32 {pv6,pv7,pv8,pv9}, [ad+192];\n"
        "add.u32 ad, %1, so; ld.shared.v2.b32 {pv10,pv11}, [ad+192];\n"
        "mov.b32 {xl, xh}, ps0; mov.b32 rr, {xl, xl}; mov.b32 mm, {xh, xh}; fma.rn.bf16x2 pa0, pa0, rr, mm; fma.rn.bf16x2 pa1, pa1, rr, mm; fma.rn.bf16x2 pa2, pa2, rr, mm; fma.rn.bf16x2 pa3, pa3, rr, mm; fma.rn.bf16x2 pa4, pa4, rr, mm; fma.rn.bf16x2 pa5, pa5, rr, mm;\n"
        "and.b32 m0, pa0, 0x7fff7fff; and.b32 m1, pa1, 0x7fff7fff; and.b32 m2, pa2, 0x7fff7fff; and.b32 m3, pa3, 0x7fff7fff; and.b32 m4, pa4, 0x7fff7fff; and.b32 m5, pa5, 0x7fff7fff;\n"
        "mad.lo.u32 y0, m0, 7, pa0; mad.lo.u32 y1, m1, 7, pa1; mad.lo.u32 y2, m2, 7, pa2; mad.lo.u32 y3, m3, 7, pa3; mad.lo.u32 y4, m4, 7, pa4; mad.lo.u32 y5, m5, 7, pa5;\n"
        "add.u32 ad, %2, so; st.shared.v4.b32 [ad+0], {y0,y1,y2,y3};\n"
        "add.u32 ad, %4, so; st.shared.v2.b32 [ad+0], {y4,y5};\n"
        "N1:\n"
        "add.u32 ad, %0, so; ld.shared.v4.b32 {pv12,pv13,pv14,pv15}, [ad+384];\n"
        "add.u32 ad, %1, so; ld.shared.v2.b32 {pv16,pv17}, [ad+384];\n"
        "add.u32 ad, %0, so; ld.shared.v4.b32 {pv18,pv19,pv20,pv21}, [ad+576];\n"
        "add.u32 ad, %1, so; ld.shared.v2.b32 {pv22,pv23}, [ad+576];\n"
        "mov.b32 {xl, xh}, ps2; mov.b32 rr, {xl, xl}; mov.b32 mm, {xh, xh}; fma.rn.bf16x2 pa6, pa6, rr, mm; fma.rn.bf16x2 pa7, pa7, rr, mm; fma.rn.bf16x2 pa8, pa8, rr, mm; fma.rn.bf16x2 pa9, pa9, rr, mm; fma.rn.bf16x2 pa10, pa10, rr, mm; fma.rn.bf16x2 pa11, pa11, rr, mm;\n"
        "and.b32 m0, pa6, 0x7fff7fff; and.b32 m1, pa7, 0x7fff7fff; and.b32 m2, pa8, 0x7fff7fff; and.b32 m3, pa9, 0x7fff7fff; and.b32 m4, pa10, 0x7fff7fff; and.b32 m5, pa11, 0x7fff7fff;\n"
        "mad.lo.u32 y0, m0, 7, pa6; mad.lo.u32 y1, m1, 7, pa7; mad.lo.u32 y2, m2, 7, pa8; mad.lo.u32 y3, m3, 7, pa9; mad.lo.u32 y4, m4, 7, pa10; mad.lo.u32 y5, m5, 7, pa11;\n"
        "add.u32 ad, %3, so; st.shared.v4.b32 [ad+0], {y0,y1,y2,y3};\n"
        "add.u32 ad, %5, so; st.shared.v2.b32 [ad+0], {y4,y5};\n"
        "N2:\n"
        "add.u32 ad, %0, so; ld.shared.v4.b32 {pv24,pv25,pv26,pv27}, [ad+768];\n"
        "add.u32 ad, %1, so; ld.shared.v2.b32 {pv28,pv29}, [ad+768];\n"
        "mov.b32 {xl, xh}, ps4; mov.b32 rr, {xl, xl}; mov.b32 mm, {xh, xh}; fma.rn.bf16x2 pa12, pa12, rr, mm; fma.rn.bf16x2 pa13, pa13, rr, mm; fma.rn.bf16x2 pa14, pa14, rr, mm; fma.rn.bf16x2 pa15, pa15, rr, mm; fma.rn.bf16x2 pa16, pa16, rr, mm; fma.rn.bf16x2 pa17, pa17, rr, mm;\n"
        "and.b32 m0, pa12, 0x7fff7fff; and.b32 m1, pa13, 0x7fff7fff; and.b32 m2, pa14, 0x7fff7fff; and.b32 m3, pa15, 0x7fff7fff; and.b32 m4, pa16, 0x7fff7fff; and.b32 m5, pa17, 0x7fff7fff;\n"
        "mad.lo.u32 y0, m0, 7, pa12; mad.lo.u32 y1, m1, 7, pa13; mad.lo.u32 y2, m2, 7, pa14; mad.lo.u32 y3, m3, 7, pa15; mad.lo.u32 y4, m4, 7, pa16; mad.lo.u32 y5, m5, 7, pa17;\n"
        "add.u32 ad, %2, so; st.shared.v4.b32 [ad+2048], {y0,y1,y2,y3};\n"
        "add.u32 ad, %4, so; st.shared.v2.b32 [ad+1024], {y4,y5};\n"
        "N3:\n"
        "add.u32 ad, %0, so; ld.shared.v4.b32 {pv30,pv31,pv32,pv33}, [ad+960];\n"
        "add.u32 ad, %1, so; ld.shared.v2.b32 {pv34,pv35}, [ad+960];\n"
        "mov.b32 {xl, xh}, ps6; mov.b32 rr, {xl, xl}; mov.b32 mm, {xh, xh}; fma.rn.bf16x2 pa18, pa18, rr, mm; fma.rn.bf16x2 pa19, pa19, rr, mm; fma.rn.bf16x2 pa20, pa20, rr, mm; fma.rn.bf16x2 pa21, pa21, rr, mm; fma.rn.bf16x2 pa22, pa22, rr, mm; fma.rn.bf16x2 pa23, pa23, rr, mm;\n"
        "and.b32 m0, pa18, 0x7fff7fff; and.b32 m1, pa19, 0x7fff7fff; and.b32 m2, pa20, 0x7fff7fff; and.b32 m3, pa21, 0x7fff7fff; and.b32 m4, pa22, 0x7fff7fff; and.b32 m5, pa23, 0x7fff7fff;\n"
        "mad.lo.u32 y0, m0, 7, pa18; mad.lo.u32 y1, m1, 7, pa19; mad.lo.u32 y2, m2, 7, pa20; mad.lo.u32 y3, m3, 7, pa21; mad.lo.u32 y4, m4, 7, pa22; mad.lo.u32 y5, m5, 7, pa23;\n"
        "add.u32 ad, %3, so; st.shared.v4.b32 [ad+2048], {y0,y1,y2,y3};\n"
        "add.u32 ad, %5, so; st.shared.v2.b32 [ad+1024], {y4,y5};\n"
        "mov.u32 sp, so; add.u32 so, so, 26624; setp.eq.u32 pr, so, 79872; selp.u32 so, 0, so, pr; selp.u32 tt, 1, 0, pr; xor.b32 ph, ph, tt;\n"
        "add.u32 t, t, 1; setp.lt.u32 pe, t, 32;\n"
        "@pe bra.uni LOOP;\n"
        "bra.uni DONE;\n"
        "SPIN: mov.u32 cnt, 0;\n"
        ASM_TRC("t", 1)
        "SPINL:\n"
        "mbarrier.try_wait.parity.shared::cta.b64 pw, [so+174992], ph;\n"
        "mbarrier.try_wait.parity.shared::cta.b64 px, [so+174976], ph;\n"
        "and.pred pw, pw, px;\n"
        "@pw bra.uni BACK;\n"
        "add.u32 cnt, cnt, 1; setp.lt.u32 pw, cnt, 0x100000;\n"
        "@pw bra.uni SPINL;\n"
        "trap;\n"
        "RARE:\n"
        "ld.volatile.shared.u32 tt, [%6];\n"
        "mov.b32 pa0, tt; mov.b32 pa1, tt; mov.b32 pa2, tt; mov.b32 pa3, tt; mov.b32 pa4, tt; mov.b32 pa5, tt; mov.b32 pa6, tt; mov.b32 pa7, tt; mov.b32 pa8, tt; mov.b32 pa9, tt; mov.b32 pa10, tt; mov.b32 pa11, tt;\n"
        "mov.b32 pa12, tt; mov.b32 pa13, tt; mov.b32 pa14, tt; mov.b32 pa15, tt; mov.b32 pa16, tt; mov.b32 pa17, tt; mov.b32 pa18, tt; mov.b32 pa19, tt; mov.b32 pa20, tt; mov.b32 pa21, tt; mov.b32 pa22, tt; mov.b32 pa23, tt;\n"
        "mov.b32 pb0, tt; mov.b32 pb1, tt; mov.b32 pb2, tt; mov.b32 pb3, tt; mov.b32 pb4, tt; mov.b32 pb5, tt; mov.b32 pb6, tt; mov.b32 pb7, tt; mov.b32 pb8, tt; mov.b32 pb9, tt; mov.b32 pb10, tt; mov.b32 pb11, tt;\n"
        "mov.b32 pb12, tt; mov.b32 pb13, tt; mov.b32 pb14, tt; mov.b32 pb15, tt; mov.b32 pb16, tt; mov.b32 pb17, tt; mov.b32 pb18, tt; mov.b32 pb19, tt; mov.b32 pb20, tt; mov.b32 pb21, tt; mov.b32 pb22, tt; mov.b32 pb23, tt;\n"
        "mov.b32 pc0, tt; mov.b32 pc1, tt; mov.b32 pc2, tt; mov.b32 pc3, tt; mov.b32 pc4, tt; mov.b32 pc5, tt; mov.b32 pc6, tt; mov.b32 pc7, tt; mov.b32 pc8, tt; mov.b32 pc9, tt; mov.b32 pc10, tt; mov.b32 pc11, tt;\n"
        "mov.b32 pc12, tt; mov.b32 pc13, tt; mov.b32 pc14, tt; mov.b32 pc15, tt; mov.b32 pc16, tt; mov.b32 pc17, tt; mov.b32 pc18, tt; mov.b32 pc19, tt; mov.b32 pc20, tt; mov.b32 pc21, tt; mov.b32 pc22, tt; mov.b32 pc23, tt;\n"
        "mov.b32 pv0, tt; mov.b32 pv1, tt; mov.b32 pv2, tt; mov.b32 pv3, tt; mov.b32 pv4, tt; mov.b32 pv5, tt; mov.b32 pv6, tt; mov.b32 pv7, tt; mov.b32 pv8, tt; mov.b32 pv9, tt; mov.b32 pv10, tt; mov.b32 pv11, tt;\n"
        "mov.b32 pv12, tt; mov.b32 pv13, tt; mov.b32 pv14, tt; mov.b32 pv15, tt; mov.b32 pv16, tt; mov.b32 pv17, tt; mov.b32 pv18, tt; mov.b32 pv19, tt; mov.b32 pv20, tt; mov.b32 pv21, tt; mov.b32 pv22, tt; mov.b32 pv23, tt;\n"
        "mov.b32 pv24, tt; mov.b32 pv25, tt; mov.b32 pv26, tt; mov.b32 pv27, tt; mov.b32 pv28, tt; mov.b32 pv29, tt; mov.b32 pv30, tt; mov.b32 pv31, tt; mov.b32 pv32, tt; mov.b32 pv33, tt; mov.b32 pv34, tt; mov.b32 pv35, tt;\n"
        "mov.b32 ps0, tt; mov.b32 ps1, tt; mov.b32 ps2, tt; mov.b32 ps3, tt; mov.b32 ps4, tt; mov.b32 ps5, tt; mov.b32 ps6, tt; mov.b32 ps7, tt; mov.b32 pq0, tt; mov.b32 pq1, tt; mov.b32 pq2, tt; mov.b32 pq3, tt;\n"
        "mov.b32 m0, tt; mov.b32 m1, tt; mov.b32 m2, tt; mov.b32 m3, tt; mov.b32 m4, tt; mov.b32 m5, tt; mov.b32 y0, tt; mov.b32 y1, tt; mov.b32 y2, tt; mov.b32 y3, tt; mov.b32 y4, tt; mov.b32 y5, tt;\n"
        "mov.b32 us, tt; setp.ne.u32 pw, t, 7;\n"
        "wgmma.fence.sync.aligned;\n"
        "setp.eq.u32 pr, t, 1000; @pr bra.uni B0;\n"
        "setp.eq.u32 pr, t, 1001; @pr bra.uni B1;\n"
        "setp.eq.u32 pr, t, 1002; @pr bra.uni C0;\n"
        "setp.eq.u32 pr, t, 1003; @pr bra.uni N0;\n"
        "setp.eq.u32 pr, t, 1004; @pr bra.uni N1;\n"
        "setp.eq.u32 pr, t, 1005; @pr bra.uni N2;\n"
        "setp.eq.u32 pr, t, 1006; @pr bra.uni N3;\n"
        "trap;\n"
        "DONE:\n"
        ASM_TRC("t", 0)
        "fence.proxy.async.shared::cta;\n"
        "@pl mbarrier.arrive.shared::cta.b64 _, [sp+174984];\n"
        "}\n"
        :: "r"(sb + SM_X + c.xoff[0]), "r"(sb + SM_X + c.xoff[1]), "r"(sb + SM_Y1 + c.yoff[0][0]), "r"(sb + SM_Y1 + c.yoff[0][1]),
           "r"(sb + SM_Y1 + c.yoff[1][0]), "r"(sb + SM_Y1 + c.yoff[1][1]), "r"(c.stat), "r"(c.own), "r"(c.lane),
           "l"(prm.sel[0]), "l"(prm.sel[1]), "l"(prm.sel[2]), "r"(prm.ydesc), "f"(LN_EPS_SCALED), "f"(RSTD_SCALE)
        : "memory");
}

__device__ __forceinline__ void produce(const Producer& c, const Params& prm) {
    uint32_t B[24], C[24];
    const RowCopy rc = row_copy(prm);
    uint32_t st[8];
    uint32_t v[6][6];
    {
        uint32_t ws[6];
#pragma unroll
        for (int u = 0; u < 6; u++) {
            ws[u] = c.w[0][u];
#pragma unroll
            for (int t = 1; t < 9; t++) ws[u] = bf2_add(ws[u], c.w[t][u]);
        }
        SMARK(2);
        mbar_wait_c<0>(sb + SM_XFULL);
        SMARK(3);
        lds128(v[0], sb + SM_X + c.xoff[0] + 2 * 192);
        asm volatile("ld.shared.v2.b32 {%0,%1}, [%2];" : "=r"(v[0][4]), "=r"(v[0][5]) : "r"(sb + SM_X + c.xoff[1] + 2 * 192));
        const uint32_t p = bf2_add(bf2_fma(v[0][2], ws[2], bf2_fma(v[0][1], ws[1], bf2_mul(v[0][0], ws[0]))),
                                   bf2_fma(v[0][5], ws[5], bf2_fma(v[0][4], ws[4], bf2_mul(v[0][3], ws[3]))));
        float e = quad_sum(bf_lo(p) + bf_hi(p));
        e = (e + __shfl_xor_sync(0xffffffffu, e, 4)) * (-1.0f / CH);
        st[1] = st[3] = st[5] = st[7] = pack_bf2(e, e);
#pragma unroll
        for (int k = 0; k < NX; k++) sts32(c.own + k * SLOT_BYTES + 4, st[1]);
#pragma unroll
        for (int r = 0; r < 24; r++) C[r] = 0;
    }
#pragma unroll 1
    for (int i = loop_init<0>();; i++) {
        mbar_wait_c<0>(sb + SM_XFULL + i * SLOT_BYTES);
        SMARK(4 + i);
        load_x(v, c, sb + SM_X + i * SLOT_BYTES);
        fence_async_smem();
        if (c.warp == i) {
            named_sync(6 + i, 128);
            issue_row_load(rc, i + NX, i);
        } else {
            asm volatile("bar.arrive %0, 128;" ::"r"(6 + i) : "memory");
        }
        if (i == 2) break;
        conv_row<1, 1>(B, C, v, c);
        conv_row<0, 0>(C, st, v, c);
    }
    asm volatile(".reg .b32 pw<54>, pb<24>, pc<24>, pv<36>, ps<8>;");
    hand_over<0>(c, B, C, v);
    asm volatile("mov.b32 ps1, %0; mov.b32 ps3, %1; mov.b32 ps5, %2; mov.b32 ps7, %3;" ::"r"(st[1]), "r"(st[3]), "r"(st[5]), "r"(st[7]));
    SMARK(7);
    produce_tiles(c, prm);
    mbar_arrive_if(sb + SM_Y1FULL + ROWS_PER_CTA % NX * SLOT_BYTES, c.lane == 0);
}

struct Duty {
    const char* g;
    const char* zeros;
    long long step;
    uint32_t s, bytes;
    int end, zero;
};
__device__ __forceinline__ Duty make_duty(const Params& prm, int wg, int w) {
    const RowCopy rc = row_copy(prm);
    Duty d;
    d.g = (w == 2 ? rc.y0 : rc.x0 + (w == 0 ? rc.cut0 : w == 1 ? 32 * 192 : 192)) +
          (wg + (w == 2 ? 0 : w < 2 ? 2 * NX : 2 * NX + L2_AHEAD)) * rc.stride;
    d.step = NX * rc.stride;
    d.s = wg * SLOT_BYTES + (w == 2 ? sb + SM_Y1 : sb + SM_X + (w == 0 ? rc.cut0 : XHALF_B));
    d.bytes = w >= 2 ? TILE_BYTES : XHALF_BYTES - (w == 0 ? rc.cut0 : rc.cut1);
    d.end = w == 2 ? ROWS_PER_CTA : w < 2 ? STEPS + 1 - 2 * NX : rc.last + 1 - 2 * NX - L2_AHEAD;
    d.zero = rc.last + 1 - 2 * NX;
    d.zeros = rc.zeros;
    return d;
}

static_assert(sb + SM_Y1FULL == 174984 && sb + SM_Y1EMPTY == 174992 && sb + SM_XFULL == 174976 && SLOT_BYTES == 26624 &&
              sb + SM_GAMMA == 229248 && SM_BETA == SM_GAMMA + 768 && sb + SM_BAR + BAR_W2 * 8 == 230872 && SM_W2 == 73728, "layout");
__device__ __forceinline__ void consume(float (&acc)[2][2], uint32_t w1t, uint32_t yd, uint32_t wd, uint32_t own_slot, const Duty& d,
                                        uint32_t role, uint32_t lane, const Params& prm) {
    asm volatile(
        "{\n"
        ".reg .b32 z<32>, w<44>, p<2>, a<4>, lo<4>, hi<4>, t<2>, g<2>, q<4>, n, so, sp, ph, c, tt, cnt;\n"
        ".reg .b16 xl, xh, xr;\n"
        ".reg .b32 f0, f1;\n"
        ".reg .b64 ds<6>, wd, gp, src;\n"
        ".reg .pred pt, pf, pr, pw, pl, pe;\n"
        "setp.ne.b32 pt, 1, 0; setp.ne.b32 pf, 0, 0; setp.eq.u32 pl, %15, 0;\n"
        "mov.b32 c, 0x40D940D9;\n"
        "ldmatrix.sync.aligned.m8n8.x4.trans.shared.b16 {z0,z1,z2,z3}, [%4+22528];\n"
        "ldmatrix.sync.aligned.m8n8.x4.trans.shared.b16 {w0,w1,w2,w3}, [%4+0];\n"
        "ldmatrix.sync.aligned.m8n8.x4.trans.shared.b16 {w4,w5,w6,w7}, [%4+2048];\n"
        "ldmatrix.sync.aligned.m8n8.x4.trans.shared.b16 {w8,w9,w10,w11}, [%4+4096];\n"
        "ldmatrix.sync.aligned.m8n8.x4.trans.shared.b16 {w12,w13,w14,w15}, [%4+6144];\n"
        "ldmatrix.sync.aligned.m8n8.x4.trans.shared.b16 {w16,w17,w18,w19}, [%4+8192];\n"
        "ldmatrix.sync.aligned.m8n8.x4.trans.shared.b16 {w20,w21,w22,w23}, [%4+10240];\n"
        "ldmatrix.sync.aligned.m8n8.x4.trans.shared.b16 {w24,w25,w26,w27}, [%4+12288];\n"
        "ldmatrix.sync.aligned.m8n8.x4.trans.shared.b16 {w28,w29,w30,w31}, [%4+14336];\n"
        "ldmatrix.sync.aligned.m8n8.x4.trans.shared.b16 {w32,w33,w34,w35}, [%4+16384];\n"
        "ldmatrix.sync.aligned.m8n8.x4.trans.shared.b16 {w36,w37,w38,w39}, [%4+18432];\n"
        "ldmatrix.sync.aligned.m8n8.x4.trans.shared.b16 {w40,w41,w42,w43}, [%4+20480];\n"
        "shl.b32 f0, z0, 16; and.b32 f1, z0, 0xffff0000; cvt.rn.f16x2.f32 z0, f1, f0; shl.b32 f0, z1, 16; and.b32 f1, z1, 0xffff0000; cvt.rn.f16x2.f32 z1, f1, f0; shl.b32 f0, z2, 16; and.b32 f1, z2, 0xffff0000; cvt.rn.f16x2.f32 z2, f1, f0; shl.b32 f0, z3, 16; and.b32 f1, z3, 0xffff0000; cvt.rn.f16x2.f32 z3, f1, f0;\n"
        "stmatrix.sync.aligned.m8n8.x4.trans.shared.b16 [%4+22528], {z0,z1,z2,z3};\n"
        "shl.b32 f0, w0, 16; and.b32 f1, w0, 0xffff0000; cvt.rn.f16x2.f32 w0, f1, f0; shl.b32 f0, w1, 16; and.b32 f1, w1, 0xffff0000; cvt.rn.f16x2.f32 w1, f1, f0; shl.b32 f0, w2, 16; and.b32 f1, w2, 0xffff0000; cvt.rn.f16x2.f32 w2, f1, f0; shl.b32 f0, w3, 16; and.b32 f1, w3, 0xffff0000; cvt.rn.f16x2.f32 w3, f1, f0;\n"
        "stmatrix.sync.aligned.m8n8.x4.trans.shared.b16 [%4+0], {w0,w1,w2,w3};\n"
        "shl.b32 f0, w4, 16; and.b32 f1, w4, 0xffff0000; cvt.rn.f16x2.f32 w4, f1, f0; shl.b32 f0, w5, 16; and.b32 f1, w5, 0xffff0000; cvt.rn.f16x2.f32 w5, f1, f0; shl.b32 f0, w6, 16; and.b32 f1, w6, 0xffff0000; cvt.rn.f16x2.f32 w6, f1, f0; shl.b32 f0, w7, 16; and.b32 f1, w7, 0xffff0000; cvt.rn.f16x2.f32 w7, f1, f0;\n"
        "stmatrix.sync.aligned.m8n8.x4.trans.shared.b16 [%4+2048], {w4,w5,w6,w7};\n"
        "shl.b32 f0, w8, 16; and.b32 f1, w8, 0xffff0000; cvt.rn.f16x2.f32 w8, f1, f0; shl.b32 f0, w9, 16; and.b32 f1, w9, 0xffff0000; cvt.rn.f16x2.f32 w9, f1, f0; shl.b32 f0, w10, 16; and.b32 f1, w10, 0xffff0000; cvt.rn.f16x2.f32 w10, f1, f0; shl.b32 f0, w11, 16; and.b32 f1, w11, 0xffff0000; cvt.rn.f16x2.f32 w11, f1, f0;\n"
        "stmatrix.sync.aligned.m8n8.x4.trans.shared.b16 [%4+4096], {w8,w9,w10,w11};\n"
        "shl.b32 f0, w12, 16; and.b32 f1, w12, 0xffff0000; cvt.rn.f16x2.f32 w12, f1, f0; shl.b32 f0, w13, 16; and.b32 f1, w13, 0xffff0000; cvt.rn.f16x2.f32 w13, f1, f0; shl.b32 f0, w14, 16; and.b32 f1, w14, 0xffff0000; cvt.rn.f16x2.f32 w14, f1, f0; shl.b32 f0, w15, 16; and.b32 f1, w15, 0xffff0000; cvt.rn.f16x2.f32 w15, f1, f0;\n"
        "stmatrix.sync.aligned.m8n8.x4.trans.shared.b16 [%4+6144], {w12,w13,w14,w15};\n"
        "shl.b32 f0, w16, 16; and.b32 f1, w16, 0xffff0000; cvt.rn.f16x2.f32 w16, f1, f0; shl.b32 f0, w17, 16; and.b32 f1, w17, 0xffff0000; cvt.rn.f16x2.f32 w17, f1, f0; shl.b32 f0, w18, 16; and.b32 f1, w18, 0xffff0000; cvt.rn.f16x2.f32 w18, f1, f0; shl.b32 f0, w19, 16; and.b32 f1, w19, 0xffff0000; cvt.rn.f16x2.f32 w19, f1, f0;\n"
        "stmatrix.sync.aligned.m8n8.x4.trans.shared.b16 [%4+8192], {w16,w17,w18,w19};\n"
        "shl.b32 f0, w20, 16; and.b32 f1, w20, 0xffff0000; cvt.rn.f16x2.f32 w20, f1, f0; shl.b32 f0, w21, 16; and.b32 f1, w21, 0xffff0000; cvt.rn.f16x2.f32 w21, f1, f0; shl.b32 f0, w22, 16; and.b32 f1, w22, 0xffff0000; cvt.rn.f16x2.f32 w22, f1, f0; shl.b32 f0, w23, 16; and.b32 f1, w23, 0xffff0000; cvt.rn.f16x2.f32 w23, f1, f0;\n"
        "stmatrix.sync.aligned.m8n8.x4.trans.shared.b16 [%4+10240], {w20,w21,w22,w23};\n"
        "shl.b32 f0, w24, 16; and.b32 f1, w24, 0xffff0000; cvt.rn.f16x2.f32 w24, f1, f0; shl.b32 f0, w25, 16; and.b32 f1, w25, 0xffff0000; cvt.rn.f16x2.f32 w25, f1, f0; shl.b32 f0, w26, 16; and.b32 f1, w26, 0xffff0000; cvt.rn.f16x2.f32 w26, f1, f0; shl.b32 f0, w27, 16; and.b32 f1, w27, 0xffff0000; cvt.rn.f16x2.f32 w27, f1, f0;\n"
        "stmatrix.sync.aligned.m8n8.x4.trans.shared.b16 [%4+12288], {w24,w25,w26,w27};\n"
        "shl.b32 f0, w28, 16; and.b32 f1, w28, 0xffff0000; cvt.rn.f16x2.f32 w28, f1, f0; shl.b32 f0, w29, 16; and.b32 f1, w29, 0xffff0000; cvt.rn.f16x2.f32 w29, f1, f0; shl.b32 f0, w30, 16; and.b32 f1, w30, 0xffff0000; cvt.rn.f16x2.f32 w30, f1, f0; shl.b32 f0, w31, 16; and.b32 f1, w31, 0xffff0000; cvt.rn.f16x2.f32 w31, f1, f0;\n"
        "stmatrix.sync.aligned.m8n8.x4.trans.shared.b16 [%4+14336], {w28,w29,w30,w31};\n"
        "shl.b32 f0, w32, 16; and.b32 f1, w32, 0xffff0000; cvt.rn.f16x2.f32 w32, f1, f0; shl.b32 f0, w33, 16; and.b32 f1, w33, 0xffff0000; cvt.rn.f16x2.f32 w33, f1, f0; shl.b32 f0, w34, 16; and.b32 f1, w34, 0xffff0000; cvt.rn.f16x2.f32 w34, f1, f0; shl.b32 f0, w35, 16; and.b32 f1, w35, 0xffff0000; cvt.rn.f16x2.f32 w35, f1, f0;\n"
        "stmatrix.sync.aligned.m8n8.x4.trans.shared.b16 [%4+16384], {w32,w33,w34,w35};\n"
        "shl.b32 f0, w36, 16; and.b32 f1, w36, 0xffff0000; cvt.rn.f16x2.f32 w36, f1, f0; shl.b32 f0, w37, 16; and.b32 f1, w37, 0xffff0000; cvt.rn.f16x2.f32 w37, f1, f0; shl.b32 f0, w38, 16; and.b32 f1, w38, 0xffff0000; cvt.rn.f16x2.f32 w38, f1, f0; shl.b32 f0, w39, 16; and.b32 f1, w39, 0xffff0000; cvt.rn.f16x2.f32 w39, f1, f0;\n"
        "stmatrix.sync.aligned.m8n8.x4.trans.shared.b16 [%4+18432], {w36,w37,w38,w39};\n"
        "shl.b32 f0, w40, 16; and.b32 f1, w40, 0xffff0000; cvt.rn.f16x2.f32 w40, f1, f0; shl.b32 f0, w41, 16; and.b32 f1, w41, 0xffff0000; cvt.rn.f16x2.f32 w41, f1, f0; shl.b32 f0, w42, 16; and.b32 f1, w42, 0xffff0000; cvt.rn.f16x2.f32 w42, f1, f0; shl.b32 f0, w43, 16; and.b32 f1, w43, 0xffff0000; cvt.rn.f16x2.f32 w43, f1, f0;\n"
        "stmatrix.sync.aligned.m8n8.x4.trans.shared.b16 [%4+20480], {w40,w41,w42,w43};\n"
        "fence.proxy.async.shared::cta;\n"
        ASM_SMARK
        "mov.b32 p0, 0; mov.b32 p1, 0; mov.b32 t0, 0; mov.b32 t1, 0; mov.b32 g0, 0; mov.b32 g1, 0; mov.b32 a0, 0; mov.b32 a1, 0; mov.b32 lo0, 0; mov.b32 lo1, 0; mov.b32 hi0, 0; mov.b32 hi1, 0; mov.b32 q0, 0; mov.b32 q1, 0; mov.b32 q2, 0; mov.b32 q3, 0;\n"
        "mov.b32 z16, 0; mov.b32 z17, 0; mov.b32 z18, 0; mov.b32 z19, 0; mov.b32 z20, 0; mov.b32 z21, 0; mov.b32 z22, 0; mov.b32 z23, 0; mov.b32 z24, 0; mov.b32 z25, 0; mov.b32 z26, 0; mov.b32 z27, 0; mov.b32 z28, 0; mov.b32 z29, 0; mov.b32 z30, 0; mov.b32 z31, 0;\n"
        "mov.f32 %0, 0f00000000; mov.f32 %1, 0f00000000; mov.f32 %2, 0f00000000; mov.f32 %3, 0f00000000;\n"
        "mov.u32 n, 0; mov.u32 so, 0; mov.u32 sp, 0; mov.u32 ph, 0; mov.b64 gp, %8; mov.b64 wd, {%6, 0x40000040};\n"
        "shr.u32 tt, so, 4; add.u32 tt, tt, %5; mov.b64 ds0, {tt, 0x40000040}; mov.b64 ds4, {tt, 0x80000020};\n"
        "add.s64 ds1, ds0, 2; add.s64 ds2, ds0, 4; add.s64 ds3, ds0, 6; add.s64 ds5, ds4, 514; add.s64 ds4, ds4, 512;\n"
        "mbarrier.try_wait.parity.shared::cta.b64 pw, [so+174984], ph;\n"
        "@!pw bra.uni SPIN0;\n"
        "BACK0:\n"
        ASM_TS
        "wgmma.fence.sync.aligned;\n"
        "wgmma.mma_async.sync.aligned.m64n64k16.f16.f16.f16 {z0,z1,z2,z3,z4,z5,z6,z7,z8,z9,z10,z11,z12,z13,z14,z15}, {w0,w1,w2,w3}, ds0, pf, 1, 1, 0;\n"
        "wgmma.mma_async.sync.aligned.m64n64k16.f16.f16.f16 {z0,z1,z2,z3,z4,z5,z6,z7,z8,z9,z10,z11,z12,z13,z14,z15}, {w4,w5,w6,w7}, ds1, pt, 1, 1, 0;\n"
        "wgmma.mma_async.sync.aligned.m64n64k16.f16.f16.f16 {z0,z1,z2,z3,z4,z5,z6,z7,z8,z9,z10,z11,z12,z13,z14,z15}, {w8,w9,w10,w11}, ds2, pt, 1, 1, 0;\n"
        "wgmma.mma_async.sync.aligned.m64n64k16.f16.f16.f16 {z0,z1,z2,z3,z4,z5,z6,z7,z8,z9,z10,z11,z12,z13,z14,z15}, {w12,w13,w14,w15}, ds3, pt, 1, 1, 0;\n"
        "wgmma.mma_async.sync.aligned.m64n64k16.f16.f16.f16 {z0,z1,z2,z3,z4,z5,z6,z7,z8,z9,z10,z11,z12,z13,z14,z15}, {w16,w17,w18,w19}, ds4, pt, 1, 1, 0;\n"
        "wgmma.mma_async.sync.aligned.m64n64k16.f16.f16.f16 {z0,z1,z2,z3,z4,z5,z6,z7,z8,z9,z10,z11,z12,z13,z14,z15}, {w20,w21,w22,w23}, ds5, pt, 1, 1, 0;\n"
        "wgmma.commit_group.sync.aligned;\n"
        "LOOP:\n"
        ASM_TRC("n", 0)
        "setp.eq.u32 pr, so, %7;\n"
        "@pr bra.uni DUTY;\n"
        "TOP:\n"
        "wgmma.wait_group.sync.aligned 0;\n"
        "mov.b32 {xl, xh}, a0; tanh.approx.f16 xr, xl; cvt.u32.u16 lo0, xr; tanh.approx.f16 xr, xh; cvt.u32.u16 hi0, xr; fma.rn.f16x2 p0, z0, z0, c; mul.rn.f16x2 a1, z31, p1; fma.rn.f16x2 q3, g1, g1, q3; fma.rn.f16x2 g0, z28, t0, z28; prmt.b32 t1, lo1, hi1, 0x5410;\n"
        "B31:\n"
        "mov.b32 {xl, xh}, a1; tanh.approx.f16 xr, xl; cvt.u32.u16 lo1, xr; tanh.approx.f16 xr, xh; cvt.u32.u16 hi1, xr; fma.rn.f16x2 p1, z1, z1, c; mul.rn.f16x2 a0, z0, p0; fma.rn.f16x2 q2, g0, g0, q2; fma.rn.f16x2 g1, z29, t1, z29; prmt.b32 t0, lo0, hi0, 0x5410;\n"
        "B0:\n"
        "mov.b32 {xl, xh}, a0; tanh.approx.f16 xr, xl; cvt.u32.u16 lo0, xr; tanh.approx.f16 xr, xh; cvt.u32.u16 hi0, xr; fma.rn.f16x2 p0, z2, z2, c; mul.rn.f16x2 a1, z1, p1; fma.rn.f16x2 q3, g1, g1, q3; fma.rn.f16x2 g0, z30, t0, z30; prmt.b32 t1, lo1, hi1, 0x5410;\n"
        "B1:\n"
        "mov.b32 {xl, xh}, a1; tanh.approx.f16 xr, xl; cvt.u32.u16 lo1, xr; tanh.approx.f16 xr, xh; cvt.u32.u16 hi1, xr; fma.rn.f16x2 p1, z3, z3, c; mul.rn.f16x2 a0, z2, p0; fma.rn.f16x2 q2, g0, g0, q2; fma.rn.f16x2 g1, z31, t1, z31; prmt.b32 t0, lo0, hi0, 0x5410;\n"
        "B2:\n"
        "wgmma.fence.sync.aligned;\n"
        "wgmma.mma_async.sync.aligned.m64n64k16.f16.f16.f16 {z16,z17,z18,z19,z20,z21,z22,z23,z24,z25,z26,z27,z28,z29,z30,z31}, {w24,w25,w26,w27}, ds0, pf, 1, 1, 0;\n"
        "wgmma.mma_async.sync.aligned.m64n64k16.f16.f16.f16 {z16,z17,z18,z19,z20,z21,z22,z23,z24,z25,z26,z27,z28,z29,z30,z31}, {w28,w29,w30,w31}, ds1, pt, 1, 1, 0;\n"
        "wgmma.mma_async.sync.aligned.m64n64k16.f16.f16.f16 {z16,z17,z18,z19,z20,z21,z22,z23,z24,z25,z26,z27,z28,z29,z30,z31}, {w32,w33,w34,w35}, ds2, pt, 1, 1, 0;\n"
        "mov.b32 {xl, xh}, a0; tanh.approx.f16 xr, xl; cvt.u32.u16 lo0, xr; tanh.approx.f16 xr, xh; cvt.u32.u16 hi0, xr; fma.rn.f16x2 p0, z4, z4, c; mul.rn.f16x2 a1, z3, p1; fma.rn.f16x2 q3, g1, g1, q3; fma.rn.f16x2 g0, z0, t0, z0; prmt.b32 t1, lo1, hi1, 0x5410;\n"
        "B3:\n"
        "mov.b32 {xl, xh}, a1; tanh.approx.f16 xr, xl; cvt.u32.u16 lo1, xr; tanh.approx.f16 xr, xh; cvt.u32.u16 hi1, xr; fma.rn.f16x2 p1, z5, z5, c; mul.rn.f16x2 a0, z4, p0; fma.rn.f16x2 q0, g0, g0, q0; fma.rn.f16x2 g1, z1, t1, z1; prmt.b32 t0, lo0, hi0, 0x5410;\n"
        "B4:\n"
        "mov.b32 {xl, xh}, a0; tanh.approx.f16 xr, xl; cvt.u32.u16 lo0, xr; tanh.approx.f16 xr, xh; cvt.u32.u16 hi0, xr; fma.rn.f16x2 p0, z6, z6, c; mul.rn.f16x2 a1, z5, p1; fma.rn.f16x2 q1, g1, g1, q1; fma.rn.f16x2 g0, z2, t0, z2; prmt.b32 t1, lo1, hi1, 0x5410;\n"
        "B5:\n"
        "wgmma.mma_async.sync.aligned.m64n64k16.f16.f16.f16 {z16,z17,z18,z19,z20,z21,z22,z23,z24,z25,z26,z27,z28,z29,z30,z31}, {w36,w37,w38,w39}, ds3, pt, 1, 1, 0;\n"
        "wgmma.mma_async.sync.aligned.m64n64k16.f16.f16.f16 {z16,z17,z18,z19,z20,z21,z22,z23,z24,z25,z26,z27,z28,z29,z30,z31}, {w40,w41,w42,w43}, ds4, pt, 1, 1, 0;\n"
        "wgmma.mma_async.sync.aligned.m64n64k16.f16.f16.f16 {z16,z17,z18,z19,z20,z21,z22,z23,z24,z25,z26,z27,z28,z29,z30,z31}, wd, ds5, pt, 1, 1, 1, 0;\n"
        "wgmma.commit_group.sync.aligned;\n"
        "mov.b32 {xl, xh}, a1; tanh.approx.f16 xr, xl; cvt.u32.u16 lo1, xr; tanh.approx.f16 xr, xh; cvt.u32.u16 hi1, xr; fma.rn.f16x2 p1, z7, z7, c; mul.rn.f16x2 a0, z6, p0; fma.rn.f16x2 q0, g0, g0, q0; fma.rn.f16x2 g1, z3, t1, z3; prmt.b32 t0, lo0, hi0, 0x5410;\n"
        "B6:\n"
        "mov.u32 sp, so; add.u32 so, so, 26624; setp.eq.u32 pr, so, 79872; selp.u32 so, 0, so, pr; selp.u32 tt, 1, 0, pr; xor.b32 ph, ph, tt;\n"
        "mov.b32 {xl, xh}, a0; tanh.approx.f16 xr, xl; cvt.u32.u16 lo0, xr; tanh.approx.f16 xr, xh; cvt.u32.u16 hi0, xr; fma.rn.f16x2 p0, z8, z8, c; mul.rn.f16x2 a1, z7, p1; fma.rn.f16x2 q1, g1, g1, q1; fma.rn.f16x2 g0, z4, t0, z4; prmt.b32 t1, lo1, hi1, 0x5410;\n"
        "B7:\n"
        "shr.u32 tt, so, 4; add.u32 tt, tt, %5; mov.b64 ds0, {tt, 0x40000040}; mov.b64 ds4, {tt, 0x80000020};\n"
        "add.s64 ds1, ds0, 2; add.s64 ds2, ds0, 4; add.s64 ds3, ds0, 6; add.s64 ds5, ds4, 514; add.s64 ds4, ds4, 512;\n"
        "mov.b32 {xl, xh}, a1; tanh.approx.f16 xr, xl; cvt.u32.u16 lo1, xr; tanh.approx.f16 xr, xh; cvt.u32.u16 hi1, xr; fma.rn.f16x2 p1, z9, z9, c; mul.rn.f16x2 a0, z8, p0; fma.rn.f16x2 q0, g0, g0, q0; fma.rn.f16x2 g1, z5, t1, z5; prmt.b32 t0, lo0, hi0, 0x5410;\n"
        "B8:\n"
        "mov.b32 {xl, xh}, a0; tanh.approx.f16 xr, xl; cvt.u32.u16 lo0, xr; tanh.approx.f16 xr, xh; cvt.u32.u16 hi0, xr; fma.rn.f16x2 p0, z10, z10, c; mul.rn.f16x2 a1, z9, p1; fma.rn.f16x2 q1, g1, g1, q1; fma.rn.f16x2 g0, z6, t0, z6; prmt.b32 t1, lo1, hi1, 0x5410;\n"
        "B9:\n"
        "mov.b32 {xl, xh}, a1; tanh.approx.f16 xr, xl; cvt.u32.u16 lo1, xr; tanh.approx.f16 xr, xh; cvt.u32.u16 hi1, xr; fma.rn.f16x2 p1, z11, z11, c; mul.rn.f16x2 a0, z10, p0; fma.rn.f16x2 q0, g0, g0, q0; fma.rn.f16x2 g1, z7, t1, z7; prmt.b32 t0, lo0, hi0, 0x5410;\n"
        "B10:\n"
        "mov.b32 {xl, xh}, a0; tanh.approx.f16 xr, xl; cvt.u32.u16 lo0, xr; tanh.approx.f16 xr, xh; cvt.u32.u16 hi0, xr; fma.rn.f16x2 p0, z12, z12, c; mul.rn.f16x2 a1, z11, p1; fma.rn.f16x2 q1, g1, g1, q1; fma.rn.f16x2 g0, z8, t0, z8; prmt.b32 t1, lo1, hi1, 0x5410;\n"
        "B11:\n"
        "mov.b32 {xl, xh}, a1; tanh.approx.f16 xr, xl; cvt.u32.u16 lo1, xr; tanh.approx.f16 xr, xh; cvt.u32.u16 hi1, xr; fma.rn.f16x2 p1, z13, z13, c; mul.rn.f16x2 a0, z12, p0; fma.rn.f16x2 q0, g0, g0, q0; fma.rn.f16x2 g1, z9, t1, z9; prmt.b32 t0, lo0, hi0, 0x5410;\n"
        "B12:\n"
        "mov.b32 {xl, xh}, a0; tanh.approx.f16 xr, xl; cvt.u32.u16 lo0, xr; tanh.approx.f16 xr, xh; cvt.u32.u16 hi0, xr; fma.rn.f16x2 p0, z14, z14, c; mul.rn.f16x2 a1, z13, p1; fma.rn.f16x2 q1, g1, g1, q1; fma.rn.f16x2 g0, z10, t0, z10; prmt.b32 t1, lo1, hi1, 0x5410;\n"
        "B13:\n"
        "mov.b32 {xl, xh}, a1; tanh.approx.f16 xr, xl; cvt.u32.u16 lo1, xr; tanh.approx.f16 xr, xh; cvt.u32.u16 hi1, xr; fma.rn.f16x2 p1, z15, z15, c; mul.rn.f16x2 a0, z14, p0; fma.rn.f16x2 q0, g0, g0, q0; fma.rn.f16x2 g1, z11, t1, z11; prmt.b32 t0, lo0, hi0, 0x5410;\n"
        "B14:\n"
        "wgmma.wait_group.sync.aligned 0;\n"
        "cp.async.bulk.wait_group.read 0;\n"
        "@pl mbarrier.arrive.shared::cta.b64 _, [sp+174992];\n"
        "mov.b32 {xl, xh}, a0; tanh.approx.f16 xr, xl; cvt.u32.u16 lo0, xr; tanh.approx.f16 xr, xh; cvt.u32.u16 hi0, xr; fma.rn.f16x2 p0, z16, z16, c; mul.rn.f16x2 a1, z15, p1; fma.rn.f16x2 q1, g1, g1, q1; fma.rn.f16x2 g0, z12, t0, z12; prmt.b32 t1, lo1, hi1, 0x5410;\n"
        "B15:\n"
        "mbarrier.try_wait.parity.shared::cta.b64 pw, [so+174984], ph;\n"
        "mov.b32 {xl, xh}, a1; tanh.approx.f16 xr, xl; cvt.u32.u16 lo1, xr; tanh.approx.f16 xr, xh; cvt.u32.u16 hi1, xr; fma.rn.f16x2 p1, z17, z17, c; mul.rn.f16x2 a0, z16, p0; fma.rn.f16x2 q0, g0, g0, q0; fma.rn.f16x2 g1, z13, t1, z13; prmt.b32 t0, lo0, hi0, 0x5410;\n"
        "B16:\n"
        "mov.b32 {xl, xh}, a0; tanh.approx.f16 xr, xl; cvt.u32.u16 lo0, xr; tanh.approx.f16 xr, xh; cvt.u32.u16 hi0, xr; fma.rn.f16x2 p0, z18, z18, c; mul.rn.f16x2 a1, z17, p1; fma.rn.f16x2 q1, g1, g1, q1; fma.rn.f16x2 g0, z14, t0, z14; prmt.b32 t1, lo1, hi1, 0x5410;\n"
        "B17:\n"
        "mov.b32 {xl, xh}, a1; tanh.approx.f16 xr, xl; cvt.u32.u16 lo1, xr; tanh.approx.f16 xr, xh; cvt.u32.u16 hi1, xr; fma.rn.f16x2 p1, z19, z19, c; mul.rn.f16x2 a0, z18, p0; fma.rn.f16x2 q0, g0, g0, q0; fma.rn.f16x2 g1, z15, t1, z15; prmt.b32 t0, lo0, hi0, 0x5410;\n"
        "B18:\n"
        "@!pw bra.uni SPIN;\n"
        "BACK:\n"
        "wgmma.fence.sync.aligned;\n"
        "wgmma.mma_async.sync.aligned.m64n64k16.f16.f16.f16 {z0,z1,z2,z3,z4,z5,z6,z7,z8,z9,z10,z11,z12,z13,z14,z15}, {w0,w1,w2,w3}, ds0, pf, 1, 1, 0;\n"
        "wgmma.mma_async.sync.aligned.m64n64k16.f16.f16.f16 {z0,z1,z2,z3,z4,z5,z6,z7,z8,z9,z10,z11,z12,z13,z14,z15}, {w4,w5,w6,w7}, ds1, pt, 1, 1, 0;\n"
        "wgmma.mma_async.sync.aligned.m64n64k16.f16.f16.f16 {z0,z1,z2,z3,z4,z5,z6,z7,z8,z9,z10,z11,z12,z13,z14,z15}, {w8,w9,w10,w11}, ds2, pt, 1, 1, 0;\n"
        "mov.b32 {xl, xh}, a0; tanh.approx.f16 xr, xl; cvt.u32.u16 lo0, xr; tanh.approx.f16 xr, xh; cvt.u32.u16 hi0, xr; fma.rn.f16x2 p0, z20, z20, c; mul.rn.f16x2 a1, z19, p1; fma.rn.f16x2 q1, g1, g1, q1; fma.rn.f16x2 g0, z16, t0, z16; prmt.b32 t1, lo1, hi1, 0x5410;\n"
        "B19:\n"
        "mov.b32 {xl, xh}, a1; tanh.approx.f16 xr, xl; cvt.u32.u16 lo1, xr; tanh.approx.f16 xr, xh; cvt.u32.u16 hi1, xr; fma.rn.f16x2 p1, z21, z21, c; mul.rn.f16x2 a0, z20, p0; fma.rn.f16x2 q2, g0, g0, q2; fma.rn.f16x2 g1, z17, t1, z17; prmt.b32 t0, lo0, hi0, 0x5410;\n"
        "B20:\n"
        "mov.b32 {xl, xh}, a0; tanh.approx.f16 xr, xl; cvt.u32.u16 lo0, xr; tanh.approx.f16 xr, xh; cvt.u32.u16 hi0, xr; fma.rn.f16x2 p0, z22, z22, c; mul.rn.f16x2 a1, z21, p1; fma.rn.f16x2 q3, g1, g1, q3; fma.rn.f16x2 g0, z18, t0, z18; prmt.b32 t1, lo1, hi1, 0x5410;\n"
        "B21:\n"
        "wgmma.mma_async.sync.aligned.m64n64k16.f16.f16.f16 {z0,z1,z2,z3,z4,z5,z6,z7,z8,z9,z10,z11,z12,z13,z14,z15}, {w12,w13,w14,w15}, ds3, pt, 1, 1, 0;\n"
        "wgmma.mma_async.sync.aligned.m64n64k16.f16.f16.f16 {z0,z1,z2,z3,z4,z5,z6,z7,z8,z9,z10,z11,z12,z13,z14,z15}, {w16,w17,w18,w19}, ds4, pt, 1, 1, 0;\n"
        "wgmma.mma_async.sync.aligned.m64n64k16.f16.f16.f16 {z0,z1,z2,z3,z4,z5,z6,z7,z8,z9,z10,z11,z12,z13,z14,z15}, {w20,w21,w22,w23}, ds5, pt, 1, 1, 0;\n"
        "wgmma.commit_group.sync.aligned;\n"
        "mov.b32 {xl, xh}, a1; tanh.approx.f16 xr, xl; cvt.u32.u16 lo1, xr; tanh.approx.f16 xr, xh; cvt.u32.u16 hi1, xr; fma.rn.f16x2 p1, z23, z23, c; mul.rn.f16x2 a0, z22, p0; fma.rn.f16x2 q2, g0, g0, q2; fma.rn.f16x2 g1, z19, t1, z19; prmt.b32 t0, lo0, hi0, 0x5410;\n"
        "B22:\n"
        "mov.b32 {xl, xh}, a0; tanh.approx.f16 xr, xl; cvt.u32.u16 lo0, xr; tanh.approx.f16 xr, xh; cvt.u32.u16 hi0, xr; fma.rn.f16x2 p0, z24, z24, c; mul.rn.f16x2 a1, z23, p1; fma.rn.f16x2 q3, g1, g1, q3; fma.rn.f16x2 g0, z20, t0, z20; prmt.b32 t1, lo1, hi1, 0x5410;\n"
        "B23:\n"
        "mov.b32 {xl, xh}, a1; tanh.approx.f16 xr, xl; cvt.u32.u16 lo1, xr; tanh.approx.f16 xr, xh; cvt.u32.u16 hi1, xr; fma.rn.f16x2 p1, z25, z25, c; mul.rn.f16x2 a0, z24, p0; fma.rn.f16x2 q2, g0, g0, q2; fma.rn.f16x2 g1, z21, t1, z21; prmt.b32 t0, lo0, hi0, 0x5410;\n"
        "B24:\n"
        "mov.b32 {xl, xh}, a0; tanh.approx.f16 xr, xl; cvt.u32.u16 lo0, xr; tanh.approx.f16 xr, xh; cvt.u32.u16 hi0, xr; fma.rn.f16x2 p0, z26, z26, c; mul.rn.f16x2 a1, z25, p1; fma.rn.f16x2 q3, g1, g1, q3; fma.rn.f16x2 g0, z22, t0, z22; prmt.b32 t1, lo1, hi1, 0x5410;\n"
        "B25:\n"
        "mov.b32 {xl, xh}, a1; tanh.approx.f16 xr, xl; cvt.u32.u16 lo1, xr; tanh.approx.f16 xr, xh; cvt.u32.u16 hi1, xr; fma.rn.f16x2 p1, z27, z27, c; mul.rn.f16x2 a0, z26, p0; fma.rn.f16x2 q2, g0, g0, q2; fma.rn.f16x2 g1, z23, t1, z23; prmt.b32 t0, lo0, hi0, 0x5410;\n"
        "B26:\n"
        "mov.b32 {xl, xh}, a0; tanh.approx.f16 xr, xl; cvt.u32.u16 lo0, xr; tanh.approx.f16 xr, xh; cvt.u32.u16 hi0, xr; fma.rn.f16x2 p0, z28, z28, c; mul.rn.f16x2 a1, z27, p1; fma.rn.f16x2 q3, g1, g1, q3; fma.rn.f16x2 g0, z24, t0, z24; prmt.b32 t1, lo1, hi1, 0x5410;\n"
        "B27:\n"
        "add.u32 n, n, 1; setp.lt.u32 pe, n, 32;\n"
        "mov.b32 {xl, xh}, a1; tanh.approx.f16 xr, xl; cvt.u32.u16 lo1, xr; tanh.approx.f16 xr, xh; cvt.u32.u16 hi1, xr; fma.rn.f16x2 p1, z29, z29, c; mul.rn.f16x2 a0, z28, p0; fma.rn.f16x2 q2, g0, g0, q2; fma.rn.f16x2 g1, z25, t1, z25; prmt.b32 t0, lo0, hi0, 0x5410;\n"
        "B28:\n"
        "mov.b32 {xl, xh}, a0; tanh.approx.f16 xr, xl; cvt.u32.u16 lo0, xr; tanh.approx.f16 xr, xh; cvt.u32.u16 hi0, xr; fma.rn.f16x2 p0, z30, z30, c; mul.rn.f16x2 a1, z29, p1; fma.rn.f16x2 q3, g1, g1, q3; fma.rn.f16x2 g0, z26, t0, z26; prmt.b32 t1, lo1, hi1, 0x5410;\n"
        "B29:\n"
        "mov.b32 {xl, xh}, a1; tanh.approx.f16 xr, xl; cvt.u32.u16 lo1, xr; tanh.approx.f16 xr, xh; cvt.u32.u16 hi1, xr; fma.rn.f16x2 p1, z31, z31, c; mul.rn.f16x2 a0, z30, p0; fma.rn.f16x2 q2, g0, g0, q2; fma.rn.f16x2 g1, z27, t1, z27; prmt.b32 t0, lo0, hi0, 0x5410;\n"
        "@pe bra.uni LOOP;\n"
        "bra.uni DONE;\n"
        "SPIN0: mov.u32 cnt, 0;\n"
        ASM_TRC("n", 1)
        "SPIN0L:\n"
        "mbarrier.try_wait.parity.shared::cta.b64 pw, [so+174984], ph;\n"
        "@pw bra.uni BACK0;\n"
        "add.u32 cnt, cnt, 1; setp.lt.u32 pw, cnt, 0x100000;\n"
        "@pw bra.uni SPIN0L;\n"
        "trap;\n"
        "SPIN: mov.u32 cnt, 0;\n"
        ASM_TRC("n", 1)
        "SPINL:\n"
        "mbarrier.try_wait.parity.shared::cta.b64 pw, [so+174984], ph;\n"
        "@pw bra.uni BACK;\n"
        "add.u32 cnt, cnt, 1; setp.lt.u32 pw, cnt, 0x100000;\n"
        "@pw bra.uni SPINL;\n"
        "trap;\n"
        "DUTY:\n"
        "setp.ge.s32 pr, n, %11;\n"
        "@pr bra.uni FLUSH;\n"
        "setp.ge.u32 pr, %13, 2;\n"
        "@pr bra.uni ROLE2;\n"
        "setp.ge.s32 pr, n, %12; selp.b64 src, %14, gp, pr; add.u32 tt, %7, 174976;\n"
        "elect.sync _|pr, 0xffffffff;\n"
        "@pr mbarrier.arrive.expect_tx.shared::cta.b64 _, [tt], %10;\n"
        "@pr cp.async.bulk.shared::cluster.global.mbarrier::complete_tx::bytes [%9], [src], %10, [tt];\n"
        "bra.uni FLUSH;\n"
        "ROLE2:\n"
        "setp.eq.u32 pr, %13, 3;\n"
        "@pr bra.uni ROLE3;\n"
        "elect.sync _|pr, 0xffffffff;\n"
        "@pr cp.async.bulk.global.shared::cta.bulk_group [gp], [%9], 12288;\n"
        "@pr cp.async.bulk.commit_group;\n"
        "bra.uni FLUSH;\n"
        "ROLE3:\n"
        "setp.ne.s32 pr, n, 8;\n"
        "@pr bra.uni AHEAD;\n"
        "mov.u32 tt, 230872;\n"
        "elect.sync _|pr, 0xffffffff;\n"
        "@pr mbarrier.arrive.expect_tx.shared::cta.b64 _, [tt], 75264;\n"
        "mov.u32 cnt, 229248; @pr cp.async.bulk.shared::cluster.global.mbarrier::complete_tx::bytes [cnt], [%18], 768, [tt];\n"
        "mov.u32 cnt, 230016; @pr cp.async.bulk.shared::cluster.global.mbarrier::complete_tx::bytes [cnt], [%19], 768, [tt];\n"
        "mov.u32 cnt, 74752; @pr cp.async.bulk.tensor.2d.shared::cluster.global.mbarrier::complete_tx::bytes [cnt], [%17, {0, 0}], [tt];\n"
        "mov.u32 cnt, 87040; @pr cp.async.bulk.tensor.2d.shared::cluster.global.mbarrier::complete_tx::bytes [cnt], [%17, {0, 192}], [tt];\n"
        "mov.u32 cnt, 99328; @pr cp.async.bulk.tensor.2d.shared::cluster.global.mbarrier::complete_tx::bytes [cnt], [%17, {32, 0}], [tt];\n"
        "mov.u32 cnt, 111616; @pr cp.async.bulk.tensor.2d.shared::cluster.global.mbarrier::complete_tx::bytes [cnt], [%17, {32, 192}], [tt];\n"
        "mov.u32 cnt, 123904; @pr cp.async.bulk.tensor.2d.shared::cluster.global.mbarrier::complete_tx::bytes [cnt], [%17, {64, 0}], [tt];\n"
        "mov.u32 cnt, 136192; @pr cp.async.bulk.tensor.2d.shared::cluster.global.mbarrier::complete_tx::bytes [cnt], [%17, {64, 192}], [tt];\n"
        "AHEAD:\n"
        "elect.sync _|pr, 0xffffffff;\n"
        "@pr cp.async.bulk.prefetch.L2.global [gp], 12288;\n"
        "FLUSH:\n"
        "add.s64 gp, gp, %16;\n"
        "mov.b32 {xl, xh}, q0; cvt.f32.f16 f0, xl; cvt.f32.f16 f1, xh; add.f32 f0, f0, f1; add.f32 %0, %0, f0; mov.b32 q0, 0;\n"
        "mov.b32 {xl, xh}, q1; cvt.f32.f16 f0, xl; cvt.f32.f16 f1, xh; add.f32 f0, f0, f1; add.f32 %1, %1, f0; mov.b32 q1, 0;\n"
        "mov.b32 {xl, xh}, q2; cvt.f32.f16 f0, xl; cvt.f32.f16 f1, xh; add.f32 f0, f0, f1; add.f32 %2, %2, f0; mov.b32 q2, 0;\n"
        "mov.b32 {xl, xh}, q3; cvt.f32.f16 f0, xl; cvt.f32.f16 f1, xh; add.f32 f0, f0, f1; add.f32 %3, %3, f0; mov.b32 q3, 0;\n"
        "setp.ne.u32 pr, %5, 0;\n"
        "@pr bra.uni TOP;\n"
        "wgmma.wait_group.sync.aligned 0;\n"
        "wgmma.fence.sync.aligned;\n"
        "setp.eq.u32 pr, n, 1000; @pr bra.uni B31;\n"
        "setp.eq.u32 pr, n, 1001; @pr bra.uni B0;\n"
        "setp.eq.u32 pr, n, 1002; @pr bra.uni B1;\n"
        "setp.eq.u32 pr, n, 1003; @pr bra.uni B2;\n"
        "setp.eq.u32 pr, n, 1004; @pr bra.uni B3;\n"
        "setp.eq.u32 pr, n, 1005; @pr bra.uni B4;\n"
        "setp.eq.u32 pr, n, 1006; @pr bra.uni B5;\n"
        "setp.eq.u32 pr, n, 1007; @pr bra.uni B6;\n"
        "setp.eq.u32 pr, n, 1008; @pr bra.uni B7;\n"
        "setp.eq.u32 pr, n, 1009; @pr bra.uni B8;\n"
        "setp.eq.u32 pr, n, 1010; @pr bra.uni B9;\n"
        "setp.eq.u32 pr, n, 1011; @pr bra.uni B10;\n"
        "setp.eq.u32 pr, n, 1012; @pr bra.uni B11;\n"
        "setp.eq.u32 pr, n, 1013; @pr bra.uni B12;\n"
        "setp.eq.u32 pr, n, 1014; @pr bra.uni B13;\n"
        "setp.eq.u32 pr, n, 1015; @pr bra.uni B14;\n"
        "setp.eq.u32 pr, n, 1016; @pr bra.uni B15;\n"
        "setp.eq.u32 pr, n, 1017; @pr bra.uni B16;\n"
        "setp.eq.u32 pr, n, 1018; @pr bra.uni B17;\n"
        "setp.eq.u32 pr, n, 1019; @pr bra.uni B18;\n"
        "setp.eq.u32 pr, n, 1020; @pr bra.uni B19;\n"
        "setp.eq.u32 pr, n, 1021; @pr bra.uni B20;\n"
        "setp.eq.u32 pr, n, 1022; @pr bra.uni B21;\n"
        "setp.eq.u32 pr, n, 1023; @pr bra.uni B22;\n"
        "setp.eq.u32 pr, n, 1024; @pr bra.uni B23;\n"
        "setp.eq.u32 pr, n, 1025; @pr bra.uni B24;\n"
        "setp.eq.u32 pr, n, 1026; @pr bra.uni B25;\n"
        "setp.eq.u32 pr, n, 1027; @pr bra.uni B26;\n"
        "setp.eq.u32 pr, n, 1028; @pr bra.uni B27;\n"
        "setp.eq.u32 pr, n, 1029; @pr bra.uni B28;\n"
        "setp.eq.u32 pr, n, 1030; @pr bra.uni B29;\n"
        "trap;\n"
        "DONE:\n"
        ASM_TRC("n", 0)
        "mov.b32 {xl, xh}, a0; tanh.approx.f16 xr, xl; cvt.u32.u16 lo0, xr; tanh.approx.f16 xr, xh; cvt.u32.u16 hi0, xr; mul.rn.f16x2 a1, z31, p1; fma.rn.f16x2 q3, g1, g1, q3; fma.rn.f16x2 g0, z28, t0, z28; prmt.b32 t1, lo1, hi1, 0x5410;\n"
        "mov.b32 {xl, xh}, a1; tanh.approx.f16 xr, xl; cvt.u32.u16 lo1, xr; tanh.approx.f16 xr, xh; cvt.u32.u16 hi1, xr; fma.rn.f16x2 q2, g0, g0, q2; fma.rn.f16x2 g1, z29, t1, z29; prmt.b32 t0, lo0, hi0, 0x5410;\n"
        "fma.rn.f16x2 q3, g1, g1, q3; fma.rn.f16x2 g0, z30, t0, z30; prmt.b32 t1, lo1, hi1, 0x5410;\n"
        "fma.rn.f16x2 q2, g0, g0, q2; fma.rn.f16x2 g1, z31, t1, z31;\n"
        "fma.rn.f16x2 q3, g1, g1, q3;\n"
        "mov.b32 {xl, xh}, q0; cvt.f32.f16 f0, xl; cvt.f32.f16 f1, xh; add.f32 f0, f0, f1; add.f32 %0, %0, f0; mov.b32 q0, 0;\n"
        "mov.b32 {xl, xh}, q1; cvt.f32.f16 f0, xl; cvt.f32.f16 f1, xh; add.f32 f0, f0, f1; add.f32 %1, %1, f0; mov.b32 q1, 0;\n"
        "mov.b32 {xl, xh}, q2; cvt.f32.f16 f0, xl; cvt.f32.f16 f1, xh; add.f32 f0, f0, f1; add.f32 %2, %2, f0; mov.b32 q2, 0;\n"
        "mov.b32 {xl, xh}, q3; cvt.f32.f16 f0, xl; cvt.f32.f16 f1, xh; add.f32 f0, f0, f1; add.f32 %3, %3, f0; mov.b32 q3, 0;\n"
        "wgmma.wait_group.sync.aligned 0;\n"
        "}\n"
        : "=f"(acc[0][0]), "=f"(acc[0][1]), "=f"(acc[1][0]), "=f"(acc[1][1])
        : "r"(w1t), "r"(yd), "r"(wd), "r"(own_slot), "l"(d.g), "r"(d.s), "r"(d.bytes), "r"(d.end), "r"(d.zero), "r"(role),
          "l"(d.zeros), "r"(lane), "l"(d.step), "l"(&prm.w2_map), "l"(prm.gamma), "l"(prm.beta)
        : "memory");
}
template <int M, bool LAST_SMEM = true>
__device__ __forceinline__ void gemm1_t(uint32_t (&d)[16], const uint32_t* wa, uint32_t yd, uint32_t wd) {
    wg_fence();
    wgmma_n64_h_set<0>(d, wa, desc<1024, 1>(yd, 0));
#pragma unroll
    for (int kk = 1; kk < (LAST_SMEM ? 5 : 6); kk++)
        wgmma_n64_h_acc<0>(d, wa + kk * 4, kk < 4 ? desc<1024, 1>(yd, kk * 32) : desc<512, 2>(yd, 8192 + (kk - 4) * 32));
    if (LAST_SMEM) wgmma_n64_h_acc_ss(d, desc<1024, 1>(wd, M * 12288), desc<512, 2>(yd, 8192 + 32));
    wg_commit();
}

#define GTAIL 0
__device__ __forceinline__ void gelu_sumsq_h(uint32_t (&d)[16], uint32_t (&q)[2], uint32_t key) {
#pragma unroll
    for (int r = 0; r < 16; r++) {
        if (GTAIL && r == 16 - GTAIL) sched_fence<GTAIL ? GTAIL : 2>(d + r, key);
        const uint32_t gv = gelu2(d[r]);
        q[r & 1] = h2_fma(gv, gv, q[r & 1]);
    }
}
__device__ __forceinline__ void flush_sumsq(uint32_t (&q)[2], float (&acc)[2]) {
#pragma unroll
    for (int h = 0; h < 2; h++) {
        float lo, hi;
        h2_unpack(q[h], lo, hi);
        acc[h] += lo + hi;
        q[h] = 0;
    }
}
__device__ __forceinline__ void gelu_sumsq_f(const uint32_t (&d)[16], float (&acc)[2]) {
#pragma unroll
    for (int r = 0; r < 16; r++) {
        float lo, hi;
        h2_unpack(gelu2(d[r]), lo, hi);
        acc[r & 1] = fmaf(lo, lo, acc[r & 1]);
        acc[r & 1] = fmaf(hi, hi, acc[r & 1]);
    }
}
__device__ __forceinline__ void load_w1t(uint32_t (&wa)[2][24], int wg, int w, int lane) {
#pragma unroll
    for (int m = 0; m < 2; m++)
#pragma unroll
        for (int kk = 0; kk < 5; kk++) {
            const int q = lane >> 3, c = 16 * kk + 8 * (q >> 1) + (lane & 7), ck = 2 * w + (q & 1);
            ldsm4_t(wa[m] + kk * 4, sb + SM_W1 + (2 * wg + m) * 12288 + c * 128 + ((ck ^ (c & 7)) * 16));
        }
}
__device__ __forceinline__ unsigned long long* acc_word(const Params& prm, uint32_t epoch, uint32_t e) {
    return &prm.g->acc[epoch & 1][(e >> 2) * 32 + (e & 3)];
}
__device__ __forceinline__ void publish_fast(const Params& prm, const float (&acc)[2][2], uint32_t epoch, int wg, int w, int lane) {
    const bool m = lane & 2, h = lane & 1;
    const float a = (m ? acc[1][0] : acc[0][0]) + __shfl_xor_sync(0xffffffffu, m ? acc[0][0] : acc[1][0], 2);
    const float b = (m ? acc[1][1] : acc[0][1]) + __shfl_xor_sync(0xffffffffu, m ? acc[0][1] : acc[1][1], 2);
    const float v = (h ? b : a) + __shfl_xor_sync(0xffffffffu, h ? a : b, 1);
    const unsigned long long q = (__float2ull_rn(fminf(v, ACC_LIMIT) * 0x1p16f) << 8) + 1;
    asm volatile("red.relaxed.gpu.global.add.u64 [%0], %1;"
                 ::"l"(acc_word(prm, epoch, 128 * wg + 32 * (lane & 2) + 16 * w + (lane >> 2) + 8 * (lane & 1))), "l"(q) : "memory");
}
__device__ __forceinline__ float collect_fast(const unsigned long long* word) {
    unsigned long long v;
    asm volatile(
        "{\n.reg .pred p;\n.reg .u32 n, lo, hi;\nmov.u32 n, 0;\n"
        "POLL:\nld.relaxed.gpu.global.u64 %0, [%1];\nmov.b64 {lo, hi}, %0;\nand.b32 lo, lo, 255;\n"
        "setp.eq.u32 p, lo, %2;\nvote.sync.all.pred p, p, 0xffffffff;\n@p bra.uni POLL_DONE;\n"
        "add.u32 n, n, 1;\nsetp.lt.u32 p, n, 0x400000;\n@p bra.uni POLL;\ntrap;\nPOLL_DONE:\n}\n"
        : "=l"(v) : "l"(word), "n"(NUM_CTAS) : "memory");
    return __ull2float_rn(v >> 8) * 0x1p-16f;
}
__device__ __forceinline__ void publish_sums(const float (&acc)[2][2], float* sums, unsigned int* counter, int wg, int w, int lane) {
#pragma unroll
    for (int m = 0; m < 2; m++)
#pragma unroll
        for (int h = 0; h < 2; h++) {
            const float v = quad_sum(acc[m][h]);
            if ((lane & 3) == 0) atomicAdd(sums + 64 * (2 * wg + m) + 16 * w + (lane >> 2) + 8 * h, v);
        }
    named_sync(1, 384);
    if (fresh_tid() == 0) asm volatile("red.release.gpu.global.add.u32 [%0], 1;" ::"l"(counter) : "memory");
}
__device__ __forceinline__ void grid_wait(const unsigned int* counter, unsigned int target) {
    if (fresh_tid() == 0) {
        unsigned int v, spins = 0;
        do {
            asm volatile("ld.acquire.gpu.global.u32 %0, [%1];" : "=r"(v) : "l"(counter) : "memory");
            if (++spins > (1u << 22)) __trap();
        } while ((int)(v - target) < 0);
    }
    __syncthreads();
}

struct Pass2 {
    uint32_t wg;
    uint32_t off;
    int step;
    uint32_t xs;
    uint32_t a_offs, xs_offs, bias_addr, out_scale;
    uint32_t w;
};

static_assert(sb + SM_BAR + BAR_Y2FULL * 8 == 230800 && sb + SM_BAR + BAR_XSFULL * 8 == 230832, "layout");
__device__ __forceinline__ void first_gemm(uint32_t tile, uint32_t offs, uint32_t w1d) {
    asm volatile(
        "{\n"
        ".reg .b32 t<2>, ad;\n"
        ".reg .b64 w1d, dt;\n"
        ".reg .pred pt, pf;\n"
        "setp.ne.b32 pt, 1, 0; setp.ne.b32 pf, 0, 0; mov.b64 w1d, {%2, 0x40000040};\n"
        "and.b32 t0, %1, 0xffff; shr.u32 t1, %1, 16;\n"
        "xor.b32 ad, t0, 0; add.u32 ad, ad, %0; ldmatrix.sync.aligned.m8n8.x4.shared.b16 {qa0,qa1,qa2,qa3}, [ad];\n"
        "xor.b32 ad, t0, 32; add.u32 ad, ad, %0; ldmatrix.sync.aligned.m8n8.x4.shared.b16 {qa4,qa5,qa6,qa7}, [ad];\n"
        "xor.b32 ad, t0, 64; add.u32 ad, ad, %0; ldmatrix.sync.aligned.m8n8.x4.shared.b16 {qa8,qa9,qa10,qa11}, [ad];\n"
        "xor.b32 ad, t0, 96; add.u32 ad, ad, %0; ldmatrix.sync.aligned.m8n8.x4.shared.b16 {qa12,qa13,qa14,qa15}, [ad];\n"
        "xor.b32 ad, t1, 0; add.u32 ad, ad, %0; ldmatrix.sync.aligned.m8n8.x4.shared.b16 {qa16,qa17,qa18,qa19}, [ad];\n"
        "xor.b32 ad, t1, 32; add.u32 ad, ad, %0; ldmatrix.sync.aligned.m8n8.x4.shared.b16 {qa20,qa21,qa22,qa23}, [ad];\n"
        "wgmma.fence.sync.aligned;\n"
        "add.s64 dt, w1d, 0; wgmma.mma_async.sync.aligned.m64n64k16.f16.f16.f16 {qz0,qz1,qz2,qz3,qz4,qz5,qz6,qz7,qz8,qz9,qz10,qz11,qz12,qz13,qz14,qz15}, {qa0,qa1,qa2,qa3}, dt, pf, 1, 1, 1;\n"
        "add.s64 dt, w1d, 128; wgmma.mma_async.sync.aligned.m64n64k16.f16.f16.f16 {qz0,qz1,qz2,qz3,qz4,qz5,qz6,qz7,qz8,qz9,qz10,qz11,qz12,qz13,qz14,qz15}, {qa4,qa5,qa6,qa7}, dt, pt, 1, 1, 1;\n"
        "add.s64 dt, w1d, 256; wgmma.mma_async.sync.aligned.m64n64k16.f16.f16.f16 {qz0,qz1,qz2,qz3,qz4,qz5,qz6,qz7,qz8,qz9,qz10,qz11,qz12,qz13,qz14,qz15}, {qa8,qa9,qa10,qa11}, dt, pt, 1, 1, 1;\n"
        "add.s64 dt, w1d, 384; wgmma.mma_async.sync.aligned.m64n64k16.f16.f16.f16 {qz0,qz1,qz2,qz3,qz4,qz5,qz6,qz7,qz8,qz9,qz10,qz11,qz12,qz13,qz14,qz15}, {qa12,qa13,qa14,qa15}, dt, pt, 1, 1, 1;\n"
        "add.s64 dt, w1d, 512; wgmma.mma_async.sync.aligned.m64n64k16.f16.f16.f16 {qz0,qz1,qz2,qz3,qz4,qz5,qz6,qz7,qz8,qz9,qz10,qz11,qz12,qz13,qz14,qz15}, {qa16,qa17,qa18,qa19}, dt, pt, 1, 1, 1;\n"
        "add.s64 dt, w1d, 640; wgmma.mma_async.sync.aligned.m64n64k16.f16.f16.f16 {qz0,qz1,qz2,qz3,qz4,qz5,qz6,qz7,qz8,qz9,qz10,qz11,qz12,qz13,qz14,qz15}, {qa20,qa21,qa22,qa23}, dt, pt, 1, 1, 1;\n"
        "wgmma.commit_group.sync.aligned;\n"
        "}\n"
        :: "r"(tile), "r"(offs), "r"(w1d) : "memory");
}
__device__ __forceinline__ void pass2_tiles(const Pass2& c, const Params& prm) {
    asm volatile(
        "{\n"
        ".reg .b32 o<24>, g<16>, p<2>, a<2>, lo<2>, hi<2>, h<2>, v<8>, n, off, c, tt, ad, cnt, ybar, xbar, tbar, tpar, id;\n"
        ".reg .b16 xl, xh, xr;\n"
        ".reg .f32 f0, f1;\n"
        ".reg .b64 w1d, w2d, dt, gp, pol;\n"
        ".reg .pred pt, pf, pr, pw, pl, pk, pm, pz, pn;\n"
        "setp.ne.b32 pt, 1, 0; setp.ne.b32 pf, 0, 0; setp.eq.u32 pl, %9, 0; setp.eq.u32 pk, %9, 0; setp.eq.u32 pz, %0, 0;\n"
        "mov.b32 c, 0x40D940D9;\n"
        "mov.b64 w1d, {%0, 0x40000040}; mov.b64 w2d, {%1, 0x80000020};\n"
        "mad.lo.u32 ybar, %2, 8, 230800; mad.lo.u32 xbar, %2, 8, 230832; add.u32 id, %2, 2;\n"
        "xor.b32 tt, %2, 0; mad.lo.u32 tbar, tt, 64, 230888; setp.eq.u32 pr, tt, 0; selp.u32 tpar, 1, 0, pr; mov.u32 tt, %laneid; setp.eq.u32 pn, tt, 0;\n"
        "mov.u32 n, -1; add.u32 off, %3, %12; mov.pred pm, pt; mov.b64 pol, 0x12F0000000000000;\n"
        "wgmma.wait_group.sync.aligned 0;\n"
        "ld.shared.v4.b32 {o0,o1,o2,o3}, [%7+0];\n"
        "ld.shared.v4.b32 {o4,o5,o6,o7}, [%7+64];\n"
        "ld.shared.v4.b32 {o8,o9,o10,o11}, [%7+128];\n"
        "ld.shared.v4.b32 {o12,o13,o14,o15}, [%7+192];\n"
        "ld.shared.v4.b32 {o16,o17,o18,o19}, [%7+256];\n"
        "ld.shared.v4.b32 {o20,o21,o22,o23}, [%7+320];\n"
        "fma.rn.f16x2 p0, qz0, qz0, c;\n"
        "fma.rn.f16x2 p1, qz1, qz1, c; mul.rn.f16x2 a0, qz0, p0;\n"
        "mov.b32 {xl, xh}, a0; tanh.approx.f16 xr, xl; cvt.u32.u16 lo0, xr; tanh.approx.f16 xr, xh; cvt.u32.u16 hi0, xr; fma.rn.f16x2 p0, qz2, qz2, c; mul.rn.f16x2 a1, qz1, p1;\n"
        "mov.b32 {xl, xh}, a1; tanh.approx.f16 xr, xl; cvt.u32.u16 lo1, xr; tanh.approx.f16 xr, xh; cvt.u32.u16 hi1, xr; fma.rn.f16x2 p1, qz3, qz3, c; mul.rn.f16x2 a0, qz2, p0; prmt.b32 h0, lo0, hi0, 0x5410;\n"
        "mov.b32 {xl, xh}, a0; tanh.approx.f16 xr, xl; cvt.u32.u16 lo0, xr; tanh.approx.f16 xr, xh; cvt.u32.u16 hi0, xr; fma.rn.f16x2 p0, qz4, qz4, c; mul.rn.f16x2 a1, qz3, p1; fma.rn.f16x2 g0, qz0, h0, qz0; prmt.b32 h1, lo1, hi1, 0x5410;\n"
        "mov.b32 {xl, xh}, a1; tanh.approx.f16 xr, xl; cvt.u32.u16 lo1, xr; tanh.approx.f16 xr, xh; cvt.u32.u16 hi1, xr; fma.rn.f16x2 p1, qz5, qz5, c; mul.rn.f16x2 a0, qz4, p0; fma.rn.f16x2 g1, qz1, h1, qz1; prmt.b32 h0, lo0, hi0, 0x5410;\n"
        "mov.b32 {xl, xh}, a0; tanh.approx.f16 xr, xl; cvt.u32.u16 lo0, xr; tanh.approx.f16 xr, xh; cvt.u32.u16 hi0, xr; fma.rn.f16x2 p0, qz6, qz6, c; mul.rn.f16x2 a1, qz5, p1; fma.rn.f16x2 g2, qz2, h0, qz2; prmt.b32 h1, lo1, hi1, 0x5410;\n"
        "mov.b32 {xl, xh}, a1; tanh.approx.f16 xr, xl; cvt.u32.u16 lo1, xr; tanh.approx.f16 xr, xh; cvt.u32.u16 hi1, xr; fma.rn.f16x2 p1, qz7, qz7, c; mul.rn.f16x2 a0, qz6, p0; fma.rn.f16x2 g3, qz3, h1, qz3; prmt.b32 h0, lo0, hi0, 0x5410;\n"
        "mov.b32 v0, 0; mov.b32 v1, 0; mov.b32 v2, 0; mov.b32 v3, 0; mov.b32 v4, 0; mov.b32 v5, 0; mov.b32 v6, 0; mov.b32 v7, 0;\n"
        "LOOP:\n"
        "@!pm bra.uni SKIP0;\n"
        "wgmma.fence.sync.aligned;\n"
        "add.s64 dt, w1d, 768; wgmma.mma_async.sync.aligned.m64n64k16.f16.f16.f16 {qz16,qz17,qz18,qz19,qz20,qz21,qz22,qz23,qz24,qz25,qz26,qz27,qz28,qz29,qz30,qz31}, {qa0,qa1,qa2,qa3}, dt, pf, 1, 1, 1;\n"
        "add.s64 dt, w1d, 896; wgmma.mma_async.sync.aligned.m64n64k16.f16.f16.f16 {qz16,qz17,qz18,qz19,qz20,qz21,qz22,qz23,qz24,qz25,qz26,qz27,qz28,qz29,qz30,qz31}, {qa4,qa5,qa6,qa7}, dt, pt, 1, 1, 1;\n"
        "add.s64 dt, w1d, 1024; wgmma.mma_async.sync.aligned.m64n64k16.f16.f16.f16 {qz16,qz17,qz18,qz19,qz20,qz21,qz22,qz23,qz24,qz25,qz26,qz27,qz28,qz29,qz30,qz31}, {qa8,qa9,qa10,qa11}, dt, pt, 1, 1, 1;\n"
        "add.s64 dt, w1d, 1152; wgmma.mma_async.sync.aligned.m64n64k16.f16.f16.f16 {qz16,qz17,qz18,qz19,qz20,qz21,qz22,qz23,qz24,qz25,qz26,qz27,qz28,qz29,qz30,qz31}, {qa12,qa13,qa14,qa15}, dt, pt, 1, 1, 1;\n"
        "add.s64 dt, w1d, 1280; wgmma.mma_async.sync.aligned.m64n64k16.f16.f16.f16 {qz16,qz17,qz18,qz19,qz20,qz21,qz22,qz23,qz24,qz25,qz26,qz27,qz28,qz29,qz30,qz31}, {qa16,qa17,qa18,qa19}, dt, pt, 1, 1, 1;\n"
        "add.s64 dt, w1d, 1408; wgmma.mma_async.sync.aligned.m64n64k16.f16.f16.f16 {qz16,qz17,qz18,qz19,qz20,qz21,qz22,qz23,qz24,qz25,qz26,qz27,qz28,qz29,qz30,qz31}, {qa20,qa21,qa22,qa23}, dt, pt, 1, 1, 1;\n"
        "SKIP0:\n"
        "wgmma.fence.sync.aligned;\n"
        "wgmma.commit_group.sync.aligned;\n"
        "setp.lt.s32 pr, n, 0;\n"
        "@pr bra.uni FIRST;\n"
        "and.b32 tt, n, 1; mbarrier.try_wait.parity.shared::cta.b64 pw, [xbar], tt;\n"
        "@!pw bra.uni SPINX;\n"
        "BACKX:\n"
        "and.b32 ad, %6, 0xffff; add.u32 ad, ad, %4; ld.shared.v4.b32 {v0,v1,v2,v3}, [ad+0];\n"
        "shr.u32 ad, %6, 16; add.u32 ad, ad, %4; ld.shared.v4.b32 {v4,v5,v6,v7}, [ad+0];\n"
        "mov.b32 {xl, xh}, o0; cvt.f32.f16 f0, xl; cvt.f32.f16 f1, xh; cvt.rn.bf16x2.f32 tt, f1, f0; fma.rn.bf16x2 v0, tt, %8, v0;\n"
        "mov.b32 {xl, xh}, o2; cvt.f32.f16 f0, xl; cvt.f32.f16 f1, xh; cvt.rn.bf16x2.f32 tt, f1, f0; fma.rn.bf16x2 v1, tt, %8, v1;\n"
        "mov.b32 {xl, xh}, o4; cvt.f32.f16 f0, xl; cvt.f32.f16 f1, xh; cvt.rn.bf16x2.f32 tt, f1, f0; fma.rn.bf16x2 v2, tt, %8, v2;\n"
        "mov.b32 {xl, xh}, o6; cvt.f32.f16 f0, xl; cvt.f32.f16 f1, xh; cvt.rn.bf16x2.f32 tt, f1, f0; fma.rn.bf16x2 v3, tt, %8, v3;\n"
        "and.b32 ad, %6, 0xffff; add.u32 ad, ad, %4; st.shared.v4.b32 [ad+0], {v0,v1,v2,v3};\n"
        "and.b32 ad, %6, 0xffff; add.u32 ad, ad, %4; ld.shared.v4.b32 {v0,v1,v2,v3}, [ad+64];\n"
        "mov.b32 {xl, xh}, o1; cvt.f32.f16 f0, xl; cvt.f32.f16 f1, xh; cvt.rn.bf16x2.f32 tt, f1, f0; fma.rn.bf16x2 v4, tt, %8, v4;\n"
        "mov.b32 {xl, xh}, o3; cvt.f32.f16 f0, xl; cvt.f32.f16 f1, xh; cvt.rn.bf16x2.f32 tt, f1, f0; fma.rn.bf16x2 v5, tt, %8, v5;\n"
        "mov.b32 {xl, xh}, o5; cvt.f32.f16 f0, xl; cvt.f32.f16 f1, xh; cvt.rn.bf16x2.f32 tt, f1, f0; fma.rn.bf16x2 v6, tt, %8, v6;\n"
        "mov.b32 {xl, xh}, o7; cvt.f32.f16 f0, xl; cvt.f32.f16 f1, xh; cvt.rn.bf16x2.f32 tt, f1, f0; fma.rn.bf16x2 v7, tt, %8, v7;\n"
        "shr.u32 ad, %6, 16; add.u32 ad, ad, %4; st.shared.v4.b32 [ad+0], {v4,v5,v6,v7};\n"
        "shr.u32 ad, %6, 16; add.u32 ad, ad, %4; ld.shared.v4.b32 {v4,v5,v6,v7}, [ad+64];\n"
        "ld.shared.v4.b32 {o0,o1,o2,o3}, [%7+0];\n"
        "ld.shared.v4.b32 {o4,o5,o6,o7}, [%7+64];\n"
        "mov.b32 {xl, xh}, o8; cvt.f32.f16 f0, xl; cvt.f32.f16 f1, xh; cvt.rn.bf16x2.f32 tt, f1, f0; fma.rn.bf16x2 v0, tt, %8, v0;\n"
        "mov.b32 {xl, xh}, o10; cvt.f32.f16 f0, xl; cvt.f32.f16 f1, xh; cvt.rn.bf16x2.f32 tt, f1, f0; fma.rn.bf16x2 v1, tt, %8, v1;\n"
        "mov.b32 {xl, xh}, o12; cvt.f32.f16 f0, xl; cvt.f32.f16 f1, xh; cvt.rn.bf16x2.f32 tt, f1, f0; fma.rn.bf16x2 v2, tt, %8, v2;\n"
        "mov.b32 {xl, xh}, o14; cvt.f32.f16 f0, xl; cvt.f32.f16 f1, xh; cvt.rn.bf16x2.f32 tt, f1, f0; fma.rn.bf16x2 v3, tt, %8, v3;\n"
        "and.b32 ad, %6, 0xffff; add.u32 ad, ad, %4; st.shared.v4.b32 [ad+64], {v0,v1,v2,v3};\n"
        "and.b32 ad, %6, 0xffff; add.u32 ad, ad, %4; ld.shared.v4.b32 {v0,v1,v2,v3}, [ad+128];\n"
        "mov.b32 {xl, xh}, o9; cvt.f32.f16 f0, xl; cvt.f32.f16 f1, xh; cvt.rn.bf16x2.f32 tt, f1, f0; fma.rn.bf16x2 v4, tt, %8, v4;\n"
        "mov.b32 {xl, xh}, o11; cvt.f32.f16 f0, xl; cvt.f32.f16 f1, xh; cvt.rn.bf16x2.f32 tt, f1, f0; fma.rn.bf16x2 v5, tt, %8, v5;\n"
        "mov.b32 {xl, xh}, o13; cvt.f32.f16 f0, xl; cvt.f32.f16 f1, xh; cvt.rn.bf16x2.f32 tt, f1, f0; fma.rn.bf16x2 v6, tt, %8, v6;\n"
        "mov.b32 {xl, xh}, o15; cvt.f32.f16 f0, xl; cvt.f32.f16 f1, xh; cvt.rn.bf16x2.f32 tt, f1, f0; fma.rn.bf16x2 v7, tt, %8, v7;\n"
        "shr.u32 ad, %6, 16; add.u32 ad, ad, %4; st.shared.v4.b32 [ad+64], {v4,v5,v6,v7};\n"
        "shr.u32 ad, %6, 16; add.u32 ad, ad, %4; ld.shared.v4.b32 {v4,v5,v6,v7}, [ad+128];\n"
        "ld.shared.v4.b32 {o8,o9,o10,o11}, [%7+128];\n"
        "ld.shared.v4.b32 {o12,o13,o14,o15}, [%7+192];\n"
        "mov.b32 {xl, xh}, o16; cvt.f32.f16 f0, xl; cvt.f32.f16 f1, xh; cvt.rn.bf16x2.f32 tt, f1, f0; fma.rn.bf16x2 v0, tt, %8, v0;\n"
        "mov.b32 {xl, xh}, o18; cvt.f32.f16 f0, xl; cvt.f32.f16 f1, xh; cvt.rn.bf16x2.f32 tt, f1, f0; fma.rn.bf16x2 v1, tt, %8, v1;\n"
        "mov.b32 {xl, xh}, o20; cvt.f32.f16 f0, xl; cvt.f32.f16 f1, xh; cvt.rn.bf16x2.f32 tt, f1, f0; fma.rn.bf16x2 v2, tt, %8, v2;\n"
        "mov.b32 {xl, xh}, o22; cvt.f32.f16 f0, xl; cvt.f32.f16 f1, xh; cvt.rn.bf16x2.f32 tt, f1, f0; fma.rn.bf16x2 v3, tt, %8, v3;\n"
        "and.b32 ad, %6, 0xffff; add.u32 ad, ad, %4; st.shared.v4.b32 [ad+128], {v0,v1,v2,v3};\n"
        "mov.b32 {xl, xh}, o17; cvt.f32.f16 f0, xl; cvt.f32.f16 f1, xh; cvt.rn.bf16x2.f32 tt, f1, f0; fma.rn.bf16x2 v4, tt, %8, v4;\n"
        "mov.b32 {xl, xh}, o19; cvt.f32.f16 f0, xl; cvt.f32.f16 f1, xh; cvt.rn.bf16x2.f32 tt, f1, f0; fma.rn.bf16x2 v5, tt, %8, v5;\n"
        "mov.b32 {xl, xh}, o21; cvt.f32.f16 f0, xl; cvt.f32.f16 f1, xh; cvt.rn.bf16x2.f32 tt, f1, f0; fma.rn.bf16x2 v6, tt, %8, v6;\n"
        "mov.b32 {xl, xh}, o23; cvt.f32.f16 f0, xl; cvt.f32.f16 f1, xh; cvt.rn.bf16x2.f32 tt, f1, f0; fma.rn.bf16x2 v7, tt, %8, v7;\n"
        "shr.u32 ad, %6, 16; add.u32 ad, ad, %4; st.shared.v4.b32 [ad+128], {v4,v5,v6,v7};\n"
        "ld.shared.v4.b32 {o16,o17,o18,o19}, [%7+256];\n"
        "ld.shared.v4.b32 {o20,o21,o22,o23}, [%7+320];\n"
        "FIRST:\n"
        "@pz bra.uni B8;\n"
        "mov.b32 {xl, xh}, a0; tanh.approx.f16 xr, xl; cvt.u32.u16 lo0, xr; tanh.approx.f16 xr, xh; cvt.u32.u16 hi0, xr; fma.rn.f16x2 p0, qz8, qz8, c; mul.rn.f16x2 a1, qz7, p1; fma.rn.f16x2 g4, qz4, h0, qz4; prmt.b32 h1, lo1, hi1, 0x5410;\n"
        "mov.b32 {xl, xh}, a1; tanh.approx.f16 xr, xl; cvt.u32.u16 lo1, xr; tanh.approx.f16 xr, xh; cvt.u32.u16 hi1, xr; fma.rn.f16x2 p1, qz9, qz9, c; mul.rn.f16x2 a0, qz8, p0; fma.rn.f16x2 g5, qz5, h1, qz5; prmt.b32 h0, lo0, hi0, 0x5410;\n"
        "B8:\n"
        "fence.proxy.async.shared::cta;\n"
        "add.u32 tt, id, 4;\n"
        "@pl bra.uni STORE;\n"
        "bar.arrive tt, 128;\n"
        "STOREB:\n"
        ASM_MARK
        "@!pm bra.uni DONE;\n"
        "add.s32 n, n, 1; sub.u32 off, off, %12; setp.lt.s32 pm, n, 7;\n"
        "@pz bra.uni B10;\n"
        "mov.b32 {xl, xh}, a0; tanh.approx.f16 xr, xl; cvt.u32.u16 lo0, xr; tanh.approx.f16 xr, xh; cvt.u32.u16 hi0, xr; fma.rn.f16x2 p0, qz10, qz10, c; mul.rn.f16x2 a1, qz9, p1; fma.rn.f16x2 g6, qz6, h0, qz6; prmt.b32 h1, lo1, hi1, 0x5410;\n"
        "mov.b32 {xl, xh}, a1; tanh.approx.f16 xr, xl; cvt.u32.u16 lo1, xr; tanh.approx.f16 xr, xh; cvt.u32.u16 hi1, xr; fma.rn.f16x2 p1, qz11, qz11, c; mul.rn.f16x2 a0, qz10, p0; fma.rn.f16x2 g7, qz7, h1, qz7; prmt.b32 h0, lo0, hi0, 0x5410;\n"
        "B10:\n"
        "wgmma.fence.sync.aligned;\n"
        "add.s64 dt, w2d, 0; wgmma.mma_async.sync.aligned.m64n96k16.f16.f16.f16 {o0,o1,o2,o3,o4,o5,o6,o7,o8,o9,o10,o11,o12,o13,o14,o15,o16,o17,o18,o19,o20,o21,o22,o23}, {g0,g1,g2,g3}, dt, pt, 1, 1, 1;\n"
        "add.s64 dt, w2d, 64; wgmma.mma_async.sync.aligned.m64n96k16.f16.f16.f16 {o0,o1,o2,o3,o4,o5,o6,o7,o8,o9,o10,o11,o12,o13,o14,o15,o16,o17,o18,o19,o20,o21,o22,o23}, {g4,g5,g6,g7}, dt, pt, 1, 1, 1;\n"
        "wgmma.commit_group.sync.aligned;\n"
        "@pz bra.uni B14;\n"
        "mov.b32 {xl, xh}, a0; tanh.approx.f16 xr, xl; cvt.u32.u16 lo0, xr; tanh.approx.f16 xr, xh; cvt.u32.u16 hi0, xr; fma.rn.f16x2 p0, qz12, qz12, c; mul.rn.f16x2 a1, qz11, p1; fma.rn.f16x2 g8, qz8, h0, qz8; prmt.b32 h1, lo1, hi1, 0x5410;\n"
        "mov.b32 {xl, xh}, a1; tanh.approx.f16 xr, xl; cvt.u32.u16 lo1, xr; tanh.approx.f16 xr, xh; cvt.u32.u16 hi1, xr; fma.rn.f16x2 p1, qz13, qz13, c; mul.rn.f16x2 a0, qz12, p0; fma.rn.f16x2 g9, qz9, h1, qz9; prmt.b32 h0, lo0, hi0, 0x5410;\n"
        "mov.b32 {xl, xh}, a0; tanh.approx.f16 xr, xl; cvt.u32.u16 lo0, xr; tanh.approx.f16 xr, xh; cvt.u32.u16 hi0, xr; fma.rn.f16x2 p0, qz14, qz14, c; mul.rn.f16x2 a1, qz13, p1; fma.rn.f16x2 g10, qz10, h0, qz10; prmt.b32 h1, lo1, hi1, 0x5410;\n"
        "mov.b32 {xl, xh}, a1; tanh.approx.f16 xr, xl; cvt.u32.u16 lo1, xr; tanh.approx.f16 xr, xh; cvt.u32.u16 hi1, xr; fma.rn.f16x2 p1, qz15, qz15, c; mul.rn.f16x2 a0, qz14, p0; fma.rn.f16x2 g11, qz11, h1, qz11; prmt.b32 h0, lo0, hi0, 0x5410;\n"
        "B14:\n"
        "wgmma.wait_group.sync.aligned 1;\n"
        "wgmma.fence.sync.aligned;\n"
        "add.s64 dt, w2d, 128; wgmma.mma_async.sync.aligned.m64n96k16.f16.f16.f16 {o0,o1,o2,o3,o4,o5,o6,o7,o8,o9,o10,o11,o12,o13,o14,o15,o16,o17,o18,o19,o20,o21,o22,o23}, {g8,g9,g10,g11}, dt, pt, 1, 1, 1;\n"
        "wgmma.commit_group.sync.aligned;\n"
        "@pz bra.uni B18;\n"
        "mov.b32 {xl, xh}, a0; tanh.approx.f16 xr, xl; cvt.u32.u16 lo0, xr; tanh.approx.f16 xr, xh; cvt.u32.u16 hi0, xr; fma.rn.f16x2 p0, qz16, qz16, c; mul.rn.f16x2 a1, qz15, p1; fma.rn.f16x2 g12, qz12, h0, qz12; prmt.b32 h1, lo1, hi1, 0x5410;\n"
        "mov.b32 {xl, xh}, a1; tanh.approx.f16 xr, xl; cvt.u32.u16 lo1, xr; tanh.approx.f16 xr, xh; cvt.u32.u16 hi1, xr; fma.rn.f16x2 p1, qz17, qz17, c; mul.rn.f16x2 a0, qz16, p0; fma.rn.f16x2 g13, qz13, h1, qz13; prmt.b32 h0, lo0, hi0, 0x5410;\n"
        "mov.b32 {xl, xh}, a0; tanh.approx.f16 xr, xl; cvt.u32.u16 lo0, xr; tanh.approx.f16 xr, xh; cvt.u32.u16 hi0, xr; fma.rn.f16x2 p0, qz18, qz18, c; mul.rn.f16x2 a1, qz17, p1; fma.rn.f16x2 g14, qz14, h0, qz14; prmt.b32 h1, lo1, hi1, 0x5410;\n"
        "mov.b32 {xl, xh}, a1; tanh.approx.f16 xr, xl; cvt.u32.u16 lo1, xr; tanh.approx.f16 xr, xh; cvt.u32.u16 hi1, xr; fma.rn.f16x2 p1, qz19, qz19, c; mul.rn.f16x2 a0, qz18, p0; fma.rn.f16x2 g15, qz15, h1, qz15; prmt.b32 h0, lo0, hi0, 0x5410;\n"
        "B18:\n"
        "wgmma.wait_group.sync.aligned 1;\n"
        "mad.lo.u32 tt, n, 8, tbar; mbarrier.try_wait.parity.shared::cta.b64 pw, [tt], tpar;\n"
        "@!pw bra.uni SPINT;\n"
        "BACKT:\n"
        "wgmma.fence.sync.aligned;\n"
        "add.s64 dt, w2d, 192; wgmma.mma_async.sync.aligned.m64n96k16.f16.f16.f16 {o0,o1,o2,o3,o4,o5,o6,o7,o8,o9,o10,o11,o12,o13,o14,o15,o16,o17,o18,o19,o20,o21,o22,o23}, {g12,g13,g14,g15}, dt, pt, 1, 1, 1;\n"
        "add.s64 dt, w1d, 1536; wgmma.mma_async.sync.aligned.m64n64k16.f16.f16.f16 {qz0,qz1,qz2,qz3,qz4,qz5,qz6,qz7,qz8,qz9,qz10,qz11,qz12,qz13,qz14,qz15}, {qa0,qa1,qa2,qa3}, dt, pf, 1, 1, 1;\n"
        "add.s64 dt, w1d, 1664; wgmma.mma_async.sync.aligned.m64n64k16.f16.f16.f16 {qz0,qz1,qz2,qz3,qz4,qz5,qz6,qz7,qz8,qz9,qz10,qz11,qz12,qz13,qz14,qz15}, {qa4,qa5,qa6,qa7}, dt, pt, 1, 1, 1;\n"
        "add.s64 dt, w1d, 1792; wgmma.mma_async.sync.aligned.m64n64k16.f16.f16.f16 {qz0,qz1,qz2,qz3,qz4,qz5,qz6,qz7,qz8,qz9,qz10,qz11,qz12,qz13,qz14,qz15}, {qa8,qa9,qa10,qa11}, dt, pt, 1, 1, 1;\n"
        "wgmma.commit_group.sync.aligned;\n"
        "@pl bra.uni YLOAD;\n"
        "YLOADB:\n"
        "@pz bra.uni B22;\n"
        "mov.b32 {xl, xh}, a0; tanh.approx.f16 xr, xl; cvt.u32.u16 lo0, xr; tanh.approx.f16 xr, xh; cvt.u32.u16 hi0, xr; fma.rn.f16x2 p0, qz20, qz20, c; mul.rn.f16x2 a1, qz19, p1; fma.rn.f16x2 g0, qz16, h0, qz16; prmt.b32 h1, lo1, hi1, 0x5410;\n"
        "mov.b32 {xl, xh}, a1; tanh.approx.f16 xr, xl; cvt.u32.u16 lo1, xr; tanh.approx.f16 xr, xh; cvt.u32.u16 hi1, xr; fma.rn.f16x2 p1, qz21, qz21, c; mul.rn.f16x2 a0, qz20, p0; fma.rn.f16x2 g1, qz17, h1, qz17; prmt.b32 h0, lo0, hi0, 0x5410;\n"
        "mov.b32 {xl, xh}, a0; tanh.approx.f16 xr, xl; cvt.u32.u16 lo0, xr; tanh.approx.f16 xr, xh; cvt.u32.u16 hi0, xr; fma.rn.f16x2 p0, qz22, qz22, c; mul.rn.f16x2 a1, qz21, p1; fma.rn.f16x2 g2, qz18, h0, qz18; prmt.b32 h1, lo1, hi1, 0x5410;\n"
        "mov.b32 {xl, xh}, a1; tanh.approx.f16 xr, xl; cvt.u32.u16 lo1, xr; tanh.approx.f16 xr, xh; cvt.u32.u16 hi1, xr; fma.rn.f16x2 p1, qz23, qz23, c; mul.rn.f16x2 a0, qz22, p0; fma.rn.f16x2 g3, qz19, h1, qz19; prmt.b32 h0, lo0, hi0, 0x5410;\n"
        "B22:\n"
        "wgmma.fence.sync.aligned;\n"
        "add.s64 dt, w2d, 256; wgmma.mma_async.sync.aligned.m64n96k16.f16.f16.f16 {o0,o1,o2,o3,o4,o5,o6,o7,o8,o9,o10,o11,o12,o13,o14,o15,o16,o17,o18,o19,o20,o21,o22,o23}, {g0,g1,g2,g3}, dt, pt, 1, 1, 1;\n"
        "add.s64 dt, w1d, 1920; wgmma.mma_async.sync.aligned.m64n64k16.f16.f16.f16 {qz0,qz1,qz2,qz3,qz4,qz5,qz6,qz7,qz8,qz9,qz10,qz11,qz12,qz13,qz14,qz15}, {qa12,qa13,qa14,qa15}, dt, pt, 1, 1, 1;\n"
        "add.s64 dt, w1d, 2048; wgmma.mma_async.sync.aligned.m64n64k16.f16.f16.f16 {qz0,qz1,qz2,qz3,qz4,qz5,qz6,qz7,qz8,qz9,qz10,qz11,qz12,qz13,qz14,qz15}, {qa16,qa17,qa18,qa19}, dt, pt, 1, 1, 1;\n"
        "add.s64 dt, w1d, 2176; wgmma.mma_async.sync.aligned.m64n64k16.f16.f16.f16 {qz0,qz1,qz2,qz3,qz4,qz5,qz6,qz7,qz8,qz9,qz10,qz11,qz12,qz13,qz14,qz15}, {qa20,qa21,qa22,qa23}, dt, pt, 1, 1, 1;\n"
        "wgmma.commit_group.sync.aligned;\n"
        "@pz bra.uni B26;\n"
        "mov.b32 {xl, xh}, a0; tanh.approx.f16 xr, xl; cvt.u32.u16 lo0, xr; tanh.approx.f16 xr, xh; cvt.u32.u16 hi0, xr; fma.rn.f16x2 p0, qz24, qz24, c; mul.rn.f16x2 a1, qz23, p1; fma.rn.f16x2 g4, qz20, h0, qz20; prmt.b32 h1, lo1, hi1, 0x5410;\n"
        "mov.b32 {xl, xh}, a1; tanh.approx.f16 xr, xl; cvt.u32.u16 lo1, xr; tanh.approx.f16 xr, xh; cvt.u32.u16 hi1, xr; fma.rn.f16x2 p1, qz25, qz25, c; mul.rn.f16x2 a0, qz24, p0; fma.rn.f16x2 g5, qz21, h1, qz21; prmt.b32 h0, lo0, hi0, 0x5410;\n"
        "mov.b32 {xl, xh}, a0; tanh.approx.f16 xr, xl; cvt.u32.u16 lo0, xr; tanh.approx.f16 xr, xh; cvt.u32.u16 hi0, xr; fma.rn.f16x2 p0, qz26, qz26, c; mul.rn.f16x2 a1, qz25, p1; fma.rn.f16x2 g6, qz22, h0, qz22; prmt.b32 h1, lo1, hi1, 0x5410;\n"
        "mov.b32 {xl, xh}, a1; tanh.approx.f16 xr, xl; cvt.u32.u16 lo1, xr; tanh.approx.f16 xr, xh; cvt.u32.u16 hi1, xr; fma.rn.f16x2 p1, qz27, qz27, c; mul.rn.f16x2 a0, qz26, p0; fma.rn.f16x2 g7, qz23, h1, qz23; prmt.b32 h0, lo0, hi0, 0x5410;\n"
        "B26:\n"
        "wgmma.wait_group.sync.aligned 2;\n"
        "wgmma.fence.sync.aligned;\n"
        "add.s64 dt, w2d, 320; wgmma.mma_async.sync.aligned.m64n96k16.f16.f16.f16 {o0,o1,o2,o3,o4,o5,o6,o7,o8,o9,o10,o11,o12,o13,o14,o15,o16,o17,o18,o19,o20,o21,o22,o23}, {g4,g5,g6,g7}, dt, pt, 1, 1, 1;\n"
        "wgmma.commit_group.sync.aligned;\n"
        "@pz bra.uni B30;\n"
        "mov.b32 {xl, xh}, a0; tanh.approx.f16 xr, xl; cvt.u32.u16 lo0, xr; tanh.approx.f16 xr, xh; cvt.u32.u16 hi0, xr; fma.rn.f16x2 p0, qz28, qz28, c; mul.rn.f16x2 a1, qz27, p1; fma.rn.f16x2 g8, qz24, h0, qz24; prmt.b32 h1, lo1, hi1, 0x5410;\n"
        "mov.b32 {xl, xh}, a1; tanh.approx.f16 xr, xl; cvt.u32.u16 lo1, xr; tanh.approx.f16 xr, xh; cvt.u32.u16 hi1, xr; fma.rn.f16x2 p1, qz29, qz29, c; mul.rn.f16x2 a0, qz28, p0; fma.rn.f16x2 g9, qz25, h1, qz25; prmt.b32 h0, lo0, hi0, 0x5410;\n"
        "mov.b32 {xl, xh}, a0; tanh.approx.f16 xr, xl; cvt.u32.u16 lo0, xr; tanh.approx.f16 xr, xh; cvt.u32.u16 hi0, xr; fma.rn.f16x2 p0, qz30, qz30, c; mul.rn.f16x2 a1, qz29, p1; fma.rn.f16x2 g10, qz26, h0, qz26; prmt.b32 h1, lo1, hi1, 0x5410;\n"
        "mov.b32 {xl, xh}, a1; tanh.approx.f16 xr, xl; cvt.u32.u16 lo1, xr; tanh.approx.f16 xr, xh; cvt.u32.u16 hi1, xr; fma.rn.f16x2 p1, qz31, qz31, c; mul.rn.f16x2 a0, qz30, p0; fma.rn.f16x2 g11, qz27, h1, qz27; prmt.b32 h0, lo0, hi0, 0x5410;\n"
        "B30:\n"
        "wgmma.wait_group.sync.aligned 1;\n"
        "wgmma.fence.sync.aligned;\n"
        "add.s64 dt, w2d, 384; wgmma.mma_async.sync.aligned.m64n96k16.f16.f16.f16 {o0,o1,o2,o3,o4,o5,o6,o7,o8,o9,o10,o11,o12,o13,o14,o15,o16,o17,o18,o19,o20,o21,o22,o23}, {g8,g9,g10,g11}, dt, pt, 1, 1, 1;\n"
        "wgmma.commit_group.sync.aligned;\n"
        "@pz bra.uni B34;\n"
        "mov.b32 {xl, xh}, a0; tanh.approx.f16 xr, xl; cvt.u32.u16 lo0, xr; tanh.approx.f16 xr, xh; cvt.u32.u16 hi0, xr; fma.rn.f16x2 p0, qz0, qz0, c; mul.rn.f16x2 a1, qz31, p1; fma.rn.f16x2 g12, qz28, h0, qz28; prmt.b32 h1, lo1, hi1, 0x5410;\n"
        "mov.b32 {xl, xh}, a1; tanh.approx.f16 xr, xl; cvt.u32.u16 lo1, xr; tanh.approx.f16 xr, xh; cvt.u32.u16 hi1, xr; fma.rn.f16x2 p1, qz1, qz1, c; mul.rn.f16x2 a0, qz0, p0; fma.rn.f16x2 g13, qz29, h1, qz29; prmt.b32 h0, lo0, hi0, 0x5410;\n"
        "mov.b32 {xl, xh}, a0; tanh.approx.f16 xr, xl; cvt.u32.u16 lo0, xr; tanh.approx.f16 xr, xh; cvt.u32.u16 hi0, xr; fma.rn.f16x2 p0, qz2, qz2, c; mul.rn.f16x2 a1, qz1, p1; fma.rn.f16x2 g14, qz30, h0, qz30; prmt.b32 h1, lo1, hi1, 0x5410;\n"
        "mov.b32 {xl, xh}, a1; tanh.approx.f16 xr, xl; cvt.u32.u16 lo1, xr; tanh.approx.f16 xr, xh; cvt.u32.u16 hi1, xr; fma.rn.f16x2 p1, qz3, qz3, c; mul.rn.f16x2 a0, qz2, p0; fma.rn.f16x2 g15, qz31, h1, qz31; prmt.b32 h0, lo0, hi0, 0x5410;\n"
        "B34:\n"
        "wgmma.fence.sync.aligned;\n"
        "add.s64 dt, w2d, 448; wgmma.mma_async.sync.aligned.m64n96k16.f16.f16.f16 {o0,o1,o2,o3,o4,o5,o6,o7,o8,o9,o10,o11,o12,o13,o14,o15,o16,o17,o18,o19,o20,o21,o22,o23}, {g12,g13,g14,g15}, dt, pt, 1, 1, 1;\n"
        "add.s64 dt, w1d, 2304; wgmma.mma_async.sync.aligned.m64n64k16.f16.f16.f16 {qz16,qz17,qz18,qz19,qz20,qz21,qz22,qz23,qz24,qz25,qz26,qz27,qz28,qz29,qz30,qz31}, {qa0,qa1,qa2,qa3}, dt, pf, 1, 1, 1;\n"
        "add.s64 dt, w1d, 2432; wgmma.mma_async.sync.aligned.m64n64k16.f16.f16.f16 {qz16,qz17,qz18,qz19,qz20,qz21,qz22,qz23,qz24,qz25,qz26,qz27,qz28,qz29,qz30,qz31}, {qa4,qa5,qa6,qa7}, dt, pt, 1, 1, 1;\n"
        "add.s64 dt, w1d, 2560; wgmma.mma_async.sync.aligned.m64n64k16.f16.f16.f16 {qz16,qz17,qz18,qz19,qz20,qz21,qz22,qz23,qz24,qz25,qz26,qz27,qz28,qz29,qz30,qz31}, {qa8,qa9,qa10,qa11}, dt, pt, 1, 1, 1;\n"
        "wgmma.commit_group.sync.aligned;\n"
        "@pz bra.uni B38;\n"
        "mov.b32 {xl, xh}, a0; tanh.approx.f16 xr, xl; cvt.u32.u16 lo0, xr; tanh.approx.f16 xr, xh; cvt.u32.u16 hi0, xr; fma.rn.f16x2 p0, qz4, qz4, c; mul.rn.f16x2 a1, qz3, p1; fma.rn.f16x2 g0, qz0, h0, qz0; prmt.b32 h1, lo1, hi1, 0x5410;\n"
        "mov.b32 {xl, xh}, a1; tanh.approx.f16 xr, xl; cvt.u32.u16 lo1, xr; tanh.approx.f16 xr, xh; cvt.u32.u16 hi1, xr; fma.rn.f16x2 p1, qz5, qz5, c; mul.rn.f16x2 a0, qz4, p0; fma.rn.f16x2 g1, qz1, h1, qz1; prmt.b32 h0, lo0, hi0, 0x5410;\n"
        "mov.b32 {xl, xh}, a0; tanh.approx.f16 xr, xl; cvt.u32.u16 lo0, xr; tanh.approx.f16 xr, xh; cvt.u32.u16 hi0, xr; fma.rn.f16x2 p0, qz6, qz6, c; mul.rn.f16x2 a1, qz5, p1; fma.rn.f16x2 g2, qz2, h0, qz2; prmt.b32 h1, lo1, hi1, 0x5410;\n"
        "mov.b32 {xl, xh}, a1; tanh.approx.f16 xr, xl; cvt.u32.u16 lo1, xr; tanh.approx.f16 xr, xh; cvt.u32.u16 hi1, xr; fma.rn.f16x2 p1, qz7, qz7, c; mul.rn.f16x2 a0, qz6, p0; fma.rn.f16x2 g3, qz3, h1, qz3; prmt.b32 h0, lo0, hi0, 0x5410;\n"
        "B38:\n"
        "wgmma.wait_group.sync.aligned 2;\n"
        "wgmma.fence.sync.aligned;\n"
        "add.s64 dt, w2d, 512; wgmma.mma_async.sync.aligned.m64n96k16.f16.f16.f16 {o0,o1,o2,o3,o4,o5,o6,o7,o8,o9,o10,o11,o12,o13,o14,o15,o16,o17,o18,o19,o20,o21,o22,o23}, {g0,g1,g2,g3}, dt, pt, 1, 1, 1;\n"
        "add.s64 dt, w1d, 2688; wgmma.mma_async.sync.aligned.m64n64k16.f16.f16.f16 {qz16,qz17,qz18,qz19,qz20,qz21,qz22,qz23,qz24,qz25,qz26,qz27,qz28,qz29,qz30,qz31}, {qa12,qa13,qa14,qa15}, dt, pt, 1, 1, 1;\n"
        "add.s64 dt, w1d, 2816; wgmma.mma_async.sync.aligned.m64n64k16.f16.f16.f16 {qz16,qz17,qz18,qz19,qz20,qz21,qz22,qz23,qz24,qz25,qz26,qz27,qz28,qz29,qz30,qz31}, {qa16,qa17,qa18,qa19}, dt, pt, 1, 1, 1;\n"
        "add.s64 dt, w1d, 2944; wgmma.mma_async.sync.aligned.m64n64k16.f16.f16.f16 {qz16,qz17,qz18,qz19,qz20,qz21,qz22,qz23,qz24,qz25,qz26,qz27,qz28,qz29,qz30,qz31}, {qa20,qa21,qa22,qa23}, dt, pt, 1, 1, 1;\n"
        "wgmma.commit_group.sync.aligned;\n"
        "@pz bra.uni B42;\n"
        "mov.b32 {xl, xh}, a0; tanh.approx.f16 xr, xl; cvt.u32.u16 lo0, xr; tanh.approx.f16 xr, xh; cvt.u32.u16 hi0, xr; fma.rn.f16x2 p0, qz8, qz8, c; mul.rn.f16x2 a1, qz7, p1; fma.rn.f16x2 g4, qz4, h0, qz4; prmt.b32 h1, lo1, hi1, 0x5410;\n"
        "mov.b32 {xl, xh}, a1; tanh.approx.f16 xr, xl; cvt.u32.u16 lo1, xr; tanh.approx.f16 xr, xh; cvt.u32.u16 hi1, xr; fma.rn.f16x2 p1, qz9, qz9, c; mul.rn.f16x2 a0, qz8, p0; fma.rn.f16x2 g5, qz5, h1, qz5; prmt.b32 h0, lo0, hi0, 0x5410;\n"
        "mov.b32 {xl, xh}, a0; tanh.approx.f16 xr, xl; cvt.u32.u16 lo0, xr; tanh.approx.f16 xr, xh; cvt.u32.u16 hi0, xr; fma.rn.f16x2 p0, qz10, qz10, c; mul.rn.f16x2 a1, qz9, p1; fma.rn.f16x2 g6, qz6, h0, qz6; prmt.b32 h1, lo1, hi1, 0x5410;\n"
        "mov.b32 {xl, xh}, a1; tanh.approx.f16 xr, xl; cvt.u32.u16 lo1, xr; tanh.approx.f16 xr, xh; cvt.u32.u16 hi1, xr; fma.rn.f16x2 p1, qz11, qz11, c; mul.rn.f16x2 a0, qz10, p0; fma.rn.f16x2 g7, qz7, h1, qz7; prmt.b32 h0, lo0, hi0, 0x5410;\n"
        "B42:\n"
        "wgmma.wait_group.sync.aligned 2;\n"
        "wgmma.fence.sync.aligned;\n"
        "add.s64 dt, w2d, 576; wgmma.mma_async.sync.aligned.m64n96k16.f16.f16.f16 {o0,o1,o2,o3,o4,o5,o6,o7,o8,o9,o10,o11,o12,o13,o14,o15,o16,o17,o18,o19,o20,o21,o22,o23}, {g4,g5,g6,g7}, dt, pt, 1, 1, 1;\n"
        "wgmma.commit_group.sync.aligned;\n"
        "mad.lo.u32 tt, n, 8, tbar;\n"
        "@pn mbarrier.arrive.shared::cta.b64 _, [tt+64];\n"
        "@pz bra.uni B46;\n"
        "mov.b32 {xl, xh}, a0; tanh.approx.f16 xr, xl; cvt.u32.u16 lo0, xr; tanh.approx.f16 xr, xh; cvt.u32.u16 hi0, xr; fma.rn.f16x2 p0, qz12, qz12, c; mul.rn.f16x2 a1, qz11, p1; fma.rn.f16x2 g8, qz8, h0, qz8; prmt.b32 h1, lo1, hi1, 0x5410;\n"
        "mov.b32 {xl, xh}, a1; tanh.approx.f16 xr, xl; cvt.u32.u16 lo1, xr; tanh.approx.f16 xr, xh; cvt.u32.u16 hi1, xr; fma.rn.f16x2 p1, qz13, qz13, c; mul.rn.f16x2 a0, qz12, p0; fma.rn.f16x2 g9, qz9, h1, qz9; prmt.b32 h0, lo0, hi0, 0x5410;\n"
        "mov.b32 {xl, xh}, a0; tanh.approx.f16 xr, xl; cvt.u32.u16 lo0, xr; tanh.approx.f16 xr, xh; cvt.u32.u16 hi0, xr; fma.rn.f16x2 p0, qz14, qz14, c; mul.rn.f16x2 a1, qz13, p1; fma.rn.f16x2 g10, qz10, h0, qz10; prmt.b32 h1, lo1, hi1, 0x5410;\n"
        "mov.b32 {xl, xh}, a1; tanh.approx.f16 xr, xl; cvt.u32.u16 lo1, xr; tanh.approx.f16 xr, xh; cvt.u32.u16 hi1, xr; fma.rn.f16x2 p1, qz15, qz15, c; mul.rn.f16x2 a0, qz14, p0; fma.rn.f16x2 g11, qz11, h1, qz11; prmt.b32 h0, lo0, hi0, 0x5410;\n"
        "B46:\n"
        "wgmma.wait_group.sync.aligned 1;\n"
        "wgmma.fence.sync.aligned;\n"
        "add.s64 dt, w2d, 640; wgmma.mma_async.sync.aligned.m64n96k16.f16.f16.f16 {o0,o1,o2,o3,o4,o5,o6,o7,o8,o9,o10,o11,o12,o13,o14,o15,o16,o17,o18,o19,o20,o21,o22,o23}, {g8,g9,g10,g11}, dt, pt, 1, 1, 1;\n"
        "wgmma.commit_group.sync.aligned;\n"
        "@pz bra.uni B50;\n"
        "mov.b32 {xl, xh}, a0; tanh.approx.f16 xr, xl; cvt.u32.u16 lo0, xr; tanh.approx.f16 xr, xh; cvt.u32.u16 hi0, xr; fma.rn.f16x2 p0, qz16, qz16, c; mul.rn.f16x2 a1, qz15, p1; fma.rn.f16x2 g12, qz12, h0, qz12; prmt.b32 h1, lo1, hi1, 0x5410;\n"
        "mov.b32 {xl, xh}, a1; tanh.approx.f16 xr, xl; cvt.u32.u16 lo1, xr; tanh.approx.f16 xr, xh; cvt.u32.u16 hi1, xr; fma.rn.f16x2 p1, qz17, qz17, c; mul.rn.f16x2 a0, qz16, p0; fma.rn.f16x2 g13, qz13, h1, qz13; prmt.b32 h0, lo0, hi0, 0x5410;\n"
        "mov.b32 {xl, xh}, a0; tanh.approx.f16 xr, xl; cvt.u32.u16 lo0, xr; tanh.approx.f16 xr, xh; cvt.u32.u16 hi0, xr; fma.rn.f16x2 p0, qz18, qz18, c; mul.rn.f16x2 a1, qz17, p1; fma.rn.f16x2 g14, qz14, h0, qz14; prmt.b32 h1, lo1, hi1, 0x5410;\n"
        "mov.b32 {xl, xh}, a1; tanh.approx.f16 xr, xl; cvt.u32.u16 lo1, xr; tanh.approx.f16 xr, xh; cvt.u32.u16 hi1, xr; fma.rn.f16x2 p1, qz19, qz19, c; mul.rn.f16x2 a0, qz18, p0; fma.rn.f16x2 g15, qz15, h1, qz15; prmt.b32 h0, lo0, hi0, 0x5410;\n"
        "B50:\n"
        "wgmma.fence.sync.aligned;\n"
        "add.s64 dt, w2d, 704; wgmma.mma_async.sync.aligned.m64n96k16.f16.f16.f16 {o0,o1,o2,o3,o4,o5,o6,o7,o8,o9,o10,o11,o12,o13,o14,o15,o16,o17,o18,o19,o20,o21,o22,o23}, {g12,g13,g14,g15}, dt, pt, 1, 1, 1;\n"
        "add.s64 dt, w1d, 3072; wgmma.mma_async.sync.aligned.m64n64k16.f16.f16.f16 {qz0,qz1,qz2,qz3,qz4,qz5,qz6,qz7,qz8,qz9,qz10,qz11,qz12,qz13,qz14,qz15}, {qa0,qa1,qa2,qa3}, dt, pf, 1, 1, 1;\n"
        "add.s64 dt, w1d, 3200; wgmma.mma_async.sync.aligned.m64n64k16.f16.f16.f16 {qz0,qz1,qz2,qz3,qz4,qz5,qz6,qz7,qz8,qz9,qz10,qz11,qz12,qz13,qz14,qz15}, {qa4,qa5,qa6,qa7}, dt, pt, 1, 1, 1;\n"
        "add.s64 dt, w1d, 3328; wgmma.mma_async.sync.aligned.m64n64k16.f16.f16.f16 {qz0,qz1,qz2,qz3,qz4,qz5,qz6,qz7,qz8,qz9,qz10,qz11,qz12,qz13,qz14,qz15}, {qa8,qa9,qa10,qa11}, dt, pt, 1, 1, 1;\n"
        "wgmma.commit_group.sync.aligned;\n"
        "@pz bra.uni B54;\n"
        "mov.b32 {xl, xh}, a0; tanh.approx.f16 xr, xl; cvt.u32.u16 lo0, xr; tanh.approx.f16 xr, xh; cvt.u32.u16 hi0, xr; fma.rn.f16x2 p0, qz20, qz20, c; mul.rn.f16x2 a1, qz19, p1; fma.rn.f16x2 g0, qz16, h0, qz16; prmt.b32 h1, lo1, hi1, 0x5410;\n"
        "mov.b32 {xl, xh}, a1; tanh.approx.f16 xr, xl; cvt.u32.u16 lo1, xr; tanh.approx.f16 xr, xh; cvt.u32.u16 hi1, xr; fma.rn.f16x2 p1, qz21, qz21, c; mul.rn.f16x2 a0, qz20, p0; fma.rn.f16x2 g1, qz17, h1, qz17; prmt.b32 h0, lo0, hi0, 0x5410;\n"
        "mov.b32 {xl, xh}, a0; tanh.approx.f16 xr, xl; cvt.u32.u16 lo0, xr; tanh.approx.f16 xr, xh; cvt.u32.u16 hi0, xr; fma.rn.f16x2 p0, qz22, qz22, c; mul.rn.f16x2 a1, qz21, p1; fma.rn.f16x2 g2, qz18, h0, qz18; prmt.b32 h1, lo1, hi1, 0x5410;\n"
        "mov.b32 {xl, xh}, a1; tanh.approx.f16 xr, xl; cvt.u32.u16 lo1, xr; tanh.approx.f16 xr, xh; cvt.u32.u16 hi1, xr; fma.rn.f16x2 p1, qz23, qz23, c; mul.rn.f16x2 a0, qz22, p0; fma.rn.f16x2 g3, qz19, h1, qz19; prmt.b32 h0, lo0, hi0, 0x5410;\n"
        "B54:\n"
        "wgmma.wait_group.sync.aligned 2;\n"
        "wgmma.fence.sync.aligned;\n"
        "add.s64 dt, w2d, 768; wgmma.mma_async.sync.aligned.m64n96k16.f16.f16.f16 {o0,o1,o2,o3,o4,o5,o6,o7,o8,o9,o10,o11,o12,o13,o14,o15,o16,o17,o18,o19,o20,o21,o22,o23}, {g0,g1,g2,g3}, dt, pt, 1, 1, 1;\n"
        "add.s64 dt, w1d, 3456; wgmma.mma_async.sync.aligned.m64n64k16.f16.f16.f16 {qz0,qz1,qz2,qz3,qz4,qz5,qz6,qz7,qz8,qz9,qz10,qz11,qz12,qz13,qz14,qz15}, {qa12,qa13,qa14,qa15}, dt, pt, 1, 1, 1;\n"
        "add.s64 dt, w1d, 3584; wgmma.mma_async.sync.aligned.m64n64k16.f16.f16.f16 {qz0,qz1,qz2,qz3,qz4,qz5,qz6,qz7,qz8,qz9,qz10,qz11,qz12,qz13,qz14,qz15}, {qa16,qa17,qa18,qa19}, dt, pt, 1, 1, 1;\n"
        "add.s64 dt, w1d, 3712; wgmma.mma_async.sync.aligned.m64n64k16.f16.f16.f16 {qz0,qz1,qz2,qz3,qz4,qz5,qz6,qz7,qz8,qz9,qz10,qz11,qz12,qz13,qz14,qz15}, {qa20,qa21,qa22,qa23}, dt, pt, 1, 1, 1;\n"
        "wgmma.commit_group.sync.aligned;\n"
        "@pz bra.uni B58;\n"
        "mov.b32 {xl, xh}, a0; tanh.approx.f16 xr, xl; cvt.u32.u16 lo0, xr; tanh.approx.f16 xr, xh; cvt.u32.u16 hi0, xr; fma.rn.f16x2 p0, qz24, qz24, c; mul.rn.f16x2 a1, qz23, p1; fma.rn.f16x2 g4, qz20, h0, qz20; prmt.b32 h1, lo1, hi1, 0x5410;\n"
        "mov.b32 {xl, xh}, a1; tanh.approx.f16 xr, xl; cvt.u32.u16 lo1, xr; tanh.approx.f16 xr, xh; cvt.u32.u16 hi1, xr; fma.rn.f16x2 p1, qz25, qz25, c; mul.rn.f16x2 a0, qz24, p0; fma.rn.f16x2 g5, qz21, h1, qz21; prmt.b32 h0, lo0, hi0, 0x5410;\n"
        "mov.b32 {xl, xh}, a0; tanh.approx.f16 xr, xl; cvt.u32.u16 lo0, xr; tanh.approx.f16 xr, xh; cvt.u32.u16 hi0, xr; fma.rn.f16x2 p0, qz26, qz26, c; mul.rn.f16x2 a1, qz25, p1; fma.rn.f16x2 g6, qz22, h0, qz22; prmt.b32 h1, lo1, hi1, 0x5410;\n"
        "mov.b32 {xl, xh}, a1; tanh.approx.f16 xr, xl; cvt.u32.u16 lo1, xr; tanh.approx.f16 xr, xh; cvt.u32.u16 hi1, xr; fma.rn.f16x2 p1, qz27, qz27, c; mul.rn.f16x2 a0, qz26, p0; fma.rn.f16x2 g7, qz23, h1, qz23; prmt.b32 h0, lo0, hi0, 0x5410;\n"
        "B58:\n"
        "wgmma.wait_group.sync.aligned 2;\n"
        "wgmma.fence.sync.aligned;\n"
        "add.s64 dt, w2d, 832; wgmma.mma_async.sync.aligned.m64n96k16.f16.f16.f16 {o0,o1,o2,o3,o4,o5,o6,o7,o8,o9,o10,o11,o12,o13,o14,o15,o16,o17,o18,o19,o20,o21,o22,o23}, {g4,g5,g6,g7}, dt, pt, 1, 1, 1;\n"
        "wgmma.commit_group.sync.aligned;\n"
        "@pz bra.uni B62;\n"
        "mov.b32 {xl, xh}, a0; tanh.approx.f16 xr, xl; cvt.u32.u16 lo0, xr; tanh.approx.f16 xr, xh; cvt.u32.u16 hi0, xr; fma.rn.f16x2 p0, qz28, qz28, c; mul.rn.f16x2 a1, qz27, p1; fma.rn.f16x2 g8, qz24, h0, qz24; prmt.b32 h1, lo1, hi1, 0x5410;\n"
        "mov.b32 {xl, xh}, a1; tanh.approx.f16 xr, xl; cvt.u32.u16 lo1, xr; tanh.approx.f16 xr, xh; cvt.u32.u16 hi1, xr; fma.rn.f16x2 p1, qz29, qz29, c; mul.rn.f16x2 a0, qz28, p0; fma.rn.f16x2 g9, qz25, h1, qz25; prmt.b32 h0, lo0, hi0, 0x5410;\n"
        "mov.b32 {xl, xh}, a0; tanh.approx.f16 xr, xl; cvt.u32.u16 lo0, xr; tanh.approx.f16 xr, xh; cvt.u32.u16 hi0, xr; fma.rn.f16x2 p0, qz30, qz30, c; mul.rn.f16x2 a1, qz29, p1; fma.rn.f16x2 g10, qz26, h0, qz26; prmt.b32 h1, lo1, hi1, 0x5410;\n"
        "mov.b32 {xl, xh}, a1; tanh.approx.f16 xr, xl; cvt.u32.u16 lo1, xr; tanh.approx.f16 xr, xh; cvt.u32.u16 hi1, xr; fma.rn.f16x2 p1, qz31, qz31, c; mul.rn.f16x2 a0, qz30, p0; fma.rn.f16x2 g11, qz27, h1, qz27; prmt.b32 h0, lo0, hi0, 0x5410;\n"
        "B62:\n"
        "wgmma.wait_group.sync.aligned 1;\n"
        "wgmma.fence.sync.aligned;\n"
        "add.s64 dt, w2d, 896; wgmma.mma_async.sync.aligned.m64n96k16.f16.f16.f16 {o0,o1,o2,o3,o4,o5,o6,o7,o8,o9,o10,o11,o12,o13,o14,o15,o16,o17,o18,o19,o20,o21,o22,o23}, {g8,g9,g10,g11}, dt, pt, 1, 1, 1;\n"
        "wgmma.commit_group.sync.aligned;\n"
        "@pz bra.uni B66;\n"
        "mov.b32 {xl, xh}, a0; tanh.approx.f16 xr, xl; cvt.u32.u16 lo0, xr; tanh.approx.f16 xr, xh; cvt.u32.u16 hi0, xr; fma.rn.f16x2 p0, qz0, qz0, c; mul.rn.f16x2 a1, qz31, p1; fma.rn.f16x2 g12, qz28, h0, qz28; prmt.b32 h1, lo1, hi1, 0x5410;\n"
        "mov.b32 {xl, xh}, a1; tanh.approx.f16 xr, xl; cvt.u32.u16 lo1, xr; tanh.approx.f16 xr, xh; cvt.u32.u16 hi1, xr; fma.rn.f16x2 p1, qz1, qz1, c; mul.rn.f16x2 a0, qz0, p0; fma.rn.f16x2 g13, qz29, h1, qz29; prmt.b32 h0, lo0, hi0, 0x5410;\n"
        "mov.b32 {xl, xh}, a0; tanh.approx.f16 xr, xl; cvt.u32.u16 lo0, xr; tanh.approx.f16 xr, xh; cvt.u32.u16 hi0, xr; fma.rn.f16x2 p0, qz2, qz2, c; mul.rn.f16x2 a1, qz1, p1; fma.rn.f16x2 g14, qz30, h0, qz30; prmt.b32 h1, lo1, hi1, 0x5410;\n"
        "mov.b32 {xl, xh}, a1; tanh.approx.f16 xr, xl; cvt.u32.u16 lo1, xr; tanh.approx.f16 xr, xh; cvt.u32.u16 hi1, xr; fma.rn.f16x2 p1, qz3, qz3, c; mul.rn.f16x2 a0, qz2, p0; fma.rn.f16x2 g15, qz31, h1, qz31; prmt.b32 h0, lo0, hi0, 0x5410;\n"
        "B66:\n"
        "wgmma.fence.sync.aligned;\n"
        "add.s64 dt, w2d, 960; wgmma.mma_async.sync.aligned.m64n96k16.f16.f16.f16 {o0,o1,o2,o3,o4,o5,o6,o7,o8,o9,o10,o11,o12,o13,o14,o15,o16,o17,o18,o19,o20,o21,o22,o23}, {g12,g13,g14,g15}, dt, pt, 1, 1, 1;\n"
        "add.s64 dt, w1d, 3840; wgmma.mma_async.sync.aligned.m64n64k16.f16.f16.f16 {qz16,qz17,qz18,qz19,qz20,qz21,qz22,qz23,qz24,qz25,qz26,qz27,qz28,qz29,qz30,qz31}, {qa0,qa1,qa2,qa3}, dt, pf, 1, 1, 1;\n"
        "add.s64 dt, w1d, 3968; wgmma.mma_async.sync.aligned.m64n64k16.f16.f16.f16 {qz16,qz17,qz18,qz19,qz20,qz21,qz22,qz23,qz24,qz25,qz26,qz27,qz28,qz29,qz30,qz31}, {qa4,qa5,qa6,qa7}, dt, pt, 1, 1, 1;\n"
        "add.s64 dt, w1d, 4096; wgmma.mma_async.sync.aligned.m64n64k16.f16.f16.f16 {qz16,qz17,qz18,qz19,qz20,qz21,qz22,qz23,qz24,qz25,qz26,qz27,qz28,qz29,qz30,qz31}, {qa8,qa9,qa10,qa11}, dt, pt, 1, 1, 1;\n"
        "wgmma.commit_group.sync.aligned;\n"
        "@pz bra.uni B70;\n"
        "mov.b32 {xl, xh}, a0; tanh.approx.f16 xr, xl; cvt.u32.u16 lo0, xr; tanh.approx.f16 xr, xh; cvt.u32.u16 hi0, xr; fma.rn.f16x2 p0, qz4, qz4, c; mul.rn.f16x2 a1, qz3, p1; fma.rn.f16x2 g0, qz0, h0, qz0; prmt.b32 h1, lo1, hi1, 0x5410;\n"
        "mov.b32 {xl, xh}, a1; tanh.approx.f16 xr, xl; cvt.u32.u16 lo1, xr; tanh.approx.f16 xr, xh; cvt.u32.u16 hi1, xr; fma.rn.f16x2 p1, qz5, qz5, c; mul.rn.f16x2 a0, qz4, p0; fma.rn.f16x2 g1, qz1, h1, qz1; prmt.b32 h0, lo0, hi0, 0x5410;\n"
        "mov.b32 {xl, xh}, a0; tanh.approx.f16 xr, xl; cvt.u32.u16 lo0, xr; tanh.approx.f16 xr, xh; cvt.u32.u16 hi0, xr; fma.rn.f16x2 p0, qz6, qz6, c; mul.rn.f16x2 a1, qz5, p1; fma.rn.f16x2 g2, qz2, h0, qz2; prmt.b32 h1, lo1, hi1, 0x5410;\n"
        "mov.b32 {xl, xh}, a1; tanh.approx.f16 xr, xl; cvt.u32.u16 lo1, xr; tanh.approx.f16 xr, xh; cvt.u32.u16 hi1, xr; fma.rn.f16x2 p1, qz7, qz7, c; mul.rn.f16x2 a0, qz6, p0; fma.rn.f16x2 g3, qz3, h1, qz3; prmt.b32 h0, lo0, hi0, 0x5410;\n"
        "B70:\n"
        "wgmma.wait_group.sync.aligned 2;\n"
        "wgmma.fence.sync.aligned;\n"
        "add.s64 dt, w2d, 1024; wgmma.mma_async.sync.aligned.m64n96k16.f16.f16.f16 {o0,o1,o2,o3,o4,o5,o6,o7,o8,o9,o10,o11,o12,o13,o14,o15,o16,o17,o18,o19,o20,o21,o22,o23}, {g0,g1,g2,g3}, dt, pt, 1, 1, 1;\n"
        "add.s64 dt, w1d, 4224; wgmma.mma_async.sync.aligned.m64n64k16.f16.f16.f16 {qz16,qz17,qz18,qz19,qz20,qz21,qz22,qz23,qz24,qz25,qz26,qz27,qz28,qz29,qz30,qz31}, {qa12,qa13,qa14,qa15}, dt, pt, 1, 1, 1;\n"
        "add.s64 dt, w1d, 4352; wgmma.mma_async.sync.aligned.m64n64k16.f16.f16.f16 {qz16,qz17,qz18,qz19,qz20,qz21,qz22,qz23,qz24,qz25,qz26,qz27,qz28,qz29,qz30,qz31}, {qa16,qa17,qa18,qa19}, dt, pt, 1, 1, 1;\n"
        "add.s64 dt, w1d, 4480; wgmma.mma_async.sync.aligned.m64n64k16.f16.f16.f16 {qz16,qz17,qz18,qz19,qz20,qz21,qz22,qz23,qz24,qz25,qz26,qz27,qz28,qz29,qz30,qz31}, {qa20,qa21,qa22,qa23}, dt, pt, 1, 1, 1;\n"
        "wgmma.commit_group.sync.aligned;\n"
        "@pz bra.uni B74;\n"
        "mov.b32 {xl, xh}, a0; tanh.approx.f16 xr, xl; cvt.u32.u16 lo0, xr; tanh.approx.f16 xr, xh; cvt.u32.u16 hi0, xr; fma.rn.f16x2 p0, qz8, qz8, c; mul.rn.f16x2 a1, qz7, p1; fma.rn.f16x2 g4, qz4, h0, qz4; prmt.b32 h1, lo1, hi1, 0x5410;\n"
        "mov.b32 {xl, xh}, a1; tanh.approx.f16 xr, xl; cvt.u32.u16 lo1, xr; tanh.approx.f16 xr, xh; cvt.u32.u16 hi1, xr; fma.rn.f16x2 p1, qz9, qz9, c; mul.rn.f16x2 a0, qz8, p0; fma.rn.f16x2 g5, qz5, h1, qz5; prmt.b32 h0, lo0, hi0, 0x5410;\n"
        "mov.b32 {xl, xh}, a0; tanh.approx.f16 xr, xl; cvt.u32.u16 lo0, xr; tanh.approx.f16 xr, xh; cvt.u32.u16 hi0, xr; fma.rn.f16x2 p0, qz10, qz10, c; mul.rn.f16x2 a1, qz9, p1; fma.rn.f16x2 g6, qz6, h0, qz6; prmt.b32 h1, lo1, hi1, 0x5410;\n"
        "mov.b32 {xl, xh}, a1; tanh.approx.f16 xr, xl; cvt.u32.u16 lo1, xr; tanh.approx.f16 xr, xh; cvt.u32.u16 hi1, xr; fma.rn.f16x2 p1, qz11, qz11, c; mul.rn.f16x2 a0, qz10, p0; fma.rn.f16x2 g7, qz7, h1, qz7; prmt.b32 h0, lo0, hi0, 0x5410;\n"
        "B74:\n"
        "wgmma.wait_group.sync.aligned 2;\n"
        "wgmma.fence.sync.aligned;\n"
        "add.s64 dt, w2d, 1088; wgmma.mma_async.sync.aligned.m64n96k16.f16.f16.f16 {o0,o1,o2,o3,o4,o5,o6,o7,o8,o9,o10,o11,o12,o13,o14,o15,o16,o17,o18,o19,o20,o21,o22,o23}, {g4,g5,g6,g7}, dt, pt, 1, 1, 1;\n"
        "wgmma.commit_group.sync.aligned;\n"
        "@pz bra.uni B78;\n"
        "mov.b32 {xl, xh}, a0; tanh.approx.f16 xr, xl; cvt.u32.u16 lo0, xr; tanh.approx.f16 xr, xh; cvt.u32.u16 hi0, xr; fma.rn.f16x2 p0, qz12, qz12, c; mul.rn.f16x2 a1, qz11, p1; fma.rn.f16x2 g8, qz8, h0, qz8; prmt.b32 h1, lo1, hi1, 0x5410;\n"
        "mov.b32 {xl, xh}, a1; tanh.approx.f16 xr, xl; cvt.u32.u16 lo1, xr; tanh.approx.f16 xr, xh; cvt.u32.u16 hi1, xr; fma.rn.f16x2 p1, qz13, qz13, c; mul.rn.f16x2 a0, qz12, p0; fma.rn.f16x2 g9, qz9, h1, qz9; prmt.b32 h0, lo0, hi0, 0x5410;\n"
        "mov.b32 {xl, xh}, a0; tanh.approx.f16 xr, xl; cvt.u32.u16 lo0, xr; tanh.approx.f16 xr, xh; cvt.u32.u16 hi0, xr; fma.rn.f16x2 p0, qz14, qz14, c; mul.rn.f16x2 a1, qz13, p1; fma.rn.f16x2 g10, qz10, h0, qz10; prmt.b32 h1, lo1, hi1, 0x5410;\n"
        "mov.b32 {xl, xh}, a1; tanh.approx.f16 xr, xl; cvt.u32.u16 lo1, xr; tanh.approx.f16 xr, xh; cvt.u32.u16 hi1, xr; fma.rn.f16x2 p1, qz15, qz15, c; mul.rn.f16x2 a0, qz14, p0; fma.rn.f16x2 g11, qz11, h1, qz11; prmt.b32 h0, lo0, hi0, 0x5410;\n"
        "B78:\n"
        "wgmma.wait_group.sync.aligned 1;\n"
        "wgmma.fence.sync.aligned;\n"
        "add.s64 dt, w2d, 1152; wgmma.mma_async.sync.aligned.m64n96k16.f16.f16.f16 {o0,o1,o2,o3,o4,o5,o6,o7,o8,o9,o10,o11,o12,o13,o14,o15,o16,o17,o18,o19,o20,o21,o22,o23}, {g8,g9,g10,g11}, dt, pt, 1, 1, 1;\n"
        "wgmma.commit_group.sync.aligned;\n"
        "@!pm bra.uni BACKY;\n"
        "add.u32 tt, n, 1; and.b32 tt, tt, 1; mbarrier.try_wait.parity.shared::cta.b64 pw, [ybar], tt;\n"
        "@!pw bra.uni SPINY;\n"
        "BACKY:\n"
        "@pz bra.uni B80;\n"
        "and.b32 ad, %5, 0xffff; xor.b32 ad, ad, 0; add.u32 ad, ad, %4; ldmatrix.sync.aligned.m8n8.x4.shared.b16 {qa0,qa1,qa2,qa3}, [ad];\n"
        "and.b32 ad, %5, 0xffff; xor.b32 ad, ad, 32; add.u32 ad, ad, %4; ldmatrix.sync.aligned.m8n8.x4.shared.b16 {qa4,qa5,qa6,qa7}, [ad];\n"
        "and.b32 ad, %5, 0xffff; xor.b32 ad, ad, 64; add.u32 ad, ad, %4; ldmatrix.sync.aligned.m8n8.x4.shared.b16 {qa8,qa9,qa10,qa11}, [ad];\n"
        "and.b32 ad, %5, 0xffff; xor.b32 ad, ad, 96; add.u32 ad, ad, %4; ldmatrix.sync.aligned.m8n8.x4.shared.b16 {qa12,qa13,qa14,qa15}, [ad];\n"
        "shr.u32 ad, %5, 16; xor.b32 ad, ad, 0; add.u32 ad, ad, %4; ldmatrix.sync.aligned.m8n8.x4.shared.b16 {qa16,qa17,qa18,qa19}, [ad];\n"
        "shr.u32 ad, %5, 16; xor.b32 ad, ad, 32; add.u32 ad, ad, %4; ldmatrix.sync.aligned.m8n8.x4.shared.b16 {qa20,qa21,qa22,qa23}, [ad];\n"
        "mov.b32 {xl, xh}, a0; tanh.approx.f16 xr, xl; cvt.u32.u16 lo0, xr; tanh.approx.f16 xr, xh; cvt.u32.u16 hi0, xr; fma.rn.f16x2 p0, qz16, qz16, c; mul.rn.f16x2 a1, qz15, p1; fma.rn.f16x2 g12, qz12, h0, qz12; prmt.b32 h1, lo1, hi1, 0x5410;\n"
        "mov.b32 {xl, xh}, a1; tanh.approx.f16 xr, xl; cvt.u32.u16 lo1, xr; tanh.approx.f16 xr, xh; cvt.u32.u16 hi1, xr; fma.rn.f16x2 p1, qz17, qz17, c; mul.rn.f16x2 a0, qz16, p0; fma.rn.f16x2 g13, qz13, h1, qz13; prmt.b32 h0, lo0, hi0, 0x5410;\n"
        "B80:\n"
        "fence.proxy.async.shared::cta;\n"
        "add.u32 tt, id, 0;\n"
        "@pk bra.uni XLOAD;\n"
        "bar.arrive tt, 128;\n"
        "XLOADB:\n"
        "@pz bra.uni B82;\n"
        "mov.b32 {xl, xh}, a0; tanh.approx.f16 xr, xl; cvt.u32.u16 lo0, xr; tanh.approx.f16 xr, xh; cvt.u32.u16 hi0, xr; fma.rn.f16x2 p0, qz18, qz18, c; mul.rn.f16x2 a1, qz17, p1; fma.rn.f16x2 g14, qz14, h0, qz14; prmt.b32 h1, lo1, hi1, 0x5410;\n"
        "mov.b32 {xl, xh}, a1; tanh.approx.f16 xr, xl; cvt.u32.u16 lo1, xr; tanh.approx.f16 xr, xh; cvt.u32.u16 hi1, xr; fma.rn.f16x2 p1, qz19, qz19, c; mul.rn.f16x2 a0, qz18, p0; fma.rn.f16x2 g15, qz15, h1, qz15; prmt.b32 h0, lo0, hi0, 0x5410;\n"
        "B82:\n"
        "wgmma.fence.sync.aligned;\n"
        "add.s64 dt, w2d, 1216; wgmma.mma_async.sync.aligned.m64n96k16.f16.f16.f16 {o0,o1,o2,o3,o4,o5,o6,o7,o8,o9,o10,o11,o12,o13,o14,o15,o16,o17,o18,o19,o20,o21,o22,o23}, {g12,g13,g14,g15}, dt, pt, 1, 1, 1;\n"
        "wgmma.commit_group.sync.aligned;\n"
        "@!pm bra.uni SKIP1;\n"
        "wgmma.fence.sync.aligned;\n"
        "add.s64 dt, w1d, 0; wgmma.mma_async.sync.aligned.m64n64k16.f16.f16.f16 {qz0,qz1,qz2,qz3,qz4,qz5,qz6,qz7,qz8,qz9,qz10,qz11,qz12,qz13,qz14,qz15}, {qa0,qa1,qa2,qa3}, dt, pf, 1, 1, 1;\n"
        "add.s64 dt, w1d, 128; wgmma.mma_async.sync.aligned.m64n64k16.f16.f16.f16 {qz0,qz1,qz2,qz3,qz4,qz5,qz6,qz7,qz8,qz9,qz10,qz11,qz12,qz13,qz14,qz15}, {qa4,qa5,qa6,qa7}, dt, pt, 1, 1, 1;\n"
        "add.s64 dt, w1d, 256; wgmma.mma_async.sync.aligned.m64n64k16.f16.f16.f16 {qz0,qz1,qz2,qz3,qz4,qz5,qz6,qz7,qz8,qz9,qz10,qz11,qz12,qz13,qz14,qz15}, {qa8,qa9,qa10,qa11}, dt, pt, 1, 1, 1;\n"
        "SKIP1:\n"
        "@pz bra.uni B86;\n"
        "mov.b32 {xl, xh}, a0; tanh.approx.f16 xr, xl; cvt.u32.u16 lo0, xr; tanh.approx.f16 xr, xh; cvt.u32.u16 hi0, xr; fma.rn.f16x2 p0, qz20, qz20, c; mul.rn.f16x2 a1, qz19, p1; fma.rn.f16x2 g0, qz16, h0, qz16; prmt.b32 h1, lo1, hi1, 0x5410;\n"
        "mov.b32 {xl, xh}, a1; tanh.approx.f16 xr, xl; cvt.u32.u16 lo1, xr; tanh.approx.f16 xr, xh; cvt.u32.u16 hi1, xr; fma.rn.f16x2 p1, qz21, qz21, c; mul.rn.f16x2 a0, qz20, p0; fma.rn.f16x2 g1, qz17, h1, qz17; prmt.b32 h0, lo0, hi0, 0x5410;\n"
        "mov.b32 {xl, xh}, a0; tanh.approx.f16 xr, xl; cvt.u32.u16 lo0, xr; tanh.approx.f16 xr, xh; cvt.u32.u16 hi0, xr; fma.rn.f16x2 p0, qz22, qz22, c; mul.rn.f16x2 a1, qz21, p1; fma.rn.f16x2 g2, qz18, h0, qz18; prmt.b32 h1, lo1, hi1, 0x5410;\n"
        "mov.b32 {xl, xh}, a1; tanh.approx.f16 xr, xl; cvt.u32.u16 lo1, xr; tanh.approx.f16 xr, xh; cvt.u32.u16 hi1, xr; fma.rn.f16x2 p1, qz23, qz23, c; mul.rn.f16x2 a0, qz22, p0; fma.rn.f16x2 g3, qz19, h1, qz19; prmt.b32 h0, lo0, hi0, 0x5410;\n"
        "B86:\n"
        "wgmma.wait_group.sync.aligned 2;\n"
        "wgmma.fence.sync.aligned;\n"
        "add.s64 dt, w2d, 1280; wgmma.mma_async.sync.aligned.m64n96k16.f16.f16.f16 {o0,o1,o2,o3,o4,o5,o6,o7,o8,o9,o10,o11,o12,o13,o14,o15,o16,o17,o18,o19,o20,o21,o22,o23}, {g0,g1,g2,g3}, dt, pt, 1, 1, 1;\n"
        "wgmma.commit_group.sync.aligned;\n"
        "@!pm bra.uni SKIP2;\n"
        "wgmma.fence.sync.aligned;\n"
        "add.s64 dt, w1d, 384; wgmma.mma_async.sync.aligned.m64n64k16.f16.f16.f16 {qz0,qz1,qz2,qz3,qz4,qz5,qz6,qz7,qz8,qz9,qz10,qz11,qz12,qz13,qz14,qz15}, {qa12,qa13,qa14,qa15}, dt, pt, 1, 1, 1;\n"
        "add.s64 dt, w1d, 512; wgmma.mma_async.sync.aligned.m64n64k16.f16.f16.f16 {qz0,qz1,qz2,qz3,qz4,qz5,qz6,qz7,qz8,qz9,qz10,qz11,qz12,qz13,qz14,qz15}, {qa16,qa17,qa18,qa19}, dt, pt, 1, 1, 1;\n"
        "add.s64 dt, w1d, 640; wgmma.mma_async.sync.aligned.m64n64k16.f16.f16.f16 {qz0,qz1,qz2,qz3,qz4,qz5,qz6,qz7,qz8,qz9,qz10,qz11,qz12,qz13,qz14,qz15}, {qa20,qa21,qa22,qa23}, dt, pt, 1, 1, 1;\n"
        "SKIP2:\n"
        "wgmma.fence.sync.aligned;\n"
        "wgmma.commit_group.sync.aligned;\n"
        "@pz bra.uni B90;\n"
        "mov.b32 {xl, xh}, a0; tanh.approx.f16 xr, xl; cvt.u32.u16 lo0, xr; tanh.approx.f16 xr, xh; cvt.u32.u16 hi0, xr; fma.rn.f16x2 p0, qz24, qz24, c; mul.rn.f16x2 a1, qz23, p1; fma.rn.f16x2 g4, qz20, h0, qz20; prmt.b32 h1, lo1, hi1, 0x5410;\n"
        "mov.b32 {xl, xh}, a1; tanh.approx.f16 xr, xl; cvt.u32.u16 lo1, xr; tanh.approx.f16 xr, xh; cvt.u32.u16 hi1, xr; fma.rn.f16x2 p1, qz25, qz25, c; mul.rn.f16x2 a0, qz24, p0; fma.rn.f16x2 g5, qz21, h1, qz21; prmt.b32 h0, lo0, hi0, 0x5410;\n"
        "mov.b32 {xl, xh}, a0; tanh.approx.f16 xr, xl; cvt.u32.u16 lo0, xr; tanh.approx.f16 xr, xh; cvt.u32.u16 hi0, xr; fma.rn.f16x2 p0, qz26, qz26, c; mul.rn.f16x2 a1, qz25, p1; fma.rn.f16x2 g6, qz22, h0, qz22; prmt.b32 h1, lo1, hi1, 0x5410;\n"
        "mov.b32 {xl, xh}, a1; tanh.approx.f16 xr, xl; cvt.u32.u16 lo1, xr; tanh.approx.f16 xr, xh; cvt.u32.u16 hi1, xr; fma.rn.f16x2 p1, qz27, qz27, c; mul.rn.f16x2 a0, qz26, p0; fma.rn.f16x2 g7, qz23, h1, qz23; prmt.b32 h0, lo0, hi0, 0x5410;\n"
        "B90:\n"
        "wgmma.wait_group.sync.aligned 3;\n"
        "wgmma.fence.sync.aligned;\n"
        "add.s64 dt, w2d, 1344; wgmma.mma_async.sync.aligned.m64n96k16.f16.f16.f16 {o0,o1,o2,o3,o4,o5,o6,o7,o8,o9,o10,o11,o12,o13,o14,o15,o16,o17,o18,o19,o20,o21,o22,o23}, {g4,g5,g6,g7}, dt, pt, 1, 1, 1;\n"
        "wgmma.commit_group.sync.aligned;\n"
        "@pz bra.uni B94;\n"
        "mov.b32 {xl, xh}, a0; tanh.approx.f16 xr, xl; cvt.u32.u16 lo0, xr; tanh.approx.f16 xr, xh; cvt.u32.u16 hi0, xr; fma.rn.f16x2 p0, qz28, qz28, c; mul.rn.f16x2 a1, qz27, p1; fma.rn.f16x2 g8, qz24, h0, qz24; prmt.b32 h1, lo1, hi1, 0x5410;\n"
        "mov.b32 {xl, xh}, a1; tanh.approx.f16 xr, xl; cvt.u32.u16 lo1, xr; tanh.approx.f16 xr, xh; cvt.u32.u16 hi1, xr; fma.rn.f16x2 p1, qz29, qz29, c; mul.rn.f16x2 a0, qz28, p0; fma.rn.f16x2 g9, qz25, h1, qz25; prmt.b32 h0, lo0, hi0, 0x5410;\n"
        "mov.b32 {xl, xh}, a0; tanh.approx.f16 xr, xl; cvt.u32.u16 lo0, xr; tanh.approx.f16 xr, xh; cvt.u32.u16 hi0, xr; fma.rn.f16x2 p0, qz30, qz30, c; mul.rn.f16x2 a1, qz29, p1; fma.rn.f16x2 g10, qz26, h0, qz26; prmt.b32 h1, lo1, hi1, 0x5410;\n"
        "mov.b32 {xl, xh}, a1; tanh.approx.f16 xr, xl; cvt.u32.u16 lo1, xr; tanh.approx.f16 xr, xh; cvt.u32.u16 hi1, xr; fma.rn.f16x2 p1, qz31, qz31, c; mul.rn.f16x2 a0, qz30, p0; fma.rn.f16x2 g11, qz27, h1, qz27; prmt.b32 h0, lo0, hi0, 0x5410;\n"
        "B94:\n"
        "wgmma.wait_group.sync.aligned 1;\n"
        "wgmma.fence.sync.aligned;\n"
        "add.s64 dt, w2d, 1408; wgmma.mma_async.sync.aligned.m64n96k16.f16.f16.f16 {o0,o1,o2,o3,o4,o5,o6,o7,o8,o9,o10,o11,o12,o13,o14,o15,o16,o17,o18,o19,o20,o21,o22,o23}, {g8,g9,g10,g11}, dt, pt, 1, 1, 1;\n"
        "wgmma.commit_group.sync.aligned;\n"
        "@pz bra.uni B2;\n"
        "mov.b32 {xl, xh}, a0; tanh.approx.f16 xr, xl; cvt.u32.u16 lo0, xr; tanh.approx.f16 xr, xh; cvt.u32.u16 hi0, xr; fma.rn.f16x2 p0, qz0, qz0, c; mul.rn.f16x2 a1, qz31, p1; fma.rn.f16x2 g12, qz28, h0, qz28; prmt.b32 h1, lo1, hi1, 0x5410;\n"
        "mov.b32 {xl, xh}, a1; tanh.approx.f16 xr, xl; cvt.u32.u16 lo1, xr; tanh.approx.f16 xr, xh; cvt.u32.u16 hi1, xr; fma.rn.f16x2 p1, qz1, qz1, c; mul.rn.f16x2 a0, qz0, p0; fma.rn.f16x2 g13, qz29, h1, qz29; prmt.b32 h0, lo0, hi0, 0x5410;\n"
        "mov.b32 {xl, xh}, a0; tanh.approx.f16 xr, xl; cvt.u32.u16 lo0, xr; tanh.approx.f16 xr, xh; cvt.u32.u16 hi0, xr; fma.rn.f16x2 p0, qz2, qz2, c; mul.rn.f16x2 a1, qz1, p1; fma.rn.f16x2 g14, qz30, h0, qz30; prmt.b32 h1, lo1, hi1, 0x5410;\n"
        "mov.b32 {xl, xh}, a1; tanh.approx.f16 xr, xl; cvt.u32.u16 lo1, xr; tanh.approx.f16 xr, xh; cvt.u32.u16 hi1, xr; fma.rn.f16x2 p1, qz3, qz3, c; mul.rn.f16x2 a0, qz2, p0; fma.rn.f16x2 g15, qz31, h1, qz31; prmt.b32 h0, lo0, hi0, 0x5410;\n"
        "B2:\n"
        "wgmma.fence.sync.aligned;\n"
        "add.s64 dt, w2d, 1472; wgmma.mma_async.sync.aligned.m64n96k16.f16.f16.f16 {o0,o1,o2,o3,o4,o5,o6,o7,o8,o9,o10,o11,o12,o13,o14,o15,o16,o17,o18,o19,o20,o21,o22,o23}, {g12,g13,g14,g15}, dt, pt, 1, 1, 1;\n"
        "wgmma.commit_group.sync.aligned;\n"
        "@pz bra.uni BE;\n"
        "mov.b32 {xl, xh}, a0; tanh.approx.f16 xr, xl; cvt.u32.u16 lo0, xr; tanh.approx.f16 xr, xh; cvt.u32.u16 hi0, xr; fma.rn.f16x2 p0, qz4, qz4, c; mul.rn.f16x2 a1, qz3, p1; fma.rn.f16x2 g0, qz0, h0, qz0; prmt.b32 h1, lo1, hi1, 0x5410;\n"
        "mov.b32 {xl, xh}, a1; tanh.approx.f16 xr, xl; cvt.u32.u16 lo1, xr; tanh.approx.f16 xr, xh; cvt.u32.u16 hi1, xr; fma.rn.f16x2 p1, qz5, qz5, c; mul.rn.f16x2 a0, qz4, p0; fma.rn.f16x2 g1, qz1, h1, qz1; prmt.b32 h0, lo0, hi0, 0x5410;\n"
        "mov.b32 {xl, xh}, a0; tanh.approx.f16 xr, xl; cvt.u32.u16 lo0, xr; tanh.approx.f16 xr, xh; cvt.u32.u16 hi0, xr; fma.rn.f16x2 p0, qz6, qz6, c; mul.rn.f16x2 a1, qz5, p1; fma.rn.f16x2 g2, qz2, h0, qz2; prmt.b32 h1, lo1, hi1, 0x5410;\n"
        "mov.b32 {xl, xh}, a1; tanh.approx.f16 xr, xl; cvt.u32.u16 lo1, xr; tanh.approx.f16 xr, xh; cvt.u32.u16 hi1, xr; fma.rn.f16x2 p1, qz7, qz7, c; mul.rn.f16x2 a0, qz6, p0; fma.rn.f16x2 g3, qz3, h1, qz3; prmt.b32 h0, lo0, hi0, 0x5410;\n"
        "BE:\n"
        "wgmma.wait_group.sync.aligned 0;\n"
        "bra.uni LOOP;\n"
        "STORE:\n"
        "bar.sync tt, 128;\n"
        "setp.lt.s32 pr, n, 0;\n"
        "@pr bra.uni STOREB;\n"
        "cvt.u64.u32 gp, off; add.s64 gp, gp, %11;\n"
        "elect.sync _|pr, 0xffffffff;\n"
        "@pr cp.async.bulk.global.shared::cta.bulk_group [gp], [%4], 12288;\n"
        "@pr cp.async.bulk.commit_group;\n"
        "bra.uni STOREB;\n"
        "YLOAD:\n"
        "@!pm bra.uni YLOADP;\n"
        "cp.async.bulk.wait_group.read 0;\n"
        "sub.u32 ad, off, %12; cvt.u64.u32 gp, ad; add.s64 gp, gp, %11;\n"
        "elect.sync _|pr, 0xffffffff;\n"
        "@pr mbarrier.arrive.expect_tx.shared::cta.b64 _, [ybar], 12288;\n"
        "@pr cp.async.bulk.shared::cluster.global.mbarrier::complete_tx::bytes [%4], [gp], 12288, [ybar];\n"
        "YLOADP:\n"
        "cvt.u64.u32 gp, off; add.s64 gp, gp, %10;\n"
        "elect.sync _|pr, 0xffffffff;\n"
        "@pr cp.async.bulk.prefetch.L2.global.L2::cache_hint [gp], 12288, pol;\n"
        "bra.uni YLOADB;\n"
        "XLOAD:\n"
        "bar.sync tt, 128;\n"
        "cp.async.bulk.wait_group.read 0;\n"
        "cvt.u64.u32 gp, off; add.s64 gp, gp, %10;\n"
        "elect.sync _|pr, 0xffffffff;\n"
        "@pr mbarrier.arrive.expect_tx.shared::cta.b64 _, [xbar], 12288;\n"
        "@pr cp.async.bulk.shared::cluster.global.mbarrier::complete_tx::bytes.L2::cache_hint [%4], [gp], 12288, [xbar], pol;\n"
        "bra.uni XLOADB;\n"
        "SPINY: mov.u32 cnt, 0;\n"
        "SPINYL:\n"
        "add.u32 tt, n, 1; and.b32 tt, tt, 1; mbarrier.try_wait.parity.shared::cta.b64 pw, [ybar], tt;\n"
        "@pw bra.uni BACKY;\n"
        "add.u32 cnt, cnt, 1; setp.lt.u32 pw, cnt, 0x100000;\n"
        "@pw bra.uni SPINYL;\n"
        "trap;\n"
        "SPINX: mov.u32 cnt, 0;\n"
        "SPINXL:\n"
        "and.b32 tt, n, 1; mbarrier.try_wait.parity.shared::cta.b64 pw, [xbar], tt;\n"
        "@pw bra.uni BACKX;\n"
        "add.u32 cnt, cnt, 1; setp.lt.u32 pw, cnt, 0x100000;\n"
        "@pw bra.uni SPINXL;\n"
        "trap;\n"
        "SPINT: mov.u32 cnt, 0;\n"
        "SPINTL:\n"
        "mad.lo.u32 tt, n, 8, tbar; mbarrier.try_wait.parity.shared::cta.b64 pw, [tt], tpar;\n"
        "@pw bra.uni BACKT;\n"
        "add.u32 cnt, cnt, 1; setp.lt.u32 pw, cnt, 0x100000;\n"
        "@pw bra.uni SPINTL;\n"
        "trap;\n"
        "DONE:\n"
        "wgmma.wait_group.sync.aligned 0;\n"
        "}\n"
        :: "r"(prm.w1desc), "r"(prm.w2desc), "r"(c.wg), "r"(c.off), "r"(c.xs), "r"(c.a_offs), "r"(c.xs_offs), "r"(c.bias_addr),
           "r"(c.out_scale), "r"(c.w), "l"(prm.x), "l"(prm.out), "r"(c.step)
        : "memory");
}

__device__ __forceinline__ void start_first_tile(const Pass2& c, const Params& prm) {
    if (c.wg == 3) mbar_wait_c<0>(sb + SM_BAR + (BAR_Y2FULL + 3) * 8);
    first_gemm(c.xs, c.a_offs, prm.w1desc);
}

__device__ __forceinline__ float warp_sum(float v) {
#pragma unroll
    for (int s = 16; s >= 1; s >>= 1) v += __shfl_xor_sync(0xffffffffu, v, s);
    return v;
}
__device__ __forceinline__ float pow2f(int e) { return __uint_as_float((uint32_t)(e + 127) << 23); }
__device__ __forceinline__ int exponent_of(float v) { return (int)(__float_as_uint(v) >> 23) - 127; }
__device__ __forceinline__ float lds_bf16(uint32_t addr) {
    uint16_t v; asm volatile("ld.shared.u16 %0, [%1];" : "=h"(v) : "r"(addr) : "memory"); return bf_lo(v);
}

__device__ __forceinline__ void publish_bias(const Params& prm, uint32_t c, uint32_t tag) {
    const uint32_t lane = fresh_tid() & 31;
    const uint32_t col = sb + SM_W2 + (c >> 5) * 24576 + lane * 64 + ((((c >> 3) ^ (lane >> 1)) & 3) * 16) + (c & 7) * 2;
    float v = 0.0f;
#pragma unroll
    for (int k = 0; k < EX / 32; k++) v = fmaf(lds_bf16(col + k * 2048), lds_bf16(sb + SM_BETA + lane * 2 + k * 64), v);
    v = warp_sum(v);
    if (lane == 0) asm volatile("st.relaxed.gpu.global.v2.b32 [%0], {%1, %2};" ::"l"(prm.g->bias + c), "f"(v), "r"(tag) : "memory");
}
__device__ __forceinline__ void collect_bias(const Params& prm, uint32_t tag) {
    const uint32_t lane = fresh_tid() & 31;
    if (lane < 24) {
        const unsigned long long* src = prm.g->bias + 32 * (lane >> 3) + 8 * (lane & 3) + (lane & 4);
        uint32_t v[4], t[4], spins = 0;
        for (;;) {
#pragma unroll
            for (int k = 0; k < 4; k++)
                asm volatile("ld.relaxed.gpu.global.v2.b32 {%0, %1}, [%2];" : "=r"(v[k]), "=r"(t[k]) : "l"(src + k) : "memory");
            if (t[0] == tag && t[1] == tag && t[2] == tag && t[3] == tag) break;
            if (++spins > (1u << 22)) __trap();
        }
        sts128(sb + SM_BIAS + lane * 16, v[0], v[1], v[2], v[3]);
    }
    __syncwarp();
}
__device__ __forceinline__ float fetch_w2_row(uint32_t (&u)[12][4], uint32_t row, uint32_t sw) {
    uint32_t mx[4] = {};
#pragma unroll
    for (int a = 0; a < 3; a++)
#pragma unroll
        for (int k = 0; k < 4; k++) {
            asm volatile("ld.shared.v4.b32 {%0,%1,%2,%3}, [%4];"
                         : "=r"(u[a * 4][k]), "=r"(u[a * 4 + 1][k]), "=r"(u[a * 4 + 2][k]), "=r"(u[a * 4 + 3][k])
                         : "r"(row + a * 24576 + ((k * 16) ^ sw)) : "memory");
#pragma unroll
            for (int b = 0; b < 4; b++) asm("max.xorsign.abs.bf16x2 %0, %0, %1;" : "+r"(mx[b]) : "r"(u[a * 4 + b][k]));
        }
#pragma unroll
    for (int b = 1; b < 4; b++) asm("max.xorsign.abs.bf16x2 %0, %0, %1;" : "+r"(mx[0]) : "r"(mx[b]));
    return fmaxf(fabsf(bf_lo(mx[0])), fabsf(bf_hi(mx[0])));
}

__device__ __forceinline__ bool grn_stats(float ss, float gm, float bt, float top, float& gx, float& inv, int& eo) {
    const int warp = fresh_warp();
    gx = sqrt_fast(fmaf(ss, INV_2A * INV_2A, 1e-6f));
    const float rt = sqrt_fast(ss + 1.0f) * INV_2A * top;
    const float r[3] = {warp_sum(gx), warp_sum(fmaf(bt, top, rt)), warp_sum(rt * fabsf(gm) * gx)};
    if ((fresh_tid() & 31) == 0 && warp < 12) {
#pragma unroll
        for (int k = 0; k < 3; k++) sts32(sb + SM_SEL + (k * 12 + warp) * 4, __float_as_uint(r[k]));
    }
    MARK(6);
    const bool bad = __syncthreads_or(!(ss >= 16.0f && ss < ACC_LIMIT));
    MARK(7);
    float tot[3];
#pragma unroll
    for (int k = 0; k < 3; k++) {
        uint32_t v[12];
#pragma unroll
        for (int q = 0; q < 3; q++) lds128(v + 4 * q, sb + SM_SEL + k * 48 + q * 16);
        float p[4];
#pragma unroll
        for (int q = 0; q < 4; q++) p[q] = __uint_as_float(v[q]) + __uint_as_float(v[q + 4]) + __uint_as_float(v[q + 8]);
        tot[k] = (p[0] + p[1]) + (p[2] + p[3]);
    }
    inv = __fdividef(1.0f, fmaf(tot[0], 1.0f / EX, 1e-6f));
    eo = min(max(exponent_of(fmaf(tot[2], inv, tot[1])), -90), 126) - 14;
    return bad;
}

__device__ __forceinline__ float exact_sums(const Params& prm, int e) {
    const int lane = fresh_tid() & 31, warp = fresh_warp(), wg = warp >> 2;
    const uint32_t epoch = lds32(sb + SM_RED + (RED_EPOCH + 1) * 4), bar = sb + SM_BAR + BAR_W1 * 8;
    if (wg < 3) {
        uint32_t wa[2][24], d[2][16];
        float acc[2][2] = {};
        const uint32_t yd = prm.ydesc + ((SM_SPARE - SM_Y1) >> 4), wd = prm.w1desc + ((2 * wg * 12288 + 5 * 2048) >> 4);
        load_w1t(wa, wg, warp & 3, lane);
#pragma unroll 1
        for (int n = 0; n < ROWS_PER_CTA; n++) {
            if (warp == 0) {
                expect_tx(bar, TILE_BYTES);
                bulk_load(sb + SM_SPARE, (const char*)prm.out + (cta_tile0(fresh_cta()) + n * cta_stride(fresh_cta())), TILE_BYTES, bar);
            }
            mbar_wait(bar, (n + 1) & 1);
            gemm1_t<0>(d[0], wa[0], yd, wd);
            gemm1_t<1>(d[1], wa[1], yd, wd);
            wg_wait<0>();
            pin(d[0]); pin(d[1]);
            gelu_sumsq_f(d[0], acc[0]);
            gelu_sumsq_f(d[1], acc[1]);
            named_sync(1, 384);
        }
        publish_sums(acc, prm.g->sums[epoch & 1], &prm.g->count[1], wg, warp & 3, lane);
    }
    grid_wait(&prm.g->count[1], (epoch + 1) * NUM_CTAS);
    return __ldcg(prm.g->sums[epoch & 1] + e);
}

__global__ void __launch_bounds__(512, 1) convnext_kernel(const __grid_constant__ Params prm) {
    extern __shared__ __align__(1024) uint8_t smem[];
    if ((uint32_t)__cvta_generic_to_shared(smem) != sb) __trap();
    if (fresh_warp() >= 12) {
        Producer pc;
        SMARK(0);
        asm volatile("setmaxnreg.inc.sync.aligned.u32 %0;" ::"n"(PRODUCER_REGS));
        SMARK(1);
        const int w = fresh_warp() & 3, lane = fresh_tid() & 31;
        const int j = lane & 7, hb = (lane >> 3) & 1, base = 4 * (2 * w + (lane >> 4));
        pc.lane = lane; pc.warp = w;
        pc.xoff[0] = hb * XHALF_B + base * 192 + j * 16;
        pc.xoff[1] = hb * XHALF_B + base * 192 + 128 + j * 8;
        const int grp = 4 * w + (lane >> 3);
#pragma unroll
        for (int o = 0; o < 2; o++) {
            const int row = (grp & 7) + 8 * (o ^ hb) + 32 * (grp >> 3);
            pc.yoff[0][o] = row * 128 + ((j ^ (row & 7)) * 16);
            pc.yoff[1][o] = 8192 + row * 64 + (((j >> 1) ^ ((row >> 1) & 3)) * 16) + (j & 1) * 8;
        }
        pc.stat = sb + SM_STAT + (8 * w + (lane >> 2)) * 32;
        pc.own = pc.stat + (lane & 3) * 8;
        const int dstep = fresh_cta() & 8 ? 3 * CH * 2 : -3 * CH * 2;
        named_sync(0, 512);
        mbar_wait_c<0>(sb + SM_BAR + BAR_DUMMY * 8);
        SMARK(8);
#pragma unroll
        for (int tap = 0; tap < 9; tap++) {
            const uint32_t dw = sb + SM_Y1 + (3 + tap % 3) * CH * 2 + (tap / 3 - 1) * dstep;
            lds128(pc.w[tap], dw + j * 16);
            asm volatile("ld.shared.v2.b32 {%0,%1}, [%2];" : "=r"(pc.w[tap][4]), "=r"(pc.w[tap][5]) : "r"(dw + 128 + j * 8) : "memory");
        }
#pragma unroll
        for (int tap = 0; tap < 9; tap++)
#pragma unroll
            for (int u = 0; u < 6; u++) pc.w[tap][u] = bf2_mul(pc.w[tap][u], TAP_SCALE_BF2);
        produce(pc, prm);
        TS(9);
        asm volatile("setmaxnreg.dec.sync.aligned.u32 %0;" ::"n"(EVEN_REGS));
        if (fresh_warp() == 12) {
            mbar_wait_c<0>(sb + SM_BAR + BAR_W2 * 8);
            if (fresh_cta() < CH) publish_bias(prm, fresh_cta(), lds32(sb + SM_RED + RED_EPOCH * 4) + 1);
        }
    } else {
        asm volatile("setmaxnreg.dec.sync.aligned.u32 %0;" ::"n"(CONSUMER_REGS));
        {
            const int tid = fresh_tid(), warp = fresh_warp(), lane = tid & 31;
            uint32_t cnt[2];
            if (warp == 0) {
                if (lane == 0) {
#pragma unroll
                    for (int k = 0; k < NX; k++) {
                        mbar_init(sb + SM_XFULL + k * SLOT_BYTES, 2);
                        mbar_init(sb + SM_Y1FULL + k * SLOT_BYTES, 4);
                        mbar_init(sb + SM_Y1EMPTY + k * SLOT_BYTES, 12);
                    }
                    mbar_init(sb + SM_BAR + BAR_DUMMY * 8, 1);
                    mbar_init(sb + SM_BAR + BAR_W1 * 8, 1);
                    fence_async_smem();
                }
                __syncwarp();
                asm volatile("bar.arrive 0, 512;" ::: "memory");
                expect_tx(sb + SM_BAR + BAR_DUMMY * 8, 9 * CH * 2);
                bulk_load(sb + SM_Y1, prm.dw, 9 * CH * 2, sb + SM_BAR + BAR_DUMMY * 8);
                bulk_prefetch((const char*)prm.w1 + fresh_cta() * (CH * EX * 2 / NUM_CTAS), CH * EX * 2 / NUM_CTAS);
                const RowCopy rc = row_copy(prm);
#pragma unroll
                for (int k = 0; k <= NX; k++) {
                    if (k == W1POS) {
                        expect_tx(sb + SM_BAR + BAR_W1 * 8, CH * EX * 2);
#pragma unroll
                        for (int q = 0; q < 6; q++) {
                            const uint32_t r = ROT ? (q + fresh_cta()) % 6 : q;
                            tma_load_2d(sb + SM_W1 + r * 12288, &prm.w1_map, 64 * r, 0, sb + SM_BAR + BAR_W1 * 8);
                        }
                    }
                    if (k < NX) issue_row_load(rc, k, k);
                    if (k == PRE) bulk_prefetch(rc.x0 + 192 + NX * rc.stride, TILE_BYTES);
                }
                SMARK(4);
            } else if (warp == 1) {
                if (lane < 2) asm volatile("prefetch.tensormap [%0];" ::"l"(&prm.w1_map + lane) : "memory");
            } else if (warp == 3) {
                const uint32_t one = (lane & 5) == ((lane & 8) >> 1) + (lane >> 4) ? 0x3f803f80u : 0u;
                sts128(sb + SM_SEL + lane * 16, one, one, one, one);
                fence_async_smem();
            } else if (tid - 128u < NX * 12 && ((fresh_cta() + 1) & 7) < 2) {
                const int k = tid - 128;
                sts128(sb + SM_X + (k / 12) * SLOT_BYTES + ((fresh_cta() & 7) == 0 ? 0 : XHALF_B + 33 * 192) + (k % 12) * 16, 0, 0, 0, 0);
            }
            __syncwarp();
            asm volatile("ld.relaxed.gpu.global.v2.u32 {%0, %1}, [%2];" : "=r"(cnt[0]), "=r"(cnt[1]) : "l"(prm.g->count) : "memory");
            SMARK(0);
            if (warp != 0) named_sync(0, 512);
            if (tid == 256) {
                sts64(sb + SM_RED + RED_EPOCH * 4, cnt[0], cnt[1] / NUM_CTAS);
#pragma unroll
                for (int k = 0; k < BAR_COUNT; k++)
                    if (k != BAR_W1 && k != BAR_DUMMY) mbar_init(sb + SM_BAR + k * 8, k < BAR_TURN ? 1 : 4);
#pragma unroll
                for (int k = 0; k < 3; k++) mbar_arrive_if(sb + SM_BAR + (BAR_Y2FULL + k) * 8, true);
            }
            if (fresh_cta() == 0) *acc_word(prm, cnt[0] + 1, tid) = 0;
            if (fresh_cta() == 1) prm.g->sums[~(cnt[1] / NUM_CTAS) & 1][tid] = 0.0f;
            __syncwarp();
            SMARK(1);
            mbar_wait_c<0>(sb + SM_BAR + BAR_W1 * 8);
            SMARK(2);
        }

        const int tid = fresh_tid(), lane = tid & 31, wg = fresh_warp() >> 2, w = fresh_warp() & 3;
        float acc[2][2];
        const int c = 8 * (lane >> 4) + (lane & 7), ck = 2 * w + ((lane >> 3) & 1);
        consume(acc, sb + SM_W1 + 2 * wg * 12288 + c * 128 + ((ck ^ (c & 7)) * 16), prm.ydesc,
                prm.w1desc + (((2 * wg + 1) * 12288 + 5 * 2048) >> 4), wg * SLOT_BYTES, make_duty(prm, wg, w), w, lane, prm);
        publish_fast(prm, acc, lds32(sb + SM_RED + RED_EPOCH * 4), wg, w, lane);
        MARK(0);
        bulk_wait_all();
        if (wg == 0) TS(3);
        asm volatile("setmaxnreg.inc.sync.aligned.u32 %0;" ::"n"(EVEN_REGS));
    }

    {
        asm volatile(".reg .b32 qa<24>, qz<32>;");
        Pass2 c;
        const int tid = fresh_tid(), lane = tid & 31, warp = fresh_warp(), wg = warp >> 2, w = warp & 3, e = min(tid, EX - 1);
        const int arow = 16 * w + (lane & 15);
        c.wg = wg;
        c.off = cta_tile0(fresh_cta()) + (ROWS_PER_CTA - 1 - wg) * cta_stride(fresh_cta());
        c.step = 4 * cta_stride(fresh_cta());
        c.xs = wg == 3 ? sb + SM_BUF3 : sb + SM_Y1 + (wg == 2 ? 2 : 1 - wg) * SLOT_BYTES;
        static_assert((ROWS_PER_CTA - 1) % NX == 1, "slot of the last tile");
        c.a_offs = (arow * 128 + (((lane >> 4) ^ (arow & 7)) * 16)) |
                   (8192 + arow * 64 + (((lane >> 4) ^ ((arow >> 1) & 3)) * 16)) << 16;
        const int g = lane >> 2, px = 33 * (g & 1) + 4 * (g >> 1) + 16 * (w >> 1) + 2 * (w & 1);
        c.xs_offs = (px * 192 + (lane & 3) * 16) | ((px ^ 1) * 192 + (lane & 3) * 16) << 16;
        c.bias_addr = sb + SM_BIAS + (lane & 3) * 16;
        c.w = w;
        const uint32_t epoch = lds32(sb + SM_RED + RED_EPOCH * 4);
        MARK(1);
        if (warp == 6) {
            const uint32_t bar = sb + SM_BAR + (BAR_Y2FULL + 3) * 8;
            expect_tx(bar, TILE_BYTES);
            bulk_load(sb + SM_BUF3, (const char*)prm.out + (c.off - c.step / 2), TILE_BYTES, bar);
        }
        mbar_wait_c<0>(sb + SM_BAR + BAR_W2 * 8);
        const float gm = lds_bf16(sb + SM_GAMMA + e * 2), bt = fabsf(lds_bf16(sb + SM_BETA + e * 2));
        const uint32_t w2row = sb + SM_W2 + e * 64, sw = ((e >> 1) & 3) * 16;
        uint32_t u[12][4];
        float top = 0.0f, ss = 16.0f;
        if (wg < 3) top = fetch_w2_row(u, w2row, sw);
        if (warp == 12) collect_bias(prm, epoch + 1);
        MARK(3);
        start_first_tile(c, prm);
        MARK(4);
        if (wg < 3) ss = collect_fast(acc_word(prm, epoch, e));
        if (warp == 0) TS(4);
        MARK(5);
        float gx, inv;
        int eo;
        if (grn_stats(ss, gm, bt, top, gx, inv, eo) || FORCE_EXACT) {
            wg_wait<0>();
            grn_stats(exact_sums(prm, e), gm, bt, top, gx, inv, eo);
            fetch_w2_row(u, w2row, sw);
            start_first_tile(c, prm);
            __syncthreads();
        }
        MARK(8);
        if (tid == 416 && fresh_cta() == 0) prm.g->count[0] = epoch + 1;
        const float up = pow2f(eo), dn = pow2f(-eo);
        c.out_scale = pack_bf2(up, up);
        if (wg < 3) {
            float sc = fmaf(gm, gx * inv, 1.0f) * INV_2A;
            if (eo > 6) {
                const uint32_t dn2 = pack_bf2(dn, dn);
#pragma unroll
                for (int k = 0; k < 48; k++) u[k >> 2][k & 3] = bf2_mul(u[k >> 2][k & 3], dn2);
            } else {
                sc *= dn;
            }
            const uint32_t s2 = pack_bf2(sc * 0x1p-112f, sc * 0x1p-112f);
#pragma unroll
            for (int k = 0; k < 12; k++) {
                uint32_t v[4];
#pragma unroll
                for (int b = 0; b < 4; b++) {
                    v[b] = bf2_mul(u[k][b], s2);
                    v[b] += (v[b] & 0x7fff7fffu) * 7u;
                }
                sts128(w2row + (k >> 2) * 24576 + (((k & 3) * 16) ^ sw), v[0], v[1], v[2], v[3]);
            }
        } else if (w == 0 && lane < 24) {
            uint32_t b[4];
            lds128(b, sb + SM_BIAS + lane * 16);
            const uint32_t p0 = pack_h2(__uint_as_float(b[0]) * dn, __uint_as_float(b[1]) * dn);
            const uint32_t p1 = pack_h2(__uint_as_float(b[2]) * dn, __uint_as_float(b[3]) * dn);
            sts128(sb + SM_BIAS + lane * 16, p0, p0, p1, p1);
        }
        MARK(9);
        fence_async_smem();
        __syncthreads();
        MARK(10);

        if (wg == 0) TS(5);
        pass2_tiles(c, prm);
        bulk_wait_all();
        MARK(13);
    }
}

}

extern "C" void kernel_launch(void* const* d_in, const int* in_sizes, int n_in, void* d_out, int out_size) {
    (void)in_sizes; (void)n_in; (void)out_size;
    typedef CUresult (*EncodeFn)(CUtensorMap*, CUtensorMapDataType, cuuint32_t, void*, const cuuint64_t*, const cuuint64_t*,
                                 const cuuint32_t*, const cuuint32_t*, CUtensorMapInterleave, CUtensorMapSwizzle,
                                 CUtensorMapL2promotion, CUtensorMapFloatOOBfill);
    void* fn = nullptr;
    cudaDriverEntryPointQueryResult status;
    cudaGetDriverEntryPoint("cuTensorMapEncodeTiled", &fn, cudaEnableDefault, &status);
    const EncodeFn encode = (EncodeFn)fn;
    const cuuint32_t ones[2] = {1, 1};

    Params p;
    {
        const cuuint64_t dims[2] = {EX, CH}, strides[1] = {EX * 2};
        const cuuint32_t box[2] = {64, CH};
        encode(&p.w1_map, CU_TENSOR_MAP_DATA_TYPE_BFLOAT16, 2, d_in[2], dims, strides, box, ones,
               CU_TENSOR_MAP_INTERLEAVE_NONE, CU_TENSOR_MAP_SWIZZLE_128B, CU_TENSOR_MAP_L2_PROMOTION_NONE,
               CU_TENSOR_MAP_FLOAT_OOB_FILL_NONE);
    }
    {
        const cuuint64_t dims[2] = {CH, EX}, strides[1] = {CH * 2};
        const cuuint32_t box[2] = {32, 192};
        encode(&p.w2_map, CU_TENSOR_MAP_DATA_TYPE_BFLOAT16, 2, d_in[3], dims, strides, box, ones,
               CU_TENSOR_MAP_INTERLEAVE_NONE, CU_TENSOR_MAP_SWIZZLE_64B, CU_TENSOR_MAP_L2_PROMOTION_NONE,
               CU_TENSOR_MAP_FLOAT_OOB_FILL_NONE);
    }
    p.x = (const __nv_bfloat16*)d_in[0];
    p.dw = (const __nv_bfloat16*)d_in[1];
    p.w1 = (const __nv_bfloat16*)d_in[2];
    p.gamma = (const __nv_bfloat16*)d_in[4];
    p.beta = (const __nv_bfloat16*)d_in[5];
    p.out = (__nv_bfloat16*)d_out;
    cudaGetSymbolAddress((void**)&p.g, g_scratch);
    p.w1desc = desc_lo(sb + SM_W1, 12288);
    p.w2desc = desc_lo(sb + SM_W2, 24576);
    p.ydesc = desc_lo(sb + SM_Y1, 16);
    for (int k = 0; k < 3; k++) p.sel[k] = (8ull << 32) | desc_lo(sb + SM_SEL + k * 128, k == 2 ? 128 : 0);
    constexpr int smem_bytes = SM_TOTAL;
    cudaFuncSetAttribute(convnext_kernel, cudaFuncAttributeMaxDynamicSharedMemorySize, smem_bytes);
    convnext_kernel<<<NUM_CTAS, 512, smem_bytes>>>(p);
}
```

```cpp
#include <cuda.h>
#include <cuda_runtime.h>
#include <cuda_bf16.h>
#include <stdint.h>

namespace {

constexpr int IMG_W = 512, CH = 96, EX = 384;
constexpr int TILE_PX = 64;
constexpr int ROWS_PER_CTA = 32;
constexpr int NUM_CTAS = 128;
constexpr int STEPS = ROWS_PER_CTA + 2;
constexpr int ROW_BYTES = IMG_W * CH * 2;

#define FORCE_EXACT 0
#define HOLD 1
#define ENDREAD 1
#define ROT 0
#define PRE 9
#define W1POS 3
#define PREGS 200
#define CREGS 104
constexpr int PRODUCER_REGS = PREGS, CONSUMER_REGS = CREGS, EVEN_REGS = 128;

constexpr int XHALF_BYTES = 34 * 192;
constexpr int XHALF_B = XHALF_BYTES + 64;
constexpr int XROW_BYTES = XHALF_B + XHALF_BYTES + 64;
constexpr int L2_AHEAD = 2;
constexpr int NX = 3;
constexpr int TILE_BYTES = TILE_PX * 192;
constexpr int NY1 = 3;

constexpr uint32_t sb = 1024;
constexpr int SM_W1 = 0;
constexpr int SM_W2 = 73728;
constexpr int SM_RING = 147456;
constexpr int SLOT_BYTES = 26624;
constexpr int SM_Y1 = SM_RING;
constexpr int SM_X = SM_Y1 + TILE_BYTES;
constexpr int SM_STAT = SM_X + XROW_BYTES;
constexpr int SM_XFULL = SM_STAT + TILE_PX * 16, SM_Y1FULL = SM_XFULL + 8, SM_Y1EMPTY = SM_XFULL + 16;
constexpr int SM_BUF3 = SM_X + SLOT_BYTES, SM_SPARE = SM_X;
constexpr int SM_SEL = SM_RING + NX * SLOT_BYTES;
constexpr int SM_BIAS = SM_SEL + 512;
constexpr int SM_GAMMA = SM_BIAS + 384;
constexpr int SM_BETA = SM_GAMMA + EX * 2;
constexpr int SM_RED = SM_BETA + EX * 2;
constexpr int SM_BAR = SM_RED + 16;
constexpr int BAR_Y2FULL = 0, BAR_XSFULL = 4, BAR_W1 = 8, BAR_W2 = 9, BAR_DUMMY = 10, BAR_TURN = 11, BAR_COUNT = 51;
constexpr int SM_TOTAL = SM_BAR + BAR_COUNT * 8;
static_assert(SM_Y1EMPTY + 8 <= SM_RING + SLOT_BYTES && XROW_BYTES >= TILE_BYTES && SM_X % 1024 == 0, "ring layout");
static_assert(SM_TOTAL <= 232448, "smem budget");
static_assert(SM_STAT % 128 == 0 && SM_BIAS % 16 == 0 && SM_BAR % 8 == 0 && SLOT_BYTES % 1024 == 0, "alignment");

static_assert(NX == NY1, "both rings are walked with one index");
constexpr int RED_EPOCH = 0;

constexpr float GELU_A = 0.32920349f;
constexpr uint32_t GELU_C_H2 = 0x40D940D9u;
constexpr float INV_2A = 1.0f / (2.0f * GELU_A);

constexpr uint32_t TAP_SCALE_BF2 = 0x2B802B80u;
constexpr float LN_EPS_SCALED = 1e-5f * 0x1p-80f;
constexpr float RSTD_SCALE = GELU_A * 0x1p-112f;

struct Scratch {
    unsigned long long acc[2][EX / 4 * 32];
    unsigned long long bias[CH];
    float sums[2][EX];
    uint4 zero_row[66 * 192 / 16];
    unsigned int count[2];
};
__device__ __align__(256) Scratch g_scratch;
constexpr float ACC_LIMIT = 0x1p30f;

#define TS(k)
#define ASM_TS
#define MARK(k)
#define SMARK(k)
#define ASM_MARK
#define ASM_SMARK
#define ASM_TRC(it, k)

#define SPLITS 2
#define FENCE_HEAD(k) "{\n.reg .pred p;\n.reg .u32 t;\nsetp.ne.u32 p, %" #k ", 0;\n@p bra.uni GO;\nSTAY:\nld.volatile.shared.u32 t, [%" #k "];\n"
#define FENCE_TAIL "setp.ne.u32 p, t, 0;\n@p bra.uni STAY;\nGO:\n}\n"
template <int N> __device__ __forceinline__ void sched_fence(uint32_t* r, uint32_t key);
template <> __device__ __forceinline__ void sched_fence<2>(uint32_t* r, uint32_t key) {
    asm volatile(FENCE_HEAD(2) "mov.b32 %0, t;\nmov.b32 %1, t;\n" FENCE_TAIL
                 : "+r"(r[0]), "+r"(r[1]) : "r"(key) : "memory");
}
template <> __device__ __forceinline__ void sched_fence<4>(uint32_t* r, uint32_t key) {
    asm volatile(FENCE_HEAD(4) "mov.b32 %0, t;\nmov.b32 %1, t;\nmov.b32 %2, t;\nmov.b32 %3, t;\n" FENCE_TAIL
                 : "+r"(r[0]), "+r"(r[1]), "+r"(r[2]), "+r"(r[3]) : "r"(key) : "memory");
}
template <> __device__ __forceinline__ void sched_fence<6>(uint32_t* r, uint32_t key) {
    asm volatile(FENCE_HEAD(6) "mov.b32 %0, t;\nmov.b32 %1, t;\nmov.b32 %2, t;\nmov.b32 %3, t;\nmov.b32 %4, t;\nmov.b32 %5, t;\n" FENCE_TAIL
                 : "+r"(r[0]), "+r"(r[1]), "+r"(r[2]), "+r"(r[3]), "+r"(r[4]), "+r"(r[5]) : "r"(key) : "memory");
}
template <> __device__ __forceinline__ void sched_fence<8>(uint32_t* r, uint32_t key) {
    asm volatile(FENCE_HEAD(8) "mov.b32 %0, t;\nmov.b32 %1, t;\nmov.b32 %2, t;\nmov.b32 %3, t;\nmov.b32 %4, t;\nmov.b32 %5, t;\nmov.b32 %6, t;\nmov.b32 %7, t;\n" FENCE_TAIL
                 : "+r"(r[0]), "+r"(r[1]), "+r"(r[2]), "+r"(r[3]), "+r"(r[4]), "+r"(r[5]), "+r"(r[6]), "+r"(r[7]) : "r"(key) : "memory");
}
template <> __device__ __forceinline__ void sched_fence<10>(uint32_t* r, uint32_t key) {
    asm volatile(FENCE_HEAD(10) "mov.b32 %0, t;\nmov.b32 %1, t;\nmov.b32 %2, t;\nmov.b32 %3, t;\nmov.b32 %4, t;\nmov.b32 %5, t;\nmov.b32 %6, t;\nmov.b32 %7, t;\nmov.b32 %8, t;\nmov.b32 %9, t;\n" FENCE_TAIL
                 : "+r"(r[0]), "+r"(r[1]), "+r"(r[2]), "+r"(r[3]), "+r"(r[4]), "+r"(r[5]), "+r"(r[6]), "+r"(r[7]), "+r"(r[8]), "+r"(r[9]) : "r"(key) : "memory");
}
template <> __device__ __forceinline__ void sched_fence<12>(uint32_t* r, uint32_t key) {
    asm volatile(FENCE_HEAD(12) "mov.b32 %0, t;\nmov.b32 %1, t;\nmov.b32 %2, t;\nmov.b32 %3, t;\nmov.b32 %4, t;\nmov.b32 %5, t;\nmov.b32 %6, t;\nmov.b32 %7, t;\nmov.b32 %8, t;\nmov.b32 %9, t;\nmov.b32 %10, t;\nmov.b32 %11, t;\n" FENCE_TAIL
                 : "+r"(r[0]), "+r"(r[1]), "+r"(r[2]), "+r"(r[3]), "+r"(r[4]), "+r"(r[5]), "+r"(r[6]), "+r"(r[7]), "+r"(r[8]), "+r"(r[9]), "+r"(r[10]), "+r"(r[11]) : "r"(key) : "memory");
}
template <> __device__ __forceinline__ void sched_fence<24>(uint32_t* r, uint32_t key) {
    asm volatile(FENCE_HEAD(24) "mov.b32 %0, t;\nmov.b32 %1, t;\nmov.b32 %2, t;\nmov.b32 %3, t;\nmov.b32 %4, t;\nmov.b32 %5, t;\nmov.b32 %6, t;\nmov.b32 %7, t;\nmov.b32 %8, t;\nmov.b32 %9, t;\nmov.b32 %10, t;\nmov.b32 %11, t;\nmov.b32 %12, t;\nmov.b32 %13, t;\nmov.b32 %14, t;\nmov.b32 %15, t;\nmov.b32 %16, t;\nmov.b32 %17, t;\nmov.b32 %18, t;\nmov.b32 %19, t;\nmov.b32 %20, t;\nmov.b32 %21, t;\nmov.b32 %22, t;\nmov.b32 %23, t;\n" FENCE_TAIL
                 : "+r"(r[0]), "+r"(r[1]), "+r"(r[2]), "+r"(r[3]), "+r"(r[4]), "+r"(r[5]), "+r"(r[6]), "+r"(r[7]), "+r"(r[8]), "+r"(r[9]), "+r"(r[10]), "+r"(r[11]), "+r"(r[12]), "+r"(r[13]), "+r"(r[14]), "+r"(r[15]), "+r"(r[16]), "+r"(r[17]), "+r"(r[18]), "+r"(r[19]), "+r"(r[20]), "+r"(r[21]), "+r"(r[22]), "+r"(r[23]) : "r"(key) : "memory");
}
#define SPLIT(k, r) do { if ((SPLITS >> (k)) & 1) sched_fence<sizeof(r) / 4>(r, prm.ydesc); } while (0)

__device__ __forceinline__ void mbar_init(uint32_t bar, uint32_t count) {
    asm volatile("mbarrier.init.shared::cta.b64 [%0], %1;" ::"r"(bar), "r"(count) : "memory");
}
__device__ __forceinline__ void mbar_arrive_if(uint32_t bar, bool pred) {
    asm volatile("{\n.reg .pred p;\nsetp.ne.u32 p, %1, 0;\n@p mbarrier.arrive.shared::cta.b64 _, [%0];\n}\n"
                 ::"r"(bar), "r"((uint32_t)pred) : "memory");
}
__device__ __forceinline__ void mbar_wait(uint32_t bar, uint32_t parity) {
    asm volatile(
        "{\n.reg .pred p;\n.reg .u32 n;\n"
        "mbarrier.try_wait.parity.shared::cta.b64 p, [%0], %1;\n"
        "@p bra.uni WAIT_DONE;\n"
        "mov.u32 n, 0;\n"
        "WAIT_LOOP:\n"
        "mbarrier.try_wait.parity.shared::cta.b64 p, [%0], %1;\n"
        "@p bra.uni WAIT_DONE;\n"
        "mbarrier.try_wait.parity.shared::cta.b64 p, [%0], %1;\n"
        "@p bra.uni WAIT_DONE;\n"
        "mbarrier.try_wait.parity.shared::cta.b64 p, [%0], %1;\n"
        "@p bra.uni WAIT_DONE;\n"
        "add.u32 n, n, 1;\nsetp.lt.u32 p, n, 0x40000;\n"
        "@p bra.uni WAIT_LOOP;\n"
        "trap;\n"
        "WAIT_DONE:\n}\n"
        ::"r"(bar), "r"(parity) : "memory");
}
template <int PARITY> __device__ __forceinline__ void mbar_wait_c(uint32_t bar) {
    asm volatile(
        "{\n.reg .pred p;\n.reg .u32 n;\n"
        "mbarrier.try_wait.parity.shared::cta.b64 p, [%0], %1;\n"
        "@p bra.uni WAIT_DONE;\n"
        "mov.u32 n, 0;\n"
        "WAIT_LOOP:\n"
        "mbarrier.try_wait.parity.shared::cta.b64 p, [%0], %1;\n"
        "@p bra.uni WAIT_DONE;\n"
        "mbarrier.try_wait.parity.shared::cta.b64 p, [%0], %1;\n"
        "@p bra.uni WAIT_DONE;\n"
        "mbarrier.try_wait.parity.shared::cta.b64 p, [%0], %1;\n"
        "@p bra.uni WAIT_DONE;\n"
        "add.u32 n, n, 1;\nsetp.lt.u32 p, n, 0x40000;\n"
        "@p bra.uni WAIT_LOOP;\n"
        "trap;\n"
        "WAIT_DONE:\n}\n"
        ::"r"(bar), "n"(PARITY) : "memory");
}
__device__ __forceinline__ bool mbar_probe(uint32_t bar, uint32_t parity) {
    uint32_t ok;
    asm volatile("{\n.reg .pred p;\nmbarrier.test_wait.parity.shared::cta.b64 p, [%1], %2;\nselp.u32 %0, 1, 0, p;\n}\n"
                 : "=r"(ok) : "r"(bar), "r"(parity) : "memory");
    return ok;
}
__device__ __forceinline__ void mbar_wait2(uint32_t bar0, uint32_t parity0, uint32_t bar1, uint32_t parity1) {
    asm volatile(
        "{\n.reg .pred p, q;\n.reg .u32 n;\n"
        "mbarrier.try_wait.parity.shared::cta.b64 p, [%0], %1;\n"
        "mbarrier.try_wait.parity.shared::cta.b64 q, [%2], %3;\n"
        "and.pred p, p, q;\n"
        "@p bra.uni WAIT_DONE;\n"
        "mov.u32 n, 0;\n"
        "WAIT_LOOP:\n"
        "mbarrier.try_wait.parity.shared::cta.b64 p, [%0], %1;\n"
        "mbarrier.try_wait.parity.shared::cta.b64 q, [%2], %3;\n"
        "and.pred p, p, q;\n"
        "@p bra.uni WAIT_DONE;\n"
        "add.u32 n, n, 1;\nsetp.lt.u32 p, n, 0x80000;\n"
        "@p bra.uni WAIT_LOOP;\n"
        "trap;\n"
        "WAIT_DONE:\n}\n"
        ::"r"(bar0), "r"(parity0), "r"(bar1), "r"(parity1) : "memory");
}
#define ELECTED(body) "{\n.reg .pred p;\nelect.sync _|p, 0xffffffff;\n" body "}\n"
__device__ __forceinline__ void expect_tx(uint32_t bar, uint32_t bytes) {
    asm volatile(ELECTED("@p mbarrier.arrive.expect_tx.shared::cta.b64 _, [%0], %1;\n") ::"r"(bar), "r"(bytes) : "memory");
}
__device__ __forceinline__ void arrive_n(uint32_t bar, uint32_t count) {
    asm volatile(ELECTED("@p mbarrier.arrive.shared::cta.b64 _, [%0], %1;\n") ::"r"(bar), "r"(count) : "memory");
}
__device__ __forceinline__ void bulk_load(uint32_t dst, const void* src, uint32_t bytes, uint32_t bar) {
    asm volatile(ELECTED("@p cp.async.bulk.shared::cluster.global.mbarrier::complete_tx::bytes [%0], [%1], %2, [%3];\n")
                 ::"r"(dst), "l"(src), "r"(bytes), "r"(bar) : "memory");
}
__device__ __forceinline__ void bulk_store(void* dst, uint32_t src, uint32_t bytes) {
    asm volatile(ELECTED("@p cp.async.bulk.global.shared::cta.bulk_group [%0], [%1], %2;\n@p cp.async.bulk.commit_group;\n")
                 ::"l"(dst), "r"(src), "r"(bytes) : "memory");
}
__device__ __forceinline__ void bulk_prefetch(const void* src, uint32_t bytes) {
    asm volatile(ELECTED("@p cp.async.bulk.prefetch.L2.global [%0], %1;\n") ::"l"(src), "r"(bytes) : "memory");
}
__device__ __forceinline__ void tma_load_2d(uint32_t dst, const CUtensorMap* map, int c0, int c1, uint32_t bar) {
    asm volatile(ELECTED("@p cp.async.bulk.tensor.2d.shared::cluster.global.mbarrier::complete_tx::bytes [%0], [%1, {%2, %3}], [%4];\n")
                 ::"r"(dst), "l"(map), "r"(c0), "r"(c1), "r"(bar) : "memory");
}
template <int N> __device__ __forceinline__ void bulk_wait_read() {
    asm volatile("cp.async.bulk.wait_group.read %0;" ::"n"(N) : "memory");
}
__device__ __forceinline__ void bulk_wait_all() { asm volatile("cp.async.bulk.wait_group 0;" ::: "memory"); }
__device__ __forceinline__ void fence_async_smem() { asm volatile("fence.proxy.async.shared::cta;" ::: "memory"); }
__device__ __forceinline__ void named_sync(int id, int n) { asm volatile("bar.sync %0, %1;" ::"r"(id), "r"(n) : "memory"); }

__device__ __forceinline__ void lds64(uint32_t (&v)[2], uint32_t addr) {
    asm volatile("ld.shared.v2.b32 {%0,%1}, [%2];" : "=r"(v[0]), "=r"(v[1]) : "r"(addr));
}
__device__ __forceinline__ void sts64(uint32_t addr, uint32_t a, uint32_t b) {
    asm volatile("st.shared.v2.b32 [%0], {%1,%2};" ::"r"(addr), "r"(a), "r"(b) : "memory");
}
__device__ __forceinline__ void sts128(uint32_t addr, uint32_t a, uint32_t b, uint32_t c, uint32_t d) {
    asm volatile("st.shared.v4.b32 [%0], {%1,%2,%3,%4};" ::"r"(addr), "r"(a), "r"(b), "r"(c), "r"(d) : "memory");
}
__device__ __forceinline__ void ldsm4(uint32_t* r, uint32_t addr) {
    asm volatile("ldmatrix.sync.aligned.m8n8.x4.shared.b16 {%0,%1,%2,%3}, [%4];"
                 : "=r"(r[0]), "=r"(r[1]), "=r"(r[2]), "=r"(r[3]) : "r"(addr) : "memory");
}
__device__ __forceinline__ void ldsm4_t(uint32_t* r, uint32_t addr) {
    asm volatile("ldmatrix.sync.aligned.m8n8.x4.trans.shared.b16 {%0,%1,%2,%3}, [%4];"
                 : "=r"(r[0]), "=r"(r[1]), "=r"(r[2]), "=r"(r[3]) : "r"(addr) : "memory");
}
__device__ __forceinline__ void lds128(uint32_t* v, uint32_t addr) {
    asm volatile("ld.shared.v4.b32 {%0,%1,%2,%3}, [%4];"
                 : "=r"(v[0]), "=r"(v[1]), "=r"(v[2]), "=r"(v[3]) : "r"(addr) : "memory");
}
__device__ __forceinline__ uint32_t lds32(uint32_t addr) {
    uint32_t v; asm volatile("ld.shared.b32 %0, [%1];" : "=r"(v) : "r"(addr) : "memory"); return v;
}
__device__ __forceinline__ void sts32(uint32_t addr, uint32_t v) {
    asm volatile("st.shared.b32 [%0], %1;" ::"r"(addr), "r"(v) : "memory");
}

__device__ __forceinline__ uint32_t bf2_fma(uint32_t a, uint32_t b, uint32_t c) {
    uint32_t d; asm("fma.rn.bf16x2 %0, %1, %2, %3;" : "=r"(d) : "r"(a), "r"(b), "r"(c)); return d;
}
__device__ __forceinline__ uint32_t bf2_mul(uint32_t a, uint32_t b) {
    uint32_t d; asm("mul.rn.bf16x2 %0, %1, %2;" : "=r"(d) : "r"(a), "r"(b)); return d;
}
__device__ __forceinline__ uint32_t bf2_add(uint32_t a, uint32_t b) {
    uint32_t d; asm("add.rn.bf16x2 %0, %1, %2;" : "=r"(d) : "r"(a), "r"(b)); return d;
}
__device__ __forceinline__ uint32_t h2_fma(uint32_t a, uint32_t b, uint32_t c) {
    uint32_t d; asm("fma.rn.f16x2 %0, %1, %2, %3;" : "=r"(d) : "r"(a), "r"(b), "r"(c)); return d;
}
__device__ __forceinline__ uint32_t h2_mul(uint32_t a, uint32_t b) {
    uint32_t d; asm("mul.rn.f16x2 %0, %1, %2;" : "=r"(d) : "r"(a), "r"(b)); return d;
}
__device__ __forceinline__ uint32_t h2_tanh(uint32_t a) {
    uint32_t d; asm("tanh.approx.f16x2 %0, %1;" : "=r"(d) : "r"(a)); return d;
}
__device__ __forceinline__ float bf_lo(uint32_t v) { return __uint_as_float(v << 16); }
__device__ __forceinline__ float bf_hi(uint32_t v) { return __uint_as_float(v & 0xffff0000u); }
__device__ __forceinline__ uint32_t pack_h2(float lo, float hi) {
    uint32_t d; asm("cvt.rn.f16x2.f32 %0, %1, %2;" : "=r"(d) : "f"(hi), "f"(lo)); return d;
}
__device__ __forceinline__ uint32_t pack_bf2(float lo, float hi) {
    uint32_t d; asm("cvt.rn.bf16x2.f32 %0, %1, %2;" : "=r"(d) : "f"(hi), "f"(lo)); return d;
}
__device__ __forceinline__ void h2_unpack(uint32_t v, float& lo, float& hi) {
    asm("{\n.reg .b16 l, h;\nmov.b32 {l, h}, %2;\ncvt.f32.f16 %0, l;\ncvt.f32.f16 %1, h;\n}\n" : "=f"(lo), "=f"(hi) : "r"(v));
}
__device__ __forceinline__ uint32_t bf2_to_h2(uint32_t v) { return pack_h2(bf_lo(v), bf_hi(v)); }

__device__ __forceinline__ uint32_t gelu2(uint32_t z) {
    uint32_t p = h2_fma(z, z, GELU_C_H2);
    uint32_t t = h2_tanh(h2_mul(z, p));
    return h2_fma(z, t, z);
}

__device__ __forceinline__ void wg_fence() { asm volatile("wgmma.fence.sync.aligned;" ::: "memory"); }
__device__ __forceinline__ void wg_commit() { asm volatile("wgmma.commit_group.sync.aligned;" ::: "memory"); }
template <int N> __device__ __forceinline__ void wg_wait() {
    asm volatile("wgmma.wait_group.sync.aligned %0;" ::"n"(N) : "memory");
}
template <int N> __device__ __forceinline__ void pin(uint32_t (&r)[N]) {
#pragma unroll
    for (int i = 0; i < N; i++) asm volatile("" : "+r"(r[i])::"memory");
}
constexpr uint32_t desc_lo(uint32_t addr, uint32_t lbo) { return ((addr & 0x3FFFF) >> 4) | ((lbo >> 4) << 16); }
template <uint32_t SBO, uint32_t SWZ> __device__ __forceinline__ uint64_t desc(uint32_t lo, uint32_t bytes) {
    return (((uint64_t)((SBO >> 4) | (SWZ << 30)) << 32) | lo) + (bytes >> 4);
}
__device__ __forceinline__ uint32_t fresh_tid() {
    uint32_t v; asm volatile("mov.u32 %0, %%tid.x;" : "=r"(v));
    return v;
}
template <uint32_t V> __device__ __forceinline__ uint32_t loop_init() {
    uint32_t v; asm volatile("mov.u32 %0, %1;" : "=r"(v) : "n"(V)); return v;
}
__device__ __forceinline__ int fresh_warp() {
    int v; asm volatile("shfl.sync.idx.b32 %0, %1, 0, 0x1f, 0xffffffff;" : "=r"(v) : "r"(fresh_tid() >> 5)); return v;
}
__device__ __forceinline__ uint32_t fresh_cta() {
    uint32_t v; asm volatile("mov.u32 %0, %%ctaid.x;" : "=r"(v)); return v;
}
__device__ __forceinline__ float rsqrt_fast(float v) { float r; asm("rsqrt.approx.ftz.f32 %0, %1;" : "=f"(r) : "f"(v)); return r; }
__device__ __forceinline__ float sqrt_fast(float v) { float r; asm("sqrt.approx.f32 %0, %1;" : "=f"(r) : "f"(v)); return r; }

template <int TB>
__device__ __forceinline__ void wgmma_n64_h_set(uint32_t (&d)[16], const uint32_t* a, uint64_t desc) {
    asm volatile(
        "{\n.reg .pred p;\nsetp.ne.b32 p, 0, 0;\n"
        "wgmma.mma_async.sync.aligned.m64n64k16.f16.f16.f16 "
        "{%0,%1,%2,%3,%4,%5,%6,%7,%8,%9,%10,%11,%12,%13,%14,%15}, {%16,%17,%18,%19}, %20, p, 1, 1, %21;\n}\n"
        : "=r"(d[0]), "=r"(d[1]), "=r"(d[2]), "=r"(d[3]), "=r"(d[4]), "=r"(d[5]), "=r"(d[6]), "=r"(d[7]), "=r"(d[8]), "=r"(d[9]), "=r"(d[10]), "=r"(d[11]), "=r"(d[12]), "=r"(d[13]), "=r"(d[14]), "=r"(d[15])
        : "r"(a[0]), "r"(a[1]), "r"(a[2]), "r"(a[3]), "l"(desc), "n"(TB));
}
template <int TB>
__device__ __forceinline__ void wgmma_n64_h_acc(uint32_t (&d)[16], const uint32_t* a, uint64_t desc) {
    asm volatile(
        "{\n.reg .pred p;\nsetp.ne.b32 p, 1, 0;\n"
        "wgmma.mma_async.sync.aligned.m64n64k16.f16.f16.f16 "
        "{%0,%1,%2,%3,%4,%5,%6,%7,%8,%9,%10,%11,%12,%13,%14,%15}, {%16,%17,%18,%19}, %20, p, 1, 1, %21;\n}\n"
        : "+r"(d[0]), "+r"(d[1]), "+r"(d[2]), "+r"(d[3]), "+r"(d[4]), "+r"(d[5]), "+r"(d[6]), "+r"(d[7]), "+r"(d[8]), "+r"(d[9]), "+r"(d[10]), "+r"(d[11]), "+r"(d[12]), "+r"(d[13]), "+r"(d[14]), "+r"(d[15])
        : "r"(a[0]), "r"(a[1]), "r"(a[2]), "r"(a[3]), "l"(desc), "n"(TB));
}
__device__ __forceinline__ void wgmma_n64_h_acc_ss(uint32_t (&d)[16], uint64_t adesc, uint64_t desc) {
    asm volatile(
        "{\n.reg .pred p;\nsetp.ne.b32 p, 1, 0;\n"
        "wgmma.mma_async.sync.aligned.m64n64k16.f16.f16.f16 "
        "{%0,%1,%2,%3,%4,%5,%6,%7,%8,%9,%10,%11,%12,%13,%14,%15}, %16, %17, p, 1, 1, 1, 0;\n}\n"
        : "+r"(d[0]), "+r"(d[1]), "+r"(d[2]), "+r"(d[3]), "+r"(d[4]), "+r"(d[5]), "+r"(d[6]), "+r"(d[7]), "+r"(d[8]), "+r"(d[9]), "+r"(d[10]), "+r"(d[11]), "+r"(d[12]), "+r"(d[13]), "+r"(d[14]), "+r"(d[15])
        : "l"(adesc), "l"(desc));
}
__device__ __forceinline__ void wgmma_n96_h_acc(uint32_t (&d)[24], const uint32_t* a, uint64_t desc) {
    asm volatile(
        "{\n.reg .pred p;\nsetp.ne.b32 p, 1, 0;\n"
        "wgmma.mma_async.sync.aligned.m64n96k16.f16.f16.f16 "
        "{%0,%1,%2,%3,%4,%5,%6,%7,%8,%9,%10,%11,%12,%13,%14,%15,%16,%17,%18,%19,%20,%21,%22,%23}, {%24,%25,%26,%27}, %28, p, 1, 1, 1;\n}\n"
        : "+r"(d[0]), "+r"(d[1]), "+r"(d[2]), "+r"(d[3]), "+r"(d[4]), "+r"(d[5]), "+r"(d[6]), "+r"(d[7]), "+r"(d[8]), "+r"(d[9]), "+r"(d[10]), "+r"(d[11]), "+r"(d[12]), "+r"(d[13]), "+r"(d[14]), "+r"(d[15]), "+r"(d[16]), "+r"(d[17]), "+r"(d[18]), "+r"(d[19]), "+r"(d[20]), "+r"(d[21]), "+r"(d[22]), "+r"(d[23])
        : "r"(a[0]), "r"(a[1]), "r"(a[2]), "r"(a[3]), "l"(desc));
}

struct Params {
    CUtensorMap w1_map, w2_map;
    const __nv_bfloat16* x;
    const __nv_bfloat16* dw;
    const __nv_bfloat16* w1;
    const __nv_bfloat16* gamma;
    const __nv_bfloat16* beta;
    __nv_bfloat16* out;
    Scratch* g;
    uint64_t ydesc64[2];
    uint64_t sel[3];
    uint32_t w1desc, w2desc, ydesc;
};

__device__ __forceinline__ int cta_stride(uint32_t cta) { return cta & 8 ? ROW_BYTES : -ROW_BYTES; }
__device__ __forceinline__ uint32_t cta_tile0(uint32_t cta) {
    return ((cta >> 3) * ROWS_PER_CTA + (cta & 8 ? 0 : ROWS_PER_CTA - 1)) * ROW_BYTES + (cta & 7) * TILE_BYTES;
}

struct Producer {
    uint32_t w[9][6];
    uint32_t xoff[2];
    uint32_t yoff[2][2];
    uint32_t stat, own;
    int lane, warp;
};

struct RowCopy {
    const char* x0;
    char* y0;
    const char* zeros;
    uint32_t cut0, cut1;
    int stride, last;
};
__device__ __forceinline__ RowCopy row_copy(const Params& prm) {
    const uint32_t cta = fresh_cta(), strip = cta & 7, t0 = cta_tile0(cta);
    RowCopy r;
    r.stride = cta_stride(cta);
    r.x0 = (const char*)prm.x + (t0 - r.stride) - 192;
    r.y0 = (char*)prm.out + t0;
    r.zeros = (const char*)prm.g->zero_row;
    r.cut0 = strip == 0 ? 192 : 0;
    r.cut1 = strip == 7 ? 192 : 0;
    r.last = cta - 8 >= NUM_CTAS - 16 ? STEPS - 2 : STEPS - 1;
    return r;
}
__device__ __forceinline__ void issue_row_load(const RowCopy& r, int i, uint32_t slot) {
    const char* src = r.x0 + i * r.stride;
    const uint32_t bar = sb + SM_XFULL + slot * SLOT_BYTES, dst = sb + SM_X + slot * SLOT_BYTES;
    expect_tx(bar, XHALF_BYTES - r.cut0);
    bulk_load(dst + r.cut0, src + r.cut0, XHALF_BYTES - r.cut0, bar);
    expect_tx(bar, XHALF_BYTES - r.cut1);
    bulk_load(dst + XHALF_B, src + 32 * 192, XHALF_BYTES - r.cut1, bar);
}

__device__ __forceinline__ float quad_sum(float v) {
    v += __shfl_xor_sync(0xffffffffu, v, 1);
    v += __shfl_xor_sync(0xffffffffu, v, 2);
    return v;
}

__device__ __forceinline__ void load_x(uint32_t (&v)[6][6], const Producer& c, uint32_t row) {
#pragma unroll
    for (int k = 0; k < 6; k++) {
        asm volatile("ld.shared.v4.b32 {%0,%1,%2,%3}, [%4];"
                     : "=r"(v[k][0]), "=r"(v[k][1]), "=r"(v[k][2]), "=r"(v[k][3]) : "r"(row + c.xoff[0] + k * 192));
        asm volatile("ld.shared.v2.b32 {%0,%1}, [%2];" : "=r"(v[k][4]), "=r"(v[k][5]) : "r"(row + c.xoff[1] + k * 192));
    }
}
template <int DY, int STRIDE>
__device__ __forceinline__ void conv_row(uint32_t (&dst)[24], const uint32_t* src, const uint32_t (&v)[6][6], const Producer& c) {
#pragma unroll
    for (int o = 0; o < 4; o++)
#pragma unroll
        for (int u = 0; u < 6; u++)
            dst[o * 6 + u] = bf2_fma(v[o + 2][u], c.w[3 * DY + 2][u], bf2_fma(v[o + 1][u], c.w[3 * DY + 1][u],
                             bf2_fma(v[o][u], c.w[3 * DY][u], STRIDE ? src[o * 6 + u] : src[2 * o + 1])));
}
#define HAND_OVER(name, base, r) asm volatile("mov.b32 " name "%6, %0; mov.b32 " name "%7, %1; mov.b32 " name "%8, %2;\n" \
    "mov.b32 " name "%9, %3; mov.b32 " name "%10, %4; mov.b32 " name "%11, %5;" ::"r"((r)[0]), "r"((r)[1]), "r"((r)[2]), \
    "r"((r)[3]), "r"((r)[4]), "r"((r)[5]), "n"(base), "n"(base + 1), "n"(base + 2), "n"(base + 3), "n"(base + 4), "n"(base + 5))
template <int K> __device__ __forceinline__ void hand_over(const Producer& c, const uint32_t (&B)[24], const uint32_t (&C)[24],
                                                           const uint32_t (&v)[6][6]) {
    HAND_OVER("pw", K * 6, c.w[K]);
    if (K < 6) HAND_OVER("pv", K * 6, v[K % 6]);
    if (K < 4) { HAND_OVER("pb", K * 6, B + K % 4 * 6); HAND_OVER("pc", K * 6, C + K % 4 * 6); }
    if constexpr (K < 8) hand_over<K + 1>(c, B, C, v);
}
static_assert(sb + SM_BAR + BAR_DUMMY * 8 == 230880, "layout");
__device__ __forceinline__ void produce_tiles(const Producer& c, const Params& prm) {
    asm volatile(
        "{\n"
        ".reg .b32 pa<24>, pq<4>, m<6>, y<6>, rr, mm, t, so, sp, sn, ph, ad, tt, cnt;\n"
        ".reg .b16 xl, xh;\n"
        ".reg .f32 d<4>, us, s0, s1, f0, f1, kq;\n"
        ".reg .pred pt, pf, pr, pw, px, pl, po, pe, pn, pp;\n"
        "setp.ne.b32 pt, 1, 0; setp.ne.b32 pf, 0, 0; setp.eq.u32 pl, %8, 0; and.b32 tt, %8, 1; setp.ne.u32 po, tt, 0;\n"
        "and.b32 tt, %8, 4; setp.ne.u32 pr, tt, 0; selp.f32 kq, 0f3F802D41, 0f3F7FA57E, pr;\n"
        "mov.u32 t, 0; mov.u32 so, 0; mov.u32 sp, 55896; mov.u32 ph, 1; mov.pred pn, pf; mov.pred pp, pf;\n"
        "setp.eq.u32 pr, %12, 0;\n"
        "@pr bra.uni RARE;\n"
        "LOOP:\n"
        ASM_TRC("t", 0)
        "fence.proxy.async.shared::cta;\n"
        "@pl mbarrier.arrive.shared::cta.b64 _, [sp+174984];\n"
        "fma.rn.bf16x2 pa0, pv0, pw36, pb0; fma.rn.bf16x2 pa1, pv1, pw37, pb1; fma.rn.bf16x2 pa2, pv2, pw38, pb2; fma.rn.bf16x2 pa3, pv3, pw39, pb3; fma.rn.bf16x2 pa4, pv4, pw40, pb4; fma.rn.bf16x2 pa5, pv5, pw41, pb5;\n"
        "fma.rn.bf16x2 pa6, pv6, pw36, pb6; fma.rn.bf16x2 pa7, pv7, pw37, pb7; fma.rn.bf16x2 pa8, pv8, pw38, pb8; fma.rn.bf16x2 pa9, pv9, pw39, pb9; fma.rn.bf16x2 pa10, pv10, pw40, pb10; fma.rn.bf16x2 pa11, pv11, pw41, pb11;\n"
        "fma.rn.bf16x2 pa12, pv12, pw36, pb12; fma.rn.bf16x2 pa13, pv13, pw37, pb13; fma.rn.bf16x2 pa14, pv14, pw38, pb14; fma.rn.bf16x2 pa15, pv15, pw39, pb15; fma.rn.bf16x2 pa16, pv16, pw40, pb16; fma.rn.bf16x2 pa17, pv17, pw41, pb17;\n"
        "fma.rn.bf16x2 pa18, pv18, pw36, pb18; fma.rn.bf16x2 pa19, pv19, pw37, pb19; fma.rn.bf16x2 pa20, pv20, pw38, pb20; fma.rn.bf16x2 pa21, pv21, pw39, pb21; fma.rn.bf16x2 pa22, pv22, pw40, pb22; fma.rn.bf16x2 pa23, pv23, pw41, pb23;\n"
        "fma.rn.bf16x2 pa0, pv6, pw42, pa0; fma.rn.bf16x2 pa1, pv7, pw43, pa1; fma.rn.bf16x2 pa2, pv8, pw44, pa2; fma.rn.bf16x2 pa3, pv9, pw45, pa3; fma.rn.bf16x2 pa4, pv10, pw46, pa4; fma.rn.bf16x2 pa5, pv11, pw47, pa5;\n"
        "fma.rn.bf16x2 pa6, pv12, pw42, pa6; fma.rn.bf16x2 pa7, pv13, pw43, pa7; fma.rn.bf16x2 pa8, pv14, pw44, pa8; fma.rn.bf16x2 pa9, pv15, pw45, pa9; fma.rn.bf16x2 pa10, pv16, pw46, pa10; fma.rn.bf16x2 pa11, pv17, pw47, pa11;\n"
        "fma.rn.bf16x2 pa12, pv18, pw42, pa12; fma.rn.bf16x2 pa13, pv19, pw43, pa13; fma.rn.bf16x2 pa14, pv20, pw44, pa14; fma.rn.bf16x2 pa15, pv21, pw45, pa15; fma.rn.bf16x2 pa16, pv22, pw46, pa16; fma.rn.bf16x2 pa17, pv23, pw47, pa17;\n"
        "fma.rn.bf16x2 pa18, pv24, pw42, pa18; fma.rn.bf16x2 pa19, pv25, pw43, pa19; fma.rn.bf16x2 pa20, pv26, pw44, pa20; fma.rn.bf16x2 pa21, pv27, pw45, pa21; fma.rn.bf16x2 pa22, pv28, pw46, pa22; fma.rn.bf16x2 pa23, pv29, pw47, pa23;\n"
        "fma.rn.bf16x2 pa0, pv12, pw48, pa0; fma.rn.bf16x2 pa1, pv13, pw49, pa1; fma.rn.bf16x2 pa2, pv14, pw50, pa2; fma.rn.bf16x2 pa3, pv15, pw51, pa3; fma.rn.bf16x2 pa4, pv16, pw52, pa4; fma.rn.bf16x2 pa5, pv17, pw53, pa5;\n"
        "fma.rn.bf16x2 pa6, pv18, pw48, pa6; fma.rn.bf16x2 pa7, pv19, pw49, pa7; fma.rn.bf16x2 pa8, pv20, pw50, pa8; fma.rn.bf16x2 pa9, pv21, pw51, pa9; fma.rn.bf16x2 pa10, pv22, pw52, pa10; fma.rn.bf16x2 pa11, pv23, pw53, pa11;\n"
        "fma.rn.bf16x2 pa12, pv24, pw48, pa12; fma.rn.bf16x2 pa13, pv25, pw49, pa13; fma.rn.bf16x2 pa14, pv26, pw50, pa14; fma.rn.bf16x2 pa15, pv27, pw51, pa15; fma.rn.bf16x2 pa16, pv28, pw52, pa16; fma.rn.bf16x2 pa17, pv29, pw53, pa17;\n"
        "fma.rn.bf16x2 pa18, pv30, pw48, pa18; fma.rn.bf16x2 pa19, pv31, pw49, pa19; fma.rn.bf16x2 pa20, pv32, pw50, pa20; fma.rn.bf16x2 pa21, pv33, pw51, pa21; fma.rn.bf16x2 pa22, pv34, pw52, pa22; fma.rn.bf16x2 pa23, pv35, pw53, pa23;\n"
        "mul.rn.bf16x2 pq0, pa0, pa0; fma.rn.bf16x2 pq0, pa1, pa1, pq0; fma.rn.bf16x2 pq0, pa2, pa2, pq0; fma.rn.bf16x2 pq0, pa3, pa3, pq0; fma.rn.bf16x2 pq0, pa4, pa4, pq0; fma.rn.bf16x2 pq0, pa5, pa5, pq0;\n"
        "mul.rn.bf16x2 pq1, pa6, pa6; fma.rn.bf16x2 pq1, pa7, pa7, pq1; fma.rn.bf16x2 pq1, pa8, pa8, pq1; fma.rn.bf16x2 pq1, pa9, pa9, pq1; fma.rn.bf16x2 pq1, pa10, pa10, pq1; fma.rn.bf16x2 pq1, pa11, pa11, pq1;\n"
        "mul.rn.bf16x2 pq2, pa12, pa12; fma.rn.bf16x2 pq2, pa13, pa13, pq2; fma.rn.bf16x2 pq2, pa14, pa14, pq2; fma.rn.bf16x2 pq2, pa15, pa15, pq2; fma.rn.bf16x2 pq2, pa16, pa16, pq2; fma.rn.bf16x2 pq2, pa17, pa17, pq2;\n"
        "mul.rn.bf16x2 pq3, pa18, pa18; fma.rn.bf16x2 pq3, pa19, pa19, pq3; fma.rn.bf16x2 pq3, pa20, pa20, pq3; fma.rn.bf16x2 pq3, pa21, pa21, pq3; fma.rn.bf16x2 pq3, pa22, pa22, pq3; fma.rn.bf16x2 pq3, pa23, pa23, pq3;\n"
        "B0:\n"
        "wgmma.fence.sync.aligned;\n"
        "wgmma.mma_async.sync.aligned.m64n8k16.f32.bf16.bf16 {d0,d1,d2,d3}, {pa0,pa6,pa1,pa7}, %9, pf, 1, 1, 0;\n"
        "wgmma.mma_async.sync.aligned.m64n8k16.f32.bf16.bf16 {d0,d1,d2,d3}, {pa2,pa8,pa3,pa9}, %9, pt, 1, 1, 0;\n"
        "wgmma.mma_async.sync.aligned.m64n8k16.f32.bf16.bf16 {d0,d1,d2,d3}, {pa4,pa10,pa5,pa11}, %9, pt, 1, 1, 0;\n"
        "wgmma.mma_async.sync.aligned.m64n8k16.f32.bf16.bf16 {d0,d1,d2,d3}, {pa12,pa18,pa13,pa19}, %10, pt, 1, 1, 0;\n"
        "wgmma.mma_async.sync.aligned.m64n8k16.f32.bf16.bf16 {d0,d1,d2,d3}, {pa14,pa20,pa15,pa21}, %10, pt, 1, 1, 0;\n"
        "wgmma.mma_async.sync.aligned.m64n8k16.f32.bf16.bf16 {d0,d1,d2,d3}, {pa16,pa22,pa17,pa23}, %10, pt, 1, 1, 0;\n"
        "wgmma.mma_async.sync.aligned.m64n8k16.f32.bf16.bf16 {d0,d1,d2,d3}, {pq0,pq1,pq2,pq3}, %11, pt, 1, 1, 0;\n"
        "wgmma.commit_group.sync.aligned;\n"
        "add.u32 ad, %7, so; ld.shared.f32 us, [ad+4];\n"
        "fma.rn.bf16x2 pb0, pv0, pw18, pc0; fma.rn.bf16x2 pb1, pv1, pw19, pc1; fma.rn.bf16x2 pb2, pv2, pw20, pc2; fma.rn.bf16x2 pb3, pv3, pw21, pc3; fma.rn.bf16x2 pb4, pv4, pw22, pc4; fma.rn.bf16x2 pb5, pv5, pw23, pc5;\n"
        "fma.rn.bf16x2 pb6, pv6, pw18, pc6; fma.rn.bf16x2 pb7, pv7, pw19, pc7; fma.rn.bf16x2 pb8, pv8, pw20, pc8; fma.rn.bf16x2 pb9, pv9, pw21, pc9; fma.rn.bf16x2 pb10, pv10, pw22, pc10; fma.rn.bf16x2 pb11, pv11, pw23, pc11;\n"
        "fma.rn.bf16x2 pb0, pv6, pw24, pb0; fma.rn.bf16x2 pb1, pv7, pw25, pb1; fma.rn.bf16x2 pb2, pv8, pw26, pb2; fma.rn.bf16x2 pb3, pv9, pw27, pb3; fma.rn.bf16x2 pb4, pv10, pw28, pb4; fma.rn.bf16x2 pb5, pv11, pw29, pb5;\n"
        "fma.rn.bf16x2 pb6, pv12, pw24, pb6; fma.rn.bf16x2 pb7, pv13, pw25, pb7; fma.rn.bf16x2 pb8, pv14, pw26, pb8; fma.rn.bf16x2 pb9, pv15, pw27, pb9; fma.rn.bf16x2 pb10, pv16, pw28, pb10; fma.rn.bf16x2 pb11, pv17, pw29, pb11;\n"
        "fma.rn.bf16x2 pb0, pv12, pw30, pb0; fma.rn.bf16x2 pb1, pv13, pw31, pb1; fma.rn.bf16x2 pb2, pv14, pw32, pb2; fma.rn.bf16x2 pb3, pv15, pw33, pb3; fma.rn.bf16x2 pb4, pv16, pw34, pb4; fma.rn.bf16x2 pb5, pv17, pw35, pb5;\n"
        "fma.rn.bf16x2 pb6, pv18, pw30, pb6; fma.rn.bf16x2 pb7, pv19, pw31, pb7; fma.rn.bf16x2 pb8, pv20, pw32, pb8; fma.rn.bf16x2 pb9, pv21, pw33, pb9; fma.rn.bf16x2 pb10, pv22, pw34, pb10; fma.rn.bf16x2 pb11, pv23, pw35, pb11;\n"
        "B1:\n"
        "fma.rn.bf16x2 pb12, pv12, pw18, pc12; fma.rn.bf16x2 pb13, pv13, pw19, pc13; fma.rn.bf16x2 pb14, pv14, pw20, pc14; fma.rn.bf16x2 pb15, pv15, pw21, pc15; fma.rn.bf16x2 pb16, pv16, pw22, pc16; fma.rn.bf16x2 pb17, pv17, pw23, pc17;\n"
        "fma.rn.bf16x2 pb18, pv18, pw18, pc18; fma.rn.bf16x2 pb19, pv19, pw19, pc19; fma.rn.bf16x2 pb20, pv20, pw20, pc20; fma.rn.bf16x2 pb21, pv21, pw21, pc21; fma.rn.bf16x2 pb22, pv22, pw22, pc22; fma.rn.bf16x2 pb23, pv23, pw23, pc23;\n"
        "fma.rn.bf16x2 pb12, pv18, pw24, pb12; fma.rn.bf16x2 pb13, pv19, pw25, pb13; fma.rn.bf16x2 pb14, pv20, pw26, pb14; fma.rn.bf16x2 pb15, pv21, pw27, pb15; fma.rn.bf16x2 pb16, pv22, pw28, pb16; fma.rn.bf16x2 pb17, pv23, pw29, pb17;\n"
        "fma.rn.bf16x2 pb18, pv24, pw24, pb18; fma.rn.bf16x2 pb19, pv25, pw25, pb19; fma.rn.bf16x2 pb20, pv26, pw26, pb20; fma.rn.bf16x2 pb21, pv27, pw27, pb21; fma.rn.bf16x2 pb22, pv28, pw28, pb22; fma.rn.bf16x2 pb23, pv29, pw29, pb23;\n"
        "fma.rn.bf16x2 pb12, pv24, pw30, pb12; fma.rn.bf16x2 pb13, pv25, pw31, pb13; fma.rn.bf16x2 pb14, pv26, pw32, pb14; fma.rn.bf16x2 pb15, pv27, pw33, pb15; fma.rn.bf16x2 pb16, pv28, pw34, pb16; fma.rn.bf16x2 pb17, pv29, pw35, pb17;\n"
        "fma.rn.bf16x2 pb18, pv30, pw30, pb18; fma.rn.bf16x2 pb19, pv31, pw31, pb19; fma.rn.bf16x2 pb20, pv32, pw32, pb20; fma.rn.bf16x2 pb21, pv33, pw33, pb21; fma.rn.bf16x2 pb22, pv34, pw34, pb22; fma.rn.bf16x2 pb23, pv35, pw35, pb23;\n"
        "C0:\n"
        "wgmma.wait_group.sync.aligned 0;\n"
        "selp.f32 s0, d2, d0, po; selp.f32 s1, d3, d1, po;\n"
        "shfl.sync.bfly.b32 f0, s0, 4, 0x1f, 0xffffffff; shfl.sync.bfly.b32 f1, s1, 4, 0x1f, 0xffffffff;\n"
        "fma.rn.bf16x2 pc0, pv0, pw0, ps1; fma.rn.bf16x2 pc1, pv1, pw1, ps1; fma.rn.bf16x2 pc2, pv2, pw2, ps1; fma.rn.bf16x2 pc3, pv3, pw3, ps1; fma.rn.bf16x2 pc4, pv4, pw4, ps1; fma.rn.bf16x2 pc5, pv5, pw5, ps1;\n"
        "fma.rn.bf16x2 pc6, pv6, pw0, ps3; fma.rn.bf16x2 pc7, pv7, pw1, ps3; fma.rn.bf16x2 pc8, pv8, pw2, ps3; fma.rn.bf16x2 pc9, pv9, pw3, ps3; fma.rn.bf16x2 pc10, pv10, pw4, ps3; fma.rn.bf16x2 pc11, pv11, pw5, ps3;\n"
        "fma.rn.bf16x2 pc12, pv12, pw0, ps5; fma.rn.bf16x2 pc13, pv13, pw1, ps5; fma.rn.bf16x2 pc14, pv14, pw2, ps5; fma.rn.bf16x2 pc15, pv15, pw3, ps5; fma.rn.bf16x2 pc16, pv16, pw4, ps5; fma.rn.bf16x2 pc17, pv17, pw5, ps5;\n"
        "fma.rn.bf16x2 pc18, pv18, pw0, ps7; fma.rn.bf16x2 pc19, pv19, pw1, ps7; fma.rn.bf16x2 pc20, pv20, pw2, ps7; fma.rn.bf16x2 pc21, pv21, pw3, ps7; fma.rn.bf16x2 pc22, pv22, pw4, ps7; fma.rn.bf16x2 pc23, pv23, pw5, ps7;\n"
        "fma.rn.bf16x2 pc0, pv6, pw6, pc0; fma.rn.bf16x2 pc1, pv7, pw7, pc1; fma.rn.bf16x2 pc2, pv8, pw8, pc2; fma.rn.bf16x2 pc3, pv9, pw9, pc3; fma.rn.bf16x2 pc4, pv10, pw10, pc4; fma.rn.bf16x2 pc5, pv11, pw11, pc5;\n"
        "fma.rn.bf16x2 pc6, pv12, pw6, pc6; fma.rn.bf16x2 pc7, pv13, pw7, pc7; fma.rn.bf16x2 pc8, pv14, pw8, pc8; fma.rn.bf16x2 pc9, pv15, pw9, pc9; fma.rn.bf16x2 pc10, pv16, pw10, pc10; fma.rn.bf16x2 pc11, pv17, pw11, pc11;\n"
        "fma.rn.bf16x2 pc12, pv18, pw6, pc12; fma.rn.bf16x2 pc13, pv19, pw7, pc13; fma.rn.bf16x2 pc14, pv20, pw8, pc14; fma.rn.bf16x2 pc15, pv21, pw9, pc15; fma.rn.bf16x2 pc16, pv22, pw10, pc16; fma.rn.bf16x2 pc17, pv23, pw11, pc17;\n"
        "fma.rn.bf16x2 pc18, pv24, pw6, pc18; fma.rn.bf16x2 pc19, pv25, pw7, pc19; fma.rn.bf16x2 pc20, pv26, pw8, pc20; fma.rn.bf16x2 pc21, pv27, pw9, pc21; fma.rn.bf16x2 pc22, pv28, pw10, pc22; fma.rn.bf16x2 pc23, pv29, pw11, pc23;\n"
        "fma.rn.bf16x2 pc0, pv12, pw12, pc0; fma.rn.bf16x2 pc1, pv13, pw13, pc1; fma.rn.bf16x2 pc2, pv14, pw14, pc2; fma.rn.bf16x2 pc3, pv15, pw15, pc3; fma.rn.bf16x2 pc4, pv16, pw16, pc4; fma.rn.bf16x2 pc5, pv17, pw17, pc5;\n"
        "fma.rn.bf16x2 pc6, pv18, pw12, pc6; fma.rn.bf16x2 pc7, pv19, pw13, pc7; fma.rn.bf16x2 pc8, pv20, pw14, pc8; fma.rn.bf16x2 pc9, pv21, pw15, pc9; fma.rn.bf16x2 pc10, pv22, pw16, pc10; fma.rn.bf16x2 pc11, pv23, pw17, pc11;\n"
        "fma.rn.bf16x2 pc12, pv24, pw12, pc12; fma.rn.bf16x2 pc13, pv25, pw13, pc13; fma.rn.bf16x2 pc14, pv26, pw14, pc14; fma.rn.bf16x2 pc15, pv27, pw15, pc15; fma.rn.bf16x2 pc16, pv28, pw16, pc16; fma.rn.bf16x2 pc17, pv29, pw17, pc17;\n"
        "fma.rn.bf16x2 pc18, pv30, pw12, pc18; fma.rn.bf16x2 pc19, pv31, pw13, pc19; fma.rn.bf16x2 pc20, pv32, pw14, pc20; fma.rn.bf16x2 pc21, pv33, pw15, pc21; fma.rn.bf16x2 pc22, pv34, pw16, pc22; fma.rn.bf16x2 pc23, pv35, pw17, pc23;\n"
        "add.f32 s0, s0, f0; add.f32 s1, s1, f1; mul.f32 s0, s0, 0fBC2AAAAB;\n"
        "neg.f32 f0, s0; fma.rn.f32 f0, f0, s0, %13; fma.rn.f32 f0, s1, 0f3C2AAAAB, f0; max.f32 f0, f0, %13;\n"
        "rsqrt.approx.ftz.f32 f0, f0; mul.f32 f0, f0, %14; cvt.rn.bf16x2.f32 tt, f0, 0f00000000; mov.b32 f0, tt;\n"
        "mul.f32 f1, s0, kq; mul.f32 f1, f1, f0; cvt.rn.bf16x2.f32 tt, f1, f0; add.f32 us, us, s0; cvt.rn.bf16x2.f32 mm, us, us;\n"
        "add.u32 ad, %7, so; st.shared.v2.b32 [ad], {tt, mm};\n"
        "add.u32 ad, %6, so; ld.shared.v4.b32 {ps0,ps1,ps2,ps3}, [ad]; ld.shared.v4.b32 {ps4,ps5,ps6,ps7}, [ad+16];\n"
        "mbarrier.try_wait.parity.shared::cta.b64 pw, [so+174992], ph;\n"
        "mbarrier.try_wait.parity.shared::cta.b64 px, [so+174976], ph;\n"
        "and.pred pw, pw, px;\n"
        "N0:\n"
        "@!pw bra.uni SPIN;\n"
        "BACK:\n"
        "add.u32 ad, %0, so; ld.shared.v4.b32 {pv0,pv1,pv2,pv3}, [ad+0];\n"
        "add.u32 ad, %1, so; ld.shared.v2.b32 {pv4,pv5}, [ad+0];\n"
        "add.u32 ad, %0, so; ld.shared.v4.b32 {pv6,pv7,pv8,pv9}, [ad+192];\n"
        "add.u32 ad, %1, so; ld.shared.v2.b32 {pv10,pv11}, [ad+192];\n"
        "mov.b32 {xl, xh}, ps0; mov.b32 rr, {xl, xl}; mov.b32 mm, {xh, xh}; fma.rn.bf16x2 pa0, pa0, rr, mm; fma.rn.bf16x2 pa1, pa1, rr, mm; fma.rn.bf16x2 pa2, pa2, rr, mm; fma.rn.bf16x2 pa3, pa3, rr, mm; fma.rn.bf16x2 pa4, pa4, rr, mm; fma.rn.bf16x2 pa5, pa5, rr, mm;\n"
        "and.b32 m0, pa0, 0x7fff7fff; and.b32 m1, pa1, 0x7fff7fff; and.b32 m2, pa2, 0x7fff7fff; and.b32 m3, pa3, 0x7fff7fff; and.b32 m4, pa4, 0x7fff7fff; and.b32 m5, pa5, 0x7fff7fff;\n"
        "mad.lo.u32 y0, m0, 7, pa0; mad.lo.u32 y1, m1, 7, pa1; mad.lo.u32 y2, m2, 7, pa2; mad.lo.u32 y3, m3, 7, pa3; mad.lo.u32 y4, m4, 7, pa4; mad.lo.u32 y5, m5, 7, pa5;\n"
        "add.u32 ad, %2, so; st.shared.v4.b32 [ad+0], {y0,y1,y2,y3};\n"
        "add.u32 ad, %4, so; st.shared.v2.b32 [ad+0], {y4,y5};\n"
        "N1:\n"
        "add.u32 ad, %0, so; ld.shared.v4.b32 {pv12,pv13,pv14,pv15}, [ad+384];\n"
        "add.u32 ad, %1, so; ld.shared.v2.b32 {pv16,pv17}, [ad+384];\n"
        "add.u32 ad, %0, so; ld.shared.v4.b32 {pv18,pv19,pv20,pv21}, [ad+576];\n"
        "add.u32 ad, %1, so; ld.shared.v2.b32 {pv22,pv23}, [ad+576];\n"
        "mov.b32 {xl, xh}, ps2; mov.b32 rr, {xl, xl}; mov.b32 mm, {xh, xh}; fma.rn.bf16x2 pa6, pa6, rr, mm; fma.rn.bf16x2 pa7, pa7, rr, mm; fma.rn.bf16x2 pa8, pa8, rr, mm; fma.rn.bf16x2 pa9, pa9, rr, mm; fma.rn.bf16x2 pa10, pa10, rr, mm; fma.rn.bf16x2 pa11, pa11, rr, mm;\n"
        "and.b32 m0, pa6, 0x7fff7fff; and.b32 m1, pa7, 0x7fff7fff; and.b32 m2, pa8, 0x7fff7fff; and.b32 m3, pa9, 0x7fff7fff; and.b32 m4, pa10, 0x7fff7fff; and.b32 m5, pa11, 0x7fff7fff;\n"
        "mad.lo.u32 y0, m0, 7, pa6; mad.lo.u32 y1, m1, 7, pa7; mad.lo.u32 y2, m2, 7, pa8; mad.lo.u32 y3, m3, 7, pa9; mad.lo.u32 y4, m4, 7, pa10; mad.lo.u32 y5, m5, 7, pa11;\n"
        "add.u32 ad, %3, so; st.shared.v4.b32 [ad+0], {y0,y1,y2,y3};\n"
        "add.u32 ad, %5, so; st.shared.v2.b32 [ad+0], {y4,y5};\n"
        "N2:\n"
        "add.u32 ad, %0, so; ld.shared.v4.b32 {pv24,pv25,pv26,pv27}, [ad+768];\n"
        "add.u32 ad, %1, so; ld.shared.v2.b32 {pv28,pv29}, [ad+768];\n"
        "mov.b32 {xl, xh}, ps4; mov.b32 rr, {xl, xl}; mov.b32 mm, {xh, xh}; fma.rn.bf16x2 pa12, pa12, rr, mm; fma.rn.bf16x2 pa13, pa13, rr, mm; fma.rn.bf16x2 pa14, pa14, rr, mm; fma.rn.bf16x2 pa15, pa15, rr, mm; fma.rn.bf16x2 pa16, pa16, rr, mm; fma.rn.bf16x2 pa17, pa17, rr, mm;\n"
        "and.b32 m0, pa12, 0x7fff7fff; and.b32 m1, pa13, 0x7fff7fff; and.b32 m2, pa14, 0x7fff7fff; and.b32 m3, pa15, 0x7fff7fff; and.b32 m4, pa16, 0x7fff7fff; and.b32 m5, pa17, 0x7fff7fff;\n"
        "mad.lo.u32 y0, m0, 7, pa12; mad.lo.u32 y1, m1, 7, pa13; mad.lo.u32 y2, m2, 7, pa14; mad.lo.u32 y3, m3, 7, pa15; mad.lo.u32 y4, m4, 7, pa16; mad.lo.u32 y5, m5, 7, pa17;\n"
        "add.u32 ad, %2, so; st.shared.v4.b32 [ad+2048], {y0,y1,y2,y3};\n"
        "add.u32 ad, %4, so; st.shared.v2.b32 [ad+1024], {y4,y5};\n"
        "N3:\n"
        "add.u32 ad, %0, so; ld.shared.v4.b32 {pv30,pv31,pv32,pv33}, [ad+960];\n"
        "add.u32 ad, %1, so; ld.shared.v2.b32 {pv34,pv35}, [ad+960];\n"
        "mov.b32 {xl, xh}, ps6; mov.b32 rr, {xl, xl}; mov.b32 mm, {xh, xh}; fma.rn.bf16x2 pa18, pa18, rr, mm; fma.rn.bf16x2 pa19, pa19, rr, mm; fma.rn.bf16x2 pa20, pa20, rr, mm; fma.rn.bf16x2 pa21, pa21, rr, mm; fma.rn.bf16x2 pa22, pa22, rr, mm; fma.rn.bf16x2 pa23, pa23, rr, mm;\n"
        "and.b32 m0, pa18, 0x7fff7fff; and.b32 m1, pa19, 0x7fff7fff; and.b32 m2, pa20, 0x7fff7fff; and.b32 m3, pa21, 0x7fff7fff; and.b32 m4, pa22, 0x7fff7fff; and.b32 m5, pa23, 0x7fff7fff;\n"
        "mad.lo.u32 y0, m0, 7, pa18; mad.lo.u32 y1, m1, 7, pa19; mad.lo.u32 y2, m2, 7, pa20; mad.lo.u32 y3, m3, 7, pa21; mad.lo.u32 y4, m4, 7, pa22; mad.lo.u32 y5, m5, 7, pa23;\n"
        "add.u32 ad, %3, so; st.shared.v4.b32 [ad+2048], {y0,y1,y2,y3};\n"
        "add.u32 ad, %5, so; st.shared.v2.b32 [ad+1024], {y4,y5};\n"
        "mov.u32 sp, so; add.u32 so, so, 26624; setp.eq.u32 pr, so, 79872; selp.u32 so, 0, so, pr; selp.u32 tt, 1, 0, pr; xor.b32 ph, ph, tt;\n"
        "add.u32 t, t, 1; setp.lt.u32 pe, t, 32;\n"
        "@pe bra.uni LOOP;\n"
        "bra.uni DONE;\n"
        "SPIN: mov.u32 cnt, 0;\n"
        ASM_TRC("t", 1)
        "SPINL:\n"
        "mbarrier.try_wait.parity.shared::cta.b64 pw, [so+174992], ph;\n"
        "mbarrier.try_wait.parity.shared::cta.b64 px, [so+174976], ph;\n"
        "and.pred pw, pw, px;\n"
        "@pw bra.uni BACK;\n"
        "add.u32 cnt, cnt, 1; setp.lt.u32 pw, cnt, 0x100000;\n"
        "@pw bra.uni SPINL;\n"
        "trap;\n"
        "RARE:\n"
        "ld.volatile.shared.u32 tt, [%6];\n"
        "mov.b32 pa0, tt; mov.b32 pa1, tt; mov.b32 pa2, tt; mov.b32 pa3, tt; mov.b32 pa4, tt; mov.b32 pa5, tt; mov.b32 pa6, tt; mov.b32 pa7, tt; mov.b32 pa8, tt; mov.b32 pa9, tt; mov.b32 pa10, tt; mov.b32 pa11, tt;\n"
        "mov.b32 pa12, tt; mov.b32 pa13, tt; mov.b32 pa14, tt; mov.b32 pa15, tt; mov.b32 pa16, tt; mov.b32 pa17, tt; mov.b32 pa18, tt; mov.b32 pa19, tt; mov.b32 pa20, tt; mov.b32 pa21, tt; mov.b32 pa22, tt; mov.b32 pa23, tt;\n"
        "mov.b32 pb0, tt; mov.b32 pb1, tt; mov.b32 pb2, tt; mov.b32 pb3, tt; mov.b32 pb4, tt; mov.b32 pb5, tt; mov.b32 pb6, tt; mov.b32 pb7, tt; mov.b32 pb8, tt; mov.b32 pb9, tt; mov.b32 pb10, tt; mov.b32 pb11, tt;\n"
        "mov.b32 pb12, tt; mov.b32 pb13, tt; mov.b32 pb14, tt; mov.b32 pb15, tt; mov.b32 pb16, tt; mov.b32 pb17, tt; mov.b32 pb18, tt; mov.b32 pb19, tt; mov.b32 pb20, tt; mov.b32 pb21, tt; mov.b32 pb22, tt; mov.b32 pb23, tt;\n"
        "mov.b32 pc0, tt; mov.b32 pc1, tt; mov.b32 pc2, tt; mov.b32 pc3, tt; mov.b32 pc4, tt; mov.b32 pc5, tt; mov.b32 pc6, tt; mov.b32 pc7, tt; mov.b32 pc8, tt; mov.b32 pc9, tt; mov.b32 pc10, tt; mov.b32 pc11, tt;\n"
        "mov.b32 pc12, tt; mov.b32 pc13, tt; mov.b32 pc14, tt; mov.b32 pc15, tt; mov.b32 pc16, tt; mov.b32 pc17, tt; mov.b32 pc18, tt; mov.b32 pc19, tt; mov.b32 pc20, tt; mov.b32 pc21, tt; mov.b32 pc22, tt; mov.b32 pc23, tt;\n"
        "mov.b32 ps0, tt; mov.b32 ps1, tt; mov.b32 ps2, tt; mov.b32 ps3, tt; mov.b32 ps4, tt; mov.b32 ps5, tt; mov.b32 ps6, tt; mov.b32 ps7, tt; mov.b32 pq0, tt; mov.b32 pq1, tt; mov.b32 pq2, tt; mov.b32 pq3, tt;\n"
        "mov.b32 us, tt; setp.ne.u32 pw, %15, 7;\n"
        "wgmma.fence.sync.aligned;\n"
        "setp.eq.u32 pr, %15, 1000; @pr bra.uni B0;\n"
        "setp.eq.u32 pr, %15, 1001; @pr bra.uni B1;\n"
        "setp.eq.u32 pr, %15, 1002; @pr bra.uni C0;\n"
        "setp.eq.u32 pr, %15, 1003; @pr bra.uni N0;\n"
        "setp.eq.u32 pr, %15, 1004; @pr bra.uni N1;\n"
        "setp.eq.u32 pr, %15, 1005; @pr bra.uni N2;\n"
        "setp.eq.u32 pr, %15, 1006; @pr bra.uni N3;\n"
        "trap;\n"
        "DONE:\n"
        ASM_TRC("t", 0)
        "fence.proxy.async.shared::cta;\n"
        "@pl mbarrier.arrive.shared::cta.b64 _, [sp+174984];\n"
        "}\n"
        :: "r"(sb + SM_X + c.xoff[0]), "r"(sb + SM_X + c.xoff[1]), "r"(sb + SM_Y1 + c.yoff[0][0]), "r"(sb + SM_Y1 + c.yoff[0][1]),
           "r"(sb + SM_Y1 + c.yoff[1][0]), "r"(sb + SM_Y1 + c.yoff[1][1]), "r"(c.stat), "r"(c.own), "r"(c.lane),
           "l"(prm.sel[0]), "l"(prm.sel[1]), "l"(prm.sel[2]), "r"(prm.ydesc), "f"(LN_EPS_SCALED), "f"(RSTD_SCALE), "r"(prm.w1desc)
        : "memory");
}

__device__ __forceinline__ void produce(const Producer& c, const Params& prm) {
    uint32_t B[24], C[24];
    const RowCopy rc = row_copy(prm);
    uint32_t st[8];
    uint32_t v[6][6];
    {
        uint32_t ws[6];
#pragma unroll
        for (int u = 0; u < 6; u++) {
            ws[u] = c.w[0][u];
#pragma unroll
            for (int t = 1; t < 9; t++) ws[u] = bf2_add(ws[u], c.w[t][u]);
        }
        SMARK(2);
        mbar_wait_c<0>(sb + SM_XFULL);
        SMARK(3);
        lds128(v[0], sb + SM_X + c.xoff[0] + 2 * 192);
        asm volatile("ld.shared.v2.b32 {%0,%1}, [%2];" : "=r"(v[0][4]), "=r"(v[0][5]) : "r"(sb + SM_X + c.xoff[1] + 2 * 192));
        const uint32_t p = bf2_add(bf2_fma(v[0][2], ws[2], bf2_fma(v[0][1], ws[1], bf2_mul(v[0][0], ws[0]))),
                                   bf2_fma(v[0][5], ws[5], bf2_fma(v[0][4], ws[4], bf2_mul(v[0][3], ws[3]))));
        float e = quad_sum(bf_lo(p) + bf_hi(p));
        e = (e + __shfl_xor_sync(0xffffffffu, e, 4)) * (-1.0f / CH);
        st[1] = st[3] = st[5] = st[7] = pack_bf2(e, e);
#pragma unroll
        for (int k = 0; k < NX; k++) sts32(c.own + k * SLOT_BYTES + 4, st[1]);
#pragma unroll
        for (int r = 0; r < 24; r++) C[r] = 0;
    }
#pragma unroll 1
    for (int i = loop_init<0>();; i++) {
        mbar_wait_c<0>(sb + SM_XFULL + i * SLOT_BYTES);
        SMARK(4 + i);
        load_x(v, c, sb + SM_X + i * SLOT_BYTES);
        fence_async_smem();
        if (c.warp == i) {
            named_sync(6 + i, 128);
            issue_row_load(rc, i + NX, i);
        } else {
            asm volatile("bar.arrive %0, 128;" ::"r"(6 + i) : "memory");
        }
        if (i == 2) break;
        conv_row<1, 1>(B, C, v, c);
        conv_row<0, 0>(C, st, v, c);
    }
    asm volatile(".reg .b32 pw<54>, pb<24>, pc<24>, pv<36>, ps<8>;");
    hand_over<0>(c, B, C, v);
    asm volatile("mov.b32 ps1, %0; mov.b32 ps3, %1; mov.b32 ps5, %2; mov.b32 ps7, %3;" ::"r"(st[1]), "r"(st[3]), "r"(st[5]), "r"(st[7]));
    SMARK(7);
    produce_tiles(c, prm);
    mbar_arrive_if(sb + SM_Y1FULL + ROWS_PER_CTA % NX * SLOT_BYTES, c.lane == 0);
}

struct Duty {
    const char* g;
    const char* zeros;
    long long step;
    uint32_t s, bytes;
    int end, zero;
};
__device__ __forceinline__ Duty make_duty(const Params& prm, int wg, int w) {
    const RowCopy rc = row_copy(prm);
    Duty d;
    d.g = (w == 2 ? rc.y0 : rc.x0 + (w == 0 ? rc.cut0 : w == 1 ? 32 * 192 : 192)) +
          (wg + (w == 2 ? 0 : w < 2 ? 2 * NX : 2 * NX + L2_AHEAD)) * rc.stride;
    d.step = NX * rc.stride;
    d.s = wg * SLOT_BYTES + (w == 2 ? sb + SM_Y1 : sb + SM_X + (w == 0 ? rc.cut0 : XHALF_B));
    d.bytes = w >= 2 ? TILE_BYTES : XHALF_BYTES - (w == 0 ? rc.cut0 : rc.cut1);
    d.end = w == 2 ? ROWS_PER_CTA : w < 2 ? STEPS + 1 - 2 * NX : rc.last + 1 - 2 * NX - L2_AHEAD;
    d.zero = rc.last + 1 - 2 * NX;
    d.zeros = rc.zeros;
    return d;
}

static_assert(sb + SM_Y1FULL == 174984 && sb + SM_Y1EMPTY == 174992 && sb + SM_XFULL == 174976 && SLOT_BYTES == 26624 &&
              sb + SM_GAMMA == 229248 && SM_BETA == SM_GAMMA + 768 && sb + SM_BAR + BAR_W2 * 8 == 230872 && SM_W2 == 73728, "layout");
__device__ __forceinline__ void consume(float (&acc)[2][2], uint32_t w1t, uint32_t yd, uint32_t wd, uint32_t own_slot, const Duty& d,
                                        uint32_t role, uint32_t lane, const Params& prm) {
    asm volatile(
        "{\n"
        ".reg .b32 z<32>, w<44>, p<2>, a<4>, lo<4>, hi<4>, t<2>, g<2>, q<4>, dl<6>, dh<6>, n, so, sp, ph, c, tt, cnt;\n"
        ".reg .b16 xl, xh, xr;\n"
        ".reg .b32 f0, f1;\n"
        ".reg .b64 ds<6>, wd, gp, src;\n"
        ".reg .pred pt, pf, pr, pw, pl, pe;\n"
        "setp.ne.b32 pt, 1, 0; setp.ne.b32 pf, 0, 0; setp.eq.u32 pl, %15, 0;\n"
        "mov.b32 c, 0x40D940D9;\n"
        "ldmatrix.sync.aligned.m8n8.x4.trans.shared.b16 {z0,z1,z2,z3}, [%4+22528];\n"
        "ldmatrix.sync.aligned.m8n8.x4.trans.shared.b16 {w0,w1,w2,w3}, [%4+0];\n"
        "ldmatrix.sync.aligned.m8n8.x4.trans.shared.b16 {w4,w5,w6,w7}, [%4+2048];\n"
        "ldmatrix.sync.aligned.m8n8.x4.trans.shared.b16 {w8,w9,w10,w11}, [%4+4096];\n"
        "ldmatrix.sync.aligned.m8n8.x4.trans.shared.b16 {w12,w13,w14,w15}, [%4+6144];\n"
        "ldmatrix.sync.aligned.m8n8.x4.trans.shared.b16 {w16,w17,w18,w19}, [%4+8192];\n"
        "ldmatrix.sync.aligned.m8n8.x4.trans.shared.b16 {w20,w21,w22,w23}, [%4+10240];\n"
        "ldmatrix.sync.aligned.m8n8.x4.trans.shared.b16 {w24,w25,w26,w27}, [%4+12288];\n"
        "ldmatrix.sync.aligned.m8n8.x4.trans.shared.b16 {w28,w29,w30,w31}, [%4+14336];\n"
        "ldmatrix.sync.aligned.m8n8.x4.trans.shared.b16 {w32,w33,w34,w35}, [%4+16384];\n"
        "ldmatrix.sync.aligned.m8n8.x4.trans.shared.b16 {w36,w37,w38,w39}, [%4+18432];\n"
        "ldmatrix.sync.aligned.m8n8.x4.trans.shared.b16 {w40,w41,w42,w43}, [%4+20480];\n"
        "shl.b32 f0, z0, 16; and.b32 f1, z0, 0xffff0000; cvt.rn.f16x2.f32 z0, f1, f0; shl.b32 f0, z1, 16; and.b32 f1, z1, 0xffff0000; cvt.rn.f16x2.f32 z1, f1, f0; shl.b32 f0, z2, 16; and.b32 f1, z2, 0xffff0000; cvt.rn.f16x2.f32 z2, f1, f0; shl.b32 f0, z3, 16; and.b32 f1, z3, 0xffff0000; cvt.rn.f16x2.f32 z3, f1, f0;\n"
        "stmatrix.sync.aligned.m8n8.x4.trans.shared.b16 [%4+22528], {z0,z1,z2,z3};\n"
        "shl.b32 f0, w0, 16; and.b32 f1, w0, 0xffff0000; cvt.rn.f16x2.f32 w0, f1, f0; shl.b32 f0, w1, 16; and.b32 f1, w1, 0xffff0000; cvt.rn.f16x2.f32 w1, f1, f0; shl.b32 f0, w2, 16; and.b32 f1, w2, 0xffff0000; cvt.rn.f16x2.f32 w2, f1, f0; shl.b32 f0, w3, 16; and.b32 f1, w3, 0xffff0000; cvt.rn.f16x2.f32 w3, f1, f0;\n"
        "stmatrix.sync.aligned.m8n8.x4.trans.shared.b16 [%4+0], {w0,w1,w2,w3};\n"
        "shl.b32 f0, w4, 16; and.b32 f1, w4, 0xffff0000; cvt.rn.f16x2.f32 w4, f1, f0; shl.b32 f0, w5, 16; and.b32 f1, w5, 0xffff0000; cvt.rn.f16x2.f32 w5, f1, f0; shl.b32 f0, w6, 16; and.b32 f1, w6, 0xffff0000; cvt.rn.f16x2.f32 w6, f1, f0; shl.b32 f0, w7, 16; and.b32 f1, w7, 0xffff0000; cvt.rn.f16x2.f32 w7, f1, f0;\n"
        "stmatrix.sync.aligned.m8n8.x4.trans.shared.b16 [%4+2048], {w4,w5,w6,w7};\n"
        "shl.b32 f0, w8, 16; and.b32 f1, w8, 0xffff0000; cvt.rn.f16x2.f32 w8, f1, f0; shl.b32 f0, w9, 16; and.b32 f1, w9, 0xffff0000; cvt.rn.f16x2.f32 w9, f1, f0; shl.b32 f0, w10, 16; and.b32 f1, w10, 0xffff0000; cvt.rn.f16x2.f32 w10, f1, f0; shl.b32 f0, w11, 16; and.b32 f1, w11, 0xffff0000; cvt.rn.f16x2.f32 w11, f1, f0;\n"
        "stmatrix.sync.aligned.m8n8.x4.trans.shared.b16 [%4+4096], {w8,w9,w10,w11};\n"
        "shl.b32 f0, w12, 16; and.b32 f1, w12, 0xffff0000; cvt.rn.f16x2.f32 w12, f1, f0; shl.b32 f0, w13, 16; and.b32 f1, w13, 0xffff0000; cvt.rn.f16x2.f32 w13, f1, f0; shl.b32 f0, w14, 16; and.b32 f1, w14, 0xffff0000; cvt.rn.f16x2.f32 w14, f1, f0; shl.b32 f0, w15, 16; and.b32 f1, w15, 0xffff0000; cvt.rn.f16x2.f32 w15, f1, f0;\n"
        "stmatrix.sync.aligned.m8n8.x4.trans.shared.b16 [%4+6144], {w12,w13,w14,w15};\n"
        "shl.b32 f0, w16, 16; and.b32 f1, w16, 0xffff0000; cvt.rn.f16x2.f32 w16, f1, f0; shl.b32 f0, w17, 16; and.b32 f1, w17, 0xffff0000; cvt.rn.f16x2.f32 w17, f1, f0; shl.b32 f0, w18, 16; and.b32 f1, w18, 0xffff0000; cvt.rn.f16x2.f32 w18, f1, f0; shl.b32 f0, w19, 16; and.b32 f1, w19, 0xffff0000; cvt.rn.f16x2.f32 w19, f1, f0;\n"
        "stmatrix.sync.aligned.m8n8.x4.trans.shared.b16 [%4+8192], {w16,w17,w18,w19};\n"
        "shl.b32 f0, w20, 16; and.b32 f1, w20, 0xffff0000; cvt.rn.f16x2.f32 w20, f1, f0; shl.b32 f0, w21, 16; and.b32 f1, w21, 0xffff0000; cvt.rn.f16x2.f32 w21, f1, f0; shl.b32 f0, w22, 16; and.b32 f1, w22, 0xffff0000; cvt.rn.f16x2.f32 w22, f1, f0; shl.b32 f0, w23, 16; and.b32 f1, w23, 0xffff0000; cvt.rn.f16x2.f32 w23, f1, f0;\n"
        "stmatrix.sync.aligned.m8n8.x4.trans.shared.b16 [%4+10240], {w20,w21,w22,w23};\n"
        "shl.b32 f0, w24, 16; and.b32 f1, w24, 0xffff0000; cvt.rn.f16x2.f32 w24, f1, f0; shl.b32 f0, w25, 16; and.b32 f1, w25, 0xffff0000; cvt.rn.f16x2.f32 w25, f1, f0; shl.b32 f0, w26, 16; and.b32 f1, w26, 0xffff0000; cvt.rn.f16x2.f32 w26, f1, f0; shl.b32 f0, w27, 16; and.b32 f1, w27, 0xffff0000; cvt.rn.f16x2.f32 w27, f1, f0;\n"
        "stmatrix.sync.aligned.m8n8.x4.trans.shared.b16 [%4+12288], {w24,w25,w26,w27};\n"
        "shl.b32 f0, w28, 16; and.b32 f1, w28, 0xffff0000; cvt.rn.f16x2.f32 w28, f1, f0; shl.b32 f0, w29, 16; and.b32 f1, w29, 0xffff0000; cvt.rn.f16x2.f32 w29, f1, f0; shl.b32 f0, w30, 16; and.b32 f1, w30, 0xffff0000; cvt.rn.f16x2.f32 w30, f1, f0; shl.b32 f0, w31, 16; and.b32 f1, w31, 0xffff0000; cvt.rn.f16x2.f32 w31, f1, f0;\n"
        "stmatrix.sync.aligned.m8n8.x4.trans.shared.b16 [%4+14336], {w28,w29,w30,w31};\n"
        "shl.b32 f0, w32, 16; and.b32 f1, w32, 0xffff0000; cvt.rn.f16x2.f32 w32, f1, f0; shl.b32 f0, w33, 16; and.b32 f1, w33, 0xffff0000; cvt.rn.f16x2.f32 w33, f1, f0; shl.b32 f0, w34, 16; and.b32 f1, w34, 0xffff0000; cvt.rn.f16x2.f32 w34, f1, f0; shl.b32 f0, w35, 16; and.b32 f1, w35, 0xffff0000; cvt.rn.f16x2.f32 w35, f1, f0;\n"
        "stmatrix.sync.aligned.m8n8.x4.trans.shared.b16 [%4+16384], {w32,w33,w34,w35};\n"
        "shl.b32 f0, w36, 16; and.b32 f1, w36, 0xffff0000; cvt.rn.f16x2.f32 w36, f1, f0; shl.b32 f0, w37, 16; and.b32 f1, w37, 0xffff0000; cvt.rn.f16x2.f32 w37, f1, f0; shl.b32 f0, w38, 16; and.b32 f1, w38, 0xffff0000; cvt.rn.f16x2.f32 w38, f1, f0; shl.b32 f0, w39, 16; and.b32 f1, w39, 0xffff0000; cvt.rn.f16x2.f32 w39, f1, f0;\n"
        "stmatrix.sync.aligned.m8n8.x4.trans.shared.b16 [%4+18432], {w36,w37,w38,w39};\n"
        "shl.b32 f0, w40, 16; and.b32 f1, w40, 0xffff0000; cvt.rn.f16x2.f32 w40, f1, f0; shl.b32 f0, w41, 16; and.b32 f1, w41, 0xffff0000; cvt.rn.f16x2.f32 w41, f1, f0; shl.b32 f0, w42, 16; and.b32 f1, w42, 0xffff0000; cvt.rn.f16x2.f32 w42, f1, f0; shl.b32 f0, w43, 16; and.b32 f1, w43, 0xffff0000; cvt.rn.f16x2.f32 w43, f1, f0;\n"
        "stmatrix.sync.aligned.m8n8.x4.trans.shared.b16 [%4+20480], {w40,w41,w42,w43};\n"
        "fence.proxy.async.shared::cta;\n"
        ASM_SMARK
        "mov.b32 p0, 0; mov.b32 p1, 0; mov.b32 t0, 0; mov.b32 t1, 0; mov.b32 g0, 0; mov.b32 g1, 0; mov.b32 a0, 0; mov.b32 a1, 0; mov.b32 a2, 0; mov.b32 a3, 0; mov.b32 lo0, 0; mov.b32 lo1, 0; mov.b32 hi0, 0; mov.b32 hi1, 0; mov.b32 q0, 0; mov.b32 q1, 0; mov.b32 q2, 0; mov.b32 q3, 0;\n"
        "mov.b32 z16, 0; mov.b32 z17, 0; mov.b32 z18, 0; mov.b32 z19, 0; mov.b32 z20, 0; mov.b32 z21, 0; mov.b32 z22, 0; mov.b32 z23, 0; mov.b32 z24, 0; mov.b32 z25, 0; mov.b32 z26, 0; mov.b32 z27, 0; mov.b32 z28, 0; mov.b32 z29, 0; mov.b32 z30, 0; mov.b32 z31, 0;\n"
        "mov.f32 %0, 0f00000000; mov.f32 %1, 0f00000000; mov.f32 %2, 0f00000000; mov.f32 %3, 0f00000000;\n"
        "mov.u32 n, 0; mov.u32 so, 0; mov.u32 sp, 0; mov.u32 ph, 0; mov.b64 gp, %8; mov.b64 wd, {%6, 0x40000040};\n"
        "shr.u32 tt, so, 4; cvt.u64.u32 ds5, tt; add.s64 ds0, ds5, %20; add.s64 ds4, ds5, %21;\n"
        "add.s64 ds1, ds0, 2; add.s64 ds2, ds0, 4; add.s64 ds3, ds0, 6; add.s64 ds5, ds4, 2;\n"
        "mbarrier.try_wait.parity.shared::cta.b64 pw, [so+174984], ph;\n"
        "@!pw bra.uni SPIN0;\n"
        "BACK0:\n"
        ASM_TS
        "wgmma.fence.sync.aligned;\n"
        "wgmma.mma_async.sync.aligned.m64n64k16.f16.f16.f16 {z0,z1,z2,z3,z4,z5,z6,z7,z8,z9,z10,z11,z12,z13,z14,z15}, {w0,w1,w2,w3}, ds0, pf, 1, 1, 0;\n"
        "wgmma.mma_async.sync.aligned.m64n64k16.f16.f16.f16 {z0,z1,z2,z3,z4,z5,z6,z7,z8,z9,z10,z11,z12,z13,z14,z15}, {w4,w5,w6,w7}, ds1, pt, 1, 1, 0;\n"
        "wgmma.mma_async.sync.aligned.m64n64k16.f16.f16.f16 {z0,z1,z2,z3,z4,z5,z6,z7,z8,z9,z10,z11,z12,z13,z14,z15}, {w8,w9,w10,w11}, ds2, pt, 1, 1, 0;\n"
        "wgmma.mma_async.sync.aligned.m64n64k16.f16.f16.f16 {z0,z1,z2,z3,z4,z5,z6,z7,z8,z9,z10,z11,z12,z13,z14,z15}, {w12,w13,w14,w15}, ds3, pt, 1, 1, 0;\n"
        "wgmma.mma_async.sync.aligned.m64n64k16.f16.f16.f16 {z0,z1,z2,z3,z4,z5,z6,z7,z8,z9,z10,z11,z12,z13,z14,z15}, {w16,w17,w18,w19}, ds4, pt, 1, 1, 0;\n"
        "wgmma.mma_async.sync.aligned.m64n64k16.f16.f16.f16 {z0,z1,z2,z3,z4,z5,z6,z7,z8,z9,z10,z11,z12,z13,z14,z15}, {w20,w21,w22,w23}, ds5, pt, 1, 1, 0;\n"
        "wgmma.commit_group.sync.aligned;\n"
        "setp.eq.u32 pr, so, %7;\n"
        "@pr bra.uni DUTY;\n"
        "TOP:\n"
        ASM_TRC("n", 0)
        "wgmma.wait_group.sync.aligned 0;\n"
        "mov.b32 {xl, xh}, a2; tanh.approx.f16 xr, xh; cvt.u32.u16 hi0, xr; mul.rn.f16x2 a3, z31, p0; fma.rn.f16x2 p0, z0, z0, c; fma.rn.f16x2 q3, g0, g0, q3; fma.rn.f16x2 g0, z28, t0, z28; prmt.b32 t0, lo1, hi1, 0x5410; mov.b32 {xl, xh}, a2; tanh.approx.f16 xr, xl; cvt.u32.u16 lo0, xr;\n"
        "B31:\n"
        "mov.b32 {xl, xh}, a3; tanh.approx.f16 xr, xh; cvt.u32.u16 hi1, xr; mul.rn.f16x2 a0, z0, p0; fma.rn.f16x2 p0, z1, z1, c; fma.rn.f16x2 q2, g0, g0, q2; fma.rn.f16x2 g0, z29, t0, z29; prmt.b32 t0, lo0, hi0, 0x5410; mov.b32 {xl, xh}, a3; tanh.approx.f16 xr, xl; cvt.u32.u16 lo1, xr;\n"
        "B0:\n"
        "mov.b32 {xl, xh}, a0; tanh.approx.f16 xr, xh; cvt.u32.u16 hi0, xr; mul.rn.f16x2 a1, z1, p0; fma.rn.f16x2 p0, z2, z2, c; fma.rn.f16x2 q3, g0, g0, q3; fma.rn.f16x2 g0, z30, t0, z30; prmt.b32 t0, lo1, hi1, 0x5410; mov.b32 {xl, xh}, a0; tanh.approx.f16 xr, xl; cvt.u32.u16 lo0, xr;\n"
        "B1:\n"
        "mov.b32 {xl, xh}, a1; tanh.approx.f16 xr, xh; cvt.u32.u16 hi1, xr; mul.rn.f16x2 a2, z2, p0; fma.rn.f16x2 p0, z3, z3, c; fma.rn.f16x2 q2, g0, g0, q2; fma.rn.f16x2 g0, z31, t0, z31; prmt.b32 t0, lo0, hi0, 0x5410; mov.b32 {xl, xh}, a1; tanh.approx.f16 xr, xl; cvt.u32.u16 lo1, xr;\n"
        "B2:\n"
        "wgmma.fence.sync.aligned;\n"
        "wgmma.mma_async.sync.aligned.m64n64k16.f16.f16.f16 {z16,z17,z18,z19,z20,z21,z22,z23,z24,z25,z26,z27,z28,z29,z30,z31}, {w24,w25,w26,w27}, ds0, pf, 1, 1, 0;\n"
        "wgmma.mma_async.sync.aligned.m64n64k16.f16.f16.f16 {z16,z17,z18,z19,z20,z21,z22,z23,z24,z25,z26,z27,z28,z29,z30,z31}, {w28,w29,w30,w31}, ds1, pt, 1, 1, 0;\n"
        "wgmma.mma_async.sync.aligned.m64n64k16.f16.f16.f16 {z16,z17,z18,z19,z20,z21,z22,z23,z24,z25,z26,z27,z28,z29,z30,z31}, {w32,w33,w34,w35}, ds2, pt, 1, 1, 0;\n"
        "mov.b32 {xl, xh}, a2; tanh.approx.f16 xr, xh; cvt.u32.u16 hi0, xr; mul.rn.f16x2 a3, z3, p0; fma.rn.f16x2 p0, z4, z4, c; fma.rn.f16x2 q3, g0, g0, q3; fma.rn.f16x2 g0, z0, t0, z0; prmt.b32 t0, lo1, hi1, 0x5410; mov.b32 {xl, xh}, a2; tanh.approx.f16 xr, xl; cvt.u32.u16 lo0, xr;\n"
        "B3:\n"
        "mov.b32 {xl, xh}, a3; tanh.approx.f16 xr, xh; cvt.u32.u16 hi1, xr; mul.rn.f16x2 a0, z4, p0; fma.rn.f16x2 p0, z5, z5, c; fma.rn.f16x2 q0, g0, g0, q0; fma.rn.f16x2 g0, z1, t0, z1; prmt.b32 t0, lo0, hi0, 0x5410; mov.b32 {xl, xh}, a3; tanh.approx.f16 xr, xl; cvt.u32.u16 lo1, xr;\n"
        "B4:\n"
        "mov.b32 {xl, xh}, a0; tanh.approx.f16 xr, xh; cvt.u32.u16 hi0, xr; mul.rn.f16x2 a1, z5, p0; fma.rn.f16x2 p0, z6, z6, c; fma.rn.f16x2 q1, g0, g0, q1; fma.rn.f16x2 g0, z2, t0, z2; prmt.b32 t0, lo1, hi1, 0x5410; mov.b32 {xl, xh}, a0; tanh.approx.f16 xr, xl; cvt.u32.u16 lo0, xr;\n"
        "B5:\n"
        "wgmma.mma_async.sync.aligned.m64n64k16.f16.f16.f16 {z16,z17,z18,z19,z20,z21,z22,z23,z24,z25,z26,z27,z28,z29,z30,z31}, {w36,w37,w38,w39}, ds3, pt, 1, 1, 0;\n"
        "wgmma.mma_async.sync.aligned.m64n64k16.f16.f16.f16 {z16,z17,z18,z19,z20,z21,z22,z23,z24,z25,z26,z27,z28,z29,z30,z31}, {w40,w41,w42,w43}, ds4, pt, 1, 1, 0;\n"
        "wgmma.mma_async.sync.aligned.m64n64k16.f16.f16.f16 {z16,z17,z18,z19,z20,z21,z22,z23,z24,z25,z26,z27,z28,z29,z30,z31}, wd, ds5, pt, 1, 1, 1, 0;\n"
        "wgmma.commit_group.sync.aligned;\n"
        "mov.b32 {xl, xh}, a1; tanh.approx.f16 xr, xh; cvt.u32.u16 hi1, xr; mul.rn.f16x2 a2, z6, p0; fma.rn.f16x2 p0, z7, z7, c; fma.rn.f16x2 q0, g0, g0, q0; fma.rn.f16x2 g0, z3, t0, z3; prmt.b32 t0, lo0, hi0, 0x5410; mov.b32 {xl, xh}, a1; tanh.approx.f16 xr, xl; cvt.u32.u16 lo1, xr;\n"
        "B6:\n"
        "mov.u32 sp, so; add.u32 so, so, 26624; setp.eq.u32 pr, so, 79872; selp.u32 so, 0, so, pr; selp.u32 tt, 1, 0, pr; xor.b32 ph, ph, tt;\n"
        "mov.b32 {xl, xh}, a2; tanh.approx.f16 xr, xh; cvt.u32.u16 hi0, xr; mul.rn.f16x2 a3, z7, p0; fma.rn.f16x2 p0, z8, z8, c; fma.rn.f16x2 q1, g0, g0, q1; fma.rn.f16x2 g0, z4, t0, z4; prmt.b32 t0, lo1, hi1, 0x5410; mov.b32 {xl, xh}, a2; tanh.approx.f16 xr, xl; cvt.u32.u16 lo0, xr;\n"
        "B7:\n"
        "shr.u32 tt, so, 4;\n"
        "mov.b64 {dl0, dh0}, ds0; add.u32 dl0, tt, 74816; mov.b64 ds0, {dl0, dh0}; mov.b64 {dl0, dh0}, ds1; add.u32 dl0, tt, 74818; mov.b64 ds1, {dl0, dh0}; mov.b64 {dl0, dh0}, ds2; add.u32 dl0, tt, 74820; mov.b64 ds2, {dl0, dh0}; mov.b64 {dl0, dh0}, ds3; add.u32 dl0, tt, 74822; mov.b64 ds3, {dl0, dh0}; mov.b64 {dl0, dh0}, ds4; add.u32 dl0, tt, 75328; mov.b64 ds4, {dl0, dh0}; mov.b64 {dl0, dh0}, ds5; add.u32 dl0, tt, 75330; mov.b64 ds5, {dl0, dh0};\n"
        "mov.b32 {xl, xh}, a3; tanh.approx.f16 xr, xh; cvt.u32.u16 hi1, xr; mul.rn.f16x2 a0, z8, p0; fma.rn.f16x2 p0, z9, z9, c; fma.rn.f16x2 q0, g0, g0, q0; fma.rn.f16x2 g0, z5, t0, z5; prmt.b32 t0, lo0, hi0, 0x5410; mov.b32 {xl, xh}, a3; tanh.approx.f16 xr, xl; cvt.u32.u16 lo1, xr;\n"
        "B8:\n"
        "mov.b32 {xl, xh}, a0; tanh.approx.f16 xr, xh; cvt.u32.u16 hi0, xr; mul.rn.f16x2 a1, z9, p0; fma.rn.f16x2 p0, z10, z10, c; fma.rn.f16x2 q1, g0, g0, q1; fma.rn.f16x2 g0, z6, t0, z6; prmt.b32 t0, lo1, hi1, 0x5410; mov.b32 {xl, xh}, a0; tanh.approx.f16 xr, xl; cvt.u32.u16 lo0, xr;\n"
        "B9:\n"
        "mov.b32 {xl, xh}, a1; tanh.approx.f16 xr, xh; cvt.u32.u16 hi1, xr; mul.rn.f16x2 a2, z10, p0; fma.rn.f16x2 p0, z11, z11, c; fma.rn.f16x2 q0, g0, g0, q0; fma.rn.f16x2 g0, z7, t0, z7; prmt.b32 t0, lo0, hi0, 0x5410; mov.b32 {xl, xh}, a1; tanh.approx.f16 xr, xl; cvt.u32.u16 lo1, xr;\n"
        "B10:\n"
        "mov.b32 {xl, xh}, a2; tanh.approx.f16 xr, xh; cvt.u32.u16 hi0, xr; mul.rn.f16x2 a3, z11, p0; fma.rn.f16x2 p0, z12, z12, c; fma.rn.f16x2 q1, g0, g0, q1; fma.rn.f16x2 g0, z8, t0, z8; prmt.b32 t0, lo1, hi1, 0x5410; mov.b32 {xl, xh}, a2; tanh.approx.f16 xr, xl; cvt.u32.u16 lo0, xr;\n"
        "B11:\n"
        "mov.b32 {xl, xh}, a3; tanh.approx.f16 xr, xh; cvt.u32.u16 hi1, xr; mul.rn.f16x2 a0, z12, p0; fma.rn.f16x2 p0, z13, z13, c; fma.rn.f16x2 q0, g0, g0, q0; fma.rn.f16x2 g0, z9, t0, z9; prmt.b32 t0, lo0, hi0, 0x5410; mov.b32 {xl, xh}, a3; tanh.approx.f16 xr, xl; cvt.u32.u16 lo1, xr;\n"
        "B12:\n"
        "mov.b32 {xl, xh}, a0; tanh.approx.f16 xr, xh; cvt.u32.u16 hi0, xr; mul.rn.f16x2 a1, z13, p0; fma.rn.f16x2 p0, z14, z14, c; fma.rn.f16x2 q1, g0, g0, q1; fma.rn.f16x2 g0, z10, t0, z10; prmt.b32 t0, lo1, hi1, 0x5410; mov.b32 {xl, xh}, a0; tanh.approx.f16 xr, xl; cvt.u32.u16 lo0, xr;\n"
        "B13:\n"
        "mov.b32 {xl, xh}, a1; tanh.approx.f16 xr, xh; cvt.u32.u16 hi1, xr; mul.rn.f16x2 a2, z14, p0; fma.rn.f16x2 p0, z15, z15, c; fma.rn.f16x2 q0, g0, g0, q0; fma.rn.f16x2 g0, z11, t0, z11; prmt.b32 t0, lo0, hi0, 0x5410; mov.b32 {xl, xh}, a1; tanh.approx.f16 xr, xl; cvt.u32.u16 lo1, xr;\n"
        "B14:\n"
        "wgmma.wait_group.sync.aligned 0;\n"
        "cp.async.bulk.wait_group.read 0;\n"
        "@pl mbarrier.arrive.shared::cta.b64 _, [sp+174992];\n"
        "mov.b32 {xl, xh}, a2; tanh.approx.f16 xr, xh; cvt.u32.u16 hi0, xr; mul.rn.f16x2 a3, z15, p0; fma.rn.f16x2 p0, z16, z16, c; fma.rn.f16x2 q1, g0, g0, q1; fma.rn.f16x2 g0, z12, t0, z12; prmt.b32 t0, lo1, hi1, 0x5410; mov.b32 {xl, xh}, a2; tanh.approx.f16 xr, xl; cvt.u32.u16 lo0, xr;\n"
        "B15:\n"
        "mbarrier.try_wait.parity.shared::cta.b64 pw, [so+174984], ph;\n"
        "mov.b32 {xl, xh}, a3; tanh.approx.f16 xr, xh; cvt.u32.u16 hi1, xr; mul.rn.f16x2 a0, z16, p0; fma.rn.f16x2 p0, z17, z17, c; fma.rn.f16x2 q0, g0, g0, q0; fma.rn.f16x2 g0, z13, t0, z13; prmt.b32 t0, lo0, hi0, 0x5410; mov.b32 {xl, xh}, a3; tanh.approx.f16 xr, xl; cvt.u32.u16 lo1, xr;\n"
        "B16:\n"
        "mov.b32 {xl, xh}, a0; tanh.approx.f16 xr, xh; cvt.u32.u16 hi0, xr; mul.rn.f16x2 a1, z17, p0; fma.rn.f16x2 p0, z18, z18, c; fma.rn.f16x2 q1, g0, g0, q1; fma.rn.f16x2 g0, z14, t0, z14; prmt.b32 t0, lo1, hi1, 0x5410; mov.b32 {xl, xh}, a0; tanh.approx.f16 xr, xl; cvt.u32.u16 lo0, xr;\n"
        "B17:\n"
        "mov.b32 {xl, xh}, a1; tanh.approx.f16 xr, xh; cvt.u32.u16 hi1, xr; mul.rn.f16x2 a2, z18, p0; fma.rn.f16x2 p0, z19, z19, c; fma.rn.f16x2 q0, g0, g0, q0; fma.rn.f16x2 g0, z15, t0, z15; prmt.b32 t0, lo0, hi0, 0x5410; mov.b32 {xl, xh}, a1; tanh.approx.f16 xr, xl; cvt.u32.u16 lo1, xr;\n"
        "B18:\n"
        "@!pw bra.uni SPIN;\n"
        "BACK:\n"
        "wgmma.fence.sync.aligned;\n"
        "wgmma.mma_async.sync.aligned.m64n64k16.f16.f16.f16 {z0,z1,z2,z3,z4,z5,z6,z7,z8,z9,z10,z11,z12,z13,z14,z15}, {w0,w1,w2,w3}, ds0, pf, 1, 1, 0;\n"
        "wgmma.mma_async.sync.aligned.m64n64k16.f16.f16.f16 {z0,z1,z2,z3,z4,z5,z6,z7,z8,z9,z10,z11,z12,z13,z14,z15}, {w4,w5,w6,w7}, ds1, pt, 1, 1, 0;\n"
        "wgmma.mma_async.sync.aligned.m64n64k16.f16.f16.f16 {z0,z1,z2,z3,z4,z5,z6,z7,z8,z9,z10,z11,z12,z13,z14,z15}, {w8,w9,w10,w11}, ds2, pt, 1, 1, 0;\n"
        "mov.b32 {xl, xh}, a2; tanh.approx.f16 xr, xh; cvt.u32.u16 hi0, xr; mul.rn.f16x2 a3, z19, p0; fma.rn.f16x2 p0, z20, z20, c; fma.rn.f16x2 q1, g0, g0, q1; fma.rn.f16x2 g0, z16, t0, z16; prmt.b32 t0, lo1, hi1, 0x5410; mov.b32 {xl, xh}, a2; tanh.approx.f16 xr, xl; cvt.u32.u16 lo0, xr;\n"
        "B19:\n"
        "mov.b32 {xl, xh}, a3; tanh.approx.f16 xr, xh; cvt.u32.u16 hi1, xr; mul.rn.f16x2 a0, z20, p0; fma.rn.f16x2 p0, z21, z21, c; fma.rn.f16x2 q2, g0, g0, q2; fma.rn.f16x2 g0, z17, t0, z17; prmt.b32 t0, lo0, hi0, 0x5410; mov.b32 {xl, xh}, a3; tanh.approx.f16 xr, xl; cvt.u32.u16 lo1, xr;\n"
        "B20:\n"
        "mov.b32 {xl, xh}, a0; tanh.approx.f16 xr, xh; cvt.u32.u16 hi0, xr; mul.rn.f16x2 a1, z21, p0; fma.rn.f16x2 p0, z22, z22, c; fma.rn.f16x2 q3, g0, g0, q3; fma.rn.f16x2 g0, z18, t0, z18; prmt.b32 t0, lo1, hi1, 0x5410; mov.b32 {xl, xh}, a0; tanh.approx.f16 xr, xl; cvt.u32.u16 lo0, xr;\n"
        "B21:\n"
        "wgmma.mma_async.sync.aligned.m64n64k16.f16.f16.f16 {z0,z1,z2,z3,z4,z5,z6,z7,z8,z9,z10,z11,z12,z13,z14,z15}, {w12,w13,w14,w15}, ds3, pt, 1, 1, 0;\n"
        "wgmma.mma_async.sync.aligned.m64n64k16.f16.f16.f16 {z0,z1,z2,z3,z4,z5,z6,z7,z8,z9,z10,z11,z12,z13,z14,z15}, {w16,w17,w18,w19}, ds4, pt, 1, 1, 0;\n"
        "wgmma.mma_async.sync.aligned.m64n64k16.f16.f16.f16 {z0,z1,z2,z3,z4,z5,z6,z7,z8,z9,z10,z11,z12,z13,z14,z15}, {w20,w21,w22,w23}, ds5, pt, 1, 1, 0;\n"
        "wgmma.commit_group.sync.aligned;\n"
        "mov.b32 {xl, xh}, a1; tanh.approx.f16 xr, xh; cvt.u32.u16 hi1, xr; mul.rn.f16x2 a2, z22, p0; fma.rn.f16x2 p0, z23, z23, c; fma.rn.f16x2 q2, g0, g0, q2; fma.rn.f16x2 g0, z19, t0, z19; prmt.b32 t0, lo0, hi0, 0x5410; mov.b32 {xl, xh}, a1; tanh.approx.f16 xr, xl; cvt.u32.u16 lo1, xr;\n"
        "B22:\n"
        "mov.b32 {xl, xh}, a2; tanh.approx.f16 xr, xh; cvt.u32.u16 hi0, xr; mul.rn.f16x2 a3, z23, p0; fma.rn.f16x2 p0, z24, z24, c; fma.rn.f16x2 q3, g0, g0, q3; fma.rn.f16x2 g0, z20, t0, z20; prmt.b32 t0, lo1, hi1, 0x5410; mov.b32 {xl, xh}, a2; tanh.approx.f16 xr, xl; cvt.u32.u16 lo0, xr;\n"
        "B23:\n"
        "mov.b32 {xl, xh}, a3; tanh.approx.f16 xr, xh; cvt.u32.u16 hi1, xr; mul.rn.f16x2 a0, z24, p0; fma.rn.f16x2 p0, z25, z25, c; fma.rn.f16x2 q2, g0, g0, q2; fma.rn.f16x2 g0, z21, t0, z21; prmt.b32 t0, lo0, hi0, 0x5410; mov.b32 {xl, xh}, a3; tanh.approx.f16 xr, xl; cvt.u32.u16 lo1, xr;\n"
        "B24:\n"
        "mov.b32 {xl, xh}, a0; tanh.approx.f16 xr, xh; cvt.u32.u16 hi0, xr; mul.rn.f16x2 a1, z25, p0; fma.rn.f16x2 p0, z26, z26, c; fma.rn.f16x2 q3, g0, g0, q3; fma.rn.f16x2 g0, z22, t0, z22; prmt.b32 t0, lo1, hi1, 0x5410; mov.b32 {xl, xh}, a0; tanh.approx.f16 xr, xl; cvt.u32.u16 lo0, xr;\n"
        "B25:\n"
        "mov.b32 {xl, xh}, a1; tanh.approx.f16 xr, xh; cvt.u32.u16 hi1, xr; mul.rn.f16x2 a2, z26, p0; fma.rn.f16x2 p0, z27, z27, c; fma.rn.f16x2 q2, g0, g0, q2; fma.rn.f16x2 g0, z23, t0, z23; prmt.b32 t0, lo0, hi0, 0x5410; mov.b32 {xl, xh}, a1; tanh.approx.f16 xr, xl; cvt.u32.u16 lo1, xr;\n"
        "B26:\n"
        "mov.b32 {xl, xh}, a2; tanh.approx.f16 xr, xh; cvt.u32.u16 hi0, xr; mul.rn.f16x2 a3, z27, p0; fma.rn.f16x2 p0, z28, z28, c; fma.rn.f16x2 q3, g0, g0, q3; fma.rn.f16x2 g0, z24, t0, z24; prmt.b32 t0, lo1, hi1, 0x5410; mov.b32 {xl, xh}, a2; tanh.approx.f16 xr, xl; cvt.u32.u16 lo0, xr;\n"
        "B27:\n"
        "add.u32 n, n, 1; setp.lt.u32 pe, n, 32; setp.ne.and.u32 pe, so, %7, pe;\n"
        "mov.b32 {xl, xh}, a3; tanh.approx.f16 xr, xh; cvt.u32.u16 hi1, xr; mul.rn.f16x2 a0, z28, p0; fma.rn.f16x2 p0, z29, z29, c; fma.rn.f16x2 q2, g0, g0, q2; fma.rn.f16x2 g0, z25, t0, z25; prmt.b32 t0, lo0, hi0, 0x5410; mov.b32 {xl, xh}, a3; tanh.approx.f16 xr, xl; cvt.u32.u16 lo1, xr;\n"
        "B28:\n"
        "mov.b32 {xl, xh}, a0; tanh.approx.f16 xr, xh; cvt.u32.u16 hi0, xr; mul.rn.f16x2 a1, z29, p0; fma.rn.f16x2 p0, z30, z30, c; fma.rn.f16x2 q3, g0, g0, q3; fma.rn.f16x2 g0, z26, t0, z26; prmt.b32 t0, lo1, hi1, 0x5410; mov.b32 {xl, xh}, a0; tanh.approx.f16 xr, xl; cvt.u32.u16 lo0, xr;\n"
        "B29:\n"
        "mov.b32 {xl, xh}, a1; tanh.approx.f16 xr, xh; cvt.u32.u16 hi1, xr; mul.rn.f16x2 a2, z30, p0; fma.rn.f16x2 p0, z31, z31, c; fma.rn.f16x2 q2, g0, g0, q2; fma.rn.f16x2 g0, z27, t0, z27; prmt.b32 t0, lo0, hi0, 0x5410; mov.b32 {xl, xh}, a1; tanh.approx.f16 xr, xl; cvt.u32.u16 lo1, xr;\n"
        "@pe bra.uni TOP;\n"
        "setp.lt.u32 pe, n, 32;\n"
        "@pe bra.uni DUTY;\n"
        "bra.uni DONE;\n"
        "SPIN0: mov.u32 cnt, 0;\n"
        ASM_TRC("n", 1)
        "SPIN0L:\n"
        "mbarrier.try_wait.parity.shared::cta.b64 pw, [so+174984], ph;\n"
        "@pw bra.uni BACK0;\n"
        "add.u32 cnt, cnt, 1; setp.lt.u32 pw, cnt, 0x100000;\n"
        "@pw bra.uni SPIN0L;\n"
        "trap;\n"
        "SPIN: mov.u32 cnt, 0;\n"
        ASM_TRC("n", 1)
        "SPINL:\n"
        "mbarrier.try_wait.parity.shared::cta.b64 pw, [so+174984], ph;\n"
        "@pw bra.uni BACK;\n"
        "add.u32 cnt, cnt, 1; setp.lt.u32 pw, cnt, 0x100000;\n"
        "@pw bra.uni SPINL;\n"
        "trap;\n"
        "DUTY:\n"
        "setp.ge.s32 pr, n, %11;\n"
        "@pr bra.uni FLUSH;\n"
        "setp.ge.u32 pr, %13, 2;\n"
        "@pr bra.uni ROLE2;\n"
        "setp.ge.s32 pr, n, %12; selp.b64 src, %14, gp, pr; add.u32 tt, %7, 174976;\n"
        "elect.sync _|pr, 0xffffffff;\n"
        "@pr mbarrier.arrive.expect_tx.shared::cta.b64 _, [tt], %10;\n"
        "@pr cp.async.bulk.shared::cluster.global.mbarrier::complete_tx::bytes [%9], [src], %10, [tt];\n"
        "bra.uni FLUSH;\n"
        "ROLE2:\n"
        "setp.eq.u32 pr, %13, 3;\n"
        "@pr bra.uni ROLE3;\n"
        "elect.sync _|pr, 0xffffffff;\n"
        "@pr cp.async.bulk.global.shared::cta.bulk_group [gp], [%9], 12288;\n"
        "@pr cp.async.bulk.commit_group;\n"
        "bra.uni FLUSH;\n"
        "ROLE3:\n"
        "setp.ne.s32 pr, n, 8;\n"
        "@pr bra.uni AHEAD;\n"
        "mov.u32 tt, 230872;\n"
        "elect.sync _|pr, 0xffffffff;\n"
        "@pr mbarrier.arrive.expect_tx.shared::cta.b64 _, [tt], 75264;\n"
        "mov.u32 cnt, 229248; @pr cp.async.bulk.shared::cluster.global.mbarrier::complete_tx::bytes [cnt], [%18], 768, [tt];\n"
        "mov.u32 cnt, 230016; @pr cp.async.bulk.shared::cluster.global.mbarrier::complete_tx::bytes [cnt], [%19], 768, [tt];\n"
        "mov.u32 cnt, 74752; @pr cp.async.bulk.tensor.2d.shared::cluster.global.mbarrier::complete_tx::bytes [cnt], [%17, {0, 0}], [tt];\n"
        "mov.u32 cnt, 87040; @pr cp.async.bulk.tensor.2d.shared::cluster.global.mbarrier::complete_tx::bytes [cnt], [%17, {0, 192}], [tt];\n"
        "mov.u32 cnt, 99328; @pr cp.async.bulk.tensor.2d.shared::cluster.global.mbarrier::complete_tx::bytes [cnt], [%17, {32, 0}], [tt];\n"
        "mov.u32 cnt, 111616; @pr cp.async.bulk.tensor.2d.shared::cluster.global.mbarrier::complete_tx::bytes [cnt], [%17, {32, 192}], [tt];\n"
        "mov.u32 cnt, 123904; @pr cp.async.bulk.tensor.2d.shared::cluster.global.mbarrier::complete_tx::bytes [cnt], [%17, {64, 0}], [tt];\n"
        "mov.u32 cnt, 136192; @pr cp.async.bulk.tensor.2d.shared::cluster.global.mbarrier::complete_tx::bytes [cnt], [%17, {64, 192}], [tt];\n"
        "AHEAD:\n"
        "elect.sync _|pr, 0xffffffff;\n"
        "@pr cp.async.bulk.prefetch.L2.global [gp], 12288;\n"
        "FLUSH:\n"
        "add.s64 gp, gp, %16;\n"
        "mov.b32 {xl, xh}, q0; cvt.f32.f16 f0, xl; cvt.f32.f16 f1, xh; add.f32 f0, f0, f1; add.f32 %0, %0, f0; mov.b32 q0, 0;\n"
        "mov.b32 {xl, xh}, q1; cvt.f32.f16 f0, xl; cvt.f32.f16 f1, xh; add.f32 f0, f0, f1; add.f32 %1, %1, f0; mov.b32 q1, 0;\n"
        "mov.b32 {xl, xh}, q2; cvt.f32.f16 f0, xl; cvt.f32.f16 f1, xh; add.f32 f0, f0, f1; add.f32 %2, %2, f0; mov.b32 q2, 0;\n"
        "mov.b32 {xl, xh}, q3; cvt.f32.f16 f0, xl; cvt.f32.f16 f1, xh; add.f32 f0, f0, f1; add.f32 %3, %3, f0; mov.b32 q3, 0;\n"
        "setp.ne.u32 pr, %5, 0;\n"
        "@pr bra.uni TOP;\n"
        "wgmma.wait_group.sync.aligned 0;\n"
        "wgmma.fence.sync.aligned;\n"
        "setp.eq.u32 pr, n, 1000; @pr bra.uni B31;\n"
        "setp.eq.u32 pr, n, 1001; @pr bra.uni B0;\n"
        "setp.eq.u32 pr, n, 1002; @pr bra.uni B1;\n"
        "setp.eq.u32 pr, n, 1003; @pr bra.uni B2;\n"
        "setp.eq.u32 pr, n, 1004; @pr bra.uni B3;\n"
        "setp.eq.u32 pr, n, 1005; @pr bra.uni B4;\n"
        "setp.eq.u32 pr, n, 1006; @pr bra.uni B5;\n"
        "setp.eq.u32 pr, n, 1007; @pr bra.uni B6;\n"
        "setp.eq.u32 pr, n, 1008; @pr bra.uni B7;\n"
        "setp.eq.u32 pr, n, 1009; @pr bra.uni B8;\n"
        "setp.eq.u32 pr, n, 1010; @pr bra.uni B9;\n"
        "setp.eq.u32 pr, n, 1011; @pr bra.uni B10;\n"
        "setp.eq.u32 pr, n, 1012; @pr bra.uni B11;\n"
        "setp.eq.u32 pr, n, 1013; @pr bra.uni B12;\n"
        "setp.eq.u32 pr, n, 1014; @pr bra.uni B13;\n"
        "setp.eq.u32 pr, n, 1015; @pr bra.uni B14;\n"
        "setp.eq.u32 pr, n, 1016; @pr bra.uni B15;\n"
        "setp.eq.u32 pr, n, 1017; @pr bra.uni B16;\n"
        "setp.eq.u32 pr, n, 1018; @pr bra.uni B17;\n"
        "setp.eq.u32 pr, n, 1019; @pr bra.uni B18;\n"
        "setp.eq.u32 pr, n, 1020; @pr bra.uni B19;\n"
        "setp.eq.u32 pr, n, 1021; @pr bra.uni B20;\n"
        "setp.eq.u32 pr, n, 1022; @pr bra.uni B21;\n"
        "setp.eq.u32 pr, n, 1023; @pr bra.uni B22;\n"
        "setp.eq.u32 pr, n, 1024; @pr bra.uni B23;\n"
        "setp.eq.u32 pr, n, 1025; @pr bra.uni B24;\n"
        "setp.eq.u32 pr, n, 1026; @pr bra.uni B25;\n"
        "setp.eq.u32 pr, n, 1027; @pr bra.uni B26;\n"
        "setp.eq.u32 pr, n, 1028; @pr bra.uni B27;\n"
        "setp.eq.u32 pr, n, 1029; @pr bra.uni B28;\n"
        "setp.eq.u32 pr, n, 1030; @pr bra.uni B29;\n"
        "trap;\n"
        "DONE:\n"
        ASM_TRC("n", 0)
        "mov.b32 {xl, xh}, a2; tanh.approx.f16 xr, xh; cvt.u32.u16 hi0, xr; mul.rn.f16x2 a3, z31, p0; fma.rn.f16x2 q3, g0, g0, q3; fma.rn.f16x2 g0, z28, t0, z28; prmt.b32 t0, lo1, hi1, 0x5410; mov.b32 {xl, xh}, a2; tanh.approx.f16 xr, xl; cvt.u32.u16 lo0, xr;\n"
        "mov.b32 {xl, xh}, a3; tanh.approx.f16 xr, xh; cvt.u32.u16 hi1, xr; fma.rn.f16x2 q2, g0, g0, q2; fma.rn.f16x2 g0, z29, t0, z29; prmt.b32 t0, lo0, hi0, 0x5410; mov.b32 {xl, xh}, a3; tanh.approx.f16 xr, xl; cvt.u32.u16 lo1, xr;\n"
        "fma.rn.f16x2 q3, g0, g0, q3; fma.rn.f16x2 g0, z30, t0, z30; prmt.b32 t0, lo1, hi1, 0x5410;\n"
        "fma.rn.f16x2 q2, g0, g0, q2; fma.rn.f16x2 g0, z31, t0, z31;\n"
        "fma.rn.f16x2 q3, g0, g0, q3;\n"
        "mov.b32 {xl, xh}, q0; cvt.f32.f16 f0, xl; cvt.f32.f16 f1, xh; add.f32 f0, f0, f1; add.f32 %0, %0, f0; mov.b32 q0, 0;\n"
        "mov.b32 {xl, xh}, q1; cvt.f32.f16 f0, xl; cvt.f32.f16 f1, xh; add.f32 f0, f0, f1; add.f32 %1, %1, f0; mov.b32 q1, 0;\n"
        "mov.b32 {xl, xh}, q2; cvt.f32.f16 f0, xl; cvt.f32.f16 f1, xh; add.f32 f0, f0, f1; add.f32 %2, %2, f0; mov.b32 q2, 0;\n"
        "mov.b32 {xl, xh}, q3; cvt.f32.f16 f0, xl; cvt.f32.f16 f1, xh; add.f32 f0, f0, f1; add.f32 %3, %3, f0; mov.b32 q3, 0;\n"
        "wgmma.wait_group.sync.aligned 0;\n"
        "}\n"
        : "=f"(acc[0][0]), "=f"(acc[0][1]), "=f"(acc[1][0]), "=f"(acc[1][1])
        : "r"(w1t), "r"(yd), "r"(wd), "r"(own_slot), "l"(d.g), "r"(d.s), "r"(d.bytes), "r"(d.end), "r"(d.zero), "r"(role),
          "l"(d.zeros), "r"(lane), "l"(d.step), "l"(&prm.w2_map), "l"(prm.gamma), "l"(prm.beta), "l"(prm.ydesc64[0]), "l"(prm.ydesc64[1])
        : "memory");
}
template <int M, bool LAST_SMEM = true>
__device__ __forceinline__ void gemm1_t(uint32_t (&d)[16], const uint32_t* wa, uint32_t yd, uint32_t wd) {
    wg_fence();
    wgmma_n64_h_set<0>(d, wa, desc<1024, 1>(yd, 0));
#pragma unroll
    for (int kk = 1; kk < (LAST_SMEM ? 5 : 6); kk++)
        wgmma_n64_h_acc<0>(d, wa + kk * 4, kk < 4 ? desc<1024, 1>(yd, kk * 32) : desc<512, 2>(yd, 8192 + (kk - 4) * 32));
    if (LAST_SMEM) wgmma_n64_h_acc_ss(d, desc<1024, 1>(wd, M * 12288), desc<512, 2>(yd, 8192 + 32));
    wg_commit();
}

#define GTAIL 0
__device__ __forceinline__ void gelu_sumsq_h(uint32_t (&d)[16], uint32_t (&q)[2], uint32_t key) {
#pragma unroll
    for (int r = 0; r < 16; r++) {
        if (GTAIL && r == 16 - GTAIL) sched_fence<GTAIL ? GTAIL : 2>(d + r, key);
        const uint32_t gv = gelu2(d[r]);
        q[r & 1] = h2_fma(gv, gv, q[r & 1]);
    }
}
__device__ __forceinline__ void flush_sumsq(uint32_t (&q)[2], float (&acc)[2]) {
#pragma unroll
    for (int h = 0; h < 2; h++) {
        float lo, hi;
        h2_unpack(q[h], lo, hi);
        acc[h] += lo + hi;
        q[h] = 0;
    }
}
__device__ __forceinline__ void gelu_sumsq_f(const uint32_t (&d)[16], float (&acc)[2]) {
#pragma unroll
    for (int r = 0; r < 16; r++) {
        float lo, hi;
        h2_unpack(gelu2(d[r]), lo, hi);
        acc[r & 1] = fmaf(lo, lo, acc[r & 1]);
        acc[r & 1] = fmaf(hi, hi, acc[r & 1]);
    }
}
__device__ __forceinline__ void load_w1t(uint32_t (&wa)[2][24], int wg, int w, int lane) {
#pragma unroll
    for (int m = 0; m < 2; m++)
#pragma unroll
        for (int kk = 0; kk < 5; kk++) {
            const int q = lane >> 3, c = 16 * kk + 8 * (q >> 1) + (lane & 7), ck = 2 * w + (q & 1);
            ldsm4_t(wa[m] + kk * 4, sb + SM_W1 + (2 * wg + m) * 12288 + c * 128 + ((ck ^ (c & 7)) * 16));
        }
}
__device__ __forceinline__ unsigned long long* acc_word(const Params& prm, uint32_t epoch, uint32_t e) {
    return &prm.g->acc[epoch & 1][(e >> 2) * 32 + (e & 3)];
}
__device__ __forceinline__ void publish_fast(const Params& prm, const float (&acc)[2][2], uint32_t epoch, int wg, int w, int lane) {
    const bool m = lane & 2, h = lane & 1;
    const float a = (m ? acc[1][0] : acc[0][0]) + __shfl_xor_sync(0xffffffffu, m ? acc[0][0] : acc[1][0], 2);
    const float b = (m ? acc[1][1] : acc[0][1]) + __shfl_xor_sync(0xffffffffu, m ? acc[0][1] : acc[1][1], 2);
    const float v = (h ? b : a) + __shfl_xor_sync(0xffffffffu, h ? a : b, 1);
    const unsigned long long q = (__float2ull_rn(fminf(v, ACC_LIMIT) * 0x1p16f) << 8) + 1;
    asm volatile("red.relaxed.gpu.global.add.u64 [%0], %1;"
                 ::"l"(acc_word(prm, epoch, 128 * wg + 32 * (lane & 2) + 16 * w + (lane >> 2) + 8 * (lane & 1))), "l"(q) : "memory");
}
__device__ __forceinline__ float collect_fast(const unsigned long long* word) {
    unsigned long long v;
    asm volatile(
        "{\n.reg .pred p;\n.reg .u32 n, lo, hi;\nmov.u32 n, 0;\n"
        "POLL:\nld.relaxed.gpu.global.u64 %0, [%1];\nmov.b64 {lo, hi}, %0;\nand.b32 lo, lo, 255;\n"
        "setp.eq.u32 p, lo, %2;\nvote.sync.all.pred p, p, 0xffffffff;\n@p bra.uni POLL_DONE;\n"
        "add.u32 n, n, 1;\nsetp.lt.u32 p, n, 0x400000;\n@p bra.uni POLL;\ntrap;\nPOLL_DONE:\n}\n"
        : "=l"(v) : "l"(word), "n"(NUM_CTAS) : "memory");
    return __ull2float_rn(v >> 8) * 0x1p-16f;
}
__device__ __forceinline__ void publish_sums(const float (&acc)[2][2], float* sums, unsigned int* counter, int wg, int w, int lane) {
#pragma unroll
    for (int m = 0; m < 2; m++)
#pragma unroll
        for (int h = 0; h < 2; h++) {
            const float v = quad_sum(acc[m][h]);
            if ((lane & 3) == 0) atomicAdd(sums + 64 * (2 * wg + m) + 16 * w + (lane >> 2) + 8 * h, v);
        }
    named_sync(1, 384);
    if (fresh_tid() == 0) asm volatile("red.release.gpu.global.add.u32 [%0], 1;" ::"l"(counter) : "memory");
}
__device__ __forceinline__ void grid_wait(const unsigned int* counter, unsigned int target) {
    if (fresh_tid() == 0) {
        unsigned int v, spins = 0;
        do {
            asm volatile("ld.acquire.gpu.global.u32 %0, [%1];" : "=r"(v) : "l"(counter) : "memory");
            if (++spins > (1u << 22)) __trap();
        } while ((int)(v - target) < 0);
    }
    __syncthreads();
}

struct Pass2 {
    uint32_t wg;
    uint32_t off;
    int step;
    uint32_t xs;
    uint32_t a_offs, xs_offs, bias_addr, out_scale;
    uint32_t w;
};

static_assert(sb + SM_BAR + BAR_Y2FULL * 8 == 230800 && sb + SM_BAR + BAR_XSFULL * 8 == 230832, "layout");
__device__ __forceinline__ void first_gemm(uint32_t tile, uint32_t offs, uint32_t w1d) {
    asm volatile(
        "{\n"
        ".reg .b32 t<2>, ad;\n"
        ".reg .b64 w1d, dt;\n"
        ".reg .pred pt, pf;\n"
        "setp.ne.b32 pt, 1, 0; setp.ne.b32 pf, 0, 0; mov.b64 w1d, {%2, 0x40000040};\n"
        "and.b32 t0, %1, 0xffff; shr.u32 t1, %1, 16;\n"
        "xor.b32 ad, t0, 0; add.u32 ad, ad, %0; ldmatrix.sync.aligned.m8n8.x4.shared.b16 {qa0,qa1,qa2,qa3}, [ad];\n"
        "xor.b32 ad, t0, 32; add.u32 ad, ad, %0; ldmatrix.sync.aligned.m8n8.x4.shared.b16 {qa4,qa5,qa6,qa7}, [ad];\n"
        "xor.b32 ad, t0, 64; add.u32 ad, ad, %0; ldmatrix.sync.aligned.m8n8.x4.shared.b16 {qa8,qa9,qa10,qa11}, [ad];\n"
        "xor.b32 ad, t0, 96; add.u32 ad, ad, %0; ldmatrix.sync.aligned.m8n8.x4.shared.b16 {qa12,qa13,qa14,qa15}, [ad];\n"
        "xor.b32 ad, t1, 0; add.u32 ad, ad, %0; ldmatrix.sync.aligned.m8n8.x4.shared.b16 {qa16,qa17,qa18,qa19}, [ad];\n"
        "xor.b32 ad, t1, 32; add.u32 ad, ad, %0; ldmatrix.sync.aligned.m8n8.x4.shared.b16 {qa20,qa21,qa22,qa23}, [ad];\n"
        "wgmma.fence.sync.aligned;\n"
        "add.s64 dt, w1d, 0; wgmma.mma_async.sync.aligned.m64n64k16.f16.f16.f16 {qz0,qz1,qz2,qz3,qz4,qz5,qz6,qz7,qz8,qz9,qz10,qz11,qz12,qz13,qz14,qz15}, {qa0,qa1,qa2,qa3}, dt, pf, 1, 1, 1;\n"
        "add.s64 dt, w1d, 128; wgmma.mma_async.sync.aligned.m64n64k16.f16.f16.f16 {qz0,qz1,qz2,qz3,qz4,qz5,qz6,qz7,qz8,qz9,qz10,qz11,qz12,qz13,qz14,qz15}, {qa4,qa5,qa6,qa7}, dt, pt, 1, 1, 1;\n"
        "add.s64 dt, w1d, 256; wgmma.mma_async.sync.aligned.m64n64k16.f16.f16.f16 {qz0,qz1,qz2,qz3,qz4,qz5,qz6,qz7,qz8,qz9,qz10,qz11,qz12,qz13,qz14,qz15}, {qa8,qa9,qa10,qa11}, dt, pt, 1, 1, 1;\n"
        "add.s64 dt, w1d, 384; wgmma.mma_async.sync.aligned.m64n64k16.f16.f16.f16 {qz0,qz1,qz2,qz3,qz4,qz5,qz6,qz7,qz8,qz9,qz10,qz11,qz12,qz13,qz14,qz15}, {qa12,qa13,qa14,qa15}, dt, pt, 1, 1, 1;\n"
        "add.s64 dt, w1d, 512; wgmma.mma_async.sync.aligned.m64n64k16.f16.f16.f16 {qz0,qz1,qz2,qz3,qz4,qz5,qz6,qz7,qz8,qz9,qz10,qz11,qz12,qz13,qz14,qz15}, {qa16,qa17,qa18,qa19}, dt, pt, 1, 1, 1;\n"
        "add.s64 dt, w1d, 640; wgmma.mma_async.sync.aligned.m64n64k16.f16.f16.f16 {qz0,qz1,qz2,qz3,qz4,qz5,qz6,qz7,qz8,qz9,qz10,qz11,qz12,qz13,qz14,qz15}, {qa20,qa21,qa22,qa23}, dt, pt, 1, 1, 1;\n"
        "wgmma.commit_group.sync.aligned;\n"
        "}\n"
        :: "r"(tile), "r"(offs), "r"(w1d) : "memory");
}
__device__ __forceinline__ void pass2_tiles(const Pass2& c, const Params& prm) {
    asm volatile(
        "{\n"
        ".reg .b32 o<24>, g<16>, p<2>, a<2>, lo<2>, hi<2>, h<2>, v<8>, n, off, c, tt, ad, cnt, ybar, xbar, tbar, tpar, id;\n"
        ".reg .b16 xl, xh, xr;\n"
        ".reg .f32 f0, f1;\n"
        ".reg .b64 w1d, w2d, dt, gp, pol;\n"
        ".reg .pred pt, pf, pr, pw, pl, pk, pm, pz, pn;\n"
        "setp.ne.b32 pt, 1, 0; setp.ne.b32 pf, 0, 0; setp.eq.u32 pl, %9, 0; setp.eq.u32 pk, %9, 0; setp.eq.u32 pz, %0, 0;\n"
        "mov.b32 c, 0x40D940D9;\n"
        "mov.b64 w1d, {%0, 0x40000040}; mov.b64 w2d, {%1, 0x80000020};\n"
        "mad.lo.u32 ybar, %2, 8, 230800; mad.lo.u32 xbar, %2, 8, 230832; add.u32 id, %2, 2;\n"
        "xor.b32 tt, %2, 0; mad.lo.u32 tbar, tt, 64, 230888; setp.eq.u32 pr, tt, 0; selp.u32 tpar, 1, 0, pr; mov.u32 tt, %laneid; setp.eq.u32 pn, tt, 0;\n"
        "mov.u32 n, -1; add.u32 off, %3, %12; mov.pred pm, pt; mov.b64 pol, 0x12F0000000000000;\n"
        "wgmma.wait_group.sync.aligned 0;\n"
        "ld.shared.v4.b32 {o0,o1,o2,o3}, [%7+0];\n"
        "ld.shared.v4.b32 {o4,o5,o6,o7}, [%7+64];\n"
        "ld.shared.v4.b32 {o8,o9,o10,o11}, [%7+128];\n"
        "ld.shared.v4.b32 {o12,o13,o14,o15}, [%7+192];\n"
        "ld.shared.v4.b32 {o16,o17,o18,o19}, [%7+256];\n"
        "ld.shared.v4.b32 {o20,o21,o22,o23}, [%7+320];\n"
        "fma.rn.f16x2 p0, qz0, qz0, c;\n"
        "fma.rn.f16x2 p1, qz1, qz1, c; mul.rn.f16x2 a0, qz0, p0;\n"
        "mov.b32 {xl, xh}, a0; tanh.approx.f16 xr, xl; cvt.u32.u16 lo0, xr; tanh.approx.f16 xr, xh; cvt.u32.u16 hi0, xr; fma.rn.f16x2 p0, qz2, qz2, c; mul.rn.f16x2 a1, qz1, p1;\n"
        "mov.b32 {xl, xh}, a1; tanh.approx.f16 xr, xl; cvt.u32.u16 lo1, xr; tanh.approx.f16 xr, xh; cvt.u32.u16 hi1, xr; fma.rn.f16x2 p1, qz3, qz3, c; mul.rn.f16x2 a0, qz2, p0; prmt.b32 h0, lo0, hi0, 0x5410;\n"
        "mov.b32 {xl, xh}, a0; tanh.approx.f16 xr, xl; cvt.u32.u16 lo0, xr; tanh.approx.f16 xr, xh; cvt.u32.u16 hi0, xr; fma.rn.f16x2 p0, qz4, qz4, c; mul.rn.f16x2 a1, qz3, p1; fma.rn.f16x2 g0, qz0, h0, qz0; prmt.b32 h1, lo1, hi1, 0x5410;\n"
        "mov.b32 {xl, xh}, a1; tanh.approx.f16 xr, xl; cvt.u32.u16 lo1, xr; tanh.approx.f16 xr, xh; cvt.u32.u16 hi1, xr; fma.rn.f16x2 p1, qz5, qz5, c; mul.rn.f16x2 a0, qz4, p0; fma.rn.f16x2 g1, qz1, h1, qz1; prmt.b32 h0, lo0, hi0, 0x5410;\n"
        "mov.b32 {xl, xh}, a0; tanh.approx.f16 xr, xl; cvt.u32.u16 lo0, xr; tanh.approx.f16 xr, xh; cvt.u32.u16 hi0, xr; fma.rn.f16x2 p0, qz6, qz6, c; mul.rn.f16x2 a1, qz5, p1; fma.rn.f16x2 g2, qz2, h0, qz2; prmt.b32 h1, lo1, hi1, 0x5410;\n"
        "mov.b32 {xl, xh}, a1; tanh.approx.f16 xr, xl; cvt.u32.u16 lo1, xr; tanh.approx.f16 xr, xh; cvt.u32.u16 hi1, xr; fma.rn.f16x2 p1, qz7, qz7, c; mul.rn.f16x2 a0, qz6, p0; fma.rn.f16x2 g3, qz3, h1, qz3; prmt.b32 h0, lo0, hi0, 0x5410;\n"
        "mov.b32 v0, 0; mov.b32 v1, 0; mov.b32 v2, 0; mov.b32 v3, 0; mov.b32 v4, 0; mov.b32 v5, 0; mov.b32 v6, 0; mov.b32 v7, 0;\n"
        "LOOP:\n"
        "@!pm bra.uni SKIP0;\n"
        "wgmma.fence.sync.aligned;\n"
        "add.s64 dt, w1d, 768; wgmma.mma_async.sync.aligned.m64n64k16.f16.f16.f16 {qz16,qz17,qz18,qz19,qz20,qz21,qz22,qz23,qz24,qz25,qz26,qz27,qz28,qz29,qz30,qz31}, {qa0,qa1,qa2,qa3}, dt, pf, 1, 1, 1;\n"
        "add.s64 dt, w1d, 896; wgmma.mma_async.sync.aligned.m64n64k16.f16.f16.f16 {qz16,qz17,qz18,qz19,qz20,qz21,qz22,qz23,qz24,qz25,qz26,qz27,qz28,qz29,qz30,qz31}, {qa4,qa5,qa6,qa7}, dt, pt, 1, 1, 1;\n"
        "add.s64 dt, w1d, 1024; wgmma.mma_async.sync.aligned.m64n64k16.f16.f16.f16 {qz16,qz17,qz18,qz19,qz20,qz21,qz22,qz23,qz24,qz25,qz26,qz27,qz28,qz29,qz30,qz31}, {qa8,qa9,qa10,qa11}, dt, pt, 1, 1, 1;\n"
        "add.s64 dt, w1d, 1152; wgmma.mma_async.sync.aligned.m64n64k16.f16.f16.f16 {qz16,qz17,qz18,qz19,qz20,qz21,qz22,qz23,qz24,qz25,qz26,qz27,qz28,qz29,qz30,qz31}, {qa12,qa13,qa14,qa15}, dt, pt, 1, 1, 1;\n"
        "add.s64 dt, w1d, 1280; wgmma.mma_async.sync.aligned.m64n64k16.f16.f16.f16 {qz16,qz17,qz18,qz19,qz20,qz21,qz22,qz23,qz24,qz25,qz26,qz27,qz28,qz29,qz30,qz31}, {qa16,qa17,qa18,qa19}, dt, pt, 1, 1, 1;\n"
        "add.s64 dt, w1d, 1408; wgmma.mma_async.sync.aligned.m64n64k16.f16.f16.f16 {qz16,qz17,qz18,qz19,qz20,qz21,qz22,qz23,qz24,qz25,qz26,qz27,qz28,qz29,qz30,qz31}, {qa20,qa21,qa22,qa23}, dt, pt, 1, 1, 1;\n"
        "SKIP0:\n"
        "wgmma.fence.sync.aligned;\n"
        "wgmma.commit_group.sync.aligned;\n"
        "setp.lt.s32 pr, n, 0;\n"
        "@pr bra.uni FIRST;\n"
        "and.b32 tt, n, 1; mbarrier.try_wait.parity.shared::cta.b64 pw, [xbar], tt;\n"
        "@!pw bra.uni SPINX;\n"
        "BACKX:\n"
        "and.b32 ad, %6, 0xffff; add.u32 ad, ad, %4; ld.shared.v4.b32 {v0,v1,v2,v3}, [ad+0];\n"
        "shr.u32 ad, %6, 16; add.u32 ad, ad, %4; ld.shared.v4.b32 {v4,v5,v6,v7}, [ad+0];\n"
        "mov.b32 {xl, xh}, o0; cvt.f32.f16 f0, xl; cvt.f32.f16 f1, xh; cvt.rn.bf16x2.f32 tt, f1, f0; fma.rn.bf16x2 v0, tt, %8, v0;\n"
        "mov.b32 {xl, xh}, o2; cvt.f32.f16 f0, xl; cvt.f32.f16 f1, xh; cvt.rn.bf16x2.f32 tt, f1, f0; fma.rn.bf16x2 v1, tt, %8, v1;\n"
        "mov.b32 {xl, xh}, o4; cvt.f32.f16 f0, xl; cvt.f32.f16 f1, xh; cvt.rn.bf16x2.f32 tt, f1, f0; fma.rn.bf16x2 v2, tt, %8, v2;\n"
        "mov.b32 {xl, xh}, o6; cvt.f32.f16 f0, xl; cvt.f32.f16 f1, xh; cvt.rn.bf16x2.f32 tt, f1, f0; fma.rn.bf16x2 v3, tt, %8, v3;\n"
        "and.b32 ad, %6, 0xffff; add.u32 ad, ad, %4; st.shared.v4.b32 [ad+0], {v0,v1,v2,v3};\n"
        "and.b32 ad, %6, 0xffff; add.u32 ad, ad, %4; ld.shared.v4.b32 {v0,v1,v2,v3}, [ad+64];\n"
        "mov.b32 {xl, xh}, o1; cvt.f32.f16 f0, xl; cvt.f32.f16 f1, xh; cvt.rn.bf16x2.f32 tt, f1, f0; fma.rn.bf16x2 v4, tt, %8, v4;\n"
        "mov.b32 {xl, xh}, o3; cvt.f32.f16 f0, xl; cvt.f32.f16 f1, xh; cvt.rn.bf16x2.f32 tt, f1, f0; fma.rn.bf16x2 v5, tt, %8, v5;\n"
        "mov.b32 {xl, xh}, o5; cvt.f32.f16 f0, xl; cvt.f32.f16 f1, xh; cvt.rn.bf16x2.f32 tt, f1, f0; fma.rn.bf16x2 v6, tt, %8, v6;\n"
        "mov.b32 {xl, xh}, o7; cvt.f32.f16 f0, xl; cvt.f32.f16 f1, xh; cvt.rn.bf16x2.f32 tt, f1, f0; fma.rn.bf16x2 v7, tt, %8, v7;\n"
        "shr.u32 ad, %6, 16; add.u32 ad, ad, %4; st.shared.v4.b32 [ad+0], {v4,v5,v6,v7};\n"
        "shr.u32 ad, %6, 16; add.u32 ad, ad, %4; ld.shared.v4.b32 {v4,v5,v6,v7}, [ad+64];\n"
        "ld.shared.v4.b32 {o0,o1,o2,o3}, [%7+0];\n"
        "ld.shared.v4.b32 {o4,o5,o6,o7}, [%7+64];\n"
        "mov.b32 {xl, xh}, o8; cvt.f32.f16 f0, xl; cvt.f32.f16 f1, xh; cvt.rn.bf16x2.f32 tt, f1, f0; fma.rn.bf16x2 v0, tt, %8, v0;\n"
        "mov.b32 {xl, xh}, o10; cvt.f32.f16 f0, xl; cvt.f32.f16 f1, xh; cvt.rn.bf16x2.f32 tt, f1, f0; fma.rn.bf16x2 v1, tt, %8, v1;\n"
        "mov.b32 {xl, xh}, o12; cvt.f32.f16 f0, xl; cvt.f32.f16 f1, xh; cvt.rn.bf16x2.f32 tt, f1, f0; fma.rn.bf16x2 v2, tt, %8, v2;\n"
        "mov.b32 {xl, xh}, o14; cvt.f32.f16 f0, xl; cvt.f32.f16 f1, xh; cvt.rn.bf16x2.f32 tt, f1, f0; fma.rn.bf16x2 v3, tt, %8, v3;\n"
        "and.b32 ad, %6, 0xffff; add.u32 ad, ad, %4; st.shared.v4.b32 [ad+64], {v0,v1,v2,v3};\n"
        "and.b32 ad, %6, 0xffff; add.u32 ad, ad, %4; ld.shared.v4.b32 {v0,v1,v2,v3}, [ad+128];\n"
        "mov.b32 {xl, xh}, o9; cvt.f32.f16 f0, xl; cvt.f32.f16 f1, xh; cvt.rn.bf16x2.f32 tt, f1, f0; fma.rn.bf16x2 v4, tt, %8, v4;\n"
        "mov.b32 {xl, xh}, o11; cvt.f32.f16 f0, xl; cvt.f32.f16 f1, xh; cvt.rn.bf16x2.f32 tt, f1, f0; fma.rn.bf16x2 v5, tt, %8, v5;\n"
        "mov.b32 {xl, xh}, o13; cvt.f32.f16 f0, xl; cvt.f32.f16 f1, xh; cvt.rn.bf16x2.f32 tt, f1, f0; fma.rn.bf16x2 v6, tt, %8, v6;\n"
        "mov.b32 {xl, xh}, o15; cvt.f32.f16 f0, xl; cvt.f32.f16 f1, xh; cvt.rn.bf16x2.f32 tt, f1, f0; fma.rn.bf16x2 v7, tt, %8, v7;\n"
        "shr.u32 ad, %6, 16; add.u32 ad, ad, %4; st.shared.v4.b32 [ad+64], {v4,v5,v6,v7};\n"
        "shr.u32 ad, %6, 16; add.u32 ad, ad, %4; ld.shared.v4.b32 {v4,v5,v6,v7}, [ad+128];\n"
        "ld.shared.v4.b32 {o8,o9,o10,o11}, [%7+128];\n"
        "ld.shared.v4.b32 {o12,o13,o14,o15}, [%7+192];\n"
        "mov.b32 {xl, xh}, o16; cvt.f32.f16 f0, xl; cvt.f32.f16 f1, xh; cvt.rn.bf16x2.f32 tt, f1, f0; fma.rn.bf16x2 v0, tt, %8, v0;\n"
        "mov.b32 {xl, xh}, o18; cvt.f32.f16 f0, xl; cvt.f32.f16 f1, xh; cvt.rn.bf16x2.f32 tt, f1, f0; fma.rn.bf16x2 v1, tt, %8, v1;\n"
        "mov.b32 {xl, xh}, o20; cvt.f32.f16 f0, xl; cvt.f32.f16 f1, xh; cvt.rn.bf16x2.f32 tt, f1, f0; fma.rn.bf16x2 v2, tt, %8, v2;\n"
        "mov.b32 {xl, xh}, o22; cvt.f32.f16 f0, xl; cvt.f32.f16 f1, xh; cvt.rn.bf16x2.f32 tt, f1, f0; fma.rn.bf16x2 v3, tt, %8, v3;\n"
        "and.b32 ad, %6, 0xffff; add.u32 ad, ad, %4; st.shared.v4.b32 [ad+128], {v0,v1,v2,v3};\n"
        "mov.b32 {xl, xh}, o17; cvt.f32.f16 f0, xl; cvt.f32.f16 f1, xh; cvt.rn.bf16x2.f32 tt, f1, f0; fma.rn.bf16x2 v4, tt, %8, v4;\n"
        "mov.b32 {xl, xh}, o19; cvt.f32.f16 f0, xl; cvt.f32.f16 f1, xh; cvt.rn.bf16x2.f32 tt, f1, f0; fma.rn.bf16x2 v5, tt, %8, v5;\n"
        "mov.b32 {xl, xh}, o21; cvt.f32.f16 f0, xl; cvt.f32.f16 f1, xh; cvt.rn.bf16x2.f32 tt, f1, f0; fma.rn.bf16x2 v6, tt, %8, v6;\n"
        "mov.b32 {xl, xh}, o23; cvt.f32.f16 f0, xl; cvt.f32.f16 f1, xh; cvt.rn.bf16x2.f32 tt, f1, f0; fma.rn.bf16x2 v7, tt, %8, v7;\n"
        "shr.u32 ad, %6, 16; add.u32 ad, ad, %4; st.shared.v4.b32 [ad+128], {v4,v5,v6,v7};\n"
        "ld.shared.v4.b32 {o16,o17,o18,o19}, [%7+256];\n"
        "ld.shared.v4.b32 {o20,o21,o22,o23}, [%7+320];\n"
        "FIRST:\n"
        "@pz bra.uni B8;\n"
        "mov.b32 {xl, xh}, a0; tanh.approx.f16 xr, xl; cvt.u32.u16 lo0, xr; tanh.approx.f16 xr, xh; cvt.u32.u16 hi0, xr; fma.rn.f16x2 p0, qz8, qz8, c; mul.rn.f16x2 a1, qz7, p1; fma.rn.f16x2 g4, qz4, h0, qz4; prmt.b32 h1, lo1, hi1, 0x5410;\n"
        "mov.b32 {xl, xh}, a1; tanh.approx.f16 xr, xl; cvt.u32.u16 lo1, xr; tanh.approx.f16 xr, xh; cvt.u32.u16 hi1, xr; fma.rn.f16x2 p1, qz9, qz9, c; mul.rn.f16x2 a0, qz8, p0; fma.rn.f16x2 g5, qz5, h1, qz5; prmt.b32 h0, lo0, hi0, 0x5410;\n"
        "B8:\n"
        "fence.proxy.async.shared::cta;\n"
        "add.u32 tt, id, 4;\n"
        "@pl bra.uni STORE;\n"
        "bar.arrive tt, 128;\n"
        "STOREB:\n"
        ASM_MARK
        "@!pm bra.uni DONE;\n"
        "add.s32 n, n, 1; sub.u32 off, off, %12; setp.lt.s32 pm, n, 7;\n"
        "@pz bra.uni B10;\n"
        "mov.b32 {xl, xh}, a0; tanh.approx.f16 xr, xl; cvt.u32.u16 lo0, xr; tanh.approx.f16 xr, xh; cvt.u32.u16 hi0, xr; fma.rn.f16x2 p0, qz10, qz10, c; mul.rn.f16x2 a1, qz9, p1; fma.rn.f16x2 g6, qz6, h0, qz6; prmt.b32 h1, lo1, hi1, 0x5410;\n"
        "mov.b32 {xl, xh}, a1; tanh.approx.f16 xr, xl; cvt.u32.u16 lo1, xr; tanh.approx.f16 xr, xh; cvt.u32.u16 hi1, xr; fma.rn.f16x2 p1, qz11, qz11, c; mul.rn.f16x2 a0, qz10, p0; fma.rn.f16x2 g7, qz7, h1, qz7; prmt.b32 h0, lo0, hi0, 0x5410;\n"
        "B10:\n"
        "wgmma.fence.sync.aligned;\n"
        "add.s64 dt, w2d, 0; wgmma.mma_async.sync.aligned.m64n96k16.f16.f16.f16 {o0,o1,o2,o3,o4,o5,o6,o7,o8,o9,o10,o11,o12,o13,o14,o15,o16,o17,o18,o19,o20,o21,o22,o23}, {g0,g1,g2,g3}, dt, pt, 1, 1, 1;\n"
        "add.s64 dt, w2d, 64; wgmma.mma_async.sync.aligned.m64n96k16.f16.f16.f16 {o0,o1,o2,o3,o4,o5,o6,o7,o8,o9,o10,o11,o12,o13,o14,o15,o16,o17,o18,o19,o20,o21,o22,o23}, {g4,g5,g6,g7}, dt, pt, 1, 1, 1;\n"
        "wgmma.commit_group.sync.aligned;\n"
        "@pz bra.uni B14;\n"
        "mov.b32 {xl, xh}, a0; tanh.approx.f16 xr, xl; cvt.u32.u16 lo0, xr; tanh.approx.f16 xr, xh; cvt.u32.u16 hi0, xr; fma.rn.f16x2 p0, qz12, qz12, c; mul.rn.f16x2 a1, qz11, p1; fma.rn.f16x2 g8, qz8, h0, qz8; prmt.b32 h1, lo1, hi1, 0x5410;\n"
        "mov.b32 {xl, xh}, a1; tanh.approx.f16 xr, xl; cvt.u32.u16 lo1, xr; tanh.approx.f16 xr, xh; cvt.u32.u16 hi1, xr; fma.rn.f16x2 p1, qz13, qz13, c; mul.rn.f16x2 a0, qz12, p0; fma.rn.f16x2 g9, qz9, h1, qz9; prmt.b32 h0, lo0, hi0, 0x5410;\n"
        "mov.b32 {xl, xh}, a0; tanh.approx.f16 xr, xl; cvt.u32.u16 lo0, xr; tanh.approx.f16 xr, xh; cvt.u32.u16 hi0, xr; fma.rn.f16x2 p0, qz14, qz14, c; mul.rn.f16x2 a1, qz13, p1; fma.rn.f16x2 g10, qz10, h0, qz10; prmt.b32 h1, lo1, hi1, 0x5410;\n"
        "mov.b32 {xl, xh}, a1; tanh.approx.f16 xr, xl; cvt.u32.u16 lo1, xr; tanh.approx.f16 xr, xh; cvt.u32.u16 hi1, xr; fma.rn.f16x2 p1, qz15, qz15, c; mul.rn.f16x2 a0, qz14, p0; fma.rn.f16x2 g11, qz11, h1, qz11; prmt.b32 h0, lo0, hi0, 0x5410;\n"
        "B14:\n"
        "wgmma.wait_group.sync.aligned 1;\n"
        "wgmma.fence.sync.aligned;\n"
        "add.s64 dt, w2d, 128; wgmma.mma_async.sync.aligned.m64n96k16.f16.f16.f16 {o0,o1,o2,o3,o4,o5,o6,o7,o8,o9,o10,o11,o12,o13,o14,o15,o16,o17,o18,o19,o20,o21,o22,o23}, {g8,g9,g10,g11}, dt, pt, 1, 1, 1;\n"
        "wgmma.commit_group.sync.aligned;\n"
        "@pz bra.uni B18;\n"
        "mov.b32 {xl, xh}, a0; tanh.approx.f16 xr, xl; cvt.u32.u16 lo0, xr; tanh.approx.f16 xr, xh; cvt.u32.u16 hi0, xr; fma.rn.f16x2 p0, qz16, qz16, c; mul.rn.f16x2 a1, qz15, p1; fma.rn.f16x2 g12, qz12, h0, qz12; prmt.b32 h1, lo1, hi1, 0x5410;\n"
        "mov.b32 {xl, xh}, a1; tanh.approx.f16 xr, xl; cvt.u32.u16 lo1, xr; tanh.approx.f16 xr, xh; cvt.u32.u16 hi1, xr; fma.rn.f16x2 p1, qz17, qz17, c; mul.rn.f16x2 a0, qz16, p0; fma.rn.f16x2 g13, qz13, h1, qz13; prmt.b32 h0, lo0, hi0, 0x5410;\n"
        "mov.b32 {xl, xh}, a0; tanh.approx.f16 xr, xl; cvt.u32.u16 lo0, xr; tanh.approx.f16 xr, xh; cvt.u32.u16 hi0, xr; fma.rn.f16x2 p0, qz18, qz18, c; mul.rn.f16x2 a1, qz17, p1; fma.rn.f16x2 g14, qz14, h0, qz14; prmt.b32 h1, lo1, hi1, 0x5410;\n"
        "mov.b32 {xl, xh}, a1; tanh.approx.f16 xr, xl; cvt.u32.u16 lo1, xr; tanh.approx.f16 xr, xh; cvt.u32.u16 hi1, xr; fma.rn.f16x2 p1, qz19, qz19, c; mul.rn.f16x2 a0, qz18, p0; fma.rn.f16x2 g15, qz15, h1, qz15; prmt.b32 h0, lo0, hi0, 0x5410;\n"
        "B18:\n"
        "wgmma.wait_group.sync.aligned 1;\n"
        "mad.lo.u32 tt, n, 8, tbar; mbarrier.try_wait.parity.shared::cta.b64 pw, [tt], tpar;\n"
        "@!pw bra.uni SPINT;\n"
        "BACKT:\n"
        "wgmma.fence.sync.aligned;\n"
        "add.s64 dt, w2d, 192; wgmma.mma_async.sync.aligned.m64n96k16.f16.f16.f16 {o0,o1,o2,o3,o4,o5,o6,o7,o8,o9,o10,o11,o12,o13,o14,o15,o16,o17,o18,o19,o20,o21,o22,o23}, {g12,g13,g14,g15}, dt, pt, 1, 1, 1;\n"
        "add.s64 dt, w1d, 1536; wgmma.mma_async.sync.aligned.m64n64k16.f16.f16.f16 {qz0,qz1,qz2,qz3,qz4,qz5,qz6,qz7,qz8,qz9,qz10,qz11,qz12,qz13,qz14,qz15}, {qa0,qa1,qa2,qa3}, dt, pf, 1, 1, 1;\n"
        "add.s64 dt, w1d, 1664; wgmma.mma_async.sync.aligned.m64n64k16.f16.f16.f16 {qz0,qz1,qz2,qz3,qz4,qz5,qz6,qz7,qz8,qz9,qz10,qz11,qz12,qz13,qz14,qz15}, {qa4,qa5,qa6,qa7}, dt, pt, 1, 1, 1;\n"
        "add.s64 dt, w1d, 1792; wgmma.mma_async.sync.aligned.m64n64k16.f16.f16.f16 {qz0,qz1,qz2,qz3,qz4,qz5,qz6,qz7,qz8,qz9,qz10,qz11,qz12,qz13,qz14,qz15}, {qa8,qa9,qa10,qa11}, dt, pt, 1, 1, 1;\n"
        "wgmma.commit_group.sync.aligned;\n"
        "@pl bra.uni YLOAD;\n"
        "YLOADB:\n"
        "@pz bra.uni B22;\n"
        "mov.b32 {xl, xh}, a0; tanh.approx.f16 xr, xl; cvt.u32.u16 lo0, xr; tanh.approx.f16 xr, xh; cvt.u32.u16 hi0, xr; fma.rn.f16x2 p0, qz20, qz20, c; mul.rn.f16x2 a1, qz19, p1; fma.rn.f16x2 g0, qz16, h0, qz16; prmt.b32 h1, lo1, hi1, 0x5410;\n"
        "mov.b32 {xl, xh}, a1; tanh.approx.f16 xr, xl; cvt.u32.u16 lo1, xr; tanh.approx.f16 xr, xh; cvt.u32.u16 hi1, xr; fma.rn.f16x2 p1, qz21, qz21, c; mul.rn.f16x2 a0, qz20, p0; fma.rn.f16x2 g1, qz17, h1, qz17; prmt.b32 h0, lo0, hi0, 0x5410;\n"
        "mov.b32 {xl, xh}, a0; tanh.approx.f16 xr, xl; cvt.u32.u16 lo0, xr; tanh.approx.f16 xr, xh; cvt.u32.u16 hi0, xr; fma.rn.f16x2 p0, qz22, qz22, c; mul.rn.f16x2 a1, qz21, p1; fma.rn.f16x2 g2, qz18, h0, qz18; prmt.b32 h1, lo1, hi1, 0x5410;\n"
        "mov.b32 {xl, xh}, a1; tanh.approx.f16 xr, xl; cvt.u32.u16 lo1, xr; tanh.approx.f16 xr, xh; cvt.u32.u16 hi1, xr; fma.rn.f16x2 p1, qz23, qz23, c; mul.rn.f16x2 a0, qz22, p0; fma.rn.f16x2 g3, qz19, h1, qz19; prmt.b32 h0, lo0, hi0, 0x5410;\n"
        "B22:\n"
        "wgmma.fence.sync.aligned;\n"
        "add.s64 dt, w2d, 256; wgmma.mma_async.sync.aligned.m64n96k16.f16.f16.f16 {o0,o1,o2,o3,o4,o5,o6,o7,o8,o9,o10,o11,o12,o13,o14,o15,o16,o17,o18,o19,o20,o21,o22,o23}, {g0,g1,g2,g3}, dt, pt, 1, 1, 1;\n"
        "add.s64 dt, w1d, 1920; wgmma.mma_async.sync.aligned.m64n64k16.f16.f16.f16 {qz0,qz1,qz2,qz3,qz4,qz5,qz6,qz7,qz8,qz9,qz10,qz11,qz12,qz13,qz14,qz15}, {qa12,qa13,qa14,qa15}, dt, pt, 1, 1, 1;\n"
        "add.s64 dt, w1d, 2048; wgmma.mma_async.sync.aligned.m64n64k16.f16.f16.f16 {qz0,qz1,qz2,qz3,qz4,qz5,qz6,qz7,qz8,qz9,qz10,qz11,qz12,qz13,qz14,qz15}, {qa16,qa17,qa18,qa19}, dt, pt, 1, 1, 1;\n"
        "add.s64 dt, w1d, 2176; wgmma.mma_async.sync.aligned.m64n64k16.f16.f16.f16 {qz0,qz1,qz2,qz3,qz4,qz5,qz6,qz7,qz8,qz9,qz10,qz11,qz12,qz13,qz14,qz15}, {qa20,qa21,qa22,qa23}, dt, pt, 1, 1, 1;\n"
        "wgmma.commit_group.sync.aligned;\n"
        "@pz bra.uni B26;\n"
        "mov.b32 {xl, xh}, a0; tanh.approx.f16 xr, xl; cvt.u32.u16 lo0, xr; tanh.approx.f16 xr, xh; cvt.u32.u16 hi0, xr; fma.rn.f16x2 p0, qz24, qz24, c; mul.rn.f16x2 a1, qz23, p1; fma.rn.f16x2 g4, qz20, h0, qz20; prmt.b32 h1, lo1, hi1, 0x5410;\n"
        "mov.b32 {xl, xh}, a1; tanh.approx.f16 xr, xl; cvt.u32.u16 lo1, xr; tanh.approx.f16 xr, xh; cvt.u32.u16 hi1, xr; fma.rn.f16x2 p1, qz25, qz25, c; mul.rn.f16x2 a0, qz24, p0; fma.rn.f16x2 g5, qz21, h1, qz21; prmt.b32 h0, lo0, hi0, 0x5410;\n"
        "mov.b32 {xl, xh}, a0; tanh.approx.f16 xr, xl; cvt.u32.u16 lo0, xr; tanh.approx.f16 xr, xh; cvt.u32.u16 hi0, xr; fma.rn.f16x2 p0, qz26, qz26, c; mul.rn.f16x2 a1, qz25, p1; fma.rn.f16x2 g6, qz22, h0, qz22; prmt.b32 h1, lo1, hi1, 0x5410;\n"
        "mov.b32 {xl, xh}, a1; tanh.approx.f16 xr, xl; cvt.u32.u16 lo1, xr; tanh.approx.f16 xr, xh; cvt.u32.u16 hi1, xr; fma.rn.f16x2 p1, qz27, qz27, c; mul.rn.f16x2 a0, qz26, p0; fma.rn.f16x2 g7, qz23, h1, qz23; prmt.b32 h0, lo0, hi0, 0x5410;\n"
        "B26:\n"
        "wgmma.wait_group.sync.aligned 2;\n"
        "wgmma.fence.sync.aligned;\n"
        "add.s64 dt, w2d, 320; wgmma.mma_async.sync.aligned.m64n96k16.f16.f16.f16 {o0,o1,o2,o3,o4,o5,o6,o7,o8,o9,o10,o11,o12,o13,o14,o15,o16,o17,o18,o19,o20,o21,o22,o23}, {g4,g5,g6,g7}, dt, pt, 1, 1, 1;\n"
        "wgmma.commit_group.sync.aligned;\n"
        "@pz bra.uni B30;\n"
        "mov.b32 {xl, xh}, a0; tanh.approx.f16 xr, xl; cvt.u32.u16 lo0, xr; tanh.approx.f16 xr, xh; cvt.u32.u16 hi0, xr; fma.rn.f16x2 p0, qz28, qz28, c; mul.rn.f16x2 a1, qz27, p1; fma.rn.f16x2 g8, qz24, h0, qz24; prmt.b32 h1, lo1, hi1, 0x5410;\n"
        "mov.b32 {xl, xh}, a1; tanh.approx.f16 xr, xl; cvt.u32.u16 lo1, xr; tanh.approx.f16 xr, xh; cvt.u32.u16 hi1, xr; fma.rn.f16x2 p1, qz29, qz29, c; mul.rn.f16x2 a0, qz28, p0; fma.rn.f16x2 g9, qz25, h1, qz25; prmt.b32 h0, lo0, hi0, 0x5410;\n"
        "mov.b32 {xl, xh}, a0; tanh.approx.f16 xr, xl; cvt.u32.u16 lo0, xr; tanh.approx.f16 xr, xh; cvt.u32.u16 hi0, xr; fma.rn.f16x2 p0, qz30, qz30, c; mul.rn.f16x2 a1, qz29, p1; fma.rn.f16x2 g10, qz26, h0, qz26; prmt.b32 h1, lo1, hi1, 0x5410;\n"
        "mov.b32 {xl, xh}, a1; tanh.approx.f16 xr, xl; cvt.u32.u16 lo1, xr; tanh.approx.f16 xr, xh; cvt.u32.u16 hi1, xr; fma.rn.f16x2 p1, qz31, qz31, c; mul.rn.f16x2 a0, qz30, p0; fma.rn.f16x2 g11, qz27, h1, qz27; prmt.b32 h0, lo0, hi0, 0x5410;\n"
        "B30:\n"
        "wgmma.wait_group.sync.aligned 1;\n"
        "wgmma.fence.sync.aligned;\n"
        "add.s64 dt, w2d, 384; wgmma.mma_async.sync.aligned.m64n96k16.f16.f16.f16 {o0,o1,o2,o3,o4,o5,o6,o7,o8,o9,o10,o11,o12,o13,o14,o15,o16,o17,o18,o19,o20,o21,o22,o23}, {g8,g9,g10,g11}, dt, pt, 1, 1, 1;\n"
        "wgmma.commit_group.sync.aligned;\n"
        "@pz bra.uni B34;\n"
        "mov.b32 {xl, xh}, a0; tanh.approx.f16 xr, xl; cvt.u32.u16 lo0, xr; tanh.approx.f16 xr, xh; cvt.u32.u16 hi0, xr; fma.rn.f16x2 p0, qz0, qz0, c; mul.rn.f16x2 a1, qz31, p1; fma.rn.f16x2 g12, qz28, h0, qz28; prmt.b32 h1, lo1, hi1, 0x5410;\n"
        "mov.b32 {xl, xh}, a1; tanh.approx.f16 xr, xl; cvt.u32.u16 lo1, xr; tanh.approx.f16 xr, xh; cvt.u32.u16 hi1, xr; fma.rn.f16x2 p1, qz1, qz1, c; mul.rn.f16x2 a0, qz0, p0; fma.rn.f16x2 g13, qz29, h1, qz29; prmt.b32 h0, lo0, hi0, 0x5410;\n"
        "mov.b32 {xl, xh}, a0; tanh.approx.f16 xr, xl; cvt.u32.u16 lo0, xr; tanh.approx.f16 xr, xh; cvt.u32.u16 hi0, xr; fma.rn.f16x2 p0, qz2, qz2, c; mul.rn.f16x2 a1, qz1, p1; fma.rn.f16x2 g14, qz30, h0, qz30; prmt.b32 h1, lo1, hi1, 0x5410;\n"
        "mov.b32 {xl, xh}, a1; tanh.approx.f16 xr, xl; cvt.u32.u16 lo1, xr; tanh.approx.f16 xr, xh; cvt.u32.u16 hi1, xr; fma.rn.f16x2 p1, qz3, qz3, c; mul.rn.f16x2 a0, qz2, p0; fma.rn.f16x2 g15, qz31, h1, qz31; prmt.b32 h0, lo0, hi0, 0x5410;\n"
        "B34:\n"
        "wgmma.fence.sync.aligned;\n"
        "add.s64 dt, w2d, 448; wgmma.mma_async.sync.aligned.m64n96k16.f16.f16.f16 {o0,o1,o2,o3,o4,o5,o6,o7,o8,o9,o10,o11,o12,o13,o14,o15,o16,o17,o18,o19,o20,o21,o22,o23}, {g12,g13,g14,g15}, dt, pt, 1, 1, 1;\n"
        "add.s64 dt, w1d, 2304; wgmma.mma_async.sync.aligned.m64n64k16.f16.f16.f16 {qz16,qz17,qz18,qz19,qz20,qz21,qz22,qz23,qz24,qz25,qz26,qz27,qz28,qz29,qz30,qz31}, {qa0,qa1,qa2,qa3}, dt, pf, 1, 1, 1;\n"
        "add.s64 dt, w1d, 2432; wgmma.mma_async.sync.aligned.m64n64k16.f16.f16.f16 {qz16,qz17,qz18,qz19,qz20,qz21,qz22,qz23,qz24,qz25,qz26,qz27,qz28,qz29,qz30,qz31}, {qa4,qa5,qa6,qa7}, dt, pt, 1, 1, 1;\n"
        "add.s64 dt, w1d, 2560; wgmma.mma_async.sync.aligned.m64n64k16.f16.f16.f16 {qz16,qz17,qz18,qz19,qz20,qz21,qz22,qz23,qz24,qz25,qz26,qz27,qz28,qz29,qz30,qz31}, {qa8,qa9,qa10,qa11}, dt, pt, 1, 1, 1;\n"
        "wgmma.commit_group.sync.aligned;\n"
        "@pz bra.uni B38;\n"
        "mov.b32 {xl, xh}, a0; tanh.approx.f16 xr, xl; cvt.u32.u16 lo0, xr; tanh.approx.f16 xr, xh; cvt.u32.u16 hi0, xr; fma.rn.f16x2 p0, qz4, qz4, c; mul.rn.f16x2 a1, qz3, p1; fma.rn.f16x2 g0, qz0, h0, qz0; prmt.b32 h1, lo1, hi1, 0x5410;\n"
        "mov.b32 {xl, xh}, a1; tanh.approx.f16 xr, xl; cvt.u32.u16 lo1, xr; tanh.approx.f16 xr, xh; cvt.u32.u16 hi1, xr; fma.rn.f16x2 p1, qz5, qz5, c; mul.rn.f16x2 a0, qz4, p0; fma.rn.f16x2 g1, qz1, h1, qz1; prmt.b32 h0, lo0, hi0, 0x5410;\n"
        "mov.b32 {xl, xh}, a0; tanh.approx.f16 xr, xl; cvt.u32.u16 lo0, xr; tanh.approx.f16 xr, xh; cvt.u32.u16 hi0, xr; fma.rn.f16x2 p0, qz6, qz6, c; mul.rn.f16x2 a1, qz5, p1; fma.rn.f16x2 g2, qz2, h0, qz2; prmt.b32 h1, lo1, hi1, 0x5410;\n"
        "mov.b32 {xl, xh}, a1; tanh.approx.f16 xr, xl; cvt.u32.u16 lo1, xr; tanh.approx.f16 xr, xh; cvt.u32.u16 hi1, xr; fma.rn.f16x2 p1, qz7, qz7, c; mul.rn.f16x2 a0, qz6, p0; fma.rn.f16x2 g3, qz3, h1, qz3; prmt.b32 h0, lo0, hi0, 0x5410;\n"
        "B38:\n"
        "wgmma.wait_group.sync.aligned 2;\n"
        "wgmma.fence.sync.aligned;\n"
        "add.s64 dt, w2d, 512; wgmma.mma_async.sync.aligned.m64n96k16.f16.f16.f16 {o0,o1,o2,o3,o4,o5,o6,o7,o8,o9,o10,o11,o12,o13,o14,o15,o16,o17,o18,o19,o20,o21,o22,o23}, {g0,g1,g2,g3}, dt, pt, 1, 1, 1;\n"
        "add.s64 dt, w1d, 2688; wgmma.mma_async.sync.aligned.m64n64k16.f16.f16.f16 {qz16,qz17,qz18,qz19,qz20,qz21,qz22,qz23,qz24,qz25,qz26,qz27,qz28,qz29,qz30,qz31}, {qa12,qa13,qa14,qa15}, dt, pt, 1, 1, 1;\n"
        "add.s64 dt, w1d, 2816; wgmma.mma_async.sync.aligned.m64n64k16.f16.f16.f16 {qz16,qz17,qz18,qz19,qz20,qz21,qz22,qz23,qz24,qz25,qz26,qz27,qz28,qz29,qz30,qz31}, {qa16,qa17,qa18,qa19}, dt, pt, 1, 1, 1;\n"
        "add.s64 dt, w1d, 2944; wgmma.mma_async.sync.aligned.m64n64k16.f16.f16.f16 {qz16,qz17,qz18,qz19,qz20,qz21,qz22,qz23,qz24,qz25,qz26,qz27,qz28,qz29,qz30,qz31}, {qa20,qa21,qa22,qa23}, dt, pt, 1, 1, 1;\n"
        "wgmma.commit_group.sync.aligned;\n"
        "@pz bra.uni B42;\n"
        "mov.b32 {xl, xh}, a0; tanh.approx.f16 xr, xl; cvt.u32.u16 lo0, xr; tanh.approx.f16 xr, xh; cvt.u32.u16 hi0, xr; fma.rn.f16x2 p0, qz8, qz8, c; mul.rn.f16x2 a1, qz7, p1; fma.rn.f16x2 g4, qz4, h0, qz4; prmt.b32 h1, lo1, hi1, 0x5410;\n"
        "mov.b32 {xl, xh}, a1; tanh.approx.f16 xr, xl; cvt.u32.u16 lo1, xr; tanh.approx.f16 xr, xh; cvt.u32.u16 hi1, xr; fma.rn.f16x2 p1, qz9, qz9, c; mul.rn.f16x2 a0, qz8, p0; fma.rn.f16x2 g5, qz5, h1, qz5; prmt.b32 h0, lo0, hi0, 0x5410;\n"
        "mov.b32 {xl, xh}, a0; tanh.approx.f16 xr, xl; cvt.u32.u16 lo0, xr; tanh.approx.f16 xr, xh; cvt.u32.u16 hi0, xr; fma.rn.f16x2 p0, qz10, qz10, c; mul.rn.f16x2 a1, qz9, p1; fma.rn.f16x2 g6, qz6, h0, qz6; prmt.b32 h1, lo1, hi1, 0x5410;\n"
        "mov.b32 {xl, xh}, a1; tanh.approx.f16 xr, xl; cvt.u32.u16 lo1, xr; tanh.approx.f16 xr, xh; cvt.u32.u16 hi1, xr; fma.rn.f16x2 p1, qz11, qz11, c; mul.rn.f16x2 a0, qz10, p0; fma.rn.f16x2 g7, qz7, h1, qz7; prmt.b32 h0, lo0, hi0, 0x5410;\n"
        "B42:\n"
        "wgmma.wait_group.sync.aligned 2;\n"
        "wgmma.fence.sync.aligned;\n"
        "add.s64 dt, w2d, 576; wgmma.mma_async.sync.aligned.m64n96k16.f16.f16.f16 {o0,o1,o2,o3,o4,o5,o6,o7,o8,o9,o10,o11,o12,o13,o14,o15,o16,o17,o18,o19,o20,o21,o22,o23}, {g4,g5,g6,g7}, dt, pt, 1, 1, 1;\n"
        "wgmma.commit_group.sync.aligned;\n"
        "mad.lo.u32 tt, n, 8, tbar;\n"
        "@pn mbarrier.arrive.shared::cta.b64 _, [tt+64];\n"
        "@pz bra.uni B46;\n"
        "mov.b32 {xl, xh}, a0; tanh.approx.f16 xr, xl; cvt.u32.u16 lo0, xr; tanh.approx.f16 xr, xh; cvt.u32.u16 hi0, xr; fma.rn.f16x2 p0, qz12, qz12, c; mul.rn.f16x2 a1, qz11, p1; fma.rn.f16x2 g8, qz8, h0, qz8; prmt.b32 h1, lo1, hi1, 0x5410;\n"
        "mov.b32 {xl, xh}, a1; tanh.approx.f16 xr, xl; cvt.u32.u16 lo1, xr; tanh.approx.f16 xr, xh; cvt.u32.u16 hi1, xr; fma.rn.f16x2 p1, qz13, qz13, c; mul.rn.f16x2 a0, qz12, p0; fma.rn.f16x2 g9, qz9, h1, qz9; prmt.b32 h0, lo0, hi0, 0x5410;\n"
        "mov.b32 {xl, xh}, a0; tanh.approx.f16 xr, xl; cvt.u32.u16 lo0, xr; tanh.approx.f16 xr, xh; cvt.u32.u16 hi0, xr; fma.rn.f16x2 p0, qz14, qz14, c; mul.rn.f16x2 a1, qz13, p1; fma.rn.f16x2 g10, qz10, h0, qz10; prmt.b32 h1, lo1, hi1, 0x5410;\n"
        "mov.b32 {xl, xh}, a1; tanh.approx.f16 xr, xl; cvt.u32.u16 lo1, xr; tanh.approx.f16 xr, xh; cvt.u32.u16 hi1, xr; fma.rn.f16x2 p1, qz15, qz15, c; mul.rn.f16x2 a0, qz14, p0; fma.rn.f16x2 g11, qz11, h1, qz11; prmt.b32 h0, lo0, hi0, 0x5410;\n"
        "B46:\n"
        "wgmma.wait_group.sync.aligned 1;\n"
        "wgmma.fence.sync.aligned;\n"
        "add.s64 dt, w2d, 640; wgmma.mma_async.sync.aligned.m64n96k16.f16.f16.f16 {o0,o1,o2,o3,o4,o5,o6,o7,o8,o9,o10,o11,o12,o13,o14,o15,o16,o17,o18,o19,o20,o21,o22,o23}, {g8,g9,g10,g11}, dt, pt, 1, 1, 1;\n"
        "wgmma.commit_group.sync.aligned;\n"
        "@pz bra.uni B50;\n"
        "mov.b32 {xl, xh}, a0; tanh.approx.f16 xr, xl; cvt.u32.u16 lo0, xr; tanh.approx.f16 xr, xh; cvt.u32.u16 hi0, xr; fma.rn.f16x2 p0, qz16, qz16, c; mul.rn.f16x2 a1, qz15, p1; fma.rn.f16x2 g12, qz12, h0, qz12; prmt.b32 h1, lo1, hi1, 0x5410;\n"
        "mov.b32 {xl, xh}, a1; tanh.approx.f16 xr, xl; cvt.u32.u16 lo1, xr; tanh.approx.f16 xr, xh; cvt.u32.u16 hi1, xr; fma.rn.f16x2 p1, qz17, qz17, c; mul.rn.f16x2 a0, qz16, p0; fma.rn.f16x2 g13, qz13, h1, qz13; prmt.b32 h0, lo0, hi0, 0x5410;\n"
        "mov.b32 {xl, xh}, a0; tanh.approx.f16 xr, xl; cvt.u32.u16 lo0, xr; tanh.approx.f16 xr, xh; cvt.u32.u16 hi0, xr; fma.rn.f16x2 p0, qz18, qz18, c; mul.rn.f16x2 a1, qz17, p1; fma.rn.f16x2 g14, qz14, h0, qz14; prmt.b32 h1, lo1, hi1, 0x5410;\n"
        "mov.b32 {xl, xh}, a1; tanh.approx.f16 xr, xl; cvt.u32.u16 lo1, xr; tanh.approx.f16 xr, xh; cvt.u32.u16 hi1, xr; fma.rn.f16x2 p1, qz19, qz19, c; mul.rn.f16x2 a0, qz18, p0; fma.rn.f16x2 g15, qz15, h1, qz15; prmt.b32 h0, lo0, hi0, 0x5410;\n"
        "B50:\n"
        "wgmma.fence.sync.aligned;\n"
        "add.s64 dt, w2d, 704; wgmma.mma_async.sync.aligned.m64n96k16.f16.f16.f16 {o0,o1,o2,o3,o4,o5,o6,o7,o8,o9,o10,o11,o12,o13,o14,o15,o16,o17,o18,o19,o20,o21,o22,o23}, {g12,g13,g14,g15}, dt, pt, 1, 1, 1;\n"
        "add.s64 dt, w1d, 3072; wgmma.mma_async.sync.aligned.m64n64k16.f16.f16.f16 {qz0,qz1,qz2,qz3,qz4,qz5,qz6,qz7,qz8,qz9,qz10,qz11,qz12,qz13,qz14,qz15}, {qa0,qa1,qa2,qa3}, dt, pf, 1, 1, 1;\n"
        "add.s64 dt, w1d, 3200; wgmma.mma_async.sync.aligned.m64n64k16.f16.f16.f16 {qz0,qz1,qz2,qz3,qz4,qz5,qz6,qz7,qz8,qz9,qz10,qz11,qz12,qz13,qz14,qz15}, {qa4,qa5,qa6,qa7}, dt, pt, 1, 1, 1;\n"
        "add.s64 dt, w1d, 3328; wgmma.mma_async.sync.aligned.m64n64k16.f16.f16.f16 {qz0,qz1,qz2,qz3,qz4,qz5,qz6,qz7,qz8,qz9,qz10,qz11,qz12,qz13,qz14,qz15}, {qa8,qa9,qa10,qa11}, dt, pt, 1, 1, 1;\n"
        "wgmma.commit_group.sync.aligned;\n"
        "@pz bra.uni B54;\n"
        "mov.b32 {xl, xh}, a0; tanh.approx.f16 xr, xl; cvt.u32.u16 lo0, xr; tanh.approx.f16 xr, xh; cvt.u32.u16 hi0, xr; fma.rn.f16x2 p0, qz20, qz20, c; mul.rn.f16x2 a1, qz19, p1; fma.rn.f16x2 g0, qz16, h0, qz16; prmt.b32 h1, lo1, hi1, 0x5410;\n"
        "mov.b32 {xl, xh}, a1; tanh.approx.f16 xr, xl; cvt.u32.u16 lo1, xr; tanh.approx.f16 xr, xh; cvt.u32.u16 hi1, xr; fma.rn.f16x2 p1, qz21, qz21, c; mul.rn.f16x2 a0, qz20, p0; fma.rn.f16x2 g1, qz17, h1, qz17; prmt.b32 h0, lo0, hi0, 0x5410;\n"
        "mov.b32 {xl, xh}, a0; tanh.approx.f16 xr, xl; cvt.u32.u16 lo0, xr; tanh.approx.f16 xr, xh; cvt.u32.u16 hi0, xr; fma.rn.f16x2 p0, qz22, qz22, c; mul.rn.f16x2 a1, qz21, p1; fma.rn.f16x2 g2, qz18, h0, qz18; prmt.b32 h1, lo1, hi1, 0x5410;\n"
        "mov.b32 {xl, xh}, a1; tanh.approx.f16 xr, xl; cvt.u32.u16 lo1, xr; tanh.approx.f16 xr, xh; cvt.u32.u16 hi1, xr; fma.rn.f16x2 p1, qz23, qz23, c; mul.rn.f16x2 a0, qz22, p0; fma.rn.f16x2 g3, qz19, h1, qz19; prmt.b32 h0, lo0, hi0, 0x5410;\n"
        "B54:\n"
        "wgmma.wait_group.sync.aligned 2;\n"
        "wgmma.fence.sync.aligned;\n"
        "add.s64 dt, w2d, 768; wgmma.mma_async.sync.aligned.m64n96k16.f16.f16.f16 {o0,o1,o2,o3,o4,o5,o6,o7,o8,o9,o10,o11,o12,o13,o14,o15,o16,o17,o18,o19,o20,o21,o22,o23}, {g0,g1,g2,g3}, dt, pt, 1, 1, 1;\n"
        "add.s64 dt, w1d, 3456; wgmma.mma_async.sync.aligned.m64n64k16.f16.f16.f16 {qz0,qz1,qz2,qz3,qz4,qz5,qz6,qz7,qz8,qz9,qz10,qz11,qz12,qz13,qz14,qz15}, {qa12,qa13,qa14,qa15}, dt, pt, 1, 1, 1;\n"
        "add.s64 dt, w1d, 3584; wgmma.mma_async.sync.aligned.m64n64k16.f16.f16.f16 {qz0,qz1,qz2,qz3,qz4,qz5,qz6,qz7,qz8,qz9,qz10,qz11,qz12,qz13,qz14,qz15}, {qa16,qa17,qa18,qa19}, dt, pt, 1, 1, 1;\n"
        "add.s64 dt, w1d, 3712; wgmma.mma_async.sync.aligned.m64n64k16.f16.f16.f16 {qz0,qz1,qz2,qz3,qz4,qz5,qz6,qz7,qz8,qz9,qz10,qz11,qz12,qz13,qz14,qz15}, {qa20,qa21,qa22,qa23}, dt, pt, 1, 1, 1;\n"
        "wgmma.commit_group.sync.aligned;\n"
        "@pz bra.uni B58;\n"
        "mov.b32 {xl, xh}, a0; tanh.approx.f16 xr, xl; cvt.u32.u16 lo0, xr; tanh.approx.f16 xr, xh; cvt.u32.u16 hi0, xr; fma.rn.f16x2 p0, qz24, qz24, c; mul.rn.f16x2 a1, qz23, p1; fma.rn.f16x2 g4, qz20, h0, qz20; prmt.b32 h1, lo1, hi1, 0x5410;\n"
        "mov.b32 {xl, xh}, a1; tanh.approx.f16 xr, xl; cvt.u32.u16 lo1, xr; tanh.approx.f16 xr, xh; cvt.u32.u16 hi1, xr; fma.rn.f16x2 p1, qz25, qz25, c; mul.rn.f16x2 a0, qz24, p0; fma.rn.f16x2 g5, qz21, h1, qz21; prmt.b32 h0, lo0, hi0, 0x5410;\n"
        "mov.b32 {xl, xh}, a0; tanh.approx.f16 xr, xl; cvt.u32.u16 lo0, xr; tanh.approx.f16 xr, xh; cvt.u32.u16 hi0, xr; fma.rn.f16x2 p0, qz26, qz26, c; mul.rn.f16x2 a1, qz25, p1; fma.rn.f16x2 g6, qz22, h0, qz22; prmt.b32 h1, lo1, hi1, 0x5410;\n"
        "mov.b32 {xl, xh}, a1; tanh.approx.f16 xr, xl; cvt.u32.u16 lo1, xr; tanh.approx.f16 xr, xh; cvt.u32.u16 hi1, xr; fma.rn.f16x2 p1, qz27, qz27, c; mul.rn.f16x2 a0, qz26, p0; fma.rn.f16x2 g7, qz23, h1, qz23; prmt.b32 h0, lo0, hi0, 0x5410;\n"
        "B58:\n"
        "wgmma.wait_group.sync.aligned 2;\n"
        "wgmma.fence.sync.aligned;\n"
        "add.s64 dt, w2d, 832; wgmma.mma_async.sync.aligned.m64n96k16.f16.f16.f16 {o0,o1,o2,o3,o4,o5,o6,o7,o8,o9,o10,o11,o12,o13,o14,o15,o16,o17,o18,o19,o20,o21,o22,o23}, {g4,g5,g6,g7}, dt, pt, 1, 1, 1;\n"
        "wgmma.commit_group.sync.aligned;\n"
        "@pz bra.uni B62;\n"
        "mov.b32 {xl, xh}, a0; tanh.approx.f16 xr, xl; cvt.u32.u16 lo0, xr; tanh.approx.f16 xr, xh; cvt.u32.u16 hi0, xr; fma.rn.f16x2 p0, qz28, qz28, c; mul.rn.f16x2 a1, qz27, p1; fma.rn.f16x2 g8, qz24, h0, qz24; prmt.b32 h1, lo1, hi1, 0x5410;\n"
        "mov.b32 {xl, xh}, a1; tanh.approx.f16 xr, xl; cvt.u32.u16 lo1, xr; tanh.approx.f16 xr, xh; cvt.u32.u16 hi1, xr; fma.rn.f16x2 p1, qz29, qz29, c; mul.rn.f16x2 a0, qz28, p0; fma.rn.f16x2 g9, qz25, h1, qz25; prmt.b32 h0, lo0, hi0, 0x5410;\n"
        "mov.b32 {xl, xh}, a0; tanh.approx.f16 xr, xl; cvt.u32.u16 lo0, xr; tanh.approx.f16 xr, xh; cvt.u32.u16 hi0, xr; fma.rn.f16x2 p0, qz30, qz30, c; mul.rn.f16x2 a1, qz29, p1; fma.rn.f16x2 g10, qz26, h0, qz26; prmt.b32 h1, lo1, hi1, 0x5410;\n"
        "mov.b32 {xl, xh}, a1; tanh.approx.f16 xr, xl; cvt.u32.u16 lo1, xr; tanh.approx.f16 xr, xh; cvt.u32.u16 hi1, xr; fma.rn.f16x2 p1, qz31, qz31, c; mul.rn.f16x2 a0, qz30, p0; fma.rn.f16x2 g11, qz27, h1, qz27; prmt.b32 h0, lo0, hi0, 0x5410;\n"
        "B62:\n"
        "wgmma.wait_group.sync.aligned 1;\n"
        "wgmma.fence.sync.aligned;\n"
        "add.s64 dt, w2d, 896; wgmma.mma_async.sync.aligned.m64n96k16.f16.f16.f16 {o0,o1,o2,o3,o4,o5,o6,o7,o8,o9,o10,o11,o12,o13,o14,o15,o16,o17,o18,o19,o20,o21,o22,o23}, {g8,g9,g10,g11}, dt, pt, 1, 1, 1;\n"
        "wgmma.commit_group.sync.aligned;\n"
        "@pz bra.uni B66;\n"
        "mov.b32 {xl, xh}, a0; tanh.approx.f16 xr, xl; cvt.u32.u16 lo0, xr; tanh.approx.f16 xr, xh; cvt.u32.u16 hi0, xr; fma.rn.f16x2 p0, qz0, qz0, c; mul.rn.f16x2 a1, qz31, p1; fma.rn.f16x2 g12, qz28, h0, qz28; prmt.b32 h1, lo1, hi1, 0x5410;\n"
        "mov.b32 {xl, xh}, a1; tanh.approx.f16 xr, xl; cvt.u32.u16 lo1, xr; tanh.approx.f16 xr, xh; cvt.u32.u16 hi1, xr; fma.rn.f16x2 p1, qz1, qz1, c; mul.rn.f16x2 a0, qz0, p0; fma.rn.f16x2 g13, qz29, h1, qz29; prmt.b32 h0, lo0, hi0, 0x5410;\n"
        "mov.b32 {xl, xh}, a0; tanh.approx.f16 xr, xl; cvt.u32.u16 lo0, xr; tanh.approx.f16 xr, xh; cvt.u32.u16 hi0, xr; fma.rn.f16x2 p0, qz2, qz2, c; mul.rn.f16x2 a1, qz1, p1; fma.rn.f16x2 g14, qz30, h0, qz30; prmt.b32 h1, lo1, hi1, 0x5410;\n"
        "mov.b32 {xl, xh}, a1; tanh.approx.f16 xr, xl; cvt.u32.u16 lo1, xr; tanh.approx.f16 xr, xh; cvt.u32.u16 hi1, xr; fma.rn.f16x2 p1, qz3, qz3, c; mul.rn.f16x2 a0, qz2, p0; fma.rn.f16x2 g15, qz31, h1, qz31; prmt.b32 h0, lo0, hi0, 0x5410;\n"
        "B66:\n"
        "wgmma.fence.sync.aligned;\n"
        "add.s64 dt, w2d, 960; wgmma.mma_async.sync.aligned.m64n96k16.f16.f16.f16 {o0,o1,o2,o3,o4,o5,o6,o7,o8,o9,o10,o11,o12,o13,o14,o15,o16,o17,o18,o19,o20,o21,o22,o23}, {g12,g13,g14,g15}, dt, pt, 1, 1, 1;\n"
        "add.s64 dt, w1d, 3840; wgmma.mma_async.sync.aligned.m64n64k16.f16.f16.f16 {qz16,qz17,qz18,qz19,qz20,qz21,qz22,qz23,qz24,qz25,qz26,qz27,qz28,qz29,qz30,qz31}, {qa0,qa1,qa2,qa3}, dt, pf, 1, 1, 1;\n"
        "add.s64 dt, w1d, 3968; wgmma.mma_async.sync.aligned.m64n64k16.f16.f16.f16 {qz16,qz17,qz18,qz19,qz20,qz21,qz22,qz23,qz24,qz25,qz26,qz27,qz28,qz29,qz30,qz31}, {qa4,qa5,qa6,qa7}, dt, pt, 1, 1, 1;\n"
        "add.s64 dt, w1d, 4096; wgmma.mma_async.sync.aligned.m64n64k16.f16.f16.f16 {qz16,qz17,qz18,qz19,qz20,qz21,qz22,qz23,qz24,qz25,qz26,qz27,qz28,qz29,qz30,qz31}, {qa8,qa9,qa10,qa11}, dt, pt, 1, 1, 1;\n"
        "wgmma.commit_group.sync.aligned;\n"
        "@pz bra.uni B70;\n"
        "mov.b32 {xl, xh}, a0; tanh.approx.f16 xr, xl; cvt.u32.u16 lo0, xr; tanh.approx.f16 xr, xh; cvt.u32.u16 hi0, xr; fma.rn.f16x2 p0, qz4, qz4, c; mul.rn.f16x2 a1, qz3, p1; fma.rn.f16x2 g0, qz0, h0, qz0; prmt.b32 h1, lo1, hi1, 0x5410;\n"
        "mov.b32 {xl, xh}, a1; tanh.approx.f16 xr, xl; cvt.u32.u16 lo1, xr; tanh.approx.f16 xr, xh; cvt.u32.u16 hi1, xr; fma.rn.f16x2 p1, qz5, qz5, c; mul.rn.f16x2 a0, qz4, p0; fma.rn.f16x2 g1, qz1, h1, qz1; prmt.b32 h0, lo0, hi0, 0x5410;\n"
        "mov.b32 {xl, xh}, a0; tanh.approx.f16 xr, xl; cvt.u32.u16 lo0, xr; tanh.approx.f16 xr, xh; cvt.u32.u16 hi0, xr; fma.rn.f16x2 p0, qz6, qz6, c; mul.rn.f16x2 a1, qz5, p1; fma.rn.f16x2 g2, qz2, h0, qz2; prmt.b32 h1, lo1, hi1, 0x5410;\n"
        "mov.b32 {xl, xh}, a1; tanh.approx.f16 xr, xl; cvt.u32.u16 lo1, xr; tanh.approx.f16 xr, xh; cvt.u32.u16 hi1, xr; fma.rn.f16x2 p1, qz7, qz7, c; mul.rn.f16x2 a0, qz6, p0; fma.rn.f16x2 g3, qz3, h1, qz3; prmt.b32 h0, lo0, hi0, 0x5410;\n"
        "B70:\n"
        "wgmma.wait_group.sync.aligned 2;\n"
        "wgmma.fence.sync.aligned;\n"
        "add.s64 dt, w2d, 1024; wgmma.mma_async.sync.aligned.m64n96k16.f16.f16.f16 {o0,o1,o2,o3,o4,o5,o6,o7,o8,o9,o10,o11,o12,o13,o14,o15,o16,o17,o18,o19,o20,o21,o22,o23}, {g0,g1,g2,g3}, dt, pt, 1, 1, 1;\n"
        "add.s64 dt, w1d, 4224; wgmma.mma_async.sync.aligned.m64n64k16.f16.f16.f16 {qz16,qz17,qz18,qz19,qz20,qz21,qz22,qz23,qz24,qz25,qz26,qz27,qz28,qz29,qz30,qz31}, {qa12,qa13,qa14,qa15}, dt, pt, 1, 1, 1;\n"
        "add.s64 dt, w1d, 4352; wgmma.mma_async.sync.aligned.m64n64k16.f16.f16.f16 {qz16,qz17,qz18,qz19,qz20,qz21,qz22,qz23,qz24,qz25,qz26,qz27,qz28,qz29,qz30,qz31}, {qa16,qa17,qa18,qa19}, dt, pt, 1, 1, 1;\n"
        "add.s64 dt, w1d, 4480; wgmma.mma_async.sync.aligned.m64n64k16.f16.f16.f16 {qz16,qz17,qz18,qz19,qz20,qz21,qz22,qz23,qz24,qz25,qz26,qz27,qz28,qz29,qz30,qz31}, {qa20,qa21,qa22,qa23}, dt, pt, 1, 1, 1;\n"
        "wgmma.commit_group.sync.aligned;\n"
        "@pz bra.uni B74;\n"
        "mov.b32 {xl, xh}, a0; tanh.approx.f16 xr, xl; cvt.u32.u16 lo0, xr; tanh.approx.f16 xr, xh; cvt.u32.u16 hi0, xr; fma.rn.f16x2 p0, qz8, qz8, c; mul.rn.f16x2 a1, qz7, p1; fma.rn.f16x2 g4, qz4, h0, qz4; prmt.b32 h1, lo1, hi1, 0x5410;\n"
        "mov.b32 {xl, xh}, a1; tanh.approx.f16 xr, xl; cvt.u32.u16 lo1, xr; tanh.approx.f16 xr, xh; cvt.u32.u16 hi1, xr; fma.rn.f16x2 p1, qz9, qz9, c; mul.rn.f16x2 a0, qz8, p0; fma.rn.f16x2 g5, qz5, h1, qz5; prmt.b32 h0, lo0, hi0, 0x5410;\n"
        "mov.b32 {xl, xh}, a0; tanh.approx.f16 xr, xl; cvt.u32.u16 lo0, xr; tanh.approx.f16 xr, xh; cvt.u32.u16 hi0, xr; fma.rn.f16x2 p0, qz10, qz10, c; mul.rn.f16x2 a1, qz9, p1; fma.rn.f16x2 g6, qz6, h0, qz6; prmt.b32 h1, lo1, hi1, 0x5410;\n"
        "mov.b32 {xl, xh}, a1; tanh.approx.f16 xr, xl; cvt.u32.u16 lo1, xr; tanh.approx.f16 xr, xh; cvt.u32.u16 hi1, xr; fma.rn.f16x2 p1, qz11, qz11, c; mul.rn.f16x2 a0, qz10, p0; fma.rn.f16x2 g7, qz7, h1, qz7; prmt.b32 h0, lo0, hi0, 0x5410;\n"
        "B74:\n"
        "wgmma.wait_group.sync.aligned 2;\n"
        "wgmma.fence.sync.aligned;\n"
        "add.s64 dt, w2d, 1088; wgmma.mma_async.sync.aligned.m64n96k16.f16.f16.f16 {o0,o1,o2,o3,o4,o5,o6,o7,o8,o9,o10,o11,o12,o13,o14,o15,o16,o17,o18,o19,o20,o21,o22,o23}, {g4,g5,g6,g7}, dt, pt, 1, 1, 1;\n"
        "wgmma.commit_group.sync.aligned;\n"
        "@pz bra.uni B78;\n"
        "mov.b32 {xl, xh}, a0; tanh.approx.f16 xr, xl; cvt.u32.u16 lo0, xr; tanh.approx.f16 xr, xh; cvt.u32.u16 hi0, xr; fma.rn.f16x2 p0, qz12, qz12, c; mul.rn.f16x2 a1, qz11, p1; fma.rn.f16x2 g8, qz8, h0, qz8; prmt.b32 h1, lo1, hi1, 0x5410;\n"
        "mov.b32 {xl, xh}, a1; tanh.approx.f16 xr, xl; cvt.u32.u16 lo1, xr; tanh.approx.f16 xr, xh; cvt.u32.u16 hi1, xr; fma.rn.f16x2 p1, qz13, qz13, c; mul.rn.f16x2 a0, qz12, p0; fma.rn.f16x2 g9, qz9, h1, qz9; prmt.b32 h0, lo0, hi0, 0x5410;\n"
        "mov.b32 {xl, xh}, a0; tanh.approx.f16 xr, xl; cvt.u32.u16 lo0, xr; tanh.approx.f16 xr, xh; cvt.u32.u16 hi0, xr; fma.rn.f16x2 p0, qz14, qz14, c; mul.rn.f16x2 a1, qz13, p1; fma.rn.f16x2 g10, qz10, h0, qz10; prmt.b32 h1, lo1, hi1, 0x5410;\n"
        "mov.b32 {xl, xh}, a1; tanh.approx.f16 xr, xl; cvt.u32.u16 lo1, xr; tanh.approx.f16 xr, xh; cvt.u32.u16 hi1, xr; fma.rn.f16x2 p1, qz15, qz15, c; mul.rn.f16x2 a0, qz14, p0; fma.rn.f16x2 g11, qz11, h1, qz11; prmt.b32 h0, lo0, hi0, 0x5410;\n"
        "B78:\n"
        "wgmma.wait_group.sync.aligned 1;\n"
        "wgmma.fence.sync.aligned;\n"
        "add.s64 dt, w2d, 1152; wgmma.mma_async.sync.aligned.m64n96k16.f16.f16.f16 {o0,o1,o2,o3,o4,o5,o6,o7,o8,o9,o10,o11,o12,o13,o14,o15,o16,o17,o18,o19,o20,o21,o22,o23}, {g8,g9,g10,g11}, dt, pt, 1, 1, 1;\n"
        "wgmma.commit_group.sync.aligned;\n"
        "@!pm bra.uni BACKY;\n"
        "add.u32 tt, n, 1; and.b32 tt, tt, 1; mbarrier.try_wait.parity.shared::cta.b64 pw, [ybar], tt;\n"
        "@!pw bra.uni SPINY;\n"
        "BACKY:\n"
        "@pz bra.uni B80;\n"
        "and.b32 ad, %5, 0xffff; xor.b32 ad, ad, 0; add.u32 ad, ad, %4; ldmatrix.sync.aligned.m8n8.x4.shared.b16 {qa0,qa1,qa2,qa3}, [ad];\n"
        "and.b32 ad, %5, 0xffff; xor.b32 ad, ad, 32; add.u32 ad, ad, %4; ldmatrix.sync.aligned.m8n8.x4.shared.b16 {qa4,qa5,qa6,qa7}, [ad];\n"
        "and.b32 ad, %5, 0xffff; xor.b32 ad, ad, 64; add.u32 ad, ad, %4; ldmatrix.sync.aligned.m8n8.x4.shared.b16 {qa8,qa9,qa10,qa11}, [ad];\n"
        "and.b32 ad, %5, 0xffff; xor.b32 ad, ad, 96; add.u32 ad, ad, %4; ldmatrix.sync.aligned.m8n8.x4.shared.b16 {qa12,qa13,qa14,qa15}, [ad];\n"
        "shr.u32 ad, %5, 16; xor.b32 ad, ad, 0; add.u32 ad, ad, %4; ldmatrix.sync.aligned.m8n8.x4.shared.b16 {qa16,qa17,qa18,qa19}, [ad];\n"
        "shr.u32 ad, %5, 16; xor.b32 ad, ad, 32; add.u32 ad, ad, %4; ldmatrix.sync.aligned.m8n8.x4.shared.b16 {qa20,qa21,qa22,qa23}, [ad];\n"
        "mov.b32 {xl, xh}, a0; tanh.approx.f16 xr, xl; cvt.u32.u16 lo0, xr; tanh.approx.f16 xr, xh; cvt.u32.u16 hi0, xr; fma.rn.f16x2 p0, qz16, qz16, c; mul.rn.f16x2 a1, qz15, p1; fma.rn.f16x2 g12, qz12, h0, qz12; prmt.b32 h1, lo1, hi1, 0x5410;\n"
        "mov.b32 {xl, xh}, a1; tanh.approx.f16 xr, xl; cvt.u32.u16 lo1, xr; tanh.approx.f16 xr, xh; cvt.u32.u16 hi1, xr; fma.rn.f16x2 p1, qz17, qz17, c; mul.rn.f16x2 a0, qz16, p0; fma.rn.f16x2 g13, qz13, h1, qz13; prmt.b32 h0, lo0, hi0, 0x5410;\n"
        "B80:\n"
        "fence.proxy.async.shared::cta;\n"
        "add.u32 tt, id, 0;\n"
        "@pk bra.uni XLOAD;\n"
        "bar.arrive tt, 128;\n"
        "XLOADB:\n"
        "@pz bra.uni B82;\n"
        "mov.b32 {xl, xh}, a0; tanh.approx.f16 xr, xl; cvt.u32.u16 lo0, xr; tanh.approx.f16 xr, xh; cvt.u32.u16 hi0, xr; fma.rn.f16x2 p0, qz18, qz18, c; mul.rn.f16x2 a1, qz17, p1; fma.rn.f16x2 g14, qz14, h0, qz14; prmt.b32 h1, lo1, hi1, 0x5410;\n"
        "mov.b32 {xl, xh}, a1; tanh.approx.f16 xr, xl; cvt.u32.u16 lo1, xr; tanh.approx.f16 xr, xh; cvt.u32.u16 hi1, xr; fma.rn.f16x2 p1, qz19, qz19, c; mul.rn.f16x2 a0, qz18, p0; fma.rn.f16x2 g15, qz15, h1, qz15; prmt.b32 h0, lo0, hi0, 0x5410;\n"
        "B82:\n"
        "wgmma.fence.sync.aligned;\n"
        "add.s64 dt, w2d, 1216; wgmma.mma_async.sync.aligned.m64n96k16.f16.f16.f16 {o0,o1,o2,o3,o4,o5,o6,o7,o8,o9,o10,o11,o12,o13,o14,o15,o16,o17,o18,o19,o20,o21,o22,o23}, {g12,g13,g14,g15}, dt, pt, 1, 1, 1;\n"
        "wgmma.commit_group.sync.aligned;\n"
        "@!pm bra.uni SKIP1;\n"
        "wgmma.fence.sync.aligned;\n"
        "add.s64 dt, w1d, 0; wgmma.mma_async.sync.aligned.m64n64k16.f16.f16.f16 {qz0,qz1,qz2,qz3,qz4,qz5,qz6,qz7,qz8,qz9,qz10,qz11,qz12,qz13,qz14,qz15}, {qa0,qa1,qa2,qa3}, dt, pf, 1, 1, 1;\n"
        "add.s64 dt, w1d, 128; wgmma.mma_async.sync.aligned.m64n64k16.f16.f16.f16 {qz0,qz1,qz2,qz3,qz4,qz5,qz6,qz7,qz8,qz9,qz10,qz11,qz12,qz13,qz14,qz15}, {qa4,qa5,qa6,qa7}, dt, pt, 1, 1, 1;\n"
        "add.s64 dt, w1d, 256; wgmma.mma_async.sync.aligned.m64n64k16.f16.f16.f16 {qz0,qz1,qz2,qz3,qz4,qz5,qz6,qz7,qz8,qz9,qz10,qz11,qz12,qz13,qz14,qz15}, {qa8,qa9,qa10,qa11}, dt, pt, 1, 1, 1;\n"
        "SKIP1:\n"
        "@pz bra.uni B86;\n"
        "mov.b32 {xl, xh}, a0; tanh.approx.f16 xr, xl; cvt.u32.u16 lo0, xr; tanh.approx.f16 xr, xh; cvt.u32.u16 hi0, xr; fma.rn.f16x2 p0, qz20, qz20, c; mul.rn.f16x2 a1, qz19, p1; fma.rn.f16x2 g0, qz16, h0, qz16; prmt.b32 h1, lo1, hi1, 0x5410;\n"
        "mov.b32 {xl, xh}, a1; tanh.approx.f16 xr, xl; cvt.u32.u16 lo1, xr; tanh.approx.f16 xr, xh; cvt.u32.u16 hi1, xr; fma.rn.f16x2 p1, qz21, qz21, c; mul.rn.f16x2 a0, qz20, p0; fma.rn.f16x2 g1, qz17, h1, qz17; prmt.b32 h0, lo0, hi0, 0x5410;\n"
        "mov.b32 {xl, xh}, a0; tanh.approx.f16 xr, xl; cvt.u32.u16 lo0, xr; tanh.approx.f16 xr, xh; cvt.u32.u16 hi0, xr; fma.rn.f16x2 p0, qz22, qz22, c; mul.rn.f16x2 a1, qz21, p1; fma.rn.f16x2 g2, qz18, h0, qz18; prmt.b32 h1, lo1, hi1, 0x5410;\n"
        "mov.b32 {xl, xh}, a1; tanh.approx.f16 xr, xl; cvt.u32.u16 lo1, xr; tanh.approx.f16 xr, xh; cvt.u32.u16 hi1, xr; fma.rn.f16x2 p1, qz23, qz23, c; mul.rn.f16x2 a0, qz22, p0; fma.rn.f16x2 g3, qz19, h1, qz19; prmt.b32 h0, lo0, hi0, 0x5410;\n"
        "B86:\n"
        "wgmma.wait_group.sync.aligned 2;\n"
        "wgmma.fence.sync.aligned;\n"
        "add.s64 dt, w2d, 1280; wgmma.mma_async.sync.aligned.m64n96k16.f16.f16.f16 {o0,o1,o2,o3,o4,o5,o6,o7,o8,o9,o10,o11,o12,o13,o14,o15,o16,o17,o18,o19,o20,o21,o22,o23}, {g0,g1,g2,g3}, dt, pt, 1, 1, 1;\n"
        "wgmma.commit_group.sync.aligned;\n"
        "@!pm bra.uni SKIP2;\n"
        "wgmma.fence.sync.aligned;\n"
        "add.s64 dt, w1d, 384; wgmma.mma_async.sync.aligned.m64n64k16.f16.f16.f16 {qz0,qz1,qz2,qz3,qz4,qz5,qz6,qz7,qz8,qz9,qz10,qz11,qz12,qz13,qz14,qz15}, {qa12,qa13,qa14,qa15}, dt, pt, 1, 1, 1;\n"
        "add.s64 dt, w1d, 512; wgmma.mma_async.sync.aligned.m64n64k16.f16.f16.f16 {qz0,qz1,qz2,qz3,qz4,qz5,qz6,qz7,qz8,qz9,qz10,qz11,qz12,qz13,qz14,qz15}, {qa16,qa17,qa18,qa19}, dt, pt, 1, 1, 1;\n"
        "add.s64 dt, w1d, 640; wgmma.mma_async.sync.aligned.m64n64k16.f16.f16.f16 {qz0,qz1,qz2,qz3,qz4,qz5,qz6,qz7,qz8,qz9,qz10,qz11,qz12,qz13,qz14,qz15}, {qa20,qa21,qa22,qa23}, dt, pt, 1, 1, 1;\n"
        "SKIP2:\n"
        "wgmma.fence.sync.aligned;\n"
        "wgmma.commit_group.sync.aligned;\n"
        "@pz bra.uni B90;\n"
        "mov.b32 {xl, xh}, a0; tanh.approx.f16 xr, xl; cvt.u32.u16 lo0, xr; tanh.approx.f16 xr, xh; cvt.u32.u16 hi0, xr; fma.rn.f16x2 p0, qz24, qz24, c; mul.rn.f16x2 a1, qz23, p1; fma.rn.f16x2 g4, qz20, h0, qz20; prmt.b32 h1, lo1, hi1, 0x5410;\n"
        "mov.b32 {xl, xh}, a1; tanh.approx.f16 xr, xl; cvt.u32.u16 lo1, xr; tanh.approx.f16 xr, xh; cvt.u32.u16 hi1, xr; fma.rn.f16x2 p1, qz25, qz25, c; mul.rn.f16x2 a0, qz24, p0; fma.rn.f16x2 g5, qz21, h1, qz21; prmt.b32 h0, lo0, hi0, 0x5410;\n"
        "mov.b32 {xl, xh}, a0; tanh.approx.f16 xr, xl; cvt.u32.u16 lo0, xr; tanh.approx.f16 xr, xh; cvt.u32.u16 hi0, xr; fma.rn.f16x2 p0, qz26, qz26, c; mul.rn.f16x2 a1, qz25, p1; fma.rn.f16x2 g6, qz22, h0, qz22; prmt.b32 h1, lo1, hi1, 0x5410;\n"
        "mov.b32 {xl, xh}, a1; tanh.approx.f16 xr, xl; cvt.u32.u16 lo1, xr; tanh.approx.f16 xr, xh; cvt.u32.u16 hi1, xr; fma.rn.f16x2 p1, qz27, qz27, c; mul.rn.f16x2 a0, qz26, p0; fma.rn.f16x2 g7, qz23, h1, qz23; prmt.b32 h0, lo0, hi0, 0x5410;\n"
        "B90:\n"
        "wgmma.wait_group.sync.aligned 3;\n"
        "wgmma.fence.sync.aligned;\n"
        "add.s64 dt, w2d, 1344; wgmma.mma_async.sync.aligned.m64n96k16.f16.f16.f16 {o0,o1,o2,o3,o4,o5,o6,o7,o8,o9,o10,o11,o12,o13,o14,o15,o16,o17,o18,o19,o20,o21,o22,o23}, {g4,g5,g6,g7}, dt, pt, 1, 1, 1;\n"
        "wgmma.commit_group.sync.aligned;\n"
        "@pz bra.uni B94;\n"
        "mov.b32 {xl, xh}, a0; tanh.approx.f16 xr, xl; cvt.u32.u16 lo0, xr; tanh.approx.f16 xr, xh; cvt.u32.u16 hi0, xr; fma.rn.f16x2 p0, qz28, qz28, c; mul.rn.f16x2 a1, qz27, p1; fma.rn.f16x2 g8, qz24, h0, qz24; prmt.b32 h1, lo1, hi1, 0x5410;\n"
        "mov.b32 {xl, xh}, a1; tanh.approx.f16 xr, xl; cvt.u32.u16 lo1, xr; tanh.approx.f16 xr, xh; cvt.u32.u16 hi1, xr; fma.rn.f16x2 p1, qz29, qz29, c; mul.rn.f16x2 a0, qz28, p0; fma.rn.f16x2 g9, qz25, h1, qz25; prmt.b32 h0, lo0, hi0, 0x5410;\n"
        "mov.b32 {xl, xh}, a0; tanh.approx.f16 xr, xl; cvt.u32.u16 lo0, xr; tanh.approx.f16 xr, xh; cvt.u32.u16 hi0, xr; fma.rn.f16x2 p0, qz30, qz30, c; mul.rn.f16x2 a1, qz29, p1; fma.rn.f16x2 g10, qz26, h0, qz26; prmt.b32 h1, lo1, hi1, 0x5410;\n"
        "mov.b32 {xl, xh}, a1; tanh.approx.f16 xr, xl; cvt.u32.u16 lo1, xr; tanh.approx.f16 xr, xh; cvt.u32.u16 hi1, xr; fma.rn.f16x2 p1, qz31, qz31, c; mul.rn.f16x2 a0, qz30, p0; fma.rn.f16x2 g11, qz27, h1, qz27; prmt.b32 h0, lo0, hi0, 0x5410;\n"
        "B94:\n"
        "wgmma.wait_group.sync.aligned 1;\n"
        "wgmma.fence.sync.aligned;\n"
        "add.s64 dt, w2d, 1408; wgmma.mma_async.sync.aligned.m64n96k16.f16.f16.f16 {o0,o1,o2,o3,o4,o5,o6,o7,o8,o9,o10,o11,o12,o13,o14,o15,o16,o17,o18,o19,o20,o21,o22,o23}, {g8,g9,g10,g11}, dt, pt, 1, 1, 1;\n"
        "wgmma.commit_group.sync.aligned;\n"
        "@pz bra.uni B2;\n"
        "mov.b32 {xl, xh}, a0; tanh.approx.f16 xr, xl; cvt.u32.u16 lo0, xr; tanh.approx.f16 xr, xh; cvt.u32.u16 hi0, xr; fma.rn.f16x2 p0, qz0, qz0, c; mul.rn.f16x2 a1, qz31, p1; fma.rn.f16x2 g12, qz28, h0, qz28; prmt.b32 h1, lo1, hi1, 0x5410;\n"
        "mov.b32 {xl, xh}, a1; tanh.approx.f16 xr, xl; cvt.u32.u16 lo1, xr; tanh.approx.f16 xr, xh; cvt.u32.u16 hi1, xr; fma.rn.f16x2 p1, qz1, qz1, c; mul.rn.f16x2 a0, qz0, p0; fma.rn.f16x2 g13, qz29, h1, qz29; prmt.b32 h0, lo0, hi0, 0x5410;\n"
        "mov.b32 {xl, xh}, a0; tanh.approx.f16 xr, xl; cvt.u32.u16 lo0, xr; tanh.approx.f16 xr, xh; cvt.u32.u16 hi0, xr; fma.rn.f16x2 p0, qz2, qz2, c; mul.rn.f16x2 a1, qz1, p1; fma.rn.f16x2 g14, qz30, h0, qz30; prmt.b32 h1, lo1, hi1, 0x5410;\n"
        "mov.b32 {xl, xh}, a1; tanh.approx.f16 xr, xl; cvt.u32.u16 lo1, xr; tanh.approx.f16 xr, xh; cvt.u32.u16 hi1, xr; fma.rn.f16x2 p1, qz3, qz3, c; mul.rn.f16x2 a0, qz2, p0; fma.rn.f16x2 g15, qz31, h1, qz31; prmt.b32 h0, lo0, hi0, 0x5410;\n"
        "B2:\n"
        "wgmma.fence.sync.aligned;\n"
        "add.s64 dt, w2d, 1472; wgmma.mma_async.sync.aligned.m64n96k16.f16.f16.f16 {o0,o1,o2,o3,o4,o5,o6,o7,o8,o9,o10,o11,o12,o13,o14,o15,o16,o17,o18,o19,o20,o21,o22,o23}, {g12,g13,g14,g15}, dt, pt, 1, 1, 1;\n"
        "wgmma.commit_group.sync.aligned;\n"
        "@pz bra.uni BE;\n"
        "mov.b32 {xl, xh}, a0; tanh.approx.f16 xr, xl; cvt.u32.u16 lo0, xr; tanh.approx.f16 xr, xh; cvt.u32.u16 hi0, xr; fma.rn.f16x2 p0, qz4, qz4, c; mul.rn.f16x2 a1, qz3, p1; fma.rn.f16x2 g0, qz0, h0, qz0; prmt.b32 h1, lo1, hi1, 0x5410;\n"
        "mov.b32 {xl, xh}, a1; tanh.approx.f16 xr, xl; cvt.u32.u16 lo1, xr; tanh.approx.f16 xr, xh; cvt.u32.u16 hi1, xr; fma.rn.f16x2 p1, qz5, qz5, c; mul.rn.f16x2 a0, qz4, p0; fma.rn.f16x2 g1, qz1, h1, qz1; prmt.b32 h0, lo0, hi0, 0x5410;\n"
        "mov.b32 {xl, xh}, a0; tanh.approx.f16 xr, xl; cvt.u32.u16 lo0, xr; tanh.approx.f16 xr, xh; cvt.u32.u16 hi0, xr; fma.rn.f16x2 p0, qz6, qz6, c; mul.rn.f16x2 a1, qz5, p1; fma.rn.f16x2 g2, qz2, h0, qz2; prmt.b32 h1, lo1, hi1, 0x5410;\n"
        "mov.b32 {xl, xh}, a1; tanh.approx.f16 xr, xl; cvt.u32.u16 lo1, xr; tanh.approx.f16 xr, xh; cvt.u32.u16 hi1, xr; fma.rn.f16x2 p1, qz7, qz7, c; mul.rn.f16x2 a0, qz6, p0; fma.rn.f16x2 g3, qz3, h1, qz3; prmt.b32 h0, lo0, hi0, 0x5410;\n"
        "BE:\n"
        "wgmma.wait_group.sync.aligned 0;\n"
        "bra.uni LOOP;\n"
        "STORE:\n"
        "bar.sync tt, 128;\n"
        "setp.lt.s32 pr, n, 0;\n"
        "@pr bra.uni STOREB;\n"
        "cvt.u64.u32 gp, off; add.s64 gp, gp, %11;\n"
        "elect.sync _|pr, 0xffffffff;\n"
        "@pr cp.async.bulk.global.shared::cta.bulk_group [gp], [%4], 12288;\n"
        "@pr cp.async.bulk.commit_group;\n"
        "bra.uni STOREB;\n"
        "YLOAD:\n"
        "@!pm bra.uni YLOADP;\n"
        "cp.async.bulk.wait_group.read 0;\n"
        "sub.u32 ad, off, %12; cvt.u64.u32 gp, ad; add.s64 gp, gp, %11;\n"
        "elect.sync _|pr, 0xffffffff;\n"
        "@pr mbarrier.arrive.expect_tx.shared::cta.b64 _, [ybar], 12288;\n"
        "@pr cp.async.bulk.shared::cluster.global.mbarrier::complete_tx::bytes [%4], [gp], 12288, [ybar];\n"
        "YLOADP:\n"
        "cvt.u64.u32 gp, off; add.s64 gp, gp, %10;\n"
        "elect.sync _|pr, 0xffffffff;\n"
        "@pr cp.async.bulk.prefetch.L2.global.L2::cache_hint [gp], 12288, pol;\n"
        "bra.uni YLOADB;\n"
        "XLOAD:\n"
        "bar.sync tt, 128;\n"
        "cp.async.bulk.wait_group.read 0;\n"
        "cvt.u64.u32 gp, off; add.s64 gp, gp, %10;\n"
        "elect.sync _|pr, 0xffffffff;\n"
        "@pr mbarrier.arrive.expect_tx.shared::cta.b64 _, [xbar], 12288;\n"
        "@pr cp.async.bulk.shared::cluster.global.mbarrier::complete_tx::bytes.L2::cache_hint [%4], [gp], 12288, [xbar], pol;\n"
        "bra.uni XLOADB;\n"
        "SPINY: mov.u32 cnt, 0;\n"
        "SPINYL:\n"
        "add.u32 tt, n, 1; and.b32 tt, tt, 1; mbarrier.try_wait.parity.shared::cta.b64 pw, [ybar], tt;\n"
        "@pw bra.uni BACKY;\n"
        "add.u32 cnt, cnt, 1; setp.lt.u32 pw, cnt, 0x100000;\n"
        "@pw bra.uni SPINYL;\n"
        "trap;\n"
        "SPINX: mov.u32 cnt, 0;\n"
        "SPINXL:\n"
        "and.b32 tt, n, 1; mbarrier.try_wait.parity.shared::cta.b64 pw, [xbar], tt;\n"
        "@pw bra.uni BACKX;\n"
        "add.u32 cnt, cnt, 1; setp.lt.u32 pw, cnt, 0x100000;\n"
        "@pw bra.uni SPINXL;\n"
        "trap;\n"
        "SPINT: mov.u32 cnt, 0;\n"
        "SPINTL:\n"
        "mad.lo.u32 tt, n, 8, tbar; mbarrier.try_wait.parity.shared::cta.b64 pw, [tt], tpar;\n"
        "@pw bra.uni BACKT;\n"
        "add.u32 cnt, cnt, 1; setp.lt.u32 pw, cnt, 0x100000;\n"
        "@pw bra.uni SPINTL;\n"
        "trap;\n"
        "DONE:\n"
        "wgmma.wait_group.sync.aligned 0;\n"
        "}\n"
        :: "r"(prm.w1desc), "r"(prm.w2desc), "r"(c.wg), "r"(c.off), "r"(c.xs), "r"(c.a_offs), "r"(c.xs_offs), "r"(c.bias_addr),
           "r"(c.out_scale), "r"(c.w), "l"(prm.x), "l"(prm.out), "r"(c.step)
        : "memory");
}

__device__ __forceinline__ void start_first_tile(const Pass2& c, const Params& prm) {
    if (c.wg == 3) mbar_wait_c<0>(sb + SM_BAR + (BAR_Y2FULL + 3) * 8);
    first_gemm(c.xs, c.a_offs, prm.w1desc);
}

__device__ __forceinline__ float warp_sum(float v) {
#pragma unroll
    for (int s = 16; s >= 1; s >>= 1) v += __shfl_xor_sync(0xffffffffu, v, s);
    return v;
}
__device__ __forceinline__ float pow2f(int e) { return __uint_as_float((uint32_t)(e + 127) << 23); }
__device__ __forceinline__ int exponent_of(float v) { return (int)(__float_as_uint(v) >> 23) - 127; }
__device__ __forceinline__ float lds_bf16(uint32_t addr) {
    uint16_t v; asm volatile("ld.shared.u16 %0, [%1];" : "=h"(v) : "r"(addr) : "memory"); return bf_lo(v);
}

__device__ __forceinline__ void publish_bias(const Params& prm, uint32_t c, uint32_t tag) {
    const uint32_t lane = fresh_tid() & 31;
    const uint32_t col = sb + SM_W2 + (c >> 5) * 24576 + lane * 64 + ((((c >> 3) ^ (lane >> 1)) & 3) * 16) + (c & 7) * 2;
    float v = 0.0f;
#pragma unroll
    for (int k = 0; k < EX / 32; k++) v = fmaf(lds_bf16(col + k * 2048), lds_bf16(sb + SM_BETA + lane * 2 + k * 64), v);
    v = warp_sum(v);
    if (lane == 0) asm volatile("st.relaxed.gpu.global.v2.b32 [%0], {%1, %2};" ::"l"(prm.g->bias + c), "f"(v), "r"(tag) : "memory");
}
__device__ __forceinline__ void collect_bias(const Params& prm, uint32_t tag) {
    const uint32_t lane = fresh_tid() & 31;
    if (lane < 24) {
        const unsigned long long* src = prm.g->bias + 32 * (lane >> 3) + 8 * (lane & 3) + (lane & 4);
        uint32_t v[4], t[4], spins = 0;
        for (;;) {
#pragma unroll
            for (int k = 0; k < 4; k++)
                asm volatile("ld.relaxed.gpu.global.v2.b32 {%0, %1}, [%2];" : "=r"(v[k]), "=r"(t[k]) : "l"(src + k) : "memory");
            if (t[0] == tag && t[1] == tag && t[2] == tag && t[3] == tag) break;
            if (++spins > (1u << 22)) __trap();
        }
        sts128(sb + SM_BIAS + lane * 16, v[0], v[1], v[2], v[3]);
    }
    __syncwarp();
}
__device__ __forceinline__ float fetch_w2_row(uint32_t (&u)[12][4], uint32_t row, uint32_t sw) {
    uint32_t mx[4] = {};
#pragma unroll
    for (int a = 0; a < 3; a++)
#pragma unroll
        for (int k = 0; k < 4; k++) {
            asm volatile("ld.shared.v4.b32 {%0,%1,%2,%3}, [%4];"
                         : "=r"(u[a * 4][k]), "=r"(u[a * 4 + 1][k]), "=r"(u[a * 4 + 2][k]), "=r"(u[a * 4 + 3][k])
                         : "r"(row + a * 24576 + ((k * 16) ^ sw)) : "memory");
#pragma unroll
            for (int b = 0; b < 4; b++) asm("max.xorsign.abs.bf16x2 %0, %0, %1;" : "+r"(mx[b]) : "r"(u[a * 4 + b][k]));
        }
#pragma unroll
    for (int b = 1; b < 4; b++) asm("max.xorsign.abs.bf16x2 %0, %0, %1;" : "+r"(mx[0]) : "r"(mx[b]));
    return fmaxf(fabsf(bf_lo(mx[0])), fabsf(bf_hi(mx[0])));
}

__device__ __forceinline__ bool grn_stats(float ss, float gm, float bt, float top, float& gx, float& inv, int& eo) {
    const int warp = fresh_warp();
    gx = sqrt_fast(fmaf(ss, INV_2A * INV_2A, 1e-6f));
    const float rt = sqrt_fast(ss + 1.0f) * INV_2A * top;
    const float r[3] = {warp_sum(gx), warp_sum(fmaf(bt, top, rt)), warp_sum(rt * fabsf(gm) * gx)};
    if ((fresh_tid() & 31) == 0 && warp < 12) {
#pragma unroll
        for (int k = 0; k < 3; k++) sts32(sb + SM_SEL + (k * 12 + warp) * 4, __float_as_uint(r[k]));
    }
    MARK(6);
    const bool bad = __syncthreads_or(!(ss >= 16.0f && ss < ACC_LIMIT));
    MARK(7);
    float tot[3];
#pragma unroll
    for (int k = 0; k < 3; k++) {
        uint32_t v[12];
#pragma unroll
        for (int q = 0; q < 3; q++) lds128(v + 4 * q, sb + SM_SEL + k * 48 + q * 16);
        float p[4];
#pragma unroll
        for (int q = 0; q < 4; q++) p[q] = __uint_as_float(v[q]) + __uint_as_float(v[q + 4]) + __uint_as_float(v[q + 8]);
        tot[k] = (p[0] + p[1]) + (p[2] + p[3]);
    }
    inv = __fdividef(1.0f, fmaf(tot[0], 1.0f / EX, 1e-6f));
    eo = min(max(exponent_of(fmaf(tot[2], inv, tot[1])), -90), 126) - 14;
    return bad;
}

__device__ __forceinline__ float exact_sums(const Params& prm, int e) {
    const int lane = fresh_tid() & 31, warp = fresh_warp(), wg = warp >> 2;
    const uint32_t epoch = lds32(sb + SM_RED + (RED_EPOCH + 1) * 4), bar = sb + SM_BAR + BAR_W1 * 8;
    if (wg < 3) {
        uint32_t wa[2][24], d[2][16];
        float acc[2][2] = {};
        const uint32_t yd = prm.ydesc + ((SM_SPARE - SM_Y1) >> 4), wd = prm.w1desc + ((2 * wg * 12288 + 5 * 2048) >> 4);
        load_w1t(wa, wg, warp & 3, lane);
#pragma unroll 1
        for (int n = 0; n < ROWS_PER_CTA; n++) {
            if (warp == 0) {
                expect_tx(bar, TILE_BYTES);
                bulk_load(sb + SM_SPARE, (const char*)prm.out + (cta_tile0(fresh_cta()) + n * cta_stride(fresh_cta())), TILE_BYTES, bar);
            }
            mbar_wait(bar, (n + 1) & 1);
            gemm1_t<0>(d[0], wa[0], yd, wd);
            gemm1_t<1>(d[1], wa[1], yd, wd);
            wg_wait<0>();
            pin(d[0]); pin(d[1]);
            gelu_sumsq_f(d[0], acc[0]);
            gelu_sumsq_f(d[1], acc[1]);
            named_sync(1, 384);
        }
        publish_sums(acc, prm.g->sums[epoch & 1], &prm.g->count[1], wg, warp & 3, lane);
    }
    grid_wait(&prm.g->count[1], (epoch + 1) * NUM_CTAS);
    return __ldcg(prm.g->sums[epoch & 1] + e);
}

__global__ void __launch_bounds__(512, 1) convnext_kernel(const __grid_constant__ Params prm) {
    extern __shared__ __align__(1024) uint8_t smem[];
    if ((uint32_t)__cvta_generic_to_shared(smem) != sb) __trap();
    if (fresh_warp() >= 12) {
        Producer pc;
        SMARK(0);
        asm volatile("setmaxnreg.inc.sync.aligned.u32 %0;" ::"n"(PRODUCER_REGS));
        SMARK(1);
        const int w = fresh_warp() & 3, lane = fresh_tid() & 31;
        const int j = lane & 7, hb = (lane >> 3) & 1, base = 4 * (2 * w + (lane >> 4));
        pc.lane = lane; pc.warp = w;
        pc.xoff[0] = hb * XHALF_B + base * 192 + j * 16;
        pc.xoff[1] = hb * XHALF_B + base * 192 + 128 + j * 8;
        const int grp = 4 * w + (lane >> 3);
#pragma unroll
        for (int o = 0; o < 2; o++) {
            const int row = (grp & 7) + 8 * (o ^ hb) + 32 * (grp >> 3);
            pc.yoff[0][o] = row * 128 + ((j ^ (row & 7)) * 16);
            pc.yoff[1][o] = 8192 + row * 64 + (((j >> 1) ^ ((row >> 1) & 3)) * 16) + (j & 1) * 8;
        }
        pc.stat = sb + SM_STAT + (8 * w + (lane >> 2)) * 32;
        pc.own = pc.stat + (lane & 3) * 8;
        const int dstep = fresh_cta() & 8 ? 3 * CH * 2 : -3 * CH * 2;
        named_sync(0, 512);
        mbar_wait_c<0>(sb + SM_BAR + BAR_DUMMY * 8);
        SMARK(8);
#pragma unroll
        for (int tap = 0; tap < 9; tap++) {
            const uint32_t dw = sb + SM_Y1 + (3 + tap % 3) * CH * 2 + (tap / 3 - 1) * dstep;
            lds128(pc.w[tap], dw + j * 16);
            asm volatile("ld.shared.v2.b32 {%0,%1}, [%2];" : "=r"(pc.w[tap][4]), "=r"(pc.w[tap][5]) : "r"(dw + 128 + j * 8) : "memory");
        }
#pragma unroll
        for (int tap = 0; tap < 9; tap++)
#pragma unroll
            for (int u = 0; u < 6; u++) pc.w[tap][u] = bf2_mul(pc.w[tap][u], TAP_SCALE_BF2);
        produce(pc, prm);
        TS(9);
        asm volatile("setmaxnreg.dec.sync.aligned.u32 %0;" ::"n"(EVEN_REGS));
        if (fresh_warp() == 12) {
            mbar_wait_c<0>(sb + SM_BAR + BAR_W2 * 8);
            if (fresh_cta() < CH) publish_bias(prm, fresh_cta(), lds32(sb + SM_RED + RED_EPOCH * 4) + 1);
        }
    } else {
        asm volatile("setmaxnreg.dec.sync.aligned.u32 %0;" ::"n"(CONSUMER_REGS));
        {
            const int tid = fresh_tid(), warp = fresh_warp(), lane = tid & 31;
            uint32_t cnt[2];
            if (warp == 0) {
                if (lane == 0) {
#pragma unroll
                    for (int k = 0; k < NX; k++) {
                        mbar_init(sb + SM_XFULL + k * SLOT_BYTES, 2);
                        mbar_init(sb + SM_Y1FULL + k * SLOT_BYTES, 4);
                        mbar_init(sb + SM_Y1EMPTY + k * SLOT_BYTES, 12);
                    }
                    mbar_init(sb + SM_BAR + BAR_DUMMY * 8, 1);
                    mbar_init(sb + SM_BAR + BAR_W1 * 8, 1);
                    fence_async_smem();
                }
                __syncwarp();
                asm volatile("bar.arrive 0, 512;" ::: "memory");
                expect_tx(sb + SM_BAR + BAR_DUMMY * 8, 9 * CH * 2);
                bulk_load(sb + SM_Y1, prm.dw, 9 * CH * 2, sb + SM_BAR + BAR_DUMMY * 8);
                bulk_prefetch((const char*)prm.w1 + fresh_cta() * (CH * EX * 2 / NUM_CTAS), CH * EX * 2 / NUM_CTAS);
                const RowCopy rc = row_copy(prm);
#pragma unroll
                for (int k = 0; k <= NX; k++) {
                    if (k == W1POS) {
                        expect_tx(sb + SM_BAR + BAR_W1 * 8, CH * EX * 2);
#pragma unroll
                        for (int q = 0; q < 6; q++) {
                            const uint32_t r = ROT ? (q + fresh_cta()) % 6 : q;
                            tma_load_2d(sb + SM_W1 + r * 12288, &prm.w1_map, 64 * r, 0, sb + SM_BAR + BAR_W1 * 8);
                        }
                    }
                    if (k < NX) issue_row_load(rc, k, k);
                    if (k == PRE) bulk_prefetch(rc.x0 + 192 + NX * rc.stride, TILE_BYTES);
                }
                SMARK(4);
            } else if (warp == 1) {
                if (lane < 2) asm volatile("prefetch.tensormap [%0];" ::"l"(&prm.w1_map + lane) : "memory");
            } else if (warp == 3) {
                const uint32_t one = (lane & 5) == ((lane & 8) >> 1) + (lane >> 4) ? 0x3f803f80u : 0u;
                sts128(sb + SM_SEL + lane * 16, one, one, one, one);
                fence_async_smem();
            } else if (tid - 128u < NX * 12 && ((fresh_cta() + 1) & 7) < 2) {
                const int k = tid - 128;
                sts128(sb + SM_X + (k / 12) * SLOT_BYTES + ((fresh_cta() & 7) == 0 ? 0 : XHALF_B + 33 * 192) + (k % 12) * 16, 0, 0, 0, 0);
            }
            __syncwarp();
            asm volatile("ld.relaxed.gpu.global.v2.u32 {%0, %1}, [%2];" : "=r"(cnt[0]), "=r"(cnt[1]) : "l"(prm.g->count) : "memory");
            SMARK(0);
            if (warp != 0) named_sync(0, 512);
            if (tid == 256) {
                sts64(sb + SM_RED + RED_EPOCH * 4, cnt[0], cnt[1] / NUM_CTAS);
#pragma unroll
                for (int k = 0; k < BAR_COUNT; k++)
                    if (k != BAR_W1 && k != BAR_DUMMY) mbar_init(sb + SM_BAR + k * 8, k < BAR_TURN ? 1 : 4);
#pragma unroll
                for (int k = 0; k < 3; k++) mbar_arrive_if(sb + SM_BAR + (BAR_Y2FULL + k) * 8, true);
            }
            if (fresh_cta() == 0) *acc_word(prm, cnt[0] + 1, tid) = 0;
            if (fresh_cta() == 1) prm.g->sums[~(cnt[1] / NUM_CTAS) & 1][tid] = 0.0f;
            __syncwarp();
            SMARK(1);
            mbar_wait_c<0>(sb + SM_BAR + BAR_W1 * 8);
            SMARK(2);
        }

        const int tid = fresh_tid(), lane = tid & 31, wg = fresh_warp() >> 2, w = fresh_warp() & 3;
        float acc[2][2];
        const int c = 8 * (lane >> 4) + (lane & 7), ck = 2 * w + ((lane >> 3) & 1);
        consume(acc, sb + SM_W1 + 2 * wg * 12288 + c * 128 + ((ck ^ (c & 7)) * 16), prm.ydesc,
                prm.w1desc + (((2 * wg + 1) * 12288 + 5 * 2048) >> 4), wg * SLOT_BYTES, make_duty(prm, wg, w), w, lane, prm);
        publish_fast(prm, acc, lds32(sb + SM_RED + RED_EPOCH * 4), wg, w, lane);
        MARK(0);
        bulk_wait_all();
        if (wg == 0) TS(3);
        asm volatile("setmaxnreg.inc.sync.aligned.u32 %0;" ::"n"(EVEN_REGS));
    }

    {
        asm volatile(".reg .b32 qa<24>, qz<32>;");
        Pass2 c;
        const int tid = fresh_tid(), lane = tid & 31, warp = fresh_warp(), wg = warp >> 2, w = warp & 3, e = min(tid, EX - 1);
        const int arow = 16 * w + (lane & 15);
        c.wg = wg;
        c.off = cta_tile0(fresh_cta()) + (ROWS_PER_CTA - 1 - wg) * cta_stride(fresh_cta());
        c.step = 4 * cta_stride(fresh_cta());
        c.xs = wg == 3 ? sb + SM_BUF3 : sb + SM_Y1 + (wg == 2 ? 2 : 1 - wg) * SLOT_BYTES;
        static_assert((ROWS_PER_CTA - 1) % NX == 1, "slot of the last tile");
        c.a_offs = (arow * 128 + (((lane >> 4) ^ (arow & 7)) * 16)) |
                   (8192 + arow * 64 + (((lane >> 4) ^ ((arow >> 1) & 3)) * 16)) << 16;
        const int g = lane >> 2, px = 33 * (g & 1) + 4 * (g >> 1) + 16 * (w >> 1) + 2 * (w & 1);
        c.xs_offs = (px * 192 + (lane & 3) * 16) | ((px ^ 1) * 192 + (lane & 3) * 16) << 16;
        c.bias_addr = sb + SM_BIAS + (lane & 3) * 16;
        c.w = w;
        const uint32_t epoch = lds32(sb + SM_RED + RED_EPOCH * 4);
        MARK(1);
        if (warp == 6) {
            const uint32_t bar = sb + SM_BAR + (BAR_Y2FULL + 3) * 8;
            expect_tx(bar, TILE_BYTES);
            bulk_load(sb + SM_BUF3, (const char*)prm.out + (c.off - c.step / 2), TILE_BYTES, bar);
        }
        mbar_wait_c<0>(sb + SM_BAR + BAR_W2 * 8);
        const float gm = lds_bf16(sb + SM_GAMMA + e * 2), bt = fabsf(lds_bf16(sb + SM_BETA + e * 2));
        const uint32_t w2row = sb + SM_W2 + e * 64, sw = ((e >> 1) & 3) * 16;
        uint32_t u[12][4];
        float top = 0.0f, ss = 16.0f;
        if (wg < 3) top = fetch_w2_row(u, w2row, sw);
        if (warp == 12) collect_bias(prm, epoch + 1);
        MARK(3);
        start_first_tile(c, prm);
        MARK(4);
        if (wg < 3) ss = collect_fast(acc_word(prm, epoch, e));
        if (warp == 0) TS(4);
        MARK(5);
        float gx, inv;
        int eo;
        if (grn_stats(ss, gm, bt, top, gx, inv, eo) || FORCE_EXACT) {
            wg_wait<0>();
            grn_stats(exact_sums(prm, e), gm, bt, top, gx, inv, eo);
            fetch_w2_row(u, w2row, sw);
            start_first_tile(c, prm);
            __syncthreads();
        }
        MARK(8);
        if (tid == 416 && fresh_cta() == 0) prm.g->count[0] = epoch + 1;
        const float up = pow2f(eo), dn = pow2f(-eo);
        c.out_scale = pack_bf2(up, up);
        if (wg < 3) {
            float sc = fmaf(gm, gx * inv, 1.0f) * INV_2A;
            if (eo > 6) {
                const uint32_t dn2 = pack_bf2(dn, dn);
#pragma unroll
                for (int k = 0; k < 48; k++) u[k >> 2][k & 3] = bf2_mul(u[k >> 2][k & 3], dn2);
            } else {
                sc *= dn;
            }
            const uint32_t s2 = pack_bf2(sc * 0x1p-112f, sc * 0x1p-112f);
#pragma unroll
            for (int k = 0; k < 12; k++) {
                uint32_t v[4];
#pragma unroll
                for (int b = 0; b < 4; b++) {
                    v[b] = bf2_mul(u[k][b], s2);
                    v[b] += (v[b] & 0x7fff7fffu) * 7u;
                }
                sts128(w2row + (k >> 2) * 24576 + (((k & 3) * 16) ^ sw), v[0], v[1], v[2], v[3]);
            }
        } else if (w == 0 && lane < 24) {
            uint32_t b[4];
            lds128(b, sb + SM_BIAS + lane * 16);
            const uint32_t p0 = pack_h2(__uint_as_float(b[0]) * dn, __uint_as_float(b[1]) * dn);
            const uint32_t p1 = pack_h2(__uint_as_float(b[2]) * dn, __uint_as_float(b[3]) * dn);
            sts128(sb + SM_BIAS + lane * 16, p0, p0, p1, p1);
        }
        MARK(9);
        fence_async_smem();
        __syncthreads();
        MARK(10);

        if (wg == 0) TS(5);
        pass2_tiles(c, prm);
        bulk_wait_read<0>();
        MARK(13);
    }
}

}

extern "C" void kernel_launch(void* const* d_in, const int* in_sizes, int n_in, void* d_out, int out_size) {
    (void)in_sizes; (void)n_in; (void)out_size;
    typedef CUresult (*EncodeFn)(CUtensorMap*, CUtensorMapDataType, cuuint32_t, void*, const cuuint64_t*, const cuuint64_t*,
                                 const cuuint32_t*, const cuuint32_t*, CUtensorMapInterleave, CUtensorMapSwizzle,
                                 CUtensorMapL2promotion, CUtensorMapFloatOOBfill);
    void* fn = nullptr;
    cudaDriverEntryPointQueryResult status;
    cudaGetDriverEntryPoint("cuTensorMapEncodeTiled", &fn, cudaEnableDefault, &status);
    const EncodeFn encode = (EncodeFn)fn;
    const cuuint32_t ones[2] = {1, 1};

    Params p;
    {
        const cuuint64_t dims[2] = {EX, CH}, strides[1] = {EX * 2};
        const cuuint32_t box[2] = {64, CH};
        encode(&p.w1_map, CU_TENSOR_MAP_DATA_TYPE_BFLOAT16, 2, d_in[2], dims, strides, box, ones,
               CU_TENSOR_MAP_INTERLEAVE_NONE, CU_TENSOR_MAP_SWIZZLE_128B, CU_TENSOR_MAP_L2_PROMOTION_NONE,
               CU_TENSOR_MAP_FLOAT_OOB_FILL_NONE);
    }
    {
        const cuuint64_t dims[2] = {CH, EX}, strides[1] = {CH * 2};
        const cuuint32_t box[2] = {32, 192};
        encode(&p.w2_map, CU_TENSOR_MAP_DATA_TYPE_BFLOAT16, 2, d_in[3], dims, strides, box, ones,
               CU_TENSOR_MAP_INTERLEAVE_NONE, CU_TENSOR_MAP_SWIZZLE_64B, CU_TENSOR_MAP_L2_PROMOTION_NONE,
               CU_TENSOR_MAP_FLOAT_OOB_FILL_NONE);
    }
    p.x = (const __nv_bfloat16*)d_in[0];
    p.dw = (const __nv_bfloat16*)d_in[1];
    p.w1 = (const __nv_bfloat16*)d_in[2];
    p.gamma = (const __nv_bfloat16*)d_in[4];
    p.beta = (const __nv_bfloat16*)d_in[5];
    p.out = (__nv_bfloat16*)d_out;
    cudaGetSymbolAddress((void**)&p.g, g_scratch);
    p.w1desc = desc_lo(sb + SM_W1, 12288);
    p.w2desc = desc_lo(sb + SM_W2, 24576);
    p.ydesc = desc_lo(sb + SM_Y1, 16);
    p.ydesc64[0] = (0x40000040ull << 32) | p.ydesc;
    p.ydesc64[1] = (0x80000020ull << 32) | (p.ydesc + 512);
    for (int k = 0; k < 3; k++) p.sel[k] = (8ull << 32) | desc_lo(sb + SM_SEL + k * 128, k == 2 ? 128 : 0);
    constexpr int smem_bytes = SM_TOTAL;
    cudaFuncSetAttribute(convnext_kernel, cudaFuncAttributeMaxDynamicSharedMemorySize, smem_bytes);
    convnext_kernel<<<NUM_CTAS, 512, smem_bytes>>>(p);
}
```

```cpp
#include <cuda.h>
#include <cuda_runtime.h>
#include <cuda_bf16.h>
#include <stdint.h>

namespace {

constexpr int IMG_W = 512, CH = 96, EX = 384;
constexpr int TILE_PX = 64;
constexpr int ROWS_PER_CTA = 32;
constexpr int NUM_CTAS = 128;
constexpr int STEPS = ROWS_PER_CTA + 2;
constexpr int ROW_BYTES = IMG_W * CH * 2;

#define FORCE_EXACT 0
#define HOLD 1
#define ENDREAD 1
#define STAGED 0
#define ROT 0
#define PRE 9
#define W1POS 3
#define PREGS 200
#define CREGS 104
constexpr int PRODUCER_REGS = PREGS, CONSUMER_REGS = CREGS, EVEN_REGS = 128;

constexpr int XHALF_BYTES = 34 * 192;
constexpr int XHALF_B = XHALF_BYTES + 64;
constexpr int XROW_BYTES = XHALF_B + XHALF_BYTES + 64;
constexpr int L2_AHEAD = 2;
constexpr int NX = 3;
constexpr int TILE_BYTES = TILE_PX * 192;
constexpr int NY1 = 3;

constexpr uint32_t sb = 1024;
constexpr int SM_W1 = 0;
constexpr int SM_W2 = 73728;
constexpr int SM_RING = 147456;
constexpr int SLOT_BYTES = 26624;
constexpr int SM_Y1 = SM_RING;
constexpr int SM_X = SM_Y1 + TILE_BYTES;
constexpr int SM_STAT = SM_X + XROW_BYTES;
constexpr int SM_XFULL = SM_STAT + TILE_PX * 16, SM_Y1FULL = SM_XFULL + 8, SM_Y1EMPTY = SM_XFULL + 16;
constexpr int SM_BUF3 = SM_X + SLOT_BYTES, SM_SPARE = SM_X;
constexpr int SM_SEL = SM_RING + NX * SLOT_BYTES;
constexpr int SM_BIAS = SM_SEL + 512;
constexpr int SM_GAMMA = SM_BIAS + 384;
constexpr int SM_BETA = SM_GAMMA + EX * 2;
constexpr int SM_RED = SM_BETA + EX * 2;
constexpr int SM_BAR = SM_RED + 16;
constexpr int BAR_Y2FULL = 0, BAR_XSFULL = 4, BAR_W1 = 8, BAR_W2 = 9, BAR_DUMMY = 10, BAR_TURN = 11, BAR_ROWS = 51,
              BAR_STAT = 53, BAR_COUNT = 54;
constexpr int SM_TOTAL = SM_BAR + BAR_COUNT * 8;
static_assert(SM_Y1EMPTY + 8 <= SM_RING + SLOT_BYTES && XROW_BYTES >= TILE_BYTES && SM_X % 1024 == 0, "ring layout");
static_assert(SM_TOTAL <= 232448, "smem budget");
static_assert(SM_STAT % 128 == 0 && SM_BIAS % 16 == 0 && SM_BAR % 8 == 0 && SLOT_BYTES % 1024 == 0, "alignment");

static_assert(NX == NY1, "both rings are walked with one index");
constexpr int RED_EPOCH = 0, RED_SCALE = 2;

constexpr float GELU_A = 0.32920349f;
constexpr uint32_t GELU_C_H2 = 0x40D940D9u;
constexpr float INV_2A = 1.0f / (2.0f * GELU_A);

constexpr uint32_t TAP_SCALE_BF2 = 0x2B802B80u;
constexpr float LN_EPS_SCALED = 1e-5f * 0x1p-80f;
constexpr float RSTD_SCALE = GELU_A * 0x1p-112f;

struct Scratch {
    unsigned long long acc[2][EX / 4 * 32];
    unsigned long long bias[CH];
    float sums[2][EX];
    uint4 zero_row[66 * 192 / 16];
    unsigned int count[2];
};
__device__ __align__(256) Scratch g_scratch;
constexpr float ACC_LIMIT = 0x1p30f;

#define TS(k)
#define ASM_TS
#define MARK(k)
#define SMARK(k)
#define ASM_MARK
#define ASM_SMARK
#define ASM_TRC(it, k)

#define SPLITS 2
#define FENCE_HEAD(k) "{\n.reg .pred p;\n.reg .u32 t;\nsetp.ne.u32 p, %" #k ", 0;\n@p bra.uni GO;\nSTAY:\nld.volatile.shared.u32 t, [%" #k "];\n"
#define FENCE_TAIL "setp.ne.u32 p, t, 0;\n@p bra.uni STAY;\nGO:\n}\n"
template <int N> __device__ __forceinline__ void sched_fence(uint32_t* r, uint32_t key);
template <> __device__ __forceinline__ void sched_fence<2>(uint32_t* r, uint32_t key) {
    asm volatile(FENCE_HEAD(2) "mov.b32 %0, t;\nmov.b32 %1, t;\n" FENCE_TAIL
                 : "+r"(r[0]), "+r"(r[1]) : "r"(key) : "memory");
}
template <> __device__ __forceinline__ void sched_fence<4>(uint32_t* r, uint32_t key) {
    asm volatile(FENCE_HEAD(4) "mov.b32 %0, t;\nmov.b32 %1, t;\nmov.b32 %2, t;\nmov.b32 %3, t;\n" FENCE_TAIL
                 : "+r"(r[0]), "+r"(r[1]), "+r"(r[2]), "+r"(r[3]) : "r"(key) : "memory");
}
template <> __device__ __forceinline__ void sched_fence<6>(uint32_t* r, uint32_t key) {
    asm volatile(FENCE_HEAD(6) "mov.b32 %0, t;\nmov.b32 %1, t;\nmov.b32 %2, t;\nmov.b32 %3, t;\nmov.b32 %4, t;\nmov.b32 %5, t;\n" FENCE_TAIL
                 : "+r"(r[0]), "+r"(r[1]), "+r"(r[2]), "+r"(r[3]), "+r"(r[4]), "+r"(r[5]) : "r"(key) : "memory");
}
template <> __device__ __forceinline__ void sched_fence<8>(uint32_t* r, uint32_t key) {
    asm volatile(FENCE_HEAD(8) "mov.b32 %0, t;\nmov.b32 %1, t;\nmov.b32 %2, t;\nmov.b32 %3, t;\nmov.b32 %4, t;\nmov.b32 %5, t;\nmov.b32 %6, t;\nmov.b32 %7, t;\n" FENCE_TAIL
                 : "+r"(r[0]), "+r"(r[1]), "+r"(r[2]), "+r"(r[3]), "+r"(r[4]), "+r"(r[5]), "+r"(r[6]), "+r"(r[7]) : "r"(key) : "memory");
}
template <> __device__ __forceinline__ void sched_fence<10>(uint32_t* r, uint32_t key) {
    asm volatile(FENCE_HEAD(10) "mov.b32 %0, t;\nmov.b32 %1, t;\nmov.b32 %2, t;\nmov.b32 %3, t;\nmov.b32 %4, t;\nmov.b32 %5, t;\nmov.b32 %6, t;\nmov.b32 %7, t;\nmov.b32 %8, t;\nmov.b32 %9, t;\n" FENCE_TAIL
                 : "+r"(r[0]), "+r"(r[1]), "+r"(r[2]), "+r"(r[3]), "+r"(r[4]), "+r"(r[5]), "+r"(r[6]), "+r"(r[7]), "+r"(r[8]), "+r"(r[9]) : "r"(key) : "memory");
}
template <> __device__ __forceinline__ void sched_fence<12>(uint32_t* r, uint32_t key) {
    asm volatile(FENCE_HEAD(12) "mov.b32 %0, t;\nmov.b32 %1, t;\nmov.b32 %2, t;\nmov.b32 %3, t;\nmov.b32 %4, t;\nmov.b32 %5, t;\nmov.b32 %6, t;\nmov.b32 %7, t;\nmov.b32 %8, t;\nmov.b32 %9, t;\nmov.b32 %10, t;\nmov.b32 %11, t;\n" FENCE_TAIL
                 : "+r"(r[0]), "+r"(r[1]), "+r"(r[2]), "+r"(r[3]), "+r"(r[4]), "+r"(r[5]), "+r"(r[6]), "+r"(r[7]), "+r"(r[8]), "+r"(r[9]), "+r"(r[10]), "+r"(r[11]) : "r"(key) : "memory");
}
template <> __device__ __forceinline__ void sched_fence<24>(uint32_t* r, uint32_t key) {
    asm volatile(FENCE_HEAD(24) "mov.b32 %0, t;\nmov.b32 %1, t;\nmov.b32 %2, t;\nmov.b32 %3, t;\nmov.b32 %4, t;\nmov.b32 %5, t;\nmov.b32 %6, t;\nmov.b32 %7, t;\nmov.b32 %8, t;\nmov.b32 %9, t;\nmov.b32 %10, t;\nmov.b32 %11, t;\nmov.b32 %12, t;\nmov.b32 %13, t;\nmov.b32 %14, t;\nmov.b32 %15, t;\nmov.b32 %16, t;\nmov.b32 %17, t;\nmov.b32 %18, t;\nmov.b32 %19, t;\nmov.b32 %20, t;\nmov.b32 %21, t;\nmov.b32 %22, t;\nmov.b32 %23, t;\n" FENCE_TAIL
                 : "+r"(r[0]), "+r"(r[1]), "+r"(r[2]), "+r"(r[3]), "+r"(r[4]), "+r"(r[5]), "+r"(r[6]), "+r"(r[7]), "+r"(r[8]), "+r"(r[9]), "+r"(r[10]), "+r"(r[11]), "+r"(r[12]), "+r"(r[13]), "+r"(r[14]), "+r"(r[15]), "+r"(r[16]), "+r"(r[17]), "+r"(r[18]), "+r"(r[19]), "+r"(r[20]), "+r"(r[21]), "+r"(r[22]), "+r"(r[23]) : "r"(key) : "memory");
}
#define SPLIT(k, r) do { if ((SPLITS >> (k)) & 1) sched_fence<sizeof(r) / 4>(r, prm.ydesc); } while (0)

__device__ __forceinline__ void mbar_init(uint32_t bar, uint32_t count) {
    asm volatile("mbarrier.init.shared::cta.b64 [%0], %1;" ::"r"(bar), "r"(count) : "memory");
}
__device__ __forceinline__ void mbar_arrive_if(uint32_t bar, bool pred) {
    asm volatile("{\n.reg .pred p;\nsetp.ne.u32 p, %1, 0;\n@p mbarrier.arrive.shared::cta.b64 _, [%0];\n}\n"
                 ::"r"(bar), "r"((uint32_t)pred) : "memory");
}
__device__ __forceinline__ void mbar_wait(uint32_t bar, uint32_t parity) {
    asm volatile(
        "{\n.reg .pred p;\n.reg .u32 n;\n"
        "mbarrier.try_wait.parity.shared::cta.b64 p, [%0], %1;\n"
        "@p bra.uni WAIT_DONE;\n"
        "mov.u32 n, 0;\n"
        "WAIT_LOOP:\n"
        "mbarrier.try_wait.parity.shared::cta.b64 p, [%0], %1;\n"
        "@p bra.uni WAIT_DONE;\n"
        "mbarrier.try_wait.parity.shared::cta.b64 p, [%0], %1;\n"
        "@p bra.uni WAIT_DONE;\n"
        "mbarrier.try_wait.parity.shared::cta.b64 p, [%0], %1;\n"
        "@p bra.uni WAIT_DONE;\n"
        "add.u32 n, n, 1;\nsetp.lt.u32 p, n, 0x40000;\n"
        "@p bra.uni WAIT_LOOP;\n"
        "trap;\n"
        "WAIT_DONE:\n}\n"
        ::"r"(bar), "r"(parity) : "memory");
}
template <int PARITY> __device__ __forceinline__ void mbar_wait_c(uint32_t bar) {
    asm volatile(
        "{\n.reg .pred p;\n.reg .u32 n;\n"
        "mbarrier.try_wait.parity.shared::cta.b64 p, [%0], %1;\n"
        "@p bra.uni WAIT_DONE;\n"
        "mov.u32 n, 0;\n"
        "WAIT_LOOP:\n"
        "mbarrier.try_wait.parity.shared::cta.b64 p, [%0], %1;\n"
        "@p bra.uni WAIT_DONE;\n"
        "mbarrier.try_wait.parity.shared::cta.b64 p, [%0], %1;\n"
        "@p bra.uni WAIT_DONE;\n"
        "mbarrier.try_wait.parity.shared::cta.b64 p, [%0], %1;\n"
        "@p bra.uni WAIT_DONE;\n"
        "add.u32 n, n, 1;\nsetp.lt.u32 p, n, 0x40000;\n"
        "@p bra.uni WAIT_LOOP;\n"
        "trap;\n"
        "WAIT_DONE:\n}\n"
        ::"r"(bar), "n"(PARITY) : "memory");
}
__device__ __forceinline__ bool mbar_probe(uint32_t bar, uint32_t parity) {
    uint32_t ok;
    asm volatile("{\n.reg .pred p;\nmbarrier.test_wait.parity.shared::cta.b64 p, [%1], %2;\nselp.u32 %0, 1, 0, p;\n}\n"
                 : "=r"(ok) : "r"(bar), "r"(parity) : "memory");
    return ok;
}
__device__ __forceinline__ void mbar_wait2(uint32_t bar0, uint32_t parity0, uint32_t bar1, uint32_t parity1) {
    asm volatile(
        "{\n.reg .pred p, q;\n.reg .u32 n;\n"
        "mbarrier.try_wait.parity.shared::cta.b64 p, [%0], %1;\n"
        "mbarrier.try_wait.parity.shared::cta.b64 q, [%2], %3;\n"
        "and.pred p, p, q;\n"
        "@p bra.uni WAIT_DONE;\n"
        "mov.u32 n, 0;\n"
        "WAIT_LOOP:\n"
        "mbarrier.try_wait.parity.shared::cta.b64 p, [%0], %1;\n"
        "mbarrier.try_wait.parity.shared::cta.b64 q, [%2], %3;\n"
        "and.pred p, p, q;\n"
        "@p bra.uni WAIT_DONE;\n"
        "add.u32 n, n, 1;\nsetp.lt.u32 p, n, 0x80000;\n"
        "@p bra.uni WAIT_LOOP;\n"
        "trap;\n"
        "WAIT_DONE:\n}\n"
        ::"r"(bar0), "r"(parity0), "r"(bar1), "r"(parity1) : "memory");
}
#define ELECTED(body) "{\n.reg .pred p;\nelect.sync _|p, 0xffffffff;\n" body "}\n"
__device__ __forceinline__ void expect_tx(uint32_t bar, uint32_t bytes) {
    asm volatile(ELECTED("@p mbarrier.arrive.expect_tx.shared::cta.b64 _, [%0], %1;\n") ::"r"(bar), "r"(bytes) : "memory");
}
__device__ __forceinline__ void arrive_n(uint32_t bar, uint32_t count) {
    asm volatile(ELECTED("@p mbarrier.arrive.shared::cta.b64 _, [%0], %1;\n") ::"r"(bar), "r"(count) : "memory");
}
__device__ __forceinline__ void bulk_load(uint32_t dst, const void* src, uint32_t bytes, uint32_t bar) {
    asm volatile(ELECTED("@p cp.async.bulk.shared::cluster.global.mbarrier::complete_tx::bytes [%0], [%1], %2, [%3];\n")
                 ::"r"(dst), "l"(src), "r"(bytes), "r"(bar) : "memory");
}
__device__ __forceinline__ void bulk_store(void* dst, uint32_t src, uint32_t bytes) {
    asm volatile(ELECTED("@p cp.async.bulk.global.shared::cta.bulk_group [%0], [%1], %2;\n@p cp.async.bulk.commit_group;\n")
                 ::"l"(dst), "r"(src), "r"(bytes) : "memory");
}
__device__ __forceinline__ void bulk_prefetch(const void* src, uint32_t bytes) {
    asm volatile(ELECTED("@p cp.async.bulk.prefetch.L2.global [%0], %1;\n") ::"l"(src), "r"(bytes) : "memory");
}
__device__ __forceinline__ void tma_load_2d(uint32_t dst, const CUtensorMap* map, int c0, int c1, uint32_t bar) {
    asm volatile(ELECTED("@p cp.async.bulk.tensor.2d.shared::cluster.global.mbarrier::complete_tx::bytes [%0], [%1, {%2, %3}], [%4];\n")
                 ::"r"(dst), "l"(map), "r"(c0), "r"(c1), "r"(bar) : "memory");
}
template <int N> __device__ __forceinline__ void bulk_wait_read() {
    asm volatile("cp.async.bulk.wait_group.read %0;" ::"n"(N) : "memory");
}
__device__ __forceinline__ void bulk_wait_all() { asm volatile("cp.async.bulk.wait_group 0;" ::: "memory"); }
__device__ __forceinline__ void fence_async_smem() { asm volatile("fence.proxy.async.shared::cta;" ::: "memory"); }
__device__ __forceinline__ void named_sync(int id, int n) { asm volatile("bar.sync %0, %1;" ::"r"(id), "r"(n) : "memory"); }

__device__ __forceinline__ void lds64(uint32_t (&v)[2], uint32_t addr) {
    asm volatile("ld.shared.v2.b32 {%0,%1}, [%2];" : "=r"(v[0]), "=r"(v[1]) : "r"(addr));
}
__device__ __forceinline__ void sts64(uint32_t addr, uint32_t a, uint32_t b) {
    asm volatile("st.shared.v2.b32 [%0], {%1,%2};" ::"r"(addr), "r"(a), "r"(b) : "memory");
}
__device__ __forceinline__ void sts128(uint32_t addr, uint32_t a, uint32_t b, uint32_t c, uint32_t d) {
    asm volatile("st.shared.v4.b32 [%0], {%1,%2,%3,%4};" ::"r"(addr), "r"(a), "r"(b), "r"(c), "r"(d) : "memory");
}
__device__ __forceinline__ void ldsm4(uint32_t* r, uint32_t addr) {
    asm volatile("ldmatrix.sync.aligned.m8n8.x4.shared.b16 {%0,%1,%2,%3}, [%4];"
                 : "=r"(r[0]), "=r"(r[1]), "=r"(r[2]), "=r"(r[3]) : "r"(addr) : "memory");
}
__device__ __forceinline__ void ldsm4_t(uint32_t* r, uint32_t addr) {
    asm volatile("ldmatrix.sync.aligned.m8n8.x4.trans.shared.b16 {%0,%1,%2,%3}, [%4];"
                 : "=r"(r[0]), "=r"(r[1]), "=r"(r[2]), "=r"(r[3]) : "r"(addr) : "memory");
}
__device__ __forceinline__ void lds128(uint32_t* v, uint32_t addr) {
    asm volatile("ld.shared.v4.b32 {%0,%1,%2,%3}, [%4];"
                 : "=r"(v[0]), "=r"(v[1]), "=r"(v[2]), "=r"(v[3]) : "r"(addr) : "memory");
}
__device__ __forceinline__ uint32_t lds32(uint32_t addr) {
    uint32_t v; asm volatile("ld.shared.b32 %0, [%1];" : "=r"(v) : "r"(addr) : "memory"); return v;
}
__device__ __forceinline__ void sts32(uint32_t addr, uint32_t v) {
    asm volatile("st.shared.b32 [%0], %1;" ::"r"(addr), "r"(v) : "memory");
}

__device__ __forceinline__ uint32_t bf2_fma(uint32_t a, uint32_t b, uint32_t c) {
    uint32_t d; asm("fma.rn.bf16x2 %0, %1, %2, %3;" : "=r"(d) : "r"(a), "r"(b), "r"(c)); return d;
}
__device__ __forceinline__ uint32_t bf2_mul(uint32_t a, uint32_t b) {
    uint32_t d; asm("mul.rn.bf16x2 %0, %1, %2;" : "=r"(d) : "r"(a), "r"(b)); return d;
}
__device__ __forceinline__ uint32_t bf2_add(uint32_t a, uint32_t b) {
    uint32_t d; asm("add.rn.bf16x2 %0, %1, %2;" : "=r"(d) : "r"(a), "r"(b)); return d;
}
__device__ __forceinline__ uint32_t h2_fma(uint32_t a, uint32_t b, uint32_t c) {
    uint32_t d; asm("fma.rn.f16x2 %0, %1, %2, %3;" : "=r"(d) : "r"(a), "r"(b), "r"(c)); return d;
}
__device__ __forceinline__ uint32_t h2_mul(uint32_t a, uint32_t b) {
    uint32_t d; asm("mul.rn.f16x2 %0, %1, %2;" : "=r"(d) : "r"(a), "r"(b)); return d;
}
__device__ __forceinline__ uint32_t h2_tanh(uint32_t a) {
    uint32_t d; asm("tanh.approx.f16x2 %0, %1;" : "=r"(d) : "r"(a)); return d;
}
__device__ __forceinline__ float bf_lo(uint32_t v) { return __uint_as_float(v << 16); }
__device__ __forceinline__ float bf_hi(uint32_t v) { return __uint_as_float(v & 0xffff0000u); }
__device__ __forceinline__ uint32_t pack_h2(float lo, float hi) {
    uint32_t d; asm("cvt.rn.f16x2.f32 %0, %1, %2;" : "=r"(d) : "f"(hi), "f"(lo)); return d;
}
__device__ __forceinline__ uint32_t pack_bf2(float lo, float hi) {
    uint32_t d; asm("cvt.rn.bf16x2.f32 %0, %1, %2;" : "=r"(d) : "f"(hi), "f"(lo)); return d;
}
__device__ __forceinline__ void h2_unpack(uint32_t v, float& lo, float& hi) {
    asm("{\n.reg .b16 l, h;\nmov.b32 {l, h}, %2;\ncvt.f32.f16 %0, l;\ncvt.f32.f16 %1, h;\n}\n" : "=f"(lo), "=f"(hi) : "r"(v));
}
__device__ __forceinline__ uint32_t bf2_to_h2(uint32_t v) { return pack_h2(bf_lo(v), bf_hi(v)); }

__device__ __forceinline__ uint32_t gelu2(uint32_t z) {
    uint32_t p = h2_fma(z, z, GELU_C_H2);
    uint32_t t = h2_tanh(h2_mul(z, p));
    return h2_fma(z, t, z);
}

__device__ __forceinline__ void wg_fence() { asm volatile("wgmma.fence.sync.aligned;" ::: "memory"); }
__device__ __forceinline__ void wg_commit() { asm volatile("wgmma.commit_group.sync.aligned;" ::: "memory"); }
template <int N> __device__ __forceinline__ void wg_wait() {
    asm volatile("wgmma.wait_group.sync.aligned %0;" ::"n"(N) : "memory");
}
template <int N> __device__ __forceinline__ void pin(uint32_t (&r)[N]) {
#pragma unroll
    for (int i = 0; i < N; i++) asm volatile("" : "+r"(r[i])::"memory");
}
constexpr uint32_t desc_lo(uint32_t addr, uint32_t lbo) { return ((addr & 0x3FFFF) >> 4) | ((lbo >> 4) << 16); }
template <uint32_t SBO, uint32_t SWZ> __device__ __forceinline__ uint64_t desc(uint32_t lo, uint32_t bytes) {
    return (((uint64_t)((SBO >> 4) | (SWZ << 30)) << 32) | lo) + (bytes >> 4);
}
__device__ __forceinline__ uint32_t fresh_tid() {
    uint32_t v; asm volatile("mov.u32 %0, %%tid.x;" : "=r"(v));
    return v;
}
template <uint32_t V> __device__ __forceinline__ uint32_t loop_init() {
    uint32_t v; asm volatile("mov.u32 %0, %1;" : "=r"(v) : "n"(V)); return v;
}
__device__ __forceinline__ int fresh_warp() {
    int v; asm volatile("shfl.sync.idx.b32 %0, %1, 0, 0x1f, 0xffffffff;" : "=r"(v) : "r"(fresh_tid() >> 5)); return v;
}
__device__ __forceinline__ uint32_t fresh_cta() {
    uint32_t v; asm volatile("mov.u32 %0, %%ctaid.x;" : "=r"(v)); return v;
}
__device__ __forceinline__ float rsqrt_fast(float v) { float r; asm("rsqrt.approx.ftz.f32 %0, %1;" : "=f"(r) : "f"(v)); return r; }
__device__ __forceinline__ float sqrt_fast(float v) { float r; asm("sqrt.approx.f32 %0, %1;" : "=f"(r) : "f"(v)); return r; }

template <int TB>
__device__ __forceinline__ void wgmma_n64_h_set(uint32_t (&d)[16], const uint32_t* a, uint64_t desc) {
    asm volatile(
        "{\n.reg .pred p;\nsetp.ne.b32 p, 0, 0;\n"
        "wgmma.mma_async.sync.aligned.m64n64k16.f16.f16.f16 "
        "{%0,%1,%2,%3,%4,%5,%6,%7,%8,%9,%10,%11,%12,%13,%14,%15}, {%16,%17,%18,%19}, %20, p, 1, 1, %21;\n}\n"
        : "=r"(d[0]), "=r"(d[1]), "=r"(d[2]), "=r"(d[3]), "=r"(d[4]), "=r"(d[5]), "=r"(d[6]), "=r"(d[7]), "=r"(d[8]), "=r"(d[9]), "=r"(d[10]), "=r"(d[11]), "=r"(d[12]), "=r"(d[13]), "=r"(d[14]), "=r"(d[15])
        : "r"(a[0]), "r"(a[1]), "r"(a[2]), "r"(a[3]), "l"(desc), "n"(TB));
}
template <int TB>
__device__ __forceinline__ void wgmma_n64_h_acc(uint32_t (&d)[16], const uint32_t* a, uint64_t desc) {
    asm volatile(
        "{\n.reg .pred p;\nsetp.ne.b32 p, 1, 0;\n"
        "wgmma.mma_async.sync.aligned.m64n64k16.f16.f16.f16 "
        "{%0,%1,%2,%3,%4,%5,%6,%7,%8,%9,%10,%11,%12,%13,%14,%15}, {%16,%17,%18,%19}, %20, p, 1, 1, %21;\n}\n"
        : "+r"(d[0]), "+r"(d[1]), "+r"(d[2]), "+r"(d[3]), "+r"(d[4]), "+r"(d[5]), "+r"(d[6]), "+r"(d[7]), "+r"(d[8]), "+r"(d[9]), "+r"(d[10]), "+r"(d[11]), "+r"(d[12]), "+r"(d[13]), "+r"(d[14]), "+r"(d[15])
        : "r"(a[0]), "r"(a[1]), "r"(a[2]), "r"(a[3]), "l"(desc), "n"(TB));
}
__device__ __forceinline__ void wgmma_n64_h_acc_ss(uint32_t (&d)[16], uint64_t adesc, uint64_t desc) {
    asm volatile(
        "{\n.reg .pred p;\nsetp.ne.b32 p, 1, 0;\n"
        "wgmma.mma_async.sync.aligned.m64n64k16.f16.f16.f16 "
        "{%0,%1,%2,%3,%4,%5,%6,%7,%8,%9,%10,%11,%12,%13,%14,%15}, %16, %17, p, 1, 1, 1, 0;\n}\n"
        : "+r"(d[0]), "+r"(d[1]), "+r"(d[2]), "+r"(d[3]), "+r"(d[4]), "+r"(d[5]), "+r"(d[6]), "+r"(d[7]), "+r"(d[8]), "+r"(d[9]), "+r"(d[10]), "+r"(d[11]), "+r"(d[12]), "+r"(d[13]), "+r"(d[14]), "+r"(d[15])
        : "l"(adesc), "l"(desc));
}
__device__ __forceinline__ void wgmma_n96_h_acc(uint32_t (&d)[24], const uint32_t* a, uint64_t desc) {
    asm volatile(
        "{\n.reg .pred p;\nsetp.ne.b32 p, 1, 0;\n"
        "wgmma.mma_async.sync.aligned.m64n96k16.f16.f16.f16 "
        "{%0,%1,%2,%3,%4,%5,%6,%7,%8,%9,%10,%11,%12,%13,%14,%15,%16,%17,%18,%19,%20,%21,%22,%23}, {%24,%25,%26,%27}, %28, p, 1, 1, 1;\n}\n"
        : "+r"(d[0]), "+r"(d[1]), "+r"(d[2]), "+r"(d[3]), "+r"(d[4]), "+r"(d[5]), "+r"(d[6]), "+r"(d[7]), "+r"(d[8]), "+r"(d[9]), "+r"(d[10]), "+r"(d[11]), "+r"(d[12]), "+r"(d[13]), "+r"(d[14]), "+r"(d[15]), "+r"(d[16]), "+r"(d[17]), "+r"(d[18]), "+r"(d[19]), "+r"(d[20]), "+r"(d[21]), "+r"(d[22]), "+r"(d[23])
        : "r"(a[0]), "r"(a[1]), "r"(a[2]), "r"(a[3]), "l"(desc));
}

struct Params {
    CUtensorMap w1_map, w2_map;
    const __nv_bfloat16* x;
    const __nv_bfloat16* dw;
    const __nv_bfloat16* w1;
    const __nv_bfloat16* gamma;
    const __nv_bfloat16* beta;
    __nv_bfloat16* out;
    Scratch* g;
    uint64_t ydesc64[2];
    uint64_t sel[3];
    uint32_t w1desc, w2desc, ydesc;
};

__device__ __forceinline__ int cta_stride(uint32_t cta) { return cta & 8 ? ROW_BYTES : -ROW_BYTES; }
__device__ __forceinline__ uint32_t cta_tile0(uint32_t cta) {
    return ((cta >> 3) * ROWS_PER_CTA + (cta & 8 ? 0 : ROWS_PER_CTA - 1)) * ROW_BYTES + (cta & 7) * TILE_BYTES;
}

struct Producer {
    uint32_t w[9][6];
    uint32_t xoff[2];
    uint32_t yoff[2][2];
    uint32_t stat, own;
    int lane, warp;
};

struct RowCopy {
    const char* x0;
    char* y0;
    const char* zeros;
    uint32_t cut0, cut1;
    int stride, last;
};
__device__ __forceinline__ RowCopy row_copy(const Params& prm) {
    const uint32_t cta = fresh_cta(), strip = cta & 7, t0 = cta_tile0(cta);
    RowCopy r;
    r.stride = cta_stride(cta);
    r.x0 = (const char*)prm.x + (t0 - r.stride) - 192;
    r.y0 = (char*)prm.out + t0;
    r.zeros = (const char*)prm.g->zero_row;
    r.cut0 = strip == 0 ? 192 : 0;
    r.cut1 = strip == 7 ? 192 : 0;
    r.last = cta - 8 >= NUM_CTAS - 16 ? STEPS - 2 : STEPS - 1;
    return r;
}
__device__ __forceinline__ void issue_row_load(const RowCopy& r, int i, uint32_t slot) {
    const char* src = r.x0 + i * r.stride;
    const uint32_t bar = sb + SM_XFULL + slot * SLOT_BYTES, dst = sb + SM_X + slot * SLOT_BYTES;
    expect_tx(bar, XHALF_BYTES - r.cut0);
    bulk_load(dst + r.cut0, src + r.cut0, XHALF_BYTES - r.cut0, bar);
    expect_tx(bar, XHALF_BYTES - r.cut1);
    bulk_load(dst + XHALF_B, src + 32 * 192, XHALF_BYTES - r.cut1, bar);
}

__device__ __forceinline__ float quad_sum(float v) {
    v += __shfl_xor_sync(0xffffffffu, v, 1);
    v += __shfl_xor_sync(0xffffffffu, v, 2);
    return v;
}

__device__ __forceinline__ void load_x(uint32_t (&v)[6][6], const Producer& c, uint32_t row) {
#pragma unroll
    for (int k = 0; k < 6; k++) {
        asm volatile("ld.shared.v4.b32 {%0,%1,%2,%3}, [%4];"
                     : "=r"(v[k][0]), "=r"(v[k][1]), "=r"(v[k][2]), "=r"(v[k][3]) : "r"(row + c.xoff[0] + k * 192));
        asm volatile("ld.shared.v2.b32 {%0,%1}, [%2];" : "=r"(v[k][4]), "=r"(v[k][5]) : "r"(row + c.xoff[1] + k * 192));
    }
}
template <int DY, int STRIDE>
__device__ __forceinline__ void conv_row(uint32_t (&dst)[24], const uint32_t* src, const uint32_t (&v)[6][6], const Producer& c) {
#pragma unroll
    for (int o = 0; o < 4; o++)
#pragma unroll
        for (int u = 0; u < 6; u++)
            dst[o * 6 + u] = bf2_fma(v[o + 2][u], c.w[3 * DY + 2][u], bf2_fma(v[o + 1][u], c.w[3 * DY + 1][u],
                             bf2_fma(v[o][u], c.w[3 * DY][u], STRIDE ? src[o * 6 + u] : src[2 * o + 1])));
}
#define HAND_OVER(name, base, r) asm volatile("mov.b32 " name "%6, %0; mov.b32 " name "%7, %1; mov.b32 " name "%8, %2;\n" \
    "mov.b32 " name "%9, %3; mov.b32 " name "%10, %4; mov.b32 " name "%11, %5;" ::"r"((r)[0]), "r"((r)[1]), "r"((r)[2]), \
    "r"((r)[3]), "r"((r)[4]), "r"((r)[5]), "n"(base), "n"(base + 1), "n"(base + 2), "n"(base + 3), "n"(base + 4), "n"(base + 5))
template <int K> __device__ __forceinline__ void hand_over(const Producer& c, const uint32_t (&B)[24], const uint32_t (&C)[24],
                                                           const uint32_t (&v)[6][6]) {
    HAND_OVER("pw", K * 6, c.w[K]);
    if (K < 6) HAND_OVER("pv", K * 6, v[K % 6]);
    if (K < 4) { HAND_OVER("pb", K * 6, B + K % 4 * 6); HAND_OVER("pc", K * 6, C + K % 4 * 6); }
    if constexpr (K < 8) hand_over<K + 1>(c, B, C, v);
}
static_assert(sb + SM_BAR + BAR_DUMMY * 8 == 230880, "layout");
__device__ __forceinline__ void produce_tiles(const Producer& c, const Params& prm) {
    asm volatile(
        "{\n"
        ".reg .b32 pa<24>, pq<4>, m<6>, y<6>, rr, mm, t, so, sp, sn, ph, ad, tt, cnt;\n"
        ".reg .b16 xl, xh;\n"
        ".reg .f32 d<4>, us, s0, s1, f0, f1, kq;\n"
        ".reg .pred pt, pf, pr, pw, px, pl, po, pe, pn, pp;\n"
        "setp.ne.b32 pt, 1, 0; setp.ne.b32 pf, 0, 0; setp.eq.u32 pl, %8, 0; and.b32 tt, %8, 1; setp.ne.u32 po, tt, 0;\n"
        "and.b32 tt, %8, 4; setp.ne.u32 pr, tt, 0; selp.f32 kq, 0f3F802D41, 0f3F7FA57E, pr;\n"
        "mov.u32 t, 0; mov.u32 so, 0; mov.u32 sp, 55896; mov.u32 ph, 1; mov.pred pn, pf; mov.pred pp, pf;\n"
        "setp.eq.u32 pr, %12, 0;\n"
        "@pr bra.uni RARE;\n"
        "LOOP:\n"
        ASM_TRC("t", 0)
        "fence.proxy.async.shared::cta;\n"
        "@pl mbarrier.arrive.shared::cta.b64 _, [sp+174984];\n"
        "fma.rn.bf16x2 pa0, pv0, pw36, pb0; fma.rn.bf16x2 pa1, pv1, pw37, pb1; fma.rn.bf16x2 pa2, pv2, pw38, pb2; fma.rn.bf16x2 pa3, pv3, pw39, pb3; fma.rn.bf16x2 pa4, pv4, pw40, pb4; fma.rn.bf16x2 pa5, pv5, pw41, pb5;\n"
        "fma.rn.bf16x2 pa6, pv6, pw36, pb6; fma.rn.bf16x2 pa7, pv7, pw37, pb7; fma.rn.bf16x2 pa8, pv8, pw38, pb8; fma.rn.bf16x2 pa9, pv9, pw39, pb9; fma.rn.bf16x2 pa10, pv10, pw40, pb10; fma.rn.bf16x2 pa11, pv11, pw41, pb11;\n"
        "fma.rn.bf16x2 pa12, pv12, pw36, pb12; fma.rn.bf16x2 pa13, pv13, pw37, pb13; fma.rn.bf16x2 pa14, pv14, pw38, pb14; fma.rn.bf16x2 pa15, pv15, pw39, pb15; fma.rn.bf16x2 pa16, pv16, pw40, pb16; fma.rn.bf16x2 pa17, pv17, pw41, pb17;\n"
        "fma.rn.bf16x2 pa18, pv18, pw36, pb18; fma.rn.bf16x2 pa19, pv19, pw37, pb19; fma.rn.bf16x2 pa20, pv20, pw38, pb20; fma.rn.bf16x2 pa21, pv21, pw39, pb21; fma.rn.bf16x2 pa22, pv22, pw40, pb22; fma.rn.bf16x2 pa23, pv23, pw41, pb23;\n"
        "fma.rn.bf16x2 pa0, pv6, pw42, pa0; fma.rn.bf16x2 pa1, pv7, pw43, pa1; fma.rn.bf16x2 pa2, pv8, pw44, pa2; fma.rn.bf16x2 pa3, pv9, pw45, pa3; fma.rn.bf16x2 pa4, pv10, pw46, pa4; fma.rn.bf16x2 pa5, pv11, pw47, pa5;\n"
        "fma.rn.bf16x2 pa6, pv12, pw42, pa6; fma.rn.bf16x2 pa7, pv13, pw43, pa7; fma.rn.bf16x2 pa8, pv14, pw44, pa8; fma.rn.bf16x2 pa9, pv15, pw45, pa9; fma.rn.bf16x2 pa10, pv16, pw46, pa10; fma.rn.bf16x2 pa11, pv17, pw47, pa11;\n"
        "fma.rn.bf16x2 pa12, pv18, pw42, pa12; fma.rn.bf16x2 pa13, pv19, pw43, pa13; fma.rn.bf16x2 pa14, pv20, pw44, pa14; fma.rn.bf16x2 pa15, pv21, pw45, pa15; fma.rn.bf16x2 pa16, pv22, pw46, pa16; fma.rn.bf16x2 pa17, pv23, pw47, pa17;\n"
        "fma.rn.bf16x2 pa18, pv24, pw42, pa18; fma.rn.bf16x2 pa19, pv25, pw43, pa19; fma.rn.bf16x2 pa20, pv26, pw44, pa20; fma.rn.bf16x2 pa21, pv27, pw45, pa21; fma.rn.bf16x2 pa22, pv28, pw46, pa22; fma.rn.bf16x2 pa23, pv29, pw47, pa23;\n"
        "fma.rn.bf16x2 pa0, pv12, pw48, pa0; fma.rn.bf16x2 pa1, pv13, pw49, pa1; fma.rn.bf16x2 pa2, pv14, pw50, pa2; fma.rn.bf16x2 pa3, pv15, pw51, pa3; fma.rn.bf16x2 pa4, pv16, pw52, pa4; fma.rn.bf16x2 pa5, pv17, pw53, pa5;\n"
        "fma.rn.bf16x2 pa6, pv18, pw48, pa6; fma.rn.bf16x2 pa7, pv19, pw49, pa7; fma.rn.bf16x2 pa8, pv20, pw50, pa8; fma.rn.bf16x2 pa9, pv21, pw51, pa9; fma.rn.bf16x2 pa10, pv22, pw52, pa10; fma.rn.bf16x2 pa11, pv23, pw53, pa11;\n"
        "fma.rn.bf16x2 pa12, pv24, pw48, pa12; fma.rn.bf16x2 pa13, pv25, pw49, pa13; fma.rn.bf16x2 pa14, pv26, pw50, pa14; fma.rn.bf16x2 pa15, pv27, pw51, pa15; fma.rn.bf16x2 pa16, pv28, pw52, pa16; fma.rn.bf16x2 pa17, pv29, pw53, pa17;\n"
        "fma.rn.bf16x2 pa18, pv30, pw48, pa18; fma.rn.bf16x2 pa19, pv31, pw49, pa19; fma.rn.bf16x2 pa20, pv32, pw50, pa20; fma.rn.bf16x2 pa21, pv33, pw51, pa21; fma.rn.bf16x2 pa22, pv34, pw52, pa22; fma.rn.bf16x2 pa23, pv35, pw53, pa23;\n"
        "mul.rn.bf16x2 pq0, pa0, pa0; fma.rn.bf16x2 pq0, pa1, pa1, pq0; fma.rn.bf16x2 pq0, pa2, pa2, pq0; fma.rn.bf16x2 pq0, pa3, pa3, pq0; fma.rn.bf16x2 pq0, pa4, pa4, pq0; fma.rn.bf16x2 pq0, pa5, pa5, pq0;\n"
        "mul.rn.bf16x2 pq1, pa6, pa6; fma.rn.bf16x2 pq1, pa7, pa7, pq1; fma.rn.bf16x2 pq1, pa8, pa8, pq1; fma.rn.bf16x2 pq1, pa9, pa9, pq1; fma.rn.bf16x2 pq1, pa10, pa10, pq1; fma.rn.bf16x2 pq1, pa11, pa11, pq1;\n"
        "mul.rn.bf16x2 pq2, pa12, pa12; fma.rn.bf16x2 pq2, pa13, pa13, pq2; fma.rn.bf16x2 pq2, pa14, pa14, pq2; fma.rn.bf16x2 pq2, pa15, pa15, pq2; fma.rn.bf16x2 pq2, pa16, pa16, pq2; fma.rn.bf16x2 pq2, pa17, pa17, pq2;\n"
        "mul.rn.bf16x2 pq3, pa18, pa18; fma.rn.bf16x2 pq3, pa19, pa19, pq3; fma.rn.bf16x2 pq3, pa20, pa20, pq3; fma.rn.bf16x2 pq3, pa21, pa21, pq3; fma.rn.bf16x2 pq3, pa22, pa22, pq3; fma.rn.bf16x2 pq3, pa23, pa23, pq3;\n"
        "B0:\n"
        "wgmma.fence.sync.aligned;\n"
        "wgmma.mma_async.sync.aligned.m64n8k16.f32.bf16.bf16 {d0,d1,d2,d3}, {pa0,pa6,pa1,pa7}, %9, pf, 1, 1, 0;\n"
        "wgmma.mma_async.sync.aligned.m64n8k16.f32.bf16.bf16 {d0,d1,d2,d3}, {pa2,pa8,pa3,pa9}, %9, pt, 1, 1, 0;\n"
        "wgmma.mma_async.sync.aligned.m64n8k16.f32.bf16.bf16 {d0,d1,d2,d3}, {pa4,pa10,pa5,pa11}, %9, pt, 1, 1, 0;\n"
        "wgmma.mma_async.sync.aligned.m64n8k16.f32.bf16.bf16 {d0,d1,d2,d3}, {pa12,pa18,pa13,pa19}, %10, pt, 1, 1, 0;\n"
        "wgmma.mma_async.sync.aligned.m64n8k16.f32.bf16.bf16 {d0,d1,d2,d3}, {pa14,pa20,pa15,pa21}, %10, pt, 1, 1, 0;\n"
        "wgmma.mma_async.sync.aligned.m64n8k16.f32.bf16.bf16 {d0,d1,d2,d3}, {pa16,pa22,pa17,pa23}, %10, pt, 1, 1, 0;\n"
        "wgmma.mma_async.sync.aligned.m64n8k16.f32.bf16.bf16 {d0,d1,d2,d3}, {pq0,pq1,pq2,pq3}, %11, pt, 1, 1, 0;\n"
        "wgmma.commit_group.sync.aligned;\n"
        "add.u32 ad, %7, so; ld.shared.f32 us, [ad+4];\n"
        "fma.rn.bf16x2 pb0, pv0, pw18, pc0; fma.rn.bf16x2 pb1, pv1, pw19, pc1; fma.rn.bf16x2 pb2, pv2, pw20, pc2; fma.rn.bf16x2 pb3, pv3, pw21, pc3; fma.rn.bf16x2 pb4, pv4, pw22, pc4; fma.rn.bf16x2 pb5, pv5, pw23, pc5;\n"
        "fma.rn.bf16x2 pb6, pv6, pw18, pc6; fma.rn.bf16x2 pb7, pv7, pw19, pc7; fma.rn.bf16x2 pb8, pv8, pw20, pc8; fma.rn.bf16x2 pb9, pv9, pw21, pc9; fma.rn.bf16x2 pb10, pv10, pw22, pc10; fma.rn.bf16x2 pb11, pv11, pw23, pc11;\n"
        "fma.rn.bf16x2 pb0, pv6, pw24, pb0; fma.rn.bf16x2 pb1, pv7, pw25, pb1; fma.rn.bf16x2 pb2, pv8, pw26, pb2; fma.rn.bf16x2 pb3, pv9, pw27, pb3; fma.rn.bf16x2 pb4, pv10, pw28, pb4; fma.rn.bf16x2 pb5, pv11, pw29, pb5;\n"
        "fma.rn.bf16x2 pb6, pv12, pw24, pb6; fma.rn.bf16x2 pb7, pv13, pw25, pb7; fma.rn.bf16x2 pb8, pv14, pw26, pb8; fma.rn.bf16x2 pb9, pv15, pw27, pb9; fma.rn.bf16x2 pb10, pv16, pw28, pb10; fma.rn.bf16x2 pb11, pv17, pw29, pb11;\n"
        "fma.rn.bf16x2 pb0, pv12, pw30, pb0; fma.rn.bf16x2 pb1, pv13, pw31, pb1; fma.rn.bf16x2 pb2, pv14, pw32, pb2; fma.rn.bf16x2 pb3, pv15, pw33, pb3; fma.rn.bf16x2 pb4, pv16, pw34, pb4; fma.rn.bf16x2 pb5, pv17, pw35, pb5;\n"
        "fma.rn.bf16x2 pb6, pv18, pw30, pb6; fma.rn.bf16x2 pb7, pv19, pw31, pb7; fma.rn.bf16x2 pb8, pv20, pw32, pb8; fma.rn.bf16x2 pb9, pv21, pw33, pb9; fma.rn.bf16x2 pb10, pv22, pw34, pb10; fma.rn.bf16x2 pb11, pv23, pw35, pb11;\n"
        "B1:\n"
        "fma.rn.bf16x2 pb12, pv12, pw18, pc12; fma.rn.bf16x2 pb13, pv13, pw19, pc13; fma.rn.bf16x2 pb14, pv14, pw20, pc14; fma.rn.bf16x2 pb15, pv15, pw21, pc15; fma.rn.bf16x2 pb16, pv16, pw22, pc16; fma.rn.bf16x2 pb17, pv17, pw23, pc17;\n"
        "fma.rn.bf16x2 pb18, pv18, pw18, pc18; fma.rn.bf16x2 pb19, pv19, pw19, pc19; fma.rn.bf16x2 pb20, pv20, pw20, pc20; fma.rn.bf16x2 pb21, pv21, pw21, pc21; fma.rn.bf16x2 pb22, pv22, pw22, pc22; fma.rn.bf16x2 pb23, pv23, pw23, pc23;\n"
        "fma.rn.bf16x2 pb12, pv18, pw24, pb12; fma.rn.bf16x2 pb13, pv19, pw25, pb13; fma.rn.bf16x2 pb14, pv20, pw26, pb14; fma.rn.bf16x2 pb15, pv21, pw27, pb15; fma.rn.bf16x2 pb16, pv22, pw28, pb16; fma.rn.bf16x2 pb17, pv23, pw29, pb17;\n"
        "fma.rn.bf16x2 pb18, pv24, pw24, pb18; fma.rn.bf16x2 pb19, pv25, pw25, pb19; fma.rn.bf16x2 pb20, pv26, pw26, pb20; fma.rn.bf16x2 pb21, pv27, pw27, pb21; fma.rn.bf16x2 pb22, pv28, pw28, pb22; fma.rn.bf16x2 pb23, pv29, pw29, pb23;\n"
        "fma.rn.bf16x2 pb12, pv24, pw30, pb12; fma.rn.bf16x2 pb13, pv25, pw31, pb13; fma.rn.bf16x2 pb14, pv26, pw32, pb14; fma.rn.bf16x2 pb15, pv27, pw33, pb15; fma.rn.bf16x2 pb16, pv28, pw34, pb16; fma.rn.bf16x2 pb17, pv29, pw35, pb17;\n"
        "fma.rn.bf16x2 pb18, pv30, pw30, pb18; fma.rn.bf16x2 pb19, pv31, pw31, pb19; fma.rn.bf16x2 pb20, pv32, pw32, pb20; fma.rn.bf16x2 pb21, pv33, pw33, pb21; fma.rn.bf16x2 pb22, pv34, pw34, pb22; fma.rn.bf16x2 pb23, pv35, pw35, pb23;\n"
        "C0:\n"
        "wgmma.wait_group.sync.aligned 0;\n"
        "selp.f32 s0, d2, d0, po; selp.f32 s1, d3, d1, po;\n"
        "shfl.sync.bfly.b32 f0, s0, 4, 0x1f, 0xffffffff; shfl.sync.bfly.b32 f1, s1, 4, 0x1f, 0xffffffff;\n"
        "fma.rn.bf16x2 pc0, pv0, pw0, ps1; fma.rn.bf16x2 pc1, pv1, pw1, ps1; fma.rn.bf16x2 pc2, pv2, pw2, ps1; fma.rn.bf16x2 pc3, pv3, pw3, ps1; fma.rn.bf16x2 pc4, pv4, pw4, ps1; fma.rn.bf16x2 pc5, pv5, pw5, ps1;\n"
        "fma.rn.bf16x2 pc6, pv6, pw0, ps3; fma.rn.bf16x2 pc7, pv7, pw1, ps3; fma.rn.bf16x2 pc8, pv8, pw2, ps3; fma.rn.bf16x2 pc9, pv9, pw3, ps3; fma.rn.bf16x2 pc10, pv10, pw4, ps3; fma.rn.bf16x2 pc11, pv11, pw5, ps3;\n"
        "fma.rn.bf16x2 pc12, pv12, pw0, ps5; fma.rn.bf16x2 pc13, pv13, pw1, ps5; fma.rn.bf16x2 pc14, pv14, pw2, ps5; fma.rn.bf16x2 pc15, pv15, pw3, ps5; fma.rn.bf16x2 pc16, pv16, pw4, ps5; fma.rn.bf16x2 pc17, pv17, pw5, ps5;\n"
        "fma.rn.bf16x2 pc18, pv18, pw0, ps7; fma.rn.bf16x2 pc19, pv19, pw1, ps7; fma.rn.bf16x2 pc20, pv20, pw2, ps7; fma.rn.bf16x2 pc21, pv21, pw3, ps7; fma.rn.bf16x2 pc22, pv22, pw4, ps7; fma.rn.bf16x2 pc23, pv23, pw5, ps7;\n"
        "fma.rn.bf16x2 pc0, pv6, pw6, pc0; fma.rn.bf16x2 pc1, pv7, pw7, pc1; fma.rn.bf16x2 pc2, pv8, pw8, pc2; fma.rn.bf16x2 pc3, pv9, pw9, pc3; fma.rn.bf16x2 pc4, pv10, pw10, pc4; fma.rn.bf16x2 pc5, pv11, pw11, pc5;\n"
        "fma.rn.bf16x2 pc6, pv12, pw6, pc6; fma.rn.bf16x2 pc7, pv13, pw7, pc7; fma.rn.bf16x2 pc8, pv14, pw8, pc8; fma.rn.bf16x2 pc9, pv15, pw9, pc9; fma.rn.bf16x2 pc10, pv16, pw10, pc10; fma.rn.bf16x2 pc11, pv17, pw11, pc11;\n"
        "fma.rn.bf16x2 pc12, pv18, pw6, pc12; fma.rn.bf16x2 pc13, pv19, pw7, pc13; fma.rn.bf16x2 pc14, pv20, pw8, pc14; fma.rn.bf16x2 pc15, pv21, pw9, pc15; fma.rn.bf16x2 pc16, pv22, pw10, pc16; fma.rn.bf16x2 pc17, pv23, pw11, pc17;\n"
        "fma.rn.bf16x2 pc18, pv24, pw6, pc18; fma.rn.bf16x2 pc19, pv25, pw7, pc19; fma.rn.bf16x2 pc20, pv26, pw8, pc20; fma.rn.bf16x2 pc21, pv27, pw9, pc21; fma.rn.bf16x2 pc22, pv28, pw10, pc22; fma.rn.bf16x2 pc23, pv29, pw11, pc23;\n"
        "fma.rn.bf16x2 pc0, pv12, pw12, pc0; fma.rn.bf16x2 pc1, pv13, pw13, pc1; fma.rn.bf16x2 pc2, pv14, pw14, pc2; fma.rn.bf16x2 pc3, pv15, pw15, pc3; fma.rn.bf16x2 pc4, pv16, pw16, pc4; fma.rn.bf16x2 pc5, pv17, pw17, pc5;\n"
        "fma.rn.bf16x2 pc6, pv18, pw12, pc6; fma.rn.bf16x2 pc7, pv19, pw13, pc7; fma.rn.bf16x2 pc8, pv20, pw14, pc8; fma.rn.bf16x2 pc9, pv21, pw15, pc9; fma.rn.bf16x2 pc10, pv22, pw16, pc10; fma.rn.bf16x2 pc11, pv23, pw17, pc11;\n"
        "fma.rn.bf16x2 pc12, pv24, pw12, pc12; fma.rn.bf16x2 pc13, pv25, pw13, pc13; fma.rn.bf16x2 pc14, pv26, pw14, pc14; fma.rn.bf16x2 pc15, pv27, pw15, pc15; fma.rn.bf16x2 pc16, pv28, pw16, pc16; fma.rn.bf16x2 pc17, pv29, pw17, pc17;\n"
        "fma.rn.bf16x2 pc18, pv30, pw12, pc18; fma.rn.bf16x2 pc19, pv31, pw13, pc19; fma.rn.bf16x2 pc20, pv32, pw14, pc20; fma.rn.bf16x2 pc21, pv33, pw15, pc21; fma.rn.bf16x2 pc22, pv34, pw16, pc22; fma.rn.bf16x2 pc23, pv35, pw17, pc23;\n"
        "add.f32 s0, s0, f0; add.f32 s1, s1, f1; mul.f32 s0, s0, 0fBC2AAAAB;\n"
        "neg.f32 f0, s0; fma.rn.f32 f0, f0, s0, %13; fma.rn.f32 f0, s1, 0f3C2AAAAB, f0; max.f32 f0, f0, %13;\n"
        "rsqrt.approx.ftz.f32 f0, f0; mul.f32 f0, f0, %14; cvt.rn.bf16x2.f32 tt, f0, 0f00000000; mov.b32 f0, tt;\n"
        "mul.f32 f1, s0, kq; mul.f32 f1, f1, f0; cvt.rn.bf16x2.f32 tt, f1, f0; add.f32 us, us, s0; cvt.rn.bf16x2.f32 mm, us, us;\n"
        "add.u32 ad, %7, so; st.shared.v2.b32 [ad], {tt, mm};\n"
        "add.u32 ad, %6, so; ld.shared.v4.b32 {ps0,ps1,ps2,ps3}, [ad]; ld.shared.v4.b32 {ps4,ps5,ps6,ps7}, [ad+16];\n"
        "mbarrier.try_wait.parity.shared::cta.b64 pw, [so+174992], ph;\n"
        "mbarrier.try_wait.parity.shared::cta.b64 px, [so+174976], ph;\n"
        "and.pred pw, pw, px;\n"
        "N0:\n"
        "@!pw bra.uni SPIN;\n"
        "BACK:\n"
        "add.u32 ad, %0, so; ld.shared.v4.b32 {pv0,pv1,pv2,pv3}, [ad+0];\n"
        "add.u32 ad, %1, so; ld.shared.v2.b32 {pv4,pv5}, [ad+0];\n"
        "add.u32 ad, %0, so; ld.shared.v4.b32 {pv6,pv7,pv8,pv9}, [ad+192];\n"
        "add.u32 ad, %1, so; ld.shared.v2.b32 {pv10,pv11}, [ad+192];\n"
        "mov.b32 {xl, xh}, ps0; mov.b32 rr, {xl, xl}; mov.b32 mm, {xh, xh}; fma.rn.bf16x2 pa0, pa0, rr, mm; fma.rn.bf16x2 pa1, pa1, rr, mm; fma.rn.bf16x2 pa2, pa2, rr, mm; fma.rn.bf16x2 pa3, pa3, rr, mm; fma.rn.bf16x2 pa4, pa4, rr, mm; fma.rn.bf16x2 pa5, pa5, rr, mm;\n"
        "and.b32 m0, pa0, 0x7fff7fff; and.b32 m1, pa1, 0x7fff7fff; and.b32 m2, pa2, 0x7fff7fff; and.b32 m3, pa3, 0x7fff7fff; and.b32 m4, pa4, 0x7fff7fff; and.b32 m5, pa5, 0x7fff7fff;\n"
        "mad.lo.u32 y0, m0, 7, pa0; mad.lo.u32 y1, m1, 7, pa1; mad.lo.u32 y2, m2, 7, pa2; mad.lo.u32 y3, m3, 7, pa3; mad.lo.u32 y4, m4, 7, pa4; mad.lo.u32 y5, m5, 7, pa5;\n"
        "add.u32 ad, %2, so; st.shared.v4.b32 [ad+0], {y0,y1,y2,y3};\n"
        "add.u32 ad, %4, so; st.shared.v2.b32 [ad+0], {y4,y5};\n"
        "N1:\n"
        "add.u32 ad, %0, so; ld.shared.v4.b32 {pv12,pv13,pv14,pv15}, [ad+384];\n"
        "add.u32 ad, %1, so; ld.shared.v2.b32 {pv16,pv17}, [ad+384];\n"
        "add.u32 ad, %0, so; ld.shared.v4.b32 {pv18,pv19,pv20,pv21}, [ad+576];\n"
        "add.u32 ad, %1, so; ld.shared.v2.b32 {pv22,pv23}, [ad+576];\n"
        "mov.b32 {xl, xh}, ps2; mov.b32 rr, {xl, xl}; mov.b32 mm, {xh, xh}; fma.rn.bf16x2 pa6, pa6, rr, mm; fma.rn.bf16x2 pa7, pa7, rr, mm; fma.rn.bf16x2 pa8, pa8, rr, mm; fma.rn.bf16x2 pa9, pa9, rr, mm; fma.rn.bf16x2 pa10, pa10, rr, mm; fma.rn.bf16x2 pa11, pa11, rr, mm;\n"
        "and.b32 m0, pa6, 0x7fff7fff; and.b32 m1, pa7, 0x7fff7fff; and.b32 m2, pa8, 0x7fff7fff; and.b32 m3, pa9, 0x7fff7fff; and.b32 m4, pa10, 0x7fff7fff; and.b32 m5, pa11, 0x7fff7fff;\n"
        "mad.lo.u32 y0, m0, 7, pa6; mad.lo.u32 y1, m1, 7, pa7; mad.lo.u32 y2, m2, 7, pa8; mad.lo.u32 y3, m3, 7, pa9; mad.lo.u32 y4, m4, 7, pa10; mad.lo.u32 y5, m5, 7, pa11;\n"
        "add.u32 ad, %3, so; st.shared.v4.b32 [ad+0], {y0,y1,y2,y3};\n"
        "add.u32 ad, %5, so; st.shared.v2.b32 [ad+0], {y4,y5};\n"
        "N2:\n"
        "add.u32 ad, %0, so; ld.shared.v4.b32 {pv24,pv25,pv26,pv27}, [ad+768];\n"
        "add.u32 ad, %1, so; ld.shared.v2.b32 {pv28,pv29}, [ad+768];\n"
        "mov.b32 {xl, xh}, ps4; mov.b32 rr, {xl, xl}; mov.b32 mm, {xh, xh}; fma.rn.bf16x2 pa12, pa12, rr, mm; fma.rn.bf16x2 pa13, pa13, rr, mm; fma.rn.bf16x2 pa14, pa14, rr, mm; fma.rn.bf16x2 pa15, pa15, rr, mm; fma.rn.bf16x2 pa16, pa16, rr, mm; fma.rn.bf16x2 pa17, pa17, rr, mm;\n"
        "and.b32 m0, pa12, 0x7fff7fff; and.b32 m1, pa13, 0x7fff7fff; and.b32 m2, pa14, 0x7fff7fff; and.b32 m3, pa15, 0x7fff7fff; and.b32 m4, pa16, 0x7fff7fff; and.b32 m5, pa17, 0x7fff7fff;\n"
        "mad.lo.u32 y0, m0, 7, pa12; mad.lo.u32 y1, m1, 7, pa13; mad.lo.u32 y2, m2, 7, pa14; mad.lo.u32 y3, m3, 7, pa15; mad.lo.u32 y4, m4, 7, pa16; mad.lo.u32 y5, m5, 7, pa17;\n"
        "add.u32 ad, %2, so; st.shared.v4.b32 [ad+2048], {y0,y1,y2,y3};\n"
        "add.u32 ad, %4, so; st.shared.v2.b32 [ad+1024], {y4,y5};\n"
        "N3:\n"
        "add.u32 ad, %0, so; ld.shared.v4.b32 {pv30,pv31,pv32,pv33}, [ad+960];\n"
        "add.u32 ad, %1, so; ld.shared.v2.b32 {pv34,pv35}, [ad+960];\n"
        "mov.b32 {xl, xh}, ps6; mov.b32 rr, {xl, xl}; mov.b32 mm, {xh, xh}; fma.rn.bf16x2 pa18, pa18, rr, mm; fma.rn.bf16x2 pa19, pa19, rr, mm; fma.rn.bf16x2 pa20, pa20, rr, mm; fma.rn.bf16x2 pa21, pa21, rr, mm; fma.rn.bf16x2 pa22, pa22, rr, mm; fma.rn.bf16x2 pa23, pa23, rr, mm;\n"
        "and.b32 m0, pa18, 0x7fff7fff; and.b32 m1, pa19, 0x7fff7fff; and.b32 m2, pa20, 0x7fff7fff; and.b32 m3, pa21, 0x7fff7fff; and.b32 m4, pa22, 0x7fff7fff; and.b32 m5, pa23, 0x7fff7fff;\n"
        "mad.lo.u32 y0, m0, 7, pa18; mad.lo.u32 y1, m1, 7, pa19; mad.lo.u32 y2, m2, 7, pa20; mad.lo.u32 y3, m3, 7, pa21; mad.lo.u32 y4, m4, 7, pa22; mad.lo.u32 y5, m5, 7, pa23;\n"
        "add.u32 ad, %3, so; st.shared.v4.b32 [ad+2048], {y0,y1,y2,y3};\n"
        "add.u32 ad, %5, so; st.shared.v2.b32 [ad+1024], {y4,y5};\n"
        "mov.u32 sp, so; add.u32 so, so, 26624; setp.eq.u32 pr, so, 79872; selp.u32 so, 0, so, pr; selp.u32 tt, 1, 0, pr; xor.b32 ph, ph, tt;\n"
        "add.u32 t, t, 1; setp.lt.u32 pe, t, 32;\n"
        "@pe bra.uni LOOP;\n"
        "bra.uni DONE;\n"
        "SPIN: mov.u32 cnt, 0;\n"
        ASM_TRC("t", 1)
        "SPINL:\n"
        "mbarrier.try_wait.parity.shared::cta.b64 pw, [so+174992], ph;\n"
        "mbarrier.try_wait.parity.shared::cta.b64 px, [so+174976], ph;\n"
        "and.pred pw, pw, px;\n"
        "@pw bra.uni BACK;\n"
        "add.u32 cnt, cnt, 1; setp.lt.u32 pw, cnt, 0x100000;\n"
        "@pw bra.uni SPINL;\n"
        "trap;\n"
        "RARE:\n"
        "ld.volatile.shared.u32 tt, [%6];\n"
        "mov.b32 pa0, tt; mov.b32 pa1, tt; mov.b32 pa2, tt; mov.b32 pa3, tt; mov.b32 pa4, tt; mov.b32 pa5, tt; mov.b32 pa6, tt; mov.b32 pa7, tt; mov.b32 pa8, tt; mov.b32 pa9, tt; mov.b32 pa10, tt; mov.b32 pa11, tt;\n"
        "mov.b32 pa12, tt; mov.b32 pa13, tt; mov.b32 pa14, tt; mov.b32 pa15, tt; mov.b32 pa16, tt; mov.b32 pa17, tt; mov.b32 pa18, tt; mov.b32 pa19, tt; mov.b32 pa20, tt; mov.b32 pa21, tt; mov.b32 pa22, tt; mov.b32 pa23, tt;\n"
        "mov.b32 pb0, tt; mov.b32 pb1, tt; mov.b32 pb2, tt; mov.b32 pb3, tt; mov.b32 pb4, tt; mov.b32 pb5, tt; mov.b32 pb6, tt; mov.b32 pb7, tt; mov.b32 pb8, tt; mov.b32 pb9, tt; mov.b32 pb10, tt; mov.b32 pb11, tt;\n"
        "mov.b32 pb12, tt; mov.b32 pb13, tt; mov.b32 pb14, tt; mov.b32 pb15, tt; mov.b32 pb16, tt; mov.b32 pb17, tt; mov.b32 pb18, tt; mov.b32 pb19, tt; mov.b32 pb20, tt; mov.b32 pb21, tt; mov.b32 pb22, tt; mov.b32 pb23, tt;\n"
        "mov.b32 pc0, tt; mov.b32 pc1, tt; mov.b32 pc2, tt; mov.b32 pc3, tt; mov.b32 pc4, tt; mov.b32 pc5, tt; mov.b32 pc6, tt; mov.b32 pc7, tt; mov.b32 pc8, tt; mov.b32 pc9, tt; mov.b32 pc10, tt; mov.b32 pc11, tt;\n"
        "mov.b32 pc12, tt; mov.b32 pc13, tt; mov.b32 pc14, tt; mov.b32 pc15, tt; mov.b32 pc16, tt; mov.b32 pc17, tt; mov.b32 pc18, tt; mov.b32 pc19, tt; mov.b32 pc20, tt; mov.b32 pc21, tt; mov.b32 pc22, tt; mov.b32 pc23, tt;\n"
        "mov.b32 ps0, tt; mov.b32 ps1, tt; mov.b32 ps2, tt; mov.b32 ps3, tt; mov.b32 ps4, tt; mov.b32 ps5, tt; mov.b32 ps6, tt; mov.b32 ps7, tt; mov.b32 pq0, tt; mov.b32 pq1, tt; mov.b32 pq2, tt; mov.b32 pq3, tt;\n"
        "ld.volatile.shared.v2.b32 {pw1, pw0}, [%6]; xor.b32 tt, tt, pw1;\n"
        "ld.volatile.shared.v2.b32 {pw3, pw2}, [%6]; xor.b32 tt, tt, pw3;\n"
        "ld.volatile.shared.v2.b32 {pw5, pw4}, [%6]; xor.b32 tt, tt, pw5;\n"
        "ld.volatile.shared.v2.b32 {pw7, pw6}, [%6]; xor.b32 tt, tt, pw7;\n"
        "ld.volatile.shared.v2.b32 {pw9, pw8}, [%6]; xor.b32 tt, tt, pw9;\n"
        "ld.volatile.shared.v2.b32 {pw11, pw10}, [%6]; xor.b32 tt, tt, pw11;\n"
        "ld.volatile.shared.v2.b32 {pw13, pw12}, [%6]; xor.b32 tt, tt, pw13;\n"
        "ld.volatile.shared.v2.b32 {pw15, pw14}, [%6]; xor.b32 tt, tt, pw15;\n"
        "ld.volatile.shared.v2.b32 {pw17, pw16}, [%6]; xor.b32 tt, tt, pw17;\n"
        "ld.volatile.shared.v2.b32 {pw19, pw18}, [%6]; xor.b32 tt, tt, pw19;\n"
        "ld.volatile.shared.v2.b32 {pw21, pw20}, [%6]; xor.b32 tt, tt, pw21;\n"
        "ld.volatile.shared.v2.b32 {pw23, pw22}, [%6]; xor.b32 tt, tt, pw23;\n"
        "ld.volatile.shared.v2.b32 {pw25, pw24}, [%6]; xor.b32 tt, tt, pw25;\n"
        "ld.volatile.shared.v2.b32 {pw27, pw26}, [%6]; xor.b32 tt, tt, pw27;\n"
        "ld.volatile.shared.v2.b32 {pw29, pw28}, [%6]; xor.b32 tt, tt, pw29;\n"
        "ld.volatile.shared.v2.b32 {pw31, pw30}, [%6]; xor.b32 tt, tt, pw31;\n"
        "ld.volatile.shared.v2.b32 {pw33, pw32}, [%6]; xor.b32 tt, tt, pw33;\n"
        "ld.volatile.shared.v2.b32 {pw35, pw34}, [%6]; xor.b32 tt, tt, pw35;\n"
        "ld.volatile.shared.v2.b32 {pw37, pw36}, [%6]; xor.b32 tt, tt, pw37;\n"
        "ld.volatile.shared.v2.b32 {pw39, pw38}, [%6]; xor.b32 tt, tt, pw39;\n"
        "ld.volatile.shared.v2.b32 {pw41, pw40}, [%6]; xor.b32 tt, tt, pw41;\n"
        "ld.volatile.shared.v2.b32 {pw43, pw42}, [%6]; xor.b32 tt, tt, pw43;\n"
        "ld.volatile.shared.v2.b32 {pw45, pw44}, [%6]; xor.b32 tt, tt, pw45;\n"
        "ld.volatile.shared.v2.b32 {pw47, pw46}, [%6]; xor.b32 tt, tt, pw47;\n"
        "ld.volatile.shared.v2.b32 {pw49, pw48}, [%6]; xor.b32 tt, tt, pw49;\n"
        "ld.volatile.shared.v2.b32 {pw51, pw50}, [%6]; xor.b32 tt, tt, pw51;\n"
        "ld.volatile.shared.v2.b32 {pw53, pw52}, [%6]; xor.b32 tt, tt, pw53;\n"
        "mov.b32 us, tt; setp.ne.u32 pw, %15, 7;\n"
        "wgmma.fence.sync.aligned;\n"
        "setp.eq.u32 pr, %15, 1000; @pr bra.uni B0;\n"
        "setp.eq.u32 pr, %15, 1001; @pr bra.uni B1;\n"
        "setp.eq.u32 pr, %15, 1002; @pr bra.uni C0;\n"
        "setp.eq.u32 pr, %15, 1003; @pr bra.uni N0;\n"
        "setp.eq.u32 pr, %15, 1004; @pr bra.uni N1;\n"
        "setp.eq.u32 pr, %15, 1005; @pr bra.uni N2;\n"
        "setp.eq.u32 pr, %15, 1006; @pr bra.uni N3;\n"
        "trap;\n"
        "DONE:\n"
        ASM_TRC("t", 0)
        "fence.proxy.async.shared::cta;\n"
        "@pl mbarrier.arrive.shared::cta.b64 _, [sp+174984];\n"
        "}\n"
        :: "r"(sb + SM_X + c.xoff[0]), "r"(sb + SM_X + c.xoff[1]), "r"(sb + SM_Y1 + c.yoff[0][0]), "r"(sb + SM_Y1 + c.yoff[0][1]),
           "r"(sb + SM_Y1 + c.yoff[1][0]), "r"(sb + SM_Y1 + c.yoff[1][1]), "r"(c.stat), "r"(c.own), "r"(c.lane),
           "l"(prm.sel[0]), "l"(prm.sel[1]), "l"(prm.sel[2]), "r"(prm.ydesc), "f"(LN_EPS_SCALED), "f"(RSTD_SCALE), "r"(prm.w1desc)
        : "memory");
}

__device__ __forceinline__ void produce(const Producer& c, const Params& prm) {
    uint32_t B[24], C[24];
    const RowCopy rc = row_copy(prm);
    uint32_t st[8];
    uint32_t v[6][6];
    {
        uint32_t ws[6];
#pragma unroll
        for (int u = 0; u < 6; u++) {
            ws[u] = c.w[0][u];
#pragma unroll
            for (int t = 1; t < 9; t++) ws[u] = bf2_add(ws[u], c.w[t][u]);
        }
        SMARK(2);
        mbar_wait_c<0>(sb + SM_XFULL);
        SMARK(3);
        lds128(v[0], sb + SM_X + c.xoff[0] + 2 * 192);
        asm volatile("ld.shared.v2.b32 {%0,%1}, [%2];" : "=r"(v[0][4]), "=r"(v[0][5]) : "r"(sb + SM_X + c.xoff[1] + 2 * 192));
        const uint32_t p = bf2_add(bf2_fma(v[0][2], ws[2], bf2_fma(v[0][1], ws[1], bf2_mul(v[0][0], ws[0]))),
                                   bf2_fma(v[0][5], ws[5], bf2_fma(v[0][4], ws[4], bf2_mul(v[0][3], ws[3]))));
        float e = quad_sum(bf_lo(p) + bf_hi(p));
        e = (e + __shfl_xor_sync(0xffffffffu, e, 4)) * (-1.0f / CH);
        st[1] = st[3] = st[5] = st[7] = pack_bf2(e, e);
#pragma unroll
        for (int k = 0; k < NX; k++) sts32(c.own + k * SLOT_BYTES + 4, st[1]);
#pragma unroll
        for (int r = 0; r < 24; r++) C[r] = 0;
    }
#pragma unroll 1
    for (int i = loop_init<0>();; i++) {
        mbar_wait_c<0>(sb + SM_XFULL + i * SLOT_BYTES);
        SMARK(4 + i);
        load_x(v, c, sb + SM_X + i * SLOT_BYTES);
        fence_async_smem();
        if (c.warp == i) {
            named_sync(6 + i, 128);
            issue_row_load(rc, i + NX, i);
        } else {
            asm volatile("bar.arrive %0, 128;" ::"r"(6 + i) : "memory");
        }
        if (i == 2) break;
        conv_row<1, 1>(B, C, v, c);
        conv_row<0, 0>(C, st, v, c);
    }
    asm volatile(".reg .b32 pw<54>, pb<24>, pc<24>, pv<36>, ps<8>;");
    hand_over<0>(c, B, C, v);
    asm volatile("mov.b32 ps1, %0; mov.b32 ps3, %1; mov.b32 ps5, %2; mov.b32 ps7, %3;" ::"r"(st[1]), "r"(st[3]), "r"(st[5]), "r"(st[7]));
    SMARK(7);
    produce_tiles(c, prm);
    mbar_arrive_if(sb + SM_Y1FULL + ROWS_PER_CTA % NX * SLOT_BYTES, c.lane == 0);
}

struct Duty {
    const char* g;
    const char* zeros;
    long long step;
    uint32_t s, bytes;
    int end, zero;
};
__device__ __forceinline__ Duty make_duty(const Params& prm, int wg, int w) {
    const RowCopy rc = row_copy(prm);
    Duty d;
    d.g = (w == 2 ? rc.y0 : rc.x0 + (w == 0 ? rc.cut0 : w == 1 ? 32 * 192 : 192)) +
          (wg + (w == 2 ? 0 : w < 2 ? 2 * NX : 2 * NX + L2_AHEAD)) * rc.stride;
    d.step = NX * rc.stride;
    d.s = wg * SLOT_BYTES + (w == 2 ? sb + SM_Y1 : sb + SM_X + (w == 0 ? rc.cut0 : XHALF_B));
    d.bytes = w >= 2 ? TILE_BYTES : XHALF_BYTES - (w == 0 ? rc.cut0 : rc.cut1);
    d.end = w == 2 ? ROWS_PER_CTA : w < 2 ? STEPS + 1 - 2 * NX : rc.last + 1 - 2 * NX - L2_AHEAD;
    d.zero = rc.last + 1 - 2 * NX;
    d.zeros = rc.zeros;
    return d;
}

static_assert(sb + SM_Y1FULL == 174984 && sb + SM_Y1EMPTY == 174992 && sb + SM_XFULL == 174976 && SLOT_BYTES == 26624 &&
              sb + SM_GAMMA == 229248 && SM_BETA == SM_GAMMA + 768 && sb + SM_BAR + BAR_W2 * 8 == 230872 && SM_W2 == 73728 &&
              sb + SM_BUF3 == 187392 && sb + SM_BAR + (BAR_Y2FULL + 3) * 8 == 230824, "layout");
__device__ __forceinline__ void consume(float (&acc)[2][2], uint32_t w1t, uint32_t yd, uint32_t wd, uint32_t own_slot, const Duty& d,
                                        uint32_t role, uint32_t lane, const Params& prm) {
    asm volatile(
        "{\n"
        ".reg .b32 z<32>, w<44>, p<2>, a<4>, lo<4>, hi<4>, t<2>, g<2>, q<4>, dl<6>, dh<6>, n, so, sp, ph, c, tt, cnt;\n"
        ".reg .b16 xl, xh, xr;\n"
        ".reg .b32 f0, f1;\n"
        ".reg .b64 ds<6>, wd, gp, src;\n"
        ".reg .pred pt, pf, pr, pw, pl, pe;\n"
        "setp.ne.b32 pt, 1, 0; setp.ne.b32 pf, 0, 0; setp.eq.u32 pl, %15, 0;\n"
        "mov.b32 c, 0x40D940D9;\n"
        "ldmatrix.sync.aligned.m8n8.x4.trans.shared.b16 {z0,z1,z2,z3}, [%4+22528];\n"
        "ldmatrix.sync.aligned.m8n8.x4.trans.shared.b16 {w0,w1,w2,w3}, [%4+0];\n"
        "ldmatrix.sync.aligned.m8n8.x4.trans.shared.b16 {w4,w5,w6,w7}, [%4+2048];\n"
        "ldmatrix.sync.aligned.m8n8.x4.trans.shared.b16 {w8,w9,w10,w11}, [%4+4096];\n"
        "ldmatrix.sync.aligned.m8n8.x4.trans.shared.b16 {w12,w13,w14,w15}, [%4+6144];\n"
        "ldmatrix.sync.aligned.m8n8.x4.trans.shared.b16 {w16,w17,w18,w19}, [%4+8192];\n"
        "ldmatrix.sync.aligned.m8n8.x4.trans.shared.b16 {w20,w21,w22,w23}, [%4+10240];\n"
        "ldmatrix.sync.aligned.m8n8.x4.trans.shared.b16 {w24,w25,w26,w27}, [%4+12288];\n"
        "ldmatrix.sync.aligned.m8n8.x4.trans.shared.b16 {w28,w29,w30,w31}, [%4+14336];\n"
        "ldmatrix.sync.aligned.m8n8.x4.trans.shared.b16 {w32,w33,w34,w35}, [%4+16384];\n"
        "ldmatrix.sync.aligned.m8n8.x4.trans.shared.b16 {w36,w37,w38,w39}, [%4+18432];\n"
        "ldmatrix.sync.aligned.m8n8.x4.trans.shared.b16 {w40,w41,w42,w43}, [%4+20480];\n"
        "shl.b32 f0, z0, 16; and.b32 f1, z0, 0xffff0000; cvt.rn.f16x2.f32 z0, f1, f0; shl.b32 f0, z1, 16; and.b32 f1, z1, 0xffff0000; cvt.rn.f16x2.f32 z1, f1, f0; shl.b32 f0, z2, 16; and.b32 f1, z2, 0xffff0000; cvt.rn.f16x2.f32 z2, f1, f0; shl.b32 f0, z3, 16; and.b32 f1, z3, 0xffff0000; cvt.rn.f16x2.f32 z3, f1, f0;\n"
        "stmatrix.sync.aligned.m8n8.x4.trans.shared.b16 [%4+22528], {z0,z1,z2,z3};\n"
        "shl.b32 f0, w0, 16; and.b32 f1, w0, 0xffff0000; cvt.rn.f16x2.f32 w0, f1, f0; shl.b32 f0, w1, 16; and.b32 f1, w1, 0xffff0000; cvt.rn.f16x2.f32 w1, f1, f0; shl.b32 f0, w2, 16; and.b32 f1, w2, 0xffff0000; cvt.rn.f16x2.f32 w2, f1, f0; shl.b32 f0, w3, 16; and.b32 f1, w3, 0xffff0000; cvt.rn.f16x2.f32 w3, f1, f0;\n"
        "stmatrix.sync.aligned.m8n8.x4.trans.shared.b16 [%4+0], {w0,w1,w2,w3};\n"
        "shl.b32 f0, w4, 16; and.b32 f1, w4, 0xffff0000; cvt.rn.f16x2.f32 w4, f1, f0; shl.b32 f0, w5, 16; and.b32 f1, w5, 0xffff0000; cvt.rn.f16x2.f32 w5, f1, f0; shl.b32 f0, w6, 16; and.b32 f1, w6, 0xffff0000; cvt.rn.f16x2.f32 w6, f1, f0; shl.b32 f0, w7, 16; and.b32 f1, w7, 0xffff0000; cvt.rn.f16x2.f32 w7, f1, f0;\n"
        "stmatrix.sync.aligned.m8n8.x4.trans.shared.b16 [%4+2048], {w4,w5,w6,w7};\n"
        "shl.b32 f0, w8, 16; and.b32 f1, w8, 0xffff0000; cvt.rn.f16x2.f32 w8, f1, f0; shl.b32 f0, w9, 16; and.b32 f1, w9, 0xffff0000; cvt.rn.f16x2.f32 w9, f1, f0; shl.b32 f0, w10, 16; and.b32 f1, w10, 0xffff0000; cvt.rn.f16x2.f32 w10, f1, f0; shl.b32 f0, w11, 16; and.b32 f1, w11, 0xffff0000; cvt.rn.f16x2.f32 w11, f1, f0;\n"
        "stmatrix.sync.aligned.m8n8.x4.trans.shared.b16 [%4+4096], {w8,w9,w10,w11};\n"
        "shl.b32 f0, w12, 16; and.b32 f1, w12, 0xffff0000; cvt.rn.f16x2.f32 w12, f1, f0; shl.b32 f0, w13, 16; and.b32 f1, w13, 0xffff0000; cvt.rn.f16x2.f32 w13, f1, f0; shl.b32 f0, w14, 16; and.b32 f1, w14, 0xffff0000; cvt.rn.f16x2.f32 w14, f1, f0; shl.b32 f0, w15, 16; and.b32 f1, w15, 0xffff0000; cvt.rn.f16x2.f32 w15, f1, f0;\n"
        "stmatrix.sync.aligned.m8n8.x4.trans.shared.b16 [%4+6144], {w12,w13,w14,w15};\n"
        "shl.b32 f0, w16, 16; and.b32 f1, w16, 0xffff0000; cvt.rn.f16x2.f32 w16, f1, f0; shl.b32 f0, w17, 16; and.b32 f1, w17, 0xffff0000; cvt.rn.f16x2.f32 w17, f1, f0; shl.b32 f0, w18, 16; and.b32 f1, w18, 0xffff0000; cvt.rn.f16x2.f32 w18, f1, f0; shl.b32 f0, w19, 16; and.b32 f1, w19, 0xffff0000; cvt.rn.f16x2.f32 w19, f1, f0;\n"
        "stmatrix.sync.aligned.m8n8.x4.trans.shared.b16 [%4+8192], {w16,w17,w18,w19};\n"
        "shl.b32 f0, w20, 16; and.b32 f1, w20, 0xffff0000; cvt.rn.f16x2.f32 w20, f1, f0; shl.b32 f0, w21, 16; and.b32 f1, w21, 0xffff0000; cvt.rn.f16x2.f32 w21, f1, f0; shl.b32 f0, w22, 16; and.b32 f1, w22, 0xffff0000; cvt.rn.f16x2.f32 w22, f1, f0; shl.b32 f0, w23, 16; and.b32 f1, w23, 0xffff0000; cvt.rn.f16x2.f32 w23, f1, f0;\n"
        "stmatrix.sync.aligned.m8n8.x4.trans.shared.b16 [%4+10240], {w20,w21,w22,w23};\n"
        "shl.b32 f0, w24, 16; and.b32 f1, w24, 0xffff0000; cvt.rn.f16x2.f32 w24, f1, f0; shl.b32 f0, w25, 16; and.b32 f1, w25, 0xffff0000; cvt.rn.f16x2.f32 w25, f1, f0; shl.b32 f0, w26, 16; and.b32 f1, w26, 0xffff0000; cvt.rn.f16x2.f32 w26, f1, f0; shl.b32 f0, w27, 16; and.b32 f1, w27, 0xffff0000; cvt.rn.f16x2.f32 w27, f1, f0;\n"
        "stmatrix.sync.aligned.m8n8.x4.trans.shared.b16 [%4+12288], {w24,w25,w26,w27};\n"
        "shl.b32 f0, w28, 16; and.b32 f1, w28, 0xffff0000; cvt.rn.f16x2.f32 w28, f1, f0; shl.b32 f0, w29, 16; and.b32 f1, w29, 0xffff0000; cvt.rn.f16x2.f32 w29, f1, f0; shl.b32 f0, w30, 16; and.b32 f1, w30, 0xffff0000; cvt.rn.f16x2.f32 w30, f1, f0; shl.b32 f0, w31, 16; and.b32 f1, w31, 0xffff0000; cvt.rn.f16x2.f32 w31, f1, f0;\n"
        "stmatrix.sync.aligned.m8n8.x4.trans.shared.b16 [%4+14336], {w28,w29,w30,w31};\n"
        "shl.b32 f0, w32, 16; and.b32 f1, w32, 0xffff0000; cvt.rn.f16x2.f32 w32, f1, f0; shl.b32 f0, w33, 16; and.b32 f1, w33, 0xffff0000; cvt.rn.f16x2.f32 w33, f1, f0; shl.b32 f0, w34, 16; and.b32 f1, w34, 0xffff0000; cvt.rn.f16x2.f32 w34, f1, f0; shl.b32 f0, w35, 16; and.b32 f1, w35, 0xffff0000; cvt.rn.f16x2.f32 w35, f1, f0;\n"
        "stmatrix.sync.aligned.m8n8.x4.trans.shared.b16 [%4+16384], {w32,w33,w34,w35};\n"
        "shl.b32 f0, w36, 16; and.b32 f1, w36, 0xffff0000; cvt.rn.f16x2.f32 w36, f1, f0; shl.b32 f0, w37, 16; and.b32 f1, w37, 0xffff0000; cvt.rn.f16x2.f32 w37, f1, f0; shl.b32 f0, w38, 16; and.b32 f1, w38, 0xffff0000; cvt.rn.f16x2.f32 w38, f1, f0; shl.b32 f0, w39, 16; and.b32 f1, w39, 0xffff0000; cvt.rn.f16x2.f32 w39, f1, f0;\n"
        "stmatrix.sync.aligned.m8n8.x4.trans.shared.b16 [%4+18432], {w36,w37,w38,w39};\n"
        "shl.b32 f0, w40, 16; and.b32 f1, w40, 0xffff0000; cvt.rn.f16x2.f32 w40, f1, f0; shl.b32 f0, w41, 16; and.b32 f1, w41, 0xffff0000; cvt.rn.f16x2.f32 w41, f1, f0; shl.b32 f0, w42, 16; and.b32 f1, w42, 0xffff0000; cvt.rn.f16x2.f32 w42, f1, f0; shl.b32 f0, w43, 16; and.b32 f1, w43, 0xffff0000; cvt.rn.f16x2.f32 w43, f1, f0;\n"
        "stmatrix.sync.aligned.m8n8.x4.trans.shared.b16 [%4+20480], {w40,w41,w42,w43};\n"
        "fence.proxy.async.shared::cta;\n"
        ASM_SMARK
        "mov.b32 p0, 0; mov.b32 p1, 0; mov.b32 t0, 0; mov.b32 t1, 0; mov.b32 g0, 0; mov.b32 g1, 0; mov.b32 a0, 0; mov.b32 a1, 0; mov.b32 a2, 0; mov.b32 a3, 0; mov.b32 lo0, 0; mov.b32 lo1, 0; mov.b32 hi0, 0; mov.b32 hi1, 0; mov.b32 q0, 0; mov.b32 q1, 0; mov.b32 q2, 0; mov.b32 q3, 0;\n"
        "mov.b32 z16, 0; mov.b32 z17, 0; mov.b32 z18, 0; mov.b32 z19, 0; mov.b32 z20, 0; mov.b32 z21, 0; mov.b32 z22, 0; mov.b32 z23, 0; mov.b32 z24, 0; mov.b32 z25, 0; mov.b32 z26, 0; mov.b32 z27, 0; mov.b32 z28, 0; mov.b32 z29, 0; mov.b32 z30, 0; mov.b32 z31, 0;\n"
        "mov.f32 %0, 0f00000000; mov.f32 %1, 0f00000000; mov.f32 %2, 0f00000000; mov.f32 %3, 0f00000000;\n"
        "mov.u32 n, 0; mov.u32 so, 0; mov.u32 sp, 0; mov.u32 ph, 0; mov.b64 gp, %8; mov.b64 wd, {%6, 0x40000040};\n"
        "shr.u32 tt, so, 4; cvt.u64.u32 ds5, tt; add.s64 ds0, ds5, %20; add.s64 ds4, ds5, %21;\n"
        "add.s64 ds1, ds0, 2; add.s64 ds2, ds0, 4; add.s64 ds3, ds0, 6; add.s64 ds5, ds4, 2;\n"
        "mbarrier.try_wait.parity.shared::cta.b64 pw, [so+174984], ph;\n"
        "@!pw bra.uni SPIN0;\n"
        "BACK0:\n"
        ASM_TS
        "wgmma.fence.sync.aligned;\n"
        "wgmma.mma_async.sync.aligned.m64n64k16.f16.f16.f16 {z0,z1,z2,z3,z4,z5,z6,z7,z8,z9,z10,z11,z12,z13,z14,z15}, {w0,w1,w2,w3}, ds0, pf, 1, 1, 0;\n"
        "wgmma.mma_async.sync.aligned.m64n64k16.f16.f16.f16 {z0,z1,z2,z3,z4,z5,z6,z7,z8,z9,z10,z11,z12,z13,z14,z15}, {w4,w5,w6,w7}, ds1, pt, 1, 1, 0;\n"
        "wgmma.mma_async.sync.aligned.m64n64k16.f16.f16.f16 {z0,z1,z2,z3,z4,z5,z6,z7,z8,z9,z10,z11,z12,z13,z14,z15}, {w8,w9,w10,w11}, ds2, pt, 1, 1, 0;\n"
        "wgmma.mma_async.sync.aligned.m64n64k16.f16.f16.f16 {z0,z1,z2,z3,z4,z5,z6,z7,z8,z9,z10,z11,z12,z13,z14,z15}, {w12,w13,w14,w15}, ds3, pt, 1, 1, 0;\n"
        "wgmma.mma_async.sync.aligned.m64n64k16.f16.f16.f16 {z0,z1,z2,z3,z4,z5,z6,z7,z8,z9,z10,z11,z12,z13,z14,z15}, {w16,w17,w18,w19}, ds4, pt, 1, 1, 0;\n"
        "wgmma.mma_async.sync.aligned.m64n64k16.f16.f16.f16 {z0,z1,z2,z3,z4,z5,z6,z7,z8,z9,z10,z11,z12,z13,z14,z15}, {w20,w21,w22,w23}, ds5, pt, 1, 1, 0;\n"
        "wgmma.commit_group.sync.aligned;\n"
        "setp.eq.u32 pr, so, %7;\n"
        "@pr bra.uni DUTY;\n"
        "TOP:\n"
        ASM_TRC("n", 0)
        "wgmma.wait_group.sync.aligned 0;\n"
        "mov.b32 {xl, xh}, a2; tanh.approx.f16 xr, xh; cvt.u32.u16 hi0, xr; mul.rn.f16x2 a3, z31, p0; fma.rn.f16x2 p0, z0, z0, c; fma.rn.f16x2 q3, g0, g0, q3; fma.rn.f16x2 g0, z28, t0, z28; prmt.b32 t0, lo1, hi1, 0x5410; mov.b32 {xl, xh}, a2; tanh.approx.f16 xr, xl; cvt.u32.u16 lo0, xr;\n"
        "B31:\n"
        "mov.b32 {xl, xh}, a3; tanh.approx.f16 xr, xh; cvt.u32.u16 hi1, xr; mul.rn.f16x2 a0, z0, p0; fma.rn.f16x2 p0, z1, z1, c; fma.rn.f16x2 q2, g0, g0, q2; fma.rn.f16x2 g0, z29, t0, z29; prmt.b32 t0, lo0, hi0, 0x5410; mov.b32 {xl, xh}, a3; tanh.approx.f16 xr, xl; cvt.u32.u16 lo1, xr;\n"
        "B0:\n"
        "mov.b32 {xl, xh}, a0; tanh.approx.f16 xr, xh; cvt.u32.u16 hi0, xr; mul.rn.f16x2 a1, z1, p0; fma.rn.f16x2 p0, z2, z2, c; fma.rn.f16x2 q3, g0, g0, q3; fma.rn.f16x2 g0, z30, t0, z30; prmt.b32 t0, lo1, hi1, 0x5410; mov.b32 {xl, xh}, a0; tanh.approx.f16 xr, xl; cvt.u32.u16 lo0, xr;\n"
        "B1:\n"
        "mov.b32 {xl, xh}, a1; tanh.approx.f16 xr, xh; cvt.u32.u16 hi1, xr; mul.rn.f16x2 a2, z2, p0; fma.rn.f16x2 p0, z3, z3, c; fma.rn.f16x2 q2, g0, g0, q2; fma.rn.f16x2 g0, z31, t0, z31; prmt.b32 t0, lo0, hi0, 0x5410; mov.b32 {xl, xh}, a1; tanh.approx.f16 xr, xl; cvt.u32.u16 lo1, xr;\n"
        "B2:\n"
        "wgmma.fence.sync.aligned;\n"
        "wgmma.mma_async.sync.aligned.m64n64k16.f16.f16.f16 {z16,z17,z18,z19,z20,z21,z22,z23,z24,z25,z26,z27,z28,z29,z30,z31}, {w24,w25,w26,w27}, ds0, pf, 1, 1, 0;\n"
        "wgmma.mma_async.sync.aligned.m64n64k16.f16.f16.f16 {z16,z17,z18,z19,z20,z21,z22,z23,z24,z25,z26,z27,z28,z29,z30,z31}, {w28,w29,w30,w31}, ds1, pt, 1, 1, 0;\n"
        "wgmma.mma_async.sync.aligned.m64n64k16.f16.f16.f16 {z16,z17,z18,z19,z20,z21,z22,z23,z24,z25,z26,z27,z28,z29,z30,z31}, {w32,w33,w34,w35}, ds2, pt, 1, 1, 0;\n"
        "mov.b32 {xl, xh}, a2; tanh.approx.f16 xr, xh; cvt.u32.u16 hi0, xr; mul.rn.f16x2 a3, z3, p0; fma.rn.f16x2 p0, z4, z4, c; fma.rn.f16x2 q3, g0, g0, q3; fma.rn.f16x2 g0, z0, t0, z0; prmt.b32 t0, lo1, hi1, 0x5410; mov.b32 {xl, xh}, a2; tanh.approx.f16 xr, xl; cvt.u32.u16 lo0, xr;\n"
        "B3:\n"
        "mov.b32 {xl, xh}, a3; tanh.approx.f16 xr, xh; cvt.u32.u16 hi1, xr; mul.rn.f16x2 a0, z4, p0; fma.rn.f16x2 p0, z5, z5, c; fma.rn.f16x2 q0, g0, g0, q0; fma.rn.f16x2 g0, z1, t0, z1; prmt.b32 t0, lo0, hi0, 0x5410; mov.b32 {xl, xh}, a3; tanh.approx.f16 xr, xl; cvt.u32.u16 lo1, xr;\n"
        "B4:\n"
        "mov.b32 {xl, xh}, a0; tanh.approx.f16 xr, xh; cvt.u32.u16 hi0, xr; mul.rn.f16x2 a1, z5, p0; fma.rn.f16x2 p0, z6, z6, c; fma.rn.f16x2 q1, g0, g0, q1; fma.rn.f16x2 g0, z2, t0, z2; prmt.b32 t0, lo1, hi1, 0x5410; mov.b32 {xl, xh}, a0; tanh.approx.f16 xr, xl; cvt.u32.u16 lo0, xr;\n"
        "B5:\n"
        "wgmma.mma_async.sync.aligned.m64n64k16.f16.f16.f16 {z16,z17,z18,z19,z20,z21,z22,z23,z24,z25,z26,z27,z28,z29,z30,z31}, {w36,w37,w38,w39}, ds3, pt, 1, 1, 0;\n"
        "wgmma.mma_async.sync.aligned.m64n64k16.f16.f16.f16 {z16,z17,z18,z19,z20,z21,z22,z23,z24,z25,z26,z27,z28,z29,z30,z31}, {w40,w41,w42,w43}, ds4, pt, 1, 1, 0;\n"
        "wgmma.mma_async.sync.aligned.m64n64k16.f16.f16.f16 {z16,z17,z18,z19,z20,z21,z22,z23,z24,z25,z26,z27,z28,z29,z30,z31}, wd, ds5, pt, 1, 1, 1, 0;\n"
        "wgmma.commit_group.sync.aligned;\n"
        "mov.b32 {xl, xh}, a1; tanh.approx.f16 xr, xh; cvt.u32.u16 hi1, xr; mul.rn.f16x2 a2, z6, p0; fma.rn.f16x2 p0, z7, z7, c; fma.rn.f16x2 q0, g0, g0, q0; fma.rn.f16x2 g0, z3, t0, z3; prmt.b32 t0, lo0, hi0, 0x5410; mov.b32 {xl, xh}, a1; tanh.approx.f16 xr, xl; cvt.u32.u16 lo1, xr;\n"
        "B6:\n"
        "mov.u32 sp, so; add.u32 so, so, 26624; setp.eq.u32 pr, so, 79872; selp.u32 so, 0, so, pr; selp.u32 tt, 1, 0, pr; xor.b32 ph, ph, tt;\n"
        "mov.b32 {xl, xh}, a2; tanh.approx.f16 xr, xh; cvt.u32.u16 hi0, xr; mul.rn.f16x2 a3, z7, p0; fma.rn.f16x2 p0, z8, z8, c; fma.rn.f16x2 q1, g0, g0, q1; fma.rn.f16x2 g0, z4, t0, z4; prmt.b32 t0, lo1, hi1, 0x5410; mov.b32 {xl, xh}, a2; tanh.approx.f16 xr, xl; cvt.u32.u16 lo0, xr;\n"
        "B7:\n"
        "shr.u32 tt, so, 4;\n"
        "mov.b64 {dl0, dh0}, ds0; add.u32 dl0, tt, 74816; mov.b64 ds0, {dl0, dh0}; mov.b64 {dl0, dh0}, ds1; add.u32 dl0, tt, 74818; mov.b64 ds1, {dl0, dh0}; mov.b64 {dl0, dh0}, ds2; add.u32 dl0, tt, 74820; mov.b64 ds2, {dl0, dh0}; mov.b64 {dl0, dh0}, ds3; add.u32 dl0, tt, 74822; mov.b64 ds3, {dl0, dh0}; mov.b64 {dl0, dh0}, ds4; add.u32 dl0, tt, 75328; mov.b64 ds4, {dl0, dh0}; mov.b64 {dl0, dh0}, ds5; add.u32 dl0, tt, 75330; mov.b64 ds5, {dl0, dh0};\n"
        "mov.b32 {xl, xh}, a3; tanh.approx.f16 xr, xh; cvt.u32.u16 hi1, xr; mul.rn.f16x2 a0, z8, p0; fma.rn.f16x2 p0, z9, z9, c; fma.rn.f16x2 q0, g0, g0, q0; fma.rn.f16x2 g0, z5, t0, z5; prmt.b32 t0, lo0, hi0, 0x5410; mov.b32 {xl, xh}, a3; tanh.approx.f16 xr, xl; cvt.u32.u16 lo1, xr;\n"
        "B8:\n"
        "mov.b32 {xl, xh}, a0; tanh.approx.f16 xr, xh; cvt.u32.u16 hi0, xr; mul.rn.f16x2 a1, z9, p0; fma.rn.f16x2 p0, z10, z10, c; fma.rn.f16x2 q1, g0, g0, q1; fma.rn.f16x2 g0, z6, t0, z6; prmt.b32 t0, lo1, hi1, 0x5410; mov.b32 {xl, xh}, a0; tanh.approx.f16 xr, xl; cvt.u32.u16 lo0, xr;\n"
        "B9:\n"
        "mov.b32 {xl, xh}, a1; tanh.approx.f16 xr, xh; cvt.u32.u16 hi1, xr; mul.rn.f16x2 a2, z10, p0; fma.rn.f16x2 p0, z11, z11, c; fma.rn.f16x2 q0, g0, g0, q0; fma.rn.f16x2 g0, z7, t0, z7; prmt.b32 t0, lo0, hi0, 0x5410; mov.b32 {xl, xh}, a1; tanh.approx.f16 xr, xl; cvt.u32.u16 lo1, xr;\n"
        "B10:\n"
        "mov.b32 {xl, xh}, a2; tanh.approx.f16 xr, xh; cvt.u32.u16 hi0, xr; mul.rn.f16x2 a3, z11, p0; fma.rn.f16x2 p0, z12, z12, c; fma.rn.f16x2 q1, g0, g0, q1; fma.rn.f16x2 g0, z8, t0, z8; prmt.b32 t0, lo1, hi1, 0x5410; mov.b32 {xl, xh}, a2; tanh.approx.f16 xr, xl; cvt.u32.u16 lo0, xr;\n"
        "B11:\n"
        "mov.b32 {xl, xh}, a3; tanh.approx.f16 xr, xh; cvt.u32.u16 hi1, xr; mul.rn.f16x2 a0, z12, p0; fma.rn.f16x2 p0, z13, z13, c; fma.rn.f16x2 q0, g0, g0, q0; fma.rn.f16x2 g0, z9, t0, z9; prmt.b32 t0, lo0, hi0, 0x5410; mov.b32 {xl, xh}, a3; tanh.approx.f16 xr, xl; cvt.u32.u16 lo1, xr;\n"
        "B12:\n"
        "mov.b32 {xl, xh}, a0; tanh.approx.f16 xr, xh; cvt.u32.u16 hi0, xr; mul.rn.f16x2 a1, z13, p0; fma.rn.f16x2 p0, z14, z14, c; fma.rn.f16x2 q1, g0, g0, q1; fma.rn.f16x2 g0, z10, t0, z10; prmt.b32 t0, lo1, hi1, 0x5410; mov.b32 {xl, xh}, a0; tanh.approx.f16 xr, xl; cvt.u32.u16 lo0, xr;\n"
        "B13:\n"
        "mov.b32 {xl, xh}, a1; tanh.approx.f16 xr, xh; cvt.u32.u16 hi1, xr; mul.rn.f16x2 a2, z14, p0; fma.rn.f16x2 p0, z15, z15, c; fma.rn.f16x2 q0, g0, g0, q0; fma.rn.f16x2 g0, z11, t0, z11; prmt.b32 t0, lo0, hi0, 0x5410; mov.b32 {xl, xh}, a1; tanh.approx.f16 xr, xl; cvt.u32.u16 lo1, xr;\n"
        "B14:\n"
        "wgmma.wait_group.sync.aligned 0;\n"
        "cp.async.bulk.wait_group.read 0;\n"
        "@pl mbarrier.arrive.shared::cta.b64 _, [sp+174992];\n"
        "mov.b32 {xl, xh}, a2; tanh.approx.f16 xr, xh; cvt.u32.u16 hi0, xr; mul.rn.f16x2 a3, z15, p0; fma.rn.f16x2 p0, z16, z16, c; fma.rn.f16x2 q1, g0, g0, q1; fma.rn.f16x2 g0, z12, t0, z12; prmt.b32 t0, lo1, hi1, 0x5410; mov.b32 {xl, xh}, a2; tanh.approx.f16 xr, xl; cvt.u32.u16 lo0, xr;\n"
        "B15:\n"
        "mov.b32 {xl, xh}, a3; tanh.approx.f16 xr, xh; cvt.u32.u16 hi1, xr; mul.rn.f16x2 a0, z16, p0; fma.rn.f16x2 p0, z17, z17, c; fma.rn.f16x2 q0, g0, g0, q0; fma.rn.f16x2 g0, z13, t0, z13; prmt.b32 t0, lo0, hi0, 0x5410; mov.b32 {xl, xh}, a3; tanh.approx.f16 xr, xl; cvt.u32.u16 lo1, xr;\n"
        "B16:\n"
        "mbarrier.try_wait.parity.shared::cta.b64 pw, [so+174984], ph;\n"
        "mov.b32 {xl, xh}, a0; tanh.approx.f16 xr, xh; cvt.u32.u16 hi0, xr; mul.rn.f16x2 a1, z17, p0; fma.rn.f16x2 p0, z18, z18, c; fma.rn.f16x2 q1, g0, g0, q1; fma.rn.f16x2 g0, z14, t0, z14; prmt.b32 t0, lo1, hi1, 0x5410; mov.b32 {xl, xh}, a0; tanh.approx.f16 xr, xl; cvt.u32.u16 lo0, xr;\n"
        "B17:\n"
        "mov.b32 {xl, xh}, a1; tanh.approx.f16 xr, xh; cvt.u32.u16 hi1, xr; mul.rn.f16x2 a2, z18, p0; fma.rn.f16x2 p0, z19, z19, c; fma.rn.f16x2 q0, g0, g0, q0; fma.rn.f16x2 g0, z15, t0, z15; prmt.b32 t0, lo0, hi0, 0x5410; mov.b32 {xl, xh}, a1; tanh.approx.f16 xr, xl; cvt.u32.u16 lo1, xr;\n"
        "B18:\n"
        "@!pw bra.uni SPIN;\n"
        "BACK:\n"
        "wgmma.fence.sync.aligned;\n"
        "wgmma.mma_async.sync.aligned.m64n64k16.f16.f16.f16 {z0,z1,z2,z3,z4,z5,z6,z7,z8,z9,z10,z11,z12,z13,z14,z15}, {w0,w1,w2,w3}, ds0, pf, 1, 1, 0;\n"
        "wgmma.mma_async.sync.aligned.m64n64k16.f16.f16.f16 {z0,z1,z2,z3,z4,z5,z6,z7,z8,z9,z10,z11,z12,z13,z14,z15}, {w4,w5,w6,w7}, ds1, pt, 1, 1, 0;\n"
        "wgmma.mma_async.sync.aligned.m64n64k16.f16.f16.f16 {z0,z1,z2,z3,z4,z5,z6,z7,z8,z9,z10,z11,z12,z13,z14,z15}, {w8,w9,w10,w11}, ds2, pt, 1, 1, 0;\n"
        "mov.b32 {xl, xh}, a2; tanh.approx.f16 xr, xh; cvt.u32.u16 hi0, xr; mul.rn.f16x2 a3, z19, p0; fma.rn.f16x2 p0, z20, z20, c; fma.rn.f16x2 q1, g0, g0, q1; fma.rn.f16x2 g0, z16, t0, z16; prmt.b32 t0, lo1, hi1, 0x5410; mov.b32 {xl, xh}, a2; tanh.approx.f16 xr, xl; cvt.u32.u16 lo0, xr;\n"
        "B19:\n"
        "mov.b32 {xl, xh}, a3; tanh.approx.f16 xr, xh; cvt.u32.u16 hi1, xr; mul.rn.f16x2 a0, z20, p0; fma.rn.f16x2 p0, z21, z21, c; fma.rn.f16x2 q2, g0, g0, q2; fma.rn.f16x2 g0, z17, t0, z17; prmt.b32 t0, lo0, hi0, 0x5410; mov.b32 {xl, xh}, a3; tanh.approx.f16 xr, xl; cvt.u32.u16 lo1, xr;\n"
        "B20:\n"
        "mov.b32 {xl, xh}, a0; tanh.approx.f16 xr, xh; cvt.u32.u16 hi0, xr; mul.rn.f16x2 a1, z21, p0; fma.rn.f16x2 p0, z22, z22, c; fma.rn.f16x2 q3, g0, g0, q3; fma.rn.f16x2 g0, z18, t0, z18; prmt.b32 t0, lo1, hi1, 0x5410; mov.b32 {xl, xh}, a0; tanh.approx.f16 xr, xl; cvt.u32.u16 lo0, xr;\n"
        "B21:\n"
        "wgmma.mma_async.sync.aligned.m64n64k16.f16.f16.f16 {z0,z1,z2,z3,z4,z5,z6,z7,z8,z9,z10,z11,z12,z13,z14,z15}, {w12,w13,w14,w15}, ds3, pt, 1, 1, 0;\n"
        "wgmma.mma_async.sync.aligned.m64n64k16.f16.f16.f16 {z0,z1,z2,z3,z4,z5,z6,z7,z8,z9,z10,z11,z12,z13,z14,z15}, {w16,w17,w18,w19}, ds4, pt, 1, 1, 0;\n"
        "wgmma.mma_async.sync.aligned.m64n64k16.f16.f16.f16 {z0,z1,z2,z3,z4,z5,z6,z7,z8,z9,z10,z11,z12,z13,z14,z15}, {w20,w21,w22,w23}, ds5, pt, 1, 1, 0;\n"
        "wgmma.commit_group.sync.aligned;\n"
        "mov.b32 {xl, xh}, a1; tanh.approx.f16 xr, xh; cvt.u32.u16 hi1, xr; mul.rn.f16x2 a2, z22, p0; fma.rn.f16x2 p0, z23, z23, c; fma.rn.f16x2 q2, g0, g0, q2; fma.rn.f16x2 g0, z19, t0, z19; prmt.b32 t0, lo0, hi0, 0x5410; mov.b32 {xl, xh}, a1; tanh.approx.f16 xr, xl; cvt.u32.u16 lo1, xr;\n"
        "B22:\n"
        "mov.b32 {xl, xh}, a2; tanh.approx.f16 xr, xh; cvt.u32.u16 hi0, xr; mul.rn.f16x2 a3, z23, p0; fma.rn.f16x2 p0, z24, z24, c; fma.rn.f16x2 q3, g0, g0, q3; fma.rn.f16x2 g0, z20, t0, z20; prmt.b32 t0, lo1, hi1, 0x5410; mov.b32 {xl, xh}, a2; tanh.approx.f16 xr, xl; cvt.u32.u16 lo0, xr;\n"
        "B23:\n"
        "mov.b32 {xl, xh}, a3; tanh.approx.f16 xr, xh; cvt.u32.u16 hi1, xr; mul.rn.f16x2 a0, z24, p0; fma.rn.f16x2 p0, z25, z25, c; fma.rn.f16x2 q2, g0, g0, q2; fma.rn.f16x2 g0, z21, t0, z21; prmt.b32 t0, lo0, hi0, 0x5410; mov.b32 {xl, xh}, a3; tanh.approx.f16 xr, xl; cvt.u32.u16 lo1, xr;\n"
        "B24:\n"
        "mov.b32 {xl, xh}, a0; tanh.approx.f16 xr, xh; cvt.u32.u16 hi0, xr; mul.rn.f16x2 a1, z25, p0; fma.rn.f16x2 p0, z26, z26, c; fma.rn.f16x2 q3, g0, g0, q3; fma.rn.f16x2 g0, z22, t0, z22; prmt.b32 t0, lo1, hi1, 0x5410; mov.b32 {xl, xh}, a0; tanh.approx.f16 xr, xl; cvt.u32.u16 lo0, xr;\n"
        "B25:\n"
        "mov.b32 {xl, xh}, a1; tanh.approx.f16 xr, xh; cvt.u32.u16 hi1, xr; mul.rn.f16x2 a2, z26, p0; fma.rn.f16x2 p0, z27, z27, c; fma.rn.f16x2 q2, g0, g0, q2; fma.rn.f16x2 g0, z23, t0, z23; prmt.b32 t0, lo0, hi0, 0x5410; mov.b32 {xl, xh}, a1; tanh.approx.f16 xr, xl; cvt.u32.u16 lo1, xr;\n"
        "B26:\n"
        "mov.b32 {xl, xh}, a2; tanh.approx.f16 xr, xh; cvt.u32.u16 hi0, xr; mul.rn.f16x2 a3, z27, p0; fma.rn.f16x2 p0, z28, z28, c; fma.rn.f16x2 q3, g0, g0, q3; fma.rn.f16x2 g0, z24, t0, z24; prmt.b32 t0, lo1, hi1, 0x5410; mov.b32 {xl, xh}, a2; tanh.approx.f16 xr, xl; cvt.u32.u16 lo0, xr;\n"
        "B27:\n"
        "add.u32 n, n, 1; setp.lt.u32 pe, n, 32; setp.ne.and.u32 pe, so, %7, pe;\n"
        "mov.b32 {xl, xh}, a3; tanh.approx.f16 xr, xh; cvt.u32.u16 hi1, xr; mul.rn.f16x2 a0, z28, p0; fma.rn.f16x2 p0, z29, z29, c; fma.rn.f16x2 q2, g0, g0, q2; fma.rn.f16x2 g0, z25, t0, z25; prmt.b32 t0, lo0, hi0, 0x5410; mov.b32 {xl, xh}, a3; tanh.approx.f16 xr, xl; cvt.u32.u16 lo1, xr;\n"
        "B28:\n"
        "mov.b32 {xl, xh}, a0; tanh.approx.f16 xr, xh; cvt.u32.u16 hi0, xr; mul.rn.f16x2 a1, z29, p0; fma.rn.f16x2 p0, z30, z30, c; fma.rn.f16x2 q3, g0, g0, q3; fma.rn.f16x2 g0, z26, t0, z26; prmt.b32 t0, lo1, hi1, 0x5410; mov.b32 {xl, xh}, a0; tanh.approx.f16 xr, xl; cvt.u32.u16 lo0, xr;\n"
        "B29:\n"
        "mov.b32 {xl, xh}, a1; tanh.approx.f16 xr, xh; cvt.u32.u16 hi1, xr; mul.rn.f16x2 a2, z30, p0; fma.rn.f16x2 p0, z31, z31, c; fma.rn.f16x2 q2, g0, g0, q2; fma.rn.f16x2 g0, z27, t0, z27; prmt.b32 t0, lo0, hi0, 0x5410; mov.b32 {xl, xh}, a1; tanh.approx.f16 xr, xl; cvt.u32.u16 lo1, xr;\n"
        "@pe bra.uni TOP;\n"
        "setp.lt.u32 pe, n, 32;\n"
        "@pe bra.uni DUTY;\n"
        "bra.uni DONE;\n"
        "SPIN0: mov.u32 cnt, 0;\n"
        ASM_TRC("n", 1)
        "SPIN0L:\n"
        "mbarrier.try_wait.parity.shared::cta.b64 pw, [so+174984], ph;\n"
        "@pw bra.uni BACK0;\n"
        "add.u32 cnt, cnt, 1; setp.lt.u32 pw, cnt, 0x100000;\n"
        "@pw bra.uni SPIN0L;\n"
        "trap;\n"
        "SPIN: mov.u32 cnt, 0;\n"
        ASM_TRC("n", 1)
        "SPINL:\n"
        "mbarrier.try_wait.parity.shared::cta.b64 pw, [so+174984], ph;\n"
        "@pw bra.uni BACK;\n"
        "add.u32 cnt, cnt, 1; setp.lt.u32 pw, cnt, 0x100000;\n"
        "@pw bra.uni SPINL;\n"
        "trap;\n"
        "DUTY:\n"
        "setp.ge.s32 pr, n, %11;\n"
        "@pr bra.uni FLUSH;\n"
        "setp.ge.u32 pr, %13, 2;\n"
        "@pr bra.uni ROLE2;\n"
        "setp.ge.s32 pr, n, %12; selp.b64 src, %14, gp, pr; add.u32 tt, %7, 174976;\n"
        "elect.sync _|pr, 0xffffffff;\n"
        "@pr mbarrier.arrive.expect_tx.shared::cta.b64 _, [tt], %10;\n"
        "@pr cp.async.bulk.shared::cluster.global.mbarrier::complete_tx::bytes [%9], [src], %10, [tt];\n"
        "bra.uni FLUSH;\n"
        "ROLE2:\n"
        "setp.eq.u32 pr, %13, 3;\n"
        "@pr bra.uni ROLE3;\n"
        "setp.ne.s32 pr, n, 31;\n"
        "@pr bra.uni PARK;\n"
        "cp.async.bulk.wait_group 0;\n"
        "sub.s64 src, gp, %16; mov.u32 tt, 230824; mov.u32 cnt, 187392;\n"
        "elect.sync _|pr, 0xffffffff;\n"
        "@pr mbarrier.arrive.expect_tx.shared::cta.b64 _, [tt], 12288;\n"
        "@pr cp.async.bulk.shared::cluster.global.mbarrier::complete_tx::bytes [cnt], [src], 12288, [tt];\n"
        "PARK:\n"
        "elect.sync _|pr, 0xffffffff;\n"
        "@pr cp.async.bulk.global.shared::cta.bulk_group [gp], [%9], 12288;\n"
        "@pr cp.async.bulk.commit_group;\n"
        "bra.uni FLUSH;\n"
        "ROLE3:\n"
        "setp.ne.s32 pr, n, 8;\n"
        "@pr bra.uni AHEAD;\n"
        "mov.u32 tt, 230872;\n"
        "elect.sync _|pr, 0xffffffff;\n"
        "@pr mbarrier.arrive.expect_tx.shared::cta.b64 _, [tt], 75264;\n"
        "mov.u32 cnt, 229248; @pr cp.async.bulk.shared::cluster.global.mbarrier::complete_tx::bytes [cnt], [%18], 768, [tt];\n"
        "mov.u32 cnt, 230016; @pr cp.async.bulk.shared::cluster.global.mbarrier::complete_tx::bytes [cnt], [%19], 768, [tt];\n"
        "mov.u32 cnt, 74752; @pr cp.async.bulk.tensor.2d.shared::cluster.global.mbarrier::complete_tx::bytes [cnt], [%17, {0, 0}], [tt];\n"
        "mov.u32 cnt, 87040; @pr cp.async.bulk.tensor.2d.shared::cluster.global.mbarrier::complete_tx::bytes [cnt], [%17, {0, 192}], [tt];\n"
        "mov.u32 cnt, 99328; @pr cp.async.bulk.tensor.2d.shared::cluster.global.mbarrier::complete_tx::bytes [cnt], [%17, {32, 0}], [tt];\n"
        "mov.u32 cnt, 111616; @pr cp.async.bulk.tensor.2d.shared::cluster.global.mbarrier::complete_tx::bytes [cnt], [%17, {32, 192}], [tt];\n"
        "mov.u32 cnt, 123904; @pr cp.async.bulk.tensor.2d.shared::cluster.global.mbarrier::complete_tx::bytes [cnt], [%17, {64, 0}], [tt];\n"
        "mov.u32 cnt, 136192; @pr cp.async.bulk.tensor.2d.shared::cluster.global.mbarrier::complete_tx::bytes [cnt], [%17, {64, 192}], [tt];\n"
        "AHEAD:\n"
        "elect.sync _|pr, 0xffffffff;\n"
        "@pr cp.async.bulk.prefetch.L2.global [gp], 12288;\n"
        "FLUSH:\n"
        "add.s64 gp, gp, %16;\n"
        "mov.b32 {xl, xh}, q0; cvt.f32.f16 f0, xl; cvt.f32.f16 f1, xh; add.f32 f0, f0, f1; add.f32 %0, %0, f0; mov.b32 q0, 0;\n"
        "mov.b32 {xl, xh}, q1; cvt.f32.f16 f0, xl; cvt.f32.f16 f1, xh; add.f32 f0, f0, f1; add.f32 %1, %1, f0; mov.b32 q1, 0;\n"
        "mov.b32 {xl, xh}, q2; cvt.f32.f16 f0, xl; cvt.f32.f16 f1, xh; add.f32 f0, f0, f1; add.f32 %2, %2, f0; mov.b32 q2, 0;\n"
        "mov.b32 {xl, xh}, q3; cvt.f32.f16 f0, xl; cvt.f32.f16 f1, xh; add.f32 f0, f0, f1; add.f32 %3, %3, f0; mov.b32 q3, 0;\n"
        "setp.ne.u32 pr, %5, 0;\n"
        "@pr bra.uni TOP;\n"
        "wgmma.wait_group.sync.aligned 0;\n"
        "wgmma.fence.sync.aligned;\n"
        "ld.volatile.shared.v2.b32 {lo0, hi0}, [so]; setp.eq.u32 pr, lo0, hi0; vote.sync.any.pred pr, pr, 0xffffffff; @pr bra.uni B0;\n"
        "ld.volatile.shared.v2.b32 {lo1, hi1}, [so]; setp.eq.u32 pr, lo1, hi1; vote.sync.any.pred pr, pr, 0xffffffff; @pr bra.uni B0;\n"
        "ld.volatile.shared.v2.b32 {q1, a0}, [so]; setp.eq.u32 pr, q1, a0; vote.sync.any.pred pr, pr, 0xffffffff; @pr bra.uni B0;\n"
        "ld.volatile.shared.v2.b32 {q2, a1}, [so]; setp.eq.u32 pr, q2, a1; vote.sync.any.pred pr, pr, 0xffffffff; @pr bra.uni B0;\n"
        "ld.volatile.shared.v2.b32 {q3, a2}, [so]; setp.eq.u32 pr, q3, a2; vote.sync.any.pred pr, pr, 0xffffffff; @pr bra.uni B0;\n"
        "ld.volatile.shared.v2.b32 {q0, a3}, [so]; setp.eq.u32 pr, q0, a3; vote.sync.any.pred pr, pr, 0xffffffff; @pr bra.uni B0;\n"
        "ld.volatile.shared.v2.b32 {t0, g0}, [so]; setp.eq.u32 pr, t0, g0; vote.sync.any.pred pr, pr, 0xffffffff; @pr bra.uni B0;\n"
        "setp.eq.u32 pr, n, 1000; @pr bra.uni B31;\n"
        "setp.eq.u32 pr, n, 1001; @pr bra.uni B0;\n"
        "setp.eq.u32 pr, n, 1002; @pr bra.uni B1;\n"
        "setp.eq.u32 pr, n, 1003; @pr bra.uni B2;\n"
        "setp.eq.u32 pr, n, 1004; @pr bra.uni B3;\n"
        "setp.eq.u32 pr, n, 1005; @pr bra.uni B4;\n"
        "setp.eq.u32 pr, n, 1006; @pr bra.uni B5;\n"
        "setp.eq.u32 pr, n, 1007; @pr bra.uni B6;\n"
        "setp.eq.u32 pr, n, 1008; @pr bra.uni B7;\n"
        "setp.eq.u32 pr, n, 1009; @pr bra.uni B8;\n"
        "setp.eq.u32 pr, n, 1010; @pr bra.uni B9;\n"
        "setp.eq.u32 pr, n, 1011; @pr bra.uni B10;\n"
        "setp.eq.u32 pr, n, 1012; @pr bra.uni B11;\n"
        "setp.eq.u32 pr, n, 1013; @pr bra.uni B12;\n"
        "setp.eq.u32 pr, n, 1014; @pr bra.uni B13;\n"
        "setp.eq.u32 pr, n, 1015; @pr bra.uni B14;\n"
        "setp.eq.u32 pr, n, 1016; @pr bra.uni B15;\n"
        "setp.eq.u32 pr, n, 1017; @pr bra.uni B16;\n"
        "setp.eq.u32 pr, n, 1018; @pr bra.uni B17;\n"
        "setp.eq.u32 pr, n, 1019; @pr bra.uni B18;\n"
        "setp.eq.u32 pr, n, 1020; @pr bra.uni B19;\n"
        "setp.eq.u32 pr, n, 1021; @pr bra.uni B20;\n"
        "setp.eq.u32 pr, n, 1022; @pr bra.uni B21;\n"
        "setp.eq.u32 pr, n, 1023; @pr bra.uni B22;\n"
        "setp.eq.u32 pr, n, 1024; @pr bra.uni B23;\n"
        "setp.eq.u32 pr, n, 1025; @pr bra.uni B24;\n"
        "setp.eq.u32 pr, n, 1026; @pr bra.uni B25;\n"
        "setp.eq.u32 pr, n, 1027; @pr bra.uni B26;\n"
        "setp.eq.u32 pr, n, 1028; @pr bra.uni B27;\n"
        "setp.eq.u32 pr, n, 1029; @pr bra.uni B28;\n"
        "setp.eq.u32 pr, n, 1030; @pr bra.uni B29;\n"
        "trap;\n"
        "DONE:\n"
        ASM_TRC("n", 0)
        "mov.b32 {xl, xh}, a2; tanh.approx.f16 xr, xh; cvt.u32.u16 hi0, xr; mul.rn.f16x2 a3, z31, p0; fma.rn.f16x2 q3, g0, g0, q3; fma.rn.f16x2 g0, z28, t0, z28; prmt.b32 t0, lo1, hi1, 0x5410; mov.b32 {xl, xh}, a2; tanh.approx.f16 xr, xl; cvt.u32.u16 lo0, xr;\n"
        "mov.b32 {xl, xh}, a3; tanh.approx.f16 xr, xh; cvt.u32.u16 hi1, xr; fma.rn.f16x2 q2, g0, g0, q2; fma.rn.f16x2 g0, z29, t0, z29; prmt.b32 t0, lo0, hi0, 0x5410; mov.b32 {xl, xh}, a3; tanh.approx.f16 xr, xl; cvt.u32.u16 lo1, xr;\n"
        "fma.rn.f16x2 q3, g0, g0, q3; fma.rn.f16x2 g0, z30, t0, z30; prmt.b32 t0, lo1, hi1, 0x5410;\n"
        "fma.rn.f16x2 q2, g0, g0, q2; fma.rn.f16x2 g0, z31, t0, z31;\n"
        "fma.rn.f16x2 q3, g0, g0, q3;\n"
        "mov.b32 {xl, xh}, q0; cvt.f32.f16 f0, xl; cvt.f32.f16 f1, xh; add.f32 f0, f0, f1; add.f32 %0, %0, f0; mov.b32 q0, 0;\n"
        "mov.b32 {xl, xh}, q1; cvt.f32.f16 f0, xl; cvt.f32.f16 f1, xh; add.f32 f0, f0, f1; add.f32 %1, %1, f0; mov.b32 q1, 0;\n"
        "mov.b32 {xl, xh}, q2; cvt.f32.f16 f0, xl; cvt.f32.f16 f1, xh; add.f32 f0, f0, f1; add.f32 %2, %2, f0; mov.b32 q2, 0;\n"
        "mov.b32 {xl, xh}, q3; cvt.f32.f16 f0, xl; cvt.f32.f16 f1, xh; add.f32 f0, f0, f1; add.f32 %3, %3, f0; mov.b32 q3, 0;\n"
        "wgmma.wait_group.sync.aligned 0;\n"
        "}\n"
        : "=f"(acc[0][0]), "=f"(acc[0][1]), "=f"(acc[1][0]), "=f"(acc[1][1])
        : "r"(w1t), "r"(yd), "r"(wd), "r"(own_slot), "l"(d.g), "r"(d.s), "r"(d.bytes), "r"(d.end), "r"(d.zero), "r"(role),
          "l"(d.zeros), "r"(lane), "l"(d.step), "l"(&prm.w2_map), "l"(prm.gamma), "l"(prm.beta), "l"(prm.ydesc64[0]), "l"(prm.ydesc64[1])
        : "memory");
}
template <int M, bool LAST_SMEM = true>
__device__ __forceinline__ void gemm1_t(uint32_t (&d)[16], const uint32_t* wa, uint32_t yd, uint32_t wd) {
    wg_fence();
    wgmma_n64_h_set<0>(d, wa, desc<1024, 1>(yd, 0));
#pragma unroll
    for (int kk = 1; kk < (LAST_SMEM ? 5 : 6); kk++)
        wgmma_n64_h_acc<0>(d, wa + kk * 4, kk < 4 ? desc<1024, 1>(yd, kk * 32) : desc<512, 2>(yd, 8192 + (kk - 4) * 32));
    if (LAST_SMEM) wgmma_n64_h_acc_ss(d, desc<1024, 1>(wd, M * 12288), desc<512, 2>(yd, 8192 + 32));
    wg_commit();
}

#define GTAIL 0
__device__ __forceinline__ void gelu_sumsq_h(uint32_t (&d)[16], uint32_t (&q)[2], uint32_t key) {
#pragma unroll
    for (int r = 0; r < 16; r++) {
        if (GTAIL && r == 16 - GTAIL) sched_fence<GTAIL ? GTAIL : 2>(d + r, key);
        const uint32_t gv = gelu2(d[r]);
        q[r & 1] = h2_fma(gv, gv, q[r & 1]);
    }
}
__device__ __forceinline__ void flush_sumsq(uint32_t (&q)[2], float (&acc)[2]) {
#pragma unroll
    for (int h = 0; h < 2; h++) {
        float lo, hi;
        h2_unpack(q[h], lo, hi);
        acc[h] += lo + hi;
        q[h] = 0;
    }
}
__device__ __forceinline__ void gelu_sumsq_f(const uint32_t (&d)[16], float (&acc)[2]) {
#pragma unroll
    for (int r = 0; r < 16; r++) {
        float lo, hi;
        h2_unpack(gelu2(d[r]), lo, hi);
        acc[r & 1] = fmaf(lo, lo, acc[r & 1]);
        acc[r & 1] = fmaf(hi, hi, acc[r & 1]);
    }
}
__device__ __forceinline__ void load_w1t(uint32_t (&wa)[2][24], int wg, int w, int lane) {
#pragma unroll
    for (int m = 0; m < 2; m++)
#pragma unroll
        for (int kk = 0; kk < 5; kk++) {
            const int q = lane >> 3, c = 16 * kk + 8 * (q >> 1) + (lane & 7), ck = 2 * w + (q & 1);
            ldsm4_t(wa[m] + kk * 4, sb + SM_W1 + (2 * wg + m) * 12288 + c * 128 + ((ck ^ (c & 7)) * 16));
        }
}
__device__ __forceinline__ unsigned long long* acc_word(const Params& prm, uint32_t epoch, uint32_t e) {
    return &prm.g->acc[epoch & 1][(e >> 2) * 32 + (e & 3)];
}
__device__ __forceinline__ void publish_fast(const Params& prm, const float (&acc)[2][2], uint32_t epoch, int wg, int w, int lane) {
    const bool m = lane & 2, h = lane & 1;
    const float a = (m ? acc[1][0] : acc[0][0]) + __shfl_xor_sync(0xffffffffu, m ? acc[0][0] : acc[1][0], 2);
    const float b = (m ? acc[1][1] : acc[0][1]) + __shfl_xor_sync(0xffffffffu, m ? acc[0][1] : acc[1][1], 2);
    const float v = (h ? b : a) + __shfl_xor_sync(0xffffffffu, h ? a : b, 1);
    const unsigned long long q = (__float2ull_rn(fminf(v, ACC_LIMIT) * 0x1p16f) << 8) + 1;
    asm volatile("red.relaxed.gpu.global.add.u64 [%0], %1;"
                 ::"l"(acc_word(prm, epoch, 128 * wg + 32 * (lane & 2) + 16 * w + (lane >> 2) + 8 * (lane & 1))), "l"(q) : "memory");
}
__device__ __forceinline__ float collect_fast(const unsigned long long* word) {
    unsigned long long v;
    asm volatile(
        "{\n.reg .pred p;\n.reg .u32 n, lo, hi;\nmov.u32 n, 0;\n"
        "POLL:\nld.relaxed.gpu.global.u64 %0, [%1];\nmov.b64 {lo, hi}, %0;\nand.b32 lo, lo, 255;\n"
        "setp.eq.u32 p, lo, %2;\nvote.sync.all.pred p, p, 0xffffffff;\n@p bra.uni POLL_DONE;\n"
        "add.u32 n, n, 1;\nsetp.lt.u32 p, n, 0x400000;\n@p bra.uni POLL;\ntrap;\nPOLL_DONE:\n}\n"
        : "=l"(v) : "l"(word), "n"(NUM_CTAS) : "memory");
    return __ull2float_rn(v >> 8) * 0x1p-16f;
}
__device__ __forceinline__ void publish_sums(const float (&acc)[2][2], float* sums, unsigned int* counter, int wg, int w, int lane) {
#pragma unroll
    for (int m = 0; m < 2; m++)
#pragma unroll
        for (int h = 0; h < 2; h++) {
            const float v = quad_sum(acc[m][h]);
            if ((lane & 3) == 0) atomicAdd(sums + 64 * (2 * wg + m) + 16 * w + (lane >> 2) + 8 * h, v);
        }
    named_sync(1, 384);
    if (fresh_tid() == 0) asm volatile("red.release.gpu.global.add.u32 [%0], 1;" ::"l"(counter) : "memory");
}
__device__ __forceinline__ void grid_wait(const unsigned int* counter, unsigned int target) {
    if (fresh_tid() == 0) {
        unsigned int v, spins = 0;
        do {
            asm volatile("ld.acquire.gpu.global.u32 %0, [%1];" : "=r"(v) : "l"(counter) : "memory");
            if (++spins > (1u << 22)) __trap();
        } while ((int)(v - target) < 0);
    }
    __syncthreads();
}

struct Pass2 {
    uint32_t wg;
    uint32_t off;
    int step;
    uint32_t xs;
    uint32_t a_offs, xs_offs, bias_addr;
    uint32_t w;
};

static_assert(sb + SM_BAR + BAR_ROWS * 8 == 231208 && BAR_STAT == BAR_ROWS + 2 && sb + SM_RED + RED_SCALE * 4 == 230792, "layout");
static_assert(sb + SM_BAR + BAR_Y2FULL * 8 == 230800 && sb + SM_BAR + BAR_XSFULL * 8 == 230832, "layout");
#define PASS2_STATE ".reg .b32 qa<24>, qz<32>, o<24>, g<16>, p<2>, a<4>, lo<2>, hi<2>, h<2>, osc;"
__device__ __forceinline__ void pass2_start(const Pass2& c, const Params& prm) {
    asm volatile(
        "{\n"
        ".reg .b32 t<2>, c, tt, ad, cnt, ybar;\n"
        ".reg .b16 xl, xh, xr;\n"
        ".reg .b64 w1d, dt;\n"
        ".reg .pred pt, pf, pw;\n"
        "setp.ne.b32 pt, 1, 0; setp.ne.b32 pf, 0, 0; mov.b32 c, 0x40D940D9; mov.b64 w1d, {%1, 0x40000040}; mad.lo.u32 ybar, %2, 8, 230800;\n"
        "mbarrier.try_wait.parity.shared::cta.b64 pw, [ybar], 0;\n"
        "@!pw bra.uni SPINY0;\n"
        "BACKY0:\n"
        "and.b32 t0, %5, 0xffff; shr.u32 t1, %5, 16;\n"
        "xor.b32 ad, t0, 0; add.u32 ad, ad, %4; ldmatrix.sync.aligned.m8n8.x4.shared.b16 {qa0,qa1,qa2,qa3}, [ad];\n"
        "xor.b32 ad, t0, 32; add.u32 ad, ad, %4; ldmatrix.sync.aligned.m8n8.x4.shared.b16 {qa4,qa5,qa6,qa7}, [ad];\n"
        "xor.b32 ad, t0, 64; add.u32 ad, ad, %4; ldmatrix.sync.aligned.m8n8.x4.shared.b16 {qa8,qa9,qa10,qa11}, [ad];\n"
        "xor.b32 ad, t0, 96; add.u32 ad, ad, %4; ldmatrix.sync.aligned.m8n8.x4.shared.b16 {qa12,qa13,qa14,qa15}, [ad];\n"
        "xor.b32 ad, t1, 0; add.u32 ad, ad, %4; ldmatrix.sync.aligned.m8n8.x4.shared.b16 {qa16,qa17,qa18,qa19}, [ad];\n"
        "xor.b32 ad, t1, 32; add.u32 ad, ad, %4; ldmatrix.sync.aligned.m8n8.x4.shared.b16 {qa20,qa21,qa22,qa23}, [ad];\n"
        "wgmma.fence.sync.aligned;\n"
        "add.s64 dt, w1d, 0; wgmma.mma_async.sync.aligned.m64n64k16.f16.f16.f16 {qz0,qz1,qz2,qz3,qz4,qz5,qz6,qz7,qz8,qz9,qz10,qz11,qz12,qz13,qz14,qz15}, {qa0,qa1,qa2,qa3}, dt, pf, 1, 1, 1;\n"
        "add.s64 dt, w1d, 128; wgmma.mma_async.sync.aligned.m64n64k16.f16.f16.f16 {qz0,qz1,qz2,qz3,qz4,qz5,qz6,qz7,qz8,qz9,qz10,qz11,qz12,qz13,qz14,qz15}, {qa4,qa5,qa6,qa7}, dt, pt, 1, 1, 1;\n"
        "add.s64 dt, w1d, 256; wgmma.mma_async.sync.aligned.m64n64k16.f16.f16.f16 {qz0,qz1,qz2,qz3,qz4,qz5,qz6,qz7,qz8,qz9,qz10,qz11,qz12,qz13,qz14,qz15}, {qa8,qa9,qa10,qa11}, dt, pt, 1, 1, 1;\n"
        "add.s64 dt, w1d, 384; wgmma.mma_async.sync.aligned.m64n64k16.f16.f16.f16 {qz0,qz1,qz2,qz3,qz4,qz5,qz6,qz7,qz8,qz9,qz10,qz11,qz12,qz13,qz14,qz15}, {qa12,qa13,qa14,qa15}, dt, pt, 1, 1, 1;\n"
        "add.s64 dt, w1d, 512; wgmma.mma_async.sync.aligned.m64n64k16.f16.f16.f16 {qz0,qz1,qz2,qz3,qz4,qz5,qz6,qz7,qz8,qz9,qz10,qz11,qz12,qz13,qz14,qz15}, {qa16,qa17,qa18,qa19}, dt, pt, 1, 1, 1;\n"
        "add.s64 dt, w1d, 640; wgmma.mma_async.sync.aligned.m64n64k16.f16.f16.f16 {qz0,qz1,qz2,qz3,qz4,qz5,qz6,qz7,qz8,qz9,qz10,qz11,qz12,qz13,qz14,qz15}, {qa20,qa21,qa22,qa23}, dt, pt, 1, 1, 1;\n"
        "wgmma.commit_group.sync.aligned;\n"
        "wgmma.wait_group.sync.aligned 0;\n"
        "fma.rn.f16x2 p0, qz0, qz0, c;\n"
        "mul.rn.f16x2 a0, qz0, p0; fma.rn.f16x2 p1, qz1, qz1, c;\n"
        "mov.b32 {xl, xh}, a0; tanh.approx.f16 xr, xl; cvt.u32.u16 lo0, xr; tanh.approx.f16 xr, xh; cvt.u32.u16 hi0, xr; mul.rn.f16x2 a1, qz1, p1; fma.rn.f16x2 p0, qz2, qz2, c;\n"
        "mov.b32 {xl, xh}, a1; tanh.approx.f16 xr, xl; cvt.u32.u16 lo1, xr; tanh.approx.f16 xr, xh; cvt.u32.u16 hi1, xr; mul.rn.f16x2 a0, qz2, p0; fma.rn.f16x2 p1, qz3, qz3, c; prmt.b32 h0, lo0, hi0, 0x5410;\n"
        "mov.b32 {xl, xh}, a0; tanh.approx.f16 xr, xl; cvt.u32.u16 lo0, xr; tanh.approx.f16 xr, xh; cvt.u32.u16 hi0, xr; mul.rn.f16x2 a1, qz3, p1; fma.rn.f16x2 p0, qz4, qz4, c; fma.rn.f16x2 g0, qz0, h0, qz0; prmt.b32 h1, lo1, hi1, 0x5410;\n"
        "mov.b32 {xl, xh}, a1; tanh.approx.f16 xr, xl; cvt.u32.u16 lo1, xr; tanh.approx.f16 xr, xh; cvt.u32.u16 hi1, xr; mul.rn.f16x2 a0, qz4, p0; fma.rn.f16x2 p1, qz5, qz5, c; fma.rn.f16x2 g1, qz1, h1, qz1; prmt.b32 h0, lo0, hi0, 0x5410;\n"
        "mov.b32 {xl, xh}, a0; tanh.approx.f16 xr, xl; cvt.u32.u16 lo0, xr; tanh.approx.f16 xr, xh; cvt.u32.u16 hi0, xr; mul.rn.f16x2 a1, qz5, p1; fma.rn.f16x2 p0, qz6, qz6, c; fma.rn.f16x2 g2, qz2, h0, qz2; prmt.b32 h1, lo1, hi1, 0x5410;\n"
        "mov.b32 {xl, xh}, a1; tanh.approx.f16 xr, xl; cvt.u32.u16 lo1, xr; tanh.approx.f16 xr, xh; cvt.u32.u16 hi1, xr; mul.rn.f16x2 a0, qz6, p0; fma.rn.f16x2 p1, qz7, qz7, c; fma.rn.f16x2 g3, qz3, h1, qz3; prmt.b32 h0, lo0, hi0, 0x5410;\n"
        "bra.uni DONE;\n"
        "SPINY0: mov.u32 cnt, 0;\n"
        "SPINY0L:\n"
        "mbarrier.try_wait.parity.shared::cta.b64 pw, [ybar], 0;\n"
        "@pw bra.uni BACKY0;\n"
        "add.u32 cnt, cnt, 1; setp.lt.u32 pw, cnt, 0x100000;\n"
        "@pw bra.uni SPINY0L;\n"
        "trap;\n"
        "DONE:\n"
        "}\n"
        :: "n"(0), "r"(prm.w1desc), "r"(c.wg), "n"(0), "r"(c.xs), "r"(c.a_offs) : "memory");
}
__device__ __forceinline__ bool pass2_head(const Pass2& c, uint32_t round) {
    uint32_t retry;
    asm volatile(
        "{\n"
        ".reg .b32 t<2>, tt, ad, cnt;\n"
        ".reg .pred pw;\n"
        "and.b32 t0, %3, 0xffff; shr.u32 t1, %3, 16;\n"
        "xor.b32 ad, t0, 0; add.u32 ad, ad, %4; ldmatrix.sync.aligned.m8n8.x4.shared.b16 {qa0,qa1,qa2,qa3}, [ad];\n"
        "xor.b32 ad, t0, 32; add.u32 ad, ad, %4; ldmatrix.sync.aligned.m8n8.x4.shared.b16 {qa4,qa5,qa6,qa7}, [ad];\n"
        "xor.b32 ad, t0, 64; add.u32 ad, ad, %4; ldmatrix.sync.aligned.m8n8.x4.shared.b16 {qa8,qa9,qa10,qa11}, [ad];\n"
        "xor.b32 ad, t0, 96; add.u32 ad, ad, %4; ldmatrix.sync.aligned.m8n8.x4.shared.b16 {qa12,qa13,qa14,qa15}, [ad];\n"
        "xor.b32 ad, t1, 0; add.u32 ad, ad, %4; ldmatrix.sync.aligned.m8n8.x4.shared.b16 {qa16,qa17,qa18,qa19}, [ad];\n"
        "xor.b32 ad, t1, 32; add.u32 ad, ad, %4; ldmatrix.sync.aligned.m8n8.x4.shared.b16 {qa20,qa21,qa22,qa23}, [ad];\n"
        "mov.b32 qz16, 0; mov.b32 qz17, 0; mov.b32 qz18, 0; mov.b32 qz19, 0; mov.b32 qz20, 0; mov.b32 qz21, 0; mov.b32 qz22, 0; mov.b32 qz23, 0; mov.b32 qz24, 0; mov.b32 qz25, 0; mov.b32 qz26, 0; mov.b32 qz27, 0; mov.b32 qz28, 0; mov.b32 qz29, 0; mov.b32 qz30, 0; mov.b32 qz31, 0;\n"
        "mov.b32 g4, 0; mov.b32 g5, 0; mov.b32 g6, 0; mov.b32 g7, 0; mov.b32 g8, 0; mov.b32 g9, 0; mov.b32 g10, 0; mov.b32 g11, 0; mov.b32 g12, 0; mov.b32 g13, 0; mov.b32 g14, 0; mov.b32 g15, 0;\n"
        "mov.u32 tt, 231224; mbarrier.try_wait.parity.shared::cta.b64 pw, [tt], %1;\n"
        "@!pw bra.uni SPINR;\n"
        "BACKR:\n"
        "mov.u32 tt, 230792; ld.shared.v2.b32 {osc, %0}, [tt];\n"
        "ld.shared.v4.b32 {o0,o1,o2,o3}, [%2+0];\n"
        "ld.shared.v4.b32 {o4,o5,o6,o7}, [%2+64];\n"
        "ld.shared.v4.b32 {o8,o9,o10,o11}, [%2+128];\n"
        "ld.shared.v4.b32 {o12,o13,o14,o15}, [%2+192];\n"
        "ld.shared.v4.b32 {o16,o17,o18,o19}, [%2+256];\n"
        "ld.shared.v4.b32 {o20,o21,o22,o23}, [%2+320];\n"
        "bra.uni DONE;\n"
        "SPINR: mov.u32 cnt, 0;\n"
        "SPINRL:\n"
        "mov.u32 tt, 231224; mbarrier.try_wait.parity.shared::cta.b64 pw, [tt], %1;\n"
        "@pw bra.uni BACKR;\n"
        "add.u32 cnt, cnt, 1; setp.lt.u32 pw, cnt, 0x100000;\n"
        "@pw bra.uni SPINRL;\n"
        "trap;\n"
        "DONE:\n"
        "}\n"
        : "=r"(retry)
        : "r"(round), "r"(c.bias_addr), "r"(c.a_offs), "r"(c.xs)
        : "memory");
    return __any_sync(0xffffffffu, retry);
}
__device__ __forceinline__ void pass2_tiles(const Pass2& c, const Params& prm) {
    asm volatile(
        "{\n"
        ".reg .b32 v<8>, n, off, c, tt, ad, cnt, ybar, xbar, tbar, tpar, id;\n"
        ".reg .b16 xl, xh, xr;\n"
        ".reg .f32 f0, f1;\n"
        ".reg .b64 w1d, w2d, dt, gp, pol;\n"
        ".reg .pred pt, pf, pr, pw, pl, pk, pm, pz, pn;\n"
        "setp.ne.b32 pt, 1, 0; setp.ne.b32 pf, 0, 0; setp.eq.u32 pl, %9, 0; setp.eq.u32 pk, %9, 0; setp.eq.u32 pz, %0, 0;\n"
        "mov.b32 c, 0x40D940D9;\n"
        "mov.b64 w1d, {%0, 0x40000040}; mov.b64 w2d, {%1, 0x80000020};\n"
        "mad.lo.u32 ybar, %2, 8, 230800; mad.lo.u32 xbar, %2, 8, 230832; add.u32 id, %2, 2;\n"
        "xor.b32 tt, %2, 0; mad.lo.u32 tbar, tt, 64, 230888; setp.eq.u32 pr, tt, 0; selp.u32 tpar, 1, 0, pr; mov.u32 tt, %laneid; setp.eq.u32 pn, tt, 0;\n"
        "mov.u32 n, -1; add.u32 off, %3, %8; mov.pred pm, pt; mov.b64 pol, 0x12F0000000000000;\n"
        "mov.b32 v0, 0; mov.b32 v1, 0; mov.b32 v2, 0; mov.b32 v3, 0; mov.b32 v4, 0; mov.b32 v5, 0; mov.b32 v6, 0; mov.b32 v7, 0;\n"
        "LOOP:\n"
        "@!pm bra.uni SKIP0;\n"
        "wgmma.fence.sync.aligned;\n"
        "add.s64 dt, w1d, 768; wgmma.mma_async.sync.aligned.m64n64k16.f16.f16.f16 {qz16,qz17,qz18,qz19,qz20,qz21,qz22,qz23,qz24,qz25,qz26,qz27,qz28,qz29,qz30,qz31}, {qa0,qa1,qa2,qa3}, dt, pf, 1, 1, 1;\n"
        "add.s64 dt, w1d, 896; wgmma.mma_async.sync.aligned.m64n64k16.f16.f16.f16 {qz16,qz17,qz18,qz19,qz20,qz21,qz22,qz23,qz24,qz25,qz26,qz27,qz28,qz29,qz30,qz31}, {qa4,qa5,qa6,qa7}, dt, pt, 1, 1, 1;\n"
        "add.s64 dt, w1d, 1024; wgmma.mma_async.sync.aligned.m64n64k16.f16.f16.f16 {qz16,qz17,qz18,qz19,qz20,qz21,qz22,qz23,qz24,qz25,qz26,qz27,qz28,qz29,qz30,qz31}, {qa8,qa9,qa10,qa11}, dt, pt, 1, 1, 1;\n"
        "add.s64 dt, w1d, 1152; wgmma.mma_async.sync.aligned.m64n64k16.f16.f16.f16 {qz16,qz17,qz18,qz19,qz20,qz21,qz22,qz23,qz24,qz25,qz26,qz27,qz28,qz29,qz30,qz31}, {qa12,qa13,qa14,qa15}, dt, pt, 1, 1, 1;\n"
        "add.s64 dt, w1d, 1280; wgmma.mma_async.sync.aligned.m64n64k16.f16.f16.f16 {qz16,qz17,qz18,qz19,qz20,qz21,qz22,qz23,qz24,qz25,qz26,qz27,qz28,qz29,qz30,qz31}, {qa16,qa17,qa18,qa19}, dt, pt, 1, 1, 1;\n"
        "add.s64 dt, w1d, 1408; wgmma.mma_async.sync.aligned.m64n64k16.f16.f16.f16 {qz16,qz17,qz18,qz19,qz20,qz21,qz22,qz23,qz24,qz25,qz26,qz27,qz28,qz29,qz30,qz31}, {qa20,qa21,qa22,qa23}, dt, pt, 1, 1, 1;\n"
        "SKIP0:\n"
        "wgmma.fence.sync.aligned;\n"
        "wgmma.commit_group.sync.aligned;\n"
        "setp.lt.s32 pr, n, 0;\n"
        "@pr bra.uni FIRST;\n"
        "and.b32 tt, n, 1; mbarrier.try_wait.parity.shared::cta.b64 pw, [xbar], tt;\n"
        "@!pw bra.uni SPINX;\n"
        "BACKX:\n"
        "and.b32 ad, %6, 0xffff; add.u32 ad, ad, %4; ld.shared.v4.b32 {v0,v1,v2,v3}, [ad+0];\n"
        "shr.u32 ad, %6, 16; add.u32 ad, ad, %4; ld.shared.v4.b32 {v4,v5,v6,v7}, [ad+0];\n"
        "mov.b32 {xl, xh}, o0; cvt.f32.f16 f0, xl; cvt.f32.f16 f1, xh; cvt.rn.bf16x2.f32 tt, f1, f0; fma.rn.bf16x2 v0, tt, osc, v0;\n"
        "mov.b32 {xl, xh}, o2; cvt.f32.f16 f0, xl; cvt.f32.f16 f1, xh; cvt.rn.bf16x2.f32 tt, f1, f0; fma.rn.bf16x2 v1, tt, osc, v1;\n"
        "mov.b32 {xl, xh}, o4; cvt.f32.f16 f0, xl; cvt.f32.f16 f1, xh; cvt.rn.bf16x2.f32 tt, f1, f0; fma.rn.bf16x2 v2, tt, osc, v2;\n"
        "mov.b32 {xl, xh}, o6; cvt.f32.f16 f0, xl; cvt.f32.f16 f1, xh; cvt.rn.bf16x2.f32 tt, f1, f0; fma.rn.bf16x2 v3, tt, osc, v3;\n"
        "and.b32 ad, %6, 0xffff; add.u32 ad, ad, %4; st.shared.v4.b32 [ad+0], {v0,v1,v2,v3};\n"
        "and.b32 ad, %6, 0xffff; add.u32 ad, ad, %4; ld.shared.v4.b32 {v0,v1,v2,v3}, [ad+64];\n"
        "mov.b32 {xl, xh}, o1; cvt.f32.f16 f0, xl; cvt.f32.f16 f1, xh; cvt.rn.bf16x2.f32 tt, f1, f0; fma.rn.bf16x2 v4, tt, osc, v4;\n"
        "mov.b32 {xl, xh}, o3; cvt.f32.f16 f0, xl; cvt.f32.f16 f1, xh; cvt.rn.bf16x2.f32 tt, f1, f0; fma.rn.bf16x2 v5, tt, osc, v5;\n"
        "mov.b32 {xl, xh}, o5; cvt.f32.f16 f0, xl; cvt.f32.f16 f1, xh; cvt.rn.bf16x2.f32 tt, f1, f0; fma.rn.bf16x2 v6, tt, osc, v6;\n"
        "mov.b32 {xl, xh}, o7; cvt.f32.f16 f0, xl; cvt.f32.f16 f1, xh; cvt.rn.bf16x2.f32 tt, f1, f0; fma.rn.bf16x2 v7, tt, osc, v7;\n"
        "shr.u32 ad, %6, 16; add.u32 ad, ad, %4; st.shared.v4.b32 [ad+0], {v4,v5,v6,v7};\n"
        "shr.u32 ad, %6, 16; add.u32 ad, ad, %4; ld.shared.v4.b32 {v4,v5,v6,v7}, [ad+64];\n"
        "ld.shared.v4.b32 {o0,o1,o2,o3}, [%7+0];\n"
        "ld.shared.v4.b32 {o4,o5,o6,o7}, [%7+64];\n"
        "mov.b32 {xl, xh}, o8; cvt.f32.f16 f0, xl; cvt.f32.f16 f1, xh; cvt.rn.bf16x2.f32 tt, f1, f0; fma.rn.bf16x2 v0, tt, osc, v0;\n"
        "mov.b32 {xl, xh}, o10; cvt.f32.f16 f0, xl; cvt.f32.f16 f1, xh; cvt.rn.bf16x2.f32 tt, f1, f0; fma.rn.bf16x2 v1, tt, osc, v1;\n"
        "mov.b32 {xl, xh}, o12; cvt.f32.f16 f0, xl; cvt.f32.f16 f1, xh; cvt.rn.bf16x2.f32 tt, f1, f0; fma.rn.bf16x2 v2, tt, osc, v2;\n"
        "mov.b32 {xl, xh}, o14; cvt.f32.f16 f0, xl; cvt.f32.f16 f1, xh; cvt.rn.bf16x2.f32 tt, f1, f0; fma.rn.bf16x2 v3, tt, osc, v3;\n"
        "and.b32 ad, %6, 0xffff; add.u32 ad, ad, %4; st.shared.v4.b32 [ad+64], {v0,v1,v2,v3};\n"
        "and.b32 ad, %6, 0xffff; add.u32 ad, ad, %4; ld.shared.v4.b32 {v0,v1,v2,v3}, [ad+128];\n"
        "mov.b32 {xl, xh}, o9; cvt.f32.f16 f0, xl; cvt.f32.f16 f1, xh; cvt.rn.bf16x2.f32 tt, f1, f0; fma.rn.bf16x2 v4, tt, osc, v4;\n"
        "mov.b32 {xl, xh}, o11; cvt.f32.f16 f0, xl; cvt.f32.f16 f1, xh; cvt.rn.bf16x2.f32 tt, f1, f0; fma.rn.bf16x2 v5, tt, osc, v5;\n"
        "mov.b32 {xl, xh}, o13; cvt.f32.f16 f0, xl; cvt.f32.f16 f1, xh; cvt.rn.bf16x2.f32 tt, f1, f0; fma.rn.bf16x2 v6, tt, osc, v6;\n"
        "mov.b32 {xl, xh}, o15; cvt.f32.f16 f0, xl; cvt.f32.f16 f1, xh; cvt.rn.bf16x2.f32 tt, f1, f0; fma.rn.bf16x2 v7, tt, osc, v7;\n"
        "shr.u32 ad, %6, 16; add.u32 ad, ad, %4; st.shared.v4.b32 [ad+64], {v4,v5,v6,v7};\n"
        "shr.u32 ad, %6, 16; add.u32 ad, ad, %4; ld.shared.v4.b32 {v4,v5,v6,v7}, [ad+128];\n"
        "ld.shared.v4.b32 {o8,o9,o10,o11}, [%7+128];\n"
        "ld.shared.v4.b32 {o12,o13,o14,o15}, [%7+192];\n"
        "mov.b32 {xl, xh}, o16; cvt.f32.f16 f0, xl; cvt.f32.f16 f1, xh; cvt.rn.bf16x2.f32 tt, f1, f0; fma.rn.bf16x2 v0, tt, osc, v0;\n"
        "mov.b32 {xl, xh}, o18; cvt.f32.f16 f0, xl; cvt.f32.f16 f1, xh; cvt.rn.bf16x2.f32 tt, f1, f0; fma.rn.bf16x2 v1, tt, osc, v1;\n"
        "mov.b32 {xl, xh}, o20; cvt.f32.f16 f0, xl; cvt.f32.f16 f1, xh; cvt.rn.bf16x2.f32 tt, f1, f0; fma.rn.bf16x2 v2, tt, osc, v2;\n"
        "mov.b32 {xl, xh}, o22; cvt.f32.f16 f0, xl; cvt.f32.f16 f1, xh; cvt.rn.bf16x2.f32 tt, f1, f0; fma.rn.bf16x2 v3, tt, osc, v3;\n"
        "and.b32 ad, %6, 0xffff; add.u32 ad, ad, %4; st.shared.v4.b32 [ad+128], {v0,v1,v2,v3};\n"
        "mov.b32 {xl, xh}, o17; cvt.f32.f16 f0, xl; cvt.f32.f16 f1, xh; cvt.rn.bf16x2.f32 tt, f1, f0; fma.rn.bf16x2 v4, tt, osc, v4;\n"
        "mov.b32 {xl, xh}, o19; cvt.f32.f16 f0, xl; cvt.f32.f16 f1, xh; cvt.rn.bf16x2.f32 tt, f1, f0; fma.rn.bf16x2 v5, tt, osc, v5;\n"
        "mov.b32 {xl, xh}, o21; cvt.f32.f16 f0, xl; cvt.f32.f16 f1, xh; cvt.rn.bf16x2.f32 tt, f1, f0; fma.rn.bf16x2 v6, tt, osc, v6;\n"
        "mov.b32 {xl, xh}, o23; cvt.f32.f16 f0, xl; cvt.f32.f16 f1, xh; cvt.rn.bf16x2.f32 tt, f1, f0; fma.rn.bf16x2 v7, tt, osc, v7;\n"
        "shr.u32 ad, %6, 16; add.u32 ad, ad, %4; st.shared.v4.b32 [ad+128], {v4,v5,v6,v7};\n"
        "ld.shared.v4.b32 {o16,o17,o18,o19}, [%7+256];\n"
        "ld.shared.v4.b32 {o20,o21,o22,o23}, [%7+320];\n"
        "FIRST:\n"
        "@pz bra.uni B8;\n"
        "mov.b32 {xl, xh}, a0; tanh.approx.f16 xr, xl; cvt.u32.u16 lo0, xr; tanh.approx.f16 xr, xh; cvt.u32.u16 hi0, xr; mul.rn.f16x2 a1, qz7, p1; fma.rn.f16x2 p0, qz8, qz8, c; fma.rn.f16x2 g4, qz4, h0, qz4; prmt.b32 h1, lo1, hi1, 0x5410;\n"
        "mov.b32 {xl, xh}, a1; tanh.approx.f16 xr, xl; cvt.u32.u16 lo1, xr; tanh.approx.f16 xr, xh; cvt.u32.u16 hi1, xr; mul.rn.f16x2 a0, qz8, p0; fma.rn.f16x2 p1, qz9, qz9, c; fma.rn.f16x2 g5, qz5, h1, qz5; prmt.b32 h0, lo0, hi0, 0x5410;\n"
        "B8:\n"
        "fence.proxy.async.shared::cta;\n"
        "add.u32 tt, id, 4;\n"
        "@pl bra.uni STORE;\n"
        "bar.arrive tt, 128;\n"
        "STOREB:\n"
        ASM_MARK
        "@!pm bra.uni DONE;\n"
        "add.s32 n, n, 1; sub.u32 off, off, %8; setp.lt.s32 pm, n, 7;\n"
        "@pz bra.uni B10;\n"
        "mov.b32 {xl, xh}, a0; tanh.approx.f16 xr, xl; cvt.u32.u16 lo0, xr; tanh.approx.f16 xr, xh; cvt.u32.u16 hi0, xr; mul.rn.f16x2 a1, qz9, p1; fma.rn.f16x2 p0, qz10, qz10, c; fma.rn.f16x2 g6, qz6, h0, qz6; prmt.b32 h1, lo1, hi1, 0x5410;\n"
        "mov.b32 {xl, xh}, a1; tanh.approx.f16 xr, xl; cvt.u32.u16 lo1, xr; tanh.approx.f16 xr, xh; cvt.u32.u16 hi1, xr; mul.rn.f16x2 a0, qz10, p0; fma.rn.f16x2 p1, qz11, qz11, c; fma.rn.f16x2 g7, qz7, h1, qz7; prmt.b32 h0, lo0, hi0, 0x5410;\n"
        "B10:\n"
        "setp.eq.s32 pr, n, 0;\n"
        "@pr bra.uni SPINW0;\n"
        "BACKW0:\n"
        "wgmma.fence.sync.aligned;\n"
        "add.s64 dt, w2d, 0; wgmma.mma_async.sync.aligned.m64n96k16.f16.f16.f16 {o0,o1,o2,o3,o4,o5,o6,o7,o8,o9,o10,o11,o12,o13,o14,o15,o16,o17,o18,o19,o20,o21,o22,o23}, {g0,g1,g2,g3}, dt, pt, 1, 1, 1;\n"
        "add.s64 dt, w2d, 64; wgmma.mma_async.sync.aligned.m64n96k16.f16.f16.f16 {o0,o1,o2,o3,o4,o5,o6,o7,o8,o9,o10,o11,o12,o13,o14,o15,o16,o17,o18,o19,o20,o21,o22,o23}, {g4,g5,g6,g7}, dt, pt, 1, 1, 1;\n"
        "wgmma.commit_group.sync.aligned;\n"
        "@pz bra.uni B14;\n"
        "mov.b32 {xl, xh}, a0; tanh.approx.f16 xr, xl; cvt.u32.u16 lo0, xr; tanh.approx.f16 xr, xh; cvt.u32.u16 hi0, xr; mul.rn.f16x2 a1, qz11, p1; fma.rn.f16x2 p0, qz12, qz12, c; fma.rn.f16x2 g8, qz8, h0, qz8; prmt.b32 h1, lo1, hi1, 0x5410;\n"
        "mov.b32 {xl, xh}, a1; tanh.approx.f16 xr, xl; cvt.u32.u16 lo1, xr; tanh.approx.f16 xr, xh; cvt.u32.u16 hi1, xr; mul.rn.f16x2 a0, qz12, p0; fma.rn.f16x2 p1, qz13, qz13, c; fma.rn.f16x2 g9, qz9, h1, qz9; prmt.b32 h0, lo0, hi0, 0x5410;\n"
        "mov.b32 {xl, xh}, a0; tanh.approx.f16 xr, xl; cvt.u32.u16 lo0, xr; tanh.approx.f16 xr, xh; cvt.u32.u16 hi0, xr; mul.rn.f16x2 a1, qz13, p1; fma.rn.f16x2 p0, qz14, qz14, c; fma.rn.f16x2 g10, qz10, h0, qz10; prmt.b32 h1, lo1, hi1, 0x5410;\n"
        "mov.b32 {xl, xh}, a1; tanh.approx.f16 xr, xl; cvt.u32.u16 lo1, xr; tanh.approx.f16 xr, xh; cvt.u32.u16 hi1, xr; mul.rn.f16x2 a0, qz14, p0; fma.rn.f16x2 p1, qz15, qz15, c; fma.rn.f16x2 g11, qz11, h1, qz11; prmt.b32 h0, lo0, hi0, 0x5410;\n"
        "B14:\n"
        "wgmma.wait_group.sync.aligned 1;\n"
        "wgmma.fence.sync.aligned;\n"
        "add.s64 dt, w2d, 128; wgmma.mma_async.sync.aligned.m64n96k16.f16.f16.f16 {o0,o1,o2,o3,o4,o5,o6,o7,o8,o9,o10,o11,o12,o13,o14,o15,o16,o17,o18,o19,o20,o21,o22,o23}, {g8,g9,g10,g11}, dt, pt, 1, 1, 1;\n"
        "wgmma.commit_group.sync.aligned;\n"
        "@pz bra.uni B18;\n"
        "mov.b32 {xl, xh}, a0; tanh.approx.f16 xr, xl; cvt.u32.u16 lo0, xr; tanh.approx.f16 xr, xh; cvt.u32.u16 hi0, xr; mul.rn.f16x2 a1, qz15, p1; fma.rn.f16x2 p0, qz16, qz16, c; fma.rn.f16x2 g12, qz12, h0, qz12; prmt.b32 h1, lo1, hi1, 0x5410;\n"
        "mov.b32 {xl, xh}, a1; tanh.approx.f16 xr, xl; cvt.u32.u16 lo1, xr; tanh.approx.f16 xr, xh; cvt.u32.u16 hi1, xr; mul.rn.f16x2 a0, qz16, p0; fma.rn.f16x2 p1, qz17, qz17, c; fma.rn.f16x2 g13, qz13, h1, qz13; prmt.b32 h0, lo0, hi0, 0x5410;\n"
        "mov.b32 {xl, xh}, a0; tanh.approx.f16 xr, xl; cvt.u32.u16 lo0, xr; tanh.approx.f16 xr, xh; cvt.u32.u16 hi0, xr; mul.rn.f16x2 a1, qz17, p1; fma.rn.f16x2 p0, qz18, qz18, c; fma.rn.f16x2 g14, qz14, h0, qz14; prmt.b32 h1, lo1, hi1, 0x5410;\n"
        "mov.b32 {xl, xh}, a1; tanh.approx.f16 xr, xl; cvt.u32.u16 lo1, xr; tanh.approx.f16 xr, xh; cvt.u32.u16 hi1, xr; mul.rn.f16x2 a0, qz18, p0; fma.rn.f16x2 p1, qz19, qz19, c; fma.rn.f16x2 g15, qz15, h1, qz15; prmt.b32 h0, lo0, hi0, 0x5410;\n"
        "B18:\n"
        "wgmma.wait_group.sync.aligned 1;\n"
        "mad.lo.u32 tt, n, 8, tbar; mbarrier.try_wait.parity.shared::cta.b64 pw, [tt], tpar;\n"
        "@!pw bra.uni SPINT;\n"
        "BACKT:\n"
        "wgmma.fence.sync.aligned;\n"
        "add.s64 dt, w2d, 192; wgmma.mma_async.sync.aligned.m64n96k16.f16.f16.f16 {o0,o1,o2,o3,o4,o5,o6,o7,o8,o9,o10,o11,o12,o13,o14,o15,o16,o17,o18,o19,o20,o21,o22,o23}, {g12,g13,g14,g15}, dt, pt, 1, 1, 1;\n"
        "add.s64 dt, w1d, 1536; wgmma.mma_async.sync.aligned.m64n64k16.f16.f16.f16 {qz0,qz1,qz2,qz3,qz4,qz5,qz6,qz7,qz8,qz9,qz10,qz11,qz12,qz13,qz14,qz15}, {qa0,qa1,qa2,qa3}, dt, pf, 1, 1, 1;\n"
        "add.s64 dt, w1d, 1664; wgmma.mma_async.sync.aligned.m64n64k16.f16.f16.f16 {qz0,qz1,qz2,qz3,qz4,qz5,qz6,qz7,qz8,qz9,qz10,qz11,qz12,qz13,qz14,qz15}, {qa4,qa5,qa6,qa7}, dt, pt, 1, 1, 1;\n"
        "add.s64 dt, w1d, 1792; wgmma.mma_async.sync.aligned.m64n64k16.f16.f16.f16 {qz0,qz1,qz2,qz3,qz4,qz5,qz6,qz7,qz8,qz9,qz10,qz11,qz12,qz13,qz14,qz15}, {qa8,qa9,qa10,qa11}, dt, pt, 1, 1, 1;\n"
        "wgmma.commit_group.sync.aligned;\n"
        "@pl bra.uni YLOAD;\n"
        "YLOADB:\n"
        "@pz bra.uni B22;\n"
        "mov.b32 {xl, xh}, a0; tanh.approx.f16 xr, xl; cvt.u32.u16 lo0, xr; tanh.approx.f16 xr, xh; cvt.u32.u16 hi0, xr; mul.rn.f16x2 a1, qz19, p1; fma.rn.f16x2 p0, qz20, qz20, c; fma.rn.f16x2 g0, qz16, h0, qz16; prmt.b32 h1, lo1, hi1, 0x5410;\n"
        "mov.b32 {xl, xh}, a1; tanh.approx.f16 xr, xl; cvt.u32.u16 lo1, xr; tanh.approx.f16 xr, xh; cvt.u32.u16 hi1, xr; mul.rn.f16x2 a0, qz20, p0; fma.rn.f16x2 p1, qz21, qz21, c; fma.rn.f16x2 g1, qz17, h1, qz17; prmt.b32 h0, lo0, hi0, 0x5410;\n"
        "mov.b32 {xl, xh}, a0; tanh.approx.f16 xr, xl; cvt.u32.u16 lo0, xr; tanh.approx.f16 xr, xh; cvt.u32.u16 hi0, xr; mul.rn.f16x2 a1, qz21, p1; fma.rn.f16x2 p0, qz22, qz22, c; fma.rn.f16x2 g2, qz18, h0, qz18; prmt.b32 h1, lo1, hi1, 0x5410;\n"
        "mov.b32 {xl, xh}, a1; tanh.approx.f16 xr, xl; cvt.u32.u16 lo1, xr; tanh.approx.f16 xr, xh; cvt.u32.u16 hi1, xr; mul.rn.f16x2 a0, qz22, p0; fma.rn.f16x2 p1, qz23, qz23, c; fma.rn.f16x2 g3, qz19, h1, qz19; prmt.b32 h0, lo0, hi0, 0x5410;\n"
        "B22:\n"
        "wgmma.fence.sync.aligned;\n"
        "add.s64 dt, w2d, 256; wgmma.mma_async.sync.aligned.m64n96k16.f16.f16.f16 {o0,o1,o2,o3,o4,o5,o6,o7,o8,o9,o10,o11,o12,o13,o14,o15,o16,o17,o18,o19,o20,o21,o22,o23}, {g0,g1,g2,g3}, dt, pt, 1, 1, 1;\n"
        "add.s64 dt, w1d, 1920; wgmma.mma_async.sync.aligned.m64n64k16.f16.f16.f16 {qz0,qz1,qz2,qz3,qz4,qz5,qz6,qz7,qz8,qz9,qz10,qz11,qz12,qz13,qz14,qz15}, {qa12,qa13,qa14,qa15}, dt, pt, 1, 1, 1;\n"
        "add.s64 dt, w1d, 2048; wgmma.mma_async.sync.aligned.m64n64k16.f16.f16.f16 {qz0,qz1,qz2,qz3,qz4,qz5,qz6,qz7,qz8,qz9,qz10,qz11,qz12,qz13,qz14,qz15}, {qa16,qa17,qa18,qa19}, dt, pt, 1, 1, 1;\n"
        "add.s64 dt, w1d, 2176; wgmma.mma_async.sync.aligned.m64n64k16.f16.f16.f16 {qz0,qz1,qz2,qz3,qz4,qz5,qz6,qz7,qz8,qz9,qz10,qz11,qz12,qz13,qz14,qz15}, {qa20,qa21,qa22,qa23}, dt, pt, 1, 1, 1;\n"
        "wgmma.commit_group.sync.aligned;\n"
        "@pz bra.uni B26;\n"
        "mov.b32 {xl, xh}, a0; tanh.approx.f16 xr, xl; cvt.u32.u16 lo0, xr; tanh.approx.f16 xr, xh; cvt.u32.u16 hi0, xr; mul.rn.f16x2 a1, qz23, p1; fma.rn.f16x2 p0, qz24, qz24, c; fma.rn.f16x2 g4, qz20, h0, qz20; prmt.b32 h1, lo1, hi1, 0x5410;\n"
        "mov.b32 {xl, xh}, a1; tanh.approx.f16 xr, xl; cvt.u32.u16 lo1, xr; tanh.approx.f16 xr, xh; cvt.u32.u16 hi1, xr; mul.rn.f16x2 a0, qz24, p0; fma.rn.f16x2 p1, qz25, qz25, c; fma.rn.f16x2 g5, qz21, h1, qz21; prmt.b32 h0, lo0, hi0, 0x5410;\n"
        "mov.b32 {xl, xh}, a0; tanh.approx.f16 xr, xl; cvt.u32.u16 lo0, xr; tanh.approx.f16 xr, xh; cvt.u32.u16 hi0, xr; mul.rn.f16x2 a1, qz25, p1; fma.rn.f16x2 p0, qz26, qz26, c; fma.rn.f16x2 g6, qz22, h0, qz22; prmt.b32 h1, lo1, hi1, 0x5410;\n"
        "mov.b32 {xl, xh}, a1; tanh.approx.f16 xr, xl; cvt.u32.u16 lo1, xr; tanh.approx.f16 xr, xh; cvt.u32.u16 hi1, xr; mul.rn.f16x2 a0, qz26, p0; fma.rn.f16x2 p1, qz27, qz27, c; fma.rn.f16x2 g7, qz23, h1, qz23; prmt.b32 h0, lo0, hi0, 0x5410;\n"
        "B26:\n"
        "wgmma.wait_group.sync.aligned 2;\n"
        "wgmma.fence.sync.aligned;\n"
        "add.s64 dt, w2d, 320; wgmma.mma_async.sync.aligned.m64n96k16.f16.f16.f16 {o0,o1,o2,o3,o4,o5,o6,o7,o8,o9,o10,o11,o12,o13,o14,o15,o16,o17,o18,o19,o20,o21,o22,o23}, {g4,g5,g6,g7}, dt, pt, 1, 1, 1;\n"
        "wgmma.commit_group.sync.aligned;\n"
        "@pz bra.uni B30;\n"
        "mov.b32 {xl, xh}, a0; tanh.approx.f16 xr, xl; cvt.u32.u16 lo0, xr; tanh.approx.f16 xr, xh; cvt.u32.u16 hi0, xr; mul.rn.f16x2 a1, qz27, p1; fma.rn.f16x2 p0, qz28, qz28, c; fma.rn.f16x2 g8, qz24, h0, qz24; prmt.b32 h1, lo1, hi1, 0x5410;\n"
        "mov.b32 {xl, xh}, a1; tanh.approx.f16 xr, xl; cvt.u32.u16 lo1, xr; tanh.approx.f16 xr, xh; cvt.u32.u16 hi1, xr; mul.rn.f16x2 a0, qz28, p0; fma.rn.f16x2 p1, qz29, qz29, c; fma.rn.f16x2 g9, qz25, h1, qz25; prmt.b32 h0, lo0, hi0, 0x5410;\n"
        "mov.b32 {xl, xh}, a0; tanh.approx.f16 xr, xl; cvt.u32.u16 lo0, xr; tanh.approx.f16 xr, xh; cvt.u32.u16 hi0, xr; mul.rn.f16x2 a1, qz29, p1; fma.rn.f16x2 p0, qz30, qz30, c; fma.rn.f16x2 g10, qz26, h0, qz26; prmt.b32 h1, lo1, hi1, 0x5410;\n"
        "mov.b32 {xl, xh}, a1; tanh.approx.f16 xr, xl; cvt.u32.u16 lo1, xr; tanh.approx.f16 xr, xh; cvt.u32.u16 hi1, xr; mul.rn.f16x2 a0, qz30, p0; fma.rn.f16x2 p1, qz31, qz31, c; fma.rn.f16x2 g11, qz27, h1, qz27; prmt.b32 h0, lo0, hi0, 0x5410;\n"
        "B30:\n"
        "wgmma.wait_group.sync.aligned 1;\n"
        "wgmma.fence.sync.aligned;\n"
        "add.s64 dt, w2d, 384; wgmma.mma_async.sync.aligned.m64n96k16.f16.f16.f16 {o0,o1,o2,o3,o4,o5,o6,o7,o8,o9,o10,o11,o12,o13,o14,o15,o16,o17,o18,o19,o20,o21,o22,o23}, {g8,g9,g10,g11}, dt, pt, 1, 1, 1;\n"
        "wgmma.commit_group.sync.aligned;\n"
        "@pz bra.uni B34;\n"
        "mov.b32 {xl, xh}, a0; tanh.approx.f16 xr, xl; cvt.u32.u16 lo0, xr; tanh.approx.f16 xr, xh; cvt.u32.u16 hi0, xr; mul.rn.f16x2 a1, qz31, p1; fma.rn.f16x2 p0, qz0, qz0, c; fma.rn.f16x2 g12, qz28, h0, qz28; prmt.b32 h1, lo1, hi1, 0x5410;\n"
        "mov.b32 {xl, xh}, a1; tanh.approx.f16 xr, xl; cvt.u32.u16 lo1, xr; tanh.approx.f16 xr, xh; cvt.u32.u16 hi1, xr; mul.rn.f16x2 a0, qz0, p0; fma.rn.f16x2 p1, qz1, qz1, c; fma.rn.f16x2 g13, qz29, h1, qz29; prmt.b32 h0, lo0, hi0, 0x5410;\n"
        "mov.b32 {xl, xh}, a0; tanh.approx.f16 xr, xl; cvt.u32.u16 lo0, xr; tanh.approx.f16 xr, xh; cvt.u32.u16 hi0, xr; mul.rn.f16x2 a1, qz1, p1; fma.rn.f16x2 p0, qz2, qz2, c; fma.rn.f16x2 g14, qz30, h0, qz30; prmt.b32 h1, lo1, hi1, 0x5410;\n"
        "mov.b32 {xl, xh}, a1; tanh.approx.f16 xr, xl; cvt.u32.u16 lo1, xr; tanh.approx.f16 xr, xh; cvt.u32.u16 hi1, xr; mul.rn.f16x2 a0, qz2, p0; fma.rn.f16x2 p1, qz3, qz3, c; fma.rn.f16x2 g15, qz31, h1, qz31; prmt.b32 h0, lo0, hi0, 0x5410;\n"
        "B34:\n"
        "wgmma.fence.sync.aligned;\n"
        "add.s64 dt, w2d, 448; wgmma.mma_async.sync.aligned.m64n96k16.f16.f16.f16 {o0,o1,o2,o3,o4,o5,o6,o7,o8,o9,o10,o11,o12,o13,o14,o15,o16,o17,o18,o19,o20,o21,o22,o23}, {g12,g13,g14,g15}, dt, pt, 1, 1, 1;\n"
        "add.s64 dt, w1d, 2304; wgmma.mma_async.sync.aligned.m64n64k16.f16.f16.f16 {qz16,qz17,qz18,qz19,qz20,qz21,qz22,qz23,qz24,qz25,qz26,qz27,qz28,qz29,qz30,qz31}, {qa0,qa1,qa2,qa3}, dt, pf, 1, 1, 1;\n"
        "add.s64 dt, w1d, 2432; wgmma.mma_async.sync.aligned.m64n64k16.f16.f16.f16 {qz16,qz17,qz18,qz19,qz20,qz21,qz22,qz23,qz24,qz25,qz26,qz27,qz28,qz29,qz30,qz31}, {qa4,qa5,qa6,qa7}, dt, pt, 1, 1, 1;\n"
        "add.s64 dt, w1d, 2560; wgmma.mma_async.sync.aligned.m64n64k16.f16.f16.f16 {qz16,qz17,qz18,qz19,qz20,qz21,qz22,qz23,qz24,qz25,qz26,qz27,qz28,qz29,qz30,qz31}, {qa8,qa9,qa10,qa11}, dt, pt, 1, 1, 1;\n"
        "wgmma.commit_group.sync.aligned;\n"
        "@pz bra.uni B38;\n"
        "mov.b32 {xl, xh}, a0; tanh.approx.f16 xr, xl; cvt.u32.u16 lo0, xr; tanh.approx.f16 xr, xh; cvt.u32.u16 hi0, xr; mul.rn.f16x2 a1, qz3, p1; fma.rn.f16x2 p0, qz4, qz4, c; fma.rn.f16x2 g0, qz0, h0, qz0; prmt.b32 h1, lo1, hi1, 0x5410;\n"
        "mov.b32 {xl, xh}, a1; tanh.approx.f16 xr, xl; cvt.u32.u16 lo1, xr; tanh.approx.f16 xr, xh; cvt.u32.u16 hi1, xr; mul.rn.f16x2 a0, qz4, p0; fma.rn.f16x2 p1, qz5, qz5, c; fma.rn.f16x2 g1, qz1, h1, qz1; prmt.b32 h0, lo0, hi0, 0x5410;\n"
        "mov.b32 {xl, xh}, a0; tanh.approx.f16 xr, xl; cvt.u32.u16 lo0, xr; tanh.approx.f16 xr, xh; cvt.u32.u16 hi0, xr; mul.rn.f16x2 a1, qz5, p1; fma.rn.f16x2 p0, qz6, qz6, c; fma.rn.f16x2 g2, qz2, h0, qz2; prmt.b32 h1, lo1, hi1, 0x5410;\n"
        "mov.b32 {xl, xh}, a1; tanh.approx.f16 xr, xl; cvt.u32.u16 lo1, xr; tanh.approx.f16 xr, xh; cvt.u32.u16 hi1, xr; mul.rn.f16x2 a0, qz6, p0; fma.rn.f16x2 p1, qz7, qz7, c; fma.rn.f16x2 g3, qz3, h1, qz3; prmt.b32 h0, lo0, hi0, 0x5410;\n"
        "B38:\n"
        "wgmma.wait_group.sync.aligned 2;\n"
        "setp.eq.s32 pr, n, 0;\n"
        "@pr bra.uni SPINW1;\n"
        "BACKW1:\n"
        "wgmma.fence.sync.aligned;\n"
        "add.s64 dt, w2d, 512; wgmma.mma_async.sync.aligned.m64n96k16.f16.f16.f16 {o0,o1,o2,o3,o4,o5,o6,o7,o8,o9,o10,o11,o12,o13,o14,o15,o16,o17,o18,o19,o20,o21,o22,o23}, {g0,g1,g2,g3}, dt, pt, 1, 1, 1;\n"
        "add.s64 dt, w1d, 2688; wgmma.mma_async.sync.aligned.m64n64k16.f16.f16.f16 {qz16,qz17,qz18,qz19,qz20,qz21,qz22,qz23,qz24,qz25,qz26,qz27,qz28,qz29,qz30,qz31}, {qa12,qa13,qa14,qa15}, dt, pt, 1, 1, 1;\n"
        "add.s64 dt, w1d, 2816; wgmma.mma_async.sync.aligned.m64n64k16.f16.f16.f16 {qz16,qz17,qz18,qz19,qz20,qz21,qz22,qz23,qz24,qz25,qz26,qz27,qz28,qz29,qz30,qz31}, {qa16,qa17,qa18,qa19}, dt, pt, 1, 1, 1;\n"
        "add.s64 dt, w1d, 2944; wgmma.mma_async.sync.aligned.m64n64k16.f16.f16.f16 {qz16,qz17,qz18,qz19,qz20,qz21,qz22,qz23,qz24,qz25,qz26,qz27,qz28,qz29,qz30,qz31}, {qa20,qa21,qa22,qa23}, dt, pt, 1, 1, 1;\n"
        "wgmma.commit_group.sync.aligned;\n"
        "@pz bra.uni B42;\n"
        "mov.b32 {xl, xh}, a0; tanh.approx.f16 xr, xl; cvt.u32.u16 lo0, xr; tanh.approx.f16 xr, xh; cvt.u32.u16 hi0, xr; mul.rn.f16x2 a1, qz7, p1; fma.rn.f16x2 p0, qz8, qz8, c; fma.rn.f16x2 g4, qz4, h0, qz4; prmt.b32 h1, lo1, hi1, 0x5410;\n"
        "mov.b32 {xl, xh}, a1; tanh.approx.f16 xr, xl; cvt.u32.u16 lo1, xr; tanh.approx.f16 xr, xh; cvt.u32.u16 hi1, xr; mul.rn.f16x2 a0, qz8, p0; fma.rn.f16x2 p1, qz9, qz9, c; fma.rn.f16x2 g5, qz5, h1, qz5; prmt.b32 h0, lo0, hi0, 0x5410;\n"
        "mov.b32 {xl, xh}, a0; tanh.approx.f16 xr, xl; cvt.u32.u16 lo0, xr; tanh.approx.f16 xr, xh; cvt.u32.u16 hi0, xr; mul.rn.f16x2 a1, qz9, p1; fma.rn.f16x2 p0, qz10, qz10, c; fma.rn.f16x2 g6, qz6, h0, qz6; prmt.b32 h1, lo1, hi1, 0x5410;\n"
        "mov.b32 {xl, xh}, a1; tanh.approx.f16 xr, xl; cvt.u32.u16 lo1, xr; tanh.approx.f16 xr, xh; cvt.u32.u16 hi1, xr; mul.rn.f16x2 a0, qz10, p0; fma.rn.f16x2 p1, qz11, qz11, c; fma.rn.f16x2 g7, qz7, h1, qz7; prmt.b32 h0, lo0, hi0, 0x5410;\n"
        "B42:\n"
        "wgmma.wait_group.sync.aligned 2;\n"
        "wgmma.fence.sync.aligned;\n"
        "add.s64 dt, w2d, 576; wgmma.mma_async.sync.aligned.m64n96k16.f16.f16.f16 {o0,o1,o2,o3,o4,o5,o6,o7,o8,o9,o10,o11,o12,o13,o14,o15,o16,o17,o18,o19,o20,o21,o22,o23}, {g4,g5,g6,g7}, dt, pt, 1, 1, 1;\n"
        "wgmma.commit_group.sync.aligned;\n"
        "@pz bra.uni B46;\n"
        "mov.b32 {xl, xh}, a0; tanh.approx.f16 xr, xl; cvt.u32.u16 lo0, xr; tanh.approx.f16 xr, xh; cvt.u32.u16 hi0, xr; mul.rn.f16x2 a1, qz11, p1; fma.rn.f16x2 p0, qz12, qz12, c; fma.rn.f16x2 g8, qz8, h0, qz8; prmt.b32 h1, lo1, hi1, 0x5410;\n"
        "mov.b32 {xl, xh}, a1; tanh.approx.f16 xr, xl; cvt.u32.u16 lo1, xr; tanh.approx.f16 xr, xh; cvt.u32.u16 hi1, xr; mul.rn.f16x2 a0, qz12, p0; fma.rn.f16x2 p1, qz13, qz13, c; fma.rn.f16x2 g9, qz9, h1, qz9; prmt.b32 h0, lo0, hi0, 0x5410;\n"
        "mov.b32 {xl, xh}, a0; tanh.approx.f16 xr, xl; cvt.u32.u16 lo0, xr; tanh.approx.f16 xr, xh; cvt.u32.u16 hi0, xr; mul.rn.f16x2 a1, qz13, p1; fma.rn.f16x2 p0, qz14, qz14, c; fma.rn.f16x2 g10, qz10, h0, qz10; prmt.b32 h1, lo1, hi1, 0x5410;\n"
        "mov.b32 {xl, xh}, a1; tanh.approx.f16 xr, xl; cvt.u32.u16 lo1, xr; tanh.approx.f16 xr, xh; cvt.u32.u16 hi1, xr; mul.rn.f16x2 a0, qz14, p0; fma.rn.f16x2 p1, qz15, qz15, c; fma.rn.f16x2 g11, qz11, h1, qz11; prmt.b32 h0, lo0, hi0, 0x5410;\n"
        "B46:\n"
        "wgmma.wait_group.sync.aligned 1;\n"
        "wgmma.fence.sync.aligned;\n"
        "add.s64 dt, w2d, 640; wgmma.mma_async.sync.aligned.m64n96k16.f16.f16.f16 {o0,o1,o2,o3,o4,o5,o6,o7,o8,o9,o10,o11,o12,o13,o14,o15,o16,o17,o18,o19,o20,o21,o22,o23}, {g8,g9,g10,g11}, dt, pt, 1, 1, 1;\n"
        "wgmma.commit_group.sync.aligned;\n"
        "mad.lo.u32 tt, n, 8, tbar;\n"
        "@pn mbarrier.arrive.shared::cta.b64 _, [tt+64];\n"
        "@pz bra.uni B50;\n"
        "mov.b32 {xl, xh}, a0; tanh.approx.f16 xr, xl; cvt.u32.u16 lo0, xr; tanh.approx.f16 xr, xh; cvt.u32.u16 hi0, xr; mul.rn.f16x2 a1, qz15, p1; fma.rn.f16x2 p0, qz16, qz16, c; fma.rn.f16x2 g12, qz12, h0, qz12; prmt.b32 h1, lo1, hi1, 0x5410;\n"
        "mov.b32 {xl, xh}, a1; tanh.approx.f16 xr, xl; cvt.u32.u16 lo1, xr; tanh.approx.f16 xr, xh; cvt.u32.u16 hi1, xr; mul.rn.f16x2 a0, qz16, p0; fma.rn.f16x2 p1, qz17, qz17, c; fma.rn.f16x2 g13, qz13, h1, qz13; prmt.b32 h0, lo0, hi0, 0x5410;\n"
        "mov.b32 {xl, xh}, a0; tanh.approx.f16 xr, xl; cvt.u32.u16 lo0, xr; tanh.approx.f16 xr, xh; cvt.u32.u16 hi0, xr; mul.rn.f16x2 a1, qz17, p1; fma.rn.f16x2 p0, qz18, qz18, c; fma.rn.f16x2 g14, qz14, h0, qz14; prmt.b32 h1, lo1, hi1, 0x5410;\n"
        "mov.b32 {xl, xh}, a1; tanh.approx.f16 xr, xl; cvt.u32.u16 lo1, xr; tanh.approx.f16 xr, xh; cvt.u32.u16 hi1, xr; mul.rn.f16x2 a0, qz18, p0; fma.rn.f16x2 p1, qz19, qz19, c; fma.rn.f16x2 g15, qz15, h1, qz15; prmt.b32 h0, lo0, hi0, 0x5410;\n"
        "B50:\n"
        "wgmma.fence.sync.aligned;\n"
        "add.s64 dt, w2d, 704; wgmma.mma_async.sync.aligned.m64n96k16.f16.f16.f16 {o0,o1,o2,o3,o4,o5,o6,o7,o8,o9,o10,o11,o12,o13,o14,o15,o16,o17,o18,o19,o20,o21,o22,o23}, {g12,g13,g14,g15}, dt, pt, 1, 1, 1;\n"
        "add.s64 dt, w1d, 3072; wgmma.mma_async.sync.aligned.m64n64k16.f16.f16.f16 {qz0,qz1,qz2,qz3,qz4,qz5,qz6,qz7,qz8,qz9,qz10,qz11,qz12,qz13,qz14,qz15}, {qa0,qa1,qa2,qa3}, dt, pf, 1, 1, 1;\n"
        "add.s64 dt, w1d, 3200; wgmma.mma_async.sync.aligned.m64n64k16.f16.f16.f16 {qz0,qz1,qz2,qz3,qz4,qz5,qz6,qz7,qz8,qz9,qz10,qz11,qz12,qz13,qz14,qz15}, {qa4,qa5,qa6,qa7}, dt, pt, 1, 1, 1;\n"
        "add.s64 dt, w1d, 3328; wgmma.mma_async.sync.aligned.m64n64k16.f16.f16.f16 {qz0,qz1,qz2,qz3,qz4,qz5,qz6,qz7,qz8,qz9,qz10,qz11,qz12,qz13,qz14,qz15}, {qa8,qa9,qa10,qa11}, dt, pt, 1, 1, 1;\n"
        "wgmma.commit_group.sync.aligned;\n"
        "@pz bra.uni B54;\n"
        "mov.b32 {xl, xh}, a0; tanh.approx.f16 xr, xl; cvt.u32.u16 lo0, xr; tanh.approx.f16 xr, xh; cvt.u32.u16 hi0, xr; mul.rn.f16x2 a1, qz19, p1; fma.rn.f16x2 p0, qz20, qz20, c; fma.rn.f16x2 g0, qz16, h0, qz16; prmt.b32 h1, lo1, hi1, 0x5410;\n"
        "mov.b32 {xl, xh}, a1; tanh.approx.f16 xr, xl; cvt.u32.u16 lo1, xr; tanh.approx.f16 xr, xh; cvt.u32.u16 hi1, xr; mul.rn.f16x2 a0, qz20, p0; fma.rn.f16x2 p1, qz21, qz21, c; fma.rn.f16x2 g1, qz17, h1, qz17; prmt.b32 h0, lo0, hi0, 0x5410;\n"
        "mov.b32 {xl, xh}, a0; tanh.approx.f16 xr, xl; cvt.u32.u16 lo0, xr; tanh.approx.f16 xr, xh; cvt.u32.u16 hi0, xr; mul.rn.f16x2 a1, qz21, p1; fma.rn.f16x2 p0, qz22, qz22, c; fma.rn.f16x2 g2, qz18, h0, qz18; prmt.b32 h1, lo1, hi1, 0x5410;\n"
        "mov.b32 {xl, xh}, a1; tanh.approx.f16 xr, xl; cvt.u32.u16 lo1, xr; tanh.approx.f16 xr, xh; cvt.u32.u16 hi1, xr; mul.rn.f16x2 a0, qz22, p0; fma.rn.f16x2 p1, qz23, qz23, c; fma.rn.f16x2 g3, qz19, h1, qz19; prmt.b32 h0, lo0, hi0, 0x5410;\n"
        "B54:\n"
        "wgmma.wait_group.sync.aligned 2;\n"
        "wgmma.fence.sync.aligned;\n"
        "add.s64 dt, w2d, 768; wgmma.mma_async.sync.aligned.m64n96k16.f16.f16.f16 {o0,o1,o2,o3,o4,o5,o6,o7,o8,o9,o10,o11,o12,o13,o14,o15,o16,o17,o18,o19,o20,o21,o22,o23}, {g0,g1,g2,g3}, dt, pt, 1, 1, 1;\n"
        "add.s64 dt, w1d, 3456; wgmma.mma_async.sync.aligned.m64n64k16.f16.f16.f16 {qz0,qz1,qz2,qz3,qz4,qz5,qz6,qz7,qz8,qz9,qz10,qz11,qz12,qz13,qz14,qz15}, {qa12,qa13,qa14,qa15}, dt, pt, 1, 1, 1;\n"
        "add.s64 dt, w1d, 3584; wgmma.mma_async.sync.aligned.m64n64k16.f16.f16.f16 {qz0,qz1,qz2,qz3,qz4,qz5,qz6,qz7,qz8,qz9,qz10,qz11,qz12,qz13,qz14,qz15}, {qa16,qa17,qa18,qa19}, dt, pt, 1, 1, 1;\n"
        "add.s64 dt, w1d, 3712; wgmma.mma_async.sync.aligned.m64n64k16.f16.f16.f16 {qz0,qz1,qz2,qz3,qz4,qz5,qz6,qz7,qz8,qz9,qz10,qz11,qz12,qz13,qz14,qz15}, {qa20,qa21,qa22,qa23}, dt, pt, 1, 1, 1;\n"
        "wgmma.commit_group.sync.aligned;\n"
        "@pz bra.uni B58;\n"
        "mov.b32 {xl, xh}, a0; tanh.approx.f16 xr, xl; cvt.u32.u16 lo0, xr; tanh.approx.f16 xr, xh; cvt.u32.u16 hi0, xr; mul.rn.f16x2 a1, qz23, p1; fma.rn.f16x2 p0, qz24, qz24, c; fma.rn.f16x2 g4, qz20, h0, qz20; prmt.b32 h1, lo1, hi1, 0x5410;\n"
        "mov.b32 {xl, xh}, a1; tanh.approx.f16 xr, xl; cvt.u32.u16 lo1, xr; tanh.approx.f16 xr, xh; cvt.u32.u16 hi1, xr; mul.rn.f16x2 a0, qz24, p0; fma.rn.f16x2 p1, qz25, qz25, c; fma.rn.f16x2 g5, qz21, h1, qz21; prmt.b32 h0, lo0, hi0, 0x5410;\n"
        "mov.b32 {xl, xh}, a0; tanh.approx.f16 xr, xl; cvt.u32.u16 lo0, xr; tanh.approx.f16 xr, xh; cvt.u32.u16 hi0, xr; mul.rn.f16x2 a1, qz25, p1; fma.rn.f16x2 p0, qz26, qz26, c; fma.rn.f16x2 g6, qz22, h0, qz22; prmt.b32 h1, lo1, hi1, 0x5410;\n"
        "mov.b32 {xl, xh}, a1; tanh.approx.f16 xr, xl; cvt.u32.u16 lo1, xr; tanh.approx.f16 xr, xh; cvt.u32.u16 hi1, xr; mul.rn.f16x2 a0, qz26, p0; fma.rn.f16x2 p1, qz27, qz27, c; fma.rn.f16x2 g7, qz23, h1, qz23; prmt.b32 h0, lo0, hi0, 0x5410;\n"
        "B58:\n"
        "wgmma.wait_group.sync.aligned 2;\n"
        "wgmma.fence.sync.aligned;\n"
        "add.s64 dt, w2d, 832; wgmma.mma_async.sync.aligned.m64n96k16.f16.f16.f16 {o0,o1,o2,o3,o4,o5,o6,o7,o8,o9,o10,o11,o12,o13,o14,o15,o16,o17,o18,o19,o20,o21,o22,o23}, {g4,g5,g6,g7}, dt, pt, 1, 1, 1;\n"
        "wgmma.commit_group.sync.aligned;\n"
        "@pz bra.uni B62;\n"
        "mov.b32 {xl, xh}, a0; tanh.approx.f16 xr, xl; cvt.u32.u16 lo0, xr; tanh.approx.f16 xr, xh; cvt.u32.u16 hi0, xr; mul.rn.f16x2 a1, qz27, p1; fma.rn.f16x2 p0, qz28, qz28, c; fma.rn.f16x2 g8, qz24, h0, qz24; prmt.b32 h1, lo1, hi1, 0x5410;\n"
        "mov.b32 {xl, xh}, a1; tanh.approx.f16 xr, xl; cvt.u32.u16 lo1, xr; tanh.approx.f16 xr, xh; cvt.u32.u16 hi1, xr; mul.rn.f16x2 a0, qz28, p0; fma.rn.f16x2 p1, qz29, qz29, c; fma.rn.f16x2 g9, qz25, h1, qz25; prmt.b32 h0, lo0, hi0, 0x5410;\n"
        "mov.b32 {xl, xh}, a0; tanh.approx.f16 xr, xl; cvt.u32.u16 lo0, xr; tanh.approx.f16 xr, xh; cvt.u32.u16 hi0, xr; mul.rn.f16x2 a1, qz29, p1; fma.rn.f16x2 p0, qz30, qz30, c; fma.rn.f16x2 g10, qz26, h0, qz26; prmt.b32 h1, lo1, hi1, 0x5410;\n"
        "mov.b32 {xl, xh}, a1; tanh.approx.f16 xr, xl; cvt.u32.u16 lo1, xr; tanh.approx.f16 xr, xh; cvt.u32.u16 hi1, xr; mul.rn.f16x2 a0, qz30, p0; fma.rn.f16x2 p1, qz31, qz31, c; fma.rn.f16x2 g11, qz27, h1, qz27; prmt.b32 h0, lo0, hi0, 0x5410;\n"
        "B62:\n"
        "wgmma.wait_group.sync.aligned 1;\n"
        "wgmma.fence.sync.aligned;\n"
        "add.s64 dt, w2d, 896; wgmma.mma_async.sync.aligned.m64n96k16.f16.f16.f16 {o0,o1,o2,o3,o4,o5,o6,o7,o8,o9,o10,o11,o12,o13,o14,o15,o16,o17,o18,o19,o20,o21,o22,o23}, {g8,g9,g10,g11}, dt, pt, 1, 1, 1;\n"
        "wgmma.commit_group.sync.aligned;\n"
        "@pz bra.uni B66;\n"
        "mov.b32 {xl, xh}, a0; tanh.approx.f16 xr, xl; cvt.u32.u16 lo0, xr; tanh.approx.f16 xr, xh; cvt.u32.u16 hi0, xr; mul.rn.f16x2 a1, qz31, p1; fma.rn.f16x2 p0, qz0, qz0, c; fma.rn.f16x2 g12, qz28, h0, qz28; prmt.b32 h1, lo1, hi1, 0x5410;\n"
        "mov.b32 {xl, xh}, a1; tanh.approx.f16 xr, xl; cvt.u32.u16 lo1, xr; tanh.approx.f16 xr, xh; cvt.u32.u16 hi1, xr; mul.rn.f16x2 a0, qz0, p0; fma.rn.f16x2 p1, qz1, qz1, c; fma.rn.f16x2 g13, qz29, h1, qz29; prmt.b32 h0, lo0, hi0, 0x5410;\n"
        "mov.b32 {xl, xh}, a0; tanh.approx.f16 xr, xl; cvt.u32.u16 lo0, xr; tanh.approx.f16 xr, xh; cvt.u32.u16 hi0, xr; mul.rn.f16x2 a1, qz1, p1; fma.rn.f16x2 p0, qz2, qz2, c; fma.rn.f16x2 g14, qz30, h0, qz30; prmt.b32 h1, lo1, hi1, 0x5410;\n"
        "mov.b32 {xl, xh}, a1; tanh.approx.f16 xr, xl; cvt.u32.u16 lo1, xr; tanh.approx.f16 xr, xh; cvt.u32.u16 hi1, xr; mul.rn.f16x2 a0, qz2, p0; fma.rn.f16x2 p1, qz3, qz3, c; fma.rn.f16x2 g15, qz31, h1, qz31; prmt.b32 h0, lo0, hi0, 0x5410;\n"
        "B66:\n"
        "wgmma.fence.sync.aligned;\n"
        "add.s64 dt, w2d, 960; wgmma.mma_async.sync.aligned.m64n96k16.f16.f16.f16 {o0,o1,o2,o3,o4,o5,o6,o7,o8,o9,o10,o11,o12,o13,o14,o15,o16,o17,o18,o19,o20,o21,o22,o23}, {g12,g13,g14,g15}, dt, pt, 1, 1, 1;\n"
        "add.s64 dt, w1d, 3840; wgmma.mma_async.sync.aligned.m64n64k16.f16.f16.f16 {qz16,qz17,qz18,qz19,qz20,qz21,qz22,qz23,qz24,qz25,qz26,qz27,qz28,qz29,qz30,qz31}, {qa0,qa1,qa2,qa3}, dt, pf, 1, 1, 1;\n"
        "add.s64 dt, w1d, 3968; wgmma.mma_async.sync.aligned.m64n64k16.f16.f16.f16 {qz16,qz17,qz18,qz19,qz20,qz21,qz22,qz23,qz24,qz25,qz26,qz27,qz28,qz29,qz30,qz31}, {qa4,qa5,qa6,qa7}, dt, pt, 1, 1, 1;\n"
        "add.s64 dt, w1d, 4096; wgmma.mma_async.sync.aligned.m64n64k16.f16.f16.f16 {qz16,qz17,qz18,qz19,qz20,qz21,qz22,qz23,qz24,qz25,qz26,qz27,qz28,qz29,qz30,qz31}, {qa8,qa9,qa10,qa11}, dt, pt, 1, 1, 1;\n"
        "wgmma.commit_group.sync.aligned;\n"
        "@pz bra.uni B70;\n"
        "mov.b32 {xl, xh}, a0; tanh.approx.f16 xr, xl; cvt.u32.u16 lo0, xr; tanh.approx.f16 xr, xh; cvt.u32.u16 hi0, xr; mul.rn.f16x2 a1, qz3, p1; fma.rn.f16x2 p0, qz4, qz4, c; fma.rn.f16x2 g0, qz0, h0, qz0; prmt.b32 h1, lo1, hi1, 0x5410;\n"
        "mov.b32 {xl, xh}, a1; tanh.approx.f16 xr, xl; cvt.u32.u16 lo1, xr; tanh.approx.f16 xr, xh; cvt.u32.u16 hi1, xr; mul.rn.f16x2 a0, qz4, p0; fma.rn.f16x2 p1, qz5, qz5, c; fma.rn.f16x2 g1, qz1, h1, qz1; prmt.b32 h0, lo0, hi0, 0x5410;\n"
        "mov.b32 {xl, xh}, a0; tanh.approx.f16 xr, xl; cvt.u32.u16 lo0, xr; tanh.approx.f16 xr, xh; cvt.u32.u16 hi0, xr; mul.rn.f16x2 a1, qz5, p1; fma.rn.f16x2 p0, qz6, qz6, c; fma.rn.f16x2 g2, qz2, h0, qz2; prmt.b32 h1, lo1, hi1, 0x5410;\n"
        "mov.b32 {xl, xh}, a1; tanh.approx.f16 xr, xl; cvt.u32.u16 lo1, xr; tanh.approx.f16 xr, xh; cvt.u32.u16 hi1, xr; mul.rn.f16x2 a0, qz6, p0; fma.rn.f16x2 p1, qz7, qz7, c; fma.rn.f16x2 g3, qz3, h1, qz3; prmt.b32 h0, lo0, hi0, 0x5410;\n"
        "B70:\n"
        "wgmma.wait_group.sync.aligned 2;\n"
        "wgmma.fence.sync.aligned;\n"
        "add.s64 dt, w2d, 1024; wgmma.mma_async.sync.aligned.m64n96k16.f16.f16.f16 {o0,o1,o2,o3,o4,o5,o6,o7,o8,o9,o10,o11,o12,o13,o14,o15,o16,o17,o18,o19,o20,o21,o22,o23}, {g0,g1,g2,g3}, dt, pt, 1, 1, 1;\n"
        "add.s64 dt, w1d, 4224; wgmma.mma_async.sync.aligned.m64n64k16.f16.f16.f16 {qz16,qz17,qz18,qz19,qz20,qz21,qz22,qz23,qz24,qz25,qz26,qz27,qz28,qz29,qz30,qz31}, {qa12,qa13,qa14,qa15}, dt, pt, 1, 1, 1;\n"
        "add.s64 dt, w1d, 4352; wgmma.mma_async.sync.aligned.m64n64k16.f16.f16.f16 {qz16,qz17,qz18,qz19,qz20,qz21,qz22,qz23,qz24,qz25,qz26,qz27,qz28,qz29,qz30,qz31}, {qa16,qa17,qa18,qa19}, dt, pt, 1, 1, 1;\n"
        "add.s64 dt, w1d, 4480; wgmma.mma_async.sync.aligned.m64n64k16.f16.f16.f16 {qz16,qz17,qz18,qz19,qz20,qz21,qz22,qz23,qz24,qz25,qz26,qz27,qz28,qz29,qz30,qz31}, {qa20,qa21,qa22,qa23}, dt, pt, 1, 1, 1;\n"
        "wgmma.commit_group.sync.aligned;\n"
        "@pz bra.uni B74;\n"
        "mov.b32 {xl, xh}, a0; tanh.approx.f16 xr, xl; cvt.u32.u16 lo0, xr; tanh.approx.f16 xr, xh; cvt.u32.u16 hi0, xr; mul.rn.f16x2 a1, qz7, p1; fma.rn.f16x2 p0, qz8, qz8, c; fma.rn.f16x2 g4, qz4, h0, qz4; prmt.b32 h1, lo1, hi1, 0x5410;\n"
        "mov.b32 {xl, xh}, a1; tanh.approx.f16 xr, xl; cvt.u32.u16 lo1, xr; tanh.approx.f16 xr, xh; cvt.u32.u16 hi1, xr; mul.rn.f16x2 a0, qz8, p0; fma.rn.f16x2 p1, qz9, qz9, c; fma.rn.f16x2 g5, qz5, h1, qz5; prmt.b32 h0, lo0, hi0, 0x5410;\n"
        "mov.b32 {xl, xh}, a0; tanh.approx.f16 xr, xl; cvt.u32.u16 lo0, xr; tanh.approx.f16 xr, xh; cvt.u32.u16 hi0, xr; mul.rn.f16x2 a1, qz9, p1; fma.rn.f16x2 p0, qz10, qz10, c; fma.rn.f16x2 g6, qz6, h0, qz6; prmt.b32 h1, lo1, hi1, 0x5410;\n"
        "mov.b32 {xl, xh}, a1; tanh.approx.f16 xr, xl; cvt.u32.u16 lo1, xr; tanh.approx.f16 xr, xh; cvt.u32.u16 hi1, xr; mul.rn.f16x2 a0, qz10, p0; fma.rn.f16x2 p1, qz11, qz11, c; fma.rn.f16x2 g7, qz7, h1, qz7; prmt.b32 h0, lo0, hi0, 0x5410;\n"
        "B74:\n"
        "wgmma.wait_group.sync.aligned 2;\n"
        "wgmma.fence.sync.aligned;\n"
        "add.s64 dt, w2d, 1088; wgmma.mma_async.sync.aligned.m64n96k16.f16.f16.f16 {o0,o1,o2,o3,o4,o5,o6,o7,o8,o9,o10,o11,o12,o13,o14,o15,o16,o17,o18,o19,o20,o21,o22,o23}, {g4,g5,g6,g7}, dt, pt, 1, 1, 1;\n"
        "wgmma.commit_group.sync.aligned;\n"
        "@pz bra.uni B78;\n"
        "mov.b32 {xl, xh}, a0; tanh.approx.f16 xr, xl; cvt.u32.u16 lo0, xr; tanh.approx.f16 xr, xh; cvt.u32.u16 hi0, xr; mul.rn.f16x2 a1, qz11, p1; fma.rn.f16x2 p0, qz12, qz12, c; fma.rn.f16x2 g8, qz8, h0, qz8; prmt.b32 h1, lo1, hi1, 0x5410;\n"
        "mov.b32 {xl, xh}, a1; tanh.approx.f16 xr, xl; cvt.u32.u16 lo1, xr; tanh.approx.f16 xr, xh; cvt.u32.u16 hi1, xr; mul.rn.f16x2 a0, qz12, p0; fma.rn.f16x2 p1, qz13, qz13, c; fma.rn.f16x2 g9, qz9, h1, qz9; prmt.b32 h0, lo0, hi0, 0x5410;\n"
        "mov.b32 {xl, xh}, a0; tanh.approx.f16 xr, xl; cvt.u32.u16 lo0, xr; tanh.approx.f16 xr, xh; cvt.u32.u16 hi0, xr; mul.rn.f16x2 a1, qz13, p1; fma.rn.f16x2 p0, qz14, qz14, c; fma.rn.f16x2 g10, qz10, h0, qz10; prmt.b32 h1, lo1, hi1, 0x5410;\n"
        "mov.b32 {xl, xh}, a1; tanh.approx.f16 xr, xl; cvt.u32.u16 lo1, xr; tanh.approx.f16 xr, xh; cvt.u32.u16 hi1, xr; mul.rn.f16x2 a0, qz14, p0; fma.rn.f16x2 p1, qz15, qz15, c; fma.rn.f16x2 g11, qz11, h1, qz11; prmt.b32 h0, lo0, hi0, 0x5410;\n"
        "B78:\n"
        "wgmma.wait_group.sync.aligned 1;\n"
        "wgmma.fence.sync.aligned;\n"
        "add.s64 dt, w2d, 1152; wgmma.mma_async.sync.aligned.m64n96k16.f16.f16.f16 {o0,o1,o2,o3,o4,o5,o6,o7,o8,o9,o10,o11,o12,o13,o14,o15,o16,o17,o18,o19,o20,o21,o22,o23}, {g8,g9,g10,g11}, dt, pt, 1, 1, 1;\n"
        "wgmma.commit_group.sync.aligned;\n"
        "@!pm bra.uni BACKY;\n"
        "add.u32 tt, n, 1; and.b32 tt, tt, 1; mbarrier.try_wait.parity.shared::cta.b64 pw, [ybar], tt;\n"
        "@!pw bra.uni SPINY;\n"
        "BACKY:\n"
        "@pz bra.uni B80;\n"
        "and.b32 ad, %5, 0xffff; xor.b32 ad, ad, 0; add.u32 ad, ad, %4; ldmatrix.sync.aligned.m8n8.x4.shared.b16 {qa0,qa1,qa2,qa3}, [ad];\n"
        "and.b32 ad, %5, 0xffff; xor.b32 ad, ad, 32; add.u32 ad, ad, %4; ldmatrix.sync.aligned.m8n8.x4.shared.b16 {qa4,qa5,qa6,qa7}, [ad];\n"
        "and.b32 ad, %5, 0xffff; xor.b32 ad, ad, 64; add.u32 ad, ad, %4; ldmatrix.sync.aligned.m8n8.x4.shared.b16 {qa8,qa9,qa10,qa11}, [ad];\n"
        "and.b32 ad, %5, 0xffff; xor.b32 ad, ad, 96; add.u32 ad, ad, %4; ldmatrix.sync.aligned.m8n8.x4.shared.b16 {qa12,qa13,qa14,qa15}, [ad];\n"
        "shr.u32 ad, %5, 16; xor.b32 ad, ad, 0; add.u32 ad, ad, %4; ldmatrix.sync.aligned.m8n8.x4.shared.b16 {qa16,qa17,qa18,qa19}, [ad];\n"
        "shr.u32 ad, %5, 16; xor.b32 ad, ad, 32; add.u32 ad, ad, %4; ldmatrix.sync.aligned.m8n8.x4.shared.b16 {qa20,qa21,qa22,qa23}, [ad];\n"
        "mov.b32 {xl, xh}, a0; tanh.approx.f16 xr, xl; cvt.u32.u16 lo0, xr; tanh.approx.f16 xr, xh; cvt.u32.u16 hi0, xr; mul.rn.f16x2 a1, qz15, p1; fma.rn.f16x2 p0, qz16, qz16, c; fma.rn.f16x2 g12, qz12, h0, qz12; prmt.b32 h1, lo1, hi1, 0x5410;\n"
        "mov.b32 {xl, xh}, a1; tanh.approx.f16 xr, xl; cvt.u32.u16 lo1, xr; tanh.approx.f16 xr, xh; cvt.u32.u16 hi1, xr; mul.rn.f16x2 a0, qz16, p0; fma.rn.f16x2 p1, qz17, qz17, c; fma.rn.f16x2 g13, qz13, h1, qz13; prmt.b32 h0, lo0, hi0, 0x5410;\n"
        "B80:\n"
        "fence.proxy.async.shared::cta;\n"
        "add.u32 tt, id, 0;\n"
        "@pk bra.uni XLOAD;\n"
        "bar.arrive tt, 128;\n"
        "XLOADB:\n"
        "@pz bra.uni B82;\n"
        "mov.b32 {xl, xh}, a0; tanh.approx.f16 xr, xl; cvt.u32.u16 lo0, xr; tanh.approx.f16 xr, xh; cvt.u32.u16 hi0, xr; mul.rn.f16x2 a1, qz17, p1; fma.rn.f16x2 p0, qz18, qz18, c; fma.rn.f16x2 g14, qz14, h0, qz14; prmt.b32 h1, lo1, hi1, 0x5410;\n"
        "mov.b32 {xl, xh}, a1; tanh.approx.f16 xr, xl; cvt.u32.u16 lo1, xr; tanh.approx.f16 xr, xh; cvt.u32.u16 hi1, xr; mul.rn.f16x2 a0, qz18, p0; fma.rn.f16x2 p1, qz19, qz19, c; fma.rn.f16x2 g15, qz15, h1, qz15; prmt.b32 h0, lo0, hi0, 0x5410;\n"
        "B82:\n"
        "wgmma.fence.sync.aligned;\n"
        "add.s64 dt, w2d, 1216; wgmma.mma_async.sync.aligned.m64n96k16.f16.f16.f16 {o0,o1,o2,o3,o4,o5,o6,o7,o8,o9,o10,o11,o12,o13,o14,o15,o16,o17,o18,o19,o20,o21,o22,o23}, {g12,g13,g14,g15}, dt, pt, 1, 1, 1;\n"
        "wgmma.commit_group.sync.aligned;\n"
        "@!pm bra.uni SKIP1;\n"
        "wgmma.fence.sync.aligned;\n"
        "add.s64 dt, w1d, 0; wgmma.mma_async.sync.aligned.m64n64k16.f16.f16.f16 {qz0,qz1,qz2,qz3,qz4,qz5,qz6,qz7,qz8,qz9,qz10,qz11,qz12,qz13,qz14,qz15}, {qa0,qa1,qa2,qa3}, dt, pf, 1, 1, 1;\n"
        "add.s64 dt, w1d, 128; wgmma.mma_async.sync.aligned.m64n64k16.f16.f16.f16 {qz0,qz1,qz2,qz3,qz4,qz5,qz6,qz7,qz8,qz9,qz10,qz11,qz12,qz13,qz14,qz15}, {qa4,qa5,qa6,qa7}, dt, pt, 1, 1, 1;\n"
        "add.s64 dt, w1d, 256; wgmma.mma_async.sync.aligned.m64n64k16.f16.f16.f16 {qz0,qz1,qz2,qz3,qz4,qz5,qz6,qz7,qz8,qz9,qz10,qz11,qz12,qz13,qz14,qz15}, {qa8,qa9,qa10,qa11}, dt, pt, 1, 1, 1;\n"
        "SKIP1:\n"
        "@pz bra.uni B86;\n"
        "mov.b32 {xl, xh}, a0; tanh.approx.f16 xr, xl; cvt.u32.u16 lo0, xr; tanh.approx.f16 xr, xh; cvt.u32.u16 hi0, xr; mul.rn.f16x2 a1, qz19, p1; fma.rn.f16x2 p0, qz20, qz20, c; fma.rn.f16x2 g0, qz16, h0, qz16; prmt.b32 h1, lo1, hi1, 0x5410;\n"
        "mov.b32 {xl, xh}, a1; tanh.approx.f16 xr, xl; cvt.u32.u16 lo1, xr; tanh.approx.f16 xr, xh; cvt.u32.u16 hi1, xr; mul.rn.f16x2 a0, qz20, p0; fma.rn.f16x2 p1, qz21, qz21, c; fma.rn.f16x2 g1, qz17, h1, qz17; prmt.b32 h0, lo0, hi0, 0x5410;\n"
        "mov.b32 {xl, xh}, a0; tanh.approx.f16 xr, xl; cvt.u32.u16 lo0, xr; tanh.approx.f16 xr, xh; cvt.u32.u16 hi0, xr; mul.rn.f16x2 a1, qz21, p1; fma.rn.f16x2 p0, qz22, qz22, c; fma.rn.f16x2 g2, qz18, h0, qz18; prmt.b32 h1, lo1, hi1, 0x5410;\n"
        "mov.b32 {xl, xh}, a1; tanh.approx.f16 xr, xl; cvt.u32.u16 lo1, xr; tanh.approx.f16 xr, xh; cvt.u32.u16 hi1, xr; mul.rn.f16x2 a0, qz22, p0; fma.rn.f16x2 p1, qz23, qz23, c; fma.rn.f16x2 g3, qz19, h1, qz19; prmt.b32 h0, lo0, hi0, 0x5410;\n"
        "B86:\n"
        "wgmma.wait_group.sync.aligned 2;\n"
        "wgmma.fence.sync.aligned;\n"
        "add.s64 dt, w2d, 1280; wgmma.mma_async.sync.aligned.m64n96k16.f16.f16.f16 {o0,o1,o2,o3,o4,o5,o6,o7,o8,o9,o10,o11,o12,o13,o14,o15,o16,o17,o18,o19,o20,o21,o22,o23}, {g0,g1,g2,g3}, dt, pt, 1, 1, 1;\n"
        "wgmma.commit_group.sync.aligned;\n"
        "@!pm bra.uni SKIP2;\n"
        "wgmma.fence.sync.aligned;\n"
        "add.s64 dt, w1d, 384; wgmma.mma_async.sync.aligned.m64n64k16.f16.f16.f16 {qz0,qz1,qz2,qz3,qz4,qz5,qz6,qz7,qz8,qz9,qz10,qz11,qz12,qz13,qz14,qz15}, {qa12,qa13,qa14,qa15}, dt, pt, 1, 1, 1;\n"
        "add.s64 dt, w1d, 512; wgmma.mma_async.sync.aligned.m64n64k16.f16.f16.f16 {qz0,qz1,qz2,qz3,qz4,qz5,qz6,qz7,qz8,qz9,qz10,qz11,qz12,qz13,qz14,qz15}, {qa16,qa17,qa18,qa19}, dt, pt, 1, 1, 1;\n"
        "add.s64 dt, w1d, 640; wgmma.mma_async.sync.aligned.m64n64k16.f16.f16.f16 {qz0,qz1,qz2,qz3,qz4,qz5,qz6,qz7,qz8,qz9,qz10,qz11,qz12,qz13,qz14,qz15}, {qa20,qa21,qa22,qa23}, dt, pt, 1, 1, 1;\n"
        "SKIP2:\n"
        "wgmma.fence.sync.aligned;\n"
        "wgmma.commit_group.sync.aligned;\n"
        "@pz bra.uni B90;\n"
        "mov.b32 {xl, xh}, a0; tanh.approx.f16 xr, xl; cvt.u32.u16 lo0, xr; tanh.approx.f16 xr, xh; cvt.u32.u16 hi0, xr; mul.rn.f16x2 a1, qz23, p1; fma.rn.f16x2 p0, qz24, qz24, c; fma.rn.f16x2 g4, qz20, h0, qz20; prmt.b32 h1, lo1, hi1, 0x5410;\n"
        "mov.b32 {xl, xh}, a1; tanh.approx.f16 xr, xl; cvt.u32.u16 lo1, xr; tanh.approx.f16 xr, xh; cvt.u32.u16 hi1, xr; mul.rn.f16x2 a0, qz24, p0; fma.rn.f16x2 p1, qz25, qz25, c; fma.rn.f16x2 g5, qz21, h1, qz21; prmt.b32 h0, lo0, hi0, 0x5410;\n"
        "mov.b32 {xl, xh}, a0; tanh.approx.f16 xr, xl; cvt.u32.u16 lo0, xr; tanh.approx.f16 xr, xh; cvt.u32.u16 hi0, xr; mul.rn.f16x2 a1, qz25, p1; fma.rn.f16x2 p0, qz26, qz26, c; fma.rn.f16x2 g6, qz22, h0, qz22; prmt.b32 h1, lo1, hi1, 0x5410;\n"
        "mov.b32 {xl, xh}, a1; tanh.approx.f16 xr, xl; cvt.u32.u16 lo1, xr; tanh.approx.f16 xr, xh; cvt.u32.u16 hi1, xr; mul.rn.f16x2 a0, qz26, p0; fma.rn.f16x2 p1, qz27, qz27, c; fma.rn.f16x2 g7, qz23, h1, qz23; prmt.b32 h0, lo0, hi0, 0x5410;\n"
        "B90:\n"
        "wgmma.wait_group.sync.aligned 3;\n"
        "wgmma.fence.sync.aligned;\n"
        "add.s64 dt, w2d, 1344; wgmma.mma_async.sync.aligned.m64n96k16.f16.f16.f16 {o0,o1,o2,o3,o4,o5,o6,o7,o8,o9,o10,o11,o12,o13,o14,o15,o16,o17,o18,o19,o20,o21,o22,o23}, {g4,g5,g6,g7}, dt, pt, 1, 1, 1;\n"
        "wgmma.commit_group.sync.aligned;\n"
        "@pz bra.uni B94;\n"
        "mov.b32 {xl, xh}, a0; tanh.approx.f16 xr, xl; cvt.u32.u16 lo0, xr; tanh.approx.f16 xr, xh; cvt.u32.u16 hi0, xr; mul.rn.f16x2 a1, qz27, p1; fma.rn.f16x2 p0, qz28, qz28, c; fma.rn.f16x2 g8, qz24, h0, qz24; prmt.b32 h1, lo1, hi1, 0x5410;\n"
        "mov.b32 {xl, xh}, a1; tanh.approx.f16 xr, xl; cvt.u32.u16 lo1, xr; tanh.approx.f16 xr, xh; cvt.u32.u16 hi1, xr; mul.rn.f16x2 a0, qz28, p0; fma.rn.f16x2 p1, qz29, qz29, c; fma.rn.f16x2 g9, qz25, h1, qz25; prmt.b32 h0, lo0, hi0, 0x5410;\n"
        "mov.b32 {xl, xh}, a0; tanh.approx.f16 xr, xl; cvt.u32.u16 lo0, xr; tanh.approx.f16 xr, xh; cvt.u32.u16 hi0, xr; mul.rn.f16x2 a1, qz29, p1; fma.rn.f16x2 p0, qz30, qz30, c; fma.rn.f16x2 g10, qz26, h0, qz26; prmt.b32 h1, lo1, hi1, 0x5410;\n"
        "mov.b32 {xl, xh}, a1; tanh.approx.f16 xr, xl; cvt.u32.u16 lo1, xr; tanh.approx.f16 xr, xh; cvt.u32.u16 hi1, xr; mul.rn.f16x2 a0, qz30, p0; fma.rn.f16x2 p1, qz31, qz31, c; fma.rn.f16x2 g11, qz27, h1, qz27; prmt.b32 h0, lo0, hi0, 0x5410;\n"
        "B94:\n"
        "wgmma.wait_group.sync.aligned 1;\n"
        "wgmma.fence.sync.aligned;\n"
        "add.s64 dt, w2d, 1408; wgmma.mma_async.sync.aligned.m64n96k16.f16.f16.f16 {o0,o1,o2,o3,o4,o5,o6,o7,o8,o9,o10,o11,o12,o13,o14,o15,o16,o17,o18,o19,o20,o21,o22,o23}, {g8,g9,g10,g11}, dt, pt, 1, 1, 1;\n"
        "wgmma.commit_group.sync.aligned;\n"
        "@pz bra.uni B2;\n"
        "mov.b32 {xl, xh}, a0; tanh.approx.f16 xr, xl; cvt.u32.u16 lo0, xr; tanh.approx.f16 xr, xh; cvt.u32.u16 hi0, xr; mul.rn.f16x2 a1, qz31, p1; fma.rn.f16x2 p0, qz0, qz0, c; fma.rn.f16x2 g12, qz28, h0, qz28; prmt.b32 h1, lo1, hi1, 0x5410;\n"
        "mov.b32 {xl, xh}, a1; tanh.approx.f16 xr, xl; cvt.u32.u16 lo1, xr; tanh.approx.f16 xr, xh; cvt.u32.u16 hi1, xr; mul.rn.f16x2 a0, qz0, p0; fma.rn.f16x2 p1, qz1, qz1, c; fma.rn.f16x2 g13, qz29, h1, qz29; prmt.b32 h0, lo0, hi0, 0x5410;\n"
        "mov.b32 {xl, xh}, a0; tanh.approx.f16 xr, xl; cvt.u32.u16 lo0, xr; tanh.approx.f16 xr, xh; cvt.u32.u16 hi0, xr; mul.rn.f16x2 a1, qz1, p1; fma.rn.f16x2 p0, qz2, qz2, c; fma.rn.f16x2 g14, qz30, h0, qz30; prmt.b32 h1, lo1, hi1, 0x5410;\n"
        "mov.b32 {xl, xh}, a1; tanh.approx.f16 xr, xl; cvt.u32.u16 lo1, xr; tanh.approx.f16 xr, xh; cvt.u32.u16 hi1, xr; mul.rn.f16x2 a0, qz2, p0; fma.rn.f16x2 p1, qz3, qz3, c; fma.rn.f16x2 g15, qz31, h1, qz31; prmt.b32 h0, lo0, hi0, 0x5410;\n"
        "B2:\n"
        "wgmma.fence.sync.aligned;\n"
        "add.s64 dt, w2d, 1472; wgmma.mma_async.sync.aligned.m64n96k16.f16.f16.f16 {o0,o1,o2,o3,o4,o5,o6,o7,o8,o9,o10,o11,o12,o13,o14,o15,o16,o17,o18,o19,o20,o21,o22,o23}, {g12,g13,g14,g15}, dt, pt, 1, 1, 1;\n"
        "wgmma.commit_group.sync.aligned;\n"
        "@pz bra.uni BE;\n"
        "mov.b32 {xl, xh}, a0; tanh.approx.f16 xr, xl; cvt.u32.u16 lo0, xr; tanh.approx.f16 xr, xh; cvt.u32.u16 hi0, xr; mul.rn.f16x2 a1, qz3, p1; fma.rn.f16x2 p0, qz4, qz4, c; fma.rn.f16x2 g0, qz0, h0, qz0; prmt.b32 h1, lo1, hi1, 0x5410;\n"
        "mov.b32 {xl, xh}, a1; tanh.approx.f16 xr, xl; cvt.u32.u16 lo1, xr; tanh.approx.f16 xr, xh; cvt.u32.u16 hi1, xr; mul.rn.f16x2 a0, qz4, p0; fma.rn.f16x2 p1, qz5, qz5, c; fma.rn.f16x2 g1, qz1, h1, qz1; prmt.b32 h0, lo0, hi0, 0x5410;\n"
        "mov.b32 {xl, xh}, a0; tanh.approx.f16 xr, xl; cvt.u32.u16 lo0, xr; tanh.approx.f16 xr, xh; cvt.u32.u16 hi0, xr; mul.rn.f16x2 a1, qz5, p1; fma.rn.f16x2 p0, qz6, qz6, c; fma.rn.f16x2 g2, qz2, h0, qz2; prmt.b32 h1, lo1, hi1, 0x5410;\n"
        "mov.b32 {xl, xh}, a1; tanh.approx.f16 xr, xl; cvt.u32.u16 lo1, xr; tanh.approx.f16 xr, xh; cvt.u32.u16 hi1, xr; mul.rn.f16x2 a0, qz6, p0; fma.rn.f16x2 p1, qz7, qz7, c; fma.rn.f16x2 g3, qz3, h1, qz3; prmt.b32 h0, lo0, hi0, 0x5410;\n"
        "BE:\n"
        "wgmma.wait_group.sync.aligned 0;\n"
        "bra.uni LOOP;\n"
        "STORE:\n"
        "bar.sync tt, 128;\n"
        "setp.lt.s32 pr, n, 0;\n"
        "@pr bra.uni STOREB;\n"
        "cvt.u64.u32 gp, off; add.s64 gp, gp, %11;\n"
        "elect.sync _|pr, 0xffffffff;\n"
        "@pr cp.async.bulk.global.shared::cta.bulk_group [gp], [%4], 12288;\n"
        "@pr cp.async.bulk.commit_group;\n"
        "bra.uni STOREB;\n"
        "YLOAD:\n"
        "@!pm bra.uni YLOADP;\n"
        "cp.async.bulk.wait_group.read 0;\n"
        "sub.u32 ad, off, %8; cvt.u64.u32 gp, ad; add.s64 gp, gp, %11;\n"
        "elect.sync _|pr, 0xffffffff;\n"
        "@pr mbarrier.arrive.expect_tx.shared::cta.b64 _, [ybar], 12288;\n"
        "@pr cp.async.bulk.shared::cluster.global.mbarrier::complete_tx::bytes [%4], [gp], 12288, [ybar];\n"
        "YLOADP:\n"
        "cvt.u64.u32 gp, off; add.s64 gp, gp, %10;\n"
        "elect.sync _|pr, 0xffffffff;\n"
        "@pr cp.async.bulk.prefetch.L2.global.L2::cache_hint [gp], 12288, pol;\n"
        "bra.uni YLOADB;\n"
        "XLOAD:\n"
        "bar.sync tt, 128;\n"
        "cp.async.bulk.wait_group.read 0;\n"
        "cvt.u64.u32 gp, off; add.s64 gp, gp, %10;\n"
        "elect.sync _|pr, 0xffffffff;\n"
        "@pr mbarrier.arrive.expect_tx.shared::cta.b64 _, [xbar], 12288;\n"
        "@pr cp.async.bulk.shared::cluster.global.mbarrier::complete_tx::bytes.L2::cache_hint [%4], [gp], 12288, [xbar], pol;\n"
        "bra.uni XLOADB;\n"
        "SPINY: mov.u32 cnt, 0;\n"
        "SPINYL:\n"
        "add.u32 tt, n, 1; and.b32 tt, tt, 1; mbarrier.try_wait.parity.shared::cta.b64 pw, [ybar], tt;\n"
        "@pw bra.uni BACKY;\n"
        "add.u32 cnt, cnt, 1; setp.lt.u32 pw, cnt, 0x100000;\n"
        "@pw bra.uni SPINYL;\n"
        "trap;\n"
        "SPINX: mov.u32 cnt, 0;\n"
        "SPINXL:\n"
        "and.b32 tt, n, 1; mbarrier.try_wait.parity.shared::cta.b64 pw, [xbar], tt;\n"
        "@pw bra.uni BACKX;\n"
        "add.u32 cnt, cnt, 1; setp.lt.u32 pw, cnt, 0x100000;\n"
        "@pw bra.uni SPINXL;\n"
        "trap;\n"
        "SPINT: mov.u32 cnt, 0;\n"
        "SPINTL:\n"
        "mad.lo.u32 tt, n, 8, tbar; mbarrier.try_wait.parity.shared::cta.b64 pw, [tt], tpar;\n"
        "@pw bra.uni BACKT;\n"
        "add.u32 cnt, cnt, 1; setp.lt.u32 pw, cnt, 0x100000;\n"
        "@pw bra.uni SPINTL;\n"
        "trap;\n"
        "SPINW0: mov.u32 cnt, 0;\n"
        "SPINW0L:\n"
        "mov.u32 tt, 231208; mbarrier.try_wait.parity.shared::cta.b64 pw, [tt], 0;\n"
        "@pw bra.uni BACKW0;\n"
        "add.u32 cnt, cnt, 1; setp.lt.u32 pw, cnt, 0x100000;\n"
        "@pw bra.uni SPINW0L;\n"
        "trap;\n"
        "SPINW1: mov.u32 cnt, 0;\n"
        "SPINW1L:\n"
        "mov.u32 tt, 231216; mbarrier.try_wait.parity.shared::cta.b64 pw, [tt], 0;\n"
        "@pw bra.uni BACKW1;\n"
        "add.u32 cnt, cnt, 1; setp.lt.u32 pw, cnt, 0x100000;\n"
        "@pw bra.uni SPINW1L;\n"
        "trap;\n"
        "DONE:\n"
        "wgmma.wait_group.sync.aligned 0;\n"
        "}\n"
        :: "r"(prm.w1desc), "r"(prm.w2desc), "r"(c.wg), "r"(c.off), "r"(c.xs), "r"(c.a_offs), "r"(c.xs_offs), "r"(c.bias_addr),
           "r"(c.step), "r"(c.w), "l"(prm.x), "l"(prm.out)
        : "memory");
}

__device__ __forceinline__ float warp_sum(float v) {
#pragma unroll
    for (int s = 16; s >= 1; s >>= 1) v += __shfl_xor_sync(0xffffffffu, v, s);
    return v;
}
__device__ __forceinline__ float pow2f(int e) { return __uint_as_float((uint32_t)(e + 127) << 23); }
__device__ __forceinline__ int exponent_of(float v) { return (int)(__float_as_uint(v) >> 23) - 127; }
__device__ __forceinline__ float lds_bf16(uint32_t addr) {
    uint16_t v; asm volatile("ld.shared.u16 %0, [%1];" : "=h"(v) : "r"(addr) : "memory"); return bf_lo(v);
}

__device__ __forceinline__ void publish_bias(const Params& prm, uint32_t c, uint32_t tag) {
    const uint32_t lane = fresh_tid() & 31;
    const uint32_t col = sb + SM_W2 + (c >> 5) * 24576 + lane * 64 + ((((c >> 3) ^ (lane >> 1)) & 3) * 16) + (c & 7) * 2;
    float v = 0.0f;
#pragma unroll
    for (int k = 0; k < EX / 32; k++) v = fmaf(lds_bf16(col + k * 2048), lds_bf16(sb + SM_BETA + lane * 2 + k * 64), v);
    v = warp_sum(v);
    if (lane == 0) asm volatile("st.relaxed.gpu.global.v2.b32 [%0], {%1, %2};" ::"l"(prm.g->bias + c), "f"(v), "r"(tag) : "memory");
}
__device__ __forceinline__ void collect_bias(const Params& prm, uint32_t tag) {
    const uint32_t lane = fresh_tid() & 31;
    if (lane < 24) {
        const unsigned long long* src = prm.g->bias + 32 * (lane >> 3) + 8 * (lane & 3) + (lane & 4);
        uint32_t v[4], t[4], spins = 0;
        for (;;) {
#pragma unroll
            for (int k = 0; k < 4; k++)
                asm volatile("ld.relaxed.gpu.global.v2.b32 {%0, %1}, [%2];" : "=r"(v[k]), "=r"(t[k]) : "l"(src + k) : "memory");
            if (t[0] == tag && t[1] == tag && t[2] == tag && t[3] == tag) break;
            if (++spins > (1u << 22)) __trap();
        }
        sts128(sb + SM_BIAS + lane * 16, v[0], v[1], v[2], v[3]);
    }
    __syncwarp();
}
__device__ __forceinline__ float fetch_w2_row(uint32_t (&u)[12][4], uint32_t row, uint32_t sw) {
    uint32_t mx[4] = {};
#pragma unroll
    for (int a = 0; a < 3; a++)
#pragma unroll
        for (int k = 0; k < 4; k++) {
            asm volatile("ld.shared.v4.b32 {%0,%1,%2,%3}, [%4];"
                         : "=r"(u[a * 4][k]), "=r"(u[a * 4 + 1][k]), "=r"(u[a * 4 + 2][k]), "=r"(u[a * 4 + 3][k])
                         : "r"(row + a * 24576 + ((k * 16) ^ sw)) : "memory");
#pragma unroll
            for (int b = 0; b < 4; b++) asm("max.xorsign.abs.bf16x2 %0, %0, %1;" : "+r"(mx[b]) : "r"(u[a * 4 + b][k]));
        }
#pragma unroll
    for (int b = 1; b < 4; b++) asm("max.xorsign.abs.bf16x2 %0, %0, %1;" : "+r"(mx[0]) : "r"(mx[b]));
    return fmaxf(fabsf(bf_lo(mx[0])), fabsf(bf_hi(mx[0])));
}

__device__ __forceinline__ bool grn_stats(float ss, float gm, float bt, float top, int e, float& gx, float& inv, int& eo) {
    gx = sqrt_fast(fmaf(ss, INV_2A * INV_2A, 1e-6f));
    const float rt = sqrt_fast(ss + 1.0f) * INV_2A * top;
    uint32_t r[4] = {__float_as_uint(warp_sum(gx)), __reduce_max_sync(0xffffffffu, __float_as_uint(fmaf(bt, top, rt))),
                     __reduce_max_sync(0xffffffffu, __float_as_uint(rt * fabsf(gm) * gx)),
                     (uint32_t)__any_sync(0xffffffffu, !(ss >= 16.0f && ss < ACC_LIMIT))};
    if ((e & 31) == 0) sts128(sb + SM_SEL + (e >> 5) * 16, r[0], r[1], r[2], r[3]);
    MARK(6);
    named_sync(10, 512);
    lds128(r, sb + SM_SEL + min(e & 15, 11) * 16);
    float tot = (e & 15) < 12 ? __uint_as_float(r[0]) : 0.0f;
#pragma unroll
    for (int k = 8; k >= 1; k >>= 1) tot += __shfl_xor_sync(0xffffffffu, tot, k);
    inv = __fdividef(1.0f, fmaf(tot, 1.0f / EX, 1e-6f));
    const float bound = fmaf(__uint_as_float(__reduce_max_sync(0xffffffffu, r[2])), inv,
                             __uint_as_float(__reduce_max_sync(0xffffffffu, r[1]))) * EX;
    eo = min(max(exponent_of(bound), -90), 126) - 14;
    return __any_sync(0xffffffffu, r[3]);
}

__device__ __forceinline__ float exact_sums(const Params& prm) {
    const int lane = fresh_tid() & 31, warp = fresh_warp(), wg = warp >> 2;
    const uint32_t epoch = lds32(sb + SM_RED + (RED_EPOCH + 1) * 4), bar = sb + SM_BAR + BAR_W1 * 8;
    if (wg < 3) {
        uint32_t wa[2][24], d[2][16];
        float acc[2][2] = {};
        const uint32_t yd = prm.ydesc + ((SM_SPARE - SM_Y1) >> 4), wd = prm.w1desc + ((2 * wg * 12288 + 5 * 2048) >> 4);
        load_w1t(wa, wg, warp & 3, lane);
#pragma unroll 1
        for (int n = 0; n < ROWS_PER_CTA; n++) {
            if (warp == 0) {
                expect_tx(bar, TILE_BYTES);
                bulk_load(sb + SM_SPARE, (const char*)prm.out + (cta_tile0(fresh_cta()) + n * cta_stride(fresh_cta())), TILE_BYTES, bar);
            }
            mbar_wait(bar, (n + 1) & 1);
            gemm1_t<0>(d[0], wa[0], yd, wd);
            gemm1_t<1>(d[1], wa[1], yd, wd);
            wg_wait<0>();
            pin(d[0]); pin(d[1]);
            gelu_sumsq_f(d[0], acc[0]);
            gelu_sumsq_f(d[1], acc[1]);
            named_sync(1, 384);
        }
        publish_sums(acc, prm.g->sums[epoch & 1], &prm.g->count[1], wg, warp & 3, lane);
    }
    grid_wait(&prm.g->count[1], (epoch + 1) * NUM_CTAS);
    return __ldcg(prm.g->sums[epoch & 1] + fresh_tid() % EX);
}

template <bool FIRST> __device__ __forceinline__ void prepare_pass2(const Pass2& c, const Params& prm, float ss) {
    const int tid = fresh_tid(), lane = tid & 31, warp = fresh_warp(), wg = warp >> 2;
    const int e = tid >= EX ? tid - EX : tid;
    const uint32_t w2row = sb + SM_W2 + e * 64, sw = ((e >> 1) & 3) * 16;
    pass2_start(c, prm);
    MARK(2);
    if (wg) {
        uint32_t u[12][4];
        mbar_wait_c<0>(sb + SM_BAR + BAR_W2 * 8);
        const float top = fetch_w2_row(u, w2row, sw);
        MARK(3);
        const float gm = lds_bf16(sb + SM_GAMMA + e * 2), bt = fabsf(lds_bf16(sb + SM_BETA + e * 2));
        if (FIRST) {
            const uint32_t epoch = lds32(sb + SM_RED + RED_EPOCH * 4);
            if (wg == 3) named_sync(11, EX);
            if (warp == 12) collect_bias(prm, epoch + 1);
            MARK(4);
            ss = collect_fast(acc_word(prm, epoch, e));
            if (tid == 416 && fresh_cta() == 0) prm.g->count[0] = epoch + 1;
        }
        if (warp == 4) TS(4);
        MARK(5);
        float gx, inv;
        int eo;
        const bool redo = (grn_stats(ss, gm, bt, top, e, gx, inv, eo) || FORCE_EXACT) && FIRST;
        MARK(8);
        const float up = pow2f(eo), dn = pow2f(-eo);
        if (warp == 4) {
            if (lane == 24) sts64(sb + SM_RED + RED_SCALE * 4, pack_bf2(up, up), redo);
            if (lane < 24 && !redo) {
                uint32_t b[4];
                lds128(b, sb + SM_BIAS + lane * 16);
                const uint32_t p0 = pack_h2(__uint_as_float(b[0]) * dn, __uint_as_float(b[1]) * dn);
                const uint32_t p1 = pack_h2(__uint_as_float(b[2]) * dn, __uint_as_float(b[3]) * dn);
                sts128(sb + SM_BIAS + lane * 16, p0, p0, p1, p1);
            }
            __syncwarp();
            mbar_arrive_if(sb + SM_BAR + BAR_STAT * 8, lane == 0);
        }
        if (!redo) {
            float sc = fmaf(gm, gx * inv, 1.0f) * INV_2A;
            if (eo > 6) {
                const uint32_t dn2 = pack_bf2(dn, dn);
#pragma unroll
                for (int k = 0; k < 48; k++) u[k >> 2][k & 3] = bf2_mul(u[k >> 2][k & 3], dn2);
            } else {
                sc *= dn;
            }
            const uint32_t s2 = pack_bf2(sc * 0x1p-112f, sc * 0x1p-112f);
#pragma unroll
            for (int k = 0; k < 12; k++) {
                uint32_t v[4];
#pragma unroll
                for (int b = 0; b < 4; b++) {
                    v[b] = bf2_mul(u[k][b], s2);
                    v[b] += (v[b] & 0x7fff7fffu) * 7u;
                }
                sts128(w2row + (k >> 2) * 24576 + (((k & 3) * 16) ^ sw), v[0], v[1], v[2], v[3]);
            }
            MARK(9);
            fence_async_smem();
            __syncwarp();
            mbar_arrive_if(sb + SM_BAR + (BAR_ROWS + (wg != 3)) * 8, lane == 0);
        }
        if (warp == 4) TS(5);
    } else {
        asm volatile("bar.arrive 10, 512;" ::: "memory");
    }
}

__device__ __forceinline__ Pass2 pass2_setup() {
    const int lane = fresh_tid() & 31, wg = fresh_warp() >> 2, w = fresh_warp() & 3, arow = 16 * w + (lane & 15);
    Pass2 c;
    c.wg = wg;
    c.w = w;
    c.off = cta_tile0(fresh_cta()) + (ROWS_PER_CTA - 1 - wg) * cta_stride(fresh_cta());
    c.step = 4 * cta_stride(fresh_cta());
    c.xs = wg == 3 ? sb + SM_BUF3 : sb + SM_Y1 + (wg == 2 ? 2 : 1 - wg) * SLOT_BYTES;
    static_assert((ROWS_PER_CTA - 1) % NX == 1, "slot of the last tile");
    c.a_offs = (arow * 128 + (((lane >> 4) ^ (arow & 7)) * 16)) |
               (8192 + arow * 64 + (((lane >> 4) ^ ((arow >> 1) & 3)) * 16)) << 16;
    const int g = lane >> 2, px = 33 * (g & 1) + 4 * (g >> 1) + 16 * (w >> 1) + 2 * (w & 1);
    c.xs_offs = (px * 192 + (lane & 3) * 16) | ((px ^ 1) * 192 + (lane & 3) * 16) << 16;
    c.bias_addr = sb + SM_BIAS + (lane & 3) * 16;
    return c;
}

__global__ void __launch_bounds__(512, 1) convnext_kernel(const __grid_constant__ Params prm) {
    extern __shared__ __align__(1024) uint8_t smem[];
    if ((uint32_t)__cvta_generic_to_shared(smem) != sb) __trap();
    if (fresh_warp() >= 12) {
        Producer pc;
        SMARK(0);
        asm volatile("setmaxnreg.inc.sync.aligned.u32 %0;" ::"n"(PRODUCER_REGS));
        SMARK(1);
        const int w = fresh_warp() & 3, lane = fresh_tid() & 31;
        const int j = lane & 7, hb = (lane >> 3) & 1, base = 4 * (2 * w + (lane >> 4));
        pc.lane = lane; pc.warp = w;
        pc.xoff[0] = hb * XHALF_B + base * 192 + j * 16;
        pc.xoff[1] = hb * XHALF_B + base * 192 + 128 + j * 8;
        const int grp = 4 * w + (lane >> 3);
#pragma unroll
        for (int o = 0; o < 2; o++) {
            const int row = (grp & 7) + 8 * (o ^ hb) + 32 * (grp >> 3);
            pc.yoff[0][o] = row * 128 + ((j ^ (row & 7)) * 16);
            pc.yoff[1][o] = 8192 + row * 64 + (((j >> 1) ^ ((row >> 1) & 3)) * 16) + (j & 1) * 8;
        }
        pc.stat = sb + SM_STAT + (8 * w + (lane >> 2)) * 32;
        pc.own = pc.stat + (lane & 3) * 8;
        const int dstep = fresh_cta() & 8 ? 3 * CH * 2 : -3 * CH * 2;
        named_sync(0, 512);
        mbar_wait_c<0>(sb + SM_BAR + BAR_DUMMY * 8);
        SMARK(8);
#pragma unroll
        for (int tap = 0; tap < 9; tap++) {
            const uint32_t dw = sb + SM_Y1 + (3 + tap % 3) * CH * 2 + (tap / 3 - 1) * dstep;
            lds128(pc.w[tap], dw + j * 16);
            asm volatile("ld.shared.v2.b32 {%0,%1}, [%2];" : "=r"(pc.w[tap][4]), "=r"(pc.w[tap][5]) : "r"(dw + 128 + j * 8) : "memory");
        }
#pragma unroll
        for (int tap = 0; tap < 9; tap++)
#pragma unroll
            for (int u = 0; u < 6; u++) pc.w[tap][u] = bf2_mul(pc.w[tap][u], TAP_SCALE_BF2);
        produce(pc, prm);
        TS(9);
        asm volatile("setmaxnreg.dec.sync.aligned.u32 %0;" ::"n"(EVEN_REGS));
        if (fresh_warp() == 12) {
            mbar_wait_c<0>(sb + SM_BAR + BAR_W2 * 8);
            if (fresh_cta() < CH) publish_bias(prm, fresh_cta(), lds32(sb + SM_RED + RED_EPOCH * 4) + 1);
        }
    } else {
        asm volatile("setmaxnreg.dec.sync.aligned.u32 %0;" ::"n"(CONSUMER_REGS));
        {
            const int tid = fresh_tid(), warp = fresh_warp(), lane = tid & 31;
            uint32_t cnt[2];
            if (warp == 0) {
                if (lane == 0) {
#pragma unroll
                    for (int k = 0; k < NX; k++) {
                        mbar_init(sb + SM_XFULL + k * SLOT_BYTES, 2);
                        mbar_init(sb + SM_Y1FULL + k * SLOT_BYTES, 4);
                        mbar_init(sb + SM_Y1EMPTY + k * SLOT_BYTES, 12);
                    }
                    mbar_init(sb + SM_BAR + BAR_DUMMY * 8, 1);
                    mbar_init(sb + SM_BAR + BAR_W1 * 8, 1);
                    fence_async_smem();
                }
                __syncwarp();
                asm volatile("bar.arrive 0, 512;" ::: "memory");
                expect_tx(sb + SM_BAR + BAR_DUMMY * 8, 9 * CH * 2);
                bulk_load(sb + SM_Y1, prm.dw, 9 * CH * 2, sb + SM_BAR + BAR_DUMMY * 8);
                bulk_prefetch((const char*)prm.w1 + fresh_cta() * (CH * EX * 2 / NUM_CTAS), CH * EX * 2 / NUM_CTAS);
                const RowCopy rc = row_copy(prm);
#pragma unroll
                for (int k = 0; k <= NX; k++) {
                    if (k == W1POS) {
                        expect_tx(sb + SM_BAR + BAR_W1 * 8, CH * EX * 2);
#pragma unroll
                        for (int q = 0; q < 6; q++) {
                            const uint32_t r = ROT ? (q + fresh_cta()) % 6 : q;
                            tma_load_2d(sb + SM_W1 + r * 12288, &prm.w1_map, 64 * r, 0, sb + SM_BAR + BAR_W1 * 8);
                        }
                    }
                    if (k < NX) issue_row_load(rc, k, k);
                    if (k == PRE) bulk_prefetch(rc.x0 + 192 + NX * rc.stride, TILE_BYTES);
                }
                SMARK(4);
            } else if (warp == 1) {
                if (lane < 2) asm volatile("prefetch.tensormap [%0];" ::"l"(&prm.w1_map + lane) : "memory");
            } else if (warp == 3) {
                const uint32_t one = (lane & 5) == ((lane & 8) >> 1) + (lane >> 4) ? 0x3f803f80u : 0u;
                sts128(sb + SM_SEL + lane * 16, one, one, one, one);
                fence_async_smem();
            } else if (tid - 128u < NX * 12 && ((fresh_cta() + 1) & 7) < 2) {
                const int k = tid - 128;
                sts128(sb + SM_X + (k / 12) * SLOT_BYTES + ((fresh_cta() & 7) == 0 ? 0 : XHALF_B + 33 * 192) + (k % 12) * 16, 0, 0, 0, 0);
            }
            __syncwarp();
            asm volatile("ld.relaxed.gpu.global.v2.u32 {%0, %1}, [%2];" : "=r"(cnt[0]), "=r"(cnt[1]) : "l"(prm.g->count) : "memory");
            SMARK(0);
            if (warp != 0) named_sync(0, 512);
            if (tid == 256) {
                sts64(sb + SM_RED + RED_EPOCH * 4, cnt[0], cnt[1] / NUM_CTAS);
#pragma unroll
                for (int k = 0; k < BAR_COUNT; k++)
                    if (k != BAR_W1 && k != BAR_DUMMY) mbar_init(sb + SM_BAR + k * 8, k < BAR_TURN || k == BAR_STAT ? 1 : k == BAR_ROWS + 1 ? 8 : 4);
#pragma unroll
                for (int k = 0; k < 3; k++) mbar_arrive_if(sb + SM_BAR + (BAR_Y2FULL + k) * 8, true);
            }
            if (fresh_cta() == 0) *acc_word(prm, cnt[0] + 1, tid) = 0;
            if (fresh_cta() == 1) prm.g->sums[~(cnt[1] / NUM_CTAS) & 1][tid] = 0.0f;
            __syncwarp();
            SMARK(1);
            mbar_wait_c<0>(sb + SM_BAR + BAR_W1 * 8);
            SMARK(2);
        }

        const int tid = fresh_tid(), lane = tid & 31, wg = fresh_warp() >> 2, w = fresh_warp() & 3;
        float acc[2][2];
        const int c = 8 * (lane >> 4) + (lane & 7), ck = 2 * w + ((lane >> 3) & 1);
        consume(acc, sb + SM_W1 + 2 * wg * 12288 + c * 128 + ((ck ^ (c & 7)) * 16), prm.ydesc,
                prm.w1desc + (((2 * wg + 1) * 12288 + 5 * 2048) >> 4), wg * SLOT_BYTES, make_duty(prm, wg, w), w, lane, prm);
        publish_fast(prm, acc, lds32(sb + SM_RED + RED_EPOCH * 4), wg, w, lane);
        if (wg) asm volatile("bar.arrive 11, 384;" ::: "memory");
        MARK(0);
        bulk_wait_all();
        if (wg == 0) TS(3);
        asm volatile("setmaxnreg.inc.sync.aligned.u32 %0;" ::"n"(EVEN_REGS));
    }

    {
        asm volatile(PASS2_STATE);
        MARK(1);
        Pass2 c = pass2_setup();
        prepare_pass2<true>(c, prm, 0.0f);
        if (pass2_head(c, 0)) {
            const float ss = exact_sums(prm);
            c = pass2_setup();
            prepare_pass2<false>(c, prm, ss);
            pass2_head(c, 1);
        }

        pass2_tiles(c, prm);
        bulk_wait_read<0>();
        MARK(13);
    }
}

}

extern "C" void kernel_launch(void* const* d_in, const int* in_sizes, int n_in, void* d_out, int out_size) {
    (void)in_sizes; (void)n_in; (void)out_size;
    typedef CUresult (*EncodeFn)(CUtensorMap*, CUtensorMapDataType, cuuint32_t, void*, const cuuint64_t*, const cuuint64_t*,
                                 const cuuint32_t*, const cuuint32_t*, CUtensorMapInterleave, CUtensorMapSwizzle,
                                 CUtensorMapL2promotion, CUtensorMapFloatOOBfill);
    void* fn = nullptr;
    cudaDriverEntryPointQueryResult status;
    cudaGetDriverEntryPoint("cuTensorMapEncodeTiled", &fn, cudaEnableDefault, &status);
    const EncodeFn encode = (EncodeFn)fn;
    const cuuint32_t ones[2] = {1, 1};

    Params p;
    {
        const cuuint64_t dims[2] = {EX, CH}, strides[1] = {EX * 2};
        const cuuint32_t box[2] = {64, CH};
        encode(&p.w1_map, CU_TENSOR_MAP_DATA_TYPE_BFLOAT16, 2, d_in[2], dims, strides, box, ones,
               CU_TENSOR_MAP_INTERLEAVE_NONE, CU_TENSOR_MAP_SWIZZLE_128B, CU_TENSOR_MAP_L2_PROMOTION_NONE,
               CU_TENSOR_MAP_FLOAT_OOB_FILL_NONE);
    }
    {
        const cuuint64_t dims[2] = {CH, EX}, strides[1] = {CH * 2};
        const cuuint32_t box[2] = {32, 192};
        encode(&p.w2_map, CU_TENSOR_MAP_DATA_TYPE_BFLOAT16, 2, d_in[3], dims, strides, box, ones,
               CU_TENSOR_MAP_INTERLEAVE_NONE, CU_TENSOR_MAP_SWIZZLE_64B, CU_TENSOR_MAP_L2_PROMOTION_NONE,
               CU_TENSOR_MAP_FLOAT_OOB_FILL_NONE);
    }
    p.x = (const __nv_bfloat16*)d_in[0];
    p.dw = (const __nv_bfloat16*)d_in[1];
    p.w1 = (const __nv_bfloat16*)d_in[2];
    p.gamma = (const __nv_bfloat16*)d_in[4];
    p.beta = (const __nv_bfloat16*)d_in[5];
    p.out = (__nv_bfloat16*)d_out;
    cudaGetSymbolAddress((void**)&p.g, g_scratch);
    p.w1desc = desc_lo(sb + SM_W1, 12288);
    p.w2desc = desc_lo(sb + SM_W2, 24576);
    p.ydesc = desc_lo(sb + SM_Y1, 16);
    p.ydesc64[0] = (0x40000040ull << 32) | p.ydesc;
    p.ydesc64[1] = (0x80000020ull << 32) | (p.ydesc + 512);
    for (int k = 0; k < 3; k++) p.sel[k] = (8ull << 32) | desc_lo(sb + SM_SEL + k * 128, k == 2 ? 128 : 0);
    constexpr int smem_bytes = SM_TOTAL;
    cudaFuncSetAttribute(convnext_kernel, cudaFuncAttributeMaxDynamicSharedMemorySize, smem_bytes);
    convnext_kernel<<<NUM_CTAS, 512, smem_bytes>>>(p);
}
```

```cpp
#include <cuda.h>
#include <cuda_runtime.h>
#include <cuda_bf16.h>
#include <stdint.h>

namespace {

constexpr int IMG_W = 512, CH = 96, EX = 384;
constexpr int TILE_PX = 64;
constexpr int ROWS_PER_CTA = 32;
constexpr int NUM_CTAS = 128;
constexpr int STEPS = ROWS_PER_CTA + 2;
constexpr int ROW_BYTES = IMG_W * CH * 2;

#define FORCE_EXACT 0
#define PREGS 200
#define CREGS 104
constexpr int PRODUCER_REGS = PREGS, CONSUMER_REGS = CREGS, EVEN_REGS = 128;

constexpr int XHALF_BYTES = 34 * 192;
constexpr int XHALF_B = XHALF_BYTES + 64;
constexpr int XROW_BYTES = XHALF_B + XHALF_BYTES + 64;
constexpr int L2_AHEAD = 2;
constexpr int NX = 3;
constexpr int TILE_BYTES = TILE_PX * 192;
constexpr int NY1 = 3;

constexpr uint32_t sb = 1024;
constexpr int SM_W1 = 0;
constexpr int SM_W2 = 73728;
constexpr int SM_RING = 147456;
constexpr int SLOT_BYTES = 26624;
constexpr int SM_Y1 = SM_RING;
constexpr int SM_X = SM_Y1 + TILE_BYTES;
constexpr int SM_STAT = SM_X + XROW_BYTES;
constexpr int SM_XFULL = SM_STAT + TILE_PX * 16, SM_Y1FULL = SM_XFULL + 8, SM_Y1EMPTY = SM_XFULL + 16;
constexpr int SM_BUF3 = SM_X + SLOT_BYTES, SM_SPARE = SM_X;
constexpr int SM_SEL = SM_RING + NX * SLOT_BYTES;
constexpr int SM_BIAS = SM_SEL + 512;
constexpr int SM_GAMMA = SM_BIAS + 384;
constexpr int SM_BETA = SM_GAMMA + EX * 2;
constexpr int SM_RED = SM_BETA + EX * 2;
constexpr int SM_BAR = SM_RED + 16;
constexpr int BAR_Y2FULL = 0, BAR_XSFULL = 4, BAR_W1 = 8, BAR_W2 = 9, BAR_DUMMY = 10, BAR_TURN = 11, BAR_ROWS = 51,
              BAR_STAT = 53, BAR_W1B = 54, BAR_DW = 55, BAR_COUNT = 56;
constexpr int SM_TOTAL = SM_BAR + BAR_COUNT * 8;
static_assert(SM_Y1EMPTY + 8 <= SM_RING + SLOT_BYTES && XROW_BYTES >= TILE_BYTES && SM_X % 1024 == 0, "ring layout");
static_assert(SM_TOTAL <= 232448, "smem budget");
static_assert(SM_STAT % 128 == 0 && SM_BIAS % 16 == 0 && SM_BAR % 8 == 0 && SLOT_BYTES % 1024 == 0, "alignment");

static_assert(NX == NY1, "both rings are walked with one index");
constexpr int RED_EPOCH = 0, RED_SCALE = 2;

constexpr float GELU_A = 0.32920349f;
constexpr uint32_t GELU_C_H2 = 0x40D940D9u;
constexpr float INV_2A = 1.0f / (2.0f * GELU_A);

constexpr uint32_t TAP_SCALE_BF2 = 0x2B802B80u;
constexpr float LN_EPS_SCALED = 1e-5f * 0x1p-80f;
constexpr float RSTD_SCALE = GELU_A * 0x1p-112f;

struct Scratch {
    unsigned long long acc[2][EX / 4 * 32];
    unsigned long long bias[CH];
    float sums[2][EX];
    uint4 zero_row[66 * 192 / 16];
    unsigned int count[2];
};
__device__ __align__(256) Scratch g_scratch;
constexpr float ACC_LIMIT = 0x1p30f;

#define TS(k)
#define ASM_TS
#define MARK(k)
#define SMARK(k)
#define ASM_MARK
#define ASM_SMARK
#define ASM_TRC(it, k)

__device__ __forceinline__ void mbar_init(uint32_t bar, uint32_t count) {
    asm volatile("mbarrier.init.shared::cta.b64 [%0], %1;" ::"r"(bar), "r"(count) : "memory");
}
__device__ __forceinline__ void mbar_arrive_if(uint32_t bar, bool pred) {
    asm volatile("{\n.reg .pred p;\nsetp.ne.u32 p, %1, 0;\n@p mbarrier.arrive.shared::cta.b64 _, [%0];\n}\n"
                 ::"r"(bar), "r"((uint32_t)pred) : "memory");
}
__device__ __forceinline__ void mbar_wait(uint32_t bar, uint32_t parity) {
    asm volatile(
        "{\n.reg .pred p;\n.reg .u32 n;\n"
        "mbarrier.try_wait.parity.shared::cta.b64 p, [%0], %1;\n"
        "@p bra.uni WAIT_DONE;\n"
        "mov.u32 n, 0;\n"
        "WAIT_LOOP:\n"
        "mbarrier.try_wait.parity.shared::cta.b64 p, [%0], %1;\n"
        "@p bra.uni WAIT_DONE;\n"
        "mbarrier.try_wait.parity.shared::cta.b64 p, [%0], %1;\n"
        "@p bra.uni WAIT_DONE;\n"
        "mbarrier.try_wait.parity.shared::cta.b64 p, [%0], %1;\n"
        "@p bra.uni WAIT_DONE;\n"
        "add.u32 n, n, 1;\nsetp.lt.u32 p, n, 0x40000;\n"
        "@p bra.uni WAIT_LOOP;\n"
        "trap;\n"
        "WAIT_DONE:\n}\n"
        ::"r"(bar), "r"(parity) : "memory");
}
template <int PARITY> __device__ __forceinline__ void mbar_wait_c(uint32_t bar) {
    asm volatile(
        "{\n.reg .pred p;\n.reg .u32 n;\n"
        "mbarrier.try_wait.parity.shared::cta.b64 p, [%0], %1;\n"
        "@p bra.uni WAIT_DONE;\n"
        "mov.u32 n, 0;\n"
        "WAIT_LOOP:\n"
        "mbarrier.try_wait.parity.shared::cta.b64 p, [%0], %1;\n"
        "@p bra.uni WAIT_DONE;\n"
        "mbarrier.try_wait.parity.shared::cta.b64 p, [%0], %1;\n"
        "@p bra.uni WAIT_DONE;\n"
        "mbarrier.try_wait.parity.shared::cta.b64 p, [%0], %1;\n"
        "@p bra.uni WAIT_DONE;\n"
        "add.u32 n, n, 1;\nsetp.lt.u32 p, n, 0x40000;\n"
        "@p bra.uni WAIT_LOOP;\n"
        "trap;\n"
        "WAIT_DONE:\n}\n"
        ::"r"(bar), "n"(PARITY) : "memory");
}
#define ELECTED(body) "{\n.reg .pred p;\nelect.sync _|p, 0xffffffff;\n" body "}\n"
__device__ __forceinline__ void expect_tx(uint32_t bar, uint32_t bytes) {
    asm volatile(ELECTED("@p mbarrier.arrive.expect_tx.shared::cta.b64 _, [%0], %1;\n") ::"r"(bar), "r"(bytes) : "memory");
}
__device__ __forceinline__ void bulk_load(uint32_t dst, const void* src, uint32_t bytes, uint32_t bar) {
    asm volatile(ELECTED("@p cp.async.bulk.shared::cluster.global.mbarrier::complete_tx::bytes [%0], [%1], %2, [%3];\n")
                 ::"r"(dst), "l"(src), "r"(bytes), "r"(bar) : "memory");
}
__device__ __forceinline__ void bulk_prefetch(const void* src, uint32_t bytes) {
    asm volatile(ELECTED("@p cp.async.bulk.prefetch.L2.global [%0], %1;\n") ::"l"(src), "r"(bytes) : "memory");
}
__device__ __forceinline__ void tma_load_2d(uint32_t dst, const CUtensorMap* map, int c0, int c1, uint32_t bar) {
    asm volatile(ELECTED("@p cp.async.bulk.tensor.2d.shared::cluster.global.mbarrier::complete_tx::bytes [%0], [%1, {%2, %3}], [%4];\n")
                 ::"r"(dst), "l"(map), "r"(c0), "r"(c1), "r"(bar) : "memory");
}
template <int N> __device__ __forceinline__ void bulk_wait_read() {
    asm volatile("cp.async.bulk.wait_group.read %0;" ::"n"(N) : "memory");
}
__device__ __forceinline__ void bulk_wait_all() { asm volatile("cp.async.bulk.wait_group 0;" ::: "memory"); }
__device__ __forceinline__ void fence_async_smem() { asm volatile("fence.proxy.async.shared::cta;" ::: "memory"); }
__device__ __forceinline__ void named_sync(int id, int n) { asm volatile("bar.sync %0, %1;" ::"r"(id), "r"(n) : "memory"); }

__device__ __forceinline__ void sts64(uint32_t addr, uint32_t a, uint32_t b) {
    asm volatile("st.shared.v2.b32 [%0], {%1,%2};" ::"r"(addr), "r"(a), "r"(b) : "memory");
}
__device__ __forceinline__ void sts128(uint32_t addr, uint32_t a, uint32_t b, uint32_t c, uint32_t d) {
    asm volatile("st.shared.v4.b32 [%0], {%1,%2,%3,%4};" ::"r"(addr), "r"(a), "r"(b), "r"(c), "r"(d) : "memory");
}
__device__ __forceinline__ void ldsm4_t(uint32_t* r, uint32_t addr) {
    asm volatile("ldmatrix.sync.aligned.m8n8.x4.trans.shared.b16 {%0,%1,%2,%3}, [%4];"
                 : "=r"(r[0]), "=r"(r[1]), "=r"(r[2]), "=r"(r[3]) : "r"(addr) : "memory");
}
__device__ __forceinline__ void lds128(uint32_t* v, uint32_t addr) {
    asm volatile("ld.shared.v4.b32 {%0,%1,%2,%3}, [%4];"
                 : "=r"(v[0]), "=r"(v[1]), "=r"(v[2]), "=r"(v[3]) : "r"(addr) : "memory");
}
__device__ __forceinline__ uint32_t lds32(uint32_t addr) {
    uint32_t v; asm volatile("ld.shared.b32 %0, [%1];" : "=r"(v) : "r"(addr) : "memory"); return v;
}
__device__ __forceinline__ void sts32(uint32_t addr, uint32_t v) {
    asm volatile("st.shared.b32 [%0], %1;" ::"r"(addr), "r"(v) : "memory");
}

__device__ __forceinline__ uint32_t bf2_fma(uint32_t a, uint32_t b, uint32_t c) {
    uint32_t d; asm("fma.rn.bf16x2 %0, %1, %2, %3;" : "=r"(d) : "r"(a), "r"(b), "r"(c)); return d;
}
__device__ __forceinline__ uint32_t bf2_mul(uint32_t a, uint32_t b) {
    uint32_t d; asm("mul.rn.bf16x2 %0, %1, %2;" : "=r"(d) : "r"(a), "r"(b)); return d;
}
__device__ __forceinline__ uint32_t bf2_add(uint32_t a, uint32_t b) {
    uint32_t d; asm("add.rn.bf16x2 %0, %1, %2;" : "=r"(d) : "r"(a), "r"(b)); return d;
}
__device__ __forceinline__ uint32_t h2_fma(uint32_t a, uint32_t b, uint32_t c) {
    uint32_t d; asm("fma.rn.f16x2 %0, %1, %2, %3;" : "=r"(d) : "r"(a), "r"(b), "r"(c)); return d;
}
__device__ __forceinline__ uint32_t h2_mul(uint32_t a, uint32_t b) {
    uint32_t d; asm("mul.rn.f16x2 %0, %1, %2;" : "=r"(d) : "r"(a), "r"(b)); return d;
}
__device__ __forceinline__ uint32_t h2_tanh(uint32_t a) {
    uint32_t d; asm("tanh.approx.f16x2 %0, %1;" : "=r"(d) : "r"(a)); return d;
}
__device__ __forceinline__ float bf_lo(uint32_t v) { return __uint_as_float(v << 16); }
__device__ __forceinline__ float bf_hi(uint32_t v) { return __uint_as_float(v & 0xffff0000u); }
__device__ __forceinline__ uint32_t pack_h2(float lo, float hi) {
    uint32_t d; asm("cvt.rn.f16x2.f32 %0, %1, %2;" : "=r"(d) : "f"(hi), "f"(lo)); return d;
}
__device__ __forceinline__ uint32_t pack_bf2(float lo, float hi) {
    uint32_t d; asm("cvt.rn.bf16x2.f32 %0, %1, %2;" : "=r"(d) : "f"(hi), "f"(lo)); return d;
}
__device__ __forceinline__ void h2_unpack(uint32_t v, float& lo, float& hi) {
    asm("{\n.reg .b16 l, h;\nmov.b32 {l, h}, %2;\ncvt.f32.f16 %0, l;\ncvt.f32.f16 %1, h;\n}\n" : "=f"(lo), "=f"(hi) : "r"(v));
}

__device__ __forceinline__ uint32_t gelu2(uint32_t z) {
    uint32_t p = h2_fma(z, z, GELU_C_H2);
    uint32_t t = h2_tanh(h2_mul(z, p));
    return h2_fma(z, t, z);
}

__device__ __forceinline__ void wg_fence() { asm volatile("wgmma.fence.sync.aligned;" ::: "memory"); }
__device__ __forceinline__ void wg_commit() { asm volatile("wgmma.commit_group.sync.aligned;" ::: "memory"); }
template <int N> __device__ __forceinline__ void wg_wait() {
    asm volatile("wgmma.wait_group.sync.aligned %0;" ::"n"(N) : "memory");
}
template <int N> __device__ __forceinline__ void pin(uint32_t (&r)[N]) {
#pragma unroll
    for (int i = 0; i < N; i++) asm volatile("" : "+r"(r[i])::"memory");
}
constexpr uint32_t desc_lo(uint32_t addr, uint32_t lbo) { return ((addr & 0x3FFFF) >> 4) | ((lbo >> 4) << 16); }
template <uint32_t SBO, uint32_t SWZ> __device__ __forceinline__ uint64_t desc(uint32_t lo, uint32_t bytes) {
    return (((uint64_t)((SBO >> 4) | (SWZ << 30)) << 32) | lo) + (bytes >> 4);
}
__device__ __forceinline__ uint32_t fresh_tid() {
    uint32_t v; asm volatile("mov.u32 %0, %%tid.x;" : "=r"(v));
    return v;
}
template <uint32_t V> __device__ __forceinline__ uint32_t loop_init() {
    uint32_t v; asm volatile("mov.u32 %0, %1;" : "=r"(v) : "n"(V)); return v;
}
__device__ __forceinline__ int fresh_warp() {
    int v; asm volatile("shfl.sync.idx.b32 %0, %1, 0, 0x1f, 0xffffffff;" : "=r"(v) : "r"(fresh_tid() >> 5)); return v;
}
__device__ __forceinline__ uint32_t fresh_cta() {
    uint32_t v; asm volatile("mov.u32 %0, %%ctaid.x;" : "=r"(v)); return v;
}
__device__ __forceinline__ float sqrt_fast(float v) { float r; asm("sqrt.approx.f32 %0, %1;" : "=f"(r) : "f"(v)); return r; }

template <int TB>
__device__ __forceinline__ void wgmma_n64_h_set(uint32_t (&d)[16], const uint32_t* a, uint64_t desc) {
    asm volatile(
        "{\n.reg .pred p;\nsetp.ne.b32 p, 0, 0;\n"
        "wgmma.mma_async.sync.aligned.m64n64k16.f16.f16.f16 "
        "{%0,%1,%2,%3,%4,%5,%6,%7,%8,%9,%10,%11,%12,%13,%14,%15}, {%16,%17,%18,%19}, %20, p, 1, 1, %21;\n}\n"
        : "=r"(d[0]), "=r"(d[1]), "=r"(d[2]), "=r"(d[3]), "=r"(d[4]), "=r"(d[5]), "=r"(d[6]), "=r"(d[7]), "=r"(d[8]), "=r"(d[9]), "=r"(d[10]), "=r"(d[11]), "=r"(d[12]), "=r"(d[13]), "=r"(d[14]), "=r"(d[15])
        : "r"(a[0]), "r"(a[1]), "r"(a[2]), "r"(a[3]), "l"(desc), "n"(TB));
}
template <int TB>
__device__ __forceinline__ void wgmma_n64_h_acc(uint32_t (&d)[16], const uint32_t* a, uint64_t desc) {
    asm volatile(
        "{\n.reg .pred p;\nsetp.ne.b32 p, 1, 0;\n"
        "wgmma.mma_async.sync.aligned.m64n64k16.f16.f16.f16 "
        "{%0,%1,%2,%3,%4,%5,%6,%7,%8,%9,%10,%11,%12,%13,%14,%15}, {%16,%17,%18,%19}, %20, p, 1, 1, %21;\n}\n"
        : "+r"(d[0]), "+r"(d[1]), "+r"(d[2]), "+r"(d[3]), "+r"(d[4]), "+r"(d[5]), "+r"(d[6]), "+r"(d[7]), "+r"(d[8]), "+r"(d[9]), "+r"(d[10]), "+r"(d[11]), "+r"(d[12]), "+r"(d[13]), "+r"(d[14]), "+r"(d[15])
        : "r"(a[0]), "r"(a[1]), "r"(a[2]), "r"(a[3]), "l"(desc), "n"(TB));
}
__device__ __forceinline__ void wgmma_n64_h_acc_ss(uint32_t (&d)[16], uint64_t adesc, uint64_t desc) {
    asm volatile(
        "{\n.reg .pred p;\nsetp.ne.b32 p, 1, 0;\n"
        "wgmma.mma_async.sync.aligned.m64n64k16.f16.f16.f16 "
        "{%0,%1,%2,%3,%4,%5,%6,%7,%8,%9,%10,%11,%12,%13,%14,%15}, %16, %17, p, 1, 1, 1, 0;\n}\n"
        : "+r"(d[0]), "+r"(d[1]), "+r"(d[2]), "+r"(d[3]), "+r"(d[4]), "+r"(d[5]), "+r"(d[6]), "+r"(d[7]), "+r"(d[8]), "+r"(d[9]), "+r"(d[10]), "+r"(d[11]), "+r"(d[12]), "+r"(d[13]), "+r"(d[14]), "+r"(d[15])
        : "l"(adesc), "l"(desc));
}

struct Params {
    CUtensorMap w1_map, w2_map;
    const __nv_bfloat16* x;
    const __nv_bfloat16* dw;
    const __nv_bfloat16* w1;
    const __nv_bfloat16* gamma;
    const __nv_bfloat16* beta;
    __nv_bfloat16* out;
    Scratch* g;
    uint64_t ydesc64[2];
    uint64_t sel[3];
    uint32_t w1desc, w2desc, ydesc;
};

__device__ __forceinline__ int cta_stride(uint32_t cta) { return cta & 8 ? ROW_BYTES : -ROW_BYTES; }
__device__ __forceinline__ uint32_t cta_tile0(uint32_t cta) {
    return ((cta >> 3) * ROWS_PER_CTA + (cta & 8 ? 0 : ROWS_PER_CTA - 1)) * ROW_BYTES + (cta & 7) * TILE_BYTES;
}

struct Producer {
    uint32_t w[9][6];
    uint32_t xoff[2];
    uint32_t yoff[2][2];
    uint32_t stat, own;
    int lane, warp;
};

struct RowCopy {
    const char* x0;
    char* y0;
    const char* zeros;
    uint32_t cut0, cut1;
    int stride, last;
};
__device__ __forceinline__ RowCopy row_copy(const Params& prm) {
    const uint32_t cta = fresh_cta(), strip = cta & 7, t0 = cta_tile0(cta);
    RowCopy r;
    r.stride = cta_stride(cta);
    r.x0 = (const char*)prm.x + (t0 - r.stride) - 192;
    r.y0 = (char*)prm.out + t0;
    r.zeros = (const char*)prm.g->zero_row;
    r.cut0 = strip == 0 ? 192 : 0;
    r.cut1 = strip == 7 ? 192 : 0;
    r.last = cta - 8 >= NUM_CTAS - 16 ? STEPS - 2 : STEPS - 1;
    return r;
}
__device__ __forceinline__ void issue_row_load(const RowCopy& r, int i, uint32_t slot) {
    const char* src = r.x0 + i * r.stride;
    const uint32_t bar = sb + SM_XFULL + slot * SLOT_BYTES, dst = sb + SM_X + slot * SLOT_BYTES;
    expect_tx(bar, XHALF_BYTES - r.cut0);
    bulk_load(dst + r.cut0, src + r.cut0, XHALF_BYTES - r.cut0, bar);
    expect_tx(bar, XHALF_BYTES - r.cut1);
    bulk_load(dst + XHALF_B, src + 32 * 192, XHALF_BYTES - r.cut1, bar);
}

__device__ __forceinline__ float quad_sum(float v) {
    v += __shfl_xor_sync(0xffffffffu, v, 1);
    v += __shfl_xor_sync(0xffffffffu, v, 2);
    return v;
}

__device__ __forceinline__ void load_x(uint32_t (&v)[6][6], const Producer& c, uint32_t row) {
#pragma unroll
    for (int k = 0; k < 6; k++) {
        asm volatile("ld.shared.v4.b32 {%0,%1,%2,%3}, [%4];"
                     : "=r"(v[k][0]), "=r"(v[k][1]), "=r"(v[k][2]), "=r"(v[k][3]) : "r"(row + c.xoff[0] + k * 192));
        asm volatile("ld.shared.v2.b32 {%0,%1}, [%2];" : "=r"(v[k][4]), "=r"(v[k][5]) : "r"(row + c.xoff[1] + k * 192));
    }
}
template <int DY, int STRIDE>
__device__ __forceinline__ void conv_row(uint32_t (&dst)[24], const uint32_t* src, const uint32_t (&v)[6][6], const Producer& c) {
#pragma unroll
    for (int o = 0; o < 4; o++)
#pragma unroll
        for (int u = 0; u < 6; u++)
            dst[o * 6 + u] = bf2_fma(v[o + 2][u], c.w[3 * DY + 2][u], bf2_fma(v[o + 1][u], c.w[3 * DY + 1][u],
                             bf2_fma(v[o][u], c.w[3 * DY][u], STRIDE ? src[o * 6 + u] : src[2 * o + 1])));
}
#define HAND_OVER(name, base, r) asm volatile("mov.b32 " name "%6, %0; mov.b32 " name "%7, %1; mov.b32 " name "%8, %2;\n" \
    "mov.b32 " name "%9, %3; mov.b32 " name "%10, %4; mov.b32 " name "%11, %5;" ::"r"((r)[0]), "r"((r)[1]), "r"((r)[2]), \
    "r"((r)[3]), "r"((r)[4]), "r"((r)[5]), "n"(base), "n"(base + 1), "n"(base + 2), "n"(base + 3), "n"(base + 4), "n"(base + 5))
template <int K> __device__ __forceinline__ void hand_over(const Producer& c, const uint32_t (&B)[24], const uint32_t (&C)[24],
                                                           const uint32_t (&v)[6][6]) {
    HAND_OVER("pw", K * 6, c.w[K]);
    if (K < 6) HAND_OVER("pv", K * 6, v[K % 6]);
    if (K < 4) { HAND_OVER("pb", K * 6, B + K % 4 * 6); HAND_OVER("pc", K * 6, C + K % 4 * 6); }
    if constexpr (K < 8) hand_over<K + 1>(c, B, C, v);
}
static_assert(sb + SM_BAR + BAR_DUMMY * 8 == 230880, "layout");
__device__ __forceinline__ void produce_tiles(const Producer& c, const Params& prm) {
    asm volatile(
        "{\n"
        ".reg .b32 pa<24>, pq<4>, m<6>, y<6>, rr, mm, t, so, sp, sn, ph, ad, tt, cnt;\n"
        ".reg .b16 xl, xh;\n"
        ".reg .f32 d<4>, us, s0, s1, f0, f1, kq;\n"
        ".reg .pred pt, pf, pr, pw, px, pl, po, pe, pn, pp;\n"
        "setp.ne.b32 pt, 1, 0; setp.ne.b32 pf, 0, 0; setp.eq.u32 pl, %8, 0; and.b32 tt, %8, 1; setp.ne.u32 po, tt, 0;\n"
        "and.b32 tt, %8, 4; setp.ne.u32 pr, tt, 0; selp.f32 kq, 0f3F802D41, 0f3F7FA57E, pr;\n"
        "mov.u32 t, 0; mov.u32 so, 0; mov.u32 sp, 55896; mov.u32 ph, 1; mov.pred pn, pf; mov.pred pp, pf;\n"
        "setp.eq.u32 pr, %12, 0;\n"
        "@pr bra.uni RARE;\n"
        "LOOP:\n"
        ASM_TRC("t", 0)
        "fence.proxy.async.shared::cta;\n"
        "@pl mbarrier.arrive.shared::cta.b64 _, [sp+174984];\n"
        "fma.rn.bf16x2 pa0, pv0, pw36, pb0; fma.rn.bf16x2 pa1, pv1, pw37, pb1; fma.rn.bf16x2 pa2, pv2, pw38, pb2; fma.rn.bf16x2 pa3, pv3, pw39, pb3; fma.rn.bf16x2 pa4, pv4, pw40, pb4; fma.rn.bf16x2 pa5, pv5, pw41, pb5;\n"
        "fma.rn.bf16x2 pa6, pv6, pw36, pb6; fma.rn.bf16x2 pa7, pv7, pw37, pb7; fma.rn.bf16x2 pa8, pv8, pw38, pb8; fma.rn.bf16x2 pa9, pv9, pw39, pb9; fma.rn.bf16x2 pa10, pv10, pw40, pb10; fma.rn.bf16x2 pa11, pv11, pw41, pb11;\n"
        "fma.rn.bf16x2 pa12, pv12, pw36, pb12; fma.rn.bf16x2 pa13, pv13, pw37, pb13; fma.rn.bf16x2 pa14, pv14, pw38, pb14; fma.rn.bf16x2 pa15, pv15, pw39, pb15; fma.rn.bf16x2 pa16, pv16, pw40, pb16; fma.rn.bf16x2 pa17, pv17, pw41, pb17;\n"
        "fma.rn.bf16x2 pa18, pv18, pw36, pb18; fma.rn.bf16x2 pa19, pv19, pw37, pb19; fma.rn.bf16x2 pa20, pv20, pw38, pb20; fma.rn.bf16x2 pa21, pv21, pw39, pb21; fma.rn.bf16x2 pa22, pv22, pw40, pb22; fma.rn.bf16x2 pa23, pv23, pw41, pb23;\n"
        "fma.rn.bf16x2 pa0, pv6, pw42, pa0; fma.rn.bf16x2 pa1, pv7, pw43, pa1; fma.rn.bf16x2 pa2, pv8, pw44, pa2; fma.rn.bf16x2 pa3, pv9, pw45, pa3; fma.rn.bf16x2 pa4, pv10, pw46, pa4; fma.rn.bf16x2 pa5, pv11, pw47, pa5;\n"
        "fma.rn.bf16x2 pa6, pv12, pw42, pa6; fma.rn.bf16x2 pa7, pv13, pw43, pa7; fma.rn.bf16x2 pa8, pv14, pw44, pa8; fma.rn.bf16x2 pa9, pv15, pw45, pa9; fma.rn.bf16x2 pa10, pv16, pw46, pa10; fma.rn.bf16x2 pa11, pv17, pw47, pa11;\n"
        "fma.rn.bf16x2 pa12, pv18, pw42, pa12; fma.rn.bf16x2 pa13, pv19, pw43, pa13; fma.rn.bf16x2 pa14, pv20, pw44, pa14; fma.rn.bf16x2 pa15, pv21, pw45, pa15; fma.rn.bf16x2 pa16, pv22, pw46, pa16; fma.rn.bf16x2 pa17, pv23, pw47, pa17;\n"
        "fma.rn.bf16x2 pa18, pv24, pw42, pa18; fma.rn.bf16x2 pa19, pv25, pw43, pa19; fma.rn.bf16x2 pa20, pv26, pw44, pa20; fma.rn.bf16x2 pa21, pv27, pw45, pa21; fma.rn.bf16x2 pa22, pv28, pw46, pa22; fma.rn.bf16x2 pa23, pv29, pw47, pa23;\n"
        "fma.rn.bf16x2 pa0, pv12, pw48, pa0; fma.rn.bf16x2 pa1, pv13, pw49, pa1; fma.rn.bf16x2 pa2, pv14, pw50, pa2; fma.rn.bf16x2 pa3, pv15, pw51, pa3; fma.rn.bf16x2 pa4, pv16, pw52, pa4; fma.rn.bf16x2 pa5, pv17, pw53, pa5;\n"
        "fma.rn.bf16x2 pa6, pv18, pw48, pa6; fma.rn.bf16x2 pa7, pv19, pw49, pa7; fma.rn.bf16x2 pa8, pv20, pw50, pa8; fma.rn.bf16x2 pa9, pv21, pw51, pa9; fma.rn.bf16x2 pa10, pv22, pw52, pa10; fma.rn.bf16x2 pa11, pv23, pw53, pa11;\n"
        "fma.rn.bf16x2 pa12, pv24, pw48, pa12; fma.rn.bf16x2 pa13, pv25, pw49, pa13; fma.rn.bf16x2 pa14, pv26, pw50, pa14; fma.rn.bf16x2 pa15, pv27, pw51, pa15; fma.rn.bf16x2 pa16, pv28, pw52, pa16; fma.rn.bf16x2 pa17, pv29, pw53, pa17;\n"
        "fma.rn.bf16x2 pa18, pv30, pw48, pa18; fma.rn.bf16x2 pa19, pv31, pw49, pa19; fma.rn.bf16x2 pa20, pv32, pw50, pa20; fma.rn.bf16x2 pa21, pv33, pw51, pa21; fma.rn.bf16x2 pa22, pv34, pw52, pa22; fma.rn.bf16x2 pa23, pv35, pw53, pa23;\n"
        "mul.rn.bf16x2 pq0, pa0, pa0; fma.rn.bf16x2 pq0, pa1, pa1, pq0; fma.rn.bf16x2 pq0, pa2, pa2, pq0; fma.rn.bf16x2 pq0, pa3, pa3, pq0; fma.rn.bf16x2 pq0, pa4, pa4, pq0; fma.rn.bf16x2 pq0, pa5, pa5, pq0;\n"
        "mul.rn.bf16x2 pq1, pa6, pa6; fma.rn.bf16x2 pq1, pa7, pa7, pq1; fma.rn.bf16x2 pq1, pa8, pa8, pq1; fma.rn.bf16x2 pq1, pa9, pa9, pq1; fma.rn.bf16x2 pq1, pa10, pa10, pq1; fma.rn.bf16x2 pq1, pa11, pa11, pq1;\n"
        "mul.rn.bf16x2 pq2, pa12, pa12; fma.rn.bf16x2 pq2, pa13, pa13, pq2; fma.rn.bf16x2 pq2, pa14, pa14, pq2; fma.rn.bf16x2 pq2, pa15, pa15, pq2; fma.rn.bf16x2 pq2, pa16, pa16, pq2; fma.rn.bf16x2 pq2, pa17, pa17, pq2;\n"
        "mul.rn.bf16x2 pq3, pa18, pa18; fma.rn.bf16x2 pq3, pa19, pa19, pq3; fma.rn.bf16x2 pq3, pa20, pa20, pq3; fma.rn.bf16x2 pq3, pa21, pa21, pq3; fma.rn.bf16x2 pq3, pa22, pa22, pq3; fma.rn.bf16x2 pq3, pa23, pa23, pq3;\n"
        "B0:\n"
        "wgmma.fence.sync.aligned;\n"
        "wgmma.mma_async.sync.aligned.m64n8k16.f32.bf16.bf16 {d0,d1,d2,d3}, {pa0,pa6,pa1,pa7}, %9, pf, 1, 1, 0;\n"
        "wgmma.mma_async.sync.aligned.m64n8k16.f32.bf16.bf16 {d0,d1,d2,d3}, {pa2,pa8,pa3,pa9}, %9, pt, 1, 1, 0;\n"
        "wgmma.mma_async.sync.aligned.m64n8k16.f32.bf16.bf16 {d0,d1,d2,d3}, {pa4,pa10,pa5,pa11}, %9, pt, 1, 1, 0;\n"
        "wgmma.mma_async.sync.aligned.m64n8k16.f32.bf16.bf16 {d0,d1,d2,d3}, {pa12,pa18,pa13,pa19}, %10, pt, 1, 1, 0;\n"
        "wgmma.mma_async.sync.aligned.m64n8k16.f32.bf16.bf16 {d0,d1,d2,d3}, {pa14,pa20,pa15,pa21}, %10, pt, 1, 1, 0;\n"
        "wgmma.mma_async.sync.aligned.m64n8k16.f32.bf16.bf16 {d0,d1,d2,d3}, {pa16,pa22,pa17,pa23}, %10, pt, 1, 1, 0;\n"
        "wgmma.mma_async.sync.aligned.m64n8k16.f32.bf16.bf16 {d0,d1,d2,d3}, {pq0,pq1,pq2,pq3}, %11, pt, 1, 1, 0;\n"
        "wgmma.commit_group.sync.aligned;\n"
        "add.u32 ad, %7, so; ld.shared.f32 us, [ad+4];\n"
        "fma.rn.bf16x2 pb0, pv0, pw18, pc0; fma.rn.bf16x2 pb1, pv1, pw19, pc1; fma.rn.bf16x2 pb2, pv2, pw20, pc2; fma.rn.bf16x2 pb3, pv3, pw21, pc3; fma.rn.bf16x2 pb4, pv4, pw22, pc4; fma.rn.bf16x2 pb5, pv5, pw23, pc5;\n"
        "fma.rn.bf16x2 pb6, pv6, pw18, pc6; fma.rn.bf16x2 pb7, pv7, pw19, pc7; fma.rn.bf16x2 pb8, pv8, pw20, pc8; fma.rn.bf16x2 pb9, pv9, pw21, pc9; fma.rn.bf16x2 pb10, pv10, pw22, pc10; fma.rn.bf16x2 pb11, pv11, pw23, pc11;\n"
        "fma.rn.bf16x2 pb0, pv6, pw24, pb0; fma.rn.bf16x2 pb1, pv7, pw25, pb1; fma.rn.bf16x2 pb2, pv8, pw26, pb2; fma.rn.bf16x2 pb3, pv9, pw27, pb3; fma.rn.bf16x2 pb4, pv10, pw28, pb4; fma.rn.bf16x2 pb5, pv11, pw29, pb5;\n"
        "fma.rn.bf16x2 pb6, pv12, pw24, pb6; fma.rn.bf16x2 pb7, pv13, pw25, pb7; fma.rn.bf16x2 pb8, pv14, pw26, pb8; fma.rn.bf16x2 pb9, pv15, pw27, pb9; fma.rn.bf16x2 pb10, pv16, pw28, pb10; fma.rn.bf16x2 pb11, pv17, pw29, pb11;\n"
        "fma.rn.bf16x2 pb0, pv12, pw30, pb0; fma.rn.bf16x2 pb1, pv13, pw31, pb1; fma.rn.bf16x2 pb2, pv14, pw32, pb2; fma.rn.bf16x2 pb3, pv15, pw33, pb3; fma.rn.bf16x2 pb4, pv16, pw34, pb4; fma.rn.bf16x2 pb5, pv17, pw35, pb5;\n"
        "fma.rn.bf16x2 pb6, pv18, pw30, pb6; fma.rn.bf16x2 pb7, pv19, pw31, pb7; fma.rn.bf16x2 pb8, pv20, pw32, pb8; fma.rn.bf16x2 pb9, pv21, pw33, pb9; fma.rn.bf16x2 pb10, pv22, pw34, pb10; fma.rn.bf16x2 pb11, pv23, pw35, pb11;\n"
        "B1:\n"
        "fma.rn.bf16x2 pb12, pv12, pw18, pc12; fma.rn.bf16x2 pb13, pv13, pw19, pc13; fma.rn.bf16x2 pb14, pv14, pw20, pc14; fma.rn.bf16x2 pb15, pv15, pw21, pc15; fma.rn.bf16x2 pb16, pv16, pw22, pc16; fma.rn.bf16x2 pb17, pv17, pw23, pc17;\n"
        "fma.rn.bf16x2 pb18, pv18, pw18, pc18; fma.rn.bf16x2 pb19, pv19, pw19, pc19; fma.rn.bf16x2 pb20, pv20, pw20, pc20; fma.rn.bf16x2 pb21, pv21, pw21, pc21; fma.rn.bf16x2 pb22, pv22, pw22, pc22; fma.rn.bf16x2 pb23, pv23, pw23, pc23;\n"
        "fma.rn.bf16x2 pb12, pv18, pw24, pb12; fma.rn.bf16x2 pb13, pv19, pw25, pb13; fma.rn.bf16x2 pb14, pv20, pw26, pb14; fma.rn.bf16x2 pb15, pv21, pw27, pb15; fma.rn.bf16x2 pb16, pv22, pw28, pb16; fma.rn.bf16x2 pb17, pv23, pw29, pb17;\n"
        "fma.rn.bf16x2 pb18, pv24, pw24, pb18; fma.rn.bf16x2 pb19, pv25, pw25, pb19; fma.rn.bf16x2 pb20, pv26, pw26, pb20; fma.rn.bf16x2 pb21, pv27, pw27, pb21; fma.rn.bf16x2 pb22, pv28, pw28, pb22; fma.rn.bf16x2 pb23, pv29, pw29, pb23;\n"
        "fma.rn.bf16x2 pb12, pv24, pw30, pb12; fma.rn.bf16x2 pb13, pv25, pw31, pb13; fma.rn.bf16x2 pb14, pv26, pw32, pb14; fma.rn.bf16x2 pb15, pv27, pw33, pb15; fma.rn.bf16x2 pb16, pv28, pw34, pb16; fma.rn.bf16x2 pb17, pv29, pw35, pb17;\n"
        "fma.rn.bf16x2 pb18, pv30, pw30, pb18; fma.rn.bf16x2 pb19, pv31, pw31, pb19; fma.rn.bf16x2 pb20, pv32, pw32, pb20; fma.rn.bf16x2 pb21, pv33, pw33, pb21; fma.rn.bf16x2 pb22, pv34, pw34, pb22; fma.rn.bf16x2 pb23, pv35, pw35, pb23;\n"
        "C0:\n"
        "wgmma.wait_group.sync.aligned 0;\n"
        "selp.f32 s0, d2, d0, po; selp.f32 s1, d3, d1, po;\n"
        "shfl.sync.bfly.b32 f0, s0, 4, 0x1f, 0xffffffff; shfl.sync.bfly.b32 f1, s1, 4, 0x1f, 0xffffffff;\n"
        "fma.rn.bf16x2 pc0, pv0, pw0, ps1; fma.rn.bf16x2 pc1, pv1, pw1, ps1; fma.rn.bf16x2 pc2, pv2, pw2, ps1; fma.rn.bf16x2 pc3, pv3, pw3, ps1; fma.rn.bf16x2 pc4, pv4, pw4, ps1; fma.rn.bf16x2 pc5, pv5, pw5, ps1;\n"
        "fma.rn.bf16x2 pc6, pv6, pw0, ps3; fma.rn.bf16x2 pc7, pv7, pw1, ps3; fma.rn.bf16x2 pc8, pv8, pw2, ps3; fma.rn.bf16x2 pc9, pv9, pw3, ps3; fma.rn.bf16x2 pc10, pv10, pw4, ps3; fma.rn.bf16x2 pc11, pv11, pw5, ps3;\n"
        "fma.rn.bf16x2 pc12, pv12, pw0, ps5; fma.rn.bf16x2 pc13, pv13, pw1, ps5; fma.rn.bf16x2 pc14, pv14, pw2, ps5; fma.rn.bf16x2 pc15, pv15, pw3, ps5; fma.rn.bf16x2 pc16, pv16, pw4, ps5; fma.rn.bf16x2 pc17, pv17, pw5, ps5;\n"
        "fma.rn.bf16x2 pc18, pv18, pw0, ps7; fma.rn.bf16x2 pc19, pv19, pw1, ps7; fma.rn.bf16x2 pc20, pv20, pw2, ps7; fma.rn.bf16x2 pc21, pv21, pw3, ps7; fma.rn.bf16x2 pc22, pv22, pw4, ps7; fma.rn.bf16x2 pc23, pv23, pw5, ps7;\n"
        "fma.rn.bf16x2 pc0, pv6, pw6, pc0; fma.rn.bf16x2 pc1, pv7, pw7, pc1; fma.rn.bf16x2 pc2, pv8, pw8, pc2; fma.rn.bf16x2 pc3, pv9, pw9, pc3; fma.rn.bf16x2 pc4, pv10, pw10, pc4; fma.rn.bf16x2 pc5, pv11, pw11, pc5;\n"
        "fma.rn.bf16x2 pc6, pv12, pw6, pc6; fma.rn.bf16x2 pc7, pv13, pw7, pc7; fma.rn.bf16x2 pc8, pv14, pw8, pc8; fma.rn.bf16x2 pc9, pv15, pw9, pc9; fma.rn.bf16x2 pc10, pv16, pw10, pc10; fma.rn.bf16x2 pc11, pv17, pw11, pc11;\n"
        "fma.rn.bf16x2 pc12, pv18, pw6, pc12; fma.rn.bf16x2 pc13, pv19, pw7, pc13; fma.rn.bf16x2 pc14, pv20, pw8, pc14; fma.rn.bf16x2 pc15, pv21, pw9, pc15; fma.rn.bf16x2 pc16, pv22, pw10, pc16; fma.rn.bf16x2 pc17, pv23, pw11, pc17;\n"
        "fma.rn.bf16x2 pc18, pv24, pw6, pc18; fma.rn.bf16x2 pc19, pv25, pw7, pc19; fma.rn.bf16x2 pc20, pv26, pw8, pc20; fma.rn.bf16x2 pc21, pv27, pw9, pc21; fma.rn.bf16x2 pc22, pv28, pw10, pc22; fma.rn.bf16x2 pc23, pv29, pw11, pc23;\n"
        "fma.rn.bf16x2 pc0, pv12, pw12, pc0; fma.rn.bf16x2 pc1, pv13, pw13, pc1; fma.rn.bf16x2 pc2, pv14, pw14, pc2; fma.rn.bf16x2 pc3, pv15, pw15, pc3; fma.rn.bf16x2 pc4, pv16, pw16, pc4; fma.rn.bf16x2 pc5, pv17, pw17, pc5;\n"
        "fma.rn.bf16x2 pc6, pv18, pw12, pc6; fma.rn.bf16x2 pc7, pv19, pw13, pc7; fma.rn.bf16x2 pc8, pv20, pw14, pc8; fma.rn.bf16x2 pc9, pv21, pw15, pc9; fma.rn.bf16x2 pc10, pv22, pw16, pc10; fma.rn.bf16x2 pc11, pv23, pw17, pc11;\n"
        "fma.rn.bf16x2 pc12, pv24, pw12, pc12; fma.rn.bf16x2 pc13, pv25, pw13, pc13; fma.rn.bf16x2 pc14, pv26, pw14, pc14; fma.rn.bf16x2 pc15, pv27, pw15, pc15; fma.rn.bf16x2 pc16, pv28, pw16, pc16; fma.rn.bf16x2 pc17, pv29, pw17, pc17;\n"
        "fma.rn.bf16x2 pc18, pv30, pw12, pc18; fma.rn.bf16x2 pc19, pv31, pw13, pc19; fma.rn.bf16x2 pc20, pv32, pw14, pc20; fma.rn.bf16x2 pc21, pv33, pw15, pc21; fma.rn.bf16x2 pc22, pv34, pw16, pc22; fma.rn.bf16x2 pc23, pv35, pw17, pc23;\n"
        "add.f32 s0, s0, f0; add.f32 s1, s1, f1; mul.f32 s0, s0, 0fBC2AAAAB;\n"
        "neg.f32 f0, s0; fma.rn.f32 f0, f0, s0, %13; fma.rn.f32 f0, s1, 0f3C2AAAAB, f0; max.f32 f0, f0, %13;\n"
        "rsqrt.approx.ftz.f32 f0, f0; mul.f32 f0, f0, %14; cvt.rn.bf16x2.f32 tt, f0, 0f00000000; mov.b32 f0, tt;\n"
        "mul.f32 f1, s0, kq; mul.f32 f1, f1, f0; cvt.rn.bf16x2.f32 tt, f1, f0; add.f32 us, us, s0; cvt.rn.bf16x2.f32 mm, us, us;\n"
        "add.u32 ad, %7, so; st.shared.v2.b32 [ad], {tt, mm};\n"
        "add.u32 ad, %6, so; ld.shared.v4.b32 {ps0,ps1,ps2,ps3}, [ad]; ld.shared.v4.b32 {ps4,ps5,ps6,ps7}, [ad+16];\n"
        "mbarrier.try_wait.parity.shared::cta.b64 pw, [so+174992], ph;\n"
        "mbarrier.try_wait.parity.shared::cta.b64 px, [so+174976], ph;\n"
        "and.pred pw, pw, px;\n"
        "N0:\n"
        "@!pw bra.uni SPIN;\n"
        "BACK:\n"
        "add.u32 ad, %0, so; ld.shared.v4.b32 {pv0,pv1,pv2,pv3}, [ad+0];\n"
        "add.u32 ad, %1, so; ld.shared.v2.b32 {pv4,pv5}, [ad+0];\n"
        "add.u32 ad, %0, so; ld.shared.v4.b32 {pv6,pv7,pv8,pv9}, [ad+192];\n"
        "add.u32 ad, %1, so; ld.shared.v2.b32 {pv10,pv11}, [ad+192];\n"
        "mov.b32 {xl, xh}, ps0; mov.b32 rr, {xl, xl}; mov.b32 mm, {xh, xh}; fma.rn.bf16x2 pa0, pa0, rr, mm; fma.rn.bf16x2 pa1, pa1, rr, mm; fma.rn.bf16x2 pa2, pa2, rr, mm; fma.rn.bf16x2 pa3, pa3, rr, mm; fma.rn.bf16x2 pa4, pa4, rr, mm; fma.rn.bf16x2 pa5, pa5, rr, mm;\n"
        "and.b32 m0, pa0, 0x7fff7fff; and.b32 m1, pa1, 0x7fff7fff; and.b32 m2, pa2, 0x7fff7fff; and.b32 m3, pa3, 0x7fff7fff; and.b32 m4, pa4, 0x7fff7fff; and.b32 m5, pa5, 0x7fff7fff;\n"
        "mad.lo.u32 y0, m0, 7, pa0; mad.lo.u32 y1, m1, 7, pa1; mad.lo.u32 y2, m2, 7, pa2; mad.lo.u32 y3, m3, 7, pa3; mad.lo.u32 y4, m4, 7, pa4; mad.lo.u32 y5, m5, 7, pa5;\n"
        "add.u32 ad, %2, so; st.shared.v4.b32 [ad+0], {y0,y1,y2,y3};\n"
        "add.u32 ad, %4, so; st.shared.v2.b32 [ad+0], {y4,y5};\n"
        "N1:\n"
        "add.u32 ad, %0, so; ld.shared.v4.b32 {pv12,pv13,pv14,pv15}, [ad+384];\n"
        "add.u32 ad, %1, so; ld.shared.v2.b32 {pv16,pv17}, [ad+384];\n"
        "add.u32 ad, %0, so; ld.shared.v4.b32 {pv18,pv19,pv20,pv21}, [ad+576];\n"
        "add.u32 ad, %1, so; ld.shared.v2.b32 {pv22,pv23}, [ad+576];\n"
        "mov.b32 {xl, xh}, ps2; mov.b32 rr, {xl, xl}; mov.b32 mm, {xh, xh}; fma.rn.bf16x2 pa6, pa6, rr, mm; fma.rn.bf16x2 pa7, pa7, rr, mm; fma.rn.bf16x2 pa8, pa8, rr, mm; fma.rn.bf16x2 pa9, pa9, rr, mm; fma.rn.bf16x2 pa10, pa10, rr, mm; fma.rn.bf16x2 pa11, pa11, rr, mm;\n"
        "and.b32 m0, pa6, 0x7fff7fff; and.b32 m1, pa7, 0x7fff7fff; and.b32 m2, pa8, 0x7fff7fff; and.b32 m3, pa9, 0x7fff7fff; and.b32 m4, pa10, 0x7fff7fff; and.b32 m5, pa11, 0x7fff7fff;\n"
        "mad.lo.u32 y0, m0, 7, pa6; mad.lo.u32 y1, m1, 7, pa7; mad.lo.u32 y2, m2, 7, pa8; mad.lo.u32 y3, m3, 7, pa9; mad.lo.u32 y4, m4, 7, pa10; mad.lo.u32 y5, m5, 7, pa11;\n"
        "add.u32 ad, %3, so; st.shared.v4.b32 [ad+0], {y0,y1,y2,y3};\n"
        "add.u32 ad, %5, so; st.shared.v2.b32 [ad+0], {y4,y5};\n"
        "N2:\n"
        "add.u32 ad, %0, so; ld.shared.v4.b32 {pv24,pv25,pv26,pv27}, [ad+768];\n"
        "add.u32 ad, %1, so; ld.shared.v2.b32 {pv28,pv29}, [ad+768];\n"
        "mov.b32 {xl, xh}, ps4; mov.b32 rr, {xl, xl}; mov.b32 mm, {xh, xh}; fma.rn.bf16x2 pa12, pa12, rr, mm; fma.rn.bf16x2 pa13, pa13, rr, mm; fma.rn.bf16x2 pa14, pa14, rr, mm; fma.rn.bf16x2 pa15, pa15, rr, mm; fma.rn.bf16x2 pa16, pa16, rr, mm; fma.rn.bf16x2 pa17, pa17, rr, mm;\n"
        "and.b32 m0, pa12, 0x7fff7fff; and.b32 m1, pa13, 0x7fff7fff; and.b32 m2, pa14, 0x7fff7fff; and.b32 m3, pa15, 0x7fff7fff; and.b32 m4, pa16, 0x7fff7fff; and.b32 m5, pa17, 0x7fff7fff;\n"
        "mad.lo.u32 y0, m0, 7, pa12; mad.lo.u32 y1, m1, 7, pa13; mad.lo.u32 y2, m2, 7, pa14; mad.lo.u32 y3, m3, 7, pa15; mad.lo.u32 y4, m4, 7, pa16; mad.lo.u32 y5, m5, 7, pa17;\n"
        "add.u32 ad, %2, so; st.shared.v4.b32 [ad+2048], {y0,y1,y2,y3};\n"
        "add.u32 ad, %4, so; st.shared.v2.b32 [ad+1024], {y4,y5};\n"
        "N3:\n"
        "add.u32 ad, %0, so; ld.shared.v4.b32 {pv30,pv31,pv32,pv33}, [ad+960];\n"
        "add.u32 ad, %1, so; ld.shared.v2.b32 {pv34,pv35}, [ad+960];\n"
        "mov.b32 {xl, xh}, ps6; mov.b32 rr, {xl, xl}; mov.b32 mm, {xh, xh}; fma.rn.bf16x2 pa18, pa18, rr, mm; fma.rn.bf16x2 pa19, pa19, rr, mm; fma.rn.bf16x2 pa20, pa20, rr, mm; fma.rn.bf16x2 pa21, pa21, rr, mm; fma.rn.bf16x2 pa22, pa22, rr, mm; fma.rn.bf16x2 pa23, pa23, rr, mm;\n"
        "and.b32 m0, pa18, 0x7fff7fff; and.b32 m1, pa19, 0x7fff7fff; and.b32 m2, pa20, 0x7fff7fff; and.b32 m3, pa21, 0x7fff7fff; and.b32 m4, pa22, 0x7fff7fff; and.b32 m5, pa23, 0x7fff7fff;\n"
        "mad.lo.u32 y0, m0, 7, pa18; mad.lo.u32 y1, m1, 7, pa19; mad.lo.u32 y2, m2, 7, pa20; mad.lo.u32 y3, m3, 7, pa21; mad.lo.u32 y4, m4, 7, pa22; mad.lo.u32 y5, m5, 7, pa23;\n"
        "add.u32 ad, %3, so; st.shared.v4.b32 [ad+2048], {y0,y1,y2,y3};\n"
        "add.u32 ad, %5, so; st.shared.v2.b32 [ad+1024], {y4,y5};\n"
        "mov.u32 sp, so; add.u32 so, so, 26624; setp.eq.u32 pr, so, 79872; selp.u32 so, 0, so, pr; selp.u32 tt, 1, 0, pr; xor.b32 ph, ph, tt;\n"
        "add.u32 t, t, 1; setp.lt.u32 pe, t, 32;\n"
        "@pe bra.uni LOOP;\n"
        "bra.uni DONE;\n"
        "SPIN: mov.u32 cnt, 0;\n"
        ASM_TRC("t", 1)
        "SPINL:\n"
        "mbarrier.try_wait.parity.shared::cta.b64 pw, [so+174992], ph;\n"
        "mbarrier.try_wait.parity.shared::cta.b64 px, [so+174976], ph;\n"
        "and.pred pw, pw, px;\n"
        "@pw bra.uni BACK;\n"
        "add.u32 cnt, cnt, 1; setp.lt.u32 pw, cnt, 0x100000;\n"
        "@pw bra.uni SPINL;\n"
        "trap;\n"
        "RARE:\n"
        "ld.volatile.shared.u32 tt, [%6];\n"
        "mov.b32 pa0, tt; mov.b32 pa1, tt; mov.b32 pa2, tt; mov.b32 pa3, tt; mov.b32 pa4, tt; mov.b32 pa5, tt; mov.b32 pa6, tt; mov.b32 pa7, tt; mov.b32 pa8, tt; mov.b32 pa9, tt; mov.b32 pa10, tt; mov.b32 pa11, tt;\n"
        "mov.b32 pa12, tt; mov.b32 pa13, tt; mov.b32 pa14, tt; mov.b32 pa15, tt; mov.b32 pa16, tt; mov.b32 pa17, tt; mov.b32 pa18, tt; mov.b32 pa19, tt; mov.b32 pa20, tt; mov.b32 pa21, tt; mov.b32 pa22, tt; mov.b32 pa23, tt;\n"
        "mov.b32 pb0, tt; mov.b32 pb1, tt; mov.b32 pb2, tt; mov.b32 pb3, tt; mov.b32 pb4, tt; mov.b32 pb5, tt; mov.b32 pb6, tt; mov.b32 pb7, tt; mov.b32 pb8, tt; mov.b32 pb9, tt; mov.b32 pb10, tt; mov.b32 pb11, tt;\n"
        "mov.b32 pb12, tt; mov.b32 pb13, tt; mov.b32 pb14, tt; mov.b32 pb15, tt; mov.b32 pb16, tt; mov.b32 pb17, tt; mov.b32 pb18, tt; mov.b32 pb19, tt; mov.b32 pb20, tt; mov.b32 pb21, tt; mov.b32 pb22, tt; mov.b32 pb23, tt;\n"
        "mov.b32 pc0, tt; mov.b32 pc1, tt; mov.b32 pc2, tt; mov.b32 pc3, tt; mov.b32 pc4, tt; mov.b32 pc5, tt; mov.b32 pc6, tt; mov.b32 pc7, tt; mov.b32 pc8, tt; mov.b32 pc9, tt; mov.b32 pc10, tt; mov.b32 pc11, tt;\n"
        "mov.b32 pc12, tt; mov.b32 pc13, tt; mov.b32 pc14, tt; mov.b32 pc15, tt; mov.b32 pc16, tt; mov.b32 pc17, tt; mov.b32 pc18, tt; mov.b32 pc19, tt; mov.b32 pc20, tt; mov.b32 pc21, tt; mov.b32 pc22, tt; mov.b32 pc23, tt;\n"
        "mov.b32 ps0, tt; mov.b32 ps1, tt; mov.b32 ps2, tt; mov.b32 ps3, tt; mov.b32 ps4, tt; mov.b32 ps5, tt; mov.b32 ps6, tt; mov.b32 ps7, tt; mov.b32 pq0, tt; mov.b32 pq1, tt; mov.b32 pq2, tt; mov.b32 pq3, tt;\n"
        "ld.volatile.shared.v2.b32 {pw1, pw0}, [%6]; xor.b32 tt, tt, pw1;\n"
        "ld.volatile.shared.v2.b32 {pw3, pw2}, [%6]; xor.b32 tt, tt, pw3;\n"
        "ld.volatile.shared.v2.b32 {pw5, pw4}, [%6]; xor.b32 tt, tt, pw5;\n"
        "ld.volatile.shared.v2.b32 {pw7, pw6}, [%6]; xor.b32 tt, tt, pw7;\n"
        "ld.volatile.shared.v2.b32 {pw9, pw8}, [%6]; xor.b32 tt, tt, pw9;\n"
        "ld.volatile.shared.v2.b32 {pw11, pw10}, [%6]; xor.b32 tt, tt, pw11;\n"
        "ld.volatile.shared.v2.b32 {pw13, pw12}, [%6]; xor.b32 tt, tt, pw13;\n"
        "ld.volatile.shared.v2.b32 {pw15, pw14}, [%6]; xor.b32 tt, tt, pw15;\n"
        "ld.volatile.shared.v2.b32 {pw17, pw16}, [%6]; xor.b32 tt, tt, pw17;\n"
        "ld.volatile.shared.v2.b32 {pw19, pw18}, [%6]; xor.b32 tt, tt, pw19;\n"
        "ld.volatile.shared.v2.b32 {pw21, pw20}, [%6]; xor.b32 tt, tt, pw21;\n"
        "ld.volatile.shared.v2.b32 {pw23, pw22}, [%6]; xor.b32 tt, tt, pw23;\n"
        "ld.volatile.shared.v2.b32 {pw25, pw24}, [%6]; xor.b32 tt, tt, pw25;\n"
        "ld.volatile.shared.v2.b32 {pw27, pw26}, [%6]; xor.b32 tt, tt, pw27;\n"
        "ld.volatile.shared.v2.b32 {pw29, pw28}, [%6]; xor.b32 tt, tt, pw29;\n"
        "ld.volatile.shared.v2.b32 {pw31, pw30}, [%6]; xor.b32 tt, tt, pw31;\n"
        "ld.volatile.shared.v2.b32 {pw33, pw32}, [%6]; xor.b32 tt, tt, pw33;\n"
        "ld.volatile.shared.v2.b32 {pw35, pw34}, [%6]; xor.b32 tt, tt, pw35;\n"
        "ld.volatile.shared.v2.b32 {pw37, pw36}, [%6]; xor.b32 tt, tt, pw37;\n"
        "ld.volatile.shared.v2.b32 {pw39, pw38}, [%6]; xor.b32 tt, tt, pw39;\n"
        "ld.volatile.shared.v2.b32 {pw41, pw40}, [%6]; xor.b32 tt, tt, pw41;\n"
        "ld.volatile.shared.v2.b32 {pw43, pw42}, [%6]; xor.b32 tt, tt, pw43;\n"
        "ld.volatile.shared.v2.b32 {pw45, pw44}, [%6]; xor.b32 tt, tt, pw45;\n"
        "ld.volatile.shared.v2.b32 {pw47, pw46}, [%6]; xor.b32 tt, tt, pw47;\n"
        "ld.volatile.shared.v2.b32 {pw49, pw48}, [%6]; xor.b32 tt, tt, pw49;\n"
        "ld.volatile.shared.v2.b32 {pw51, pw50}, [%6]; xor.b32 tt, tt, pw51;\n"
        "ld.volatile.shared.v2.b32 {pw53, pw52}, [%6]; xor.b32 tt, tt, pw53;\n"
        "mov.b32 us, tt; setp.ne.u32 pw, %15, 7;\n"
        "wgmma.fence.sync.aligned;\n"
        "setp.eq.u32 pr, %15, 1000; @pr bra.uni B0;\n"
        "setp.eq.u32 pr, %15, 1001; @pr bra.uni B1;\n"
        "setp.eq.u32 pr, %15, 1002; @pr bra.uni C0;\n"
        "setp.eq.u32 pr, %15, 1003; @pr bra.uni N0;\n"
        "setp.eq.u32 pr, %15, 1004; @pr bra.uni N1;\n"
        "setp.eq.u32 pr, %15, 1005; @pr bra.uni N2;\n"
        "setp.eq.u32 pr, %15, 1006; @pr bra.uni N3;\n"
        "trap;\n"
        "DONE:\n"
        ASM_TRC("t", 0)
        "fence.proxy.async.shared::cta;\n"
        "@pl mbarrier.arrive.shared::cta.b64 _, [sp+174984];\n"
        "}\n"
        :: "r"(sb + SM_X + c.xoff[0]), "r"(sb + SM_X + c.xoff[1]), "r"(sb + SM_Y1 + c.yoff[0][0]), "r"(sb + SM_Y1 + c.yoff[0][1]),
           "r"(sb + SM_Y1 + c.yoff[1][0]), "r"(sb + SM_Y1 + c.yoff[1][1]), "r"(c.stat), "r"(c.own), "r"(c.lane),
           "l"(prm.sel[0]), "l"(prm.sel[1]), "l"(prm.sel[2]), "r"(prm.ydesc), "f"(LN_EPS_SCALED), "f"(RSTD_SCALE), "r"(prm.w1desc)
        : "memory");
}

__device__ __forceinline__ void produce(const Producer& c, const Params& prm) {
    uint32_t B[24], C[24];
    const RowCopy rc = row_copy(prm);
    uint32_t st[8];
    uint32_t v[6][6];
    {
        uint32_t ws[6];
#pragma unroll
        for (int u = 0; u < 6; u++) {
            ws[u] = c.w[0][u];
#pragma unroll
            for (int t = 1; t < 9; t++) ws[u] = bf2_add(ws[u], c.w[t][u]);
        }
        SMARK(2);
        mbar_wait_c<0>(sb + SM_XFULL);
        SMARK(3);
        lds128(v[0], sb + SM_X + c.xoff[0] + 2 * 192);
        asm volatile("ld.shared.v2.b32 {%0,%1}, [%2];" : "=r"(v[0][4]), "=r"(v[0][5]) : "r"(sb + SM_X + c.xoff[1] + 2 * 192));
        const uint32_t p = bf2_add(bf2_fma(v[0][2], ws[2], bf2_fma(v[0][1], ws[1], bf2_mul(v[0][0], ws[0]))),
                                   bf2_fma(v[0][5], ws[5], bf2_fma(v[0][4], ws[4], bf2_mul(v[0][3], ws[3]))));
        float e = quad_sum(bf_lo(p) + bf_hi(p));
        e = (e + __shfl_xor_sync(0xffffffffu, e, 4)) * (-1.0f / CH);
        st[1] = st[3] = st[5] = st[7] = pack_bf2(e, e);
#pragma unroll
        for (int k = 0; k < NX; k++) sts32(c.own + k * SLOT_BYTES + 4, st[1]);
#pragma unroll
        for (int r = 0; r < 24; r++) C[r] = 0;
    }
#pragma unroll 1
    for (int i = loop_init<0>();; i++) {
        mbar_wait_c<0>(sb + SM_XFULL + i * SLOT_BYTES);
        SMARK(4 + i);
        load_x(v, c, sb + SM_X + i * SLOT_BYTES);
        fence_async_smem();
        if (c.warp == i) {
            named_sync(6 + i, 128);
            issue_row_load(rc, i + NX, i);
        } else {
            asm volatile("bar.arrive %0, 128;" ::"r"(6 + i) : "memory");
        }
        if (i == 2) break;
        conv_row<1, 1>(B, C, v, c);
        conv_row<0, 0>(C, st, v, c);
    }
    asm volatile(".reg .b32 pw<54>, pb<24>, pc<24>, pv<36>, ps<8>;");
    hand_over<0>(c, B, C, v);
    asm volatile("mov.b32 ps1, %0; mov.b32 ps3, %1; mov.b32 ps5, %2; mov.b32 ps7, %3;" ::"r"(st[1]), "r"(st[3]), "r"(st[5]), "r"(st[7]));
    SMARK(7);
    produce_tiles(c, prm);
    mbar_arrive_if(sb + SM_Y1FULL + ROWS_PER_CTA % NX * SLOT_BYTES, c.lane == 0);
}

struct Duty {
    const char* g;
    const char* zeros;
    long long step;
    uint32_t s, bytes;
    int end, zero;
};
__device__ __forceinline__ Duty make_duty(const Params& prm, int wg, int w) {
    const RowCopy rc = row_copy(prm);
    Duty d;
    d.g = (w == 2 ? rc.y0 : rc.x0 + (w == 0 ? rc.cut0 : w == 1 ? 32 * 192 : 192)) +
          (wg + (w == 2 ? 0 : w < 2 ? 2 * NX : 2 * NX + L2_AHEAD)) * rc.stride;
    d.step = NX * rc.stride;
    d.s = wg * SLOT_BYTES + (w == 2 ? sb + SM_Y1 : sb + SM_X + (w == 0 ? rc.cut0 : XHALF_B));
    d.bytes = w >= 2 ? TILE_BYTES : XHALF_BYTES - (w == 0 ? rc.cut0 : rc.cut1);
    d.end = w == 2 ? ROWS_PER_CTA : w < 2 ? STEPS + 1 - 2 * NX : rc.last + 1 - 2 * NX - L2_AHEAD;
    d.zero = rc.last + 1 - 2 * NX;
    d.zeros = rc.zeros;
    return d;
}

static_assert(sb + SM_Y1FULL == 174984 && sb + SM_Y1EMPTY == 174992 && sb + SM_XFULL == 174976 && SLOT_BYTES == 26624 &&
              sb + SM_GAMMA == 229248 && SM_BETA == SM_GAMMA + 768 && sb + SM_BAR + BAR_W2 * 8 == 230872 && SM_W2 == 73728 &&
              BAR_W1B == 54 && sb + SM_BUF3 == 187392 && sb + SM_BAR + (BAR_Y2FULL + 3) * 8 == 230824, "layout");
__device__ __forceinline__ void consume(float (&acc)[2][2], uint32_t w1t, uint32_t yd, uint32_t wd, uint32_t own_slot, const Duty& d,
                                        uint32_t role, uint32_t lane, const Params& prm) {
    asm volatile(
        "{\n"
        ".reg .b32 z<32>, w<44>, p<2>, a<4>, lo<4>, hi<4>, t<2>, g<2>, q<4>, dl<6>, dh<6>, n, so, sp, ph, c, tt, cnt;\n"
        ".reg .b16 xl, xh, xr;\n"
        ".reg .b32 f0, f1;\n"
        ".reg .b64 ds<6>, wd, gp, src;\n"
        ".reg .pred pt, pf, pr, pw, pl, pe;\n"
        "setp.ne.b32 pt, 1, 0; setp.ne.b32 pf, 0, 0; setp.eq.u32 pl, %15, 0;\n"
        "mov.b32 c, 0x40D940D9;\n"
        "ldmatrix.sync.aligned.m8n8.x4.trans.shared.b16 {w0,w1,w2,w3}, [%4+0];\n"
        "ldmatrix.sync.aligned.m8n8.x4.trans.shared.b16 {w4,w5,w6,w7}, [%4+2048];\n"
        "ldmatrix.sync.aligned.m8n8.x4.trans.shared.b16 {w8,w9,w10,w11}, [%4+4096];\n"
        "ldmatrix.sync.aligned.m8n8.x4.trans.shared.b16 {w12,w13,w14,w15}, [%4+6144];\n"
        "ldmatrix.sync.aligned.m8n8.x4.trans.shared.b16 {w16,w17,w18,w19}, [%4+8192];\n"
        "ldmatrix.sync.aligned.m8n8.x4.trans.shared.b16 {w20,w21,w22,w23}, [%4+10240];\n"
        "shl.b32 f0, w0, 16; and.b32 f1, w0, 0xffff0000; cvt.rn.f16x2.f32 w0, f1, f0; shl.b32 f0, w1, 16; and.b32 f1, w1, 0xffff0000; cvt.rn.f16x2.f32 w1, f1, f0; shl.b32 f0, w2, 16; and.b32 f1, w2, 0xffff0000; cvt.rn.f16x2.f32 w2, f1, f0; shl.b32 f0, w3, 16; and.b32 f1, w3, 0xffff0000; cvt.rn.f16x2.f32 w3, f1, f0;\n"
        "stmatrix.sync.aligned.m8n8.x4.trans.shared.b16 [%4+0], {w0,w1,w2,w3};\n"
        "shl.b32 f0, w4, 16; and.b32 f1, w4, 0xffff0000; cvt.rn.f16x2.f32 w4, f1, f0; shl.b32 f0, w5, 16; and.b32 f1, w5, 0xffff0000; cvt.rn.f16x2.f32 w5, f1, f0; shl.b32 f0, w6, 16; and.b32 f1, w6, 0xffff0000; cvt.rn.f16x2.f32 w6, f1, f0; shl.b32 f0, w7, 16; and.b32 f1, w7, 0xffff0000; cvt.rn.f16x2.f32 w7, f1, f0;\n"
        "stmatrix.sync.aligned.m8n8.x4.trans.shared.b16 [%4+2048], {w4,w5,w6,w7};\n"
        "shl.b32 f0, w8, 16; and.b32 f1, w8, 0xffff0000; cvt.rn.f16x2.f32 w8, f1, f0; shl.b32 f0, w9, 16; and.b32 f1, w9, 0xffff0000; cvt.rn.f16x2.f32 w9, f1, f0; shl.b32 f0, w10, 16; and.b32 f1, w10, 0xffff0000; cvt.rn.f16x2.f32 w10, f1, f0; shl.b32 f0, w11, 16; and.b32 f1, w11, 0xffff0000; cvt.rn.f16x2.f32 w11, f1, f0;\n"
        "stmatrix.sync.aligned.m8n8.x4.trans.shared.b16 [%4+4096], {w8,w9,w10,w11};\n"
        "shl.b32 f0, w12, 16; and.b32 f1, w12, 0xffff0000; cvt.rn.f16x2.f32 w12, f1, f0; shl.b32 f0, w13, 16; and.b32 f1, w13, 0xffff0000; cvt.rn.f16x2.f32 w13, f1, f0; shl.b32 f0, w14, 16; and.b32 f1, w14, 0xffff0000; cvt.rn.f16x2.f32 w14, f1, f0; shl.b32 f0, w15, 16; and.b32 f1, w15, 0xffff0000; cvt.rn.f16x2.f32 w15, f1, f0;\n"
        "stmatrix.sync.aligned.m8n8.x4.trans.shared.b16 [%4+6144], {w12,w13,w14,w15};\n"
        "shl.b32 f0, w16, 16; and.b32 f1, w16, 0xffff0000; cvt.rn.f16x2.f32 w16, f1, f0; shl.b32 f0, w17, 16; and.b32 f1, w17, 0xffff0000; cvt.rn.f16x2.f32 w17, f1, f0; shl.b32 f0, w18, 16; and.b32 f1, w18, 0xffff0000; cvt.rn.f16x2.f32 w18, f1, f0; shl.b32 f0, w19, 16; and.b32 f1, w19, 0xffff0000; cvt.rn.f16x2.f32 w19, f1, f0;\n"
        "stmatrix.sync.aligned.m8n8.x4.trans.shared.b16 [%4+8192], {w16,w17,w18,w19};\n"
        "shl.b32 f0, w20, 16; and.b32 f1, w20, 0xffff0000; cvt.rn.f16x2.f32 w20, f1, f0; shl.b32 f0, w21, 16; and.b32 f1, w21, 0xffff0000; cvt.rn.f16x2.f32 w21, f1, f0; shl.b32 f0, w22, 16; and.b32 f1, w22, 0xffff0000; cvt.rn.f16x2.f32 w22, f1, f0; shl.b32 f0, w23, 16; and.b32 f1, w23, 0xffff0000; cvt.rn.f16x2.f32 w23, f1, f0;\n"
        "stmatrix.sync.aligned.m8n8.x4.trans.shared.b16 [%4+10240], {w20,w21,w22,w23};\n"
        "mov.u32 tt, 231232; mbarrier.try_wait.parity.shared::cta.b64 pw, [tt], 0;\n"
        "@!pw bra.uni SPINW;\n"
        "BACKW:\n"
        "ldmatrix.sync.aligned.m8n8.x4.trans.shared.b16 {z0,z1,z2,z3}, [%4+22528];\n"
        "ldmatrix.sync.aligned.m8n8.x4.trans.shared.b16 {w24,w25,w26,w27}, [%4+12288];\n"
        "ldmatrix.sync.aligned.m8n8.x4.trans.shared.b16 {w28,w29,w30,w31}, [%4+14336];\n"
        "ldmatrix.sync.aligned.m8n8.x4.trans.shared.b16 {w32,w33,w34,w35}, [%4+16384];\n"
        "ldmatrix.sync.aligned.m8n8.x4.trans.shared.b16 {w36,w37,w38,w39}, [%4+18432];\n"
        "ldmatrix.sync.aligned.m8n8.x4.trans.shared.b16 {w40,w41,w42,w43}, [%4+20480];\n"
        "shl.b32 f0, z0, 16; and.b32 f1, z0, 0xffff0000; cvt.rn.f16x2.f32 z0, f1, f0; shl.b32 f0, z1, 16; and.b32 f1, z1, 0xffff0000; cvt.rn.f16x2.f32 z1, f1, f0; shl.b32 f0, z2, 16; and.b32 f1, z2, 0xffff0000; cvt.rn.f16x2.f32 z2, f1, f0; shl.b32 f0, z3, 16; and.b32 f1, z3, 0xffff0000; cvt.rn.f16x2.f32 z3, f1, f0;\n"
        "stmatrix.sync.aligned.m8n8.x4.trans.shared.b16 [%4+22528], {z0,z1,z2,z3};\n"
        "shl.b32 f0, w24, 16; and.b32 f1, w24, 0xffff0000; cvt.rn.f16x2.f32 w24, f1, f0; shl.b32 f0, w25, 16; and.b32 f1, w25, 0xffff0000; cvt.rn.f16x2.f32 w25, f1, f0; shl.b32 f0, w26, 16; and.b32 f1, w26, 0xffff0000; cvt.rn.f16x2.f32 w26, f1, f0; shl.b32 f0, w27, 16; and.b32 f1, w27, 0xffff0000; cvt.rn.f16x2.f32 w27, f1, f0;\n"
        "stmatrix.sync.aligned.m8n8.x4.trans.shared.b16 [%4+12288], {w24,w25,w26,w27};\n"
        "shl.b32 f0, w28, 16; and.b32 f1, w28, 0xffff0000; cvt.rn.f16x2.f32 w28, f1, f0; shl.b32 f0, w29, 16; and.b32 f1, w29, 0xffff0000; cvt.rn.f16x2.f32 w29, f1, f0; shl.b32 f0, w30, 16; and.b32 f1, w30, 0xffff0000; cvt.rn.f16x2.f32 w30, f1, f0; shl.b32 f0, w31, 16; and.b32 f1, w31, 0xffff0000; cvt.rn.f16x2.f32 w31, f1, f0;\n"
        "stmatrix.sync.aligned.m8n8.x4.trans.shared.b16 [%4+14336], {w28,w29,w30,w31};\n"
        "shl.b32 f0, w32, 16; and.b32 f1, w32, 0xffff0000; cvt.rn.f16x2.f32 w32, f1, f0; shl.b32 f0, w33, 16; and.b32 f1, w33, 0xffff0000; cvt.rn.f16x2.f32 w33, f1, f0; shl.b32 f0, w34, 16; and.b32 f1, w34, 0xffff0000; cvt.rn.f16x2.f32 w34, f1, f0; shl.b32 f0, w35, 16; and.b32 f1, w35, 0xffff0000; cvt.rn.f16x2.f32 w35, f1, f0;\n"
        "stmatrix.sync.aligned.m8n8.x4.trans.shared.b16 [%4+16384], {w32,w33,w34,w35};\n"
        "shl.b32 f0, w36, 16; and.b32 f1, w36, 0xffff0000; cvt.rn.f16x2.f32 w36, f1, f0; shl.b32 f0, w37, 16; and.b32 f1, w37, 0xffff0000; cvt.rn.f16x2.f32 w37, f1, f0; shl.b32 f0, w38, 16; and.b32 f1, w38, 0xffff0000; cvt.rn.f16x2.f32 w38, f1, f0; shl.b32 f0, w39, 16; and.b32 f1, w39, 0xffff0000; cvt.rn.f16x2.f32 w39, f1, f0;\n"
        "stmatrix.sync.aligned.m8n8.x4.trans.shared.b16 [%4+18432], {w36,w37,w38,w39};\n"
        "shl.b32 f0, w40, 16; and.b32 f1, w40, 0xffff0000; cvt.rn.f16x2.f32 w40, f1, f0; shl.b32 f0, w41, 16; and.b32 f1, w41, 0xffff0000; cvt.rn.f16x2.f32 w41, f1, f0; shl.b32 f0, w42, 16; and.b32 f1, w42, 0xffff0000; cvt.rn.f16x2.f32 w42, f1, f0; shl.b32 f0, w43, 16; and.b32 f1, w43, 0xffff0000; cvt.rn.f16x2.f32 w43, f1, f0;\n"
        "stmatrix.sync.aligned.m8n8.x4.trans.shared.b16 [%4+20480], {w40,w41,w42,w43};\n"
        "fence.proxy.async.shared::cta;\n"
        ASM_SMARK
        "mov.b32 p0, 0; mov.b32 p1, 0; mov.b32 t0, 0; mov.b32 t1, 0; mov.b32 g0, 0; mov.b32 g1, 0; mov.b32 a0, 0; mov.b32 a1, 0; mov.b32 a2, 0; mov.b32 a3, 0; mov.b32 lo0, 0; mov.b32 lo1, 0; mov.b32 hi0, 0; mov.b32 hi1, 0; mov.b32 q0, 0; mov.b32 q1, 0; mov.b32 q2, 0; mov.b32 q3, 0;\n"
        "mov.b32 z16, 0; mov.b32 z17, 0; mov.b32 z18, 0; mov.b32 z19, 0; mov.b32 z20, 0; mov.b32 z21, 0; mov.b32 z22, 0; mov.b32 z23, 0; mov.b32 z24, 0; mov.b32 z25, 0; mov.b32 z26, 0; mov.b32 z27, 0; mov.b32 z28, 0; mov.b32 z29, 0; mov.b32 z30, 0; mov.b32 z31, 0;\n"
        "mov.f32 %0, 0f00000000; mov.f32 %1, 0f00000000; mov.f32 %2, 0f00000000; mov.f32 %3, 0f00000000;\n"
        "mov.u32 n, 0; mov.u32 so, 0; mov.u32 sp, 0; mov.u32 ph, 0; mov.b64 gp, %8; mov.b64 wd, {%6, 0x40000040};\n"
        "shr.u32 tt, so, 4; cvt.u64.u32 ds5, tt; add.s64 ds0, ds5, %20; add.s64 ds4, ds5, %21;\n"
        "add.s64 ds1, ds0, 2; add.s64 ds2, ds0, 4; add.s64 ds3, ds0, 6; add.s64 ds5, ds4, 2;\n"
        "mbarrier.try_wait.parity.shared::cta.b64 pw, [so+174984], ph;\n"
        "@!pw bra.uni SPIN0;\n"
        "BACK0:\n"
        ASM_TS
        "wgmma.fence.sync.aligned;\n"
        "wgmma.mma_async.sync.aligned.m64n64k16.f16.f16.f16 {z0,z1,z2,z3,z4,z5,z6,z7,z8,z9,z10,z11,z12,z13,z14,z15}, {w0,w1,w2,w3}, ds0, pf, 1, 1, 0;\n"
        "wgmma.mma_async.sync.aligned.m64n64k16.f16.f16.f16 {z0,z1,z2,z3,z4,z5,z6,z7,z8,z9,z10,z11,z12,z13,z14,z15}, {w4,w5,w6,w7}, ds1, pt, 1, 1, 0;\n"
        "wgmma.mma_async.sync.aligned.m64n64k16.f16.f16.f16 {z0,z1,z2,z3,z4,z5,z6,z7,z8,z9,z10,z11,z12,z13,z14,z15}, {w8,w9,w10,w11}, ds2, pt, 1, 1, 0;\n"
        "wgmma.mma_async.sync.aligned.m64n64k16.f16.f16.f16 {z0,z1,z2,z3,z4,z5,z6,z7,z8,z9,z10,z11,z12,z13,z14,z15}, {w12,w13,w14,w15}, ds3, pt, 1, 1, 0;\n"
        "wgmma.mma_async.sync.aligned.m64n64k16.f16.f16.f16 {z0,z1,z2,z3,z4,z5,z6,z7,z8,z9,z10,z11,z12,z13,z14,z15}, {w16,w17,w18,w19}, ds4, pt, 1, 1, 0;\n"
        "wgmma.mma_async.sync.aligned.m64n64k16.f16.f16.f16 {z0,z1,z2,z3,z4,z5,z6,z7,z8,z9,z10,z11,z12,z13,z14,z15}, {w20,w21,w22,w23}, ds5, pt, 1, 1, 0;\n"
        "wgmma.commit_group.sync.aligned;\n"
        "setp.eq.u32 pr, so, %7;\n"
        "@pr bra.uni DUTY;\n"
        "TOP:\n"
        ASM_TRC("n", 0)
        "wgmma.wait_group.sync.aligned 0;\n"
        "mov.b32 {xl, xh}, a2; tanh.approx.f16 xr, xh; cvt.u32.u16 hi0, xr; mul.rn.f16x2 a3, z31, p0; fma.rn.f16x2 p0, z0, z0, c; fma.rn.f16x2 q3, g0, g0, q3; fma.rn.f16x2 g0, z28, t0, z28; prmt.b32 t0, lo1, hi1, 0x5410; mov.b32 {xl, xh}, a2; tanh.approx.f16 xr, xl; cvt.u32.u16 lo0, xr;\n"
        "B31:\n"
        "mov.b32 {xl, xh}, a3; tanh.approx.f16 xr, xh; cvt.u32.u16 hi1, xr; mul.rn.f16x2 a0, z0, p0; fma.rn.f16x2 p0, z1, z1, c; fma.rn.f16x2 q2, g0, g0, q2; fma.rn.f16x2 g0, z29, t0, z29; prmt.b32 t0, lo0, hi0, 0x5410; mov.b32 {xl, xh}, a3; tanh.approx.f16 xr, xl; cvt.u32.u16 lo1, xr;\n"
        "B0:\n"
        "mov.b32 {xl, xh}, a0; tanh.approx.f16 xr, xh; cvt.u32.u16 hi0, xr; mul.rn.f16x2 a1, z1, p0; fma.rn.f16x2 p0, z2, z2, c; fma.rn.f16x2 q3, g0, g0, q3; fma.rn.f16x2 g0, z30, t0, z30; prmt.b32 t0, lo1, hi1, 0x5410; mov.b32 {xl, xh}, a0; tanh.approx.f16 xr, xl; cvt.u32.u16 lo0, xr;\n"
        "B1:\n"
        "mov.b32 {xl, xh}, a1; tanh.approx.f16 xr, xh; cvt.u32.u16 hi1, xr; mul.rn.f16x2 a2, z2, p0; fma.rn.f16x2 p0, z3, z3, c; fma.rn.f16x2 q2, g0, g0, q2; fma.rn.f16x2 g0, z31, t0, z31; prmt.b32 t0, lo0, hi0, 0x5410; mov.b32 {xl, xh}, a1; tanh.approx.f16 xr, xl; cvt.u32.u16 lo1, xr;\n"
        "B2:\n"
        "wgmma.fence.sync.aligned;\n"
        "wgmma.mma_async.sync.aligned.m64n64k16.f16.f16.f16 {z16,z17,z18,z19,z20,z21,z22,z23,z24,z25,z26,z27,z28,z29,z30,z31}, {w24,w25,w26,w27}, ds0, pf, 1, 1, 0;\n"
        "wgmma.mma_async.sync.aligned.m64n64k16.f16.f16.f16 {z16,z17,z18,z19,z20,z21,z22,z23,z24,z25,z26,z27,z28,z29,z30,z31}, {w28,w29,w30,w31}, ds1, pt, 1, 1, 0;\n"
        "wgmma.mma_async.sync.aligned.m64n64k16.f16.f16.f16 {z16,z17,z18,z19,z20,z21,z22,z23,z24,z25,z26,z27,z28,z29,z30,z31}, {w32,w33,w34,w35}, ds2, pt, 1, 1, 0;\n"
        "mov.b32 {xl, xh}, a2; tanh.approx.f16 xr, xh; cvt.u32.u16 hi0, xr; mul.rn.f16x2 a3, z3, p0; fma.rn.f16x2 p0, z4, z4, c; fma.rn.f16x2 q3, g0, g0, q3; fma.rn.f16x2 g0, z0, t0, z0; prmt.b32 t0, lo1, hi1, 0x5410; mov.b32 {xl, xh}, a2; tanh.approx.f16 xr, xl; cvt.u32.u16 lo0, xr;\n"
        "B3:\n"
        "mov.b32 {xl, xh}, a3; tanh.approx.f16 xr, xh; cvt.u32.u16 hi1, xr; mul.rn.f16x2 a0, z4, p0; fma.rn.f16x2 p0, z5, z5, c; fma.rn.f16x2 q0, g0, g0, q0; fma.rn.f16x2 g0, z1, t0, z1; prmt.b32 t0, lo0, hi0, 0x5410; mov.b32 {xl, xh}, a3; tanh.approx.f16 xr, xl; cvt.u32.u16 lo1, xr;\n"
        "B4:\n"
        "mov.b32 {xl, xh}, a0; tanh.approx.f16 xr, xh; cvt.u32.u16 hi0, xr; mul.rn.f16x2 a1, z5, p0; fma.rn.f16x2 p0, z6, z6, c; fma.rn.f16x2 q1, g0, g0, q1; fma.rn.f16x2 g0, z2, t0, z2; prmt.b32 t0, lo1, hi1, 0x5410; mov.b32 {xl, xh}, a0; tanh.approx.f16 xr, xl; cvt.u32.u16 lo0, xr;\n"
        "B5:\n"
        "wgmma.mma_async.sync.aligned.m64n64k16.f16.f16.f16 {z16,z17,z18,z19,z20,z21,z22,z23,z24,z25,z26,z27,z28,z29,z30,z31}, {w36,w37,w38,w39}, ds3, pt, 1, 1, 0;\n"
        "wgmma.mma_async.sync.aligned.m64n64k16.f16.f16.f16 {z16,z17,z18,z19,z20,z21,z22,z23,z24,z25,z26,z27,z28,z29,z30,z31}, {w40,w41,w42,w43}, ds4, pt, 1, 1, 0;\n"
        "wgmma.mma_async.sync.aligned.m64n64k16.f16.f16.f16 {z16,z17,z18,z19,z20,z21,z22,z23,z24,z25,z26,z27,z28,z29,z30,z31}, wd, ds5, pt, 1, 1, 1, 0;\n"
        "wgmma.commit_group.sync.aligned;\n"
        "mov.b32 {xl, xh}, a1; tanh.approx.f16 xr, xh; cvt.u32.u16 hi1, xr; mul.rn.f16x2 a2, z6, p0; fma.rn.f16x2 p0, z7, z7, c; fma.rn.f16x2 q0, g0, g0, q0; fma.rn.f16x2 g0, z3, t0, z3; prmt.b32 t0, lo0, hi0, 0x5410; mov.b32 {xl, xh}, a1; tanh.approx.f16 xr, xl; cvt.u32.u16 lo1, xr;\n"
        "B6:\n"
        "mov.u32 sp, so; add.u32 so, so, 26624; setp.eq.u32 pr, so, 79872; selp.u32 so, 0, so, pr; selp.u32 tt, 1, 0, pr; xor.b32 ph, ph, tt;\n"
        "mov.b32 {xl, xh}, a2; tanh.approx.f16 xr, xh; cvt.u32.u16 hi0, xr; mul.rn.f16x2 a3, z7, p0; fma.rn.f16x2 p0, z8, z8, c; fma.rn.f16x2 q1, g0, g0, q1; fma.rn.f16x2 g0, z4, t0, z4; prmt.b32 t0, lo1, hi1, 0x5410; mov.b32 {xl, xh}, a2; tanh.approx.f16 xr, xl; cvt.u32.u16 lo0, xr;\n"
        "B7:\n"
        "shr.u32 tt, so, 4;\n"
        "mov.b64 {dl0, dh0}, ds0; add.u32 dl0, tt, 74816; mov.b64 ds0, {dl0, dh0}; mov.b64 {dl0, dh0}, ds1; add.u32 dl0, tt, 74818; mov.b64 ds1, {dl0, dh0}; mov.b64 {dl0, dh0}, ds2; add.u32 dl0, tt, 74820; mov.b64 ds2, {dl0, dh0}; mov.b64 {dl0, dh0}, ds3; add.u32 dl0, tt, 74822; mov.b64 ds3, {dl0, dh0}; mov.b64 {dl0, dh0}, ds4; add.u32 dl0, tt, 75328; mov.b64 ds4, {dl0, dh0}; mov.b64 {dl0, dh0}, ds5; add.u32 dl0, tt, 75330; mov.b64 ds5, {dl0, dh0};\n"
        "mov.b32 {xl, xh}, a3; tanh.approx.f16 xr, xh; cvt.u32.u16 hi1, xr; mul.rn.f16x2 a0, z8, p0; fma.rn.f16x2 p0, z9, z9, c; fma.rn.f16x2 q0, g0, g0, q0; fma.rn.f16x2 g0, z5, t0, z5; prmt.b32 t0, lo0, hi0, 0x5410; mov.b32 {xl, xh}, a3; tanh.approx.f16 xr, xl; cvt.u32.u16 lo1, xr;\n"
        "B8:\n"
        "mov.b32 {xl, xh}, a0; tanh.approx.f16 xr, xh; cvt.u32.u16 hi0, xr; mul.rn.f16x2 a1, z9, p0; fma.rn.f16x2 p0, z10, z10, c; fma.rn.f16x2 q1, g0, g0, q1; fma.rn.f16x2 g0, z6, t0, z6; prmt.b32 t0, lo1, hi1, 0x5410; mov.b32 {xl, xh}, a0; tanh.approx.f16 xr, xl; cvt.u32.u16 lo0, xr;\n"
        "B9:\n"
        "mov.b32 {xl, xh}, a1; tanh.approx.f16 xr, xh; cvt.u32.u16 hi1, xr; mul.rn.f16x2 a2, z10, p0; fma.rn.f16x2 p0, z11, z11, c; fma.rn.f16x2 q0, g0, g0, q0; fma.rn.f16x2 g0, z7, t0, z7; prmt.b32 t0, lo0, hi0, 0x5410; mov.b32 {xl, xh}, a1; tanh.approx.f16 xr, xl; cvt.u32.u16 lo1, xr;\n"
        "B10:\n"
        "mov.b32 {xl, xh}, a2; tanh.approx.f16 xr, xh; cvt.u32.u16 hi0, xr; mul.rn.f16x2 a3, z11, p0; fma.rn.f16x2 p0, z12, z12, c; fma.rn.f16x2 q1, g0, g0, q1; fma.rn.f16x2 g0, z8, t0, z8; prmt.b32 t0, lo1, hi1, 0x5410; mov.b32 {xl, xh}, a2; tanh.approx.f16 xr, xl; cvt.u32.u16 lo0, xr;\n"
        "B11:\n"
        "mov.b32 {xl, xh}, a3; tanh.approx.f16 xr, xh; cvt.u32.u16 hi1, xr; mul.rn.f16x2 a0, z12, p0; fma.rn.f16x2 p0, z13, z13, c; fma.rn.f16x2 q0, g0, g0, q0; fma.rn.f16x2 g0, z9, t0, z9; prmt.b32 t0, lo0, hi0, 0x5410; mov.b32 {xl, xh}, a3; tanh.approx.f16 xr, xl; cvt.u32.u16 lo1, xr;\n"
        "B12:\n"
        "mov.b32 {xl, xh}, a0; tanh.approx.f16 xr, xh; cvt.u32.u16 hi0, xr; mul.rn.f16x2 a1, z13, p0; fma.rn.f16x2 p0, z14, z14, c; fma.rn.f16x2 q1, g0, g0, q1; fma.rn.f16x2 g0, z10, t0, z10; prmt.b32 t0, lo1, hi1, 0x5410; mov.b32 {xl, xh}, a0; tanh.approx.f16 xr, xl; cvt.u32.u16 lo0, xr;\n"
        "B13:\n"
        "mov.b32 {xl, xh}, a1; tanh.approx.f16 xr, xh; cvt.u32.u16 hi1, xr; mul.rn.f16x2 a2, z14, p0; fma.rn.f16x2 p0, z15, z15, c; fma.rn.f16x2 q0, g0, g0, q0; fma.rn.f16x2 g0, z11, t0, z11; prmt.b32 t0, lo0, hi0, 0x5410; mov.b32 {xl, xh}, a1; tanh.approx.f16 xr, xl; cvt.u32.u16 lo1, xr;\n"
        "B14:\n"
        "wgmma.wait_group.sync.aligned 0;\n"
        "cp.async.bulk.wait_group.read 0;\n"
        "@pl mbarrier.arrive.shared::cta.b64 _, [sp+174992];\n"
        "mov.b32 {xl, xh}, a2; tanh.approx.f16 xr, xh; cvt.u32.u16 hi0, xr; mul.rn.f16x2 a3, z15, p0; fma.rn.f16x2 p0, z16, z16, c; fma.rn.f16x2 q1, g0, g0, q1; fma.rn.f16x2 g0, z12, t0, z12; prmt.b32 t0, lo1, hi1, 0x5410; mov.b32 {xl, xh}, a2; tanh.approx.f16 xr, xl; cvt.u32.u16 lo0, xr;\n"
        "B15:\n"
        "mov.b32 {xl, xh}, a3; tanh.approx.f16 xr, xh; cvt.u32.u16 hi1, xr; mul.rn.f16x2 a0, z16, p0; fma.rn.f16x2 p0, z17, z17, c; fma.rn.f16x2 q0, g0, g0, q0; fma.rn.f16x2 g0, z13, t0, z13; prmt.b32 t0, lo0, hi0, 0x5410; mov.b32 {xl, xh}, a3; tanh.approx.f16 xr, xl; cvt.u32.u16 lo1, xr;\n"
        "B16:\n"
        "mbarrier.try_wait.parity.shared::cta.b64 pw, [so+174984], ph;\n"
        "mov.b32 {xl, xh}, a0; tanh.approx.f16 xr, xh; cvt.u32.u16 hi0, xr; mul.rn.f16x2 a1, z17, p0; fma.rn.f16x2 p0, z18, z18, c; fma.rn.f16x2 q1, g0, g0, q1; fma.rn.f16x2 g0, z14, t0, z14; prmt.b32 t0, lo1, hi1, 0x5410; mov.b32 {xl, xh}, a0; tanh.approx.f16 xr, xl; cvt.u32.u16 lo0, xr;\n"
        "B17:\n"
        "mov.b32 {xl, xh}, a1; tanh.approx.f16 xr, xh; cvt.u32.u16 hi1, xr; mul.rn.f16x2 a2, z18, p0; fma.rn.f16x2 p0, z19, z19, c; fma.rn.f16x2 q0, g0, g0, q0; fma.rn.f16x2 g0, z15, t0, z15; prmt.b32 t0, lo0, hi0, 0x5410; mov.b32 {xl, xh}, a1; tanh.approx.f16 xr, xl; cvt.u32.u16 lo1, xr;\n"
        "B18:\n"
        "@!pw bra.uni SPIN;\n"
        "BACK:\n"
        "wgmma.fence.sync.aligned;\n"
        "wgmma.mma_async.sync.aligned.m64n64k16.f16.f16.f16 {z0,z1,z2,z3,z4,z5,z6,z7,z8,z9,z10,z11,z12,z13,z14,z15}, {w0,w1,w2,w3}, ds0, pf, 1, 1, 0;\n"
        "wgmma.mma_async.sync.aligned.m64n64k16.f16.f16.f16 {z0,z1,z2,z3,z4,z5,z6,z7,z8,z9,z10,z11,z12,z13,z14,z15}, {w4,w5,w6,w7}, ds1, pt, 1, 1, 0;\n"
        "wgmma.mma_async.sync.aligned.m64n64k16.f16.f16.f16 {z0,z1,z2,z3,z4,z5,z6,z7,z8,z9,z10,z11,z12,z13,z14,z15}, {w8,w9,w10,w11}, ds2, pt, 1, 1, 0;\n"
        "mov.b32 {xl, xh}, a2; tanh.approx.f16 xr, xh; cvt.u32.u16 hi0, xr; mul.rn.f16x2 a3, z19, p0; fma.rn.f16x2 p0, z20, z20, c; fma.rn.f16x2 q1, g0, g0, q1; fma.rn.f16x2 g0, z16, t0, z16; prmt.b32 t0, lo1, hi1, 0x5410; mov.b32 {xl, xh}, a2; tanh.approx.f16 xr, xl; cvt.u32.u16 lo0, xr;\n"
        "B19:\n"
        "mov.b32 {xl, xh}, a3; tanh.approx.f16 xr, xh; cvt.u32.u16 hi1, xr; mul.rn.f16x2 a0, z20, p0; fma.rn.f16x2 p0, z21, z21, c; fma.rn.f16x2 q2, g0, g0, q2; fma.rn.f16x2 g0, z17, t0, z17; prmt.b32 t0, lo0, hi0, 0x5410; mov.b32 {xl, xh}, a3; tanh.approx.f16 xr, xl; cvt.u32.u16 lo1, xr;\n"
        "B20:\n"
        "mov.b32 {xl, xh}, a0; tanh.approx.f16 xr, xh; cvt.u32.u16 hi0, xr; mul.rn.f16x2 a1, z21, p0; fma.rn.f16x2 p0, z22, z22, c; fma.rn.f16x2 q3, g0, g0, q3; fma.rn.f16x2 g0, z18, t0, z18; prmt.b32 t0, lo1, hi1, 0x5410; mov.b32 {xl, xh}, a0; tanh.approx.f16 xr, xl; cvt.u32.u16 lo0, xr;\n"
        "B21:\n"
        "wgmma.mma_async.sync.aligned.m64n64k16.f16.f16.f16 {z0,z1,z2,z3,z4,z5,z6,z7,z8,z9,z10,z11,z12,z13,z14,z15}, {w12,w13,w14,w15}, ds3, pt, 1, 1, 0;\n"
        "wgmma.mma_async.sync.aligned.m64n64k16.f16.f16.f16 {z0,z1,z2,z3,z4,z5,z6,z7,z8,z9,z10,z11,z12,z13,z14,z15}, {w16,w17,w18,w19}, ds4, pt, 1, 1, 0;\n"
        "wgmma.mma_async.sync.aligned.m64n64k16.f16.f16.f16 {z0,z1,z2,z3,z4,z5,z6,z7,z8,z9,z10,z11,z12,z13,z14,z15}, {w20,w21,w22,w23}, ds5, pt, 1, 1, 0;\n"
        "wgmma.commit_group.sync.aligned;\n"
        "mov.b32 {xl, xh}, a1; tanh.approx.f16 xr, xh; cvt.u32.u16 hi1, xr; mul.rn.f16x2 a2, z22, p0; fma.rn.f16x2 p0, z23, z23, c; fma.rn.f16x2 q2, g0, g0, q2; fma.rn.f16x2 g0, z19, t0, z19; prmt.b32 t0, lo0, hi0, 0x5410; mov.b32 {xl, xh}, a1; tanh.approx.f16 xr, xl; cvt.u32.u16 lo1, xr;\n"
        "B22:\n"
        "mov.b32 {xl, xh}, a2; tanh.approx.f16 xr, xh; cvt.u32.u16 hi0, xr; mul.rn.f16x2 a3, z23, p0; fma.rn.f16x2 p0, z24, z24, c; fma.rn.f16x2 q3, g0, g0, q3; fma.rn.f16x2 g0, z20, t0, z20; prmt.b32 t0, lo1, hi1, 0x5410; mov.b32 {xl, xh}, a2; tanh.approx.f16 xr, xl; cvt.u32.u16 lo0, xr;\n"
        "B23:\n"
        "mov.b32 {xl, xh}, a3; tanh.approx.f16 xr, xh; cvt.u32.u16 hi1, xr; mul.rn.f16x2 a0, z24, p0; fma.rn.f16x2 p0, z25, z25, c; fma.rn.f16x2 q2, g0, g0, q2; fma.rn.f16x2 g0, z21, t0, z21; prmt.b32 t0, lo0, hi0, 0x5410; mov.b32 {xl, xh}, a3; tanh.approx.f16 xr, xl; cvt.u32.u16 lo1, xr;\n"
        "B24:\n"
        "mov.b32 {xl, xh}, a0; tanh.approx.f16 xr, xh; cvt.u32.u16 hi0, xr; mul.rn.f16x2 a1, z25, p0; fma.rn.f16x2 p0, z26, z26, c; fma.rn.f16x2 q3, g0, g0, q3; fma.rn.f16x2 g0, z22, t0, z22; prmt.b32 t0, lo1, hi1, 0x5410; mov.b32 {xl, xh}, a0; tanh.approx.f16 xr, xl; cvt.u32.u16 lo0, xr;\n"
        "B25:\n"
        "mov.b32 {xl, xh}, a1; tanh.approx.f16 xr, xh; cvt.u32.u16 hi1, xr; mul.rn.f16x2 a2, z26, p0; fma.rn.f16x2 p0, z27, z27, c; fma.rn.f16x2 q2, g0, g0, q2; fma.rn.f16x2 g0, z23, t0, z23; prmt.b32 t0, lo0, hi0, 0x5410; mov.b32 {xl, xh}, a1; tanh.approx.f16 xr, xl; cvt.u32.u16 lo1, xr;\n"
        "B26:\n"
        "mov.b32 {xl, xh}, a2; tanh.approx.f16 xr, xh; cvt.u32.u16 hi0, xr; mul.rn.f16x2 a3, z27, p0; fma.rn.f16x2 p0, z28, z28, c; fma.rn.f16x2 q3, g0, g0, q3; fma.rn.f16x2 g0, z24, t0, z24; prmt.b32 t0, lo1, hi1, 0x5410; mov.b32 {xl, xh}, a2; tanh.approx.f16 xr, xl; cvt.u32.u16 lo0, xr;\n"
        "B27:\n"
        "add.u32 n, n, 1; setp.lt.u32 pe, n, 32; setp.ne.and.u32 pe, so, %7, pe;\n"
        "mov.b32 {xl, xh}, a3; tanh.approx.f16 xr, xh; cvt.u32.u16 hi1, xr; mul.rn.f16x2 a0, z28, p0; fma.rn.f16x2 p0, z29, z29, c; fma.rn.f16x2 q2, g0, g0, q2; fma.rn.f16x2 g0, z25, t0, z25; prmt.b32 t0, lo0, hi0, 0x5410; mov.b32 {xl, xh}, a3; tanh.approx.f16 xr, xl; cvt.u32.u16 lo1, xr;\n"
        "B28:\n"
        "mov.b32 {xl, xh}, a0; tanh.approx.f16 xr, xh; cvt.u32.u16 hi0, xr; mul.rn.f16x2 a1, z29, p0; fma.rn.f16x2 p0, z30, z30, c; fma.rn.f16x2 q3, g0, g0, q3; fma.rn.f16x2 g0, z26, t0, z26; prmt.b32 t0, lo1, hi1, 0x5410; mov.b32 {xl, xh}, a0; tanh.approx.f16 xr, xl; cvt.u32.u16 lo0, xr;\n"
        "B29:\n"
        "mov.b32 {xl, xh}, a1; tanh.approx.f16 xr, xh; cvt.u32.u16 hi1, xr; mul.rn.f16x2 a2, z30, p0; fma.rn.f16x2 p0, z31, z31, c; fma.rn.f16x2 q2, g0, g0, q2; fma.rn.f16x2 g0, z27, t0, z27; prmt.b32 t0, lo0, hi0, 0x5410; mov.b32 {xl, xh}, a1; tanh.approx.f16 xr, xl; cvt.u32.u16 lo1, xr;\n"
        "@pe bra.uni TOP;\n"
        "setp.lt.u32 pe, n, 32;\n"
        "@pe bra.uni DUTY;\n"
        "bra.uni DONE;\n"
        "SPINW: mov.u32 cnt, 0;\n"
        "SPINWL:\n"
        "mov.u32 tt, 231232; mbarrier.try_wait.parity.shared::cta.b64 pw, [tt], 0;\n"
        "@pw bra.uni BACKW;\n"
        "add.u32 cnt, cnt, 1; setp.lt.u32 pw, cnt, 0x100000;\n"
        "@pw bra.uni SPINWL;\n"
        "trap;\n"
        "SPIN0: mov.u32 cnt, 0;\n"
        ASM_TRC("n", 1)
        "SPIN0L:\n"
        "mbarrier.try_wait.parity.shared::cta.b64 pw, [so+174984], ph;\n"
        "@pw bra.uni BACK0;\n"
        "add.u32 cnt, cnt, 1; setp.lt.u32 pw, cnt, 0x100000;\n"
        "@pw bra.uni SPIN0L;\n"
        "trap;\n"
        "SPIN: mov.u32 cnt, 0;\n"
        ASM_TRC("n", 1)
        "SPINL:\n"
        "mbarrier.try_wait.parity.shared::cta.b64 pw, [so+174984], ph;\n"
        "@pw bra.uni BACK;\n"
        "add.u32 cnt, cnt, 1; setp.lt.u32 pw, cnt, 0x100000;\n"
        "@pw bra.uni SPINL;\n"
        "trap;\n"
        "DUTY:\n"
        "setp.ge.s32 pr, n, %11;\n"
        "@pr bra.uni FLUSH;\n"
        "setp.ge.u32 pr, %13, 2;\n"
        "@pr bra.uni ROLE2;\n"
        "setp.ge.s32 pr, n, %12; selp.b64 src, %14, gp, pr; add.u32 tt, %7, 174976;\n"
        "elect.sync _|pr, 0xffffffff;\n"
        "@pr mbarrier.arrive.expect_tx.shared::cta.b64 _, [tt], %10;\n"
        "@pr cp.async.bulk.shared::cluster.global.mbarrier::complete_tx::bytes [%9], [src], %10, [tt];\n"
        "bra.uni FLUSH;\n"
        "ROLE2:\n"
        "setp.eq.u32 pr, %13, 3;\n"
        "@pr bra.uni ROLE3;\n"
        "setp.ne.s32 pr, n, 31;\n"
        "@pr bra.uni PARK;\n"
        "cp.async.bulk.wait_group 0;\n"
        "sub.s64 src, gp, %16; mov.u32 tt, 230824; mov.u32 cnt, 187392;\n"
        "elect.sync _|pr, 0xffffffff;\n"
        "@pr mbarrier.arrive.expect_tx.shared::cta.b64 _, [tt], 12288;\n"
        "@pr cp.async.bulk.shared::cluster.global.mbarrier::complete_tx::bytes [cnt], [src], 12288, [tt];\n"
        "PARK:\n"
        "elect.sync _|pr, 0xffffffff;\n"
        "@pr cp.async.bulk.global.shared::cta.bulk_group [gp], [%9], 12288;\n"
        "@pr cp.async.bulk.commit_group;\n"
        "bra.uni FLUSH;\n"
        "ROLE3:\n"
        "setp.ne.s32 pr, n, 8;\n"
        "@pr bra.uni AHEAD;\n"
        "mov.u32 tt, 230872;\n"
        "elect.sync _|pr, 0xffffffff;\n"
        "@pr mbarrier.arrive.expect_tx.shared::cta.b64 _, [tt], 75264;\n"
        "mov.u32 cnt, 229248; @pr cp.async.bulk.shared::cluster.global.mbarrier::complete_tx::bytes [cnt], [%18], 768, [tt];\n"
        "mov.u32 cnt, 230016; @pr cp.async.bulk.shared::cluster.global.mbarrier::complete_tx::bytes [cnt], [%19], 768, [tt];\n"
        "mov.u32 cnt, 74752; @pr cp.async.bulk.tensor.2d.shared::cluster.global.mbarrier::complete_tx::bytes [cnt], [%17, {0, 0}], [tt];\n"
        "mov.u32 cnt, 87040; @pr cp.async.bulk.tensor.2d.shared::cluster.global.mbarrier::complete_tx::bytes [cnt], [%17, {0, 192}], [tt];\n"
        "mov.u32 cnt, 99328; @pr cp.async.bulk.tensor.2d.shared::cluster.global.mbarrier::complete_tx::bytes [cnt], [%17, {32, 0}], [tt];\n"
        "mov.u32 cnt, 111616; @pr cp.async.bulk.tensor.2d.shared::cluster.global.mbarrier::complete_tx::bytes [cnt], [%17, {32, 192}], [tt];\n"
        "mov.u32 cnt, 123904; @pr cp.async.bulk.tensor.2d.shared::cluster.global.mbarrier::complete_tx::bytes [cnt], [%17, {64, 0}], [tt];\n"
        "mov.u32 cnt, 136192; @pr cp.async.bulk.tensor.2d.shared::cluster.global.mbarrier::complete_tx::bytes [cnt], [%17, {64, 192}], [tt];\n"
        "AHEAD:\n"
        "elect.sync _|pr, 0xffffffff;\n"
        "@pr cp.async.bulk.prefetch.L2.global [gp], 12288;\n"
        "FLUSH:\n"
        "add.s64 gp, gp, %16;\n"
        "mov.b32 {xl, xh}, q0; cvt.f32.f16 f0, xl; cvt.f32.f16 f1, xh; add.f32 f0, f0, f1; add.f32 %0, %0, f0; mov.b32 q0, 0;\n"
        "mov.b32 {xl, xh}, q1; cvt.f32.f16 f0, xl; cvt.f32.f16 f1, xh; add.f32 f0, f0, f1; add.f32 %1, %1, f0; mov.b32 q1, 0;\n"
        "mov.b32 {xl, xh}, q2; cvt.f32.f16 f0, xl; cvt.f32.f16 f1, xh; add.f32 f0, f0, f1; add.f32 %2, %2, f0; mov.b32 q2, 0;\n"
        "mov.b32 {xl, xh}, q3; cvt.f32.f16 f0, xl; cvt.f32.f16 f1, xh; add.f32 f0, f0, f1; add.f32 %3, %3, f0; mov.b32 q3, 0;\n"
        "setp.ne.u32 pr, %5, 0;\n"
        "@pr bra.uni TOP;\n"
        "wgmma.wait_group.sync.aligned 0;\n"
        "wgmma.fence.sync.aligned;\n"
        "ld.volatile.shared.v2.b32 {lo0, hi0}, [so]; setp.eq.u32 pr, lo0, hi0; vote.sync.any.pred pr, pr, 0xffffffff; @pr bra.uni B0;\n"
        "ld.volatile.shared.v2.b32 {lo1, hi1}, [so]; setp.eq.u32 pr, lo1, hi1; vote.sync.any.pred pr, pr, 0xffffffff; @pr bra.uni B0;\n"
        "ld.volatile.shared.v2.b32 {q1, a0}, [so]; setp.eq.u32 pr, q1, a0; vote.sync.any.pred pr, pr, 0xffffffff; @pr bra.uni B0;\n"
        "ld.volatile.shared.v2.b32 {q2, a1}, [so]; setp.eq.u32 pr, q2, a1; vote.sync.any.pred pr, pr, 0xffffffff; @pr bra.uni B0;\n"
        "ld.volatile.shared.v2.b32 {q3, a2}, [so]; setp.eq.u32 pr, q3, a2; vote.sync.any.pred pr, pr, 0xffffffff; @pr bra.uni B0;\n"
        "ld.volatile.shared.v2.b32 {q0, a3}, [so]; setp.eq.u32 pr, q0, a3; vote.sync.any.pred pr, pr, 0xffffffff; @pr bra.uni B0;\n"
        "ld.volatile.shared.v2.b32 {t0, g0}, [so]; setp.eq.u32 pr, t0, g0; vote.sync.any.pred pr, pr, 0xffffffff; @pr bra.uni B0;\n"
        "setp.eq.u32 pr, n, 1000; @pr bra.uni B31;\n"
        "setp.eq.u32 pr, n, 1001; @pr bra.uni B0;\n"
        "setp.eq.u32 pr, n, 1002; @pr bra.uni B1;\n"
        "setp.eq.u32 pr, n, 1003; @pr bra.uni B2;\n"
        "setp.eq.u32 pr, n, 1004; @pr bra.uni B3;\n"
        "setp.eq.u32 pr, n, 1005; @pr bra.uni B4;\n"
        "setp.eq.u32 pr, n, 1006; @pr bra.uni B5;\n"
        "setp.eq.u32 pr, n, 1007; @pr bra.uni B6;\n"
        "setp.eq.u32 pr, n, 1008; @pr bra.uni B7;\n"
        "setp.eq.u32 pr, n, 1009; @pr bra.uni B8;\n"
        "setp.eq.u32 pr, n, 1010; @pr bra.uni B9;\n"
        "setp.eq.u32 pr, n, 1011; @pr bra.uni B10;\n"
        "setp.eq.u32 pr, n, 1012; @pr bra.uni B11;\n"
        "setp.eq.u32 pr, n, 1013; @pr bra.uni B12;\n"
        "setp.eq.u32 pr, n, 1014; @pr bra.uni B13;\n"
        "setp.eq.u32 pr, n, 1015; @pr bra.uni B14;\n"
        "setp.eq.u32 pr, n, 1016; @pr bra.uni B15;\n"
        "setp.eq.u32 pr, n, 1017; @pr bra.uni B16;\n"
        "setp.eq.u32 pr, n, 1018; @pr bra.uni B17;\n"
        "setp.eq.u32 pr, n, 1019; @pr bra.uni B18;\n"
        "setp.eq.u32 pr, n, 1020; @pr bra.uni B19;\n"
        "setp.eq.u32 pr, n, 1021; @pr bra.uni B20;\n"
        "setp.eq.u32 pr, n, 1022; @pr bra.uni B21;\n"
        "setp.eq.u32 pr, n, 1023; @pr bra.uni B22;\n"
        "setp.eq.u32 pr, n, 1024; @pr bra.uni B23;\n"
        "setp.eq.u32 pr, n, 1025; @pr bra.uni B24;\n"
        "setp.eq.u32 pr, n, 1026; @pr bra.uni B25;\n"
        "setp.eq.u32 pr, n, 1027; @pr bra.uni B26;\n"
        "setp.eq.u32 pr, n, 1028; @pr bra.uni B27;\n"
        "setp.eq.u32 pr, n, 1029; @pr bra.uni B28;\n"
        "setp.eq.u32 pr, n, 1030; @pr bra.uni B29;\n"
        "trap;\n"
        "DONE:\n"
        ASM_TRC("n", 0)
        "mov.b32 {xl, xh}, a2; tanh.approx.f16 xr, xh; cvt.u32.u16 hi0, xr; mul.rn.f16x2 a3, z31, p0; fma.rn.f16x2 q3, g0, g0, q3; fma.rn.f16x2 g0, z28, t0, z28; prmt.b32 t0, lo1, hi1, 0x5410; mov.b32 {xl, xh}, a2; tanh.approx.f16 xr, xl; cvt.u32.u16 lo0, xr;\n"
        "mov.b32 {xl, xh}, a3; tanh.approx.f16 xr, xh; cvt.u32.u16 hi1, xr; fma.rn.f16x2 q2, g0, g0, q2; fma.rn.f16x2 g0, z29, t0, z29; prmt.b32 t0, lo0, hi0, 0x5410; mov.b32 {xl, xh}, a3; tanh.approx.f16 xr, xl; cvt.u32.u16 lo1, xr;\n"
        "fma.rn.f16x2 q3, g0, g0, q3; fma.rn.f16x2 g0, z30, t0, z30; prmt.b32 t0, lo1, hi1, 0x5410;\n"
        "fma.rn.f16x2 q2, g0, g0, q2; fma.rn.f16x2 g0, z31, t0, z31;\n"
        "fma.rn.f16x2 q3, g0, g0, q3;\n"
        "mov.b32 {xl, xh}, q0; cvt.f32.f16 f0, xl; cvt.f32.f16 f1, xh; add.f32 f0, f0, f1; add.f32 %0, %0, f0; mov.b32 q0, 0;\n"
        "mov.b32 {xl, xh}, q1; cvt.f32.f16 f0, xl; cvt.f32.f16 f1, xh; add.f32 f0, f0, f1; add.f32 %1, %1, f0; mov.b32 q1, 0;\n"
        "mov.b32 {xl, xh}, q2; cvt.f32.f16 f0, xl; cvt.f32.f16 f1, xh; add.f32 f0, f0, f1; add.f32 %2, %2, f0; mov.b32 q2, 0;\n"
        "mov.b32 {xl, xh}, q3; cvt.f32.f16 f0, xl; cvt.f32.f16 f1, xh; add.f32 f0, f0, f1; add.f32 %3, %3, f0; mov.b32 q3, 0;\n"
        "wgmma.wait_group.sync.aligned 0;\n"
        "}\n"
        : "=f"(acc[0][0]), "=f"(acc[0][1]), "=f"(acc[1][0]), "=f"(acc[1][1])
        : "r"(w1t), "r"(yd), "r"(wd), "r"(own_slot), "l"(d.g), "r"(d.s), "r"(d.bytes), "r"(d.end), "r"(d.zero), "r"(role),
          "l"(d.zeros), "r"(lane), "l"(d.step), "l"(&prm.w2_map), "l"(prm.gamma), "l"(prm.beta), "l"(prm.ydesc64[0]), "l"(prm.ydesc64[1])
        : "memory");
}
template <int M, bool LAST_SMEM = true>
__device__ __forceinline__ void gemm1_t(uint32_t (&d)[16], const uint32_t* wa, uint32_t yd, uint32_t wd) {
    wg_fence();
    wgmma_n64_h_set<0>(d, wa, desc<1024, 1>(yd, 0));
#pragma unroll
    for (int kk = 1; kk < (LAST_SMEM ? 5 : 6); kk++)
        wgmma_n64_h_acc<0>(d, wa + kk * 4, kk < 4 ? desc<1024, 1>(yd, kk * 32) : desc<512, 2>(yd, 8192 + (kk - 4) * 32));
    if (LAST_SMEM) wgmma_n64_h_acc_ss(d, desc<1024, 1>(wd, M * 12288), desc<512, 2>(yd, 8192 + 32));
    wg_commit();
}

__device__ __forceinline__ void gelu_sumsq_f(const uint32_t (&d)[16], float (&acc)[2]) {
#pragma unroll
    for (int r = 0; r < 16; r++) {
        float lo, hi;
        h2_unpack(gelu2(d[r]), lo, hi);
        acc[r & 1] = fmaf(lo, lo, acc[r & 1]);
        acc[r & 1] = fmaf(hi, hi, acc[r & 1]);
    }
}
__device__ __forceinline__ void load_w1t(uint32_t (&wa)[2][24], int wg, int w, int lane) {
#pragma unroll
    for (int m = 0; m < 2; m++)
#pragma unroll
        for (int kk = 0; kk < 5; kk++) {
            const int q = lane >> 3, c = 16 * kk + 8 * (q >> 1) + (lane & 7), ck = 2 * w + (q & 1);
            ldsm4_t(wa[m] + kk * 4, sb + SM_W1 + (2 * wg + m) * 12288 + c * 128 + ((ck ^ (c & 7)) * 16));
        }
}
__device__ __forceinline__ unsigned long long* acc_word(const Params& prm, uint32_t epoch, uint32_t e) {
    return &prm.g->acc[epoch & 1][(e >> 2) * 32 + (e & 3)];
}
__device__ __forceinline__ void publish_fast(const Params& prm, const float (&acc)[2][2], uint32_t epoch, int wg, int w, int lane) {
    const bool m = lane & 2, h = lane & 1;
    const float a = (m ? acc[1][0] : acc[0][0]) + __shfl_xor_sync(0xffffffffu, m ? acc[0][0] : acc[1][0], 2);
    const float b = (m ? acc[1][1] : acc[0][1]) + __shfl_xor_sync(0xffffffffu, m ? acc[0][1] : acc[1][1], 2);
    const float v = (h ? b : a) + __shfl_xor_sync(0xffffffffu, h ? a : b, 1);
    const unsigned long long q = (__float2ull_rn(fminf(v, ACC_LIMIT) * 0x1p16f) << 8) + 1;
    asm volatile("red.relaxed.gpu.global.add.u64 [%0], %1;"
                 ::"l"(acc_word(prm, epoch, 128 * wg + 32 * (lane & 2) + 16 * w + (lane >> 2) + 8 * (lane & 1))), "l"(q) : "memory");
}
__device__ __forceinline__ float collect_fast(const unsigned long long* word) {
    unsigned long long v;
    asm volatile(
        "{\n.reg .pred p;\n.reg .u32 n, lo, hi;\nmov.u32 n, 0;\n"
        "POLL:\nld.relaxed.gpu.global.u64 %0, [%1];\nmov.b64 {lo, hi}, %0;\nand.b32 lo, lo, 255;\n"
        "setp.eq.u32 p, lo, %2;\nvote.sync.all.pred p, p, 0xffffffff;\n@p bra.uni POLL_DONE;\n"
        "add.u32 n, n, 1;\nsetp.lt.u32 p, n, 0x400000;\n@p bra.uni POLL;\ntrap;\nPOLL_DONE:\n}\n"
        : "=l"(v) : "l"(word), "n"(NUM_CTAS) : "memory");
    return __ull2float_rn(v >> 8) * 0x1p-16f;
}
__device__ __forceinline__ void publish_sums(const float (&acc)[2][2], float* sums, unsigned int* counter, int wg, int w, int lane) {
#pragma unroll
    for (int m = 0; m < 2; m++)
#pragma unroll
        for (int h = 0; h < 2; h++) {
            const float v = quad_sum(acc[m][h]);
            if ((lane & 3) == 0) atomicAdd(sums + 64 * (2 * wg + m) + 16 * w + (lane >> 2) + 8 * h, v);
        }
    named_sync(1, 384);
    if (fresh_tid() == 0) asm volatile("red.release.gpu.global.add.u32 [%0], 1;" ::"l"(counter) : "memory");
}
__device__ __forceinline__ void grid_wait(const unsigned int* counter, unsigned int target) {
    if (fresh_tid() == 0) {
        unsigned int v, spins = 0;
        do {
            asm volatile("ld.acquire.gpu.global.u32 %0, [%1];" : "=r"(v) : "l"(counter) : "memory");
            if (++spins > (1u << 22)) __trap();
        } while ((int)(v - target) < 0);
    }
    __syncthreads();
}

struct Pass2 {
    uint32_t wg;
    uint32_t off;
    int step;
    uint32_t xs;
    uint32_t a_offs, xs_offs, bias_addr;
    uint32_t w;
};

static_assert(sb + SM_BAR + BAR_ROWS * 8 == 231208 && BAR_STAT == BAR_ROWS + 2 && sb + SM_RED + RED_SCALE * 4 == 230792, "layout");
static_assert(sb + SM_BAR + BAR_Y2FULL * 8 == 230800 && sb + SM_BAR + BAR_XSFULL * 8 == 230832, "layout");
#define PASS2_STATE ".reg .b32 qa<24>, qz<32>, o<24>, g<16>, p<2>, a<4>, lo<2>, hi<2>, h<2>, osc;"
__device__ __forceinline__ void pass2_start(const Pass2& c, const Params& prm) {
    asm volatile(
        "{\n"
        ".reg .b32 t<2>, c, tt, ad, cnt, ybar;\n"
        ".reg .b16 xl, xh, xr;\n"
        ".reg .b64 w1d, dt;\n"
        ".reg .pred pt, pf, pw;\n"
        "setp.ne.b32 pt, 1, 0; setp.ne.b32 pf, 0, 0; mov.b32 c, 0x40D940D9; mov.b64 w1d, {%1, 0x40000040}; mad.lo.u32 ybar, %2, 8, 230800;\n"
        "mbarrier.try_wait.parity.shared::cta.b64 pw, [ybar], 0;\n"
        "@!pw bra.uni SPINY0;\n"
        "BACKY0:\n"
        "and.b32 t0, %5, 0xffff; shr.u32 t1, %5, 16;\n"
        "xor.b32 ad, t0, 0; add.u32 ad, ad, %4; ldmatrix.sync.aligned.m8n8.x4.shared.b16 {qa0,qa1,qa2,qa3}, [ad];\n"
        "xor.b32 ad, t0, 32; add.u32 ad, ad, %4; ldmatrix.sync.aligned.m8n8.x4.shared.b16 {qa4,qa5,qa6,qa7}, [ad];\n"
        "xor.b32 ad, t0, 64; add.u32 ad, ad, %4; ldmatrix.sync.aligned.m8n8.x4.shared.b16 {qa8,qa9,qa10,qa11}, [ad];\n"
        "xor.b32 ad, t0, 96; add.u32 ad, ad, %4; ldmatrix.sync.aligned.m8n8.x4.shared.b16 {qa12,qa13,qa14,qa15}, [ad];\n"
        "xor.b32 ad, t1, 0; add.u32 ad, ad, %4; ldmatrix.sync.aligned.m8n8.x4.shared.b16 {qa16,qa17,qa18,qa19}, [ad];\n"
        "xor.b32 ad, t1, 32; add.u32 ad, ad, %4; ldmatrix.sync.aligned.m8n8.x4.shared.b16 {qa20,qa21,qa22,qa23}, [ad];\n"
        "wgmma.fence.sync.aligned;\n"
        "add.s64 dt, w1d, 0; wgmma.mma_async.sync.aligned.m64n64k16.f16.f16.f16 {qz0,qz1,qz2,qz3,qz4,qz5,qz6,qz7,qz8,qz9,qz10,qz11,qz12,qz13,qz14,qz15}, {qa0,qa1,qa2,qa3}, dt, pf, 1, 1, 1;\n"
        "add.s64 dt, w1d, 128; wgmma.mma_async.sync.aligned.m64n64k16.f16.f16.f16 {qz0,qz1,qz2,qz3,qz4,qz5,qz6,qz7,qz8,qz9,qz10,qz11,qz12,qz13,qz14,qz15}, {qa4,qa5,qa6,qa7}, dt, pt, 1, 1, 1;\n"
        "add.s64 dt, w1d, 256; wgmma.mma_async.sync.aligned.m64n64k16.f16.f16.f16 {qz0,qz1,qz2,qz3,qz4,qz5,qz6,qz7,qz8,qz9,qz10,qz11,qz12,qz13,qz14,qz15}, {qa8,qa9,qa10,qa11}, dt, pt, 1, 1, 1;\n"
        "add.s64 dt, w1d, 384; wgmma.mma_async.sync.aligned.m64n64k16.f16.f16.f16 {qz0,qz1,qz2,qz3,qz4,qz5,qz6,qz7,qz8,qz9,qz10,qz11,qz12,qz13,qz14,qz15}, {qa12,qa13,qa14,qa15}, dt, pt, 1, 1, 1;\n"
        "add.s64 dt, w1d, 512; wgmma.mma_async.sync.aligned.m64n64k16.f16.f16.f16 {qz0,qz1,qz2,qz3,qz4,qz5,qz6,qz7,qz8,qz9,qz10,qz11,qz12,qz13,qz14,qz15}, {qa16,qa17,qa18,qa19}, dt, pt, 1, 1, 1;\n"
        "add.s64 dt, w1d, 640; wgmma.mma_async.sync.aligned.m64n64k16.f16.f16.f16 {qz0,qz1,qz2,qz3,qz4,qz5,qz6,qz7,qz8,qz9,qz10,qz11,qz12,qz13,qz14,qz15}, {qa20,qa21,qa22,qa23}, dt, pt, 1, 1, 1;\n"
        "wgmma.commit_group.sync.aligned;\n"
        "wgmma.wait_group.sync.aligned 0;\n"
        "fma.rn.f16x2 p0, qz0, qz0, c;\n"
        "mul.rn.f16x2 a0, qz0, p0; fma.rn.f16x2 p1, qz1, qz1, c;\n"
        "mov.b32 {xl, xh}, a0; tanh.approx.f16 xr, xl; cvt.u32.u16 lo0, xr; tanh.approx.f16 xr, xh; cvt.u32.u16 hi0, xr; mul.rn.f16x2 a1, qz1, p1; fma.rn.f16x2 p0, qz2, qz2, c;\n"
        "mov.b32 {xl, xh}, a1; tanh.approx.f16 xr, xl; cvt.u32.u16 lo1, xr; tanh.approx.f16 xr, xh; cvt.u32.u16 hi1, xr; mul.rn.f16x2 a0, qz2, p0; fma.rn.f16x2 p1, qz3, qz3, c; prmt.b32 h0, lo0, hi0, 0x5410;\n"
        "mov.b32 {xl, xh}, a0; tanh.approx.f16 xr, xl; cvt.u32.u16 lo0, xr; tanh.approx.f16 xr, xh; cvt.u32.u16 hi0, xr; mul.rn.f16x2 a1, qz3, p1; fma.rn.f16x2 p0, qz4, qz4, c; fma.rn.f16x2 g0, qz0, h0, qz0; prmt.b32 h1, lo1, hi1, 0x5410;\n"
        "mov.b32 {xl, xh}, a1; tanh.approx.f16 xr, xl; cvt.u32.u16 lo1, xr; tanh.approx.f16 xr, xh; cvt.u32.u16 hi1, xr; mul.rn.f16x2 a0, qz4, p0; fma.rn.f16x2 p1, qz5, qz5, c; fma.rn.f16x2 g1, qz1, h1, qz1; prmt.b32 h0, lo0, hi0, 0x5410;\n"
        "mov.b32 {xl, xh}, a0; tanh.approx.f16 xr, xl; cvt.u32.u16 lo0, xr; tanh.approx.f16 xr, xh; cvt.u32.u16 hi0, xr; mul.rn.f16x2 a1, qz5, p1; fma.rn.f16x2 p0, qz6, qz6, c; fma.rn.f16x2 g2, qz2, h0, qz2; prmt.b32 h1, lo1, hi1, 0x5410;\n"
        "mov.b32 {xl, xh}, a1; tanh.approx.f16 xr, xl; cvt.u32.u16 lo1, xr; tanh.approx.f16 xr, xh; cvt.u32.u16 hi1, xr; mul.rn.f16x2 a0, qz6, p0; fma.rn.f16x2 p1, qz7, qz7, c; fma.rn.f16x2 g3, qz3, h1, qz3; prmt.b32 h0, lo0, hi0, 0x5410;\n"
        "bra.uni DONE;\n"
        "SPINY0: mov.u32 cnt, 0;\n"
        "SPINY0L:\n"
        "mbarrier.try_wait.parity.shared::cta.b64 pw, [ybar], 0;\n"
        "@pw bra.uni BACKY0;\n"
        "add.u32 cnt, cnt, 1; setp.lt.u32 pw, cnt, 0x100000;\n"
        "@pw bra.uni SPINY0L;\n"
        "trap;\n"
        "DONE:\n"
        "}\n"
        :: "n"(0), "r"(prm.w1desc), "r"(c.wg), "n"(0), "r"(c.xs), "r"(c.a_offs) : "memory");
}
__device__ __forceinline__ bool pass2_head(const Pass2& c, uint32_t round) {
    uint32_t retry;
    asm volatile(
        "{\n"
        ".reg .b32 t<2>, tt, ad, cnt;\n"
        ".reg .pred pw;\n"
        "and.b32 t0, %3, 0xffff; shr.u32 t1, %3, 16;\n"
        "xor.b32 ad, t0, 0; add.u32 ad, ad, %4; ldmatrix.sync.aligned.m8n8.x4.shared.b16 {qa0,qa1,qa2,qa3}, [ad];\n"
        "xor.b32 ad, t0, 32; add.u32 ad, ad, %4; ldmatrix.sync.aligned.m8n8.x4.shared.b16 {qa4,qa5,qa6,qa7}, [ad];\n"
        "xor.b32 ad, t0, 64; add.u32 ad, ad, %4; ldmatrix.sync.aligned.m8n8.x4.shared.b16 {qa8,qa9,qa10,qa11}, [ad];\n"
        "xor.b32 ad, t0, 96; add.u32 ad, ad, %4; ldmatrix.sync.aligned.m8n8.x4.shared.b16 {qa12,qa13,qa14,qa15}, [ad];\n"
        "xor.b32 ad, t1, 0; add.u32 ad, ad, %4; ldmatrix.sync.aligned.m8n8.x4.shared.b16 {qa16,qa17,qa18,qa19}, [ad];\n"
        "xor.b32 ad, t1, 32; add.u32 ad, ad, %4; ldmatrix.sync.aligned.m8n8.x4.shared.b16 {qa20,qa21,qa22,qa23}, [ad];\n"
        "mov.b32 qz16, 0; mov.b32 qz17, 0; mov.b32 qz18, 0; mov.b32 qz19, 0; mov.b32 qz20, 0; mov.b32 qz21, 0; mov.b32 qz22, 0; mov.b32 qz23, 0; mov.b32 qz24, 0; mov.b32 qz25, 0; mov.b32 qz26, 0; mov.b32 qz27, 0; mov.b32 qz28, 0; mov.b32 qz29, 0; mov.b32 qz30, 0; mov.b32 qz31, 0;\n"
        "mov.b32 g4, 0; mov.b32 g5, 0; mov.b32 g6, 0; mov.b32 g7, 0; mov.b32 g8, 0; mov.b32 g9, 0; mov.b32 g10, 0; mov.b32 g11, 0; mov.b32 g12, 0; mov.b32 g13, 0; mov.b32 g14, 0; mov.b32 g15, 0;\n"
        "mov.u32 tt, 231224; mbarrier.try_wait.parity.shared::cta.b64 pw, [tt], %1;\n"
        "@!pw bra.uni SPINR;\n"
        "BACKR:\n"
        "mov.u32 tt, 230792; ld.shared.v2.b32 {osc, %0}, [tt];\n"
        "ld.shared.v4.b32 {o0,o1,o2,o3}, [%2+0];\n"
        "ld.shared.v4.b32 {o4,o5,o6,o7}, [%2+64];\n"
        "ld.shared.v4.b32 {o8,o9,o10,o11}, [%2+128];\n"
        "ld.shared.v4.b32 {o12,o13,o14,o15}, [%2+192];\n"
        "ld.shared.v4.b32 {o16,o17,o18,o19}, [%2+256];\n"
        "ld.shared.v4.b32 {o20,o21,o22,o23}, [%2+320];\n"
        "bra.uni DONE;\n"
        "SPINR: mov.u32 cnt, 0;\n"
        "SPINRL:\n"
        "mov.u32 tt, 231224; mbarrier.try_wait.parity.shared::cta.b64 pw, [tt], %1;\n"
        "@pw bra.uni BACKR;\n"
        "add.u32 cnt, cnt, 1; setp.lt.u32 pw, cnt, 0x100000;\n"
        "@pw bra.uni SPINRL;\n"
        "trap;\n"
        "DONE:\n"
        "}\n"
        : "=r"(retry)
        : "r"(round), "r"(c.bias_addr), "r"(c.a_offs), "r"(c.xs)
        : "memory");
    return __any_sync(0xffffffffu, retry);
}
__device__ __forceinline__ void pass2_tiles(const Pass2& c, const Params& prm) {
    asm volatile(
        "{\n"
        ".reg .b32 v<8>, n, off, c, tt, ad, cnt, ybar, xbar, tbar, tpar, id;\n"
        ".reg .b16 xl, xh, xr;\n"
        ".reg .f32 f0, f1;\n"
        ".reg .b64 w1d, w2d, dt, gp, pol;\n"
        ".reg .pred pt, pf, pr, pw, pl, pk, pm, pz, pn;\n"
        "setp.ne.b32 pt, 1, 0; setp.ne.b32 pf, 0, 0; setp.eq.u32 pl, %9, 0; setp.eq.u32 pk, %9, 0; setp.eq.u32 pz, %0, 0;\n"
        "mov.b32 c, 0x40D940D9;\n"
        "mov.b64 w1d, {%0, 0x40000040}; mov.b64 w2d, {%1, 0x80000020};\n"
        "mad.lo.u32 ybar, %2, 8, 230800; mad.lo.u32 xbar, %2, 8, 230832; add.u32 id, %2, 2;\n"
        "xor.b32 tt, %2, 0; mad.lo.u32 tbar, tt, 64, 230888; setp.eq.u32 pr, tt, 0; selp.u32 tpar, 1, 0, pr; mov.u32 tt, %laneid; setp.eq.u32 pn, tt, 0;\n"
        "mov.u32 n, -1; add.u32 off, %3, %8; mov.pred pm, pt; mov.b64 pol, 0x12F0000000000000;\n"
        "mov.b32 v0, 0; mov.b32 v1, 0; mov.b32 v2, 0; mov.b32 v3, 0; mov.b32 v4, 0; mov.b32 v5, 0; mov.b32 v6, 0; mov.b32 v7, 0;\n"
        "LOOP:\n"
        "@!pm bra.uni SKIP0;\n"
        "wgmma.fence.sync.aligned;\n"
        "add.s64 dt, w1d, 768; wgmma.mma_async.sync.aligned.m64n64k16.f16.f16.f16 {qz16,qz17,qz18,qz19,qz20,qz21,qz22,qz23,qz24,qz25,qz26,qz27,qz28,qz29,qz30,qz31}, {qa0,qa1,qa2,qa3}, dt, pf, 1, 1, 1;\n"
        "add.s64 dt, w1d, 896; wgmma.mma_async.sync.aligned.m64n64k16.f16.f16.f16 {qz16,qz17,qz18,qz19,qz20,qz21,qz22,qz23,qz24,qz25,qz26,qz27,qz28,qz29,qz30,qz31}, {qa4,qa5,qa6,qa7}, dt, pt, 1, 1, 1;\n"
        "add.s64 dt, w1d, 1024; wgmma.mma_async.sync.aligned.m64n64k16.f16.f16.f16 {qz16,qz17,qz18,qz19,qz20,qz21,qz22,qz23,qz24,qz25,qz26,qz27,qz28,qz29,qz30,qz31}, {qa8,qa9,qa10,qa11}, dt, pt, 1, 1, 1;\n"
        "add.s64 dt, w1d, 1152; wgmma.mma_async.sync.aligned.m64n64k16.f16.f16.f16 {qz16,qz17,qz18,qz19,qz20,qz21,qz22,qz23,qz24,qz25,qz26,qz27,qz28,qz29,qz30,qz31}, {qa12,qa13,qa14,qa15}, dt, pt, 1, 1, 1;\n"
        "add.s64 dt, w1d, 1280; wgmma.mma_async.sync.aligned.m64n64k16.f16.f16.f16 {qz16,qz17,qz18,qz19,qz20,qz21,qz22,qz23,qz24,qz25,qz26,qz27,qz28,qz29,qz30,qz31}, {qa16,qa17,qa18,qa19}, dt, pt, 1, 1, 1;\n"
        "add.s64 dt, w1d, 1408; wgmma.mma_async.sync.aligned.m64n64k16.f16.f16.f16 {qz16,qz17,qz18,qz19,qz20,qz21,qz22,qz23,qz24,qz25,qz26,qz27,qz28,qz29,qz30,qz31}, {qa20,qa21,qa22,qa23}, dt, pt, 1, 1, 1;\n"
        "SKIP0:\n"
        "wgmma.fence.sync.aligned;\n"
        "wgmma.commit_group.sync.aligned;\n"
        "setp.lt.s32 pr, n, 0;\n"
        "@pr bra.uni FIRST;\n"
        "and.b32 tt, n, 1; mbarrier.try_wait.parity.shared::cta.b64 pw, [xbar], tt;\n"
        "@!pw bra.uni SPINX;\n"
        "BACKX:\n"
        "and.b32 ad, %6, 0xffff; add.u32 ad, ad, %4; ld.shared.v4.b32 {v0,v1,v2,v3}, [ad+0];\n"
        "shr.u32 ad, %6, 16; add.u32 ad, ad, %4; ld.shared.v4.b32 {v4,v5,v6,v7}, [ad+0];\n"
        "mov.b32 {xl, xh}, o0; cvt.f32.f16 f0, xl; cvt.f32.f16 f1, xh; cvt.rn.bf16x2.f32 tt, f1, f0; fma.rn.bf16x2 v0, tt, osc, v0;\n"
        "mov.b32 {xl, xh}, o2; cvt.f32.f16 f0, xl; cvt.f32.f16 f1, xh; cvt.rn.bf16x2.f32 tt, f1, f0; fma.rn.bf16x2 v1, tt, osc, v1;\n"
        "mov.b32 {xl, xh}, o4; cvt.f32.f16 f0, xl; cvt.f32.f16 f1, xh; cvt.rn.bf16x2.f32 tt, f1, f0; fma.rn.bf16x2 v2, tt, osc, v2;\n"
        "mov.b32 {xl, xh}, o6; cvt.f32.f16 f0, xl; cvt.f32.f16 f1, xh; cvt.rn.bf16x2.f32 tt, f1, f0; fma.rn.bf16x2 v3, tt, osc, v3;\n"
        "and.b32 ad, %6, 0xffff; add.u32 ad, ad, %4; st.shared.v4.b32 [ad+0], {v0,v1,v2,v3};\n"
        "and.b32 ad, %6, 0xffff; add.u32 ad, ad, %4; ld.shared.v4.b32 {v0,v1,v2,v3}, [ad+64];\n"
        "mov.b32 {xl, xh}, o1; cvt.f32.f16 f0, xl; cvt.f32.f16 f1, xh; cvt.rn.bf16x2.f32 tt, f1, f0; fma.rn.bf16x2 v4, tt, osc, v4;\n"
        "mov.b32 {xl, xh}, o3; cvt.f32.f16 f0, xl; cvt.f32.f16 f1, xh; cvt.rn.bf16x2.f32 tt, f1, f0; fma.rn.bf16x2 v5, tt, osc, v5;\n"
        "mov.b32 {xl, xh}, o5; cvt.f32.f16 f0, xl; cvt.f32.f16 f1, xh; cvt.rn.bf16x2.f32 tt, f1, f0; fma.rn.bf16x2 v6, tt, osc, v6;\n"
        "mov.b32 {xl, xh}, o7; cvt.f32.f16 f0, xl; cvt.f32.f16 f1, xh; cvt.rn.bf16x2.f32 tt, f1, f0; fma.rn.bf16x2 v7, tt, osc, v7;\n"
        "shr.u32 ad, %6, 16; add.u32 ad, ad, %4; st.shared.v4.b32 [ad+0], {v4,v5,v6,v7};\n"
        "shr.u32 ad, %6, 16; add.u32 ad, ad, %4; ld.shared.v4.b32 {v4,v5,v6,v7}, [ad+64];\n"
        "ld.shared.v4.b32 {o0,o1,o2,o3}, [%7+0];\n"
        "ld.shared.v4.b32 {o4,o5,o6,o7}, [%7+64];\n"
        "mov.b32 {xl, xh}, o8; cvt.f32.f16 f0, xl; cvt.f32.f16 f1, xh; cvt.rn.bf16x2.f32 tt, f1, f0; fma.rn.bf16x2 v0, tt, osc, v0;\n"
        "mov.b32 {xl, xh}, o10; cvt.f32.f16 f0, xl; cvt.f32.f16 f1, xh; cvt.rn.bf16x2.f32 tt, f1, f0; fma.rn.bf16x2 v1, tt, osc, v1;\n"
        "mov.b32 {xl, xh}, o12; cvt.f32.f16 f0, xl; cvt.f32.f16 f1, xh; cvt.rn.bf16x2.f32 tt, f1, f0; fma.rn.bf16x2 v2, tt, osc, v2;\n"
        "mov.b32 {xl, xh}, o14; cvt.f32.f16 f0, xl; cvt.f32.f16 f1, xh; cvt.rn.bf16x2.f32 tt, f1, f0; fma.rn.bf16x2 v3, tt, osc, v3;\n"
        "and.b32 ad, %6, 0xffff; add.u32 ad, ad, %4; st.shared.v4.b32 [ad+64], {v0,v1,v2,v3};\n"
        "and.b32 ad, %6, 0xffff; add.u32 ad, ad, %4; ld.shared.v4.b32 {v0,v1,v2,v3}, [ad+128];\n"
        "mov.b32 {xl, xh}, o9; cvt.f32.f16 f0, xl; cvt.f32.f16 f1, xh; cvt.rn.bf16x2.f32 tt, f1, f0; fma.rn.bf16x2 v4, tt, osc, v4;\n"
        "mov.b32 {xl, xh}, o11; cvt.f32.f16 f0, xl; cvt.f32.f16 f1, xh; cvt.rn.bf16x2.f32 tt, f1, f0; fma.rn.bf16x2 v5, tt, osc, v5;\n"
        "mov.b32 {xl, xh}, o13; cvt.f32.f16 f0, xl; cvt.f32.f16 f1, xh; cvt.rn.bf16x2.f32 tt, f1, f0; fma.rn.bf16x2 v6, tt, osc, v6;\n"
        "mov.b32 {xl, xh}, o15; cvt.f32.f16 f0, xl; cvt.f32.f16 f1, xh; cvt.rn.bf16x2.f32 tt, f1, f0; fma.rn.bf16x2 v7, tt, osc, v7;\n"
        "shr.u32 ad, %6, 16; add.u32 ad, ad, %4; st.shared.v4.b32 [ad+64], {v4,v5,v6,v7};\n"
        "shr.u32 ad, %6, 16; add.u32 ad, ad, %4; ld.shared.v4.b32 {v4,v5,v6,v7}, [ad+128];\n"
        "ld.shared.v4.b32 {o8,o9,o10,o11}, [%7+128];\n"
        "ld.shared.v4.b32 {o12,o13,o14,o15}, [%7+192];\n"
        "mov.b32 {xl, xh}, o16; cvt.f32.f16 f0, xl; cvt.f32.f16 f1, xh; cvt.rn.bf16x2.f32 tt, f1, f0; fma.rn.bf16x2 v0, tt, osc, v0;\n"
        "mov.b32 {xl, xh}, o18; cvt.f32.f16 f0, xl; cvt.f32.f16 f1, xh; cvt.rn.bf16x2.f32 tt, f1, f0; fma.rn.bf16x2 v1, tt, osc, v1;\n"
        "mov.b32 {xl, xh}, o20; cvt.f32.f16 f0, xl; cvt.f32.f16 f1, xh; cvt.rn.bf16x2.f32 tt, f1, f0; fma.rn.bf16x2 v2, tt, osc, v2;\n"
        "mov.b32 {xl, xh}, o22; cvt.f32.f16 f0, xl; cvt.f32.f16 f1, xh; cvt.rn.bf16x2.f32 tt, f1, f0; fma.rn.bf16x2 v3, tt, osc, v3;\n"
        "and.b32 ad, %6, 0xffff; add.u32 ad, ad, %4; st.shared.v4.b32 [ad+128], {v0,v1,v2,v3};\n"
        "mov.b32 {xl, xh}, o17; cvt.f32.f16 f0, xl; cvt.f32.f16 f1, xh; cvt.rn.bf16x2.f32 tt, f1, f0; fma.rn.bf16x2 v4, tt, osc, v4;\n"
        "mov.b32 {xl, xh}, o19; cvt.f32.f16 f0, xl; cvt.f32.f16 f1, xh; cvt.rn.bf16x2.f32 tt, f1, f0; fma.rn.bf16x2 v5, tt, osc, v5;\n"
        "mov.b32 {xl, xh}, o21; cvt.f32.f16 f0, xl; cvt.f32.f16 f1, xh; cvt.rn.bf16x2.f32 tt, f1, f0; fma.rn.bf16x2 v6, tt, osc, v6;\n"
        "mov.b32 {xl, xh}, o23; cvt.f32.f16 f0, xl; cvt.f32.f16 f1, xh; cvt.rn.bf16x2.f32 tt, f1, f0; fma.rn.bf16x2 v7, tt, osc, v7;\n"
        "shr.u32 ad, %6, 16; add.u32 ad, ad, %4; st.shared.v4.b32 [ad+128], {v4,v5,v6,v7};\n"
        "ld.shared.v4.b32 {o16,o17,o18,o19}, [%7+256];\n"
        "ld.shared.v4.b32 {o20,o21,o22,o23}, [%7+320];\n"
        "FIRST:\n"
        "@pz bra.uni B8;\n"
        "mov.b32 {xl, xh}, a0; tanh.approx.f16 xr, xl; cvt.u32.u16 lo0, xr; tanh.approx.f16 xr, xh; cvt.u32.u16 hi0, xr; mul.rn.f16x2 a1, qz7, p1; fma.rn.f16x2 p0, qz8, qz8, c; fma.rn.f16x2 g4, qz4, h0, qz4; prmt.b32 h1, lo1, hi1, 0x5410;\n"
        "mov.b32 {xl, xh}, a1; tanh.approx.f16 xr, xl; cvt.u32.u16 lo1, xr; tanh.approx.f16 xr, xh; cvt.u32.u16 hi1, xr; mul.rn.f16x2 a0, qz8, p0; fma.rn.f16x2 p1, qz9, qz9, c; fma.rn.f16x2 g5, qz5, h1, qz5; prmt.b32 h0, lo0, hi0, 0x5410;\n"
        "B8:\n"
        "fence.proxy.async.shared::cta;\n"
        "add.u32 tt, id, 4;\n"
        "@pl bra.uni STORE;\n"
        "bar.arrive tt, 128;\n"
        "STOREB:\n"
        ASM_MARK
        "@!pm bra.uni DONE;\n"
        "add.s32 n, n, 1; sub.u32 off, off, %8; setp.lt.s32 pm, n, 7;\n"
        "@pz bra.uni B10;\n"
        "mov.b32 {xl, xh}, a0; tanh.approx.f16 xr, xl; cvt.u32.u16 lo0, xr; tanh.approx.f16 xr, xh; cvt.u32.u16 hi0, xr; mul.rn.f16x2 a1, qz9, p1; fma.rn.f16x2 p0, qz10, qz10, c; fma.rn.f16x2 g6, qz6, h0, qz6; prmt.b32 h1, lo1, hi1, 0x5410;\n"
        "mov.b32 {xl, xh}, a1; tanh.approx.f16 xr, xl; cvt.u32.u16 lo1, xr; tanh.approx.f16 xr, xh; cvt.u32.u16 hi1, xr; mul.rn.f16x2 a0, qz10, p0; fma.rn.f16x2 p1, qz11, qz11, c; fma.rn.f16x2 g7, qz7, h1, qz7; prmt.b32 h0, lo0, hi0, 0x5410;\n"
        "B10:\n"
        "setp.eq.s32 pr, n, 0;\n"
        "@pr bra.uni SPINW0;\n"
        "BACKW0:\n"
        "wgmma.fence.sync.aligned;\n"
        "add.s64 dt, w2d, 0; wgmma.mma_async.sync.aligned.m64n96k16.f16.f16.f16 {o0,o1,o2,o3,o4,o5,o6,o7,o8,o9,o10,o11,o12,o13,o14,o15,o16,o17,o18,o19,o20,o21,o22,o23}, {g0,g1,g2,g3}, dt, pt, 1, 1, 1;\n"
        "add.s64 dt, w2d, 64; wgmma.mma_async.sync.aligned.m64n96k16.f16.f16.f16 {o0,o1,o2,o3,o4,o5,o6,o7,o8,o9,o10,o11,o12,o13,o14,o15,o16,o17,o18,o19,o20,o21,o22,o23}, {g4,g5,g6,g7}, dt, pt, 1, 1, 1;\n"
        "wgmma.commit_group.sync.aligned;\n"
        "@pz bra.uni B14;\n"
        "mov.b32 {xl, xh}, a0; tanh.approx.f16 xr, xl; cvt.u32.u16 lo0, xr; tanh.approx.f16 xr, xh; cvt.u32.u16 hi0, xr; mul.rn.f16x2 a1, qz11, p1; fma.rn.f16x2 p0, qz12, qz12, c; fma.rn.f16x2 g8, qz8, h0, qz8; prmt.b32 h1, lo1, hi1, 0x5410;\n"
        "mov.b32 {xl, xh}, a1; tanh.approx.f16 xr, xl; cvt.u32.u16 lo1, xr; tanh.approx.f16 xr, xh; cvt.u32.u16 hi1, xr; mul.rn.f16x2 a0, qz12, p0; fma.rn.f16x2 p1, qz13, qz13, c; fma.rn.f16x2 g9, qz9, h1, qz9; prmt.b32 h0, lo0, hi0, 0x5410;\n"
        "mov.b32 {xl, xh}, a0; tanh.approx.f16 xr, xl; cvt.u32.u16 lo0, xr; tanh.approx.f16 xr, xh; cvt.u32.u16 hi0, xr; mul.rn.f16x2 a1, qz13, p1; fma.rn.f16x2 p0, qz14, qz14, c; fma.rn.f16x2 g10, qz10, h0, qz10; prmt.b32 h1, lo1, hi1, 0x5410;\n"
        "mov.b32 {xl, xh}, a1; tanh.approx.f16 xr, xl; cvt.u32.u16 lo1, xr; tanh.approx.f16 xr, xh; cvt.u32.u16 hi1, xr; mul.rn.f16x2 a0, qz14, p0; fma.rn.f16x2 p1, qz15, qz15, c; fma.rn.f16x2 g11, qz11, h1, qz11; prmt.b32 h0, lo0, hi0, 0x5410;\n"
        "B14:\n"
        "wgmma.wait_group.sync.aligned 1;\n"
        "wgmma.fence.sync.aligned;\n"
        "add.s64 dt, w2d, 128; wgmma.mma_async.sync.aligned.m64n96k16.f16.f16.f16 {o0,o1,o2,o3,o4,o5,o6,o7,o8,o9,o10,o11,o12,o13,o14,o15,o16,o17,o18,o19,o20,o21,o22,o23}, {g8,g9,g10,g11}, dt, pt, 1, 1, 1;\n"
        "wgmma.commit_group.sync.aligned;\n"
        "@pz bra.uni B18;\n"
        "mov.b32 {xl, xh}, a0; tanh.approx.f16 xr, xl; cvt.u32.u16 lo0, xr; tanh.approx.f16 xr, xh; cvt.u32.u16 hi0, xr; mul.rn.f16x2 a1, qz15, p1; fma.rn.f16x2 p0, qz16, qz16, c; fma.rn.f16x2 g12, qz12, h0, qz12; prmt.b32 h1, lo1, hi1, 0x5410;\n"
        "mov.b32 {xl, xh}, a1; tanh.approx.f16 xr, xl; cvt.u32.u16 lo1, xr; tanh.approx.f16 xr, xh; cvt.u32.u16 hi1, xr; mul.rn.f16x2 a0, qz16, p0; fma.rn.f16x2 p1, qz17, qz17, c; fma.rn.f16x2 g13, qz13, h1, qz13; prmt.b32 h0, lo0, hi0, 0x5410;\n"
        "mov.b32 {xl, xh}, a0; tanh.approx.f16 xr, xl; cvt.u32.u16 lo0, xr; tanh.approx.f16 xr, xh; cvt.u32.u16 hi0, xr; mul.rn.f16x2 a1, qz17, p1; fma.rn.f16x2 p0, qz18, qz18, c; fma.rn.f16x2 g14, qz14, h0, qz14; prmt.b32 h1, lo1, hi1, 0x5410;\n"
        "mov.b32 {xl, xh}, a1; tanh.approx.f16 xr, xl; cvt.u32.u16 lo1, xr; tanh.approx.f16 xr, xh; cvt.u32.u16 hi1, xr; mul.rn.f16x2 a0, qz18, p0; fma.rn.f16x2 p1, qz19, qz19, c; fma.rn.f16x2 g15, qz15, h1, qz15; prmt.b32 h0, lo0, hi0, 0x5410;\n"
        "B18:\n"
        "wgmma.wait_group.sync.aligned 1;\n"
        "mad.lo.u32 tt, n, 8, tbar; mbarrier.try_wait.parity.shared::cta.b64 pw, [tt], tpar;\n"
        "@!pw bra.uni SPINT;\n"
        "BACKT:\n"
        "wgmma.fence.sync.aligned;\n"
        "add.s64 dt, w2d, 192; wgmma.mma_async.sync.aligned.m64n96k16.f16.f16.f16 {o0,o1,o2,o3,o4,o5,o6,o7,o8,o9,o10,o11,o12,o13,o14,o15,o16,o17,o18,o19,o20,o21,o22,o23}, {g12,g13,g14,g15}, dt, pt, 1, 1, 1;\n"
        "add.s64 dt, w1d, 1536; wgmma.mma_async.sync.aligned.m64n64k16.f16.f16.f16 {qz0,qz1,qz2,qz3,qz4,qz5,qz6,qz7,qz8,qz9,qz10,qz11,qz12,qz13,qz14,qz15}, {qa0,qa1,qa2,qa3}, dt, pf, 1, 1, 1;\n"
        "add.s64 dt, w1d, 1664; wgmma.mma_async.sync.aligned.m64n64k16.f16.f16.f16 {qz0,qz1,qz2,qz3,qz4,qz5,qz6,qz7,qz8,qz9,qz10,qz11,qz12,qz13,qz14,qz15}, {qa4,qa5,qa6,qa7}, dt, pt, 1, 1, 1;\n"
        "add.s64 dt, w1d, 1792; wgmma.mma_async.sync.aligned.m64n64k16.f16.f16.f16 {qz0,qz1,qz2,qz3,qz4,qz5,qz6,qz7,qz8,qz9,qz10,qz11,qz12,qz13,qz14,qz15}, {qa8,qa9,qa10,qa11}, dt, pt, 1, 1, 1;\n"
        "wgmma.commit_group.sync.aligned;\n"
        "@pl bra.uni YLOAD;\n"
        "YLOADB:\n"
        "@pz bra.uni B22;\n"
        "mov.b32 {xl, xh}, a0; tanh.approx.f16 xr, xl; cvt.u32.u16 lo0, xr; tanh.approx.f16 xr, xh; cvt.u32.u16 hi0, xr; mul.rn.f16x2 a1, qz19, p1; fma.rn.f16x2 p0, qz20, qz20, c; fma.rn.f16x2 g0, qz16, h0, qz16; prmt.b32 h1, lo1, hi1, 0x5410;\n"
        "mov.b32 {xl, xh}, a1; tanh.approx.f16 xr, xl; cvt.u32.u16 lo1, xr; tanh.approx.f16 xr, xh; cvt.u32.u16 hi1, xr; mul.rn.f16x2 a0, qz20, p0; fma.rn.f16x2 p1, qz21, qz21, c; fma.rn.f16x2 g1, qz17, h1, qz17; prmt.b32 h0, lo0, hi0, 0x5410;\n"
        "mov.b32 {xl, xh}, a0; tanh.approx.f16 xr, xl; cvt.u32.u16 lo0, xr; tanh.approx.f16 xr, xh; cvt.u32.u16 hi0, xr; mul.rn.f16x2 a1, qz21, p1; fma.rn.f16x2 p0, qz22, qz22, c; fma.rn.f16x2 g2, qz18, h0, qz18; prmt.b32 h1, lo1, hi1, 0x5410;\n"
        "mov.b32 {xl, xh}, a1; tanh.approx.f16 xr, xl; cvt.u32.u16 lo1, xr; tanh.approx.f16 xr, xh; cvt.u32.u16 hi1, xr; mul.rn.f16x2 a0, qz22, p0; fma.rn.f16x2 p1, qz23, qz23, c; fma.rn.f16x2 g3, qz19, h1, qz19; prmt.b32 h0, lo0, hi0, 0x5410;\n"
        "B22:\n"
        "wgmma.fence.sync.aligned;\n"
        "add.s64 dt, w2d, 256; wgmma.mma_async.sync.aligned.m64n96k16.f16.f16.f16 {o0,o1,o2,o3,o4,o5,o6,o7,o8,o9,o10,o11,o12,o13,o14,o15,o16,o17,o18,o19,o20,o21,o22,o23}, {g0,g1,g2,g3}, dt, pt, 1, 1, 1;\n"
        "add.s64 dt, w1d, 1920; wgmma.mma_async.sync.aligned.m64n64k16.f16.f16.f16 {qz0,qz1,qz2,qz3,qz4,qz5,qz6,qz7,qz8,qz9,qz10,qz11,qz12,qz13,qz14,qz15}, {qa12,qa13,qa14,qa15}, dt, pt, 1, 1, 1;\n"
        "add.s64 dt, w1d, 2048; wgmma.mma_async.sync.aligned.m64n64k16.f16.f16.f16 {qz0,qz1,qz2,qz3,qz4,qz5,qz6,qz7,qz8,qz9,qz10,qz11,qz12,qz13,qz14,qz15}, {qa16,qa17,qa18,qa19}, dt, pt, 1, 1, 1;\n"
        "add.s64 dt, w1d, 2176; wgmma.mma_async.sync.aligned.m64n64k16.f16.f16.f16 {qz0,qz1,qz2,qz3,qz4,qz5,qz6,qz7,qz8,qz9,qz10,qz11,qz12,qz13,qz14,qz15}, {qa20,qa21,qa22,qa23}, dt, pt, 1, 1, 1;\n"
        "wgmma.commit_group.sync.aligned;\n"
        "@pz bra.uni B26;\n"
        "mov.b32 {xl, xh}, a0; tanh.approx.f16 xr, xl; cvt.u32.u16 lo0, xr; tanh.approx.f16 xr, xh; cvt.u32.u16 hi0, xr; mul.rn.f16x2 a1, qz23, p1; fma.rn.f16x2 p0, qz24, qz24, c; fma.rn.f16x2 g4, qz20, h0, qz20; prmt.b32 h1, lo1, hi1, 0x5410;\n"
        "mov.b32 {xl, xh}, a1; tanh.approx.f16 xr, xl; cvt.u32.u16 lo1, xr; tanh.approx.f16 xr, xh; cvt.u32.u16 hi1, xr; mul.rn.f16x2 a0, qz24, p0; fma.rn.f16x2 p1, qz25, qz25, c; fma.rn.f16x2 g5, qz21, h1, qz21; prmt.b32 h0, lo0, hi0, 0x5410;\n"
        "mov.b32 {xl, xh}, a0; tanh.approx.f16 xr, xl; cvt.u32.u16 lo0, xr; tanh.approx.f16 xr, xh; cvt.u32.u16 hi0, xr; mul.rn.f16x2 a1, qz25, p1; fma.rn.f16x2 p0, qz26, qz26, c; fma.rn.f16x2 g6, qz22, h0, qz22; prmt.b32 h1, lo1, hi1, 0x5410;\n"
        "mov.b32 {xl, xh}, a1; tanh.approx.f16 xr, xl; cvt.u32.u16 lo1, xr; tanh.approx.f16 xr, xh; cvt.u32.u16 hi1, xr; mul.rn.f16x2 a0, qz26, p0; fma.rn.f16x2 p1, qz27, qz27, c; fma.rn.f16x2 g7, qz23, h1, qz23; prmt.b32 h0, lo0, hi0, 0x5410;\n"
        "B26:\n"
        "wgmma.wait_group.sync.aligned 2;\n"
        "wgmma.fence.sync.aligned;\n"
        "add.s64 dt, w2d, 320; wgmma.mma_async.sync.aligned.m64n96k16.f16.f16.f16 {o0,o1,o2,o3,o4,o5,o6,o7,o8,o9,o10,o11,o12,o13,o14,o15,o16,o17,o18,o19,o20,o21,o22,o23}, {g4,g5,g6,g7}, dt, pt, 1, 1, 1;\n"
        "wgmma.commit_group.sync.aligned;\n"
        "@pz bra.uni B30;\n"
        "mov.b32 {xl, xh}, a0; tanh.approx.f16 xr, xl; cvt.u32.u16 lo0, xr; tanh.approx.f16 xr, xh; cvt.u32.u16 hi0, xr; mul.rn.f16x2 a1, qz27, p1; fma.rn.f16x2 p0, qz28, qz28, c; fma.rn.f16x2 g8, qz24, h0, qz24; prmt.b32 h1, lo1, hi1, 0x5410;\n"
        "mov.b32 {xl, xh}, a1; tanh.approx.f16 xr, xl; cvt.u32.u16 lo1, xr; tanh.approx.f16 xr, xh; cvt.u32.u16 hi1, xr; mul.rn.f16x2 a0, qz28, p0; fma.rn.f16x2 p1, qz29, qz29, c; fma.rn.f16x2 g9, qz25, h1, qz25; prmt.b32 h0, lo0, hi0, 0x5410;\n"
        "mov.b32 {xl, xh}, a0; tanh.approx.f16 xr, xl; cvt.u32.u16 lo0, xr; tanh.approx.f16 xr, xh; cvt.u32.u16 hi0, xr; mul.rn.f16x2 a1, qz29, p1; fma.rn.f16x2 p0, qz30, qz30, c; fma.rn.f16x2 g10, qz26, h0, qz26; prmt.b32 h1, lo1, hi1, 0x5410;\n"
        "mov.b32 {xl, xh}, a1; tanh.approx.f16 xr, xl; cvt.u32.u16 lo1, xr; tanh.approx.f16 xr, xh; cvt.u32.u16 hi1, xr; mul.rn.f16x2 a0, qz30, p0; fma.rn.f16x2 p1, qz31, qz31, c; fma.rn.f16x2 g11, qz27, h1, qz27; prmt.b32 h0, lo0, hi0, 0x5410;\n"
        "B30:\n"
        "wgmma.wait_group.sync.aligned 1;\n"
        "wgmma.fence.sync.aligned;\n"
        "add.s64 dt, w2d, 384; wgmma.mma_async.sync.aligned.m64n96k16.f16.f16.f16 {o0,o1,o2,o3,o4,o5,o6,o7,o8,o9,o10,o11,o12,o13,o14,o15,o16,o17,o18,o19,o20,o21,o22,o23}, {g8,g9,g10,g11}, dt, pt, 1, 1, 1;\n"
        "wgmma.commit_group.sync.aligned;\n"
        "@pz bra.uni B34;\n"
        "mov.b32 {xl, xh}, a0; tanh.approx.f16 xr, xl; cvt.u32.u16 lo0, xr; tanh.approx.f16 xr, xh; cvt.u32.u16 hi0, xr; mul.rn.f16x2 a1, qz31, p1; fma.rn.f16x2 p0, qz0, qz0, c; fma.rn.f16x2 g12, qz28, h0, qz28; prmt.b32 h1, lo1, hi1, 0x5410;\n"
        "mov.b32 {xl, xh}, a1; tanh.approx.f16 xr, xl; cvt.u32.u16 lo1, xr; tanh.approx.f16 xr, xh; cvt.u32.u16 hi1, xr; mul.rn.f16x2 a0, qz0, p0; fma.rn.f16x2 p1, qz1, qz1, c; fma.rn.f16x2 g13, qz29, h1, qz29; prmt.b32 h0, lo0, hi0, 0x5410;\n"
        "mov.b32 {xl, xh}, a0; tanh.approx.f16 xr, xl; cvt.u32.u16 lo0, xr; tanh.approx.f16 xr, xh; cvt.u32.u16 hi0, xr; mul.rn.f16x2 a1, qz1, p1; fma.rn.f16x2 p0, qz2, qz2, c; fma.rn.f16x2 g14, qz30, h0, qz30; prmt.b32 h1, lo1, hi1, 0x5410;\n"
        "mov.b32 {xl, xh}, a1; tanh.approx.f16 xr, xl; cvt.u32.u16 lo1, xr; tanh.approx.f16 xr, xh; cvt.u32.u16 hi1, xr; mul.rn.f16x2 a0, qz2, p0; fma.rn.f16x2 p1, qz3, qz3, c; fma.rn.f16x2 g15, qz31, h1, qz31; prmt.b32 h0, lo0, hi0, 0x5410;\n"
        "B34:\n"
        "wgmma.fence.sync.aligned;\n"
        "add.s64 dt, w2d, 448; wgmma.mma_async.sync.aligned.m64n96k16.f16.f16.f16 {o0,o1,o2,o3,o4,o5,o6,o7,o8,o9,o10,o11,o12,o13,o14,o15,o16,o17,o18,o19,o20,o21,o22,o23}, {g12,g13,g14,g15}, dt, pt, 1, 1, 1;\n"
        "add.s64 dt, w1d, 2304; wgmma.mma_async.sync.aligned.m64n64k16.f16.f16.f16 {qz16,qz17,qz18,qz19,qz20,qz21,qz22,qz23,qz24,qz25,qz26,qz27,qz28,qz29,qz30,qz31}, {qa0,qa1,qa2,qa3}, dt, pf, 1, 1, 1;\n"
        "add.s64 dt, w1d, 2432; wgmma.mma_async.sync.aligned.m64n64k16.f16.f16.f16 {qz16,qz17,qz18,qz19,qz20,qz21,qz22,qz23,qz24,qz25,qz26,qz27,qz28,qz29,qz30,qz31}, {qa4,qa5,qa6,qa7}, dt, pt, 1, 1, 1;\n"
        "add.s64 dt, w1d, 2560; wgmma.mma_async.sync.aligned.m64n64k16.f16.f16.f16 {qz16,qz17,qz18,qz19,qz20,qz21,qz22,qz23,qz24,qz25,qz26,qz27,qz28,qz29,qz30,qz31}, {qa8,qa9,qa10,qa11}, dt, pt, 1, 1, 1;\n"
        "wgmma.commit_group.sync.aligned;\n"
        "@pz bra.uni B38;\n"
        "mov.b32 {xl, xh}, a0; tanh.approx.f16 xr, xl; cvt.u32.u16 lo0, xr; tanh.approx.f16 xr, xh; cvt.u32.u16 hi0, xr; mul.rn.f16x2 a1, qz3, p1; fma.rn.f16x2 p0, qz4, qz4, c; fma.rn.f16x2 g0, qz0, h0, qz0; prmt.b32 h1, lo1, hi1, 0x5410;\n"
        "mov.b32 {xl, xh}, a1; tanh.approx.f16 xr, xl; cvt.u32.u16 lo1, xr; tanh.approx.f16 xr, xh; cvt.u32.u16 hi1, xr; mul.rn.f16x2 a0, qz4, p0; fma.rn.f16x2 p1, qz5, qz5, c; fma.rn.f16x2 g1, qz1, h1, qz1; prmt.b32 h0, lo0, hi0, 0x5410;\n"
        "mov.b32 {xl, xh}, a0; tanh.approx.f16 xr, xl; cvt.u32.u16 lo0, xr; tanh.approx.f16 xr, xh; cvt.u32.u16 hi0, xr; mul.rn.f16x2 a1, qz5, p1; fma.rn.f16x2 p0, qz6, qz6, c; fma.rn.f16x2 g2, qz2, h0, qz2; prmt.b32 h1, lo1, hi1, 0x5410;\n"
        "mov.b32 {xl, xh}, a1; tanh.approx.f16 xr, xl; cvt.u32.u16 lo1, xr; tanh.approx.f16 xr, xh; cvt.u32.u16 hi1, xr; mul.rn.f16x2 a0, qz6, p0; fma.rn.f16x2 p1, qz7, qz7, c; fma.rn.f16x2 g3, qz3, h1, qz3; prmt.b32 h0, lo0, hi0, 0x5410;\n"
        "B38:\n"
        "wgmma.wait_group.sync.aligned 2;\n"
        "setp.eq.s32 pr, n, 0;\n"
        "@pr bra.uni SPINW1;\n"
        "BACKW1:\n"
        "wgmma.fence.sync.aligned;\n"
        "add.s64 dt, w2d, 512; wgmma.mma_async.sync.aligned.m64n96k16.f16.f16.f16 {o0,o1,o2,o3,o4,o5,o6,o7,o8,o9,o10,o11,o12,o13,o14,o15,o16,o17,o18,o19,o20,o21,o22,o23}, {g0,g1,g2,g3}, dt, pt, 1, 1, 1;\n"
        "add.s64 dt, w1d, 2688; wgmma.mma_async.sync.aligned.m64n64k16.f16.f16.f16 {qz16,qz17,qz18,qz19,qz20,qz21,qz22,qz23,qz24,qz25,qz26,qz27,qz28,qz29,qz30,qz31}, {qa12,qa13,qa14,qa15}, dt, pt, 1, 1, 1;\n"
        "add.s64 dt, w1d, 2816; wgmma.mma_async.sync.aligned.m64n64k16.f16.f16.f16 {qz16,qz17,qz18,qz19,qz20,qz21,qz22,qz23,qz24,qz25,qz26,qz27,qz28,qz29,qz30,qz31}, {qa16,qa17,qa18,qa19}, dt, pt, 1, 1, 1;\n"
        "add.s64 dt, w1d, 2944; wgmma.mma_async.sync.aligned.m64n64k16.f16.f16.f16 {qz16,qz17,qz18,qz19,qz20,qz21,qz22,qz23,qz24,qz25,qz26,qz27,qz28,qz29,qz30,qz31}, {qa20,qa21,qa22,qa23}, dt, pt, 1, 1, 1;\n"
        "wgmma.commit_group.sync.aligned;\n"
        "@pz bra.uni B42;\n"
        "mov.b32 {xl, xh}, a0; tanh.approx.f16 xr, xl; cvt.u32.u16 lo0, xr; tanh.approx.f16 xr, xh; cvt.u32.u16 hi0, xr; mul.rn.f16x2 a1, qz7, p1; fma.rn.f16x2 p0, qz8, qz8, c; fma.rn.f16x2 g4, qz4, h0, qz4; prmt.b32 h1, lo1, hi1, 0x5410;\n"
        "mov.b32 {xl, xh}, a1; tanh.approx.f16 xr, xl; cvt.u32.u16 lo1, xr; tanh.approx.f16 xr, xh; cvt.u32.u16 hi1, xr; mul.rn.f16x2 a0, qz8, p0; fma.rn.f16x2 p1, qz9, qz9, c; fma.rn.f16x2 g5, qz5, h1, qz5; prmt.b32 h0, lo0, hi0, 0x5410;\n"
        "mov.b32 {xl, xh}, a0; tanh.approx.f16 xr, xl; cvt.u32.u16 lo0, xr; tanh.approx.f16 xr, xh; cvt.u32.u16 hi0, xr; mul.rn.f16x2 a1, qz9, p1; fma.rn.f16x2 p0, qz10, qz10, c; fma.rn.f16x2 g6, qz6, h0, qz6; prmt.b32 h1, lo1, hi1, 0x5410;\n"
        "mov.b32 {xl, xh}, a1; tanh.approx.f16 xr, xl; cvt.u32.u16 lo1, xr; tanh.approx.f16 xr, xh; cvt.u32.u16 hi1, xr; mul.rn.f16x2 a0, qz10, p0; fma.rn.f16x2 p1, qz11, qz11, c; fma.rn.f16x2 g7, qz7, h1, qz7; prmt.b32 h0, lo0, hi0, 0x5410;\n"
        "B42:\n"
        "wgmma.wait_group.sync.aligned 2;\n"
        "wgmma.fence.sync.aligned;\n"
        "add.s64 dt, w2d, 576; wgmma.mma_async.sync.aligned.m64n96k16.f16.f16.f16 {o0,o1,o2,o3,o4,o5,o6,o7,o8,o9,o10,o11,o12,o13,o14,o15,o16,o17,o18,o19,o20,o21,o22,o23}, {g4,g5,g6,g7}, dt, pt, 1, 1, 1;\n"
        "wgmma.commit_group.sync.aligned;\n"
        "@pz bra.uni B46;\n"
        "mov.b32 {xl, xh}, a0; tanh.approx.f16 xr, xl; cvt.u32.u16 lo0, xr; tanh.approx.f16 xr, xh; cvt.u32.u16 hi0, xr; mul.rn.f16x2 a1, qz11, p1; fma.rn.f16x2 p0, qz12, qz12, c; fma.rn.f16x2 g8, qz8, h0, qz8; prmt.b32 h1, lo1, hi1, 0x5410;\n"
        "mov.b32 {xl, xh}, a1; tanh.approx.f16 xr, xl; cvt.u32.u16 lo1, xr; tanh.approx.f16 xr, xh; cvt.u32.u16 hi1, xr; mul.rn.f16x2 a0, qz12, p0; fma.rn.f16x2 p1, qz13, qz13, c; fma.rn.f16x2 g9, qz9, h1, qz9; prmt.b32 h0, lo0, hi0, 0x5410;\n"
        "mov.b32 {xl, xh}, a0; tanh.approx.f16 xr, xl; cvt.u32.u16 lo0, xr; tanh.approx.f16 xr, xh; cvt.u32.u16 hi0, xr; mul.rn.f16x2 a1, qz13, p1; fma.rn.f16x2 p0, qz14, qz14, c; fma.rn.f16x2 g10, qz10, h0, qz10; prmt.b32 h1, lo1, hi1, 0x5410;\n"
        "mov.b32 {xl, xh}, a1; tanh.approx.f16 xr, xl; cvt.u32.u16 lo1, xr; tanh.approx.f16 xr, xh; cvt.u32.u16 hi1, xr; mul.rn.f16x2 a0, qz14, p0; fma.rn.f16x2 p1, qz15, qz15, c; fma.rn.f16x2 g11, qz11, h1, qz11; prmt.b32 h0, lo0, hi0, 0x5410;\n"
        "B46:\n"
        "wgmma.wait_group.sync.aligned 1;\n"
        "wgmma.fence.sync.aligned;\n"
        "add.s64 dt, w2d, 640; wgmma.mma_async.sync.aligned.m64n96k16.f16.f16.f16 {o0,o1,o2,o3,o4,o5,o6,o7,o8,o9,o10,o11,o12,o13,o14,o15,o16,o17,o18,o19,o20,o21,o22,o23}, {g8,g9,g10,g11}, dt, pt, 1, 1, 1;\n"
        "wgmma.commit_group.sync.aligned;\n"
        "mad.lo.u32 tt, n, 8, tbar;\n"
        "@pn mbarrier.arrive.shared::cta.b64 _, [tt+64];\n"
        "@pz bra.uni B50;\n"
        "mov.b32 {xl, xh}, a0; tanh.approx.f16 xr, xl; cvt.u32.u16 lo0, xr; tanh.approx.f16 xr, xh; cvt.u32.u16 hi0, xr; mul.rn.f16x2 a1, qz15, p1; fma.rn.f16x2 p0, qz16, qz16, c; fma.rn.f16x2 g12, qz12, h0, qz12; prmt.b32 h1, lo1, hi1, 0x5410;\n"
        "mov.b32 {xl, xh}, a1; tanh.approx.f16 xr, xl; cvt.u32.u16 lo1, xr; tanh.approx.f16 xr, xh; cvt.u32.u16 hi1, xr; mul.rn.f16x2 a0, qz16, p0; fma.rn.f16x2 p1, qz17, qz17, c; fma.rn.f16x2 g13, qz13, h1, qz13; prmt.b32 h0, lo0, hi0, 0x5410;\n"
        "mov.b32 {xl, xh}, a0; tanh.approx.f16 xr, xl; cvt.u32.u16 lo0, xr; tanh.approx.f16 xr, xh; cvt.u32.u16 hi0, xr; mul.rn.f16x2 a1, qz17, p1; fma.rn.f16x2 p0, qz18, qz18, c; fma.rn.f16x2 g14, qz14, h0, qz14; prmt.b32 h1, lo1, hi1, 0x5410;\n"
        "mov.b32 {xl, xh}, a1; tanh.approx.f16 xr, xl; cvt.u32.u16 lo1, xr; tanh.approx.f16 xr, xh; cvt.u32.u16 hi1, xr; mul.rn.f16x2 a0, qz18, p0; fma.rn.f16x2 p1, qz19, qz19, c; fma.rn.f16x2 g15, qz15, h1, qz15; prmt.b32 h0, lo0, hi0, 0x5410;\n"
        "B50:\n"
        "wgmma.fence.sync.aligned;\n"
        "add.s64 dt, w2d, 704; wgmma.mma_async.sync.aligned.m64n96k16.f16.f16.f16 {o0,o1,o2,o3,o4,o5,o6,o7,o8,o9,o10,o11,o12,o13,o14,o15,o16,o17,o18,o19,o20,o21,o22,o23}, {g12,g13,g14,g15}, dt, pt, 1, 1, 1;\n"
        "add.s64 dt, w1d, 3072; wgmma.mma_async.sync.aligned.m64n64k16.f16.f16.f16 {qz0,qz1,qz2,qz3,qz4,qz5,qz6,qz7,qz8,qz9,qz10,qz11,qz12,qz13,qz14,qz15}, {qa0,qa1,qa2,qa3}, dt, pf, 1, 1, 1;\n"
        "add.s64 dt, w1d, 3200; wgmma.mma_async.sync.aligned.m64n64k16.f16.f16.f16 {qz0,qz1,qz2,qz3,qz4,qz5,qz6,qz7,qz8,qz9,qz10,qz11,qz12,qz13,qz14,qz15}, {qa4,qa5,qa6,qa7}, dt, pt, 1, 1, 1;\n"
        "add.s64 dt, w1d, 3328; wgmma.mma_async.sync.aligned.m64n64k16.f16.f16.f16 {qz0,qz1,qz2,qz3,qz4,qz5,qz6,qz7,qz8,qz9,qz10,qz11,qz12,qz13,qz14,qz15}, {qa8,qa9,qa10,qa11}, dt, pt, 1, 1, 1;\n"
        "wgmma.commit_group.sync.aligned;\n"
        "@pz bra.uni B54;\n"
        "mov.b32 {xl, xh}, a0; tanh.approx.f16 xr, xl; cvt.u32.u16 lo0, xr; tanh.approx.f16 xr, xh; cvt.u32.u16 hi0, xr; mul.rn.f16x2 a1, qz19, p1; fma.rn.f16x2 p0, qz20, qz20, c; fma.rn.f16x2 g0, qz16, h0, qz16; prmt.b32 h1, lo1, hi1, 0x5410;\n"
        "mov.b32 {xl, xh}, a1; tanh.approx.f16 xr, xl; cvt.u32.u16 lo1, xr; tanh.approx.f16 xr, xh; cvt.u32.u16 hi1, xr; mul.rn.f16x2 a0, qz20, p0; fma.rn.f16x2 p1, qz21, qz21, c; fma.rn.f16x2 g1, qz17, h1, qz17; prmt.b32 h0, lo0, hi0, 0x5410;\n"
        "mov.b32 {xl, xh}, a0; tanh.approx.f16 xr, xl; cvt.u32.u16 lo0, xr; tanh.approx.f16 xr, xh; cvt.u32.u16 hi0, xr; mul.rn.f16x2 a1, qz21, p1; fma.rn.f16x2 p0, qz22, qz22, c; fma.rn.f16x2 g2, qz18, h0, qz18; prmt.b32 h1, lo1, hi1, 0x5410;\n"
        "mov.b32 {xl, xh}, a1; tanh.approx.f16 xr, xl; cvt.u32.u16 lo1, xr; tanh.approx.f16 xr, xh; cvt.u32.u16 hi1, xr; mul.rn.f16x2 a0, qz22, p0; fma.rn.f16x2 p1, qz23, qz23, c; fma.rn.f16x2 g3, qz19, h1, qz19; prmt.b32 h0, lo0, hi0, 0x5410;\n"
        "B54:\n"
        "wgmma.wait_group.sync.aligned 2;\n"
        "wgmma.fence.sync.aligned;\n"
        "add.s64 dt, w2d, 768; wgmma.mma_async.sync.aligned.m64n96k16.f16.f16.f16 {o0,o1,o2,o3,o4,o5,o6,o7,o8,o9,o10,o11,o12,o13,o14,o15,o16,o17,o18,o19,o20,o21,o22,o23}, {g0,g1,g2,g3}, dt, pt, 1, 1, 1;\n"
        "add.s64 dt, w1d, 3456; wgmma.mma_async.sync.aligned.m64n64k16.f16.f16.f16 {qz0,qz1,qz2,qz3,qz4,qz5,qz6,qz7,qz8,qz9,qz10,qz11,qz12,qz13,qz14,qz15}, {qa12,qa13,qa14,qa15}, dt, pt, 1, 1, 1;\n"
        "add.s64 dt, w1d, 3584; wgmma.mma_async.sync.aligned.m64n64k16.f16.f16.f16 {qz0,qz1,qz2,qz3,qz4,qz5,qz6,qz7,qz8,qz9,qz10,qz11,qz12,qz13,qz14,qz15}, {qa16,qa17,qa18,qa19}, dt, pt, 1, 1, 1;\n"
        "add.s64 dt, w1d, 3712; wgmma.mma_async.sync.aligned.m64n64k16.f16.f16.f16 {qz0,qz1,qz2,qz3,qz4,qz5,qz6,qz7,qz8,qz9,qz10,qz11,qz12,qz13,qz14,qz15}, {qa20,qa21,qa22,qa23}, dt, pt, 1, 1, 1;\n"
        "wgmma.commit_group.sync.aligned;\n"
        "@pz bra.uni B58;\n"
        "mov.b32 {xl, xh}, a0; tanh.approx.f16 xr, xl; cvt.u32.u16 lo0, xr; tanh.approx.f16 xr, xh; cvt.u32.u16 hi0, xr; mul.rn.f16x2 a1, qz23, p1; fma.rn.f16x2 p0, qz24, qz24, c; fma.rn.f16x2 g4, qz20, h0, qz20; prmt.b32 h1, lo1, hi1, 0x5410;\n"
        "mov.b32 {xl, xh}, a1; tanh.approx.f16 xr, xl; cvt.u32.u16 lo1, xr; tanh.approx.f16 xr, xh; cvt.u32.u16 hi1, xr; mul.rn.f16x2 a0, qz24, p0; fma.rn.f16x2 p1, qz25, qz25, c; fma.rn.f16x2 g5, qz21, h1, qz21; prmt.b32 h0, lo0, hi0, 0x5410;\n"
        "mov.b32 {xl, xh}, a0; tanh.approx.f16 xr, xl; cvt.u32.u16 lo0, xr; tanh.approx.f16 xr, xh; cvt.u32.u16 hi0, xr; mul.rn.f16x2 a1, qz25, p1; fma.rn.f16x2 p0, qz26, qz26, c; fma.rn.f16x2 g6, qz22, h0, qz22; prmt.b32 h1, lo1, hi1, 0x5410;\n"
        "mov.b32 {xl, xh}, a1; tanh.approx.f16 xr, xl; cvt.u32.u16 lo1, xr; tanh.approx.f16 xr, xh; cvt.u32.u16 hi1, xr; mul.rn.f16x2 a0, qz26, p0; fma.rn.f16x2 p1, qz27, qz27, c; fma.rn.f16x2 g7, qz23, h1, qz23; prmt.b32 h0, lo0, hi0, 0x5410;\n"
        "B58:\n"
        "wgmma.wait_group.sync.aligned 2;\n"
        "wgmma.fence.sync.aligned;\n"
        "add.s64 dt, w2d, 832; wgmma.mma_async.sync.aligned.m64n96k16.f16.f16.f16 {o0,o1,o2,o3,o4,o5,o6,o7,o8,o9,o10,o11,o12,o13,o14,o15,o16,o17,o18,o19,o20,o21,o22,o23}, {g4,g5,g6,g7}, dt, pt, 1, 1, 1;\n"
        "wgmma.commit_group.sync.aligned;\n"
        "@pz bra.uni B62;\n"
        "mov.b32 {xl, xh}, a0; tanh.approx.f16 xr, xl; cvt.u32.u16 lo0, xr; tanh.approx.f16 xr, xh; cvt.u32.u16 hi0, xr; mul.rn.f16x2 a1, qz27, p1; fma.rn.f16x2 p0, qz28, qz28, c; fma.rn.f16x2 g8, qz24, h0, qz24; prmt.b32 h1, lo1, hi1, 0x5410;\n"
        "mov.b32 {xl, xh}, a1; tanh.approx.f16 xr, xl; cvt.u32.u16 lo1, xr; tanh.approx.f16 xr, xh; cvt.u32.u16 hi1, xr; mul.rn.f16x2 a0, qz28, p0; fma.rn.f16x2 p1, qz29, qz29, c; fma.rn.f16x2 g9, qz25, h1, qz25; prmt.b32 h0, lo0, hi0, 0x5410;\n"
        "mov.b32 {xl, xh}, a0; tanh.approx.f16 xr, xl; cvt.u32.u16 lo0, xr; tanh.approx.f16 xr, xh; cvt.u32.u16 hi0, xr; mul.rn.f16x2 a1, qz29, p1; fma.rn.f16x2 p0, qz30, qz30, c; fma.rn.f16x2 g10, qz26, h0, qz26; prmt.b32 h1, lo1, hi1, 0x5410;\n"
        "mov.b32 {xl, xh}, a1; tanh.approx.f16 xr, xl; cvt.u32.u16 lo1, xr; tanh.approx.f16 xr, xh; cvt.u32.u16 hi1, xr; mul.rn.f16x2 a0, qz30, p0; fma.rn.f16x2 p1, qz31, qz31, c; fma.rn.f16x2 g11, qz27, h1, qz27; prmt.b32 h0, lo0, hi0, 0x5410;\n"
        "B62:\n"
        "wgmma.wait_group.sync.aligned 1;\n"
        "wgmma.fence.sync.aligned;\n"
        "add.s64 dt, w2d, 896; wgmma.mma_async.sync.aligned.m64n96k16.f16.f16.f16 {o0,o1,o2,o3,o4,o5,o6,o7,o8,o9,o10,o11,o12,o13,o14,o15,o16,o17,o18,o19,o20,o21,o22,o23}, {g8,g9,g10,g11}, dt, pt, 1, 1, 1;\n"
        "wgmma.commit_group.sync.aligned;\n"
        "@pz bra.uni B66;\n"
        "mov.b32 {xl, xh}, a0; tanh.approx.f16 xr, xl; cvt.u32.u16 lo0, xr; tanh.approx.f16 xr, xh; cvt.u32.u16 hi0, xr; mul.rn.f16x2 a1, qz31, p1; fma.rn.f16x2 p0, qz0, qz0, c; fma.rn.f16x2 g12, qz28, h0, qz28; prmt.b32 h1, lo1, hi1, 0x5410;\n"
        "mov.b32 {xl, xh}, a1; tanh.approx.f16 xr, xl; cvt.u32.u16 lo1, xr; tanh.approx.f16 xr, xh; cvt.u32.u16 hi1, xr; mul.rn.f16x2 a0, qz0, p0; fma.rn.f16x2 p1, qz1, qz1, c; fma.rn.f16x2 g13, qz29, h1, qz29; prmt.b32 h0, lo0, hi0, 0x5410;\n"
        "mov.b32 {xl, xh}, a0; tanh.approx.f16 xr, xl; cvt.u32.u16 lo0, xr; tanh.approx.f16 xr, xh; cvt.u32.u16 hi0, xr; mul.rn.f16x2 a1, qz1, p1; fma.rn.f16x2 p0, qz2, qz2, c; fma.rn.f16x2 g14, qz30, h0, qz30; prmt.b32 h1, lo1, hi1, 0x5410;\n"
        "mov.b32 {xl, xh}, a1; tanh.approx.f16 xr, xl; cvt.u32.u16 lo1, xr; tanh.approx.f16 xr, xh; cvt.u32.u16 hi1, xr; mul.rn.f16x2 a0, qz2, p0; fma.rn.f16x2 p1, qz3, qz3, c; fma.rn.f16x2 g15, qz31, h1, qz31; prmt.b32 h0, lo0, hi0, 0x5410;\n"
        "B66:\n"
        "wgmma.fence.sync.aligned;\n"
        "add.s64 dt, w2d, 960; wgmma.mma_async.sync.aligned.m64n96k16.f16.f16.f16 {o0,o1,o2,o3,o4,o5,o6,o7,o8,o9,o10,o11,o12,o13,o14,o15,o16,o17,o18,o19,o20,o21,o22,o23}, {g12,g13,g14,g15}, dt, pt, 1, 1, 1;\n"
        "add.s64 dt, w1d, 3840; wgmma.mma_async.sync.aligned.m64n64k16.f16.f16.f16 {qz16,qz17,qz18,qz19,qz20,qz21,qz22,qz23,qz24,qz25,qz26,qz27,qz28,qz29,qz30,qz31}, {qa0,qa1,qa2,qa3}, dt, pf, 1, 1, 1;\n"
        "add.s64 dt, w1d, 3968; wgmma.mma_async.sync.aligned.m64n64k16.f16.f16.f16 {qz16,qz17,qz18,qz19,qz20,qz21,qz22,qz23,qz24,qz25,qz26,qz27,qz28,qz29,qz30,qz31}, {qa4,qa5,qa6,qa7}, dt, pt, 1, 1, 1;\n"
        "add.s64 dt, w1d, 4096; wgmma.mma_async.sync.aligned.m64n64k16.f16.f16.f16 {qz16,qz17,qz18,qz19,qz20,qz21,qz22,qz23,qz24,qz25,qz26,qz27,qz28,qz29,qz30,qz31}, {qa8,qa9,qa10,qa11}, dt, pt, 1, 1, 1;\n"
        "wgmma.commit_group.sync.aligned;\n"
        "@pz bra.uni B70;\n"
        "mov.b32 {xl, xh}, a0; tanh.approx.f16 xr, xl; cvt.u32.u16 lo0, xr; tanh.approx.f16 xr, xh; cvt.u32.u16 hi0, xr; mul.rn.f16x2 a1, qz3, p1; fma.rn.f16x2 p0, qz4, qz4, c; fma.rn.f16x2 g0, qz0, h0, qz0; prmt.b32 h1, lo1, hi1, 0x5410;\n"
        "mov.b32 {xl, xh}, a1; tanh.approx.f16 xr, xl; cvt.u32.u16 lo1, xr; tanh.approx.f16 xr, xh; cvt.u32.u16 hi1, xr; mul.rn.f16x2 a0, qz4, p0; fma.rn.f16x2 p1, qz5, qz5, c; fma.rn.f16x2 g1, qz1, h1, qz1; prmt.b32 h0, lo0, hi0, 0x5410;\n"
        "mov.b32 {xl, xh}, a0; tanh.approx.f16 xr, xl; cvt.u32.u16 lo0, xr; tanh.approx.f16 xr, xh; cvt.u32.u16 hi0, xr; mul.rn.f16x2 a1, qz5, p1; fma.rn.f16x2 p0, qz6, qz6, c; fma.rn.f16x2 g2, qz2, h0, qz2; prmt.b32 h1, lo1, hi1, 0x5410;\n"
        "mov.b32 {xl, xh}, a1; tanh.approx.f16 xr, xl; cvt.u32.u16 lo1, xr; tanh.approx.f16 xr, xh; cvt.u32.u16 hi1, xr; mul.rn.f16x2 a0, qz6, p0; fma.rn.f16x2 p1, qz7, qz7, c; fma.rn.f16x2 g3, qz3, h1, qz3; prmt.b32 h0, lo0, hi0, 0x5410;\n"
        "B70:\n"
        "wgmma.wait_group.sync.aligned 2;\n"
        "wgmma.fence.sync.aligned;\n"
        "add.s64 dt, w2d, 1024; wgmma.mma_async.sync.aligned.m64n96k16.f16.f16.f16 {o0,o1,o2,o3,o4,o5,o6,o7,o8,o9,o10,o11,o12,o13,o14,o15,o16,o17,o18,o19,o20,o21,o22,o23}, {g0,g1,g2,g3}, dt, pt, 1, 1, 1;\n"
        "add.s64 dt, w1d, 4224; wgmma.mma_async.sync.aligned.m64n64k16.f16.f16.f16 {qz16,qz17,qz18,qz19,qz20,qz21,qz22,qz23,qz24,qz25,qz26,qz27,qz28,qz29,qz30,qz31}, {qa12,qa13,qa14,qa15}, dt, pt, 1, 1, 1;\n"
        "add.s64 dt, w1d, 4352; wgmma.mma_async.sync.aligned.m64n64k16.f16.f16.f16 {qz16,qz17,qz18,qz19,qz20,qz21,qz22,qz23,qz24,qz25,qz26,qz27,qz28,qz29,qz30,qz31}, {qa16,qa17,qa18,qa19}, dt, pt, 1, 1, 1;\n"
        "add.s64 dt, w1d, 4480; wgmma.mma_async.sync.aligned.m64n64k16.f16.f16.f16 {qz16,qz17,qz18,qz19,qz20,qz21,qz22,qz23,qz24,qz25,qz26,qz27,qz28,qz29,qz30,qz31}, {qa20,qa21,qa22,qa23}, dt, pt, 1, 1, 1;\n"
        "wgmma.commit_group.sync.aligned;\n"
        "@pz bra.uni B74;\n"
        "mov.b32 {xl, xh}, a0; tanh.approx.f16 xr, xl; cvt.u32.u16 lo0, xr; tanh.approx.f16 xr, xh; cvt.u32.u16 hi0, xr; mul.rn.f16x2 a1, qz7, p1; fma.rn.f16x2 p0, qz8, qz8, c; fma.rn.f16x2 g4, qz4, h0, qz4; prmt.b32 h1, lo1, hi1, 0x5410;\n"
        "mov.b32 {xl, xh}, a1; tanh.approx.f16 xr, xl; cvt.u32.u16 lo1, xr; tanh.approx.f16 xr, xh; cvt.u32.u16 hi1, xr; mul.rn.f16x2 a0, qz8, p0; fma.rn.f16x2 p1, qz9, qz9, c; fma.rn.f16x2 g5, qz5, h1, qz5; prmt.b32 h0, lo0, hi0, 0x5410;\n"
        "mov.b32 {xl, xh}, a0; tanh.approx.f16 xr, xl; cvt.u32.u16 lo0, xr; tanh.approx.f16 xr, xh; cvt.u32.u16 hi0, xr; mul.rn.f16x2 a1, qz9, p1; fma.rn.f16x2 p0, qz10, qz10, c; fma.rn.f16x2 g6, qz6, h0, qz6; prmt.b32 h1, lo1, hi1, 0x5410;\n"
        "mov.b32 {xl, xh}, a1; tanh.approx.f16 xr, xl; cvt.u32.u16 lo1, xr; tanh.approx.f16 xr, xh; cvt.u32.u16 hi1, xr; mul.rn.f16x2 a0, qz10, p0; fma.rn.f16x2 p1, qz11, qz11, c; fma.rn.f16x2 g7, qz7, h1, qz7; prmt.b32 h0, lo0, hi0, 0x5410;\n"
        "B74:\n"
        "wgmma.wait_group.sync.aligned 2;\n"
        "wgmma.fence.sync.aligned;\n"
        "add.s64 dt, w2d, 1088; wgmma.mma_async.sync.aligned.m64n96k16.f16.f16.f16 {o0,o1,o2,o3,o4,o5,o6,o7,o8,o9,o10,o11,o12,o13,o14,o15,o16,o17,o18,o19,o20,o21,o22,o23}, {g4,g5,g6,g7}, dt, pt, 1, 1, 1;\n"
        "wgmma.commit_group.sync.aligned;\n"
        "@pz bra.uni B78;\n"
        "mov.b32 {xl, xh}, a0; tanh.approx.f16 xr, xl; cvt.u32.u16 lo0, xr; tanh.approx.f16 xr, xh; cvt.u32.u16 hi0, xr; mul.rn.f16x2 a1, qz11, p1; fma.rn.f16x2 p0, qz12, qz12, c; fma.rn.f16x2 g8, qz8, h0, qz8; prmt.b32 h1, lo1, hi1, 0x5410;\n"
        "mov.b32 {xl, xh}, a1; tanh.approx.f16 xr, xl; cvt.u32.u16 lo1, xr; tanh.approx.f16 xr, xh; cvt.u32.u16 hi1, xr; mul.rn.f16x2 a0, qz12, p0; fma.rn.f16x2 p1, qz13, qz13, c; fma.rn.f16x2 g9, qz9, h1, qz9; prmt.b32 h0, lo0, hi0, 0x5410;\n"
        "mov.b32 {xl, xh}, a0; tanh.approx.f16 xr, xl; cvt.u32.u16 lo0, xr; tanh.approx.f16 xr, xh; cvt.u32.u16 hi0, xr; mul.rn.f16x2 a1, qz13, p1; fma.rn.f16x2 p0, qz14, qz14, c; fma.rn.f16x2 g10, qz10, h0, qz10; prmt.b32 h1, lo1, hi1, 0x5410;\n"
        "mov.b32 {xl, xh}, a1; tanh.approx.f16 xr, xl; cvt.u32.u16 lo1, xr; tanh.approx.f16 xr, xh; cvt.u32.u16 hi1, xr; mul.rn.f16x2 a0, qz14, p0; fma.rn.f16x2 p1, qz15, qz15, c; fma.rn.f16x2 g11, qz11, h1, qz11; prmt.b32 h0, lo0, hi0, 0x5410;\n"
        "B78:\n"
        "wgmma.wait_group.sync.aligned 1;\n"
        "wgmma.fence.sync.aligned;\n"
        "add.s64 dt, w2d, 1152; wgmma.mma_async.sync.aligned.m64n96k16.f16.f16.f16 {o0,o1,o2,o3,o4,o5,o6,o7,o8,o9,o10,o11,o12,o13,o14,o15,o16,o17,o18,o19,o20,o21,o22,o23}, {g8,g9,g10,g11}, dt, pt, 1, 1, 1;\n"
        "wgmma.commit_group.sync.aligned;\n"
        "@!pm bra.uni BACKY;\n"
        "add.u32 tt, n, 1; and.b32 tt, tt, 1; mbarrier.try_wait.parity.shared::cta.b64 pw, [ybar], tt;\n"
        "@!pw bra.uni SPINY;\n"
        "BACKY:\n"
        "@pz bra.uni B80;\n"
        "and.b32 ad, %5, 0xffff; xor.b32 ad, ad, 0; add.u32 ad, ad, %4; ldmatrix.sync.aligned.m8n8.x4.shared.b16 {qa0,qa1,qa2,qa3}, [ad];\n"
        "and.b32 ad, %5, 0xffff; xor.b32 ad, ad, 32; add.u32 ad, ad, %4; ldmatrix.sync.aligned.m8n8.x4.shared.b16 {qa4,qa5,qa6,qa7}, [ad];\n"
        "and.b32 ad, %5, 0xffff; xor.b32 ad, ad, 64; add.u32 ad, ad, %4; ldmatrix.sync.aligned.m8n8.x4.shared.b16 {qa8,qa9,qa10,qa11}, [ad];\n"
        "and.b32 ad, %5, 0xffff; xor.b32 ad, ad, 96; add.u32 ad, ad, %4; ldmatrix.sync.aligned.m8n8.x4.shared.b16 {qa12,qa13,qa14,qa15}, [ad];\n"
        "shr.u32 ad, %5, 16; xor.b32 ad, ad, 0; add.u32 ad, ad, %4; ldmatrix.sync.aligned.m8n8.x4.shared.b16 {qa16,qa17,qa18,qa19}, [ad];\n"
        "shr.u32 ad, %5, 16; xor.b32 ad, ad, 32; add.u32 ad, ad, %4; ldmatrix.sync.aligned.m8n8.x4.shared.b16 {qa20,qa21,qa22,qa23}, [ad];\n"
        "mov.b32 {xl, xh}, a0; tanh.approx.f16 xr, xl; cvt.u32.u16 lo0, xr; tanh.approx.f16 xr, xh; cvt.u32.u16 hi0, xr; mul.rn.f16x2 a1, qz15, p1; fma.rn.f16x2 p0, qz16, qz16, c; fma.rn.f16x2 g12, qz12, h0, qz12; prmt.b32 h1, lo1, hi1, 0x5410;\n"
        "mov.b32 {xl, xh}, a1; tanh.approx.f16 xr, xl; cvt.u32.u16 lo1, xr; tanh.approx.f16 xr, xh; cvt.u32.u16 hi1, xr; mul.rn.f16x2 a0, qz16, p0; fma.rn.f16x2 p1, qz17, qz17, c; fma.rn.f16x2 g13, qz13, h1, qz13; prmt.b32 h0, lo0, hi0, 0x5410;\n"
        "B80:\n"
        "fence.proxy.async.shared::cta;\n"
        "add.u32 tt, id, 0;\n"
        "@pk bra.uni XLOAD;\n"
        "bar.arrive tt, 128;\n"
        "XLOADB:\n"
        "@pz bra.uni B82;\n"
        "mov.b32 {xl, xh}, a0; tanh.approx.f16 xr, xl; cvt.u32.u16 lo0, xr; tanh.approx.f16 xr, xh; cvt.u32.u16 hi0, xr; mul.rn.f16x2 a1, qz17, p1; fma.rn.f16x2 p0, qz18, qz18, c; fma.rn.f16x2 g14, qz14, h0, qz14; prmt.b32 h1, lo1, hi1, 0x5410;\n"
        "mov.b32 {xl, xh}, a1; tanh.approx.f16 xr, xl; cvt.u32.u16 lo1, xr; tanh.approx.f16 xr, xh; cvt.u32.u16 hi1, xr; mul.rn.f16x2 a0, qz18, p0; fma.rn.f16x2 p1, qz19, qz19, c; fma.rn.f16x2 g15, qz15, h1, qz15; prmt.b32 h0, lo0, hi0, 0x5410;\n"
        "B82:\n"
        "wgmma.fence.sync.aligned;\n"
        "add.s64 dt, w2d, 1216; wgmma.mma_async.sync.aligned.m64n96k16.f16.f16.f16 {o0,o1,o2,o3,o4,o5,o6,o7,o8,o9,o10,o11,o12,o13,o14,o15,o16,o17,o18,o19,o20,o21,o22,o23}, {g12,g13,g14,g15}, dt, pt, 1, 1, 1;\n"
        "wgmma.commit_group.sync.aligned;\n"
        "@!pm bra.uni SKIP1;\n"
        "wgmma.fence.sync.aligned;\n"
        "add.s64 dt, w1d, 0; wgmma.mma_async.sync.aligned.m64n64k16.f16.f16.f16 {qz0,qz1,qz2,qz3,qz4,qz5,qz6,qz7,qz8,qz9,qz10,qz11,qz12,qz13,qz14,qz15}, {qa0,qa1,qa2,qa3}, dt, pf, 1, 1, 1;\n"
        "add.s64 dt, w1d, 128; wgmma.mma_async.sync.aligned.m64n64k16.f16.f16.f16 {qz0,qz1,qz2,qz3,qz4,qz5,qz6,qz7,qz8,qz9,qz10,qz11,qz12,qz13,qz14,qz15}, {qa4,qa5,qa6,qa7}, dt, pt, 1, 1, 1;\n"
        "add.s64 dt, w1d, 256; wgmma.mma_async.sync.aligned.m64n64k16.f16.f16.f16 {qz0,qz1,qz2,qz3,qz4,qz5,qz6,qz7,qz8,qz9,qz10,qz11,qz12,qz13,qz14,qz15}, {qa8,qa9,qa10,qa11}, dt, pt, 1, 1, 1;\n"
        "SKIP1:\n"
        "@pz bra.uni B86;\n"
        "mov.b32 {xl, xh}, a0; tanh.approx.f16 xr, xl; cvt.u32.u16 lo0, xr; tanh.approx.f16 xr, xh; cvt.u32.u16 hi0, xr; mul.rn.f16x2 a1, qz19, p1; fma.rn.f16x2 p0, qz20, qz20, c; fma.rn.f16x2 g0, qz16, h0, qz16; prmt.b32 h1, lo1, hi1, 0x5410;\n"
        "mov.b32 {xl, xh}, a1; tanh.approx.f16 xr, xl; cvt.u32.u16 lo1, xr; tanh.approx.f16 xr, xh; cvt.u32.u16 hi1, xr; mul.rn.f16x2 a0, qz20, p0; fma.rn.f16x2 p1, qz21, qz21, c; fma.rn.f16x2 g1, qz17, h1, qz17; prmt.b32 h0, lo0, hi0, 0x5410;\n"
        "mov.b32 {xl, xh}, a0; tanh.approx.f16 xr, xl; cvt.u32.u16 lo0, xr; tanh.approx.f16 xr, xh; cvt.u32.u16 hi0, xr; mul.rn.f16x2 a1, qz21, p1; fma.rn.f16x2 p0, qz22, qz22, c; fma.rn.f16x2 g2, qz18, h0, qz18; prmt.b32 h1, lo1, hi1, 0x5410;\n"
        "mov.b32 {xl, xh}, a1; tanh.approx.f16 xr, xl; cvt.u32.u16 lo1, xr; tanh.approx.f16 xr, xh; cvt.u32.u16 hi1, xr; mul.rn.f16x2 a0, qz22, p0; fma.rn.f16x2 p1, qz23, qz23, c; fma.rn.f16x2 g3, qz19, h1, qz19; prmt.b32 h0, lo0, hi0, 0x5410;\n"
        "B86:\n"
        "wgmma.wait_group.sync.aligned 2;\n"
        "wgmma.fence.sync.aligned;\n"
        "add.s64 dt, w2d, 1280; wgmma.mma_async.sync.aligned.m64n96k16.f16.f16.f16 {o0,o1,o2,o3,o4,o5,o6,o7,o8,o9,o10,o11,o12,o13,o14,o15,o16,o17,o18,o19,o20,o21,o22,o23}, {g0,g1,g2,g3}, dt, pt, 1, 1, 1;\n"
        "wgmma.commit_group.sync.aligned;\n"
        "@!pm bra.uni SKIP2;\n"
        "wgmma.fence.sync.aligned;\n"
        "add.s64 dt, w1d, 384; wgmma.mma_async.sync.aligned.m64n64k16.f16.f16.f16 {qz0,qz1,qz2,qz3,qz4,qz5,qz6,qz7,qz8,qz9,qz10,qz11,qz12,qz13,qz14,qz15}, {qa12,qa13,qa14,qa15}, dt, pt, 1, 1, 1;\n"
        "add.s64 dt, w1d, 512; wgmma.mma_async.sync.aligned.m64n64k16.f16.f16.f16 {qz0,qz1,qz2,qz3,qz4,qz5,qz6,qz7,qz8,qz9,qz10,qz11,qz12,qz13,qz14,qz15}, {qa16,qa17,qa18,qa19}, dt, pt, 1, 1, 1;\n"
        "add.s64 dt, w1d, 640; wgmma.mma_async.sync.aligned.m64n64k16.f16.f16.f16 {qz0,qz1,qz2,qz3,qz4,qz5,qz6,qz7,qz8,qz9,qz10,qz11,qz12,qz13,qz14,qz15}, {qa20,qa21,qa22,qa23}, dt, pt, 1, 1, 1;\n"
        "SKIP2:\n"
        "wgmma.fence.sync.aligned;\n"
        "wgmma.commit_group.sync.aligned;\n"
        "@pz bra.uni B90;\n"
        "mov.b32 {xl, xh}, a0; tanh.approx.f16 xr, xl; cvt.u32.u16 lo0, xr; tanh.approx.f16 xr, xh; cvt.u32.u16 hi0, xr; mul.rn.f16x2 a1, qz23, p1; fma.rn.f16x2 p0, qz24, qz24, c; fma.rn.f16x2 g4, qz20, h0, qz20; prmt.b32 h1, lo1, hi1, 0x5410;\n"
        "mov.b32 {xl, xh}, a1; tanh.approx.f16 xr, xl; cvt.u32.u16 lo1, xr; tanh.approx.f16 xr, xh; cvt.u32.u16 hi1, xr; mul.rn.f16x2 a0, qz24, p0; fma.rn.f16x2 p1, qz25, qz25, c; fma.rn.f16x2 g5, qz21, h1, qz21; prmt.b32 h0, lo0, hi0, 0x5410;\n"
        "mov.b32 {xl, xh}, a0; tanh.approx.f16 xr, xl; cvt.u32.u16 lo0, xr; tanh.approx.f16 xr, xh; cvt.u32.u16 hi0, xr; mul.rn.f16x2 a1, qz25, p1; fma.rn.f16x2 p0, qz26, qz26, c; fma.rn.f16x2 g6, qz22, h0, qz22; prmt.b32 h1, lo1, hi1, 0x5410;\n"
        "mov.b32 {xl, xh}, a1; tanh.approx.f16 xr, xl; cvt.u32.u16 lo1, xr; tanh.approx.f16 xr, xh; cvt.u32.u16 hi1, xr; mul.rn.f16x2 a0, qz26, p0; fma.rn.f16x2 p1, qz27, qz27, c; fma.rn.f16x2 g7, qz23, h1, qz23; prmt.b32 h0, lo0, hi0, 0x5410;\n"
        "B90:\n"
        "wgmma.wait_group.sync.aligned 3;\n"
        "wgmma.fence.sync.aligned;\n"
        "add.s64 dt, w2d, 1344; wgmma.mma_async.sync.aligned.m64n96k16.f16.f16.f16 {o0,o1,o2,o3,o4,o5,o6,o7,o8,o9,o10,o11,o12,o13,o14,o15,o16,o17,o18,o19,o20,o21,o22,o23}, {g4,g5,g6,g7}, dt, pt, 1, 1, 1;\n"
        "wgmma.commit_group.sync.aligned;\n"
        "@pz bra.uni B94;\n"
        "mov.b32 {xl, xh}, a0; tanh.approx.f16 xr, xl; cvt.u32.u16 lo0, xr; tanh.approx.f16 xr, xh; cvt.u32.u16 hi0, xr; mul.rn.f16x2 a1, qz27, p1; fma.rn.f16x2 p0, qz28, qz28, c; fma.rn.f16x2 g8, qz24, h0, qz24; prmt.b32 h1, lo1, hi1, 0x5410;\n"
        "mov.b32 {xl, xh}, a1; tanh.approx.f16 xr, xl; cvt.u32.u16 lo1, xr; tanh.approx.f16 xr, xh; cvt.u32.u16 hi1, xr; mul.rn.f16x2 a0, qz28, p0; fma.rn.f16x2 p1, qz29, qz29, c; fma.rn.f16x2 g9, qz25, h1, qz25; prmt.b32 h0, lo0, hi0, 0x5410;\n"
        "mov.b32 {xl, xh}, a0; tanh.approx.f16 xr, xl; cvt.u32.u16 lo0, xr; tanh.approx.f16 xr, xh; cvt.u32.u16 hi0, xr; mul.rn.f16x2 a1, qz29, p1; fma.rn.f16x2 p0, qz30, qz30, c; fma.rn.f16x2 g10, qz26, h0, qz26; prmt.b32 h1, lo1, hi1, 0x5410;\n"
        "mov.b32 {xl, xh}, a1; tanh.approx.f16 xr, xl; cvt.u32.u16 lo1, xr; tanh.approx.f16 xr, xh; cvt.u32.u16 hi1, xr; mul.rn.f16x2 a0, qz30, p0; fma.rn.f16x2 p1, qz31, qz31, c; fma.rn.f16x2 g11, qz27, h1, qz27; prmt.b32 h0, lo0, hi0, 0x5410;\n"
        "B94:\n"
        "wgmma.wait_group.sync.aligned 1;\n"
        "wgmma.fence.sync.aligned;\n"
        "add.s64 dt, w2d, 1408; wgmma.mma_async.sync.aligned.m64n96k16.f16.f16.f16 {o0,o1,o2,o3,o4,o5,o6,o7,o8,o9,o10,o11,o12,o13,o14,o15,o16,o17,o18,o19,o20,o21,o22,o23}, {g8,g9,g10,g11}, dt, pt, 1, 1, 1;\n"
        "wgmma.commit_group.sync.aligned;\n"
        "@pz bra.uni B2;\n"
        "mov.b32 {xl, xh}, a0; tanh.approx.f16 xr, xl; cvt.u32.u16 lo0, xr; tanh.approx.f16 xr, xh; cvt.u32.u16 hi0, xr; mul.rn.f16x2 a1, qz31, p1; fma.rn.f16x2 p0, qz0, qz0, c; fma.rn.f16x2 g12, qz28, h0, qz28; prmt.b32 h1, lo1, hi1, 0x5410;\n"
        "mov.b32 {xl, xh}, a1; tanh.approx.f16 xr, xl; cvt.u32.u16 lo1, xr; tanh.approx.f16 xr, xh; cvt.u32.u16 hi1, xr; mul.rn.f16x2 a0, qz0, p0; fma.rn.f16x2 p1, qz1, qz1, c; fma.rn.f16x2 g13, qz29, h1, qz29; prmt.b32 h0, lo0, hi0, 0x5410;\n"
        "mov.b32 {xl, xh}, a0; tanh.approx.f16 xr, xl; cvt.u32.u16 lo0, xr; tanh.approx.f16 xr, xh; cvt.u32.u16 hi0, xr; mul.rn.f16x2 a1, qz1, p1; fma.rn.f16x2 p0, qz2, qz2, c; fma.rn.f16x2 g14, qz30, h0, qz30; prmt.b32 h1, lo1, hi1, 0x5410;\n"
        "mov.b32 {xl, xh}, a1; tanh.approx.f16 xr, xl; cvt.u32.u16 lo1, xr; tanh.approx.f16 xr, xh; cvt.u32.u16 hi1, xr; mul.rn.f16x2 a0, qz2, p0; fma.rn.f16x2 p1, qz3, qz3, c; fma.rn.f16x2 g15, qz31, h1, qz31; prmt.b32 h0, lo0, hi0, 0x5410;\n"
        "B2:\n"
        "wgmma.fence.sync.aligned;\n"
        "add.s64 dt, w2d, 1472; wgmma.mma_async.sync.aligned.m64n96k16.f16.f16.f16 {o0,o1,o2,o3,o4,o5,o6,o7,o8,o9,o10,o11,o12,o13,o14,o15,o16,o17,o18,o19,o20,o21,o22,o23}, {g12,g13,g14,g15}, dt, pt, 1, 1, 1;\n"
        "wgmma.commit_group.sync.aligned;\n"
        "@pz bra.uni BE;\n"
        "mov.b32 {xl, xh}, a0; tanh.approx.f16 xr, xl; cvt.u32.u16 lo0, xr; tanh.approx.f16 xr, xh; cvt.u32.u16 hi0, xr; mul.rn.f16x2 a1, qz3, p1; fma.rn.f16x2 p0, qz4, qz4, c; fma.rn.f16x2 g0, qz0, h0, qz0; prmt.b32 h1, lo1, hi1, 0x5410;\n"
        "mov.b32 {xl, xh}, a1; tanh.approx.f16 xr, xl; cvt.u32.u16 lo1, xr; tanh.approx.f16 xr, xh; cvt.u32.u16 hi1, xr; mul.rn.f16x2 a0, qz4, p0; fma.rn.f16x2 p1, qz5, qz5, c; fma.rn.f16x2 g1, qz1, h1, qz1; prmt.b32 h0, lo0, hi0, 0x5410;\n"
        "mov.b32 {xl, xh}, a0; tanh.approx.f16 xr, xl; cvt.u32.u16 lo0, xr; tanh.approx.f16 xr, xh; cvt.u32.u16 hi0, xr; mul.rn.f16x2 a1, qz5, p1; fma.rn.f16x2 p0, qz6, qz6, c; fma.rn.f16x2 g2, qz2, h0, qz2; prmt.b32 h1, lo1, hi1, 0x5410;\n"
        "mov.b32 {xl, xh}, a1; tanh.approx.f16 xr, xl; cvt.u32.u16 lo1, xr; tanh.approx.f16 xr, xh; cvt.u32.u16 hi1, xr; mul.rn.f16x2 a0, qz6, p0; fma.rn.f16x2 p1, qz7, qz7, c; fma.rn.f16x2 g3, qz3, h1, qz3; prmt.b32 h0, lo0, hi0, 0x5410;\n"
        "BE:\n"
        "wgmma.wait_group.sync.aligned 0;\n"
        "bra.uni LOOP;\n"
        "STORE:\n"
        "bar.sync tt, 128;\n"
        "setp.lt.s32 pr, n, 0;\n"
        "@pr bra.uni STOREB;\n"
        "cvt.u64.u32 gp, off; add.s64 gp, gp, %11;\n"
        "elect.sync _|pr, 0xffffffff;\n"
        "@pr cp.async.bulk.global.shared::cta.bulk_group [gp], [%4], 12288;\n"
        "@pr cp.async.bulk.commit_group;\n"
        "bra.uni STOREB;\n"
        "YLOAD:\n"
        "@!pm bra.uni YLOADP;\n"
        "cp.async.bulk.wait_group.read 0;\n"
        "sub.u32 ad, off, %8; cvt.u64.u32 gp, ad; add.s64 gp, gp, %11;\n"
        "elect.sync _|pr, 0xffffffff;\n"
        "@pr mbarrier.arrive.expect_tx.shared::cta.b64 _, [ybar], 12288;\n"
        "@pr cp.async.bulk.shared::cluster.global.mbarrier::complete_tx::bytes [%4], [gp], 12288, [ybar];\n"
        "YLOADP:\n"
        "cvt.u64.u32 gp, off; add.s64 gp, gp, %10;\n"
        "elect.sync _|pr, 0xffffffff;\n"
        "@pr cp.async.bulk.prefetch.L2.global.L2::cache_hint [gp], 12288, pol;\n"
        "bra.uni YLOADB;\n"
        "XLOAD:\n"
        "bar.sync tt, 128;\n"
        "cp.async.bulk.wait_group.read 0;\n"
        "cvt.u64.u32 gp, off; add.s64 gp, gp, %10;\n"
        "elect.sync _|pr, 0xffffffff;\n"
        "@pr mbarrier.arrive.expect_tx.shared::cta.b64 _, [xbar], 12288;\n"
        "@pr cp.async.bulk.shared::cluster.global.mbarrier::complete_tx::bytes.L2::cache_hint [%4], [gp], 12288, [xbar], pol;\n"
        "bra.uni XLOADB;\n"
        "SPINY: mov.u32 cnt, 0;\n"
        "SPINYL:\n"
        "add.u32 tt, n, 1; and.b32 tt, tt, 1; mbarrier.try_wait.parity.shared::cta.b64 pw, [ybar], tt;\n"
        "@pw bra.uni BACKY;\n"
        "add.u32 cnt, cnt, 1; setp.lt.u32 pw, cnt, 0x100000;\n"
        "@pw bra.uni SPINYL;\n"
        "trap;\n"
        "SPINX: mov.u32 cnt, 0;\n"
        "SPINXL:\n"
        "and.b32 tt, n, 1; mbarrier.try_wait.parity.shared::cta.b64 pw, [xbar], tt;\n"
        "@pw bra.uni BACKX;\n"
        "add.u32 cnt, cnt, 1; setp.lt.u32 pw, cnt, 0x100000;\n"
        "@pw bra.uni SPINXL;\n"
        "trap;\n"
        "SPINT: mov.u32 cnt, 0;\n"
        "SPINTL:\n"
        "mad.lo.u32 tt, n, 8, tbar; mbarrier.try_wait.parity.shared::cta.b64 pw, [tt], tpar;\n"
        "@pw bra.uni BACKT;\n"
        "add.u32 cnt, cnt, 1; setp.lt.u32 pw, cnt, 0x100000;\n"
        "@pw bra.uni SPINTL;\n"
        "trap;\n"
        "SPINW0: mov.u32 cnt, 0;\n"
        "SPINW0L:\n"
        "mov.u32 tt, 231208; mbarrier.try_wait.parity.shared::cta.b64 pw, [tt], 0;\n"
        "@pw bra.uni BACKW0;\n"
        "add.u32 cnt, cnt, 1; setp.lt.u32 pw, cnt, 0x100000;\n"
        "@pw bra.uni SPINW0L;\n"
        "trap;\n"
        "SPINW1: mov.u32 cnt, 0;\n"
        "SPINW1L:\n"
        "mov.u32 tt, 231216; mbarrier.try_wait.parity.shared::cta.b64 pw, [tt], 0;\n"
        "@pw bra.uni BACKW1;\n"
        "add.u32 cnt, cnt, 1; setp.lt.u32 pw, cnt, 0x100000;\n"
        "@pw bra.uni SPINW1L;\n"
        "trap;\n"
        "DONE:\n"
        "wgmma.wait_group.sync.aligned 0;\n"
        "}\n"
        :: "r"(prm.w1desc), "r"(prm.w2desc), "r"(c.wg), "r"(c.off), "r"(c.xs), "r"(c.a_offs), "r"(c.xs_offs), "r"(c.bias_addr),
           "r"(c.step), "r"(c.w), "l"(prm.x), "l"(prm.out)
        : "memory");
}

__device__ __forceinline__ float warp_sum(float v) {
#pragma unroll
    for (int s = 16; s >= 1; s >>= 1) v += __shfl_xor_sync(0xffffffffu, v, s);
    return v;
}
__device__ __forceinline__ float pow2f(int e) { return __uint_as_float((uint32_t)(e + 127) << 23); }
__device__ __forceinline__ int exponent_of(float v) { return (int)(__float_as_uint(v) >> 23) - 127; }
__device__ __forceinline__ float lds_bf16(uint32_t addr) {
    uint16_t v; asm volatile("ld.shared.u16 %0, [%1];" : "=h"(v) : "r"(addr) : "memory"); return bf_lo(v);
}

__device__ __forceinline__ void publish_bias(const Params& prm, uint32_t c, uint32_t tag) {
    const uint32_t lane = fresh_tid() & 31;
    const uint32_t col = sb + SM_W2 + (c >> 5) * 24576 + lane * 64 + ((((c >> 3) ^ (lane >> 1)) & 3) * 16) + (c & 7) * 2;
    float v = 0.0f;
#pragma unroll
    for (int k = 0; k < EX / 32; k++) v = fmaf(lds_bf16(col + k * 2048), lds_bf16(sb + SM_BETA + lane * 2 + k * 64), v);
    v = warp_sum(v);
    if (lane == 0) asm volatile("st.relaxed.gpu.global.v2.b32 [%0], {%1, %2};" ::"l"(prm.g->bias + c), "f"(v), "r"(tag) : "memory");
}
__device__ __forceinline__ void collect_bias(const Params& prm, uint32_t tag) {
    const uint32_t lane = fresh_tid() & 31;
    if (lane < 24) {
        const unsigned long long* src = prm.g->bias + 32 * (lane >> 3) + 8 * (lane & 3) + (lane & 4);
        uint32_t v[4], t[4], spins = 0;
        for (;;) {
#pragma unroll
            for (int k = 0; k < 4; k++)
                asm volatile("ld.relaxed.gpu.global.v2.b32 {%0, %1}, [%2];" : "=r"(v[k]), "=r"(t[k]) : "l"(src + k) : "memory");
            if (t[0] == tag && t[1] == tag && t[2] == tag && t[3] == tag) break;
            if (++spins > (1u << 22)) __trap();
        }
        sts128(sb + SM_BIAS + lane * 16, v[0], v[1], v[2], v[3]);
    }
    __syncwarp();
}
__device__ __forceinline__ float fetch_w2_row(uint32_t (&u)[12][4], uint32_t row, uint32_t sw) {
    uint32_t mx[4] = {};
#pragma unroll
    for (int a = 0; a < 3; a++)
#pragma unroll
        for (int k = 0; k < 4; k++) {
            asm volatile("ld.shared.v4.b32 {%0,%1,%2,%3}, [%4];"
                         : "=r"(u[a * 4][k]), "=r"(u[a * 4 + 1][k]), "=r"(u[a * 4 + 2][k]), "=r"(u[a * 4 + 3][k])
                         : "r"(row + a * 24576 + ((k * 16) ^ sw)) : "memory");
#pragma unroll
            for (int b = 0; b < 4; b++) asm("max.xorsign.abs.bf16x2 %0, %0, %1;" : "+r"(mx[b]) : "r"(u[a * 4 + b][k]));
        }
#pragma unroll
    for (int b = 1; b < 4; b++) asm("max.xorsign.abs.bf16x2 %0, %0, %1;" : "+r"(mx[0]) : "r"(mx[b]));
    return fmaxf(fabsf(bf_lo(mx[0])), fabsf(bf_hi(mx[0])));
}

__device__ __forceinline__ bool grn_stats(float ss, float gm, float bt, float top, int e, float& gx, float& inv, int& eo) {
    gx = sqrt_fast(fmaf(ss, INV_2A * INV_2A, 1e-6f));
    const float rt = sqrt_fast(ss + 1.0f) * INV_2A * top;
    uint32_t r[4] = {__float_as_uint(warp_sum(gx)), __reduce_max_sync(0xffffffffu, __float_as_uint(fmaf(bt, top, rt))),
                     __reduce_max_sync(0xffffffffu, __float_as_uint(rt * fabsf(gm) * gx)),
                     (uint32_t)__any_sync(0xffffffffu, !(ss >= 16.0f && ss < ACC_LIMIT))};
    if ((e & 31) == 0) sts128(sb + SM_SEL + (e >> 5) * 16, r[0], r[1], r[2], r[3]);
    MARK(6);
    named_sync(10, 512);
    lds128(r, sb + SM_SEL + min(e & 15, 11) * 16);
    float tot = (e & 15) < 12 ? __uint_as_float(r[0]) : 0.0f;
#pragma unroll
    for (int k = 8; k >= 1; k >>= 1) tot += __shfl_xor_sync(0xffffffffu, tot, k);
    inv = __fdividef(1.0f, fmaf(tot, 1.0f / EX, 1e-6f));
    const float bound = fmaf(__uint_as_float(__reduce_max_sync(0xffffffffu, r[2])), inv,
                             __uint_as_float(__reduce_max_sync(0xffffffffu, r[1]))) * EX;
    eo = min(max(exponent_of(bound), -90), 126) - 14;
    return __any_sync(0xffffffffu, r[3]);
}

__device__ __forceinline__ float exact_sums(const Params& prm) {
    const int lane = fresh_tid() & 31, warp = fresh_warp(), wg = warp >> 2;
    const uint32_t epoch = lds32(sb + SM_RED + (RED_EPOCH + 1) * 4), bar = sb + SM_BAR + BAR_W1 * 8;
    if (wg < 3) {
        uint32_t wa[2][24], d[2][16];
        float acc[2][2] = {};
        const uint32_t yd = prm.ydesc + ((SM_SPARE - SM_Y1) >> 4), wd = prm.w1desc + ((2 * wg * 12288 + 5 * 2048) >> 4);
        load_w1t(wa, wg, warp & 3, lane);
#pragma unroll 1
        for (int n = 0; n < ROWS_PER_CTA; n++) {
            if (warp == 0) {
                expect_tx(bar, TILE_BYTES);
                bulk_load(sb + SM_SPARE, (const char*)prm.out + (cta_tile0(fresh_cta()) + n * cta_stride(fresh_cta())), TILE_BYTES, bar);
            }
            mbar_wait(bar, (n + 1) & 1);
            gemm1_t<0>(d[0], wa[0], yd, wd);
            gemm1_t<1>(d[1], wa[1], yd, wd);
            wg_wait<0>();
            pin(d[0]); pin(d[1]);
            gelu_sumsq_f(d[0], acc[0]);
            gelu_sumsq_f(d[1], acc[1]);
            named_sync(1, 384);
        }
        publish_sums(acc, prm.g->sums[epoch & 1], &prm.g->count[1], wg, warp & 3, lane);
    }
    grid_wait(&prm.g->count[1], (epoch + 1) * NUM_CTAS);
    return __ldcg(prm.g->sums[epoch & 1] + fresh_tid() % EX);
}

template <bool FIRST> __device__ __forceinline__ void prepare_pass2(const Pass2& c, const Params& prm, float ss) {
    const int tid = fresh_tid(), lane = tid & 31, warp = fresh_warp(), wg = warp >> 2;
    const int e = tid >= EX ? tid - EX : tid;
    const uint32_t w2row = sb + SM_W2 + e * 64, sw = ((e >> 1) & 3) * 16;
    pass2_start(c, prm);
    MARK(2);
    if (wg) {
        uint32_t u[12][4];
        mbar_wait_c<0>(sb + SM_BAR + BAR_W2 * 8);
        const float top = fetch_w2_row(u, w2row, sw);
        MARK(3);
        const float gm = lds_bf16(sb + SM_GAMMA + e * 2), bt = fabsf(lds_bf16(sb + SM_BETA + e * 2));
        if (FIRST) {
            const uint32_t epoch = lds32(sb + SM_RED + RED_EPOCH * 4);
            if (wg == 3) named_sync(11, EX);
            if (warp == 12) collect_bias(prm, epoch + 1);
            MARK(4);
            ss = collect_fast(acc_word(prm, epoch, e));
            if (tid == 416 && fresh_cta() == 0) prm.g->count[0] = epoch + 1;
        }
        if (warp == 4) TS(4);
        MARK(5);
        float gx, inv;
        int eo;
        const bool redo = (grn_stats(ss, gm, bt, top, e, gx, inv, eo) || FORCE_EXACT) && FIRST;
        MARK(8);
        const float up = pow2f(eo), dn = pow2f(-eo);
        if (warp == 4) {
            if (lane == 24) sts64(sb + SM_RED + RED_SCALE * 4, pack_bf2(up, up), redo);
            if (lane < 24 && !redo) {
                uint32_t b[4];
                lds128(b, sb + SM_BIAS + lane * 16);
                const uint32_t p0 = pack_h2(__uint_as_float(b[0]) * dn, __uint_as_float(b[1]) * dn);
                const uint32_t p1 = pack_h2(__uint_as_float(b[2]) * dn, __uint_as_float(b[3]) * dn);
                sts128(sb + SM_BIAS + lane * 16, p0, p0, p1, p1);
            }
            __syncwarp();
            mbar_arrive_if(sb + SM_BAR + BAR_STAT * 8, lane == 0);
        }
        if (!redo) {
            float sc = fmaf(gm, gx * inv, 1.0f) * INV_2A;
            if (eo > 6) {
                const uint32_t dn2 = pack_bf2(dn, dn);
#pragma unroll
                for (int k = 0; k < 48; k++) u[k >> 2][k & 3] = bf2_mul(u[k >> 2][k & 3], dn2);
            } else {
                sc *= dn;
            }
            const uint32_t s2 = pack_bf2(sc * 0x1p-112f, sc * 0x1p-112f);
#pragma unroll
            for (int k = 0; k < 12; k++) {
                uint32_t v[4];
#pragma unroll
                for (int b = 0; b < 4; b++) {
                    v[b] = bf2_mul(u[k][b], s2);
                    v[b] += (v[b] & 0x7fff7fffu) * 7u;
                }
                sts128(w2row + (k >> 2) * 24576 + (((k & 3) * 16) ^ sw), v[0], v[1], v[2], v[3]);
            }
            MARK(9);
            fence_async_smem();
            __syncwarp();
            mbar_arrive_if(sb + SM_BAR + (BAR_ROWS + (wg != 3)) * 8, lane == 0);
        }
        if (warp == 4) TS(5);
    } else {
        asm volatile("bar.arrive 10, 512;" ::: "memory");
    }
}

__device__ __forceinline__ Pass2 pass2_setup() {
    const int lane = fresh_tid() & 31, wg = fresh_warp() >> 2, w = fresh_warp() & 3, arow = 16 * w + (lane & 15);
    Pass2 c;
    c.wg = wg;
    c.w = w;
    c.off = cta_tile0(fresh_cta()) + (ROWS_PER_CTA - 1 - wg) * cta_stride(fresh_cta());
    c.step = 4 * cta_stride(fresh_cta());
    c.xs = wg == 3 ? sb + SM_BUF3 : sb + SM_Y1 + (wg == 2 ? 2 : 1 - wg) * SLOT_BYTES;
    static_assert((ROWS_PER_CTA - 1) % NX == 1, "slot of the last tile");
    c.a_offs = (arow * 128 + (((lane >> 4) ^ (arow & 7)) * 16)) |
               (8192 + arow * 64 + (((lane >> 4) ^ ((arow >> 1) & 3)) * 16)) << 16;
    const int g = lane >> 2, px = 33 * (g & 1) + 4 * (g >> 1) + 16 * (w >> 1) + 2 * (w & 1);
    c.xs_offs = (px * 192 + (lane & 3) * 16) | ((px ^ 1) * 192 + (lane & 3) * 16) << 16;
    c.bias_addr = sb + SM_BIAS + (lane & 3) * 16;
    return c;
}

__global__ void __launch_bounds__(512, 1) convnext_kernel(const __grid_constant__ Params prm) {
    extern __shared__ __align__(1024) uint8_t smem[];
    if ((uint32_t)__cvta_generic_to_shared(smem) != sb) __trap();
    if (fresh_warp() == 0) {
        if (fresh_tid() == 0) {
#pragma unroll
            for (int k = 0; k < NX; k++) mbar_init(sb + SM_XFULL + k * SLOT_BYTES, 2);
            mbar_init(sb + SM_BAR + BAR_DW * 8, 1);
            fence_async_smem();
        }
        __syncwarp();
        expect_tx(sb + SM_BAR + BAR_DW * 8, 9 * CH * 2);
        bulk_load(sb + SM_Y1, prm.dw, 9 * CH * 2, sb + SM_BAR + BAR_DW * 8);
        const RowCopy rc = row_copy(prm);
#pragma unroll
        for (int k = 0; k < NX; k++) issue_row_load(rc, k, k);
        if (fresh_tid() == 0) {
#pragma unroll
            for (int k = 0; k < NX; k++) {
                mbar_init(sb + SM_Y1FULL + k * SLOT_BYTES, 4);
                mbar_init(sb + SM_Y1EMPTY + k * SLOT_BYTES, 12);
            }
            mbar_init(sb + SM_BAR + BAR_DUMMY * 8, 4);
        }
        __syncwarp();
        SMARK(4);
    } else if (fresh_warp() == 15) {
        const uint32_t cta = fresh_cta();
        bulk_prefetch((const char*)prm.w1 + cta * (CH * EX * 2 / NUM_CTAS), CH * EX * 2 / NUM_CTAS);
        bulk_prefetch(prm.dw, 9 * CH * 2);
        bulk_prefetch((const char*)prm.x + (cta_tile0(cta) - cta_stride(cta)), TILE_BYTES);
    }
    if (fresh_warp() >= 12) {
        Producer pc;
        SMARK(0);
        asm volatile("setmaxnreg.inc.sync.aligned.u32 %0;" ::"n"(PRODUCER_REGS));
        SMARK(1);
        const int w = fresh_warp() & 3, lane = fresh_tid() & 31;
        const int j = lane & 7, hb = (lane >> 3) & 1, base = 4 * (2 * w + (lane >> 4));
        pc.lane = lane; pc.warp = w;
        pc.xoff[0] = hb * XHALF_B + base * 192 + j * 16;
        pc.xoff[1] = hb * XHALF_B + base * 192 + 128 + j * 8;
        const int grp = 4 * w + (lane >> 3);
#pragma unroll
        for (int o = 0; o < 2; o++) {
            const int row = (grp & 7) + 8 * (o ^ hb) + 32 * (grp >> 3);
            pc.yoff[0][o] = row * 128 + ((j ^ (row & 7)) * 16);
            pc.yoff[1][o] = 8192 + row * 64 + (((j >> 1) ^ ((row >> 1) & 3)) * 16) + (j & 1) * 8;
        }
        pc.stat = sb + SM_STAT + (8 * w + (lane >> 2)) * 32;
        pc.own = pc.stat + (lane & 3) * 8;
        const int dstep = fresh_cta() & 8 ? 3 * CH * 2 : -3 * CH * 2;
        named_sync(0, 512);
        mbar_wait_c<0>(sb + SM_BAR + BAR_DW * 8);
        SMARK(8);
#pragma unroll
        for (int tap = 0; tap < 9; tap++) {
            const uint32_t dw = sb + SM_Y1 + (3 + tap % 3) * CH * 2 + (tap / 3 - 1) * dstep;
            lds128(pc.w[tap], dw + j * 16);
            asm volatile("ld.shared.v2.b32 {%0,%1}, [%2];" : "=r"(pc.w[tap][4]), "=r"(pc.w[tap][5]) : "r"(dw + 128 + j * 8) : "memory");
        }
#pragma unroll
        for (int tap = 0; tap < 9; tap++)
#pragma unroll
            for (int u = 0; u < 6; u++) pc.w[tap][u] = bf2_mul(pc.w[tap][u], TAP_SCALE_BF2);
        produce(pc, prm);
        TS(9);
        asm volatile("setmaxnreg.dec.sync.aligned.u32 %0;" ::"n"(EVEN_REGS));
        if (fresh_warp() == 12) {
            mbar_wait_c<0>(sb + SM_BAR + BAR_W2 * 8);
            if (fresh_cta() < CH) publish_bias(prm, fresh_cta(), lds32(sb + SM_RED + RED_EPOCH * 4) + 1);
        }
    } else {
        asm volatile("setmaxnreg.dec.sync.aligned.u32 %0;" ::"n"(CONSUMER_REGS));
        {
            const int tid = fresh_tid(), warp = fresh_warp(), lane = tid & 31;
            uint32_t cnt[2];
            if (warp == 1) {
                if (lane == 0) {
                    mbar_init(sb + SM_BAR + BAR_W1 * 8, 1);
                    mbar_init(sb + SM_BAR + BAR_W1B * 8, 1);
                    fence_async_smem();
                }
                __syncwarp();
#pragma unroll
                for (int h = 0; h < 2; h++) {
                    const uint32_t bar = sb + SM_BAR + (h ? BAR_W1B : BAR_W1) * 8;
                    expect_tx(bar, CH * EX);
#pragma unroll
                    for (int q = h; q < 6; q += 2) tma_load_2d(sb + SM_W1 + q * 12288, &prm.w1_map, 64 * q, 0, bar);
                }
            } else if (warp == 2) {
                if (lane < 2) asm volatile("prefetch.tensormap [%0];" ::"l"(&prm.w1_map + lane) : "memory");
            } else if (warp == 3) {
                const uint32_t one = (lane & 5) == ((lane & 8) >> 1) + (lane >> 4) ? 0x3f803f80u : 0u;
                sts128(sb + SM_SEL + lane * 16, one, one, one, one);
                fence_async_smem();
            } else if (tid - 128u < NX * 12 && ((fresh_cta() + 1) & 7) < 2) {
                const int k = tid - 128;
                sts128(sb + SM_X + (k / 12) * SLOT_BYTES + ((fresh_cta() & 7) == 0 ? 0 : XHALF_B + 33 * 192) + (k % 12) * 16, 0, 0, 0, 0);
            }
            __syncwarp();
            asm volatile("ld.relaxed.gpu.global.v2.u32 {%0, %1}, [%2];" : "=r"(cnt[0]), "=r"(cnt[1]) : "l"(prm.g->count) : "memory");
            SMARK(0);
            named_sync(0, 512);
            if (tid == 256) {
                sts64(sb + SM_RED + RED_EPOCH * 4, cnt[0], cnt[1] / NUM_CTAS);
#pragma unroll
                for (int k = 0; k < BAR_W1B; k++)
                    if (k != BAR_W1 && k != BAR_DUMMY) mbar_init(sb + SM_BAR + k * 8, k < BAR_TURN || k == BAR_STAT ? 1 : k == BAR_ROWS + 1 ? 8 : 4);
#pragma unroll
                for (int k = 0; k < 3; k++) mbar_arrive_if(sb + SM_BAR + (BAR_Y2FULL + k) * 8, true);
            }
            if (fresh_cta() == 0) *acc_word(prm, cnt[0] + 1, tid) = 0;
            if (fresh_cta() == 1) prm.g->sums[~(cnt[1] / NUM_CTAS) & 1][tid] = 0.0f;
            __syncwarp();
            SMARK(1);
            mbar_wait_c<0>(sb + SM_BAR + BAR_W1 * 8);
            SMARK(2);
        }

        const int tid = fresh_tid(), lane = tid & 31, wg = fresh_warp() >> 2, w = fresh_warp() & 3;
        float acc[2][2];
        const int c = 8 * (lane >> 4) + (lane & 7), ck = 2 * w + ((lane >> 3) & 1);
        consume(acc, sb + SM_W1 + 2 * wg * 12288 + c * 128 + ((ck ^ (c & 7)) * 16), prm.ydesc,
                prm.w1desc + (((2 * wg + 1) * 12288 + 5 * 2048) >> 4), wg * SLOT_BYTES, make_duty(prm, wg, w), w, lane, prm);
        publish_fast(prm, acc, lds32(sb + SM_RED + RED_EPOCH * 4), wg, w, lane);
        if (wg) asm volatile("bar.arrive 11, 384;" ::: "memory");
        MARK(0);
        bulk_wait_all();
        if (wg == 0) TS(3);
        asm volatile("setmaxnreg.inc.sync.aligned.u32 %0;" ::"n"(EVEN_REGS));
    }

    {
        asm volatile(PASS2_STATE);
        MARK(1);
        Pass2 c = pass2_setup();
        prepare_pass2<true>(c, prm, 0.0f);
        if (pass2_head(c, 0)) {
            const float ss = exact_sums(prm);
            c = pass2_setup();
            prepare_pass2<false>(c, prm, ss);
            pass2_head(c, 1);
        }

        pass2_tiles(c, prm);
        bulk_wait_read<0>();
        MARK(13);
    }
}

}

extern "C" void kernel_launch(void* const* d_in, const int* in_sizes, int n_in, void* d_out, int out_size) {
    (void)in_sizes; (void)n_in; (void)out_size;
    typedef CUresult (*EncodeFn)(CUtensorMap*, CUtensorMapDataType, cuuint32_t, void*, const cuuint64_t*, const cuuint64_t*,
                                 const cuuint32_t*, const cuuint32_t*, CUtensorMapInterleave, CUtensorMapSwizzle,
                                 CUtensorMapL2promotion, CUtensorMapFloatOOBfill);
    void* fn = nullptr;
    cudaDriverEntryPointQueryResult status;
    cudaGetDriverEntryPoint("cuTensorMapEncodeTiled", &fn, cudaEnableDefault, &status);
    const EncodeFn encode = (EncodeFn)fn;
    const cuuint32_t ones[2] = {1, 1};

    Params p;
    {
        const cuuint64_t dims[2] = {EX, CH}, strides[1] = {EX * 2};
        const cuuint32_t box[2] = {64, CH};
        encode(&p.w1_map, CU_TENSOR_MAP_DATA_TYPE_BFLOAT16, 2, d_in[2], dims, strides, box, ones,
               CU_TENSOR_MAP_INTERLEAVE_NONE, CU_TENSOR_MAP_SWIZZLE_128B, CU_TENSOR_MAP_L2_PROMOTION_NONE,
               CU_TENSOR_MAP_FLOAT_OOB_FILL_NONE);
    }
    {
        const cuuint64_t dims[2] = {CH, EX}, strides[1] = {CH * 2};
        const cuuint32_t box[2] = {32, 192};
        encode(&p.w2_map, CU_TENSOR_MAP_DATA_TYPE_BFLOAT16, 2, d_in[3], dims, strides, box, ones,
               CU_TENSOR_MAP_INTERLEAVE_NONE, CU_TENSOR_MAP_SWIZZLE_64B, CU_TENSOR_MAP_L2_PROMOTION_NONE,
               CU_TENSOR_MAP_FLOAT_OOB_FILL_NONE);
    }
    p.x = (const __nv_bfloat16*)d_in[0];
    p.dw = (const __nv_bfloat16*)d_in[1];
    p.w1 = (const __nv_bfloat16*)d_in[2];
    p.gamma = (const __nv_bfloat16*)d_in[4];
    p.beta = (const __nv_bfloat16*)d_in[5];
    p.out = (__nv_bfloat16*)d_out;
    cudaGetSymbolAddress((void**)&p.g, g_scratch);
    p.w1desc = desc_lo(sb + SM_W1, 12288);
    p.w2desc = desc_lo(sb + SM_W2, 24576);
    p.ydesc = desc_lo(sb + SM_Y1, 16);
    p.ydesc64[0] = (0x40000040ull << 32) | p.ydesc;
    p.ydesc64[1] = (0x80000020ull << 32) | (p.ydesc + 512);
    for (int k = 0; k < 3; k++) p.sel[k] = (8ull << 32) | desc_lo(sb + SM_SEL + k * 128, k == 2 ? 128 : 0);
    constexpr int smem_bytes = SM_TOTAL;
    cudaFuncSetAttribute(convnext_kernel, cudaFuncAttributeMaxDynamicSharedMemorySize, smem_bytes);
    convnext_kernel<<<NUM_CTAS, 512, smem_bytes>>>(p);
}
```

```cpp
#include <cuda.h>
#include <cuda_runtime.h>
#include <cuda_bf16.h>
#include <stdint.h>

namespace {

constexpr int IMG_W = 512, CH = 96, EX = 384;
constexpr int TILE_PX = 64;
constexpr int ROWS_PER_CTA = 32;
constexpr int NUM_CTAS = 128;
constexpr int STEPS = ROWS_PER_CTA + 2;
constexpr int ROW_BYTES = IMG_W * CH * 2;

#define FORCE_EXACT 0
#define PREGS 200
#define CREGS 104
constexpr int PRODUCER_REGS = PREGS, CONSUMER_REGS = CREGS, EVEN_REGS = 128;

constexpr int XHALF_BYTES = 34 * 192;
constexpr int XHALF_B = XHALF_BYTES + 64;
constexpr int XROW_BYTES = XHALF_B + XHALF_BYTES + 64;
constexpr int L2_AHEAD = 2;
constexpr int NX = 3;
constexpr int TILE_BYTES = TILE_PX * 192;
constexpr int NY1 = 3;

constexpr uint32_t sb = 1024;
constexpr int SM_W1 = 0;
constexpr int SM_W2 = 73728;
constexpr int SM_RING = 147456;
constexpr int SLOT_BYTES = 26624;
constexpr int SM_Y1 = SM_RING;
constexpr int SM_X = SM_Y1 + TILE_BYTES;
constexpr int SM_STAT = SM_X + XROW_BYTES;
constexpr int SM_BUF3 = SM_X + SLOT_BYTES, SM_SPARE = SM_X;
constexpr int SM_SEL = SM_RING + NX * SLOT_BYTES;
constexpr int SM_BIAS = SM_SEL + 512;
constexpr int SM_GAMMA = SM_BIAS + 384;
constexpr int SM_BETA = SM_GAMMA + EX * 2;
constexpr int SM_RED = SM_BETA + EX * 2;
constexpr int SM_BAR = SM_RED + 16;
constexpr int BAR_Y2FULL = 0, BAR_XSFULL = 4, BAR_W1 = 8, BAR_W2 = 9, BAR_W1B = 10, BAR_TURN = 11, BAR_ROWS = 51,
              BAR_STAT = 53, BAR_DW = 54, BAR_COUNT = 55;
constexpr int SM_GO = SM_BAR + BAR_COUNT * 8, GO_COUNT = ROWS_PER_CTA + 2 * NX;
constexpr int SM_YFULL = SM_GO + (GO_COUNT + 1) * 8;
constexpr int SM_TOTAL = SM_YFULL + (ROWS_PER_CTA + 1) * 8;
static_assert(SM_STAT + TILE_PX * 16 <= SM_RING + SLOT_BYTES && XROW_BYTES >= TILE_BYTES && SM_X % 1024 == 0, "ring layout");
static_assert(SM_TOTAL <= 232448, "smem budget");
static_assert(SM_STAT % 128 == 0 && SM_BIAS % 16 == 0 && SM_BAR % 8 == 0 && SLOT_BYTES % 1024 == 0, "alignment");

static_assert(NX == NY1, "both rings are walked with one index");
constexpr int RED_EPOCH = 0, RED_SCALE = 2;

constexpr float GELU_A = 0.32920349f;
constexpr uint32_t GELU_C_H2 = 0x40D940D9u;
constexpr float INV_2A = 1.0f / (2.0f * GELU_A);

constexpr uint32_t TAP_SCALE_BF2 = 0x2B802B80u;
constexpr float LN_EPS_SCALED = 1e-5f * 0x1p-80f;
constexpr float RSTD_SCALE = GELU_A * 0x1p-112f;

struct Scratch {
    unsigned long long acc[2][EX / 4 * 32];
    unsigned long long bias[CH];
    float sums[2][EX];
    uint4 zero_row[66 * 192 / 16];
    unsigned int count[2];
};
__device__ __align__(256) Scratch g_scratch;
constexpr float ACC_LIMIT = 0x1p30f;

#define TS(k)
#define ASM_TS
#define MARK(k)
#define SMARK(k)
#define ASM_MARK
#define ASM_SMARK
#define ASM_TRC(it)

__device__ __forceinline__ void mbar_init(uint32_t bar, uint32_t count) {
    asm volatile("mbarrier.init.shared::cta.b64 [%0], %1;" ::"r"(bar), "r"(count) : "memory");
}
__device__ __forceinline__ void mbar_arrive_if(uint32_t bar, bool pred) {
    asm volatile("{\n.reg .pred p;\nsetp.ne.u32 p, %1, 0;\n@p mbarrier.arrive.shared::cta.b64 _, [%0];\n}\n"
                 ::"r"(bar), "r"((uint32_t)pred) : "memory");
}
__device__ __forceinline__ void mbar_wait(uint32_t bar, uint32_t parity) {
    asm volatile(
        "{\n.reg .pred p;\n.reg .u32 n;\n"
        "mbarrier.try_wait.parity.shared::cta.b64 p, [%0], %1;\n"
        "@p bra.uni WAIT_DONE;\n"
        "mov.u32 n, 0;\n"
        "WAIT_LOOP:\n"
        "mbarrier.try_wait.parity.shared::cta.b64 p, [%0], %1;\n"
        "@p bra.uni WAIT_DONE;\n"
        "mbarrier.try_wait.parity.shared::cta.b64 p, [%0], %1;\n"
        "@p bra.uni WAIT_DONE;\n"
        "mbarrier.try_wait.parity.shared::cta.b64 p, [%0], %1;\n"
        "@p bra.uni WAIT_DONE;\n"
        "add.u32 n, n, 1;\nsetp.lt.u32 p, n, 0x40000;\n"
        "@p bra.uni WAIT_LOOP;\n"
        "trap;\n"
        "WAIT_DONE:\n}\n"
        ::"r"(bar), "r"(parity) : "memory");
}
template <int PARITY> __device__ __forceinline__ void mbar_wait_c(uint32_t bar) {
    asm volatile(
        "{\n.reg .pred p;\n.reg .u32 n;\n"
        "mbarrier.try_wait.parity.shared::cta.b64 p, [%0], %1;\n"
        "@p bra.uni WAIT_DONE;\n"
        "mov.u32 n, 0;\n"
        "WAIT_LOOP:\n"
        "mbarrier.try_wait.parity.shared::cta.b64 p, [%0], %1;\n"
        "@p bra.uni WAIT_DONE;\n"
        "mbarrier.try_wait.parity.shared::cta.b64 p, [%0], %1;\n"
        "@p bra.uni WAIT_DONE;\n"
        "mbarrier.try_wait.parity.shared::cta.b64 p, [%0], %1;\n"
        "@p bra.uni WAIT_DONE;\n"
        "add.u32 n, n, 1;\nsetp.lt.u32 p, n, 0x40000;\n"
        "@p bra.uni WAIT_LOOP;\n"
        "trap;\n"
        "WAIT_DONE:\n}\n"
        ::"r"(bar), "n"(PARITY) : "memory");
}
#define ELECTED(body) "{\n.reg .pred p;\nelect.sync _|p, 0xffffffff;\n" body "}\n"
__device__ __forceinline__ void expect_tx(uint32_t bar, uint32_t bytes) {
    asm volatile(ELECTED("@p mbarrier.arrive.expect_tx.shared::cta.b64 _, [%0], %1;\n") ::"r"(bar), "r"(bytes) : "memory");
}
__device__ __forceinline__ void bulk_load(uint32_t dst, const void* src, uint32_t bytes, uint32_t bar) {
    asm volatile(ELECTED("@p cp.async.bulk.shared::cluster.global.mbarrier::complete_tx::bytes [%0], [%1], %2, [%3];\n")
                 ::"r"(dst), "l"(src), "r"(bytes), "r"(bar) : "memory");
}
__device__ __forceinline__ void bulk_prefetch(const void* src, uint32_t bytes) {
    asm volatile(ELECTED("@p cp.async.bulk.prefetch.L2.global [%0], %1;\n") ::"l"(src), "r"(bytes) : "memory");
}
__device__ __forceinline__ void tma_load_2d(uint32_t dst, const CUtensorMap* map, int c0, int c1, uint32_t bar) {
    asm volatile(ELECTED("@p cp.async.bulk.tensor.2d.shared::cluster.global.mbarrier::complete_tx::bytes [%0], [%1, {%2, %3}], [%4];\n")
                 ::"r"(dst), "l"(map), "r"(c0), "r"(c1), "r"(bar) : "memory");
}
template <int N> __device__ __forceinline__ void bulk_wait_read() {
    asm volatile("cp.async.bulk.wait_group.read %0;" ::"n"(N) : "memory");
}
__device__ __forceinline__ void bulk_wait_all() { asm volatile("cp.async.bulk.wait_group 0;" ::: "memory"); }
__device__ __forceinline__ void fence_async_smem() { asm volatile("fence.proxy.async.shared::cta;" ::: "memory"); }
__device__ __forceinline__ void named_sync(int id, int n) { asm volatile("bar.sync %0, %1;" ::"r"(id), "r"(n) : "memory"); }

__device__ __forceinline__ void sts64(uint32_t addr, uint32_t a, uint32_t b) {
    asm volatile("st.shared.v2.b32 [%0], {%1,%2};" ::"r"(addr), "r"(a), "r"(b) : "memory");
}
__device__ __forceinline__ void sts128(uint32_t addr, uint32_t a, uint32_t b, uint32_t c, uint32_t d) {
    asm volatile("st.shared.v4.b32 [%0], {%1,%2,%3,%4};" ::"r"(addr), "r"(a), "r"(b), "r"(c), "r"(d) : "memory");
}
__device__ __forceinline__ void ldsm4_t(uint32_t* r, uint32_t addr) {
    asm volatile("ldmatrix.sync.aligned.m8n8.x4.trans.shared.b16 {%0,%1,%2,%3}, [%4];"
                 : "=r"(r[0]), "=r"(r[1]), "=r"(r[2]), "=r"(r[3]) : "r"(addr) : "memory");
}
__device__ __forceinline__ void lds128(uint32_t* v, uint32_t addr) {
    asm volatile("ld.shared.v4.b32 {%0,%1,%2,%3}, [%4];"
                 : "=r"(v[0]), "=r"(v[1]), "=r"(v[2]), "=r"(v[3]) : "r"(addr) : "memory");
}
__device__ __forceinline__ uint32_t lds32(uint32_t addr) {
    uint32_t v; asm volatile("ld.shared.b32 %0, [%1];" : "=r"(v) : "r"(addr) : "memory"); return v;
}
__device__ __forceinline__ void sts32(uint32_t addr, uint32_t v) {
    asm volatile("st.shared.b32 [%0], %1;" ::"r"(addr), "r"(v) : "memory");
}

__device__ __forceinline__ uint32_t bf2_fma(uint32_t a, uint32_t b, uint32_t c) {
    uint32_t d; asm("fma.rn.bf16x2 %0, %1, %2, %3;" : "=r"(d) : "r"(a), "r"(b), "r"(c)); return d;
}
__device__ __forceinline__ uint32_t bf2_mul(uint32_t a, uint32_t b) {
    uint32_t d; asm("mul.rn.bf16x2 %0, %1, %2;" : "=r"(d) : "r"(a), "r"(b)); return d;
}
__device__ __forceinline__ uint32_t bf2_add(uint32_t a, uint32_t b) {
    uint32_t d; asm("add.rn.bf16x2 %0, %1, %2;" : "=r"(d) : "r"(a), "r"(b)); return d;
}
__device__ __forceinline__ uint32_t h2_fma(uint32_t a, uint32_t b, uint32_t c) {
    uint32_t d; asm("fma.rn.f16x2 %0, %1, %2, %3;" : "=r"(d) : "r"(a), "r"(b), "r"(c)); return d;
}
__device__ __forceinline__ uint32_t h2_mul(uint32_t a, uint32_t b) {
    uint32_t d; asm("mul.rn.f16x2 %0, %1, %2;" : "=r"(d) : "r"(a), "r"(b)); return d;
}
__device__ __forceinline__ uint32_t h2_tanh(uint32_t a) {
    uint32_t d; asm("tanh.approx.f16x2 %0, %1;" : "=r"(d) : "r"(a)); return d;
}
__device__ __forceinline__ float bf_lo(uint32_t v) { return __uint_as_float(v << 16); }
__device__ __forceinline__ float bf_hi(uint32_t v) { return __uint_as_float(v & 0xffff0000u); }
__device__ __forceinline__ uint32_t pack_h2(float lo, float hi) {
    uint32_t d; asm("cvt.rn.f16x2.f32 %0, %1, %2;" : "=r"(d) : "f"(hi), "f"(lo)); return d;
}
__device__ __forceinline__ uint32_t pack_bf2(float lo, float hi) {
    uint32_t d; asm("cvt.rn.bf16x2.f32 %0, %1, %2;" : "=r"(d) : "f"(hi), "f"(lo)); return d;
}
__device__ __forceinline__ void h2_unpack(uint32_t v, float& lo, float& hi) {
    asm("{\n.reg .b16 l, h;\nmov.b32 {l, h}, %2;\ncvt.f32.f16 %0, l;\ncvt.f32.f16 %1, h;\n}\n" : "=f"(lo), "=f"(hi) : "r"(v));
}

__device__ __forceinline__ uint32_t gelu2(uint32_t z) {
    uint32_t p = h2_fma(z, z, GELU_C_H2);
    uint32_t t = h2_tanh(h2_mul(z, p));
    return h2_fma(z, t, z);
}

__device__ __forceinline__ void wg_fence() { asm volatile("wgmma.fence.sync.aligned;" ::: "memory"); }
__device__ __forceinline__ void wg_commit() { asm volatile("wgmma.commit_group.sync.aligned;" ::: "memory"); }
template <int N> __device__ __forceinline__ void wg_wait() {
    asm volatile("wgmma.wait_group.sync.aligned %0;" ::"n"(N) : "memory");
}
template <int N> __device__ __forceinline__ void pin(uint32_t (&r)[N]) {
#pragma unroll
    for (int i = 0; i < N; i++) asm volatile("" : "+r"(r[i])::"memory");
}
constexpr uint32_t desc_lo(uint32_t addr, uint32_t lbo) { return ((addr & 0x3FFFF) >> 4) | ((lbo >> 4) << 16); }
template <uint32_t SBO, uint32_t SWZ> __device__ __forceinline__ uint64_t desc(uint32_t lo, uint32_t bytes) {
    return (((uint64_t)((SBO >> 4) | (SWZ << 30)) << 32) | lo) + (bytes >> 4);
}
__device__ __forceinline__ uint32_t fresh_tid() {
    uint32_t v; asm volatile("mov.u32 %0, %%tid.x;" : "=r"(v));
    return v;
}
template <uint32_t V> __device__ __forceinline__ uint32_t loop_init() {
    uint32_t v; asm volatile("mov.u32 %0, %1;" : "=r"(v) : "n"(V)); return v;
}
__device__ __forceinline__ int fresh_warp() {
    int v; asm volatile("shfl.sync.idx.b32 %0, %1, 0, 0x1f, 0xffffffff;" : "=r"(v) : "r"(fresh_tid() >> 5)); return v;
}
__device__ __forceinline__ uint32_t fresh_cta() {
    uint32_t v; asm volatile("mov.u32 %0, %%ctaid.x;" : "=r"(v)); return v;
}
__device__ __forceinline__ float sqrt_fast(float v) { float r; asm("sqrt.approx.f32 %0, %1;" : "=f"(r) : "f"(v)); return r; }

template <int TB>
__device__ __forceinline__ void wgmma_n64_h_set(uint32_t (&d)[16], const uint32_t* a, uint64_t desc) {
    asm volatile(
        "{\n.reg .pred p;\nsetp.ne.b32 p, 0, 0;\n"
        "wgmma.mma_async.sync.aligned.m64n64k16.f16.f16.f16 "
        "{%0,%1,%2,%3,%4,%5,%6,%7,%8,%9,%10,%11,%12,%13,%14,%15}, {%16,%17,%18,%19}, %20, p, 1, 1, %21;\n}\n"
        : "=r"(d[0]), "=r"(d[1]), "=r"(d[2]), "=r"(d[3]), "=r"(d[4]), "=r"(d[5]), "=r"(d[6]), "=r"(d[7]), "=r"(d[8]), "=r"(d[9]), "=r"(d[10]), "=r"(d[11]), "=r"(d[12]), "=r"(d[13]), "=r"(d[14]), "=r"(d[15])
        : "r"(a[0]), "r"(a[1]), "r"(a[2]), "r"(a[3]), "l"(desc), "n"(TB));
}
template <int TB>
__device__ __forceinline__ void wgmma_n64_h_acc(uint32_t (&d)[16], const uint32_t* a, uint64_t desc) {
    asm volatile(
        "{\n.reg .pred p;\nsetp.ne.b32 p, 1, 0;\n"
        "wgmma.mma_async.sync.aligned.m64n64k16.f16.f16.f16 "
        "{%0,%1,%2,%3,%4,%5,%6,%7,%8,%9,%10,%11,%12,%13,%14,%15}, {%16,%17,%18,%19}, %20, p, 1, 1, %21;\n}\n"
        : "+r"(d[0]), "+r"(d[1]), "+r"(d[2]), "+r"(d[3]), "+r"(d[4]), "+r"(d[5]), "+r"(d[6]), "+r"(d[7]), "+r"(d[8]), "+r"(d[9]), "+r"(d[10]), "+r"(d[11]), "+r"(d[12]), "+r"(d[13]), "+r"(d[14]), "+r"(d[15])
        : "r"(a[0]), "r"(a[1]), "r"(a[2]), "r"(a[3]), "l"(desc), "n"(TB));
}
__device__ __forceinline__ void wgmma_n64_h_acc_ss(uint32_t (&d)[16], uint64_t adesc, uint64_t desc) {
    asm volatile(
        "{\n.reg .pred p;\nsetp.ne.b32 p, 1, 0;\n"
        "wgmma.mma_async.sync.aligned.m64n64k16.f16.f16.f16 "
        "{%0,%1,%2,%3,%4,%5,%6,%7,%8,%9,%10,%11,%12,%13,%14,%15}, %16, %17, p, 1, 1, 1, 0;\n}\n"
        : "+r"(d[0]), "+r"(d[1]), "+r"(d[2]), "+r"(d[3]), "+r"(d[4]), "+r"(d[5]), "+r"(d[6]), "+r"(d[7]), "+r"(d[8]), "+r"(d[9]), "+r"(d[10]), "+r"(d[11]), "+r"(d[12]), "+r"(d[13]), "+r"(d[14]), "+r"(d[15])
        : "l"(adesc), "l"(desc));
}

struct Params {
    CUtensorMap w1_map, w2_map;
    const __nv_bfloat16* x;
    const __nv_bfloat16* dw;
    const __nv_bfloat16* w1;
    const __nv_bfloat16* gamma;
    const __nv_bfloat16* beta;
    __nv_bfloat16* out;
    Scratch* g;
    uint64_t ydesc64[2];
    uint64_t sel[3];
    uint32_t w1desc, w2desc, ydesc;
};

__device__ __forceinline__ int cta_stride(uint32_t cta) { return cta & 8 ? ROW_BYTES : -ROW_BYTES; }
__device__ __forceinline__ uint32_t cta_tile0(uint32_t cta) {
    return ((cta >> 3) * ROWS_PER_CTA + (cta & 8 ? 0 : ROWS_PER_CTA - 1)) * ROW_BYTES + (cta & 7) * TILE_BYTES;
}

struct Producer {
    uint32_t w[9][6];
    uint32_t xoff[2];
    uint32_t yoff[2][2];
    uint32_t stat, own;
    int lane, warp;
};

struct RowCopy {
    const char* x0;
    char* y0;
    const char* zeros;
    uint32_t cut0, cut1;
    int stride, last;
};
__device__ __forceinline__ RowCopy row_copy(const Params& prm) {
    const uint32_t cta = fresh_cta(), strip = cta & 7, t0 = cta_tile0(cta);
    RowCopy r;
    r.stride = cta_stride(cta);
    r.x0 = (const char*)prm.x + (t0 - r.stride) - 192;
    r.y0 = (char*)prm.out + t0;
    r.zeros = (const char*)prm.g->zero_row;
    r.cut0 = strip == 0 ? 192 : 0;
    r.cut1 = strip == 7 ? 192 : 0;
    r.last = cta - 8 >= NUM_CTAS - 16 ? STEPS - 2 : STEPS - 1;
    return r;
}
__device__ __forceinline__ void issue_row_load(const RowCopy& r, int i, uint32_t slot) {
    const char* src = r.x0 + i * r.stride;
    const uint32_t bar = sb + SM_GO + i * 8, dst = sb + SM_X + slot * SLOT_BYTES;
    expect_tx(bar, XHALF_BYTES - r.cut0);
    bulk_load(dst + r.cut0, src + r.cut0, XHALF_BYTES - r.cut0, bar);
    expect_tx(bar, XHALF_BYTES - r.cut1);
    bulk_load(dst + XHALF_B, src + 32 * 192, XHALF_BYTES - r.cut1, bar);
}

__device__ __forceinline__ float quad_sum(float v) {
    v += __shfl_xor_sync(0xffffffffu, v, 1);
    v += __shfl_xor_sync(0xffffffffu, v, 2);
    return v;
}

__device__ __forceinline__ void load_x(uint32_t (&v)[6][6], const Producer& c, uint32_t row) {
#pragma unroll
    for (int k = 0; k < 6; k++) {
        asm volatile("ld.shared.v4.b32 {%0,%1,%2,%3}, [%4];"
                     : "=r"(v[k][0]), "=r"(v[k][1]), "=r"(v[k][2]), "=r"(v[k][3]) : "r"(row + c.xoff[0] + k * 192));
        asm volatile("ld.shared.v2.b32 {%0,%1}, [%2];" : "=r"(v[k][4]), "=r"(v[k][5]) : "r"(row + c.xoff[1] + k * 192));
    }
}
template <int DY, int STRIDE>
__device__ __forceinline__ void conv_row(uint32_t (&dst)[24], const uint32_t* src, const uint32_t (&v)[6][6], const Producer& c) {
#pragma unroll
    for (int o = 0; o < 4; o++)
#pragma unroll
        for (int u = 0; u < 6; u++)
            dst[o * 6 + u] = bf2_fma(v[o + 2][u], c.w[3 * DY + 2][u], bf2_fma(v[o + 1][u], c.w[3 * DY + 1][u],
                             bf2_fma(v[o][u], c.w[3 * DY][u], STRIDE ? src[o * 6 + u] : src[2 * o + 1])));
}
#define HAND_OVER(name, base, r) asm volatile("mov.b32 " name "%6, %0; mov.b32 " name "%7, %1; mov.b32 " name "%8, %2;\n" \
    "mov.b32 " name "%9, %3; mov.b32 " name "%10, %4; mov.b32 " name "%11, %5;" ::"r"((r)[0]), "r"((r)[1]), "r"((r)[2]), \
    "r"((r)[3]), "r"((r)[4]), "r"((r)[5]), "n"(base), "n"(base + 1), "n"(base + 2), "n"(base + 3), "n"(base + 4), "n"(base + 5))
template <int K> __device__ __forceinline__ void hand_over(const Producer& c, const uint32_t (&B)[24], const uint32_t (&C)[24],
                                                           const uint32_t (&v)[6][6]) {
    HAND_OVER("pw", K * 6, c.w[K]);
    if (K < 6) HAND_OVER("pv", K * 6, v[K % 6]);
    if (K < 4) { HAND_OVER("pb", K * 6, B + K % 4 * 6); HAND_OVER("pc", K * 6, C + K % 4 * 6); }
    if constexpr (K < 8) hand_over<K + 1>(c, B, C, v);
}
__device__ __forceinline__ void produce_tiles(const Producer& c, const Params& prm) {
    asm volatile(
        "{\n"
        ".reg .b32 pa<24>, pq<4>, m<6>, y<6>, rr, mm, t, so, ad, tt, cnt;\n"
        ".reg .b16 xl, xh;\n"
        ".reg .f32 d<4>, us, s0, s1, f0, f1, kq;\n"
        ".reg .pred pt, pf, pr, pw, pl, po, pe;\n"
        "setp.ne.b32 pt, 1, 0; setp.ne.b32 pf, 0, 0; setp.eq.u32 pl, %8, 0; and.b32 tt, %8, 1; setp.ne.u32 po, tt, 0;\n"
        "and.b32 tt, %8, 4; setp.ne.u32 pr, tt, 0; selp.f32 kq, 0f3F802D41, 0f3F7FA57E, pr;\n"
        "mov.u32 t, 0; mov.u32 so, 0;\n"
        "setp.eq.u32 pr, %12, 0;\n"
        "@pr bra.uni RARE;\n"
        "LOOP:\n"
        ASM_TRC("t")
        "fma.rn.bf16x2 pa0, pv0, pw36, pb0; fma.rn.bf16x2 pa1, pv1, pw37, pb1; fma.rn.bf16x2 pa2, pv2, pw38, pb2; fma.rn.bf16x2 pa3, pv3, pw39, pb3; fma.rn.bf16x2 pa4, pv4, pw40, pb4; fma.rn.bf16x2 pa5, pv5, pw41, pb5;\n"
        "fma.rn.bf16x2 pa6, pv6, pw36, pb6; fma.rn.bf16x2 pa7, pv7, pw37, pb7; fma.rn.bf16x2 pa8, pv8, pw38, pb8; fma.rn.bf16x2 pa9, pv9, pw39, pb9; fma.rn.bf16x2 pa10, pv10, pw40, pb10; fma.rn.bf16x2 pa11, pv11, pw41, pb11;\n"
        "fma.rn.bf16x2 pa12, pv12, pw36, pb12; fma.rn.bf16x2 pa13, pv13, pw37, pb13; fma.rn.bf16x2 pa14, pv14, pw38, pb14; fma.rn.bf16x2 pa15, pv15, pw39, pb15; fma.rn.bf16x2 pa16, pv16, pw40, pb16; fma.rn.bf16x2 pa17, pv17, pw41, pb17;\n"
        "fma.rn.bf16x2 pa18, pv18, pw36, pb18; fma.rn.bf16x2 pa19, pv19, pw37, pb19; fma.rn.bf16x2 pa20, pv20, pw38, pb20; fma.rn.bf16x2 pa21, pv21, pw39, pb21; fma.rn.bf16x2 pa22, pv22, pw40, pb22; fma.rn.bf16x2 pa23, pv23, pw41, pb23;\n"
        "fma.rn.bf16x2 pa0, pv6, pw42, pa0; fma.rn.bf16x2 pa1, pv7, pw43, pa1; fma.rn.bf16x2 pa2, pv8, pw44, pa2; fma.rn.bf16x2 pa3, pv9, pw45, pa3; fma.rn.bf16x2 pa4, pv10, pw46, pa4; fma.rn.bf16x2 pa5, pv11, pw47, pa5;\n"
        "fma.rn.bf16x2 pa6, pv12, pw42, pa6; fma.rn.bf16x2 pa7, pv13, pw43, pa7; fma.rn.bf16x2 pa8, pv14, pw44, pa8; fma.rn.bf16x2 pa9, pv15, pw45, pa9; fma.rn.bf16x2 pa10, pv16, pw46, pa10; fma.rn.bf16x2 pa11, pv17, pw47, pa11;\n"
        "fma.rn.bf16x2 pa12, pv18, pw42, pa12; fma.rn.bf16x2 pa13, pv19, pw43, pa13; fma.rn.bf16x2 pa14, pv20, pw44, pa14; fma.rn.bf16x2 pa15, pv21, pw45, pa15; fma.rn.bf16x2 pa16, pv22, pw46, pa16; fma.rn.bf16x2 pa17, pv23, pw47, pa17;\n"
        "fma.rn.bf16x2 pa18, pv24, pw42, pa18; fma.rn.bf16x2 pa19, pv25, pw43, pa19; fma.rn.bf16x2 pa20, pv26, pw44, pa20; fma.rn.bf16x2 pa21, pv27, pw45, pa21; fma.rn.bf16x2 pa22, pv28, pw46, pa22; fma.rn.bf16x2 pa23, pv29, pw47, pa23;\n"
        "fma.rn.bf16x2 pa0, pv12, pw48, pa0; fma.rn.bf16x2 pa1, pv13, pw49, pa1; fma.rn.bf16x2 pa2, pv14, pw50, pa2; fma.rn.bf16x2 pa3, pv15, pw51, pa3; fma.rn.bf16x2 pa4, pv16, pw52, pa4; fma.rn.bf16x2 pa5, pv17, pw53, pa5;\n"
        "fma.rn.bf16x2 pa6, pv18, pw48, pa6; fma.rn.bf16x2 pa7, pv19, pw49, pa7; fma.rn.bf16x2 pa8, pv20, pw50, pa8; fma.rn.bf16x2 pa9, pv21, pw51, pa9; fma.rn.bf16x2 pa10, pv22, pw52, pa10; fma.rn.bf16x2 pa11, pv23, pw53, pa11;\n"
        "fma.rn.bf16x2 pa12, pv24, pw48, pa12; fma.rn.bf16x2 pa13, pv25, pw49, pa13; fma.rn.bf16x2 pa14, pv26, pw50, pa14; fma.rn.bf16x2 pa15, pv27, pw51, pa15; fma.rn.bf16x2 pa16, pv28, pw52, pa16; fma.rn.bf16x2 pa17, pv29, pw53, pa17;\n"
        "fma.rn.bf16x2 pa18, pv30, pw48, pa18; fma.rn.bf16x2 pa19, pv31, pw49, pa19; fma.rn.bf16x2 pa20, pv32, pw50, pa20; fma.rn.bf16x2 pa21, pv33, pw51, pa21; fma.rn.bf16x2 pa22, pv34, pw52, pa22; fma.rn.bf16x2 pa23, pv35, pw53, pa23;\n"
        "mul.rn.bf16x2 pq0, pa0, pa0; fma.rn.bf16x2 pq0, pa1, pa1, pq0; fma.rn.bf16x2 pq0, pa2, pa2, pq0; fma.rn.bf16x2 pq0, pa3, pa3, pq0; fma.rn.bf16x2 pq0, pa4, pa4, pq0; fma.rn.bf16x2 pq0, pa5, pa5, pq0;\n"
        "mul.rn.bf16x2 pq1, pa6, pa6; fma.rn.bf16x2 pq1, pa7, pa7, pq1; fma.rn.bf16x2 pq1, pa8, pa8, pq1; fma.rn.bf16x2 pq1, pa9, pa9, pq1; fma.rn.bf16x2 pq1, pa10, pa10, pq1; fma.rn.bf16x2 pq1, pa11, pa11, pq1;\n"
        "mul.rn.bf16x2 pq2, pa12, pa12; fma.rn.bf16x2 pq2, pa13, pa13, pq2; fma.rn.bf16x2 pq2, pa14, pa14, pq2; fma.rn.bf16x2 pq2, pa15, pa15, pq2; fma.rn.bf16x2 pq2, pa16, pa16, pq2; fma.rn.bf16x2 pq2, pa17, pa17, pq2;\n"
        "mul.rn.bf16x2 pq3, pa18, pa18; fma.rn.bf16x2 pq3, pa19, pa19, pq3; fma.rn.bf16x2 pq3, pa20, pa20, pq3; fma.rn.bf16x2 pq3, pa21, pa21, pq3; fma.rn.bf16x2 pq3, pa22, pa22, pq3; fma.rn.bf16x2 pq3, pa23, pa23, pq3;\n"
        "B0:\n"
        "wgmma.fence.sync.aligned;\n"
        "wgmma.mma_async.sync.aligned.m64n8k16.f32.bf16.bf16 {d0,d1,d2,d3}, {pa0,pa6,pa1,pa7}, %9, pf, 1, 1, 0;\n"
        "wgmma.mma_async.sync.aligned.m64n8k16.f32.bf16.bf16 {d0,d1,d2,d3}, {pa2,pa8,pa3,pa9}, %9, pt, 1, 1, 0;\n"
        "wgmma.mma_async.sync.aligned.m64n8k16.f32.bf16.bf16 {d0,d1,d2,d3}, {pa4,pa10,pa5,pa11}, %9, pt, 1, 1, 0;\n"
        "wgmma.mma_async.sync.aligned.m64n8k16.f32.bf16.bf16 {d0,d1,d2,d3}, {pa12,pa18,pa13,pa19}, %10, pt, 1, 1, 0;\n"
        "wgmma.mma_async.sync.aligned.m64n8k16.f32.bf16.bf16 {d0,d1,d2,d3}, {pa14,pa20,pa15,pa21}, %10, pt, 1, 1, 0;\n"
        "wgmma.mma_async.sync.aligned.m64n8k16.f32.bf16.bf16 {d0,d1,d2,d3}, {pa16,pa22,pa17,pa23}, %10, pt, 1, 1, 0;\n"
        "wgmma.mma_async.sync.aligned.m64n8k16.f32.bf16.bf16 {d0,d1,d2,d3}, {pq0,pq1,pq2,pq3}, %11, pt, 1, 1, 0;\n"
        "wgmma.commit_group.sync.aligned;\n"
        "fence.proxy.async.shared::cta;\n"
        "@pl mbarrier.arrive.shared::cta.b64 _, [t+231544];\n"
        "add.u32 ad, %7, so; ld.shared.f32 us, [ad+4];\n"
        "fma.rn.bf16x2 pb0, pv0, pw18, pc0; fma.rn.bf16x2 pb1, pv1, pw19, pc1; fma.rn.bf16x2 pb2, pv2, pw20, pc2; fma.rn.bf16x2 pb3, pv3, pw21, pc3; fma.rn.bf16x2 pb4, pv4, pw22, pc4; fma.rn.bf16x2 pb5, pv5, pw23, pc5;\n"
        "fma.rn.bf16x2 pb6, pv6, pw18, pc6; fma.rn.bf16x2 pb7, pv7, pw19, pc7; fma.rn.bf16x2 pb8, pv8, pw20, pc8; fma.rn.bf16x2 pb9, pv9, pw21, pc9; fma.rn.bf16x2 pb10, pv10, pw22, pc10; fma.rn.bf16x2 pb11, pv11, pw23, pc11;\n"
        "fma.rn.bf16x2 pb0, pv6, pw24, pb0; fma.rn.bf16x2 pb1, pv7, pw25, pb1; fma.rn.bf16x2 pb2, pv8, pw26, pb2; fma.rn.bf16x2 pb3, pv9, pw27, pb3; fma.rn.bf16x2 pb4, pv10, pw28, pb4; fma.rn.bf16x2 pb5, pv11, pw29, pb5;\n"
        "fma.rn.bf16x2 pb6, pv12, pw24, pb6; fma.rn.bf16x2 pb7, pv13, pw25, pb7; fma.rn.bf16x2 pb8, pv14, pw26, pb8; fma.rn.bf16x2 pb9, pv15, pw27, pb9; fma.rn.bf16x2 pb10, pv16, pw28, pb10; fma.rn.bf16x2 pb11, pv17, pw29, pb11;\n"
        "fma.rn.bf16x2 pb0, pv12, pw30, pb0; fma.rn.bf16x2 pb1, pv13, pw31, pb1; fma.rn.bf16x2 pb2, pv14, pw32, pb2; fma.rn.bf16x2 pb3, pv15, pw33, pb3; fma.rn.bf16x2 pb4, pv16, pw34, pb4; fma.rn.bf16x2 pb5, pv17, pw35, pb5;\n"
        "fma.rn.bf16x2 pb6, pv18, pw30, pb6; fma.rn.bf16x2 pb7, pv19, pw31, pb7; fma.rn.bf16x2 pb8, pv20, pw32, pb8; fma.rn.bf16x2 pb9, pv21, pw33, pb9; fma.rn.bf16x2 pb10, pv22, pw34, pb10; fma.rn.bf16x2 pb11, pv23, pw35, pb11;\n"
        "B1:\n"
        "fma.rn.bf16x2 pb12, pv12, pw18, pc12; fma.rn.bf16x2 pb13, pv13, pw19, pc13; fma.rn.bf16x2 pb14, pv14, pw20, pc14; fma.rn.bf16x2 pb15, pv15, pw21, pc15; fma.rn.bf16x2 pb16, pv16, pw22, pc16; fma.rn.bf16x2 pb17, pv17, pw23, pc17;\n"
        "fma.rn.bf16x2 pb18, pv18, pw18, pc18; fma.rn.bf16x2 pb19, pv19, pw19, pc19; fma.rn.bf16x2 pb20, pv20, pw20, pc20; fma.rn.bf16x2 pb21, pv21, pw21, pc21; fma.rn.bf16x2 pb22, pv22, pw22, pc22; fma.rn.bf16x2 pb23, pv23, pw23, pc23;\n"
        "fma.rn.bf16x2 pb12, pv18, pw24, pb12; fma.rn.bf16x2 pb13, pv19, pw25, pb13; fma.rn.bf16x2 pb14, pv20, pw26, pb14; fma.rn.bf16x2 pb15, pv21, pw27, pb15; fma.rn.bf16x2 pb16, pv22, pw28, pb16; fma.rn.bf16x2 pb17, pv23, pw29, pb17;\n"
        "fma.rn.bf16x2 pb18, pv24, pw24, pb18; fma.rn.bf16x2 pb19, pv25, pw25, pb19; fma.rn.bf16x2 pb20, pv26, pw26, pb20; fma.rn.bf16x2 pb21, pv27, pw27, pb21; fma.rn.bf16x2 pb22, pv28, pw28, pb22; fma.rn.bf16x2 pb23, pv29, pw29, pb23;\n"
        "fma.rn.bf16x2 pb12, pv24, pw30, pb12; fma.rn.bf16x2 pb13, pv25, pw31, pb13; fma.rn.bf16x2 pb14, pv26, pw32, pb14; fma.rn.bf16x2 pb15, pv27, pw33, pb15; fma.rn.bf16x2 pb16, pv28, pw34, pb16; fma.rn.bf16x2 pb17, pv29, pw35, pb17;\n"
        "fma.rn.bf16x2 pb18, pv30, pw30, pb18; fma.rn.bf16x2 pb19, pv31, pw31, pb19; fma.rn.bf16x2 pb20, pv32, pw32, pb20; fma.rn.bf16x2 pb21, pv33, pw33, pb21; fma.rn.bf16x2 pb22, pv34, pw34, pb22; fma.rn.bf16x2 pb23, pv35, pw35, pb23;\n"
        "C0:\n"
        "wgmma.wait_group.sync.aligned 0;\n"
        "selp.f32 s0, d2, d0, po; selp.f32 s1, d3, d1, po;\n"
        "shfl.sync.bfly.b32 f0, s0, 4, 0x1f, 0xffffffff; shfl.sync.bfly.b32 f1, s1, 4, 0x1f, 0xffffffff;\n"
        "fma.rn.bf16x2 pc0, pv0, pw0, ps1; fma.rn.bf16x2 pc1, pv1, pw1, ps1; fma.rn.bf16x2 pc2, pv2, pw2, ps1; fma.rn.bf16x2 pc3, pv3, pw3, ps1; fma.rn.bf16x2 pc4, pv4, pw4, ps1; fma.rn.bf16x2 pc5, pv5, pw5, ps1;\n"
        "fma.rn.bf16x2 pc6, pv6, pw0, ps3; fma.rn.bf16x2 pc7, pv7, pw1, ps3; fma.rn.bf16x2 pc8, pv8, pw2, ps3; fma.rn.bf16x2 pc9, pv9, pw3, ps3; fma.rn.bf16x2 pc10, pv10, pw4, ps3; fma.rn.bf16x2 pc11, pv11, pw5, ps3;\n"
        "fma.rn.bf16x2 pc12, pv12, pw0, ps5; fma.rn.bf16x2 pc13, pv13, pw1, ps5; fma.rn.bf16x2 pc14, pv14, pw2, ps5; fma.rn.bf16x2 pc15, pv15, pw3, ps5; fma.rn.bf16x2 pc16, pv16, pw4, ps5; fma.rn.bf16x2 pc17, pv17, pw5, ps5;\n"
        "fma.rn.bf16x2 pc18, pv18, pw0, ps7; fma.rn.bf16x2 pc19, pv19, pw1, ps7; fma.rn.bf16x2 pc20, pv20, pw2, ps7; fma.rn.bf16x2 pc21, pv21, pw3, ps7; fma.rn.bf16x2 pc22, pv22, pw4, ps7; fma.rn.bf16x2 pc23, pv23, pw5, ps7;\n"
        "fma.rn.bf16x2 pc0, pv6, pw6, pc0; fma.rn.bf16x2 pc1, pv7, pw7, pc1; fma.rn.bf16x2 pc2, pv8, pw8, pc2; fma.rn.bf16x2 pc3, pv9, pw9, pc3; fma.rn.bf16x2 pc4, pv10, pw10, pc4; fma.rn.bf16x2 pc5, pv11, pw11, pc5;\n"
        "fma.rn.bf16x2 pc6, pv12, pw6, pc6; fma.rn.bf16x2 pc7, pv13, pw7, pc7; fma.rn.bf16x2 pc8, pv14, pw8, pc8; fma.rn.bf16x2 pc9, pv15, pw9, pc9; fma.rn.bf16x2 pc10, pv16, pw10, pc10; fma.rn.bf16x2 pc11, pv17, pw11, pc11;\n"
        "fma.rn.bf16x2 pc12, pv18, pw6, pc12; fma.rn.bf16x2 pc13, pv19, pw7, pc13; fma.rn.bf16x2 pc14, pv20, pw8, pc14; fma.rn.bf16x2 pc15, pv21, pw9, pc15; fma.rn.bf16x2 pc16, pv22, pw10, pc16; fma.rn.bf16x2 pc17, pv23, pw11, pc17;\n"
        "fma.rn.bf16x2 pc18, pv24, pw6, pc18; fma.rn.bf16x2 pc19, pv25, pw7, pc19; fma.rn.bf16x2 pc20, pv26, pw8, pc20; fma.rn.bf16x2 pc21, pv27, pw9, pc21; fma.rn.bf16x2 pc22, pv28, pw10, pc22; fma.rn.bf16x2 pc23, pv29, pw11, pc23;\n"
        "fma.rn.bf16x2 pc0, pv12, pw12, pc0; fma.rn.bf16x2 pc1, pv13, pw13, pc1; fma.rn.bf16x2 pc2, pv14, pw14, pc2; fma.rn.bf16x2 pc3, pv15, pw15, pc3; fma.rn.bf16x2 pc4, pv16, pw16, pc4; fma.rn.bf16x2 pc5, pv17, pw17, pc5;\n"
        "fma.rn.bf16x2 pc6, pv18, pw12, pc6; fma.rn.bf16x2 pc7, pv19, pw13, pc7; fma.rn.bf16x2 pc8, pv20, pw14, pc8; fma.rn.bf16x2 pc9, pv21, pw15, pc9; fma.rn.bf16x2 pc10, pv22, pw16, pc10; fma.rn.bf16x2 pc11, pv23, pw17, pc11;\n"
        "fma.rn.bf16x2 pc12, pv24, pw12, pc12; fma.rn.bf16x2 pc13, pv25, pw13, pc13; fma.rn.bf16x2 pc14, pv26, pw14, pc14; fma.rn.bf16x2 pc15, pv27, pw15, pc15; fma.rn.bf16x2 pc16, pv28, pw16, pc16; fma.rn.bf16x2 pc17, pv29, pw17, pc17;\n"
        "fma.rn.bf16x2 pc18, pv30, pw12, pc18; fma.rn.bf16x2 pc19, pv31, pw13, pc19; fma.rn.bf16x2 pc20, pv32, pw14, pc20; fma.rn.bf16x2 pc21, pv33, pw15, pc21; fma.rn.bf16x2 pc22, pv34, pw16, pc22; fma.rn.bf16x2 pc23, pv35, pw17, pc23;\n"
        "add.f32 s0, s0, f0; add.f32 s1, s1, f1; mul.f32 s0, s0, 0fBC2AAAAB;\n"
        "neg.f32 f0, s0; fma.rn.f32 f0, f0, s0, %13; fma.rn.f32 f0, s1, 0f3C2AAAAB, f0; max.f32 f0, f0, %13;\n"
        "rsqrt.approx.ftz.f32 f0, f0; mul.f32 f0, f0, %14; cvt.rn.bf16x2.f32 tt, f0, 0f00000000; mov.b32 f0, tt;\n"
        "mul.f32 f1, s0, kq; mul.f32 f1, f1, f0; cvt.rn.bf16x2.f32 tt, f1, f0; add.f32 us, us, s0; cvt.rn.bf16x2.f32 mm, us, us;\n"
        "add.u32 ad, %7, so; st.shared.v2.b32 [ad], {tt, mm};\n"
        "add.u32 ad, %6, so; ld.shared.v4.b32 {ps0,ps1,ps2,ps3}, [ad]; ld.shared.v4.b32 {ps4,ps5,ps6,ps7}, [ad+16];\n"
        "mbarrier.try_wait.parity.shared::cta.b64 pw, [t+231264], 0;\n"
        "N0:\n"
        "@!pw bra.uni SPIN;\n"
        "BACK:\n"
        "add.u32 ad, %0, so; ld.shared.v4.b32 {pv0,pv1,pv2,pv3}, [ad+0];\n"
        "add.u32 ad, %1, so; ld.shared.v2.b32 {pv4,pv5}, [ad+0];\n"
        "add.u32 ad, %0, so; ld.shared.v4.b32 {pv6,pv7,pv8,pv9}, [ad+192];\n"
        "add.u32 ad, %1, so; ld.shared.v2.b32 {pv10,pv11}, [ad+192];\n"
        "mov.b32 {xl, xh}, ps0; mov.b32 rr, {xl, xl}; mov.b32 mm, {xh, xh}; fma.rn.bf16x2 pa0, pa0, rr, mm; fma.rn.bf16x2 pa1, pa1, rr, mm; fma.rn.bf16x2 pa2, pa2, rr, mm; fma.rn.bf16x2 pa3, pa3, rr, mm; fma.rn.bf16x2 pa4, pa4, rr, mm; fma.rn.bf16x2 pa5, pa5, rr, mm;\n"
        "and.b32 m0, pa0, 0x7fff7fff; and.b32 m1, pa1, 0x7fff7fff; and.b32 m2, pa2, 0x7fff7fff; and.b32 m3, pa3, 0x7fff7fff; and.b32 m4, pa4, 0x7fff7fff; and.b32 m5, pa5, 0x7fff7fff;\n"
        "mad.lo.u32 y0, m0, 7, pa0; mad.lo.u32 y1, m1, 7, pa1; mad.lo.u32 y2, m2, 7, pa2; mad.lo.u32 y3, m3, 7, pa3; mad.lo.u32 y4, m4, 7, pa4; mad.lo.u32 y5, m5, 7, pa5;\n"
        "add.u32 ad, %2, so; st.shared.v4.b32 [ad+0], {y0,y1,y2,y3};\n"
        "add.u32 ad, %4, so; st.shared.v2.b32 [ad+0], {y4,y5};\n"
        "N1:\n"
        "add.u32 ad, %0, so; ld.shared.v4.b32 {pv12,pv13,pv14,pv15}, [ad+384];\n"
        "add.u32 ad, %1, so; ld.shared.v2.b32 {pv16,pv17}, [ad+384];\n"
        "add.u32 ad, %0, so; ld.shared.v4.b32 {pv18,pv19,pv20,pv21}, [ad+576];\n"
        "add.u32 ad, %1, so; ld.shared.v2.b32 {pv22,pv23}, [ad+576];\n"
        "mov.b32 {xl, xh}, ps2; mov.b32 rr, {xl, xl}; mov.b32 mm, {xh, xh}; fma.rn.bf16x2 pa6, pa6, rr, mm; fma.rn.bf16x2 pa7, pa7, rr, mm; fma.rn.bf16x2 pa8, pa8, rr, mm; fma.rn.bf16x2 pa9, pa9, rr, mm; fma.rn.bf16x2 pa10, pa10, rr, mm; fma.rn.bf16x2 pa11, pa11, rr, mm;\n"
        "and.b32 m0, pa6, 0x7fff7fff; and.b32 m1, pa7, 0x7fff7fff; and.b32 m2, pa8, 0x7fff7fff; and.b32 m3, pa9, 0x7fff7fff; and.b32 m4, pa10, 0x7fff7fff; and.b32 m5, pa11, 0x7fff7fff;\n"
        "mad.lo.u32 y0, m0, 7, pa6; mad.lo.u32 y1, m1, 7, pa7; mad.lo.u32 y2, m2, 7, pa8; mad.lo.u32 y3, m3, 7, pa9; mad.lo.u32 y4, m4, 7, pa10; mad.lo.u32 y5, m5, 7, pa11;\n"
        "add.u32 ad, %3, so; st.shared.v4.b32 [ad+0], {y0,y1,y2,y3};\n"
        "add.u32 ad, %5, so; st.shared.v2.b32 [ad+0], {y4,y5};\n"
        "N2:\n"
        "add.u32 ad, %0, so; ld.shared.v4.b32 {pv24,pv25,pv26,pv27}, [ad+768];\n"
        "add.u32 ad, %1, so; ld.shared.v2.b32 {pv28,pv29}, [ad+768];\n"
        "mov.b32 {xl, xh}, ps4; mov.b32 rr, {xl, xl}; mov.b32 mm, {xh, xh}; fma.rn.bf16x2 pa12, pa12, rr, mm; fma.rn.bf16x2 pa13, pa13, rr, mm; fma.rn.bf16x2 pa14, pa14, rr, mm; fma.rn.bf16x2 pa15, pa15, rr, mm; fma.rn.bf16x2 pa16, pa16, rr, mm; fma.rn.bf16x2 pa17, pa17, rr, mm;\n"
        "and.b32 m0, pa12, 0x7fff7fff; and.b32 m1, pa13, 0x7fff7fff; and.b32 m2, pa14, 0x7fff7fff; and.b32 m3, pa15, 0x7fff7fff; and.b32 m4, pa16, 0x7fff7fff; and.b32 m5, pa17, 0x7fff7fff;\n"
        "mad.lo.u32 y0, m0, 7, pa12; mad.lo.u32 y1, m1, 7, pa13; mad.lo.u32 y2, m2, 7, pa14; mad.lo.u32 y3, m3, 7, pa15; mad.lo.u32 y4, m4, 7, pa16; mad.lo.u32 y5, m5, 7, pa17;\n"
        "add.u32 ad, %2, so; st.shared.v4.b32 [ad+2048], {y0,y1,y2,y3};\n"
        "add.u32 ad, %4, so; st.shared.v2.b32 [ad+1024], {y4,y5};\n"
        "N3:\n"
        "add.u32 ad, %0, so; ld.shared.v4.b32 {pv30,pv31,pv32,pv33}, [ad+960];\n"
        "add.u32 ad, %1, so; ld.shared.v2.b32 {pv34,pv35}, [ad+960];\n"
        "mov.b32 {xl, xh}, ps6; mov.b32 rr, {xl, xl}; mov.b32 mm, {xh, xh}; fma.rn.bf16x2 pa18, pa18, rr, mm; fma.rn.bf16x2 pa19, pa19, rr, mm; fma.rn.bf16x2 pa20, pa20, rr, mm; fma.rn.bf16x2 pa21, pa21, rr, mm; fma.rn.bf16x2 pa22, pa22, rr, mm; fma.rn.bf16x2 pa23, pa23, rr, mm;\n"
        "and.b32 m0, pa18, 0x7fff7fff; and.b32 m1, pa19, 0x7fff7fff; and.b32 m2, pa20, 0x7fff7fff; and.b32 m3, pa21, 0x7fff7fff; and.b32 m4, pa22, 0x7fff7fff; and.b32 m5, pa23, 0x7fff7fff;\n"
        "mad.lo.u32 y0, m0, 7, pa18; mad.lo.u32 y1, m1, 7, pa19; mad.lo.u32 y2, m2, 7, pa20; mad.lo.u32 y3, m3, 7, pa21; mad.lo.u32 y4, m4, 7, pa22; mad.lo.u32 y5, m5, 7, pa23;\n"
        "add.u32 ad, %3, so; st.shared.v4.b32 [ad+2048], {y0,y1,y2,y3};\n"
        "add.u32 ad, %5, so; st.shared.v2.b32 [ad+1024], {y4,y5};\n"
        "add.u32 so, so, 26624; setp.eq.u32 pr, so, 79872; selp.u32 so, 0, so, pr;\n"
        "add.u32 t, t, 8; setp.lt.u32 pe, t, 256;\n"
        "@pe bra.uni LOOP;\n"
        "bra.uni DONE;\n"
        "SPIN: mov.u32 cnt, 0;\n"
        "SPINL:\n"
        "mbarrier.try_wait.parity.shared::cta.b64 pw, [t+231264], 0;\n"
        "@pw bra.uni BACK;\n"
        "add.u32 cnt, cnt, 1; setp.lt.u32 pw, cnt, 0x100000;\n"
        "@pw bra.uni SPINL;\n"
        "trap;\n"
        "RARE:\n"
        "ld.volatile.shared.u32 tt, [%6];\n"
        "mov.b32 pa0, tt; mov.b32 pa1, tt; mov.b32 pa2, tt; mov.b32 pa3, tt; mov.b32 pa4, tt; mov.b32 pa5, tt; mov.b32 pa6, tt; mov.b32 pa7, tt; mov.b32 pa8, tt; mov.b32 pa9, tt; mov.b32 pa10, tt; mov.b32 pa11, tt;\n"
        "mov.b32 pa12, tt; mov.b32 pa13, tt; mov.b32 pa14, tt; mov.b32 pa15, tt; mov.b32 pa16, tt; mov.b32 pa17, tt; mov.b32 pa18, tt; mov.b32 pa19, tt; mov.b32 pa20, tt; mov.b32 pa21, tt; mov.b32 pa22, tt; mov.b32 pa23, tt;\n"
        "mov.b32 pb0, tt; mov.b32 pb1, tt; mov.b32 pb2, tt; mov.b32 pb3, tt; mov.b32 pb4, tt; mov.b32 pb5, tt; mov.b32 pb6, tt; mov.b32 pb7, tt; mov.b32 pb8, tt; mov.b32 pb9, tt; mov.b32 pb10, tt; mov.b32 pb11, tt;\n"
        "mov.b32 pb12, tt; mov.b32 pb13, tt; mov.b32 pb14, tt; mov.b32 pb15, tt; mov.b32 pb16, tt; mov.b32 pb17, tt; mov.b32 pb18, tt; mov.b32 pb19, tt; mov.b32 pb20, tt; mov.b32 pb21, tt; mov.b32 pb22, tt; mov.b32 pb23, tt;\n"
        "mov.b32 pc0, tt; mov.b32 pc1, tt; mov.b32 pc2, tt; mov.b32 pc3, tt; mov.b32 pc4, tt; mov.b32 pc5, tt; mov.b32 pc6, tt; mov.b32 pc7, tt; mov.b32 pc8, tt; mov.b32 pc9, tt; mov.b32 pc10, tt; mov.b32 pc11, tt;\n"
        "mov.b32 pc12, tt; mov.b32 pc13, tt; mov.b32 pc14, tt; mov.b32 pc15, tt; mov.b32 pc16, tt; mov.b32 pc17, tt; mov.b32 pc18, tt; mov.b32 pc19, tt; mov.b32 pc20, tt; mov.b32 pc21, tt; mov.b32 pc22, tt; mov.b32 pc23, tt;\n"
        "mov.b32 ps0, tt; mov.b32 ps1, tt; mov.b32 ps2, tt; mov.b32 ps3, tt; mov.b32 ps4, tt; mov.b32 ps5, tt; mov.b32 ps6, tt; mov.b32 ps7, tt; mov.b32 pq0, tt; mov.b32 pq1, tt; mov.b32 pq2, tt; mov.b32 pq3, tt;\n"
        "ld.volatile.shared.v2.b32 {pw1, pw0}, [%6]; xor.b32 tt, tt, pw1;\n"
        "ld.volatile.shared.v2.b32 {pw3, pw2}, [%6]; xor.b32 tt, tt, pw3;\n"
        "ld.volatile.shared.v2.b32 {pw5, pw4}, [%6]; xor.b32 tt, tt, pw5;\n"
        "ld.volatile.shared.v2.b32 {pw7, pw6}, [%6]; xor.b32 tt, tt, pw7;\n"
        "ld.volatile.shared.v2.b32 {pw9, pw8}, [%6]; xor.b32 tt, tt, pw9;\n"
        "ld.volatile.shared.v2.b32 {pw11, pw10}, [%6]; xor.b32 tt, tt, pw11;\n"
        "ld.volatile.shared.v2.b32 {pw13, pw12}, [%6]; xor.b32 tt, tt, pw13;\n"
        "ld.volatile.shared.v2.b32 {pw15, pw14}, [%6]; xor.b32 tt, tt, pw15;\n"
        "ld.volatile.shared.v2.b32 {pw17, pw16}, [%6]; xor.b32 tt, tt, pw17;\n"
        "ld.volatile.shared.v2.b32 {pw19, pw18}, [%6]; xor.b32 tt, tt, pw19;\n"
        "ld.volatile.shared.v2.b32 {pw21, pw20}, [%6]; xor.b32 tt, tt, pw21;\n"
        "ld.volatile.shared.v2.b32 {pw23, pw22}, [%6]; xor.b32 tt, tt, pw23;\n"
        "ld.volatile.shared.v2.b32 {pw25, pw24}, [%6]; xor.b32 tt, tt, pw25;\n"
        "ld.volatile.shared.v2.b32 {pw27, pw26}, [%6]; xor.b32 tt, tt, pw27;\n"
        "ld.volatile.shared.v2.b32 {pw29, pw28}, [%6]; xor.b32 tt, tt, pw29;\n"
        "ld.volatile.shared.v2.b32 {pw31, pw30}, [%6]; xor.b32 tt, tt, pw31;\n"
        "ld.volatile.shared.v2.b32 {pw33, pw32}, [%6]; xor.b32 tt, tt, pw33;\n"
        "ld.volatile.shared.v2.b32 {pw35, pw34}, [%6]; xor.b32 tt, tt, pw35;\n"
        "ld.volatile.shared.v2.b32 {pw37, pw36}, [%6]; xor.b32 tt, tt, pw37;\n"
        "ld.volatile.shared.v2.b32 {pw39, pw38}, [%6]; xor.b32 tt, tt, pw39;\n"
        "ld.volatile.shared.v2.b32 {pw41, pw40}, [%6]; xor.b32 tt, tt, pw41;\n"
        "ld.volatile.shared.v2.b32 {pw43, pw42}, [%6]; xor.b32 tt, tt, pw43;\n"
        "ld.volatile.shared.v2.b32 {pw45, pw44}, [%6]; xor.b32 tt, tt, pw45;\n"
        "ld.volatile.shared.v2.b32 {pw47, pw46}, [%6]; xor.b32 tt, tt, pw47;\n"
        "ld.volatile.shared.v2.b32 {pw49, pw48}, [%6]; xor.b32 tt, tt, pw49;\n"
        "ld.volatile.shared.v2.b32 {pw51, pw50}, [%6]; xor.b32 tt, tt, pw51;\n"
        "ld.volatile.shared.v2.b32 {pw53, pw52}, [%6]; xor.b32 tt, tt, pw53;\n"
        "mov.b32 us, tt; setp.ne.u32 pw, %15, 7;\n"
        "wgmma.fence.sync.aligned;\n"
        "setp.eq.u32 pr, %15, 1000; @pr bra.uni B0;\n"
        "setp.eq.u32 pr, %15, 1001; @pr bra.uni B1;\n"
        "setp.eq.u32 pr, %15, 1002; @pr bra.uni C0;\n"
        "setp.eq.u32 pr, %15, 1003; @pr bra.uni N0;\n"
        "setp.eq.u32 pr, %15, 1004; @pr bra.uni N1;\n"
        "setp.eq.u32 pr, %15, 1005; @pr bra.uni N2;\n"
        "setp.eq.u32 pr, %15, 1006; @pr bra.uni N3;\n"
        "trap;\n"
        "DONE:\n"
        ASM_TRC("t")
        "fence.proxy.async.shared::cta;\n"
        "@pl mbarrier.arrive.shared::cta.b64 _, [t+231544];\n"
        "}\n"
        :: "r"(sb + SM_X + c.xoff[0]), "r"(sb + SM_X + c.xoff[1]), "r"(sb + SM_Y1 + c.yoff[0][0]), "r"(sb + SM_Y1 + c.yoff[0][1]),
           "r"(sb + SM_Y1 + c.yoff[1][0]), "r"(sb + SM_Y1 + c.yoff[1][1]), "r"(c.stat), "r"(c.own), "r"(c.lane),
           "l"(prm.sel[0]), "l"(prm.sel[1]), "l"(prm.sel[2]), "r"(prm.ydesc), "f"(LN_EPS_SCALED), "f"(RSTD_SCALE), "r"(prm.w1desc)
        : "memory");
}

__device__ __forceinline__ void produce(const Producer& c, const Params& prm) {
    uint32_t B[24], C[24];
    const RowCopy rc = row_copy(prm);
    uint32_t st[8];
    uint32_t v[6][6];
    {
        uint32_t ws[6];
#pragma unroll
        for (int u = 0; u < 6; u++) {
            ws[u] = c.w[0][u];
#pragma unroll
            for (int t = 1; t < 9; t++) ws[u] = bf2_add(ws[u], c.w[t][u]);
        }
        SMARK(2);
        mbar_wait_c<0>(sb + SM_GO);
        SMARK(3);
        lds128(v[0], sb + SM_X + c.xoff[0] + 2 * 192);
        asm volatile("ld.shared.v2.b32 {%0,%1}, [%2];" : "=r"(v[0][4]), "=r"(v[0][5]) : "r"(sb + SM_X + c.xoff[1] + 2 * 192));
        const uint32_t p = bf2_add(bf2_fma(v[0][2], ws[2], bf2_fma(v[0][1], ws[1], bf2_mul(v[0][0], ws[0]))),
                                   bf2_fma(v[0][5], ws[5], bf2_fma(v[0][4], ws[4], bf2_mul(v[0][3], ws[3]))));
        float e = quad_sum(bf_lo(p) + bf_hi(p));
        e = (e + __shfl_xor_sync(0xffffffffu, e, 4)) * (-1.0f / CH);
        st[1] = st[3] = st[5] = st[7] = pack_bf2(e, e);
#pragma unroll
        for (int k = 0; k < NX; k++) sts32(c.own + k * SLOT_BYTES + 4, st[1]);
#pragma unroll
        for (int r = 0; r < 24; r++) C[r] = 0;
    }
#pragma unroll 1
    for (int i = loop_init<0>();; i++) {
        mbar_wait_c<0>(sb + SM_GO + i * 8);
        SMARK(4 + i);
        load_x(v, c, sb + SM_X + i * SLOT_BYTES);
        fence_async_smem();
        if (c.warp == i) {
            named_sync(6 + i, 128);
            issue_row_load(rc, i + NX, i);
        } else {
            asm volatile("bar.arrive %0, 128;" ::"r"(6 + i) : "memory");
        }
        if (i == 2) break;
        conv_row<1, 1>(B, C, v, c);
        conv_row<0, 0>(C, st, v, c);
    }
    asm volatile(".reg .b32 pw<54>, pb<24>, pc<24>, pv<36>, ps<8>;");
    hand_over<0>(c, B, C, v);
    asm volatile("mov.b32 ps1, %0; mov.b32 ps3, %1; mov.b32 ps5, %2; mov.b32 ps7, %3;" ::"r"(st[1]), "r"(st[3]), "r"(st[5]), "r"(st[7]));
    SMARK(7);
    produce_tiles(c, prm);
    mbar_arrive_if(sb + SM_YFULL + ROWS_PER_CTA * 8, c.lane == 0);
}

struct Duty {
    const char* g;
    const char* zeros;
    long long step;
    uint32_t s, bytes;
    int end, zero;
};
__device__ __forceinline__ Duty make_duty(const Params& prm, int wg, int w) {
    const RowCopy rc = row_copy(prm);
    Duty d;
    d.g = (w == 2 ? rc.y0 : rc.x0 + (w == 0 ? rc.cut0 : w == 1 ? 32 * 192 : 192)) +
          (wg + (w == 2 ? 0 : w < 2 ? 2 * NX : 2 * NX + L2_AHEAD)) * rc.stride;
    d.step = NX * rc.stride;
    d.s = wg * SLOT_BYTES + (w == 2 ? sb + SM_Y1 : sb + SM_X + (w == 0 ? rc.cut0 : XHALF_B));
    d.bytes = w >= 2 ? TILE_BYTES : XHALF_BYTES - (w == 0 ? rc.cut0 : rc.cut1);
    d.end = w == 2 ? ROWS_PER_CTA : w < 2 ? STEPS + 1 - 2 * NX : rc.last + 1 - 2 * NX - L2_AHEAD;
    d.zero = rc.last + 1 - 2 * NX;
    d.zeros = rc.zeros;
    return d;
}

static_assert(sb + SM_BAR == 230800 && sb + SM_YFULL == 231552 && sb + SM_GO == 231240 && SLOT_BYTES == 26624 && sb + SM_GAMMA == 229248 &&
              SM_BETA == SM_GAMMA + 768 && SM_W2 == 73728 && sb + SM_BUF3 == 187392 && BAR_W2 == 9 && BAR_W1B == 10, "layout");
__device__ __forceinline__ void consume(float (&acc)[2][2], uint32_t w1t, uint32_t yd, uint32_t wd, uint32_t own_slot, const Duty& d,
                                        uint32_t role, uint32_t lane, const Params& prm) {
    asm volatile(
        "{\n"
        ".reg .b32 z<32>, w<44>, p, a<4>, lo<2>, hi<2>, t, g, q<4>, dl, dh, n, so, c, tt, cnt, f0, f1;\n"
        ".reg .b16 xl, xh, xr;\n"
        ".reg .b64 ds<6>, wd, gp, src;\n"
        ".reg .pred pt, pf, pr, pw, pl, pe;\n"
        "setp.ne.b32 pt, 1, 0; setp.ne.b32 pf, 0, 0; setp.eq.u32 pl, %15, 0;\n"
        "mov.b32 c, 0x40D940D9;\n"
        "ldmatrix.sync.aligned.m8n8.x4.trans.shared.b16 {w0,w1,w2,w3}, [%4+0];\n"
        "ldmatrix.sync.aligned.m8n8.x4.trans.shared.b16 {w4,w5,w6,w7}, [%4+2048];\n"
        "ldmatrix.sync.aligned.m8n8.x4.trans.shared.b16 {w8,w9,w10,w11}, [%4+4096];\n"
        "ldmatrix.sync.aligned.m8n8.x4.trans.shared.b16 {w12,w13,w14,w15}, [%4+6144];\n"
        "ldmatrix.sync.aligned.m8n8.x4.trans.shared.b16 {w16,w17,w18,w19}, [%4+8192];\n"
        "ldmatrix.sync.aligned.m8n8.x4.trans.shared.b16 {w20,w21,w22,w23}, [%4+10240];\n"
        "shl.b32 f0, w0, 16; and.b32 f1, w0, 0xffff0000; cvt.rn.f16x2.f32 w0, f1, f0; shl.b32 f0, w1, 16; and.b32 f1, w1, 0xffff0000; cvt.rn.f16x2.f32 w1, f1, f0; shl.b32 f0, w2, 16; and.b32 f1, w2, 0xffff0000; cvt.rn.f16x2.f32 w2, f1, f0; shl.b32 f0, w3, 16; and.b32 f1, w3, 0xffff0000; cvt.rn.f16x2.f32 w3, f1, f0;\n"
        "stmatrix.sync.aligned.m8n8.x4.trans.shared.b16 [%4+0], {w0,w1,w2,w3};\n"
        "shl.b32 f0, w4, 16; and.b32 f1, w4, 0xffff0000; cvt.rn.f16x2.f32 w4, f1, f0; shl.b32 f0, w5, 16; and.b32 f1, w5, 0xffff0000; cvt.rn.f16x2.f32 w5, f1, f0; shl.b32 f0, w6, 16; and.b32 f1, w6, 0xffff0000; cvt.rn.f16x2.f32 w6, f1, f0; shl.b32 f0, w7, 16; and.b32 f1, w7, 0xffff0000; cvt.rn.f16x2.f32 w7, f1, f0;\n"
        "stmatrix.sync.aligned.m8n8.x4.trans.shared.b16 [%4+2048], {w4,w5,w6,w7};\n"
        "shl.b32 f0, w8, 16; and.b32 f1, w8, 0xffff0000; cvt.rn.f16x2.f32 w8, f1, f0; shl.b32 f0, w9, 16; and.b32 f1, w9, 0xffff0000; cvt.rn.f16x2.f32 w9, f1, f0; shl.b32 f0, w10, 16; and.b32 f1, w10, 0xffff0000; cvt.rn.f16x2.f32 w10, f1, f0; shl.b32 f0, w11, 16; and.b32 f1, w11, 0xffff0000; cvt.rn.f16x2.f32 w11, f1, f0;\n"
        "stmatrix.sync.aligned.m8n8.x4.trans.shared.b16 [%4+4096], {w8,w9,w10,w11};\n"
        "shl.b32 f0, w12, 16; and.b32 f1, w12, 0xffff0000; cvt.rn.f16x2.f32 w12, f1, f0; shl.b32 f0, w13, 16; and.b32 f1, w13, 0xffff0000; cvt.rn.f16x2.f32 w13, f1, f0; shl.b32 f0, w14, 16; and.b32 f1, w14, 0xffff0000; cvt.rn.f16x2.f32 w14, f1, f0; shl.b32 f0, w15, 16; and.b32 f1, w15, 0xffff0000; cvt.rn.f16x2.f32 w15, f1, f0;\n"
        "stmatrix.sync.aligned.m8n8.x4.trans.shared.b16 [%4+6144], {w12,w13,w14,w15};\n"
        "shl.b32 f0, w16, 16; and.b32 f1, w16, 0xffff0000; cvt.rn.f16x2.f32 w16, f1, f0; shl.b32 f0, w17, 16; and.b32 f1, w17, 0xffff0000; cvt.rn.f16x2.f32 w17, f1, f0; shl.b32 f0, w18, 16; and.b32 f1, w18, 0xffff0000; cvt.rn.f16x2.f32 w18, f1, f0; shl.b32 f0, w19, 16; and.b32 f1, w19, 0xffff0000; cvt.rn.f16x2.f32 w19, f1, f0;\n"
        "stmatrix.sync.aligned.m8n8.x4.trans.shared.b16 [%4+8192], {w16,w17,w18,w19};\n"
        "shl.b32 f0, w20, 16; and.b32 f1, w20, 0xffff0000; cvt.rn.f16x2.f32 w20, f1, f0; shl.b32 f0, w21, 16; and.b32 f1, w21, 0xffff0000; cvt.rn.f16x2.f32 w21, f1, f0; shl.b32 f0, w22, 16; and.b32 f1, w22, 0xffff0000; cvt.rn.f16x2.f32 w22, f1, f0; shl.b32 f0, w23, 16; and.b32 f1, w23, 0xffff0000; cvt.rn.f16x2.f32 w23, f1, f0;\n"
        "stmatrix.sync.aligned.m8n8.x4.trans.shared.b16 [%4+10240], {w20,w21,w22,w23};\n"
        "mov.u32 tt, 230880; mbarrier.try_wait.parity.shared::cta.b64 pw, [tt], 0;\n"
        "@!pw bra.uni SPINW;\n"
        "BACKW:\n"
        "ldmatrix.sync.aligned.m8n8.x4.trans.shared.b16 {z0,z1,z2,z3}, [%4+22528];\n"
        "ldmatrix.sync.aligned.m8n8.x4.trans.shared.b16 {w24,w25,w26,w27}, [%4+12288];\n"
        "ldmatrix.sync.aligned.m8n8.x4.trans.shared.b16 {w28,w29,w30,w31}, [%4+14336];\n"
        "ldmatrix.sync.aligned.m8n8.x4.trans.shared.b16 {w32,w33,w34,w35}, [%4+16384];\n"
        "ldmatrix.sync.aligned.m8n8.x4.trans.shared.b16 {w36,w37,w38,w39}, [%4+18432];\n"
        "ldmatrix.sync.aligned.m8n8.x4.trans.shared.b16 {w40,w41,w42,w43}, [%4+20480];\n"
        "shl.b32 f0, z0, 16; and.b32 f1, z0, 0xffff0000; cvt.rn.f16x2.f32 z0, f1, f0; shl.b32 f0, z1, 16; and.b32 f1, z1, 0xffff0000; cvt.rn.f16x2.f32 z1, f1, f0; shl.b32 f0, z2, 16; and.b32 f1, z2, 0xffff0000; cvt.rn.f16x2.f32 z2, f1, f0; shl.b32 f0, z3, 16; and.b32 f1, z3, 0xffff0000; cvt.rn.f16x2.f32 z3, f1, f0;\n"
        "stmatrix.sync.aligned.m8n8.x4.trans.shared.b16 [%4+22528], {z0,z1,z2,z3};\n"
        "shl.b32 f0, w24, 16; and.b32 f1, w24, 0xffff0000; cvt.rn.f16x2.f32 w24, f1, f0; shl.b32 f0, w25, 16; and.b32 f1, w25, 0xffff0000; cvt.rn.f16x2.f32 w25, f1, f0; shl.b32 f0, w26, 16; and.b32 f1, w26, 0xffff0000; cvt.rn.f16x2.f32 w26, f1, f0; shl.b32 f0, w27, 16; and.b32 f1, w27, 0xffff0000; cvt.rn.f16x2.f32 w27, f1, f0;\n"
        "stmatrix.sync.aligned.m8n8.x4.trans.shared.b16 [%4+12288], {w24,w25,w26,w27};\n"
        "shl.b32 f0, w28, 16; and.b32 f1, w28, 0xffff0000; cvt.rn.f16x2.f32 w28, f1, f0; shl.b32 f0, w29, 16; and.b32 f1, w29, 0xffff0000; cvt.rn.f16x2.f32 w29, f1, f0; shl.b32 f0, w30, 16; and.b32 f1, w30, 0xffff0000; cvt.rn.f16x2.f32 w30, f1, f0; shl.b32 f0, w31, 16; and.b32 f1, w31, 0xffff0000; cvt.rn.f16x2.f32 w31, f1, f0;\n"
        "stmatrix.sync.aligned.m8n8.x4.trans.shared.b16 [%4+14336], {w28,w29,w30,w31};\n"
        "shl.b32 f0, w32, 16; and.b32 f1, w32, 0xffff0000; cvt.rn.f16x2.f32 w32, f1, f0; shl.b32 f0, w33, 16; and.b32 f1, w33, 0xffff0000; cvt.rn.f16x2.f32 w33, f1, f0; shl.b32 f0, w34, 16; and.b32 f1, w34, 0xffff0000; cvt.rn.f16x2.f32 w34, f1, f0; shl.b32 f0, w35, 16; and.b32 f1, w35, 0xffff0000; cvt.rn.f16x2.f32 w35, f1, f0;\n"
        "stmatrix.sync.aligned.m8n8.x4.trans.shared.b16 [%4+16384], {w32,w33,w34,w35};\n"
        "shl.b32 f0, w36, 16; and.b32 f1, w36, 0xffff0000; cvt.rn.f16x2.f32 w36, f1, f0; shl.b32 f0, w37, 16; and.b32 f1, w37, 0xffff0000; cvt.rn.f16x2.f32 w37, f1, f0; shl.b32 f0, w38, 16; and.b32 f1, w38, 0xffff0000; cvt.rn.f16x2.f32 w38, f1, f0; shl.b32 f0, w39, 16; and.b32 f1, w39, 0xffff0000; cvt.rn.f16x2.f32 w39, f1, f0;\n"
        "stmatrix.sync.aligned.m8n8.x4.trans.shared.b16 [%4+18432], {w36,w37,w38,w39};\n"
        "shl.b32 f0, w40, 16; and.b32 f1, w40, 0xffff0000; cvt.rn.f16x2.f32 w40, f1, f0; shl.b32 f0, w41, 16; and.b32 f1, w41, 0xffff0000; cvt.rn.f16x2.f32 w41, f1, f0; shl.b32 f0, w42, 16; and.b32 f1, w42, 0xffff0000; cvt.rn.f16x2.f32 w42, f1, f0; shl.b32 f0, w43, 16; and.b32 f1, w43, 0xffff0000; cvt.rn.f16x2.f32 w43, f1, f0;\n"
        "stmatrix.sync.aligned.m8n8.x4.trans.shared.b16 [%4+20480], {w40,w41,w42,w43};\n"
        "fence.proxy.async.shared::cta;\n"
        ASM_SMARK
        "mov.b32 p, 0; mov.b32 t, 0; mov.b32 g, 0; mov.b32 a0, 0; mov.b32 a1, 0; mov.b32 a2, 0; mov.b32 a3, 0; mov.b32 lo0, 0; mov.b32 lo1, 0; mov.b32 hi0, 0; mov.b32 hi1, 0; mov.b32 q0, 0; mov.b32 q1, 0; mov.b32 q2, 0; mov.b32 q3, 0;\n"
        "mov.b32 z16, 0; mov.b32 z17, 0; mov.b32 z18, 0; mov.b32 z19, 0; mov.b32 z20, 0; mov.b32 z21, 0; mov.b32 z22, 0; mov.b32 z23, 0; mov.b32 z24, 0; mov.b32 z25, 0; mov.b32 z26, 0; mov.b32 z27, 0; mov.b32 z28, 0; mov.b32 z29, 0; mov.b32 z30, 0; mov.b32 z31, 0;\n"
        "mov.f32 %0, 0f00000000; mov.f32 %1, 0f00000000; mov.f32 %2, 0f00000000; mov.f32 %3, 0f00000000;\n"
        "mov.u32 n, 0; mov.u32 so, 0; mov.b64 gp, %8; mov.b64 wd, {%6, 0x40000040};\n"
        "mov.b64 ds0, %20; add.s64 ds1, ds0, 2; add.s64 ds2, ds0, 4; add.s64 ds3, ds0, 6; mov.b64 ds4, %21; add.s64 ds5, ds4, 2;\n"
        "mbarrier.try_wait.parity.shared::cta.b64 pw, [n+231552], 0;\n"
        "@!pw bra.uni SPIN0;\n"
        "BACK0:\n"
        ASM_TS
        "wgmma.fence.sync.aligned;\n"
        "wgmma.mma_async.sync.aligned.m64n64k16.f16.f16.f16 {z0,z1,z2,z3,z4,z5,z6,z7,z8,z9,z10,z11,z12,z13,z14,z15}, {w0,w1,w2,w3}, ds0, pf, 1, 1, 0;\n"
        "wgmma.mma_async.sync.aligned.m64n64k16.f16.f16.f16 {z0,z1,z2,z3,z4,z5,z6,z7,z8,z9,z10,z11,z12,z13,z14,z15}, {w4,w5,w6,w7}, ds1, pt, 1, 1, 0;\n"
        "wgmma.mma_async.sync.aligned.m64n64k16.f16.f16.f16 {z0,z1,z2,z3,z4,z5,z6,z7,z8,z9,z10,z11,z12,z13,z14,z15}, {w8,w9,w10,w11}, ds2, pt, 1, 1, 0;\n"
        "wgmma.fence.sync.aligned;\n"
        "wgmma.mma_async.sync.aligned.m64n64k16.f16.f16.f16 {z0,z1,z2,z3,z4,z5,z6,z7,z8,z9,z10,z11,z12,z13,z14,z15}, {w12,w13,w14,w15}, ds3, pt, 1, 1, 0;\n"
        "wgmma.mma_async.sync.aligned.m64n64k16.f16.f16.f16 {z0,z1,z2,z3,z4,z5,z6,z7,z8,z9,z10,z11,z12,z13,z14,z15}, {w16,w17,w18,w19}, ds4, pt, 1, 1, 0;\n"
        "wgmma.mma_async.sync.aligned.m64n64k16.f16.f16.f16 {z0,z1,z2,z3,z4,z5,z6,z7,z8,z9,z10,z11,z12,z13,z14,z15}, {w20,w21,w22,w23}, ds5, pt, 1, 1, 0;\n"
        "wgmma.commit_group.sync.aligned;\n"
        "setp.eq.u32 pr, so, %7;\n"
        "@pr bra.uni DUTY;\n"
        "TOP:\n"
        ASM_TRC("n")
        "wgmma.wait_group.sync.aligned 0;\n"
        "mov.b32 {xl, xh}, a2; tanh.approx.f16 xr, xh; cvt.u32.u16 hi0, xr; mul.rn.f16x2 a3, z31, p; fma.rn.f16x2 p, z0, z0, c; fma.rn.f16x2 q3, g, g, q3; fma.rn.f16x2 g, z28, t, z28; prmt.b32 t, lo1, hi1, 0x5410; tanh.approx.f16 xr, xl; cvt.u32.u16 lo0, xr;\n"
        "B31:\n"
        "mov.b32 {xl, xh}, a3; tanh.approx.f16 xr, xh; cvt.u32.u16 hi1, xr; mul.rn.f16x2 a0, z0, p; fma.rn.f16x2 p, z1, z1, c; fma.rn.f16x2 q2, g, g, q2; fma.rn.f16x2 g, z29, t, z29; prmt.b32 t, lo0, hi0, 0x5410; tanh.approx.f16 xr, xl; cvt.u32.u16 lo1, xr;\n"
        "B0:\n"
        "mov.b32 {xl, xh}, a0; tanh.approx.f16 xr, xh; cvt.u32.u16 hi0, xr; mul.rn.f16x2 a1, z1, p; fma.rn.f16x2 p, z2, z2, c; fma.rn.f16x2 q3, g, g, q3; fma.rn.f16x2 g, z30, t, z30; prmt.b32 t, lo1, hi1, 0x5410; tanh.approx.f16 xr, xl; cvt.u32.u16 lo0, xr;\n"
        "B1:\n"
        "mov.b32 {xl, xh}, a1; tanh.approx.f16 xr, xh; cvt.u32.u16 hi1, xr; mul.rn.f16x2 a2, z2, p; fma.rn.f16x2 p, z3, z3, c; fma.rn.f16x2 q2, g, g, q2; fma.rn.f16x2 g, z31, t, z31; prmt.b32 t, lo0, hi0, 0x5410; tanh.approx.f16 xr, xl; cvt.u32.u16 lo1, xr;\n"
        "B2:\n"
        "wgmma.fence.sync.aligned;\n"
        "wgmma.mma_async.sync.aligned.m64n64k16.f16.f16.f16 {z16,z17,z18,z19,z20,z21,z22,z23,z24,z25,z26,z27,z28,z29,z30,z31}, {w24,w25,w26,w27}, ds0, pf, 1, 1, 0;\n"
        "wgmma.mma_async.sync.aligned.m64n64k16.f16.f16.f16 {z16,z17,z18,z19,z20,z21,z22,z23,z24,z25,z26,z27,z28,z29,z30,z31}, {w28,w29,w30,w31}, ds1, pt, 1, 1, 0;\n"
        "wgmma.mma_async.sync.aligned.m64n64k16.f16.f16.f16 {z16,z17,z18,z19,z20,z21,z22,z23,z24,z25,z26,z27,z28,z29,z30,z31}, {w32,w33,w34,w35}, ds2, pt, 1, 1, 0;\n"
        "mov.b32 {xl, xh}, a2; tanh.approx.f16 xr, xh; cvt.u32.u16 hi0, xr; mul.rn.f16x2 a3, z3, p; fma.rn.f16x2 p, z4, z4, c; fma.rn.f16x2 q3, g, g, q3; fma.rn.f16x2 g, z0, t, z0; prmt.b32 t, lo1, hi1, 0x5410; tanh.approx.f16 xr, xl; cvt.u32.u16 lo0, xr;\n"
        "B3:\n"
        "mov.b32 {xl, xh}, a3; tanh.approx.f16 xr, xh; cvt.u32.u16 hi1, xr; mul.rn.f16x2 a0, z4, p; fma.rn.f16x2 p, z5, z5, c; fma.rn.f16x2 q0, g, g, q0; fma.rn.f16x2 g, z1, t, z1; prmt.b32 t, lo0, hi0, 0x5410; tanh.approx.f16 xr, xl; cvt.u32.u16 lo1, xr;\n"
        "B4:\n"
        "mov.b32 {xl, xh}, a0; tanh.approx.f16 xr, xh; cvt.u32.u16 hi0, xr; mul.rn.f16x2 a1, z5, p; fma.rn.f16x2 p, z6, z6, c; fma.rn.f16x2 q1, g, g, q1; fma.rn.f16x2 g, z2, t, z2; prmt.b32 t, lo1, hi1, 0x5410; tanh.approx.f16 xr, xl; cvt.u32.u16 lo0, xr;\n"
        "B5:\n"
        "wgmma.fence.sync.aligned;\n"
        "wgmma.mma_async.sync.aligned.m64n64k16.f16.f16.f16 {z16,z17,z18,z19,z20,z21,z22,z23,z24,z25,z26,z27,z28,z29,z30,z31}, {w36,w37,w38,w39}, ds3, pt, 1, 1, 0;\n"
        "wgmma.mma_async.sync.aligned.m64n64k16.f16.f16.f16 {z16,z17,z18,z19,z20,z21,z22,z23,z24,z25,z26,z27,z28,z29,z30,z31}, {w40,w41,w42,w43}, ds4, pt, 1, 1, 0;\n"
        "wgmma.mma_async.sync.aligned.m64n64k16.f16.f16.f16 {z16,z17,z18,z19,z20,z21,z22,z23,z24,z25,z26,z27,z28,z29,z30,z31}, wd, ds5, pt, 1, 1, 1, 0;\n"
        "wgmma.commit_group.sync.aligned;\n"
        "mov.b32 {xl, xh}, a1; tanh.approx.f16 xr, xh; cvt.u32.u16 hi1, xr; mul.rn.f16x2 a2, z6, p; fma.rn.f16x2 p, z7, z7, c; fma.rn.f16x2 q0, g, g, q0; fma.rn.f16x2 g, z3, t, z3; prmt.b32 t, lo0, hi0, 0x5410; tanh.approx.f16 xr, xl; cvt.u32.u16 lo1, xr;\n"
        "B6:\n"
        "add.u32 so, so, 26624; setp.eq.u32 pr, so, 79872; selp.u32 so, 0, so, pr;\n"
        "mov.b32 {xl, xh}, a2; tanh.approx.f16 xr, xh; cvt.u32.u16 hi0, xr; mul.rn.f16x2 a3, z7, p; fma.rn.f16x2 p, z8, z8, c; fma.rn.f16x2 q1, g, g, q1; fma.rn.f16x2 g, z4, t, z4; prmt.b32 t, lo1, hi1, 0x5410; tanh.approx.f16 xr, xl; cvt.u32.u16 lo0, xr;\n"
        "B7:\n"
        "shr.u32 tt, so, 4;\n"
        "mov.b64 {dl, dh}, ds0; add.u32 dl, tt, 74816; mov.b64 ds0, {dl, dh}; mov.b64 {dl, dh}, ds1; add.u32 dl, tt, 74818; mov.b64 ds1, {dl, dh}; mov.b64 {dl, dh}, ds2; add.u32 dl, tt, 74820; mov.b64 ds2, {dl, dh};\n"
        "mov.b32 {xl, xh}, a3; tanh.approx.f16 xr, xh; cvt.u32.u16 hi1, xr; mul.rn.f16x2 a0, z8, p; fma.rn.f16x2 p, z9, z9, c; fma.rn.f16x2 q0, g, g, q0; fma.rn.f16x2 g, z5, t, z5; prmt.b32 t, lo0, hi0, 0x5410; tanh.approx.f16 xr, xl; cvt.u32.u16 lo1, xr;\n"
        "B8:\n"
        "shr.u32 tt, so, 4;\n"
        "mov.b64 {dl, dh}, ds3; add.u32 dl, tt, 74822; mov.b64 ds3, {dl, dh}; mov.b64 {dl, dh}, ds4; add.u32 dl, tt, 75328; mov.b64 ds4, {dl, dh}; mov.b64 {dl, dh}, ds5; add.u32 dl, tt, 75330; mov.b64 ds5, {dl, dh};\n"
        "mov.b32 {xl, xh}, a0; tanh.approx.f16 xr, xh; cvt.u32.u16 hi0, xr; mul.rn.f16x2 a1, z9, p; fma.rn.f16x2 p, z10, z10, c; fma.rn.f16x2 q1, g, g, q1; fma.rn.f16x2 g, z6, t, z6; prmt.b32 t, lo1, hi1, 0x5410; tanh.approx.f16 xr, xl; cvt.u32.u16 lo0, xr;\n"
        "B9:\n"
        "mov.b32 {xl, xh}, a1; tanh.approx.f16 xr, xh; cvt.u32.u16 hi1, xr; mul.rn.f16x2 a2, z10, p; fma.rn.f16x2 p, z11, z11, c; fma.rn.f16x2 q0, g, g, q0; fma.rn.f16x2 g, z7, t, z7; prmt.b32 t, lo0, hi0, 0x5410; tanh.approx.f16 xr, xl; cvt.u32.u16 lo1, xr;\n"
        "B10:\n"
        "mov.b32 {xl, xh}, a2; tanh.approx.f16 xr, xh; cvt.u32.u16 hi0, xr; mul.rn.f16x2 a3, z11, p; fma.rn.f16x2 p, z12, z12, c; fma.rn.f16x2 q1, g, g, q1; fma.rn.f16x2 g, z8, t, z8; prmt.b32 t, lo1, hi1, 0x5410; tanh.approx.f16 xr, xl; cvt.u32.u16 lo0, xr;\n"
        "B11:\n"
        "mov.b32 {xl, xh}, a3; tanh.approx.f16 xr, xh; cvt.u32.u16 hi1, xr; mul.rn.f16x2 a0, z12, p; fma.rn.f16x2 p, z13, z13, c; fma.rn.f16x2 q0, g, g, q0; fma.rn.f16x2 g, z9, t, z9; prmt.b32 t, lo0, hi0, 0x5410; tanh.approx.f16 xr, xl; cvt.u32.u16 lo1, xr;\n"
        "B12:\n"
        "mov.b32 {xl, xh}, a0; tanh.approx.f16 xr, xh; cvt.u32.u16 hi0, xr; mul.rn.f16x2 a1, z13, p; fma.rn.f16x2 p, z14, z14, c; fma.rn.f16x2 q1, g, g, q1; fma.rn.f16x2 g, z10, t, z10; prmt.b32 t, lo1, hi1, 0x5410; tanh.approx.f16 xr, xl; cvt.u32.u16 lo0, xr;\n"
        "B13:\n"
        "mov.b32 {xl, xh}, a1; tanh.approx.f16 xr, xh; cvt.u32.u16 hi1, xr; mul.rn.f16x2 a2, z14, p; fma.rn.f16x2 p, z15, z15, c; fma.rn.f16x2 q0, g, g, q0; fma.rn.f16x2 g, z11, t, z11; prmt.b32 t, lo0, hi0, 0x5410; tanh.approx.f16 xr, xl; cvt.u32.u16 lo1, xr;\n"
        "B14:\n"
        "wgmma.wait_group.sync.aligned 0;\n"
        "cp.async.bulk.wait_group.read 0;\n"
        "@pl mbarrier.arrive.shared::cta.b64 _, [n+231288];\n"
        "mov.b32 {xl, xh}, a2; tanh.approx.f16 xr, xh; cvt.u32.u16 hi0, xr; mul.rn.f16x2 a3, z15, p; fma.rn.f16x2 p, z16, z16, c; fma.rn.f16x2 q1, g, g, q1; fma.rn.f16x2 g, z12, t, z12; prmt.b32 t, lo1, hi1, 0x5410; tanh.approx.f16 xr, xl; cvt.u32.u16 lo0, xr;\n"
        "B15:\n"
        "mov.b32 {xl, xh}, a3; tanh.approx.f16 xr, xh; cvt.u32.u16 hi1, xr; mul.rn.f16x2 a0, z16, p; fma.rn.f16x2 p, z17, z17, c; fma.rn.f16x2 q0, g, g, q0; fma.rn.f16x2 g, z13, t, z13; prmt.b32 t, lo0, hi0, 0x5410; tanh.approx.f16 xr, xl; cvt.u32.u16 lo1, xr;\n"
        "B16:\n"
        "mbarrier.try_wait.parity.shared::cta.b64 pw, [n+231560], 0;\n"
        "mov.b32 {xl, xh}, a0; tanh.approx.f16 xr, xh; cvt.u32.u16 hi0, xr; mul.rn.f16x2 a1, z17, p; fma.rn.f16x2 p, z18, z18, c; fma.rn.f16x2 q1, g, g, q1; fma.rn.f16x2 g, z14, t, z14; prmt.b32 t, lo1, hi1, 0x5410; tanh.approx.f16 xr, xl; cvt.u32.u16 lo0, xr;\n"
        "B17:\n"
        "mov.b32 {xl, xh}, a1; tanh.approx.f16 xr, xh; cvt.u32.u16 hi1, xr; mul.rn.f16x2 a2, z18, p; fma.rn.f16x2 p, z19, z19, c; fma.rn.f16x2 q0, g, g, q0; fma.rn.f16x2 g, z15, t, z15; prmt.b32 t, lo0, hi0, 0x5410; tanh.approx.f16 xr, xl; cvt.u32.u16 lo1, xr;\n"
        "B18:\n"
        "@!pw bra.uni SPIN;\n"
        "BACK:\n"
        "wgmma.fence.sync.aligned;\n"
        "wgmma.mma_async.sync.aligned.m64n64k16.f16.f16.f16 {z0,z1,z2,z3,z4,z5,z6,z7,z8,z9,z10,z11,z12,z13,z14,z15}, {w0,w1,w2,w3}, ds0, pf, 1, 1, 0;\n"
        "wgmma.mma_async.sync.aligned.m64n64k16.f16.f16.f16 {z0,z1,z2,z3,z4,z5,z6,z7,z8,z9,z10,z11,z12,z13,z14,z15}, {w4,w5,w6,w7}, ds1, pt, 1, 1, 0;\n"
        "wgmma.mma_async.sync.aligned.m64n64k16.f16.f16.f16 {z0,z1,z2,z3,z4,z5,z6,z7,z8,z9,z10,z11,z12,z13,z14,z15}, {w8,w9,w10,w11}, ds2, pt, 1, 1, 0;\n"
        "mov.b32 {xl, xh}, a2; tanh.approx.f16 xr, xh; cvt.u32.u16 hi0, xr; mul.rn.f16x2 a3, z19, p; fma.rn.f16x2 p, z20, z20, c; fma.rn.f16x2 q1, g, g, q1; fma.rn.f16x2 g, z16, t, z16; prmt.b32 t, lo1, hi1, 0x5410; tanh.approx.f16 xr, xl; cvt.u32.u16 lo0, xr;\n"
        "B19:\n"
        "mov.b32 {xl, xh}, a3; tanh.approx.f16 xr, xh; cvt.u32.u16 hi1, xr; mul.rn.f16x2 a0, z20, p; fma.rn.f16x2 p, z21, z21, c; fma.rn.f16x2 q2, g, g, q2; fma.rn.f16x2 g, z17, t, z17; prmt.b32 t, lo0, hi0, 0x5410; tanh.approx.f16 xr, xl; cvt.u32.u16 lo1, xr;\n"
        "B20:\n"
        "mov.b32 {xl, xh}, a0; tanh.approx.f16 xr, xh; cvt.u32.u16 hi0, xr; mul.rn.f16x2 a1, z21, p; fma.rn.f16x2 p, z22, z22, c; fma.rn.f16x2 q3, g, g, q3; fma.rn.f16x2 g, z18, t, z18; prmt.b32 t, lo1, hi1, 0x5410; tanh.approx.f16 xr, xl; cvt.u32.u16 lo0, xr;\n"
        "B21:\n"
        "wgmma.fence.sync.aligned;\n"
        "wgmma.mma_async.sync.aligned.m64n64k16.f16.f16.f16 {z0,z1,z2,z3,z4,z5,z6,z7,z8,z9,z10,z11,z12,z13,z14,z15}, {w12,w13,w14,w15}, ds3, pt, 1, 1, 0;\n"
        "wgmma.mma_async.sync.aligned.m64n64k16.f16.f16.f16 {z0,z1,z2,z3,z4,z5,z6,z7,z8,z9,z10,z11,z12,z13,z14,z15}, {w16,w17,w18,w19}, ds4, pt, 1, 1, 0;\n"
        "wgmma.mma_async.sync.aligned.m64n64k16.f16.f16.f16 {z0,z1,z2,z3,z4,z5,z6,z7,z8,z9,z10,z11,z12,z13,z14,z15}, {w20,w21,w22,w23}, ds5, pt, 1, 1, 0;\n"
        "wgmma.commit_group.sync.aligned;\n"
        "mov.b32 {xl, xh}, a1; tanh.approx.f16 xr, xh; cvt.u32.u16 hi1, xr; mul.rn.f16x2 a2, z22, p; fma.rn.f16x2 p, z23, z23, c; fma.rn.f16x2 q2, g, g, q2; fma.rn.f16x2 g, z19, t, z19; prmt.b32 t, lo0, hi0, 0x5410; tanh.approx.f16 xr, xl; cvt.u32.u16 lo1, xr;\n"
        "B22:\n"
        "mov.b32 {xl, xh}, a2; tanh.approx.f16 xr, xh; cvt.u32.u16 hi0, xr; mul.rn.f16x2 a3, z23, p; fma.rn.f16x2 p, z24, z24, c; fma.rn.f16x2 q3, g, g, q3; fma.rn.f16x2 g, z20, t, z20; prmt.b32 t, lo1, hi1, 0x5410; tanh.approx.f16 xr, xl; cvt.u32.u16 lo0, xr;\n"
        "B23:\n"
        "mov.b32 {xl, xh}, a3; tanh.approx.f16 xr, xh; cvt.u32.u16 hi1, xr; mul.rn.f16x2 a0, z24, p; fma.rn.f16x2 p, z25, z25, c; fma.rn.f16x2 q2, g, g, q2; fma.rn.f16x2 g, z21, t, z21; prmt.b32 t, lo0, hi0, 0x5410; tanh.approx.f16 xr, xl; cvt.u32.u16 lo1, xr;\n"
        "B24:\n"
        "mov.b32 {xl, xh}, a0; tanh.approx.f16 xr, xh; cvt.u32.u16 hi0, xr; mul.rn.f16x2 a1, z25, p; fma.rn.f16x2 p, z26, z26, c; fma.rn.f16x2 q3, g, g, q3; fma.rn.f16x2 g, z22, t, z22; prmt.b32 t, lo1, hi1, 0x5410; tanh.approx.f16 xr, xl; cvt.u32.u16 lo0, xr;\n"
        "B25:\n"
        "mov.b32 {xl, xh}, a1; tanh.approx.f16 xr, xh; cvt.u32.u16 hi1, xr; mul.rn.f16x2 a2, z26, p; fma.rn.f16x2 p, z27, z27, c; fma.rn.f16x2 q2, g, g, q2; fma.rn.f16x2 g, z23, t, z23; prmt.b32 t, lo0, hi0, 0x5410; tanh.approx.f16 xr, xl; cvt.u32.u16 lo1, xr;\n"
        "B26:\n"
        "mov.b32 {xl, xh}, a2; tanh.approx.f16 xr, xh; cvt.u32.u16 hi0, xr; mul.rn.f16x2 a3, z27, p; fma.rn.f16x2 p, z28, z28, c; fma.rn.f16x2 q3, g, g, q3; fma.rn.f16x2 g, z24, t, z24; prmt.b32 t, lo1, hi1, 0x5410; tanh.approx.f16 xr, xl; cvt.u32.u16 lo0, xr;\n"
        "B27:\n"
        "add.u32 n, n, 8; setp.lt.u32 pe, n, 256; setp.ne.and.u32 pe, so, %7, pe;\n"
        "mov.b32 {xl, xh}, a3; tanh.approx.f16 xr, xh; cvt.u32.u16 hi1, xr; mul.rn.f16x2 a0, z28, p; fma.rn.f16x2 p, z29, z29, c; fma.rn.f16x2 q2, g, g, q2; fma.rn.f16x2 g, z25, t, z25; prmt.b32 t, lo0, hi0, 0x5410; tanh.approx.f16 xr, xl; cvt.u32.u16 lo1, xr;\n"
        "B28:\n"
        "mov.b32 {xl, xh}, a0; tanh.approx.f16 xr, xh; cvt.u32.u16 hi0, xr; mul.rn.f16x2 a1, z29, p; fma.rn.f16x2 p, z30, z30, c; fma.rn.f16x2 q3, g, g, q3; fma.rn.f16x2 g, z26, t, z26; prmt.b32 t, lo1, hi1, 0x5410; tanh.approx.f16 xr, xl; cvt.u32.u16 lo0, xr;\n"
        "B29:\n"
        "mov.b32 {xl, xh}, a1; tanh.approx.f16 xr, xh; cvt.u32.u16 hi1, xr; mul.rn.f16x2 a2, z30, p; fma.rn.f16x2 p, z31, z31, c; fma.rn.f16x2 q2, g, g, q2; fma.rn.f16x2 g, z27, t, z27; prmt.b32 t, lo0, hi0, 0x5410; tanh.approx.f16 xr, xl; cvt.u32.u16 lo1, xr;\n"
        "@pe bra.uni TOP;\n"
        "setp.lt.u32 pe, n, 256;\n"
        "@pe bra.uni DUTY;\n"
        "bra.uni DONE;\n"
        "SPINW: mov.u32 cnt, 0;\n"
        "SPINWL:\n"
        "mov.u32 tt, 230880; mbarrier.try_wait.parity.shared::cta.b64 pw, [tt], 0;\n"
        "@pw bra.uni BACKW;\n"
        "add.u32 cnt, cnt, 1; setp.lt.u32 pw, cnt, 0x100000;\n"
        "@pw bra.uni SPINWL;\n"
        "trap;\n"
        "SPIN0: mov.u32 cnt, 0;\n"
        "SPIN0L:\n"
        "mbarrier.try_wait.parity.shared::cta.b64 pw, [n+231552], 0;\n"
        "@pw bra.uni BACK0;\n"
        "add.u32 cnt, cnt, 1; setp.lt.u32 pw, cnt, 0x100000;\n"
        "@pw bra.uni SPIN0L;\n"
        "trap;\n"
        "SPIN: mov.u32 cnt, 0;\n"
        "SPINL:\n"
        "mbarrier.try_wait.parity.shared::cta.b64 pw, [n+231560], 0;\n"
        "@pw bra.uni BACK;\n"
        "add.u32 cnt, cnt, 1; setp.lt.u32 pw, cnt, 0x100000;\n"
        "@pw bra.uni SPINL;\n"
        "trap;\n"
        "DUTY:\n"
        "setp.ge.s32 pr, n, %11;\n"
        "@pr bra.uni FLUSH;\n"
        "setp.ge.u32 pr, %13, 2;\n"
        "@pr bra.uni ROLE2;\n"
        "setp.ge.s32 pr, n, %12; selp.b64 src, %14, gp, pr; add.u32 tt, n, 231288;\n"
        "elect.sync _|pr, 0xffffffff;\n"
        "@pr mbarrier.arrive.expect_tx.shared::cta.b64 _, [tt], %10;\n"
        "@pr cp.async.bulk.shared::cluster.global.mbarrier::complete_tx::bytes [%9], [src], %10, [tt];\n"
        "bra.uni FLUSH;\n"
        "ROLE2:\n"
        "setp.eq.u32 pr, %13, 3;\n"
        "@pr bra.uni ROLE3;\n"
        "setp.ne.s32 pr, n, 248;\n"
        "@pr bra.uni PARK;\n"
        "cp.async.bulk.wait_group 0;\n"
        "sub.s64 src, gp, %16; mov.u32 tt, 230824; mov.u32 cnt, 187392;\n"
        "elect.sync _|pr, 0xffffffff;\n"
        "@pr mbarrier.arrive.expect_tx.shared::cta.b64 _, [tt], 12288;\n"
        "@pr cp.async.bulk.shared::cluster.global.mbarrier::complete_tx::bytes [cnt], [src], 12288, [tt];\n"
        "PARK:\n"
        "elect.sync _|pr, 0xffffffff;\n"
        "@pr cp.async.bulk.global.shared::cta.bulk_group [gp], [%9], 12288;\n"
        "@pr cp.async.bulk.commit_group;\n"
        "bra.uni FLUSH;\n"
        "ROLE3:\n"
        "setp.ne.s32 pr, n, 64;\n"
        "@pr bra.uni AHEAD;\n"
        "mov.u32 tt, 230872;\n"
        "elect.sync _|pr, 0xffffffff;\n"
        "@pr mbarrier.arrive.expect_tx.shared::cta.b64 _, [tt], 75264;\n"
        "mov.u32 cnt, 229248; @pr cp.async.bulk.shared::cluster.global.mbarrier::complete_tx::bytes [cnt], [%18], 768, [tt];\n"
        "mov.u32 cnt, 230016; @pr cp.async.bulk.shared::cluster.global.mbarrier::complete_tx::bytes [cnt], [%19], 768, [tt];\n"
        "mov.u32 cnt, 74752; @pr cp.async.bulk.tensor.2d.shared::cluster.global.mbarrier::complete_tx::bytes [cnt], [%17, {0, 0}], [tt];\n"
        "mov.u32 cnt, 87040; @pr cp.async.bulk.tensor.2d.shared::cluster.global.mbarrier::complete_tx::bytes [cnt], [%17, {0, 192}], [tt];\n"
        "mov.u32 cnt, 99328; @pr cp.async.bulk.tensor.2d.shared::cluster.global.mbarrier::complete_tx::bytes [cnt], [%17, {32, 0}], [tt];\n"
        "mov.u32 cnt, 111616; @pr cp.async.bulk.tensor.2d.shared::cluster.global.mbarrier::complete_tx::bytes [cnt], [%17, {32, 192}], [tt];\n"
        "mov.u32 cnt, 123904; @pr cp.async.bulk.tensor.2d.shared::cluster.global.mbarrier::complete_tx::bytes [cnt], [%17, {64, 0}], [tt];\n"
        "mov.u32 cnt, 136192; @pr cp.async.bulk.tensor.2d.shared::cluster.global.mbarrier::complete_tx::bytes [cnt], [%17, {64, 192}], [tt];\n"
        "AHEAD:\n"
        "elect.sync _|pr, 0xffffffff;\n"
        "@pr cp.async.bulk.prefetch.L2.global [gp], 12288;\n"
        "FLUSH:\n"
        "add.s64 gp, gp, %16;\n"
        "mov.b32 {xl, xh}, q0; cvt.f32.f16 f0, xl; cvt.f32.f16 f1, xh; add.f32 f0, f0, f1; add.f32 %0, %0, f0; mov.b32 q0, 0;\n"
        "mov.b32 {xl, xh}, q1; cvt.f32.f16 f0, xl; cvt.f32.f16 f1, xh; add.f32 f0, f0, f1; add.f32 %1, %1, f0; mov.b32 q1, 0;\n"
        "mov.b32 {xl, xh}, q2; cvt.f32.f16 f0, xl; cvt.f32.f16 f1, xh; add.f32 f0, f0, f1; add.f32 %2, %2, f0; mov.b32 q2, 0;\n"
        "mov.b32 {xl, xh}, q3; cvt.f32.f16 f0, xl; cvt.f32.f16 f1, xh; add.f32 f0, f0, f1; add.f32 %3, %3, f0; mov.b32 q3, 0;\n"
        "setp.ne.u32 pr, %5, 0;\n"
        "@pr bra.uni TOP;\n"
        "wgmma.wait_group.sync.aligned 0;\n"
        "wgmma.fence.sync.aligned;\n"
        "ld.volatile.shared.v2.b32 {lo0, hi0}, [so]; xor.b32 f0, f0, lo0;\n"
        "ld.volatile.shared.v2.b32 {lo1, hi1}, [so]; xor.b32 f0, f0, lo1;\n"
        "ld.volatile.shared.v2.b32 {q1, a0}, [so]; xor.b32 f0, f0, q1;\n"
        "ld.volatile.shared.v2.b32 {q2, a1}, [so]; xor.b32 f0, f0, q2;\n"
        "ld.volatile.shared.v2.b32 {q3, a2}, [so]; xor.b32 f0, f0, q3;\n"
        "ld.volatile.shared.v2.b32 {q0, a3}, [so]; xor.b32 f0, f0, q0;\n"
        "ld.volatile.shared.v2.b32 {t, g}, [so]; xor.b32 f0, f0, t;\n"
        "ld.volatile.shared.v2.b32 {p, f1}, [so]; xor.b32 f0, f0, p;\n"
        "add.f32 %0, %0, f0;\n"
        "setp.eq.u32 pr, n, 1000; @pr bra.uni B31;\n"
        "setp.eq.u32 pr, n, 1001; @pr bra.uni B0;\n"
        "setp.eq.u32 pr, n, 1002; @pr bra.uni B1;\n"
        "setp.eq.u32 pr, n, 1003; @pr bra.uni B2;\n"
        "setp.eq.u32 pr, n, 1004; @pr bra.uni B3;\n"
        "setp.eq.u32 pr, n, 1005; @pr bra.uni B4;\n"
        "setp.eq.u32 pr, n, 1006; @pr bra.uni B5;\n"
        "setp.eq.u32 pr, n, 1007; @pr bra.uni B6;\n"
        "setp.eq.u32 pr, n, 1008; @pr bra.uni B7;\n"
        "setp.eq.u32 pr, n, 1009; @pr bra.uni B8;\n"
        "setp.eq.u32 pr, n, 1010; @pr bra.uni B9;\n"
        "setp.eq.u32 pr, n, 1011; @pr bra.uni B10;\n"
        "setp.eq.u32 pr, n, 1012; @pr bra.uni B11;\n"
        "setp.eq.u32 pr, n, 1013; @pr bra.uni B12;\n"
        "setp.eq.u32 pr, n, 1014; @pr bra.uni B13;\n"
        "setp.eq.u32 pr, n, 1015; @pr bra.uni B14;\n"
        "setp.eq.u32 pr, n, 1016; @pr bra.uni B15;\n"
        "setp.eq.u32 pr, n, 1017; @pr bra.uni B16;\n"
        "setp.eq.u32 pr, n, 1018; @pr bra.uni B17;\n"
        "setp.eq.u32 pr, n, 1019; @pr bra.uni B18;\n"
        "setp.eq.u32 pr, n, 1020; @pr bra.uni B19;\n"
        "setp.eq.u32 pr, n, 1021; @pr bra.uni B20;\n"
        "setp.eq.u32 pr, n, 1022; @pr bra.uni B21;\n"
        "setp.eq.u32 pr, n, 1023; @pr bra.uni B22;\n"
        "setp.eq.u32 pr, n, 1024; @pr bra.uni B23;\n"
        "setp.eq.u32 pr, n, 1025; @pr bra.uni B24;\n"
        "setp.eq.u32 pr, n, 1026; @pr bra.uni B25;\n"
        "setp.eq.u32 pr, n, 1027; @pr bra.uni B26;\n"
        "setp.eq.u32 pr, n, 1028; @pr bra.uni B27;\n"
        "setp.eq.u32 pr, n, 1029; @pr bra.uni B28;\n"
        "setp.eq.u32 pr, n, 1030; @pr bra.uni B29;\n"
        "setp.eq.u32 pr, n, 1031; @pr bra.uni TOP;\n"
        "trap;\n"
        "DONE:\n"
        ASM_TRC("n")
        "mov.b32 {xl, xh}, a2; tanh.approx.f16 xr, xh; cvt.u32.u16 hi0, xr; mul.rn.f16x2 a3, z31, p; fma.rn.f16x2 q3, g, g, q3; fma.rn.f16x2 g, z28, t, z28; prmt.b32 t, lo1, hi1, 0x5410; tanh.approx.f16 xr, xl; cvt.u32.u16 lo0, xr;\n"
        "mov.b32 {xl, xh}, a3; tanh.approx.f16 xr, xh; cvt.u32.u16 hi1, xr; fma.rn.f16x2 q2, g, g, q2; fma.rn.f16x2 g, z29, t, z29; prmt.b32 t, lo0, hi0, 0x5410; tanh.approx.f16 xr, xl; cvt.u32.u16 lo1, xr;\n"
        "fma.rn.f16x2 q3, g, g, q3; fma.rn.f16x2 g, z30, t, z30; prmt.b32 t, lo1, hi1, 0x5410;\n"
        "fma.rn.f16x2 q2, g, g, q2; fma.rn.f16x2 g, z31, t, z31;\n"
        "fma.rn.f16x2 q3, g, g, q3;\n"
        "mov.b32 {xl, xh}, q0; cvt.f32.f16 f0, xl; cvt.f32.f16 f1, xh; add.f32 f0, f0, f1; add.f32 %0, %0, f0; mov.b32 q0, 0;\n"
        "mov.b32 {xl, xh}, q1; cvt.f32.f16 f0, xl; cvt.f32.f16 f1, xh; add.f32 f0, f0, f1; add.f32 %1, %1, f0; mov.b32 q1, 0;\n"
        "mov.b32 {xl, xh}, q2; cvt.f32.f16 f0, xl; cvt.f32.f16 f1, xh; add.f32 f0, f0, f1; add.f32 %2, %2, f0; mov.b32 q2, 0;\n"
        "mov.b32 {xl, xh}, q3; cvt.f32.f16 f0, xl; cvt.f32.f16 f1, xh; add.f32 f0, f0, f1; add.f32 %3, %3, f0; mov.b32 q3, 0;\n"
        "wgmma.wait_group.sync.aligned 0;\n"
        "}\n"
        : "=f"(acc[0][0]), "=f"(acc[0][1]), "=f"(acc[1][0]), "=f"(acc[1][1])
        : "r"(w1t), "r"(yd), "r"(wd), "r"(own_slot), "l"(d.g), "r"(d.s), "r"(d.bytes), "r"(8 * d.end), "r"(8 * d.zero), "r"(role),
          "l"(d.zeros), "r"(lane), "l"(d.step), "l"(&prm.w2_map), "l"(prm.gamma), "l"(prm.beta), "l"(prm.ydesc64[0]), "l"(prm.ydesc64[1])
        : "memory");
}
template <int M, bool LAST_SMEM = true>
__device__ __forceinline__ void gemm1_t(uint32_t (&d)[16], const uint32_t* wa, uint32_t yd, uint32_t wd) {
    wg_fence();
    wgmma_n64_h_set<0>(d, wa, desc<1024, 1>(yd, 0));
#pragma unroll
    for (int kk = 1; kk < (LAST_SMEM ? 5 : 6); kk++)
        wgmma_n64_h_acc<0>(d, wa + kk * 4, kk < 4 ? desc<1024, 1>(yd, kk * 32) : desc<512, 2>(yd, 8192 + (kk - 4) * 32));
    if (LAST_SMEM) wgmma_n64_h_acc_ss(d, desc<1024, 1>(wd, M * 12288), desc<512, 2>(yd, 8192 + 32));
    wg_commit();
}

__device__ __forceinline__ void gelu_sumsq_f(const uint32_t (&d)[16], float (&acc)[2]) {
#pragma unroll
    for (int r = 0; r < 16; r++) {
        float lo, hi;
        h2_unpack(gelu2(d[r]), lo, hi);
        acc[r & 1] = fmaf(lo, lo, acc[r & 1]);
        acc[r & 1] = fmaf(hi, hi, acc[r & 1]);
    }
}
__device__ __forceinline__ void load_w1t(uint32_t (&wa)[2][24], int wg, int w, int lane) {
#pragma unroll
    for (int m = 0; m < 2; m++)
#pragma unroll
        for (int kk = 0; kk < 5; kk++) {
            const int q = lane >> 3, c = 16 * kk + 8 * (q >> 1) + (lane & 7), ck = 2 * w + (q & 1);
            ldsm4_t(wa[m] + kk * 4, sb + SM_W1 + (2 * wg + m) * 12288 + c * 128 + ((ck ^ (c & 7)) * 16));
        }
}
__device__ __forceinline__ unsigned long long* acc_word(const Params& prm, uint32_t epoch, uint32_t e) {
    return &prm.g->acc[epoch & 1][(e >> 2) * 32 + (e & 3)];
}
__device__ __forceinline__ void publish_fast(const Params& prm, const float (&acc)[2][2], uint32_t epoch, int wg, int w, int lane) {
    const bool m = lane & 2, h = lane & 1;
    const float a = (m ? acc[1][0] : acc[0][0]) + __shfl_xor_sync(0xffffffffu, m ? acc[0][0] : acc[1][0], 2);
    const float b = (m ? acc[1][1] : acc[0][1]) + __shfl_xor_sync(0xffffffffu, m ? acc[0][1] : acc[1][1], 2);
    const float v = (h ? b : a) + __shfl_xor_sync(0xffffffffu, h ? a : b, 1);
    const unsigned long long q = (__float2ull_rn(fminf(v, ACC_LIMIT) * 0x1p16f) << 8) + 1;
    asm volatile("red.relaxed.gpu.global.add.u64 [%0], %1;"
                 ::"l"(acc_word(prm, epoch, 128 * wg + 32 * (lane & 2) + 16 * w + (lane >> 2) + 8 * (lane & 1))), "l"(q) : "memory");
}
__device__ __forceinline__ float collect_fast(const unsigned long long* word) {
    unsigned long long v;
    asm volatile(
        "{\n.reg .pred p;\n.reg .u32 n, lo, hi;\nmov.u32 n, 0;\n"
        "POLL:\nld.relaxed.gpu.global.u64 %0, [%1];\nmov.b64 {lo, hi}, %0;\nand.b32 lo, lo, 255;\n"
        "setp.eq.u32 p, lo, %2;\nvote.sync.all.pred p, p, 0xffffffff;\n@p bra.uni POLL_DONE;\n"
        "add.u32 n, n, 1;\nsetp.lt.u32 p, n, 0x400000;\n@p bra.uni POLL;\ntrap;\nPOLL_DONE:\n}\n"
        : "=l"(v) : "l"(word), "n"(NUM_CTAS) : "memory");
    return __ull2float_rn(v >> 8) * 0x1p-16f;
}
__device__ __forceinline__ void publish_sums(const float (&acc)[2][2], float* sums, unsigned int* counter, int wg, int w, int lane) {
#pragma unroll
    for (int m = 0; m < 2; m++)
#pragma unroll
        for (int h = 0; h < 2; h++) {
            const float v = quad_sum(acc[m][h]);
            if ((lane & 3) == 0) atomicAdd(sums + 64 * (2 * wg + m) + 16 * w + (lane >> 2) + 8 * h, v);
        }
    named_sync(1, 384);
    if (fresh_tid() == 0) asm volatile("red.release.gpu.global.add.u32 [%0], 1;" ::"l"(counter) : "memory");
}
__device__ __forceinline__ void grid_wait(const unsigned int* counter, unsigned int target) {
    if (fresh_tid() == 0) {
        unsigned int v, spins = 0;
        do {
            asm volatile("ld.acquire.gpu.global.u32 %0, [%1];" : "=r"(v) : "l"(counter) : "memory");
            if (++spins > (1u << 22)) __trap();
        } while ((int)(v - target) < 0);
    }
    __syncthreads();
}

struct Pass2 {
    uint32_t wg;
    uint32_t off;
    int step;
    uint32_t xs;
    uint32_t a_offs, xs_offs, bias_addr;
    uint32_t w;
};

static_assert(sb + SM_BAR + BAR_ROWS * 8 == 231208 && BAR_STAT == BAR_ROWS + 2 && sb + SM_RED + RED_SCALE * 4 == 230792, "layout");
static_assert(sb + SM_BAR + BAR_Y2FULL * 8 == 230800 && sb + SM_BAR + BAR_XSFULL * 8 == 230832, "layout");
#define PASS2_STATE ".reg .b32 qa<24>, qz<32>, o<24>, g<16>, p<2>, a<4>, lo<2>, hi<2>, h<2>, osc;"
__device__ __forceinline__ void pass2_start(const Pass2& c, const Params& prm) {
    asm volatile(
        "{\n"
        ".reg .b32 t<2>, c, tt, ad, cnt, ybar;\n"
        ".reg .b16 xl, xh, xr;\n"
        ".reg .b64 w1d, dt;\n"
        ".reg .pred pt, pf, pw;\n"
        "setp.ne.b32 pt, 1, 0; setp.ne.b32 pf, 0, 0; mov.b32 c, 0x40D940D9; mov.b64 w1d, {%1, 0x40000040}; mad.lo.u32 ybar, %2, 8, 230800;\n"
        "mbarrier.try_wait.parity.shared::cta.b64 pw, [ybar], 0;\n"
        "@!pw bra.uni SPINY0;\n"
        "BACKY0:\n"
        "and.b32 t0, %5, 0xffff; shr.u32 t1, %5, 16;\n"
        "xor.b32 ad, t0, 0; add.u32 ad, ad, %4; ldmatrix.sync.aligned.m8n8.x4.shared.b16 {qa0,qa1,qa2,qa3}, [ad];\n"
        "xor.b32 ad, t0, 32; add.u32 ad, ad, %4; ldmatrix.sync.aligned.m8n8.x4.shared.b16 {qa4,qa5,qa6,qa7}, [ad];\n"
        "xor.b32 ad, t0, 64; add.u32 ad, ad, %4; ldmatrix.sync.aligned.m8n8.x4.shared.b16 {qa8,qa9,qa10,qa11}, [ad];\n"
        "xor.b32 ad, t0, 96; add.u32 ad, ad, %4; ldmatrix.sync.aligned.m8n8.x4.shared.b16 {qa12,qa13,qa14,qa15}, [ad];\n"
        "xor.b32 ad, t1, 0; add.u32 ad, ad, %4; ldmatrix.sync.aligned.m8n8.x4.shared.b16 {qa16,qa17,qa18,qa19}, [ad];\n"
        "xor.b32 ad, t1, 32; add.u32 ad, ad, %4; ldmatrix.sync.aligned.m8n8.x4.shared.b16 {qa20,qa21,qa22,qa23}, [ad];\n"
        "wgmma.fence.sync.aligned;\n"
        "add.s64 dt, w1d, 0; wgmma.mma_async.sync.aligned.m64n64k16.f16.f16.f16 {qz0,qz1,qz2,qz3,qz4,qz5,qz6,qz7,qz8,qz9,qz10,qz11,qz12,qz13,qz14,qz15}, {qa0,qa1,qa2,qa3}, dt, pf, 1, 1, 1;\n"
        "add.s64 dt, w1d, 128; wgmma.mma_async.sync.aligned.m64n64k16.f16.f16.f16 {qz0,qz1,qz2,qz3,qz4,qz5,qz6,qz7,qz8,qz9,qz10,qz11,qz12,qz13,qz14,qz15}, {qa4,qa5,qa6,qa7}, dt, pt, 1, 1, 1;\n"
        "add.s64 dt, w1d, 256; wgmma.mma_async.sync.aligned.m64n64k16.f16.f16.f16 {qz0,qz1,qz2,qz3,qz4,qz5,qz6,qz7,qz8,qz9,qz10,qz11,qz12,qz13,qz14,qz15}, {qa8,qa9,qa10,qa11}, dt, pt, 1, 1, 1;\n"
        "add.s64 dt, w1d, 384; wgmma.mma_async.sync.aligned.m64n64k16.f16.f16.f16 {qz0,qz1,qz2,qz3,qz4,qz5,qz6,qz7,qz8,qz9,qz10,qz11,qz12,qz13,qz14,qz15}, {qa12,qa13,qa14,qa15}, dt, pt, 1, 1, 1;\n"
        "add.s64 dt, w1d, 512; wgmma.mma_async.sync.aligned.m64n64k16.f16.f16.f16 {qz0,qz1,qz2,qz3,qz4,qz5,qz6,qz7,qz8,qz9,qz10,qz11,qz12,qz13,qz14,qz15}, {qa16,qa17,qa18,qa19}, dt, pt, 1, 1, 1;\n"
        "add.s64 dt, w1d, 640; wgmma.mma_async.sync.aligned.m64n64k16.f16.f16.f16 {qz0,qz1,qz2,qz3,qz4,qz5,qz6,qz7,qz8,qz9,qz10,qz11,qz12,qz13,qz14,qz15}, {qa20,qa21,qa22,qa23}, dt, pt, 1, 1, 1;\n"
        "wgmma.commit_group.sync.aligned;\n"
        "wgmma.wait_group.sync.aligned 0;\n"
        "fma.rn.f16x2 p0, qz0, qz0, c;\n"
        "mul.rn.f16x2 a0, qz0, p0; fma.rn.f16x2 p1, qz1, qz1, c;\n"
        "mov.b32 {xl, xh}, a0; tanh.approx.f16 xr, xl; cvt.u32.u16 lo0, xr; tanh.approx.f16 xr, xh; cvt.u32.u16 hi0, xr; mul.rn.f16x2 a1, qz1, p1; fma.rn.f16x2 p0, qz2, qz2, c;\n"
        "mov.b32 {xl, xh}, a1; tanh.approx.f16 xr, xl; cvt.u32.u16 lo1, xr; tanh.approx.f16 xr, xh; cvt.u32.u16 hi1, xr; mul.rn.f16x2 a0, qz2, p0; fma.rn.f16x2 p1, qz3, qz3, c; prmt.b32 h0, lo0, hi0, 0x5410;\n"
        "mov.b32 {xl, xh}, a0; tanh.approx.f16 xr, xl; cvt.u32.u16 lo0, xr; tanh.approx.f16 xr, xh; cvt.u32.u16 hi0, xr; mul.rn.f16x2 a1, qz3, p1; fma.rn.f16x2 p0, qz4, qz4, c; fma.rn.f16x2 g0, qz0, h0, qz0; prmt.b32 h1, lo1, hi1, 0x5410;\n"
        "mov.b32 {xl, xh}, a1; tanh.approx.f16 xr, xl; cvt.u32.u16 lo1, xr; tanh.approx.f16 xr, xh; cvt.u32.u16 hi1, xr; mul.rn.f16x2 a0, qz4, p0; fma.rn.f16x2 p1, qz5, qz5, c; fma.rn.f16x2 g1, qz1, h1, qz1; prmt.b32 h0, lo0, hi0, 0x5410;\n"
        "mov.b32 {xl, xh}, a0; tanh.approx.f16 xr, xl; cvt.u32.u16 lo0, xr; tanh.approx.f16 xr, xh; cvt.u32.u16 hi0, xr; mul.rn.f16x2 a1, qz5, p1; fma.rn.f16x2 p0, qz6, qz6, c; fma.rn.f16x2 g2, qz2, h0, qz2; prmt.b32 h1, lo1, hi1, 0x5410;\n"
        "mov.b32 {xl, xh}, a1; tanh.approx.f16 xr, xl; cvt.u32.u16 lo1, xr; tanh.approx.f16 xr, xh; cvt.u32.u16 hi1, xr; mul.rn.f16x2 a0, qz6, p0; fma.rn.f16x2 p1, qz7, qz7, c; fma.rn.f16x2 g3, qz3, h1, qz3; prmt.b32 h0, lo0, hi0, 0x5410;\n"
        "bra.uni DONE;\n"
        "SPINY0: mov.u32 cnt, 0;\n"
        "SPINY0L:\n"
        "mbarrier.try_wait.parity.shared::cta.b64 pw, [ybar], 0;\n"
        "@pw bra.uni BACKY0;\n"
        "add.u32 cnt, cnt, 1; setp.lt.u32 pw, cnt, 0x100000;\n"
        "@pw bra.uni SPINY0L;\n"
        "trap;\n"
        "DONE:\n"
        "}\n"
        :: "n"(0), "r"(prm.w1desc), "r"(c.wg), "n"(0), "r"(c.xs), "r"(c.a_offs) : "memory");
}
__device__ __forceinline__ bool pass2_head(const Pass2& c, uint32_t round) {
    uint32_t retry;
    asm volatile(
        "{\n"
        ".reg .b32 t<2>, tt, ad, cnt;\n"
        ".reg .pred pw;\n"
        "and.b32 t0, %3, 0xffff; shr.u32 t1, %3, 16;\n"
        "xor.b32 ad, t0, 0; add.u32 ad, ad, %4; ldmatrix.sync.aligned.m8n8.x4.shared.b16 {qa0,qa1,qa2,qa3}, [ad];\n"
        "xor.b32 ad, t0, 32; add.u32 ad, ad, %4; ldmatrix.sync.aligned.m8n8.x4.shared.b16 {qa4,qa5,qa6,qa7}, [ad];\n"
        "xor.b32 ad, t0, 64; add.u32 ad, ad, %4; ldmatrix.sync.aligned.m8n8.x4.shared.b16 {qa8,qa9,qa10,qa11}, [ad];\n"
        "xor.b32 ad, t0, 96; add.u32 ad, ad, %4; ldmatrix.sync.aligned.m8n8.x4.shared.b16 {qa12,qa13,qa14,qa15}, [ad];\n"
        "xor.b32 ad, t1, 0; add.u32 ad, ad, %4; ldmatrix.sync.aligned.m8n8.x4.shared.b16 {qa16,qa17,qa18,qa19}, [ad];\n"
        "xor.b32 ad, t1, 32; add.u32 ad, ad, %4; ldmatrix.sync.aligned.m8n8.x4.shared.b16 {qa20,qa21,qa22,qa23}, [ad];\n"
        "mov.b32 qz16, 0; mov.b32 qz17, 0; mov.b32 qz18, 0; mov.b32 qz19, 0; mov.b32 qz20, 0; mov.b32 qz21, 0; mov.b32 qz22, 0; mov.b32 qz23, 0; mov.b32 qz24, 0; mov.b32 qz25, 0; mov.b32 qz26, 0; mov.b32 qz27, 0; mov.b32 qz28, 0; mov.b32 qz29, 0; mov.b32 qz30, 0; mov.b32 qz31, 0;\n"
        "mov.b32 g4, 0; mov.b32 g5, 0; mov.b32 g6, 0; mov.b32 g7, 0; mov.b32 g8, 0; mov.b32 g9, 0; mov.b32 g10, 0; mov.b32 g11, 0; mov.b32 g12, 0; mov.b32 g13, 0; mov.b32 g14, 0; mov.b32 g15, 0;\n"
        "mov.u32 tt, 231224; mbarrier.try_wait.parity.shared::cta.b64 pw, [tt], %1;\n"
        "@!pw bra.uni SPINR;\n"
        "BACKR:\n"
        "mov.u32 tt, 230792; ld.shared.v2.b32 {osc, %0}, [tt];\n"
        "ld.shared.v4.b32 {o0,o1,o2,o3}, [%2+0];\n"
        "ld.shared.v4.b32 {o4,o5,o6,o7}, [%2+64];\n"
        "ld.shared.v4.b32 {o8,o9,o10,o11}, [%2+128];\n"
        "ld.shared.v4.b32 {o12,o13,o14,o15}, [%2+192];\n"
        "ld.shared.v4.b32 {o16,o17,o18,o19}, [%2+256];\n"
        "ld.shared.v4.b32 {o20,o21,o22,o23}, [%2+320];\n"
        "bra.uni DONE;\n"
        "SPINR: mov.u32 cnt, 0;\n"
        "SPINRL:\n"
        "mov.u32 tt, 231224; mbarrier.try_wait.parity.shared::cta.b64 pw, [tt], %1;\n"
        "@pw bra.uni BACKR;\n"
        "add.u32 cnt, cnt, 1; setp.lt.u32 pw, cnt, 0x100000;\n"
        "@pw bra.uni SPINRL;\n"
        "trap;\n"
        "DONE:\n"
        "}\n"
        : "=r"(retry)
        : "r"(round), "r"(c.bias_addr), "r"(c.a_offs), "r"(c.xs)
        : "memory");
    return __any_sync(0xffffffffu, retry);
}
__device__ __forceinline__ void pass2_tiles(const Pass2& c, const Params& prm) {
    asm volatile(
        "{\n"
        ".reg .b32 v<8>, n, off, c, tt, ad, cnt, ybar, xbar, tbar, tpar, id;\n"
        ".reg .b16 xl, xh, xr;\n"
        ".reg .f32 f0, f1;\n"
        ".reg .b64 w1d, w2d, dt, gp, pol;\n"
        ".reg .pred pt, pf, pr, pw, pl, pk, pm, pz, pn;\n"
        "setp.ne.b32 pt, 1, 0; setp.ne.b32 pf, 0, 0; setp.eq.u32 pl, %9, 0; setp.eq.u32 pk, %9, 0; setp.eq.u32 pz, %0, 0;\n"
        "mov.b32 c, 0x40D940D9;\n"
        "mov.b64 w1d, {%0, 0x40000040}; mov.b64 w2d, {%1, 0x80000020};\n"
        "mad.lo.u32 ybar, %2, 8, 230800; mad.lo.u32 xbar, %2, 8, 230832; add.u32 id, %2, 2;\n"
        "xor.b32 tt, %2, 0; mad.lo.u32 tbar, tt, 64, 230888; setp.eq.u32 pr, tt, 0; selp.u32 tpar, 1, 0, pr; mov.u32 tt, %laneid; setp.eq.u32 pn, tt, 0;\n"
        "mov.u32 n, -1; add.u32 off, %3, %8; mov.pred pm, pt; mov.b64 pol, 0x12F0000000000000;\n"
        "mov.b32 v0, 0; mov.b32 v1, 0; mov.b32 v2, 0; mov.b32 v3, 0; mov.b32 v4, 0; mov.b32 v5, 0; mov.b32 v6, 0; mov.b32 v7, 0;\n"
        "LOOP:\n"
        "@!pm bra.uni SKIP0;\n"
        "wgmma.fence.sync.aligned;\n"
        "add.s64 dt, w1d, 768; wgmma.mma_async.sync.aligned.m64n64k16.f16.f16.f16 {qz16,qz17,qz18,qz19,qz20,qz21,qz22,qz23,qz24,qz25,qz26,qz27,qz28,qz29,qz30,qz31}, {qa0,qa1,qa2,qa3}, dt, pf, 1, 1, 1;\n"
        "add.s64 dt, w1d, 896; wgmma.mma_async.sync.aligned.m64n64k16.f16.f16.f16 {qz16,qz17,qz18,qz19,qz20,qz21,qz22,qz23,qz24,qz25,qz26,qz27,qz28,qz29,qz30,qz31}, {qa4,qa5,qa6,qa7}, dt, pt, 1, 1, 1;\n"
        "add.s64 dt, w1d, 1024; wgmma.mma_async.sync.aligned.m64n64k16.f16.f16.f16 {qz16,qz17,qz18,qz19,qz20,qz21,qz22,qz23,qz24,qz25,qz26,qz27,qz28,qz29,qz30,qz31}, {qa8,qa9,qa10,qa11}, dt, pt, 1, 1, 1;\n"
        "add.s64 dt, w1d, 1152; wgmma.mma_async.sync.aligned.m64n64k16.f16.f16.f16 {qz16,qz17,qz18,qz19,qz20,qz21,qz22,qz23,qz24,qz25,qz26,qz27,qz28,qz29,qz30,qz31}, {qa12,qa13,qa14,qa15}, dt, pt, 1, 1, 1;\n"
        "add.s64 dt, w1d, 1280; wgmma.mma_async.sync.aligned.m64n64k16.f16.f16.f16 {qz16,qz17,qz18,qz19,qz20,qz21,qz22,qz23,qz24,qz25,qz26,qz27,qz28,qz29,qz30,qz31}, {qa16,qa17,qa18,qa19}, dt, pt, 1, 1, 1;\n"
        "add.s64 dt, w1d, 1408; wgmma.mma_async.sync.aligned.m64n64k16.f16.f16.f16 {qz16,qz17,qz18,qz19,qz20,qz21,qz22,qz23,qz24,qz25,qz26,qz27,qz28,qz29,qz30,qz31}, {qa20,qa21,qa22,qa23}, dt, pt, 1, 1, 1;\n"
        "SKIP0:\n"
        "wgmma.fence.sync.aligned;\n"
        "wgmma.commit_group.sync.aligned;\n"
        "setp.lt.s32 pr, n, 0;\n"
        "@pr bra.uni FIRST;\n"
        "and.b32 tt, n, 1; mbarrier.try_wait.parity.shared::cta.b64 pw, [xbar], tt;\n"
        "@!pw bra.uni SPINX;\n"
        "BACKX:\n"
        "and.b32 ad, %6, 0xffff; add.u32 ad, ad, %4; ld.shared.v4.b32 {v0,v1,v2,v3}, [ad+0];\n"
        "shr.u32 ad, %6, 16; add.u32 ad, ad, %4; ld.shared.v4.b32 {v4,v5,v6,v7}, [ad+0];\n"
        "mov.b32 {xl, xh}, o0; cvt.f32.f16 f0, xl; cvt.f32.f16 f1, xh; cvt.rn.bf16x2.f32 tt, f1, f0; fma.rn.bf16x2 v0, tt, osc, v0;\n"
        "mov.b32 {xl, xh}, o2; cvt.f32.f16 f0, xl; cvt.f32.f16 f1, xh; cvt.rn.bf16x2.f32 tt, f1, f0; fma.rn.bf16x2 v1, tt, osc, v1;\n"
        "mov.b32 {xl, xh}, o4; cvt.f32.f16 f0, xl; cvt.f32.f16 f1, xh; cvt.rn.bf16x2.f32 tt, f1, f0; fma.rn.bf16x2 v2, tt, osc, v2;\n"
        "mov.b32 {xl, xh}, o6; cvt.f32.f16 f0, xl; cvt.f32.f16 f1, xh; cvt.rn.bf16x2.f32 tt, f1, f0; fma.rn.bf16x2 v3, tt, osc, v3;\n"
        "and.b32 ad, %6, 0xffff; add.u32 ad, ad, %4; st.shared.v4.b32 [ad+0], {v0,v1,v2,v3};\n"
        "and.b32 ad, %6, 0xffff; add.u32 ad, ad, %4; ld.shared.v4.b32 {v0,v1,v2,v3}, [ad+64];\n"
        "mov.b32 {xl, xh}, o1; cvt.f32.f16 f0, xl; cvt.f32.f16 f1, xh; cvt.rn.bf16x2.f32 tt, f1, f0; fma.rn.bf16x2 v4, tt, osc, v4;\n"
        "mov.b32 {xl, xh}, o3; cvt.f32.f16 f0, xl; cvt.f32.f16 f1, xh; cvt.rn.bf16x2.f32 tt, f1, f0; fma.rn.bf16x2 v5, tt, osc, v5;\n"
        "mov.b32 {xl, xh}, o5; cvt.f32.f16 f0, xl; cvt.f32.f16 f1, xh; cvt.rn.bf16x2.f32 tt, f1, f0; fma.rn.bf16x2 v6, tt, osc, v6;\n"
        "mov.b32 {xl, xh}, o7; cvt.f32.f16 f0, xl; cvt.f32.f16 f1, xh; cvt.rn.bf16x2.f32 tt, f1, f0; fma.rn.bf16x2 v7, tt, osc, v7;\n"
        "shr.u32 ad, %6, 16; add.u32 ad, ad, %4; st.shared.v4.b32 [ad+0], {v4,v5,v6,v7};\n"
        "shr.u32 ad, %6, 16; add.u32 ad, ad, %4; ld.shared.v4.b32 {v4,v5,v6,v7}, [ad+64];\n"
        "ld.shared.v4.b32 {o0,o1,o2,o3}, [%7+0];\n"
        "ld.shared.v4.b32 {o4,o5,o6,o7}, [%7+64];\n"
        "mov.b32 {xl, xh}, o8; cvt.f32.f16 f0, xl; cvt.f32.f16 f1, xh; cvt.rn.bf16x2.f32 tt, f1, f0; fma.rn.bf16x2 v0, tt, osc, v0;\n"
        "mov.b32 {xl, xh}, o10; cvt.f32.f16 f0, xl; cvt.f32.f16 f1, xh; cvt.rn.bf16x2.f32 tt, f1, f0; fma.rn.bf16x2 v1, tt, osc, v1;\n"
        "mov.b32 {xl, xh}, o12; cvt.f32.f16 f0, xl; cvt.f32.f16 f1, xh; cvt.rn.bf16x2.f32 tt, f1, f0; fma.rn.bf16x2 v2, tt, osc, v2;\n"
        "mov.b32 {xl, xh}, o14; cvt.f32.f16 f0, xl; cvt.f32.f16 f1, xh; cvt.rn.bf16x2.f32 tt, f1, f0; fma.rn.bf16x2 v3, tt, osc, v3;\n"
        "and.b32 ad, %6, 0xffff; add.u32 ad, ad, %4; st.shared.v4.b32 [ad+64], {v0,v1,v2,v3};\n"
        "and.b32 ad, %6, 0xffff; add.u32 ad, ad, %4; ld.shared.v4.b32 {v0,v1,v2,v3}, [ad+128];\n"
        "mov.b32 {xl, xh}, o9; cvt.f32.f16 f0, xl; cvt.f32.f16 f1, xh; cvt.rn.bf16x2.f32 tt, f1, f0; fma.rn.bf16x2 v4, tt, osc, v4;\n"
        "mov.b32 {xl, xh}, o11; cvt.f32.f16 f0, xl; cvt.f32.f16 f1, xh; cvt.rn.bf16x2.f32 tt, f1, f0; fma.rn.bf16x2 v5, tt, osc, v5;\n"
        "mov.b32 {xl, xh}, o13; cvt.f32.f16 f0, xl; cvt.f32.f16 f1, xh; cvt.rn.bf16x2.f32 tt, f1, f0; fma.rn.bf16x2 v6, tt, osc, v6;\n"
        "mov.b32 {xl, xh}, o15; cvt.f32.f16 f0, xl; cvt.f32.f16 f1, xh; cvt.rn.bf16x2.f32 tt, f1, f0; fma.rn.bf16x2 v7, tt, osc, v7;\n"
        "shr.u32 ad, %6, 16; add.u32 ad, ad, %4; st.shared.v4.b32 [ad+64], {v4,v5,v6,v7};\n"
        "shr.u32 ad, %6, 16; add.u32 ad, ad, %4; ld.shared.v4.b32 {v4,v5,v6,v7}, [ad+128];\n"
        "ld.shared.v4.b32 {o8,o9,o10,o11}, [%7+128];\n"
        "ld.shared.v4.b32 {o12,o13,o14,o15}, [%7+192];\n"
        "mov.b32 {xl, xh}, o16; cvt.f32.f16 f0, xl; cvt.f32.f16 f1, xh; cvt.rn.bf16x2.f32 tt, f1, f0; fma.rn.bf16x2 v0, tt, osc, v0;\n"
        "mov.b32 {xl, xh}, o18; cvt.f32.f16 f0, xl; cvt.f32.f16 f1, xh; cvt.rn.bf16x2.f32 tt, f1, f0; fma.rn.bf16x2 v1, tt, osc, v1;\n"
        "mov.b32 {xl, xh}, o20; cvt.f32.f16 f0, xl; cvt.f32.f16 f1, xh; cvt.rn.bf16x2.f32 tt, f1, f0; fma.rn.bf16x2 v2, tt, osc, v2;\n"
        "mov.b32 {xl, xh}, o22; cvt.f32.f16 f0, xl; cvt.f32.f16 f1, xh; cvt.rn.bf16x2.f32 tt, f1, f0; fma.rn.bf16x2 v3, tt, osc, v3;\n"
        "and.b32 ad, %6, 0xffff; add.u32 ad, ad, %4; st.shared.v4.b32 [ad+128], {v0,v1,v2,v3};\n"
        "mov.b32 {xl, xh}, o17; cvt.f32.f16 f0, xl; cvt.f32.f16 f1, xh; cvt.rn.bf16x2.f32 tt, f1, f0; fma.rn.bf16x2 v4, tt, osc, v4;\n"
        "mov.b32 {xl, xh}, o19; cvt.f32.f16 f0, xl; cvt.f32.f16 f1, xh; cvt.rn.bf16x2.f32 tt, f1, f0; fma.rn.bf16x2 v5, tt, osc, v5;\n"
        "mov.b32 {xl, xh}, o21; cvt.f32.f16 f0, xl; cvt.f32.f16 f1, xh; cvt.rn.bf16x2.f32 tt, f1, f0; fma.rn.bf16x2 v6, tt, osc, v6;\n"
        "mov.b32 {xl, xh}, o23; cvt.f32.f16 f0, xl; cvt.f32.f16 f1, xh; cvt.rn.bf16x2.f32 tt, f1, f0; fma.rn.bf16x2 v7, tt, osc, v7;\n"
        "shr.u32 ad, %6, 16; add.u32 ad, ad, %4; st.shared.v4.b32 [ad+128], {v4,v5,v6,v7};\n"
        "ld.shared.v4.b32 {o16,o17,o18,o19}, [%7+256];\n"
        "ld.shared.v4.b32 {o20,o21,o22,o23}, [%7+320];\n"
        "FIRST:\n"
        "@pz bra.uni B7;\n"
        "mov.b32 {xl, xh}, a0; tanh.approx.f16 xr, xl; cvt.u32.u16 lo0, xr; tanh.approx.f16 xr, xh; cvt.u32.u16 hi0, xr; mul.rn.f16x2 a1, qz7, p1; fma.rn.f16x2 p0, qz8, qz8, c; fma.rn.f16x2 g4, qz4, h0, qz4; prmt.b32 h1, lo1, hi1, 0x5410;\n"
        "B7:\n"
        "fence.proxy.async.shared::cta;\n"
        "add.u32 tt, id, 4;\n"
        "@pl bra.uni STORE;\n"
        "bar.arrive tt, 128;\n"
        "STOREB:\n"
        ASM_MARK
        "@!pm bra.uni DONE;\n"
        "add.s32 n, n, 1; sub.u32 off, off, %8; setp.lt.s32 pm, n, 7;\n"
        "@pz bra.uni B10;\n"
        "mov.b32 {xl, xh}, a1; tanh.approx.f16 xr, xl; cvt.u32.u16 lo1, xr; tanh.approx.f16 xr, xh; cvt.u32.u16 hi1, xr; mul.rn.f16x2 a0, qz8, p0; fma.rn.f16x2 p1, qz9, qz9, c; fma.rn.f16x2 g5, qz5, h1, qz5; prmt.b32 h0, lo0, hi0, 0x5410;\n"
        "mov.b32 {xl, xh}, a0; tanh.approx.f16 xr, xl; cvt.u32.u16 lo0, xr; tanh.approx.f16 xr, xh; cvt.u32.u16 hi0, xr; mul.rn.f16x2 a1, qz9, p1; fma.rn.f16x2 p0, qz10, qz10, c; fma.rn.f16x2 g6, qz6, h0, qz6; prmt.b32 h1, lo1, hi1, 0x5410;\n"
        "mov.b32 {xl, xh}, a1; tanh.approx.f16 xr, xl; cvt.u32.u16 lo1, xr; tanh.approx.f16 xr, xh; cvt.u32.u16 hi1, xr; mul.rn.f16x2 a0, qz10, p0; fma.rn.f16x2 p1, qz11, qz11, c; fma.rn.f16x2 g7, qz7, h1, qz7; prmt.b32 h0, lo0, hi0, 0x5410;\n"
        "B10:\n"
        "setp.eq.s32 pr, n, 0;\n"
        "@pr bra.uni SPINW0;\n"
        "BACKW0:\n"
        "wgmma.fence.sync.aligned;\n"
        "add.s64 dt, w2d, 0; wgmma.mma_async.sync.aligned.m64n96k16.f16.f16.f16 {o0,o1,o2,o3,o4,o5,o6,o7,o8,o9,o10,o11,o12,o13,o14,o15,o16,o17,o18,o19,o20,o21,o22,o23}, {g0,g1,g2,g3}, dt, pt, 1, 1, 1;\n"
        "add.s64 dt, w2d, 64; wgmma.mma_async.sync.aligned.m64n96k16.f16.f16.f16 {o0,o1,o2,o3,o4,o5,o6,o7,o8,o9,o10,o11,o12,o13,o14,o15,o16,o17,o18,o19,o20,o21,o22,o23}, {g4,g5,g6,g7}, dt, pt, 1, 1, 1;\n"
        "wgmma.commit_group.sync.aligned;\n"
        "@pz bra.uni B14;\n"
        "mov.b32 {xl, xh}, a0; tanh.approx.f16 xr, xl; cvt.u32.u16 lo0, xr; tanh.approx.f16 xr, xh; cvt.u32.u16 hi0, xr; mul.rn.f16x2 a1, qz11, p1; fma.rn.f16x2 p0, qz12, qz12, c; fma.rn.f16x2 g8, qz8, h0, qz8; prmt.b32 h1, lo1, hi1, 0x5410;\n"
        "mov.b32 {xl, xh}, a1; tanh.approx.f16 xr, xl; cvt.u32.u16 lo1, xr; tanh.approx.f16 xr, xh; cvt.u32.u16 hi1, xr; mul.rn.f16x2 a0, qz12, p0; fma.rn.f16x2 p1, qz13, qz13, c; fma.rn.f16x2 g9, qz9, h1, qz9; prmt.b32 h0, lo0, hi0, 0x5410;\n"
        "mov.b32 {xl, xh}, a0; tanh.approx.f16 xr, xl; cvt.u32.u16 lo0, xr; tanh.approx.f16 xr, xh; cvt.u32.u16 hi0, xr; mul.rn.f16x2 a1, qz13, p1; fma.rn.f16x2 p0, qz14, qz14, c; fma.rn.f16x2 g10, qz10, h0, qz10; prmt.b32 h1, lo1, hi1, 0x5410;\n"
        "mov.b32 {xl, xh}, a1; tanh.approx.f16 xr, xl; cvt.u32.u16 lo1, xr; tanh.approx.f16 xr, xh; cvt.u32.u16 hi1, xr; mul.rn.f16x2 a0, qz14, p0; fma.rn.f16x2 p1, qz15, qz15, c; fma.rn.f16x2 g11, qz11, h1, qz11; prmt.b32 h0, lo0, hi0, 0x5410;\n"
        "B14:\n"
        "wgmma.wait_group.sync.aligned 1;\n"
        "wgmma.fence.sync.aligned;\n"
        "add.s64 dt, w2d, 128; wgmma.mma_async.sync.aligned.m64n96k16.f16.f16.f16 {o0,o1,o2,o3,o4,o5,o6,o7,o8,o9,o10,o11,o12,o13,o14,o15,o16,o17,o18,o19,o20,o21,o22,o23}, {g8,g9,g10,g11}, dt, pt, 1, 1, 1;\n"
        "wgmma.commit_group.sync.aligned;\n"
        "@pz bra.uni B18;\n"
        "mov.b32 {xl, xh}, a0; tanh.approx.f16 xr, xl; cvt.u32.u16 lo0, xr; tanh.approx.f16 xr, xh; cvt.u32.u16 hi0, xr; mul.rn.f16x2 a1, qz15, p1; fma.rn.f16x2 p0, qz16, qz16, c; fma.rn.f16x2 g12, qz12, h0, qz12; prmt.b32 h1, lo1, hi1, 0x5410;\n"
        "mov.b32 {xl, xh}, a1; tanh.approx.f16 xr, xl; cvt.u32.u16 lo1, xr; tanh.approx.f16 xr, xh; cvt.u32.u16 hi1, xr; mul.rn.f16x2 a0, qz16, p0; fma.rn.f16x2 p1, qz17, qz17, c; fma.rn.f16x2 g13, qz13, h1, qz13; prmt.b32 h0, lo0, hi0, 0x5410;\n"
        "mov.b32 {xl, xh}, a0; tanh.approx.f16 xr, xl; cvt.u32.u16 lo0, xr; tanh.approx.f16 xr, xh; cvt.u32.u16 hi0, xr; mul.rn.f16x2 a1, qz17, p1; fma.rn.f16x2 p0, qz18, qz18, c; fma.rn.f16x2 g14, qz14, h0, qz14; prmt.b32 h1, lo1, hi1, 0x5410;\n"
        "mov.b32 {xl, xh}, a1; tanh.approx.f16 xr, xl; cvt.u32.u16 lo1, xr; tanh.approx.f16 xr, xh; cvt.u32.u16 hi1, xr; mul.rn.f16x2 a0, qz18, p0; fma.rn.f16x2 p1, qz19, qz19, c; fma.rn.f16x2 g15, qz15, h1, qz15; prmt.b32 h0, lo0, hi0, 0x5410;\n"
        "B18:\n"
        "wgmma.wait_group.sync.aligned 1;\n"
        "mad.lo.u32 tt, n, 8, tbar; mbarrier.try_wait.parity.shared::cta.b64 pw, [tt], tpar;\n"
        "@!pw bra.uni SPINT;\n"
        "BACKT:\n"
        "wgmma.fence.sync.aligned;\n"
        "add.s64 dt, w2d, 192; wgmma.mma_async.sync.aligned.m64n96k16.f16.f16.f16 {o0,o1,o2,o3,o4,o5,o6,o7,o8,o9,o10,o11,o12,o13,o14,o15,o16,o17,o18,o19,o20,o21,o22,o23}, {g12,g13,g14,g15}, dt, pt, 1, 1, 1;\n"
        "add.s64 dt, w1d, 1536; wgmma.mma_async.sync.aligned.m64n64k16.f16.f16.f16 {qz0,qz1,qz2,qz3,qz4,qz5,qz6,qz7,qz8,qz9,qz10,qz11,qz12,qz13,qz14,qz15}, {qa0,qa1,qa2,qa3}, dt, pf, 1, 1, 1;\n"
        "add.s64 dt, w1d, 1664; wgmma.mma_async.sync.aligned.m64n64k16.f16.f16.f16 {qz0,qz1,qz2,qz3,qz4,qz5,qz6,qz7,qz8,qz9,qz10,qz11,qz12,qz13,qz14,qz15}, {qa4,qa5,qa6,qa7}, dt, pt, 1, 1, 1;\n"
        "add.s64 dt, w1d, 1792; wgmma.mma_async.sync.aligned.m64n64k16.f16.f16.f16 {qz0,qz1,qz2,qz3,qz4,qz5,qz6,qz7,qz8,qz9,qz10,qz11,qz12,qz13,qz14,qz15}, {qa8,qa9,qa10,qa11}, dt, pt, 1, 1, 1;\n"
        "wgmma.commit_group.sync.aligned;\n"
        "@pl bra.uni YLOAD;\n"
        "YLOADB:\n"
        "@pz bra.uni B22;\n"
        "mov.b32 {xl, xh}, a0; tanh.approx.f16 xr, xl; cvt.u32.u16 lo0, xr; tanh.approx.f16 xr, xh; cvt.u32.u16 hi0, xr; mul.rn.f16x2 a1, qz19, p1; fma.rn.f16x2 p0, qz20, qz20, c; fma.rn.f16x2 g0, qz16, h0, qz16; prmt.b32 h1, lo1, hi1, 0x5410;\n"
        "mov.b32 {xl, xh}, a1; tanh.approx.f16 xr, xl; cvt.u32.u16 lo1, xr; tanh.approx.f16 xr, xh; cvt.u32.u16 hi1, xr; mul.rn.f16x2 a0, qz20, p0; fma.rn.f16x2 p1, qz21, qz21, c; fma.rn.f16x2 g1, qz17, h1, qz17; prmt.b32 h0, lo0, hi0, 0x5410;\n"
        "mov.b32 {xl, xh}, a0; tanh.approx.f16 xr, xl; cvt.u32.u16 lo0, xr; tanh.approx.f16 xr, xh; cvt.u32.u16 hi0, xr; mul.rn.f16x2 a1, qz21, p1; fma.rn.f16x2 p0, qz22, qz22, c; fma.rn.f16x2 g2, qz18, h0, qz18; prmt.b32 h1, lo1, hi1, 0x5410;\n"
        "mov.b32 {xl, xh}, a1; tanh.approx.f16 xr, xl; cvt.u32.u16 lo1, xr; tanh.approx.f16 xr, xh; cvt.u32.u16 hi1, xr; mul.rn.f16x2 a0, qz22, p0; fma.rn.f16x2 p1, qz23, qz23, c; fma.rn.f16x2 g3, qz19, h1, qz19; prmt.b32 h0, lo0, hi0, 0x5410;\n"
        "B22:\n"
        "wgmma.fence.sync.aligned;\n"
        "add.s64 dt, w2d, 256; wgmma.mma_async.sync.aligned.m64n96k16.f16.f16.f16 {o0,o1,o2,o3,o4,o5,o6,o7,o8,o9,o10,o11,o12,o13,o14,o15,o16,o17,o18,o19,o20,o21,o22,o23}, {g0,g1,g2,g3}, dt, pt, 1, 1, 1;\n"
        "add.s64 dt, w1d, 1920; wgmma.mma_async.sync.aligned.m64n64k16.f16.f16.f16 {qz0,qz1,qz2,qz3,qz4,qz5,qz6,qz7,qz8,qz9,qz10,qz11,qz12,qz13,qz14,qz15}, {qa12,qa13,qa14,qa15}, dt, pt, 1, 1, 1;\n"
        "add.s64 dt, w1d, 2048; wgmma.mma_async.sync.aligned.m64n64k16.f16.f16.f16 {qz0,qz1,qz2,qz3,qz4,qz5,qz6,qz7,qz8,qz9,qz10,qz11,qz12,qz13,qz14,qz15}, {qa16,qa17,qa18,qa19}, dt, pt, 1, 1, 1;\n"
        "add.s64 dt, w1d, 2176; wgmma.mma_async.sync.aligned.m64n64k16.f16.f16.f16 {qz0,qz1,qz2,qz3,qz4,qz5,qz6,qz7,qz8,qz9,qz10,qz11,qz12,qz13,qz14,qz15}, {qa20,qa21,qa22,qa23}, dt, pt, 1, 1, 1;\n"
        "wgmma.commit_group.sync.aligned;\n"
        "@pz bra.uni B26;\n"
        "mov.b32 {xl, xh}, a0; tanh.approx.f16 xr, xl; cvt.u32.u16 lo0, xr; tanh.approx.f16 xr, xh; cvt.u32.u16 hi0, xr; mul.rn.f16x2 a1, qz23, p1; fma.rn.f16x2 p0, qz24, qz24, c; fma.rn.f16x2 g4, qz20, h0, qz20; prmt.b32 h1, lo1, hi1, 0x5410;\n"
        "mov.b32 {xl, xh}, a1; tanh.approx.f16 xr, xl; cvt.u32.u16 lo1, xr; tanh.approx.f16 xr, xh; cvt.u32.u16 hi1, xr; mul.rn.f16x2 a0, qz24, p0; fma.rn.f16x2 p1, qz25, qz25, c; fma.rn.f16x2 g5, qz21, h1, qz21; prmt.b32 h0, lo0, hi0, 0x5410;\n"
        "mov.b32 {xl, xh}, a0; tanh.approx.f16 xr, xl; cvt.u32.u16 lo0, xr; tanh.approx.f16 xr, xh; cvt.u32.u16 hi0, xr; mul.rn.f16x2 a1, qz25, p1; fma.rn.f16x2 p0, qz26, qz26, c; fma.rn.f16x2 g6, qz22, h0, qz22; prmt.b32 h1, lo1, hi1, 0x5410;\n"
        "mov.b32 {xl, xh}, a1; tanh.approx.f16 xr, xl; cvt.u32.u16 lo1, xr; tanh.approx.f16 xr, xh; cvt.u32.u16 hi1, xr; mul.rn.f16x2 a0, qz26, p0; fma.rn.f16x2 p1, qz27, qz27, c; fma.rn.f16x2 g7, qz23, h1, qz23; prmt.b32 h0, lo0, hi0, 0x5410;\n"
        "B26:\n"
        "wgmma.wait_group.sync.aligned 2;\n"
        "wgmma.fence.sync.aligned;\n"
        "add.s64 dt, w2d, 320; wgmma.mma_async.sync.aligned.m64n96k16.f16.f16.f16 {o0,o1,o2,o3,o4,o5,o6,o7,o8,o9,o10,o11,o12,o13,o14,o15,o16,o17,o18,o19,o20,o21,o22,o23}, {g4,g5,g6,g7}, dt, pt, 1, 1, 1;\n"
        "wgmma.commit_group.sync.aligned;\n"
        "@pz bra.uni B30;\n"
        "mov.b32 {xl, xh}, a0; tanh.approx.f16 xr, xl; cvt.u32.u16 lo0, xr; tanh.approx.f16 xr, xh; cvt.u32.u16 hi0, xr; mul.rn.f16x2 a1, qz27, p1; fma.rn.f16x2 p0, qz28, qz28, c; fma.rn.f16x2 g8, qz24, h0, qz24; prmt.b32 h1, lo1, hi1, 0x5410;\n"
        "mov.b32 {xl, xh}, a1; tanh.approx.f16 xr, xl; cvt.u32.u16 lo1, xr; tanh.approx.f16 xr, xh; cvt.u32.u16 hi1, xr; mul.rn.f16x2 a0, qz28, p0; fma.rn.f16x2 p1, qz29, qz29, c; fma.rn.f16x2 g9, qz25, h1, qz25; prmt.b32 h0, lo0, hi0, 0x5410;\n"
        "mov.b32 {xl, xh}, a0; tanh.approx.f16 xr, xl; cvt.u32.u16 lo0, xr; tanh.approx.f16 xr, xh; cvt.u32.u16 hi0, xr; mul.rn.f16x2 a1, qz29, p1; fma.rn.f16x2 p0, qz30, qz30, c; fma.rn.f16x2 g10, qz26, h0, qz26; prmt.b32 h1, lo1, hi1, 0x5410;\n"
        "mov.b32 {xl, xh}, a1; tanh.approx.f16 xr, xl; cvt.u32.u16 lo1, xr; tanh.approx.f16 xr, xh; cvt.u32.u16 hi1, xr; mul.rn.f16x2 a0, qz30, p0; fma.rn.f16x2 p1, qz31, qz31, c; fma.rn.f16x2 g11, qz27, h1, qz27; prmt.b32 h0, lo0, hi0, 0x5410;\n"
        "B30:\n"
        "wgmma.wait_group.sync.aligned 1;\n"
        "wgmma.fence.sync.aligned;\n"
        "add.s64 dt, w2d, 384; wgmma.mma_async.sync.aligned.m64n96k16.f16.f16.f16 {o0,o1,o2,o3,o4,o5,o6,o7,o8,o9,o10,o11,o12,o13,o14,o15,o16,o17,o18,o19,o20,o21,o22,o23}, {g8,g9,g10,g11}, dt, pt, 1, 1, 1;\n"
        "wgmma.commit_group.sync.aligned;\n"
        "@pz bra.uni B34;\n"
        "mov.b32 {xl, xh}, a0; tanh.approx.f16 xr, xl; cvt.u32.u16 lo0, xr; tanh.approx.f16 xr, xh; cvt.u32.u16 hi0, xr; mul.rn.f16x2 a1, qz31, p1; fma.rn.f16x2 p0, qz0, qz0, c; fma.rn.f16x2 g12, qz28, h0, qz28; prmt.b32 h1, lo1, hi1, 0x5410;\n"
        "mov.b32 {xl, xh}, a1; tanh.approx.f16 xr, xl; cvt.u32.u16 lo1, xr; tanh.approx.f16 xr, xh; cvt.u32.u16 hi1, xr; mul.rn.f16x2 a0, qz0, p0; fma.rn.f16x2 p1, qz1, qz1, c; fma.rn.f16x2 g13, qz29, h1, qz29; prmt.b32 h0, lo0, hi0, 0x5410;\n"
        "mov.b32 {xl, xh}, a0; tanh.approx.f16 xr, xl; cvt.u32.u16 lo0, xr; tanh.approx.f16 xr, xh; cvt.u32.u16 hi0, xr; mul.rn.f16x2 a1, qz1, p1; fma.rn.f16x2 p0, qz2, qz2, c; fma.rn.f16x2 g14, qz30, h0, qz30; prmt.b32 h1, lo1, hi1, 0x5410;\n"
        "mov.b32 {xl, xh}, a1; tanh.approx.f16 xr, xl; cvt.u32.u16 lo1, xr; tanh.approx.f16 xr, xh; cvt.u32.u16 hi1, xr; mul.rn.f16x2 a0, qz2, p0; fma.rn.f16x2 p1, qz3, qz3, c; fma.rn.f16x2 g15, qz31, h1, qz31; prmt.b32 h0, lo0, hi0, 0x5410;\n"
        "B34:\n"
        "wgmma.fence.sync.aligned;\n"
        "add.s64 dt, w2d, 448; wgmma.mma_async.sync.aligned.m64n96k16.f16.f16.f16 {o0,o1,o2,o3,o4,o5,o6,o7,o8,o9,o10,o11,o12,o13,o14,o15,o16,o17,o18,o19,o20,o21,o22,o23}, {g12,g13,g14,g15}, dt, pt, 1, 1, 1;\n"
        "add.s64 dt, w1d, 2304; wgmma.mma_async.sync.aligned.m64n64k16.f16.f16.f16 {qz16,qz17,qz18,qz19,qz20,qz21,qz22,qz23,qz24,qz25,qz26,qz27,qz28,qz29,qz30,qz31}, {qa0,qa1,qa2,qa3}, dt, pf, 1, 1, 1;\n"
        "add.s64 dt, w1d, 2432; wgmma.mma_async.sync.aligned.m64n64k16.f16.f16.f16 {qz16,qz17,qz18,qz19,qz20,qz21,qz22,qz23,qz24,qz25,qz26,qz27,qz28,qz29,qz30,qz31}, {qa4,qa5,qa6,qa7}, dt, pt, 1, 1, 1;\n"
        "add.s64 dt, w1d, 2560; wgmma.mma_async.sync.aligned.m64n64k16.f16.f16.f16 {qz16,qz17,qz18,qz19,qz20,qz21,qz22,qz23,qz24,qz25,qz26,qz27,qz28,qz29,qz30,qz31}, {qa8,qa9,qa10,qa11}, dt, pt, 1, 1, 1;\n"
        "wgmma.commit_group.sync.aligned;\n"
        "@pz bra.uni B38;\n"
        "mov.b32 {xl, xh}, a0; tanh.approx.f16 xr, xl; cvt.u32.u16 lo0, xr; tanh.approx.f16 xr, xh; cvt.u32.u16 hi0, xr; mul.rn.f16x2 a1, qz3, p1; fma.rn.f16x2 p0, qz4, qz4, c; fma.rn.f16x2 g0, qz0, h0, qz0; prmt.b32 h1, lo1, hi1, 0x5410;\n"
        "mov.b32 {xl, xh}, a1; tanh.approx.f16 xr, xl; cvt.u32.u16 lo1, xr; tanh.approx.f16 xr, xh; cvt.u32.u16 hi1, xr; mul.rn.f16x2 a0, qz4, p0; fma.rn.f16x2 p1, qz5, qz5, c; fma.rn.f16x2 g1, qz1, h1, qz1; prmt.b32 h0, lo0, hi0, 0x5410;\n"
        "mov.b32 {xl, xh}, a0; tanh.approx.f16 xr, xl; cvt.u32.u16 lo0, xr; tanh.approx.f16 xr, xh; cvt.u32.u16 hi0, xr; mul.rn.f16x2 a1, qz5, p1; fma.rn.f16x2 p0, qz6, qz6, c; fma.rn.f16x2 g2, qz2, h0, qz2; prmt.b32 h1, lo1, hi1, 0x5410;\n"
        "mov.b32 {xl, xh}, a1; tanh.approx.f16 xr, xl; cvt.u32.u16 lo1, xr; tanh.approx.f16 xr, xh; cvt.u32.u16 hi1, xr; mul.rn.f16x2 a0, qz6, p0; fma.rn.f16x2 p1, qz7, qz7, c; fma.rn.f16x2 g3, qz3, h1, qz3; prmt.b32 h0, lo0, hi0, 0x5410;\n"
        "B38:\n"
        "wgmma.wait_group.sync.aligned 2;\n"
        "setp.eq.s32 pr, n, 0;\n"
        "@pr bra.uni SPINW1;\n"
        "BACKW1:\n"
        "wgmma.fence.sync.aligned;\n"
        "add.s64 dt, w2d, 512; wgmma.mma_async.sync.aligned.m64n96k16.f16.f16.f16 {o0,o1,o2,o3,o4,o5,o6,o7,o8,o9,o10,o11,o12,o13,o14,o15,o16,o17,o18,o19,o20,o21,o22,o23}, {g0,g1,g2,g3}, dt, pt, 1, 1, 1;\n"
        "add.s64 dt, w1d, 2688; wgmma.mma_async.sync.aligned.m64n64k16.f16.f16.f16 {qz16,qz17,qz18,qz19,qz20,qz21,qz22,qz23,qz24,qz25,qz26,qz27,qz28,qz29,qz30,qz31}, {qa12,qa13,qa14,qa15}, dt, pt, 1, 1, 1;\n"
        "add.s64 dt, w1d, 2816; wgmma.mma_async.sync.aligned.m64n64k16.f16.f16.f16 {qz16,qz17,qz18,qz19,qz20,qz21,qz22,qz23,qz24,qz25,qz26,qz27,qz28,qz29,qz30,qz31}, {qa16,qa17,qa18,qa19}, dt, pt, 1, 1, 1;\n"
        "add.s64 dt, w1d, 2944; wgmma.mma_async.sync.aligned.m64n64k16.f16.f16.f16 {qz16,qz17,qz18,qz19,qz20,qz21,qz22,qz23,qz24,qz25,qz26,qz27,qz28,qz29,qz30,qz31}, {qa20,qa21,qa22,qa23}, dt, pt, 1, 1, 1;\n"
        "wgmma.commit_group.sync.aligned;\n"
        "@pz bra.uni B42;\n"
        "mov.b32 {xl, xh}, a0; tanh.approx.f16 xr, xl; cvt.u32.u16 lo0, xr; tanh.approx.f16 xr, xh; cvt.u32.u16 hi0, xr; mul.rn.f16x2 a1, qz7, p1; fma.rn.f16x2 p0, qz8, qz8, c; fma.rn.f16x2 g4, qz4, h0, qz4; prmt.b32 h1, lo1, hi1, 0x5410;\n"
        "mov.b32 {xl, xh}, a1; tanh.approx.f16 xr, xl; cvt.u32.u16 lo1, xr; tanh.approx.f16 xr, xh; cvt.u32.u16 hi1, xr; mul.rn.f16x2 a0, qz8, p0; fma.rn.f16x2 p1, qz9, qz9, c; fma.rn.f16x2 g5, qz5, h1, qz5; prmt.b32 h0, lo0, hi0, 0x5410;\n"
        "mov.b32 {xl, xh}, a0; tanh.approx.f16 xr, xl; cvt.u32.u16 lo0, xr; tanh.approx.f16 xr, xh; cvt.u32.u16 hi0, xr; mul.rn.f16x2 a1, qz9, p1; fma.rn.f16x2 p0, qz10, qz10, c; fma.rn.f16x2 g6, qz6, h0, qz6; prmt.b32 h1, lo1, hi1, 0x5410;\n"
        "mov.b32 {xl, xh}, a1; tanh.approx.f16 xr, xl; cvt.u32.u16 lo1, xr; tanh.approx.f16 xr, xh; cvt.u32.u16 hi1, xr; mul.rn.f16x2 a0, qz10, p0; fma.rn.f16x2 p1, qz11, qz11, c; fma.rn.f16x2 g7, qz7, h1, qz7; prmt.b32 h0, lo0, hi0, 0x5410;\n"
        "B42:\n"
        "wgmma.wait_group.sync.aligned 2;\n"
        "wgmma.fence.sync.aligned;\n"
        "add.s64 dt, w2d, 576; wgmma.mma_async.sync.aligned.m64n96k16.f16.f16.f16 {o0,o1,o2,o3,o4,o5,o6,o7,o8,o9,o10,o11,o12,o13,o14,o15,o16,o17,o18,o19,o20,o21,o22,o23}, {g4,g5,g6,g7}, dt, pt, 1, 1, 1;\n"
        "wgmma.commit_group.sync.aligned;\n"
        "@pz bra.uni B46;\n"
        "mov.b32 {xl, xh}, a0; tanh.approx.f16 xr, xl; cvt.u32.u16 lo0, xr; tanh.approx.f16 xr, xh; cvt.u32.u16 hi0, xr; mul.rn.f16x2 a1, qz11, p1; fma.rn.f16x2 p0, qz12, qz12, c; fma.rn.f16x2 g8, qz8, h0, qz8; prmt.b32 h1, lo1, hi1, 0x5410;\n"
        "mov.b32 {xl, xh}, a1; tanh.approx.f16 xr, xl; cvt.u32.u16 lo1, xr; tanh.approx.f16 xr, xh; cvt.u32.u16 hi1, xr; mul.rn.f16x2 a0, qz12, p0; fma.rn.f16x2 p1, qz13, qz13, c; fma.rn.f16x2 g9, qz9, h1, qz9; prmt.b32 h0, lo0, hi0, 0x5410;\n"
        "mov.b32 {xl, xh}, a0; tanh.approx.f16 xr, xl; cvt.u32.u16 lo0, xr; tanh.approx.f16 xr, xh; cvt.u32.u16 hi0, xr; mul.rn.f16x2 a1, qz13, p1; fma.rn.f16x2 p0, qz14, qz14, c; fma.rn.f16x2 g10, qz10, h0, qz10; prmt.b32 h1, lo1, hi1, 0x5410;\n"
        "mov.b32 {xl, xh}, a1; tanh.approx.f16 xr, xl; cvt.u32.u16 lo1, xr; tanh.approx.f16 xr, xh; cvt.u32.u16 hi1, xr; mul.rn.f16x2 a0, qz14, p0; fma.rn.f16x2 p1, qz15, qz15, c; fma.rn.f16x2 g11, qz11, h1, qz11; prmt.b32 h0, lo0, hi0, 0x5410;\n"
        "B46:\n"
        "wgmma.wait_group.sync.aligned 1;\n"
        "wgmma.fence.sync.aligned;\n"
        "add.s64 dt, w2d, 640; wgmma.mma_async.sync.aligned.m64n96k16.f16.f16.f16 {o0,o1,o2,o3,o4,o5,o6,o7,o8,o9,o10,o11,o12,o13,o14,o15,o16,o17,o18,o19,o20,o21,o22,o23}, {g8,g9,g10,g11}, dt, pt, 1, 1, 1;\n"
        "wgmma.commit_group.sync.aligned;\n"
        "mad.lo.u32 tt, n, 8, tbar;\n"
        "@pn mbarrier.arrive.shared::cta.b64 _, [tt+64];\n"
        "@pz bra.uni B50;\n"
        "mov.b32 {xl, xh}, a0; tanh.approx.f16 xr, xl; cvt.u32.u16 lo0, xr; tanh.approx.f16 xr, xh; cvt.u32.u16 hi0, xr; mul.rn.f16x2 a1, qz15, p1; fma.rn.f16x2 p0, qz16, qz16, c; fma.rn.f16x2 g12, qz12, h0, qz12; prmt.b32 h1, lo1, hi1, 0x5410;\n"
        "mov.b32 {xl, xh}, a1; tanh.approx.f16 xr, xl; cvt.u32.u16 lo1, xr; tanh.approx.f16 xr, xh; cvt.u32.u16 hi1, xr; mul.rn.f16x2 a0, qz16, p0; fma.rn.f16x2 p1, qz17, qz17, c; fma.rn.f16x2 g13, qz13, h1, qz13; prmt.b32 h0, lo0, hi0, 0x5410;\n"
        "mov.b32 {xl, xh}, a0; tanh.approx.f16 xr, xl; cvt.u32.u16 lo0, xr; tanh.approx.f16 xr, xh; cvt.u32.u16 hi0, xr; mul.rn.f16x2 a1, qz17, p1; fma.rn.f16x2 p0, qz18, qz18, c; fma.rn.f16x2 g14, qz14, h0, qz14; prmt.b32 h1, lo1, hi1, 0x5410;\n"
        "mov.b32 {xl, xh}, a1; tanh.approx.f16 xr, xl; cvt.u32.u16 lo1, xr; tanh.approx.f16 xr, xh; cvt.u32.u16 hi1, xr; mul.rn.f16x2 a0, qz18, p0; fma.rn.f16x2 p1, qz19, qz19, c; fma.rn.f16x2 g15, qz15, h1, qz15; prmt.b32 h0, lo0, hi0, 0x5410;\n"
        "B50:\n"
        "wgmma.fence.sync.aligned;\n"
        "add.s64 dt, w2d, 704; wgmma.mma_async.sync.aligned.m64n96k16.f16.f16.f16 {o0,o1,o2,o3,o4,o5,o6,o7,o8,o9,o10,o11,o12,o13,o14,o15,o16,o17,o18,o19,o20,o21,o22,o23}, {g12,g13,g14,g15}, dt, pt, 1, 1, 1;\n"
        "add.s64 dt, w1d, 3072; wgmma.mma_async.sync.aligned.m64n64k16.f16.f16.f16 {qz0,qz1,qz2,qz3,qz4,qz5,qz6,qz7,qz8,qz9,qz10,qz11,qz12,qz13,qz14,qz15}, {qa0,qa1,qa2,qa3}, dt, pf, 1, 1, 1;\n"
        "add.s64 dt, w1d, 3200; wgmma.mma_async.sync.aligned.m64n64k16.f16.f16.f16 {qz0,qz1,qz2,qz3,qz4,qz5,qz6,qz7,qz8,qz9,qz10,qz11,qz12,qz13,qz14,qz15}, {qa4,qa5,qa6,qa7}, dt, pt, 1, 1, 1;\n"
        "add.s64 dt, w1d, 3328; wgmma.mma_async.sync.aligned.m64n64k16.f16.f16.f16 {qz0,qz1,qz2,qz3,qz4,qz5,qz6,qz7,qz8,qz9,qz10,qz11,qz12,qz13,qz14,qz15}, {qa8,qa9,qa10,qa11}, dt, pt, 1, 1, 1;\n"
        "wgmma.commit_group.sync.aligned;\n"
        "@pz bra.uni B54;\n"
        "mov.b32 {xl, xh}, a0; tanh.approx.f16 xr, xl; cvt.u32.u16 lo0, xr; tanh.approx.f16 xr, xh; cvt.u32.u16 hi0, xr; mul.rn.f16x2 a1, qz19, p1; fma.rn.f16x2 p0, qz20, qz20, c; fma.rn.f16x2 g0, qz16, h0, qz16; prmt.b32 h1, lo1, hi1, 0x5410;\n"
        "mov.b32 {xl, xh}, a1; tanh.approx.f16 xr, xl; cvt.u32.u16 lo1, xr; tanh.approx.f16 xr, xh; cvt.u32.u16 hi1, xr; mul.rn.f16x2 a0, qz20, p0; fma.rn.f16x2 p1, qz21, qz21, c; fma.rn.f16x2 g1, qz17, h1, qz17; prmt.b32 h0, lo0, hi0, 0x5410;\n"
        "mov.b32 {xl, xh}, a0; tanh.approx.f16 xr, xl; cvt.u32.u16 lo0, xr; tanh.approx.f16 xr, xh; cvt.u32.u16 hi0, xr; mul.rn.f16x2 a1, qz21, p1; fma.rn.f16x2 p0, qz22, qz22, c; fma.rn.f16x2 g2, qz18, h0, qz18; prmt.b32 h1, lo1, hi1, 0x5410;\n"
        "mov.b32 {xl, xh}, a1; tanh.approx.f16 xr, xl; cvt.u32.u16 lo1, xr; tanh.approx.f16 xr, xh; cvt.u32.u16 hi1, xr; mul.rn.f16x2 a0, qz22, p0; fma.rn.f16x2 p1, qz23, qz23, c; fma.rn.f16x2 g3, qz19, h1, qz19; prmt.b32 h0, lo0, hi0, 0x5410;\n"
        "B54:\n"
        "wgmma.wait_group.sync.aligned 2;\n"
        "wgmma.fence.sync.aligned;\n"
        "add.s64 dt, w2d, 768; wgmma.mma_async.sync.aligned.m64n96k16.f16.f16.f16 {o0,o1,o2,o3,o4,o5,o6,o7,o8,o9,o10,o11,o12,o13,o14,o15,o16,o17,o18,o19,o20,o21,o22,o23}, {g0,g1,g2,g3}, dt, pt, 1, 1, 1;\n"
        "add.s64 dt, w1d, 3456; wgmma.mma_async.sync.aligned.m64n64k16.f16.f16.f16 {qz0,qz1,qz2,qz3,qz4,qz5,qz6,qz7,qz8,qz9,qz10,qz11,qz12,qz13,qz14,qz15}, {qa12,qa13,qa14,qa15}, dt, pt, 1, 1, 1;\n"
        "add.s64 dt, w1d, 3584; wgmma.mma_async.sync.aligned.m64n64k16.f16.f16.f16 {qz0,qz1,qz2,qz3,qz4,qz5,qz6,qz7,qz8,qz9,qz10,qz11,qz12,qz13,qz14,qz15}, {qa16,qa17,qa18,qa19}, dt, pt, 1, 1, 1;\n"
        "add.s64 dt, w1d, 3712; wgmma.mma_async.sync.aligned.m64n64k16.f16.f16.f16 {qz0,qz1,qz2,qz3,qz4,qz5,qz6,qz7,qz8,qz9,qz10,qz11,qz12,qz13,qz14,qz15}, {qa20,qa21,qa22,qa23}, dt, pt, 1, 1, 1;\n"
        "wgmma.commit_group.sync.aligned;\n"
        "@pz bra.uni B58;\n"
        "mov.b32 {xl, xh}, a0; tanh.approx.f16 xr, xl; cvt.u32.u16 lo0, xr; tanh.approx.f16 xr, xh; cvt.u32.u16 hi0, xr; mul.rn.f16x2 a1, qz23, p1; fma.rn.f16x2 p0, qz24, qz24, c; fma.rn.f16x2 g4, qz20, h0, qz20; prmt.b32 h1, lo1, hi1, 0x5410;\n"
        "mov.b32 {xl, xh}, a1; tanh.approx.f16 xr, xl; cvt.u32.u16 lo1, xr; tanh.approx.f16 xr, xh; cvt.u32.u16 hi1, xr; mul.rn.f16x2 a0, qz24, p0; fma.rn.f16x2 p1, qz25, qz25, c; fma.rn.f16x2 g5, qz21, h1, qz21; prmt.b32 h0, lo0, hi0, 0x5410;\n"
        "mov.b32 {xl, xh}, a0; tanh.approx.f16 xr, xl; cvt.u32.u16 lo0, xr; tanh.approx.f16 xr, xh; cvt.u32.u16 hi0, xr; mul.rn.f16x2 a1, qz25, p1; fma.rn.f16x2 p0, qz26, qz26, c; fma.rn.f16x2 g6, qz22, h0, qz22; prmt.b32 h1, lo1, hi1, 0x5410;\n"
        "mov.b32 {xl, xh}, a1; tanh.approx.f16 xr, xl; cvt.u32.u16 lo1, xr; tanh.approx.f16 xr, xh; cvt.u32.u16 hi1, xr; mul.rn.f16x2 a0, qz26, p0; fma.rn.f16x2 p1, qz27, qz27, c; fma.rn.f16x2 g7, qz23, h1, qz23; prmt.b32 h0, lo0, hi0, 0x5410;\n"
        "B58:\n"
        "wgmma.wait_group.sync.aligned 2;\n"
        "wgmma.fence.sync.aligned;\n"
        "add.s64 dt, w2d, 832; wgmma.mma_async.sync.aligned.m64n96k16.f16.f16.f16 {o0,o1,o2,o3,o4,o5,o6,o7,o8,o9,o10,o11,o12,o13,o14,o15,o16,o17,o18,o19,o20,o21,o22,o23}, {g4,g5,g6,g7}, dt, pt, 1, 1, 1;\n"
        "wgmma.commit_group.sync.aligned;\n"
        "@pz bra.uni B62;\n"
        "mov.b32 {xl, xh}, a0; tanh.approx.f16 xr, xl; cvt.u32.u16 lo0, xr; tanh.approx.f16 xr, xh; cvt.u32.u16 hi0, xr; mul.rn.f16x2 a1, qz27, p1; fma.rn.f16x2 p0, qz28, qz28, c; fma.rn.f16x2 g8, qz24, h0, qz24; prmt.b32 h1, lo1, hi1, 0x5410;\n"
        "mov.b32 {xl, xh}, a1; tanh.approx.f16 xr, xl; cvt.u32.u16 lo1, xr; tanh.approx.f16 xr, xh; cvt.u32.u16 hi1, xr; mul.rn.f16x2 a0, qz28, p0; fma.rn.f16x2 p1, qz29, qz29, c; fma.rn.f16x2 g9, qz25, h1, qz25; prmt.b32 h0, lo0, hi0, 0x5410;\n"
        "mov.b32 {xl, xh}, a0; tanh.approx.f16 xr, xl; cvt.u32.u16 lo0, xr; tanh.approx.f16 xr, xh; cvt.u32.u16 hi0, xr; mul.rn.f16x2 a1, qz29, p1; fma.rn.f16x2 p0, qz30, qz30, c; fma.rn.f16x2 g10, qz26, h0, qz26; prmt.b32 h1, lo1, hi1, 0x5410;\n"
        "mov.b32 {xl, xh}, a1; tanh.approx.f16 xr, xl; cvt.u32.u16 lo1, xr; tanh.approx.f16 xr, xh; cvt.u32.u16 hi1, xr; mul.rn.f16x2 a0, qz30, p0; fma.rn.f16x2 p1, qz31, qz31, c; fma.rn.f16x2 g11, qz27, h1, qz27; prmt.b32 h0, lo0, hi0, 0x5410;\n"
        "B62:\n"
        "wgmma.wait_group.sync.aligned 1;\n"
        "wgmma.fence.sync.aligned;\n"
        "add.s64 dt, w2d, 896; wgmma.mma_async.sync.aligned.m64n96k16.f16.f16.f16 {o0,o1,o2,o3,o4,o5,o6,o7,o8,o9,o10,o11,o12,o13,o14,o15,o16,o17,o18,o19,o20,o21,o22,o23}, {g8,g9,g10,g11}, dt, pt, 1, 1, 1;\n"
        "wgmma.commit_group.sync.aligned;\n"
        "@pz bra.uni B66;\n"
        "mov.b32 {xl, xh}, a0; tanh.approx.f16 xr, xl; cvt.u32.u16 lo0, xr; tanh.approx.f16 xr, xh; cvt.u32.u16 hi0, xr; mul.rn.f16x2 a1, qz31, p1; fma.rn.f16x2 p0, qz0, qz0, c; fma.rn.f16x2 g12, qz28, h0, qz28; prmt.b32 h1, lo1, hi1, 0x5410;\n"
        "mov.b32 {xl, xh}, a1; tanh.approx.f16 xr, xl; cvt.u32.u16 lo1, xr; tanh.approx.f16 xr, xh; cvt.u32.u16 hi1, xr; mul.rn.f16x2 a0, qz0, p0; fma.rn.f16x2 p1, qz1, qz1, c; fma.rn.f16x2 g13, qz29, h1, qz29; prmt.b32 h0, lo0, hi0, 0x5410;\n"
        "mov.b32 {xl, xh}, a0; tanh.approx.f16 xr, xl; cvt.u32.u16 lo0, xr; tanh.approx.f16 xr, xh; cvt.u32.u16 hi0, xr; mul.rn.f16x2 a1, qz1, p1; fma.rn.f16x2 p0, qz2, qz2, c; fma.rn.f16x2 g14, qz30, h0, qz30; prmt.b32 h1, lo1, hi1, 0x5410;\n"
        "mov.b32 {xl, xh}, a1; tanh.approx.f16 xr, xl; cvt.u32.u16 lo1, xr; tanh.approx.f16 xr, xh; cvt.u32.u16 hi1, xr; mul.rn.f16x2 a0, qz2, p0; fma.rn.f16x2 p1, qz3, qz3, c; fma.rn.f16x2 g15, qz31, h1, qz31; prmt.b32 h0, lo0, hi0, 0x5410;\n"
        "B66:\n"
        "wgmma.fence.sync.aligned;\n"
        "add.s64 dt, w2d, 960; wgmma.mma_async.sync.aligned.m64n96k16.f16.f16.f16 {o0,o1,o2,o3,o4,o5,o6,o7,o8,o9,o10,o11,o12,o13,o14,o15,o16,o17,o18,o19,o20,o21,o22,o23}, {g12,g13,g14,g15}, dt, pt, 1, 1, 1;\n"
        "add.s64 dt, w1d, 3840; wgmma.mma_async.sync.aligned.m64n64k16.f16.f16.f16 {qz16,qz17,qz18,qz19,qz20,qz21,qz22,qz23,qz24,qz25,qz26,qz27,qz28,qz29,qz30,qz31}, {qa0,qa1,qa2,qa3}, dt, pf, 1, 1, 1;\n"
        "add.s64 dt, w1d, 3968; wgmma.mma_async.sync.aligned.m64n64k16.f16.f16.f16 {qz16,qz17,qz18,qz19,qz20,qz21,qz22,qz23,qz24,qz25,qz26,qz27,qz28,qz29,qz30,qz31}, {qa4,qa5,qa6,qa7}, dt, pt, 1, 1, 1;\n"
        "add.s64 dt, w1d, 4096; wgmma.mma_async.sync.aligned.m64n64k16.f16.f16.f16 {qz16,qz17,qz18,qz19,qz20,qz21,qz22,qz23,qz24,qz25,qz26,qz27,qz28,qz29,qz30,qz31}, {qa8,qa9,qa10,qa11}, dt, pt, 1, 1, 1;\n"
        "wgmma.commit_group.sync.aligned;\n"
        "@pz bra.uni B70;\n"
        "mov.b32 {xl, xh}, a0; tanh.approx.f16 xr, xl; cvt.u32.u16 lo0, xr; tanh.approx.f16 xr, xh; cvt.u32.u16 hi0, xr; mul.rn.f16x2 a1, qz3, p1; fma.rn.f16x2 p0, qz4, qz4, c; fma.rn.f16x2 g0, qz0, h0, qz0; prmt.b32 h1, lo1, hi1, 0x5410;\n"
        "mov.b32 {xl, xh}, a1; tanh.approx.f16 xr, xl; cvt.u32.u16 lo1, xr; tanh.approx.f16 xr, xh; cvt.u32.u16 hi1, xr; mul.rn.f16x2 a0, qz4, p0; fma.rn.f16x2 p1, qz5, qz5, c; fma.rn.f16x2 g1, qz1, h1, qz1; prmt.b32 h0, lo0, hi0, 0x5410;\n"
        "mov.b32 {xl, xh}, a0; tanh.approx.f16 xr, xl; cvt.u32.u16 lo0, xr; tanh.approx.f16 xr, xh; cvt.u32.u16 hi0, xr; mul.rn.f16x2 a1, qz5, p1; fma.rn.f16x2 p0, qz6, qz6, c; fma.rn.f16x2 g2, qz2, h0, qz2; prmt.b32 h1, lo1, hi1, 0x5410;\n"
        "mov.b32 {xl, xh}, a1; tanh.approx.f16 xr, xl; cvt.u32.u16 lo1, xr; tanh.approx.f16 xr, xh; cvt.u32.u16 hi1, xr; mul.rn.f16x2 a0, qz6, p0; fma.rn.f16x2 p1, qz7, qz7, c; fma.rn.f16x2 g3, qz3, h1, qz3; prmt.b32 h0, lo0, hi0, 0x5410;\n"
        "B70:\n"
        "wgmma.wait_group.sync.aligned 2;\n"
        "wgmma.fence.sync.aligned;\n"
        "add.s64 dt, w2d, 1024; wgmma.mma_async.sync.aligned.m64n96k16.f16.f16.f16 {o0,o1,o2,o3,o4,o5,o6,o7,o8,o9,o10,o11,o12,o13,o14,o15,o16,o17,o18,o19,o20,o21,o22,o23}, {g0,g1,g2,g3}, dt, pt, 1, 1, 1;\n"
        "add.s64 dt, w1d, 4224; wgmma.mma_async.sync.aligned.m64n64k16.f16.f16.f16 {qz16,qz17,qz18,qz19,qz20,qz21,qz22,qz23,qz24,qz25,qz26,qz27,qz28,qz29,qz30,qz31}, {qa12,qa13,qa14,qa15}, dt, pt, 1, 1, 1;\n"
        "add.s64 dt, w1d, 4352; wgmma.mma_async.sync.aligned.m64n64k16.f16.f16.f16 {qz16,qz17,qz18,qz19,qz20,qz21,qz22,qz23,qz24,qz25,qz26,qz27,qz28,qz29,qz30,qz31}, {qa16,qa17,qa18,qa19}, dt, pt, 1, 1, 1;\n"
        "add.s64 dt, w1d, 4480; wgmma.mma_async.sync.aligned.m64n64k16.f16.f16.f16 {qz16,qz17,qz18,qz19,qz20,qz21,qz22,qz23,qz24,qz25,qz26,qz27,qz28,qz29,qz30,qz31}, {qa20,qa21,qa22,qa23}, dt, pt, 1, 1, 1;\n"
        "wgmma.commit_group.sync.aligned;\n"
        "@pz bra.uni B74;\n"
        "mov.b32 {xl, xh}, a0; tanh.approx.f16 xr, xl; cvt.u32.u16 lo0, xr; tanh.approx.f16 xr, xh; cvt.u32.u16 hi0, xr; mul.rn.f16x2 a1, qz7, p1; fma.rn.f16x2 p0, qz8, qz8, c; fma.rn.f16x2 g4, qz4, h0, qz4; prmt.b32 h1, lo1, hi1, 0x5410;\n"
        "mov.b32 {xl, xh}, a1; tanh.approx.f16 xr, xl; cvt.u32.u16 lo1, xr; tanh.approx.f16 xr, xh; cvt.u32.u16 hi1, xr; mul.rn.f16x2 a0, qz8, p0; fma.rn.f16x2 p1, qz9, qz9, c; fma.rn.f16x2 g5, qz5, h1, qz5; prmt.b32 h0, lo0, hi0, 0x5410;\n"
        "mov.b32 {xl, xh}, a0; tanh.approx.f16 xr, xl; cvt.u32.u16 lo0, xr; tanh.approx.f16 xr, xh; cvt.u32.u16 hi0, xr; mul.rn.f16x2 a1, qz9, p1; fma.rn.f16x2 p0, qz10, qz10, c; fma.rn.f16x2 g6, qz6, h0, qz6; prmt.b32 h1, lo1, hi1, 0x5410;\n"
        "mov.b32 {xl, xh}, a1; tanh.approx.f16 xr, xl; cvt.u32.u16 lo1, xr; tanh.approx.f16 xr, xh; cvt.u32.u16 hi1, xr; mul.rn.f16x2 a0, qz10, p0; fma.rn.f16x2 p1, qz11, qz11, c; fma.rn.f16x2 g7, qz7, h1, qz7; prmt.b32 h0, lo0, hi0, 0x5410;\n"
        "B74:\n"
        "wgmma.wait_group.sync.aligned 2;\n"
        "wgmma.fence.sync.aligned;\n"
        "add.s64 dt, w2d, 1088; wgmma.mma_async.sync.aligned.m64n96k16.f16.f16.f16 {o0,o1,o2,o3,o4,o5,o6,o7,o8,o9,o10,o11,o12,o13,o14,o15,o16,o17,o18,o19,o20,o21,o22,o23}, {g4,g5,g6,g7}, dt, pt, 1, 1, 1;\n"
        "wgmma.commit_group.sync.aligned;\n"
        "@pz bra.uni B78;\n"
        "mov.b32 {xl, xh}, a0; tanh.approx.f16 xr, xl; cvt.u32.u16 lo0, xr; tanh.approx.f16 xr, xh; cvt.u32.u16 hi0, xr; mul.rn.f16x2 a1, qz11, p1; fma.rn.f16x2 p0, qz12, qz12, c; fma.rn.f16x2 g8, qz8, h0, qz8; prmt.b32 h1, lo1, hi1, 0x5410;\n"
        "mov.b32 {xl, xh}, a1; tanh.approx.f16 xr, xl; cvt.u32.u16 lo1, xr; tanh.approx.f16 xr, xh; cvt.u32.u16 hi1, xr; mul.rn.f16x2 a0, qz12, p0; fma.rn.f16x2 p1, qz13, qz13, c; fma.rn.f16x2 g9, qz9, h1, qz9; prmt.b32 h0, lo0, hi0, 0x5410;\n"
        "mov.b32 {xl, xh}, a0; tanh.approx.f16 xr, xl; cvt.u32.u16 lo0, xr; tanh.approx.f16 xr, xh; cvt.u32.u16 hi0, xr; mul.rn.f16x2 a1, qz13, p1; fma.rn.f16x2 p0, qz14, qz14, c; fma.rn.f16x2 g10, qz10, h0, qz10; prmt.b32 h1, lo1, hi1, 0x5410;\n"
        "mov.b32 {xl, xh}, a1; tanh.approx.f16 xr, xl; cvt.u32.u16 lo1, xr; tanh.approx.f16 xr, xh; cvt.u32.u16 hi1, xr; mul.rn.f16x2 a0, qz14, p0; fma.rn.f16x2 p1, qz15, qz15, c; fma.rn.f16x2 g11, qz11, h1, qz11; prmt.b32 h0, lo0, hi0, 0x5410;\n"
        "B78:\n"
        "wgmma.wait_group.sync.aligned 1;\n"
        "wgmma.fence.sync.aligned;\n"
        "add.s64 dt, w2d, 1152; wgmma.mma_async.sync.aligned.m64n96k16.f16.f16.f16 {o0,o1,o2,o3,o4,o5,o6,o7,o8,o9,o10,o11,o12,o13,o14,o15,o16,o17,o18,o19,o20,o21,o22,o23}, {g8,g9,g10,g11}, dt, pt, 1, 1, 1;\n"
        "wgmma.commit_group.sync.aligned;\n"
        "@!pm bra.uni BACKY;\n"
        "add.u32 tt, n, 1; and.b32 tt, tt, 1; mbarrier.try_wait.parity.shared::cta.b64 pw, [ybar], tt;\n"
        "@!pw bra.uni SPINY;\n"
        "BACKY:\n"
        "@pz bra.uni B80;\n"
        "and.b32 ad, %5, 0xffff; xor.b32 ad, ad, 0; add.u32 ad, ad, %4; ldmatrix.sync.aligned.m8n8.x4.shared.b16 {qa0,qa1,qa2,qa3}, [ad];\n"
        "and.b32 ad, %5, 0xffff; xor.b32 ad, ad, 32; add.u32 ad, ad, %4; ldmatrix.sync.aligned.m8n8.x4.shared.b16 {qa4,qa5,qa6,qa7}, [ad];\n"
        "and.b32 ad, %5, 0xffff; xor.b32 ad, ad, 64; add.u32 ad, ad, %4; ldmatrix.sync.aligned.m8n8.x4.shared.b16 {qa8,qa9,qa10,qa11}, [ad];\n"
        "and.b32 ad, %5, 0xffff; xor.b32 ad, ad, 96; add.u32 ad, ad, %4; ldmatrix.sync.aligned.m8n8.x4.shared.b16 {qa12,qa13,qa14,qa15}, [ad];\n"
        "shr.u32 ad, %5, 16; xor.b32 ad, ad, 0; add.u32 ad, ad, %4; ldmatrix.sync.aligned.m8n8.x4.shared.b16 {qa16,qa17,qa18,qa19}, [ad];\n"
        "shr.u32 ad, %5, 16; xor.b32 ad, ad, 32; add.u32 ad, ad, %4; ldmatrix.sync.aligned.m8n8.x4.shared.b16 {qa20,qa21,qa22,qa23}, [ad];\n"
        "mov.b32 {xl, xh}, a0; tanh.approx.f16 xr, xl; cvt.u32.u16 lo0, xr; tanh.approx.f16 xr, xh; cvt.u32.u16 hi0, xr; mul.rn.f16x2 a1, qz15, p1; fma.rn.f16x2 p0, qz16, qz16, c; fma.rn.f16x2 g12, qz12, h0, qz12; prmt.b32 h1, lo1, hi1, 0x5410;\n"
        "mov.b32 {xl, xh}, a1; tanh.approx.f16 xr, xl; cvt.u32.u16 lo1, xr; tanh.approx.f16 xr, xh; cvt.u32.u16 hi1, xr; mul.rn.f16x2 a0, qz16, p0; fma.rn.f16x2 p1, qz17, qz17, c; fma.rn.f16x2 g13, qz13, h1, qz13; prmt.b32 h0, lo0, hi0, 0x5410;\n"
        "B80:\n"
        "fence.proxy.async.shared::cta;\n"
        "add.u32 tt, id, 0;\n"
        "@pk bra.uni XLOAD;\n"
        "bar.arrive tt, 128;\n"
        "XLOADB:\n"
        "@pz bra.uni B82;\n"
        "mov.b32 {xl, xh}, a0; tanh.approx.f16 xr, xl; cvt.u32.u16 lo0, xr; tanh.approx.f16 xr, xh; cvt.u32.u16 hi0, xr; mul.rn.f16x2 a1, qz17, p1; fma.rn.f16x2 p0, qz18, qz18, c; fma.rn.f16x2 g14, qz14, h0, qz14; prmt.b32 h1, lo1, hi1, 0x5410;\n"
        "mov.b32 {xl, xh}, a1; tanh.approx.f16 xr, xl; cvt.u32.u16 lo1, xr; tanh.approx.f16 xr, xh; cvt.u32.u16 hi1, xr; mul.rn.f16x2 a0, qz18, p0; fma.rn.f16x2 p1, qz19, qz19, c; fma.rn.f16x2 g15, qz15, h1, qz15; prmt.b32 h0, lo0, hi0, 0x5410;\n"
        "B82:\n"
        "wgmma.fence.sync.aligned;\n"
        "add.s64 dt, w2d, 1216; wgmma.mma_async.sync.aligned.m64n96k16.f16.f16.f16 {o0,o1,o2,o3,o4,o5,o6,o7,o8,o9,o10,o11,o12,o13,o14,o15,o16,o17,o18,o19,o20,o21,o22,o23}, {g12,g13,g14,g15}, dt, pt, 1, 1, 1;\n"
        "wgmma.commit_group.sync.aligned;\n"
        "@!pm bra.uni SKIP1;\n"
        "wgmma.fence.sync.aligned;\n"
        "add.s64 dt, w1d, 0; wgmma.mma_async.sync.aligned.m64n64k16.f16.f16.f16 {qz0,qz1,qz2,qz3,qz4,qz5,qz6,qz7,qz8,qz9,qz10,qz11,qz12,qz13,qz14,qz15}, {qa0,qa1,qa2,qa3}, dt, pf, 1, 1, 1;\n"
        "add.s64 dt, w1d, 128; wgmma.mma_async.sync.aligned.m64n64k16.f16.f16.f16 {qz0,qz1,qz2,qz3,qz4,qz5,qz6,qz7,qz8,qz9,qz10,qz11,qz12,qz13,qz14,qz15}, {qa4,qa5,qa6,qa7}, dt, pt, 1, 1, 1;\n"
        "add.s64 dt, w1d, 256; wgmma.mma_async.sync.aligned.m64n64k16.f16.f16.f16 {qz0,qz1,qz2,qz3,qz4,qz5,qz6,qz7,qz8,qz9,qz10,qz11,qz12,qz13,qz14,qz15}, {qa8,qa9,qa10,qa11}, dt, pt, 1, 1, 1;\n"
        "SKIP1:\n"
        "@pz bra.uni B86;\n"
        "mov.b32 {xl, xh}, a0; tanh.approx.f16 xr, xl; cvt.u32.u16 lo0, xr; tanh.approx.f16 xr, xh; cvt.u32.u16 hi0, xr; mul.rn.f16x2 a1, qz19, p1; fma.rn.f16x2 p0, qz20, qz20, c; fma.rn.f16x2 g0, qz16, h0, qz16; prmt.b32 h1, lo1, hi1, 0x5410;\n"
        "mov.b32 {xl, xh}, a1; tanh.approx.f16 xr, xl; cvt.u32.u16 lo1, xr; tanh.approx.f16 xr, xh; cvt.u32.u16 hi1, xr; mul.rn.f16x2 a0, qz20, p0; fma.rn.f16x2 p1, qz21, qz21, c; fma.rn.f16x2 g1, qz17, h1, qz17; prmt.b32 h0, lo0, hi0, 0x5410;\n"
        "mov.b32 {xl, xh}, a0; tanh.approx.f16 xr, xl; cvt.u32.u16 lo0, xr; tanh.approx.f16 xr, xh; cvt.u32.u16 hi0, xr; mul.rn.f16x2 a1, qz21, p1; fma.rn.f16x2 p0, qz22, qz22, c; fma.rn.f16x2 g2, qz18, h0, qz18; prmt.b32 h1, lo1, hi1, 0x5410;\n"
        "mov.b32 {xl, xh}, a1; tanh.approx.f16 xr, xl; cvt.u32.u16 lo1, xr; tanh.approx.f16 xr, xh; cvt.u32.u16 hi1, xr; mul.rn.f16x2 a0, qz22, p0; fma.rn.f16x2 p1, qz23, qz23, c; fma.rn.f16x2 g3, qz19, h1, qz19; prmt.b32 h0, lo0, hi0, 0x5410;\n"
        "B86:\n"
        "wgmma.wait_group.sync.aligned 2;\n"
        "wgmma.fence.sync.aligned;\n"
        "add.s64 dt, w2d, 1280; wgmma.mma_async.sync.aligned.m64n96k16.f16.f16.f16 {o0,o1,o2,o3,o4,o5,o6,o7,o8,o9,o10,o11,o12,o13,o14,o15,o16,o17,o18,o19,o20,o21,o22,o23}, {g0,g1,g2,g3}, dt, pt, 1, 1, 1;\n"
        "wgmma.commit_group.sync.aligned;\n"
        "@!pm bra.uni SKIP2;\n"
        "wgmma.fence.sync.aligned;\n"
        "add.s64 dt, w1d, 384; wgmma.mma_async.sync.aligned.m64n64k16.f16.f16.f16 {qz0,qz1,qz2,qz3,qz4,qz5,qz6,qz7,qz8,qz9,qz10,qz11,qz12,qz13,qz14,qz15}, {qa12,qa13,qa14,qa15}, dt, pt, 1, 1, 1;\n"
        "add.s64 dt, w1d, 512; wgmma.mma_async.sync.aligned.m64n64k16.f16.f16.f16 {qz0,qz1,qz2,qz3,qz4,qz5,qz6,qz7,qz8,qz9,qz10,qz11,qz12,qz13,qz14,qz15}, {qa16,qa17,qa18,qa19}, dt, pt, 1, 1, 1;\n"
        "add.s64 dt, w1d, 640; wgmma.mma_async.sync.aligned.m64n64k16.f16.f16.f16 {qz0,qz1,qz2,qz3,qz4,qz5,qz6,qz7,qz8,qz9,qz10,qz11,qz12,qz13,qz14,qz15}, {qa20,qa21,qa22,qa23}, dt, pt, 1, 1, 1;\n"
        "SKIP2:\n"
        "wgmma.fence.sync.aligned;\n"
        "wgmma.commit_group.sync.aligned;\n"
        "@pz bra.uni B90;\n"
        "mov.b32 {xl, xh}, a0; tanh.approx.f16 xr, xl; cvt.u32.u16 lo0, xr; tanh.approx.f16 xr, xh; cvt.u32.u16 hi0, xr; mul.rn.f16x2 a1, qz23, p1; fma.rn.f16x2 p0, qz24, qz24, c; fma.rn.f16x2 g4, qz20, h0, qz20; prmt.b32 h1, lo1, hi1, 0x5410;\n"
        "mov.b32 {xl, xh}, a1; tanh.approx.f16 xr, xl; cvt.u32.u16 lo1, xr; tanh.approx.f16 xr, xh; cvt.u32.u16 hi1, xr; mul.rn.f16x2 a0, qz24, p0; fma.rn.f16x2 p1, qz25, qz25, c; fma.rn.f16x2 g5, qz21, h1, qz21; prmt.b32 h0, lo0, hi0, 0x5410;\n"
        "mov.b32 {xl, xh}, a0; tanh.approx.f16 xr, xl; cvt.u32.u16 lo0, xr; tanh.approx.f16 xr, xh; cvt.u32.u16 hi0, xr; mul.rn.f16x2 a1, qz25, p1; fma.rn.f16x2 p0, qz26, qz26, c; fma.rn.f16x2 g6, qz22, h0, qz22; prmt.b32 h1, lo1, hi1, 0x5410;\n"
        "mov.b32 {xl, xh}, a1; tanh.approx.f16 xr, xl; cvt.u32.u16 lo1, xr; tanh.approx.f16 xr, xh; cvt.u32.u16 hi1, xr; mul.rn.f16x2 a0, qz26, p0; fma.rn.f16x2 p1, qz27, qz27, c; fma.rn.f16x2 g7, qz23, h1, qz23; prmt.b32 h0, lo0, hi0, 0x5410;\n"
        "B90:\n"
        "wgmma.wait_group.sync.aligned 3;\n"
        "wgmma.fence.sync.aligned;\n"
        "add.s64 dt, w2d, 1344; wgmma.mma_async.sync.aligned.m64n96k16.f16.f16.f16 {o0,o1,o2,o3,o4,o5,o6,o7,o8,o9,o10,o11,o12,o13,o14,o15,o16,o17,o18,o19,o20,o21,o22,o23}, {g4,g5,g6,g7}, dt, pt, 1, 1, 1;\n"
        "wgmma.commit_group.sync.aligned;\n"
        "@pz bra.uni B94;\n"
        "mov.b32 {xl, xh}, a0; tanh.approx.f16 xr, xl; cvt.u32.u16 lo0, xr; tanh.approx.f16 xr, xh; cvt.u32.u16 hi0, xr; mul.rn.f16x2 a1, qz27, p1; fma.rn.f16x2 p0, qz28, qz28, c; fma.rn.f16x2 g8, qz24, h0, qz24; prmt.b32 h1, lo1, hi1, 0x5410;\n"
        "mov.b32 {xl, xh}, a1; tanh.approx.f16 xr, xl; cvt.u32.u16 lo1, xr; tanh.approx.f16 xr, xh; cvt.u32.u16 hi1, xr; mul.rn.f16x2 a0, qz28, p0; fma.rn.f16x2 p1, qz29, qz29, c; fma.rn.f16x2 g9, qz25, h1, qz25; prmt.b32 h0, lo0, hi0, 0x5410;\n"
        "mov.b32 {xl, xh}, a0; tanh.approx.f16 xr, xl; cvt.u32.u16 lo0, xr; tanh.approx.f16 xr, xh; cvt.u32.u16 hi0, xr; mul.rn.f16x2 a1, qz29, p1; fma.rn.f16x2 p0, qz30, qz30, c; fma.rn.f16x2 g10, qz26, h0, qz26; prmt.b32 h1, lo1, hi1, 0x5410;\n"
        "mov.b32 {xl, xh}, a1; tanh.approx.f16 xr, xl; cvt.u32.u16 lo1, xr; tanh.approx.f16 xr, xh; cvt.u32.u16 hi1, xr; mul.rn.f16x2 a0, qz30, p0; fma.rn.f16x2 p1, qz31, qz31, c; fma.rn.f16x2 g11, qz27, h1, qz27; prmt.b32 h0, lo0, hi0, 0x5410;\n"
        "B94:\n"
        "wgmma.wait_group.sync.aligned 1;\n"
        "wgmma.fence.sync.aligned;\n"
        "add.s64 dt, w2d, 1408; wgmma.mma_async.sync.aligned.m64n96k16.f16.f16.f16 {o0,o1,o2,o3,o4,o5,o6,o7,o8,o9,o10,o11,o12,o13,o14,o15,o16,o17,o18,o19,o20,o21,o22,o23}, {g8,g9,g10,g11}, dt, pt, 1, 1, 1;\n"
        "wgmma.commit_group.sync.aligned;\n"
        "@pz bra.uni B2;\n"
        "mov.b32 {xl, xh}, a0; tanh.approx.f16 xr, xl; cvt.u32.u16 lo0, xr; tanh.approx.f16 xr, xh; cvt.u32.u16 hi0, xr; mul.rn.f16x2 a1, qz31, p1; fma.rn.f16x2 p0, qz0, qz0, c; fma.rn.f16x2 g12, qz28, h0, qz28; prmt.b32 h1, lo1, hi1, 0x5410;\n"
        "mov.b32 {xl, xh}, a1; tanh.approx.f16 xr, xl; cvt.u32.u16 lo1, xr; tanh.approx.f16 xr, xh; cvt.u32.u16 hi1, xr; mul.rn.f16x2 a0, qz0, p0; fma.rn.f16x2 p1, qz1, qz1, c; fma.rn.f16x2 g13, qz29, h1, qz29; prmt.b32 h0, lo0, hi0, 0x5410;\n"
        "mov.b32 {xl, xh}, a0; tanh.approx.f16 xr, xl; cvt.u32.u16 lo0, xr; tanh.approx.f16 xr, xh; cvt.u32.u16 hi0, xr; mul.rn.f16x2 a1, qz1, p1; fma.rn.f16x2 p0, qz2, qz2, c; fma.rn.f16x2 g14, qz30, h0, qz30; prmt.b32 h1, lo1, hi1, 0x5410;\n"
        "mov.b32 {xl, xh}, a1; tanh.approx.f16 xr, xl; cvt.u32.u16 lo1, xr; tanh.approx.f16 xr, xh; cvt.u32.u16 hi1, xr; mul.rn.f16x2 a0, qz2, p0; fma.rn.f16x2 p1, qz3, qz3, c; fma.rn.f16x2 g15, qz31, h1, qz31; prmt.b32 h0, lo0, hi0, 0x5410;\n"
        "B2:\n"
        "wgmma.fence.sync.aligned;\n"
        "add.s64 dt, w2d, 1472; wgmma.mma_async.sync.aligned.m64n96k16.f16.f16.f16 {o0,o1,o2,o3,o4,o5,o6,o7,o8,o9,o10,o11,o12,o13,o14,o15,o16,o17,o18,o19,o20,o21,o22,o23}, {g12,g13,g14,g15}, dt, pt, 1, 1, 1;\n"
        "wgmma.commit_group.sync.aligned;\n"
        "@!pm bra.uni BE;\n"
        "mov.b32 {xl, xh}, a0; tanh.approx.f16 xr, xl; cvt.u32.u16 lo0, xr; tanh.approx.f16 xr, xh; cvt.u32.u16 hi0, xr; mul.rn.f16x2 a1, qz3, p1; fma.rn.f16x2 p0, qz4, qz4, c; fma.rn.f16x2 g0, qz0, h0, qz0; prmt.b32 h1, lo1, hi1, 0x5410;\n"
        "mov.b32 {xl, xh}, a1; tanh.approx.f16 xr, xl; cvt.u32.u16 lo1, xr; tanh.approx.f16 xr, xh; cvt.u32.u16 hi1, xr; mul.rn.f16x2 a0, qz4, p0; fma.rn.f16x2 p1, qz5, qz5, c; fma.rn.f16x2 g1, qz1, h1, qz1; prmt.b32 h0, lo0, hi0, 0x5410;\n"
        "mov.b32 {xl, xh}, a0; tanh.approx.f16 xr, xl; cvt.u32.u16 lo0, xr; tanh.approx.f16 xr, xh; cvt.u32.u16 hi0, xr; mul.rn.f16x2 a1, qz5, p1; fma.rn.f16x2 p0, qz6, qz6, c; fma.rn.f16x2 g2, qz2, h0, qz2; prmt.b32 h1, lo1, hi1, 0x5410;\n"
        "mov.b32 {xl, xh}, a1; tanh.approx.f16 xr, xl; cvt.u32.u16 lo1, xr; tanh.approx.f16 xr, xh; cvt.u32.u16 hi1, xr; mul.rn.f16x2 a0, qz6, p0; fma.rn.f16x2 p1, qz7, qz7, c; fma.rn.f16x2 g3, qz3, h1, qz3; prmt.b32 h0, lo0, hi0, 0x5410;\n"
        "BE:\n"
        "wgmma.wait_group.sync.aligned 0;\n"
        "bra.uni LOOP;\n"
        "STORE:\n"
        "bar.sync tt, 128;\n"
        "setp.lt.s32 pr, n, 0;\n"
        "@pr bra.uni STOREB;\n"
        "cvt.u64.u32 gp, off; add.s64 gp, gp, %11;\n"
        "elect.sync _|pr, 0xffffffff;\n"
        "@pr cp.async.bulk.global.shared::cta.bulk_group [gp], [%4], 12288;\n"
        "@pr cp.async.bulk.commit_group;\n"
        "bra.uni STOREB;\n"
        "YLOAD:\n"
        "@!pm bra.uni YLOADP;\n"
        "cp.async.bulk.wait_group.read 0;\n"
        "sub.u32 ad, off, %8; cvt.u64.u32 gp, ad; add.s64 gp, gp, %11;\n"
        "elect.sync _|pr, 0xffffffff;\n"
        "@pr mbarrier.arrive.expect_tx.shared::cta.b64 _, [ybar], 12288;\n"
        "@pr cp.async.bulk.shared::cluster.global.mbarrier::complete_tx::bytes [%4], [gp], 12288, [ybar];\n"
        "YLOADP:\n"
        "cvt.u64.u32 gp, off; add.s64 gp, gp, %10;\n"
        "elect.sync _|pr, 0xffffffff;\n"
        "@pr cp.async.bulk.prefetch.L2.global.L2::cache_hint [gp], 12288, pol;\n"
        "bra.uni YLOADB;\n"
        "XLOAD:\n"
        "bar.sync tt, 128;\n"
        "cp.async.bulk.wait_group.read 0;\n"
        "cvt.u64.u32 gp, off; add.s64 gp, gp, %10;\n"
        "elect.sync _|pr, 0xffffffff;\n"
        "@pr mbarrier.arrive.expect_tx.shared::cta.b64 _, [xbar], 12288;\n"
        "@pr cp.async.bulk.shared::cluster.global.mbarrier::complete_tx::bytes.L2::cache_hint [%4], [gp], 12288, [xbar], pol;\n"
        "bra.uni XLOADB;\n"
        "SPINY: mov.u32 cnt, 0;\n"
        "SPINYL:\n"
        "add.u32 tt, n, 1; and.b32 tt, tt, 1; mbarrier.try_wait.parity.shared::cta.b64 pw, [ybar], tt;\n"
        "@pw bra.uni BACKY;\n"
        "add.u32 cnt, cnt, 1; setp.lt.u32 pw, cnt, 0x100000;\n"
        "@pw bra.uni SPINYL;\n"
        "trap;\n"
        "SPINX: mov.u32 cnt, 0;\n"
        "SPINXL:\n"
        "and.b32 tt, n, 1; mbarrier.try_wait.parity.shared::cta.b64 pw, [xbar], tt;\n"
        "@pw bra.uni BACKX;\n"
        "add.u32 cnt, cnt, 1; setp.lt.u32 pw, cnt, 0x100000;\n"
        "@pw bra.uni SPINXL;\n"
        "trap;\n"
        "SPINT: mov.u32 cnt, 0;\n"
        "SPINTL:\n"
        "mad.lo.u32 tt, n, 8, tbar; mbarrier.try_wait.parity.shared::cta.b64 pw, [tt], tpar;\n"
        "@pw bra.uni BACKT;\n"
        "add.u32 cnt, cnt, 1; setp.lt.u32 pw, cnt, 0x100000;\n"
        "@pw bra.uni SPINTL;\n"
        "trap;\n"
        "SPINW0: mov.u32 cnt, 0;\n"
        "SPINW0L:\n"
        "mov.u32 tt, 231208; mbarrier.try_wait.parity.shared::cta.b64 pw, [tt], 0;\n"
        "@pw bra.uni BACKW0;\n"
        "add.u32 cnt, cnt, 1; setp.lt.u32 pw, cnt, 0x100000;\n"
        "@pw bra.uni SPINW0L;\n"
        "trap;\n"
        "SPINW1: mov.u32 cnt, 0;\n"
        "SPINW1L:\n"
        "mov.u32 tt, 231216; mbarrier.try_wait.parity.shared::cta.b64 pw, [tt], 0;\n"
        "@pw bra.uni BACKW1;\n"
        "add.u32 cnt, cnt, 1; setp.lt.u32 pw, cnt, 0x100000;\n"
        "@pw bra.uni SPINW1L;\n"
        "trap;\n"
        "DONE:\n"
        "wgmma.wait_group.sync.aligned 0;\n"
        "}\n"
        :: "r"(prm.w1desc), "r"(prm.w2desc), "r"(c.wg), "r"(c.off), "r"(c.xs), "r"(c.a_offs), "r"(c.xs_offs), "r"(c.bias_addr),
           "r"(c.step), "r"(c.w), "l"(prm.x), "l"(prm.out)
        : "memory");
}

__device__ __forceinline__ float warp_sum(float v) {
#pragma unroll
    for (int s = 16; s >= 1; s >>= 1) v += __shfl_xor_sync(0xffffffffu, v, s);
    return v;
}
__device__ __forceinline__ float pow2f(int e) { return __uint_as_float((uint32_t)(e + 127) << 23); }
__device__ __forceinline__ int exponent_of(float v) { return (int)(__float_as_uint(v) >> 23) - 127; }
__device__ __forceinline__ float lds_bf16(uint32_t addr) {
    uint16_t v; asm volatile("ld.shared.u16 %0, [%1];" : "=h"(v) : "r"(addr) : "memory"); return bf_lo(v);
}

__device__ __forceinline__ void publish_bias(const Params& prm, uint32_t c, uint32_t tag) {
    const uint32_t lane = fresh_tid() & 31;
    const uint32_t col = sb + SM_W2 + (c >> 5) * 24576 + lane * 64 + ((((c >> 3) ^ (lane >> 1)) & 3) * 16) + (c & 7) * 2;
    float v = 0.0f;
#pragma unroll
    for (int k = 0; k < EX / 32; k++) v = fmaf(lds_bf16(col + k * 2048), lds_bf16(sb + SM_BETA + lane * 2 + k * 64), v);
    v = warp_sum(v);
    if (lane == 0) asm volatile("st.relaxed.gpu.global.v2.b32 [%0], {%1, %2};" ::"l"(prm.g->bias + c), "f"(v), "r"(tag) : "memory");
}
__device__ __forceinline__ void collect_bias(const Params& prm, uint32_t tag) {
    const uint32_t lane = fresh_tid() & 31;
    if (lane < 24) {
        const unsigned long long* src = prm.g->bias + 32 * (lane >> 3) + 8 * (lane & 3) + (lane & 4);
        uint32_t v[4], t[4], spins = 0;
        for (;;) {
#pragma unroll
            for (int k = 0; k < 4; k++)
                asm volatile("ld.relaxed.gpu.global.v2.b32 {%0, %1}, [%2];" : "=r"(v[k]), "=r"(t[k]) : "l"(src + k) : "memory");
            if (t[0] == tag && t[1] == tag && t[2] == tag && t[3] == tag) break;
            if (++spins > (1u << 22)) __trap();
        }
        sts128(sb + SM_BIAS + lane * 16, v[0], v[1], v[2], v[3]);
    }
    __syncwarp();
}
__device__ __forceinline__ float fetch_w2_row(uint32_t (&u)[12][4], uint32_t row, uint32_t sw) {
    uint32_t mx[4] = {};
#pragma unroll
    for (int a = 0; a < 3; a++)
#pragma unroll
        for (int k = 0; k < 4; k++) {
            asm volatile("ld.shared.v4.b32 {%0,%1,%2,%3}, [%4];"
                         : "=r"(u[a * 4][k]), "=r"(u[a * 4 + 1][k]), "=r"(u[a * 4 + 2][k]), "=r"(u[a * 4 + 3][k])
                         : "r"(row + a * 24576 + ((k * 16) ^ sw)) : "memory");
#pragma unroll
            for (int b = 0; b < 4; b++) asm("max.xorsign.abs.bf16x2 %0, %0, %1;" : "+r"(mx[b]) : "r"(u[a * 4 + b][k]));
        }
#pragma unroll
    for (int b = 1; b < 4; b++) asm("max.xorsign.abs.bf16x2 %0, %0, %1;" : "+r"(mx[0]) : "r"(mx[b]));
    return fmaxf(fabsf(bf_lo(mx[0])), fabsf(bf_hi(mx[0])));
}

template <bool FAST> __device__ __forceinline__ bool grn_stats(float ss, float gm, float bt, float top, int e, float& gx, float& inv, int& eo) {
    gx = sqrt_fast(fmaf(ss, INV_2A * INV_2A, 1e-6f));
    const float rt = sqrt_fast(ss + 1.0f) * INV_2A * top;
    uint32_t r[4] = {FAST ? __reduce_add_sync(0xffffffffu, __float2uint_rn(gx * 128.0f)) : __float_as_uint(warp_sum(gx)),
                     __reduce_max_sync(0xffffffffu, __float_as_uint(fmaf(bt, top, rt))),
                     __reduce_max_sync(0xffffffffu, __float_as_uint(rt * fabsf(gm) * gx)),
                     (uint32_t)__any_sync(0xffffffffu, !(ss >= 16.0f && ss < ACC_LIMIT))};
    if ((e & 31) == 0) sts128(sb + SM_SEL + (e >> 5) * 16, r[0], r[1], r[2], r[3]);
    MARK(6);
    named_sync(10, 512);
    lds128(r, sb + SM_SEL + min(e & 15, 11) * 16);
    if ((e & 31) >= 12) r[0] = 0;
    const float tot = FAST ? __uint2float_rn(__reduce_add_sync(0xffffffffu, r[0])) * (1.0f / 128) : warp_sum(__uint_as_float(r[0]));
    inv = __fdividef(1.0f, fmaf(tot, 1.0f / EX, 1e-6f));
    const float bound = fmaf(__uint_as_float(__reduce_max_sync(0xffffffffu, r[2])), inv,
                             __uint_as_float(__reduce_max_sync(0xffffffffu, r[1]))) * EX;
    eo = min(max(exponent_of(bound), -90), 126) - 14;
    return __any_sync(0xffffffffu, r[3]);
}

__device__ __forceinline__ float exact_sums(const Params& prm) {
    const int lane = fresh_tid() & 31, warp = fresh_warp(), wg = warp >> 2;
    const uint32_t epoch = lds32(sb + SM_RED + (RED_EPOCH + 1) * 4), bar = sb + SM_BAR + BAR_W1 * 8;
    if (wg < 3) {
        uint32_t wa[2][24], d[2][16];
        float acc[2][2] = {};
        const uint32_t yd = prm.ydesc + ((SM_SPARE - SM_Y1) >> 4), wd = prm.w1desc + ((2 * wg * 12288 + 5 * 2048) >> 4);
        load_w1t(wa, wg, warp & 3, lane);
#pragma unroll 1
        for (int n = 0; n < ROWS_PER_CTA; n++) {
            if (warp == 0) {
                expect_tx(bar, TILE_BYTES);
                bulk_load(sb + SM_SPARE, (const char*)prm.out + (cta_tile0(fresh_cta()) + n * cta_stride(fresh_cta())), TILE_BYTES, bar);
            }
            mbar_wait(bar, (n + 1) & 1);
            gemm1_t<0>(d[0], wa[0], yd, wd);
            gemm1_t<1>(d[1], wa[1], yd, wd);
            wg_wait<0>();
            pin(d[0]); pin(d[1]);
            gelu_sumsq_f(d[0], acc[0]);
            gelu_sumsq_f(d[1], acc[1]);
            named_sync(1, 384);
        }
        publish_sums(acc, prm.g->sums[epoch & 1], &prm.g->count[1], wg, warp & 3, lane);
    }
    grid_wait(&prm.g->count[1], (epoch + 1) * NUM_CTAS);
    return __ldcg(prm.g->sums[epoch & 1] + fresh_tid() % EX);
}

template <bool FIRST> __device__ __forceinline__ void prepare_pass2(const Pass2& c, const Params& prm, float ss) {
    const int tid = fresh_tid(), lane = tid & 31, warp = fresh_warp(), wg = warp >> 2;
    const int e = tid >= EX ? tid - EX : tid;
    const uint32_t w2row = sb + SM_W2 + e * 64, sw = ((e >> 1) & 3) * 16;
    pass2_start(c, prm);
    MARK(2);
    if (wg) {
        uint32_t u[12][4];
        mbar_wait_c<0>(sb + SM_BAR + BAR_W2 * 8);
        const float top = fetch_w2_row(u, w2row, sw);
        MARK(3);
        const float gm = lds_bf16(sb + SM_GAMMA + e * 2), bt = fabsf(lds_bf16(sb + SM_BETA + e * 2));
        if (FIRST) {
            const uint32_t epoch = lds32(sb + SM_RED + RED_EPOCH * 4);
            if (wg == 3) named_sync(11, EX);
            if (warp == 12) collect_bias(prm, epoch + 1);
            MARK(4);
            ss = collect_fast(acc_word(prm, epoch, e));
            if (tid == 416 && fresh_cta() == 0) prm.g->count[0] = epoch + 1;
        }
        if (warp == 4) TS(4);
        MARK(5);
        float gx, inv;
        int eo;
        const bool redo = (grn_stats<FIRST>(ss, gm, bt, top, e, gx, inv, eo) || FORCE_EXACT) && FIRST;
        MARK(8);
        const float up = pow2f(eo), dn = pow2f(-eo);
        if (warp == 4) {
            if (lane == 24) sts64(sb + SM_RED + RED_SCALE * 4, pack_bf2(up, up), redo);
            if (lane < 24 && !redo) {
                uint32_t b[4];
                lds128(b, sb + SM_BIAS + lane * 16);
                const uint32_t p0 = pack_h2(__uint_as_float(b[0]) * dn, __uint_as_float(b[1]) * dn);
                const uint32_t p1 = pack_h2(__uint_as_float(b[2]) * dn, __uint_as_float(b[3]) * dn);
                sts128(sb + SM_BIAS + lane * 16, p0, p0, p1, p1);
            }
            __syncwarp();
            mbar_arrive_if(sb + SM_BAR + BAR_STAT * 8, lane == 0);
        }
        if (!redo) {
            float sc = fmaf(gm, gx * inv, 1.0f) * INV_2A;
            if (eo > 6) {
                const uint32_t dn2 = pack_bf2(dn, dn);
#pragma unroll
                for (int k = 0; k < 48; k++) u[k >> 2][k & 3] = bf2_mul(u[k >> 2][k & 3], dn2);
            } else {
                sc *= dn;
            }
            const uint32_t s2 = pack_bf2(sc * 0x1p-112f, sc * 0x1p-112f);
#pragma unroll
            for (int k = 0; k < 12; k++) {
                uint32_t v[4];
#pragma unroll
                for (int b = 0; b < 4; b++) {
                    v[b] = bf2_mul(u[k][b], s2);
                    v[b] += (v[b] & 0x7fff7fffu) * 7u;
                }
                sts128(w2row + (k >> 2) * 24576 + (((k & 3) * 16) ^ sw), v[0], v[1], v[2], v[3]);
            }
            MARK(9);
            fence_async_smem();
            __syncwarp();
            mbar_arrive_if(sb + SM_BAR + (BAR_ROWS + (wg != 3)) * 8, lane == 0);
        }
        if (warp == 4) TS(5);
    } else {
        asm volatile("bar.arrive 10, 512;" ::: "memory");
    }
}

__device__ __forceinline__ Pass2 pass2_setup() {
    const int lane = fresh_tid() & 31, wg = fresh_warp() >> 2, w = fresh_warp() & 3, arow = 16 * w + (lane & 15);
    Pass2 c;
    c.wg = wg;
    c.w = w;
    c.off = cta_tile0(fresh_cta()) + (ROWS_PER_CTA - 1 - wg) * cta_stride(fresh_cta());
    c.step = 4 * cta_stride(fresh_cta());
    c.xs = wg == 3 ? sb + SM_BUF3 : sb + SM_Y1 + (wg == 2 ? 2 : 1 - wg) * SLOT_BYTES;
    static_assert((ROWS_PER_CTA - 1) % NX == 1, "slot of the last tile");
    c.a_offs = (arow * 128 + (((lane >> 4) ^ (arow & 7)) * 16)) |
               (8192 + arow * 64 + (((lane >> 4) ^ ((arow >> 1) & 3)) * 16)) << 16;
    const int g = lane >> 2, px = 33 * (g & 1) + 4 * (g >> 1) + 16 * (w >> 1) + 2 * (w & 1);
    c.xs_offs = (px * 192 + (lane & 3) * 16) | ((px ^ 1) * 192 + (lane & 3) * 16) << 16;
    c.bias_addr = sb + SM_BIAS + (lane & 3) * 16;
    return c;
}

__global__ void __launch_bounds__(512, 1) convnext_kernel(const __grid_constant__ Params prm) {
    extern __shared__ __align__(1024) uint8_t smem[];
    if ((uint32_t)__cvta_generic_to_shared(smem) != sb) __trap();
    if (fresh_warp() == 0) {
        if (fresh_tid() == 0) {
#pragma unroll
            for (int k = 0; k < NX; k++) mbar_init(sb + SM_GO + k * 8, 2);
            mbar_init(sb + SM_BAR + BAR_DW * 8, 1);
            fence_async_smem();
        }
        __syncwarp();
        expect_tx(sb + SM_BAR + BAR_DW * 8, 9 * CH * 2);
        bulk_load(sb + SM_Y1, prm.dw, 9 * CH * 2, sb + SM_BAR + BAR_DW * 8);
        const RowCopy rc = row_copy(prm);
#pragma unroll
        for (int k = 0; k < NX; k++) issue_row_load(rc, k, k);
        SMARK(4);
    } else if (fresh_warp() == 15) {
        const uint32_t cta = fresh_cta();
        bulk_prefetch((const char*)prm.w1 + cta * (CH * EX * 2 / NUM_CTAS), CH * EX * 2 / NUM_CTAS);
        bulk_prefetch(prm.dw, 9 * CH * 2);
        bulk_prefetch((const char*)prm.x + (cta_tile0(cta) - cta_stride(cta)), TILE_BYTES);
    }
    if (fresh_warp() >= 12) {
        Producer pc;
        SMARK(0);
        asm volatile("setmaxnreg.inc.sync.aligned.u32 %0;" ::"n"(PRODUCER_REGS));
        SMARK(1);
        const int w = fresh_warp() & 3, lane = fresh_tid() & 31;
        const int j = lane & 7, hb = (lane >> 3) & 1, base = 4 * (2 * w + (lane >> 4));
        pc.lane = lane; pc.warp = w;
        pc.xoff[0] = hb * XHALF_B + base * 192 + j * 16;
        pc.xoff[1] = hb * XHALF_B + base * 192 + 128 + j * 8;
        const int grp = 4 * w + (lane >> 3);
#pragma unroll
        for (int o = 0; o < 2; o++) {
            const int row = (grp & 7) + 8 * (o ^ hb) + 32 * (grp >> 3);
            pc.yoff[0][o] = row * 128 + ((j ^ (row & 7)) * 16);
            pc.yoff[1][o] = 8192 + row * 64 + (((j >> 1) ^ ((row >> 1) & 3)) * 16) + (j & 1) * 8;
        }
        pc.stat = sb + SM_STAT + (8 * w + (lane >> 2)) * 32;
        pc.own = pc.stat + (lane & 3) * 8;
        const int dstep = fresh_cta() & 8 ? 3 * CH * 2 : -3 * CH * 2;
        named_sync(0, 512);
        mbar_wait_c<0>(sb + SM_BAR + BAR_DW * 8);
        SMARK(8);
#pragma unroll
        for (int tap = 0; tap < 9; tap++) {
            const uint32_t dw = sb + SM_Y1 + (3 + tap % 3) * CH * 2 + (tap / 3 - 1) * dstep;
            lds128(pc.w[tap], dw + j * 16);
            asm volatile("ld.shared.v2.b32 {%0,%1}, [%2];" : "=r"(pc.w[tap][4]), "=r"(pc.w[tap][5]) : "r"(dw + 128 + j * 8) : "memory");
        }
#pragma unroll
        for (int tap = 0; tap < 9; tap++)
#pragma unroll
            for (int u = 0; u < 6; u++) pc.w[tap][u] = bf2_mul(pc.w[tap][u], TAP_SCALE_BF2);
        produce(pc, prm);
        TS(9);
        asm volatile("setmaxnreg.dec.sync.aligned.u32 %0;" ::"n"(EVEN_REGS));
        if (fresh_warp() == 12) {
            mbar_wait_c<0>(sb + SM_BAR + BAR_W2 * 8);
            if (fresh_cta() < CH) publish_bias(prm, fresh_cta(), lds32(sb + SM_RED + RED_EPOCH * 4) + 1);
        }
    } else {
        asm volatile("setmaxnreg.dec.sync.aligned.u32 %0;" ::"n"(CONSUMER_REGS));
        {
            const int tid = fresh_tid(), warp = fresh_warp(), lane = tid & 31;
            uint32_t cnt[2];
            if (warp == 1) {
                if (lane == 0) {
                    mbar_init(sb + SM_BAR + BAR_W1 * 8, 1);
                    mbar_init(sb + SM_BAR + BAR_W1B * 8, 1);
                    fence_async_smem();
                }
                __syncwarp();
#pragma unroll
                for (int h = 0; h < 2; h++) {
                    const uint32_t bar = sb + SM_BAR + (h ? BAR_W1B : BAR_W1) * 8;
                    expect_tx(bar, CH * EX);
#pragma unroll
                    for (int q = h; q < 6; q += 2) tma_load_2d(sb + SM_W1 + q * 12288, &prm.w1_map, 64 * q, 0, bar);
                }
            } else if (warp == 2) {
                if (lane < 2) asm volatile("prefetch.tensormap [%0];" ::"l"(&prm.w1_map + lane) : "memory");
            } else if (warp >= 8) {
                if (lane == 0) {
#pragma unroll 1
                    for (int k = NX + warp - 8; k < GO_COUNT + ROWS_PER_CTA + 2; k += 4)
                        mbar_init(sb + SM_GO + k * 8, k < 2 * NX ? 2 : k < GO_COUNT ? 14 : 4);
                    fence_async_smem();
                }
            } else if (warp == 3) {
                const uint32_t one = (lane & 5) == ((lane & 8) >> 1) + (lane >> 4) ? 0x3f803f80u : 0u;
                sts128(sb + SM_SEL + lane * 16, one, one, one, one);
                fence_async_smem();
            } else if (tid - 128u < NX * 12 && ((fresh_cta() + 1) & 7) < 2) {
                const int k = tid - 128;
                sts128(sb + SM_X + (k / 12) * SLOT_BYTES + ((fresh_cta() & 7) == 0 ? 0 : XHALF_B + 33 * 192) + (k % 12) * 16, 0, 0, 0, 0);
            }
            __syncwarp();
            asm volatile("ld.relaxed.gpu.global.v2.u32 {%0, %1}, [%2];" : "=r"(cnt[0]), "=r"(cnt[1]) : "l"(prm.g->count) : "memory");
            SMARK(0);
            named_sync(0, 512);
            if (tid == 256) {
                sts64(sb + SM_RED + RED_EPOCH * 4, cnt[0], cnt[1] / NUM_CTAS);
#pragma unroll
                for (int k = 0; k < BAR_DW; k++)
                    if (k != BAR_W1 && k != BAR_W1B) mbar_init(sb + SM_BAR + k * 8, k < BAR_TURN || k == BAR_STAT ? 1 : k == BAR_ROWS + 1 ? 8 : 4);
#pragma unroll
                for (int k = 0; k < 3; k++) mbar_arrive_if(sb + SM_BAR + (BAR_Y2FULL + k) * 8, true);
            }
            if (fresh_cta() == 0) *acc_word(prm, cnt[0] + 1, tid) = 0;
            if (fresh_cta() == 1) prm.g->sums[~(cnt[1] / NUM_CTAS) & 1][tid] = 0.0f;
            __syncwarp();
            SMARK(1);
            mbar_wait_c<0>(sb + SM_BAR + BAR_W1 * 8);
            SMARK(2);
        }

        const int tid = fresh_tid(), lane = tid & 31, wg = fresh_warp() >> 2, w = fresh_warp() & 3;
        float acc[2][2];
        const int c = 8 * (lane >> 4) + (lane & 7), ck = 2 * w + ((lane >> 3) & 1);
        consume(acc, sb + SM_W1 + 2 * wg * 12288 + c * 128 + ((ck ^ (c & 7)) * 16), prm.ydesc,
                prm.w1desc + (((2 * wg + 1) * 12288 + 5 * 2048) >> 4), wg * SLOT_BYTES, make_duty(prm, wg, w), w, lane, prm);
        publish_fast(prm, acc, lds32(sb + SM_RED + RED_EPOCH * 4), wg, w, lane);
        if (wg) asm volatile("bar.arrive 11, 384;" ::: "memory");
        MARK(0);
        bulk_wait_all();
        if (wg == 0) TS(3);
        asm volatile("setmaxnreg.inc.sync.aligned.u32 %0;" ::"n"(EVEN_REGS));
    }

    {
        asm volatile(PASS2_STATE);
        MARK(1);
        Pass2 c = pass2_setup();
        prepare_pass2<true>(c, prm, 0.0f);
        if (pass2_head(c, 0)) {
            const float ss = exact_sums(prm);
            c = pass2_setup();
            prepare_pass2<false>(c, prm, ss);
            pass2_head(c, 1);
        }

        pass2_tiles(c, prm);
        bulk_wait_read<0>();
        MARK(13);
    }
}

}

extern "C" void kernel_launch(void* const* d_in, const int* in_sizes, int n_in, void* d_out, int out_size) {
    (void)in_sizes; (void)n_in; (void)out_size;
    typedef CUresult (*EncodeFn)(CUtensorMap*, CUtensorMapDataType, cuuint32_t, void*, const cuuint64_t*, const cuuint64_t*,
                                 const cuuint32_t*, const cuuint32_t*, CUtensorMapInterleave, CUtensorMapSwizzle,
                                 CUtensorMapL2promotion, CUtensorMapFloatOOBfill);
    void* fn = nullptr;
    cudaDriverEntryPointQueryResult status;
    cudaGetDriverEntryPoint("cuTensorMapEncodeTiled", &fn, cudaEnableDefault, &status);
    const EncodeFn encode = (EncodeFn)fn;
    const cuuint32_t ones[2] = {1, 1};

    Params p;
    {
        const cuuint64_t dims[2] = {EX, CH}, strides[1] = {EX * 2};
        const cuuint32_t box[2] = {64, CH};
        encode(&p.w1_map, CU_TENSOR_MAP_DATA_TYPE_BFLOAT16, 2, d_in[2], dims, strides, box, ones,
               CU_TENSOR_MAP_INTERLEAVE_NONE, CU_TENSOR_MAP_SWIZZLE_128B, CU_TENSOR_MAP_L2_PROMOTION_NONE,
               CU_TENSOR_MAP_FLOAT_OOB_FILL_NONE);
    }
    {
        const cuuint64_t dims[2] = {CH, EX}, strides[1] = {CH * 2};
        const cuuint32_t box[2] = {32, 192};
        encode(&p.w2_map, CU_TENSOR_MAP_DATA_TYPE_BFLOAT16, 2, d_in[3], dims, strides, box, ones,
               CU_TENSOR_MAP_INTERLEAVE_NONE, CU_TENSOR_MAP_SWIZZLE_64B, CU_TENSOR_MAP_L2_PROMOTION_NONE,
               CU_TENSOR_MAP_FLOAT_OOB_FILL_NONE);
    }
    p.x = (const __nv_bfloat16*)d_in[0];
    p.dw = (const __nv_bfloat16*)d_in[1];
    p.w1 = (const __nv_bfloat16*)d_in[2];
    p.gamma = (const __nv_bfloat16*)d_in[4];
    p.beta = (const __nv_bfloat16*)d_in[5];
    p.out = (__nv_bfloat16*)d_out;
    cudaGetSymbolAddress((void**)&p.g, g_scratch);
    p.w1desc = desc_lo(sb + SM_W1, 12288);
    p.w2desc = desc_lo(sb + SM_W2, 24576);
    p.ydesc = desc_lo(sb + SM_Y1, 16);
    p.ydesc64[0] = (0x40000040ull << 32) | p.ydesc;
    p.ydesc64[1] = (0x80000020ull << 32) | (p.ydesc + 512);
    for (int k = 0; k < 3; k++) p.sel[k] = (8ull << 32) | desc_lo(sb + SM_SEL + k * 128, k == 2 ? 128 : 0);
    constexpr int smem_bytes = SM_TOTAL;
    cudaFuncSetAttribute(convnext_kernel, cudaFuncAttributeMaxDynamicSharedMemorySize, smem_bytes);
    convnext_kernel<<<NUM_CTAS, 512, smem_bytes>>>(p);
}
```

```cpp
#include <cuda.h>
#include <cuda_runtime.h>
#include <cuda_bf16.h>
#include <stdint.h>

namespace {

constexpr int IMG_W = 512, CH = 96, EX = 384;
constexpr int TILE_PX = 64;
constexpr int ROWS_PER_CTA = 32;
constexpr int NUM_CTAS = 128;
constexpr int STEPS = ROWS_PER_CTA + 2;
constexpr int ROW_BYTES = IMG_W * CH * 2;

#define FORCE_EXACT 0
#define PREGS 200
#define CREGS 104
constexpr int PRODUCER_REGS = PREGS, CONSUMER_REGS = CREGS, EVEN_REGS = 128;

constexpr int XHALF_BYTES = 34 * 192;
constexpr int XHALF_B = XHALF_BYTES + 64;
constexpr int XROW_BYTES = XHALF_B + XHALF_BYTES + 64;
constexpr int L2_AHEAD = 2;
constexpr int NX = 3;
constexpr int TILE_BYTES = TILE_PX * 192;
constexpr int NY1 = 3;

constexpr uint32_t sb = 1024;
constexpr int SM_W1 = 0;
constexpr int SM_W2 = 73728;
constexpr int SM_RING = 147456;
constexpr int SLOT_BYTES = 26624;
constexpr int SM_Y1 = SM_RING;
constexpr int SM_X = SM_Y1 + TILE_BYTES;
constexpr int SM_STAT = SM_X + XROW_BYTES;
constexpr int SM_BUF3 = SM_X + SLOT_BYTES, SM_SPARE = SM_X;
constexpr int SM_SEL = SM_RING + NX * SLOT_BYTES;
constexpr int SM_BIAS = SM_SEL + 512;
constexpr int SM_GAMMA = SM_BIAS + 384;
constexpr int SM_BETA = SM_GAMMA + EX * 2;
constexpr int SM_RED = SM_BETA + EX * 2;
constexpr int SM_BAR = SM_RED + 16;
constexpr int BAR_Y2FULL = 0, BAR_XSFULL = 4, BAR_W1 = 8, BAR_W2 = 9, BAR_W1B = 10, BAR_TURN = 11, BAR_ROWS = 51,
              BAR_STAT = 53, BAR_DW = 54, BAR_COUNT = 55;
constexpr int SM_GO = SM_BAR + BAR_COUNT * 8, GO_COUNT = ROWS_PER_CTA + 2 * NX;
constexpr int SM_YFULL = SM_GO + (GO_COUNT + 1) * 8;
constexpr int SM_TOTAL = SM_YFULL + (ROWS_PER_CTA + 1) * 8;
static_assert(SM_STAT + TILE_PX * 16 <= SM_RING + SLOT_BYTES && XROW_BYTES >= TILE_BYTES && SM_X % 1024 == 0, "ring layout");
static_assert(SM_TOTAL <= 232448, "smem budget");
static_assert(SM_STAT % 128 == 0 && SM_BIAS % 16 == 0 && SM_BAR % 8 == 0 && SLOT_BYTES % 1024 == 0, "alignment");

static_assert(NX == NY1, "both rings are walked with one index");
constexpr int RED_EPOCH = 0, RED_SCALE = 2;

constexpr float GELU_A = 0.32920349f;
constexpr uint32_t GELU_C_H2 = 0x40D940D9u;
constexpr float INV_2A = 1.0f / (2.0f * GELU_A);

constexpr uint32_t TAP_SCALE_BF2 = 0x2B802B80u;
constexpr float LN_EPS_SCALED = 1e-5f * 0x1p-80f;
constexpr float RSTD_SCALE = GELU_A * 0x1p-112f;

struct Scratch {
    unsigned long long acc[2][EX / 4 * 32];
    unsigned long long bias[CH];
    float sums[2][EX];
    uint4 zero_row[66 * 192 / 16];
    unsigned int count[2];
};
__device__ __align__(256) Scratch g_scratch;
constexpr float ACC_LIMIT = 0x1p30f;

#define TS(k)
#define ASM_TS
#define MARK(k)
#define SMARK(k)
#define ASM_MARK
#define ASM_SMARK
#define ASM_TRC(it)

__device__ __forceinline__ void mbar_init(uint32_t bar, uint32_t count) {
    asm volatile("mbarrier.init.shared::cta.b64 [%0], %1;" ::"r"(bar), "r"(count) : "memory");
}
__device__ __forceinline__ void mbar_arrive_if(uint32_t bar, bool pred) {
    asm volatile("{\n.reg .pred p;\nsetp.ne.u32 p, %1, 0;\n@p mbarrier.arrive.shared::cta.b64 _, [%0];\n}\n"
                 ::"r"(bar), "r"((uint32_t)pred) : "memory");
}
__device__ __forceinline__ void mbar_wait(uint32_t bar, uint32_t parity) {
    asm volatile(
        "{\n.reg .pred p;\n.reg .u32 n;\n"
        "mbarrier.try_wait.parity.shared::cta.b64 p, [%0], %1;\n"
        "@p bra.uni WAIT_DONE;\n"
        "mov.u32 n, 0;\n"
        "WAIT_LOOP:\n"
        "mbarrier.try_wait.parity.shared::cta.b64 p, [%0], %1;\n"
        "@p bra.uni WAIT_DONE;\n"
        "mbarrier.try_wait.parity.shared::cta.b64 p, [%0], %1;\n"
        "@p bra.uni WAIT_DONE;\n"
        "mbarrier.try_wait.parity.shared::cta.b64 p, [%0], %1;\n"
        "@p bra.uni WAIT_DONE;\n"
        "add.u32 n, n, 1;\nsetp.lt.u32 p, n, 0x40000;\n"
        "@p bra.uni WAIT_LOOP;\n"
        "trap;\n"
        "WAIT_DONE:\n}\n"
        ::"r"(bar), "r"(parity) : "memory");
}
template <int PARITY> __device__ __forceinline__ void mbar_wait_c(uint32_t bar) {
    asm volatile(
        "{\n.reg .pred p;\n.reg .u32 n;\n"
        "mbarrier.try_wait.parity.shared::cta.b64 p, [%0], %1;\n"
        "@p bra.uni WAIT_DONE;\n"
        "mov.u32 n, 0;\n"
        "WAIT_LOOP:\n"
        "mbarrier.try_wait.parity.shared::cta.b64 p, [%0], %1;\n"
        "@p bra.uni WAIT_DONE;\n"
        "mbarrier.try_wait.parity.shared::cta.b64 p, [%0], %1;\n"
        "@p bra.uni WAIT_DONE;\n"
        "mbarrier.try_wait.parity.shared::cta.b64 p, [%0], %1;\n"
        "@p bra.uni WAIT_DONE;\n"
        "add.u32 n, n, 1;\nsetp.lt.u32 p, n, 0x40000;\n"
        "@p bra.uni WAIT_LOOP;\n"
        "trap;\n"
        "WAIT_DONE:\n}\n"
        ::"r"(bar), "n"(PARITY) : "memory");
}
#define ELECTED(body) "{\n.reg .pred p;\nelect.sync _|p, 0xffffffff;\n" body "}\n"
__device__ __forceinline__ void expect_tx(uint32_t bar, uint32_t bytes) {
    asm volatile(ELECTED("@p mbarrier.arrive.expect_tx.shared::cta.b64 _, [%0], %1;\n") ::"r"(bar), "r"(bytes) : "memory");
}
__device__ __forceinline__ void bulk_load(uint32_t dst, const void* src, uint32_t bytes, uint32_t bar) {
    asm volatile(ELECTED("@p cp.async.bulk.shared::cluster.global.mbarrier::complete_tx::bytes [%0], [%1], %2, [%3];\n")
                 ::"r"(dst), "l"(src), "r"(bytes), "r"(bar) : "memory");
}
__device__ __forceinline__ void bulk_prefetch(const void* src, uint32_t bytes) {
    asm volatile(ELECTED("@p cp.async.bulk.prefetch.L2.global [%0], %1;\n") ::"l"(src), "r"(bytes) : "memory");
}
__device__ __forceinline__ void tma_load_2d(uint32_t dst, const CUtensorMap* map, int c0, int c1, uint32_t bar) {
    asm volatile(ELECTED("@p cp.async.bulk.tensor.2d.shared::cluster.global.mbarrier::complete_tx::bytes [%0], [%1, {%2, %3}], [%4];\n")
                 ::"r"(dst), "l"(map), "r"(c0), "r"(c1), "r"(bar) : "memory");
}
template <int N> __device__ __forceinline__ void bulk_wait_read() {
    asm volatile("cp.async.bulk.wait_group.read %0;" ::"n"(N) : "memory");
}
__device__ __forceinline__ void bulk_wait_all() { asm volatile("cp.async.bulk.wait_group 0;" ::: "memory"); }
__device__ __forceinline__ void fence_async_smem() { asm volatile("fence.proxy.async.shared::cta;" ::: "memory"); }
__device__ __forceinline__ void named_sync(int id, int n) { asm volatile("bar.sync %0, %1;" ::"r"(id), "r"(n) : "memory"); }

__device__ __forceinline__ void sts64(uint32_t addr, uint32_t a, uint32_t b) {
    asm volatile("st.shared.v2.b32 [%0], {%1,%2};" ::"r"(addr), "r"(a), "r"(b) : "memory");
}
__device__ __forceinline__ void sts128(uint32_t addr, uint32_t a, uint32_t b, uint32_t c, uint32_t d) {
    asm volatile("st.shared.v4.b32 [%0], {%1,%2,%3,%4};" ::"r"(addr), "r"(a), "r"(b), "r"(c), "r"(d) : "memory");
}
__device__ __forceinline__ void ldsm4_t(uint32_t* r, uint32_t addr) {
    asm volatile("ldmatrix.sync.aligned.m8n8.x4.trans.shared.b16 {%0,%1,%2,%3}, [%4];"
                 : "=r"(r[0]), "=r"(r[1]), "=r"(r[2]), "=r"(r[3]) : "r"(addr) : "memory");
}
__device__ __forceinline__ void lds128(uint32_t* v, uint32_t addr) {
    asm volatile("ld.shared.v4.b32 {%0,%1,%2,%3}, [%4];"
                 : "=r"(v[0]), "=r"(v[1]), "=r"(v[2]), "=r"(v[3]) : "r"(addr) : "memory");
}
__device__ __forceinline__ uint32_t lds32(uint32_t addr) {
    uint32_t v; asm volatile("ld.shared.b32 %0, [%1];" : "=r"(v) : "r"(addr) : "memory"); return v;
}
__device__ __forceinline__ void sts32(uint32_t addr, uint32_t v) {
    asm volatile("st.shared.b32 [%0], %1;" ::"r"(addr), "r"(v) : "memory");
}

__device__ __forceinline__ uint32_t bf2_fma(uint32_t a, uint32_t b, uint32_t c) {
    uint32_t d; asm("fma.rn.bf16x2 %0, %1, %2, %3;" : "=r"(d) : "r"(a), "r"(b), "r"(c)); return d;
}
__device__ __forceinline__ uint32_t bf2_mul(uint32_t a, uint32_t b) {
    uint32_t d; asm("mul.rn.bf16x2 %0, %1, %2;" : "=r"(d) : "r"(a), "r"(b)); return d;
}
__device__ __forceinline__ uint32_t bf2_add(uint32_t a, uint32_t b) {
    uint32_t d; asm("add.rn.bf16x2 %0, %1, %2;" : "=r"(d) : "r"(a), "r"(b)); return d;
}
__device__ __forceinline__ uint32_t h2_fma(uint32_t a, uint32_t b, uint32_t c) {
    uint32_t d; asm("fma.rn.f16x2 %0, %1, %2, %3;" : "=r"(d) : "r"(a), "r"(b), "r"(c)); return d;
}
__device__ __forceinline__ uint32_t h2_mul(uint32_t a, uint32_t b) {
    uint32_t d; asm("mul.rn.f16x2 %0, %1, %2;" : "=r"(d) : "r"(a), "r"(b)); return d;
}
__device__ __forceinline__ uint32_t h2_tanh(uint32_t a) {
    uint32_t d; asm("tanh.approx.f16x2 %0, %1;" : "=r"(d) : "r"(a)); return d;
}
__device__ __forceinline__ float bf_lo(uint32_t v) { return __uint_as_float(v << 16); }
__device__ __forceinline__ float bf_hi(uint32_t v) { return __uint_as_float(v & 0xffff0000u); }
__device__ __forceinline__ uint32_t pack_h2(float lo, float hi) {
    uint32_t d; asm("cvt.rn.f16x2.f32 %0, %1, %2;" : "=r"(d) : "f"(hi), "f"(lo)); return d;
}
__device__ __forceinline__ uint32_t pack_bf2(float lo, float hi) {
    uint32_t d; asm("cvt.rn.bf16x2.f32 %0, %1, %2;" : "=r"(d) : "f"(hi), "f"(lo)); return d;
}
__device__ __forceinline__ void h2_unpack(uint32_t v, float& lo, float& hi) {
    asm("{\n.reg .b16 l, h;\nmov.b32 {l, h}, %2;\ncvt.f32.f16 %0, l;\ncvt.f32.f16 %1, h;\n}\n" : "=f"(lo), "=f"(hi) : "r"(v));
}

__device__ __forceinline__ uint32_t gelu2(uint32_t z) {
    uint32_t p = h2_fma(z, z, GELU_C_H2);
    uint32_t t = h2_tanh(h2_mul(z, p));
    return h2_fma(z, t, z);
}

__device__ __forceinline__ void wg_fence() { asm volatile("wgmma.fence.sync.aligned;" ::: "memory"); }
__device__ __forceinline__ void wg_commit() { asm volatile("wgmma.commit_group.sync.aligned;" ::: "memory"); }
template <int N> __device__ __forceinline__ void wg_wait() {
    asm volatile("wgmma.wait_group.sync.aligned %0;" ::"n"(N) : "memory");
}
template <int N> __device__ __forceinline__ void pin(uint32_t (&r)[N]) {
#pragma unroll
    for (int i = 0; i < N; i++) asm volatile("" : "+r"(r[i])::"memory");
}
constexpr uint32_t desc_lo(uint32_t addr, uint32_t lbo) { return ((addr & 0x3FFFF) >> 4) | ((lbo >> 4) << 16); }
template <uint32_t SBO, uint32_t SWZ> __device__ __forceinline__ uint64_t desc(uint32_t lo, uint32_t bytes) {
    return (((uint64_t)((SBO >> 4) | (SWZ << 30)) << 32) | lo) + (bytes >> 4);
}
__device__ __forceinline__ uint32_t fresh_tid() {
    uint32_t v; asm volatile("mov.u32 %0, %%tid.x;" : "=r"(v));
    return v;
}
template <uint32_t V> __device__ __forceinline__ uint32_t loop_init() {
    uint32_t v; asm volatile("mov.u32 %0, %1;" : "=r"(v) : "n"(V)); return v;
}
__device__ __forceinline__ int fresh_warp() {
    int v; asm volatile("shfl.sync.idx.b32 %0, %1, 0, 0x1f, 0xffffffff;" : "=r"(v) : "r"(fresh_tid() >> 5)); return v;
}
__device__ __forceinline__ uint32_t fresh_cta() {
    uint32_t v; asm volatile("mov.u32 %0, %%ctaid.x;" : "=r"(v)); return v;
}
__device__ __forceinline__ float sqrt_fast(float v) { float r; asm("sqrt.approx.f32 %0, %1;" : "=f"(r) : "f"(v)); return r; }

template <int TB>
__device__ __forceinline__ void wgmma_n64_h_set(uint32_t (&d)[16], const uint32_t* a, uint64_t desc) {
    asm volatile(
        "{\n.reg .pred p;\nsetp.ne.b32 p, 0, 0;\n"
        "wgmma.mma_async.sync.aligned.m64n64k16.f16.f16.f16 "
        "{%0,%1,%2,%3,%4,%5,%6,%7,%8,%9,%10,%11,%12,%13,%14,%15}, {%16,%17,%18,%19}, %20, p, 1, 1, %21;\n}\n"
        : "=r"(d[0]), "=r"(d[1]), "=r"(d[2]), "=r"(d[3]), "=r"(d[4]), "=r"(d[5]), "=r"(d[6]), "=r"(d[7]), "=r"(d[8]), "=r"(d[9]), "=r"(d[10]), "=r"(d[11]), "=r"(d[12]), "=r"(d[13]), "=r"(d[14]), "=r"(d[15])
        : "r"(a[0]), "r"(a[1]), "r"(a[2]), "r"(a[3]), "l"(desc), "n"(TB));
}
template <int TB>
__device__ __forceinline__ void wgmma_n64_h_acc(uint32_t (&d)[16], const uint32_t* a, uint64_t desc) {
    asm volatile(
        "{\n.reg .pred p;\nsetp.ne.b32 p, 1, 0;\n"
        "wgmma.mma_async.sync.aligned.m64n64k16.f16.f16.f16 "
        "{%0,%1,%2,%3,%4,%5,%6,%7,%8,%9,%10,%11,%12,%13,%14,%15}, {%16,%17,%18,%19}, %20, p, 1, 1, %21;\n}\n"
        : "+r"(d[0]), "+r"(d[1]), "+r"(d[2]), "+r"(d[3]), "+r"(d[4]), "+r"(d[5]), "+r"(d[6]), "+r"(d[7]), "+r"(d[8]), "+r"(d[9]), "+r"(d[10]), "+r"(d[11]), "+r"(d[12]), "+r"(d[13]), "+r"(d[14]), "+r"(d[15])
        : "r"(a[0]), "r"(a[1]), "r"(a[2]), "r"(a[3]), "l"(desc), "n"(TB));
}
__device__ __forceinline__ void wgmma_n64_h_acc_ss(uint32_t (&d)[16], uint64_t adesc, uint64_t desc) {
    asm volatile(
        "{\n.reg .pred p;\nsetp.ne.b32 p, 1, 0;\n"
        "wgmma.mma_async.sync.aligned.m64n64k16.f16.f16.f16 "
        "{%0,%1,%2,%3,%4,%5,%6,%7,%8,%9,%10,%11,%12,%13,%14,%15}, %16, %17, p, 1, 1, 1, 0;\n}\n"
        : "+r"(d[0]), "+r"(d[1]), "+r"(d[2]), "+r"(d[3]), "+r"(d[4]), "+r"(d[5]), "+r"(d[6]), "+r"(d[7]), "+r"(d[8]), "+r"(d[9]), "+r"(d[10]), "+r"(d[11]), "+r"(d[12]), "+r"(d[13]), "+r"(d[14]), "+r"(d[15])
        : "l"(adesc), "l"(desc));
}

struct Params {
    CUtensorMap w1_map, w2_map;
    const __nv_bfloat16* x;
    const __nv_bfloat16* dw;
    const __nv_bfloat16* w1;
    const __nv_bfloat16* gamma;
    const __nv_bfloat16* beta;
    __nv_bfloat16* out;
    Scratch* g;
    uint64_t ydesc64[2];
    uint64_t sel[3];
    uint32_t w1desc, w2desc, ydesc;
};

__device__ __forceinline__ int cta_stride(uint32_t cta) { return cta & 8 ? ROW_BYTES : -ROW_BYTES; }
__device__ __forceinline__ uint32_t cta_tile0(uint32_t cta) {
    return ((cta >> 3) * ROWS_PER_CTA + (cta & 8 ? 0 : ROWS_PER_CTA - 1)) * ROW_BYTES + (cta & 7) * TILE_BYTES;
}

struct Producer {
    uint32_t w[9][6];
    uint32_t xoff[2];
    uint32_t yoff[2][2];
    uint32_t stat, own;
    int lane, warp;
};

struct RowCopy {
    const char* x0;
    char* y0;
    const char* zeros;
    uint32_t cut0, cut1;
    int stride, last;
};
__device__ __forceinline__ RowCopy row_copy(const Params& prm) {
    const uint32_t cta = fresh_cta(), strip = cta & 7, t0 = cta_tile0(cta);
    RowCopy r;
    r.stride = cta_stride(cta);
    r.x0 = (const char*)prm.x + (t0 - r.stride) - 192;
    r.y0 = (char*)prm.out + t0;
    r.zeros = (const char*)prm.g->zero_row;
    r.cut0 = strip == 0 ? 192 : 0;
    r.cut1 = strip == 7 ? 192 : 0;
    r.last = cta - 8 >= NUM_CTAS - 16 ? STEPS - 2 : STEPS - 1;
    return r;
}
__device__ __forceinline__ void issue_row_load(const RowCopy& r, int i, uint32_t slot) {
    const char* src = r.x0 + i * r.stride;
    const uint32_t bar = sb + SM_GO + i * 8, dst = sb + SM_X + slot * SLOT_BYTES;
    expect_tx(bar, XHALF_BYTES - r.cut0);
    bulk_load(dst + r.cut0, src + r.cut0, XHALF_BYTES - r.cut0, bar);
    expect_tx(bar, XHALF_BYTES - r.cut1);
    bulk_load(dst + XHALF_B, src + 32 * 192, XHALF_BYTES - r.cut1, bar);
}

__device__ __forceinline__ float quad_sum(float v) {
    v += __shfl_xor_sync(0xffffffffu, v, 1);
    v += __shfl_xor_sync(0xffffffffu, v, 2);
    return v;
}

__device__ __forceinline__ void load_x(uint32_t (&v)[6][6], const Producer& c, uint32_t row) {
#pragma unroll
    for (int k = 0; k < 6; k++) {
        asm volatile("ld.shared.v4.b32 {%0,%1,%2,%3}, [%4];"
                     : "=r"(v[k][0]), "=r"(v[k][1]), "=r"(v[k][2]), "=r"(v[k][3]) : "r"(row + c.xoff[0] + k * 192));
        asm volatile("ld.shared.v2.b32 {%0,%1}, [%2];" : "=r"(v[k][4]), "=r"(v[k][5]) : "r"(row + c.xoff[1] + k * 192));
    }
}
template <int DY, int STRIDE>
__device__ __forceinline__ void conv_row(uint32_t (&dst)[24], const uint32_t* src, const uint32_t (&v)[6][6], const Producer& c) {
#pragma unroll
    for (int o = 0; o < 4; o++)
#pragma unroll
        for (int u = 0; u < 6; u++)
            dst[o * 6 + u] = bf2_fma(v[o + 2][u], c.w[3 * DY + 2][u], bf2_fma(v[o + 1][u], c.w[3 * DY + 1][u],
                             bf2_fma(v[o][u], c.w[3 * DY][u], STRIDE ? src[o * 6 + u] : src[2 * o + 1])));
}
#define HAND_OVER(name, base, r) asm volatile("mov.b32 " name "%6, %0; mov.b32 " name "%7, %1; mov.b32 " name "%8, %2;\n" \
    "mov.b32 " name "%9, %3; mov.b32 " name "%10, %4; mov.b32 " name "%11, %5;" ::"r"((r)[0]), "r"((r)[1]), "r"((r)[2]), \
    "r"((r)[3]), "r"((r)[4]), "r"((r)[5]), "n"(base), "n"(base + 1), "n"(base + 2), "n"(base + 3), "n"(base + 4), "n"(base + 5))
template <int K> __device__ __forceinline__ void hand_over(const Producer& c, const uint32_t (&B)[24], const uint32_t (&C)[24],
                                                           const uint32_t (&v)[6][6]) {
    HAND_OVER("pw", K * 6, c.w[K]);
    if (K < 6) HAND_OVER("pv", K * 6, v[K % 6]);
    if (K < 4) { HAND_OVER("pb", K * 6, B + K % 4 * 6); HAND_OVER("pc", K * 6, C + K % 4 * 6); }
    if constexpr (K < 8) hand_over<K + 1>(c, B, C, v);
}
__device__ __forceinline__ void produce_tiles(const Producer& c, const Params& prm) {
    asm volatile(
        "{\n"
        ".reg .b32 pa<24>, pq<4>, m<6>, y<6>, rr, mm, t, so, ad, tt, cnt;\n"
        ".reg .b16 xl, xh;\n"
        ".reg .f32 d<4>, us, s0, s1, f0, f1, kq;\n"
        ".reg .pred pt, pf, pr, pw, pl, po, pe;\n"
        "setp.ne.b32 pt, 1, 0; setp.ne.b32 pf, 0, 0; setp.eq.u32 pl, %8, 0; and.b32 tt, %8, 1; setp.ne.u32 po, tt, 0;\n"
        "and.b32 tt, %8, 4; setp.ne.u32 pr, tt, 0; selp.f32 kq, 0f3F802D41, 0f3F7FA57E, pr;\n"
        "mov.u32 t, 0; mov.u32 so, 0;\n"
        "setp.eq.u32 pr, %12, 0;\n"
        "@pr bra.uni RARE;\n"
        "LOOP:\n"
        ASM_TRC("t")
        "fma.rn.bf16x2 pa0, pv0, pw36, pb0; fma.rn.bf16x2 pa1, pv1, pw37, pb1; fma.rn.bf16x2 pa2, pv2, pw38, pb2; fma.rn.bf16x2 pa3, pv3, pw39, pb3; fma.rn.bf16x2 pa4, pv4, pw40, pb4; fma.rn.bf16x2 pa5, pv5, pw41, pb5;\n"
        "fma.rn.bf16x2 pa6, pv6, pw36, pb6; fma.rn.bf16x2 pa7, pv7, pw37, pb7; fma.rn.bf16x2 pa8, pv8, pw38, pb8; fma.rn.bf16x2 pa9, pv9, pw39, pb9; fma.rn.bf16x2 pa10, pv10, pw40, pb10; fma.rn.bf16x2 pa11, pv11, pw41, pb11;\n"
        "fma.rn.bf16x2 pa12, pv12, pw36, pb12; fma.rn.bf16x2 pa13, pv13, pw37, pb13; fma.rn.bf16x2 pa14, pv14, pw38, pb14; fma.rn.bf16x2 pa15, pv15, pw39, pb15; fma.rn.bf16x2 pa16, pv16, pw40, pb16; fma.rn.bf16x2 pa17, pv17, pw41, pb17;\n"
        "fma.rn.bf16x2 pa18, pv18, pw36, pb18; fma.rn.bf16x2 pa19, pv19, pw37, pb19; fma.rn.bf16x2 pa20, pv20, pw38, pb20; fma.rn.bf16x2 pa21, pv21, pw39, pb21; fma.rn.bf16x2 pa22, pv22, pw40, pb22; fma.rn.bf16x2 pa23, pv23, pw41, pb23;\n"
        "fma.rn.bf16x2 pa0, pv6, pw42, pa0; fma.rn.bf16x2 pa1, pv7, pw43, pa1; fma.rn.bf16x2 pa2, pv8, pw44, pa2; fma.rn.bf16x2 pa3, pv9, pw45, pa3; fma.rn.bf16x2 pa4, pv10, pw46, pa4; fma.rn.bf16x2 pa5, pv11, pw47, pa5;\n"
        "fma.rn.bf16x2 pa6, pv12, pw42, pa6; fma.rn.bf16x2 pa7, pv13, pw43, pa7; fma.rn.bf16x2 pa8, pv14, pw44, pa8; fma.rn.bf16x2 pa9, pv15, pw45, pa9; fma.rn.bf16x2 pa10, pv16, pw46, pa10; fma.rn.bf16x2 pa11, pv17, pw47, pa11;\n"
        "fma.rn.bf16x2 pa12, pv18, pw42, pa12; fma.rn.bf16x2 pa13, pv19, pw43, pa13; fma.rn.bf16x2 pa14, pv20, pw44, pa14; fma.rn.bf16x2 pa15, pv21, pw45, pa15; fma.rn.bf16x2 pa16, pv22, pw46, pa16; fma.rn.bf16x2 pa17, pv23, pw47, pa17;\n"
        "fma.rn.bf16x2 pa18, pv24, pw42, pa18; fma.rn.bf16x2 pa19, pv25, pw43, pa19; fma.rn.bf16x2 pa20, pv26, pw44, pa20; fma.rn.bf16x2 pa21, pv27, pw45, pa21; fma.rn.bf16x2 pa22, pv28, pw46, pa22; fma.rn.bf16x2 pa23, pv29, pw47, pa23;\n"
        "fma.rn.bf16x2 pa0, pv12, pw48, pa0; fma.rn.bf16x2 pa1, pv13, pw49, pa1; fma.rn.bf16x2 pa2, pv14, pw50, pa2; fma.rn.bf16x2 pa3, pv15, pw51, pa3; fma.rn.bf16x2 pa4, pv16, pw52, pa4; fma.rn.bf16x2 pa5, pv17, pw53, pa5;\n"
        "fma.rn.bf16x2 pa6, pv18, pw48, pa6; fma.rn.bf16x2 pa7, pv19, pw49, pa7; fma.rn.bf16x2 pa8, pv20, pw50, pa8; fma.rn.bf16x2 pa9, pv21, pw51, pa9; fma.rn.bf16x2 pa10, pv22, pw52, pa10; fma.rn.bf16x2 pa11, pv23, pw53, pa11;\n"
        "fma.rn.bf16x2 pa12, pv24, pw48, pa12; fma.rn.bf16x2 pa13, pv25, pw49, pa13; fma.rn.bf16x2 pa14, pv26, pw50, pa14; fma.rn.bf16x2 pa15, pv27, pw51, pa15; fma.rn.bf16x2 pa16, pv28, pw52, pa16; fma.rn.bf16x2 pa17, pv29, pw53, pa17;\n"
        "fma.rn.bf16x2 pa18, pv30, pw48, pa18; fma.rn.bf16x2 pa19, pv31, pw49, pa19; fma.rn.bf16x2 pa20, pv32, pw50, pa20; fma.rn.bf16x2 pa21, pv33, pw51, pa21; fma.rn.bf16x2 pa22, pv34, pw52, pa22; fma.rn.bf16x2 pa23, pv35, pw53, pa23;\n"
        "mul.rn.bf16x2 pq0, pa0, pa0; fma.rn.bf16x2 pq0, pa1, pa1, pq0; fma.rn.bf16x2 pq0, pa2, pa2, pq0; fma.rn.bf16x2 pq0, pa3, pa3, pq0; fma.rn.bf16x2 pq0, pa4, pa4, pq0; fma.rn.bf16x2 pq0, pa5, pa5, pq0;\n"
        "mul.rn.bf16x2 pq1, pa6, pa6; fma.rn.bf16x2 pq1, pa7, pa7, pq1; fma.rn.bf16x2 pq1, pa8, pa8, pq1; fma.rn.bf16x2 pq1, pa9, pa9, pq1; fma.rn.bf16x2 pq1, pa10, pa10, pq1; fma.rn.bf16x2 pq1, pa11, pa11, pq1;\n"
        "mul.rn.bf16x2 pq2, pa12, pa12; fma.rn.bf16x2 pq2, pa13, pa13, pq2; fma.rn.bf16x2 pq2, pa14, pa14, pq2; fma.rn.bf16x2 pq2, pa15, pa15, pq2; fma.rn.bf16x2 pq2, pa16, pa16, pq2; fma.rn.bf16x2 pq2, pa17, pa17, pq2;\n"
        "mul.rn.bf16x2 pq3, pa18, pa18; fma.rn.bf16x2 pq3, pa19, pa19, pq3; fma.rn.bf16x2 pq3, pa20, pa20, pq3; fma.rn.bf16x2 pq3, pa21, pa21, pq3; fma.rn.bf16x2 pq3, pa22, pa22, pq3; fma.rn.bf16x2 pq3, pa23, pa23, pq3;\n"
        "B0:\n"
        "wgmma.fence.sync.aligned;\n"
        "wgmma.mma_async.sync.aligned.m64n8k16.f32.bf16.bf16 {d0,d1,d2,d3}, {pa0,pa6,pa1,pa7}, %9, pf, 1, 1, 0;\n"
        "wgmma.mma_async.sync.aligned.m64n8k16.f32.bf16.bf16 {d0,d1,d2,d3}, {pa2,pa8,pa3,pa9}, %9, pt, 1, 1, 0;\n"
        "wgmma.mma_async.sync.aligned.m64n8k16.f32.bf16.bf16 {d0,d1,d2,d3}, {pa4,pa10,pa5,pa11}, %9, pt, 1, 1, 0;\n"
        "wgmma.mma_async.sync.aligned.m64n8k16.f32.bf16.bf16 {d0,d1,d2,d3}, {pa12,pa18,pa13,pa19}, %10, pt, 1, 1, 0;\n"
        "wgmma.mma_async.sync.aligned.m64n8k16.f32.bf16.bf16 {d0,d1,d2,d3}, {pa14,pa20,pa15,pa21}, %10, pt, 1, 1, 0;\n"
        "wgmma.mma_async.sync.aligned.m64n8k16.f32.bf16.bf16 {d0,d1,d2,d3}, {pa16,pa22,pa17,pa23}, %10, pt, 1, 1, 0;\n"
        "wgmma.mma_async.sync.aligned.m64n8k16.f32.bf16.bf16 {d0,d1,d2,d3}, {pq0,pq1,pq2,pq3}, %11, pt, 1, 1, 0;\n"
        "wgmma.commit_group.sync.aligned;\n"
        "fence.proxy.async.shared::cta;\n"
        "@pl mbarrier.arrive.shared::cta.b64 _, [t+231544];\n"
        "add.u32 ad, %7, so; ld.shared.f32 us, [ad+4];\n"
        "fma.rn.bf16x2 pb0, pv0, pw18, pc0; fma.rn.bf16x2 pb1, pv1, pw19, pc1; fma.rn.bf16x2 pb2, pv2, pw20, pc2; fma.rn.bf16x2 pb3, pv3, pw21, pc3; fma.rn.bf16x2 pb4, pv4, pw22, pc4; fma.rn.bf16x2 pb5, pv5, pw23, pc5;\n"
        "fma.rn.bf16x2 pb6, pv6, pw18, pc6; fma.rn.bf16x2 pb7, pv7, pw19, pc7; fma.rn.bf16x2 pb8, pv8, pw20, pc8; fma.rn.bf16x2 pb9, pv9, pw21, pc9; fma.rn.bf16x2 pb10, pv10, pw22, pc10; fma.rn.bf16x2 pb11, pv11, pw23, pc11;\n"
        "fma.rn.bf16x2 pb0, pv6, pw24, pb0; fma.rn.bf16x2 pb1, pv7, pw25, pb1; fma.rn.bf16x2 pb2, pv8, pw26, pb2; fma.rn.bf16x2 pb3, pv9, pw27, pb3; fma.rn.bf16x2 pb4, pv10, pw28, pb4; fma.rn.bf16x2 pb5, pv11, pw29, pb5;\n"
        "fma.rn.bf16x2 pb6, pv12, pw24, pb6; fma.rn.bf16x2 pb7, pv13, pw25, pb7; fma.rn.bf16x2 pb8, pv14, pw26, pb8; fma.rn.bf16x2 pb9, pv15, pw27, pb9; fma.rn.bf16x2 pb10, pv16, pw28, pb10; fma.rn.bf16x2 pb11, pv17, pw29, pb11;\n"
        "fma.rn.bf16x2 pb0, pv12, pw30, pb0; fma.rn.bf16x2 pb1, pv13, pw31, pb1; fma.rn.bf16x2 pb2, pv14, pw32, pb2; fma.rn.bf16x2 pb3, pv15, pw33, pb3; fma.rn.bf16x2 pb4, pv16, pw34, pb4; fma.rn.bf16x2 pb5, pv17, pw35, pb5;\n"
        "fma.rn.bf16x2 pb6, pv18, pw30, pb6; fma.rn.bf16x2 pb7, pv19, pw31, pb7; fma.rn.bf16x2 pb8, pv20, pw32, pb8; fma.rn.bf16x2 pb9, pv21, pw33, pb9; fma.rn.bf16x2 pb10, pv22, pw34, pb10; fma.rn.bf16x2 pb11, pv23, pw35, pb11;\n"
        "B1:\n"
        "fma.rn.bf16x2 pb12, pv12, pw18, pc12; fma.rn.bf16x2 pb13, pv13, pw19, pc13; fma.rn.bf16x2 pb14, pv14, pw20, pc14; fma.rn.bf16x2 pb15, pv15, pw21, pc15; fma.rn.bf16x2 pb16, pv16, pw22, pc16; fma.rn.bf16x2 pb17, pv17, pw23, pc17;\n"
        "fma.rn.bf16x2 pb18, pv18, pw18, pc18; fma.rn.bf16x2 pb19, pv19, pw19, pc19; fma.rn.bf16x2 pb20, pv20, pw20, pc20; fma.rn.bf16x2 pb21, pv21, pw21, pc21; fma.rn.bf16x2 pb22, pv22, pw22, pc22; fma.rn.bf16x2 pb23, pv23, pw23, pc23;\n"
        "fma.rn.bf16x2 pb12, pv18, pw24, pb12; fma.rn.bf16x2 pb13, pv19, pw25, pb13; fma.rn.bf16x2 pb14, pv20, pw26, pb14; fma.rn.bf16x2 pb15, pv21, pw27, pb15; fma.rn.bf16x2 pb16, pv22, pw28, pb16; fma.rn.bf16x2 pb17, pv23, pw29, pb17;\n"
        "fma.rn.bf16x2 pb18, pv24, pw24, pb18; fma.rn.bf16x2 pb19, pv25, pw25, pb19; fma.rn.bf16x2 pb20, pv26, pw26, pb20; fma.rn.bf16x2 pb21, pv27, pw27, pb21; fma.rn.bf16x2 pb22, pv28, pw28, pb22; fma.rn.bf16x2 pb23, pv29, pw29, pb23;\n"
        "fma.rn.bf16x2 pb12, pv24, pw30, pb12; fma.rn.bf16x2 pb13, pv25, pw31, pb13; fma.rn.bf16x2 pb14, pv26, pw32, pb14; fma.rn.bf16x2 pb15, pv27, pw33, pb15; fma.rn.bf16x2 pb16, pv28, pw34, pb16; fma.rn.bf16x2 pb17, pv29, pw35, pb17;\n"
        "fma.rn.bf16x2 pb18, pv30, pw30, pb18; fma.rn.bf16x2 pb19, pv31, pw31, pb19; fma.rn.bf16x2 pb20, pv32, pw32, pb20; fma.rn.bf16x2 pb21, pv33, pw33, pb21; fma.rn.bf16x2 pb22, pv34, pw34, pb22; fma.rn.bf16x2 pb23, pv35, pw35, pb23;\n"
        "C0:\n"
        "wgmma.wait_group.sync.aligned 0;\n"
        "selp.f32 s0, d2, d0, po; selp.f32 s1, d3, d1, po;\n"
        "shfl.sync.bfly.b32 f0, s0, 4, 0x1f, 0xffffffff; shfl.sync.bfly.b32 f1, s1, 4, 0x1f, 0xffffffff;\n"
        "fma.rn.bf16x2 pc0, pv0, pw0, ps1; fma.rn.bf16x2 pc1, pv1, pw1, ps1; fma.rn.bf16x2 pc2, pv2, pw2, ps1; fma.rn.bf16x2 pc3, pv3, pw3, ps1; fma.rn.bf16x2 pc4, pv4, pw4, ps1; fma.rn.bf16x2 pc5, pv5, pw5, ps1;\n"
        "fma.rn.bf16x2 pc6, pv6, pw0, ps3; fma.rn.bf16x2 pc7, pv7, pw1, ps3; fma.rn.bf16x2 pc8, pv8, pw2, ps3; fma.rn.bf16x2 pc9, pv9, pw3, ps3; fma.rn.bf16x2 pc10, pv10, pw4, ps3; fma.rn.bf16x2 pc11, pv11, pw5, ps3;\n"
        "fma.rn.bf16x2 pc12, pv12, pw0, ps5; fma.rn.bf16x2 pc13, pv13, pw1, ps5; fma.rn.bf16x2 pc14, pv14, pw2, ps5; fma.rn.bf16x2 pc15, pv15, pw3, ps5; fma.rn.bf16x2 pc16, pv16, pw4, ps5; fma.rn.bf16x2 pc17, pv17, pw5, ps5;\n"
        "fma.rn.bf16x2 pc18, pv18, pw0, ps7; fma.rn.bf16x2 pc19, pv19, pw1, ps7; fma.rn.bf16x2 pc20, pv20, pw2, ps7; fma.rn.bf16x2 pc21, pv21, pw3, ps7; fma.rn.bf16x2 pc22, pv22, pw4, ps7; fma.rn.bf16x2 pc23, pv23, pw5, ps7;\n"
        "fma.rn.bf16x2 pc0, pv6, pw6, pc0; fma.rn.bf16x2 pc1, pv7, pw7, pc1; fma.rn.bf16x2 pc2, pv8, pw8, pc2; fma.rn.bf16x2 pc3, pv9, pw9, pc3; fma.rn.bf16x2 pc4, pv10, pw10, pc4; fma.rn.bf16x2 pc5, pv11, pw11, pc5;\n"
        "fma.rn.bf16x2 pc6, pv12, pw6, pc6; fma.rn.bf16x2 pc7, pv13, pw7, pc7; fma.rn.bf16x2 pc8, pv14, pw8, pc8; fma.rn.bf16x2 pc9, pv15, pw9, pc9; fma.rn.bf16x2 pc10, pv16, pw10, pc10; fma.rn.bf16x2 pc11, pv17, pw11, pc11;\n"
        "fma.rn.bf16x2 pc12, pv18, pw6, pc12; fma.rn.bf16x2 pc13, pv19, pw7, pc13; fma.rn.bf16x2 pc14, pv20, pw8, pc14; fma.rn.bf16x2 pc15, pv21, pw9, pc15; fma.rn.bf16x2 pc16, pv22, pw10, pc16; fma.rn.bf16x2 pc17, pv23, pw11, pc17;\n"
        "fma.rn.bf16x2 pc18, pv24, pw6, pc18; fma.rn.bf16x2 pc19, pv25, pw7, pc19; fma.rn.bf16x2 pc20, pv26, pw8, pc20; fma.rn.bf16x2 pc21, pv27, pw9, pc21; fma.rn.bf16x2 pc22, pv28, pw10, pc22; fma.rn.bf16x2 pc23, pv29, pw11, pc23;\n"
        "fma.rn.bf16x2 pc0, pv12, pw12, pc0; fma.rn.bf16x2 pc1, pv13, pw13, pc1; fma.rn.bf16x2 pc2, pv14, pw14, pc2; fma.rn.bf16x2 pc3, pv15, pw15, pc3; fma.rn.bf16x2 pc4, pv16, pw16, pc4; fma.rn.bf16x2 pc5, pv17, pw17, pc5;\n"
        "fma.rn.bf16x2 pc6, pv18, pw12, pc6; fma.rn.bf16x2 pc7, pv19, pw13, pc7; fma.rn.bf16x2 pc8, pv20, pw14, pc8; fma.rn.bf16x2 pc9, pv21, pw15, pc9; fma.rn.bf16x2 pc10, pv22, pw16, pc10; fma.rn.bf16x2 pc11, pv23, pw17, pc11;\n"
        "fma.rn.bf16x2 pc12, pv24, pw12, pc12; fma.rn.bf16x2 pc13, pv25, pw13, pc13; fma.rn.bf16x2 pc14, pv26, pw14, pc14; fma.rn.bf16x2 pc15, pv27, pw15, pc15; fma.rn.bf16x2 pc16, pv28, pw16, pc16; fma.rn.bf16x2 pc17, pv29, pw17, pc17;\n"
        "fma.rn.bf16x2 pc18, pv30, pw12, pc18; fma.rn.bf16x2 pc19, pv31, pw13, pc19; fma.rn.bf16x2 pc20, pv32, pw14, pc20; fma.rn.bf16x2 pc21, pv33, pw15, pc21; fma.rn.bf16x2 pc22, pv34, pw16, pc22; fma.rn.bf16x2 pc23, pv35, pw17, pc23;\n"
        "add.f32 s0, s0, f0; add.f32 s1, s1, f1; mul.f32 s0, s0, 0fBC2AAAAB;\n"
        "neg.f32 f0, s0; fma.rn.f32 f0, f0, s0, %13; fma.rn.f32 f0, s1, 0f3C2AAAAB, f0; max.f32 f0, f0, %13;\n"
        "rsqrt.approx.ftz.f32 f0, f0; mul.f32 f0, f0, %14; cvt.rn.bf16x2.f32 tt, f0, 0f00000000; mov.b32 f0, tt;\n"
        "mul.f32 f1, s0, kq; mul.f32 f1, f1, f0; cvt.rn.bf16x2.f32 tt, f1, f0; add.f32 us, us, s0; cvt.rn.bf16x2.f32 mm, us, us;\n"
        "add.u32 ad, %7, so; st.shared.v2.b32 [ad], {tt, mm};\n"
        "add.u32 ad, %6, so; ld.shared.v4.b32 {ps0,ps1,ps2,ps3}, [ad]; ld.shared.v4.b32 {ps4,ps5,ps6,ps7}, [ad+16];\n"
        "mbarrier.try_wait.parity.shared::cta.b64 pw, [t+231264], 0;\n"
        "N0:\n"
        "@!pw bra.uni SPIN;\n"
        "BACK:\n"
        "add.u32 ad, %0, so; ld.shared.v4.b32 {pv0,pv1,pv2,pv3}, [ad+0];\n"
        "add.u32 ad, %1, so; ld.shared.v2.b32 {pv4,pv5}, [ad+0];\n"
        "add.u32 ad, %0, so; ld.shared.v4.b32 {pv6,pv7,pv8,pv9}, [ad+192];\n"
        "add.u32 ad, %1, so; ld.shared.v2.b32 {pv10,pv11}, [ad+192];\n"
        "mov.b32 {xl, xh}, ps0; mov.b32 rr, {xl, xl}; mov.b32 mm, {xh, xh}; fma.rn.bf16x2 pa0, pa0, rr, mm; fma.rn.bf16x2 pa1, pa1, rr, mm; fma.rn.bf16x2 pa2, pa2, rr, mm; fma.rn.bf16x2 pa3, pa3, rr, mm; fma.rn.bf16x2 pa4, pa4, rr, mm; fma.rn.bf16x2 pa5, pa5, rr, mm;\n"
        "and.b32 m0, pa0, 0x7fff7fff; and.b32 m1, pa1, 0x7fff7fff; and.b32 m2, pa2, 0x7fff7fff; and.b32 m3, pa3, 0x7fff7fff; and.b32 m4, pa4, 0x7fff7fff; and.b32 m5, pa5, 0x7fff7fff;\n"
        "mad.lo.u32 y0, m0, 7, pa0; mad.lo.u32 y1, m1, 7, pa1; mad.lo.u32 y2, m2, 7, pa2; mad.lo.u32 y3, m3, 7, pa3; mad.lo.u32 y4, m4, 7, pa4; mad.lo.u32 y5, m5, 7, pa5;\n"
        "add.u32 ad, %2, so; st.shared.v4.b32 [ad+0], {y0,y1,y2,y3};\n"
        "add.u32 ad, %4, so; st.shared.v2.b32 [ad+0], {y4,y5};\n"
        "N1:\n"
        "add.u32 ad, %0, so; ld.shared.v4.b32 {pv12,pv13,pv14,pv15}, [ad+384];\n"
        "add.u32 ad, %1, so; ld.shared.v2.b32 {pv16,pv17}, [ad+384];\n"
        "add.u32 ad, %0, so; ld.shared.v4.b32 {pv18,pv19,pv20,pv21}, [ad+576];\n"
        "add.u32 ad, %1, so; ld.shared.v2.b32 {pv22,pv23}, [ad+576];\n"
        "mov.b32 {xl, xh}, ps2; mov.b32 rr, {xl, xl}; mov.b32 mm, {xh, xh}; fma.rn.bf16x2 pa6, pa6, rr, mm; fma.rn.bf16x2 pa7, pa7, rr, mm; fma.rn.bf16x2 pa8, pa8, rr, mm; fma.rn.bf16x2 pa9, pa9, rr, mm; fma.rn.bf16x2 pa10, pa10, rr, mm; fma.rn.bf16x2 pa11, pa11, rr, mm;\n"
        "and.b32 m0, pa6, 0x7fff7fff; and.b32 m1, pa7, 0x7fff7fff; and.b32 m2, pa8, 0x7fff7fff; and.b32 m3, pa9, 0x7fff7fff; and.b32 m4, pa10, 0x7fff7fff; and.b32 m5, pa11, 0x7fff7fff;\n"
        "mad.lo.u32 y0, m0, 7, pa6; mad.lo.u32 y1, m1, 7, pa7; mad.lo.u32 y2, m2, 7, pa8; mad.lo.u32 y3, m3, 7, pa9; mad.lo.u32 y4, m4, 7, pa10; mad.lo.u32 y5, m5, 7, pa11;\n"
        "add.u32 ad, %3, so; st.shared.v4.b32 [ad+0], {y0,y1,y2,y3};\n"
        "add.u32 ad, %5, so; st.shared.v2.b32 [ad+0], {y4,y5};\n"
        "N2:\n"
        "add.u32 ad, %0, so; ld.shared.v4.b32 {pv24,pv25,pv26,pv27}, [ad+768];\n"
        "add.u32 ad, %1, so; ld.shared.v2.b32 {pv28,pv29}, [ad+768];\n"
        "mov.b32 {xl, xh}, ps4; mov.b32 rr, {xl, xl}; mov.b32 mm, {xh, xh}; fma.rn.bf16x2 pa12, pa12, rr, mm; fma.rn.bf16x2 pa13, pa13, rr, mm; fma.rn.bf16x2 pa14, pa14, rr, mm; fma.rn.bf16x2 pa15, pa15, rr, mm; fma.rn.bf16x2 pa16, pa16, rr, mm; fma.rn.bf16x2 pa17, pa17, rr, mm;\n"
        "and.b32 m0, pa12, 0x7fff7fff; and.b32 m1, pa13, 0x7fff7fff; and.b32 m2, pa14, 0x7fff7fff; and.b32 m3, pa15, 0x7fff7fff; and.b32 m4, pa16, 0x7fff7fff; and.b32 m5, pa17, 0x7fff7fff;\n"
        "mad.lo.u32 y0, m0, 7, pa12; mad.lo.u32 y1, m1, 7, pa13; mad.lo.u32 y2, m2, 7, pa14; mad.lo.u32 y3, m3, 7, pa15; mad.lo.u32 y4, m4, 7, pa16; mad.lo.u32 y5, m5, 7, pa17;\n"
        "add.u32 ad, %2, so; st.shared.v4.b32 [ad+2048], {y0,y1,y2,y3};\n"
        "add.u32 ad, %4, so; st.shared.v2.b32 [ad+1024], {y4,y5};\n"
        "N3:\n"
        "add.u32 ad, %0, so; ld.shared.v4.b32 {pv30,pv31,pv32,pv33}, [ad+960];\n"
        "add.u32 ad, %1, so; ld.shared.v2.b32 {pv34,pv35}, [ad+960];\n"
        "mov.b32 {xl, xh}, ps6; mov.b32 rr, {xl, xl}; mov.b32 mm, {xh, xh}; fma.rn.bf16x2 pa18, pa18, rr, mm; fma.rn.bf16x2 pa19, pa19, rr, mm; fma.rn.bf16x2 pa20, pa20, rr, mm; fma.rn.bf16x2 pa21, pa21, rr, mm; fma.rn.bf16x2 pa22, pa22, rr, mm; fma.rn.bf16x2 pa23, pa23, rr, mm;\n"
        "and.b32 m0, pa18, 0x7fff7fff; and.b32 m1, pa19, 0x7fff7fff; and.b32 m2, pa20, 0x7fff7fff; and.b32 m3, pa21, 0x7fff7fff; and.b32 m4, pa22, 0x7fff7fff; and.b32 m5, pa23, 0x7fff7fff;\n"
        "mad.lo.u32 y0, m0, 7, pa18; mad.lo.u32 y1, m1, 7, pa19; mad.lo.u32 y2, m2, 7, pa20; mad.lo.u32 y3, m3, 7, pa21; mad.lo.u32 y4, m4, 7, pa22; mad.lo.u32 y5, m5, 7, pa23;\n"
        "add.u32 ad, %3, so; st.shared.v4.b32 [ad+2048], {y0,y1,y2,y3};\n"
        "add.u32 ad, %5, so; st.shared.v2.b32 [ad+1024], {y4,y5};\n"
        "add.u32 so, so, 26624; setp.eq.u32 pr, so, 79872; selp.u32 so, 0, so, pr;\n"
        "add.u32 t, t, 8; setp.lt.u32 pe, t, 256;\n"
        "@pe bra.uni LOOP;\n"
        "bra.uni DONE;\n"
        "SPIN: mov.u32 cnt, 0;\n"
        "SPINL:\n"
        "mbarrier.try_wait.parity.shared::cta.b64 pw, [t+231264], 0;\n"
        "@pw bra.uni BACK;\n"
        "add.u32 cnt, cnt, 1; setp.lt.u32 pw, cnt, 0x100000;\n"
        "@pw bra.uni SPINL;\n"
        "trap;\n"
        "RARE:\n"
        "ld.volatile.shared.u32 tt, [%6];\n"
        "mov.b32 pa0, tt; mov.b32 pa1, tt; mov.b32 pa2, tt; mov.b32 pa3, tt; mov.b32 pa4, tt; mov.b32 pa5, tt; mov.b32 pa6, tt; mov.b32 pa7, tt; mov.b32 pa8, tt; mov.b32 pa9, tt; mov.b32 pa10, tt; mov.b32 pa11, tt;\n"
        "mov.b32 pa12, tt; mov.b32 pa13, tt; mov.b32 pa14, tt; mov.b32 pa15, tt; mov.b32 pa16, tt; mov.b32 pa17, tt; mov.b32 pa18, tt; mov.b32 pa19, tt; mov.b32 pa20, tt; mov.b32 pa21, tt; mov.b32 pa22, tt; mov.b32 pa23, tt;\n"
        "mov.b32 pb0, tt; mov.b32 pb1, tt; mov.b32 pb2, tt; mov.b32 pb3, tt; mov.b32 pb4, tt; mov.b32 pb5, tt; mov.b32 pb6, tt; mov.b32 pb7, tt; mov.b32 pb8, tt; mov.b32 pb9, tt; mov.b32 pb10, tt; mov.b32 pb11, tt;\n"
        "mov.b32 pb12, tt; mov.b32 pb13, tt; mov.b32 pb14, tt; mov.b32 pb15, tt; mov.b32 pb16, tt; mov.b32 pb17, tt; mov.b32 pb18, tt; mov.b32 pb19, tt; mov.b32 pb20, tt; mov.b32 pb21, tt; mov.b32 pb22, tt; mov.b32 pb23, tt;\n"
        "mov.b32 pc0, tt; mov.b32 pc1, tt; mov.b32 pc2, tt; mov.b32 pc3, tt; mov.b32 pc4, tt; mov.b32 pc5, tt; mov.b32 pc6, tt; mov.b32 pc7, tt; mov.b32 pc8, tt; mov.b32 pc9, tt; mov.b32 pc10, tt; mov.b32 pc11, tt;\n"
        "mov.b32 pc12, tt; mov.b32 pc13, tt; mov.b32 pc14, tt; mov.b32 pc15, tt; mov.b32 pc16, tt; mov.b32 pc17, tt; mov.b32 pc18, tt; mov.b32 pc19, tt; mov.b32 pc20, tt; mov.b32 pc21, tt; mov.b32 pc22, tt; mov.b32 pc23, tt;\n"
        "mov.b32 ps0, tt; mov.b32 ps1, tt; mov.b32 ps2, tt; mov.b32 ps3, tt; mov.b32 ps4, tt; mov.b32 ps5, tt; mov.b32 ps6, tt; mov.b32 ps7, tt; mov.b32 pq0, tt; mov.b32 pq1, tt; mov.b32 pq2, tt; mov.b32 pq3, tt;\n"
        "ld.volatile.shared.v2.b32 {pw1, pw0}, [%6]; xor.b32 tt, tt, pw1;\n"
        "ld.volatile.shared.v2.b32 {pw3, pw2}, [%6]; xor.b32 tt, tt, pw3;\n"
        "ld.volatile.shared.v2.b32 {pw5, pw4}, [%6]; xor.b32 tt, tt, pw5;\n"
        "ld.volatile.shared.v2.b32 {pw7, pw6}, [%6]; xor.b32 tt, tt, pw7;\n"
        "ld.volatile.shared.v2.b32 {pw9, pw8}, [%6]; xor.b32 tt, tt, pw9;\n"
        "ld.volatile.shared.v2.b32 {pw11, pw10}, [%6]; xor.b32 tt, tt, pw11;\n"
        "ld.volatile.shared.v2.b32 {pw13, pw12}, [%6]; xor.b32 tt, tt, pw13;\n"
        "ld.volatile.shared.v2.b32 {pw15, pw14}, [%6]; xor.b32 tt, tt, pw15;\n"
        "ld.volatile.shared.v2.b32 {pw17, pw16}, [%6]; xor.b32 tt, tt, pw17;\n"
        "ld.volatile.shared.v2.b32 {pw19, pw18}, [%6]; xor.b32 tt, tt, pw19;\n"
        "ld.volatile.shared.v2.b32 {pw21, pw20}, [%6]; xor.b32 tt, tt, pw21;\n"
        "ld.volatile.shared.v2.b32 {pw23, pw22}, [%6]; xor.b32 tt, tt, pw23;\n"
        "ld.volatile.shared.v2.b32 {pw25, pw24}, [%6]; xor.b32 tt, tt, pw25;\n"
        "ld.volatile.shared.v2.b32 {pw27, pw26}, [%6]; xor.b32 tt, tt, pw27;\n"
        "ld.volatile.shared.v2.b32 {pw29, pw28}, [%6]; xor.b32 tt, tt, pw29;\n"
        "ld.volatile.shared.v2.b32 {pw31, pw30}, [%6]; xor.b32 tt, tt, pw31;\n"
        "ld.volatile.shared.v2.b32 {pw33, pw32}, [%6]; xor.b32 tt, tt, pw33;\n"
        "ld.volatile.shared.v2.b32 {pw35, pw34}, [%6]; xor.b32 tt, tt, pw35;\n"
        "ld.volatile.shared.v2.b32 {pw37, pw36}, [%6]; xor.b32 tt, tt, pw37;\n"
        "ld.volatile.shared.v2.b32 {pw39, pw38}, [%6]; xor.b32 tt, tt, pw39;\n"
        "ld.volatile.shared.v2.b32 {pw41, pw40}, [%6]; xor.b32 tt, tt, pw41;\n"
        "ld.volatile.shared.v2.b32 {pw43, pw42}, [%6]; xor.b32 tt, tt, pw43;\n"
        "ld.volatile.shared.v2.b32 {pw45, pw44}, [%6]; xor.b32 tt, tt, pw45;\n"
        "ld.volatile.shared.v2.b32 {pw47, pw46}, [%6]; xor.b32 tt, tt, pw47;\n"
        "ld.volatile.shared.v2.b32 {pw49, pw48}, [%6]; xor.b32 tt, tt, pw49;\n"
        "ld.volatile.shared.v2.b32 {pw51, pw50}, [%6]; xor.b32 tt, tt, pw51;\n"
        "ld.volatile.shared.v2.b32 {pw53, pw52}, [%6]; xor.b32 tt, tt, pw53;\n"
        "mov.b32 us, tt; setp.ne.u32 pw, %15, 7;\n"
        "wgmma.fence.sync.aligned;\n"
        "setp.eq.u32 pr, %15, 1000; @pr bra.uni B0;\n"
        "setp.eq.u32 pr, %15, 1001; @pr bra.uni B1;\n"
        "setp.eq.u32 pr, %15, 1002; @pr bra.uni C0;\n"
        "setp.eq.u32 pr, %15, 1003; @pr bra.uni N0;\n"
        "setp.eq.u32 pr, %15, 1004; @pr bra.uni N1;\n"
        "setp.eq.u32 pr, %15, 1005; @pr bra.uni N2;\n"
        "setp.eq.u32 pr, %15, 1006; @pr bra.uni N3;\n"
        "trap;\n"
        "DONE:\n"
        ASM_TRC("t")
        "fence.proxy.async.shared::cta;\n"
        "@pl mbarrier.arrive.shared::cta.b64 _, [t+231544];\n"
        "}\n"
        :: "r"(sb + SM_X + c.xoff[0]), "r"(sb + SM_X + c.xoff[1]), "r"(sb + SM_Y1 + c.yoff[0][0]), "r"(sb + SM_Y1 + c.yoff[0][1]),
           "r"(sb + SM_Y1 + c.yoff[1][0]), "r"(sb + SM_Y1 + c.yoff[1][1]), "r"(c.stat), "r"(c.own), "r"(c.lane),
           "l"(prm.sel[0]), "l"(prm.sel[1]), "l"(prm.sel[2]), "r"(prm.ydesc), "f"(LN_EPS_SCALED), "f"(RSTD_SCALE), "r"(prm.w1desc)
        : "memory");
}

__device__ __forceinline__ void produce(const Producer& c, const Params& prm) {
    uint32_t B[24], C[24];
    const RowCopy rc = row_copy(prm);
    uint32_t st[8];
    uint32_t v[6][6];
    {
        uint32_t ws[6];
#pragma unroll
        for (int u = 0; u < 6; u++) {
            ws[u] = c.w[0][u];
#pragma unroll
            for (int t = 1; t < 9; t++) ws[u] = bf2_add(ws[u], c.w[t][u]);
        }
        SMARK(2);
        mbar_wait_c<0>(sb + SM_GO);
        SMARK(3);
        lds128(v[0], sb + SM_X + c.xoff[0] + 2 * 192);
        asm volatile("ld.shared.v2.b32 {%0,%1}, [%2];" : "=r"(v[0][4]), "=r"(v[0][5]) : "r"(sb + SM_X + c.xoff[1] + 2 * 192));
        const uint32_t p = bf2_add(bf2_fma(v[0][2], ws[2], bf2_fma(v[0][1], ws[1], bf2_mul(v[0][0], ws[0]))),
                                   bf2_fma(v[0][5], ws[5], bf2_fma(v[0][4], ws[4], bf2_mul(v[0][3], ws[3]))));
        float e = quad_sum(bf_lo(p) + bf_hi(p));
        e = (e + __shfl_xor_sync(0xffffffffu, e, 4)) * (-1.0f / CH);
        st[1] = st[3] = st[5] = st[7] = pack_bf2(e, e);
#pragma unroll
        for (int k = 0; k < NX; k++) sts32(c.own + k * SLOT_BYTES + 4, st[1]);
#pragma unroll
        for (int r = 0; r < 24; r++) C[r] = 0;
    }
#pragma unroll 1
    for (int i = loop_init<0>();; i++) {
        mbar_wait_c<0>(sb + SM_GO + i * 8);
        SMARK(4 + i);
        load_x(v, c, sb + SM_X + i * SLOT_BYTES);
        fence_async_smem();
        if (c.warp == i) {
            named_sync(6 + i, 128);
            issue_row_load(rc, i + NX, i);
        } else {
            asm volatile("bar.arrive %0, 128;" ::"r"(6 + i) : "memory");
        }
        if (i == 2) break;
        conv_row<1, 1>(B, C, v, c);
        conv_row<0, 0>(C, st, v, c);
    }
    asm volatile(".reg .b32 pw<54>, pb<24>, pc<24>, pv<36>, ps<8>;");
    hand_over<0>(c, B, C, v);
    asm volatile("mov.b32 ps1, %0; mov.b32 ps3, %1; mov.b32 ps5, %2; mov.b32 ps7, %3;" ::"r"(st[1]), "r"(st[3]), "r"(st[5]), "r"(st[7]));
    SMARK(7);
    produce_tiles(c, prm);
    mbar_arrive_if(sb + SM_YFULL + ROWS_PER_CTA * 8, c.lane == 0);
}

struct Duty {
    const char* g;
    const char* zeros;
    long long step;
    uint32_t s, bytes;
    int end, zero;
};
__device__ __forceinline__ Duty make_duty(const Params& prm, int wg, int w) {
    const RowCopy rc = row_copy(prm);
    Duty d;
    d.g = (w == 2 ? rc.y0 : rc.x0 + (w == 0 ? rc.cut0 : w == 1 ? 32 * 192 : 192)) +
          (wg + (w == 2 ? 0 : w < 2 ? 2 * NX : 2 * NX + L2_AHEAD)) * rc.stride;
    d.step = NX * rc.stride;
    d.s = wg * SLOT_BYTES + (w == 2 ? sb + SM_Y1 : sb + SM_X + (w == 0 ? rc.cut0 : XHALF_B));
    d.bytes = w >= 2 ? TILE_BYTES : XHALF_BYTES - (w == 0 ? rc.cut0 : rc.cut1);
    d.end = w == 2 ? ROWS_PER_CTA : w < 2 ? STEPS + 1 - 2 * NX : rc.last + 1 - 2 * NX - L2_AHEAD;
    d.zero = rc.last + 1 - 2 * NX;
    d.zeros = rc.zeros;
    return d;
}

static_assert(sb + SM_BAR == 230800 && sb + SM_YFULL == 231552 && sb + SM_GO == 231240 && SLOT_BYTES == 26624 && sb + SM_GAMMA == 229248 &&
              SM_BETA == SM_GAMMA + 768 && SM_W2 == 73728 && sb + SM_BUF3 == 187392 && BAR_W2 == 9 && BAR_W1B == 10, "layout");
__device__ __forceinline__ void consume(float (&acc)[2][2], uint32_t w1t, uint32_t yd, uint32_t wd, uint32_t own_slot, const Duty& d,
                                        uint32_t role, uint32_t lane, const Params& prm) {
    asm volatile(
        "{\n"
        ".reg .b32 z<32>, w<44>, p, a<4>, lo<2>, hi<2>, t, g, q<4>, dl, dh, n, so, c, tt, cnt, f0, f1;\n"
        ".reg .b16 xl, xh, xr;\n"
        ".reg .b64 ds<6>, wd, gp, src;\n"
        ".reg .pred pt, pf, pr, pw, pl, pe;\n"
        "setp.ne.b32 pt, 1, 0; setp.ne.b32 pf, 0, 0; setp.eq.u32 pl, %15, 0;\n"
        "mov.b32 c, 0x40D940D9;\n"
        "ldmatrix.sync.aligned.m8n8.x4.trans.shared.b16 {w0,w1,w2,w3}, [%4+0];\n"
        "ldmatrix.sync.aligned.m8n8.x4.trans.shared.b16 {w4,w5,w6,w7}, [%4+2048];\n"
        "ldmatrix.sync.aligned.m8n8.x4.trans.shared.b16 {w8,w9,w10,w11}, [%4+4096];\n"
        "ldmatrix.sync.aligned.m8n8.x4.trans.shared.b16 {w12,w13,w14,w15}, [%4+6144];\n"
        "ldmatrix.sync.aligned.m8n8.x4.trans.shared.b16 {w16,w17,w18,w19}, [%4+8192];\n"
        "ldmatrix.sync.aligned.m8n8.x4.trans.shared.b16 {w20,w21,w22,w23}, [%4+10240];\n"
        "shl.b32 f0, w0, 16; and.b32 f1, w0, 0xffff0000; cvt.rn.f16x2.f32 w0, f1, f0; shl.b32 f0, w1, 16; and.b32 f1, w1, 0xffff0000; cvt.rn.f16x2.f32 w1, f1, f0; shl.b32 f0, w2, 16; and.b32 f1, w2, 0xffff0000; cvt.rn.f16x2.f32 w2, f1, f0; shl.b32 f0, w3, 16; and.b32 f1, w3, 0xffff0000; cvt.rn.f16x2.f32 w3, f1, f0;\n"
        "stmatrix.sync.aligned.m8n8.x4.trans.shared.b16 [%4+0], {w0,w1,w2,w3};\n"
        "shl.b32 f0, w4, 16; and.b32 f1, w4, 0xffff0000; cvt.rn.f16x2.f32 w4, f1, f0; shl.b32 f0, w5, 16; and.b32 f1, w5, 0xffff0000; cvt.rn.f16x2.f32 w5, f1, f0; shl.b32 f0, w6, 16; and.b32 f1, w6, 0xffff0000; cvt.rn.f16x2.f32 w6, f1, f0; shl.b32 f0, w7, 16; and.b32 f1, w7, 0xffff0000; cvt.rn.f16x2.f32 w7, f1, f0;\n"
        "stmatrix.sync.aligned.m8n8.x4.trans.shared.b16 [%4+2048], {w4,w5,w6,w7};\n"
        "shl.b32 f0, w8, 16; and.b32 f1, w8, 0xffff0000; cvt.rn.f16x2.f32 w8, f1, f0; shl.b32 f0, w9, 16; and.b32 f1, w9, 0xffff0000; cvt.rn.f16x2.f32 w9, f1, f0; shl.b32 f0, w10, 16; and.b32 f1, w10, 0xffff0000; cvt.rn.f16x2.f32 w10, f1, f0; shl.b32 f0, w11, 16; and.b32 f1, w11, 0xffff0000; cvt.rn.f16x2.f32 w11, f1, f0;\n"
        "stmatrix.sync.aligned.m8n8.x4.trans.shared.b16 [%4+4096], {w8,w9,w10,w11};\n"
        "shl.b32 f0, w12, 16; and.b32 f1, w12, 0xffff0000; cvt.rn.f16x2.f32 w12, f1, f0; shl.b32 f0, w13, 16; and.b32 f1, w13, 0xffff0000; cvt.rn.f16x2.f32 w13, f1, f0; shl.b32 f0, w14, 16; and.b32 f1, w14, 0xffff0000; cvt.rn.f16x2.f32 w14, f1, f0; shl.b32 f0, w15, 16; and.b32 f1, w15, 0xffff0000; cvt.rn.f16x2.f32 w15, f1, f0;\n"
        "stmatrix.sync.aligned.m8n8.x4.trans.shared.b16 [%4+6144], {w12,w13,w14,w15};\n"
        "shl.b32 f0, w16, 16; and.b32 f1, w16, 0xffff0000; cvt.rn.f16x2.f32 w16, f1, f0; shl.b32 f0, w17, 16; and.b32 f1, w17, 0xffff0000; cvt.rn.f16x2.f32 w17, f1, f0; shl.b32 f0, w18, 16; and.b32 f1, w18, 0xffff0000; cvt.rn.f16x2.f32 w18, f1, f0; shl.b32 f0, w19, 16; and.b32 f1, w19, 0xffff0000; cvt.rn.f16x2.f32 w19, f1, f0;\n"
        "stmatrix.sync.aligned.m8n8.x4.trans.shared.b16 [%4+8192], {w16,w17,w18,w19};\n"
        "shl.b32 f0, w20, 16; and.b32 f1, w20, 0xffff0000; cvt.rn.f16x2.f32 w20, f1, f0; shl.b32 f0, w21, 16; and.b32 f1, w21, 0xffff0000; cvt.rn.f16x2.f32 w21, f1, f0; shl.b32 f0, w22, 16; and.b32 f1, w22, 0xffff0000; cvt.rn.f16x2.f32 w22, f1, f0; shl.b32 f0, w23, 16; and.b32 f1, w23, 0xffff0000; cvt.rn.f16x2.f32 w23, f1, f0;\n"
        "stmatrix.sync.aligned.m8n8.x4.trans.shared.b16 [%4+10240], {w20,w21,w22,w23};\n"
        "mov.u32 tt, 230880; mbarrier.try_wait.parity.shared::cta.b64 pw, [tt], 0;\n"
        "@!pw bra.uni SPINW;\n"
        "BACKW:\n"
        "ldmatrix.sync.aligned.m8n8.x4.trans.shared.b16 {z0,z1,z2,z3}, [%4+22528];\n"
        "ldmatrix.sync.aligned.m8n8.x4.trans.shared.b16 {w24,w25,w26,w27}, [%4+12288];\n"
        "ldmatrix.sync.aligned.m8n8.x4.trans.shared.b16 {w28,w29,w30,w31}, [%4+14336];\n"
        "ldmatrix.sync.aligned.m8n8.x4.trans.shared.b16 {w32,w33,w34,w35}, [%4+16384];\n"
        "ldmatrix.sync.aligned.m8n8.x4.trans.shared.b16 {w36,w37,w38,w39}, [%4+18432];\n"
        "ldmatrix.sync.aligned.m8n8.x4.trans.shared.b16 {w40,w41,w42,w43}, [%4+20480];\n"
        "shl.b32 f0, z0, 16; and.b32 f1, z0, 0xffff0000; cvt.rn.f16x2.f32 z0, f1, f0; shl.b32 f0, z1, 16; and.b32 f1, z1, 0xffff0000; cvt.rn.f16x2.f32 z1, f1, f0; shl.b32 f0, z2, 16; and.b32 f1, z2, 0xffff0000; cvt.rn.f16x2.f32 z2, f1, f0; shl.b32 f0, z3, 16; and.b32 f1, z3, 0xffff0000; cvt.rn.f16x2.f32 z3, f1, f0;\n"
        "stmatrix.sync.aligned.m8n8.x4.trans.shared.b16 [%4+22528], {z0,z1,z2,z3};\n"
        "shl.b32 f0, w24, 16; and.b32 f1, w24, 0xffff0000; cvt.rn.f16x2.f32 w24, f1, f0; shl.b32 f0, w25, 16; and.b32 f1, w25, 0xffff0000; cvt.rn.f16x2.f32 w25, f1, f0; shl.b32 f0, w26, 16; and.b32 f1, w26, 0xffff0000; cvt.rn.f16x2.f32 w26, f1, f0; shl.b32 f0, w27, 16; and.b32 f1, w27, 0xffff0000; cvt.rn.f16x2.f32 w27, f1, f0;\n"
        "stmatrix.sync.aligned.m8n8.x4.trans.shared.b16 [%4+12288], {w24,w25,w26,w27};\n"
        "shl.b32 f0, w28, 16; and.b32 f1, w28, 0xffff0000; cvt.rn.f16x2.f32 w28, f1, f0; shl.b32 f0, w29, 16; and.b32 f1, w29, 0xffff0000; cvt.rn.f16x2.f32 w29, f1, f0; shl.b32 f0, w30, 16; and.b32 f1, w30, 0xffff0000; cvt.rn.f16x2.f32 w30, f1, f0; shl.b32 f0, w31, 16; and.b32 f1, w31, 0xffff0000; cvt.rn.f16x2.f32 w31, f1, f0;\n"
        "stmatrix.sync.aligned.m8n8.x4.trans.shared.b16 [%4+14336], {w28,w29,w30,w31};\n"
        "shl.b32 f0, w32, 16; and.b32 f1, w32, 0xffff0000; cvt.rn.f16x2.f32 w32, f1, f0; shl.b32 f0, w33, 16; and.b32 f1, w33, 0xffff0000; cvt.rn.f16x2.f32 w33, f1, f0; shl.b32 f0, w34, 16; and.b32 f1, w34, 0xffff0000; cvt.rn.f16x2.f32 w34, f1, f0; shl.b32 f0, w35, 16; and.b32 f1, w35, 0xffff0000; cvt.rn.f16x2.f32 w35, f1, f0;\n"
        "stmatrix.sync.aligned.m8n8.x4.trans.shared.b16 [%4+16384], {w32,w33,w34,w35};\n"
        "shl.b32 f0, w36, 16; and.b32 f1, w36, 0xffff0000; cvt.rn.f16x2.f32 w36, f1, f0; shl.b32 f0, w37, 16; and.b32 f1, w37, 0xffff0000; cvt.rn.f16x2.f32 w37, f1, f0; shl.b32 f0, w38, 16; and.b32 f1, w38, 0xffff0000; cvt.rn.f16x2.f32 w38, f1, f0; shl.b32 f0, w39, 16; and.b32 f1, w39, 0xffff0000; cvt.rn.f16x2.f32 w39, f1, f0;\n"
        "stmatrix.sync.aligned.m8n8.x4.trans.shared.b16 [%4+18432], {w36,w37,w38,w39};\n"
        "shl.b32 f0, w40, 16; and.b32 f1, w40, 0xffff0000; cvt.rn.f16x2.f32 w40, f1, f0; shl.b32 f0, w41, 16; and.b32 f1, w41, 0xffff0000; cvt.rn.f16x2.f32 w41, f1, f0; shl.b32 f0, w42, 16; and.b32 f1, w42, 0xffff0000; cvt.rn.f16x2.f32 w42, f1, f0; shl.b32 f0, w43, 16; and.b32 f1, w43, 0xffff0000; cvt.rn.f16x2.f32 w43, f1, f0;\n"
        "stmatrix.sync.aligned.m8n8.x4.trans.shared.b16 [%4+20480], {w40,w41,w42,w43};\n"
        "fence.proxy.async.shared::cta;\n"
        ASM_SMARK
        "mov.b32 p, 0; mov.b32 t, 0; mov.b32 g, 0; mov.b32 a0, 0; mov.b32 a1, 0; mov.b32 a2, 0; mov.b32 a3, 0; mov.b32 lo0, 0; mov.b32 lo1, 0; mov.b32 hi0, 0; mov.b32 hi1, 0; mov.b32 q0, 0; mov.b32 q1, 0; mov.b32 q2, 0; mov.b32 q3, 0;\n"
        "mov.b32 z16, 0; mov.b32 z17, 0; mov.b32 z18, 0; mov.b32 z19, 0; mov.b32 z20, 0; mov.b32 z21, 0; mov.b32 z22, 0; mov.b32 z23, 0; mov.b32 z24, 0; mov.b32 z25, 0; mov.b32 z26, 0; mov.b32 z27, 0; mov.b32 z28, 0; mov.b32 z29, 0; mov.b32 z30, 0; mov.b32 z31, 0;\n"
        "mov.f32 %0, 0f00000000; mov.f32 %1, 0f00000000; mov.f32 %2, 0f00000000; mov.f32 %3, 0f00000000;\n"
        "mov.u32 n, 0; mov.u32 so, 0; mov.b64 gp, %8; mov.b64 wd, {%6, 0x40000040};\n"
        "mov.b64 ds0, %20; add.s64 ds1, ds0, 2; add.s64 ds2, ds0, 4; add.s64 ds3, ds0, 6; mov.b64 ds4, %21; add.s64 ds5, ds4, 2;\n"
        "mbarrier.try_wait.parity.shared::cta.b64 pw, [n+231552], 0;\n"
        "@!pw bra.uni SPIN0;\n"
        "BACK0:\n"
        ASM_TS
        "wgmma.fence.sync.aligned;\n"
        "wgmma.mma_async.sync.aligned.m64n64k16.f16.f16.f16 {z0,z1,z2,z3,z4,z5,z6,z7,z8,z9,z10,z11,z12,z13,z14,z15}, {w0,w1,w2,w3}, ds0, pf, 1, 1, 0;\n"
        "wgmma.mma_async.sync.aligned.m64n64k16.f16.f16.f16 {z0,z1,z2,z3,z4,z5,z6,z7,z8,z9,z10,z11,z12,z13,z14,z15}, {w4,w5,w6,w7}, ds1, pt, 1, 1, 0;\n"
        "wgmma.mma_async.sync.aligned.m64n64k16.f16.f16.f16 {z0,z1,z2,z3,z4,z5,z6,z7,z8,z9,z10,z11,z12,z13,z14,z15}, {w8,w9,w10,w11}, ds2, pt, 1, 1, 0;\n"
        "wgmma.fence.sync.aligned;\n"
        "wgmma.mma_async.sync.aligned.m64n64k16.f16.f16.f16 {z0,z1,z2,z3,z4,z5,z6,z7,z8,z9,z10,z11,z12,z13,z14,z15}, {w12,w13,w14,w15}, ds3, pt, 1, 1, 0;\n"
        "wgmma.mma_async.sync.aligned.m64n64k16.f16.f16.f16 {z0,z1,z2,z3,z4,z5,z6,z7,z8,z9,z10,z11,z12,z13,z14,z15}, {w16,w17,w18,w19}, ds4, pt, 1, 1, 0;\n"
        "wgmma.mma_async.sync.aligned.m64n64k16.f16.f16.f16 {z0,z1,z2,z3,z4,z5,z6,z7,z8,z9,z10,z11,z12,z13,z14,z15}, {w20,w21,w22,w23}, ds5, pt, 1, 1, 0;\n"
        "wgmma.commit_group.sync.aligned;\n"
        "setp.eq.u32 pr, so, %7;\n"
        "@pr bra.uni DUTY;\n"
        "TOP:\n"
        ASM_TRC("n")
        "wgmma.wait_group.sync.aligned 0;\n"
        "mov.b32 {xl, xh}, a2; tanh.approx.f16 xr, xh; cvt.u32.u16 hi0, xr; mul.rn.f16x2 a3, z31, p; fma.rn.f16x2 p, z0, z0, c; fma.rn.f16x2 q3, g, g, q3; fma.rn.f16x2 g, z28, t, z28; prmt.b32 t, lo1, hi1, 0x5410; tanh.approx.f16 xr, xl; cvt.u32.u16 lo0, xr;\n"
        "B31:\n"
        "mov.b32 {xl, xh}, a3; tanh.approx.f16 xr, xh; cvt.u32.u16 hi1, xr; mul.rn.f16x2 a0, z0, p; fma.rn.f16x2 p, z1, z1, c; fma.rn.f16x2 q2, g, g, q2; fma.rn.f16x2 g, z29, t, z29; prmt.b32 t, lo0, hi0, 0x5410; tanh.approx.f16 xr, xl; cvt.u32.u16 lo1, xr;\n"
        "B0:\n"
        "mov.b32 {xl, xh}, a0; tanh.approx.f16 xr, xh; cvt.u32.u16 hi0, xr; mul.rn.f16x2 a1, z1, p; fma.rn.f16x2 p, z2, z2, c; fma.rn.f16x2 q3, g, g, q3; fma.rn.f16x2 g, z30, t, z30; prmt.b32 t, lo1, hi1, 0x5410; tanh.approx.f16 xr, xl; cvt.u32.u16 lo0, xr;\n"
        "B1:\n"
        "mov.b32 {xl, xh}, a1; tanh.approx.f16 xr, xh; cvt.u32.u16 hi1, xr; mul.rn.f16x2 a2, z2, p; fma.rn.f16x2 p, z3, z3, c; fma.rn.f16x2 q2, g, g, q2; fma.rn.f16x2 g, z31, t, z31; prmt.b32 t, lo0, hi0, 0x5410; tanh.approx.f16 xr, xl; cvt.u32.u16 lo1, xr;\n"
        "B2:\n"
        "wgmma.fence.sync.aligned;\n"
        "wgmma.mma_async.sync.aligned.m64n64k16.f16.f16.f16 {z16,z17,z18,z19,z20,z21,z22,z23,z24,z25,z26,z27,z28,z29,z30,z31}, {w24,w25,w26,w27}, ds0, pf, 1, 1, 0;\n"
        "wgmma.mma_async.sync.aligned.m64n64k16.f16.f16.f16 {z16,z17,z18,z19,z20,z21,z22,z23,z24,z25,z26,z27,z28,z29,z30,z31}, {w28,w29,w30,w31}, ds1, pt, 1, 1, 0;\n"
        "wgmma.mma_async.sync.aligned.m64n64k16.f16.f16.f16 {z16,z17,z18,z19,z20,z21,z22,z23,z24,z25,z26,z27,z28,z29,z30,z31}, {w32,w33,w34,w35}, ds2, pt, 1, 1, 0;\n"
        "mov.b32 {xl, xh}, a2; tanh.approx.f16 xr, xh; cvt.u32.u16 hi0, xr; mul.rn.f16x2 a3, z3, p; fma.rn.f16x2 p, z4, z4, c; fma.rn.f16x2 q3, g, g, q3; fma.rn.f16x2 g, z0, t, z0; prmt.b32 t, lo1, hi1, 0x5410; tanh.approx.f16 xr, xl; cvt.u32.u16 lo0, xr;\n"
        "B3:\n"
        "mov.b32 {xl, xh}, a3; tanh.approx.f16 xr, xh; cvt.u32.u16 hi1, xr; mul.rn.f16x2 a0, z4, p; fma.rn.f16x2 p, z5, z5, c; fma.rn.f16x2 q0, g, g, q0; fma.rn.f16x2 g, z1, t, z1; prmt.b32 t, lo0, hi0, 0x5410; tanh.approx.f16 xr, xl; cvt.u32.u16 lo1, xr;\n"
        "B4:\n"
        "mov.b32 {xl, xh}, a0; tanh.approx.f16 xr, xh; cvt.u32.u16 hi0, xr; mul.rn.f16x2 a1, z5, p; fma.rn.f16x2 p, z6, z6, c; fma.rn.f16x2 q1, g, g, q1; fma.rn.f16x2 g, z2, t, z2; prmt.b32 t, lo1, hi1, 0x5410; tanh.approx.f16 xr, xl; cvt.u32.u16 lo0, xr;\n"
        "B5:\n"
        "wgmma.fence.sync.aligned;\n"
        "wgmma.mma_async.sync.aligned.m64n64k16.f16.f16.f16 {z16,z17,z18,z19,z20,z21,z22,z23,z24,z25,z26,z27,z28,z29,z30,z31}, {w36,w37,w38,w39}, ds3, pt, 1, 1, 0;\n"
        "wgmma.mma_async.sync.aligned.m64n64k16.f16.f16.f16 {z16,z17,z18,z19,z20,z21,z22,z23,z24,z25,z26,z27,z28,z29,z30,z31}, {w40,w41,w42,w43}, ds4, pt, 1, 1, 0;\n"
        "wgmma.mma_async.sync.aligned.m64n64k16.f16.f16.f16 {z16,z17,z18,z19,z20,z21,z22,z23,z24,z25,z26,z27,z28,z29,z30,z31}, wd, ds5, pt, 1, 1, 1, 0;\n"
        "wgmma.commit_group.sync.aligned;\n"
        "mov.b32 {xl, xh}, a1; tanh.approx.f16 xr, xh; cvt.u32.u16 hi1, xr; mul.rn.f16x2 a2, z6, p; fma.rn.f16x2 p, z7, z7, c; fma.rn.f16x2 q0, g, g, q0; fma.rn.f16x2 g, z3, t, z3; prmt.b32 t, lo0, hi0, 0x5410; tanh.approx.f16 xr, xl; cvt.u32.u16 lo1, xr;\n"
        "B6:\n"
        "add.u32 so, so, 26624; setp.eq.u32 pr, so, 79872; selp.u32 so, 0, so, pr;\n"
        "mov.b32 {xl, xh}, a2; tanh.approx.f16 xr, xh; cvt.u32.u16 hi0, xr; mul.rn.f16x2 a3, z7, p; fma.rn.f16x2 p, z8, z8, c; fma.rn.f16x2 q1, g, g, q1; fma.rn.f16x2 g, z4, t, z4; prmt.b32 t, lo1, hi1, 0x5410; tanh.approx.f16 xr, xl; cvt.u32.u16 lo0, xr;\n"
        "B7:\n"
        "shr.u32 tt, so, 4;\n"
        "mov.b64 {dl, dh}, ds0; add.u32 dl, tt, 74816; mov.b64 ds0, {dl, dh}; mov.b64 {dl, dh}, ds1; add.u32 dl, tt, 74818; mov.b64 ds1, {dl, dh}; mov.b64 {dl, dh}, ds2; add.u32 dl, tt, 74820; mov.b64 ds2, {dl, dh};\n"
        "mov.b32 {xl, xh}, a3; tanh.approx.f16 xr, xh; cvt.u32.u16 hi1, xr; mul.rn.f16x2 a0, z8, p; fma.rn.f16x2 p, z9, z9, c; fma.rn.f16x2 q0, g, g, q0; fma.rn.f16x2 g, z5, t, z5; prmt.b32 t, lo0, hi0, 0x5410; tanh.approx.f16 xr, xl; cvt.u32.u16 lo1, xr;\n"
        "B8:\n"
        "shr.u32 tt, so, 4;\n"
        "mov.b64 {dl, dh}, ds3; add.u32 dl, tt, 74822; mov.b64 ds3, {dl, dh}; mov.b64 {dl, dh}, ds4; add.u32 dl, tt, 75328; mov.b64 ds4, {dl, dh}; mov.b64 {dl, dh}, ds5; add.u32 dl, tt, 75330; mov.b64 ds5, {dl, dh};\n"
        "mov.b32 {xl, xh}, a0; tanh.approx.f16 xr, xh; cvt.u32.u16 hi0, xr; mul.rn.f16x2 a1, z9, p; fma.rn.f16x2 p, z10, z10, c; fma.rn.f16x2 q1, g, g, q1; fma.rn.f16x2 g, z6, t, z6; prmt.b32 t, lo1, hi1, 0x5410; tanh.approx.f16 xr, xl; cvt.u32.u16 lo0, xr;\n"
        "B9:\n"
        "mov.b32 {xl, xh}, a1; tanh.approx.f16 xr, xh; cvt.u32.u16 hi1, xr; mul.rn.f16x2 a2, z10, p; fma.rn.f16x2 p, z11, z11, c; fma.rn.f16x2 q0, g, g, q0; fma.rn.f16x2 g, z7, t, z7; prmt.b32 t, lo0, hi0, 0x5410; tanh.approx.f16 xr, xl; cvt.u32.u16 lo1, xr;\n"
        "B10:\n"
        "mov.b32 {xl, xh}, a2; tanh.approx.f16 xr, xh; cvt.u32.u16 hi0, xr; mul.rn.f16x2 a3, z11, p; fma.rn.f16x2 p, z12, z12, c; fma.rn.f16x2 q1, g, g, q1; fma.rn.f16x2 g, z8, t, z8; prmt.b32 t, lo1, hi1, 0x5410; tanh.approx.f16 xr, xl; cvt.u32.u16 lo0, xr;\n"
        "B11:\n"
        "mov.b32 {xl, xh}, a3; tanh.approx.f16 xr, xh; cvt.u32.u16 hi1, xr; mul.rn.f16x2 a0, z12, p; fma.rn.f16x2 p, z13, z13, c; fma.rn.f16x2 q0, g, g, q0; fma.rn.f16x2 g, z9, t, z9; prmt.b32 t, lo0, hi0, 0x5410; tanh.approx.f16 xr, xl; cvt.u32.u16 lo1, xr;\n"
        "B12:\n"
        "mov.b32 {xl, xh}, a0; tanh.approx.f16 xr, xh; cvt.u32.u16 hi0, xr; mul.rn.f16x2 a1, z13, p; fma.rn.f16x2 p, z14, z14, c; fma.rn.f16x2 q1, g, g, q1; fma.rn.f16x2 g, z10, t, z10; prmt.b32 t, lo1, hi1, 0x5410; tanh.approx.f16 xr, xl; cvt.u32.u16 lo0, xr;\n"
        "B13:\n"
        "mov.b32 {xl, xh}, a1; tanh.approx.f16 xr, xh; cvt.u32.u16 hi1, xr; mul.rn.f16x2 a2, z14, p; fma.rn.f16x2 p, z15, z15, c; fma.rn.f16x2 q0, g, g, q0; fma.rn.f16x2 g, z11, t, z11; prmt.b32 t, lo0, hi0, 0x5410; tanh.approx.f16 xr, xl; cvt.u32.u16 lo1, xr;\n"
        "B14:\n"
        "wgmma.wait_group.sync.aligned 0;\n"
        "cp.async.bulk.wait_group.read 0;\n"
        "@pl mbarrier.arrive.shared::cta.b64 _, [n+231288];\n"
        "mov.b32 {xl, xh}, a2; tanh.approx.f16 xr, xh; cvt.u32.u16 hi0, xr; mul.rn.f16x2 a3, z15, p; fma.rn.f16x2 p, z16, z16, c; fma.rn.f16x2 q1, g, g, q1; fma.rn.f16x2 g, z12, t, z12; prmt.b32 t, lo1, hi1, 0x5410; tanh.approx.f16 xr, xl; cvt.u32.u16 lo0, xr;\n"
        "B15:\n"
        "mov.b32 {xl, xh}, a3; tanh.approx.f16 xr, xh; cvt.u32.u16 hi1, xr; mul.rn.f16x2 a0, z16, p; fma.rn.f16x2 p, z17, z17, c; fma.rn.f16x2 q0, g, g, q0; fma.rn.f16x2 g, z13, t, z13; prmt.b32 t, lo0, hi0, 0x5410; tanh.approx.f16 xr, xl; cvt.u32.u16 lo1, xr;\n"
        "B16:\n"
        "mbarrier.try_wait.parity.shared::cta.b64 pw, [n+231560], 0;\n"
        "mov.b32 {xl, xh}, a0; tanh.approx.f16 xr, xh; cvt.u32.u16 hi0, xr; mul.rn.f16x2 a1, z17, p; fma.rn.f16x2 p, z18, z18, c; fma.rn.f16x2 q1, g, g, q1; fma.rn.f16x2 g, z14, t, z14; prmt.b32 t, lo1, hi1, 0x5410; tanh.approx.f16 xr, xl; cvt.u32.u16 lo0, xr;\n"
        "B17:\n"
        "mov.b32 {xl, xh}, a1; tanh.approx.f16 xr, xh; cvt.u32.u16 hi1, xr; mul.rn.f16x2 a2, z18, p; fma.rn.f16x2 p, z19, z19, c; fma.rn.f16x2 q0, g, g, q0; fma.rn.f16x2 g, z15, t, z15; prmt.b32 t, lo0, hi0, 0x5410; tanh.approx.f16 xr, xl; cvt.u32.u16 lo1, xr;\n"
        "B18:\n"
        "@!pw bra.uni SPIN;\n"
        "BACK:\n"
        "wgmma.fence.sync.aligned;\n"
        "wgmma.mma_async.sync.aligned.m64n64k16.f16.f16.f16 {z0,z1,z2,z3,z4,z5,z6,z7,z8,z9,z10,z11,z12,z13,z14,z15}, {w0,w1,w2,w3}, ds0, pf, 1, 1, 0;\n"
        "wgmma.mma_async.sync.aligned.m64n64k16.f16.f16.f16 {z0,z1,z2,z3,z4,z5,z6,z7,z8,z9,z10,z11,z12,z13,z14,z15}, {w4,w5,w6,w7}, ds1, pt, 1, 1, 0;\n"
        "wgmma.mma_async.sync.aligned.m64n64k16.f16.f16.f16 {z0,z1,z2,z3,z4,z5,z6,z7,z8,z9,z10,z11,z12,z13,z14,z15}, {w8,w9,w10,w11}, ds2, pt, 1, 1, 0;\n"
        "mov.b32 {xl, xh}, a2; tanh.approx.f16 xr, xh; cvt.u32.u16 hi0, xr; mul.rn.f16x2 a3, z19, p; fma.rn.f16x2 p, z20, z20, c; fma.rn.f16x2 q1, g, g, q1; fma.rn.f16x2 g, z16, t, z16; prmt.b32 t, lo1, hi1, 0x5410; tanh.approx.f16 xr, xl; cvt.u32.u16 lo0, xr;\n"
        "B19:\n"
        "mov.b32 {xl, xh}, a3; tanh.approx.f16 xr, xh; cvt.u32.u16 hi1, xr; mul.rn.f16x2 a0, z20, p; fma.rn.f16x2 p, z21, z21, c; fma.rn.f16x2 q2, g, g, q2; fma.rn.f16x2 g, z17, t, z17; prmt.b32 t, lo0, hi0, 0x5410; tanh.approx.f16 xr, xl; cvt.u32.u16 lo1, xr;\n"
        "B20:\n"
        "mov.b32 {xl, xh}, a0; tanh.approx.f16 xr, xh; cvt.u32.u16 hi0, xr; mul.rn.f16x2 a1, z21, p; fma.rn.f16x2 p, z22, z22, c; fma.rn.f16x2 q3, g, g, q3; fma.rn.f16x2 g, z18, t, z18; prmt.b32 t, lo1, hi1, 0x5410; tanh.approx.f16 xr, xl; cvt.u32.u16 lo0, xr;\n"
        "B21:\n"
        "wgmma.fence.sync.aligned;\n"
        "wgmma.mma_async.sync.aligned.m64n64k16.f16.f16.f16 {z0,z1,z2,z3,z4,z5,z6,z7,z8,z9,z10,z11,z12,z13,z14,z15}, {w12,w13,w14,w15}, ds3, pt, 1, 1, 0;\n"
        "wgmma.mma_async.sync.aligned.m64n64k16.f16.f16.f16 {z0,z1,z2,z3,z4,z5,z6,z7,z8,z9,z10,z11,z12,z13,z14,z15}, {w16,w17,w18,w19}, ds4, pt, 1, 1, 0;\n"
        "wgmma.mma_async.sync.aligned.m64n64k16.f16.f16.f16 {z0,z1,z2,z3,z4,z5,z6,z7,z8,z9,z10,z11,z12,z13,z14,z15}, {w20,w21,w22,w23}, ds5, pt, 1, 1, 0;\n"
        "wgmma.commit_group.sync.aligned;\n"
        "mov.b32 {xl, xh}, a1; tanh.approx.f16 xr, xh; cvt.u32.u16 hi1, xr; mul.rn.f16x2 a2, z22, p; fma.rn.f16x2 p, z23, z23, c; fma.rn.f16x2 q2, g, g, q2; fma.rn.f16x2 g, z19, t, z19; prmt.b32 t, lo0, hi0, 0x5410; tanh.approx.f16 xr, xl; cvt.u32.u16 lo1, xr;\n"
        "B22:\n"
        "mov.b32 {xl, xh}, a2; tanh.approx.f16 xr, xh; cvt.u32.u16 hi0, xr; mul.rn.f16x2 a3, z23, p; fma.rn.f16x2 p, z24, z24, c; fma.rn.f16x2 q3, g, g, q3; fma.rn.f16x2 g, z20, t, z20; prmt.b32 t, lo1, hi1, 0x5410; tanh.approx.f16 xr, xl; cvt.u32.u16 lo0, xr;\n"
        "B23:\n"
        "mov.b32 {xl, xh}, a3; tanh.approx.f16 xr, xh; cvt.u32.u16 hi1, xr; mul.rn.f16x2 a0, z24, p; fma.rn.f16x2 p, z25, z25, c; fma.rn.f16x2 q2, g, g, q2; fma.rn.f16x2 g, z21, t, z21; prmt.b32 t, lo0, hi0, 0x5410; tanh.approx.f16 xr, xl; cvt.u32.u16 lo1, xr;\n"
        "B24:\n"
        "mov.b32 {xl, xh}, a0; tanh.approx.f16 xr, xh; cvt.u32.u16 hi0, xr; mul.rn.f16x2 a1, z25, p; fma.rn.f16x2 p, z26, z26, c; fma.rn.f16x2 q3, g, g, q3; fma.rn.f16x2 g, z22, t, z22; prmt.b32 t, lo1, hi1, 0x5410; tanh.approx.f16 xr, xl; cvt.u32.u16 lo0, xr;\n"
        "B25:\n"
        "mov.b32 {xl, xh}, a1; tanh.approx.f16 xr, xh; cvt.u32.u16 hi1, xr; mul.rn.f16x2 a2, z26, p; fma.rn.f16x2 p, z27, z27, c; fma.rn.f16x2 q2, g, g, q2; fma.rn.f16x2 g, z23, t, z23; prmt.b32 t, lo0, hi0, 0x5410; tanh.approx.f16 xr, xl; cvt.u32.u16 lo1, xr;\n"
        "B26:\n"
        "mov.b32 {xl, xh}, a2; tanh.approx.f16 xr, xh; cvt.u32.u16 hi0, xr; mul.rn.f16x2 a3, z27, p; fma.rn.f16x2 p, z28, z28, c; fma.rn.f16x2 q3, g, g, q3; fma.rn.f16x2 g, z24, t, z24; prmt.b32 t, lo1, hi1, 0x5410; tanh.approx.f16 xr, xl; cvt.u32.u16 lo0, xr;\n"
        "B27:\n"
        "add.u32 n, n, 8; setp.lt.u32 pe, n, 256; setp.ne.and.u32 pe, so, %7, pe;\n"
        "mov.b32 {xl, xh}, a3; tanh.approx.f16 xr, xh; cvt.u32.u16 hi1, xr; mul.rn.f16x2 a0, z28, p; fma.rn.f16x2 p, z29, z29, c; fma.rn.f16x2 q2, g, g, q2; fma.rn.f16x2 g, z25, t, z25; prmt.b32 t, lo0, hi0, 0x5410; tanh.approx.f16 xr, xl; cvt.u32.u16 lo1, xr;\n"
        "B28:\n"
        "mov.b32 {xl, xh}, a0; tanh.approx.f16 xr, xh; cvt.u32.u16 hi0, xr; mul.rn.f16x2 a1, z29, p; fma.rn.f16x2 p, z30, z30, c; fma.rn.f16x2 q3, g, g, q3; fma.rn.f16x2 g, z26, t, z26; prmt.b32 t, lo1, hi1, 0x5410; tanh.approx.f16 xr, xl; cvt.u32.u16 lo0, xr;\n"
        "B29:\n"
        "mov.b32 {xl, xh}, a1; tanh.approx.f16 xr, xh; cvt.u32.u16 hi1, xr; mul.rn.f16x2 a2, z30, p; fma.rn.f16x2 p, z31, z31, c; fma.rn.f16x2 q2, g, g, q2; fma.rn.f16x2 g, z27, t, z27; prmt.b32 t, lo0, hi0, 0x5410; tanh.approx.f16 xr, xl; cvt.u32.u16 lo1, xr;\n"
        "@pe bra.uni TOP;\n"
        "setp.lt.u32 pe, n, 256;\n"
        "@pe bra.uni DUTY;\n"
        "bra.uni DONE;\n"
        "SPINW: mov.u32 cnt, 0;\n"
        "SPINWL:\n"
        "mov.u32 tt, 230880; mbarrier.try_wait.parity.shared::cta.b64 pw, [tt], 0;\n"
        "@pw bra.uni BACKW;\n"
        "add.u32 cnt, cnt, 1; setp.lt.u32 pw, cnt, 0x100000;\n"
        "@pw bra.uni SPINWL;\n"
        "trap;\n"
        "SPIN0: mov.u32 cnt, 0;\n"
        "SPIN0L:\n"
        "mbarrier.try_wait.parity.shared::cta.b64 pw, [n+231552], 0;\n"
        "@pw bra.uni BACK0;\n"
        "add.u32 cnt, cnt, 1; setp.lt.u32 pw, cnt, 0x100000;\n"
        "@pw bra.uni SPIN0L;\n"
        "trap;\n"
        "SPIN: mov.u32 cnt, 0;\n"
        "SPINL:\n"
        "mbarrier.try_wait.parity.shared::cta.b64 pw, [n+231560], 0;\n"
        "@pw bra.uni BACK;\n"
        "add.u32 cnt, cnt, 1; setp.lt.u32 pw, cnt, 0x100000;\n"
        "@pw bra.uni SPINL;\n"
        "trap;\n"
        "DUTY:\n"
        "setp.ge.s32 pr, n, %11;\n"
        "@pr bra.uni FLUSH;\n"
        "setp.ge.u32 pr, %13, 2;\n"
        "@pr bra.uni ROLE2;\n"
        "setp.ge.s32 pr, n, %12; selp.b64 src, %14, gp, pr; add.u32 tt, n, 231288;\n"
        "elect.sync _|pr, 0xffffffff;\n"
        "@pr mbarrier.arrive.expect_tx.shared::cta.b64 _, [tt], %10;\n"
        "@pr cp.async.bulk.shared::cluster.global.mbarrier::complete_tx::bytes [%9], [src], %10, [tt];\n"
        "bra.uni FLUSH;\n"
        "ROLE2:\n"
        "setp.eq.u32 pr, %13, 3;\n"
        "@pr bra.uni ROLE3;\n"
        "setp.ne.s32 pr, n, 248;\n"
        "@pr bra.uni PARK;\n"
        "cp.async.bulk.wait_group 0;\n"
        "sub.s64 src, gp, %16; mov.u32 tt, 230824; mov.u32 cnt, 187392;\n"
        "elect.sync _|pr, 0xffffffff;\n"
        "@pr mbarrier.arrive.expect_tx.shared::cta.b64 _, [tt], 12288;\n"
        "@pr cp.async.bulk.shared::cluster.global.mbarrier::complete_tx::bytes [cnt], [src], 12288, [tt];\n"
        "PARK:\n"
        "elect.sync _|pr, 0xffffffff;\n"
        "@pr cp.async.bulk.global.shared::cta.bulk_group [gp], [%9], 12288;\n"
        "@pr cp.async.bulk.commit_group;\n"
        "bra.uni FLUSH;\n"
        "ROLE3:\n"
        "setp.ne.s32 pr, n, 64;\n"
        "@pr bra.uni AHEAD;\n"
        "mov.u32 tt, 230872;\n"
        "elect.sync _|pr, 0xffffffff;\n"
        "@pr mbarrier.arrive.expect_tx.shared::cta.b64 _, [tt], 75264;\n"
        "mov.u32 cnt, 229248; @pr cp.async.bulk.shared::cluster.global.mbarrier::complete_tx::bytes [cnt], [%18], 768, [tt];\n"
        "mov.u32 cnt, 230016; @pr cp.async.bulk.shared::cluster.global.mbarrier::complete_tx::bytes [cnt], [%19], 768, [tt];\n"
        "mov.u32 cnt, 74752; @pr cp.async.bulk.tensor.2d.shared::cluster.global.mbarrier::complete_tx::bytes [cnt], [%17, {0, 0}], [tt];\n"
        "mov.u32 cnt, 87040; @pr cp.async.bulk.tensor.2d.shared::cluster.global.mbarrier::complete_tx::bytes [cnt], [%17, {0, 192}], [tt];\n"
        "mov.u32 cnt, 99328; @pr cp.async.bulk.tensor.2d.shared::cluster.global.mbarrier::complete_tx::bytes [cnt], [%17, {32, 0}], [tt];\n"
        "mov.u32 cnt, 111616; @pr cp.async.bulk.tensor.2d.shared::cluster.global.mbarrier::complete_tx::bytes [cnt], [%17, {32, 192}], [tt];\n"
        "mov.u32 cnt, 123904; @pr cp.async.bulk.tensor.2d.shared::cluster.global.mbarrier::complete_tx::bytes [cnt], [%17, {64, 0}], [tt];\n"
        "mov.u32 cnt, 136192; @pr cp.async.bulk.tensor.2d.shared::cluster.global.mbarrier::complete_tx::bytes [cnt], [%17, {64, 192}], [tt];\n"
        "AHEAD:\n"
        "elect.sync _|pr, 0xffffffff;\n"
        "@pr cp.async.bulk.prefetch.L2.global [gp], 12288;\n"
        "FLUSH:\n"
        "add.s64 gp, gp, %16;\n"
        "mov.b32 {xl, xh}, q0; cvt.f32.f16 f0, xl; cvt.f32.f16 f1, xh; add.f32 f0, f0, f1; add.f32 %0, %0, f0; mov.b32 q0, 0;\n"
        "mov.b32 {xl, xh}, q1; cvt.f32.f16 f0, xl; cvt.f32.f16 f1, xh; add.f32 f0, f0, f1; add.f32 %1, %1, f0; mov.b32 q1, 0;\n"
        "mov.b32 {xl, xh}, q2; cvt.f32.f16 f0, xl; cvt.f32.f16 f1, xh; add.f32 f0, f0, f1; add.f32 %2, %2, f0; mov.b32 q2, 0;\n"
        "mov.b32 {xl, xh}, q3; cvt.f32.f16 f0, xl; cvt.f32.f16 f1, xh; add.f32 f0, f0, f1; add.f32 %3, %3, f0; mov.b32 q3, 0;\n"
        "setp.ne.u32 pr, %5, 0;\n"
        "@pr bra.uni TOP;\n"
        "wgmma.wait_group.sync.aligned 0;\n"
        "wgmma.fence.sync.aligned;\n"
        "ld.volatile.shared.v2.b32 {lo0, hi0}, [so]; xor.b32 f0, f0, lo0;\n"
        "ld.volatile.shared.v2.b32 {lo1, hi1}, [so]; xor.b32 f0, f0, lo1;\n"
        "ld.volatile.shared.v2.b32 {q1, a0}, [so]; xor.b32 f0, f0, q1;\n"
        "ld.volatile.shared.v2.b32 {q2, a1}, [so]; xor.b32 f0, f0, q2;\n"
        "ld.volatile.shared.v2.b32 {q3, a2}, [so]; xor.b32 f0, f0, q3;\n"
        "ld.volatile.shared.v2.b32 {q0, a3}, [so]; xor.b32 f0, f0, q0;\n"
        "ld.volatile.shared.v2.b32 {t, g}, [so]; xor.b32 f0, f0, t;\n"
        "ld.volatile.shared.v2.b32 {p, f1}, [so]; xor.b32 f0, f0, p;\n"
        "add.f32 %0, %0, f0;\n"
        "setp.eq.u32 pr, n, 1000; @pr bra.uni B31;\n"
        "setp.eq.u32 pr, n, 1001; @pr bra.uni B0;\n"
        "setp.eq.u32 pr, n, 1002; @pr bra.uni B1;\n"
        "setp.eq.u32 pr, n, 1003; @pr bra.uni B2;\n"
        "setp.eq.u32 pr, n, 1004; @pr bra.uni B3;\n"
        "setp.eq.u32 pr, n, 1005; @pr bra.uni B4;\n"
        "setp.eq.u32 pr, n, 1006; @pr bra.uni B5;\n"
        "setp.eq.u32 pr, n, 1007; @pr bra.uni B6;\n"
        "setp.eq.u32 pr, n, 1008; @pr bra.uni B7;\n"
        "setp.eq.u32 pr, n, 1009; @pr bra.uni B8;\n"
        "setp.eq.u32 pr, n, 1010; @pr bra.uni B9;\n"
        "setp.eq.u32 pr, n, 1011; @pr bra.uni B10;\n"
        "setp.eq.u32 pr, n, 1012; @pr bra.uni B11;\n"
        "setp.eq.u32 pr, n, 1013; @pr bra.uni B12;\n"
        "setp.eq.u32 pr, n, 1014; @pr bra.uni B13;\n"
        "setp.eq.u32 pr, n, 1015; @pr bra.uni B14;\n"
        "setp.eq.u32 pr, n, 1016; @pr bra.uni B15;\n"
        "setp.eq.u32 pr, n, 1017; @pr bra.uni B16;\n"
        "setp.eq.u32 pr, n, 1018; @pr bra.uni B17;\n"
        "setp.eq.u32 pr, n, 1019; @pr bra.uni B18;\n"
        "setp.eq.u32 pr, n, 1020; @pr bra.uni B19;\n"
        "setp.eq.u32 pr, n, 1021; @pr bra.uni B20;\n"
        "setp.eq.u32 pr, n, 1022; @pr bra.uni B21;\n"
        "setp.eq.u32 pr, n, 1023; @pr bra.uni B22;\n"
        "setp.eq.u32 pr, n, 1024; @pr bra.uni B23;\n"
        "setp.eq.u32 pr, n, 1025; @pr bra.uni B24;\n"
        "setp.eq.u32 pr, n, 1026; @pr bra.uni B25;\n"
        "setp.eq.u32 pr, n, 1027; @pr bra.uni B26;\n"
        "setp.eq.u32 pr, n, 1028; @pr bra.uni B27;\n"
        "setp.eq.u32 pr, n, 1029; @pr bra.uni B28;\n"
        "setp.eq.u32 pr, n, 1030; @pr bra.uni B29;\n"
        "setp.eq.u32 pr, n, 1031; @pr bra.uni TOP;\n"
        "trap;\n"
        "DONE:\n"
        ASM_TRC("n")
        "mov.b32 {xl, xh}, a2; tanh.approx.f16 xr, xh; cvt.u32.u16 hi0, xr; mul.rn.f16x2 a3, z31, p; fma.rn.f16x2 q3, g, g, q3; fma.rn.f16x2 g, z28, t, z28; prmt.b32 t, lo1, hi1, 0x5410; tanh.approx.f16 xr, xl; cvt.u32.u16 lo0, xr;\n"
        "mov.b32 {xl, xh}, a3; tanh.approx.f16 xr, xh; cvt.u32.u16 hi1, xr; fma.rn.f16x2 q2, g, g, q2; fma.rn.f16x2 g, z29, t, z29; prmt.b32 t, lo0, hi0, 0x5410; tanh.approx.f16 xr, xl; cvt.u32.u16 lo1, xr;\n"
        "fma.rn.f16x2 q3, g, g, q3; fma.rn.f16x2 g, z30, t, z30; prmt.b32 t, lo1, hi1, 0x5410;\n"
        "fma.rn.f16x2 q2, g, g, q2; fma.rn.f16x2 g, z31, t, z31;\n"
        "fma.rn.f16x2 q3, g, g, q3;\n"
        "mov.b32 {xl, xh}, q0; cvt.f32.f16 f0, xl; cvt.f32.f16 f1, xh; add.f32 f0, f0, f1; add.f32 %0, %0, f0; mov.b32 q0, 0;\n"
        "mov.b32 {xl, xh}, q1; cvt.f32.f16 f0, xl; cvt.f32.f16 f1, xh; add.f32 f0, f0, f1; add.f32 %1, %1, f0; mov.b32 q1, 0;\n"
        "mov.b32 {xl, xh}, q2; cvt.f32.f16 f0, xl; cvt.f32.f16 f1, xh; add.f32 f0, f0, f1; add.f32 %2, %2, f0; mov.b32 q2, 0;\n"
        "mov.b32 {xl, xh}, q3; cvt.f32.f16 f0, xl; cvt.f32.f16 f1, xh; add.f32 f0, f0, f1; add.f32 %3, %3, f0; mov.b32 q3, 0;\n"
        "wgmma.wait_group.sync.aligned 0;\n"
        "}\n"
        : "=f"(acc[0][0]), "=f"(acc[0][1]), "=f"(acc[1][0]), "=f"(acc[1][1])
        : "r"(w1t), "r"(yd), "r"(wd), "r"(own_slot), "l"(d.g), "r"(d.s), "r"(d.bytes), "r"(8 * d.end), "r"(8 * d.zero), "r"(role),
          "l"(d.zeros), "r"(lane), "l"(d.step), "l"(&prm.w2_map), "l"(prm.gamma), "l"(prm.beta), "l"(prm.ydesc64[0]), "l"(prm.ydesc64[1])
        : "memory");
}
template <int M, bool LAST_SMEM = true>
__device__ __forceinline__ void gemm1_t(uint32_t (&d)[16], const uint32_t* wa, uint32_t yd, uint32_t wd) {
    wg_fence();
    wgmma_n64_h_set<0>(d, wa, desc<1024, 1>(yd, 0));
#pragma unroll
    for (int kk = 1; kk < (LAST_SMEM ? 5 : 6); kk++)
        wgmma_n64_h_acc<0>(d, wa + kk * 4, kk < 4 ? desc<1024, 1>(yd, kk * 32) : desc<512, 2>(yd, 8192 + (kk - 4) * 32));
    if (LAST_SMEM) wgmma_n64_h_acc_ss(d, desc<1024, 1>(wd, M * 12288), desc<512, 2>(yd, 8192 + 32));
    wg_commit();
}

__device__ __forceinline__ void gelu_sumsq_f(const uint32_t (&d)[16], float (&acc)[2]) {
#pragma unroll
    for (int r = 0; r < 16; r++) {
        float lo, hi;
        h2_unpack(gelu2(d[r]), lo, hi);
        acc[r & 1] = fmaf(lo, lo, acc[r & 1]);
        acc[r & 1] = fmaf(hi, hi, acc[r & 1]);
    }
}
__device__ __forceinline__ void load_w1t(uint32_t (&wa)[2][24], int wg, int w, int lane) {
#pragma unroll
    for (int m = 0; m < 2; m++)
#pragma unroll
        for (int kk = 0; kk < 5; kk++) {
            const int q = lane >> 3, c = 16 * kk + 8 * (q >> 1) + (lane & 7), ck = 2 * w + (q & 1);
            ldsm4_t(wa[m] + kk * 4, sb + SM_W1 + (2 * wg + m) * 12288 + c * 128 + ((ck ^ (c & 7)) * 16));
        }
}
__device__ __forceinline__ unsigned long long* acc_word(const Params& prm, uint32_t epoch, uint32_t e) {
    return &prm.g->acc[epoch & 1][(e >> 2) * 32 + (e & 3)];
}
__device__ __forceinline__ void publish_fast(const Params& prm, const float (&acc)[2][2], uint32_t epoch, int wg, int w, int lane) {
    const bool m = lane & 2, h = lane & 1;
    const float a = (m ? acc[1][0] : acc[0][0]) + __shfl_xor_sync(0xffffffffu, m ? acc[0][0] : acc[1][0], 2);
    const float b = (m ? acc[1][1] : acc[0][1]) + __shfl_xor_sync(0xffffffffu, m ? acc[0][1] : acc[1][1], 2);
    const float v = (h ? b : a) + __shfl_xor_sync(0xffffffffu, h ? a : b, 1);
    const unsigned long long q = (__float2ull_rn(fminf(v, ACC_LIMIT) * 0x1p16f) << 8) + 1;
    asm volatile("red.relaxed.gpu.global.add.u64 [%0], %1;"
                 ::"l"(acc_word(prm, epoch, 128 * wg + 32 * (lane & 2) + 16 * w + (lane >> 2) + 8 * (lane & 1))), "l"(q) : "memory");
}
__device__ __forceinline__ float collect_fast(const unsigned long long* word) {
    unsigned long long v;
    asm volatile(
        "{\n.reg .pred p;\n.reg .u32 n, lo, hi;\nmov.u32 n, 0;\n"
        "POLL:\nld.relaxed.gpu.global.u64 %0, [%1];\nmov.b64 {lo, hi}, %0;\nand.b32 lo, lo, 255;\n"
        "setp.eq.u32 p, lo, %2;\nvote.sync.all.pred p, p, 0xffffffff;\n@p bra.uni POLL_DONE;\n"
        "add.u32 n, n, 1;\nsetp.lt.u32 p, n, 0x400000;\n@p bra.uni POLL;\ntrap;\nPOLL_DONE:\n}\n"
        : "=l"(v) : "l"(word), "n"(NUM_CTAS) : "memory");
    return __ull2float_rn(v >> 8) * 0x1p-16f;
}
__device__ __forceinline__ void publish_sums(const float (&acc)[2][2], float* sums, unsigned int* counter, int wg, int w, int lane) {
#pragma unroll
    for (int m = 0; m < 2; m++)
#pragma unroll
        for (int h = 0; h < 2; h++) {
            const float v = quad_sum(acc[m][h]);
            if ((lane & 3) == 0) atomicAdd(sums + 64 * (2 * wg + m) + 16 * w + (lane >> 2) + 8 * h, v);
        }
    named_sync(1, 384);
    if (fresh_tid() == 0) asm volatile("red.release.gpu.global.add.u32 [%0], 1;" ::"l"(counter) : "memory");
}
__device__ __forceinline__ void grid_wait(const unsigned int* counter, unsigned int target) {
    if (fresh_tid() == 0) {
        unsigned int v, spins = 0;
        do {
            asm volatile("ld.acquire.gpu.global.u32 %0, [%1];" : "=r"(v) : "l"(counter) : "memory");
            if (++spins > (1u << 22)) __trap();
        } while ((int)(v - target) < 0);
    }
    __syncthreads();
}

struct Pass2 {
    uint32_t wg;
    uint32_t off;
    int step;
    uint32_t xs;
    uint32_t a_offs, xs_offs, bias_addr;
    uint32_t w;
};

static_assert(sb + SM_BAR + BAR_ROWS * 8 == 231208 && BAR_STAT == BAR_ROWS + 2 && sb + SM_RED + RED_SCALE * 4 == 230792, "layout");
static_assert(sb + SM_BAR + BAR_Y2FULL * 8 == 230800 && sb + SM_BAR + BAR_XSFULL * 8 == 230832, "layout");
#define PASS2_STATE ".reg .b32 qa<24>, qz<32>, o<24>, g<16>, p<2>, a<4>, lo<2>, hi<2>, h<2>, osc;"
__device__ __forceinline__ void pass2_start(const Pass2& c, const Params& prm) {
    asm volatile(
        "{\n"
        ".reg .b32 t<2>, c, tt, ad, cnt, ybar;\n"
        ".reg .b16 xl, xh, xr;\n"
        ".reg .b64 w1d, dt;\n"
        ".reg .pred pt, pf, pw;\n"
        "setp.ne.b32 pt, 1, 0; setp.ne.b32 pf, 0, 0; mov.b32 c, 0x40D940D9; mov.b64 w1d, {%1, 0x40000040}; mad.lo.u32 ybar, %2, 8, 230800;\n"
        "mbarrier.try_wait.parity.shared::cta.b64 pw, [ybar], 0;\n"
        "@!pw bra.uni SPINY0;\n"
        "BACKY0:\n"
        "and.b32 t0, %5, 0xffff; shr.u32 t1, %5, 16;\n"
        "xor.b32 ad, t0, 0; add.u32 ad, ad, %4; ldmatrix.sync.aligned.m8n8.x4.shared.b16 {qa0,qa1,qa2,qa3}, [ad];\n"
        "xor.b32 ad, t0, 32; add.u32 ad, ad, %4; ldmatrix.sync.aligned.m8n8.x4.shared.b16 {qa4,qa5,qa6,qa7}, [ad];\n"
        "xor.b32 ad, t0, 64; add.u32 ad, ad, %4; ldmatrix.sync.aligned.m8n8.x4.shared.b16 {qa8,qa9,qa10,qa11}, [ad];\n"
        "xor.b32 ad, t0, 96; add.u32 ad, ad, %4; ldmatrix.sync.aligned.m8n8.x4.shared.b16 {qa12,qa13,qa14,qa15}, [ad];\n"
        "xor.b32 ad, t1, 0; add.u32 ad, ad, %4; ldmatrix.sync.aligned.m8n8.x4.shared.b16 {qa16,qa17,qa18,qa19}, [ad];\n"
        "xor.b32 ad, t1, 32; add.u32 ad, ad, %4; ldmatrix.sync.aligned.m8n8.x4.shared.b16 {qa20,qa21,qa22,qa23}, [ad];\n"
        "wgmma.fence.sync.aligned;\n"
        "add.s64 dt, w1d, 0; wgmma.mma_async.sync.aligned.m64n64k16.f16.f16.f16 {qz0,qz1,qz2,qz3,qz4,qz5,qz6,qz7,qz8,qz9,qz10,qz11,qz12,qz13,qz14,qz15}, {qa0,qa1,qa2,qa3}, dt, pf, 1, 1, 1;\n"
        "add.s64 dt, w1d, 128; wgmma.mma_async.sync.aligned.m64n64k16.f16.f16.f16 {qz0,qz1,qz2,qz3,qz4,qz5,qz6,qz7,qz8,qz9,qz10,qz11,qz12,qz13,qz14,qz15}, {qa4,qa5,qa6,qa7}, dt, pt, 1, 1, 1;\n"
        "add.s64 dt, w1d, 256; wgmma.mma_async.sync.aligned.m64n64k16.f16.f16.f16 {qz0,qz1,qz2,qz3,qz4,qz5,qz6,qz7,qz8,qz9,qz10,qz11,qz12,qz13,qz14,qz15}, {qa8,qa9,qa10,qa11}, dt, pt, 1, 1, 1;\n"
        "add.s64 dt, w1d, 384; wgmma.mma_async.sync.aligned.m64n64k16.f16.f16.f16 {qz0,qz1,qz2,qz3,qz4,qz5,qz6,qz7,qz8,qz9,qz10,qz11,qz12,qz13,qz14,qz15}, {qa12,qa13,qa14,qa15}, dt, pt, 1, 1, 1;\n"
        "add.s64 dt, w1d, 512; wgmma.mma_async.sync.aligned.m64n64k16.f16.f16.f16 {qz0,qz1,qz2,qz3,qz4,qz5,qz6,qz7,qz8,qz9,qz10,qz11,qz12,qz13,qz14,qz15}, {qa16,qa17,qa18,qa19}, dt, pt, 1, 1, 1;\n"
        "add.s64 dt, w1d, 640; wgmma.mma_async.sync.aligned.m64n64k16.f16.f16.f16 {qz0,qz1,qz2,qz3,qz4,qz5,qz6,qz7,qz8,qz9,qz10,qz11,qz12,qz13,qz14,qz15}, {qa20,qa21,qa22,qa23}, dt, pt, 1, 1, 1;\n"
        "wgmma.commit_group.sync.aligned;\n"
        "wgmma.wait_group.sync.aligned 0;\n"
        "fma.rn.f16x2 p0, qz0, qz0, c;\n"
        "mul.rn.f16x2 a0, qz0, p0; fma.rn.f16x2 p1, qz1, qz1, c;\n"
        "mov.b32 {xl, xh}, a0; tanh.approx.f16 xr, xl; cvt.u32.u16 lo0, xr; tanh.approx.f16 xr, xh; cvt.u32.u16 hi0, xr; mul.rn.f16x2 a1, qz1, p1; fma.rn.f16x2 p0, qz2, qz2, c;\n"
        "mov.b32 {xl, xh}, a1; tanh.approx.f16 xr, xl; cvt.u32.u16 lo1, xr; tanh.approx.f16 xr, xh; cvt.u32.u16 hi1, xr; mul.rn.f16x2 a2, qz2, p0; fma.rn.f16x2 p1, qz3, qz3, c; prmt.b32 h0, lo0, hi0, 0x5410;\n"
        "mov.b32 {xl, xh}, a2; tanh.approx.f16 xr, xl; cvt.u32.u16 lo0, xr; tanh.approx.f16 xr, xh; cvt.u32.u16 hi0, xr; mul.rn.f16x2 a3, qz3, p1; fma.rn.f16x2 p0, qz4, qz4, c; fma.rn.f16x2 g0, qz0, h0, qz0; prmt.b32 h1, lo1, hi1, 0x5410;\n"
        "mov.b32 {xl, xh}, a3; tanh.approx.f16 xr, xl; cvt.u32.u16 lo1, xr; tanh.approx.f16 xr, xh; cvt.u32.u16 hi1, xr; mul.rn.f16x2 a0, qz4, p0; fma.rn.f16x2 p1, qz5, qz5, c; fma.rn.f16x2 g1, qz1, h1, qz1; prmt.b32 h0, lo0, hi0, 0x5410;\n"
        "mov.b32 {xl, xh}, a0; tanh.approx.f16 xr, xl; cvt.u32.u16 lo0, xr; tanh.approx.f16 xr, xh; cvt.u32.u16 hi0, xr; mul.rn.f16x2 a1, qz5, p1; fma.rn.f16x2 p0, qz6, qz6, c; fma.rn.f16x2 g2, qz2, h0, qz2; prmt.b32 h1, lo1, hi1, 0x5410;\n"
        "mov.b32 {xl, xh}, a1; tanh.approx.f16 xr, xl; cvt.u32.u16 lo1, xr; tanh.approx.f16 xr, xh; cvt.u32.u16 hi1, xr; mul.rn.f16x2 a2, qz6, p0; fma.rn.f16x2 p1, qz7, qz7, c; fma.rn.f16x2 g3, qz3, h1, qz3; prmt.b32 h0, lo0, hi0, 0x5410;\n"
        "bra.uni DONE;\n"
        "SPINY0: mov.u32 cnt, 0;\n"
        "SPINY0L:\n"
        "mbarrier.try_wait.parity.shared::cta.b64 pw, [ybar], 0;\n"
        "@pw bra.uni BACKY0;\n"
        "add.u32 cnt, cnt, 1; setp.lt.u32 pw, cnt, 0x100000;\n"
        "@pw bra.uni SPINY0L;\n"
        "trap;\n"
        "DONE:\n"
        "}\n"
        :: "n"(0), "r"(prm.w1desc), "r"(c.wg), "n"(0), "r"(c.xs), "r"(c.a_offs) : "memory");
}
__device__ __forceinline__ bool pass2_head(const Pass2& c, uint32_t round) {
    uint32_t retry;
    asm volatile(
        "{\n"
        ".reg .b32 t<2>, tt, ad, cnt;\n"
        ".reg .pred pw;\n"
        "and.b32 t0, %3, 0xffff; shr.u32 t1, %3, 16;\n"
        "xor.b32 ad, t0, 0; add.u32 ad, ad, %4; ldmatrix.sync.aligned.m8n8.x4.shared.b16 {qa0,qa1,qa2,qa3}, [ad];\n"
        "xor.b32 ad, t0, 32; add.u32 ad, ad, %4; ldmatrix.sync.aligned.m8n8.x4.shared.b16 {qa4,qa5,qa6,qa7}, [ad];\n"
        "xor.b32 ad, t0, 64; add.u32 ad, ad, %4; ldmatrix.sync.aligned.m8n8.x4.shared.b16 {qa8,qa9,qa10,qa11}, [ad];\n"
        "xor.b32 ad, t0, 96; add.u32 ad, ad, %4; ldmatrix.sync.aligned.m8n8.x4.shared.b16 {qa12,qa13,qa14,qa15}, [ad];\n"
        "xor.b32 ad, t1, 0; add.u32 ad, ad, %4; ldmatrix.sync.aligned.m8n8.x4.shared.b16 {qa16,qa17,qa18,qa19}, [ad];\n"
        "xor.b32 ad, t1, 32; add.u32 ad, ad, %4; ldmatrix.sync.aligned.m8n8.x4.shared.b16 {qa20,qa21,qa22,qa23}, [ad];\n"
        "mov.b32 qz16, 0; mov.b32 qz17, 0; mov.b32 qz18, 0; mov.b32 qz19, 0; mov.b32 qz20, 0; mov.b32 qz21, 0; mov.b32 qz22, 0; mov.b32 qz23, 0; mov.b32 qz24, 0; mov.b32 qz25, 0; mov.b32 qz26, 0; mov.b32 qz27, 0; mov.b32 qz28, 0; mov.b32 qz29, 0; mov.b32 qz30, 0; mov.b32 qz31, 0;\n"
        "mov.b32 g4, 0; mov.b32 g5, 0; mov.b32 g6, 0; mov.b32 g7, 0; mov.b32 g8, 0; mov.b32 g9, 0; mov.b32 g10, 0; mov.b32 g11, 0; mov.b32 g12, 0; mov.b32 g13, 0; mov.b32 g14, 0; mov.b32 g15, 0;\n"
        "mov.u32 tt, 231224; mbarrier.try_wait.parity.shared::cta.b64 pw, [tt], %1;\n"
        "@!pw bra.uni SPINR;\n"
        "BACKR:\n"
        "mov.u32 tt, 230792; ld.shared.v2.b32 {osc, %0}, [tt];\n"
        "ld.shared.v4.b32 {o0,o1,o2,o3}, [%2+0];\n"
        "ld.shared.v4.b32 {o4,o5,o6,o7}, [%2+64];\n"
        "ld.shared.v4.b32 {o8,o9,o10,o11}, [%2+128];\n"
        "ld.shared.v4.b32 {o12,o13,o14,o15}, [%2+192];\n"
        "ld.shared.v4.b32 {o16,o17,o18,o19}, [%2+256];\n"
        "ld.shared.v4.b32 {o20,o21,o22,o23}, [%2+320];\n"
        "bra.uni DONE;\n"
        "SPINR: mov.u32 cnt, 0;\n"
        "SPINRL:\n"
        "mov.u32 tt, 231224; mbarrier.try_wait.parity.shared::cta.b64 pw, [tt], %1;\n"
        "@pw bra.uni BACKR;\n"
        "add.u32 cnt, cnt, 1; setp.lt.u32 pw, cnt, 0x100000;\n"
        "@pw bra.uni SPINRL;\n"
        "trap;\n"
        "DONE:\n"
        "}\n"
        : "=r"(retry)
        : "r"(round), "r"(c.bias_addr), "r"(c.a_offs), "r"(c.xs)
        : "memory");
    return __any_sync(0xffffffffu, retry);
}
__device__ __forceinline__ void pass2_tiles(const Pass2& c, const Params& prm) {
    asm volatile(
        "{\n"
        ".reg .b32 v<8>, n, off, c, tt, ad, cnt, ybar, xbar, tbar, tpar, id;\n"
        ".reg .b16 xl, xh, xr;\n"
        ".reg .f32 f0, f1;\n"
        ".reg .b64 w1d, w2d, dt, gp, pol;\n"
        ".reg .pred pt, pf, pr, pw, pl, pk, pm, pz, pn;\n"
        "setp.ne.b32 pt, 1, 0; setp.ne.b32 pf, 0, 0; setp.eq.u32 pl, %9, 0; setp.eq.u32 pk, %9, 0; setp.eq.u32 pz, %0, 0;\n"
        "mov.b32 c, 0x40D940D9;\n"
        "mov.b64 w1d, {%0, 0x40000040}; mov.b64 w2d, {%1, 0x80000020};\n"
        "mad.lo.u32 ybar, %2, 8, 230800; mad.lo.u32 xbar, %2, 8, 230832; add.u32 id, %2, 2;\n"
        "xor.b32 tt, %2, 0; mad.lo.u32 tbar, tt, 64, 230888; setp.eq.u32 pr, tt, 0; selp.u32 tpar, 1, 0, pr; mov.u32 tt, %laneid; setp.eq.u32 pn, tt, 0;\n"
        "mov.u32 n, -1; add.u32 off, %3, %8; mov.pred pm, pt; mov.b64 pol, 0x12F0000000000000;\n"
        "mov.b32 v0, 0; mov.b32 v1, 0; mov.b32 v2, 0; mov.b32 v3, 0; mov.b32 v4, 0; mov.b32 v5, 0; mov.b32 v6, 0; mov.b32 v7, 0;\n"
        "LOOP:\n"
        "@!pm bra.uni SKIP0;\n"
        "wgmma.fence.sync.aligned;\n"
        "add.s64 dt, w1d, 768; wgmma.mma_async.sync.aligned.m64n64k16.f16.f16.f16 {qz16,qz17,qz18,qz19,qz20,qz21,qz22,qz23,qz24,qz25,qz26,qz27,qz28,qz29,qz30,qz31}, {qa0,qa1,qa2,qa3}, dt, pf, 1, 1, 1;\n"
        "add.s64 dt, w1d, 896; wgmma.mma_async.sync.aligned.m64n64k16.f16.f16.f16 {qz16,qz17,qz18,qz19,qz20,qz21,qz22,qz23,qz24,qz25,qz26,qz27,qz28,qz29,qz30,qz31}, {qa4,qa5,qa6,qa7}, dt, pt, 1, 1, 1;\n"
        "add.s64 dt, w1d, 1024; wgmma.mma_async.sync.aligned.m64n64k16.f16.f16.f16 {qz16,qz17,qz18,qz19,qz20,qz21,qz22,qz23,qz24,qz25,qz26,qz27,qz28,qz29,qz30,qz31}, {qa8,qa9,qa10,qa11}, dt, pt, 1, 1, 1;\n"
        "add.s64 dt, w1d, 1152; wgmma.mma_async.sync.aligned.m64n64k16.f16.f16.f16 {qz16,qz17,qz18,qz19,qz20,qz21,qz22,qz23,qz24,qz25,qz26,qz27,qz28,qz29,qz30,qz31}, {qa12,qa13,qa14,qa15}, dt, pt, 1, 1, 1;\n"
        "add.s64 dt, w1d, 1280; wgmma.mma_async.sync.aligned.m64n64k16.f16.f16.f16 {qz16,qz17,qz18,qz19,qz20,qz21,qz22,qz23,qz24,qz25,qz26,qz27,qz28,qz29,qz30,qz31}, {qa16,qa17,qa18,qa19}, dt, pt, 1, 1, 1;\n"
        "add.s64 dt, w1d, 1408; wgmma.mma_async.sync.aligned.m64n64k16.f16.f16.f16 {qz16,qz17,qz18,qz19,qz20,qz21,qz22,qz23,qz24,qz25,qz26,qz27,qz28,qz29,qz30,qz31}, {qa20,qa21,qa22,qa23}, dt, pt, 1, 1, 1;\n"
        "SKIP0:\n"
        "wgmma.fence.sync.aligned;\n"
        "wgmma.commit_group.sync.aligned;\n"
        "setp.lt.s32 pr, n, 0;\n"
        "@pr bra.uni FIRST;\n"
        "and.b32 tt, n, 1; mbarrier.try_wait.parity.shared::cta.b64 pw, [xbar], tt;\n"
        "@!pw bra.uni SPINX;\n"
        "BACKX:\n"
        "and.b32 ad, %6, 0xffff; add.u32 ad, ad, %4; ld.shared.v4.b32 {v0,v1,v2,v3}, [ad+0];\n"
        "shr.u32 ad, %6, 16; add.u32 ad, ad, %4; ld.shared.v4.b32 {v4,v5,v6,v7}, [ad+0];\n"
        "mov.b32 {xl, xh}, o0; cvt.f32.f16 f0, xl; cvt.f32.f16 f1, xh; cvt.rn.bf16x2.f32 tt, f1, f0; fma.rn.bf16x2 v0, tt, osc, v0;\n"
        "mov.b32 {xl, xh}, o2; cvt.f32.f16 f0, xl; cvt.f32.f16 f1, xh; cvt.rn.bf16x2.f32 tt, f1, f0; fma.rn.bf16x2 v1, tt, osc, v1;\n"
        "mov.b32 {xl, xh}, o4; cvt.f32.f16 f0, xl; cvt.f32.f16 f1, xh; cvt.rn.bf16x2.f32 tt, f1, f0; fma.rn.bf16x2 v2, tt, osc, v2;\n"
        "mov.b32 {xl, xh}, o6; cvt.f32.f16 f0, xl; cvt.f32.f16 f1, xh; cvt.rn.bf16x2.f32 tt, f1, f0; fma.rn.bf16x2 v3, tt, osc, v3;\n"
        "and.b32 ad, %6, 0xffff; add.u32 ad, ad, %4; st.shared.v4.b32 [ad+0], {v0,v1,v2,v3};\n"
        "and.b32 ad, %6, 0xffff; add.u32 ad, ad, %4; ld.shared.v4.b32 {v0,v1,v2,v3}, [ad+64];\n"
        "mov.b32 {xl, xh}, o1; cvt.f32.f16 f0, xl; cvt.f32.f16 f1, xh; cvt.rn.bf16x2.f32 tt, f1, f0; fma.rn.bf16x2 v4, tt, osc, v4;\n"
        "mov.b32 {xl, xh}, o3; cvt.f32.f16 f0, xl; cvt.f32.f16 f1, xh; cvt.rn.bf16x2.f32 tt, f1, f0; fma.rn.bf16x2 v5, tt, osc, v5;\n"
        "mov.b32 {xl, xh}, o5; cvt.f32.f16 f0, xl; cvt.f32.f16 f1, xh; cvt.rn.bf16x2.f32 tt, f1, f0; fma.rn.bf16x2 v6, tt, osc, v6;\n"
        "mov.b32 {xl, xh}, o7; cvt.f32.f16 f0, xl; cvt.f32.f16 f1, xh; cvt.rn.bf16x2.f32 tt, f1, f0; fma.rn.bf16x2 v7, tt, osc, v7;\n"
        "shr.u32 ad, %6, 16; add.u32 ad, ad, %4; st.shared.v4.b32 [ad+0], {v4,v5,v6,v7};\n"
        "shr.u32 ad, %6, 16; add.u32 ad, ad, %4; ld.shared.v4.b32 {v4,v5,v6,v7}, [ad+64];\n"
        "ld.shared.v4.b32 {o0,o1,o2,o3}, [%7+0];\n"
        "ld.shared.v4.b32 {o4,o5,o6,o7}, [%7+64];\n"
        "mov.b32 {xl, xh}, o8; cvt.f32.f16 f0, xl; cvt.f32.f16 f1, xh; cvt.rn.bf16x2.f32 tt, f1, f0; fma.rn.bf16x2 v0, tt, osc, v0;\n"
        "mov.b32 {xl, xh}, o10; cvt.f32.f16 f0, xl; cvt.f32.f16 f1, xh; cvt.rn.bf16x2.f32 tt, f1, f0; fma.rn.bf16x2 v1, tt, osc, v1;\n"
        "mov.b32 {xl, xh}, o12; cvt.f32.f16 f0, xl; cvt.f32.f16 f1, xh; cvt.rn.bf16x2.f32 tt, f1, f0; fma.rn.bf16x2 v2, tt, osc, v2;\n"
        "mov.b32 {xl, xh}, o14; cvt.f32.f16 f0, xl; cvt.f32.f16 f1, xh; cvt.rn.bf16x2.f32 tt, f1, f0; fma.rn.bf16x2 v3, tt, osc, v3;\n"
        "and.b32 ad, %6, 0xffff; add.u32 ad, ad, %4; st.shared.v4.b32 [ad+64], {v0,v1,v2,v3};\n"
        "and.b32 ad, %6, 0xffff; add.u32 ad, ad, %4; ld.shared.v4.b32 {v0,v1,v2,v3}, [ad+128];\n"
        "mov.b32 {xl, xh}, o9; cvt.f32.f16 f0, xl; cvt.f32.f16 f1, xh; cvt.rn.bf16x2.f32 tt, f1, f0; fma.rn.bf16x2 v4, tt, osc, v4;\n"
        "mov.b32 {xl, xh}, o11; cvt.f32.f16 f0, xl; cvt.f32.f16 f1, xh; cvt.rn.bf16x2.f32 tt, f1, f0; fma.rn.bf16x2 v5, tt, osc, v5;\n"
        "mov.b32 {xl, xh}, o13; cvt.f32.f16 f0, xl; cvt.f32.f16 f1, xh; cvt.rn.bf16x2.f32 tt, f1, f0; fma.rn.bf16x2 v6, tt, osc, v6;\n"
        "mov.b32 {xl, xh}, o15; cvt.f32.f16 f0, xl; cvt.f32.f16 f1, xh; cvt.rn.bf16x2.f32 tt, f1, f0; fma.rn.bf16x2 v7, tt, osc, v7;\n"
        "shr.u32 ad, %6, 16; add.u32 ad, ad, %4; st.shared.v4.b32 [ad+64], {v4,v5,v6,v7};\n"
        "shr.u32 ad, %6, 16; add.u32 ad, ad, %4; ld.shared.v4.b32 {v4,v5,v6,v7}, [ad+128];\n"
        "ld.shared.v4.b32 {o8,o9,o10,o11}, [%7+128];\n"
        "ld.shared.v4.b32 {o12,o13,o14,o15}, [%7+192];\n"
        "mov.b32 {xl, xh}, o16; cvt.f32.f16 f0, xl; cvt.f32.f16 f1, xh; cvt.rn.bf16x2.f32 tt, f1, f0; fma.rn.bf16x2 v0, tt, osc, v0;\n"
        "mov.b32 {xl, xh}, o18; cvt.f32.f16 f0, xl; cvt.f32.f16 f1, xh; cvt.rn.bf16x2.f32 tt, f1, f0; fma.rn.bf16x2 v1, tt, osc, v1;\n"
        "mov.b32 {xl, xh}, o20; cvt.f32.f16 f0, xl; cvt.f32.f16 f1, xh; cvt.rn.bf16x2.f32 tt, f1, f0; fma.rn.bf16x2 v2, tt, osc, v2;\n"
        "mov.b32 {xl, xh}, o22; cvt.f32.f16 f0, xl; cvt.f32.f16 f1, xh; cvt.rn.bf16x2.f32 tt, f1, f0; fma.rn.bf16x2 v3, tt, osc, v3;\n"
        "and.b32 ad, %6, 0xffff; add.u32 ad, ad, %4; st.shared.v4.b32 [ad+128], {v0,v1,v2,v3};\n"
        "mov.b32 {xl, xh}, o17; cvt.f32.f16 f0, xl; cvt.f32.f16 f1, xh; cvt.rn.bf16x2.f32 tt, f1, f0; fma.rn.bf16x2 v4, tt, osc, v4;\n"
        "mov.b32 {xl, xh}, o19; cvt.f32.f16 f0, xl; cvt.f32.f16 f1, xh; cvt.rn.bf16x2.f32 tt, f1, f0; fma.rn.bf16x2 v5, tt, osc, v5;\n"
        "mov.b32 {xl, xh}, o21; cvt.f32.f16 f0, xl; cvt.f32.f16 f1, xh; cvt.rn.bf16x2.f32 tt, f1, f0; fma.rn.bf16x2 v6, tt, osc, v6;\n"
        "mov.b32 {xl, xh}, o23; cvt.f32.f16 f0, xl; cvt.f32.f16 f1, xh; cvt.rn.bf16x2.f32 tt, f1, f0; fma.rn.bf16x2 v7, tt, osc, v7;\n"
        "shr.u32 ad, %6, 16; add.u32 ad, ad, %4; st.shared.v4.b32 [ad+128], {v4,v5,v6,v7};\n"
        "ld.shared.v4.b32 {o16,o17,o18,o19}, [%7+256];\n"
        "ld.shared.v4.b32 {o20,o21,o22,o23}, [%7+320];\n"
        "FIRST:\n"
        "@pz bra.uni B7;\n"
        "mov.b32 {xl, xh}, a2; tanh.approx.f16 xr, xl; cvt.u32.u16 lo0, xr; tanh.approx.f16 xr, xh; cvt.u32.u16 hi0, xr; mul.rn.f16x2 a3, qz7, p1; fma.rn.f16x2 p0, qz8, qz8, c; fma.rn.f16x2 g4, qz4, h0, qz4; prmt.b32 h1, lo1, hi1, 0x5410;\n"
        "B7:\n"
        "fence.proxy.async.shared::cta;\n"
        "add.u32 tt, id, 4;\n"
        "@pl bra.uni STORE;\n"
        "bar.arrive tt, 128;\n"
        "STOREB:\n"
        ASM_MARK
        "@!pm bra.uni DONE;\n"
        "add.s32 n, n, 1; sub.u32 off, off, %8; setp.lt.s32 pm, n, 7;\n"
        "@pz bra.uni B10;\n"
        "mov.b32 {xl, xh}, a3; tanh.approx.f16 xr, xl; cvt.u32.u16 lo1, xr; tanh.approx.f16 xr, xh; cvt.u32.u16 hi1, xr; mul.rn.f16x2 a0, qz8, p0; fma.rn.f16x2 p1, qz9, qz9, c; fma.rn.f16x2 g5, qz5, h1, qz5; prmt.b32 h0, lo0, hi0, 0x5410;\n"
        "mov.b32 {xl, xh}, a0; tanh.approx.f16 xr, xl; cvt.u32.u16 lo0, xr; tanh.approx.f16 xr, xh; cvt.u32.u16 hi0, xr; mul.rn.f16x2 a1, qz9, p1; fma.rn.f16x2 p0, qz10, qz10, c; fma.rn.f16x2 g6, qz6, h0, qz6; prmt.b32 h1, lo1, hi1, 0x5410;\n"
        "mov.b32 {xl, xh}, a1; tanh.approx.f16 xr, xl; cvt.u32.u16 lo1, xr; tanh.approx.f16 xr, xh; cvt.u32.u16 hi1, xr; mul.rn.f16x2 a2, qz10, p0; fma.rn.f16x2 p1, qz11, qz11, c; fma.rn.f16x2 g7, qz7, h1, qz7; prmt.b32 h0, lo0, hi0, 0x5410;\n"
        "B10:\n"
        "setp.eq.s32 pr, n, 0;\n"
        "@pr bra.uni SPINW0;\n"
        "BACKW0:\n"
        "wgmma.fence.sync.aligned;\n"
        "add.s64 dt, w2d, 0; wgmma.mma_async.sync.aligned.m64n96k16.f16.f16.f16 {o0,o1,o2,o3,o4,o5,o6,o7,o8,o9,o10,o11,o12,o13,o14,o15,o16,o17,o18,o19,o20,o21,o22,o23}, {g0,g1,g2,g3}, dt, pt, 1, 1, 1;\n"
        "add.s64 dt, w2d, 64; wgmma.mma_async.sync.aligned.m64n96k16.f16.f16.f16 {o0,o1,o2,o3,o4,o5,o6,o7,o8,o9,o10,o11,o12,o13,o14,o15,o16,o17,o18,o19,o20,o21,o22,o23}, {g4,g5,g6,g7}, dt, pt, 1, 1, 1;\n"
        "wgmma.commit_group.sync.aligned;\n"
        "@pz bra.uni B14;\n"
        "mov.b32 {xl, xh}, a2; tanh.approx.f16 xr, xl; cvt.u32.u16 lo0, xr; tanh.approx.f16 xr, xh; cvt.u32.u16 hi0, xr; mul.rn.f16x2 a3, qz11, p1; fma.rn.f16x2 p0, qz12, qz12, c; fma.rn.f16x2 g8, qz8, h0, qz8; prmt.b32 h1, lo1, hi1, 0x5410;\n"
        "mov.b32 {xl, xh}, a3; tanh.approx.f16 xr, xl; cvt.u32.u16 lo1, xr; tanh.approx.f16 xr, xh; cvt.u32.u16 hi1, xr; mul.rn.f16x2 a0, qz12, p0; fma.rn.f16x2 p1, qz13, qz13, c; fma.rn.f16x2 g9, qz9, h1, qz9; prmt.b32 h0, lo0, hi0, 0x5410;\n"
        "mov.b32 {xl, xh}, a0; tanh.approx.f16 xr, xl; cvt.u32.u16 lo0, xr; tanh.approx.f16 xr, xh; cvt.u32.u16 hi0, xr; mul.rn.f16x2 a1, qz13, p1; fma.rn.f16x2 p0, qz14, qz14, c; fma.rn.f16x2 g10, qz10, h0, qz10; prmt.b32 h1, lo1, hi1, 0x5410;\n"
        "mov.b32 {xl, xh}, a1; tanh.approx.f16 xr, xl; cvt.u32.u16 lo1, xr; tanh.approx.f16 xr, xh; cvt.u32.u16 hi1, xr; mul.rn.f16x2 a2, qz14, p0; fma.rn.f16x2 p1, qz15, qz15, c; fma.rn.f16x2 g11, qz11, h1, qz11; prmt.b32 h0, lo0, hi0, 0x5410;\n"
        "B14:\n"
        "wgmma.wait_group.sync.aligned 1;\n"
        "wgmma.fence.sync.aligned;\n"
        "add.s64 dt, w2d, 128; wgmma.mma_async.sync.aligned.m64n96k16.f16.f16.f16 {o0,o1,o2,o3,o4,o5,o6,o7,o8,o9,o10,o11,o12,o13,o14,o15,o16,o17,o18,o19,o20,o21,o22,o23}, {g8,g9,g10,g11}, dt, pt, 1, 1, 1;\n"
        "wgmma.commit_group.sync.aligned;\n"
        "@pz bra.uni B18;\n"
        "mov.b32 {xl, xh}, a2; tanh.approx.f16 xr, xl; cvt.u32.u16 lo0, xr; tanh.approx.f16 xr, xh; cvt.u32.u16 hi0, xr; mul.rn.f16x2 a3, qz15, p1; fma.rn.f16x2 p0, qz16, qz16, c; fma.rn.f16x2 g12, qz12, h0, qz12; prmt.b32 h1, lo1, hi1, 0x5410;\n"
        "mov.b32 {xl, xh}, a3; tanh.approx.f16 xr, xl; cvt.u32.u16 lo1, xr; tanh.approx.f16 xr, xh; cvt.u32.u16 hi1, xr; mul.rn.f16x2 a0, qz16, p0; fma.rn.f16x2 p1, qz17, qz17, c; fma.rn.f16x2 g13, qz13, h1, qz13; prmt.b32 h0, lo0, hi0, 0x5410;\n"
        "mov.b32 {xl, xh}, a0; tanh.approx.f16 xr, xl; cvt.u32.u16 lo0, xr; tanh.approx.f16 xr, xh; cvt.u32.u16 hi0, xr; mul.rn.f16x2 a1, qz17, p1; fma.rn.f16x2 p0, qz18, qz18, c; fma.rn.f16x2 g14, qz14, h0, qz14; prmt.b32 h1, lo1, hi1, 0x5410;\n"
        "mov.b32 {xl, xh}, a1; tanh.approx.f16 xr, xl; cvt.u32.u16 lo1, xr; tanh.approx.f16 xr, xh; cvt.u32.u16 hi1, xr; mul.rn.f16x2 a2, qz18, p0; fma.rn.f16x2 p1, qz19, qz19, c; fma.rn.f16x2 g15, qz15, h1, qz15; prmt.b32 h0, lo0, hi0, 0x5410;\n"
        "B18:\n"
        "wgmma.wait_group.sync.aligned 1;\n"
        "mad.lo.u32 tt, n, 8, tbar; mbarrier.try_wait.parity.shared::cta.b64 pw, [tt], tpar;\n"
        "@!pw bra.uni SPINT;\n"
        "BACKT:\n"
        "wgmma.fence.sync.aligned;\n"
        "add.s64 dt, w2d, 192; wgmma.mma_async.sync.aligned.m64n96k16.f16.f16.f16 {o0,o1,o2,o3,o4,o5,o6,o7,o8,o9,o10,o11,o12,o13,o14,o15,o16,o17,o18,o19,o20,o21,o22,o23}, {g12,g13,g14,g15}, dt, pt, 1, 1, 1;\n"
        "add.s64 dt, w1d, 1536; wgmma.mma_async.sync.aligned.m64n64k16.f16.f16.f16 {qz0,qz1,qz2,qz3,qz4,qz5,qz6,qz7,qz8,qz9,qz10,qz11,qz12,qz13,qz14,qz15}, {qa0,qa1,qa2,qa3}, dt, pf, 1, 1, 1;\n"
        "add.s64 dt, w1d, 1664; wgmma.mma_async.sync.aligned.m64n64k16.f16.f16.f16 {qz0,qz1,qz2,qz3,qz4,qz5,qz6,qz7,qz8,qz9,qz10,qz11,qz12,qz13,qz14,qz15}, {qa4,qa5,qa6,qa7}, dt, pt, 1, 1, 1;\n"
        "add.s64 dt, w1d, 1792; wgmma.mma_async.sync.aligned.m64n64k16.f16.f16.f16 {qz0,qz1,qz2,qz3,qz4,qz5,qz6,qz7,qz8,qz9,qz10,qz11,qz12,qz13,qz14,qz15}, {qa8,qa9,qa10,qa11}, dt, pt, 1, 1, 1;\n"
        "wgmma.commit_group.sync.aligned;\n"
        "@pl bra.uni YLOAD;\n"
        "YLOADB:\n"
        "@pz bra.uni B22;\n"
        "mov.b32 {xl, xh}, a2; tanh.approx.f16 xr, xl; cvt.u32.u16 lo0, xr; tanh.approx.f16 xr, xh; cvt.u32.u16 hi0, xr; mul.rn.f16x2 a3, qz19, p1; fma.rn.f16x2 p0, qz20, qz20, c; fma.rn.f16x2 g0, qz16, h0, qz16; prmt.b32 h1, lo1, hi1, 0x5410;\n"
        "mov.b32 {xl, xh}, a3; tanh.approx.f16 xr, xl; cvt.u32.u16 lo1, xr; tanh.approx.f16 xr, xh; cvt.u32.u16 hi1, xr; mul.rn.f16x2 a0, qz20, p0; fma.rn.f16x2 p1, qz21, qz21, c; fma.rn.f16x2 g1, qz17, h1, qz17; prmt.b32 h0, lo0, hi0, 0x5410;\n"
        "mov.b32 {xl, xh}, a0; tanh.approx.f16 xr, xl; cvt.u32.u16 lo0, xr; tanh.approx.f16 xr, xh; cvt.u32.u16 hi0, xr; mul.rn.f16x2 a1, qz21, p1; fma.rn.f16x2 p0, qz22, qz22, c; fma.rn.f16x2 g2, qz18, h0, qz18; prmt.b32 h1, lo1, hi1, 0x5410;\n"
        "mov.b32 {xl, xh}, a1; tanh.approx.f16 xr, xl; cvt.u32.u16 lo1, xr; tanh.approx.f16 xr, xh; cvt.u32.u16 hi1, xr; mul.rn.f16x2 a2, qz22, p0; fma.rn.f16x2 p1, qz23, qz23, c; fma.rn.f16x2 g3, qz19, h1, qz19; prmt.b32 h0, lo0, hi0, 0x5410;\n"
        "B22:\n"
        "wgmma.fence.sync.aligned;\n"
        "add.s64 dt, w2d, 256; wgmma.mma_async.sync.aligned.m64n96k16.f16.f16.f16 {o0,o1,o2,o3,o4,o5,o6,o7,o8,o9,o10,o11,o12,o13,o14,o15,o16,o17,o18,o19,o20,o21,o22,o23}, {g0,g1,g2,g3}, dt, pt, 1, 1, 1;\n"
        "add.s64 dt, w1d, 1920; wgmma.mma_async.sync.aligned.m64n64k16.f16.f16.f16 {qz0,qz1,qz2,qz3,qz4,qz5,qz6,qz7,qz8,qz9,qz10,qz11,qz12,qz13,qz14,qz15}, {qa12,qa13,qa14,qa15}, dt, pt, 1, 1, 1;\n"
        "add.s64 dt, w1d, 2048; wgmma.mma_async.sync.aligned.m64n64k16.f16.f16.f16 {qz0,qz1,qz2,qz3,qz4,qz5,qz6,qz7,qz8,qz9,qz10,qz11,qz12,qz13,qz14,qz15}, {qa16,qa17,qa18,qa19}, dt, pt, 1, 1, 1;\n"
        "add.s64 dt, w1d, 2176; wgmma.mma_async.sync.aligned.m64n64k16.f16.f16.f16 {qz0,qz1,qz2,qz3,qz4,qz5,qz6,qz7,qz8,qz9,qz10,qz11,qz12,qz13,qz14,qz15}, {qa20,qa21,qa22,qa23}, dt, pt, 1, 1, 1;\n"
        "wgmma.commit_group.sync.aligned;\n"
        "@pz bra.uni B26;\n"
        "mov.b32 {xl, xh}, a2; tanh.approx.f16 xr, xl; cvt.u32.u16 lo0, xr; tanh.approx.f16 xr, xh; cvt.u32.u16 hi0, xr; mul.rn.f16x2 a3, qz23, p1; fma.rn.f16x2 p0, qz24, qz24, c; fma.rn.f16x2 g4, qz20, h0, qz20; prmt.b32 h1, lo1, hi1, 0x5410;\n"
        "mov.b32 {xl, xh}, a3; tanh.approx.f16 xr, xl; cvt.u32.u16 lo1, xr; tanh.approx.f16 xr, xh; cvt.u32.u16 hi1, xr; mul.rn.f16x2 a0, qz24, p0; fma.rn.f16x2 p1, qz25, qz25, c; fma.rn.f16x2 g5, qz21, h1, qz21; prmt.b32 h0, lo0, hi0, 0x5410;\n"
        "mov.b32 {xl, xh}, a0; tanh.approx.f16 xr, xl; cvt.u32.u16 lo0, xr; tanh.approx.f16 xr, xh; cvt.u32.u16 hi0, xr; mul.rn.f16x2 a1, qz25, p1; fma.rn.f16x2 p0, qz26, qz26, c; fma.rn.f16x2 g6, qz22, h0, qz22; prmt.b32 h1, lo1, hi1, 0x5410;\n"
        "mov.b32 {xl, xh}, a1; tanh.approx.f16 xr, xl; cvt.u32.u16 lo1, xr; tanh.approx.f16 xr, xh; cvt.u32.u16 hi1, xr; mul.rn.f16x2 a2, qz26, p0; fma.rn.f16x2 p1, qz27, qz27, c; fma.rn.f16x2 g7, qz23, h1, qz23; prmt.b32 h0, lo0, hi0, 0x5410;\n"
        "B26:\n"
        "wgmma.wait_group.sync.aligned 2;\n"
        "wgmma.fence.sync.aligned;\n"
        "add.s64 dt, w2d, 320; wgmma.mma_async.sync.aligned.m64n96k16.f16.f16.f16 {o0,o1,o2,o3,o4,o5,o6,o7,o8,o9,o10,o11,o12,o13,o14,o15,o16,o17,o18,o19,o20,o21,o22,o23}, {g4,g5,g6,g7}, dt, pt, 1, 1, 1;\n"
        "wgmma.commit_group.sync.aligned;\n"
        "@pz bra.uni B30;\n"
        "mov.b32 {xl, xh}, a2; tanh.approx.f16 xr, xl; cvt.u32.u16 lo0, xr; tanh.approx.f16 xr, xh; cvt.u32.u16 hi0, xr; mul.rn.f16x2 a3, qz27, p1; fma.rn.f16x2 p0, qz28, qz28, c; fma.rn.f16x2 g8, qz24, h0, qz24; prmt.b32 h1, lo1, hi1, 0x5410;\n"
        "mov.b32 {xl, xh}, a3; tanh.approx.f16 xr, xl; cvt.u32.u16 lo1, xr; tanh.approx.f16 xr, xh; cvt.u32.u16 hi1, xr; mul.rn.f16x2 a0, qz28, p0; fma.rn.f16x2 p1, qz29, qz29, c; fma.rn.f16x2 g9, qz25, h1, qz25; prmt.b32 h0, lo0, hi0, 0x5410;\n"
        "mov.b32 {xl, xh}, a0; tanh.approx.f16 xr, xl; cvt.u32.u16 lo0, xr; tanh.approx.f16 xr, xh; cvt.u32.u16 hi0, xr; mul.rn.f16x2 a1, qz29, p1; fma.rn.f16x2 p0, qz30, qz30, c; fma.rn.f16x2 g10, qz26, h0, qz26; prmt.b32 h1, lo1, hi1, 0x5410;\n"
        "mov.b32 {xl, xh}, a1; tanh.approx.f16 xr, xl; cvt.u32.u16 lo1, xr; tanh.approx.f16 xr, xh; cvt.u32.u16 hi1, xr; mul.rn.f16x2 a2, qz30, p0; fma.rn.f16x2 p1, qz31, qz31, c; fma.rn.f16x2 g11, qz27, h1, qz27; prmt.b32 h0, lo0, hi0, 0x5410;\n"
        "B30:\n"
        "wgmma.wait_group.sync.aligned 1;\n"
        "wgmma.fence.sync.aligned;\n"
        "add.s64 dt, w2d, 384; wgmma.mma_async.sync.aligned.m64n96k16.f16.f16.f16 {o0,o1,o2,o3,o4,o5,o6,o7,o8,o9,o10,o11,o12,o13,o14,o15,o16,o17,o18,o19,o20,o21,o22,o23}, {g8,g9,g10,g11}, dt, pt, 1, 1, 1;\n"
        "wgmma.commit_group.sync.aligned;\n"
        "@pz bra.uni B34;\n"
        "mov.b32 {xl, xh}, a2; tanh.approx.f16 xr, xl; cvt.u32.u16 lo0, xr; tanh.approx.f16 xr, xh; cvt.u32.u16 hi0, xr; mul.rn.f16x2 a3, qz31, p1; fma.rn.f16x2 p0, qz0, qz0, c; fma.rn.f16x2 g12, qz28, h0, qz28; prmt.b32 h1, lo1, hi1, 0x5410;\n"
        "mov.b32 {xl, xh}, a3; tanh.approx.f16 xr, xl; cvt.u32.u16 lo1, xr; tanh.approx.f16 xr, xh; cvt.u32.u16 hi1, xr; mul.rn.f16x2 a0, qz0, p0; fma.rn.f16x2 p1, qz1, qz1, c; fma.rn.f16x2 g13, qz29, h1, qz29; prmt.b32 h0, lo0, hi0, 0x5410;\n"
        "mov.b32 {xl, xh}, a0; tanh.approx.f16 xr, xl; cvt.u32.u16 lo0, xr; tanh.approx.f16 xr, xh; cvt.u32.u16 hi0, xr; mul.rn.f16x2 a1, qz1, p1; fma.rn.f16x2 p0, qz2, qz2, c; fma.rn.f16x2 g14, qz30, h0, qz30; prmt.b32 h1, lo1, hi1, 0x5410;\n"
        "mov.b32 {xl, xh}, a1; tanh.approx.f16 xr, xl; cvt.u32.u16 lo1, xr; tanh.approx.f16 xr, xh; cvt.u32.u16 hi1, xr; mul.rn.f16x2 a2, qz2, p0; fma.rn.f16x2 p1, qz3, qz3, c; fma.rn.f16x2 g15, qz31, h1, qz31; prmt.b32 h0, lo0, hi0, 0x5410;\n"
        "B34:\n"
        "wgmma.fence.sync.aligned;\n"
        "add.s64 dt, w2d, 448; wgmma.mma_async.sync.aligned.m64n96k16.f16.f16.f16 {o0,o1,o2,o3,o4,o5,o6,o7,o8,o9,o10,o11,o12,o13,o14,o15,o16,o17,o18,o19,o20,o21,o22,o23}, {g12,g13,g14,g15}, dt, pt, 1, 1, 1;\n"
        "add.s64 dt, w1d, 2304; wgmma.mma_async.sync.aligned.m64n64k16.f16.f16.f16 {qz16,qz17,qz18,qz19,qz20,qz21,qz22,qz23,qz24,qz25,qz26,qz27,qz28,qz29,qz30,qz31}, {qa0,qa1,qa2,qa3}, dt, pf, 1, 1, 1;\n"
        "add.s64 dt, w1d, 2432; wgmma.mma_async.sync.aligned.m64n64k16.f16.f16.f16 {qz16,qz17,qz18,qz19,qz20,qz21,qz22,qz23,qz24,qz25,qz26,qz27,qz28,qz29,qz30,qz31}, {qa4,qa5,qa6,qa7}, dt, pt, 1, 1, 1;\n"
        "add.s64 dt, w1d, 2560; wgmma.mma_async.sync.aligned.m64n64k16.f16.f16.f16 {qz16,qz17,qz18,qz19,qz20,qz21,qz22,qz23,qz24,qz25,qz26,qz27,qz28,qz29,qz30,qz31}, {qa8,qa9,qa10,qa11}, dt, pt, 1, 1, 1;\n"
        "wgmma.commit_group.sync.aligned;\n"
        "@pz bra.uni B38;\n"
        "mov.b32 {xl, xh}, a2; tanh.approx.f16 xr, xl; cvt.u32.u16 lo0, xr; tanh.approx.f16 xr, xh; cvt.u32.u16 hi0, xr; mul.rn.f16x2 a3, qz3, p1; fma.rn.f16x2 p0, qz4, qz4, c; fma.rn.f16x2 g0, qz0, h0, qz0; prmt.b32 h1, lo1, hi1, 0x5410;\n"
        "mov.b32 {xl, xh}, a3; tanh.approx.f16 xr, xl; cvt.u32.u16 lo1, xr; tanh.approx.f16 xr, xh; cvt.u32.u16 hi1, xr; mul.rn.f16x2 a0, qz4, p0; fma.rn.f16x2 p1, qz5, qz5, c; fma.rn.f16x2 g1, qz1, h1, qz1; prmt.b32 h0, lo0, hi0, 0x5410;\n"
        "mov.b32 {xl, xh}, a0; tanh.approx.f16 xr, xl; cvt.u32.u16 lo0, xr; tanh.approx.f16 xr, xh; cvt.u32.u16 hi0, xr; mul.rn.f16x2 a1, qz5, p1; fma.rn.f16x2 p0, qz6, qz6, c; fma.rn.f16x2 g2, qz2, h0, qz2; prmt.b32 h1, lo1, hi1, 0x5410;\n"
        "mov.b32 {xl, xh}, a1; tanh.approx.f16 xr, xl; cvt.u32.u16 lo1, xr; tanh.approx.f16 xr, xh; cvt.u32.u16 hi1, xr; mul.rn.f16x2 a2, qz6, p0; fma.rn.f16x2 p1, qz7, qz7, c; fma.rn.f16x2 g3, qz3, h1, qz3; prmt.b32 h0, lo0, hi0, 0x5410;\n"
        "B38:\n"
        "wgmma.wait_group.sync.aligned 2;\n"
        "setp.eq.s32 pr, n, 0;\n"
        "@pr bra.uni SPINW1;\n"
        "BACKW1:\n"
        "wgmma.fence.sync.aligned;\n"
        "add.s64 dt, w2d, 512; wgmma.mma_async.sync.aligned.m64n96k16.f16.f16.f16 {o0,o1,o2,o3,o4,o5,o6,o7,o8,o9,o10,o11,o12,o13,o14,o15,o16,o17,o18,o19,o20,o21,o22,o23}, {g0,g1,g2,g3}, dt, pt, 1, 1, 1;\n"
        "add.s64 dt, w1d, 2688; wgmma.mma_async.sync.aligned.m64n64k16.f16.f16.f16 {qz16,qz17,qz18,qz19,qz20,qz21,qz22,qz23,qz24,qz25,qz26,qz27,qz28,qz29,qz30,qz31}, {qa12,qa13,qa14,qa15}, dt, pt, 1, 1, 1;\n"
        "add.s64 dt, w1d, 2816; wgmma.mma_async.sync.aligned.m64n64k16.f16.f16.f16 {qz16,qz17,qz18,qz19,qz20,qz21,qz22,qz23,qz24,qz25,qz26,qz27,qz28,qz29,qz30,qz31}, {qa16,qa17,qa18,qa19}, dt, pt, 1, 1, 1;\n"
        "add.s64 dt, w1d, 2944; wgmma.mma_async.sync.aligned.m64n64k16.f16.f16.f16 {qz16,qz17,qz18,qz19,qz20,qz21,qz22,qz23,qz24,qz25,qz26,qz27,qz28,qz29,qz30,qz31}, {qa20,qa21,qa22,qa23}, dt, pt, 1, 1, 1;\n"
        "wgmma.commit_group.sync.aligned;\n"
        "@pz bra.uni B42;\n"
        "mov.b32 {xl, xh}, a2; tanh.approx.f16 xr, xl; cvt.u32.u16 lo0, xr; tanh.approx.f16 xr, xh; cvt.u32.u16 hi0, xr; mul.rn.f16x2 a3, qz7, p1; fma.rn.f16x2 p0, qz8, qz8, c; fma.rn.f16x2 g4, qz4, h0, qz4; prmt.b32 h1, lo1, hi1, 0x5410;\n"
        "mov.b32 {xl, xh}, a3; tanh.approx.f16 xr, xl; cvt.u32.u16 lo1, xr; tanh.approx.f16 xr, xh; cvt.u32.u16 hi1, xr; mul.rn.f16x2 a0, qz8, p0; fma.rn.f16x2 p1, qz9, qz9, c; fma.rn.f16x2 g5, qz5, h1, qz5; prmt.b32 h0, lo0, hi0, 0x5410;\n"
        "mov.b32 {xl, xh}, a0; tanh.approx.f16 xr, xl; cvt.u32.u16 lo0, xr; tanh.approx.f16 xr, xh; cvt.u32.u16 hi0, xr; mul.rn.f16x2 a1, qz9, p1; fma.rn.f16x2 p0, qz10, qz10, c; fma.rn.f16x2 g6, qz6, h0, qz6; prmt.b32 h1, lo1, hi1, 0x5410;\n"
        "mov.b32 {xl, xh}, a1; tanh.approx.f16 xr, xl; cvt.u32.u16 lo1, xr; tanh.approx.f16 xr, xh; cvt.u32.u16 hi1, xr; mul.rn.f16x2 a2, qz10, p0; fma.rn.f16x2 p1, qz11, qz11, c; fma.rn.f16x2 g7, qz7, h1, qz7; prmt.b32 h0, lo0, hi0, 0x5410;\n"
        "B42:\n"
        "wgmma.wait_group.sync.aligned 2;\n"
        "wgmma.fence.sync.aligned;\n"
        "add.s64 dt, w2d, 576; wgmma.mma_async.sync.aligned.m64n96k16.f16.f16.f16 {o0,o1,o2,o3,o4,o5,o6,o7,o8,o9,o10,o11,o12,o13,o14,o15,o16,o17,o18,o19,o20,o21,o22,o23}, {g4,g5,g6,g7}, dt, pt, 1, 1, 1;\n"
        "wgmma.commit_group.sync.aligned;\n"
        "@pz bra.uni B46;\n"
        "mov.b32 {xl, xh}, a2; tanh.approx.f16 xr, xl; cvt.u32.u16 lo0, xr; tanh.approx.f16 xr, xh; cvt.u32.u16 hi0, xr; mul.rn.f16x2 a3, qz11, p1; fma.rn.f16x2 p0, qz12, qz12, c; fma.rn.f16x2 g8, qz8, h0, qz8; prmt.b32 h1, lo1, hi1, 0x5410;\n"
        "mov.b32 {xl, xh}, a3; tanh.approx.f16 xr, xl; cvt.u32.u16 lo1, xr; tanh.approx.f16 xr, xh; cvt.u32.u16 hi1, xr; mul.rn.f16x2 a0, qz12, p0; fma.rn.f16x2 p1, qz13, qz13, c; fma.rn.f16x2 g9, qz9, h1, qz9; prmt.b32 h0, lo0, hi0, 0x5410;\n"
        "mov.b32 {xl, xh}, a0; tanh.approx.f16 xr, xl; cvt.u32.u16 lo0, xr; tanh.approx.f16 xr, xh; cvt.u32.u16 hi0, xr; mul.rn.f16x2 a1, qz13, p1; fma.rn.f16x2 p0, qz14, qz14, c; fma.rn.f16x2 g10, qz10, h0, qz10; prmt.b32 h1, lo1, hi1, 0x5410;\n"
        "mov.b32 {xl, xh}, a1; tanh.approx.f16 xr, xl; cvt.u32.u16 lo1, xr; tanh.approx.f16 xr, xh; cvt.u32.u16 hi1, xr; mul.rn.f16x2 a2, qz14, p0; fma.rn.f16x2 p1, qz15, qz15, c; fma.rn.f16x2 g11, qz11, h1, qz11; prmt.b32 h0, lo0, hi0, 0x5410;\n"
        "B46:\n"
        "wgmma.wait_group.sync.aligned 1;\n"
        "wgmma.fence.sync.aligned;\n"
        "add.s64 dt, w2d, 640; wgmma.mma_async.sync.aligned.m64n96k16.f16.f16.f16 {o0,o1,o2,o3,o4,o5,o6,o7,o8,o9,o10,o11,o12,o13,o14,o15,o16,o17,o18,o19,o20,o21,o22,o23}, {g8,g9,g10,g11}, dt, pt, 1, 1, 1;\n"
        "wgmma.commit_group.sync.aligned;\n"
        "mad.lo.u32 tt, n, 8, tbar;\n"
        "@pn mbarrier.arrive.shared::cta.b64 _, [tt+64];\n"
        "@pz bra.uni B50;\n"
        "mov.b32 {xl, xh}, a2; tanh.approx.f16 xr, xl; cvt.u32.u16 lo0, xr; tanh.approx.f16 xr, xh; cvt.u32.u16 hi0, xr; mul.rn.f16x2 a3, qz15, p1; fma.rn.f16x2 p0, qz16, qz16, c; fma.rn.f16x2 g12, qz12, h0, qz12; prmt.b32 h1, lo1, hi1, 0x5410;\n"
        "mov.b32 {xl, xh}, a3; tanh.approx.f16 xr, xl; cvt.u32.u16 lo1, xr; tanh.approx.f16 xr, xh; cvt.u32.u16 hi1, xr; mul.rn.f16x2 a0, qz16, p0; fma.rn.f16x2 p1, qz17, qz17, c; fma.rn.f16x2 g13, qz13, h1, qz13; prmt.b32 h0, lo0, hi0, 0x5410;\n"
        "mov.b32 {xl, xh}, a0; tanh.approx.f16 xr, xl; cvt.u32.u16 lo0, xr; tanh.approx.f16 xr, xh; cvt.u32.u16 hi0, xr; mul.rn.f16x2 a1, qz17, p1; fma.rn.f16x2 p0, qz18, qz18, c; fma.rn.f16x2 g14, qz14, h0, qz14; prmt.b32 h1, lo1, hi1, 0x5410;\n"
        "mov.b32 {xl, xh}, a1; tanh.approx.f16 xr, xl; cvt.u32.u16 lo1, xr; tanh.approx.f16 xr, xh; cvt.u32.u16 hi1, xr; mul.rn.f16x2 a2, qz18, p0; fma.rn.f16x2 p1, qz19, qz19, c; fma.rn.f16x2 g15, qz15, h1, qz15; prmt.b32 h0, lo0, hi0, 0x5410;\n"
        "B50:\n"
        "wgmma.fence.sync.aligned;\n"
        "add.s64 dt, w2d, 704; wgmma.mma_async.sync.aligned.m64n96k16.f16.f16.f16 {o0,o1,o2,o3,o4,o5,o6,o7,o8,o9,o10,o11,o12,o13,o14,o15,o16,o17,o18,o19,o20,o21,o22,o23}, {g12,g13,g14,g15}, dt, pt, 1, 1, 1;\n"
        "add.s64 dt, w1d, 3072; wgmma.mma_async.sync.aligned.m64n64k16.f16.f16.f16 {qz0,qz1,qz2,qz3,qz4,qz5,qz6,qz7,qz8,qz9,qz10,qz11,qz12,qz13,qz14,qz15}, {qa0,qa1,qa2,qa3}, dt, pf, 1, 1, 1;\n"
        "add.s64 dt, w1d, 3200; wgmma.mma_async.sync.aligned.m64n64k16.f16.f16.f16 {qz0,qz1,qz2,qz3,qz4,qz5,qz6,qz7,qz8,qz9,qz10,qz11,qz12,qz13,qz14,qz15}, {qa4,qa5,qa6,qa7}, dt, pt, 1, 1, 1;\n"
        "add.s64 dt, w1d, 3328; wgmma.mma_async.sync.aligned.m64n64k16.f16.f16.f16 {qz0,qz1,qz2,qz3,qz4,qz5,qz6,qz7,qz8,qz9,qz10,qz11,qz12,qz13,qz14,qz15}, {qa8,qa9,qa10,qa11}, dt, pt, 1, 1, 1;\n"
        "wgmma.commit_group.sync.aligned;\n"
        "@pz bra.uni B54;\n"
        "mov.b32 {xl, xh}, a2; tanh.approx.f16 xr, xl; cvt.u32.u16 lo0, xr; tanh.approx.f16 xr, xh; cvt.u32.u16 hi0, xr; mul.rn.f16x2 a3, qz19, p1; fma.rn.f16x2 p0, qz20, qz20, c; fma.rn.f16x2 g0, qz16, h0, qz16; prmt.b32 h1, lo1, hi1, 0x5410;\n"
        "mov.b32 {xl, xh}, a3; tanh.approx.f16 xr, xl; cvt.u32.u16 lo1, xr; tanh.approx.f16 xr, xh; cvt.u32.u16 hi1, xr; mul.rn.f16x2 a0, qz20, p0; fma.rn.f16x2 p1, qz21, qz21, c; fma.rn.f16x2 g1, qz17, h1, qz17; prmt.b32 h0, lo0, hi0, 0x5410;\n"
        "mov.b32 {xl, xh}, a0; tanh.approx.f16 xr, xl; cvt.u32.u16 lo0, xr; tanh.approx.f16 xr, xh; cvt.u32.u16 hi0, xr; mul.rn.f16x2 a1, qz21, p1; fma.rn.f16x2 p0, qz22, qz22, c; fma.rn.f16x2 g2, qz18, h0, qz18; prmt.b32 h1, lo1, hi1, 0x5410;\n"
        "mov.b32 {xl, xh}, a1; tanh.approx.f16 xr, xl; cvt.u32.u16 lo1, xr; tanh.approx.f16 xr, xh; cvt.u32.u16 hi1, xr; mul.rn.f16x2 a2, qz22, p0; fma.rn.f16x2 p1, qz23, qz23, c; fma.rn.f16x2 g3, qz19, h1, qz19; prmt.b32 h0, lo0, hi0, 0x5410;\n"
        "B54:\n"
        "wgmma.wait_group.sync.aligned 2;\n"
        "wgmma.fence.sync.aligned;\n"
        "add.s64 dt, w2d, 768; wgmma.mma_async.sync.aligned.m64n96k16.f16.f16.f16 {o0,o1,o2,o3,o4,o5,o6,o7,o8,o9,o10,o11,o12,o13,o14,o15,o16,o17,o18,o19,o20,o21,o22,o23}, {g0,g1,g2,g3}, dt, pt, 1, 1, 1;\n"
        "add.s64 dt, w1d, 3456; wgmma.mma_async.sync.aligned.m64n64k16.f16.f16.f16 {qz0,qz1,qz2,qz3,qz4,qz5,qz6,qz7,qz8,qz9,qz10,qz11,qz12,qz13,qz14,qz15}, {qa12,qa13,qa14,qa15}, dt, pt, 1, 1, 1;\n"
        "add.s64 dt, w1d, 3584; wgmma.mma_async.sync.aligned.m64n64k16.f16.f16.f16 {qz0,qz1,qz2,qz3,qz4,qz5,qz6,qz7,qz8,qz9,qz10,qz11,qz12,qz13,qz14,qz15}, {qa16,qa17,qa18,qa19}, dt, pt, 1, 1, 1;\n"
        "add.s64 dt, w1d, 3712; wgmma.mma_async.sync.aligned.m64n64k16.f16.f16.f16 {qz0,qz1,qz2,qz3,qz4,qz5,qz6,qz7,qz8,qz9,qz10,qz11,qz12,qz13,qz14,qz15}, {qa20,qa21,qa22,qa23}, dt, pt, 1, 1, 1;\n"
        "wgmma.commit_group.sync.aligned;\n"
        "@pz bra.uni B58;\n"
        "mov.b32 {xl, xh}, a2; tanh.approx.f16 xr, xl; cvt.u32.u16 lo0, xr; tanh.approx.f16 xr, xh; cvt.u32.u16 hi0, xr; mul.rn.f16x2 a3, qz23, p1; fma.rn.f16x2 p0, qz24, qz24, c; fma.rn.f16x2 g4, qz20, h0, qz20; prmt.b32 h1, lo1, hi1, 0x5410;\n"
        "mov.b32 {xl, xh}, a3; tanh.approx.f16 xr, xl; cvt.u32.u16 lo1, xr; tanh.approx.f16 xr, xh; cvt.u32.u16 hi1, xr; mul.rn.f16x2 a0, qz24, p0; fma.rn.f16x2 p1, qz25, qz25, c; fma.rn.f16x2 g5, qz21, h1, qz21; prmt.b32 h0, lo0, hi0, 0x5410;\n"
        "mov.b32 {xl, xh}, a0; tanh.approx.f16 xr, xl; cvt.u32.u16 lo0, xr; tanh.approx.f16 xr, xh; cvt.u32.u16 hi0, xr; mul.rn.f16x2 a1, qz25, p1; fma.rn.f16x2 p0, qz26, qz26, c; fma.rn.f16x2 g6, qz22, h0, qz22; prmt.b32 h1, lo1, hi1, 0x5410;\n"
        "mov.b32 {xl, xh}, a1; tanh.approx.f16 xr, xl; cvt.u32.u16 lo1, xr; tanh.approx.f16 xr, xh; cvt.u32.u16 hi1, xr; mul.rn.f16x2 a2, qz26, p0; fma.rn.f16x2 p1, qz27, qz27, c; fma.rn.f16x2 g7, qz23, h1, qz23; prmt.b32 h0, lo0, hi0, 0x5410;\n"
        "B58:\n"
        "wgmma.wait_group.sync.aligned 2;\n"
        "wgmma.fence.sync.aligned;\n"
        "add.s64 dt, w2d, 832; wgmma.mma_async.sync.aligned.m64n96k16.f16.f16.f16 {o0,o1,o2,o3,o4,o5,o6,o7,o8,o9,o10,o11,o12,o13,o14,o15,o16,o17,o18,o19,o20,o21,o22,o23}, {g4,g5,g6,g7}, dt, pt, 1, 1, 1;\n"
        "wgmma.commit_group.sync.aligned;\n"
        "@pz bra.uni B62;\n"
        "mov.b32 {xl, xh}, a2; tanh.approx.f16 xr, xl; cvt.u32.u16 lo0, xr; tanh.approx.f16 xr, xh; cvt.u32.u16 hi0, xr; mul.rn.f16x2 a3, qz27, p1; fma.rn.f16x2 p0, qz28, qz28, c; fma.rn.f16x2 g8, qz24, h0, qz24; prmt.b32 h1, lo1, hi1, 0x5410;\n"
        "mov.b32 {xl, xh}, a3; tanh.approx.f16 xr, xl; cvt.u32.u16 lo1, xr; tanh.approx.f16 xr, xh; cvt.u32.u16 hi1, xr; mul.rn.f16x2 a0, qz28, p0; fma.rn.f16x2 p1, qz29, qz29, c; fma.rn.f16x2 g9, qz25, h1, qz25; prmt.b32 h0, lo0, hi0, 0x5410;\n"
        "mov.b32 {xl, xh}, a0; tanh.approx.f16 xr, xl; cvt.u32.u16 lo0, xr; tanh.approx.f16 xr, xh; cvt.u32.u16 hi0, xr; mul.rn.f16x2 a1, qz29, p1; fma.rn.f16x2 p0, qz30, qz30, c; fma.rn.f16x2 g10, qz26, h0, qz26; prmt.b32 h1, lo1, hi1, 0x5410;\n"
        "mov.b32 {xl, xh}, a1; tanh.approx.f16 xr, xl; cvt.u32.u16 lo1, xr; tanh.approx.f16 xr, xh; cvt.u32.u16 hi1, xr; mul.rn.f16x2 a2, qz30, p0; fma.rn.f16x2 p1, qz31, qz31, c; fma.rn.f16x2 g11, qz27, h1, qz27; prmt.b32 h0, lo0, hi0, 0x5410;\n"
        "B62:\n"
        "wgmma.wait_group.sync.aligned 1;\n"
        "wgmma.fence.sync.aligned;\n"
        "add.s64 dt, w2d, 896; wgmma.mma_async.sync.aligned.m64n96k16.f16.f16.f16 {o0,o1,o2,o3,o4,o5,o6,o7,o8,o9,o10,o11,o12,o13,o14,o15,o16,o17,o18,o19,o20,o21,o22,o23}, {g8,g9,g10,g11}, dt, pt, 1, 1, 1;\n"
        "wgmma.commit_group.sync.aligned;\n"
        "@pz bra.uni B66;\n"
        "mov.b32 {xl, xh}, a2; tanh.approx.f16 xr, xl; cvt.u32.u16 lo0, xr; tanh.approx.f16 xr, xh; cvt.u32.u16 hi0, xr; mul.rn.f16x2 a3, qz31, p1; fma.rn.f16x2 p0, qz0, qz0, c; fma.rn.f16x2 g12, qz28, h0, qz28; prmt.b32 h1, lo1, hi1, 0x5410;\n"
        "mov.b32 {xl, xh}, a3; tanh.approx.f16 xr, xl; cvt.u32.u16 lo1, xr; tanh.approx.f16 xr, xh; cvt.u32.u16 hi1, xr; mul.rn.f16x2 a0, qz0, p0; fma.rn.f16x2 p1, qz1, qz1, c; fma.rn.f16x2 g13, qz29, h1, qz29; prmt.b32 h0, lo0, hi0, 0x5410;\n"
        "mov.b32 {xl, xh}, a0; tanh.approx.f16 xr, xl; cvt.u32.u16 lo0, xr; tanh.approx.f16 xr, xh; cvt.u32.u16 hi0, xr; mul.rn.f16x2 a1, qz1, p1; fma.rn.f16x2 p0, qz2, qz2, c; fma.rn.f16x2 g14, qz30, h0, qz30; prmt.b32 h1, lo1, hi1, 0x5410;\n"
        "mov.b32 {xl, xh}, a1; tanh.approx.f16 xr, xl; cvt.u32.u16 lo1, xr; tanh.approx.f16 xr, xh; cvt.u32.u16 hi1, xr; mul.rn.f16x2 a2, qz2, p0; fma.rn.f16x2 p1, qz3, qz3, c; fma.rn.f16x2 g15, qz31, h1, qz31; prmt.b32 h0, lo0, hi0, 0x5410;\n"
        "B66:\n"
        "wgmma.fence.sync.aligned;\n"
        "add.s64 dt, w2d, 960; wgmma.mma_async.sync.aligned.m64n96k16.f16.f16.f16 {o0,o1,o2,o3,o4,o5,o6,o7,o8,o9,o10,o11,o12,o13,o14,o15,o16,o17,o18,o19,o20,o21,o22,o23}, {g12,g13,g14,g15}, dt, pt, 1, 1, 1;\n"
        "add.s64 dt, w1d, 3840; wgmma.mma_async.sync.aligned.m64n64k16.f16.f16.f16 {qz16,qz17,qz18,qz19,qz20,qz21,qz22,qz23,qz24,qz25,qz26,qz27,qz28,qz29,qz30,qz31}, {qa0,qa1,qa2,qa3}, dt, pf, 1, 1, 1;\n"
        "add.s64 dt, w1d, 3968; wgmma.mma_async.sync.aligned.m64n64k16.f16.f16.f16 {qz16,qz17,qz18,qz19,qz20,qz21,qz22,qz23,qz24,qz25,qz26,qz27,qz28,qz29,qz30,qz31}, {qa4,qa5,qa6,qa7}, dt, pt, 1, 1, 1;\n"
        "add.s64 dt, w1d, 4096; wgmma.mma_async.sync.aligned.m64n64k16.f16.f16.f16 {qz16,qz17,qz18,qz19,qz20,qz21,qz22,qz23,qz24,qz25,qz26,qz27,qz28,qz29,qz30,qz31}, {qa8,qa9,qa10,qa11}, dt, pt, 1, 1, 1;\n"
        "wgmma.commit_group.sync.aligned;\n"
        "@pz bra.uni B70;\n"
        "mov.b32 {xl, xh}, a2; tanh.approx.f16 xr, xl; cvt.u32.u16 lo0, xr; tanh.approx.f16 xr, xh; cvt.u32.u16 hi0, xr; mul.rn.f16x2 a3, qz3, p1; fma.rn.f16x2 p0, qz4, qz4, c; fma.rn.f16x2 g0, qz0, h0, qz0; prmt.b32 h1, lo1, hi1, 0x5410;\n"
        "mov.b32 {xl, xh}, a3; tanh.approx.f16 xr, xl; cvt.u32.u16 lo1, xr; tanh.approx.f16 xr, xh; cvt.u32.u16 hi1, xr; mul.rn.f16x2 a0, qz4, p0; fma.rn.f16x2 p1, qz5, qz5, c; fma.rn.f16x2 g1, qz1, h1, qz1; prmt.b32 h0, lo0, hi0, 0x5410;\n"
        "mov.b32 {xl, xh}, a0; tanh.approx.f16 xr, xl; cvt.u32.u16 lo0, xr; tanh.approx.f16 xr, xh; cvt.u32.u16 hi0, xr; mul.rn.f16x2 a1, qz5, p1; fma.rn.f16x2 p0, qz6, qz6, c; fma.rn.f16x2 g2, qz2, h0, qz2; prmt.b32 h1, lo1, hi1, 0x5410;\n"
        "mov.b32 {xl, xh}, a1; tanh.approx.f16 xr, xl; cvt.u32.u16 lo1, xr; tanh.approx.f16 xr, xh; cvt.u32.u16 hi1, xr; mul.rn.f16x2 a2, qz6, p0; fma.rn.f16x2 p1, qz7, qz7, c; fma.rn.f16x2 g3, qz3, h1, qz3; prmt.b32 h0, lo0, hi0, 0x5410;\n"
        "B70:\n"
        "wgmma.wait_group.sync.aligned 2;\n"
        "wgmma.fence.sync.aligned;\n"
        "add.s64 dt, w2d, 1024; wgmma.mma_async.sync.aligned.m64n96k16.f16.f16.f16 {o0,o1,o2,o3,o4,o5,o6,o7,o8,o9,o10,o11,o12,o13,o14,o15,o16,o17,o18,o19,o20,o21,o22,o23}, {g0,g1,g2,g3}, dt, pt, 1, 1, 1;\n"
        "add.s64 dt, w1d, 4224; wgmma.mma_async.sync.aligned.m64n64k16.f16.f16.f16 {qz16,qz17,qz18,qz19,qz20,qz21,qz22,qz23,qz24,qz25,qz26,qz27,qz28,qz29,qz30,qz31}, {qa12,qa13,qa14,qa15}, dt, pt, 1, 1, 1;\n"
        "add.s64 dt, w1d, 4352; wgmma.mma_async.sync.aligned.m64n64k16.f16.f16.f16 {qz16,qz17,qz18,qz19,qz20,qz21,qz22,qz23,qz24,qz25,qz26,qz27,qz28,qz29,qz30,qz31}, {qa16,qa17,qa18,qa19}, dt, pt, 1, 1, 1;\n"
        "add.s64 dt, w1d, 4480; wgmma.mma_async.sync.aligned.m64n64k16.f16.f16.f16 {qz16,qz17,qz18,qz19,qz20,qz21,qz22,qz23,qz24,qz25,qz26,qz27,qz28,qz29,qz30,qz31}, {qa20,qa21,qa22,qa23}, dt, pt, 1, 1, 1;\n"
        "wgmma.commit_group.sync.aligned;\n"
        "@pz bra.uni B74;\n"
        "mov.b32 {xl, xh}, a2; tanh.approx.f16 xr, xl; cvt.u32.u16 lo0, xr; tanh.approx.f16 xr, xh; cvt.u32.u16 hi0, xr; mul.rn.f16x2 a3, qz7, p1; fma.rn.f16x2 p0, qz8, qz8, c; fma.rn.f16x2 g4, qz4, h0, qz4; prmt.b32 h1, lo1, hi1, 0x5410;\n"
        "mov.b32 {xl, xh}, a3; tanh.approx.f16 xr, xl; cvt.u32.u16 lo1, xr; tanh.approx.f16 xr, xh; cvt.u32.u16 hi1, xr; mul.rn.f16x2 a0, qz8, p0; fma.rn.f16x2 p1, qz9, qz9, c; fma.rn.f16x2 g5, qz5, h1, qz5; prmt.b32 h0, lo0, hi0, 0x5410;\n"
        "mov.b32 {xl, xh}, a0; tanh.approx.f16 xr, xl; cvt.u32.u16 lo0, xr; tanh.approx.f16 xr, xh; cvt.u32.u16 hi0, xr; mul.rn.f16x2 a1, qz9, p1; fma.rn.f16x2 p0, qz10, qz10, c; fma.rn.f16x2 g6, qz6, h0, qz6; prmt.b32 h1, lo1, hi1, 0x5410;\n"
        "mov.b32 {xl, xh}, a1; tanh.approx.f16 xr, xl; cvt.u32.u16 lo1, xr; tanh.approx.f16 xr, xh; cvt.u32.u16 hi1, xr; mul.rn.f16x2 a2, qz10, p0; fma.rn.f16x2 p1, qz11, qz11, c; fma.rn.f16x2 g7, qz7, h1, qz7; prmt.b32 h0, lo0, hi0, 0x5410;\n"
        "B74:\n"
        "wgmma.wait_group.sync.aligned 2;\n"
        "wgmma.fence.sync.aligned;\n"
        "add.s64 dt, w2d, 1088; wgmma.mma_async.sync.aligned.m64n96k16.f16.f16.f16 {o0,o1,o2,o3,o4,o5,o6,o7,o8,o9,o10,o11,o12,o13,o14,o15,o16,o17,o18,o19,o20,o21,o22,o23}, {g4,g5,g6,g7}, dt, pt, 1, 1, 1;\n"
        "wgmma.commit_group.sync.aligned;\n"
        "@pz bra.uni B78;\n"
        "mov.b32 {xl, xh}, a2; tanh.approx.f16 xr, xl; cvt.u32.u16 lo0, xr; tanh.approx.f16 xr, xh; cvt.u32.u16 hi0, xr; mul.rn.f16x2 a3, qz11, p1; fma.rn.f16x2 p0, qz12, qz12, c; fma.rn.f16x2 g8, qz8, h0, qz8; prmt.b32 h1, lo1, hi1, 0x5410;\n"
        "mov.b32 {xl, xh}, a3; tanh.approx.f16 xr, xl; cvt.u32.u16 lo1, xr; tanh.approx.f16 xr, xh; cvt.u32.u16 hi1, xr; mul.rn.f16x2 a0, qz12, p0; fma.rn.f16x2 p1, qz13, qz13, c; fma.rn.f16x2 g9, qz9, h1, qz9; prmt.b32 h0, lo0, hi0, 0x5410;\n"
        "mov.b32 {xl, xh}, a0; tanh.approx.f16 xr, xl; cvt.u32.u16 lo0, xr; tanh.approx.f16 xr, xh; cvt.u32.u16 hi0, xr; mul.rn.f16x2 a1, qz13, p1; fma.rn.f16x2 p0, qz14, qz14, c; fma.rn.f16x2 g10, qz10, h0, qz10; prmt.b32 h1, lo1, hi1, 0x5410;\n"
        "mov.b32 {xl, xh}, a1; tanh.approx.f16 xr, xl; cvt.u32.u16 lo1, xr; tanh.approx.f16 xr, xh; cvt.u32.u16 hi1, xr; mul.rn.f16x2 a2, qz14, p0; fma.rn.f16x2 p1, qz15, qz15, c; fma.rn.f16x2 g11, qz11, h1, qz11; prmt.b32 h0, lo0, hi0, 0x5410;\n"
        "B78:\n"
        "wgmma.wait_group.sync.aligned 1;\n"
        "wgmma.fence.sync.aligned;\n"
        "add.s64 dt, w2d, 1152; wgmma.mma_async.sync.aligned.m64n96k16.f16.f16.f16 {o0,o1,o2,o3,o4,o5,o6,o7,o8,o9,o10,o11,o12,o13,o14,o15,o16,o17,o18,o19,o20,o21,o22,o23}, {g8,g9,g10,g11}, dt, pt, 1, 1, 1;\n"
        "wgmma.commit_group.sync.aligned;\n"
        "@!pm bra.uni BACKY;\n"
        "add.u32 tt, n, 1; and.b32 tt, tt, 1; mbarrier.try_wait.parity.shared::cta.b64 pw, [ybar], tt;\n"
        "@!pw bra.uni SPINY;\n"
        "BACKY:\n"
        "@pz bra.uni B80;\n"
        "and.b32 ad, %5, 0xffff; xor.b32 ad, ad, 0; add.u32 ad, ad, %4; ldmatrix.sync.aligned.m8n8.x4.shared.b16 {qa0,qa1,qa2,qa3}, [ad];\n"
        "and.b32 ad, %5, 0xffff; xor.b32 ad, ad, 32; add.u32 ad, ad, %4; ldmatrix.sync.aligned.m8n8.x4.shared.b16 {qa4,qa5,qa6,qa7}, [ad];\n"
        "and.b32 ad, %5, 0xffff; xor.b32 ad, ad, 64; add.u32 ad, ad, %4; ldmatrix.sync.aligned.m8n8.x4.shared.b16 {qa8,qa9,qa10,qa11}, [ad];\n"
        "and.b32 ad, %5, 0xffff; xor.b32 ad, ad, 96; add.u32 ad, ad, %4; ldmatrix.sync.aligned.m8n8.x4.shared.b16 {qa12,qa13,qa14,qa15}, [ad];\n"
        "shr.u32 ad, %5, 16; xor.b32 ad, ad, 0; add.u32 ad, ad, %4; ldmatrix.sync.aligned.m8n8.x4.shared.b16 {qa16,qa17,qa18,qa19}, [ad];\n"
        "shr.u32 ad, %5, 16; xor.b32 ad, ad, 32; add.u32 ad, ad, %4; ldmatrix.sync.aligned.m8n8.x4.shared.b16 {qa20,qa21,qa22,qa23}, [ad];\n"
        "mov.b32 {xl, xh}, a2; tanh.approx.f16 xr, xl; cvt.u32.u16 lo0, xr; tanh.approx.f16 xr, xh; cvt.u32.u16 hi0, xr; mul.rn.f16x2 a3, qz15, p1; fma.rn.f16x2 p0, qz16, qz16, c; fma.rn.f16x2 g12, qz12, h0, qz12; prmt.b32 h1, lo1, hi1, 0x5410;\n"
        "mov.b32 {xl, xh}, a3; tanh.approx.f16 xr, xl; cvt.u32.u16 lo1, xr; tanh.approx.f16 xr, xh; cvt.u32.u16 hi1, xr; mul.rn.f16x2 a0, qz16, p0; fma.rn.f16x2 p1, qz17, qz17, c; fma.rn.f16x2 g13, qz13, h1, qz13; prmt.b32 h0, lo0, hi0, 0x5410;\n"
        "B80:\n"
        "fence.proxy.async.shared::cta;\n"
        "add.u32 tt, id, 0;\n"
        "@pk bra.uni XLOAD;\n"
        "bar.arrive tt, 128;\n"
        "XLOADB:\n"
        "@pz bra.uni B82;\n"
        "mov.b32 {xl, xh}, a0; tanh.approx.f16 xr, xl; cvt.u32.u16 lo0, xr; tanh.approx.f16 xr, xh; cvt.u32.u16 hi0, xr; mul.rn.f16x2 a1, qz17, p1; fma.rn.f16x2 p0, qz18, qz18, c; fma.rn.f16x2 g14, qz14, h0, qz14; prmt.b32 h1, lo1, hi1, 0x5410;\n"
        "mov.b32 {xl, xh}, a1; tanh.approx.f16 xr, xl; cvt.u32.u16 lo1, xr; tanh.approx.f16 xr, xh; cvt.u32.u16 hi1, xr; mul.rn.f16x2 a2, qz18, p0; fma.rn.f16x2 p1, qz19, qz19, c; fma.rn.f16x2 g15, qz15, h1, qz15; prmt.b32 h0, lo0, hi0, 0x5410;\n"
        "B82:\n"
        "wgmma.fence.sync.aligned;\n"
        "add.s64 dt, w2d, 1216; wgmma.mma_async.sync.aligned.m64n96k16.f16.f16.f16 {o0,o1,o2,o3,o4,o5,o6,o7,o8,o9,o10,o11,o12,o13,o14,o15,o16,o17,o18,o19,o20,o21,o22,o23}, {g12,g13,g14,g15}, dt, pt, 1, 1, 1;\n"
        "wgmma.commit_group.sync.aligned;\n"
        "@!pm bra.uni SKIP1;\n"
        "wgmma.fence.sync.aligned;\n"
        "add.s64 dt, w1d, 0; wgmma.mma_async.sync.aligned.m64n64k16.f16.f16.f16 {qz0,qz1,qz2,qz3,qz4,qz5,qz6,qz7,qz8,qz9,qz10,qz11,qz12,qz13,qz14,qz15}, {qa0,qa1,qa2,qa3}, dt, pf, 1, 1, 1;\n"
        "add.s64 dt, w1d, 128; wgmma.mma_async.sync.aligned.m64n64k16.f16.f16.f16 {qz0,qz1,qz2,qz3,qz4,qz5,qz6,qz7,qz8,qz9,qz10,qz11,qz12,qz13,qz14,qz15}, {qa4,qa5,qa6,qa7}, dt, pt, 1, 1, 1;\n"
        "add.s64 dt, w1d, 256; wgmma.mma_async.sync.aligned.m64n64k16.f16.f16.f16 {qz0,qz1,qz2,qz3,qz4,qz5,qz6,qz7,qz8,qz9,qz10,qz11,qz12,qz13,qz14,qz15}, {qa8,qa9,qa10,qa11}, dt, pt, 1, 1, 1;\n"
        "SKIP1:\n"
        "@pz bra.uni B86;\n"
        "mov.b32 {xl, xh}, a2; tanh.approx.f16 xr, xl; cvt.u32.u16 lo0, xr; tanh.approx.f16 xr, xh; cvt.u32.u16 hi0, xr; mul.rn.f16x2 a3, qz19, p1; fma.rn.f16x2 p0, qz20, qz20, c; fma.rn.f16x2 g0, qz16, h0, qz16; prmt.b32 h1, lo1, hi1, 0x5410;\n"
        "mov.b32 {xl, xh}, a3; tanh.approx.f16 xr, xl; cvt.u32.u16 lo1, xr; tanh.approx.f16 xr, xh; cvt.u32.u16 hi1, xr; mul.rn.f16x2 a0, qz20, p0; fma.rn.f16x2 p1, qz21, qz21, c; fma.rn.f16x2 g1, qz17, h1, qz17; prmt.b32 h0, lo0, hi0, 0x5410;\n"
        "mov.b32 {xl, xh}, a0; tanh.approx.f16 xr, xl; cvt.u32.u16 lo0, xr; tanh.approx.f16 xr, xh; cvt.u32.u16 hi0, xr; mul.rn.f16x2 a1, qz21, p1; fma.rn.f16x2 p0, qz22, qz22, c; fma.rn.f16x2 g2, qz18, h0, qz18; prmt.b32 h1, lo1, hi1, 0x5410;\n"
        "mov.b32 {xl, xh}, a1; tanh.approx.f16 xr, xl; cvt.u32.u16 lo1, xr; tanh.approx.f16 xr, xh; cvt.u32.u16 hi1, xr; mul.rn.f16x2 a2, qz22, p0; fma.rn.f16x2 p1, qz23, qz23, c; fma.rn.f16x2 g3, qz19, h1, qz19; prmt.b32 h0, lo0, hi0, 0x5410;\n"
        "B86:\n"
        "wgmma.wait_group.sync.aligned 2;\n"
        "wgmma.fence.sync.aligned;\n"
        "add.s64 dt, w2d, 1280; wgmma.mma_async.sync.aligned.m64n96k16.f16.f16.f16 {o0,o1,o2,o3,o4,o5,o6,o7,o8,o9,o10,o11,o12,o13,o14,o15,o16,o17,o18,o19,o20,o21,o22,o23}, {g0,g1,g2,g3}, dt, pt, 1, 1, 1;\n"
        "wgmma.commit_group.sync.aligned;\n"
        "@!pm bra.uni SKIP2;\n"
        "wgmma.fence.sync.aligned;\n"
        "add.s64 dt, w1d, 384; wgmma.mma_async.sync.aligned.m64n64k16.f16.f16.f16 {qz0,qz1,qz2,qz3,qz4,qz5,qz6,qz7,qz8,qz9,qz10,qz11,qz12,qz13,qz14,qz15}, {qa12,qa13,qa14,qa15}, dt, pt, 1, 1, 1;\n"
        "add.s64 dt, w1d, 512; wgmma.mma_async.sync.aligned.m64n64k16.f16.f16.f16 {qz0,qz1,qz2,qz3,qz4,qz5,qz6,qz7,qz8,qz9,qz10,qz11,qz12,qz13,qz14,qz15}, {qa16,qa17,qa18,qa19}, dt, pt, 1, 1, 1;\n"
        "add.s64 dt, w1d, 640; wgmma.mma_async.sync.aligned.m64n64k16.f16.f16.f16 {qz0,qz1,qz2,qz3,qz4,qz5,qz6,qz7,qz8,qz9,qz10,qz11,qz12,qz13,qz14,qz15}, {qa20,qa21,qa22,qa23}, dt, pt, 1, 1, 1;\n"
        "SKIP2:\n"
        "wgmma.fence.sync.aligned;\n"
        "wgmma.commit_group.sync.aligned;\n"
        "@pz bra.uni B90;\n"
        "mov.b32 {xl, xh}, a2; tanh.approx.f16 xr, xl; cvt.u32.u16 lo0, xr; tanh.approx.f16 xr, xh; cvt.u32.u16 hi0, xr; mul.rn.f16x2 a3, qz23, p1; fma.rn.f16x2 p0, qz24, qz24, c; fma.rn.f16x2 g4, qz20, h0, qz20; prmt.b32 h1, lo1, hi1, 0x5410;\n"
        "mov.b32 {xl, xh}, a3; tanh.approx.f16 xr, xl; cvt.u32.u16 lo1, xr; tanh.approx.f16 xr, xh; cvt.u32.u16 hi1, xr; mul.rn.f16x2 a0, qz24, p0; fma.rn.f16x2 p1, qz25, qz25, c; fma.rn.f16x2 g5, qz21, h1, qz21; prmt.b32 h0, lo0, hi0, 0x5410;\n"
        "mov.b32 {xl, xh}, a0; tanh.approx.f16 xr, xl; cvt.u32.u16 lo0, xr; tanh.approx.f16 xr, xh; cvt.u32.u16 hi0, xr; mul.rn.f16x2 a1, qz25, p1; fma.rn.f16x2 p0, qz26, qz26, c; fma.rn.f16x2 g6, qz22, h0, qz22; prmt.b32 h1, lo1, hi1, 0x5410;\n"
        "mov.b32 {xl, xh}, a1; tanh.approx.f16 xr, xl; cvt.u32.u16 lo1, xr; tanh.approx.f16 xr, xh; cvt.u32.u16 hi1, xr; mul.rn.f16x2 a2, qz26, p0; fma.rn.f16x2 p1, qz27, qz27, c; fma.rn.f16x2 g7, qz23, h1, qz23; prmt.b32 h0, lo0, hi0, 0x5410;\n"
        "B90:\n"
        "wgmma.wait_group.sync.aligned 3;\n"
        "wgmma.fence.sync.aligned;\n"
        "add.s64 dt, w2d, 1344; wgmma.mma_async.sync.aligned.m64n96k16.f16.f16.f16 {o0,o1,o2,o3,o4,o5,o6,o7,o8,o9,o10,o11,o12,o13,o14,o15,o16,o17,o18,o19,o20,o21,o22,o23}, {g4,g5,g6,g7}, dt, pt, 1, 1, 1;\n"
        "wgmma.commit_group.sync.aligned;\n"
        "@pz bra.uni B94;\n"
        "mov.b32 {xl, xh}, a2; tanh.approx.f16 xr, xl; cvt.u32.u16 lo0, xr; tanh.approx.f16 xr, xh; cvt.u32.u16 hi0, xr; mul.rn.f16x2 a3, qz27, p1; fma.rn.f16x2 p0, qz28, qz28, c; fma.rn.f16x2 g8, qz24, h0, qz24; prmt.b32 h1, lo1, hi1, 0x5410;\n"
        "mov.b32 {xl, xh}, a3; tanh.approx.f16 xr, xl; cvt.u32.u16 lo1, xr; tanh.approx.f16 xr, xh; cvt.u32.u16 hi1, xr; mul.rn.f16x2 a0, qz28, p0; fma.rn.f16x2 p1, qz29, qz29, c; fma.rn.f16x2 g9, qz25, h1, qz25; prmt.b32 h0, lo0, hi0, 0x5410;\n"
        "mov.b32 {xl, xh}, a0; tanh.approx.f16 xr, xl; cvt.u32.u16 lo0, xr; tanh.approx.f16 xr, xh; cvt.u32.u16 hi0, xr; mul.rn.f16x2 a1, qz29, p1; fma.rn.f16x2 p0, qz30, qz30, c; fma.rn.f16x2 g10, qz26, h0, qz26; prmt.b32 h1, lo1, hi1, 0x5410;\n"
        "mov.b32 {xl, xh}, a1; tanh.approx.f16 xr, xl; cvt.u32.u16 lo1, xr; tanh.approx.f16 xr, xh; cvt.u32.u16 hi1, xr; mul.rn.f16x2 a2, qz30, p0; fma.rn.f16x2 p1, qz31, qz31, c; fma.rn.f16x2 g11, qz27, h1, qz27; prmt.b32 h0, lo0, hi0, 0x5410;\n"
        "B94:\n"
        "wgmma.wait_group.sync.aligned 1;\n"
        "wgmma.fence.sync.aligned;\n"
        "add.s64 dt, w2d, 1408; wgmma.mma_async.sync.aligned.m64n96k16.f16.f16.f16 {o0,o1,o2,o3,o4,o5,o6,o7,o8,o9,o10,o11,o12,o13,o14,o15,o16,o17,o18,o19,o20,o21,o22,o23}, {g8,g9,g10,g11}, dt, pt, 1, 1, 1;\n"
        "wgmma.commit_group.sync.aligned;\n"
        "@pz bra.uni B2;\n"
        "mov.b32 {xl, xh}, a2; tanh.approx.f16 xr, xl; cvt.u32.u16 lo0, xr; tanh.approx.f16 xr, xh; cvt.u32.u16 hi0, xr; mul.rn.f16x2 a3, qz31, p1; fma.rn.f16x2 p0, qz0, qz0, c; fma.rn.f16x2 g12, qz28, h0, qz28; prmt.b32 h1, lo1, hi1, 0x5410;\n"
        "mov.b32 {xl, xh}, a3; tanh.approx.f16 xr, xl; cvt.u32.u16 lo1, xr; tanh.approx.f16 xr, xh; cvt.u32.u16 hi1, xr; mul.rn.f16x2 a0, qz0, p0; fma.rn.f16x2 p1, qz1, qz1, c; fma.rn.f16x2 g13, qz29, h1, qz29; prmt.b32 h0, lo0, hi0, 0x5410;\n"
        "mov.b32 {xl, xh}, a0; tanh.approx.f16 xr, xl; cvt.u32.u16 lo0, xr; tanh.approx.f16 xr, xh; cvt.u32.u16 hi0, xr; mul.rn.f16x2 a1, qz1, p1; fma.rn.f16x2 p0, qz2, qz2, c; fma.rn.f16x2 g14, qz30, h0, qz30; prmt.b32 h1, lo1, hi1, 0x5410;\n"
        "mov.b32 {xl, xh}, a1; tanh.approx.f16 xr, xl; cvt.u32.u16 lo1, xr; tanh.approx.f16 xr, xh; cvt.u32.u16 hi1, xr; mul.rn.f16x2 a2, qz2, p0; fma.rn.f16x2 p1, qz3, qz3, c; fma.rn.f16x2 g15, qz31, h1, qz31; prmt.b32 h0, lo0, hi0, 0x5410;\n"
        "B2:\n"
        "wgmma.fence.sync.aligned;\n"
        "add.s64 dt, w2d, 1472; wgmma.mma_async.sync.aligned.m64n96k16.f16.f16.f16 {o0,o1,o2,o3,o4,o5,o6,o7,o8,o9,o10,o11,o12,o13,o14,o15,o16,o17,o18,o19,o20,o21,o22,o23}, {g12,g13,g14,g15}, dt, pt, 1, 1, 1;\n"
        "wgmma.commit_group.sync.aligned;\n"
        "@!pm bra.uni BE;\n"
        "mov.b32 {xl, xh}, a2; tanh.approx.f16 xr, xl; cvt.u32.u16 lo0, xr; tanh.approx.f16 xr, xh; cvt.u32.u16 hi0, xr; mul.rn.f16x2 a3, qz3, p1; fma.rn.f16x2 p0, qz4, qz4, c; fma.rn.f16x2 g0, qz0, h0, qz0; prmt.b32 h1, lo1, hi1, 0x5410;\n"
        "mov.b32 {xl, xh}, a3; tanh.approx.f16 xr, xl; cvt.u32.u16 lo1, xr; tanh.approx.f16 xr, xh; cvt.u32.u16 hi1, xr; mul.rn.f16x2 a0, qz4, p0; fma.rn.f16x2 p1, qz5, qz5, c; fma.rn.f16x2 g1, qz1, h1, qz1; prmt.b32 h0, lo0, hi0, 0x5410;\n"
        "mov.b32 {xl, xh}, a0; tanh.approx.f16 xr, xl; cvt.u32.u16 lo0, xr; tanh.approx.f16 xr, xh; cvt.u32.u16 hi0, xr; mul.rn.f16x2 a1, qz5, p1; fma.rn.f16x2 p0, qz6, qz6, c; fma.rn.f16x2 g2, qz2, h0, qz2; prmt.b32 h1, lo1, hi1, 0x5410;\n"
        "mov.b32 {xl, xh}, a1; tanh.approx.f16 xr, xl; cvt.u32.u16 lo1, xr; tanh.approx.f16 xr, xh; cvt.u32.u16 hi1, xr; mul.rn.f16x2 a2, qz6, p0; fma.rn.f16x2 p1, qz7, qz7, c; fma.rn.f16x2 g3, qz3, h1, qz3; prmt.b32 h0, lo0, hi0, 0x5410;\n"
        "BE:\n"
        "wgmma.wait_group.sync.aligned 0;\n"
        "bra.uni LOOP;\n"
        "STORE:\n"
        "bar.sync tt, 128;\n"
        "setp.lt.s32 pr, n, 0;\n"
        "@pr bra.uni STOREB;\n"
        "cvt.u64.u32 gp, off; add.s64 gp, gp, %11;\n"
        "elect.sync _|pr, 0xffffffff;\n"
        "@pr cp.async.bulk.global.shared::cta.bulk_group [gp], [%4], 12288;\n"
        "@pr cp.async.bulk.commit_group;\n"
        "bra.uni STOREB;\n"
        "YLOAD:\n"
        "@!pm bra.uni YLOADP;\n"
        "cp.async.bulk.wait_group.read 0;\n"
        "sub.u32 ad, off, %8; cvt.u64.u32 gp, ad; add.s64 gp, gp, %11;\n"
        "elect.sync _|pr, 0xffffffff;\n"
        "@pr mbarrier.arrive.expect_tx.shared::cta.b64 _, [ybar], 12288;\n"
        "@pr cp.async.bulk.shared::cluster.global.mbarrier::complete_tx::bytes [%4], [gp], 12288, [ybar];\n"
        "YLOADP:\n"
        "cvt.u64.u32 gp, off; add.s64 gp, gp, %10;\n"
        "elect.sync _|pr, 0xffffffff;\n"
        "@pr cp.async.bulk.prefetch.L2.global.L2::cache_hint [gp], 12288, pol;\n"
        "bra.uni YLOADB;\n"
        "XLOAD:\n"
        "bar.sync tt, 128;\n"
        "cp.async.bulk.wait_group.read 0;\n"
        "cvt.u64.u32 gp, off; add.s64 gp, gp, %10;\n"
        "elect.sync _|pr, 0xffffffff;\n"
        "@pr mbarrier.arrive.expect_tx.shared::cta.b64 _, [xbar], 12288;\n"
        "@pr cp.async.bulk.shared::cluster.global.mbarrier::complete_tx::bytes.L2::cache_hint [%4], [gp], 12288, [xbar], pol;\n"
        "bra.uni XLOADB;\n"
        "SPINY: mov.u32 cnt, 0;\n"
        "SPINYL:\n"
        "add.u32 tt, n, 1; and.b32 tt, tt, 1; mbarrier.try_wait.parity.shared::cta.b64 pw, [ybar], tt;\n"
        "@pw bra.uni BACKY;\n"
        "add.u32 cnt, cnt, 1; setp.lt.u32 pw, cnt, 0x100000;\n"
        "@pw bra.uni SPINYL;\n"
        "trap;\n"
        "SPINX: mov.u32 cnt, 0;\n"
        "SPINXL:\n"
        "and.b32 tt, n, 1; mbarrier.try_wait.parity.shared::cta.b64 pw, [xbar], tt;\n"
        "@pw bra.uni BACKX;\n"
        "add.u32 cnt, cnt, 1; setp.lt.u32 pw, cnt, 0x100000;\n"
        "@pw bra.uni SPINXL;\n"
        "trap;\n"
        "SPINT: mov.u32 cnt, 0;\n"
        "SPINTL:\n"
        "mad.lo.u32 tt, n, 8, tbar; mbarrier.try_wait.parity.shared::cta.b64 pw, [tt], tpar;\n"
        "@pw bra.uni BACKT;\n"
        "add.u32 cnt, cnt, 1; setp.lt.u32 pw, cnt, 0x100000;\n"
        "@pw bra.uni SPINTL;\n"
        "trap;\n"
        "SPINW0: mov.u32 cnt, 0;\n"
        "SPINW0L:\n"
        "mov.u32 tt, 231208; mbarrier.try_wait.parity.shared::cta.b64 pw, [tt], 0;\n"
        "@pw bra.uni BACKW0;\n"
        "add.u32 cnt, cnt, 1; setp.lt.u32 pw, cnt, 0x100000;\n"
        "@pw bra.uni SPINW0L;\n"
        "trap;\n"
        "SPINW1: mov.u32 cnt, 0;\n"
        "SPINW1L:\n"
        "mov.u32 tt, 231216; mbarrier.try_wait.parity.shared::cta.b64 pw, [tt], 0;\n"
        "@pw bra.uni BACKW1;\n"
        "add.u32 cnt, cnt, 1; setp.lt.u32 pw, cnt, 0x100000;\n"
        "@pw bra.uni SPINW1L;\n"
        "trap;\n"
        "DONE:\n"
        "wgmma.wait_group.sync.aligned 0;\n"
        "}\n"
        :: "r"(prm.w1desc), "r"(prm.w2desc), "r"(c.wg), "r"(c.off), "r"(c.xs), "r"(c.a_offs), "r"(c.xs_offs), "r"(c.bias_addr),
           "r"(c.step), "r"(c.w), "l"(prm.x), "l"(prm.out)
        : "memory");
}

__device__ __forceinline__ float warp_sum(float v) {
#pragma unroll
    for (int s = 16; s >= 1; s >>= 1) v += __shfl_xor_sync(0xffffffffu, v, s);
    return v;
}
__device__ __forceinline__ float pow2f(int e) { return __uint_as_float((uint32_t)(e + 127) << 23); }
__device__ __forceinline__ int exponent_of(float v) { return (int)(__float_as_uint(v) >> 23) - 127; }
__device__ __forceinline__ float lds_bf16(uint32_t addr) {
    uint16_t v; asm volatile("ld.shared.u16 %0, [%1];" : "=h"(v) : "r"(addr) : "memory"); return bf_lo(v);
}

__device__ __forceinline__ void publish_bias(const Params& prm, uint32_t c, uint32_t tag) {
    const uint32_t lane = fresh_tid() & 31;
    const uint32_t col = sb + SM_W2 + (c >> 5) * 24576 + lane * 64 + ((((c >> 3) ^ (lane >> 1)) & 3) * 16) + (c & 7) * 2;
    float v = 0.0f;
#pragma unroll
    for (int k = 0; k < EX / 32; k++) v = fmaf(lds_bf16(col + k * 2048), lds_bf16(sb + SM_BETA + lane * 2 + k * 64), v);
    v = warp_sum(v);
    if (lane == 0) asm volatile("st.relaxed.gpu.global.v2.b32 [%0], {%1, %2};" ::"l"(prm.g->bias + c), "f"(v), "r"(tag) : "memory");
}
__device__ __forceinline__ void collect_bias(const Params& prm, uint32_t tag) {
    const uint32_t lane = fresh_tid() & 31;
    if (lane < 24) {
        const unsigned long long* src = prm.g->bias + 32 * (lane >> 3) + 8 * (lane & 3) + (lane & 4);
        uint32_t v[4], t[4], spins = 0;
        for (;;) {
#pragma unroll
            for (int k = 0; k < 4; k++)
                asm volatile("ld.relaxed.gpu.global.v2.b32 {%0, %1}, [%2];" : "=r"(v[k]), "=r"(t[k]) : "l"(src + k) : "memory");
            if (t[0] == tag && t[1] == tag && t[2] == tag && t[3] == tag) break;
            if (++spins > (1u << 22)) __trap();
        }
        sts128(sb + SM_BIAS + lane * 16, v[0], v[1], v[2], v[3]);
    }
    __syncwarp();
}
__device__ __forceinline__ float fetch_w2_row(uint32_t (&u)[12][4], uint32_t row, uint32_t sw) {
    uint32_t mx[4] = {};
#pragma unroll
    for (int a = 0; a < 3; a++)
#pragma unroll
        for (int k = 0; k < 4; k++) {
            asm volatile("ld.shared.v4.b32 {%0,%1,%2,%3}, [%4];"
                         : "=r"(u[a * 4][k]), "=r"(u[a * 4 + 1][k]), "=r"(u[a * 4 + 2][k]), "=r"(u[a * 4 + 3][k])
                         : "r"(row + a * 24576 + ((k * 16) ^ sw)) : "memory");
#pragma unroll
            for (int b = 0; b < 4; b++) asm("max.xorsign.abs.bf16x2 %0, %0, %1;" : "+r"(mx[b]) : "r"(u[a * 4 + b][k]));
        }
#pragma unroll
    for (int b = 1; b < 4; b++) asm("max.xorsign.abs.bf16x2 %0, %0, %1;" : "+r"(mx[0]) : "r"(mx[b]));
    return fmaxf(fabsf(bf_lo(mx[0])), fabsf(bf_hi(mx[0])));
}

template <bool FAST> __device__ __forceinline__ bool grn_stats(float ss, float gm, float bt, float top, int e, float& gx, float& inv, int& eo) {
    gx = sqrt_fast(fmaf(ss, INV_2A * INV_2A, 1e-6f));
    const float rt = sqrt_fast(ss + 1.0f) * INV_2A * top;
    uint32_t r[4] = {FAST ? __reduce_add_sync(0xffffffffu, __float2uint_rn(gx * 128.0f)) : __float_as_uint(warp_sum(gx)),
                     __reduce_max_sync(0xffffffffu, __float_as_uint(fmaf(bt, top, rt))),
                     __reduce_max_sync(0xffffffffu, __float_as_uint(rt * fabsf(gm) * gx)),
                     (uint32_t)__any_sync(0xffffffffu, !(ss >= 16.0f && ss < ACC_LIMIT))};
    if ((e & 31) == 0) sts128(sb + SM_SEL + (e >> 5) * 16, r[0], r[1], r[2], r[3]);
    MARK(6);
    named_sync(10, 512);
    lds128(r, sb + SM_SEL + min(e & 15, 11) * 16);
    if ((e & 31) >= 12) r[0] = 0;
    const float tot = FAST ? __uint2float_rn(__reduce_add_sync(0xffffffffu, r[0])) * (1.0f / 128) : warp_sum(__uint_as_float(r[0]));
    inv = __fdividef(1.0f, fmaf(tot, 1.0f / EX, 1e-6f));
    const float bound = fmaf(__uint_as_float(__reduce_max_sync(0xffffffffu, r[2])), inv,
                             __uint_as_float(__reduce_max_sync(0xffffffffu, r[1]))) * EX;
    eo = min(max(exponent_of(bound), -90), 126) - 14;
    return __any_sync(0xffffffffu, r[3]);
}

__device__ __forceinline__ float exact_sums(const Params& prm) {
    const int lane = fresh_tid() & 31, warp = fresh_warp(), wg = warp >> 2;
    const uint32_t epoch = lds32(sb + SM_RED + (RED_EPOCH + 1) * 4), bar = sb + SM_BAR + BAR_W1 * 8;
    if (wg < 3) {
        uint32_t wa[2][24], d[2][16];
        float acc[2][2] = {};
        const uint32_t yd = prm.ydesc + ((SM_SPARE - SM_Y1) >> 4), wd = prm.w1desc + ((2 * wg * 12288 + 5 * 2048) >> 4);
        load_w1t(wa, wg, warp & 3, lane);
#pragma unroll 1
        for (int n = 0; n < ROWS_PER_CTA; n++) {
            if (warp == 0) {
                expect_tx(bar, TILE_BYTES);
                bulk_load(sb + SM_SPARE, (const char*)prm.out + (cta_tile0(fresh_cta()) + n * cta_stride(fresh_cta())), TILE_BYTES, bar);
            }
            mbar_wait(bar, (n + 1) & 1);
            gemm1_t<0>(d[0], wa[0], yd, wd);
            gemm1_t<1>(d[1], wa[1], yd, wd);
            wg_wait<0>();
            pin(d[0]); pin(d[1]);
            gelu_sumsq_f(d[0], acc[0]);
            gelu_sumsq_f(d[1], acc[1]);
            named_sync(1, 384);
        }
        publish_sums(acc, prm.g->sums[epoch & 1], &prm.g->count[1], wg, warp & 3, lane);
    }
    grid_wait(&prm.g->count[1], (epoch + 1) * NUM_CTAS);
    return __ldcg(prm.g->sums[epoch & 1] + fresh_tid() % EX);
}

template <bool FIRST> __device__ __forceinline__ void prepare_pass2(const Pass2& c, const Params& prm, float ss) {
    const int tid = fresh_tid(), lane = tid & 31, warp = fresh_warp(), wg = warp >> 2;
    const int e = tid >= EX ? tid - EX : tid;
    const uint32_t w2row = sb + SM_W2 + e * 64, sw = ((e >> 1) & 3) * 16;
    pass2_start(c, prm);
    MARK(2);
    if (wg) {
        uint32_t u[12][4];
        mbar_wait_c<0>(sb + SM_BAR + BAR_W2 * 8);
        const float top = fetch_w2_row(u, w2row, sw);
        MARK(3);
        const float gm = lds_bf16(sb + SM_GAMMA + e * 2), bt = fabsf(lds_bf16(sb + SM_BETA + e * 2));
        if (FIRST) {
            const uint32_t epoch = lds32(sb + SM_RED + RED_EPOCH * 4);
            if (wg == 3) named_sync(11, EX);
            if (warp == 12) collect_bias(prm, epoch + 1);
            MARK(4);
            ss = collect_fast(acc_word(prm, epoch, e));
            if (tid == 416 && fresh_cta() == 0) prm.g->count[0] = epoch + 1;
        }
        if (warp == 4) TS(4);
        MARK(5);
        float gx, inv;
        int eo;
        const bool redo = (grn_stats<FIRST>(ss, gm, bt, top, e, gx, inv, eo) || FORCE_EXACT) && FIRST;
        MARK(8);
        const float up = pow2f(eo), dn = pow2f(-eo);
        if (warp == 4) {
            if (lane == 24) sts64(sb + SM_RED + RED_SCALE * 4, pack_bf2(up, up), redo);
            if (lane < 24 && !redo) {
                uint32_t b[4];
                lds128(b, sb + SM_BIAS + lane * 16);
                const uint32_t p0 = pack_h2(__uint_as_float(b[0]) * dn, __uint_as_float(b[1]) * dn);
                const uint32_t p1 = pack_h2(__uint_as_float(b[2]) * dn, __uint_as_float(b[3]) * dn);
                sts128(sb + SM_BIAS + lane * 16, p0, p0, p1, p1);
            }
            __syncwarp();
            mbar_arrive_if(sb + SM_BAR + BAR_STAT * 8, lane == 0);
        }
        if (!redo) {
            float sc = fmaf(gm, gx * inv, 1.0f) * INV_2A;
            if (eo > 6) {
                const uint32_t dn2 = pack_bf2(dn, dn);
#pragma unroll
                for (int k = 0; k < 48; k++) u[k >> 2][k & 3] = bf2_mul(u[k >> 2][k & 3], dn2);
            } else {
                sc *= dn;
            }
            const uint32_t s2 = pack_bf2(sc * 0x1p-112f, sc * 0x1p-112f);
#pragma unroll
            for (int k = 0; k < 12; k++) {
                uint32_t v[4];
#pragma unroll
                for (int b = 0; b < 4; b++) {
                    v[b] = bf2_mul(u[k][b], s2);
                    v[b] += (v[b] & 0x7fff7fffu) * 7u;
                }
                sts128(w2row + (k >> 2) * 24576 + (((k & 3) * 16) ^ sw), v[0], v[1], v[2], v[3]);
            }
            MARK(9);
            fence_async_smem();
            __syncwarp();
            mbar_arrive_if(sb + SM_BAR + (BAR_ROWS + (wg != 3)) * 8, lane == 0);
        }
        if (warp == 4) TS(5);
    } else {
        asm volatile("bar.arrive 10, 512;" ::: "memory");
    }
}

__device__ __forceinline__ void pass2_uniform(Pass2& c) {
    const int warp = fresh_warp(), wg = warp >> 2;
    c.wg = wg;
    c.w = warp & 3;
    c.off = cta_tile0(fresh_cta()) + (ROWS_PER_CTA - 1 - wg) * cta_stride(fresh_cta());
    c.step = 4 * cta_stride(fresh_cta());
    c.xs = wg == 3 ? sb + SM_BUF3 : sb + SM_Y1 + (wg == 2 ? 2 : 1 - wg) * SLOT_BYTES;
    static_assert((ROWS_PER_CTA - 1) % NX == 1, "slot of the last tile");
}
__device__ __forceinline__ Pass2 pass2_setup() {
    Pass2 c;
    pass2_uniform(c);
    const int lane = fresh_tid() & 31, w = c.w, arow = 16 * w + (lane & 15);
    c.a_offs = (arow * 128 + (((lane >> 4) ^ (arow & 7)) * 16)) |
               (8192 + arow * 64 + (((lane >> 4) ^ ((arow >> 1) & 3)) * 16)) << 16;
    const int g = lane >> 2, px = 33 * (g & 1) + 4 * (g >> 1) + 16 * (w >> 1) + 2 * (w & 1);
    c.xs_offs = (px * 192 + (lane & 3) * 16) | ((px ^ 1) * 192 + (lane & 3) * 16) << 16;
    c.bias_addr = sb + SM_BIAS + (lane & 3) * 16;
    return c;
}

__global__ void __launch_bounds__(512, 1) convnext_kernel(const __grid_constant__ Params prm) {
    extern __shared__ __align__(1024) uint8_t smem[];
    if ((uint32_t)__cvta_generic_to_shared(smem) != sb) __trap();
    if (fresh_warp() == 0) {
        if (fresh_tid() == 0) {
#pragma unroll
            for (int k = 0; k < NX; k++) mbar_init(sb + SM_GO + k * 8, 2);
            mbar_init(sb + SM_BAR + BAR_DW * 8, 1);
            fence_async_smem();
        }
        __syncwarp();
        expect_tx(sb + SM_BAR + BAR_DW * 8, 9 * CH * 2);
        bulk_load(sb + SM_Y1, prm.dw, 9 * CH * 2, sb + SM_BAR + BAR_DW * 8);
        const RowCopy rc = row_copy(prm);
#pragma unroll
        for (int k = 0; k < NX; k++) issue_row_load(rc, k, k);
        SMARK(4);
    } else if (fresh_warp() == 15) {
        const uint32_t cta = fresh_cta();
        bulk_prefetch((const char*)prm.w1 + cta * (CH * EX * 2 / NUM_CTAS), CH * EX * 2 / NUM_CTAS);
        bulk_prefetch(prm.dw, 9 * CH * 2);
        bulk_prefetch((const char*)prm.x + (cta_tile0(cta) - cta_stride(cta)), TILE_BYTES);
    }
    if (fresh_warp() >= 12) {
        Producer pc;
        SMARK(0);
        asm volatile("setmaxnreg.inc.sync.aligned.u32 %0;" ::"n"(PRODUCER_REGS));
        SMARK(1);
        const int w = fresh_warp() & 3, lane = fresh_tid() & 31;
        const int j = lane & 7, hb = (lane >> 3) & 1, base = 4 * (2 * w + (lane >> 4));
        pc.lane = lane; pc.warp = w;
        pc.xoff[0] = hb * XHALF_B + base * 192 + j * 16;
        pc.xoff[1] = hb * XHALF_B + base * 192 + 128 + j * 8;
        const int grp = 4 * w + (lane >> 3);
#pragma unroll
        for (int o = 0; o < 2; o++) {
            const int row = (grp & 7) + 8 * (o ^ hb) + 32 * (grp >> 3);
            pc.yoff[0][o] = row * 128 + ((j ^ (row & 7)) * 16);
            pc.yoff[1][o] = 8192 + row * 64 + (((j >> 1) ^ ((row >> 1) & 3)) * 16) + (j & 1) * 8;
        }
        pc.stat = sb + SM_STAT + (8 * w + (lane >> 2)) * 32;
        pc.own = pc.stat + (lane & 3) * 8;
        const int dstep = fresh_cta() & 8 ? 3 * CH * 2 : -3 * CH * 2;
        named_sync(0, 512);
        mbar_wait_c<0>(sb + SM_BAR + BAR_DW * 8);
        SMARK(8);
#pragma unroll
        for (int tap = 0; tap < 9; tap++) {
            const uint32_t dw = sb + SM_Y1 + (3 + tap % 3) * CH * 2 + (tap / 3 - 1) * dstep;
            lds128(pc.w[tap], dw + j * 16);
            asm volatile("ld.shared.v2.b32 {%0,%1}, [%2];" : "=r"(pc.w[tap][4]), "=r"(pc.w[tap][5]) : "r"(dw + 128 + j * 8) : "memory");
        }
#pragma unroll
        for (int tap = 0; tap < 9; tap++)
#pragma unroll
            for (int u = 0; u < 6; u++) pc.w[tap][u] = bf2_mul(pc.w[tap][u], TAP_SCALE_BF2);
        produce(pc, prm);
        TS(9);
        asm volatile("setmaxnreg.dec.sync.aligned.u32 %0;" ::"n"(EVEN_REGS));
        if (fresh_warp() == 12) {
            mbar_wait_c<0>(sb + SM_BAR + BAR_W2 * 8);
            if (fresh_cta() < CH) publish_bias(prm, fresh_cta(), lds32(sb + SM_RED + RED_EPOCH * 4) + 1);
        }
    } else {
        asm volatile("setmaxnreg.dec.sync.aligned.u32 %0;" ::"n"(CONSUMER_REGS));
        {
            const int tid = fresh_tid(), warp = fresh_warp(), lane = tid & 31;
            uint32_t cnt[2];
            if (warp == 1) {
                if (lane == 0) {
                    mbar_init(sb + SM_BAR + BAR_W1 * 8, 1);
                    mbar_init(sb + SM_BAR + BAR_W1B * 8, 1);
                    fence_async_smem();
                }
                __syncwarp();
#pragma unroll
                for (int h = 0; h < 2; h++) {
                    const uint32_t bar = sb + SM_BAR + (h ? BAR_W1B : BAR_W1) * 8;
                    expect_tx(bar, CH * EX);
#pragma unroll
                    for (int q = h; q < 6; q += 2) tma_load_2d(sb + SM_W1 + q * 12288, &prm.w1_map, 64 * q, 0, bar);
                }
            } else if (warp == 2) {
                if (lane < 2) asm volatile("prefetch.tensormap [%0];" ::"l"(&prm.w1_map + lane) : "memory");
            } else if (warp >= 6) {
                if (lane == 0) {
#pragma unroll 1
                    for (int k = NX + warp - 6; k < GO_COUNT + ROWS_PER_CTA + 2; k += 6)
                        mbar_init(sb + SM_GO + k * 8, k < 2 * NX ? 2 : k < GO_COUNT ? 14 : 4);
                    fence_async_smem();
                }
            } else if (warp == 3) {
                const uint32_t one = (lane & 5) == ((lane & 8) >> 1) + (lane >> 4) ? 0x3f803f80u : 0u;
                sts128(sb + SM_SEL + lane * 16, one, one, one, one);
                fence_async_smem();
            } else if (tid - 128u < NX * 12 && ((fresh_cta() + 1) & 7) < 2) {
                const int k = tid - 128;
                sts128(sb + SM_X + (k / 12) * SLOT_BYTES + ((fresh_cta() & 7) == 0 ? 0 : XHALF_B + 33 * 192) + (k % 12) * 16, 0, 0, 0, 0);
            }
            __syncwarp();
            asm volatile("ld.relaxed.gpu.global.v2.u32 {%0, %1}, [%2];" : "=r"(cnt[0]), "=r"(cnt[1]) : "l"(prm.g->count) : "memory");
            SMARK(0);
            named_sync(0, 512);
            if (tid == 256) {
                sts64(sb + SM_RED + RED_EPOCH * 4, cnt[0], cnt[1] / NUM_CTAS);
#pragma unroll
                for (int k = 0; k < BAR_DW; k++)
                    if (k != BAR_W1 && k != BAR_W1B) mbar_init(sb + SM_BAR + k * 8, k < BAR_TURN || k == BAR_STAT ? 1 : k == BAR_ROWS + 1 ? 8 : 4);
#pragma unroll
                for (int k = 0; k < 3; k++) mbar_arrive_if(sb + SM_BAR + (BAR_Y2FULL + k) * 8, true);
            }
            if (fresh_cta() == 0) *acc_word(prm, cnt[0] + 1, tid) = 0;
            if (fresh_cta() == 1) prm.g->sums[~(cnt[1] / NUM_CTAS) & 1][tid] = 0.0f;
            __syncwarp();
            SMARK(1);
            mbar_wait_c<0>(sb + SM_BAR + BAR_W1 * 8);
            SMARK(2);
        }

        const int tid = fresh_tid(), lane = tid & 31, wg = fresh_warp() >> 2, w = fresh_warp() & 3;
        float acc[2][2];
        const int c = 8 * (lane >> 4) + (lane & 7), ck = 2 * w + ((lane >> 3) & 1);
        consume(acc, sb + SM_W1 + 2 * wg * 12288 + c * 128 + ((ck ^ (c & 7)) * 16), prm.ydesc,
                prm.w1desc + (((2 * wg + 1) * 12288 + 5 * 2048) >> 4), wg * SLOT_BYTES, make_duty(prm, wg, w), w, lane, prm);
        publish_fast(prm, acc, lds32(sb + SM_RED + RED_EPOCH * 4), wg, w, lane);
        if (wg) asm volatile("bar.arrive 11, 384;" ::: "memory");
        MARK(0);
        bulk_wait_all();
        if (wg == 0) TS(3);
        asm volatile("setmaxnreg.inc.sync.aligned.u32 %0;" ::"n"(EVEN_REGS));
    }

    {
        asm volatile(PASS2_STATE);
        MARK(1);
        Pass2 c = pass2_setup();
        prepare_pass2<true>(c, prm, 0.0f);
        if (pass2_head(c, 0)) {
            const float ss = exact_sums(prm);
            c = pass2_setup();
            prepare_pass2<false>(c, prm, ss);
            pass2_head(c, 1);
        }

        pass2_uniform(c);
        pass2_tiles(c, prm);
        bulk_wait_read<0>();
        MARK(13);
    }
}

}

extern "C" void kernel_launch(void* const* d_in, const int* in_sizes, int n_in, void* d_out, int out_size) {
    (void)in_sizes; (void)n_in; (void)out_size;
    typedef CUresult (*EncodeFn)(CUtensorMap*, CUtensorMapDataType, cuuint32_t, void*, const cuuint64_t*, const cuuint64_t*,
                                 const cuuint32_t*, const cuuint32_t*, CUtensorMapInterleave, CUtensorMapSwizzle,
                                 CUtensorMapL2promotion, CUtensorMapFloatOOBfill);
    void* fn = nullptr;
    cudaDriverEntryPointQueryResult status;
    cudaGetDriverEntryPoint("cuTensorMapEncodeTiled", &fn, cudaEnableDefault, &status);
    const EncodeFn encode = (EncodeFn)fn;
    const cuuint32_t ones[2] = {1, 1};

    Params p;
    {
        const cuuint64_t dims[2] = {EX, CH}, strides[1] = {EX * 2};
        const cuuint32_t box[2] = {64, CH};
        encode(&p.w1_map, CU_TENSOR_MAP_DATA_TYPE_BFLOAT16, 2, d_in[2], dims, strides, box, ones,
               CU_TENSOR_MAP_INTERLEAVE_NONE, CU_TENSOR_MAP_SWIZZLE_128B, CU_TENSOR_MAP_L2_PROMOTION_NONE,
               CU_TENSOR_MAP_FLOAT_OOB_FILL_NONE);
    }
    {
        const cuuint64_t dims[2] = {CH, EX}, strides[1] = {CH * 2};
        const cuuint32_t box[2] = {32, 192};
        encode(&p.w2_map, CU_TENSOR_MAP_DATA_TYPE_BFLOAT16, 2, d_in[3], dims, strides, box, ones,
               CU_TENSOR_MAP_INTERLEAVE_NONE, CU_TENSOR_MAP_SWIZZLE_64B, CU_TENSOR_MAP_L2_PROMOTION_NONE,
               CU_TENSOR_MAP_FLOAT_OOB_FILL_NONE);
    }
    p.x = (const __nv_bfloat16*)d_in[0];
    p.dw = (const __nv_bfloat16*)d_in[1];
    p.w1 = (const __nv_bfloat16*)d_in[2];
    p.gamma = (const __nv_bfloat16*)d_in[4];
    p.beta = (const __nv_bfloat16*)d_in[5];
    p.out = (__nv_bfloat16*)d_out;
    cudaGetSymbolAddress((void**)&p.g, g_scratch);
    p.w1desc = desc_lo(sb + SM_W1, 12288);
    p.w2desc = desc_lo(sb + SM_W2, 24576);
    p.ydesc = desc_lo(sb + SM_Y1, 16);
    p.ydesc64[0] = (0x40000040ull << 32) | p.ydesc;
    p.ydesc64[1] = (0x80000020ull << 32) | (p.ydesc + 512);
    for (int k = 0; k < 3; k++) p.sel[k] = (8ull << 32) | desc_lo(sb + SM_SEL + k * 128, k == 2 ? 128 : 0);
    constexpr int smem_bytes = SM_TOTAL;
    cudaFuncSetAttribute(convnext_kernel, cudaFuncAttributeMaxDynamicSharedMemorySize, smem_bytes);
    convnext_kernel<<<NUM_CTAS, 512, smem_bytes>>>(p);
}
```

```cpp
#include <cuda.h>
#include <cuda_runtime.h>
#include <cuda_bf16.h>
#include <stdint.h>

namespace {

constexpr int IMG_W = 512, CH = 96, EX = 384;
constexpr int TILE_PX = 64;
constexpr int ROWS_PER_CTA = 32;
constexpr int NUM_CTAS = 128;
constexpr int STEPS = ROWS_PER_CTA + 2;
constexpr int ROW_BYTES = IMG_W * CH * 2;

#define FORCE_EXACT 0
constexpr int PRODUCER_REGS = 200, CONSUMER_REGS = 104, EVEN_REGS = 128;

constexpr int XHALF_BYTES = 34 * 192;
constexpr int XHALF_B = XHALF_BYTES + 64;
constexpr int XROW_BYTES = XHALF_B + XHALF_BYTES + 64;
constexpr int L2_AHEAD = 2;
constexpr int NX = 3;
constexpr int TILE_BYTES = TILE_PX * 192;

constexpr uint32_t sb = 1024;
constexpr int SM_W1 = 0;
constexpr int SM_W2 = 73728;
constexpr int SM_RING = 147456;
constexpr int SLOT_BYTES = 26624;
constexpr int SM_Y1 = SM_RING;
constexpr int SM_X = SM_Y1 + TILE_BYTES;
constexpr int SM_STAT = SM_X + XROW_BYTES;
constexpr int SM_BUF3 = SM_X + SLOT_BYTES, SM_SPARE = SM_X;
constexpr int SM_SEL = SM_RING + NX * SLOT_BYTES;
constexpr int SM_BIAS = SM_SEL + 512;
constexpr int SM_GAMMA = SM_BIAS + 384;
constexpr int SM_BETA = SM_GAMMA + EX * 2;
constexpr int SM_RED = SM_BETA + EX * 2;
constexpr int SM_BAR = SM_RED + 16;
constexpr int BAR_Y2FULL = 0, BAR_XSFULL = 4, BAR_W1 = 8, BAR_W2 = 9, BAR_W1B = 10, BAR_TURN = 11, BAR_ROWS = 51,
              BAR_STAT = 53, BAR_DW = 54, BAR_COUNT = 55;
constexpr int SM_GO = SM_BAR + BAR_COUNT * 8, GO_COUNT = ROWS_PER_CTA + 2 * NX;
constexpr int SM_YFULL = SM_GO + (GO_COUNT + 1) * 8;
constexpr int SM_TOTAL = SM_YFULL + (ROWS_PER_CTA + 1) * 8;
static_assert(SM_STAT + TILE_PX * 16 <= SM_RING + SLOT_BYTES && XROW_BYTES >= TILE_BYTES && SM_X % 1024 == 0, "ring layout");
static_assert(SM_TOTAL <= 232448, "smem budget");
static_assert(SM_STAT % 128 == 0 && SM_BIAS % 16 == 0 && SM_BAR % 8 == 0 && SLOT_BYTES % 1024 == 0, "alignment");

constexpr int RED_EPOCH = 0, RED_SCALE = 2;

constexpr float GELU_A = 0.32920349f;
constexpr uint32_t GELU_C_H2 = 0x40D940D9u;
constexpr float INV_2A = 1.0f / (2.0f * GELU_A);

constexpr uint32_t TAP_SCALE_BF2 = 0x2B802B80u;
constexpr float LN_EPS_SCALED = 1e-5f * 0x1p-80f;
constexpr float RSTD_SCALE = GELU_A * 0x1p-112f;

struct Scratch {
    unsigned long long acc[2][EX / 4 * 32];
    unsigned long long bias[CH];
    float sums[2][EX];
    uint4 zero_row[66 * 192 / 16];
    unsigned int count[2];
};
__device__ __align__(256) Scratch g_scratch;
constexpr float ACC_LIMIT = 0x1p30f;

#define TS(k)
#define ASM_TS
#define MARK(k)
#define SMARK(k)
#define ASM_MARK
#define ASM_SMARK
#define ASM_TRC(it)

__device__ __forceinline__ void mbar_init(uint32_t bar, uint32_t count) {
    asm volatile("mbarrier.init.shared::cta.b64 [%0], %1;" ::"r"(bar), "r"(count) : "memory");
}
__device__ __forceinline__ void mbar_arrive_if(uint32_t bar, bool pred) {
    asm volatile("{\n.reg .pred p;\nsetp.ne.u32 p, %1, 0;\n@p mbarrier.arrive.shared::cta.b64 _, [%0];\n}\n"
                 ::"r"(bar), "r"((uint32_t)pred) : "memory");
}
__device__ __forceinline__ void mbar_wait(uint32_t bar, uint32_t parity) {
    asm volatile(
        "{\n.reg .pred p;\n.reg .u32 n;\n"
        "mbarrier.try_wait.parity.shared::cta.b64 p, [%0], %1;\n"
        "@p bra.uni WAIT_DONE;\n"
        "mov.u32 n, 0;\n"
        "WAIT_LOOP:\n"
        "mbarrier.try_wait.parity.shared::cta.b64 p, [%0], %1;\n"
        "@p bra.uni WAIT_DONE;\n"
        "mbarrier.try_wait.parity.shared::cta.b64 p, [%0], %1;\n"
        "@p bra.uni WAIT_DONE;\n"
        "mbarrier.try_wait.parity.shared::cta.b64 p, [%0], %1;\n"
        "@p bra.uni WAIT_DONE;\n"
        "add.u32 n, n, 1;\nsetp.lt.u32 p, n, 0x40000;\n"
        "@p bra.uni WAIT_LOOP;\n"
        "trap;\n"
        "WAIT_DONE:\n}\n"
        ::"r"(bar), "r"(parity) : "memory");
}
template <int PARITY> __device__ __forceinline__ void mbar_wait_c(uint32_t bar) {
    asm volatile(
        "{\n.reg .pred p;\n.reg .u32 n;\n"
        "mbarrier.try_wait.parity.shared::cta.b64 p, [%0], %1;\n"
        "@p bra.uni WAIT_DONE;\n"
        "mov.u32 n, 0;\n"
        "WAIT_LOOP:\n"
        "mbarrier.try_wait.parity.shared::cta.b64 p, [%0], %1;\n"
        "@p bra.uni WAIT_DONE;\n"
        "mbarrier.try_wait.parity.shared::cta.b64 p, [%0], %1;\n"
        "@p bra.uni WAIT_DONE;\n"
        "mbarrier.try_wait.parity.shared::cta.b64 p, [%0], %1;\n"
        "@p bra.uni WAIT_DONE;\n"
        "add.u32 n, n, 1;\nsetp.lt.u32 p, n, 0x40000;\n"
        "@p bra.uni WAIT_LOOP;\n"
        "trap;\n"
        "WAIT_DONE:\n}\n"
        ::"r"(bar), "n"(PARITY) : "memory");
}
#define ELECTED(body) "{\n.reg .pred p;\nelect.sync _|p, 0xffffffff;\n" body "}\n"
__device__ __forceinline__ void expect_tx(uint32_t bar, uint32_t bytes) {
    asm volatile(ELECTED("@p mbarrier.arrive.expect_tx.shared::cta.b64 _, [%0], %1;\n") ::"r"(bar), "r"(bytes) : "memory");
}
__device__ __forceinline__ void bulk_load(uint32_t dst, const void* src, uint32_t bytes, uint32_t bar) {
    asm volatile(ELECTED("@p cp.async.bulk.shared::cluster.global.mbarrier::complete_tx::bytes [%0], [%1], %2, [%3];\n")
                 ::"r"(dst), "l"(src), "r"(bytes), "r"(bar) : "memory");
}
__device__ __forceinline__ void bulk_prefetch(const void* src, uint32_t bytes) {
    asm volatile(ELECTED("@p cp.async.bulk.prefetch.L2.global [%0], %1;\n") ::"l"(src), "r"(bytes) : "memory");
}
__device__ __forceinline__ void tma_load_2d(uint32_t dst, const CUtensorMap* map, int c0, int c1, uint32_t bar) {
    asm volatile(ELECTED("@p cp.async.bulk.tensor.2d.shared::cluster.global.mbarrier::complete_tx::bytes [%0], [%1, {%2, %3}], [%4];\n")
                 ::"r"(dst), "l"(map), "r"(c0), "r"(c1), "r"(bar) : "memory");
}
template <int N> __device__ __forceinline__ void bulk_wait_read() {
    asm volatile("cp.async.bulk.wait_group.read %0;" ::"n"(N) : "memory");
}
__device__ __forceinline__ void bulk_wait_all() { asm volatile("cp.async.bulk.wait_group 0;" ::: "memory"); }
__device__ __forceinline__ void fence_async_smem() { asm volatile("fence.proxy.async.shared::cta;" ::: "memory"); }
__device__ __forceinline__ void named_sync(int id, int n) { asm volatile("bar.sync %0, %1;" ::"r"(id), "r"(n) : "memory"); }

__device__ __forceinline__ void sts64(uint32_t addr, uint32_t a, uint32_t b) {
    asm volatile("st.shared.v2.b32 [%0], {%1,%2};" ::"r"(addr), "r"(a), "r"(b) : "memory");
}
__device__ __forceinline__ void sts128(uint32_t addr, uint32_t a, uint32_t b, uint32_t c, uint32_t d) {
    asm volatile("st.shared.v4.b32 [%0], {%1,%2,%3,%4};" ::"r"(addr), "r"(a), "r"(b), "r"(c), "r"(d) : "memory");
}
__device__ __forceinline__ void ldsm4_t(uint32_t* r, uint32_t addr) {
    asm volatile("ldmatrix.sync.aligned.m8n8.x4.trans.shared.b16 {%0,%1,%2,%3}, [%4];"
                 : "=r"(r[0]), "=r"(r[1]), "=r"(r[2]), "=r"(r[3]) : "r"(addr) : "memory");
}
__device__ __forceinline__ void lds128(uint32_t* v, uint32_t addr) {
    asm volatile("ld.shared.v4.b32 {%0,%1,%2,%3}, [%4];"
                 : "=r"(v[0]), "=r"(v[1]), "=r"(v[2]), "=r"(v[3]) : "r"(addr) : "memory");
}
__device__ __forceinline__ uint32_t lds32(uint32_t addr) {
    uint32_t v; asm volatile("ld.shared.b32 %0, [%1];" : "=r"(v) : "r"(addr) : "memory"); return v;
}
__device__ __forceinline__ void sts32(uint32_t addr, uint32_t v) {
    asm volatile("st.shared.b32 [%0], %1;" ::"r"(addr), "r"(v) : "memory");
}

__device__ __forceinline__ uint32_t bf2_fma(uint32_t a, uint32_t b, uint32_t c) {
    uint32_t d; asm("fma.rn.bf16x2 %0, %1, %2, %3;" : "=r"(d) : "r"(a), "r"(b), "r"(c)); return d;
}
__device__ __forceinline__ uint32_t bf2_mul(uint32_t a, uint32_t b) {
    uint32_t d; asm("mul.rn.bf16x2 %0, %1, %2;" : "=r"(d) : "r"(a), "r"(b)); return d;
}
__device__ __forceinline__ uint32_t bf2_add(uint32_t a, uint32_t b) {
    uint32_t d; asm("add.rn.bf16x2 %0, %1, %2;" : "=r"(d) : "r"(a), "r"(b)); return d;
}
__device__ __forceinline__ uint32_t h2_fma(uint32_t a, uint32_t b, uint32_t c) {
    uint32_t d; asm("fma.rn.f16x2 %0, %1, %2, %3;" : "=r"(d) : "r"(a), "r"(b), "r"(c)); return d;
}
__device__ __forceinline__ uint32_t h2_mul(uint32_t a, uint32_t b) {
    uint32_t d; asm("mul.rn.f16x2 %0, %1, %2;" : "=r"(d) : "r"(a), "r"(b)); return d;
}
__device__ __forceinline__ uint32_t h2_tanh(uint32_t a) {
    uint32_t d; asm("tanh.approx.f16x2 %0, %1;" : "=r"(d) : "r"(a)); return d;
}
__device__ __forceinline__ float bf_lo(uint32_t v) { return __uint_as_float(v << 16); }
__device__ __forceinline__ float bf_hi(uint32_t v) { return __uint_as_float(v & 0xffff0000u); }
__device__ __forceinline__ uint32_t pack_h2(float lo, float hi) {
    uint32_t d; asm("cvt.rn.f16x2.f32 %0, %1, %2;" : "=r"(d) : "f"(hi), "f"(lo)); return d;
}
__device__ __forceinline__ uint32_t pack_bf2(float lo, float hi) {
    uint32_t d; asm("cvt.rn.bf16x2.f32 %0, %1, %2;" : "=r"(d) : "f"(hi), "f"(lo)); return d;
}
__device__ __forceinline__ void h2_unpack(uint32_t v, float& lo, float& hi) {
    asm("{\n.reg .b16 l, h;\nmov.b32 {l, h}, %2;\ncvt.f32.f16 %0, l;\ncvt.f32.f16 %1, h;\n}\n" : "=f"(lo), "=f"(hi) : "r"(v));
}

__device__ __forceinline__ uint32_t gelu2(uint32_t z) {
    uint32_t p = h2_fma(z, z, GELU_C_H2);
    uint32_t t = h2_tanh(h2_mul(z, p));
    return h2_fma(z, t, z);
}

__device__ __forceinline__ void wg_fence() { asm volatile("wgmma.fence.sync.aligned;" ::: "memory"); }
__device__ __forceinline__ void wg_commit() { asm volatile("wgmma.commit_group.sync.aligned;" ::: "memory"); }
template <int N> __device__ __forceinline__ void wg_wait() {
    asm volatile("wgmma.wait_group.sync.aligned %0;" ::"n"(N) : "memory");
}
template <int N> __device__ __forceinline__ void pin(uint32_t (&r)[N]) {
#pragma unroll
    for (int i = 0; i < N; i++) asm volatile("" : "+r"(r[i])::"memory");
}
constexpr uint32_t desc_lo(uint32_t addr, uint32_t lbo) { return ((addr & 0x3FFFF) >> 4) | ((lbo >> 4) << 16); }
template <uint32_t SBO, uint32_t SWZ> __device__ __forceinline__ uint64_t desc(uint32_t lo, uint32_t bytes) {
    return (((uint64_t)((SBO >> 4) | (SWZ << 30)) << 32) | lo) + (bytes >> 4);
}
__device__ __forceinline__ uint32_t fresh_tid() {
    uint32_t v; asm volatile("mov.u32 %0, %%tid.x;" : "=r"(v));
    return v;
}
template <uint32_t V> __device__ __forceinline__ uint32_t loop_init() {
    uint32_t v; asm volatile("mov.u32 %0, %1;" : "=r"(v) : "n"(V)); return v;
}
__device__ __forceinline__ int fresh_warp() {
    int v; asm volatile("shfl.sync.idx.b32 %0, %1, 0, 0x1f, 0xffffffff;" : "=r"(v) : "r"(fresh_tid() >> 5)); return v;
}
__device__ __forceinline__ uint32_t fresh_cta() {
    uint32_t v; asm volatile("mov.u32 %0, %%ctaid.x;" : "=r"(v)); return v;
}
__device__ __forceinline__ float sqrt_fast(float v) { float r; asm("sqrt.approx.f32 %0, %1;" : "=f"(r) : "f"(v)); return r; }

template <int TB>
__device__ __forceinline__ void wgmma_n64_h_set(uint32_t (&d)[16], const uint32_t* a, uint64_t desc) {
    asm volatile(
        "{\n.reg .pred p;\nsetp.ne.b32 p, 0, 0;\n"
        "wgmma.mma_async.sync.aligned.m64n64k16.f16.f16.f16 "
        "{%0,%1,%2,%3,%4,%5,%6,%7,%8,%9,%10,%11,%12,%13,%14,%15}, {%16,%17,%18,%19}, %20, p, 1, 1, %21;\n}\n"
        : "=r"(d[0]), "=r"(d[1]), "=r"(d[2]), "=r"(d[3]), "=r"(d[4]), "=r"(d[5]), "=r"(d[6]), "=r"(d[7]), "=r"(d[8]), "=r"(d[9]), "=r"(d[10]), "=r"(d[11]), "=r"(d[12]), "=r"(d[13]), "=r"(d[14]), "=r"(d[15])
        : "r"(a[0]), "r"(a[1]), "r"(a[2]), "r"(a[3]), "l"(desc), "n"(TB));
}
template <int TB>
__device__ __forceinline__ void wgmma_n64_h_acc(uint32_t (&d)[16], const uint32_t* a, uint64_t desc) {
    asm volatile(
        "{\n.reg .pred p;\nsetp.ne.b32 p, 1, 0;\n"
        "wgmma.mma_async.sync.aligned.m64n64k16.f16.f16.f16 "
        "{%0,%1,%2,%3,%4,%5,%6,%7,%8,%9,%10,%11,%12,%13,%14,%15}, {%16,%17,%18,%19}, %20, p, 1, 1, %21;\n}\n"
        : "+r"(d[0]), "+r"(d[1]), "+r"(d[2]), "+r"(d[3]), "+r"(d[4]), "+r"(d[5]), "+r"(d[6]), "+r"(d[7]), "+r"(d[8]), "+r"(d[9]), "+r"(d[10]), "+r"(d[11]), "+r"(d[12]), "+r"(d[13]), "+r"(d[14]), "+r"(d[15])
        : "r"(a[0]), "r"(a[1]), "r"(a[2]), "r"(a[3]), "l"(desc), "n"(TB));
}
__device__ __forceinline__ void wgmma_n64_h_acc_ss(uint32_t (&d)[16], uint64_t adesc, uint64_t desc) {
    asm volatile(
        "{\n.reg .pred p;\nsetp.ne.b32 p, 1, 0;\n"
        "wgmma.mma_async.sync.aligned.m64n64k16.f16.f16.f16 "
        "{%0,%1,%2,%3,%4,%5,%6,%7,%8,%9,%10,%11,%12,%13,%14,%15}, %16, %17, p, 1, 1, 1, 0;\n}\n"
        : "+r"(d[0]), "+r"(d[1]), "+r"(d[2]), "+r"(d[3]), "+r"(d[4]), "+r"(d[5]), "+r"(d[6]), "+r"(d[7]), "+r"(d[8]), "+r"(d[9]), "+r"(d[10]), "+r"(d[11]), "+r"(d[12]), "+r"(d[13]), "+r"(d[14]), "+r"(d[15])
        : "l"(adesc), "l"(desc));
}

struct Params {
    CUtensorMap w1_map, w2_map;
    const __nv_bfloat16* x;
    const __nv_bfloat16* dw;
    const __nv_bfloat16* w1;
    const __nv_bfloat16* gamma;
    const __nv_bfloat16* beta;
    __nv_bfloat16* out;
    Scratch* g;
    uint64_t ydesc64[2];
    uint64_t sel[3];
    uint32_t w1desc, w2desc, ydesc;
};

__device__ __forceinline__ int cta_stride(uint32_t cta) { return cta & 8 ? ROW_BYTES : -ROW_BYTES; }
__device__ __forceinline__ uint32_t cta_tile0(uint32_t cta) {
    return ((cta >> 3) * ROWS_PER_CTA + (cta & 8 ? 0 : ROWS_PER_CTA - 1)) * ROW_BYTES + (cta & 7) * TILE_BYTES;
}

struct Producer {
    uint32_t w[9][6];
    uint32_t xoff[2];
    uint32_t yoff[2][2];
    uint32_t stat, own;
    int lane;
};

struct RowCopy {
    const char* x0;
    char* y0;
    const char* zeros;
    uint32_t cut0, cut1;
    int stride, last;
};
__device__ __forceinline__ RowCopy row_copy(const Params& prm) {
    const uint32_t cta = fresh_cta(), strip = cta & 7, t0 = cta_tile0(cta);
    RowCopy r;
    r.stride = cta_stride(cta);
    r.x0 = (const char*)prm.x + (t0 - r.stride) - 192;
    r.y0 = (char*)prm.out + t0;
    r.zeros = (const char*)prm.g->zero_row;
    r.cut0 = strip == 0 ? 192 : 0;
    r.cut1 = strip == 7 ? 192 : 0;
    r.last = cta - 8 >= NUM_CTAS - 16 ? STEPS - 2 : STEPS - 1;
    return r;
}
__device__ __forceinline__ void issue_row_load(const RowCopy& r, int i, uint32_t slot) {
    const char* src = r.x0 + i * r.stride;
    const uint32_t bar = sb + SM_GO + i * 8, dst = sb + SM_X + slot * SLOT_BYTES;
    expect_tx(bar, XHALF_BYTES - r.cut0);
    bulk_load(dst + r.cut0, src + r.cut0, XHALF_BYTES - r.cut0, bar);
    expect_tx(bar, XHALF_BYTES - r.cut1);
    bulk_load(dst + XHALF_B, src + 32 * 192, XHALF_BYTES - r.cut1, bar);
}

__device__ __forceinline__ float quad_sum(float v) {
    v += __shfl_xor_sync(0xffffffffu, v, 1);
    v += __shfl_xor_sync(0xffffffffu, v, 2);
    return v;
}

__device__ __forceinline__ void load_x(uint32_t (&v)[6][6], const Producer& c, uint32_t row) {
#pragma unroll
    for (int k = 0; k < 6; k++) {
        asm volatile("ld.shared.v4.b32 {%0,%1,%2,%3}, [%4];"
                     : "=r"(v[k][0]), "=r"(v[k][1]), "=r"(v[k][2]), "=r"(v[k][3]) : "r"(row + c.xoff[0] + k * 192));
        asm volatile("ld.shared.v2.b32 {%0,%1}, [%2];" : "=r"(v[k][4]), "=r"(v[k][5]) : "r"(row + c.xoff[1] + k * 192));
    }
}
template <int DY, int STRIDE>
__device__ __forceinline__ void conv_row(uint32_t (&dst)[24], const uint32_t* src, const uint32_t (&v)[6][6], const Producer& c) {
#pragma unroll
    for (int o = 0; o < 4; o++)
#pragma unroll
        for (int u = 0; u < 6; u++)
            dst[o * 6 + u] = bf2_fma(v[o + 2][u], c.w[3 * DY + 2][u], bf2_fma(v[o + 1][u], c.w[3 * DY + 1][u],
                             bf2_fma(v[o][u], c.w[3 * DY][u], STRIDE ? src[o * 6 + u] : src[2 * o + 1])));
}
#define HAND_OVER(name, base, r) asm volatile("mov.b32 " name "%6, %0; mov.b32 " name "%7, %1; mov.b32 " name "%8, %2;\n" \
    "mov.b32 " name "%9, %3; mov.b32 " name "%10, %4; mov.b32 " name "%11, %5;" ::"r"((r)[0]), "r"((r)[1]), "r"((r)[2]), \
    "r"((r)[3]), "r"((r)[4]), "r"((r)[5]), "n"(base), "n"(base + 1), "n"(base + 2), "n"(base + 3), "n"(base + 4), "n"(base + 5))
template <int K> __device__ __forceinline__ void hand_over(const Producer& c, const uint32_t (&B)[24], const uint32_t (&C)[24],
                                                           const uint32_t (&v)[6][6]) {
    HAND_OVER("pw", K * 6, c.w[K]);
    if (K < 6) HAND_OVER("pv", K * 6, v[K % 6]);
    if (K < 4) { HAND_OVER("pb", K * 6, B + K % 4 * 6); HAND_OVER("pc", K * 6, C + K % 4 * 6); }
    if constexpr (K < 8) hand_over<K + 1>(c, B, C, v);
}
__device__ __forceinline__ void produce_tiles(const Producer& c, const Params& prm) {
    asm volatile(
        "{\n"
        ".reg .b32 pa<24>, pq<4>, m<6>, y<6>, rr, mm, t, so, ad, tt, cnt;\n"
        ".reg .b16 xl, xh;\n"
        ".reg .f32 d<4>, us, s0, s1, f0, f1, kq;\n"
        ".reg .pred pt, pf, pr, pw, pl, po, pe;\n"
        "setp.ne.b32 pt, 1, 0; setp.ne.b32 pf, 0, 0; setp.eq.u32 pl, %8, 0; and.b32 tt, %8, 1; setp.ne.u32 po, tt, 0;\n"
        "and.b32 tt, %8, 4; setp.ne.u32 pr, tt, 0; selp.f32 kq, 0f3F802D41, 0f3F7FA57E, pr;\n"
        "mov.u32 t, 0; mov.u32 so, 0;\n"
        "setp.eq.u32 pr, %12, 0;\n"
        "@pr bra.uni RARE;\n"
        "LOOP:\n"
        ASM_TRC("t")
        "fma.rn.bf16x2 pa0, pv0, pw36, pb0; fma.rn.bf16x2 pa1, pv1, pw37, pb1; fma.rn.bf16x2 pa2, pv2, pw38, pb2; fma.rn.bf16x2 pa3, pv3, pw39, pb3; fma.rn.bf16x2 pa4, pv4, pw40, pb4; fma.rn.bf16x2 pa5, pv5, pw41, pb5;\n"
        "fma.rn.bf16x2 pa6, pv6, pw36, pb6; fma.rn.bf16x2 pa7, pv7, pw37, pb7; fma.rn.bf16x2 pa8, pv8, pw38, pb8; fma.rn.bf16x2 pa9, pv9, pw39, pb9; fma.rn.bf16x2 pa10, pv10, pw40, pb10; fma.rn.bf16x2 pa11, pv11, pw41, pb11;\n"
        "fma.rn.bf16x2 pa12, pv12, pw36, pb12; fma.rn.bf16x2 pa13, pv13, pw37, pb13; fma.rn.bf16x2 pa14, pv14, pw38, pb14; fma.rn.bf16x2 pa15, pv15, pw39, pb15; fma.rn.bf16x2 pa16, pv16, pw40, pb16; fma.rn.bf16x2 pa17, pv17, pw41, pb17;\n"
        "fma.rn.bf16x2 pa18, pv18, pw36, pb18; fma.rn.bf16x2 pa19, pv19, pw37, pb19; fma.rn.bf16x2 pa20, pv20, pw38, pb20; fma.rn.bf16x2 pa21, pv21, pw39, pb21; fma.rn.bf16x2 pa22, pv22, pw40, pb22; fma.rn.bf16x2 pa23, pv23, pw41, pb23;\n"
        "fma.rn.bf16x2 pa0, pv6, pw42, pa0; fma.rn.bf16x2 pa1, pv7, pw43, pa1; fma.rn.bf16x2 pa2, pv8, pw44, pa2; fma.rn.bf16x2 pa3, pv9, pw45, pa3; fma.rn.bf16x2 pa4, pv10, pw46, pa4; fma.rn.bf16x2 pa5, pv11, pw47, pa5;\n"
        "fma.rn.bf16x2 pa6, pv12, pw42, pa6; fma.rn.bf16x2 pa7, pv13, pw43, pa7; fma.rn.bf16x2 pa8, pv14, pw44, pa8; fma.rn.bf16x2 pa9, pv15, pw45, pa9; fma.rn.bf16x2 pa10, pv16, pw46, pa10; fma.rn.bf16x2 pa11, pv17, pw47, pa11;\n"
        "fma.rn.bf16x2 pa12, pv18, pw42, pa12; fma.rn.bf16x2 pa13, pv19, pw43, pa13; fma.rn.bf16x2 pa14, pv20, pw44, pa14; fma.rn.bf16x2 pa15, pv21, pw45, pa15; fma.rn.bf16x2 pa16, pv22, pw46, pa16; fma.rn.bf16x2 pa17, pv23, pw47, pa17;\n"
        "fma.rn.bf16x2 pa18, pv24, pw42, pa18; fma.rn.bf16x2 pa19, pv25, pw43, pa19; fma.rn.bf16x2 pa20, pv26, pw44, pa20; fma.rn.bf16x2 pa21, pv27, pw45, pa21; fma.rn.bf16x2 pa22, pv28, pw46, pa22; fma.rn.bf16x2 pa23, pv29, pw47, pa23;\n"
        "fma.rn.bf16x2 pa0, pv12, pw48, pa0; fma.rn.bf16x2 pa1, pv13, pw49, pa1; fma.rn.bf16x2 pa2, pv14, pw50, pa2; fma.rn.bf16x2 pa3, pv15, pw51, pa3; fma.rn.bf16x2 pa4, pv16, pw52, pa4; fma.rn.bf16x2 pa5, pv17, pw53, pa5;\n"
        "fma.rn.bf16x2 pa6, pv18, pw48, pa6; fma.rn.bf16x2 pa7, pv19, pw49, pa7; fma.rn.bf16x2 pa8, pv20, pw50, pa8; fma.rn.bf16x2 pa9, pv21, pw51, pa9; fma.rn.bf16x2 pa10, pv22, pw52, pa10; fma.rn.bf16x2 pa11, pv23, pw53, pa11;\n"
        "fma.rn.bf16x2 pa12, pv24, pw48, pa12; fma.rn.bf16x2 pa13, pv25, pw49, pa13; fma.rn.bf16x2 pa14, pv26, pw50, pa14; fma.rn.bf16x2 pa15, pv27, pw51, pa15; fma.rn.bf16x2 pa16, pv28, pw52, pa16; fma.rn.bf16x2 pa17, pv29, pw53, pa17;\n"
        "fma.rn.bf16x2 pa18, pv30, pw48, pa18; fma.rn.bf16x2 pa19, pv31, pw49, pa19; fma.rn.bf16x2 pa20, pv32, pw50, pa20; fma.rn.bf16x2 pa21, pv33, pw51, pa21; fma.rn.bf16x2 pa22, pv34, pw52, pa22; fma.rn.bf16x2 pa23, pv35, pw53, pa23;\n"
        "mul.rn.bf16x2 pq0, pa0, pa0; fma.rn.bf16x2 pq0, pa1, pa1, pq0; fma.rn.bf16x2 pq0, pa2, pa2, pq0; fma.rn.bf16x2 pq0, pa3, pa3, pq0; fma.rn.bf16x2 pq0, pa4, pa4, pq0; fma.rn.bf16x2 pq0, pa5, pa5, pq0;\n"
        "mul.rn.bf16x2 pq1, pa6, pa6; fma.rn.bf16x2 pq1, pa7, pa7, pq1; fma.rn.bf16x2 pq1, pa8, pa8, pq1; fma.rn.bf16x2 pq1, pa9, pa9, pq1; fma.rn.bf16x2 pq1, pa10, pa10, pq1; fma.rn.bf16x2 pq1, pa11, pa11, pq1;\n"
        "mul.rn.bf16x2 pq2, pa12, pa12; fma.rn.bf16x2 pq2, pa13, pa13, pq2; fma.rn.bf16x2 pq2, pa14, pa14, pq2; fma.rn.bf16x2 pq2, pa15, pa15, pq2; fma.rn.bf16x2 pq2, pa16, pa16, pq2; fma.rn.bf16x2 pq2, pa17, pa17, pq2;\n"
        "mul.rn.bf16x2 pq3, pa18, pa18; fma.rn.bf16x2 pq3, pa19, pa19, pq3; fma.rn.bf16x2 pq3, pa20, pa20, pq3; fma.rn.bf16x2 pq3, pa21, pa21, pq3; fma.rn.bf16x2 pq3, pa22, pa22, pq3; fma.rn.bf16x2 pq3, pa23, pa23, pq3;\n"
        "B0:\n"
        "wgmma.fence.sync.aligned;\n"
        "wgmma.mma_async.sync.aligned.m64n8k16.f32.bf16.bf16 {d0,d1,d2,d3}, {pa0,pa6,pa1,pa7}, %9, pf, 1, 1, 0;\n"
        "wgmma.mma_async.sync.aligned.m64n8k16.f32.bf16.bf16 {d0,d1,d2,d3}, {pa2,pa8,pa3,pa9}, %9, pt, 1, 1, 0;\n"
        "wgmma.mma_async.sync.aligned.m64n8k16.f32.bf16.bf16 {d0,d1,d2,d3}, {pa4,pa10,pa5,pa11}, %9, pt, 1, 1, 0;\n"
        "wgmma.mma_async.sync.aligned.m64n8k16.f32.bf16.bf16 {d0,d1,d2,d3}, {pa12,pa18,pa13,pa19}, %10, pt, 1, 1, 0;\n"
        "wgmma.mma_async.sync.aligned.m64n8k16.f32.bf16.bf16 {d0,d1,d2,d3}, {pa14,pa20,pa15,pa21}, %10, pt, 1, 1, 0;\n"
        "wgmma.mma_async.sync.aligned.m64n8k16.f32.bf16.bf16 {d0,d1,d2,d3}, {pa16,pa22,pa17,pa23}, %10, pt, 1, 1, 0;\n"
        "wgmma.mma_async.sync.aligned.m64n8k16.f32.bf16.bf16 {d0,d1,d2,d3}, {pq0,pq1,pq2,pq3}, %11, pt, 1, 1, 0;\n"
        "wgmma.commit_group.sync.aligned;\n"
        "fence.proxy.async.shared::cta;\n"
        "@pl mbarrier.arrive.shared::cta.b64 _, [t+231544];\n"
        "add.u32 ad, %7, so; ld.shared.f32 us, [ad+4];\n"
        "fma.rn.bf16x2 pb0, pv0, pw18, pc0; fma.rn.bf16x2 pb1, pv1, pw19, pc1; fma.rn.bf16x2 pb2, pv2, pw20, pc2; fma.rn.bf16x2 pb3, pv3, pw21, pc3; fma.rn.bf16x2 pb4, pv4, pw22, pc4; fma.rn.bf16x2 pb5, pv5, pw23, pc5;\n"
        "fma.rn.bf16x2 pb6, pv6, pw18, pc6; fma.rn.bf16x2 pb7, pv7, pw19, pc7; fma.rn.bf16x2 pb8, pv8, pw20, pc8; fma.rn.bf16x2 pb9, pv9, pw21, pc9; fma.rn.bf16x2 pb10, pv10, pw22, pc10; fma.rn.bf16x2 pb11, pv11, pw23, pc11;\n"
        "fma.rn.bf16x2 pb0, pv6, pw24, pb0; fma.rn.bf16x2 pb1, pv7, pw25, pb1; fma.rn.bf16x2 pb2, pv8, pw26, pb2; fma.rn.bf16x2 pb3, pv9, pw27, pb3; fma.rn.bf16x2 pb4, pv10, pw28, pb4; fma.rn.bf16x2 pb5, pv11, pw29, pb5;\n"
        "fma.rn.bf16x2 pb6, pv12, pw24, pb6; fma.rn.bf16x2 pb7, pv13, pw25, pb7; fma.rn.bf16x2 pb8, pv14, pw26, pb8; fma.rn.bf16x2 pb9, pv15, pw27, pb9; fma.rn.bf16x2 pb10, pv16, pw28, pb10; fma.rn.bf16x2 pb11, pv17, pw29, pb11;\n"
        "fma.rn.bf16x2 pb0, pv12, pw30, pb0; fma.rn.bf16x2 pb1, pv13, pw31, pb1; fma.rn.bf16x2 pb2, pv14, pw32, pb2; fma.rn.bf16x2 pb3, pv15, pw33, pb3; fma.rn.bf16x2 pb4, pv16, pw34, pb4; fma.rn.bf16x2 pb5, pv17, pw35, pb5;\n"
        "fma.rn.bf16x2 pb6, pv18, pw30, pb6; fma.rn.bf16x2 pb7, pv19, pw31, pb7; fma.rn.bf16x2 pb8, pv20, pw32, pb8; fma.rn.bf16x2 pb9, pv21, pw33, pb9; fma.rn.bf16x2 pb10, pv22, pw34, pb10; fma.rn.bf16x2 pb11, pv23, pw35, pb11;\n"
        "B1:\n"
        "fma.rn.bf16x2 pb12, pv12, pw18, pc12; fma.rn.bf16x2 pb13, pv13, pw19, pc13; fma.rn.bf16x2 pb14, pv14, pw20, pc14; fma.rn.bf16x2 pb15, pv15, pw21, pc15; fma.rn.bf16x2 pb16, pv16, pw22, pc16; fma.rn.bf16x2 pb17, pv17, pw23, pc17;\n"
        "fma.rn.bf16x2 pb18, pv18, pw18, pc18; fma.rn.bf16x2 pb19, pv19, pw19, pc19; fma.rn.bf16x2 pb20, pv20, pw20, pc20; fma.rn.bf16x2 pb21, pv21, pw21, pc21; fma.rn.bf16x2 pb22, pv22, pw22, pc22; fma.rn.bf16x2 pb23, pv23, pw23, pc23;\n"
        "fma.rn.bf16x2 pb12, pv18, pw24, pb12; fma.rn.bf16x2 pb13, pv19, pw25, pb13; fma.rn.bf16x2 pb14, pv20, pw26, pb14; fma.rn.bf16x2 pb15, pv21, pw27, pb15; fma.rn.bf16x2 pb16, pv22, pw28, pb16; fma.rn.bf16x2 pb17, pv23, pw29, pb17;\n"
        "fma.rn.bf16x2 pb18, pv24, pw24, pb18; fma.rn.bf16x2 pb19, pv25, pw25, pb19; fma.rn.bf16x2 pb20, pv26, pw26, pb20; fma.rn.bf16x2 pb21, pv27, pw27, pb21; fma.rn.bf16x2 pb22, pv28, pw28, pb22; fma.rn.bf16x2 pb23, pv29, pw29, pb23;\n"
        "fma.rn.bf16x2 pb12, pv24, pw30, pb12; fma.rn.bf16x2 pb13, pv25, pw31, pb13; fma.rn.bf16x2 pb14, pv26, pw32, pb14; fma.rn.bf16x2 pb15, pv27, pw33, pb15; fma.rn.bf16x2 pb16, pv28, pw34, pb16; fma.rn.bf16x2 pb17, pv29, pw35, pb17;\n"
        "fma.rn.bf16x2 pb18, pv30, pw30, pb18; fma.rn.bf16x2 pb19, pv31, pw31, pb19; fma.rn.bf16x2 pb20, pv32, pw32, pb20; fma.rn.bf16x2 pb21, pv33, pw33, pb21; fma.rn.bf16x2 pb22, pv34, pw34, pb22; fma.rn.bf16x2 pb23, pv35, pw35, pb23;\n"
        "C0:\n"
        "wgmma.wait_group.sync.aligned 0;\n"
        "selp.f32 s0, d2, d0, po; selp.f32 s1, d3, d1, po;\n"
        "shfl.sync.bfly.b32 f0, s0, 4, 0x1f, 0xffffffff; shfl.sync.bfly.b32 f1, s1, 4, 0x1f, 0xffffffff;\n"
        "fma.rn.bf16x2 pc0, pv0, pw0, ps1; fma.rn.bf16x2 pc1, pv1, pw1, ps1; fma.rn.bf16x2 pc2, pv2, pw2, ps1; fma.rn.bf16x2 pc3, pv3, pw3, ps1; fma.rn.bf16x2 pc4, pv4, pw4, ps1; fma.rn.bf16x2 pc5, pv5, pw5, ps1;\n"
        "fma.rn.bf16x2 pc6, pv6, pw0, ps3; fma.rn.bf16x2 pc7, pv7, pw1, ps3; fma.rn.bf16x2 pc8, pv8, pw2, ps3; fma.rn.bf16x2 pc9, pv9, pw3, ps3; fma.rn.bf16x2 pc10, pv10, pw4, ps3; fma.rn.bf16x2 pc11, pv11, pw5, ps3;\n"
        "fma.rn.bf16x2 pc12, pv12, pw0, ps5; fma.rn.bf16x2 pc13, pv13, pw1, ps5; fma.rn.bf16x2 pc14, pv14, pw2, ps5; fma.rn.bf16x2 pc15, pv15, pw3, ps5; fma.rn.bf16x2 pc16, pv16, pw4, ps5; fma.rn.bf16x2 pc17, pv17, pw5, ps5;\n"
        "fma.rn.bf16x2 pc18, pv18, pw0, ps7; fma.rn.bf16x2 pc19, pv19, pw1, ps7; fma.rn.bf16x2 pc20, pv20, pw2, ps7; fma.rn.bf16x2 pc21, pv21, pw3, ps7; fma.rn.bf16x2 pc22, pv22, pw4, ps7; fma.rn.bf16x2 pc23, pv23, pw5, ps7;\n"
        "fma.rn.bf16x2 pc0, pv6, pw6, pc0; fma.rn.bf16x2 pc1, pv7, pw7, pc1; fma.rn.bf16x2 pc2, pv8, pw8, pc2; fma.rn.bf16x2 pc3, pv9, pw9, pc3; fma.rn.bf16x2 pc4, pv10, pw10, pc4; fma.rn.bf16x2 pc5, pv11, pw11, pc5;\n"
        "fma.rn.bf16x2 pc6, pv12, pw6, pc6; fma.rn.bf16x2 pc7, pv13, pw7, pc7; fma.rn.bf16x2 pc8, pv14, pw8, pc8; fma.rn.bf16x2 pc9, pv15, pw9, pc9; fma.rn.bf16x2 pc10, pv16, pw10, pc10; fma.rn.bf16x2 pc11, pv17, pw11, pc11;\n"
        "fma.rn.bf16x2 pc12, pv18, pw6, pc12; fma.rn.bf16x2 pc13, pv19, pw7, pc13; fma.rn.bf16x2 pc14, pv20, pw8, pc14; fma.rn.bf16x2 pc15, pv21, pw9, pc15; fma.rn.bf16x2 pc16, pv22, pw10, pc16; fma.rn.bf16x2 pc17, pv23, pw11, pc17;\n"
        "fma.rn.bf16x2 pc18, pv24, pw6, pc18; fma.rn.bf16x2 pc19, pv25, pw7, pc19; fma.rn.bf16x2 pc20, pv26, pw8, pc20; fma.rn.bf16x2 pc21, pv27, pw9, pc21; fma.rn.bf16x2 pc22, pv28, pw10, pc22; fma.rn.bf16x2 pc23, pv29, pw11, pc23;\n"
        "fma.rn.bf16x2 pc0, pv12, pw12, pc0; fma.rn.bf16x2 pc1, pv13, pw13, pc1; fma.rn.bf16x2 pc2, pv14, pw14, pc2; fma.rn.bf16x2 pc3, pv15, pw15, pc3; fma.rn.bf16x2 pc4, pv16, pw16, pc4; fma.rn.bf16x2 pc5, pv17, pw17, pc5;\n"
        "fma.rn.bf16x2 pc6, pv18, pw12, pc6; fma.rn.bf16x2 pc7, pv19, pw13, pc7; fma.rn.bf16x2 pc8, pv20, pw14, pc8; fma.rn.bf16x2 pc9, pv21, pw15, pc9; fma.rn.bf16x2 pc10, pv22, pw16, pc10; fma.rn.bf16x2 pc11, pv23, pw17, pc11;\n"
        "fma.rn.bf16x2 pc12, pv24, pw12, pc12; fma.rn.bf16x2 pc13, pv25, pw13, pc13; fma.rn.bf16x2 pc14, pv26, pw14, pc14; fma.rn.bf16x2 pc15, pv27, pw15, pc15; fma.rn.bf16x2 pc16, pv28, pw16, pc16; fma.rn.bf16x2 pc17, pv29, pw17, pc17;\n"
        "fma.rn.bf16x2 pc18, pv30, pw12, pc18; fma.rn.bf16x2 pc19, pv31, pw13, pc19; fma.rn.bf16x2 pc20, pv32, pw14, pc20; fma.rn.bf16x2 pc21, pv33, pw15, pc21; fma.rn.bf16x2 pc22, pv34, pw16, pc22; fma.rn.bf16x2 pc23, pv35, pw17, pc23;\n"
        "add.f32 s0, s0, f0; add.f32 s1, s1, f1; mul.f32 s0, s0, 0fBC2AAAAB;\n"
        "neg.f32 f0, s0; fma.rn.f32 f0, f0, s0, %13; fma.rn.f32 f0, s1, 0f3C2AAAAB, f0; max.f32 f0, f0, %13;\n"
        "rsqrt.approx.ftz.f32 f0, f0; mul.f32 f0, f0, %14; cvt.rn.bf16x2.f32 tt, f0, 0f00000000; mov.b32 f0, tt;\n"
        "mul.f32 f1, s0, kq; mul.f32 f1, f1, f0; cvt.rn.bf16x2.f32 tt, f1, f0; add.f32 us, us, s0; cvt.rn.bf16x2.f32 mm, us, us;\n"
        "add.u32 ad, %7, so; st.shared.v2.b32 [ad], {tt, mm};\n"
        "add.u32 ad, %6, so; ld.shared.v4.b32 {ps0,ps1,ps2,ps3}, [ad]; ld.shared.v4.b32 {ps4,ps5,ps6,ps7}, [ad+16];\n"
        "mbarrier.try_wait.parity.shared::cta.b64 pw, [t+231264], 0;\n"
        "N0:\n"
        "@!pw bra.uni SPIN;\n"
        "BACK:\n"
        "add.u32 ad, %0, so; ld.shared.v4.b32 {pv0,pv1,pv2,pv3}, [ad+0];\n"
        "add.u32 ad, %1, so; ld.shared.v2.b32 {pv4,pv5}, [ad+0];\n"
        "add.u32 ad, %0, so; ld.shared.v4.b32 {pv6,pv7,pv8,pv9}, [ad+192];\n"
        "add.u32 ad, %1, so; ld.shared.v2.b32 {pv10,pv11}, [ad+192];\n"
        "mov.b32 {xl, xh}, ps0; mov.b32 rr, {xl, xl}; mov.b32 mm, {xh, xh}; fma.rn.bf16x2 pa0, pa0, rr, mm; fma.rn.bf16x2 pa1, pa1, rr, mm; fma.rn.bf16x2 pa2, pa2, rr, mm; fma.rn.bf16x2 pa3, pa3, rr, mm; fma.rn.bf16x2 pa4, pa4, rr, mm; fma.rn.bf16x2 pa5, pa5, rr, mm;\n"
        "and.b32 m0, pa0, 0x7fff7fff; and.b32 m1, pa1, 0x7fff7fff; and.b32 m2, pa2, 0x7fff7fff; and.b32 m3, pa3, 0x7fff7fff; and.b32 m4, pa4, 0x7fff7fff; and.b32 m5, pa5, 0x7fff7fff;\n"
        "mad.lo.u32 y0, m0, 7, pa0; mad.lo.u32 y1, m1, 7, pa1; mad.lo.u32 y2, m2, 7, pa2; mad.lo.u32 y3, m3, 7, pa3; mad.lo.u32 y4, m4, 7, pa4; mad.lo.u32 y5, m5, 7, pa5;\n"
        "add.u32 ad, %2, so; st.shared.v4.b32 [ad+0], {y0,y1,y2,y3};\n"
        "add.u32 ad, %4, so; st.shared.v2.b32 [ad+0], {y4,y5};\n"
        "N1:\n"
        "add.u32 ad, %0, so; ld.shared.v4.b32 {pv12,pv13,pv14,pv15}, [ad+384];\n"
        "add.u32 ad, %1, so; ld.shared.v2.b32 {pv16,pv17}, [ad+384];\n"
        "add.u32 ad, %0, so; ld.shared.v4.b32 {pv18,pv19,pv20,pv21}, [ad+576];\n"
        "add.u32 ad, %1, so; ld.shared.v2.b32 {pv22,pv23}, [ad+576];\n"
        "mov.b32 {xl, xh}, ps2; mov.b32 rr, {xl, xl}; mov.b32 mm, {xh, xh}; fma.rn.bf16x2 pa6, pa6, rr, mm; fma.rn.bf16x2 pa7, pa7, rr, mm; fma.rn.bf16x2 pa8, pa8, rr, mm; fma.rn.bf16x2 pa9, pa9, rr, mm; fma.rn.bf16x2 pa10, pa10, rr, mm; fma.rn.bf16x2 pa11, pa11, rr, mm;\n"
        "and.b32 m0, pa6, 0x7fff7fff; and.b32 m1, pa7, 0x7fff7fff; and.b32 m2, pa8, 0x7fff7fff; and.b32 m3, pa9, 0x7fff7fff; and.b32 m4, pa10, 0x7fff7fff; and.b32 m5, pa11, 0x7fff7fff;\n"
        "mad.lo.u32 y0, m0, 7, pa6; mad.lo.u32 y1, m1, 7, pa7; mad.lo.u32 y2, m2, 7, pa8; mad.lo.u32 y3, m3, 7, pa9; mad.lo.u32 y4, m4, 7, pa10; mad.lo.u32 y5, m5, 7, pa11;\n"
        "add.u32 ad, %3, so; st.shared.v4.b32 [ad+0], {y0,y1,y2,y3};\n"
        "add.u32 ad, %5, so; st.shared.v2.b32 [ad+0], {y4,y5};\n"
        "N2:\n"
        "add.u32 ad, %0, so; ld.shared.v4.b32 {pv24,pv25,pv26,pv27}, [ad+768];\n"
        "add.u32 ad, %1, so; ld.shared.v2.b32 {pv28,pv29}, [ad+768];\n"
        "mov.b32 {xl, xh}, ps4; mov.b32 rr, {xl, xl}; mov.b32 mm, {xh, xh}; fma.rn.bf16x2 pa12, pa12, rr, mm; fma.rn.bf16x2 pa13, pa13, rr, mm; fma.rn.bf16x2 pa14, pa14, rr, mm; fma.rn.bf16x2 pa15, pa15, rr, mm; fma.rn.bf16x2 pa16, pa16, rr, mm; fma.rn.bf16x2 pa17, pa17, rr, mm;\n"
        "and.b32 m0, pa12, 0x7fff7fff; and.b32 m1, pa13, 0x7fff7fff; and.b32 m2, pa14, 0x7fff7fff; and.b32 m3, pa15, 0x7fff7fff; and.b32 m4, pa16, 0x7fff7fff; and.b32 m5, pa17, 0x7fff7fff;\n"
        "mad.lo.u32 y0, m0, 7, pa12; mad.lo.u32 y1, m1, 7, pa13; mad.lo.u32 y2, m2, 7, pa14; mad.lo.u32 y3, m3, 7, pa15; mad.lo.u32 y4, m4, 7, pa16; mad.lo.u32 y5, m5, 7, pa17;\n"
        "add.u32 ad, %2, so; st.shared.v4.b32 [ad+2048], {y0,y1,y2,y3};\n"
        "add.u32 ad, %4, so; st.shared.v2.b32 [ad+1024], {y4,y5};\n"
        "N3:\n"
        "add.u32 ad, %0, so; ld.shared.v4.b32 {pv30,pv31,pv32,pv33}, [ad+960];\n"
        "add.u32 ad, %1, so; ld.shared.v2.b32 {pv34,pv35}, [ad+960];\n"
        "mov.b32 {xl, xh}, ps6; mov.b32 rr, {xl, xl}; mov.b32 mm, {xh, xh}; fma.rn.bf16x2 pa18, pa18, rr, mm; fma.rn.bf16x2 pa19, pa19, rr, mm; fma.rn.bf16x2 pa20, pa20, rr, mm; fma.rn.bf16x2 pa21, pa21, rr, mm; fma.rn.bf16x2 pa22, pa22, rr, mm; fma.rn.bf16x2 pa23, pa23, rr, mm;\n"
        "and.b32 m0, pa18, 0x7fff7fff; and.b32 m1, pa19, 0x7fff7fff; and.b32 m2, pa20, 0x7fff7fff; and.b32 m3, pa21, 0x7fff7fff; and.b32 m4, pa22, 0x7fff7fff; and.b32 m5, pa23, 0x7fff7fff;\n"
        "mad.lo.u32 y0, m0, 7, pa18; mad.lo.u32 y1, m1, 7, pa19; mad.lo.u32 y2, m2, 7, pa20; mad.lo.u32 y3, m3, 7, pa21; mad.lo.u32 y4, m4, 7, pa22; mad.lo.u32 y5, m5, 7, pa23;\n"
        "add.u32 ad, %3, so; st.shared.v4.b32 [ad+2048], {y0,y1,y2,y3};\n"
        "add.u32 ad, %5, so; st.shared.v2.b32 [ad+1024], {y4,y5};\n"
        "add.u32 so, so, 26624; setp.eq.u32 pr, so, 79872; selp.u32 so, 0, so, pr;\n"
        "add.u32 t, t, 8; setp.lt.u32 pe, t, 256;\n"
        "@pe bra.uni LOOP;\n"
        "bra.uni DONE;\n"
        "SPIN: mov.u32 cnt, 0;\n"
        "SPINL:\n"
        "mbarrier.try_wait.parity.shared::cta.b64 pw, [t+231264], 0;\n"
        "@pw bra.uni BACK;\n"
        "add.u32 cnt, cnt, 1; setp.lt.u32 pw, cnt, 0x100000;\n"
        "@pw bra.uni SPINL;\n"
        "trap;\n"
        "RARE:\n"
        "ld.volatile.shared.u32 tt, [%6];\n"
        "mov.b32 pa0, tt; mov.b32 pa1, tt; mov.b32 pa2, tt; mov.b32 pa3, tt; mov.b32 pa4, tt; mov.b32 pa5, tt; mov.b32 pa6, tt; mov.b32 pa7, tt; mov.b32 pa8, tt; mov.b32 pa9, tt; mov.b32 pa10, tt; mov.b32 pa11, tt;\n"
        "mov.b32 pa12, tt; mov.b32 pa13, tt; mov.b32 pa14, tt; mov.b32 pa15, tt; mov.b32 pa16, tt; mov.b32 pa17, tt; mov.b32 pa18, tt; mov.b32 pa19, tt; mov.b32 pa20, tt; mov.b32 pa21, tt; mov.b32 pa22, tt; mov.b32 pa23, tt;\n"
        "mov.b32 pb0, tt; mov.b32 pb1, tt; mov.b32 pb2, tt; mov.b32 pb3, tt; mov.b32 pb4, tt; mov.b32 pb5, tt; mov.b32 pb6, tt; mov.b32 pb7, tt; mov.b32 pb8, tt; mov.b32 pb9, tt; mov.b32 pb10, tt; mov.b32 pb11, tt;\n"
        "mov.b32 pb12, tt; mov.b32 pb13, tt; mov.b32 pb14, tt; mov.b32 pb15, tt; mov.b32 pb16, tt; mov.b32 pb17, tt; mov.b32 pb18, tt; mov.b32 pb19, tt; mov.b32 pb20, tt; mov.b32 pb21, tt; mov.b32 pb22, tt; mov.b32 pb23, tt;\n"
        "mov.b32 pc0, tt; mov.b32 pc1, tt; mov.b32 pc2, tt; mov.b32 pc3, tt; mov.b32 pc4, tt; mov.b32 pc5, tt; mov.b32 pc6, tt; mov.b32 pc7, tt; mov.b32 pc8, tt; mov.b32 pc9, tt; mov.b32 pc10, tt; mov.b32 pc11, tt;\n"
        "mov.b32 pc12, tt; mov.b32 pc13, tt; mov.b32 pc14, tt; mov.b32 pc15, tt; mov.b32 pc16, tt; mov.b32 pc17, tt; mov.b32 pc18, tt; mov.b32 pc19, tt; mov.b32 pc20, tt; mov.b32 pc21, tt; mov.b32 pc22, tt; mov.b32 pc23, tt;\n"
        "mov.b32 ps0, tt; mov.b32 ps1, tt; mov.b32 ps2, tt; mov.b32 ps3, tt; mov.b32 ps4, tt; mov.b32 ps5, tt; mov.b32 ps6, tt; mov.b32 ps7, tt; mov.b32 pq0, tt; mov.b32 pq1, tt; mov.b32 pq2, tt; mov.b32 pq3, tt;\n"
        "ld.volatile.shared.v2.b32 {pw1, pw0}, [%6]; xor.b32 tt, tt, pw1;\n"
        "ld.volatile.shared.v2.b32 {pw3, pw2}, [%6]; xor.b32 tt, tt, pw3;\n"
        "ld.volatile.shared.v2.b32 {pw5, pw4}, [%6]; xor.b32 tt, tt, pw5;\n"
        "ld.volatile.shared.v2.b32 {pw7, pw6}, [%6]; xor.b32 tt, tt, pw7;\n"
        "ld.volatile.shared.v2.b32 {pw9, pw8}, [%6]; xor.b32 tt, tt, pw9;\n"
        "ld.volatile.shared.v2.b32 {pw11, pw10}, [%6]; xor.b32 tt, tt, pw11;\n"
        "ld.volatile.shared.v2.b32 {pw13, pw12}, [%6]; xor.b32 tt, tt, pw13;\n"
        "ld.volatile.shared.v2.b32 {pw15, pw14}, [%6]; xor.b32 tt, tt, pw15;\n"
        "ld.volatile.shared.v2.b32 {pw17, pw16}, [%6]; xor.b32 tt, tt, pw17;\n"
        "ld.volatile.shared.v2.b32 {pw19, pw18}, [%6]; xor.b32 tt, tt, pw19;\n"
        "ld.volatile.shared.v2.b32 {pw21, pw20}, [%6]; xor.b32 tt, tt, pw21;\n"
        "ld.volatile.shared.v2.b32 {pw23, pw22}, [%6]; xor.b32 tt, tt, pw23;\n"
        "ld.volatile.shared.v2.b32 {pw25, pw24}, [%6]; xor.b32 tt, tt, pw25;\n"
        "ld.volatile.shared.v2.b32 {pw27, pw26}, [%6]; xor.b32 tt, tt, pw27;\n"
        "ld.volatile.shared.v2.b32 {pw29, pw28}, [%6]; xor.b32 tt, tt, pw29;\n"
        "ld.volatile.shared.v2.b32 {pw31, pw30}, [%6]; xor.b32 tt, tt, pw31;\n"
        "ld.volatile.shared.v2.b32 {pw33, pw32}, [%6]; xor.b32 tt, tt, pw33;\n"
        "ld.volatile.shared.v2.b32 {pw35, pw34}, [%6]; xor.b32 tt, tt, pw35;\n"
        "ld.volatile.shared.v2.b32 {pw37, pw36}, [%6]; xor.b32 tt, tt, pw37;\n"
        "ld.volatile.shared.v2.b32 {pw39, pw38}, [%6]; xor.b32 tt, tt, pw39;\n"
        "ld.volatile.shared.v2.b32 {pw41, pw40}, [%6]; xor.b32 tt, tt, pw41;\n"
        "ld.volatile.shared.v2.b32 {pw43, pw42}, [%6]; xor.b32 tt, tt, pw43;\n"
        "ld.volatile.shared.v2.b32 {pw45, pw44}, [%6]; xor.b32 tt, tt, pw45;\n"
        "ld.volatile.shared.v2.b32 {pw47, pw46}, [%6]; xor.b32 tt, tt, pw47;\n"
        "ld.volatile.shared.v2.b32 {pw49, pw48}, [%6]; xor.b32 tt, tt, pw49;\n"
        "ld.volatile.shared.v2.b32 {pw51, pw50}, [%6]; xor.b32 tt, tt, pw51;\n"
        "ld.volatile.shared.v2.b32 {pw53, pw52}, [%6]; xor.b32 tt, tt, pw53;\n"
        "mov.b32 us, tt; setp.ne.u32 pw, %15, 7;\n"
        "wgmma.fence.sync.aligned;\n"
        "setp.eq.u32 pr, %15, 1000; @pr bra.uni B0;\n"
        "setp.eq.u32 pr, %15, 1001; @pr bra.uni B1;\n"
        "setp.eq.u32 pr, %15, 1002; @pr bra.uni C0;\n"
        "setp.eq.u32 pr, %15, 1003; @pr bra.uni N0;\n"
        "setp.eq.u32 pr, %15, 1004; @pr bra.uni N1;\n"
        "setp.eq.u32 pr, %15, 1005; @pr bra.uni N2;\n"
        "setp.eq.u32 pr, %15, 1006; @pr bra.uni N3;\n"
        "trap;\n"
        "DONE:\n"
        ASM_TRC("t")
        "fence.proxy.async.shared::cta;\n"
        "@pl mbarrier.arrive.shared::cta.b64 _, [t+231544];\n"
        "}\n"
        :: "r"(sb + SM_X + c.xoff[0]), "r"(sb + SM_X + c.xoff[1]), "r"(sb + SM_Y1 + c.yoff[0][0]), "r"(sb + SM_Y1 + c.yoff[0][1]),
           "r"(sb + SM_Y1 + c.yoff[1][0]), "r"(sb + SM_Y1 + c.yoff[1][1]), "r"(c.stat), "r"(c.own), "r"(c.lane),
           "l"(prm.sel[0]), "l"(prm.sel[1]), "l"(prm.sel[2]), "r"(prm.ydesc), "f"(LN_EPS_SCALED), "f"(RSTD_SCALE), "r"(prm.w1desc)
        : "memory");
}

__device__ __forceinline__ void produce(const Producer& c, const Params& prm) {
    uint32_t B[24], C[24];
    uint32_t st[8];
    uint32_t v[6][6];
    uint32_t ws[6];
#pragma unroll
    for (int u = 0; u < 6; u++) {
        ws[u] = c.w[0][u];
#pragma unroll
        for (int t = 1; t < 9; t++) ws[u] = bf2_add(ws[u], c.w[t][u]);
    }
    SMARK(2);
#pragma unroll 1
    for (int i = loop_init<0>();; i++) {
        mbar_wait_c<0>(sb + SM_GO + i * 8);
        SMARK(4 + i);
        load_x(v, c, sb + SM_X + i * SLOT_BYTES);
        fence_async_smem();
        asm volatile("bar.arrive %0, 160;" ::"r"(6 + i) : "memory");
        if (i == 2) break;
        if (i == 0) {
            const uint32_t p = bf2_add(bf2_fma(v[2][2], ws[2], bf2_fma(v[2][1], ws[1], bf2_mul(v[2][0], ws[0]))),
                                       bf2_fma(v[2][5], ws[5], bf2_fma(v[2][4], ws[4], bf2_mul(v[2][3], ws[3]))));
            float e = quad_sum(bf_lo(p) + bf_hi(p));
            e = (e + __shfl_xor_sync(0xffffffffu, e, 4)) * (-1.0f / CH);
            st[1] = st[3] = st[5] = st[7] = pack_bf2(e, e);
#pragma unroll
            for (int k = 0; k < NX; k++) sts32(c.own + k * SLOT_BYTES + 4, st[1]);
        } else {
            conv_row<1, 1>(B, C, v, c);
        }
        conv_row<0, 0>(C, st, v, c);
    }
    asm volatile(".reg .b32 pw<54>, pb<24>, pc<24>, pv<36>, ps<8>;");
    hand_over<0>(c, B, C, v);
    asm volatile("mov.b32 ps1, %0; mov.b32 ps3, %1; mov.b32 ps5, %2; mov.b32 ps7, %3;" ::"r"(st[1]), "r"(st[3]), "r"(st[5]), "r"(st[7]));
    SMARK(7);
    produce_tiles(c, prm);
    mbar_arrive_if(sb + SM_YFULL + ROWS_PER_CTA * 8, c.lane == 0);
}

struct Duty {
    const char* g;
    const char* zeros;
    long long step;
    uint32_t s, bytes;
    int end, zero;
};
__device__ __forceinline__ Duty make_duty(const Params& prm, int wg, int w) {
    const RowCopy rc = row_copy(prm);
    Duty d;
    d.g = (w == 2 ? rc.y0 : rc.x0 + (w == 0 ? rc.cut0 : w == 1 ? 32 * 192 : 192)) +
          (wg + (w == 2 ? 0 : w < 2 ? 2 * NX : 2 * NX + L2_AHEAD)) * rc.stride;
    d.step = NX * rc.stride;
    d.s = wg * SLOT_BYTES + (w == 2 ? sb + SM_Y1 : sb + SM_X + (w == 0 ? rc.cut0 : XHALF_B));
    d.bytes = w >= 2 ? TILE_BYTES : XHALF_BYTES - (w == 0 ? rc.cut0 : rc.cut1);
    d.end = w == 2 ? ROWS_PER_CTA : w < 2 ? STEPS + 1 - 2 * NX : rc.last + 1 - 2 * NX - L2_AHEAD;
    d.zero = rc.last + 1 - 2 * NX;
    d.zeros = rc.zeros;
    return d;
}

static_assert(sb + SM_BAR == 230800 && sb + SM_YFULL == 231552 && sb + SM_GO == 231240 && SLOT_BYTES == 26624 && sb + SM_GAMMA == 229248 &&
              SM_BETA == SM_GAMMA + 768 && SM_W2 == 73728 && sb + SM_BUF3 == 187392 && BAR_W2 == 9 && BAR_W1B == 10, "layout");
__device__ __forceinline__ void consume(float (&acc)[2][2], uint32_t w1t, uint32_t yd, uint32_t wd, uint32_t own_slot, const Duty& d,
                                        uint32_t role, uint32_t lane, const Params& prm) {
    asm volatile(
        "{\n"
        ".reg .b32 z<32>, w<44>, p, a<4>, lo<2>, hi<2>, t, g, q<4>, dl, dh, n, so, c, tt, cnt, f0, f1;\n"
        ".reg .b16 xl, xh, xr;\n"
        ".reg .b64 ds<6>, wd, gp, src;\n"
        ".reg .pred pt, pf, pr, pw, pl, pe;\n"
        "setp.ne.b32 pt, 1, 0; setp.ne.b32 pf, 0, 0; setp.eq.u32 pl, %15, 0;\n"
        "mov.b32 c, 0x40D940D9;\n"
        "ldmatrix.sync.aligned.m8n8.x4.trans.shared.b16 {w0,w1,w2,w3}, [%4+0];\n"
        "ldmatrix.sync.aligned.m8n8.x4.trans.shared.b16 {w4,w5,w6,w7}, [%4+2048];\n"
        "ldmatrix.sync.aligned.m8n8.x4.trans.shared.b16 {w8,w9,w10,w11}, [%4+4096];\n"
        "ldmatrix.sync.aligned.m8n8.x4.trans.shared.b16 {w12,w13,w14,w15}, [%4+6144];\n"
        "ldmatrix.sync.aligned.m8n8.x4.trans.shared.b16 {w16,w17,w18,w19}, [%4+8192];\n"
        "ldmatrix.sync.aligned.m8n8.x4.trans.shared.b16 {w20,w21,w22,w23}, [%4+10240];\n"
        "shl.b32 f0, w0, 16; and.b32 f1, w0, 0xffff0000; cvt.rn.f16x2.f32 w0, f1, f0; shl.b32 f0, w1, 16; and.b32 f1, w1, 0xffff0000; cvt.rn.f16x2.f32 w1, f1, f0; shl.b32 f0, w2, 16; and.b32 f1, w2, 0xffff0000; cvt.rn.f16x2.f32 w2, f1, f0; shl.b32 f0, w3, 16; and.b32 f1, w3, 0xffff0000; cvt.rn.f16x2.f32 w3, f1, f0;\n"
        "stmatrix.sync.aligned.m8n8.x4.trans.shared.b16 [%4+0], {w0,w1,w2,w3};\n"
        "shl.b32 f0, w4, 16; and.b32 f1, w4, 0xffff0000; cvt.rn.f16x2.f32 w4, f1, f0; shl.b32 f0, w5, 16; and.b32 f1, w5, 0xffff0000; cvt.rn.f16x2.f32 w5, f1, f0; shl.b32 f0, w6, 16; and.b32 f1, w6, 0xffff0000; cvt.rn.f16x2.f32 w6, f1, f0; shl.b32 f0, w7, 16; and.b32 f1, w7, 0xffff0000; cvt.rn.f16x2.f32 w7, f1, f0;\n"
        "stmatrix.sync.aligned.m8n8.x4.trans.shared.b16 [%4+2048], {w4,w5,w6,w7};\n"
        "shl.b32 f0, w8, 16; and.b32 f1, w8, 0xffff0000; cvt.rn.f16x2.f32 w8, f1, f0; shl.b32 f0, w9, 16; and.b32 f1, w9, 0xffff0000; cvt.rn.f16x2.f32 w9, f1, f0; shl.b32 f0, w10, 16; and.b32 f1, w10, 0xffff0000; cvt.rn.f16x2.f32 w10, f1, f0; shl.b32 f0, w11, 16; and.b32 f1, w11, 0xffff0000; cvt.rn.f16x2.f32 w11, f1, f0;\n"
        "stmatrix.sync.aligned.m8n8.x4.trans.shared.b16 [%4+4096], {w8,w9,w10,w11};\n"
        "shl.b32 f0, w12, 16; and.b32 f1, w12, 0xffff0000; cvt.rn.f16x2.f32 w12, f1, f0; shl.b32 f0, w13, 16; and.b32 f1, w13, 0xffff0000; cvt.rn.f16x2.f32 w13, f1, f0; shl.b32 f0, w14, 16; and.b32 f1, w14, 0xffff0000; cvt.rn.f16x2.f32 w14, f1, f0; shl.b32 f0, w15, 16; and.b32 f1, w15, 0xffff0000; cvt.rn.f16x2.f32 w15, f1, f0;\n"
        "stmatrix.sync.aligned.m8n8.x4.trans.shared.b16 [%4+6144], {w12,w13,w14,w15};\n"
        "shl.b32 f0, w16, 16; and.b32 f1, w16, 0xffff0000; cvt.rn.f16x2.f32 w16, f1, f0; shl.b32 f0, w17, 16; and.b32 f1, w17, 0xffff0000; cvt.rn.f16x2.f32 w17, f1, f0; shl.b32 f0, w18, 16; and.b32 f1, w18, 0xffff0000; cvt.rn.f16x2.f32 w18, f1, f0; shl.b32 f0, w19, 16; and.b32 f1, w19, 0xffff0000; cvt.rn.f16x2.f32 w19, f1, f0;\n"
        "stmatrix.sync.aligned.m8n8.x4.trans.shared.b16 [%4+8192], {w16,w17,w18,w19};\n"
        "shl.b32 f0, w20, 16; and.b32 f1, w20, 0xffff0000; cvt.rn.f16x2.f32 w20, f1, f0; shl.b32 f0, w21, 16; and.b32 f1, w21, 0xffff0000; cvt.rn.f16x2.f32 w21, f1, f0; shl.b32 f0, w22, 16; and.b32 f1, w22, 0xffff0000; cvt.rn.f16x2.f32 w22, f1, f0; shl.b32 f0, w23, 16; and.b32 f1, w23, 0xffff0000; cvt.rn.f16x2.f32 w23, f1, f0;\n"
        "stmatrix.sync.aligned.m8n8.x4.trans.shared.b16 [%4+10240], {w20,w21,w22,w23};\n"
        "mov.u32 tt, 230880; mbarrier.try_wait.parity.shared::cta.b64 pw, [tt], 0;\n"
        "@!pw bra.uni SPINW;\n"
        "BACKW:\n"
        "ldmatrix.sync.aligned.m8n8.x4.trans.shared.b16 {z0,z1,z2,z3}, [%4+22528];\n"
        "ldmatrix.sync.aligned.m8n8.x4.trans.shared.b16 {w24,w25,w26,w27}, [%4+12288];\n"
        "ldmatrix.sync.aligned.m8n8.x4.trans.shared.b16 {w28,w29,w30,w31}, [%4+14336];\n"
        "ldmatrix.sync.aligned.m8n8.x4.trans.shared.b16 {w32,w33,w34,w35}, [%4+16384];\n"
        "ldmatrix.sync.aligned.m8n8.x4.trans.shared.b16 {w36,w37,w38,w39}, [%4+18432];\n"
        "ldmatrix.sync.aligned.m8n8.x4.trans.shared.b16 {w40,w41,w42,w43}, [%4+20480];\n"
        "shl.b32 f0, z0, 16; and.b32 f1, z0, 0xffff0000; cvt.rn.f16x2.f32 z0, f1, f0; shl.b32 f0, z1, 16; and.b32 f1, z1, 0xffff0000; cvt.rn.f16x2.f32 z1, f1, f0; shl.b32 f0, z2, 16; and.b32 f1, z2, 0xffff0000; cvt.rn.f16x2.f32 z2, f1, f0; shl.b32 f0, z3, 16; and.b32 f1, z3, 0xffff0000; cvt.rn.f16x2.f32 z3, f1, f0;\n"
        "stmatrix.sync.aligned.m8n8.x4.trans.shared.b16 [%4+22528], {z0,z1,z2,z3};\n"
        "shl.b32 f0, w24, 16; and.b32 f1, w24, 0xffff0000; cvt.rn.f16x2.f32 w24, f1, f0; shl.b32 f0, w25, 16; and.b32 f1, w25, 0xffff0000; cvt.rn.f16x2.f32 w25, f1, f0; shl.b32 f0, w26, 16; and.b32 f1, w26, 0xffff0000; cvt.rn.f16x2.f32 w26, f1, f0; shl.b32 f0, w27, 16; and.b32 f1, w27, 0xffff0000; cvt.rn.f16x2.f32 w27, f1, f0;\n"
        "stmatrix.sync.aligned.m8n8.x4.trans.shared.b16 [%4+12288], {w24,w25,w26,w27};\n"
        "shl.b32 f0, w28, 16; and.b32 f1, w28, 0xffff0000; cvt.rn.f16x2.f32 w28, f1, f0; shl.b32 f0, w29, 16; and.b32 f1, w29, 0xffff0000; cvt.rn.f16x2.f32 w29, f1, f0; shl.b32 f0, w30, 16; and.b32 f1, w30, 0xffff0000; cvt.rn.f16x2.f32 w30, f1, f0; shl.b32 f0, w31, 16; and.b32 f1, w31, 0xffff0000; cvt.rn.f16x2.f32 w31, f1, f0;\n"
        "stmatrix.sync.aligned.m8n8.x4.trans.shared.b16 [%4+14336], {w28,w29,w30,w31};\n"
        "shl.b32 f0, w32, 16; and.b32 f1, w32, 0xffff0000; cvt.rn.f16x2.f32 w32, f1, f0; shl.b32 f0, w33, 16; and.b32 f1, w33, 0xffff0000; cvt.rn.f16x2.f32 w33, f1, f0; shl.b32 f0, w34, 16; and.b32 f1, w34, 0xffff0000; cvt.rn.f16x2.f32 w34, f1, f0; shl.b32 f0, w35, 16; and.b32 f1, w35, 0xffff0000; cvt.rn.f16x2.f32 w35, f1, f0;\n"
        "stmatrix.sync.aligned.m8n8.x4.trans.shared.b16 [%4+16384], {w32,w33,w34,w35};\n"
        "shl.b32 f0, w36, 16; and.b32 f1, w36, 0xffff0000; cvt.rn.f16x2.f32 w36, f1, f0; shl.b32 f0, w37, 16; and.b32 f1, w37, 0xffff0000; cvt.rn.f16x2.f32 w37, f1, f0; shl.b32 f0, w38, 16; and.b32 f1, w38, 0xffff0000; cvt.rn.f16x2.f32 w38, f1, f0; shl.b32 f0, w39, 16; and.b32 f1, w39, 0xffff0000; cvt.rn.f16x2.f32 w39, f1, f0;\n"
        "stmatrix.sync.aligned.m8n8.x4.trans.shared.b16 [%4+18432], {w36,w37,w38,w39};\n"
        "shl.b32 f0, w40, 16; and.b32 f1, w40, 0xffff0000; cvt.rn.f16x2.f32 w40, f1, f0; shl.b32 f0, w41, 16; and.b32 f1, w41, 0xffff0000; cvt.rn.f16x2.f32 w41, f1, f0; shl.b32 f0, w42, 16; and.b32 f1, w42, 0xffff0000; cvt.rn.f16x2.f32 w42, f1, f0; shl.b32 f0, w43, 16; and.b32 f1, w43, 0xffff0000; cvt.rn.f16x2.f32 w43, f1, f0;\n"
        "stmatrix.sync.aligned.m8n8.x4.trans.shared.b16 [%4+20480], {w40,w41,w42,w43};\n"
        "fence.proxy.async.shared::cta;\n"
        ASM_SMARK
        "mov.b32 p, 0; mov.b32 t, 0; mov.b32 g, 0; mov.b32 a0, 0; mov.b32 a1, 0; mov.b32 a2, 0; mov.b32 a3, 0; mov.b32 lo0, 0; mov.b32 lo1, 0; mov.b32 hi0, 0; mov.b32 hi1, 0; mov.b32 q0, 0; mov.b32 q1, 0; mov.b32 q2, 0; mov.b32 q3, 0;\n"
        "mov.b32 z16, 0; mov.b32 z17, 0; mov.b32 z18, 0; mov.b32 z19, 0; mov.b32 z20, 0; mov.b32 z21, 0; mov.b32 z22, 0; mov.b32 z23, 0; mov.b32 z24, 0; mov.b32 z25, 0; mov.b32 z26, 0; mov.b32 z27, 0; mov.b32 z28, 0; mov.b32 z29, 0; mov.b32 z30, 0; mov.b32 z31, 0;\n"
        "mov.f32 %0, 0f00000000; mov.f32 %1, 0f00000000; mov.f32 %2, 0f00000000; mov.f32 %3, 0f00000000;\n"
        "mov.u32 n, 0; mov.u32 so, 0; mov.b64 gp, %8; mov.b64 wd, {%6, 0x40000040};\n"
        "mov.b64 ds0, %20; add.s64 ds1, ds0, 2; add.s64 ds2, ds0, 4; add.s64 ds3, ds0, 6; mov.b64 ds4, %21; add.s64 ds5, ds4, 2;\n"
        "mbarrier.try_wait.parity.shared::cta.b64 pw, [n+231552], 0;\n"
        "@!pw bra.uni SPIN0;\n"
        "BACK0:\n"
        ASM_TS
        "wgmma.fence.sync.aligned;\n"
        "wgmma.mma_async.sync.aligned.m64n64k16.f16.f16.f16 {z0,z1,z2,z3,z4,z5,z6,z7,z8,z9,z10,z11,z12,z13,z14,z15}, {w0,w1,w2,w3}, ds0, pf, 1, 1, 0;\n"
        "wgmma.mma_async.sync.aligned.m64n64k16.f16.f16.f16 {z0,z1,z2,z3,z4,z5,z6,z7,z8,z9,z10,z11,z12,z13,z14,z15}, {w4,w5,w6,w7}, ds1, pt, 1, 1, 0;\n"
        "wgmma.mma_async.sync.aligned.m64n64k16.f16.f16.f16 {z0,z1,z2,z3,z4,z5,z6,z7,z8,z9,z10,z11,z12,z13,z14,z15}, {w8,w9,w10,w11}, ds2, pt, 1, 1, 0;\n"
        "wgmma.fence.sync.aligned;\n"
        "wgmma.mma_async.sync.aligned.m64n64k16.f16.f16.f16 {z0,z1,z2,z3,z4,z5,z6,z7,z8,z9,z10,z11,z12,z13,z14,z15}, {w12,w13,w14,w15}, ds3, pt, 1, 1, 0;\n"
        "wgmma.mma_async.sync.aligned.m64n64k16.f16.f16.f16 {z0,z1,z2,z3,z4,z5,z6,z7,z8,z9,z10,z11,z12,z13,z14,z15}, {w16,w17,w18,w19}, ds4, pt, 1, 1, 0;\n"
        "wgmma.mma_async.sync.aligned.m64n64k16.f16.f16.f16 {z0,z1,z2,z3,z4,z5,z6,z7,z8,z9,z10,z11,z12,z13,z14,z15}, {w20,w21,w22,w23}, ds5, pt, 1, 1, 0;\n"
        "wgmma.commit_group.sync.aligned;\n"
        "setp.eq.u32 pr, so, %7;\n"
        "@pr bra.uni DUTY;\n"
        "TOP:\n"
        ASM_TRC("n")
        "wgmma.wait_group.sync.aligned 0;\n"
        "mov.b32 {xl, xh}, a2; tanh.approx.f16 xr, xh; cvt.u32.u16 hi0, xr; mul.rn.f16x2 a3, z31, p; fma.rn.f16x2 p, z0, z0, c; fma.rn.f16x2 q3, g, g, q3; fma.rn.f16x2 g, z28, t, z28; prmt.b32 t, lo1, hi1, 0x5410; tanh.approx.f16 xr, xl; cvt.u32.u16 lo0, xr;\n"
        "B31:\n"
        "mov.b32 {xl, xh}, a3; tanh.approx.f16 xr, xh; cvt.u32.u16 hi1, xr; mul.rn.f16x2 a0, z0, p; fma.rn.f16x2 p, z1, z1, c; fma.rn.f16x2 q2, g, g, q2; fma.rn.f16x2 g, z29, t, z29; prmt.b32 t, lo0, hi0, 0x5410; tanh.approx.f16 xr, xl; cvt.u32.u16 lo1, xr;\n"
        "B0:\n"
        "mov.b32 {xl, xh}, a0; tanh.approx.f16 xr, xh; cvt.u32.u16 hi0, xr; mul.rn.f16x2 a1, z1, p; fma.rn.f16x2 p, z2, z2, c; fma.rn.f16x2 q3, g, g, q3; fma.rn.f16x2 g, z30, t, z30; prmt.b32 t, lo1, hi1, 0x5410; tanh.approx.f16 xr, xl; cvt.u32.u16 lo0, xr;\n"
        "B1:\n"
        "mov.b32 {xl, xh}, a1; tanh.approx.f16 xr, xh; cvt.u32.u16 hi1, xr; mul.rn.f16x2 a2, z2, p; fma.rn.f16x2 p, z3, z3, c; fma.rn.f16x2 q2, g, g, q2; fma.rn.f16x2 g, z31, t, z31; prmt.b32 t, lo0, hi0, 0x5410; tanh.approx.f16 xr, xl; cvt.u32.u16 lo1, xr;\n"
        "B2:\n"
        "wgmma.fence.sync.aligned;\n"
        "wgmma.mma_async.sync.aligned.m64n64k16.f16.f16.f16 {z16,z17,z18,z19,z20,z21,z22,z23,z24,z25,z26,z27,z28,z29,z30,z31}, {w24,w25,w26,w27}, ds0, pf, 1, 1, 0;\n"
        "wgmma.mma_async.sync.aligned.m64n64k16.f16.f16.f16 {z16,z17,z18,z19,z20,z21,z22,z23,z24,z25,z26,z27,z28,z29,z30,z31}, {w28,w29,w30,w31}, ds1, pt, 1, 1, 0;\n"
        "wgmma.mma_async.sync.aligned.m64n64k16.f16.f16.f16 {z16,z17,z18,z19,z20,z21,z22,z23,z24,z25,z26,z27,z28,z29,z30,z31}, {w32,w33,w34,w35}, ds2, pt, 1, 1, 0;\n"
        "mov.b32 {xl, xh}, a2; tanh.approx.f16 xr, xh; cvt.u32.u16 hi0, xr; mul.rn.f16x2 a3, z3, p; fma.rn.f16x2 p, z4, z4, c; fma.rn.f16x2 q3, g, g, q3; fma.rn.f16x2 g, z0, t, z0; prmt.b32 t, lo1, hi1, 0x5410; tanh.approx.f16 xr, xl; cvt.u32.u16 lo0, xr;\n"
        "B3:\n"
        "mov.b32 {xl, xh}, a3; tanh.approx.f16 xr, xh; cvt.u32.u16 hi1, xr; mul.rn.f16x2 a0, z4, p; fma.rn.f16x2 p, z5, z5, c; fma.rn.f16x2 q0, g, g, q0; fma.rn.f16x2 g, z1, t, z1; prmt.b32 t, lo0, hi0, 0x5410; tanh.approx.f16 xr, xl; cvt.u32.u16 lo1, xr;\n"
        "B4:\n"
        "mov.b32 {xl, xh}, a0; tanh.approx.f16 xr, xh; cvt.u32.u16 hi0, xr; mul.rn.f16x2 a1, z5, p; fma.rn.f16x2 p, z6, z6, c; fma.rn.f16x2 q1, g, g, q1; fma.rn.f16x2 g, z2, t, z2; prmt.b32 t, lo1, hi1, 0x5410; tanh.approx.f16 xr, xl; cvt.u32.u16 lo0, xr;\n"
        "B5:\n"
        "wgmma.fence.sync.aligned;\n"
        "wgmma.mma_async.sync.aligned.m64n64k16.f16.f16.f16 {z16,z17,z18,z19,z20,z21,z22,z23,z24,z25,z26,z27,z28,z29,z30,z31}, {w36,w37,w38,w39}, ds3, pt, 1, 1, 0;\n"
        "wgmma.mma_async.sync.aligned.m64n64k16.f16.f16.f16 {z16,z17,z18,z19,z20,z21,z22,z23,z24,z25,z26,z27,z28,z29,z30,z31}, {w40,w41,w42,w43}, ds4, pt, 1, 1, 0;\n"
        "wgmma.mma_async.sync.aligned.m64n64k16.f16.f16.f16 {z16,z17,z18,z19,z20,z21,z22,z23,z24,z25,z26,z27,z28,z29,z30,z31}, wd, ds5, pt, 1, 1, 1, 0;\n"
        "wgmma.commit_group.sync.aligned;\n"
        "mov.b32 {xl, xh}, a1; tanh.approx.f16 xr, xh; cvt.u32.u16 hi1, xr; mul.rn.f16x2 a2, z6, p; fma.rn.f16x2 p, z7, z7, c; fma.rn.f16x2 q0, g, g, q0; fma.rn.f16x2 g, z3, t, z3; prmt.b32 t, lo0, hi0, 0x5410; tanh.approx.f16 xr, xl; cvt.u32.u16 lo1, xr;\n"
        "B6:\n"
        "add.u32 so, so, 26624; setp.eq.u32 pr, so, 79872; selp.u32 so, 0, so, pr;\n"
        "mov.b32 {xl, xh}, a2; tanh.approx.f16 xr, xh; cvt.u32.u16 hi0, xr; mul.rn.f16x2 a3, z7, p; fma.rn.f16x2 p, z8, z8, c; fma.rn.f16x2 q1, g, g, q1; fma.rn.f16x2 g, z4, t, z4; prmt.b32 t, lo1, hi1, 0x5410; tanh.approx.f16 xr, xl; cvt.u32.u16 lo0, xr;\n"
        "B7:\n"
        "shr.u32 tt, so, 4;\n"
        "mov.b64 {dl, dh}, ds0; add.u32 dl, tt, 74816; mov.b64 ds0, {dl, dh}; mov.b64 {dl, dh}, ds1; add.u32 dl, tt, 74818; mov.b64 ds1, {dl, dh}; mov.b64 {dl, dh}, ds2; add.u32 dl, tt, 74820; mov.b64 ds2, {dl, dh};\n"
        "mov.b32 {xl, xh}, a3; tanh.approx.f16 xr, xh; cvt.u32.u16 hi1, xr; mul.rn.f16x2 a0, z8, p; fma.rn.f16x2 p, z9, z9, c; fma.rn.f16x2 q0, g, g, q0; fma.rn.f16x2 g, z5, t, z5; prmt.b32 t, lo0, hi0, 0x5410; tanh.approx.f16 xr, xl; cvt.u32.u16 lo1, xr;\n"
        "B8:\n"
        "shr.u32 tt, so, 4;\n"
        "mov.b64 {dl, dh}, ds3; add.u32 dl, tt, 74822; mov.b64 ds3, {dl, dh}; mov.b64 {dl, dh}, ds4; add.u32 dl, tt, 75328; mov.b64 ds4, {dl, dh}; mov.b64 {dl, dh}, ds5; add.u32 dl, tt, 75330; mov.b64 ds5, {dl, dh};\n"
        "mov.b32 {xl, xh}, a0; tanh.approx.f16 xr, xh; cvt.u32.u16 hi0, xr; mul.rn.f16x2 a1, z9, p; fma.rn.f16x2 p, z10, z10, c; fma.rn.f16x2 q1, g, g, q1; fma.rn.f16x2 g, z6, t, z6; prmt.b32 t, lo1, hi1, 0x5410; tanh.approx.f16 xr, xl; cvt.u32.u16 lo0, xr;\n"
        "B9:\n"
        "mov.b32 {xl, xh}, a1; tanh.approx.f16 xr, xh; cvt.u32.u16 hi1, xr; mul.rn.f16x2 a2, z10, p; fma.rn.f16x2 p, z11, z11, c; fma.rn.f16x2 q0, g, g, q0; fma.rn.f16x2 g, z7, t, z7; prmt.b32 t, lo0, hi0, 0x5410; tanh.approx.f16 xr, xl; cvt.u32.u16 lo1, xr;\n"
        "B10:\n"
        "mov.b32 {xl, xh}, a2; tanh.approx.f16 xr, xh; cvt.u32.u16 hi0, xr; mul.rn.f16x2 a3, z11, p; fma.rn.f16x2 p, z12, z12, c; fma.rn.f16x2 q1, g, g, q1; fma.rn.f16x2 g, z8, t, z8; prmt.b32 t, lo1, hi1, 0x5410; tanh.approx.f16 xr, xl; cvt.u32.u16 lo0, xr;\n"
        "B11:\n"
        "mov.b32 {xl, xh}, a3; tanh.approx.f16 xr, xh; cvt.u32.u16 hi1, xr; mul.rn.f16x2 a0, z12, p; fma.rn.f16x2 p, z13, z13, c; fma.rn.f16x2 q0, g, g, q0; fma.rn.f16x2 g, z9, t, z9; prmt.b32 t, lo0, hi0, 0x5410; tanh.approx.f16 xr, xl; cvt.u32.u16 lo1, xr;\n"
        "B12:\n"
        "mov.b32 {xl, xh}, a0; tanh.approx.f16 xr, xh; cvt.u32.u16 hi0, xr; mul.rn.f16x2 a1, z13, p; fma.rn.f16x2 p, z14, z14, c; fma.rn.f16x2 q1, g, g, q1; fma.rn.f16x2 g, z10, t, z10; prmt.b32 t, lo1, hi1, 0x5410; tanh.approx.f16 xr, xl; cvt.u32.u16 lo0, xr;\n"
        "B13:\n"
        "mov.b32 {xl, xh}, a1; tanh.approx.f16 xr, xh; cvt.u32.u16 hi1, xr; mul.rn.f16x2 a2, z14, p; fma.rn.f16x2 p, z15, z15, c; fma.rn.f16x2 q0, g, g, q0; fma.rn.f16x2 g, z11, t, z11; prmt.b32 t, lo0, hi0, 0x5410; tanh.approx.f16 xr, xl; cvt.u32.u16 lo1, xr;\n"
        "B14:\n"
        "wgmma.wait_group.sync.aligned 0;\n"
        "cp.async.bulk.wait_group.read 0;\n"
        "@pl mbarrier.arrive.shared::cta.b64 _, [n+231288];\n"
        "mov.b32 {xl, xh}, a2; tanh.approx.f16 xr, xh; cvt.u32.u16 hi0, xr; mul.rn.f16x2 a3, z15, p; fma.rn.f16x2 p, z16, z16, c; fma.rn.f16x2 q1, g, g, q1; fma.rn.f16x2 g, z12, t, z12; prmt.b32 t, lo1, hi1, 0x5410; tanh.approx.f16 xr, xl; cvt.u32.u16 lo0, xr;\n"
        "B15:\n"
        "mov.b32 {xl, xh}, a3; tanh.approx.f16 xr, xh; cvt.u32.u16 hi1, xr; mul.rn.f16x2 a0, z16, p; fma.rn.f16x2 p, z17, z17, c; fma.rn.f16x2 q0, g, g, q0; fma.rn.f16x2 g, z13, t, z13; prmt.b32 t, lo0, hi0, 0x5410; tanh.approx.f16 xr, xl; cvt.u32.u16 lo1, xr;\n"
        "B16:\n"
        "mbarrier.try_wait.parity.shared::cta.b64 pw, [n+231560], 0;\n"
        "mov.b32 {xl, xh}, a0; tanh.approx.f16 xr, xh; cvt.u32.u16 hi0, xr; mul.rn.f16x2 a1, z17, p; fma.rn.f16x2 p, z18, z18, c; fma.rn.f16x2 q1, g, g, q1; fma.rn.f16x2 g, z14, t, z14; prmt.b32 t, lo1, hi1, 0x5410; tanh.approx.f16 xr, xl; cvt.u32.u16 lo0, xr;\n"
        "B17:\n"
        "mov.b32 {xl, xh}, a1; tanh.approx.f16 xr, xh; cvt.u32.u16 hi1, xr; mul.rn.f16x2 a2, z18, p; fma.rn.f16x2 p, z19, z19, c; fma.rn.f16x2 q0, g, g, q0; fma.rn.f16x2 g, z15, t, z15; prmt.b32 t, lo0, hi0, 0x5410; tanh.approx.f16 xr, xl; cvt.u32.u16 lo1, xr;\n"
        "B18:\n"
        "@!pw bra.uni SPIN;\n"
        "BACK:\n"
        "wgmma.fence.sync.aligned;\n"
        "wgmma.mma_async.sync.aligned.m64n64k16.f16.f16.f16 {z0,z1,z2,z3,z4,z5,z6,z7,z8,z9,z10,z11,z12,z13,z14,z15}, {w0,w1,w2,w3}, ds0, pf, 1, 1, 0;\n"
        "wgmma.mma_async.sync.aligned.m64n64k16.f16.f16.f16 {z0,z1,z2,z3,z4,z5,z6,z7,z8,z9,z10,z11,z12,z13,z14,z15}, {w4,w5,w6,w7}, ds1, pt, 1, 1, 0;\n"
        "wgmma.mma_async.sync.aligned.m64n64k16.f16.f16.f16 {z0,z1,z2,z3,z4,z5,z6,z7,z8,z9,z10,z11,z12,z13,z14,z15}, {w8,w9,w10,w11}, ds2, pt, 1, 1, 0;\n"
        "mov.b32 {xl, xh}, a2; tanh.approx.f16 xr, xh; cvt.u32.u16 hi0, xr; mul.rn.f16x2 a3, z19, p; fma.rn.f16x2 p, z20, z20, c; fma.rn.f16x2 q1, g, g, q1; fma.rn.f16x2 g, z16, t, z16; prmt.b32 t, lo1, hi1, 0x5410; tanh.approx.f16 xr, xl; cvt.u32.u16 lo0, xr;\n"
        "B19:\n"
        "mov.b32 {xl, xh}, a3; tanh.approx.f16 xr, xh; cvt.u32.u16 hi1, xr; mul.rn.f16x2 a0, z20, p; fma.rn.f16x2 p, z21, z21, c; fma.rn.f16x2 q2, g, g, q2; fma.rn.f16x2 g, z17, t, z17; prmt.b32 t, lo0, hi0, 0x5410; tanh.approx.f16 xr, xl; cvt.u32.u16 lo1, xr;\n"
        "B20:\n"
        "mov.b32 {xl, xh}, a0; tanh.approx.f16 xr, xh; cvt.u32.u16 hi0, xr; mul.rn.f16x2 a1, z21, p; fma.rn.f16x2 p, z22, z22, c; fma.rn.f16x2 q3, g, g, q3; fma.rn.f16x2 g, z18, t, z18; prmt.b32 t, lo1, hi1, 0x5410; tanh.approx.f16 xr, xl; cvt.u32.u16 lo0, xr;\n"
        "B21:\n"
        "wgmma.fence.sync.aligned;\n"
        "wgmma.mma_async.sync.aligned.m64n64k16.f16.f16.f16 {z0,z1,z2,z3,z4,z5,z6,z7,z8,z9,z10,z11,z12,z13,z14,z15}, {w12,w13,w14,w15}, ds3, pt, 1, 1, 0;\n"
        "wgmma.mma_async.sync.aligned.m64n64k16.f16.f16.f16 {z0,z1,z2,z3,z4,z5,z6,z7,z8,z9,z10,z11,z12,z13,z14,z15}, {w16,w17,w18,w19}, ds4, pt, 1, 1, 0;\n"
        "wgmma.mma_async.sync.aligned.m64n64k16.f16.f16.f16 {z0,z1,z2,z3,z4,z5,z6,z7,z8,z9,z10,z11,z12,z13,z14,z15}, {w20,w21,w22,w23}, ds5, pt, 1, 1, 0;\n"
        "wgmma.commit_group.sync.aligned;\n"
        "mov.b32 {xl, xh}, a1; tanh.approx.f16 xr, xh; cvt.u32.u16 hi1, xr; mul.rn.f16x2 a2, z22, p; fma.rn.f16x2 p, z23, z23, c; fma.rn.f16x2 q2, g, g, q2; fma.rn.f16x2 g, z19, t, z19; prmt.b32 t, lo0, hi0, 0x5410; tanh.approx.f16 xr, xl; cvt.u32.u16 lo1, xr;\n"
        "B22:\n"
        "mov.b32 {xl, xh}, a2; tanh.approx.f16 xr, xh; cvt.u32.u16 hi0, xr; mul.rn.f16x2 a3, z23, p; fma.rn.f16x2 p, z24, z24, c; fma.rn.f16x2 q3, g, g, q3; fma.rn.f16x2 g, z20, t, z20; prmt.b32 t, lo1, hi1, 0x5410; tanh.approx.f16 xr, xl; cvt.u32.u16 lo0, xr;\n"
        "B23:\n"
        "mov.b32 {xl, xh}, a3; tanh.approx.f16 xr, xh; cvt.u32.u16 hi1, xr; mul.rn.f16x2 a0, z24, p; fma.rn.f16x2 p, z25, z25, c; fma.rn.f16x2 q2, g, g, q2; fma.rn.f16x2 g, z21, t, z21; prmt.b32 t, lo0, hi0, 0x5410; tanh.approx.f16 xr, xl; cvt.u32.u16 lo1, xr;\n"
        "B24:\n"
        "mov.b32 {xl, xh}, a0; tanh.approx.f16 xr, xh; cvt.u32.u16 hi0, xr; mul.rn.f16x2 a1, z25, p; fma.rn.f16x2 p, z26, z26, c; fma.rn.f16x2 q3, g, g, q3; fma.rn.f16x2 g, z22, t, z22; prmt.b32 t, lo1, hi1, 0x5410; tanh.approx.f16 xr, xl; cvt.u32.u16 lo0, xr;\n"
        "B25:\n"
        "mov.b32 {xl, xh}, a1; tanh.approx.f16 xr, xh; cvt.u32.u16 hi1, xr; mul.rn.f16x2 a2, z26, p; fma.rn.f16x2 p, z27, z27, c; fma.rn.f16x2 q2, g, g, q2; fma.rn.f16x2 g, z23, t, z23; prmt.b32 t, lo0, hi0, 0x5410; tanh.approx.f16 xr, xl; cvt.u32.u16 lo1, xr;\n"
        "B26:\n"
        "mov.b32 {xl, xh}, a2; tanh.approx.f16 xr, xh; cvt.u32.u16 hi0, xr; mul.rn.f16x2 a3, z27, p; fma.rn.f16x2 p, z28, z28, c; fma.rn.f16x2 q3, g, g, q3; fma.rn.f16x2 g, z24, t, z24; prmt.b32 t, lo1, hi1, 0x5410; tanh.approx.f16 xr, xl; cvt.u32.u16 lo0, xr;\n"
        "B27:\n"
        "add.u32 n, n, 8; setp.lt.u32 pe, n, 256; setp.ne.and.u32 pe, so, %7, pe;\n"
        "mov.b32 {xl, xh}, a3; tanh.approx.f16 xr, xh; cvt.u32.u16 hi1, xr; mul.rn.f16x2 a0, z28, p; fma.rn.f16x2 p, z29, z29, c; fma.rn.f16x2 q2, g, g, q2; fma.rn.f16x2 g, z25, t, z25; prmt.b32 t, lo0, hi0, 0x5410; tanh.approx.f16 xr, xl; cvt.u32.u16 lo1, xr;\n"
        "B28:\n"
        "mov.b32 {xl, xh}, a0; tanh.approx.f16 xr, xh; cvt.u32.u16 hi0, xr; mul.rn.f16x2 a1, z29, p; fma.rn.f16x2 p, z30, z30, c; fma.rn.f16x2 q3, g, g, q3; fma.rn.f16x2 g, z26, t, z26; prmt.b32 t, lo1, hi1, 0x5410; tanh.approx.f16 xr, xl; cvt.u32.u16 lo0, xr;\n"
        "B29:\n"
        "mov.b32 {xl, xh}, a1; tanh.approx.f16 xr, xh; cvt.u32.u16 hi1, xr; mul.rn.f16x2 a2, z30, p; fma.rn.f16x2 p, z31, z31, c; fma.rn.f16x2 q2, g, g, q2; fma.rn.f16x2 g, z27, t, z27; prmt.b32 t, lo0, hi0, 0x5410; tanh.approx.f16 xr, xl; cvt.u32.u16 lo1, xr;\n"
        "@pe bra.uni TOP;\n"
        "setp.lt.u32 pe, n, 256;\n"
        "@pe bra.uni DUTY;\n"
        "bra.uni DONE;\n"
        "SPINW: mov.u32 cnt, 0;\n"
        "SPINWL:\n"
        "mov.u32 tt, 230880; mbarrier.try_wait.parity.shared::cta.b64 pw, [tt], 0;\n"
        "@pw bra.uni BACKW;\n"
        "add.u32 cnt, cnt, 1; setp.lt.u32 pw, cnt, 0x100000;\n"
        "@pw bra.uni SPINWL;\n"
        "trap;\n"
        "SPIN0: mov.u32 cnt, 0;\n"
        "SPIN0L:\n"
        "mbarrier.try_wait.parity.shared::cta.b64 pw, [n+231552], 0;\n"
        "@pw bra.uni BACK0;\n"
        "add.u32 cnt, cnt, 1; setp.lt.u32 pw, cnt, 0x100000;\n"
        "@pw bra.uni SPIN0L;\n"
        "trap;\n"
        "SPIN: mov.u32 cnt, 0;\n"
        "SPINL:\n"
        "mbarrier.try_wait.parity.shared::cta.b64 pw, [n+231560], 0;\n"
        "@pw bra.uni BACK;\n"
        "add.u32 cnt, cnt, 1; setp.lt.u32 pw, cnt, 0x100000;\n"
        "@pw bra.uni SPINL;\n"
        "trap;\n"
        "DUTY:\n"
        "setp.ge.s32 pr, n, %11;\n"
        "@pr bra.uni FLUSH;\n"
        "setp.ge.u32 pr, %13, 2;\n"
        "@pr bra.uni ROLE2;\n"
        "setp.ge.s32 pr, n, %12; selp.b64 src, %14, gp, pr; add.u32 tt, n, 231288;\n"
        "elect.sync _|pr, 0xffffffff;\n"
        "@pr mbarrier.arrive.expect_tx.shared::cta.b64 _, [tt], %10;\n"
        "@pr cp.async.bulk.shared::cluster.global.mbarrier::complete_tx::bytes [%9], [src], %10, [tt];\n"
        "bra.uni FLUSH;\n"
        "ROLE2:\n"
        "setp.eq.u32 pr, %13, 3;\n"
        "@pr bra.uni ROLE3;\n"
        "setp.ne.s32 pr, n, 248;\n"
        "@pr bra.uni PARK;\n"
        "cp.async.bulk.wait_group 0;\n"
        "sub.s64 src, gp, %16; mov.u32 tt, 230824; mov.u32 cnt, 187392;\n"
        "elect.sync _|pr, 0xffffffff;\n"
        "@pr mbarrier.arrive.expect_tx.shared::cta.b64 _, [tt], 12288;\n"
        "@pr cp.async.bulk.shared::cluster.global.mbarrier::complete_tx::bytes [cnt], [src], 12288, [tt];\n"
        "PARK:\n"
        "elect.sync _|pr, 0xffffffff;\n"
        "@pr cp.async.bulk.global.shared::cta.bulk_group [gp], [%9], 12288;\n"
        "@pr cp.async.bulk.commit_group;\n"
        "bra.uni FLUSH;\n"
        "ROLE3:\n"
        "setp.ne.s32 pr, n, 64;\n"
        "@pr bra.uni AHEAD;\n"
        "mov.u32 tt, 230872;\n"
        "elect.sync _|pr, 0xffffffff;\n"
        "@pr mbarrier.arrive.expect_tx.shared::cta.b64 _, [tt], 75264;\n"
        "mov.u32 cnt, 229248; @pr cp.async.bulk.shared::cluster.global.mbarrier::complete_tx::bytes [cnt], [%18], 768, [tt];\n"
        "mov.u32 cnt, 230016; @pr cp.async.bulk.shared::cluster.global.mbarrier::complete_tx::bytes [cnt], [%19], 768, [tt];\n"
        "mov.u32 cnt, 74752; @pr cp.async.bulk.tensor.2d.shared::cluster.global.mbarrier::complete_tx::bytes [cnt], [%17, {0, 0}], [tt];\n"
        "mov.u32 cnt, 87040; @pr cp.async.bulk.tensor.2d.shared::cluster.global.mbarrier::complete_tx::bytes [cnt], [%17, {0, 192}], [tt];\n"
        "mov.u32 cnt, 99328; @pr cp.async.bulk.tensor.2d.shared::cluster.global.mbarrier::complete_tx::bytes [cnt], [%17, {32, 0}], [tt];\n"
        "mov.u32 cnt, 111616; @pr cp.async.bulk.tensor.2d.shared::cluster.global.mbarrier::complete_tx::bytes [cnt], [%17, {32, 192}], [tt];\n"
        "mov.u32 cnt, 123904; @pr cp.async.bulk.tensor.2d.shared::cluster.global.mbarrier::complete_tx::bytes [cnt], [%17, {64, 0}], [tt];\n"
        "mov.u32 cnt, 136192; @pr cp.async.bulk.tensor.2d.shared::cluster.global.mbarrier::complete_tx::bytes [cnt], [%17, {64, 192}], [tt];\n"
        "AHEAD:\n"
        "elect.sync _|pr, 0xffffffff;\n"
        "@pr cp.async.bulk.prefetch.L2.global [gp], 12288;\n"
        "FLUSH:\n"
        "add.s64 gp, gp, %16;\n"
        "mov.b32 {xl, xh}, q0; cvt.f32.f16 f0, xl; cvt.f32.f16 f1, xh; add.f32 f0, f0, f1; add.f32 %0, %0, f0; mov.b32 q0, 0;\n"
        "mov.b32 {xl, xh}, q1; cvt.f32.f16 f0, xl; cvt.f32.f16 f1, xh; add.f32 f0, f0, f1; add.f32 %1, %1, f0; mov.b32 q1, 0;\n"
        "mov.b32 {xl, xh}, q2; cvt.f32.f16 f0, xl; cvt.f32.f16 f1, xh; add.f32 f0, f0, f1; add.f32 %2, %2, f0; mov.b32 q2, 0;\n"
        "mov.b32 {xl, xh}, q3; cvt.f32.f16 f0, xl; cvt.f32.f16 f1, xh; add.f32 f0, f0, f1; add.f32 %3, %3, f0; mov.b32 q3, 0;\n"
        "setp.ne.u32 pr, %5, 0;\n"
        "@pr bra.uni TOP;\n"
        "wgmma.wait_group.sync.aligned 0;\n"
        "wgmma.fence.sync.aligned;\n"
        "ld.volatile.shared.v2.b32 {lo0, hi0}, [so]; xor.b32 f0, f0, lo0;\n"
        "ld.volatile.shared.v2.b32 {lo1, hi1}, [so]; xor.b32 f0, f0, lo1;\n"
        "ld.volatile.shared.v2.b32 {q1, a0}, [so]; xor.b32 f0, f0, q1;\n"
        "ld.volatile.shared.v2.b32 {q2, a1}, [so]; xor.b32 f0, f0, q2;\n"
        "ld.volatile.shared.v2.b32 {q3, a2}, [so]; xor.b32 f0, f0, q3;\n"
        "ld.volatile.shared.v2.b32 {q0, a3}, [so]; xor.b32 f0, f0, q0;\n"
        "ld.volatile.shared.v2.b32 {t, g}, [so]; xor.b32 f0, f0, t;\n"
        "ld.volatile.shared.v2.b32 {p, f1}, [so]; xor.b32 f0, f0, p;\n"
        "add.f32 %0, %0, f0;\n"
        "setp.eq.u32 pr, n, 1000; @pr bra.uni B31;\n"
        "setp.eq.u32 pr, n, 1001; @pr bra.uni B0;\n"
        "setp.eq.u32 pr, n, 1002; @pr bra.uni B1;\n"
        "setp.eq.u32 pr, n, 1003; @pr bra.uni B2;\n"
        "setp.eq.u32 pr, n, 1004; @pr bra.uni B3;\n"
        "setp.eq.u32 pr, n, 1005; @pr bra.uni B4;\n"
        "setp.eq.u32 pr, n, 1006; @pr bra.uni B5;\n"
        "setp.eq.u32 pr, n, 1007; @pr bra.uni B6;\n"
        "setp.eq.u32 pr, n, 1008; @pr bra.uni B7;\n"
        "setp.eq.u32 pr, n, 1009; @pr bra.uni B8;\n"
        "setp.eq.u32 pr, n, 1010; @pr bra.uni B9;\n"
        "setp.eq.u32 pr, n, 1011; @pr bra.uni B10;\n"
        "setp.eq.u32 pr, n, 1012; @pr bra.uni B11;\n"
        "setp.eq.u32 pr, n, 1013; @pr bra.uni B12;\n"
        "setp.eq.u32 pr, n, 1014; @pr bra.uni B13;\n"
        "setp.eq.u32 pr, n, 1015; @pr bra.uni B14;\n"
        "setp.eq.u32 pr, n, 1016; @pr bra.uni B15;\n"
        "setp.eq.u32 pr, n, 1017; @pr bra.uni B16;\n"
        "setp.eq.u32 pr, n, 1018; @pr bra.uni B17;\n"
        "setp.eq.u32 pr, n, 1019; @pr bra.uni B18;\n"
        "setp.eq.u32 pr, n, 1020; @pr bra.uni B19;\n"
        "setp.eq.u32 pr, n, 1021; @pr bra.uni B20;\n"
        "setp.eq.u32 pr, n, 1022; @pr bra.uni B21;\n"
        "setp.eq.u32 pr, n, 1023; @pr bra.uni B22;\n"
        "setp.eq.u32 pr, n, 1024; @pr bra.uni B23;\n"
        "setp.eq.u32 pr, n, 1025; @pr bra.uni B24;\n"
        "setp.eq.u32 pr, n, 1026; @pr bra.uni B25;\n"
        "setp.eq.u32 pr, n, 1027; @pr bra.uni B26;\n"
        "setp.eq.u32 pr, n, 1028; @pr bra.uni B27;\n"
        "setp.eq.u32 pr, n, 1029; @pr bra.uni B28;\n"
        "setp.eq.u32 pr, n, 1030; @pr bra.uni B29;\n"
        "setp.eq.u32 pr, n, 1031; @pr bra.uni TOP;\n"
        "trap;\n"
        "DONE:\n"
        ASM_TRC("n")
        "mov.b32 {xl, xh}, a2; tanh.approx.f16 xr, xh; cvt.u32.u16 hi0, xr; mul.rn.f16x2 a3, z31, p; fma.rn.f16x2 q3, g, g, q3; fma.rn.f16x2 g, z28, t, z28; prmt.b32 t, lo1, hi1, 0x5410; tanh.approx.f16 xr, xl; cvt.u32.u16 lo0, xr;\n"
        "mov.b32 {xl, xh}, a3; tanh.approx.f16 xr, xh; cvt.u32.u16 hi1, xr; fma.rn.f16x2 q2, g, g, q2; fma.rn.f16x2 g, z29, t, z29; prmt.b32 t, lo0, hi0, 0x5410; tanh.approx.f16 xr, xl; cvt.u32.u16 lo1, xr;\n"
        "fma.rn.f16x2 q3, g, g, q3; fma.rn.f16x2 g, z30, t, z30; prmt.b32 t, lo1, hi1, 0x5410;\n"
        "fma.rn.f16x2 q2, g, g, q2; fma.rn.f16x2 g, z31, t, z31;\n"
        "fma.rn.f16x2 q3, g, g, q3;\n"
        "mov.b32 {xl, xh}, q0; cvt.f32.f16 f0, xl; cvt.f32.f16 f1, xh; add.f32 f0, f0, f1; add.f32 %0, %0, f0; mov.b32 q0, 0;\n"
        "mov.b32 {xl, xh}, q1; cvt.f32.f16 f0, xl; cvt.f32.f16 f1, xh; add.f32 f0, f0, f1; add.f32 %1, %1, f0; mov.b32 q1, 0;\n"
        "mov.b32 {xl, xh}, q2; cvt.f32.f16 f0, xl; cvt.f32.f16 f1, xh; add.f32 f0, f0, f1; add.f32 %2, %2, f0; mov.b32 q2, 0;\n"
        "mov.b32 {xl, xh}, q3; cvt.f32.f16 f0, xl; cvt.f32.f16 f1, xh; add.f32 f0, f0, f1; add.f32 %3, %3, f0; mov.b32 q3, 0;\n"
        "wgmma.wait_group.sync.aligned 0;\n"
        "}\n"
        : "=f"(acc[0][0]), "=f"(acc[0][1]), "=f"(acc[1][0]), "=f"(acc[1][1])
        : "r"(w1t), "r"(yd), "r"(wd), "r"(own_slot), "l"(d.g), "r"(d.s), "r"(d.bytes), "r"(8 * d.end), "r"(8 * d.zero), "r"(role),
          "l"(d.zeros), "r"(lane), "l"(d.step), "l"(&prm.w2_map), "l"(prm.gamma), "l"(prm.beta), "l"(prm.ydesc64[0]), "l"(prm.ydesc64[1])
        : "memory");
}

template <int M>
__device__ __forceinline__ void gemm1_t(uint32_t (&d)[16], const uint32_t* wa, uint32_t yd, uint32_t wd) {
    wg_fence();
    wgmma_n64_h_set<0>(d, wa, desc<1024, 1>(yd, 0));
#pragma unroll
    for (int kk = 1; kk < 5; kk++)
        wgmma_n64_h_acc<0>(d, wa + kk * 4, kk < 4 ? desc<1024, 1>(yd, kk * 32) : desc<512, 2>(yd, 8192 + (kk - 4) * 32));
    wgmma_n64_h_acc_ss(d, desc<1024, 1>(wd, M * 12288), desc<512, 2>(yd, 8192 + 32));
    wg_commit();
}

__device__ __forceinline__ void gelu_sumsq_f(const uint32_t (&d)[16], float (&acc)[2]) {
#pragma unroll
    for (int r = 0; r < 16; r++) {
        float lo, hi;
        h2_unpack(gelu2(d[r]), lo, hi);
        acc[r & 1] = fmaf(lo, lo, acc[r & 1]);
        acc[r & 1] = fmaf(hi, hi, acc[r & 1]);
    }
}
__device__ __forceinline__ void load_w1t(uint32_t (&wa)[2][24], int wg, int w, int lane) {
#pragma unroll
    for (int m = 0; m < 2; m++)
#pragma unroll
        for (int kk = 0; kk < 5; kk++) {
            const int q = lane >> 3, c = 16 * kk + 8 * (q >> 1) + (lane & 7), ck = 2 * w + (q & 1);
            ldsm4_t(wa[m] + kk * 4, sb + SM_W1 + (2 * wg + m) * 12288 + c * 128 + ((ck ^ (c & 7)) * 16));
        }
}
__device__ __forceinline__ unsigned long long* acc_word(const Params& prm, uint32_t epoch, uint32_t e) {
    return &prm.g->acc[epoch & 1][(e >> 2) * 32 + (e & 3)];
}
__device__ __forceinline__ void publish_fast(const Params& prm, const float (&acc)[2][2], uint32_t epoch, int wg, int w, int lane) {
    const bool m = lane & 2, h = lane & 1;
    const float a = (m ? acc[1][0] : acc[0][0]) + __shfl_xor_sync(0xffffffffu, m ? acc[0][0] : acc[1][0], 2);
    const float b = (m ? acc[1][1] : acc[0][1]) + __shfl_xor_sync(0xffffffffu, m ? acc[0][1] : acc[1][1], 2);
    const float v = (h ? b : a) + __shfl_xor_sync(0xffffffffu, h ? a : b, 1);
    const unsigned long long q = (__float2ull_rn(fminf(v, ACC_LIMIT) * 0x1p16f) << 8) + 1;
    asm volatile("red.relaxed.gpu.global.add.u64 [%0], %1;"
                 ::"l"(acc_word(prm, epoch, 128 * wg + 32 * (lane & 2) + 16 * w + (lane >> 2) + 8 * (lane & 1))), "l"(q) : "memory");
}
__device__ __forceinline__ float collect_fast(const unsigned long long* word) {
    unsigned long long v;
    asm volatile(
        "{\n.reg .pred p;\n.reg .u32 n, lo, hi;\nmov.u32 n, 0;\n"
        "POLL:\nld.relaxed.gpu.global.u64 %0, [%1];\nmov.b64 {lo, hi}, %0;\nand.b32 lo, lo, 255;\n"
        "setp.eq.u32 p, lo, %2;\nvote.sync.all.pred p, p, 0xffffffff;\n@p bra.uni POLL_DONE;\n"
        "add.u32 n, n, 1;\nsetp.lt.u32 p, n, 0x400000;\n@p bra.uni POLL;\ntrap;\nPOLL_DONE:\n}\n"
        : "=l"(v) : "l"(word), "n"(NUM_CTAS) : "memory");
    return __ull2float_rn(v >> 8) * 0x1p-16f;
}
__device__ __forceinline__ void publish_sums(const float (&acc)[2][2], float* sums, unsigned int* counter, int wg, int w, int lane) {
#pragma unroll
    for (int m = 0; m < 2; m++)
#pragma unroll
        for (int h = 0; h < 2; h++) {
            const float v = quad_sum(acc[m][h]);
            if ((lane & 3) == 0) atomicAdd(sums + 64 * (2 * wg + m) + 16 * w + (lane >> 2) + 8 * h, v);
        }
    named_sync(1, 384);
    if (fresh_tid() == 0) asm volatile("red.release.gpu.global.add.u32 [%0], 1;" ::"l"(counter) : "memory");
}
__device__ __forceinline__ void grid_wait(const unsigned int* counter, unsigned int target) {
    if (fresh_tid() == 0) {
        unsigned int v, spins = 0;
        do {
            asm volatile("ld.acquire.gpu.global.u32 %0, [%1];" : "=r"(v) : "l"(counter) : "memory");
            if (++spins > (1u << 22)) __trap();
        } while ((int)(v - target) < 0);
    }
    __syncthreads();
}

struct Pass2 {
    uint32_t wg;
    uint32_t off;
    int step;
    uint32_t xs;
    uint32_t a_offs, xs_offs, bias_addr;
    uint32_t w;
};

static_assert(sb + SM_BAR + BAR_ROWS * 8 == 231208 && BAR_STAT == BAR_ROWS + 2 && sb + SM_RED + RED_SCALE * 4 == 230792, "layout");
static_assert(sb + SM_BAR + BAR_Y2FULL * 8 == 230800 && sb + SM_BAR + BAR_XSFULL * 8 == 230832, "layout");
#define PASS2_STATE ".reg .b32 qa<24>, qz<32>, o<24>, g<16>, p<2>, a<4>, lo<2>, hi<2>, h<2>, osc;"
__device__ __forceinline__ void pass2_start(const Pass2& c, const Params& prm) {
    asm volatile(
        "{\n"
        ".reg .b32 t<2>, c, tt, ad, cnt, ybar;\n"
        ".reg .b16 xl, xh, xr;\n"
        ".reg .b64 w1d, dt;\n"
        ".reg .pred pt, pf, pw;\n"
        "setp.ne.b32 pt, 1, 0; setp.ne.b32 pf, 0, 0; mov.b32 c, 0x40D940D9; mov.b64 w1d, {%1, 0x40000040}; mad.lo.u32 ybar, %2, 8, 230800;\n"
        "mbarrier.try_wait.parity.shared::cta.b64 pw, [ybar], 0;\n"
        "@!pw bra.uni SPINY0;\n"
        "BACKY0:\n"
        "and.b32 t0, %5, 0xffff; shr.u32 t1, %5, 16;\n"
        "xor.b32 ad, t0, 0; add.u32 ad, ad, %4; ldmatrix.sync.aligned.m8n8.x4.shared.b16 {qa0,qa1,qa2,qa3}, [ad];\n"
        "xor.b32 ad, t0, 32; add.u32 ad, ad, %4; ldmatrix.sync.aligned.m8n8.x4.shared.b16 {qa4,qa5,qa6,qa7}, [ad];\n"
        "xor.b32 ad, t0, 64; add.u32 ad, ad, %4; ldmatrix.sync.aligned.m8n8.x4.shared.b16 {qa8,qa9,qa10,qa11}, [ad];\n"
        "xor.b32 ad, t0, 96; add.u32 ad, ad, %4; ldmatrix.sync.aligned.m8n8.x4.shared.b16 {qa12,qa13,qa14,qa15}, [ad];\n"
        "xor.b32 ad, t1, 0; add.u32 ad, ad, %4; ldmatrix.sync.aligned.m8n8.x4.shared.b16 {qa16,qa17,qa18,qa19}, [ad];\n"
        "xor.b32 ad, t1, 32; add.u32 ad, ad, %4; ldmatrix.sync.aligned.m8n8.x4.shared.b16 {qa20,qa21,qa22,qa23}, [ad];\n"
        "wgmma.fence.sync.aligned;\n"
        "add.s64 dt, w1d, 0; wgmma.mma_async.sync.aligned.m64n64k16.f16.f16.f16 {qz0,qz1,qz2,qz3,qz4,qz5,qz6,qz7,qz8,qz9,qz10,qz11,qz12,qz13,qz14,qz15}, {qa0,qa1,qa2,qa3}, dt, pf, 1, 1, 1;\n"
        "add.s64 dt, w1d, 128; wgmma.mma_async.sync.aligned.m64n64k16.f16.f16.f16 {qz0,qz1,qz2,qz3,qz4,qz5,qz6,qz7,qz8,qz9,qz10,qz11,qz12,qz13,qz14,qz15}, {qa4,qa5,qa6,qa7}, dt, pt, 1, 1, 1;\n"
        "add.s64 dt, w1d, 256; wgmma.mma_async.sync.aligned.m64n64k16.f16.f16.f16 {qz0,qz1,qz2,qz3,qz4,qz5,qz6,qz7,qz8,qz9,qz10,qz11,qz12,qz13,qz14,qz15}, {qa8,qa9,qa10,qa11}, dt, pt, 1, 1, 1;\n"
        "add.s64 dt, w1d, 384; wgmma.mma_async.sync.aligned.m64n64k16.f16.f16.f16 {qz0,qz1,qz2,qz3,qz4,qz5,qz6,qz7,qz8,qz9,qz10,qz11,qz12,qz13,qz14,qz15}, {qa12,qa13,qa14,qa15}, dt, pt, 1, 1, 1;\n"
        "add.s64 dt, w1d, 512; wgmma.mma_async.sync.aligned.m64n64k16.f16.f16.f16 {qz0,qz1,qz2,qz3,qz4,qz5,qz6,qz7,qz8,qz9,qz10,qz11,qz12,qz13,qz14,qz15}, {qa16,qa17,qa18,qa19}, dt, pt, 1, 1, 1;\n"
        "add.s64 dt, w1d, 640; wgmma.mma_async.sync.aligned.m64n64k16.f16.f16.f16 {qz0,qz1,qz2,qz3,qz4,qz5,qz6,qz7,qz8,qz9,qz10,qz11,qz12,qz13,qz14,qz15}, {qa20,qa21,qa22,qa23}, dt, pt, 1, 1, 1;\n"
        "wgmma.commit_group.sync.aligned;\n"
        "wgmma.wait_group.sync.aligned 0;\n"
        "fma.rn.f16x2 p0, qz0, qz0, c;\n"
        "mul.rn.f16x2 a0, qz0, p0; fma.rn.f16x2 p1, qz1, qz1, c;\n"
        "mov.b32 {xl, xh}, a0; tanh.approx.f16 xr, xl; cvt.u32.u16 lo0, xr; tanh.approx.f16 xr, xh; cvt.u32.u16 hi0, xr; mul.rn.f16x2 a1, qz1, p1; fma.rn.f16x2 p0, qz2, qz2, c;\n"
        "mov.b32 {xl, xh}, a1; tanh.approx.f16 xr, xl; cvt.u32.u16 lo1, xr; tanh.approx.f16 xr, xh; cvt.u32.u16 hi1, xr; mul.rn.f16x2 a2, qz2, p0; fma.rn.f16x2 p1, qz3, qz3, c; prmt.b32 h0, lo0, hi0, 0x5410;\n"
        "mov.b32 {xl, xh}, a2; tanh.approx.f16 xr, xl; cvt.u32.u16 lo0, xr; tanh.approx.f16 xr, xh; cvt.u32.u16 hi0, xr; mul.rn.f16x2 a3, qz3, p1; fma.rn.f16x2 p0, qz4, qz4, c; fma.rn.f16x2 g0, qz0, h0, qz0; prmt.b32 h1, lo1, hi1, 0x5410;\n"
        "mov.b32 {xl, xh}, a3; tanh.approx.f16 xr, xl; cvt.u32.u16 lo1, xr; tanh.approx.f16 xr, xh; cvt.u32.u16 hi1, xr; mul.rn.f16x2 a0, qz4, p0; fma.rn.f16x2 p1, qz5, qz5, c; fma.rn.f16x2 g1, qz1, h1, qz1; prmt.b32 h0, lo0, hi0, 0x5410;\n"
        "mov.b32 {xl, xh}, a0; tanh.approx.f16 xr, xl; cvt.u32.u16 lo0, xr; tanh.approx.f16 xr, xh; cvt.u32.u16 hi0, xr; mul.rn.f16x2 a1, qz5, p1; fma.rn.f16x2 p0, qz6, qz6, c; fma.rn.f16x2 g2, qz2, h0, qz2; prmt.b32 h1, lo1, hi1, 0x5410;\n"
        "mov.b32 {xl, xh}, a1; tanh.approx.f16 xr, xl; cvt.u32.u16 lo1, xr; tanh.approx.f16 xr, xh; cvt.u32.u16 hi1, xr; mul.rn.f16x2 a2, qz6, p0; fma.rn.f16x2 p1, qz7, qz7, c; fma.rn.f16x2 g3, qz3, h1, qz3; prmt.b32 h0, lo0, hi0, 0x5410;\n"
        "bra.uni DONE;\n"
        "SPINY0: mov.u32 cnt, 0;\n"
        "SPINY0L:\n"
        "mbarrier.try_wait.parity.shared::cta.b64 pw, [ybar], 0;\n"
        "@pw bra.uni BACKY0;\n"
        "add.u32 cnt, cnt, 1; setp.lt.u32 pw, cnt, 0x100000;\n"
        "@pw bra.uni SPINY0L;\n"
        "trap;\n"
        "DONE:\n"
        "}\n"
        :: "n"(0), "r"(prm.w1desc), "r"(c.wg), "n"(0), "r"(c.xs), "r"(c.a_offs) : "memory");
}
__device__ __forceinline__ bool pass2_head(const Pass2& c, uint32_t round) {
    uint32_t retry;
    asm volatile(
        "{\n"
        ".reg .b32 t<2>, tt, ad, cnt;\n"
        ".reg .pred pw;\n"
        "and.b32 t0, %3, 0xffff; shr.u32 t1, %3, 16;\n"
        "xor.b32 ad, t0, 0; add.u32 ad, ad, %4; ldmatrix.sync.aligned.m8n8.x4.shared.b16 {qa0,qa1,qa2,qa3}, [ad];\n"
        "xor.b32 ad, t0, 32; add.u32 ad, ad, %4; ldmatrix.sync.aligned.m8n8.x4.shared.b16 {qa4,qa5,qa6,qa7}, [ad];\n"
        "xor.b32 ad, t0, 64; add.u32 ad, ad, %4; ldmatrix.sync.aligned.m8n8.x4.shared.b16 {qa8,qa9,qa10,qa11}, [ad];\n"
        "xor.b32 ad, t0, 96; add.u32 ad, ad, %4; ldmatrix.sync.aligned.m8n8.x4.shared.b16 {qa12,qa13,qa14,qa15}, [ad];\n"
        "xor.b32 ad, t1, 0; add.u32 ad, ad, %4; ldmatrix.sync.aligned.m8n8.x4.shared.b16 {qa16,qa17,qa18,qa19}, [ad];\n"
        "xor.b32 ad, t1, 32; add.u32 ad, ad, %4; ldmatrix.sync.aligned.m8n8.x4.shared.b16 {qa20,qa21,qa22,qa23}, [ad];\n"
        "mov.b32 qz16, 0; mov.b32 qz17, 0; mov.b32 qz18, 0; mov.b32 qz19, 0; mov.b32 qz20, 0; mov.b32 qz21, 0; mov.b32 qz22, 0; mov.b32 qz23, 0; mov.b32 qz24, 0; mov.b32 qz25, 0; mov.b32 qz26, 0; mov.b32 qz27, 0; mov.b32 qz28, 0; mov.b32 qz29, 0; mov.b32 qz30, 0; mov.b32 qz31, 0;\n"
        "mov.b32 g4, 0; mov.b32 g5, 0; mov.b32 g6, 0; mov.b32 g7, 0; mov.b32 g8, 0; mov.b32 g9, 0; mov.b32 g10, 0; mov.b32 g11, 0; mov.b32 g12, 0; mov.b32 g13, 0; mov.b32 g14, 0; mov.b32 g15, 0;\n"
        "mov.u32 tt, 231224; mbarrier.try_wait.parity.shared::cta.b64 pw, [tt], %1;\n"
        "@!pw bra.uni SPINR;\n"
        "BACKR:\n"
        "mov.u32 tt, 230792; ld.shared.v2.b32 {osc, %0}, [tt];\n"
        "ld.shared.v4.b32 {o0,o1,o2,o3}, [%2+0];\n"
        "ld.shared.v4.b32 {o4,o5,o6,o7}, [%2+64];\n"
        "ld.shared.v4.b32 {o8,o9,o10,o11}, [%2+128];\n"
        "ld.shared.v4.b32 {o12,o13,o14,o15}, [%2+192];\n"
        "ld.shared.v4.b32 {o16,o17,o18,o19}, [%2+256];\n"
        "ld.shared.v4.b32 {o20,o21,o22,o23}, [%2+320];\n"
        "bra.uni DONE;\n"
        "SPINR: mov.u32 cnt, 0;\n"
        "SPINRL:\n"
        "mov.u32 tt, 231224; mbarrier.try_wait.parity.shared::cta.b64 pw, [tt], %1;\n"
        "@pw bra.uni BACKR;\n"
        "add.u32 cnt, cnt, 1; setp.lt.u32 pw, cnt, 0x100000;\n"
        "@pw bra.uni SPINRL;\n"
        "trap;\n"
        "DONE:\n"
        "}\n"
        : "=r"(retry)
        : "r"(round), "r"(c.bias_addr), "r"(c.a_offs), "r"(c.xs)
        : "memory");
    return __any_sync(0xffffffffu, retry);
}
__device__ __forceinline__ void pass2_tiles(const Pass2& c, const Params& prm) {
    asm volatile(
        "{\n"
        ".reg .b32 v<8>, n, off, c, tt, ad, cnt, ybar, xbar, tbar, tpar, id;\n"
        ".reg .b16 xl, xh, xr;\n"
        ".reg .f32 f0, f1;\n"
        ".reg .b64 w1d, w2d, dt, gp, pol;\n"
        ".reg .pred pt, pf, pr, pw, pl, pk, pm, pz, pn;\n"
        "setp.ne.b32 pt, 1, 0; setp.ne.b32 pf, 0, 0; setp.eq.u32 pl, %9, 0; setp.eq.u32 pk, %9, 0; setp.eq.u32 pz, %0, 0;\n"
        "mov.b32 c, 0x40D940D9;\n"
        "mov.b64 w1d, {%0, 0x40000040}; mov.b64 w2d, {%1, 0x80000020};\n"
        "mad.lo.u32 ybar, %2, 8, 230800; mad.lo.u32 xbar, %2, 8, 230832; add.u32 id, %2, 2;\n"
        "xor.b32 tt, %2, 0; mad.lo.u32 tbar, tt, 64, 230888; setp.eq.u32 pr, tt, 0; selp.u32 tpar, 1, 0, pr; mov.u32 tt, %laneid; setp.eq.u32 pn, tt, 0;\n"
        "mov.u32 n, -1; add.u32 off, %3, %8; mov.pred pm, pt; mov.b64 pol, 0x12F0000000000000;\n"
        "mov.b32 v0, 0; mov.b32 v1, 0; mov.b32 v2, 0; mov.b32 v3, 0; mov.b32 v4, 0; mov.b32 v5, 0; mov.b32 v6, 0; mov.b32 v7, 0;\n"
        "LOOP:\n"
        "@!pm bra.uni SKIP0;\n"
        "wgmma.fence.sync.aligned;\n"
        "add.s64 dt, w1d, 768; wgmma.mma_async.sync.aligned.m64n64k16.f16.f16.f16 {qz16,qz17,qz18,qz19,qz20,qz21,qz22,qz23,qz24,qz25,qz26,qz27,qz28,qz29,qz30,qz31}, {qa0,qa1,qa2,qa3}, dt, pf, 1, 1, 1;\n"
        "add.s64 dt, w1d, 896; wgmma.mma_async.sync.aligned.m64n64k16.f16.f16.f16 {qz16,qz17,qz18,qz19,qz20,qz21,qz22,qz23,qz24,qz25,qz26,qz27,qz28,qz29,qz30,qz31}, {qa4,qa5,qa6,qa7}, dt, pt, 1, 1, 1;\n"
        "add.s64 dt, w1d, 1024; wgmma.mma_async.sync.aligned.m64n64k16.f16.f16.f16 {qz16,qz17,qz18,qz19,qz20,qz21,qz22,qz23,qz24,qz25,qz26,qz27,qz28,qz29,qz30,qz31}, {qa8,qa9,qa10,qa11}, dt, pt, 1, 1, 1;\n"
        "add.s64 dt, w1d, 1152; wgmma.mma_async.sync.aligned.m64n64k16.f16.f16.f16 {qz16,qz17,qz18,qz19,qz20,qz21,qz22,qz23,qz24,qz25,qz26,qz27,qz28,qz29,qz30,qz31}, {qa12,qa13,qa14,qa15}, dt, pt, 1, 1, 1;\n"
        "add.s64 dt, w1d, 1280; wgmma.mma_async.sync.aligned.m64n64k16.f16.f16.f16 {qz16,qz17,qz18,qz19,qz20,qz21,qz22,qz23,qz24,qz25,qz26,qz27,qz28,qz29,qz30,qz31}, {qa16,qa17,qa18,qa19}, dt, pt, 1, 1, 1;\n"
        "add.s64 dt, w1d, 1408; wgmma.mma_async.sync.aligned.m64n64k16.f16.f16.f16 {qz16,qz17,qz18,qz19,qz20,qz21,qz22,qz23,qz24,qz25,qz26,qz27,qz28,qz29,qz30,qz31}, {qa20,qa21,qa22,qa23}, dt, pt, 1, 1, 1;\n"
        "SKIP0:\n"
        "setp.lt.s32 pr, n, 0;\n"
        "@pr bra.uni FIRST;\n"
        "and.b32 tt, n, 1; mbarrier.try_wait.parity.shared::cta.b64 pw, [xbar], tt;\n"
        "@!pw bra.uni SPINX;\n"
        "BACKX:\n"
        "and.b32 ad, %6, 0xffff; add.u32 ad, ad, %4; ld.shared.v4.b32 {v0,v1,v2,v3}, [ad+0];\n"
        "shr.u32 ad, %6, 16; add.u32 ad, ad, %4; ld.shared.v4.b32 {v4,v5,v6,v7}, [ad+0];\n"
        "mov.b32 {xl, xh}, o0; cvt.f32.f16 f0, xl; cvt.f32.f16 f1, xh; cvt.rn.bf16x2.f32 tt, f1, f0; fma.rn.bf16x2 v0, tt, osc, v0;\n"
        "mov.b32 {xl, xh}, o2; cvt.f32.f16 f0, xl; cvt.f32.f16 f1, xh; cvt.rn.bf16x2.f32 tt, f1, f0; fma.rn.bf16x2 v1, tt, osc, v1;\n"
        "mov.b32 {xl, xh}, o4; cvt.f32.f16 f0, xl; cvt.f32.f16 f1, xh; cvt.rn.bf16x2.f32 tt, f1, f0; fma.rn.bf16x2 v2, tt, osc, v2;\n"
        "mov.b32 {xl, xh}, o6; cvt.f32.f16 f0, xl; cvt.f32.f16 f1, xh; cvt.rn.bf16x2.f32 tt, f1, f0; fma.rn.bf16x2 v3, tt, osc, v3;\n"
        "and.b32 ad, %6, 0xffff; add.u32 ad, ad, %4; st.shared.v4.b32 [ad+0], {v0,v1,v2,v3};\n"
        "and.b32 ad, %6, 0xffff; add.u32 ad, ad, %4; ld.shared.v4.b32 {v0,v1,v2,v3}, [ad+64];\n"
        "mov.b32 {xl, xh}, o1; cvt.f32.f16 f0, xl; cvt.f32.f16 f1, xh; cvt.rn.bf16x2.f32 tt, f1, f0; fma.rn.bf16x2 v4, tt, osc, v4;\n"
        "mov.b32 {xl, xh}, o3; cvt.f32.f16 f0, xl; cvt.f32.f16 f1, xh; cvt.rn.bf16x2.f32 tt, f1, f0; fma.rn.bf16x2 v5, tt, osc, v5;\n"
        "mov.b32 {xl, xh}, o5; cvt.f32.f16 f0, xl; cvt.f32.f16 f1, xh; cvt.rn.bf16x2.f32 tt, f1, f0; fma.rn.bf16x2 v6, tt, osc, v6;\n"
        "mov.b32 {xl, xh}, o7; cvt.f32.f16 f0, xl; cvt.f32.f16 f1, xh; cvt.rn.bf16x2.f32 tt, f1, f0; fma.rn.bf16x2 v7, tt, osc, v7;\n"
        "shr.u32 ad, %6, 16; add.u32 ad, ad, %4; st.shared.v4.b32 [ad+0], {v4,v5,v6,v7};\n"
        "shr.u32 ad, %6, 16; add.u32 ad, ad, %4; ld.shared.v4.b32 {v4,v5,v6,v7}, [ad+64];\n"
        "ld.shared.v4.b32 {o0,o1,o2,o3}, [%7+0];\n"
        "ld.shared.v4.b32 {o4,o5,o6,o7}, [%7+64];\n"
        "mov.b32 {xl, xh}, o8; cvt.f32.f16 f0, xl; cvt.f32.f16 f1, xh; cvt.rn.bf16x2.f32 tt, f1, f0; fma.rn.bf16x2 v0, tt, osc, v0;\n"
        "mov.b32 {xl, xh}, o10; cvt.f32.f16 f0, xl; cvt.f32.f16 f1, xh; cvt.rn.bf16x2.f32 tt, f1, f0; fma.rn.bf16x2 v1, tt, osc, v1;\n"
        "mov.b32 {xl, xh}, o12; cvt.f32.f16 f0, xl; cvt.f32.f16 f1, xh; cvt.rn.bf16x2.f32 tt, f1, f0; fma.rn.bf16x2 v2, tt, osc, v2;\n"
        "mov.b32 {xl, xh}, o14; cvt.f32.f16 f0, xl; cvt.f32.f16 f1, xh; cvt.rn.bf16x2.f32 tt, f1, f0; fma.rn.bf16x2 v3, tt, osc, v3;\n"
        "and.b32 ad, %6, 0xffff; add.u32 ad, ad, %4; st.shared.v4.b32 [ad+64], {v0,v1,v2,v3};\n"
        "and.b32 ad, %6, 0xffff; add.u32 ad, ad, %4; ld.shared.v4.b32 {v0,v1,v2,v3}, [ad+128];\n"
        "mov.b32 {xl, xh}, o9; cvt.f32.f16 f0, xl; cvt.f32.f16 f1, xh; cvt.rn.bf16x2.f32 tt, f1, f0; fma.rn.bf16x2 v4, tt, osc, v4;\n"
        "mov.b32 {xl, xh}, o11; cvt.f32.f16 f0, xl; cvt.f32.f16 f1, xh; cvt.rn.bf16x2.f32 tt, f1, f0; fma.rn.bf16x2 v5, tt, osc, v5;\n"
        "mov.b32 {xl, xh}, o13; cvt.f32.f16 f0, xl; cvt.f32.f16 f1, xh; cvt.rn.bf16x2.f32 tt, f1, f0; fma.rn.bf16x2 v6, tt, osc, v6;\n"
        "mov.b32 {xl, xh}, o15; cvt.f32.f16 f0, xl; cvt.f32.f16 f1, xh; cvt.rn.bf16x2.f32 tt, f1, f0; fma.rn.bf16x2 v7, tt, osc, v7;\n"
        "shr.u32 ad, %6, 16; add.u32 ad, ad, %4; st.shared.v4.b32 [ad+64], {v4,v5,v6,v7};\n"
        "shr.u32 ad, %6, 16; add.u32 ad, ad, %4; ld.shared.v4.b32 {v4,v5,v6,v7}, [ad+128];\n"
        "ld.shared.v4.b32 {o8,o9,o10,o11}, [%7+128];\n"
        "ld.shared.v4.b32 {o12,o13,o14,o15}, [%7+192];\n"
        "mov.b32 {xl, xh}, o16; cvt.f32.f16 f0, xl; cvt.f32.f16 f1, xh; cvt.rn.bf16x2.f32 tt, f1, f0; fma.rn.bf16x2 v0, tt, osc, v0;\n"
        "mov.b32 {xl, xh}, o18; cvt.f32.f16 f0, xl; cvt.f32.f16 f1, xh; cvt.rn.bf16x2.f32 tt, f1, f0; fma.rn.bf16x2 v1, tt, osc, v1;\n"
        "mov.b32 {xl, xh}, o20; cvt.f32.f16 f0, xl; cvt.f32.f16 f1, xh; cvt.rn.bf16x2.f32 tt, f1, f0; fma.rn.bf16x2 v2, tt, osc, v2;\n"
        "mov.b32 {xl, xh}, o22; cvt.f32.f16 f0, xl; cvt.f32.f16 f1, xh; cvt.rn.bf16x2.f32 tt, f1, f0; fma.rn.bf16x2 v3, tt, osc, v3;\n"
        "and.b32 ad, %6, 0xffff; add.u32 ad, ad, %4; st.shared.v4.b32 [ad+128], {v0,v1,v2,v3};\n"
        "mov.b32 {xl, xh}, o17; cvt.f32.f16 f0, xl; cvt.f32.f16 f1, xh; cvt.rn.bf16x2.f32 tt, f1, f0; fma.rn.bf16x2 v4, tt, osc, v4;\n"
        "mov.b32 {xl, xh}, o19; cvt.f32.f16 f0, xl; cvt.f32.f16 f1, xh; cvt.rn.bf16x2.f32 tt, f1, f0; fma.rn.bf16x2 v5, tt, osc, v5;\n"
        "mov.b32 {xl, xh}, o21; cvt.f32.f16 f0, xl; cvt.f32.f16 f1, xh; cvt.rn.bf16x2.f32 tt, f1, f0; fma.rn.bf16x2 v6, tt, osc, v6;\n"
        "mov.b32 {xl, xh}, o23; cvt.f32.f16 f0, xl; cvt.f32.f16 f1, xh; cvt.rn.bf16x2.f32 tt, f1, f0; fma.rn.bf16x2 v7, tt, osc, v7;\n"
        "shr.u32 ad, %6, 16; add.u32 ad, ad, %4; st.shared.v4.b32 [ad+128], {v4,v5,v6,v7};\n"
        "ld.shared.v4.b32 {o16,o17,o18,o19}, [%7+256];\n"
        "ld.shared.v4.b32 {o20,o21,o22,o23}, [%7+320];\n"
        "FIRST:\n"
        "@pz bra.uni B7;\n"
        "mov.b32 {xl, xh}, a2; tanh.approx.f16 xr, xl; cvt.u32.u16 lo0, xr; tanh.approx.f16 xr, xh; cvt.u32.u16 hi0, xr; mul.rn.f16x2 a3, qz7, p1; fma.rn.f16x2 p0, qz8, qz8, c; fma.rn.f16x2 g4, qz4, h0, qz4; prmt.b32 h1, lo1, hi1, 0x5410;\n"
        "B7:\n"
        "fence.proxy.async.shared::cta;\n"
        "add.u32 tt, id, 4;\n"
        "@pl bra.uni STORE;\n"
        "bar.arrive tt, 128;\n"
        "STOREB:\n"
        ASM_MARK
        "@!pm bra.uni DONE;\n"
        "add.s32 n, n, 1; sub.u32 off, off, %8; setp.lt.s32 pm, n, 7;\n"
        "@pz bra.uni B10;\n"
        "mov.b32 {xl, xh}, a3; tanh.approx.f16 xr, xl; cvt.u32.u16 lo1, xr; tanh.approx.f16 xr, xh; cvt.u32.u16 hi1, xr; mul.rn.f16x2 a0, qz8, p0; fma.rn.f16x2 p1, qz9, qz9, c; fma.rn.f16x2 g5, qz5, h1, qz5; prmt.b32 h0, lo0, hi0, 0x5410;\n"
        "mov.b32 {xl, xh}, a0; tanh.approx.f16 xr, xl; cvt.u32.u16 lo0, xr; tanh.approx.f16 xr, xh; cvt.u32.u16 hi0, xr; mul.rn.f16x2 a1, qz9, p1; fma.rn.f16x2 p0, qz10, qz10, c; fma.rn.f16x2 g6, qz6, h0, qz6; prmt.b32 h1, lo1, hi1, 0x5410;\n"
        "mov.b32 {xl, xh}, a1; tanh.approx.f16 xr, xl; cvt.u32.u16 lo1, xr; tanh.approx.f16 xr, xh; cvt.u32.u16 hi1, xr; mul.rn.f16x2 a2, qz10, p0; fma.rn.f16x2 p1, qz11, qz11, c; fma.rn.f16x2 g7, qz7, h1, qz7; prmt.b32 h0, lo0, hi0, 0x5410;\n"
        "B10:\n"
        "setp.eq.s32 pr, n, 0;\n"
        "@pr bra.uni SPINW0;\n"
        "BACKW0:\n"
        "wgmma.fence.sync.aligned;\n"
        "add.s64 dt, w2d, 0; wgmma.mma_async.sync.aligned.m64n96k16.f16.f16.f16 {o0,o1,o2,o3,o4,o5,o6,o7,o8,o9,o10,o11,o12,o13,o14,o15,o16,o17,o18,o19,o20,o21,o22,o23}, {g0,g1,g2,g3}, dt, pt, 1, 1, 1;\n"
        "add.s64 dt, w2d, 64; wgmma.mma_async.sync.aligned.m64n96k16.f16.f16.f16 {o0,o1,o2,o3,o4,o5,o6,o7,o8,o9,o10,o11,o12,o13,o14,o15,o16,o17,o18,o19,o20,o21,o22,o23}, {g4,g5,g6,g7}, dt, pt, 1, 1, 1;\n"
        "wgmma.commit_group.sync.aligned;\n"
        "@pz bra.uni B14;\n"
        "mov.b32 {xl, xh}, a2; tanh.approx.f16 xr, xl; cvt.u32.u16 lo0, xr; tanh.approx.f16 xr, xh; cvt.u32.u16 hi0, xr; mul.rn.f16x2 a3, qz11, p1; fma.rn.f16x2 p0, qz12, qz12, c; fma.rn.f16x2 g8, qz8, h0, qz8; prmt.b32 h1, lo1, hi1, 0x5410;\n"
        "mov.b32 {xl, xh}, a3; tanh.approx.f16 xr, xl; cvt.u32.u16 lo1, xr; tanh.approx.f16 xr, xh; cvt.u32.u16 hi1, xr; mul.rn.f16x2 a0, qz12, p0; fma.rn.f16x2 p1, qz13, qz13, c; fma.rn.f16x2 g9, qz9, h1, qz9; prmt.b32 h0, lo0, hi0, 0x5410;\n"
        "mov.b32 {xl, xh}, a0; tanh.approx.f16 xr, xl; cvt.u32.u16 lo0, xr; tanh.approx.f16 xr, xh; cvt.u32.u16 hi0, xr; mul.rn.f16x2 a1, qz13, p1; fma.rn.f16x2 p0, qz14, qz14, c; fma.rn.f16x2 g10, qz10, h0, qz10; prmt.b32 h1, lo1, hi1, 0x5410;\n"
        "mov.b32 {xl, xh}, a1; tanh.approx.f16 xr, xl; cvt.u32.u16 lo1, xr; tanh.approx.f16 xr, xh; cvt.u32.u16 hi1, xr; mul.rn.f16x2 a2, qz14, p0; fma.rn.f16x2 p1, qz15, qz15, c; fma.rn.f16x2 g11, qz11, h1, qz11; prmt.b32 h0, lo0, hi0, 0x5410;\n"
        "B14:\n"
        "wgmma.wait_group.sync.aligned 0;\n"
        "wgmma.fence.sync.aligned;\n"
        "add.s64 dt, w2d, 128; wgmma.mma_async.sync.aligned.m64n96k16.f16.f16.f16 {o0,o1,o2,o3,o4,o5,o6,o7,o8,o9,o10,o11,o12,o13,o14,o15,o16,o17,o18,o19,o20,o21,o22,o23}, {g8,g9,g10,g11}, dt, pt, 1, 1, 1;\n"
        "wgmma.commit_group.sync.aligned;\n"
        "@pz bra.uni B18;\n"
        "mov.b32 {xl, xh}, a2; tanh.approx.f16 xr, xl; cvt.u32.u16 lo0, xr; tanh.approx.f16 xr, xh; cvt.u32.u16 hi0, xr; mul.rn.f16x2 a3, qz15, p1; fma.rn.f16x2 p0, qz16, qz16, c; fma.rn.f16x2 g12, qz12, h0, qz12; prmt.b32 h1, lo1, hi1, 0x5410;\n"
        "mov.b32 {xl, xh}, a3; tanh.approx.f16 xr, xl; cvt.u32.u16 lo1, xr; tanh.approx.f16 xr, xh; cvt.u32.u16 hi1, xr; mul.rn.f16x2 a0, qz16, p0; fma.rn.f16x2 p1, qz17, qz17, c; fma.rn.f16x2 g13, qz13, h1, qz13; prmt.b32 h0, lo0, hi0, 0x5410;\n"
        "mov.b32 {xl, xh}, a0; tanh.approx.f16 xr, xl; cvt.u32.u16 lo0, xr; tanh.approx.f16 xr, xh; cvt.u32.u16 hi0, xr; mul.rn.f16x2 a1, qz17, p1; fma.rn.f16x2 p0, qz18, qz18, c; fma.rn.f16x2 g14, qz14, h0, qz14; prmt.b32 h1, lo1, hi1, 0x5410;\n"
        "mov.b32 {xl, xh}, a1; tanh.approx.f16 xr, xl; cvt.u32.u16 lo1, xr; tanh.approx.f16 xr, xh; cvt.u32.u16 hi1, xr; mul.rn.f16x2 a2, qz18, p0; fma.rn.f16x2 p1, qz19, qz19, c; fma.rn.f16x2 g15, qz15, h1, qz15; prmt.b32 h0, lo0, hi0, 0x5410;\n"
        "B18:\n"
        "mad.lo.u32 tt, n, 8, tbar; mbarrier.try_wait.parity.shared::cta.b64 pw, [tt], tpar;\n"
        "@!pw bra.uni SPINT;\n"
        "BACKT:\n"
        "wgmma.fence.sync.aligned;\n"
        "add.s64 dt, w2d, 192; wgmma.mma_async.sync.aligned.m64n96k16.f16.f16.f16 {o0,o1,o2,o3,o4,o5,o6,o7,o8,o9,o10,o11,o12,o13,o14,o15,o16,o17,o18,o19,o20,o21,o22,o23}, {g12,g13,g14,g15}, dt, pt, 1, 1, 1;\n"
        "add.s64 dt, w1d, 1536; wgmma.mma_async.sync.aligned.m64n64k16.f16.f16.f16 {qz0,qz1,qz2,qz3,qz4,qz5,qz6,qz7,qz8,qz9,qz10,qz11,qz12,qz13,qz14,qz15}, {qa0,qa1,qa2,qa3}, dt, pf, 1, 1, 1;\n"
        "add.s64 dt, w1d, 1664; wgmma.mma_async.sync.aligned.m64n64k16.f16.f16.f16 {qz0,qz1,qz2,qz3,qz4,qz5,qz6,qz7,qz8,qz9,qz10,qz11,qz12,qz13,qz14,qz15}, {qa4,qa5,qa6,qa7}, dt, pt, 1, 1, 1;\n"
        "add.s64 dt, w1d, 1792; wgmma.mma_async.sync.aligned.m64n64k16.f16.f16.f16 {qz0,qz1,qz2,qz3,qz4,qz5,qz6,qz7,qz8,qz9,qz10,qz11,qz12,qz13,qz14,qz15}, {qa8,qa9,qa10,qa11}, dt, pt, 1, 1, 1;\n"
        "wgmma.commit_group.sync.aligned;\n"
        "@pl bra.uni YLOAD;\n"
        "YLOADB:\n"
        "@pz bra.uni B22;\n"
        "mov.b32 {xl, xh}, a2; tanh.approx.f16 xr, xl; cvt.u32.u16 lo0, xr; tanh.approx.f16 xr, xh; cvt.u32.u16 hi0, xr; mul.rn.f16x2 a3, qz19, p1; fma.rn.f16x2 p0, qz20, qz20, c; fma.rn.f16x2 g0, qz16, h0, qz16; prmt.b32 h1, lo1, hi1, 0x5410;\n"
        "mov.b32 {xl, xh}, a3; tanh.approx.f16 xr, xl; cvt.u32.u16 lo1, xr; tanh.approx.f16 xr, xh; cvt.u32.u16 hi1, xr; mul.rn.f16x2 a0, qz20, p0; fma.rn.f16x2 p1, qz21, qz21, c; fma.rn.f16x2 g1, qz17, h1, qz17; prmt.b32 h0, lo0, hi0, 0x5410;\n"
        "mov.b32 {xl, xh}, a0; tanh.approx.f16 xr, xl; cvt.u32.u16 lo0, xr; tanh.approx.f16 xr, xh; cvt.u32.u16 hi0, xr; mul.rn.f16x2 a1, qz21, p1; fma.rn.f16x2 p0, qz22, qz22, c; fma.rn.f16x2 g2, qz18, h0, qz18; prmt.b32 h1, lo1, hi1, 0x5410;\n"
        "mov.b32 {xl, xh}, a1; tanh.approx.f16 xr, xl; cvt.u32.u16 lo1, xr; tanh.approx.f16 xr, xh; cvt.u32.u16 hi1, xr; mul.rn.f16x2 a2, qz22, p0; fma.rn.f16x2 p1, qz23, qz23, c; fma.rn.f16x2 g3, qz19, h1, qz19; prmt.b32 h0, lo0, hi0, 0x5410;\n"
        "B22:\n"
        "wgmma.fence.sync.aligned;\n"
        "add.s64 dt, w1d, 1920; wgmma.mma_async.sync.aligned.m64n64k16.f16.f16.f16 {qz0,qz1,qz2,qz3,qz4,qz5,qz6,qz7,qz8,qz9,qz10,qz11,qz12,qz13,qz14,qz15}, {qa12,qa13,qa14,qa15}, dt, pt, 1, 1, 1;\n"
        "add.s64 dt, w1d, 2048; wgmma.mma_async.sync.aligned.m64n64k16.f16.f16.f16 {qz0,qz1,qz2,qz3,qz4,qz5,qz6,qz7,qz8,qz9,qz10,qz11,qz12,qz13,qz14,qz15}, {qa16,qa17,qa18,qa19}, dt, pt, 1, 1, 1;\n"
        "add.s64 dt, w1d, 2176; wgmma.mma_async.sync.aligned.m64n64k16.f16.f16.f16 {qz0,qz1,qz2,qz3,qz4,qz5,qz6,qz7,qz8,qz9,qz10,qz11,qz12,qz13,qz14,qz15}, {qa20,qa21,qa22,qa23}, dt, pt, 1, 1, 1;\n"
        "wgmma.commit_group.sync.aligned;\n"
        "@pz bra.uni B26;\n"
        "mov.b32 {xl, xh}, a2; tanh.approx.f16 xr, xl; cvt.u32.u16 lo0, xr; tanh.approx.f16 xr, xh; cvt.u32.u16 hi0, xr; mul.rn.f16x2 a3, qz23, p1; fma.rn.f16x2 p0, qz24, qz24, c; fma.rn.f16x2 g4, qz20, h0, qz20; prmt.b32 h1, lo1, hi1, 0x5410;\n"
        "mov.b32 {xl, xh}, a3; tanh.approx.f16 xr, xl; cvt.u32.u16 lo1, xr; tanh.approx.f16 xr, xh; cvt.u32.u16 hi1, xr; mul.rn.f16x2 a0, qz24, p0; fma.rn.f16x2 p1, qz25, qz25, c; fma.rn.f16x2 g5, qz21, h1, qz21; prmt.b32 h0, lo0, hi0, 0x5410;\n"
        "mov.b32 {xl, xh}, a0; tanh.approx.f16 xr, xl; cvt.u32.u16 lo0, xr; tanh.approx.f16 xr, xh; cvt.u32.u16 hi0, xr; mul.rn.f16x2 a1, qz25, p1; fma.rn.f16x2 p0, qz26, qz26, c; fma.rn.f16x2 g6, qz22, h0, qz22; prmt.b32 h1, lo1, hi1, 0x5410;\n"
        "mov.b32 {xl, xh}, a1; tanh.approx.f16 xr, xl; cvt.u32.u16 lo1, xr; tanh.approx.f16 xr, xh; cvt.u32.u16 hi1, xr; mul.rn.f16x2 a2, qz26, p0; fma.rn.f16x2 p1, qz27, qz27, c; fma.rn.f16x2 g7, qz23, h1, qz23; prmt.b32 h0, lo0, hi0, 0x5410;\n"
        "B26:\n"
        "wgmma.wait_group.sync.aligned 2;\n"
        "wgmma.fence.sync.aligned;\n"
        "add.s64 dt, w2d, 256; wgmma.mma_async.sync.aligned.m64n96k16.f16.f16.f16 {o0,o1,o2,o3,o4,o5,o6,o7,o8,o9,o10,o11,o12,o13,o14,o15,o16,o17,o18,o19,o20,o21,o22,o23}, {g0,g1,g2,g3}, dt, pt, 1, 1, 1;\n"
        "add.s64 dt, w2d, 320; wgmma.mma_async.sync.aligned.m64n96k16.f16.f16.f16 {o0,o1,o2,o3,o4,o5,o6,o7,o8,o9,o10,o11,o12,o13,o14,o15,o16,o17,o18,o19,o20,o21,o22,o23}, {g4,g5,g6,g7}, dt, pt, 1, 1, 1;\n"
        "wgmma.commit_group.sync.aligned;\n"
        "@pz bra.uni B30;\n"
        "mov.b32 {xl, xh}, a2; tanh.approx.f16 xr, xl; cvt.u32.u16 lo0, xr; tanh.approx.f16 xr, xh; cvt.u32.u16 hi0, xr; mul.rn.f16x2 a3, qz27, p1; fma.rn.f16x2 p0, qz28, qz28, c; fma.rn.f16x2 g8, qz24, h0, qz24; prmt.b32 h1, lo1, hi1, 0x5410;\n"
        "mov.b32 {xl, xh}, a3; tanh.approx.f16 xr, xl; cvt.u32.u16 lo1, xr; tanh.approx.f16 xr, xh; cvt.u32.u16 hi1, xr; mul.rn.f16x2 a0, qz28, p0; fma.rn.f16x2 p1, qz29, qz29, c; fma.rn.f16x2 g9, qz25, h1, qz25; prmt.b32 h0, lo0, hi0, 0x5410;\n"
        "mov.b32 {xl, xh}, a0; tanh.approx.f16 xr, xl; cvt.u32.u16 lo0, xr; tanh.approx.f16 xr, xh; cvt.u32.u16 hi0, xr; mul.rn.f16x2 a1, qz29, p1; fma.rn.f16x2 p0, qz30, qz30, c; fma.rn.f16x2 g10, qz26, h0, qz26; prmt.b32 h1, lo1, hi1, 0x5410;\n"
        "mov.b32 {xl, xh}, a1; tanh.approx.f16 xr, xl; cvt.u32.u16 lo1, xr; tanh.approx.f16 xr, xh; cvt.u32.u16 hi1, xr; mul.rn.f16x2 a2, qz30, p0; fma.rn.f16x2 p1, qz31, qz31, c; fma.rn.f16x2 g11, qz27, h1, qz27; prmt.b32 h0, lo0, hi0, 0x5410;\n"
        "B30:\n"
        "wgmma.wait_group.sync.aligned 1;\n"
        "wgmma.fence.sync.aligned;\n"
        "add.s64 dt, w2d, 384; wgmma.mma_async.sync.aligned.m64n96k16.f16.f16.f16 {o0,o1,o2,o3,o4,o5,o6,o7,o8,o9,o10,o11,o12,o13,o14,o15,o16,o17,o18,o19,o20,o21,o22,o23}, {g8,g9,g10,g11}, dt, pt, 1, 1, 1;\n"
        "wgmma.commit_group.sync.aligned;\n"
        "@pz bra.uni B34;\n"
        "mov.b32 {xl, xh}, a2; tanh.approx.f16 xr, xl; cvt.u32.u16 lo0, xr; tanh.approx.f16 xr, xh; cvt.u32.u16 hi0, xr; mul.rn.f16x2 a3, qz31, p1; fma.rn.f16x2 p0, qz0, qz0, c; fma.rn.f16x2 g12, qz28, h0, qz28; prmt.b32 h1, lo1, hi1, 0x5410;\n"
        "mov.b32 {xl, xh}, a3; tanh.approx.f16 xr, xl; cvt.u32.u16 lo1, xr; tanh.approx.f16 xr, xh; cvt.u32.u16 hi1, xr; mul.rn.f16x2 a0, qz0, p0; fma.rn.f16x2 p1, qz1, qz1, c; fma.rn.f16x2 g13, qz29, h1, qz29; prmt.b32 h0, lo0, hi0, 0x5410;\n"
        "mov.b32 {xl, xh}, a0; tanh.approx.f16 xr, xl; cvt.u32.u16 lo0, xr; tanh.approx.f16 xr, xh; cvt.u32.u16 hi0, xr; mul.rn.f16x2 a1, qz1, p1; fma.rn.f16x2 p0, qz2, qz2, c; fma.rn.f16x2 g14, qz30, h0, qz30; prmt.b32 h1, lo1, hi1, 0x5410;\n"
        "mov.b32 {xl, xh}, a1; tanh.approx.f16 xr, xl; cvt.u32.u16 lo1, xr; tanh.approx.f16 xr, xh; cvt.u32.u16 hi1, xr; mul.rn.f16x2 a2, qz2, p0; fma.rn.f16x2 p1, qz3, qz3, c; fma.rn.f16x2 g15, qz31, h1, qz31; prmt.b32 h0, lo0, hi0, 0x5410;\n"
        "B34:\n"
        "wgmma.wait_group.sync.aligned 1;\n"
        "wgmma.fence.sync.aligned;\n"
        "add.s64 dt, w2d, 448; wgmma.mma_async.sync.aligned.m64n96k16.f16.f16.f16 {o0,o1,o2,o3,o4,o5,o6,o7,o8,o9,o10,o11,o12,o13,o14,o15,o16,o17,o18,o19,o20,o21,o22,o23}, {g12,g13,g14,g15}, dt, pt, 1, 1, 1;\n"
        "add.s64 dt, w1d, 2304; wgmma.mma_async.sync.aligned.m64n64k16.f16.f16.f16 {qz16,qz17,qz18,qz19,qz20,qz21,qz22,qz23,qz24,qz25,qz26,qz27,qz28,qz29,qz30,qz31}, {qa0,qa1,qa2,qa3}, dt, pf, 1, 1, 1;\n"
        "add.s64 dt, w1d, 2432; wgmma.mma_async.sync.aligned.m64n64k16.f16.f16.f16 {qz16,qz17,qz18,qz19,qz20,qz21,qz22,qz23,qz24,qz25,qz26,qz27,qz28,qz29,qz30,qz31}, {qa4,qa5,qa6,qa7}, dt, pt, 1, 1, 1;\n"
        "add.s64 dt, w1d, 2560; wgmma.mma_async.sync.aligned.m64n64k16.f16.f16.f16 {qz16,qz17,qz18,qz19,qz20,qz21,qz22,qz23,qz24,qz25,qz26,qz27,qz28,qz29,qz30,qz31}, {qa8,qa9,qa10,qa11}, dt, pt, 1, 1, 1;\n"
        "wgmma.commit_group.sync.aligned;\n"
        "@pz bra.uni B38;\n"
        "mov.b32 {xl, xh}, a2; tanh.approx.f16 xr, xl; cvt.u32.u16 lo0, xr; tanh.approx.f16 xr, xh; cvt.u32.u16 hi0, xr; mul.rn.f16x2 a3, qz3, p1; fma.rn.f16x2 p0, qz4, qz4, c; fma.rn.f16x2 g0, qz0, h0, qz0; prmt.b32 h1, lo1, hi1, 0x5410;\n"
        "mov.b32 {xl, xh}, a3; tanh.approx.f16 xr, xl; cvt.u32.u16 lo1, xr; tanh.approx.f16 xr, xh; cvt.u32.u16 hi1, xr; mul.rn.f16x2 a0, qz4, p0; fma.rn.f16x2 p1, qz5, qz5, c; fma.rn.f16x2 g1, qz1, h1, qz1; prmt.b32 h0, lo0, hi0, 0x5410;\n"
        "mov.b32 {xl, xh}, a0; tanh.approx.f16 xr, xl; cvt.u32.u16 lo0, xr; tanh.approx.f16 xr, xh; cvt.u32.u16 hi0, xr; mul.rn.f16x2 a1, qz5, p1; fma.rn.f16x2 p0, qz6, qz6, c; fma.rn.f16x2 g2, qz2, h0, qz2; prmt.b32 h1, lo1, hi1, 0x5410;\n"
        "mov.b32 {xl, xh}, a1; tanh.approx.f16 xr, xl; cvt.u32.u16 lo1, xr; tanh.approx.f16 xr, xh; cvt.u32.u16 hi1, xr; mul.rn.f16x2 a2, qz6, p0; fma.rn.f16x2 p1, qz7, qz7, c; fma.rn.f16x2 g3, qz3, h1, qz3; prmt.b32 h0, lo0, hi0, 0x5410;\n"
        "B38:\n"
        "wgmma.fence.sync.aligned;\n"
        "add.s64 dt, w1d, 2688; wgmma.mma_async.sync.aligned.m64n64k16.f16.f16.f16 {qz16,qz17,qz18,qz19,qz20,qz21,qz22,qz23,qz24,qz25,qz26,qz27,qz28,qz29,qz30,qz31}, {qa12,qa13,qa14,qa15}, dt, pt, 1, 1, 1;\n"
        "add.s64 dt, w1d, 2816; wgmma.mma_async.sync.aligned.m64n64k16.f16.f16.f16 {qz16,qz17,qz18,qz19,qz20,qz21,qz22,qz23,qz24,qz25,qz26,qz27,qz28,qz29,qz30,qz31}, {qa16,qa17,qa18,qa19}, dt, pt, 1, 1, 1;\n"
        "add.s64 dt, w1d, 2944; wgmma.mma_async.sync.aligned.m64n64k16.f16.f16.f16 {qz16,qz17,qz18,qz19,qz20,qz21,qz22,qz23,qz24,qz25,qz26,qz27,qz28,qz29,qz30,qz31}, {qa20,qa21,qa22,qa23}, dt, pt, 1, 1, 1;\n"
        "wgmma.commit_group.sync.aligned;\n"
        "@pz bra.uni B42;\n"
        "mov.b32 {xl, xh}, a2; tanh.approx.f16 xr, xl; cvt.u32.u16 lo0, xr; tanh.approx.f16 xr, xh; cvt.u32.u16 hi0, xr; mul.rn.f16x2 a3, qz7, p1; fma.rn.f16x2 p0, qz8, qz8, c; fma.rn.f16x2 g4, qz4, h0, qz4; prmt.b32 h1, lo1, hi1, 0x5410;\n"
        "mov.b32 {xl, xh}, a3; tanh.approx.f16 xr, xl; cvt.u32.u16 lo1, xr; tanh.approx.f16 xr, xh; cvt.u32.u16 hi1, xr; mul.rn.f16x2 a0, qz8, p0; fma.rn.f16x2 p1, qz9, qz9, c; fma.rn.f16x2 g5, qz5, h1, qz5; prmt.b32 h0, lo0, hi0, 0x5410;\n"
        "mov.b32 {xl, xh}, a0; tanh.approx.f16 xr, xl; cvt.u32.u16 lo0, xr; tanh.approx.f16 xr, xh; cvt.u32.u16 hi0, xr; mul.rn.f16x2 a1, qz9, p1; fma.rn.f16x2 p0, qz10, qz10, c; fma.rn.f16x2 g6, qz6, h0, qz6; prmt.b32 h1, lo1, hi1, 0x5410;\n"
        "mov.b32 {xl, xh}, a1; tanh.approx.f16 xr, xl; cvt.u32.u16 lo1, xr; tanh.approx.f16 xr, xh; cvt.u32.u16 hi1, xr; mul.rn.f16x2 a2, qz10, p0; fma.rn.f16x2 p1, qz11, qz11, c; fma.rn.f16x2 g7, qz7, h1, qz7; prmt.b32 h0, lo0, hi0, 0x5410;\n"
        "B42:\n"
        "wgmma.wait_group.sync.aligned 2;\n"
        "setp.eq.s32 pr, n, 0;\n"
        "@pr bra.uni SPINW1;\n"
        "BACKW1:\n"
        "wgmma.fence.sync.aligned;\n"
        "add.s64 dt, w2d, 512; wgmma.mma_async.sync.aligned.m64n96k16.f16.f16.f16 {o0,o1,o2,o3,o4,o5,o6,o7,o8,o9,o10,o11,o12,o13,o14,o15,o16,o17,o18,o19,o20,o21,o22,o23}, {g0,g1,g2,g3}, dt, pt, 1, 1, 1;\n"
        "add.s64 dt, w2d, 576; wgmma.mma_async.sync.aligned.m64n96k16.f16.f16.f16 {o0,o1,o2,o3,o4,o5,o6,o7,o8,o9,o10,o11,o12,o13,o14,o15,o16,o17,o18,o19,o20,o21,o22,o23}, {g4,g5,g6,g7}, dt, pt, 1, 1, 1;\n"
        "wgmma.commit_group.sync.aligned;\n"
        "@pz bra.uni B46;\n"
        "mov.b32 {xl, xh}, a2; tanh.approx.f16 xr, xl; cvt.u32.u16 lo0, xr; tanh.approx.f16 xr, xh; cvt.u32.u16 hi0, xr; mul.rn.f16x2 a3, qz11, p1; fma.rn.f16x2 p0, qz12, qz12, c; fma.rn.f16x2 g8, qz8, h0, qz8; prmt.b32 h1, lo1, hi1, 0x5410;\n"
        "mov.b32 {xl, xh}, a3; tanh.approx.f16 xr, xl; cvt.u32.u16 lo1, xr; tanh.approx.f16 xr, xh; cvt.u32.u16 hi1, xr; mul.rn.f16x2 a0, qz12, p0; fma.rn.f16x2 p1, qz13, qz13, c; fma.rn.f16x2 g9, qz9, h1, qz9; prmt.b32 h0, lo0, hi0, 0x5410;\n"
        "mov.b32 {xl, xh}, a0; tanh.approx.f16 xr, xl; cvt.u32.u16 lo0, xr; tanh.approx.f16 xr, xh; cvt.u32.u16 hi0, xr; mul.rn.f16x2 a1, qz13, p1; fma.rn.f16x2 p0, qz14, qz14, c; fma.rn.f16x2 g10, qz10, h0, qz10; prmt.b32 h1, lo1, hi1, 0x5410;\n"
        "mov.b32 {xl, xh}, a1; tanh.approx.f16 xr, xl; cvt.u32.u16 lo1, xr; tanh.approx.f16 xr, xh; cvt.u32.u16 hi1, xr; mul.rn.f16x2 a2, qz14, p0; fma.rn.f16x2 p1, qz15, qz15, c; fma.rn.f16x2 g11, qz11, h1, qz11; prmt.b32 h0, lo0, hi0, 0x5410;\n"
        "B46:\n"
        "wgmma.wait_group.sync.aligned 1;\n"
        "wgmma.fence.sync.aligned;\n"
        "add.s64 dt, w2d, 640; wgmma.mma_async.sync.aligned.m64n96k16.f16.f16.f16 {o0,o1,o2,o3,o4,o5,o6,o7,o8,o9,o10,o11,o12,o13,o14,o15,o16,o17,o18,o19,o20,o21,o22,o23}, {g8,g9,g10,g11}, dt, pt, 1, 1, 1;\n"
        "wgmma.commit_group.sync.aligned;\n"
        "mad.lo.u32 tt, n, 8, tbar;\n"
        "@pn mbarrier.arrive.shared::cta.b64 _, [tt+64];\n"
        "@pz bra.uni B50;\n"
        "mov.b32 {xl, xh}, a2; tanh.approx.f16 xr, xl; cvt.u32.u16 lo0, xr; tanh.approx.f16 xr, xh; cvt.u32.u16 hi0, xr; mul.rn.f16x2 a3, qz15, p1; fma.rn.f16x2 p0, qz16, qz16, c; fma.rn.f16x2 g12, qz12, h0, qz12; prmt.b32 h1, lo1, hi1, 0x5410;\n"
        "mov.b32 {xl, xh}, a3; tanh.approx.f16 xr, xl; cvt.u32.u16 lo1, xr; tanh.approx.f16 xr, xh; cvt.u32.u16 hi1, xr; mul.rn.f16x2 a0, qz16, p0; fma.rn.f16x2 p1, qz17, qz17, c; fma.rn.f16x2 g13, qz13, h1, qz13; prmt.b32 h0, lo0, hi0, 0x5410;\n"
        "mov.b32 {xl, xh}, a0; tanh.approx.f16 xr, xl; cvt.u32.u16 lo0, xr; tanh.approx.f16 xr, xh; cvt.u32.u16 hi0, xr; mul.rn.f16x2 a1, qz17, p1; fma.rn.f16x2 p0, qz18, qz18, c; fma.rn.f16x2 g14, qz14, h0, qz14; prmt.b32 h1, lo1, hi1, 0x5410;\n"
        "mov.b32 {xl, xh}, a1; tanh.approx.f16 xr, xl; cvt.u32.u16 lo1, xr; tanh.approx.f16 xr, xh; cvt.u32.u16 hi1, xr; mul.rn.f16x2 a2, qz18, p0; fma.rn.f16x2 p1, qz19, qz19, c; fma.rn.f16x2 g15, qz15, h1, qz15; prmt.b32 h0, lo0, hi0, 0x5410;\n"
        "B50:\n"
        "wgmma.wait_group.sync.aligned 1;\n"
        "wgmma.fence.sync.aligned;\n"
        "add.s64 dt, w2d, 704; wgmma.mma_async.sync.aligned.m64n96k16.f16.f16.f16 {o0,o1,o2,o3,o4,o5,o6,o7,o8,o9,o10,o11,o12,o13,o14,o15,o16,o17,o18,o19,o20,o21,o22,o23}, {g12,g13,g14,g15}, dt, pt, 1, 1, 1;\n"
        "add.s64 dt, w1d, 3072; wgmma.mma_async.sync.aligned.m64n64k16.f16.f16.f16 {qz0,qz1,qz2,qz3,qz4,qz5,qz6,qz7,qz8,qz9,qz10,qz11,qz12,qz13,qz14,qz15}, {qa0,qa1,qa2,qa3}, dt, pf, 1, 1, 1;\n"
        "add.s64 dt, w1d, 3200; wgmma.mma_async.sync.aligned.m64n64k16.f16.f16.f16 {qz0,qz1,qz2,qz3,qz4,qz5,qz6,qz7,qz8,qz9,qz10,qz11,qz12,qz13,qz14,qz15}, {qa4,qa5,qa6,qa7}, dt, pt, 1, 1, 1;\n"
        "add.s64 dt, w1d, 3328; wgmma.mma_async.sync.aligned.m64n64k16.f16.f16.f16 {qz0,qz1,qz2,qz3,qz4,qz5,qz6,qz7,qz8,qz9,qz10,qz11,qz12,qz13,qz14,qz15}, {qa8,qa9,qa10,qa11}, dt, pt, 1, 1, 1;\n"
        "wgmma.commit_group.sync.aligned;\n"
        "@pz bra.uni B54;\n"
        "mov.b32 {xl, xh}, a2; tanh.approx.f16 xr, xl; cvt.u32.u16 lo0, xr; tanh.approx.f16 xr, xh; cvt.u32.u16 hi0, xr; mul.rn.f16x2 a3, qz19, p1; fma.rn.f16x2 p0, qz20, qz20, c; fma.rn.f16x2 g0, qz16, h0, qz16; prmt.b32 h1, lo1, hi1, 0x5410;\n"
        "mov.b32 {xl, xh}, a3; tanh.approx.f16 xr, xl; cvt.u32.u16 lo1, xr; tanh.approx.f16 xr, xh; cvt.u32.u16 hi1, xr; mul.rn.f16x2 a0, qz20, p0; fma.rn.f16x2 p1, qz21, qz21, c; fma.rn.f16x2 g1, qz17, h1, qz17; prmt.b32 h0, lo0, hi0, 0x5410;\n"
        "mov.b32 {xl, xh}, a0; tanh.approx.f16 xr, xl; cvt.u32.u16 lo0, xr; tanh.approx.f16 xr, xh; cvt.u32.u16 hi0, xr; mul.rn.f16x2 a1, qz21, p1; fma.rn.f16x2 p0, qz22, qz22, c; fma.rn.f16x2 g2, qz18, h0, qz18; prmt.b32 h1, lo1, hi1, 0x5410;\n"
        "mov.b32 {xl, xh}, a1; tanh.approx.f16 xr, xl; cvt.u32.u16 lo1, xr; tanh.approx.f16 xr, xh; cvt.u32.u16 hi1, xr; mul.rn.f16x2 a2, qz22, p0; fma.rn.f16x2 p1, qz23, qz23, c; fma.rn.f16x2 g3, qz19, h1, qz19; prmt.b32 h0, lo0, hi0, 0x5410;\n"
        "B54:\n"
        "wgmma.fence.sync.aligned;\n"
        "add.s64 dt, w1d, 3456; wgmma.mma_async.sync.aligned.m64n64k16.f16.f16.f16 {qz0,qz1,qz2,qz3,qz4,qz5,qz6,qz7,qz8,qz9,qz10,qz11,qz12,qz13,qz14,qz15}, {qa12,qa13,qa14,qa15}, dt, pt, 1, 1, 1;\n"
        "add.s64 dt, w1d, 3584; wgmma.mma_async.sync.aligned.m64n64k16.f16.f16.f16 {qz0,qz1,qz2,qz3,qz4,qz5,qz6,qz7,qz8,qz9,qz10,qz11,qz12,qz13,qz14,qz15}, {qa16,qa17,qa18,qa19}, dt, pt, 1, 1, 1;\n"
        "add.s64 dt, w1d, 3712; wgmma.mma_async.sync.aligned.m64n64k16.f16.f16.f16 {qz0,qz1,qz2,qz3,qz4,qz5,qz6,qz7,qz8,qz9,qz10,qz11,qz12,qz13,qz14,qz15}, {qa20,qa21,qa22,qa23}, dt, pt, 1, 1, 1;\n"
        "wgmma.commit_group.sync.aligned;\n"
        "@pz bra.uni B58;\n"
        "mov.b32 {xl, xh}, a2; tanh.approx.f16 xr, xl; cvt.u32.u16 lo0, xr; tanh.approx.f16 xr, xh; cvt.u32.u16 hi0, xr; mul.rn.f16x2 a3, qz23, p1; fma.rn.f16x2 p0, qz24, qz24, c; fma.rn.f16x2 g4, qz20, h0, qz20; prmt.b32 h1, lo1, hi1, 0x5410;\n"
        "mov.b32 {xl, xh}, a3; tanh.approx.f16 xr, xl; cvt.u32.u16 lo1, xr; tanh.approx.f16 xr, xh; cvt.u32.u16 hi1, xr; mul.rn.f16x2 a0, qz24, p0; fma.rn.f16x2 p1, qz25, qz25, c; fma.rn.f16x2 g5, qz21, h1, qz21; prmt.b32 h0, lo0, hi0, 0x5410;\n"
        "mov.b32 {xl, xh}, a0; tanh.approx.f16 xr, xl; cvt.u32.u16 lo0, xr; tanh.approx.f16 xr, xh; cvt.u32.u16 hi0, xr; mul.rn.f16x2 a1, qz25, p1; fma.rn.f16x2 p0, qz26, qz26, c; fma.rn.f16x2 g6, qz22, h0, qz22; prmt.b32 h1, lo1, hi1, 0x5410;\n"
        "mov.b32 {xl, xh}, a1; tanh.approx.f16 xr, xl; cvt.u32.u16 lo1, xr; tanh.approx.f16 xr, xh; cvt.u32.u16 hi1, xr; mul.rn.f16x2 a2, qz26, p0; fma.rn.f16x2 p1, qz27, qz27, c; fma.rn.f16x2 g7, qz23, h1, qz23; prmt.b32 h0, lo0, hi0, 0x5410;\n"
        "B58:\n"
        "wgmma.wait_group.sync.aligned 2;\n"
        "wgmma.fence.sync.aligned;\n"
        "add.s64 dt, w2d, 768; wgmma.mma_async.sync.aligned.m64n96k16.f16.f16.f16 {o0,o1,o2,o3,o4,o5,o6,o7,o8,o9,o10,o11,o12,o13,o14,o15,o16,o17,o18,o19,o20,o21,o22,o23}, {g0,g1,g2,g3}, dt, pt, 1, 1, 1;\n"
        "add.s64 dt, w2d, 832; wgmma.mma_async.sync.aligned.m64n96k16.f16.f16.f16 {o0,o1,o2,o3,o4,o5,o6,o7,o8,o9,o10,o11,o12,o13,o14,o15,o16,o17,o18,o19,o20,o21,o22,o23}, {g4,g5,g6,g7}, dt, pt, 1, 1, 1;\n"
        "wgmma.commit_group.sync.aligned;\n"
        "@pz bra.uni B62;\n"
        "mov.b32 {xl, xh}, a2; tanh.approx.f16 xr, xl; cvt.u32.u16 lo0, xr; tanh.approx.f16 xr, xh; cvt.u32.u16 hi0, xr; mul.rn.f16x2 a3, qz27, p1; fma.rn.f16x2 p0, qz28, qz28, c; fma.rn.f16x2 g8, qz24, h0, qz24; prmt.b32 h1, lo1, hi1, 0x5410;\n"
        "mov.b32 {xl, xh}, a3; tanh.approx.f16 xr, xl; cvt.u32.u16 lo1, xr; tanh.approx.f16 xr, xh; cvt.u32.u16 hi1, xr; mul.rn.f16x2 a0, qz28, p0; fma.rn.f16x2 p1, qz29, qz29, c; fma.rn.f16x2 g9, qz25, h1, qz25; prmt.b32 h0, lo0, hi0, 0x5410;\n"
        "mov.b32 {xl, xh}, a0; tanh.approx.f16 xr, xl; cvt.u32.u16 lo0, xr; tanh.approx.f16 xr, xh; cvt.u32.u16 hi0, xr; mul.rn.f16x2 a1, qz29, p1; fma.rn.f16x2 p0, qz30, qz30, c; fma.rn.f16x2 g10, qz26, h0, qz26; prmt.b32 h1, lo1, hi1, 0x5410;\n"
        "mov.b32 {xl, xh}, a1; tanh.approx.f16 xr, xl; cvt.u32.u16 lo1, xr; tanh.approx.f16 xr, xh; cvt.u32.u16 hi1, xr; mul.rn.f16x2 a2, qz30, p0; fma.rn.f16x2 p1, qz31, qz31, c; fma.rn.f16x2 g11, qz27, h1, qz27; prmt.b32 h0, lo0, hi0, 0x5410;\n"
        "B62:\n"
        "wgmma.wait_group.sync.aligned 1;\n"
        "wgmma.fence.sync.aligned;\n"
        "add.s64 dt, w2d, 896; wgmma.mma_async.sync.aligned.m64n96k16.f16.f16.f16 {o0,o1,o2,o3,o4,o5,o6,o7,o8,o9,o10,o11,o12,o13,o14,o15,o16,o17,o18,o19,o20,o21,o22,o23}, {g8,g9,g10,g11}, dt, pt, 1, 1, 1;\n"
        "wgmma.commit_group.sync.aligned;\n"
        "@pz bra.uni B66;\n"
        "mov.b32 {xl, xh}, a2; tanh.approx.f16 xr, xl; cvt.u32.u16 lo0, xr; tanh.approx.f16 xr, xh; cvt.u32.u16 hi0, xr; mul.rn.f16x2 a3, qz31, p1; fma.rn.f16x2 p0, qz0, qz0, c; fma.rn.f16x2 g12, qz28, h0, qz28; prmt.b32 h1, lo1, hi1, 0x5410;\n"
        "mov.b32 {xl, xh}, a3; tanh.approx.f16 xr, xl; cvt.u32.u16 lo1, xr; tanh.approx.f16 xr, xh; cvt.u32.u16 hi1, xr; mul.rn.f16x2 a0, qz0, p0; fma.rn.f16x2 p1, qz1, qz1, c; fma.rn.f16x2 g13, qz29, h1, qz29; prmt.b32 h0, lo0, hi0, 0x5410;\n"
        "mov.b32 {xl, xh}, a0; tanh.approx.f16 xr, xl; cvt.u32.u16 lo0, xr; tanh.approx.f16 xr, xh; cvt.u32.u16 hi0, xr; mul.rn.f16x2 a1, qz1, p1; fma.rn.f16x2 p0, qz2, qz2, c; fma.rn.f16x2 g14, qz30, h0, qz30; prmt.b32 h1, lo1, hi1, 0x5410;\n"
        "mov.b32 {xl, xh}, a1; tanh.approx.f16 xr, xl; cvt.u32.u16 lo1, xr; tanh.approx.f16 xr, xh; cvt.u32.u16 hi1, xr; mul.rn.f16x2 a2, qz2, p0; fma.rn.f16x2 p1, qz3, qz3, c; fma.rn.f16x2 g15, qz31, h1, qz31; prmt.b32 h0, lo0, hi0, 0x5410;\n"
        "B66:\n"
        "wgmma.wait_group.sync.aligned 1;\n"
        "wgmma.fence.sync.aligned;\n"
        "add.s64 dt, w2d, 960; wgmma.mma_async.sync.aligned.m64n96k16.f16.f16.f16 {o0,o1,o2,o3,o4,o5,o6,o7,o8,o9,o10,o11,o12,o13,o14,o15,o16,o17,o18,o19,o20,o21,o22,o23}, {g12,g13,g14,g15}, dt, pt, 1, 1, 1;\n"
        "add.s64 dt, w1d, 3840; wgmma.mma_async.sync.aligned.m64n64k16.f16.f16.f16 {qz16,qz17,qz18,qz19,qz20,qz21,qz22,qz23,qz24,qz25,qz26,qz27,qz28,qz29,qz30,qz31}, {qa0,qa1,qa2,qa3}, dt, pf, 1, 1, 1;\n"
        "add.s64 dt, w1d, 3968; wgmma.mma_async.sync.aligned.m64n64k16.f16.f16.f16 {qz16,qz17,qz18,qz19,qz20,qz21,qz22,qz23,qz24,qz25,qz26,qz27,qz28,qz29,qz30,qz31}, {qa4,qa5,qa6,qa7}, dt, pt, 1, 1, 1;\n"
        "add.s64 dt, w1d, 4096; wgmma.mma_async.sync.aligned.m64n64k16.f16.f16.f16 {qz16,qz17,qz18,qz19,qz20,qz21,qz22,qz23,qz24,qz25,qz26,qz27,qz28,qz29,qz30,qz31}, {qa8,qa9,qa10,qa11}, dt, pt, 1, 1, 1;\n"
        "wgmma.commit_group.sync.aligned;\n"
        "@pz bra.uni B70;\n"
        "mov.b32 {xl, xh}, a2; tanh.approx.f16 xr, xl; cvt.u32.u16 lo0, xr; tanh.approx.f16 xr, xh; cvt.u32.u16 hi0, xr; mul.rn.f16x2 a3, qz3, p1; fma.rn.f16x2 p0, qz4, qz4, c; fma.rn.f16x2 g0, qz0, h0, qz0; prmt.b32 h1, lo1, hi1, 0x5410;\n"
        "mov.b32 {xl, xh}, a3; tanh.approx.f16 xr, xl; cvt.u32.u16 lo1, xr; tanh.approx.f16 xr, xh; cvt.u32.u16 hi1, xr; mul.rn.f16x2 a0, qz4, p0; fma.rn.f16x2 p1, qz5, qz5, c; fma.rn.f16x2 g1, qz1, h1, qz1; prmt.b32 h0, lo0, hi0, 0x5410;\n"
        "mov.b32 {xl, xh}, a0; tanh.approx.f16 xr, xl; cvt.u32.u16 lo0, xr; tanh.approx.f16 xr, xh; cvt.u32.u16 hi0, xr; mul.rn.f16x2 a1, qz5, p1; fma.rn.f16x2 p0, qz6, qz6, c; fma.rn.f16x2 g2, qz2, h0, qz2; prmt.b32 h1, lo1, hi1, 0x5410;\n"
        "mov.b32 {xl, xh}, a1; tanh.approx.f16 xr, xl; cvt.u32.u16 lo1, xr; tanh.approx.f16 xr, xh; cvt.u32.u16 hi1, xr; mul.rn.f16x2 a2, qz6, p0; fma.rn.f16x2 p1, qz7, qz7, c; fma.rn.f16x2 g3, qz3, h1, qz3; prmt.b32 h0, lo0, hi0, 0x5410;\n"
        "B70:\n"
        "wgmma.fence.sync.aligned;\n"
        "add.s64 dt, w1d, 4224; wgmma.mma_async.sync.aligned.m64n64k16.f16.f16.f16 {qz16,qz17,qz18,qz19,qz20,qz21,qz22,qz23,qz24,qz25,qz26,qz27,qz28,qz29,qz30,qz31}, {qa12,qa13,qa14,qa15}, dt, pt, 1, 1, 1;\n"
        "add.s64 dt, w1d, 4352; wgmma.mma_async.sync.aligned.m64n64k16.f16.f16.f16 {qz16,qz17,qz18,qz19,qz20,qz21,qz22,qz23,qz24,qz25,qz26,qz27,qz28,qz29,qz30,qz31}, {qa16,qa17,qa18,qa19}, dt, pt, 1, 1, 1;\n"
        "add.s64 dt, w1d, 4480; wgmma.mma_async.sync.aligned.m64n64k16.f16.f16.f16 {qz16,qz17,qz18,qz19,qz20,qz21,qz22,qz23,qz24,qz25,qz26,qz27,qz28,qz29,qz30,qz31}, {qa20,qa21,qa22,qa23}, dt, pt, 1, 1, 1;\n"
        "wgmma.commit_group.sync.aligned;\n"
        "@pz bra.uni B74;\n"
        "mov.b32 {xl, xh}, a2; tanh.approx.f16 xr, xl; cvt.u32.u16 lo0, xr; tanh.approx.f16 xr, xh; cvt.u32.u16 hi0, xr; mul.rn.f16x2 a3, qz7, p1; fma.rn.f16x2 p0, qz8, qz8, c; fma.rn.f16x2 g4, qz4, h0, qz4; prmt.b32 h1, lo1, hi1, 0x5410;\n"
        "mov.b32 {xl, xh}, a3; tanh.approx.f16 xr, xl; cvt.u32.u16 lo1, xr; tanh.approx.f16 xr, xh; cvt.u32.u16 hi1, xr; mul.rn.f16x2 a0, qz8, p0; fma.rn.f16x2 p1, qz9, qz9, c; fma.rn.f16x2 g5, qz5, h1, qz5; prmt.b32 h0, lo0, hi0, 0x5410;\n"
        "mov.b32 {xl, xh}, a0; tanh.approx.f16 xr, xl; cvt.u32.u16 lo0, xr; tanh.approx.f16 xr, xh; cvt.u32.u16 hi0, xr; mul.rn.f16x2 a1, qz9, p1; fma.rn.f16x2 p0, qz10, qz10, c; fma.rn.f16x2 g6, qz6, h0, qz6; prmt.b32 h1, lo1, hi1, 0x5410;\n"
        "mov.b32 {xl, xh}, a1; tanh.approx.f16 xr, xl; cvt.u32.u16 lo1, xr; tanh.approx.f16 xr, xh; cvt.u32.u16 hi1, xr; mul.rn.f16x2 a2, qz10, p0; fma.rn.f16x2 p1, qz11, qz11, c; fma.rn.f16x2 g7, qz7, h1, qz7; prmt.b32 h0, lo0, hi0, 0x5410;\n"
        "B74:\n"
        "wgmma.wait_group.sync.aligned 2;\n"
        "wgmma.fence.sync.aligned;\n"
        "add.s64 dt, w2d, 1024; wgmma.mma_async.sync.aligned.m64n96k16.f16.f16.f16 {o0,o1,o2,o3,o4,o5,o6,o7,o8,o9,o10,o11,o12,o13,o14,o15,o16,o17,o18,o19,o20,o21,o22,o23}, {g0,g1,g2,g3}, dt, pt, 1, 1, 1;\n"
        "add.s64 dt, w2d, 1088; wgmma.mma_async.sync.aligned.m64n96k16.f16.f16.f16 {o0,o1,o2,o3,o4,o5,o6,o7,o8,o9,o10,o11,o12,o13,o14,o15,o16,o17,o18,o19,o20,o21,o22,o23}, {g4,g5,g6,g7}, dt, pt, 1, 1, 1;\n"
        "wgmma.commit_group.sync.aligned;\n"
        "@pz bra.uni B78;\n"
        "mov.b32 {xl, xh}, a2; tanh.approx.f16 xr, xl; cvt.u32.u16 lo0, xr; tanh.approx.f16 xr, xh; cvt.u32.u16 hi0, xr; mul.rn.f16x2 a3, qz11, p1; fma.rn.f16x2 p0, qz12, qz12, c; fma.rn.f16x2 g8, qz8, h0, qz8; prmt.b32 h1, lo1, hi1, 0x5410;\n"
        "mov.b32 {xl, xh}, a3; tanh.approx.f16 xr, xl; cvt.u32.u16 lo1, xr; tanh.approx.f16 xr, xh; cvt.u32.u16 hi1, xr; mul.rn.f16x2 a0, qz12, p0; fma.rn.f16x2 p1, qz13, qz13, c; fma.rn.f16x2 g9, qz9, h1, qz9; prmt.b32 h0, lo0, hi0, 0x5410;\n"
        "mov.b32 {xl, xh}, a0; tanh.approx.f16 xr, xl; cvt.u32.u16 lo0, xr; tanh.approx.f16 xr, xh; cvt.u32.u16 hi0, xr; mul.rn.f16x2 a1, qz13, p1; fma.rn.f16x2 p0, qz14, qz14, c; fma.rn.f16x2 g10, qz10, h0, qz10; prmt.b32 h1, lo1, hi1, 0x5410;\n"
        "mov.b32 {xl, xh}, a1; tanh.approx.f16 xr, xl; cvt.u32.u16 lo1, xr; tanh.approx.f16 xr, xh; cvt.u32.u16 hi1, xr; mul.rn.f16x2 a2, qz14, p0; fma.rn.f16x2 p1, qz15, qz15, c; fma.rn.f16x2 g11, qz11, h1, qz11; prmt.b32 h0, lo0, hi0, 0x5410;\n"
        "B78:\n"
        "wgmma.wait_group.sync.aligned 1;\n"
        "@!pm bra.uni BACKY;\n"
        "add.u32 tt, n, 1; and.b32 tt, tt, 1; mbarrier.try_wait.parity.shared::cta.b64 pw, [ybar], tt;\n"
        "@!pw bra.uni SPINY;\n"
        "BACKY:\n"
        "@pz bra.uni B80;\n"
        "and.b32 ad, %5, 0xffff; xor.b32 ad, ad, 0; add.u32 ad, ad, %4; ldmatrix.sync.aligned.m8n8.x4.shared.b16 {qa0,qa1,qa2,qa3}, [ad];\n"
        "and.b32 ad, %5, 0xffff; xor.b32 ad, ad, 32; add.u32 ad, ad, %4; ldmatrix.sync.aligned.m8n8.x4.shared.b16 {qa4,qa5,qa6,qa7}, [ad];\n"
        "and.b32 ad, %5, 0xffff; xor.b32 ad, ad, 64; add.u32 ad, ad, %4; ldmatrix.sync.aligned.m8n8.x4.shared.b16 {qa8,qa9,qa10,qa11}, [ad];\n"
        "and.b32 ad, %5, 0xffff; xor.b32 ad, ad, 96; add.u32 ad, ad, %4; ldmatrix.sync.aligned.m8n8.x4.shared.b16 {qa12,qa13,qa14,qa15}, [ad];\n"
        "shr.u32 ad, %5, 16; xor.b32 ad, ad, 0; add.u32 ad, ad, %4; ldmatrix.sync.aligned.m8n8.x4.shared.b16 {qa16,qa17,qa18,qa19}, [ad];\n"
        "shr.u32 ad, %5, 16; xor.b32 ad, ad, 32; add.u32 ad, ad, %4; ldmatrix.sync.aligned.m8n8.x4.shared.b16 {qa20,qa21,qa22,qa23}, [ad];\n"
        "mov.b32 {xl, xh}, a2; tanh.approx.f16 xr, xl; cvt.u32.u16 lo0, xr; tanh.approx.f16 xr, xh; cvt.u32.u16 hi0, xr; mul.rn.f16x2 a3, qz15, p1; fma.rn.f16x2 p0, qz16, qz16, c; fma.rn.f16x2 g12, qz12, h0, qz12; prmt.b32 h1, lo1, hi1, 0x5410;\n"
        "mov.b32 {xl, xh}, a3; tanh.approx.f16 xr, xl; cvt.u32.u16 lo1, xr; tanh.approx.f16 xr, xh; cvt.u32.u16 hi1, xr; mul.rn.f16x2 a0, qz16, p0; fma.rn.f16x2 p1, qz17, qz17, c; fma.rn.f16x2 g13, qz13, h1, qz13; prmt.b32 h0, lo0, hi0, 0x5410;\n"
        "B80:\n"
        "fence.proxy.async.shared::cta;\n"
        "add.u32 tt, id, 0;\n"
        "@pk bra.uni XLOAD;\n"
        "bar.arrive tt, 128;\n"
        "XLOADB:\n"
        "wgmma.fence.sync.aligned;\n"
        "add.s64 dt, w2d, 1152; wgmma.mma_async.sync.aligned.m64n96k16.f16.f16.f16 {o0,o1,o2,o3,o4,o5,o6,o7,o8,o9,o10,o11,o12,o13,o14,o15,o16,o17,o18,o19,o20,o21,o22,o23}, {g8,g9,g10,g11}, dt, pt, 1, 1, 1;\n"
        "wgmma.commit_group.sync.aligned;\n"
        "@pz bra.uni B82;\n"
        "mov.b32 {xl, xh}, a0; tanh.approx.f16 xr, xl; cvt.u32.u16 lo0, xr; tanh.approx.f16 xr, xh; cvt.u32.u16 hi0, xr; mul.rn.f16x2 a1, qz17, p1; fma.rn.f16x2 p0, qz18, qz18, c; fma.rn.f16x2 g14, qz14, h0, qz14; prmt.b32 h1, lo1, hi1, 0x5410;\n"
        "mov.b32 {xl, xh}, a1; tanh.approx.f16 xr, xl; cvt.u32.u16 lo1, xr; tanh.approx.f16 xr, xh; cvt.u32.u16 hi1, xr; mul.rn.f16x2 a2, qz18, p0; fma.rn.f16x2 p1, qz19, qz19, c; fma.rn.f16x2 g15, qz15, h1, qz15; prmt.b32 h0, lo0, hi0, 0x5410;\n"
        "B82:\n"
        "wgmma.wait_group.sync.aligned 1;\n"
        "@!pm bra.uni SKIP1;\n"
        "wgmma.fence.sync.aligned;\n"
        "add.s64 dt, w1d, 0; wgmma.mma_async.sync.aligned.m64n64k16.f16.f16.f16 {qz0,qz1,qz2,qz3,qz4,qz5,qz6,qz7,qz8,qz9,qz10,qz11,qz12,qz13,qz14,qz15}, {qa0,qa1,qa2,qa3}, dt, pf, 1, 1, 1;\n"
        "add.s64 dt, w1d, 128; wgmma.mma_async.sync.aligned.m64n64k16.f16.f16.f16 {qz0,qz1,qz2,qz3,qz4,qz5,qz6,qz7,qz8,qz9,qz10,qz11,qz12,qz13,qz14,qz15}, {qa4,qa5,qa6,qa7}, dt, pt, 1, 1, 1;\n"
        "add.s64 dt, w1d, 256; wgmma.mma_async.sync.aligned.m64n64k16.f16.f16.f16 {qz0,qz1,qz2,qz3,qz4,qz5,qz6,qz7,qz8,qz9,qz10,qz11,qz12,qz13,qz14,qz15}, {qa8,qa9,qa10,qa11}, dt, pt, 1, 1, 1;\n"
        "SKIP1:\n"
        "wgmma.fence.sync.aligned;\n"
        "add.s64 dt, w2d, 1216; wgmma.mma_async.sync.aligned.m64n96k16.f16.f16.f16 {o0,o1,o2,o3,o4,o5,o6,o7,o8,o9,o10,o11,o12,o13,o14,o15,o16,o17,o18,o19,o20,o21,o22,o23}, {g12,g13,g14,g15}, dt, pt, 1, 1, 1;\n"
        "wgmma.commit_group.sync.aligned;\n"
        "@pz bra.uni B86;\n"
        "mov.b32 {xl, xh}, a2; tanh.approx.f16 xr, xl; cvt.u32.u16 lo0, xr; tanh.approx.f16 xr, xh; cvt.u32.u16 hi0, xr; mul.rn.f16x2 a3, qz19, p1; fma.rn.f16x2 p0, qz20, qz20, c; fma.rn.f16x2 g0, qz16, h0, qz16; prmt.b32 h1, lo1, hi1, 0x5410;\n"
        "mov.b32 {xl, xh}, a3; tanh.approx.f16 xr, xl; cvt.u32.u16 lo1, xr; tanh.approx.f16 xr, xh; cvt.u32.u16 hi1, xr; mul.rn.f16x2 a0, qz20, p0; fma.rn.f16x2 p1, qz21, qz21, c; fma.rn.f16x2 g1, qz17, h1, qz17; prmt.b32 h0, lo0, hi0, 0x5410;\n"
        "mov.b32 {xl, xh}, a0; tanh.approx.f16 xr, xl; cvt.u32.u16 lo0, xr; tanh.approx.f16 xr, xh; cvt.u32.u16 hi0, xr; mul.rn.f16x2 a1, qz21, p1; fma.rn.f16x2 p0, qz22, qz22, c; fma.rn.f16x2 g2, qz18, h0, qz18; prmt.b32 h1, lo1, hi1, 0x5410;\n"
        "mov.b32 {xl, xh}, a1; tanh.approx.f16 xr, xl; cvt.u32.u16 lo1, xr; tanh.approx.f16 xr, xh; cvt.u32.u16 hi1, xr; mul.rn.f16x2 a2, qz22, p0; fma.rn.f16x2 p1, qz23, qz23, c; fma.rn.f16x2 g3, qz19, h1, qz19; prmt.b32 h0, lo0, hi0, 0x5410;\n"
        "B86:\n"
        "@!pm bra.uni SKIP2;\n"
        "wgmma.fence.sync.aligned;\n"
        "add.s64 dt, w1d, 384; wgmma.mma_async.sync.aligned.m64n64k16.f16.f16.f16 {qz0,qz1,qz2,qz3,qz4,qz5,qz6,qz7,qz8,qz9,qz10,qz11,qz12,qz13,qz14,qz15}, {qa12,qa13,qa14,qa15}, dt, pt, 1, 1, 1;\n"
        "add.s64 dt, w1d, 512; wgmma.mma_async.sync.aligned.m64n64k16.f16.f16.f16 {qz0,qz1,qz2,qz3,qz4,qz5,qz6,qz7,qz8,qz9,qz10,qz11,qz12,qz13,qz14,qz15}, {qa16,qa17,qa18,qa19}, dt, pt, 1, 1, 1;\n"
        "add.s64 dt, w1d, 640; wgmma.mma_async.sync.aligned.m64n64k16.f16.f16.f16 {qz0,qz1,qz2,qz3,qz4,qz5,qz6,qz7,qz8,qz9,qz10,qz11,qz12,qz13,qz14,qz15}, {qa20,qa21,qa22,qa23}, dt, pt, 1, 1, 1;\n"
        "SKIP2:\n"
        "@pz bra.uni B90;\n"
        "mov.b32 {xl, xh}, a2; tanh.approx.f16 xr, xl; cvt.u32.u16 lo0, xr; tanh.approx.f16 xr, xh; cvt.u32.u16 hi0, xr; mul.rn.f16x2 a3, qz23, p1; fma.rn.f16x2 p0, qz24, qz24, c; fma.rn.f16x2 g4, qz20, h0, qz20; prmt.b32 h1, lo1, hi1, 0x5410;\n"
        "mov.b32 {xl, xh}, a3; tanh.approx.f16 xr, xl; cvt.u32.u16 lo1, xr; tanh.approx.f16 xr, xh; cvt.u32.u16 hi1, xr; mul.rn.f16x2 a0, qz24, p0; fma.rn.f16x2 p1, qz25, qz25, c; fma.rn.f16x2 g5, qz21, h1, qz21; prmt.b32 h0, lo0, hi0, 0x5410;\n"
        "mov.b32 {xl, xh}, a0; tanh.approx.f16 xr, xl; cvt.u32.u16 lo0, xr; tanh.approx.f16 xr, xh; cvt.u32.u16 hi0, xr; mul.rn.f16x2 a1, qz25, p1; fma.rn.f16x2 p0, qz26, qz26, c; fma.rn.f16x2 g6, qz22, h0, qz22; prmt.b32 h1, lo1, hi1, 0x5410;\n"
        "mov.b32 {xl, xh}, a1; tanh.approx.f16 xr, xl; cvt.u32.u16 lo1, xr; tanh.approx.f16 xr, xh; cvt.u32.u16 hi1, xr; mul.rn.f16x2 a2, qz26, p0; fma.rn.f16x2 p1, qz27, qz27, c; fma.rn.f16x2 g7, qz23, h1, qz23; prmt.b32 h0, lo0, hi0, 0x5410;\n"
        "B90:\n"
        "wgmma.wait_group.sync.aligned 1;\n"
        "wgmma.fence.sync.aligned;\n"
        "add.s64 dt, w2d, 1280; wgmma.mma_async.sync.aligned.m64n96k16.f16.f16.f16 {o0,o1,o2,o3,o4,o5,o6,o7,o8,o9,o10,o11,o12,o13,o14,o15,o16,o17,o18,o19,o20,o21,o22,o23}, {g0,g1,g2,g3}, dt, pt, 1, 1, 1;\n"
        "add.s64 dt, w2d, 1344; wgmma.mma_async.sync.aligned.m64n96k16.f16.f16.f16 {o0,o1,o2,o3,o4,o5,o6,o7,o8,o9,o10,o11,o12,o13,o14,o15,o16,o17,o18,o19,o20,o21,o22,o23}, {g4,g5,g6,g7}, dt, pt, 1, 1, 1;\n"
        "wgmma.commit_group.sync.aligned;\n"
        "@pz bra.uni B94;\n"
        "mov.b32 {xl, xh}, a2; tanh.approx.f16 xr, xl; cvt.u32.u16 lo0, xr; tanh.approx.f16 xr, xh; cvt.u32.u16 hi0, xr; mul.rn.f16x2 a3, qz27, p1; fma.rn.f16x2 p0, qz28, qz28, c; fma.rn.f16x2 g8, qz24, h0, qz24; prmt.b32 h1, lo1, hi1, 0x5410;\n"
        "mov.b32 {xl, xh}, a3; tanh.approx.f16 xr, xl; cvt.u32.u16 lo1, xr; tanh.approx.f16 xr, xh; cvt.u32.u16 hi1, xr; mul.rn.f16x2 a0, qz28, p0; fma.rn.f16x2 p1, qz29, qz29, c; fma.rn.f16x2 g9, qz25, h1, qz25; prmt.b32 h0, lo0, hi0, 0x5410;\n"
        "mov.b32 {xl, xh}, a0; tanh.approx.f16 xr, xl; cvt.u32.u16 lo0, xr; tanh.approx.f16 xr, xh; cvt.u32.u16 hi0, xr; mul.rn.f16x2 a1, qz29, p1; fma.rn.f16x2 p0, qz30, qz30, c; fma.rn.f16x2 g10, qz26, h0, qz26; prmt.b32 h1, lo1, hi1, 0x5410;\n"
        "mov.b32 {xl, xh}, a1; tanh.approx.f16 xr, xl; cvt.u32.u16 lo1, xr; tanh.approx.f16 xr, xh; cvt.u32.u16 hi1, xr; mul.rn.f16x2 a2, qz30, p0; fma.rn.f16x2 p1, qz31, qz31, c; fma.rn.f16x2 g11, qz27, h1, qz27; prmt.b32 h0, lo0, hi0, 0x5410;\n"
        "B94:\n"
        "wgmma.wait_group.sync.aligned 0;\n"
        "wgmma.fence.sync.aligned;\n"
        "add.s64 dt, w2d, 1408; wgmma.mma_async.sync.aligned.m64n96k16.f16.f16.f16 {o0,o1,o2,o3,o4,o5,o6,o7,o8,o9,o10,o11,o12,o13,o14,o15,o16,o17,o18,o19,o20,o21,o22,o23}, {g8,g9,g10,g11}, dt, pt, 1, 1, 1;\n"
        "wgmma.commit_group.sync.aligned;\n"
        "@pz bra.uni B2;\n"
        "mov.b32 {xl, xh}, a2; tanh.approx.f16 xr, xl; cvt.u32.u16 lo0, xr; tanh.approx.f16 xr, xh; cvt.u32.u16 hi0, xr; mul.rn.f16x2 a3, qz31, p1; fma.rn.f16x2 p0, qz0, qz0, c; fma.rn.f16x2 g12, qz28, h0, qz28; prmt.b32 h1, lo1, hi1, 0x5410;\n"
        "mov.b32 {xl, xh}, a3; tanh.approx.f16 xr, xl; cvt.u32.u16 lo1, xr; tanh.approx.f16 xr, xh; cvt.u32.u16 hi1, xr; mul.rn.f16x2 a0, qz0, p0; fma.rn.f16x2 p1, qz1, qz1, c; fma.rn.f16x2 g13, qz29, h1, qz29; prmt.b32 h0, lo0, hi0, 0x5410;\n"
        "mov.b32 {xl, xh}, a0; tanh.approx.f16 xr, xl; cvt.u32.u16 lo0, xr; tanh.approx.f16 xr, xh; cvt.u32.u16 hi0, xr; mul.rn.f16x2 a1, qz1, p1; fma.rn.f16x2 p0, qz2, qz2, c; fma.rn.f16x2 g14, qz30, h0, qz30; prmt.b32 h1, lo1, hi1, 0x5410;\n"
        "mov.b32 {xl, xh}, a1; tanh.approx.f16 xr, xl; cvt.u32.u16 lo1, xr; tanh.approx.f16 xr, xh; cvt.u32.u16 hi1, xr; mul.rn.f16x2 a2, qz2, p0; fma.rn.f16x2 p1, qz3, qz3, c; fma.rn.f16x2 g15, qz31, h1, qz31; prmt.b32 h0, lo0, hi0, 0x5410;\n"
        "B2:\n"
        "wgmma.fence.sync.aligned;\n"
        "add.s64 dt, w2d, 1472; wgmma.mma_async.sync.aligned.m64n96k16.f16.f16.f16 {o0,o1,o2,o3,o4,o5,o6,o7,o8,o9,o10,o11,o12,o13,o14,o15,o16,o17,o18,o19,o20,o21,o22,o23}, {g12,g13,g14,g15}, dt, pt, 1, 1, 1;\n"
        "wgmma.commit_group.sync.aligned;\n"
        "@!pm bra.uni BE;\n"
        "mov.b32 {xl, xh}, a2; tanh.approx.f16 xr, xl; cvt.u32.u16 lo0, xr; tanh.approx.f16 xr, xh; cvt.u32.u16 hi0, xr; mul.rn.f16x2 a3, qz3, p1; fma.rn.f16x2 p0, qz4, qz4, c; fma.rn.f16x2 g0, qz0, h0, qz0; prmt.b32 h1, lo1, hi1, 0x5410;\n"
        "mov.b32 {xl, xh}, a3; tanh.approx.f16 xr, xl; cvt.u32.u16 lo1, xr; tanh.approx.f16 xr, xh; cvt.u32.u16 hi1, xr; mul.rn.f16x2 a0, qz4, p0; fma.rn.f16x2 p1, qz5, qz5, c; fma.rn.f16x2 g1, qz1, h1, qz1; prmt.b32 h0, lo0, hi0, 0x5410;\n"
        "mov.b32 {xl, xh}, a0; tanh.approx.f16 xr, xl; cvt.u32.u16 lo0, xr; tanh.approx.f16 xr, xh; cvt.u32.u16 hi0, xr; mul.rn.f16x2 a1, qz5, p1; fma.rn.f16x2 p0, qz6, qz6, c; fma.rn.f16x2 g2, qz2, h0, qz2; prmt.b32 h1, lo1, hi1, 0x5410;\n"
        "mov.b32 {xl, xh}, a1; tanh.approx.f16 xr, xl; cvt.u32.u16 lo1, xr; tanh.approx.f16 xr, xh; cvt.u32.u16 hi1, xr; mul.rn.f16x2 a2, qz6, p0; fma.rn.f16x2 p1, qz7, qz7, c; fma.rn.f16x2 g3, qz3, h1, qz3; prmt.b32 h0, lo0, hi0, 0x5410;\n"
        "BE:\n"
        "wgmma.wait_group.sync.aligned 0;\n"
        "bra.uni LOOP;\n"
        "STORE:\n"
        "bar.sync tt, 128;\n"
        "setp.lt.s32 pr, n, 0;\n"
        "@pr bra.uni STOREB;\n"
        "cvt.u64.u32 gp, off; add.s64 gp, gp, %11;\n"
        "elect.sync _|pr, 0xffffffff;\n"
        "@pr cp.async.bulk.global.shared::cta.bulk_group [gp], [%4], 12288;\n"
        "@pr cp.async.bulk.commit_group;\n"
        "bra.uni STOREB;\n"
        "YLOAD:\n"
        "@!pm bra.uni YLOADP;\n"
        "cp.async.bulk.wait_group.read 0;\n"
        "sub.u32 ad, off, %8; cvt.u64.u32 gp, ad; add.s64 gp, gp, %11;\n"
        "elect.sync _|pr, 0xffffffff;\n"
        "@pr mbarrier.arrive.expect_tx.shared::cta.b64 _, [ybar], 12288;\n"
        "@pr cp.async.bulk.shared::cluster.global.mbarrier::complete_tx::bytes [%4], [gp], 12288, [ybar];\n"
        "YLOADP:\n"
        "cvt.u64.u32 gp, off; add.s64 gp, gp, %10;\n"
        "elect.sync _|pr, 0xffffffff;\n"
        "@pr cp.async.bulk.prefetch.L2.global.L2::cache_hint [gp], 12288, pol;\n"
        "bra.uni YLOADB;\n"
        "XLOAD:\n"
        "bar.sync tt, 128;\n"
        "cp.async.bulk.wait_group.read 0;\n"
        "cvt.u64.u32 gp, off; add.s64 gp, gp, %10;\n"
        "elect.sync _|pr, 0xffffffff;\n"
        "@pr mbarrier.arrive.expect_tx.shared::cta.b64 _, [xbar], 12288;\n"
        "@pr cp.async.bulk.shared::cluster.global.mbarrier::complete_tx::bytes.L2::cache_hint [%4], [gp], 12288, [xbar], pol;\n"
        "bra.uni XLOADB;\n"
        "SPINY: mov.u32 cnt, 0;\n"
        "SPINYL:\n"
        "add.u32 tt, n, 1; and.b32 tt, tt, 1; mbarrier.try_wait.parity.shared::cta.b64 pw, [ybar], tt;\n"
        "@pw bra.uni BACKY;\n"
        "add.u32 cnt, cnt, 1; setp.lt.u32 pw, cnt, 0x100000;\n"
        "@pw bra.uni SPINYL;\n"
        "trap;\n"
        "SPINX: mov.u32 cnt, 0;\n"
        "SPINXL:\n"
        "and.b32 tt, n, 1; mbarrier.try_wait.parity.shared::cta.b64 pw, [xbar], tt;\n"
        "@pw bra.uni BACKX;\n"
        "add.u32 cnt, cnt, 1; setp.lt.u32 pw, cnt, 0x100000;\n"
        "@pw bra.uni SPINXL;\n"
        "trap;\n"
        "SPINT: mov.u32 cnt, 0;\n"
        "SPINTL:\n"
        "mad.lo.u32 tt, n, 8, tbar; mbarrier.try_wait.parity.shared::cta.b64 pw, [tt], tpar;\n"
        "@pw bra.uni BACKT;\n"
        "add.u32 cnt, cnt, 1; setp.lt.u32 pw, cnt, 0x100000;\n"
        "@pw bra.uni SPINTL;\n"
        "trap;\n"
        "SPINW0: mov.u32 cnt, 0;\n"
        "SPINW0L:\n"
        "mov.u32 tt, 231208; mbarrier.try_wait.parity.shared::cta.b64 pw, [tt], 0;\n"
        "@pw bra.uni BACKW0;\n"
        "add.u32 cnt, cnt, 1; setp.lt.u32 pw, cnt, 0x100000;\n"
        "@pw bra.uni SPINW0L;\n"
        "trap;\n"
        "SPINW1: mov.u32 cnt, 0;\n"
        "SPINW1L:\n"
        "mov.u32 tt, 231216; mbarrier.try_wait.parity.shared::cta.b64 pw, [tt], 0;\n"
        "@pw bra.uni BACKW1;\n"
        "add.u32 cnt, cnt, 1; setp.lt.u32 pw, cnt, 0x100000;\n"
        "@pw bra.uni SPINW1L;\n"
        "trap;\n"
        "DONE:\n"
        "wgmma.wait_group.sync.aligned 0;\n"
        "}\n"
        :: "r"(prm.w1desc), "r"(prm.w2desc), "r"(c.wg), "r"(c.off), "r"(c.xs), "r"(c.a_offs), "r"(c.xs_offs), "r"(c.bias_addr),
           "r"(c.step), "r"(c.w), "l"(prm.x), "l"(prm.out)
        : "memory");
}

__device__ __forceinline__ float warp_sum(float v) {
#pragma unroll
    for (int s = 16; s >= 1; s >>= 1) v += __shfl_xor_sync(0xffffffffu, v, s);
    return v;
}
__device__ __forceinline__ float pow2f(int e) { return __uint_as_float((uint32_t)(e + 127) << 23); }
__device__ __forceinline__ int exponent_of(float v) { return (int)(__float_as_uint(v) >> 23) - 127; }
__device__ __forceinline__ float lds_bf16(uint32_t addr) {
    uint16_t v; asm volatile("ld.shared.u16 %0, [%1];" : "=h"(v) : "r"(addr) : "memory"); return bf_lo(v);
}

__device__ __forceinline__ void publish_bias(const Params& prm, uint32_t c, uint32_t tag) {
    const uint32_t lane = fresh_tid() & 31;
    const uint32_t col = sb + SM_W2 + (c >> 5) * 24576 + lane * 64 + ((((c >> 3) ^ (lane >> 1)) & 3) * 16) + (c & 7) * 2;
    float v = 0.0f;
#pragma unroll
    for (int k = 0; k < EX / 32; k++) v = fmaf(lds_bf16(col + k * 2048), lds_bf16(sb + SM_BETA + lane * 2 + k * 64), v);
    v = warp_sum(v);
    if (lane == 0)
        asm volatile("st.relaxed.gpu.global.u64 [%0], %1;" ::"l"(prm.g->bias + c), "l"((uint64_t)tag << 32 | __float_as_uint(v)) : "memory");
}
__device__ __forceinline__ void collect_bias(const Params& prm, uint32_t tag) {
    const uint32_t lane = fresh_tid() & 31;
    if (lane < 24) {
        const unsigned long long* src = prm.g->bias + 32 * (lane >> 3) + 8 * (lane & 3) + (lane & 4);
        uint32_t v[4], t[4], spins = 0;
        for (;;) {
#pragma unroll
            for (int k = 0; k < 4; k++)
                asm volatile("{\n.reg .b64 w;\nld.relaxed.gpu.global.u64 w, [%2];\nmov.b64 {%0, %1}, w;\n}\n"
                             : "=r"(v[k]), "=r"(t[k]) : "l"(src + k) : "memory");
            if (t[0] == tag && t[1] == tag && t[2] == tag && t[3] == tag) break;
            if (++spins > (1u << 22)) __trap();
        }
        sts128(sb + SM_BIAS + lane * 16, v[0], v[1], v[2], v[3]);
    }
    __syncwarp();
}
__device__ __forceinline__ float fetch_w2_row(uint32_t (&u)[12][4], uint32_t row, uint32_t sw) {
    uint32_t mx[4] = {};
#pragma unroll
    for (int a = 0; a < 3; a++)
#pragma unroll
        for (int k = 0; k < 4; k++) {
            asm volatile("ld.shared.v4.b32 {%0,%1,%2,%3}, [%4];"
                         : "=r"(u[a * 4][k]), "=r"(u[a * 4 + 1][k]), "=r"(u[a * 4 + 2][k]), "=r"(u[a * 4 + 3][k])
                         : "r"(row + a * 24576 + ((k * 16) ^ sw)) : "memory");
#pragma unroll
            for (int b = 0; b < 4; b++) asm("max.xorsign.abs.bf16x2 %0, %0, %1;" : "+r"(mx[b]) : "r"(u[a * 4 + b][k]));
        }
#pragma unroll
    for (int b = 1; b < 4; b++) asm("max.xorsign.abs.bf16x2 %0, %0, %1;" : "+r"(mx[0]) : "r"(mx[b]));
    return fmaxf(fabsf(bf_lo(mx[0])), fabsf(bf_hi(mx[0])));
}

template <bool FAST> __device__ __forceinline__ bool grn_stats(float ss, float gm, float bt, float top, int e, float& gx, float& inv, int& eo) {
    gx = sqrt_fast(fmaf(ss, INV_2A * INV_2A, 1e-6f));
    const float rt = sqrt_fast(ss + 1.0f) * INV_2A * top;
    uint32_t r[4] = {FAST ? __reduce_add_sync(0xffffffffu, __float2uint_rn(gx * 128.0f)) : __float_as_uint(warp_sum(gx)),
                     __reduce_max_sync(0xffffffffu, __float_as_uint(fmaf(bt, top, rt))),
                     __reduce_max_sync(0xffffffffu, __float_as_uint(rt * fabsf(gm) * gx)),
                     (uint32_t)__any_sync(0xffffffffu, !(ss >= 16.0f && ss < ACC_LIMIT))};
    if ((e & 31) == 0) sts128(sb + SM_SEL + (e >> 5) * 16, r[0], r[1], r[2], r[3]);
    MARK(6);
    named_sync(10, 512);
    lds128(r, sb + SM_SEL + min(e & 15, 11) * 16);
    if ((e & 31) >= 12) r[0] = 0;
    const float tot = FAST ? __uint2float_rn(__reduce_add_sync(0xffffffffu, r[0])) * (1.0f / 128) : warp_sum(__uint_as_float(r[0]));
    inv = __fdividef(1.0f, fmaf(tot, 1.0f / EX, 1e-6f));
    const float bound = fmaf(__uint_as_float(__reduce_max_sync(0xffffffffu, r[2])), inv,
                             __uint_as_float(__reduce_max_sync(0xffffffffu, r[1]))) * EX;
    eo = min(max(exponent_of(bound), -90), 126) - 14;
    return __any_sync(0xffffffffu, r[3]);
}

__device__ __forceinline__ float exact_sums(const Params& prm) {
    const int lane = fresh_tid() & 31, warp = fresh_warp(), wg = warp >> 2;
    const uint32_t epoch = lds32(sb + SM_RED + (RED_EPOCH + 1) * 4), bar = sb + SM_BAR + BAR_W1 * 8;
    if (wg < 3) {
        uint32_t wa[2][24], d[2][16];
        float acc[2][2] = {};
        const uint32_t yd = prm.ydesc + ((SM_SPARE - SM_Y1) >> 4), wd = prm.w1desc + ((2 * wg * 12288 + 5 * 2048) >> 4);
        load_w1t(wa, wg, warp & 3, lane);
#pragma unroll 1
        for (int n = 0; n < ROWS_PER_CTA; n++) {
            if (warp == 0) {
                expect_tx(bar, TILE_BYTES);
                bulk_load(sb + SM_SPARE, (const char*)prm.out + (cta_tile0(fresh_cta()) + n * cta_stride(fresh_cta())), TILE_BYTES, bar);
            }
            mbar_wait(bar, (n + 1) & 1);
            gemm1_t<0>(d[0], wa[0], yd, wd);
            gemm1_t<1>(d[1], wa[1], yd, wd);
            wg_wait<0>();
            pin(d[0]); pin(d[1]);
            gelu_sumsq_f(d[0], acc[0]);
            gelu_sumsq_f(d[1], acc[1]);
            named_sync(1, 384);
        }
        publish_sums(acc, prm.g->sums[epoch & 1], &prm.g->count[1], wg, warp & 3, lane);
    }
    grid_wait(&prm.g->count[1], (epoch + 1) * NUM_CTAS);
    return __ldcg(prm.g->sums[epoch & 1] + fresh_tid() % EX);
}

template <bool FIRST> __device__ __forceinline__ void prepare_pass2(const Pass2& c, const Params& prm, float ss) {
    const int tid = fresh_tid(), lane = tid & 31, warp = fresh_warp(), wg = warp >> 2;
    const int e = tid >= EX ? tid - EX : tid;
    const uint32_t w2row = sb + SM_W2 + e * 64, sw = ((e >> 1) & 3) * 16;
    pass2_start(c, prm);
    MARK(2);
    if (wg) {
        uint32_t u[12][4];
        mbar_wait_c<0>(sb + SM_BAR + BAR_W2 * 8);
        const float top = fetch_w2_row(u, w2row, sw);
        MARK(3);
        const float gm = lds_bf16(sb + SM_GAMMA + e * 2), bt = fabsf(lds_bf16(sb + SM_BETA + e * 2));
        if (FIRST) {
            const uint32_t epoch = lds32(sb + SM_RED + RED_EPOCH * 4);
            if (wg == 3) named_sync(11, EX);
            if (warp == 12) collect_bias(prm, epoch + 1);
            MARK(4);
            ss = collect_fast(acc_word(prm, epoch, e));
            if (tid == 416 && fresh_cta() == 0) prm.g->count[0] = epoch + 1;
        }
        if (warp == 4) TS(4);
        MARK(5);
        float gx, inv;
        int eo;
        const bool redo = (grn_stats<FIRST>(ss, gm, bt, top, e, gx, inv, eo) || FORCE_EXACT) && FIRST;
        MARK(8);
        const float up = pow2f(eo), dn = pow2f(-eo);
        if (warp == 4) {
            if (lane == 24) sts64(sb + SM_RED + RED_SCALE * 4, pack_bf2(up, up), redo);
            if (lane < 24 && !redo) {
                uint32_t b[4];
                lds128(b, sb + SM_BIAS + lane * 16);
                const uint32_t p0 = pack_h2(__uint_as_float(b[0]) * dn, __uint_as_float(b[1]) * dn);
                const uint32_t p1 = pack_h2(__uint_as_float(b[2]) * dn, __uint_as_float(b[3]) * dn);
                sts128(sb + SM_BIAS + lane * 16, p0, p0, p1, p1);
            }
            __syncwarp();
            mbar_arrive_if(sb + SM_BAR + BAR_STAT * 8, lane == 0);
        }
        if (!redo) {
            float sc = fmaf(gm, gx * inv, 1.0f) * INV_2A;
            if (eo > 6) {
                const uint32_t dn2 = pack_bf2(dn, dn);
#pragma unroll
                for (int k = 0; k < 48; k++) u[k >> 2][k & 3] = bf2_mul(u[k >> 2][k & 3], dn2);
            } else {
                sc *= dn;
            }
            const uint32_t s2 = pack_bf2(sc * 0x1p-112f, sc * 0x1p-112f);
#pragma unroll
            for (int k = 0; k < 12; k++) {
                uint32_t v[4];
#pragma unroll
                for (int b = 0; b < 4; b++) {
                    v[b] = bf2_mul(u[k][b], s2);
                    v[b] += (v[b] & 0x7fff7fffu) * 7u;
                }
                sts128(w2row + (k >> 2) * 24576 + (((k & 3) * 16) ^ sw), v[0], v[1], v[2], v[3]);
            }
            MARK(9);
            fence_async_smem();
            __syncwarp();
            mbar_arrive_if(sb + SM_BAR + (BAR_ROWS + (wg != 3)) * 8, lane == 0);
        }
        if (warp == 4) TS(5);
    } else {
        asm volatile("bar.arrive 10, 512;" ::: "memory");
    }
}

__device__ __forceinline__ void pass2_uniform(Pass2& c) {
    const int warp = fresh_warp(), wg = warp >> 2;
    c.wg = wg;
    c.w = warp & 3;
    c.off = cta_tile0(fresh_cta()) + (ROWS_PER_CTA - 1 - wg) * cta_stride(fresh_cta());
    c.step = 4 * cta_stride(fresh_cta());
    c.xs = wg == 3 ? sb + SM_BUF3 : sb + SM_Y1 + (wg == 2 ? 2 : 1 - wg) * SLOT_BYTES;
    static_assert((ROWS_PER_CTA - 1) % NX == 1, "slot of the last tile");
}
__device__ __forceinline__ Pass2 pass2_setup() {
    Pass2 c;
    pass2_uniform(c);
    const int lane = fresh_tid() & 31, w = c.w, arow = 16 * w + (lane & 15);
    c.a_offs = (arow * 128 + (((lane >> 4) ^ (arow & 7)) * 16)) |
               (8192 + arow * 64 + (((lane >> 4) ^ ((arow >> 1) & 3)) * 16)) << 16;
    const int g = lane >> 2, px = 33 * (g & 1) + 4 * (g >> 1) + 16 * (w >> 1) + 2 * (w & 1);
    c.xs_offs = (px * 192 + (lane & 3) * 16) | ((px ^ 1) * 192 + (lane & 3) * 16) << 16;
    c.bias_addr = sb + SM_BIAS + (lane & 3) * 16;
    return c;
}

__global__ void __launch_bounds__(512, 1) convnext_kernel(const __grid_constant__ Params prm) {
    extern __shared__ __align__(1024) uint8_t smem[];
    if ((uint32_t)__cvta_generic_to_shared(smem) != sb) __trap();
    {
        const uint32_t tid = fresh_tid(), warp = fresh_warp(), lane = tid & 31;
        if (warp == 0) {
            if (lane == 0) {
#pragma unroll
                for (int k = 0; k < NX; k++) mbar_init(sb + SM_GO + k * 8, 2);
                mbar_init(sb + SM_BAR + BAR_DW * 8, 1);
                mbar_init(sb + SM_BAR + BAR_W1 * 8, 1);
                mbar_init(sb + SM_BAR + BAR_W1B * 8, 1);
                fence_async_smem();
            }
            __syncwarp();
            expect_tx(sb + SM_BAR + BAR_DW * 8, 9 * CH * 2);
            bulk_load(sb + SM_Y1, prm.dw, 9 * CH * 2, sb + SM_BAR + BAR_DW * 8);
            const RowCopy rc = row_copy(prm);
#pragma unroll
            for (int k = 0; k < NX; k++) issue_row_load(rc, k, k);
            SMARK(4);
        }
        if (fresh_warp() == 15) {
            const uint32_t cta = fresh_cta();
            bulk_prefetch((const char*)prm.w1 + cta * (CH * EX * 2 / NUM_CTAS), CH * EX * 2 / NUM_CTAS);
            bulk_prefetch(prm.dw, 9 * CH * 2);
            bulk_prefetch((const char*)prm.x + (cta_tile0(cta) - cta_stride(cta)), TILE_BYTES);
        } else if (warp == 2) {
            if (lane < 2) asm volatile("prefetch.tensormap [%0];" ::"l"(&prm.w1_map + lane) : "memory");
        } else if (warp - 6u < 6) {
            if (lane == 0) {
#pragma unroll 1
                for (int k = NX + warp - 6; k < GO_COUNT + ROWS_PER_CTA + 2; k += 6)
                    mbar_init(sb + SM_GO + k * 8, k < 2 * NX ? 2 : k < GO_COUNT ? 14 : 4);
                fence_async_smem();
            }
        } else if (warp == 3) {
            const uint32_t one = (lane & 5) == ((lane & 8) >> 1) + (lane >> 4) ? 0x3f803f80u : 0u;
            sts128(sb + SM_SEL + lane * 16, one, one, one, one);
            fence_async_smem();
        } else if (tid - 128u < NX * 12 && ((fresh_cta() + 1) & 7) < 2) {
            const int k = tid - 128;
            sts128(sb + SM_X + (k / 12) * SLOT_BYTES + ((fresh_cta() & 7) == 0 ? 0 : XHALF_B + 33 * 192) + (k % 12) * 16, 0, 0, 0, 0);
        }
        __syncwarp();
        SMARK(3);
        named_sync(0, 512);
    }
    if (fresh_warp() >= 12) {
        Producer pc;
        SMARK(0);
        asm volatile("setmaxnreg.inc.sync.aligned.u32 %0;" ::"n"(PRODUCER_REGS));
        SMARK(1);
        const int w = fresh_warp() & 3, lane = fresh_tid() & 31;
        const int j = lane & 7, hb = (lane >> 3) & 1, base = 4 * (2 * w + (lane >> 4));
        pc.lane = lane;
        pc.xoff[0] = hb * XHALF_B + base * 192 + j * 16;
        pc.xoff[1] = hb * XHALF_B + base * 192 + 128 + j * 8;
        const int grp = 4 * w + (lane >> 3);
#pragma unroll
        for (int o = 0; o < 2; o++) {
            const int row = (grp & 7) + 8 * (o ^ hb) + 32 * (grp >> 3);
            pc.yoff[0][o] = row * 128 + ((j ^ (row & 7)) * 16);
            pc.yoff[1][o] = 8192 + row * 64 + (((j >> 1) ^ ((row >> 1) & 3)) * 16) + (j & 1) * 8;
        }
        pc.stat = sb + SM_STAT + (8 * w + (lane >> 2)) * 32;
        pc.own = pc.stat + (lane & 3) * 8;
        const int dstep = fresh_cta() & 8 ? 3 * CH * 2 : -3 * CH * 2;
        mbar_wait_c<0>(sb + SM_BAR + BAR_DW * 8);
        SMARK(8);
#pragma unroll
        for (int tap = 0; tap < 9; tap++) {
            const uint32_t dw = sb + SM_Y1 + (3 + tap % 3) * CH * 2 + (tap / 3 - 1) * dstep;
            lds128(pc.w[tap], dw + j * 16);
            asm volatile("ld.shared.v2.b32 {%0,%1}, [%2];" : "=r"(pc.w[tap][4]), "=r"(pc.w[tap][5]) : "r"(dw + 128 + j * 8) : "memory");
        }
#pragma unroll
        for (int tap = 0; tap < 9; tap++)
#pragma unroll
            for (int u = 0; u < 6; u++) pc.w[tap][u] = bf2_mul(pc.w[tap][u], TAP_SCALE_BF2);
        produce(pc, prm);
        TS(9);
        asm volatile("setmaxnreg.dec.sync.aligned.u32 %0;" ::"n"(EVEN_REGS));
        if (fresh_warp() == 12) {
            mbar_wait_c<0>(sb + SM_BAR + BAR_W2 * 8);
            if (fresh_cta() < CH) publish_bias(prm, fresh_cta(), lds32(sb + SM_RED + RED_EPOCH * 4) + 1);
        }
    } else {
        asm volatile("setmaxnreg.dec.sync.aligned.u32 %0;" ::"n"(CONSUMER_REGS));
        {
            const int tid = fresh_tid(), warp = fresh_warp();
            if (warp == 1) {
#pragma unroll
                for (int h = 0; h < 2; h++) {
                    const uint32_t bar = sb + SM_BAR + (h ? BAR_W1B : BAR_W1) * 8;
                    expect_tx(bar, CH * EX);
#pragma unroll
                    for (int q = h; q < 6; q += 2) tma_load_2d(sb + SM_W1 + q * 12288, &prm.w1_map, 64 * q, 0, bar);
                }
            }
            uint32_t cnt[2];
            asm volatile("ld.relaxed.gpu.global.v2.u32 {%0, %1}, [%2];" : "=r"(cnt[0]), "=r"(cnt[1]) : "l"(prm.g->count) : "memory");
            SMARK(0);
            if (warp == 2) {
                const RowCopy rc = row_copy(prm);
#pragma unroll 1
                for (int i = loop_init<0>(); i < NX; i++) {
                    named_sync(6 + i, 160);
                    issue_row_load(rc, i + NX, i);
                }
            }
            if (tid == 256) {
                sts64(sb + SM_RED + RED_EPOCH * 4, cnt[0], cnt[1] / NUM_CTAS);
#pragma unroll
                for (int k = 0; k < BAR_DW; k++)
                    if (k != BAR_W1 && k != BAR_W1B) mbar_init(sb + SM_BAR + k * 8, k < BAR_TURN || k == BAR_STAT ? 1 : k == BAR_ROWS + 1 ? 8 : 4);
#pragma unroll
                for (int k = 0; k < 3; k++) mbar_arrive_if(sb + SM_BAR + (BAR_Y2FULL + k) * 8, true);
            }
            if (fresh_cta() == 0) *acc_word(prm, cnt[0] + 1, tid) = 0;
            if (fresh_cta() == 1) prm.g->sums[~(cnt[1] / NUM_CTAS) & 1][tid] = 0.0f;
            __syncwarp();
            SMARK(1);
            mbar_wait_c<0>(sb + SM_BAR + BAR_W1 * 8);
            SMARK(2);
        }

        const int tid = fresh_tid(), lane = tid & 31, wg = fresh_warp() >> 2, w = fresh_warp() & 3;
        float acc[2][2];
        const int c = 8 * (lane >> 4) + (lane & 7), ck = 2 * w + ((lane >> 3) & 1);
        consume(acc, sb + SM_W1 + 2 * wg * 12288 + c * 128 + ((ck ^ (c & 7)) * 16), prm.ydesc,
                prm.w1desc + (((2 * wg + 1) * 12288 + 5 * 2048) >> 4), wg * SLOT_BYTES, make_duty(prm, wg, w), w, lane, prm);
        publish_fast(prm, acc, lds32(sb + SM_RED + RED_EPOCH * 4), wg, w, lane);
        if (wg) asm volatile("bar.arrive 11, 384;" ::: "memory");
        MARK(0);
        bulk_wait_all();
        if (wg == 0) TS(3);
        asm volatile("setmaxnreg.inc.sync.aligned.u32 %0;" ::"n"(EVEN_REGS));
    }

    {
        asm volatile(PASS2_STATE);
        MARK(1);
        Pass2 c = pass2_setup();
        prepare_pass2<true>(c, prm, 0.0f);
        if (pass2_head(c, 0)) {
            const float ss = exact_sums(prm);
            c = pass2_setup();
            prepare_pass2<false>(c, prm, ss);
            pass2_head(c, 1);
        }

        pass2_uniform(c);
        pass2_tiles(c, prm);
        bulk_wait_read<0>();
        MARK(13);
    }
}

}

extern "C" void kernel_launch(void* const* d_in, const int* in_sizes, int n_in, void* d_out, int out_size) {
    (void)in_sizes; (void)n_in; (void)out_size;
    typedef CUresult (*EncodeFn)(CUtensorMap*, CUtensorMapDataType, cuuint32_t, void*, const cuuint64_t*, const cuuint64_t*,
                                 const cuuint32_t*, const cuuint32_t*, CUtensorMapInterleave, CUtensorMapSwizzle,
                                 CUtensorMapL2promotion, CUtensorMapFloatOOBfill);
    void* fn = nullptr;
    cudaDriverEntryPointQueryResult status;
    cudaGetDriverEntryPoint("cuTensorMapEncodeTiled", &fn, cudaEnableDefault, &status);
    const EncodeFn encode = (EncodeFn)fn;
    const cuuint32_t ones[2] = {1, 1};

    Params p;
    {
        const cuuint64_t dims[2] = {EX, CH}, strides[1] = {EX * 2};
        const cuuint32_t box[2] = {64, CH};
        encode(&p.w1_map, CU_TENSOR_MAP_DATA_TYPE_BFLOAT16, 2, d_in[2], dims, strides, box, ones,
               CU_TENSOR_MAP_INTERLEAVE_NONE, CU_TENSOR_MAP_SWIZZLE_128B, CU_TENSOR_MAP_L2_PROMOTION_NONE,
               CU_TENSOR_MAP_FLOAT_OOB_FILL_NONE);
    }
    {
        const cuuint64_t dims[2] = {CH, EX}, strides[1] = {CH * 2};
        const cuuint32_t box[2] = {32, 192};
        encode(&p.w2_map, CU_TENSOR_MAP_DATA_TYPE_BFLOAT16, 2, d_in[3], dims, strides, box, ones,
               CU_TENSOR_MAP_INTERLEAVE_NONE, CU_TENSOR_MAP_SWIZZLE_64B, CU_TENSOR_MAP_L2_PROMOTION_NONE,
               CU_TENSOR_MAP_FLOAT_OOB_FILL_NONE);
    }
    p.x = (const __nv_bfloat16*)d_in[0];
    p.dw = (const __nv_bfloat16*)d_in[1];
    p.w1 = (const __nv_bfloat16*)d_in[2];
    p.gamma = (const __nv_bfloat16*)d_in[4];
    p.beta = (const __nv_bfloat16*)d_in[5];
    p.out = (__nv_bfloat16*)d_out;
    cudaGetSymbolAddress((void**)&p.g, g_scratch);
    p.w1desc = desc_lo(sb + SM_W1, 12288);
    p.w2desc = desc_lo(sb + SM_W2, 24576);
    p.ydesc = desc_lo(sb + SM_Y1, 16);
    p.ydesc64[0] = (0x40000040ull << 32) | p.ydesc;
    p.ydesc64[1] = (0x80000020ull << 32) | (p.ydesc + 512);
    for (int k = 0; k < 3; k++) p.sel[k] = (8ull << 32) | desc_lo(sb + SM_SEL + k * 128, k == 2 ? 128 : 0);
    constexpr int smem_bytes = SM_TOTAL;
    cudaFuncSetAttribute(convnext_kernel, cudaFuncAttributeMaxDynamicSharedMemorySize, smem_bytes);
    convnext_kernel<<<NUM_CTAS, 512, smem_bytes>>>(p);
}
```

```cpp
#include <cuda.h>
#include <cuda_runtime.h>
#include <cuda_bf16.h>
#include <stdint.h>

namespace {

constexpr int IMG_W = 512, CH = 96, EX = 384;
constexpr int TILE_PX = 64;
constexpr int ROWS_PER_CTA = 32;
constexpr int NUM_CTAS = 128;
constexpr int STEPS = ROWS_PER_CTA + 2;
constexpr int ROW_BYTES = IMG_W * CH * 2;

#define FORCE_EXACT 0
constexpr int PRODUCER_REGS = 200, CONSUMER_REGS = 104, EVEN_REGS = 128;

constexpr int XHALF_BYTES = 34 * 192;
constexpr int XHALF_B = XHALF_BYTES + 64;
constexpr int XROW_BYTES = XHALF_B + XHALF_BYTES + 64;
constexpr int L2_AHEAD = 2;
constexpr int NX = 3;
constexpr int TILE_BYTES = TILE_PX * 192;

constexpr uint32_t sb = 1024;
constexpr int SM_W1 = 0;
constexpr int SM_W2 = 73728;
constexpr int SM_RING = 147456;
constexpr int SLOT_BYTES = 26624;
constexpr int SM_Y1 = SM_RING;
constexpr int SM_X = SM_Y1 + TILE_BYTES;
constexpr int SM_STAT = SM_X + XROW_BYTES;
constexpr int SM_BUF3 = SM_X + SLOT_BYTES, SM_SPARE = SM_X;
constexpr int SM_SEL = SM_RING + NX * SLOT_BYTES;
constexpr int SM_BIAS = SM_SEL + 512;
constexpr int SM_GAMMA = SM_BIAS + 384;
constexpr int SM_BETA = SM_GAMMA + EX * 2;
constexpr int SM_RED = SM_BETA + EX * 2;
constexpr int SM_BAR = SM_RED + 16;
constexpr int BAR_Y2FULL = 0, BAR_XSFULL = 4, BAR_W1 = 8, BAR_W2 = 9, BAR_W1B = 10, BAR_TURN = 11, BAR_ROWS = 51,
              BAR_STAT = 53, BAR_DW = 54, BAR_COUNT = 55;
constexpr int SM_GO = SM_BAR + BAR_COUNT * 8, GO_COUNT = ROWS_PER_CTA + 2 * NX;
constexpr int SM_YFULL = SM_GO + (GO_COUNT + 1) * 8;
constexpr int SM_TOTAL = SM_YFULL + (ROWS_PER_CTA + 1) * 8;
static_assert(SM_STAT + TILE_PX * 16 <= SM_RING + SLOT_BYTES && XROW_BYTES >= TILE_BYTES && SM_X % 1024 == 0, "ring layout");
static_assert(SM_TOTAL <= 232448, "smem budget");
static_assert(SM_STAT % 128 == 0 && SM_BIAS % 16 == 0 && SM_BAR % 8 == 0 && SLOT_BYTES % 1024 == 0, "alignment");

constexpr int RED_EPOCH = 0, RED_SCALE = 2;

constexpr float GELU_A = 0.32920349f;
constexpr uint32_t GELU_C_H2 = 0x40D940D9u;
constexpr float INV_2A = 1.0f / (2.0f * GELU_A);

constexpr uint32_t TAP_SCALE_BF2 = 0x2B802B80u;
constexpr float LN_EPS_SCALED = 1e-5f * 0x1p-80f;
constexpr float RSTD_SCALE = GELU_A * 0x1p-112f;

struct Scratch {
    unsigned long long acc[2][EX / 4 * 32];
    unsigned long long bias[CH];
    float sums[2][EX];
    uint4 zero_row[66 * 192 / 16];
    unsigned int count[2];
};
__device__ __align__(256) Scratch g_scratch;
constexpr float ACC_LIMIT = 0x1p30f;

#define TS(k)
#define ASM_TS
#define MARK(k)
#define SMARK(k)
#define ASM_MARK
#define ASM_SMARK
#define ASM_TRC(it)

__device__ __forceinline__ void mbar_init(uint32_t bar, uint32_t count) {
    asm volatile("mbarrier.init.shared::cta.b64 [%0], %1;" ::"r"(bar), "r"(count) : "memory");
}
__device__ __forceinline__ void mbar_arrive_if(uint32_t bar, bool pred) {
    asm volatile("{\n.reg .pred p;\nsetp.ne.u32 p, %1, 0;\n@p mbarrier.arrive.shared::cta.b64 _, [%0];\n}\n"
                 ::"r"(bar), "r"((uint32_t)pred) : "memory");
}
__device__ __forceinline__ void mbar_wait(uint32_t bar, uint32_t parity) {
    asm volatile(
        "{\n.reg .pred p;\n.reg .u32 n;\n"
        "mbarrier.try_wait.parity.shared::cta.b64 p, [%0], %1;\n"
        "@p bra.uni WAIT_DONE;\n"
        "mov.u32 n, 0;\n"
        "WAIT_LOOP:\n"
        "mbarrier.try_wait.parity.shared::cta.b64 p, [%0], %1;\n"
        "@p bra.uni WAIT_DONE;\n"
        "mbarrier.try_wait.parity.shared::cta.b64 p, [%0], %1;\n"
        "@p bra.uni WAIT_DONE;\n"
        "mbarrier.try_wait.parity.shared::cta.b64 p, [%0], %1;\n"
        "@p bra.uni WAIT_DONE;\n"
        "add.u32 n, n, 1;\nsetp.lt.u32 p, n, 0x40000;\n"
        "@p bra.uni WAIT_LOOP;\n"
        "trap;\n"
        "WAIT_DONE:\n}\n"
        ::"r"(bar), "r"(parity) : "memory");
}
template <int PARITY> __device__ __forceinline__ void mbar_wait_c(uint32_t bar) {
    asm volatile(
        "{\n.reg .pred p;\n.reg .u32 n;\n"
        "mbarrier.try_wait.parity.shared::cta.b64 p, [%0], %1;\n"
        "@p bra.uni WAIT_DONE;\n"
        "mov.u32 n, 0;\n"
        "WAIT_LOOP:\n"
        "mbarrier.try_wait.parity.shared::cta.b64 p, [%0], %1;\n"
        "@p bra.uni WAIT_DONE;\n"
        "mbarrier.try_wait.parity.shared::cta.b64 p, [%0], %1;\n"
        "@p bra.uni WAIT_DONE;\n"
        "mbarrier.try_wait.parity.shared::cta.b64 p, [%0], %1;\n"
        "@p bra.uni WAIT_DONE;\n"
        "add.u32 n, n, 1;\nsetp.lt.u32 p, n, 0x40000;\n"
        "@p bra.uni WAIT_LOOP;\n"
        "trap;\n"
        "WAIT_DONE:\n}\n"
        ::"r"(bar), "n"(PARITY) : "memory");
}
#define ELECTED(body) "{\n.reg .pred p;\nelect.sync _|p, 0xffffffff;\n" body "}\n"
__device__ __forceinline__ void expect_tx(uint32_t bar, uint32_t bytes) {
    asm volatile(ELECTED("@p mbarrier.arrive.expect_tx.shared::cta.b64 _, [%0], %1;\n") ::"r"(bar), "r"(bytes) : "memory");
}
__device__ __forceinline__ void bulk_load(uint32_t dst, const void* src, uint32_t bytes, uint32_t bar) {
    asm volatile(ELECTED("@p cp.async.bulk.shared::cluster.global.mbarrier::complete_tx::bytes [%0], [%1], %2, [%3];\n")
                 ::"r"(dst), "l"(src), "r"(bytes), "r"(bar) : "memory");
}
__device__ __forceinline__ void bulk_prefetch(const void* src, uint32_t bytes) {
    asm volatile(ELECTED("@p cp.async.bulk.prefetch.L2.global [%0], %1;\n") ::"l"(src), "r"(bytes) : "memory");
}
__device__ __forceinline__ void tma_load_2d(uint32_t dst, const CUtensorMap* map, int c0, int c1, uint32_t bar) {
    asm volatile(ELECTED("@p cp.async.bulk.tensor.2d.shared::cluster.global.mbarrier::complete_tx::bytes [%0], [%1, {%2, %3}], [%4];\n")
                 ::"r"(dst), "l"(map), "r"(c0), "r"(c1), "r"(bar) : "memory");
}
template <int N> __device__ __forceinline__ void bulk_wait_read() {
    asm volatile("cp.async.bulk.wait_group.read %0;" ::"n"(N) : "memory");
}
__device__ __forceinline__ void bulk_wait_all() { asm volatile("cp.async.bulk.wait_group 0;" ::: "memory"); }
__device__ __forceinline__ void fence_async_smem() { asm volatile("fence.proxy.async.shared::cta;" ::: "memory"); }
__device__ __forceinline__ void named_sync(int id, int n) { asm volatile("bar.sync %0, %1;" ::"r"(id), "r"(n) : "memory"); }

__device__ __forceinline__ void sts64(uint32_t addr, uint32_t a, uint32_t b) {
    asm volatile("st.shared.v2.b32 [%0], {%1,%2};" ::"r"(addr), "r"(a), "r"(b) : "memory");
}
__device__ __forceinline__ void sts128(uint32_t addr, uint32_t a, uint32_t b, uint32_t c, uint32_t d) {
    asm volatile("st.shared.v4.b32 [%0], {%1,%2,%3,%4};" ::"r"(addr), "r"(a), "r"(b), "r"(c), "r"(d) : "memory");
}
__device__ __forceinline__ void ldsm4_t(uint32_t* r, uint32_t addr) {
    asm volatile("ldmatrix.sync.aligned.m8n8.x4.trans.shared.b16 {%0,%1,%2,%3}, [%4];"
                 : "=r"(r[0]), "=r"(r[1]), "=r"(r[2]), "=r"(r[3]) : "r"(addr) : "memory");
}
__device__ __forceinline__ void lds128(uint32_t* v, uint32_t addr) {
    asm volatile("ld.shared.v4.b32 {%0,%1,%2,%3}, [%4];"
                 : "=r"(v[0]), "=r"(v[1]), "=r"(v[2]), "=r"(v[3]) : "r"(addr) : "memory");
}
__device__ __forceinline__ uint32_t lds32(uint32_t addr) {
    uint32_t v; asm volatile("ld.shared.b32 %0, [%1];" : "=r"(v) : "r"(addr) : "memory"); return v;
}
__device__ __forceinline__ void sts32(uint32_t addr, uint32_t v) {
    asm volatile("st.shared.b32 [%0], %1;" ::"r"(addr), "r"(v) : "memory");
}

__device__ __forceinline__ uint32_t bf2_fma(uint32_t a, uint32_t b, uint32_t c) {
    uint32_t d; asm("fma.rn.bf16x2 %0, %1, %2, %3;" : "=r"(d) : "r"(a), "r"(b), "r"(c)); return d;
}
__device__ __forceinline__ uint32_t bf2_mul(uint32_t a, uint32_t b) {
    uint32_t d; asm("mul.rn.bf16x2 %0, %1, %2;" : "=r"(d) : "r"(a), "r"(b)); return d;
}
__device__ __forceinline__ uint32_t bf2_add(uint32_t a, uint32_t b) {
    uint32_t d; asm("add.rn.bf16x2 %0, %1, %2;" : "=r"(d) : "r"(a), "r"(b)); return d;
}
__device__ __forceinline__ uint32_t h2_fma(uint32_t a, uint32_t b, uint32_t c) {
    uint32_t d; asm("fma.rn.f16x2 %0, %1, %2, %3;" : "=r"(d) : "r"(a), "r"(b), "r"(c)); return d;
}
__device__ __forceinline__ uint32_t h2_mul(uint32_t a, uint32_t b) {
    uint32_t d; asm("mul.rn.f16x2 %0, %1, %2;" : "=r"(d) : "r"(a), "r"(b)); return d;
}
__device__ __forceinline__ uint32_t h2_tanh(uint32_t a) {
    uint32_t d; asm("tanh.approx.f16x2 %0, %1;" : "=r"(d) : "r"(a)); return d;
}
__device__ __forceinline__ float bf_lo(uint32_t v) { return __uint_as_float(v << 16); }
__device__ __forceinline__ float bf_hi(uint32_t v) { return __uint_as_float(v & 0xffff0000u); }
__device__ __forceinline__ uint32_t pack_h2(float lo, float hi) {
    uint32_t d; asm("cvt.rn.f16x2.f32 %0, %1, %2;" : "=r"(d) : "f"(hi), "f"(lo)); return d;
}
__device__ __forceinline__ uint32_t pack_bf2(float lo, float hi) {
    uint32_t d; asm("cvt.rn.bf16x2.f32 %0, %1, %2;" : "=r"(d) : "f"(hi), "f"(lo)); return d;
}
__device__ __forceinline__ void h2_unpack(uint32_t v, float& lo, float& hi) {
    asm("{\n.reg .b16 l, h;\nmov.b32 {l, h}, %2;\ncvt.f32.f16 %0, l;\ncvt.f32.f16 %1, h;\n}\n" : "=f"(lo), "=f"(hi) : "r"(v));
}

__device__ __forceinline__ uint32_t gelu2(uint32_t z) {
    uint32_t p = h2_fma(z, z, GELU_C_H2);
    uint32_t t = h2_tanh(h2_mul(z, p));
    return h2_fma(z, t, z);
}

__device__ __forceinline__ void wg_fence() { asm volatile("wgmma.fence.sync.aligned;" ::: "memory"); }
__device__ __forceinline__ void wg_commit() { asm volatile("wgmma.commit_group.sync.aligned;" ::: "memory"); }
template <int N> __device__ __forceinline__ void wg_wait() {
    asm volatile("wgmma.wait_group.sync.aligned %0;" ::"n"(N) : "memory");
}
template <int N> __device__ __forceinline__ void pin(uint32_t (&r)[N]) {
#pragma unroll
    for (int i = 0; i < N; i++) asm volatile("" : "+r"(r[i])::"memory");
}
constexpr uint32_t desc_lo(uint32_t addr, uint32_t lbo) { return ((addr & 0x3FFFF) >> 4) | ((lbo >> 4) << 16); }
template <uint32_t SBO, uint32_t SWZ> __device__ __forceinline__ uint64_t desc(uint32_t lo, uint32_t bytes) {
    return (((uint64_t)((SBO >> 4) | (SWZ << 30)) << 32) | lo) + (bytes >> 4);
}
__device__ __forceinline__ uint32_t fresh_tid() {
    uint32_t v; asm volatile("mov.u32 %0, %%tid.x;" : "=r"(v));
    return v;
}
template <uint32_t V> __device__ __forceinline__ uint32_t loop_init() {
    uint32_t v; asm volatile("mov.u32 %0, %1;" : "=r"(v) : "n"(V)); return v;
}
__device__ __forceinline__ int fresh_warp() {
    int v; asm volatile("shfl.sync.idx.b32 %0, %1, 0, 0x1f, 0xffffffff;" : "=r"(v) : "r"(fresh_tid() >> 5)); return v;
}
__device__ __forceinline__ uint32_t fresh_cta() {
    uint32_t v; asm volatile("mov.u32 %0, %%ctaid.x;" : "=r"(v)); return v;
}
__device__ __forceinline__ float sqrt_fast(float v) { float r; asm("sqrt.approx.f32 %0, %1;" : "=f"(r) : "f"(v)); return r; }

template <int TB>
__device__ __forceinline__ void wgmma_n64_h_set(uint32_t (&d)[16], const uint32_t* a, uint64_t desc) {
    asm volatile(
        "{\n.reg .pred p;\nsetp.ne.b32 p, 0, 0;\n"
        "wgmma.mma_async.sync.aligned.m64n64k16.f16.f16.f16 "
        "{%0,%1,%2,%3,%4,%5,%6,%7,%8,%9,%10,%11,%12,%13,%14,%15}, {%16,%17,%18,%19}, %20, p, 1, 1, %21;\n}\n"
        : "=r"(d[0]), "=r"(d[1]), "=r"(d[2]), "=r"(d[3]), "=r"(d[4]), "=r"(d[5]), "=r"(d[6]), "=r"(d[7]), "=r"(d[8]), "=r"(d[9]), "=r"(d[10]), "=r"(d[11]), "=r"(d[12]), "=r"(d[13]), "=r"(d[14]), "=r"(d[15])
        : "r"(a[0]), "r"(a[1]), "r"(a[2]), "r"(a[3]), "l"(desc), "n"(TB));
}
template <int TB>
__device__ __forceinline__ void wgmma_n64_h_acc(uint32_t (&d)[16], const uint32_t* a, uint64_t desc) {
    asm volatile(
        "{\n.reg .pred p;\nsetp.ne.b32 p, 1, 0;\n"
        "wgmma.mma_async.sync.aligned.m64n64k16.f16.f16.f16 "
        "{%0,%1,%2,%3,%4,%5,%6,%7,%8,%9,%10,%11,%12,%13,%14,%15}, {%16,%17,%18,%19}, %20, p, 1, 1, %21;\n}\n"
        : "+r"(d[0]), "+r"(d[1]), "+r"(d[2]), "+r"(d[3]), "+r"(d[4]), "+r"(d[5]), "+r"(d[6]), "+r"(d[7]), "+r"(d[8]), "+r"(d[9]), "+r"(d[10]), "+r"(d[11]), "+r"(d[12]), "+r"(d[13]), "+r"(d[14]), "+r"(d[15])
        : "r"(a[0]), "r"(a[1]), "r"(a[2]), "r"(a[3]), "l"(desc), "n"(TB));
}
__device__ __forceinline__ void wgmma_n64_h_acc_ss(uint32_t (&d)[16], uint64_t adesc, uint64_t desc) {
    asm volatile(
        "{\n.reg .pred p;\nsetp.ne.b32 p, 1, 0;\n"
        "wgmma.mma_async.sync.aligned.m64n64k16.f16.f16.f16 "
        "{%0,%1,%2,%3,%4,%5,%6,%7,%8,%9,%10,%11,%12,%13,%14,%15}, %16, %17, p, 1, 1, 1, 0;\n}\n"
        : "+r"(d[0]), "+r"(d[1]), "+r"(d[2]), "+r"(d[3]), "+r"(d[4]), "+r"(d[5]), "+r"(d[6]), "+r"(d[7]), "+r"(d[8]), "+r"(d[9]), "+r"(d[10]), "+r"(d[11]), "+r"(d[12]), "+r"(d[13]), "+r"(d[14]), "+r"(d[15])
        : "l"(adesc), "l"(desc));
}

struct Params {
    CUtensorMap w1_map, w2_map;
    const __nv_bfloat16* x;
    const __nv_bfloat16* dw;
    const __nv_bfloat16* w1;
    const __nv_bfloat16* gamma;
    const __nv_bfloat16* beta;
    __nv_bfloat16* out;
    Scratch* g;
    uint64_t ydesc64[2];
    uint64_t sel[3];
    uint32_t w1desc, w2desc, ydesc;
};

__device__ __forceinline__ int cta_stride(uint32_t cta) { return cta & 8 ? ROW_BYTES : -ROW_BYTES; }
__device__ __forceinline__ uint32_t cta_tile0(uint32_t cta) {
    return ((cta >> 3) * ROWS_PER_CTA + (cta & 8 ? 0 : ROWS_PER_CTA - 1)) * ROW_BYTES + (cta & 7) * TILE_BYTES;
}

struct Producer {
    uint32_t w[9][6];
    uint32_t xoff[2];
    uint32_t yoff[2][2];
    uint32_t stat, own;
    int lane;
};

struct RowCopy {
    const char* x0;
    char* y0;
    const char* zeros;
    uint32_t cut0, cut1;
    int stride, last;
};
__device__ __forceinline__ RowCopy row_copy(const Params& prm) {
    const uint32_t cta = fresh_cta(), strip = cta & 7, t0 = cta_tile0(cta);
    RowCopy r;
    r.stride = cta_stride(cta);
    r.x0 = (const char*)prm.x + (t0 - r.stride) - 192;
    r.y0 = (char*)prm.out + t0;
    r.zeros = (const char*)prm.g->zero_row;
    r.cut0 = strip == 0 ? 192 : 0;
    r.cut1 = strip == 7 ? 192 : 0;
    r.last = cta - 8 >= NUM_CTAS - 16 ? STEPS - 2 : STEPS - 1;
    return r;
}
__device__ __forceinline__ void issue_row_load(const RowCopy& r, int i, uint32_t slot) {
    const char* src = r.x0 + i * r.stride;
    const uint32_t bar = sb + SM_GO + i * 8, dst = sb + SM_X + slot * SLOT_BYTES;
    expect_tx(bar, XHALF_BYTES - r.cut0);
    bulk_load(dst + r.cut0, src + r.cut0, XHALF_BYTES - r.cut0, bar);
    expect_tx(bar, XHALF_BYTES - r.cut1);
    bulk_load(dst + XHALF_B, src + 32 * 192, XHALF_BYTES - r.cut1, bar);
}

__device__ __forceinline__ float quad_sum(float v) {
    v += __shfl_xor_sync(0xffffffffu, v, 1);
    v += __shfl_xor_sync(0xffffffffu, v, 2);
    return v;
}

__device__ __forceinline__ void load_x(uint32_t (&v)[6][6], const Producer& c, uint32_t row) {
#pragma unroll
    for (int k = 0; k < 6; k++) {
        asm volatile("ld.shared.v4.b32 {%0,%1,%2,%3}, [%4];"
                     : "=r"(v[k][0]), "=r"(v[k][1]), "=r"(v[k][2]), "=r"(v[k][3]) : "r"(row + c.xoff[0] + k * 192));
        asm volatile("ld.shared.v2.b32 {%0,%1}, [%2];" : "=r"(v[k][4]), "=r"(v[k][5]) : "r"(row + c.xoff[1] + k * 192));
    }
}
template <int DY, int STRIDE>
__device__ __forceinline__ void conv_row(uint32_t (&dst)[24], const uint32_t* src, const uint32_t (&v)[6][6], const Producer& c) {
#pragma unroll
    for (int o = 0; o < 4; o++)
#pragma unroll
        for (int u = 0; u < 6; u++)
            dst[o * 6 + u] = bf2_fma(v[o + 2][u], c.w[3 * DY + 2][u], bf2_fma(v[o + 1][u], c.w[3 * DY + 1][u],
                             bf2_fma(v[o][u], c.w[3 * DY][u], STRIDE ? src[o * 6 + u] : src[2 * o + 1])));
}
#define HAND_OVER(name, base, r) asm volatile("mov.b32 " name "%6, %0; mov.b32 " name "%7, %1; mov.b32 " name "%8, %2;\n" \
    "mov.b32 " name "%9, %3; mov.b32 " name "%10, %4; mov.b32 " name "%11, %5;" ::"r"((r)[0]), "r"((r)[1]), "r"((r)[2]), \
    "r"((r)[3]), "r"((r)[4]), "r"((r)[5]), "n"(base), "n"(base + 1), "n"(base + 2), "n"(base + 3), "n"(base + 4), "n"(base + 5))
template <int K> __device__ __forceinline__ void hand_over(const Producer& c, const uint32_t (&B)[24], const uint32_t (&C)[24],
                                                           const uint32_t (&v)[6][6]) {
    HAND_OVER("pw", K * 6, c.w[K]);
    if (K < 6) HAND_OVER("pv", K * 6, v[K % 6]);
    if (K < 4) { HAND_OVER("pb", K * 6, B + K % 4 * 6); HAND_OVER("pc", K * 6, C + K % 4 * 6); }
    if constexpr (K < 8) hand_over<K + 1>(c, B, C, v);
}
__device__ __forceinline__ void produce_tiles(const Producer& c, const Params& prm) {
    asm volatile(
        "{\n"
        ".reg .b32 pa<24>, pq<4>, m<6>, y<6>, rr, mm, t, so, ad, tt, cnt;\n"
        ".reg .b16 xl, xh;\n"
        ".reg .f32 d<4>, us, s0, s1, f0, f1, kq;\n"
        ".reg .pred pt, pf, pr, pw, pl, po, pe;\n"
        "setp.ne.b32 pt, 1, 0; setp.ne.b32 pf, 0, 0; setp.eq.u32 pl, %8, 0; and.b32 tt, %8, 1; setp.ne.u32 po, tt, 0;\n"
        "and.b32 tt, %8, 4; setp.ne.u32 pr, tt, 0; selp.f32 kq, 0f3F802D41, 0f3F7FA57E, pr;\n"
        "mov.u32 t, 0; mov.u32 so, 0;\n"
        "setp.eq.u32 pr, %12, 0;\n"
        "@pr bra.uni RARE;\n"
        "LOOP:\n"
        ASM_TRC("t")
        "fma.rn.bf16x2 pa0, pv0, pw36, pb0; fma.rn.bf16x2 pa1, pv1, pw37, pb1; fma.rn.bf16x2 pa2, pv2, pw38, pb2; fma.rn.bf16x2 pa3, pv3, pw39, pb3; fma.rn.bf16x2 pa4, pv4, pw40, pb4; fma.rn.bf16x2 pa5, pv5, pw41, pb5;\n"
        "fma.rn.bf16x2 pa6, pv6, pw36, pb6; fma.rn.bf16x2 pa7, pv7, pw37, pb7; fma.rn.bf16x2 pa8, pv8, pw38, pb8; fma.rn.bf16x2 pa9, pv9, pw39, pb9; fma.rn.bf16x2 pa10, pv10, pw40, pb10; fma.rn.bf16x2 pa11, pv11, pw41, pb11;\n"
        "fma.rn.bf16x2 pa12, pv12, pw36, pb12; fma.rn.bf16x2 pa13, pv13, pw37, pb13; fma.rn.bf16x2 pa14, pv14, pw38, pb14; fma.rn.bf16x2 pa15, pv15, pw39, pb15; fma.rn.bf16x2 pa16, pv16, pw40, pb16; fma.rn.bf16x2 pa17, pv17, pw41, pb17;\n"
        "fma.rn.bf16x2 pa18, pv18, pw36, pb18; fma.rn.bf16x2 pa19, pv19, pw37, pb19; fma.rn.bf16x2 pa20, pv20, pw38, pb20; fma.rn.bf16x2 pa21, pv21, pw39, pb21; fma.rn.bf16x2 pa22, pv22, pw40, pb22; fma.rn.bf16x2 pa23, pv23, pw41, pb23;\n"
        "fma.rn.bf16x2 pa0, pv6, pw42, pa0; fma.rn.bf16x2 pa1, pv7, pw43, pa1; fma.rn.bf16x2 pa2, pv8, pw44, pa2; fma.rn.bf16x2 pa3, pv9, pw45, pa3; fma.rn.bf16x2 pa4, pv10, pw46, pa4; fma.rn.bf16x2 pa5, pv11, pw47, pa5;\n"
        "fma.rn.bf16x2 pa6, pv12, pw42, pa6; fma.rn.bf16x2 pa7, pv13, pw43, pa7; fma.rn.bf16x2 pa8, pv14, pw44, pa8; fma.rn.bf16x2 pa9, pv15, pw45, pa9; fma.rn.bf16x2 pa10, pv16, pw46, pa10; fma.rn.bf16x2 pa11, pv17, pw47, pa11;\n"
        "fma.rn.bf16x2 pa12, pv18, pw42, pa12; fma.rn.bf16x2 pa13, pv19, pw43, pa13; fma.rn.bf16x2 pa14, pv20, pw44, pa14; fma.rn.bf16x2 pa15, pv21, pw45, pa15; fma.rn.bf16x2 pa16, pv22, pw46, pa16; fma.rn.bf16x2 pa17, pv23, pw47, pa17;\n"
        "fma.rn.bf16x2 pa18, pv24, pw42, pa18; fma.rn.bf16x2 pa19, pv25, pw43, pa19; fma.rn.bf16x2 pa20, pv26, pw44, pa20; fma.rn.bf16x2 pa21, pv27, pw45, pa21; fma.rn.bf16x2 pa22, pv28, pw46, pa22; fma.rn.bf16x2 pa23, pv29, pw47, pa23;\n"
        "fma.rn.bf16x2 pa0, pv12, pw48, pa0; fma.rn.bf16x2 pa1, pv13, pw49, pa1; fma.rn.bf16x2 pa2, pv14, pw50, pa2; fma.rn.bf16x2 pa3, pv15, pw51, pa3; fma.rn.bf16x2 pa4, pv16, pw52, pa4; fma.rn.bf16x2 pa5, pv17, pw53, pa5;\n"
        "fma.rn.bf16x2 pa6, pv18, pw48, pa6; fma.rn.bf16x2 pa7, pv19, pw49, pa7; fma.rn.bf16x2 pa8, pv20, pw50, pa8; fma.rn.bf16x2 pa9, pv21, pw51, pa9; fma.rn.bf16x2 pa10, pv22, pw52, pa10; fma.rn.bf16x2 pa11, pv23, pw53, pa11;\n"
        "fma.rn.bf16x2 pa12, pv24, pw48, pa12; fma.rn.bf16x2 pa13, pv25, pw49, pa13; fma.rn.bf16x2 pa14, pv26, pw50, pa14; fma.rn.bf16x2 pa15, pv27, pw51, pa15; fma.rn.bf16x2 pa16, pv28, pw52, pa16; fma.rn.bf16x2 pa17, pv29, pw53, pa17;\n"
        "fma.rn.bf16x2 pa18, pv30, pw48, pa18; fma.rn.bf16x2 pa19, pv31, pw49, pa19; fma.rn.bf16x2 pa20, pv32, pw50, pa20; fma.rn.bf16x2 pa21, pv33, pw51, pa21; fma.rn.bf16x2 pa22, pv34, pw52, pa22; fma.rn.bf16x2 pa23, pv35, pw53, pa23;\n"
        "mul.rn.bf16x2 pq0, pa0, pa0; fma.rn.bf16x2 pq0, pa1, pa1, pq0; fma.rn.bf16x2 pq0, pa2, pa2, pq0; fma.rn.bf16x2 pq0, pa3, pa3, pq0; fma.rn.bf16x2 pq0, pa4, pa4, pq0; fma.rn.bf16x2 pq0, pa5, pa5, pq0;\n"
        "mul.rn.bf16x2 pq1, pa6, pa6; fma.rn.bf16x2 pq1, pa7, pa7, pq1; fma.rn.bf16x2 pq1, pa8, pa8, pq1; fma.rn.bf16x2 pq1, pa9, pa9, pq1; fma.rn.bf16x2 pq1, pa10, pa10, pq1; fma.rn.bf16x2 pq1, pa11, pa11, pq1;\n"
        "mul.rn.bf16x2 pq2, pa12, pa12; fma.rn.bf16x2 pq2, pa13, pa13, pq2; fma.rn.bf16x2 pq2, pa14, pa14, pq2; fma.rn.bf16x2 pq2, pa15, pa15, pq2; fma.rn.bf16x2 pq2, pa16, pa16, pq2; fma.rn.bf16x2 pq2, pa17, pa17, pq2;\n"
        "mul.rn.bf16x2 pq3, pa18, pa18; fma.rn.bf16x2 pq3, pa19, pa19, pq3; fma.rn.bf16x2 pq3, pa20, pa20, pq3; fma.rn.bf16x2 pq3, pa21, pa21, pq3; fma.rn.bf16x2 pq3, pa22, pa22, pq3; fma.rn.bf16x2 pq3, pa23, pa23, pq3;\n"
        "B0:\n"
        "wgmma.fence.sync.aligned;\n"
        "wgmma.mma_async.sync.aligned.m64n8k16.f32.bf16.bf16 {d0,d1,d2,d3}, {pa0,pa6,pa1,pa7}, %9, pf, 1, 1, 0;\n"
        "wgmma.mma_async.sync.aligned.m64n8k16.f32.bf16.bf16 {d0,d1,d2,d3}, {pa2,pa8,pa3,pa9}, %9, pt, 1, 1, 0;\n"
        "wgmma.mma_async.sync.aligned.m64n8k16.f32.bf16.bf16 {d0,d1,d2,d3}, {pa4,pa10,pa5,pa11}, %9, pt, 1, 1, 0;\n"
        "wgmma.mma_async.sync.aligned.m64n8k16.f32.bf16.bf16 {d0,d1,d2,d3}, {pa12,pa18,pa13,pa19}, %10, pt, 1, 1, 0;\n"
        "wgmma.mma_async.sync.aligned.m64n8k16.f32.bf16.bf16 {d0,d1,d2,d3}, {pa14,pa20,pa15,pa21}, %10, pt, 1, 1, 0;\n"
        "wgmma.mma_async.sync.aligned.m64n8k16.f32.bf16.bf16 {d0,d1,d2,d3}, {pa16,pa22,pa17,pa23}, %10, pt, 1, 1, 0;\n"
        "wgmma.mma_async.sync.aligned.m64n8k16.f32.bf16.bf16 {d0,d1,d2,d3}, {pq0,pq1,pq2,pq3}, %11, pt, 1, 1, 0;\n"
        "wgmma.commit_group.sync.aligned;\n"
        "fence.proxy.async.shared::cta;\n"
        "@pl mbarrier.arrive.shared::cta.b64 _, [t+231544];\n"
        "add.u32 ad, %7, so; ld.shared.f32 us, [ad+4];\n"
        "fma.rn.bf16x2 pb0, pv0, pw18, pc0; fma.rn.bf16x2 pb1, pv1, pw19, pc1; fma.rn.bf16x2 pb2, pv2, pw20, pc2; fma.rn.bf16x2 pb3, pv3, pw21, pc3; fma.rn.bf16x2 pb4, pv4, pw22, pc4; fma.rn.bf16x2 pb5, pv5, pw23, pc5;\n"
        "fma.rn.bf16x2 pb6, pv6, pw18, pc6; fma.rn.bf16x2 pb7, pv7, pw19, pc7; fma.rn.bf16x2 pb8, pv8, pw20, pc8; fma.rn.bf16x2 pb9, pv9, pw21, pc9; fma.rn.bf16x2 pb10, pv10, pw22, pc10; fma.rn.bf16x2 pb11, pv11, pw23, pc11;\n"
        "fma.rn.bf16x2 pb0, pv6, pw24, pb0; fma.rn.bf16x2 pb1, pv7, pw25, pb1; fma.rn.bf16x2 pb2, pv8, pw26, pb2; fma.rn.bf16x2 pb3, pv9, pw27, pb3; fma.rn.bf16x2 pb4, pv10, pw28, pb4; fma.rn.bf16x2 pb5, pv11, pw29, pb5;\n"
        "fma.rn.bf16x2 pb6, pv12, pw24, pb6; fma.rn.bf16x2 pb7, pv13, pw25, pb7; fma.rn.bf16x2 pb8, pv14, pw26, pb8; fma.rn.bf16x2 pb9, pv15, pw27, pb9; fma.rn.bf16x2 pb10, pv16, pw28, pb10; fma.rn.bf16x2 pb11, pv17, pw29, pb11;\n"
        "fma.rn.bf16x2 pb0, pv12, pw30, pb0; fma.rn.bf16x2 pb1, pv13, pw31, pb1; fma.rn.bf16x2 pb2, pv14, pw32, pb2; fma.rn.bf16x2 pb3, pv15, pw33, pb3; fma.rn.bf16x2 pb4, pv16, pw34, pb4; fma.rn.bf16x2 pb5, pv17, pw35, pb5;\n"
        "fma.rn.bf16x2 pb6, pv18, pw30, pb6; fma.rn.bf16x2 pb7, pv19, pw31, pb7; fma.rn.bf16x2 pb8, pv20, pw32, pb8; fma.rn.bf16x2 pb9, pv21, pw33, pb9; fma.rn.bf16x2 pb10, pv22, pw34, pb10; fma.rn.bf16x2 pb11, pv23, pw35, pb11;\n"
        "B1:\n"
        "fma.rn.bf16x2 pb12, pv12, pw18, pc12; fma.rn.bf16x2 pb13, pv13, pw19, pc13; fma.rn.bf16x2 pb14, pv14, pw20, pc14; fma.rn.bf16x2 pb15, pv15, pw21, pc15; fma.rn.bf16x2 pb16, pv16, pw22, pc16; fma.rn.bf16x2 pb17, pv17, pw23, pc17;\n"
        "fma.rn.bf16x2 pb18, pv18, pw18, pc18; fma.rn.bf16x2 pb19, pv19, pw19, pc19; fma.rn.bf16x2 pb20, pv20, pw20, pc20; fma.rn.bf16x2 pb21, pv21, pw21, pc21; fma.rn.bf16x2 pb22, pv22, pw22, pc22; fma.rn.bf16x2 pb23, pv23, pw23, pc23;\n"
        "fma.rn.bf16x2 pb12, pv18, pw24, pb12; fma.rn.bf16x2 pb13, pv19, pw25, pb13; fma.rn.bf16x2 pb14, pv20, pw26, pb14; fma.rn.bf16x2 pb15, pv21, pw27, pb15; fma.rn.bf16x2 pb16, pv22, pw28, pb16; fma.rn.bf16x2 pb17, pv23, pw29, pb17;\n"
        "fma.rn.bf16x2 pb18, pv24, pw24, pb18; fma.rn.bf16x2 pb19, pv25, pw25, pb19; fma.rn.bf16x2 pb20, pv26, pw26, pb20; fma.rn.bf16x2 pb21, pv27, pw27, pb21; fma.rn.bf16x2 pb22, pv28, pw28, pb22; fma.rn.bf16x2 pb23, pv29, pw29, pb23;\n"
        "fma.rn.bf16x2 pb12, pv24, pw30, pb12; fma.rn.bf16x2 pb13, pv25, pw31, pb13; fma.rn.bf16x2 pb14, pv26, pw32, pb14; fma.rn.bf16x2 pb15, pv27, pw33, pb15; fma.rn.bf16x2 pb16, pv28, pw34, pb16; fma.rn.bf16x2 pb17, pv29, pw35, pb17;\n"
        "fma.rn.bf16x2 pb18, pv30, pw30, pb18; fma.rn.bf16x2 pb19, pv31, pw31, pb19; fma.rn.bf16x2 pb20, pv32, pw32, pb20; fma.rn.bf16x2 pb21, pv33, pw33, pb21; fma.rn.bf16x2 pb22, pv34, pw34, pb22; fma.rn.bf16x2 pb23, pv35, pw35, pb23;\n"
        "C0:\n"
        "wgmma.wait_group.sync.aligned 0;\n"
        "selp.f32 s0, d2, d0, po; selp.f32 s1, d3, d1, po;\n"
        "shfl.sync.bfly.b32 f0, s0, 4, 0x1f, 0xffffffff; shfl.sync.bfly.b32 f1, s1, 4, 0x1f, 0xffffffff;\n"
        "fma.rn.bf16x2 pc0, pv0, pw0, ps1; fma.rn.bf16x2 pc1, pv1, pw1, ps1; fma.rn.bf16x2 pc2, pv2, pw2, ps1; fma.rn.bf16x2 pc3, pv3, pw3, ps1; fma.rn.bf16x2 pc4, pv4, pw4, ps1; fma.rn.bf16x2 pc5, pv5, pw5, ps1;\n"
        "fma.rn.bf16x2 pc6, pv6, pw0, ps3; fma.rn.bf16x2 pc7, pv7, pw1, ps3; fma.rn.bf16x2 pc8, pv8, pw2, ps3; fma.rn.bf16x2 pc9, pv9, pw3, ps3; fma.rn.bf16x2 pc10, pv10, pw4, ps3; fma.rn.bf16x2 pc11, pv11, pw5, ps3;\n"
        "fma.rn.bf16x2 pc12, pv12, pw0, ps5; fma.rn.bf16x2 pc13, pv13, pw1, ps5; fma.rn.bf16x2 pc14, pv14, pw2, ps5; fma.rn.bf16x2 pc15, pv15, pw3, ps5; fma.rn.bf16x2 pc16, pv16, pw4, ps5; fma.rn.bf16x2 pc17, pv17, pw5, ps5;\n"
        "fma.rn.bf16x2 pc18, pv18, pw0, ps7; fma.rn.bf16x2 pc19, pv19, pw1, ps7; fma.rn.bf16x2 pc20, pv20, pw2, ps7; fma.rn.bf16x2 pc21, pv21, pw3, ps7; fma.rn.bf16x2 pc22, pv22, pw4, ps7; fma.rn.bf16x2 pc23, pv23, pw5, ps7;\n"
        "fma.rn.bf16x2 pc0, pv6, pw6, pc0; fma.rn.bf16x2 pc1, pv7, pw7, pc1; fma.rn.bf16x2 pc2, pv8, pw8, pc2; fma.rn.bf16x2 pc3, pv9, pw9, pc3; fma.rn.bf16x2 pc4, pv10, pw10, pc4; fma.rn.bf16x2 pc5, pv11, pw11, pc5;\n"
        "fma.rn.bf16x2 pc6, pv12, pw6, pc6; fma.rn.bf16x2 pc7, pv13, pw7, pc7; fma.rn.bf16x2 pc8, pv14, pw8, pc8; fma.rn.bf16x2 pc9, pv15, pw9, pc9; fma.rn.bf16x2 pc10, pv16, pw10, pc10; fma.rn.bf16x2 pc11, pv17, pw11, pc11;\n"
        "fma.rn.bf16x2 pc12, pv18, pw6, pc12; fma.rn.bf16x2 pc13, pv19, pw7, pc13; fma.rn.bf16x2 pc14, pv20, pw8, pc14; fma.rn.bf16x2 pc15, pv21, pw9, pc15; fma.rn.bf16x2 pc16, pv22, pw10, pc16; fma.rn.bf16x2 pc17, pv23, pw11, pc17;\n"
        "fma.rn.bf16x2 pc18, pv24, pw6, pc18; fma.rn.bf16x2 pc19, pv25, pw7, pc19; fma.rn.bf16x2 pc20, pv26, pw8, pc20; fma.rn.bf16x2 pc21, pv27, pw9, pc21; fma.rn.bf16x2 pc22, pv28, pw10, pc22; fma.rn.bf16x2 pc23, pv29, pw11, pc23;\n"
        "fma.rn.bf16x2 pc0, pv12, pw12, pc0; fma.rn.bf16x2 pc1, pv13, pw13, pc1; fma.rn.bf16x2 pc2, pv14, pw14, pc2; fma.rn.bf16x2 pc3, pv15, pw15, pc3; fma.rn.bf16x2 pc4, pv16, pw16, pc4; fma.rn.bf16x2 pc5, pv17, pw17, pc5;\n"
        "fma.rn.bf16x2 pc6, pv18, pw12, pc6; fma.rn.bf16x2 pc7, pv19, pw13, pc7; fma.rn.bf16x2 pc8, pv20, pw14, pc8; fma.rn.bf16x2 pc9, pv21, pw15, pc9; fma.rn.bf16x2 pc10, pv22, pw16, pc10; fma.rn.bf16x2 pc11, pv23, pw17, pc11;\n"
        "fma.rn.bf16x2 pc12, pv24, pw12, pc12; fma.rn.bf16x2 pc13, pv25, pw13, pc13; fma.rn.bf16x2 pc14, pv26, pw14, pc14; fma.rn.bf16x2 pc15, pv27, pw15, pc15; fma.rn.bf16x2 pc16, pv28, pw16, pc16; fma.rn.bf16x2 pc17, pv29, pw17, pc17;\n"
        "fma.rn.bf16x2 pc18, pv30, pw12, pc18; fma.rn.bf16x2 pc19, pv31, pw13, pc19; fma.rn.bf16x2 pc20, pv32, pw14, pc20; fma.rn.bf16x2 pc21, pv33, pw15, pc21; fma.rn.bf16x2 pc22, pv34, pw16, pc22; fma.rn.bf16x2 pc23, pv35, pw17, pc23;\n"
        "add.f32 s0, s0, f0; add.f32 s1, s1, f1; mul.f32 s0, s0, 0fBC2AAAAB;\n"
        "neg.f32 f0, s0; fma.rn.f32 f0, f0, s0, %13; fma.rn.f32 f0, s1, 0f3C2AAAAB, f0; max.f32 f0, f0, %13;\n"
        "rsqrt.approx.ftz.f32 f0, f0; mul.f32 f0, f0, %14; cvt.rn.bf16x2.f32 tt, f0, 0f00000000; mov.b32 f0, tt;\n"
        "mul.f32 f1, s0, kq; mul.f32 f1, f1, f0; cvt.rn.bf16x2.f32 tt, f1, f0; add.f32 us, us, s0; cvt.rn.bf16x2.f32 mm, us, us;\n"
        "add.u32 ad, %7, so; st.shared.v2.b32 [ad], {tt, mm};\n"
        "add.u32 ad, %6, so; ld.shared.v4.b32 {ps0,ps1,ps2,ps3}, [ad]; ld.shared.v4.b32 {ps4,ps5,ps6,ps7}, [ad+16];\n"
        "mbarrier.try_wait.parity.shared::cta.b64 pw, [t+231264], 0;\n"
        "N0:\n"
        "@!pw bra.uni SPIN;\n"
        "BACK:\n"
        "add.u32 ad, %0, so; ld.shared.v4.b32 {pv0,pv1,pv2,pv3}, [ad+0];\n"
        "add.u32 ad, %1, so; ld.shared.v2.b32 {pv4,pv5}, [ad+0];\n"
        "add.u32 ad, %0, so; ld.shared.v4.b32 {pv6,pv7,pv8,pv9}, [ad+192];\n"
        "add.u32 ad, %1, so; ld.shared.v2.b32 {pv10,pv11}, [ad+192];\n"
        "mov.b32 {xl, xh}, ps0; mov.b32 rr, {xl, xl}; mov.b32 mm, {xh, xh}; fma.rn.bf16x2 pa0, pa0, rr, mm; fma.rn.bf16x2 pa1, pa1, rr, mm; fma.rn.bf16x2 pa2, pa2, rr, mm; fma.rn.bf16x2 pa3, pa3, rr, mm; fma.rn.bf16x2 pa4, pa4, rr, mm; fma.rn.bf16x2 pa5, pa5, rr, mm;\n"
        "and.b32 m0, pa0, 0x7fff7fff; and.b32 m1, pa1, 0x7fff7fff; and.b32 m2, pa2, 0x7fff7fff; and.b32 m3, pa3, 0x7fff7fff; and.b32 m4, pa4, 0x7fff7fff; and.b32 m5, pa5, 0x7fff7fff;\n"
        "mad.lo.u32 y0, m0, 7, pa0; mad.lo.u32 y1, m1, 7, pa1; mad.lo.u32 y2, m2, 7, pa2; mad.lo.u32 y3, m3, 7, pa3; mad.lo.u32 y4, m4, 7, pa4; mad.lo.u32 y5, m5, 7, pa5;\n"
        "add.u32 ad, %2, so; st.shared.v4.b32 [ad+0], {y0,y1,y2,y3};\n"
        "add.u32 ad, %4, so; st.shared.v2.b32 [ad+0], {y4,y5};\n"
        "N1:\n"
        "add.u32 ad, %0, so; ld.shared.v4.b32 {pv12,pv13,pv14,pv15}, [ad+384];\n"
        "add.u32 ad, %1, so; ld.shared.v2.b32 {pv16,pv17}, [ad+384];\n"
        "add.u32 ad, %0, so; ld.shared.v4.b32 {pv18,pv19,pv20,pv21}, [ad+576];\n"
        "add.u32 ad, %1, so; ld.shared.v2.b32 {pv22,pv23}, [ad+576];\n"
        "mov.b32 {xl, xh}, ps2; mov.b32 rr, {xl, xl}; mov.b32 mm, {xh, xh}; fma.rn.bf16x2 pa6, pa6, rr, mm; fma.rn.bf16x2 pa7, pa7, rr, mm; fma.rn.bf16x2 pa8, pa8, rr, mm; fma.rn.bf16x2 pa9, pa9, rr, mm; fma.rn.bf16x2 pa10, pa10, rr, mm; fma.rn.bf16x2 pa11, pa11, rr, mm;\n"
        "and.b32 m0, pa6, 0x7fff7fff; and.b32 m1, pa7, 0x7fff7fff; and.b32 m2, pa8, 0x7fff7fff; and.b32 m3, pa9, 0x7fff7fff; and.b32 m4, pa10, 0x7fff7fff; and.b32 m5, pa11, 0x7fff7fff;\n"
        "mad.lo.u32 y0, m0, 7, pa6; mad.lo.u32 y1, m1, 7, pa7; mad.lo.u32 y2, m2, 7, pa8; mad.lo.u32 y3, m3, 7, pa9; mad.lo.u32 y4, m4, 7, pa10; mad.lo.u32 y5, m5, 7, pa11;\n"
        "add.u32 ad, %3, so; st.shared.v4.b32 [ad+0], {y0,y1,y2,y3};\n"
        "add.u32 ad, %5, so; st.shared.v2.b32 [ad+0], {y4,y5};\n"
        "N2:\n"
        "add.u32 ad, %0, so; ld.shared.v4.b32 {pv24,pv25,pv26,pv27}, [ad+768];\n"
        "add.u32 ad, %1, so; ld.shared.v2.b32 {pv28,pv29}, [ad+768];\n"
        "mov.b32 {xl, xh}, ps4; mov.b32 rr, {xl, xl}; mov.b32 mm, {xh, xh}; fma.rn.bf16x2 pa12, pa12, rr, mm; fma.rn.bf16x2 pa13, pa13, rr, mm; fma.rn.bf16x2 pa14, pa14, rr, mm; fma.rn.bf16x2 pa15, pa15, rr, mm; fma.rn.bf16x2 pa16, pa16, rr, mm; fma.rn.bf16x2 pa17, pa17, rr, mm;\n"
        "and.b32 m0, pa12, 0x7fff7fff; and.b32 m1, pa13, 0x7fff7fff; and.b32 m2, pa14, 0x7fff7fff; and.b32 m3, pa15, 0x7fff7fff; and.b32 m4, pa16, 0x7fff7fff; and.b32 m5, pa17, 0x7fff7fff;\n"
        "mad.lo.u32 y0, m0, 7, pa12; mad.lo.u32 y1, m1, 7, pa13; mad.lo.u32 y2, m2, 7, pa14; mad.lo.u32 y3, m3, 7, pa15; mad.lo.u32 y4, m4, 7, pa16; mad.lo.u32 y5, m5, 7, pa17;\n"
        "add.u32 ad, %2, so; st.shared.v4.b32 [ad+2048], {y0,y1,y2,y3};\n"
        "add.u32 ad, %4, so; st.shared.v2.b32 [ad+1024], {y4,y5};\n"
        "N3:\n"
        "add.u32 ad, %0, so; ld.shared.v4.b32 {pv30,pv31,pv32,pv33}, [ad+960];\n"
        "add.u32 ad, %1, so; ld.shared.v2.b32 {pv34,pv35}, [ad+960];\n"
        "mov.b32 {xl, xh}, ps6; mov.b32 rr, {xl, xl}; mov.b32 mm, {xh, xh}; fma.rn.bf16x2 pa18, pa18, rr, mm; fma.rn.bf16x2 pa19, pa19, rr, mm; fma.rn.bf16x2 pa20, pa20, rr, mm; fma.rn.bf16x2 pa21, pa21, rr, mm; fma.rn.bf16x2 pa22, pa22, rr, mm; fma.rn.bf16x2 pa23, pa23, rr, mm;\n"
        "and.b32 m0, pa18, 0x7fff7fff; and.b32 m1, pa19, 0x7fff7fff; and.b32 m2, pa20, 0x7fff7fff; and.b32 m3, pa21, 0x7fff7fff; and.b32 m4, pa22, 0x7fff7fff; and.b32 m5, pa23, 0x7fff7fff;\n"
        "mad.lo.u32 y0, m0, 7, pa18; mad.lo.u32 y1, m1, 7, pa19; mad.lo.u32 y2, m2, 7, pa20; mad.lo.u32 y3, m3, 7, pa21; mad.lo.u32 y4, m4, 7, pa22; mad.lo.u32 y5, m5, 7, pa23;\n"
        "add.u32 ad, %3, so; st.shared.v4.b32 [ad+2048], {y0,y1,y2,y3};\n"
        "add.u32 ad, %5, so; st.shared.v2.b32 [ad+1024], {y4,y5};\n"
        "add.u32 so, so, 26624; setp.eq.u32 pr, so, 79872; selp.u32 so, 0, so, pr;\n"
        "add.u32 t, t, 8; setp.lt.u32 pe, t, 256;\n"
        "@pe bra.uni LOOP;\n"
        "bra.uni DONE;\n"
        "SPIN: mov.u32 cnt, 0;\n"
        "SPINL:\n"
        "mbarrier.try_wait.parity.shared::cta.b64 pw, [t+231264], 0;\n"
        "@pw bra.uni BACK;\n"
        "add.u32 cnt, cnt, 1; setp.lt.u32 pw, cnt, 0x100000;\n"
        "@pw bra.uni SPINL;\n"
        "trap;\n"
        "RARE:\n"
        "ld.volatile.shared.u32 tt, [%6];\n"
        "mov.b32 pa0, tt; mov.b32 pa1, tt; mov.b32 pa2, tt; mov.b32 pa3, tt; mov.b32 pa4, tt; mov.b32 pa5, tt; mov.b32 pa6, tt; mov.b32 pa7, tt; mov.b32 pa8, tt; mov.b32 pa9, tt; mov.b32 pa10, tt; mov.b32 pa11, tt;\n"
        "mov.b32 pa12, tt; mov.b32 pa13, tt; mov.b32 pa14, tt; mov.b32 pa15, tt; mov.b32 pa16, tt; mov.b32 pa17, tt; mov.b32 pa18, tt; mov.b32 pa19, tt; mov.b32 pa20, tt; mov.b32 pa21, tt; mov.b32 pa22, tt; mov.b32 pa23, tt;\n"
        "mov.b32 pb0, tt; mov.b32 pb1, tt; mov.b32 pb2, tt; mov.b32 pb3, tt; mov.b32 pb4, tt; mov.b32 pb5, tt; mov.b32 pb6, tt; mov.b32 pb7, tt; mov.b32 pb8, tt; mov.b32 pb9, tt; mov.b32 pb10, tt; mov.b32 pb11, tt;\n"
        "mov.b32 pb12, tt; mov.b32 pb13, tt; mov.b32 pb14, tt; mov.b32 pb15, tt; mov.b32 pb16, tt; mov.b32 pb17, tt; mov.b32 pb18, tt; mov.b32 pb19, tt; mov.b32 pb20, tt; mov.b32 pb21, tt; mov.b32 pb22, tt; mov.b32 pb23, tt;\n"
        "mov.b32 pc0, tt; mov.b32 pc1, tt; mov.b32 pc2, tt; mov.b32 pc3, tt; mov.b32 pc4, tt; mov.b32 pc5, tt; mov.b32 pc6, tt; mov.b32 pc7, tt; mov.b32 pc8, tt; mov.b32 pc9, tt; mov.b32 pc10, tt; mov.b32 pc11, tt;\n"
        "mov.b32 pc12, tt; mov.b32 pc13, tt; mov.b32 pc14, tt; mov.b32 pc15, tt; mov.b32 pc16, tt; mov.b32 pc17, tt; mov.b32 pc18, tt; mov.b32 pc19, tt; mov.b32 pc20, tt; mov.b32 pc21, tt; mov.b32 pc22, tt; mov.b32 pc23, tt;\n"
        "mov.b32 ps0, tt; mov.b32 ps1, tt; mov.b32 ps2, tt; mov.b32 ps3, tt; mov.b32 ps4, tt; mov.b32 ps5, tt; mov.b32 ps6, tt; mov.b32 ps7, tt; mov.b32 pq0, tt; mov.b32 pq1, tt; mov.b32 pq2, tt; mov.b32 pq3, tt;\n"
        "ld.volatile.shared.v2.b32 {pw1, pw0}, [%6]; xor.b32 tt, tt, pw1;\n"
        "ld.volatile.shared.v2.b32 {pw3, pw2}, [%6]; xor.b32 tt, tt, pw3;\n"
        "ld.volatile.shared.v2.b32 {pw5, pw4}, [%6]; xor.b32 tt, tt, pw5;\n"
        "ld.volatile.shared.v2.b32 {pw7, pw6}, [%6]; xor.b32 tt, tt, pw7;\n"
        "ld.volatile.shared.v2.b32 {pw9, pw8}, [%6]; xor.b32 tt, tt, pw9;\n"
        "ld.volatile.shared.v2.b32 {pw11, pw10}, [%6]; xor.b32 tt, tt, pw11;\n"
        "ld.volatile.shared.v2.b32 {pw13, pw12}, [%6]; xor.b32 tt, tt, pw13;\n"
        "ld.volatile.shared.v2.b32 {pw15, pw14}, [%6]; xor.b32 tt, tt, pw15;\n"
        "ld.volatile.shared.v2.b32 {pw17, pw16}, [%6]; xor.b32 tt, tt, pw17;\n"
        "ld.volatile.shared.v2.b32 {pw19, pw18}, [%6]; xor.b32 tt, tt, pw19;\n"
        "ld.volatile.shared.v2.b32 {pw21, pw20}, [%6]; xor.b32 tt, tt, pw21;\n"
        "ld.volatile.shared.v2.b32 {pw23, pw22}, [%6]; xor.b32 tt, tt, pw23;\n"
        "ld.volatile.shared.v2.b32 {pw25, pw24}, [%6]; xor.b32 tt, tt, pw25;\n"
        "ld.volatile.shared.v2.b32 {pw27, pw26}, [%6]; xor.b32 tt, tt, pw27;\n"
        "ld.volatile.shared.v2.b32 {pw29, pw28}, [%6]; xor.b32 tt, tt, pw29;\n"
        "ld.volatile.shared.v2.b32 {pw31, pw30}, [%6]; xor.b32 tt, tt, pw31;\n"
        "ld.volatile.shared.v2.b32 {pw33, pw32}, [%6]; xor.b32 tt, tt, pw33;\n"
        "ld.volatile.shared.v2.b32 {pw35, pw34}, [%6]; xor.b32 tt, tt, pw35;\n"
        "ld.volatile.shared.v2.b32 {pw37, pw36}, [%6]; xor.b32 tt, tt, pw37;\n"
        "ld.volatile.shared.v2.b32 {pw39, pw38}, [%6]; xor.b32 tt, tt, pw39;\n"
        "ld.volatile.shared.v2.b32 {pw41, pw40}, [%6]; xor.b32 tt, tt, pw41;\n"
        "ld.volatile.shared.v2.b32 {pw43, pw42}, [%6]; xor.b32 tt, tt, pw43;\n"
        "ld.volatile.shared.v2.b32 {pw45, pw44}, [%6]; xor.b32 tt, tt, pw45;\n"
        "ld.volatile.shared.v2.b32 {pw47, pw46}, [%6]; xor.b32 tt, tt, pw47;\n"
        "ld.volatile.shared.v2.b32 {pw49, pw48}, [%6]; xor.b32 tt, tt, pw49;\n"
        "ld.volatile.shared.v2.b32 {pw51, pw50}, [%6]; xor.b32 tt, tt, pw51;\n"
        "ld.volatile.shared.v2.b32 {pw53, pw52}, [%6]; xor.b32 tt, tt, pw53;\n"
        "mov.b32 us, tt; setp.ne.u32 pw, %15, 7;\n"
        "wgmma.fence.sync.aligned;\n"
        "setp.eq.u32 pr, %15, 1000; @pr bra.uni B0;\n"
        "setp.eq.u32 pr, %15, 1001; @pr bra.uni B1;\n"
        "setp.eq.u32 pr, %15, 1002; @pr bra.uni C0;\n"
        "setp.eq.u32 pr, %15, 1003; @pr bra.uni N0;\n"
        "setp.eq.u32 pr, %15, 1004; @pr bra.uni N1;\n"
        "setp.eq.u32 pr, %15, 1005; @pr bra.uni N2;\n"
        "setp.eq.u32 pr, %15, 1006; @pr bra.uni N3;\n"
        "trap;\n"
        "DONE:\n"
        ASM_TRC("t")
        "fence.proxy.async.shared::cta;\n"
        "@pl mbarrier.arrive.shared::cta.b64 _, [t+231544];\n"
        "}\n"
        :: "r"(sb + SM_X + c.xoff[0]), "r"(sb + SM_X + c.xoff[1]), "r"(sb + SM_Y1 + c.yoff[0][0]), "r"(sb + SM_Y1 + c.yoff[0][1]),
           "r"(sb + SM_Y1 + c.yoff[1][0]), "r"(sb + SM_Y1 + c.yoff[1][1]), "r"(c.stat), "r"(c.own), "r"(c.lane),
           "l"(prm.sel[0]), "l"(prm.sel[1]), "l"(prm.sel[2]), "r"(prm.ydesc), "f"(LN_EPS_SCALED), "f"(RSTD_SCALE), "r"(prm.w1desc)
        : "memory");
}

__device__ __forceinline__ void produce(const Producer& c, const Params& prm) {
    uint32_t B[24], C[24];
    uint32_t st[8];
    uint32_t v[6][6];
    uint32_t ws[6];
#pragma unroll
    for (int u = 0; u < 6; u++) {
        ws[u] = c.w[0][u];
#pragma unroll
        for (int t = 1; t < 9; t++) ws[u] = bf2_add(ws[u], c.w[t][u]);
    }
    SMARK(2);
#pragma unroll 1
    for (int i = loop_init<0>();; i++) {
        mbar_wait_c<0>(sb + SM_GO + i * 8);
        SMARK(4 + i);
        load_x(v, c, sb + SM_X + i * SLOT_BYTES);
        fence_async_smem();
        asm volatile("bar.arrive %0, 160;" ::"r"(6 + i) : "memory");
        if (i == 2) break;
        if (i == 0) {
            const uint32_t p = bf2_add(bf2_fma(v[2][2], ws[2], bf2_fma(v[2][1], ws[1], bf2_mul(v[2][0], ws[0]))),
                                       bf2_fma(v[2][5], ws[5], bf2_fma(v[2][4], ws[4], bf2_mul(v[2][3], ws[3]))));
            float e = quad_sum(bf_lo(p) + bf_hi(p));
            e = (e + __shfl_xor_sync(0xffffffffu, e, 4)) * (-1.0f / CH);
            st[1] = st[3] = st[5] = st[7] = pack_bf2(e, e);
#pragma unroll
            for (int k = 0; k < NX; k++) sts32(c.own + k * SLOT_BYTES + 4, st[1]);
        } else {
            conv_row<1, 1>(B, C, v, c);
        }
        conv_row<0, 0>(C, st, v, c);
    }
    asm volatile(".reg .b32 pw<54>, pb<24>, pc<24>, pv<36>, ps<8>;");
    hand_over<0>(c, B, C, v);
    asm volatile("mov.b32 ps1, %0; mov.b32 ps3, %1; mov.b32 ps5, %2; mov.b32 ps7, %3;" ::"r"(st[1]), "r"(st[3]), "r"(st[5]), "r"(st[7]));
    SMARK(7);
    produce_tiles(c, prm);
    mbar_arrive_if(sb + SM_YFULL + ROWS_PER_CTA * 8, c.lane == 0);
}

struct Duty {
    const char* g;
    const char* zeros;
    long long step;
    uint32_t s, bytes;
    int end, zero;
};
__device__ __forceinline__ Duty make_duty(const Params& prm, int wg, int w) {
    const RowCopy rc = row_copy(prm);
    Duty d;
    d.g = (w == 2 ? rc.y0 : rc.x0 + (w == 0 ? rc.cut0 : w == 1 ? 32 * 192 : 192)) +
          (wg + (w == 2 ? 0 : w < 2 ? 2 * NX : 2 * NX + L2_AHEAD)) * rc.stride;
    d.step = NX * rc.stride;
    d.s = wg * SLOT_BYTES + (w == 2 ? sb + SM_Y1 : sb + SM_X + (w == 0 ? rc.cut0 : XHALF_B));
    d.bytes = w >= 2 ? TILE_BYTES : XHALF_BYTES - (w == 0 ? rc.cut0 : rc.cut1);
    d.end = w == 2 ? ROWS_PER_CTA : w < 2 ? STEPS + 1 - 2 * NX : rc.last + 1 - 2 * NX - L2_AHEAD;
    d.zero = rc.last + 1 - 2 * NX;
    d.zeros = rc.zeros;
    return d;
}

static_assert(sb + SM_BAR == 230800 && sb + SM_YFULL == 231552 && sb + SM_GO == 231240 && SLOT_BYTES == 26624 && sb + SM_GAMMA == 229248 &&
              SM_BETA == SM_GAMMA + 768 && SM_W2 == 73728 && sb + SM_BUF3 == 187392 && BAR_W2 == 9 && BAR_W1B == 10, "layout");
__device__ __forceinline__ void consume(float (&acc)[2][2], uint32_t w1t, uint32_t yd, uint32_t wd, uint32_t own_slot, const Duty& d,
                                        uint32_t role, uint32_t lane, const Params& prm) {
    asm volatile(
        "{\n"
        ".reg .b32 z<32>, w<44>, p, a<4>, lo<2>, hi<2>, t, g, q<4>, dl, dh, n, so, c, tt, cnt, f0, f1;\n"
        ".reg .b16 xl, xh, xr;\n"
        ".reg .b64 ds<6>, wd, gp, src;\n"
        ".reg .pred pt, pf, pr, pw, pl, pe;\n"
        "setp.ne.b32 pt, 1, 0; setp.ne.b32 pf, 0, 0; setp.eq.u32 pl, %15, 0;\n"
        "mov.b32 c, 0x40D940D9;\n"
        "ldmatrix.sync.aligned.m8n8.x4.trans.shared.b16 {w0,w1,w2,w3}, [%4+0];\n"
        "ldmatrix.sync.aligned.m8n8.x4.trans.shared.b16 {w4,w5,w6,w7}, [%4+2048];\n"
        "ldmatrix.sync.aligned.m8n8.x4.trans.shared.b16 {w8,w9,w10,w11}, [%4+4096];\n"
        "ldmatrix.sync.aligned.m8n8.x4.trans.shared.b16 {w12,w13,w14,w15}, [%4+6144];\n"
        "ldmatrix.sync.aligned.m8n8.x4.trans.shared.b16 {w16,w17,w18,w19}, [%4+8192];\n"
        "ldmatrix.sync.aligned.m8n8.x4.trans.shared.b16 {w20,w21,w22,w23}, [%4+10240];\n"
        "shl.b32 f0, w0, 16; and.b32 f1, w0, 0xffff0000; cvt.rn.f16x2.f32 w0, f1, f0; shl.b32 f0, w1, 16; and.b32 f1, w1, 0xffff0000; cvt.rn.f16x2.f32 w1, f1, f0; shl.b32 f0, w2, 16; and.b32 f1, w2, 0xffff0000; cvt.rn.f16x2.f32 w2, f1, f0; shl.b32 f0, w3, 16; and.b32 f1, w3, 0xffff0000; cvt.rn.f16x2.f32 w3, f1, f0;\n"
        "stmatrix.sync.aligned.m8n8.x4.trans.shared.b16 [%4+0], {w0,w1,w2,w3};\n"
        "shl.b32 f0, w4, 16; and.b32 f1, w4, 0xffff0000; cvt.rn.f16x2.f32 w4, f1, f0; shl.b32 f0, w5, 16; and.b32 f1, w5, 0xffff0000; cvt.rn.f16x2.f32 w5, f1, f0; shl.b32 f0, w6, 16; and.b32 f1, w6, 0xffff0000; cvt.rn.f16x2.f32 w6, f1, f0; shl.b32 f0, w7, 16; and.b32 f1, w7, 0xffff0000; cvt.rn.f16x2.f32 w7, f1, f0;\n"
        "stmatrix.sync.aligned.m8n8.x4.trans.shared.b16 [%4+2048], {w4,w5,w6,w7};\n"
        "shl.b32 f0, w8, 16; and.b32 f1, w8, 0xffff0000; cvt.rn.f16x2.f32 w8, f1, f0; shl.b32 f0, w9, 16; and.b32 f1, w9, 0xffff0000; cvt.rn.f16x2.f32 w9, f1, f0; shl.b32 f0, w10, 16; and.b32 f1, w10, 0xffff0000; cvt.rn.f16x2.f32 w10, f1, f0; shl.b32 f0, w11, 16; and.b32 f1, w11, 0xffff0000; cvt.rn.f16x2.f32 w11, f1, f0;\n"
        "stmatrix.sync.aligned.m8n8.x4.trans.shared.b16 [%4+4096], {w8,w9,w10,w11};\n"
        "shl.b32 f0, w12, 16; and.b32 f1, w12, 0xffff0000; cvt.rn.f16x2.f32 w12, f1, f0; shl.b32 f0, w13, 16; and.b32 f1, w13, 0xffff0000; cvt.rn.f16x2.f32 w13, f1, f0; shl.b32 f0, w14, 16; and.b32 f1, w14, 0xffff0000; cvt.rn.f16x2.f32 w14, f1, f0; shl.b32 f0, w15, 16; and.b32 f1, w15, 0xffff0000; cvt.rn.f16x2.f32 w15, f1, f0;\n"
        "stmatrix.sync.aligned.m8n8.x4.trans.shared.b16 [%4+6144], {w12,w13,w14,w15};\n"
        "shl.b32 f0, w16, 16; and.b32 f1, w16, 0xffff0000; cvt.rn.f16x2.f32 w16, f1, f0; shl.b32 f0, w17, 16; and.b32 f1, w17, 0xffff0000; cvt.rn.f16x2.f32 w17, f1, f0; shl.b32 f0, w18, 16; and.b32 f1, w18, 0xffff0000; cvt.rn.f16x2.f32 w18, f1, f0; shl.b32 f0, w19, 16; and.b32 f1, w19, 0xffff0000; cvt.rn.f16x2.f32 w19, f1, f0;\n"
        "stmatrix.sync.aligned.m8n8.x4.trans.shared.b16 [%4+8192], {w16,w17,w18,w19};\n"
        "shl.b32 f0, w20, 16; and.b32 f1, w20, 0xffff0000; cvt.rn.f16x2.f32 w20, f1, f0; shl.b32 f0, w21, 16; and.b32 f1, w21, 0xffff0000; cvt.rn.f16x2.f32 w21, f1, f0; shl.b32 f0, w22, 16; and.b32 f1, w22, 0xffff0000; cvt.rn.f16x2.f32 w22, f1, f0; shl.b32 f0, w23, 16; and.b32 f1, w23, 0xffff0000; cvt.rn.f16x2.f32 w23, f1, f0;\n"
        "stmatrix.sync.aligned.m8n8.x4.trans.shared.b16 [%4+10240], {w20,w21,w22,w23};\n"
        "mov.u32 tt, 230880; mbarrier.try_wait.parity.shared::cta.b64 pw, [tt], 0;\n"
        "@!pw bra.uni SPINW;\n"
        "BACKW:\n"
        "ldmatrix.sync.aligned.m8n8.x4.trans.shared.b16 {z0,z1,z2,z3}, [%4+22528];\n"
        "ldmatrix.sync.aligned.m8n8.x4.trans.shared.b16 {w24,w25,w26,w27}, [%4+12288];\n"
        "ldmatrix.sync.aligned.m8n8.x4.trans.shared.b16 {w28,w29,w30,w31}, [%4+14336];\n"
        "ldmatrix.sync.aligned.m8n8.x4.trans.shared.b16 {w32,w33,w34,w35}, [%4+16384];\n"
        "ldmatrix.sync.aligned.m8n8.x4.trans.shared.b16 {w36,w37,w38,w39}, [%4+18432];\n"
        "ldmatrix.sync.aligned.m8n8.x4.trans.shared.b16 {w40,w41,w42,w43}, [%4+20480];\n"
        "shl.b32 f0, z0, 16; and.b32 f1, z0, 0xffff0000; cvt.rn.f16x2.f32 z0, f1, f0; shl.b32 f0, z1, 16; and.b32 f1, z1, 0xffff0000; cvt.rn.f16x2.f32 z1, f1, f0; shl.b32 f0, z2, 16; and.b32 f1, z2, 0xffff0000; cvt.rn.f16x2.f32 z2, f1, f0; shl.b32 f0, z3, 16; and.b32 f1, z3, 0xffff0000; cvt.rn.f16x2.f32 z3, f1, f0;\n"
        "stmatrix.sync.aligned.m8n8.x4.trans.shared.b16 [%4+22528], {z0,z1,z2,z3};\n"
        "shl.b32 f0, w24, 16; and.b32 f1, w24, 0xffff0000; cvt.rn.f16x2.f32 w24, f1, f0; shl.b32 f0, w25, 16; and.b32 f1, w25, 0xffff0000; cvt.rn.f16x2.f32 w25, f1, f0; shl.b32 f0, w26, 16; and.b32 f1, w26, 0xffff0000; cvt.rn.f16x2.f32 w26, f1, f0; shl.b32 f0, w27, 16; and.b32 f1, w27, 0xffff0000; cvt.rn.f16x2.f32 w27, f1, f0;\n"
        "stmatrix.sync.aligned.m8n8.x4.trans.shared.b16 [%4+12288], {w24,w25,w26,w27};\n"
        "shl.b32 f0, w28, 16; and.b32 f1, w28, 0xffff0000; cvt.rn.f16x2.f32 w28, f1, f0; shl.b32 f0, w29, 16; and.b32 f1, w29, 0xffff0000; cvt.rn.f16x2.f32 w29, f1, f0; shl.b32 f0, w30, 16; and.b32 f1, w30, 0xffff0000; cvt.rn.f16x2.f32 w30, f1, f0; shl.b32 f0, w31, 16; and.b32 f1, w31, 0xffff0000; cvt.rn.f16x2.f32 w31, f1, f0;\n"
        "stmatrix.sync.aligned.m8n8.x4.trans.shared.b16 [%4+14336], {w28,w29,w30,w31};\n"
        "shl.b32 f0, w32, 16; and.b32 f1, w32, 0xffff0000; cvt.rn.f16x2.f32 w32, f1, f0; shl.b32 f0, w33, 16; and.b32 f1, w33, 0xffff0000; cvt.rn.f16x2.f32 w33, f1, f0; shl.b32 f0, w34, 16; and.b32 f1, w34, 0xffff0000; cvt.rn.f16x2.f32 w34, f1, f0; shl.b32 f0, w35, 16; and.b32 f1, w35, 0xffff0000; cvt.rn.f16x2.f32 w35, f1, f0;\n"
        "stmatrix.sync.aligned.m8n8.x4.trans.shared.b16 [%4+16384], {w32,w33,w34,w35};\n"
        "shl.b32 f0, w36, 16; and.b32 f1, w36, 0xffff0000; cvt.rn.f16x2.f32 w36, f1, f0; shl.b32 f0, w37, 16; and.b32 f1, w37, 0xffff0000; cvt.rn.f16x2.f32 w37, f1, f0; shl.b32 f0, w38, 16; and.b32 f1, w38, 0xffff0000; cvt.rn.f16x2.f32 w38, f1, f0; shl.b32 f0, w39, 16; and.b32 f1, w39, 0xffff0000; cvt.rn.f16x2.f32 w39, f1, f0;\n"
        "stmatrix.sync.aligned.m8n8.x4.trans.shared.b16 [%4+18432], {w36,w37,w38,w39};\n"
        "shl.b32 f0, w40, 16; and.b32 f1, w40, 0xffff0000; cvt.rn.f16x2.f32 w40, f1, f0; shl.b32 f0, w41, 16; and.b32 f1, w41, 0xffff0000; cvt.rn.f16x2.f32 w41, f1, f0; shl.b32 f0, w42, 16; and.b32 f1, w42, 0xffff0000; cvt.rn.f16x2.f32 w42, f1, f0; shl.b32 f0, w43, 16; and.b32 f1, w43, 0xffff0000; cvt.rn.f16x2.f32 w43, f1, f0;\n"
        "stmatrix.sync.aligned.m8n8.x4.trans.shared.b16 [%4+20480], {w40,w41,w42,w43};\n"
        "fence.proxy.async.shared::cta;\n"
        ASM_SMARK
        "mov.b32 p, 0; mov.b32 t, 0; mov.b32 g, 0; mov.b32 a0, 0; mov.b32 a1, 0; mov.b32 a2, 0; mov.b32 a3, 0; mov.b32 lo0, 0; mov.b32 lo1, 0; mov.b32 hi0, 0; mov.b32 hi1, 0; mov.b32 q0, 0; mov.b32 q1, 0; mov.b32 q2, 0; mov.b32 q3, 0;\n"
        "mov.b32 z16, 0; mov.b32 z17, 0; mov.b32 z18, 0; mov.b32 z19, 0; mov.b32 z20, 0; mov.b32 z21, 0; mov.b32 z22, 0; mov.b32 z23, 0; mov.b32 z24, 0; mov.b32 z25, 0; mov.b32 z26, 0; mov.b32 z27, 0; mov.b32 z28, 0; mov.b32 z29, 0; mov.b32 z30, 0; mov.b32 z31, 0;\n"
        "mov.f32 %0, 0f00000000; mov.f32 %1, 0f00000000; mov.f32 %2, 0f00000000; mov.f32 %3, 0f00000000;\n"
        "mov.u32 n, 0; mov.u32 so, 0; mov.b64 gp, %8; mov.b64 wd, {%6, 0x40000040};\n"
        "mov.b64 ds0, %20; add.s64 ds1, ds0, 2; add.s64 ds2, ds0, 4; add.s64 ds3, ds0, 6; mov.b64 ds4, %21; add.s64 ds5, ds4, 2;\n"
        "mbarrier.try_wait.parity.shared::cta.b64 pw, [n+231552], 0;\n"
        "@!pw bra.uni SPIN0;\n"
        "BACK0:\n"
        ASM_TS
        "wgmma.fence.sync.aligned;\n"
        "wgmma.mma_async.sync.aligned.m64n64k16.f16.f16.f16 {z0,z1,z2,z3,z4,z5,z6,z7,z8,z9,z10,z11,z12,z13,z14,z15}, {w0,w1,w2,w3}, ds0, pf, 1, 1, 0;\n"
        "wgmma.mma_async.sync.aligned.m64n64k16.f16.f16.f16 {z0,z1,z2,z3,z4,z5,z6,z7,z8,z9,z10,z11,z12,z13,z14,z15}, {w4,w5,w6,w7}, ds1, pt, 1, 1, 0;\n"
        "wgmma.mma_async.sync.aligned.m64n64k16.f16.f16.f16 {z0,z1,z2,z3,z4,z5,z6,z7,z8,z9,z10,z11,z12,z13,z14,z15}, {w8,w9,w10,w11}, ds2, pt, 1, 1, 0;\n"
        "wgmma.fence.sync.aligned;\n"
        "wgmma.mma_async.sync.aligned.m64n64k16.f16.f16.f16 {z0,z1,z2,z3,z4,z5,z6,z7,z8,z9,z10,z11,z12,z13,z14,z15}, {w12,w13,w14,w15}, ds3, pt, 1, 1, 0;\n"
        "wgmma.mma_async.sync.aligned.m64n64k16.f16.f16.f16 {z0,z1,z2,z3,z4,z5,z6,z7,z8,z9,z10,z11,z12,z13,z14,z15}, {w16,w17,w18,w19}, ds4, pt, 1, 1, 0;\n"
        "wgmma.mma_async.sync.aligned.m64n64k16.f16.f16.f16 {z0,z1,z2,z3,z4,z5,z6,z7,z8,z9,z10,z11,z12,z13,z14,z15}, {w20,w21,w22,w23}, ds5, pt, 1, 1, 0;\n"
        "wgmma.commit_group.sync.aligned;\n"
        "setp.eq.u32 pr, so, %7;\n"
        "@pr bra.uni DUTY;\n"
        "TOP:\n"
        ASM_TRC("n")
        "wgmma.wait_group.sync.aligned 0;\n"
        "mov.b32 {xl, xh}, a2; tanh.approx.f16 xr, xh; cvt.u32.u16 hi0, xr; mul.rn.f16x2 a3, z31, p; fma.rn.f16x2 p, z0, z0, c; fma.rn.f16x2 q3, g, g, q3; fma.rn.f16x2 g, z28, t, z28; prmt.b32 t, lo1, hi1, 0x5410; tanh.approx.f16 xr, xl; cvt.u32.u16 lo0, xr;\n"
        "B31:\n"
        "mov.b32 {xl, xh}, a3; tanh.approx.f16 xr, xh; cvt.u32.u16 hi1, xr; mul.rn.f16x2 a0, z0, p; fma.rn.f16x2 p, z1, z1, c; fma.rn.f16x2 q2, g, g, q2; fma.rn.f16x2 g, z29, t, z29; prmt.b32 t, lo0, hi0, 0x5410; tanh.approx.f16 xr, xl; cvt.u32.u16 lo1, xr;\n"
        "B0:\n"
        "mov.b32 {xl, xh}, a0; tanh.approx.f16 xr, xh; cvt.u32.u16 hi0, xr; mul.rn.f16x2 a1, z1, p; fma.rn.f16x2 p, z2, z2, c; fma.rn.f16x2 q3, g, g, q3; fma.rn.f16x2 g, z30, t, z30; prmt.b32 t, lo1, hi1, 0x5410; tanh.approx.f16 xr, xl; cvt.u32.u16 lo0, xr;\n"
        "B1:\n"
        "mov.b32 {xl, xh}, a1; tanh.approx.f16 xr, xh; cvt.u32.u16 hi1, xr; mul.rn.f16x2 a2, z2, p; fma.rn.f16x2 p, z3, z3, c; fma.rn.f16x2 q2, g, g, q2; fma.rn.f16x2 g, z31, t, z31; prmt.b32 t, lo0, hi0, 0x5410; tanh.approx.f16 xr, xl; cvt.u32.u16 lo1, xr;\n"
        "B2:\n"
        "wgmma.fence.sync.aligned;\n"
        "wgmma.mma_async.sync.aligned.m64n64k16.f16.f16.f16 {z16,z17,z18,z19,z20,z21,z22,z23,z24,z25,z26,z27,z28,z29,z30,z31}, {w24,w25,w26,w27}, ds0, pf, 1, 1, 0;\n"
        "wgmma.mma_async.sync.aligned.m64n64k16.f16.f16.f16 {z16,z17,z18,z19,z20,z21,z22,z23,z24,z25,z26,z27,z28,z29,z30,z31}, {w28,w29,w30,w31}, ds1, pt, 1, 1, 0;\n"
        "wgmma.mma_async.sync.aligned.m64n64k16.f16.f16.f16 {z16,z17,z18,z19,z20,z21,z22,z23,z24,z25,z26,z27,z28,z29,z30,z31}, {w32,w33,w34,w35}, ds2, pt, 1, 1, 0;\n"
        "mov.b32 {xl, xh}, a2; tanh.approx.f16 xr, xh; cvt.u32.u16 hi0, xr; mul.rn.f16x2 a3, z3, p; fma.rn.f16x2 p, z4, z4, c; fma.rn.f16x2 q3, g, g, q3; fma.rn.f16x2 g, z0, t, z0; prmt.b32 t, lo1, hi1, 0x5410; tanh.approx.f16 xr, xl; cvt.u32.u16 lo0, xr;\n"
        "B3:\n"
        "mov.b32 {xl, xh}, a3; tanh.approx.f16 xr, xh; cvt.u32.u16 hi1, xr; mul.rn.f16x2 a0, z4, p; fma.rn.f16x2 p, z5, z5, c; fma.rn.f16x2 q0, g, g, q0; fma.rn.f16x2 g, z1, t, z1; prmt.b32 t, lo0, hi0, 0x5410; tanh.approx.f16 xr, xl; cvt.u32.u16 lo1, xr;\n"
        "B4:\n"
        "mov.b32 {xl, xh}, a0; tanh.approx.f16 xr, xh; cvt.u32.u16 hi0, xr; mul.rn.f16x2 a1, z5, p; fma.rn.f16x2 p, z6, z6, c; fma.rn.f16x2 q1, g, g, q1; fma.rn.f16x2 g, z2, t, z2; prmt.b32 t, lo1, hi1, 0x5410; tanh.approx.f16 xr, xl; cvt.u32.u16 lo0, xr;\n"
        "B5:\n"
        "wgmma.fence.sync.aligned;\n"
        "wgmma.mma_async.sync.aligned.m64n64k16.f16.f16.f16 {z16,z17,z18,z19,z20,z21,z22,z23,z24,z25,z26,z27,z28,z29,z30,z31}, {w36,w37,w38,w39}, ds3, pt, 1, 1, 0;\n"
        "wgmma.mma_async.sync.aligned.m64n64k16.f16.f16.f16 {z16,z17,z18,z19,z20,z21,z22,z23,z24,z25,z26,z27,z28,z29,z30,z31}, {w40,w41,w42,w43}, ds4, pt, 1, 1, 0;\n"
        "wgmma.mma_async.sync.aligned.m64n64k16.f16.f16.f16 {z16,z17,z18,z19,z20,z21,z22,z23,z24,z25,z26,z27,z28,z29,z30,z31}, wd, ds5, pt, 1, 1, 1, 0;\n"
        "wgmma.commit_group.sync.aligned;\n"
        "mov.b32 {xl, xh}, a1; tanh.approx.f16 xr, xh; cvt.u32.u16 hi1, xr; mul.rn.f16x2 a2, z6, p; fma.rn.f16x2 p, z7, z7, c; fma.rn.f16x2 q0, g, g, q0; fma.rn.f16x2 g, z3, t, z3; prmt.b32 t, lo0, hi0, 0x5410; tanh.approx.f16 xr, xl; cvt.u32.u16 lo1, xr;\n"
        "B6:\n"
        "add.u32 so, so, 26624; setp.eq.u32 pr, so, 79872; selp.u32 so, 0, so, pr;\n"
        "mov.b32 {xl, xh}, a2; tanh.approx.f16 xr, xh; cvt.u32.u16 hi0, xr; mul.rn.f16x2 a3, z7, p; fma.rn.f16x2 p, z8, z8, c; fma.rn.f16x2 q1, g, g, q1; fma.rn.f16x2 g, z4, t, z4; prmt.b32 t, lo1, hi1, 0x5410; tanh.approx.f16 xr, xl; cvt.u32.u16 lo0, xr;\n"
        "B7:\n"
        "shr.u32 tt, so, 4;\n"
        "mov.b64 {dl, dh}, ds0; add.u32 dl, tt, 74816; mov.b64 ds0, {dl, dh}; mov.b64 {dl, dh}, ds1; add.u32 dl, tt, 74818; mov.b64 ds1, {dl, dh}; mov.b64 {dl, dh}, ds2; add.u32 dl, tt, 74820; mov.b64 ds2, {dl, dh};\n"
        "mov.b32 {xl, xh}, a3; tanh.approx.f16 xr, xh; cvt.u32.u16 hi1, xr; mul.rn.f16x2 a0, z8, p; fma.rn.f16x2 p, z9, z9, c; fma.rn.f16x2 q0, g, g, q0; fma.rn.f16x2 g, z5, t, z5; prmt.b32 t, lo0, hi0, 0x5410; tanh.approx.f16 xr, xl; cvt.u32.u16 lo1, xr;\n"
        "B8:\n"
        "shr.u32 tt, so, 4;\n"
        "mov.b64 {dl, dh}, ds3; add.u32 dl, tt, 74822; mov.b64 ds3, {dl, dh}; mov.b64 {dl, dh}, ds4; add.u32 dl, tt, 75328; mov.b64 ds4, {dl, dh}; mov.b64 {dl, dh}, ds5; add.u32 dl, tt, 75330; mov.b64 ds5, {dl, dh};\n"
        "mov.b32 {xl, xh}, a0; tanh.approx.f16 xr, xh; cvt.u32.u16 hi0, xr; mul.rn.f16x2 a1, z9, p; fma.rn.f16x2 p, z10, z10, c; fma.rn.f16x2 q1, g, g, q1; fma.rn.f16x2 g, z6, t, z6; prmt.b32 t, lo1, hi1, 0x5410; tanh.approx.f16 xr, xl; cvt.u32.u16 lo0, xr;\n"
        "B9:\n"
        "mov.b32 {xl, xh}, a1; tanh.approx.f16 xr, xh; cvt.u32.u16 hi1, xr; mul.rn.f16x2 a2, z10, p; fma.rn.f16x2 p, z11, z11, c; fma.rn.f16x2 q0, g, g, q0; fma.rn.f16x2 g, z7, t, z7; prmt.b32 t, lo0, hi0, 0x5410; tanh.approx.f16 xr, xl; cvt.u32.u16 lo1, xr;\n"
        "B10:\n"
        "mov.b32 {xl, xh}, a2; tanh.approx.f16 xr, xh; cvt.u32.u16 hi0, xr; mul.rn.f16x2 a3, z11, p; fma.rn.f16x2 p, z12, z12, c; fma.rn.f16x2 q1, g, g, q1; fma.rn.f16x2 g, z8, t, z8; prmt.b32 t, lo1, hi1, 0x5410; tanh.approx.f16 xr, xl; cvt.u32.u16 lo0, xr;\n"
        "B11:\n"
        "mov.b32 {xl, xh}, a3; tanh.approx.f16 xr, xh; cvt.u32.u16 hi1, xr; mul.rn.f16x2 a0, z12, p; fma.rn.f16x2 p, z13, z13, c; fma.rn.f16x2 q0, g, g, q0; fma.rn.f16x2 g, z9, t, z9; prmt.b32 t, lo0, hi0, 0x5410; tanh.approx.f16 xr, xl; cvt.u32.u16 lo1, xr;\n"
        "B12:\n"
        "mov.b32 {xl, xh}, a0; tanh.approx.f16 xr, xh; cvt.u32.u16 hi0, xr; mul.rn.f16x2 a1, z13, p; fma.rn.f16x2 p, z14, z14, c; fma.rn.f16x2 q1, g, g, q1; fma.rn.f16x2 g, z10, t, z10; prmt.b32 t, lo1, hi1, 0x5410; tanh.approx.f16 xr, xl; cvt.u32.u16 lo0, xr;\n"
        "B13:\n"
        "mov.b32 {xl, xh}, a1; tanh.approx.f16 xr, xh; cvt.u32.u16 hi1, xr; mul.rn.f16x2 a2, z14, p; fma.rn.f16x2 p, z15, z15, c; fma.rn.f16x2 q0, g, g, q0; fma.rn.f16x2 g, z11, t, z11; prmt.b32 t, lo0, hi0, 0x5410; tanh.approx.f16 xr, xl; cvt.u32.u16 lo1, xr;\n"
        "B14:\n"
        "wgmma.wait_group.sync.aligned 0;\n"
        "cp.async.bulk.wait_group.read 0;\n"
        "@pl mbarrier.arrive.shared::cta.b64 _, [n+231288];\n"
        "mov.b32 {xl, xh}, a2; tanh.approx.f16 xr, xh; cvt.u32.u16 hi0, xr; mul.rn.f16x2 a3, z15, p; fma.rn.f16x2 p, z16, z16, c; fma.rn.f16x2 q1, g, g, q1; fma.rn.f16x2 g, z12, t, z12; prmt.b32 t, lo1, hi1, 0x5410; tanh.approx.f16 xr, xl; cvt.u32.u16 lo0, xr;\n"
        "B15:\n"
        "mov.b32 {xl, xh}, a3; tanh.approx.f16 xr, xh; cvt.u32.u16 hi1, xr; mul.rn.f16x2 a0, z16, p; fma.rn.f16x2 p, z17, z17, c; fma.rn.f16x2 q0, g, g, q0; fma.rn.f16x2 g, z13, t, z13; prmt.b32 t, lo0, hi0, 0x5410; tanh.approx.f16 xr, xl; cvt.u32.u16 lo1, xr;\n"
        "B16:\n"
        "mbarrier.try_wait.parity.shared::cta.b64 pw, [n+231560], 0;\n"
        "mov.b32 {xl, xh}, a0; tanh.approx.f16 xr, xh; cvt.u32.u16 hi0, xr; mul.rn.f16x2 a1, z17, p; fma.rn.f16x2 p, z18, z18, c; fma.rn.f16x2 q1, g, g, q1; fma.rn.f16x2 g, z14, t, z14; prmt.b32 t, lo1, hi1, 0x5410; tanh.approx.f16 xr, xl; cvt.u32.u16 lo0, xr;\n"
        "B17:\n"
        "mov.b32 {xl, xh}, a1; tanh.approx.f16 xr, xh; cvt.u32.u16 hi1, xr; mul.rn.f16x2 a2, z18, p; fma.rn.f16x2 p, z19, z19, c; fma.rn.f16x2 q0, g, g, q0; fma.rn.f16x2 g, z15, t, z15; prmt.b32 t, lo0, hi0, 0x5410; tanh.approx.f16 xr, xl; cvt.u32.u16 lo1, xr;\n"
        "B18:\n"
        "@!pw bra.uni SPIN;\n"
        "BACK:\n"
        "wgmma.fence.sync.aligned;\n"
        "wgmma.mma_async.sync.aligned.m64n64k16.f16.f16.f16 {z0,z1,z2,z3,z4,z5,z6,z7,z8,z9,z10,z11,z12,z13,z14,z15}, {w0,w1,w2,w3}, ds0, pf, 1, 1, 0;\n"
        "wgmma.mma_async.sync.aligned.m64n64k16.f16.f16.f16 {z0,z1,z2,z3,z4,z5,z6,z7,z8,z9,z10,z11,z12,z13,z14,z15}, {w4,w5,w6,w7}, ds1, pt, 1, 1, 0;\n"
        "wgmma.mma_async.sync.aligned.m64n64k16.f16.f16.f16 {z0,z1,z2,z3,z4,z5,z6,z7,z8,z9,z10,z11,z12,z13,z14,z15}, {w8,w9,w10,w11}, ds2, pt, 1, 1, 0;\n"
        "mov.b32 {xl, xh}, a2; tanh.approx.f16 xr, xh; cvt.u32.u16 hi0, xr; mul.rn.f16x2 a3, z19, p; fma.rn.f16x2 p, z20, z20, c; fma.rn.f16x2 q1, g, g, q1; fma.rn.f16x2 g, z16, t, z16; prmt.b32 t, lo1, hi1, 0x5410; tanh.approx.f16 xr, xl; cvt.u32.u16 lo0, xr;\n"
        "B19:\n"
        "mov.b32 {xl, xh}, a3; tanh.approx.f16 xr, xh; cvt.u32.u16 hi1, xr; mul.rn.f16x2 a0, z20, p; fma.rn.f16x2 p, z21, z21, c; fma.rn.f16x2 q2, g, g, q2; fma.rn.f16x2 g, z17, t, z17; prmt.b32 t, lo0, hi0, 0x5410; tanh.approx.f16 xr, xl; cvt.u32.u16 lo1, xr;\n"
        "B20:\n"
        "mov.b32 {xl, xh}, a0; tanh.approx.f16 xr, xh; cvt.u32.u16 hi0, xr; mul.rn.f16x2 a1, z21, p; fma.rn.f16x2 p, z22, z22, c; fma.rn.f16x2 q3, g, g, q3; fma.rn.f16x2 g, z18, t, z18; prmt.b32 t, lo1, hi1, 0x5410; tanh.approx.f16 xr, xl; cvt.u32.u16 lo0, xr;\n"
        "B21:\n"
        "wgmma.fence.sync.aligned;\n"
        "wgmma.mma_async.sync.aligned.m64n64k16.f16.f16.f16 {z0,z1,z2,z3,z4,z5,z6,z7,z8,z9,z10,z11,z12,z13,z14,z15}, {w12,w13,w14,w15}, ds3, pt, 1, 1, 0;\n"
        "wgmma.mma_async.sync.aligned.m64n64k16.f16.f16.f16 {z0,z1,z2,z3,z4,z5,z6,z7,z8,z9,z10,z11,z12,z13,z14,z15}, {w16,w17,w18,w19}, ds4, pt, 1, 1, 0;\n"
        "wgmma.mma_async.sync.aligned.m64n64k16.f16.f16.f16 {z0,z1,z2,z3,z4,z5,z6,z7,z8,z9,z10,z11,z12,z13,z14,z15}, {w20,w21,w22,w23}, ds5, pt, 1, 1, 0;\n"
        "wgmma.commit_group.sync.aligned;\n"
        "mov.b32 {xl, xh}, a1; tanh.approx.f16 xr, xh; cvt.u32.u16 hi1, xr; mul.rn.f16x2 a2, z22, p; fma.rn.f16x2 p, z23, z23, c; fma.rn.f16x2 q2, g, g, q2; fma.rn.f16x2 g, z19, t, z19; prmt.b32 t, lo0, hi0, 0x5410; tanh.approx.f16 xr, xl; cvt.u32.u16 lo1, xr;\n"
        "B22:\n"
        "mov.b32 {xl, xh}, a2; tanh.approx.f16 xr, xh; cvt.u32.u16 hi0, xr; mul.rn.f16x2 a3, z23, p; fma.rn.f16x2 p, z24, z24, c; fma.rn.f16x2 q3, g, g, q3; fma.rn.f16x2 g, z20, t, z20; prmt.b32 t, lo1, hi1, 0x5410; tanh.approx.f16 xr, xl; cvt.u32.u16 lo0, xr;\n"
        "B23:\n"
        "mov.b32 {xl, xh}, a3; tanh.approx.f16 xr, xh; cvt.u32.u16 hi1, xr; mul.rn.f16x2 a0, z24, p; fma.rn.f16x2 p, z25, z25, c; fma.rn.f16x2 q2, g, g, q2; fma.rn.f16x2 g, z21, t, z21; prmt.b32 t, lo0, hi0, 0x5410; tanh.approx.f16 xr, xl; cvt.u32.u16 lo1, xr;\n"
        "B24:\n"
        "mov.b32 {xl, xh}, a0; tanh.approx.f16 xr, xh; cvt.u32.u16 hi0, xr; mul.rn.f16x2 a1, z25, p; fma.rn.f16x2 p, z26, z26, c; fma.rn.f16x2 q3, g, g, q3; fma.rn.f16x2 g, z22, t, z22; prmt.b32 t, lo1, hi1, 0x5410; tanh.approx.f16 xr, xl; cvt.u32.u16 lo0, xr;\n"
        "B25:\n"
        "mov.b32 {xl, xh}, a1; tanh.approx.f16 xr, xh; cvt.u32.u16 hi1, xr; mul.rn.f16x2 a2, z26, p; fma.rn.f16x2 p, z27, z27, c; fma.rn.f16x2 q2, g, g, q2; fma.rn.f16x2 g, z23, t, z23; prmt.b32 t, lo0, hi0, 0x5410; tanh.approx.f16 xr, xl; cvt.u32.u16 lo1, xr;\n"
        "B26:\n"
        "mov.b32 {xl, xh}, a2; tanh.approx.f16 xr, xh; cvt.u32.u16 hi0, xr; mul.rn.f16x2 a3, z27, p; fma.rn.f16x2 p, z28, z28, c; fma.rn.f16x2 q3, g, g, q3; fma.rn.f16x2 g, z24, t, z24; prmt.b32 t, lo1, hi1, 0x5410; tanh.approx.f16 xr, xl; cvt.u32.u16 lo0, xr;\n"
        "B27:\n"
        "add.u32 n, n, 8; setp.lt.u32 pe, n, 256; setp.ne.and.u32 pe, so, %7, pe;\n"
        "mov.b32 {xl, xh}, a3; tanh.approx.f16 xr, xh; cvt.u32.u16 hi1, xr; mul.rn.f16x2 a0, z28, p; fma.rn.f16x2 p, z29, z29, c; fma.rn.f16x2 q2, g, g, q2; fma.rn.f16x2 g, z25, t, z25; prmt.b32 t, lo0, hi0, 0x5410; tanh.approx.f16 xr, xl; cvt.u32.u16 lo1, xr;\n"
        "B28:\n"
        "mov.b32 {xl, xh}, a0; tanh.approx.f16 xr, xh; cvt.u32.u16 hi0, xr; mul.rn.f16x2 a1, z29, p; fma.rn.f16x2 p, z30, z30, c; fma.rn.f16x2 q3, g, g, q3; fma.rn.f16x2 g, z26, t, z26; prmt.b32 t, lo1, hi1, 0x5410; tanh.approx.f16 xr, xl; cvt.u32.u16 lo0, xr;\n"
        "B29:\n"
        "mov.b32 {xl, xh}, a1; tanh.approx.f16 xr, xh; cvt.u32.u16 hi1, xr; mul.rn.f16x2 a2, z30, p; fma.rn.f16x2 p, z31, z31, c; fma.rn.f16x2 q2, g, g, q2; fma.rn.f16x2 g, z27, t, z27; prmt.b32 t, lo0, hi0, 0x5410; tanh.approx.f16 xr, xl; cvt.u32.u16 lo1, xr;\n"
        "@pe bra.uni TOP;\n"
        "setp.lt.u32 pe, n, 256;\n"
        "@pe bra.uni DUTY;\n"
        "bra.uni DONE;\n"
        "SPINW: mov.u32 cnt, 0;\n"
        "SPINWL:\n"
        "mov.u32 tt, 230880; mbarrier.try_wait.parity.shared::cta.b64 pw, [tt], 0;\n"
        "@pw bra.uni BACKW;\n"
        "add.u32 cnt, cnt, 1; setp.lt.u32 pw, cnt, 0x100000;\n"
        "@pw bra.uni SPINWL;\n"
        "trap;\n"
        "SPIN0: mov.u32 cnt, 0;\n"
        "SPIN0L:\n"
        "mbarrier.try_wait.parity.shared::cta.b64 pw, [n+231552], 0;\n"
        "@pw bra.uni BACK0;\n"
        "add.u32 cnt, cnt, 1; setp.lt.u32 pw, cnt, 0x100000;\n"
        "@pw bra.uni SPIN0L;\n"
        "trap;\n"
        "SPIN: mov.u32 cnt, 0;\n"
        "SPINL:\n"
        "mbarrier.try_wait.parity.shared::cta.b64 pw, [n+231560], 0;\n"
        "@pw bra.uni BACK;\n"
        "add.u32 cnt, cnt, 1; setp.lt.u32 pw, cnt, 0x100000;\n"
        "@pw bra.uni SPINL;\n"
        "trap;\n"
        "DUTY:\n"
        "setp.ge.s32 pr, n, %11;\n"
        "@pr bra.uni FLUSH;\n"
        "setp.ge.u32 pr, %13, 2;\n"
        "@pr bra.uni ROLE2;\n"
        "setp.ge.s32 pr, n, %12; selp.b64 src, %14, gp, pr; add.u32 tt, n, 231288;\n"
        "elect.sync _|pr, 0xffffffff;\n"
        "@pr mbarrier.arrive.expect_tx.shared::cta.b64 _, [tt], %10;\n"
        "@pr cp.async.bulk.shared::cluster.global.mbarrier::complete_tx::bytes [%9], [src], %10, [tt];\n"
        "bra.uni FLUSH;\n"
        "ROLE2:\n"
        "setp.eq.u32 pr, %13, 3;\n"
        "@pr bra.uni ROLE3;\n"
        "setp.ne.s32 pr, n, 248;\n"
        "@pr bra.uni PARK;\n"
        "cp.async.bulk.wait_group 0;\n"
        "sub.s64 src, gp, %16; mov.u32 tt, 230824; mov.u32 cnt, 187392;\n"
        "elect.sync _|pr, 0xffffffff;\n"
        "@pr mbarrier.arrive.expect_tx.shared::cta.b64 _, [tt], 12288;\n"
        "@pr cp.async.bulk.shared::cluster.global.mbarrier::complete_tx::bytes [cnt], [src], 12288, [tt];\n"
        "PARK:\n"
        "elect.sync _|pr, 0xffffffff;\n"
        "@pr cp.async.bulk.global.shared::cta.bulk_group [gp], [%9], 12288;\n"
        "@pr cp.async.bulk.commit_group;\n"
        "bra.uni FLUSH;\n"
        "ROLE3:\n"
        "setp.ne.s32 pr, n, 64;\n"
        "@pr bra.uni AHEAD;\n"
        "mov.u32 tt, 230872;\n"
        "elect.sync _|pr, 0xffffffff;\n"
        "@pr mbarrier.arrive.expect_tx.shared::cta.b64 _, [tt], 75264;\n"
        "mov.u32 cnt, 229248; @pr cp.async.bulk.shared::cluster.global.mbarrier::complete_tx::bytes [cnt], [%18], 768, [tt];\n"
        "mov.u32 cnt, 230016; @pr cp.async.bulk.shared::cluster.global.mbarrier::complete_tx::bytes [cnt], [%19], 768, [tt];\n"
        "mov.u32 cnt, 74752; @pr cp.async.bulk.tensor.2d.shared::cluster.global.mbarrier::complete_tx::bytes [cnt], [%17, {0, 0}], [tt];\n"
        "mov.u32 cnt, 87040; @pr cp.async.bulk.tensor.2d.shared::cluster.global.mbarrier::complete_tx::bytes [cnt], [%17, {0, 192}], [tt];\n"
        "mov.u32 cnt, 99328; @pr cp.async.bulk.tensor.2d.shared::cluster.global.mbarrier::complete_tx::bytes [cnt], [%17, {32, 0}], [tt];\n"
        "mov.u32 cnt, 111616; @pr cp.async.bulk.tensor.2d.shared::cluster.global.mbarrier::complete_tx::bytes [cnt], [%17, {32, 192}], [tt];\n"
        "mov.u32 cnt, 123904; @pr cp.async.bulk.tensor.2d.shared::cluster.global.mbarrier::complete_tx::bytes [cnt], [%17, {64, 0}], [tt];\n"
        "mov.u32 cnt, 136192; @pr cp.async.bulk.tensor.2d.shared::cluster.global.mbarrier::complete_tx::bytes [cnt], [%17, {64, 192}], [tt];\n"
        "AHEAD:\n"
        "elect.sync _|pr, 0xffffffff;\n"
        "@pr cp.async.bulk.prefetch.L2.global [gp], 12288;\n"
        "FLUSH:\n"
        "add.s64 gp, gp, %16;\n"
        "mov.b32 {xl, xh}, q0; cvt.f32.f16 f0, xl; cvt.f32.f16 f1, xh; add.f32 f0, f0, f1; add.f32 %0, %0, f0; mov.b32 q0, 0;\n"
        "mov.b32 {xl, xh}, q1; cvt.f32.f16 f0, xl; cvt.f32.f16 f1, xh; add.f32 f0, f0, f1; add.f32 %1, %1, f0; mov.b32 q1, 0;\n"
        "mov.b32 {xl, xh}, q2; cvt.f32.f16 f0, xl; cvt.f32.f16 f1, xh; add.f32 f0, f0, f1; add.f32 %2, %2, f0; mov.b32 q2, 0;\n"
        "mov.b32 {xl, xh}, q3; cvt.f32.f16 f0, xl; cvt.f32.f16 f1, xh; add.f32 f0, f0, f1; add.f32 %3, %3, f0; mov.b32 q3, 0;\n"
        "setp.ne.u32 pr, %5, 0;\n"
        "@pr bra.uni TOP;\n"
        "wgmma.wait_group.sync.aligned 0;\n"
        "wgmma.fence.sync.aligned;\n"
        "ld.volatile.shared.v2.b32 {lo0, hi0}, [so]; xor.b32 f0, f0, lo0;\n"
        "ld.volatile.shared.v2.b32 {lo1, hi1}, [so]; xor.b32 f0, f0, lo1;\n"
        "ld.volatile.shared.v2.b32 {q1, a0}, [so]; xor.b32 f0, f0, q1;\n"
        "ld.volatile.shared.v2.b32 {q2, a1}, [so]; xor.b32 f0, f0, q2;\n"
        "ld.volatile.shared.v2.b32 {q3, a2}, [so]; xor.b32 f0, f0, q3;\n"
        "ld.volatile.shared.v2.b32 {q0, a3}, [so]; xor.b32 f0, f0, q0;\n"
        "ld.volatile.shared.v2.b32 {t, g}, [so]; xor.b32 f0, f0, t;\n"
        "ld.volatile.shared.v2.b32 {p, f1}, [so]; xor.b32 f0, f0, p;\n"
        "add.f32 %0, %0, f0;\n"
        "setp.eq.u32 pr, n, 1000; @pr bra.uni B31;\n"
        "setp.eq.u32 pr, n, 1001; @pr bra.uni B0;\n"
        "setp.eq.u32 pr, n, 1002; @pr bra.uni B1;\n"
        "setp.eq.u32 pr, n, 1003; @pr bra.uni B2;\n"
        "setp.eq.u32 pr, n, 1004; @pr bra.uni B3;\n"
        "setp.eq.u32 pr, n, 1005; @pr bra.uni B4;\n"
        "setp.eq.u32 pr, n, 1006; @pr bra.uni B5;\n"
        "setp.eq.u32 pr, n, 1007; @pr bra.uni B6;\n"
        "setp.eq.u32 pr, n, 1008; @pr bra.uni B7;\n"
        "setp.eq.u32 pr, n, 1009; @pr bra.uni B8;\n"
        "setp.eq.u32 pr, n, 1010; @pr bra.uni B9;\n"
        "setp.eq.u32 pr, n, 1011; @pr bra.uni B10;\n"
        "setp.eq.u32 pr, n, 1012; @pr bra.uni B11;\n"
        "setp.eq.u32 pr, n, 1013; @pr bra.uni B12;\n"
        "setp.eq.u32 pr, n, 1014; @pr bra.uni B13;\n"
        "setp.eq.u32 pr, n, 1015; @pr bra.uni B14;\n"
        "setp.eq.u32 pr, n, 1016; @pr bra.uni B15;\n"
        "setp.eq.u32 pr, n, 1017; @pr bra.uni B16;\n"
        "setp.eq.u32 pr, n, 1018; @pr bra.uni B17;\n"
        "setp.eq.u32 pr, n, 1019; @pr bra.uni B18;\n"
        "setp.eq.u32 pr, n, 1020; @pr bra.uni B19;\n"
        "setp.eq.u32 pr, n, 1021; @pr bra.uni B20;\n"
        "setp.eq.u32 pr, n, 1022; @pr bra.uni B21;\n"
        "setp.eq.u32 pr, n, 1023; @pr bra.uni B22;\n"
        "setp.eq.u32 pr, n, 1024; @pr bra.uni B23;\n"
        "setp.eq.u32 pr, n, 1025; @pr bra.uni B24;\n"
        "setp.eq.u32 pr, n, 1026; @pr bra.uni B25;\n"
        "setp.eq.u32 pr, n, 1027; @pr bra.uni B26;\n"
        "setp.eq.u32 pr, n, 1028; @pr bra.uni B27;\n"
        "setp.eq.u32 pr, n, 1029; @pr bra.uni B28;\n"
        "setp.eq.u32 pr, n, 1030; @pr bra.uni B29;\n"
        "setp.eq.u32 pr, n, 1031; @pr bra.uni TOP;\n"
        "trap;\n"
        "DONE:\n"
        ASM_TRC("n")
        "mov.b32 {xl, xh}, a2; tanh.approx.f16 xr, xh; cvt.u32.u16 hi0, xr; mul.rn.f16x2 a3, z31, p; fma.rn.f16x2 q3, g, g, q3; fma.rn.f16x2 g, z28, t, z28; prmt.b32 t, lo1, hi1, 0x5410; tanh.approx.f16 xr, xl; cvt.u32.u16 lo0, xr;\n"
        "mov.b32 {xl, xh}, a3; tanh.approx.f16 xr, xh; cvt.u32.u16 hi1, xr; fma.rn.f16x2 q2, g, g, q2; fma.rn.f16x2 g, z29, t, z29; prmt.b32 t, lo0, hi0, 0x5410; tanh.approx.f16 xr, xl; cvt.u32.u16 lo1, xr;\n"
        "fma.rn.f16x2 q3, g, g, q3; fma.rn.f16x2 g, z30, t, z30; prmt.b32 t, lo1, hi1, 0x5410;\n"
        "fma.rn.f16x2 q2, g, g, q2; fma.rn.f16x2 g, z31, t, z31;\n"
        "fma.rn.f16x2 q3, g, g, q3;\n"
        "mov.b32 {xl, xh}, q0; cvt.f32.f16 f0, xl; cvt.f32.f16 f1, xh; add.f32 f0, f0, f1; add.f32 %0, %0, f0; mov.b32 q0, 0;\n"
        "mov.b32 {xl, xh}, q1; cvt.f32.f16 f0, xl; cvt.f32.f16 f1, xh; add.f32 f0, f0, f1; add.f32 %1, %1, f0; mov.b32 q1, 0;\n"
        "mov.b32 {xl, xh}, q2; cvt.f32.f16 f0, xl; cvt.f32.f16 f1, xh; add.f32 f0, f0, f1; add.f32 %2, %2, f0; mov.b32 q2, 0;\n"
        "mov.b32 {xl, xh}, q3; cvt.f32.f16 f0, xl; cvt.f32.f16 f1, xh; add.f32 f0, f0, f1; add.f32 %3, %3, f0; mov.b32 q3, 0;\n"
        "wgmma.wait_group.sync.aligned 0;\n"
        "}\n"
        : "=f"(acc[0][0]), "=f"(acc[0][1]), "=f"(acc[1][0]), "=f"(acc[1][1])
        : "r"(w1t), "r"(yd), "r"(wd), "r"(own_slot), "l"(d.g), "r"(d.s), "r"(d.bytes), "r"(8 * d.end), "r"(8 * d.zero), "r"(role),
          "l"(d.zeros), "r"(lane), "l"(d.step), "l"(&prm.w2_map), "l"(prm.gamma), "l"(prm.beta), "l"(prm.ydesc64[0]), "l"(prm.ydesc64[1])
        : "memory");
}

template <int M>
__device__ __forceinline__ void gemm1_t(uint32_t (&d)[16], const uint32_t* wa, uint32_t yd, uint32_t wd) {
    wg_fence();
    wgmma_n64_h_set<0>(d, wa, desc<1024, 1>(yd, 0));
#pragma unroll
    for (int kk = 1; kk < 5; kk++)
        wgmma_n64_h_acc<0>(d, wa + kk * 4, kk < 4 ? desc<1024, 1>(yd, kk * 32) : desc<512, 2>(yd, 8192 + (kk - 4) * 32));
    wgmma_n64_h_acc_ss(d, desc<1024, 1>(wd, M * 12288), desc<512, 2>(yd, 8192 + 32));
    wg_commit();
}

__device__ __forceinline__ void gelu_sumsq_f(const uint32_t (&d)[16], float (&acc)[2]) {
#pragma unroll
    for (int r = 0; r < 16; r++) {
        float lo, hi;
        h2_unpack(gelu2(d[r]), lo, hi);
        acc[r & 1] = fmaf(lo, lo, acc[r & 1]);
        acc[r & 1] = fmaf(hi, hi, acc[r & 1]);
    }
}
__device__ __forceinline__ void load_w1t(uint32_t (&wa)[2][24], int wg, int w, int lane) {
#pragma unroll
    for (int m = 0; m < 2; m++)
#pragma unroll
        for (int kk = 0; kk < 5; kk++) {
            const int q = lane >> 3, c = 16 * kk + 8 * (q >> 1) + (lane & 7), ck = 2 * w + (q & 1);
            ldsm4_t(wa[m] + kk * 4, sb + SM_W1 + (2 * wg + m) * 12288 + c * 128 + ((ck ^ (c & 7)) * 16));
        }
}
__device__ __forceinline__ unsigned long long* acc_word(const Params& prm, uint32_t epoch, uint32_t e) {
    return &prm.g->acc[epoch & 1][(e >> 2) * 32 + (e & 3)];
}
__device__ __forceinline__ void publish_fast(const Params& prm, const float (&acc)[2][2], uint32_t epoch, int wg, int w, int lane) {
    const bool m = lane & 2, h = lane & 1;
    const float a = (m ? acc[1][0] : acc[0][0]) + __shfl_xor_sync(0xffffffffu, m ? acc[0][0] : acc[1][0], 2);
    const float b = (m ? acc[1][1] : acc[0][1]) + __shfl_xor_sync(0xffffffffu, m ? acc[0][1] : acc[1][1], 2);
    const float v = (h ? b : a) + __shfl_xor_sync(0xffffffffu, h ? a : b, 1);
    const unsigned long long q = (__float2ull_rn(fminf(v, ACC_LIMIT) * 0x1p16f) << 8) + 1;
    asm volatile("red.relaxed.gpu.global.add.u64 [%0], %1;"
                 ::"l"(acc_word(prm, epoch, 128 * wg + 32 * (lane & 2) + 16 * w + (lane >> 2) + 8 * (lane & 1))), "l"(q) : "memory");
}
__device__ __forceinline__ float collect_fast(const unsigned long long* word) {
    unsigned long long v;
    asm volatile(
        "{\n.reg .pred p;\n.reg .u32 n, lo, hi;\nmov.u32 n, 0;\n"
        "POLL:\nld.relaxed.gpu.global.u64 %0, [%1];\nmov.b64 {lo, hi}, %0;\nand.b32 lo, lo, 255;\n"
        "setp.eq.u32 p, lo, %2;\nvote.sync.all.pred p, p, 0xffffffff;\n@p bra.uni POLL_DONE;\n"
        "add.u32 n, n, 1;\nsetp.lt.u32 p, n, 0x400000;\n@p bra.uni POLL;\ntrap;\nPOLL_DONE:\n}\n"
        : "=l"(v) : "l"(word), "n"(NUM_CTAS) : "memory");
    return __ull2float_rn(v >> 8) * 0x1p-16f;
}
__device__ __forceinline__ void publish_sums(const float (&acc)[2][2], float* sums, unsigned int* counter, int wg, int w, int lane) {
#pragma unroll
    for (int m = 0; m < 2; m++)
#pragma unroll
        for (int h = 0; h < 2; h++) {
            const float v = quad_sum(acc[m][h]);
            if ((lane & 3) == 0) atomicAdd(sums + 64 * (2 * wg + m) + 16 * w + (lane >> 2) + 8 * h, v);
        }
    named_sync(1, 384);
    if (fresh_tid() == 0) asm volatile("red.release.gpu.global.add.u32 [%0], 1;" ::"l"(counter) : "memory");
}
__device__ __forceinline__ void grid_wait(const unsigned int* counter, unsigned int target) {
    if (fresh_tid() == 0) {
        unsigned int v, spins = 0;
        do {
            asm volatile("ld.acquire.gpu.global.u32 %0, [%1];" : "=r"(v) : "l"(counter) : "memory");
            if (++spins > (1u << 22)) __trap();
        } while ((int)(v - target) < 0);
    }
    __syncthreads();
}

struct Pass2 {
    uint32_t wg;
    uint32_t off;
    int step;
    uint32_t xs;
    uint32_t a_offs, xs_offs, bias_addr;
    uint32_t w;
};

static_assert(BAR_Y2FULL == 0 && BAR_XSFULL == 4 && BAR_TURN == 11 && BAR_ROWS == 51 && BAR_STAT == 53 &&
              sb + SM_RED + RED_SCALE * 4 == 230792, "layout");
#define PASS2_STATE ".reg .b32 qa<24>, qz<32>, o<24>, g<16>, p<2>, a<4>, lo<2>, hi<2>, h<2>, osc;"
__device__ __forceinline__ void pass2_start(const Pass2& c, const Params& prm) {
    asm volatile(
        "{\n"
        ".reg .b32 t<2>, c, ad, cnt, ybar;\n"
        ".reg .b16 xl, xh, xr;\n"
        ".reg .b64 w1d, dt;\n"
        ".reg .pred pt, pf, pw;\n"
        "setp.ne.b32 pt, 1, 0; setp.ne.b32 pf, 0, 0; mov.b32 c, 0x40D940D9; mov.b64 w1d, {%0, 0x40000040}; mad.lo.u32 ybar, %1, 8, 230800;\n"
        "mbarrier.try_wait.parity.shared::cta.b64 pw, [ybar], 0;\n"
        "@!pw bra.uni SPINY0;\n"
        "BACKY0:\n"
        "and.b32 t0, %3, 0xffff; shr.u32 t1, %3, 16;\n"
        "xor.b32 ad, t0, 0; add.u32 ad, ad, %2; ldmatrix.sync.aligned.m8n8.x4.shared.b16 {qa0,qa1,qa2,qa3}, [ad];\n"
        "xor.b32 ad, t0, 32; add.u32 ad, ad, %2; ldmatrix.sync.aligned.m8n8.x4.shared.b16 {qa4,qa5,qa6,qa7}, [ad];\n"
        "xor.b32 ad, t0, 64; add.u32 ad, ad, %2; ldmatrix.sync.aligned.m8n8.x4.shared.b16 {qa8,qa9,qa10,qa11}, [ad];\n"
        "xor.b32 ad, t0, 96; add.u32 ad, ad, %2; ldmatrix.sync.aligned.m8n8.x4.shared.b16 {qa12,qa13,qa14,qa15}, [ad];\n"
        "xor.b32 ad, t1, 0; add.u32 ad, ad, %2; ldmatrix.sync.aligned.m8n8.x4.shared.b16 {qa16,qa17,qa18,qa19}, [ad];\n"
        "xor.b32 ad, t1, 32; add.u32 ad, ad, %2; ldmatrix.sync.aligned.m8n8.x4.shared.b16 {qa20,qa21,qa22,qa23}, [ad];\n"
        "wgmma.fence.sync.aligned;\n"
        "add.s64 dt, w1d, 0; wgmma.mma_async.sync.aligned.m64n64k16.f16.f16.f16 {qz0,qz1,qz2,qz3,qz4,qz5,qz6,qz7,qz8,qz9,qz10,qz11,qz12,qz13,qz14,qz15}, {qa0,qa1,qa2,qa3}, dt, pf, 1, 1, 1;\n"
        "add.s64 dt, w1d, 128; wgmma.mma_async.sync.aligned.m64n64k16.f16.f16.f16 {qz0,qz1,qz2,qz3,qz4,qz5,qz6,qz7,qz8,qz9,qz10,qz11,qz12,qz13,qz14,qz15}, {qa4,qa5,qa6,qa7}, dt, pt, 1, 1, 1;\n"
        "add.s64 dt, w1d, 256; wgmma.mma_async.sync.aligned.m64n64k16.f16.f16.f16 {qz0,qz1,qz2,qz3,qz4,qz5,qz6,qz7,qz8,qz9,qz10,qz11,qz12,qz13,qz14,qz15}, {qa8,qa9,qa10,qa11}, dt, pt, 1, 1, 1;\n"
        "add.s64 dt, w1d, 384; wgmma.mma_async.sync.aligned.m64n64k16.f16.f16.f16 {qz0,qz1,qz2,qz3,qz4,qz5,qz6,qz7,qz8,qz9,qz10,qz11,qz12,qz13,qz14,qz15}, {qa12,qa13,qa14,qa15}, dt, pt, 1, 1, 1;\n"
        "add.s64 dt, w1d, 512; wgmma.mma_async.sync.aligned.m64n64k16.f16.f16.f16 {qz0,qz1,qz2,qz3,qz4,qz5,qz6,qz7,qz8,qz9,qz10,qz11,qz12,qz13,qz14,qz15}, {qa16,qa17,qa18,qa19}, dt, pt, 1, 1, 1;\n"
        "add.s64 dt, w1d, 640; wgmma.mma_async.sync.aligned.m64n64k16.f16.f16.f16 {qz0,qz1,qz2,qz3,qz4,qz5,qz6,qz7,qz8,qz9,qz10,qz11,qz12,qz13,qz14,qz15}, {qa20,qa21,qa22,qa23}, dt, pt, 1, 1, 1;\n"
        "wgmma.commit_group.sync.aligned;\n"
        "wgmma.wait_group.sync.aligned 0;\n"
        "fma.rn.f16x2 p0, qz0, qz0, c;\n"
        "mul.rn.f16x2 a0, qz0, p0; fma.rn.f16x2 p1, qz1, qz1, c;\n"
        "mov.b32 {xl, xh}, a0; tanh.approx.f16 xr, xl; cvt.u32.u16 lo0, xr; tanh.approx.f16 xr, xh; cvt.u32.u16 hi0, xr; mul.rn.f16x2 a1, qz1, p1; fma.rn.f16x2 p0, qz2, qz2, c;\n"
        "mov.b32 {xl, xh}, a1; tanh.approx.f16 xr, xl; cvt.u32.u16 lo1, xr; tanh.approx.f16 xr, xh; cvt.u32.u16 hi1, xr; mul.rn.f16x2 a2, qz2, p0; fma.rn.f16x2 p1, qz3, qz3, c; prmt.b32 h0, lo0, hi0, 0x5410;\n"
        "mov.b32 {xl, xh}, a2; tanh.approx.f16 xr, xl; cvt.u32.u16 lo0, xr; tanh.approx.f16 xr, xh; cvt.u32.u16 hi0, xr; mul.rn.f16x2 a3, qz3, p1; fma.rn.f16x2 p0, qz4, qz4, c; fma.rn.f16x2 g0, qz0, h0, qz0; prmt.b32 h1, lo1, hi1, 0x5410;\n"
        "mov.b32 {xl, xh}, a3; tanh.approx.f16 xr, xl; cvt.u32.u16 lo1, xr; tanh.approx.f16 xr, xh; cvt.u32.u16 hi1, xr; mul.rn.f16x2 a0, qz4, p0; fma.rn.f16x2 p1, qz5, qz5, c; fma.rn.f16x2 g1, qz1, h1, qz1; prmt.b32 h0, lo0, hi0, 0x5410;\n"
        "mov.b32 {xl, xh}, a0; tanh.approx.f16 xr, xl; cvt.u32.u16 lo0, xr; tanh.approx.f16 xr, xh; cvt.u32.u16 hi0, xr; mul.rn.f16x2 a1, qz5, p1; fma.rn.f16x2 p0, qz6, qz6, c; fma.rn.f16x2 g2, qz2, h0, qz2; prmt.b32 h1, lo1, hi1, 0x5410;\n"
        "mov.b32 {xl, xh}, a1; tanh.approx.f16 xr, xl; cvt.u32.u16 lo1, xr; tanh.approx.f16 xr, xh; cvt.u32.u16 hi1, xr; mul.rn.f16x2 a2, qz6, p0; fma.rn.f16x2 p1, qz7, qz7, c; fma.rn.f16x2 g3, qz3, h1, qz3; prmt.b32 h0, lo0, hi0, 0x5410;\n"
        "bra.uni DONE;\n"
        "SPINY0: mov.u32 cnt, 0;\n"
        "SPINY0L:\n"
        "mbarrier.try_wait.parity.shared::cta.b64 pw, [ybar], 0;\n"
        "@pw bra.uni BACKY0;\n"
        "add.u32 cnt, cnt, 1; setp.lt.u32 pw, cnt, 0x100000;\n"
        "@pw bra.uni SPINY0L;\n"
        "trap;\n"
        "DONE:\n"
        "}\n"
        :: "r"(prm.w1desc), "r"(c.wg), "r"(c.xs), "r"(c.a_offs) : "memory");
}
__device__ __forceinline__ bool pass2_head(const Pass2& c, uint32_t round) {
    uint32_t retry;
    asm volatile(
        "{\n"
        ".reg .b32 t<2>, tt, ad, cnt;\n"
        ".reg .pred pw;\n"
        "and.b32 t0, %3, 0xffff; shr.u32 t1, %3, 16;\n"
        "xor.b32 ad, t0, 0; add.u32 ad, ad, %4; ldmatrix.sync.aligned.m8n8.x4.shared.b16 {qa0,qa1,qa2,qa3}, [ad];\n"
        "xor.b32 ad, t0, 32; add.u32 ad, ad, %4; ldmatrix.sync.aligned.m8n8.x4.shared.b16 {qa4,qa5,qa6,qa7}, [ad];\n"
        "xor.b32 ad, t0, 64; add.u32 ad, ad, %4; ldmatrix.sync.aligned.m8n8.x4.shared.b16 {qa8,qa9,qa10,qa11}, [ad];\n"
        "xor.b32 ad, t0, 96; add.u32 ad, ad, %4; ldmatrix.sync.aligned.m8n8.x4.shared.b16 {qa12,qa13,qa14,qa15}, [ad];\n"
        "xor.b32 ad, t1, 0; add.u32 ad, ad, %4; ldmatrix.sync.aligned.m8n8.x4.shared.b16 {qa16,qa17,qa18,qa19}, [ad];\n"
        "xor.b32 ad, t1, 32; add.u32 ad, ad, %4; ldmatrix.sync.aligned.m8n8.x4.shared.b16 {qa20,qa21,qa22,qa23}, [ad];\n"
        "mov.b32 qz16, 0; mov.b32 qz17, 0; mov.b32 qz18, 0; mov.b32 qz19, 0; mov.b32 qz20, 0; mov.b32 qz21, 0; mov.b32 qz22, 0; mov.b32 qz23, 0; mov.b32 qz24, 0; mov.b32 qz25, 0; mov.b32 qz26, 0; mov.b32 qz27, 0; mov.b32 qz28, 0; mov.b32 qz29, 0; mov.b32 qz30, 0; mov.b32 qz31, 0;\n"
        "mov.b32 g4, 0; mov.b32 g5, 0; mov.b32 g6, 0; mov.b32 g7, 0; mov.b32 g8, 0; mov.b32 g9, 0; mov.b32 g10, 0; mov.b32 g11, 0; mov.b32 g12, 0; mov.b32 g13, 0; mov.b32 g14, 0; mov.b32 g15, 0;\n"
        "mov.u32 tt, 231224; mbarrier.try_wait.parity.shared::cta.b64 pw, [tt], %1;\n"
        "@!pw bra.uni SPINR;\n"
        "BACKR:\n"
        "mov.u32 tt, 230792; ld.shared.v2.b32 {osc, %0}, [tt];\n"
        "ld.shared.v4.b32 {o0,o1,o2,o3}, [%2+0];\n"
        "ld.shared.v4.b32 {o4,o5,o6,o7}, [%2+64];\n"
        "ld.shared.v4.b32 {o8,o9,o10,o11}, [%2+128];\n"
        "ld.shared.v4.b32 {o12,o13,o14,o15}, [%2+192];\n"
        "ld.shared.v4.b32 {o16,o17,o18,o19}, [%2+256];\n"
        "ld.shared.v4.b32 {o20,o21,o22,o23}, [%2+320];\n"
        "bra.uni DONE;\n"
        "SPINR: mov.u32 cnt, 0;\n"
        "SPINRL:\n"
        "mov.u32 tt, 231224; mbarrier.try_wait.parity.shared::cta.b64 pw, [tt], %1;\n"
        "@pw bra.uni BACKR;\n"
        "add.u32 cnt, cnt, 1; setp.lt.u32 pw, cnt, 0x100000;\n"
        "@pw bra.uni SPINRL;\n"
        "trap;\n"
        "DONE:\n"
        "}\n"
        : "=r"(retry) : "r"(round), "r"(c.bias_addr), "r"(c.a_offs), "r"(c.xs) : "memory");
    return __any_sync(0xffffffffu, retry);
}
__device__ __forceinline__ void pass2_tiles(const Pass2& c, const Params& prm) {
    asm volatile(
        "{\n"
        ".reg .b32 v<8>, n, off, c, tt, ad, cnt, ybar, xbar, tbar, tpar, id;\n"
        ".reg .b16 xl, xh, xr;\n"
        ".reg .f32 f0, f1;\n"
        ".reg .b64 w1d, w2d, dt, gp, pol;\n"
        ".reg .pred pt, pf, pr, pw, pl, pm, pz, pn;\n"
        "setp.ne.b32 pt, 1, 0; setp.ne.b32 pf, 0, 0; setp.eq.u32 pl, %9, 0; setp.eq.u32 pz, %0, 0;\n"
        "mov.b32 c, 0x40D940D9;\n"
        "mov.b64 w1d, {%0, 0x40000040}; mov.b64 w2d, {%1, 0x80000020};\n"
        "mad.lo.u32 ybar, %2, 8, 230800; mad.lo.u32 xbar, %2, 8, 230832; add.u32 id, %2, 2;\n"
        "mad.lo.u32 tbar, %2, 64, 230888; setp.eq.u32 pr, %2, 0; selp.u32 tpar, 1, 0, pr; mov.u32 tt, %laneid; setp.eq.u32 pn, tt, 0;\n"
        "mov.u32 n, -1; add.u32 off, %3, %8; mov.pred pm, pt; createpolicy.fractional.L2::evict_first.b64 pol, 1.0;\n"
        "LOOP:\n"
        "@!pm bra.uni SKIP0;\n"
        "wgmma.fence.sync.aligned;\n"
        "add.s64 dt, w1d, 768; wgmma.mma_async.sync.aligned.m64n64k16.f16.f16.f16 {qz16,qz17,qz18,qz19,qz20,qz21,qz22,qz23,qz24,qz25,qz26,qz27,qz28,qz29,qz30,qz31}, {qa0,qa1,qa2,qa3}, dt, pf, 1, 1, 1;\n"
        "add.s64 dt, w1d, 896; wgmma.mma_async.sync.aligned.m64n64k16.f16.f16.f16 {qz16,qz17,qz18,qz19,qz20,qz21,qz22,qz23,qz24,qz25,qz26,qz27,qz28,qz29,qz30,qz31}, {qa4,qa5,qa6,qa7}, dt, pt, 1, 1, 1;\n"
        "add.s64 dt, w1d, 1024; wgmma.mma_async.sync.aligned.m64n64k16.f16.f16.f16 {qz16,qz17,qz18,qz19,qz20,qz21,qz22,qz23,qz24,qz25,qz26,qz27,qz28,qz29,qz30,qz31}, {qa8,qa9,qa10,qa11}, dt, pt, 1, 1, 1;\n"
        "add.s64 dt, w1d, 1152; wgmma.mma_async.sync.aligned.m64n64k16.f16.f16.f16 {qz16,qz17,qz18,qz19,qz20,qz21,qz22,qz23,qz24,qz25,qz26,qz27,qz28,qz29,qz30,qz31}, {qa12,qa13,qa14,qa15}, dt, pt, 1, 1, 1;\n"
        "add.s64 dt, w1d, 1280; wgmma.mma_async.sync.aligned.m64n64k16.f16.f16.f16 {qz16,qz17,qz18,qz19,qz20,qz21,qz22,qz23,qz24,qz25,qz26,qz27,qz28,qz29,qz30,qz31}, {qa16,qa17,qa18,qa19}, dt, pt, 1, 1, 1;\n"
        "add.s64 dt, w1d, 1408; wgmma.mma_async.sync.aligned.m64n64k16.f16.f16.f16 {qz16,qz17,qz18,qz19,qz20,qz21,qz22,qz23,qz24,qz25,qz26,qz27,qz28,qz29,qz30,qz31}, {qa20,qa21,qa22,qa23}, dt, pt, 1, 1, 1;\n"
        "SKIP0:\n"
        "setp.lt.s32 pr, n, 0;\n"
        "@pr bra.uni FIRST;\n"
        "and.b32 tt, n, 1; mbarrier.try_wait.parity.shared::cta.b64 pw, [xbar], tt;\n"
        "@!pw bra.uni SPINX;\n"
        "BACKX:\n"
        "and.b32 ad, %6, 0xffff; add.u32 ad, ad, %4; ld.shared.v4.b32 {v0,v1,v2,v3}, [ad+0];\n"
        "shr.u32 ad, %6, 16; add.u32 ad, ad, %4; ld.shared.v4.b32 {v4,v5,v6,v7}, [ad+0];\n"
        "mov.b32 {xl, xh}, o0; cvt.f32.f16 f0, xl; cvt.f32.f16 f1, xh; cvt.rn.bf16x2.f32 tt, f1, f0; fma.rn.bf16x2 v0, tt, osc, v0;\n"
        "mov.b32 {xl, xh}, o2; cvt.f32.f16 f0, xl; cvt.f32.f16 f1, xh; cvt.rn.bf16x2.f32 tt, f1, f0; fma.rn.bf16x2 v1, tt, osc, v1;\n"
        "mov.b32 {xl, xh}, o4; cvt.f32.f16 f0, xl; cvt.f32.f16 f1, xh; cvt.rn.bf16x2.f32 tt, f1, f0; fma.rn.bf16x2 v2, tt, osc, v2;\n"
        "mov.b32 {xl, xh}, o6; cvt.f32.f16 f0, xl; cvt.f32.f16 f1, xh; cvt.rn.bf16x2.f32 tt, f1, f0; fma.rn.bf16x2 v3, tt, osc, v3;\n"
        "and.b32 ad, %6, 0xffff; add.u32 ad, ad, %4; st.shared.v4.b32 [ad+0], {v0,v1,v2,v3};\n"
        "and.b32 ad, %6, 0xffff; add.u32 ad, ad, %4; ld.shared.v4.b32 {v0,v1,v2,v3}, [ad+64];\n"
        "mov.b32 {xl, xh}, o1; cvt.f32.f16 f0, xl; cvt.f32.f16 f1, xh; cvt.rn.bf16x2.f32 tt, f1, f0; fma.rn.bf16x2 v4, tt, osc, v4;\n"
        "mov.b32 {xl, xh}, o3; cvt.f32.f16 f0, xl; cvt.f32.f16 f1, xh; cvt.rn.bf16x2.f32 tt, f1, f0; fma.rn.bf16x2 v5, tt, osc, v5;\n"
        "mov.b32 {xl, xh}, o5; cvt.f32.f16 f0, xl; cvt.f32.f16 f1, xh; cvt.rn.bf16x2.f32 tt, f1, f0; fma.rn.bf16x2 v6, tt, osc, v6;\n"
        "mov.b32 {xl, xh}, o7; cvt.f32.f16 f0, xl; cvt.f32.f16 f1, xh; cvt.rn.bf16x2.f32 tt, f1, f0; fma.rn.bf16x2 v7, tt, osc, v7;\n"
        "shr.u32 ad, %6, 16; add.u32 ad, ad, %4; st.shared.v4.b32 [ad+0], {v4,v5,v6,v7};\n"
        "shr.u32 ad, %6, 16; add.u32 ad, ad, %4; ld.shared.v4.b32 {v4,v5,v6,v7}, [ad+64];\n"
        "ld.shared.v4.b32 {o0,o1,o2,o3}, [%7+0];\n"
        "ld.shared.v4.b32 {o4,o5,o6,o7}, [%7+64];\n"
        "mov.b32 {xl, xh}, o8; cvt.f32.f16 f0, xl; cvt.f32.f16 f1, xh; cvt.rn.bf16x2.f32 tt, f1, f0; fma.rn.bf16x2 v0, tt, osc, v0;\n"
        "mov.b32 {xl, xh}, o10; cvt.f32.f16 f0, xl; cvt.f32.f16 f1, xh; cvt.rn.bf16x2.f32 tt, f1, f0; fma.rn.bf16x2 v1, tt, osc, v1;\n"
        "mov.b32 {xl, xh}, o12; cvt.f32.f16 f0, xl; cvt.f32.f16 f1, xh; cvt.rn.bf16x2.f32 tt, f1, f0; fma.rn.bf16x2 v2, tt, osc, v2;\n"
        "mov.b32 {xl, xh}, o14; cvt.f32.f16 f0, xl; cvt.f32.f16 f1, xh; cvt.rn.bf16x2.f32 tt, f1, f0; fma.rn.bf16x2 v3, tt, osc, v3;\n"
        "and.b32 ad, %6, 0xffff; add.u32 ad, ad, %4; st.shared.v4.b32 [ad+64], {v0,v1,v2,v3};\n"
        "and.b32 ad, %6, 0xffff; add.u32 ad, ad, %4; ld.shared.v4.b32 {v0,v1,v2,v3}, [ad+128];\n"
        "mov.b32 {xl, xh}, o9; cvt.f32.f16 f0, xl; cvt.f32.f16 f1, xh; cvt.rn.bf16x2.f32 tt, f1, f0; fma.rn.bf16x2 v4, tt, osc, v4;\n"
        "mov.b32 {xl, xh}, o11; cvt.f32.f16 f0, xl; cvt.f32.f16 f1, xh; cvt.rn.bf16x2.f32 tt, f1, f0; fma.rn.bf16x2 v5, tt, osc, v5;\n"
        "mov.b32 {xl, xh}, o13; cvt.f32.f16 f0, xl; cvt.f32.f16 f1, xh; cvt.rn.bf16x2.f32 tt, f1, f0; fma.rn.bf16x2 v6, tt, osc, v6;\n"
        "mov.b32 {xl, xh}, o15; cvt.f32.f16 f0, xl; cvt.f32.f16 f1, xh; cvt.rn.bf16x2.f32 tt, f1, f0; fma.rn.bf16x2 v7, tt, osc, v7;\n"
        "shr.u32 ad, %6, 16; add.u32 ad, ad, %4; st.shared.v4.b32 [ad+64], {v4,v5,v6,v7};\n"
        "shr.u32 ad, %6, 16; add.u32 ad, ad, %4; ld.shared.v4.b32 {v4,v5,v6,v7}, [ad+128];\n"
        "ld.shared.v4.b32 {o8,o9,o10,o11}, [%7+128];\n"
        "ld.shared.v4.b32 {o12,o13,o14,o15}, [%7+192];\n"
        "mov.b32 {xl, xh}, o16; cvt.f32.f16 f0, xl; cvt.f32.f16 f1, xh; cvt.rn.bf16x2.f32 tt, f1, f0; fma.rn.bf16x2 v0, tt, osc, v0;\n"
        "mov.b32 {xl, xh}, o18; cvt.f32.f16 f0, xl; cvt.f32.f16 f1, xh; cvt.rn.bf16x2.f32 tt, f1, f0; fma.rn.bf16x2 v1, tt, osc, v1;\n"
        "mov.b32 {xl, xh}, o20; cvt.f32.f16 f0, xl; cvt.f32.f16 f1, xh; cvt.rn.bf16x2.f32 tt, f1, f0; fma.rn.bf16x2 v2, tt, osc, v2;\n"
        "mov.b32 {xl, xh}, o22; cvt.f32.f16 f0, xl; cvt.f32.f16 f1, xh; cvt.rn.bf16x2.f32 tt, f1, f0; fma.rn.bf16x2 v3, tt, osc, v3;\n"
        "and.b32 ad, %6, 0xffff; add.u32 ad, ad, %4; st.shared.v4.b32 [ad+128], {v0,v1,v2,v3};\n"
        "mov.b32 {xl, xh}, o17; cvt.f32.f16 f0, xl; cvt.f32.f16 f1, xh; cvt.rn.bf16x2.f32 tt, f1, f0; fma.rn.bf16x2 v4, tt, osc, v4;\n"
        "mov.b32 {xl, xh}, o19; cvt.f32.f16 f0, xl; cvt.f32.f16 f1, xh; cvt.rn.bf16x2.f32 tt, f1, f0; fma.rn.bf16x2 v5, tt, osc, v5;\n"
        "mov.b32 {xl, xh}, o21; cvt.f32.f16 f0, xl; cvt.f32.f16 f1, xh; cvt.rn.bf16x2.f32 tt, f1, f0; fma.rn.bf16x2 v6, tt, osc, v6;\n"
        "mov.b32 {xl, xh}, o23; cvt.f32.f16 f0, xl; cvt.f32.f16 f1, xh; cvt.rn.bf16x2.f32 tt, f1, f0; fma.rn.bf16x2 v7, tt, osc, v7;\n"
        "shr.u32 ad, %6, 16; add.u32 ad, ad, %4; st.shared.v4.b32 [ad+128], {v4,v5,v6,v7};\n"
        "ld.shared.v4.b32 {o16,o17,o18,o19}, [%7+256];\n"
        "ld.shared.v4.b32 {o20,o21,o22,o23}, [%7+320];\n"
        "FIRST:\n"
        "@pz bra.uni B7;\n"
        "mov.b32 {xl, xh}, a2; tanh.approx.f16 xr, xl; cvt.u32.u16 lo0, xr; tanh.approx.f16 xr, xh; cvt.u32.u16 hi0, xr; mul.rn.f16x2 a3, qz7, p1; fma.rn.f16x2 p0, qz8, qz8, c; fma.rn.f16x2 g4, qz4, h0, qz4; prmt.b32 h1, lo1, hi1, 0x5410;\n"
        "B7:\n"
        "fence.proxy.async.shared::cta;\n"
        "add.u32 tt, id, 4;\n"
        "@pl bra.uni STORE;\n"
        "bar.arrive tt, 128;\n"
        "STOREB:\n"
        ASM_MARK
        "@!pm bra.uni DONE;\n"
        "add.s32 n, n, 1; sub.u32 off, off, %8; setp.lt.s32 pm, n, 7;\n"
        "@pz bra.uni B10;\n"
        "mov.b32 {xl, xh}, a3; tanh.approx.f16 xr, xl; cvt.u32.u16 lo1, xr; tanh.approx.f16 xr, xh; cvt.u32.u16 hi1, xr; mul.rn.f16x2 a0, qz8, p0; fma.rn.f16x2 p1, qz9, qz9, c; fma.rn.f16x2 g5, qz5, h1, qz5; prmt.b32 h0, lo0, hi0, 0x5410;\n"
        "mov.b32 {xl, xh}, a0; tanh.approx.f16 xr, xl; cvt.u32.u16 lo0, xr; tanh.approx.f16 xr, xh; cvt.u32.u16 hi0, xr; mul.rn.f16x2 a1, qz9, p1; fma.rn.f16x2 p0, qz10, qz10, c; fma.rn.f16x2 g6, qz6, h0, qz6; prmt.b32 h1, lo1, hi1, 0x5410;\n"
        "mov.b32 {xl, xh}, a1; tanh.approx.f16 xr, xl; cvt.u32.u16 lo1, xr; tanh.approx.f16 xr, xh; cvt.u32.u16 hi1, xr; mul.rn.f16x2 a2, qz10, p0; fma.rn.f16x2 p1, qz11, qz11, c; fma.rn.f16x2 g7, qz7, h1, qz7; prmt.b32 h0, lo0, hi0, 0x5410;\n"
        "B10:\n"
        "setp.eq.s32 pr, n, 0;\n"
        "@pr bra.uni SPINW0;\n"
        "BACKW0:\n"
        "wgmma.fence.sync.aligned;\n"
        "add.s64 dt, w2d, 0; wgmma.mma_async.sync.aligned.m64n96k16.f16.f16.f16 {o0,o1,o2,o3,o4,o5,o6,o7,o8,o9,o10,o11,o12,o13,o14,o15,o16,o17,o18,o19,o20,o21,o22,o23}, {g0,g1,g2,g3}, dt, pt, 1, 1, 1;\n"
        "add.s64 dt, w2d, 64; wgmma.mma_async.sync.aligned.m64n96k16.f16.f16.f16 {o0,o1,o2,o3,o4,o5,o6,o7,o8,o9,o10,o11,o12,o13,o14,o15,o16,o17,o18,o19,o20,o21,o22,o23}, {g4,g5,g6,g7}, dt, pt, 1, 1, 1;\n"
        "wgmma.commit_group.sync.aligned;\n"
        "@pz bra.uni B14;\n"
        "mov.b32 {xl, xh}, a2; tanh.approx.f16 xr, xl; cvt.u32.u16 lo0, xr; tanh.approx.f16 xr, xh; cvt.u32.u16 hi0, xr; mul.rn.f16x2 a3, qz11, p1; fma.rn.f16x2 p0, qz12, qz12, c; fma.rn.f16x2 g8, qz8, h0, qz8; prmt.b32 h1, lo1, hi1, 0x5410;\n"
        "mov.b32 {xl, xh}, a3; tanh.approx.f16 xr, xl; cvt.u32.u16 lo1, xr; tanh.approx.f16 xr, xh; cvt.u32.u16 hi1, xr; mul.rn.f16x2 a0, qz12, p0; fma.rn.f16x2 p1, qz13, qz13, c; fma.rn.f16x2 g9, qz9, h1, qz9; prmt.b32 h0, lo0, hi0, 0x5410;\n"
        "mov.b32 {xl, xh}, a0; tanh.approx.f16 xr, xl; cvt.u32.u16 lo0, xr; tanh.approx.f16 xr, xh; cvt.u32.u16 hi0, xr; mul.rn.f16x2 a1, qz13, p1; fma.rn.f16x2 p0, qz14, qz14, c; fma.rn.f16x2 g10, qz10, h0, qz10; prmt.b32 h1, lo1, hi1, 0x5410;\n"
        "mov.b32 {xl, xh}, a1; tanh.approx.f16 xr, xl; cvt.u32.u16 lo1, xr; tanh.approx.f16 xr, xh; cvt.u32.u16 hi1, xr; mul.rn.f16x2 a2, qz14, p0; fma.rn.f16x2 p1, qz15, qz15, c; fma.rn.f16x2 g11, qz11, h1, qz11; prmt.b32 h0, lo0, hi0, 0x5410;\n"
        "B14:\n"
        "wgmma.wait_group.sync.aligned 0;\n"
        "wgmma.fence.sync.aligned;\n"
        "add.s64 dt, w2d, 128; wgmma.mma_async.sync.aligned.m64n96k16.f16.f16.f16 {o0,o1,o2,o3,o4,o5,o6,o7,o8,o9,o10,o11,o12,o13,o14,o15,o16,o17,o18,o19,o20,o21,o22,o23}, {g8,g9,g10,g11}, dt, pt, 1, 1, 1;\n"
        "wgmma.commit_group.sync.aligned;\n"
        "@pz bra.uni B18;\n"
        "mov.b32 {xl, xh}, a2; tanh.approx.f16 xr, xl; cvt.u32.u16 lo0, xr; tanh.approx.f16 xr, xh; cvt.u32.u16 hi0, xr; mul.rn.f16x2 a3, qz15, p1; fma.rn.f16x2 p0, qz16, qz16, c; fma.rn.f16x2 g12, qz12, h0, qz12; prmt.b32 h1, lo1, hi1, 0x5410;\n"
        "mov.b32 {xl, xh}, a3; tanh.approx.f16 xr, xl; cvt.u32.u16 lo1, xr; tanh.approx.f16 xr, xh; cvt.u32.u16 hi1, xr; mul.rn.f16x2 a0, qz16, p0; fma.rn.f16x2 p1, qz17, qz17, c; fma.rn.f16x2 g13, qz13, h1, qz13; prmt.b32 h0, lo0, hi0, 0x5410;\n"
        "mov.b32 {xl, xh}, a0; tanh.approx.f16 xr, xl; cvt.u32.u16 lo0, xr; tanh.approx.f16 xr, xh; cvt.u32.u16 hi0, xr; mul.rn.f16x2 a1, qz17, p1; fma.rn.f16x2 p0, qz18, qz18, c; fma.rn.f16x2 g14, qz14, h0, qz14; prmt.b32 h1, lo1, hi1, 0x5410;\n"
        "mov.b32 {xl, xh}, a1; tanh.approx.f16 xr, xl; cvt.u32.u16 lo1, xr; tanh.approx.f16 xr, xh; cvt.u32.u16 hi1, xr; mul.rn.f16x2 a2, qz18, p0; fma.rn.f16x2 p1, qz19, qz19, c; fma.rn.f16x2 g15, qz15, h1, qz15; prmt.b32 h0, lo0, hi0, 0x5410;\n"
        "B18:\n"
        "mad.lo.u32 tt, n, 8, tbar; mbarrier.try_wait.parity.shared::cta.b64 pw, [tt], tpar;\n"
        "@!pw bra.uni SPINT;\n"
        "BACKT:\n"
        "wgmma.fence.sync.aligned;\n"
        "add.s64 dt, w2d, 192; wgmma.mma_async.sync.aligned.m64n96k16.f16.f16.f16 {o0,o1,o2,o3,o4,o5,o6,o7,o8,o9,o10,o11,o12,o13,o14,o15,o16,o17,o18,o19,o20,o21,o22,o23}, {g12,g13,g14,g15}, dt, pt, 1, 1, 1;\n"
        "add.s64 dt, w1d, 1536; wgmma.mma_async.sync.aligned.m64n64k16.f16.f16.f16 {qz0,qz1,qz2,qz3,qz4,qz5,qz6,qz7,qz8,qz9,qz10,qz11,qz12,qz13,qz14,qz15}, {qa0,qa1,qa2,qa3}, dt, pf, 1, 1, 1;\n"
        "add.s64 dt, w1d, 1664; wgmma.mma_async.sync.aligned.m64n64k16.f16.f16.f16 {qz0,qz1,qz2,qz3,qz4,qz5,qz6,qz7,qz8,qz9,qz10,qz11,qz12,qz13,qz14,qz15}, {qa4,qa5,qa6,qa7}, dt, pt, 1, 1, 1;\n"
        "add.s64 dt, w1d, 1792; wgmma.mma_async.sync.aligned.m64n64k16.f16.f16.f16 {qz0,qz1,qz2,qz3,qz4,qz5,qz6,qz7,qz8,qz9,qz10,qz11,qz12,qz13,qz14,qz15}, {qa8,qa9,qa10,qa11}, dt, pt, 1, 1, 1;\n"
        "wgmma.commit_group.sync.aligned;\n"
        "@pl bra.uni YLOAD;\n"
        "YLOADB:\n"
        "@pz bra.uni B22;\n"
        "mov.b32 {xl, xh}, a2; tanh.approx.f16 xr, xl; cvt.u32.u16 lo0, xr; tanh.approx.f16 xr, xh; cvt.u32.u16 hi0, xr; mul.rn.f16x2 a3, qz19, p1; fma.rn.f16x2 p0, qz20, qz20, c; fma.rn.f16x2 g0, qz16, h0, qz16; prmt.b32 h1, lo1, hi1, 0x5410;\n"
        "mov.b32 {xl, xh}, a3; tanh.approx.f16 xr, xl; cvt.u32.u16 lo1, xr; tanh.approx.f16 xr, xh; cvt.u32.u16 hi1, xr; mul.rn.f16x2 a0, qz20, p0; fma.rn.f16x2 p1, qz21, qz21, c; fma.rn.f16x2 g1, qz17, h1, qz17; prmt.b32 h0, lo0, hi0, 0x5410;\n"
        "mov.b32 {xl, xh}, a0; tanh.approx.f16 xr, xl; cvt.u32.u16 lo0, xr; tanh.approx.f16 xr, xh; cvt.u32.u16 hi0, xr; mul.rn.f16x2 a1, qz21, p1; fma.rn.f16x2 p0, qz22, qz22, c; fma.rn.f16x2 g2, qz18, h0, qz18; prmt.b32 h1, lo1, hi1, 0x5410;\n"
        "mov.b32 {xl, xh}, a1; tanh.approx.f16 xr, xl; cvt.u32.u16 lo1, xr; tanh.approx.f16 xr, xh; cvt.u32.u16 hi1, xr; mul.rn.f16x2 a2, qz22, p0; fma.rn.f16x2 p1, qz23, qz23, c; fma.rn.f16x2 g3, qz19, h1, qz19; prmt.b32 h0, lo0, hi0, 0x5410;\n"
        "B22:\n"
        "wgmma.fence.sync.aligned;\n"
        "add.s64 dt, w1d, 1920; wgmma.mma_async.sync.aligned.m64n64k16.f16.f16.f16 {qz0,qz1,qz2,qz3,qz4,qz5,qz6,qz7,qz8,qz9,qz10,qz11,qz12,qz13,qz14,qz15}, {qa12,qa13,qa14,qa15}, dt, pt, 1, 1, 1;\n"
        "add.s64 dt, w1d, 2048; wgmma.mma_async.sync.aligned.m64n64k16.f16.f16.f16 {qz0,qz1,qz2,qz3,qz4,qz5,qz6,qz7,qz8,qz9,qz10,qz11,qz12,qz13,qz14,qz15}, {qa16,qa17,qa18,qa19}, dt, pt, 1, 1, 1;\n"
        "add.s64 dt, w1d, 2176; wgmma.mma_async.sync.aligned.m64n64k16.f16.f16.f16 {qz0,qz1,qz2,qz3,qz4,qz5,qz6,qz7,qz8,qz9,qz10,qz11,qz12,qz13,qz14,qz15}, {qa20,qa21,qa22,qa23}, dt, pt, 1, 1, 1;\n"
        "wgmma.commit_group.sync.aligned;\n"
        "@pz bra.uni B26;\n"
        "mov.b32 {xl, xh}, a2; tanh.approx.f16 xr, xl; cvt.u32.u16 lo0, xr; tanh.approx.f16 xr, xh; cvt.u32.u16 hi0, xr; mul.rn.f16x2 a3, qz23, p1; fma.rn.f16x2 p0, qz24, qz24, c; fma.rn.f16x2 g4, qz20, h0, qz20; prmt.b32 h1, lo1, hi1, 0x5410;\n"
        "mov.b32 {xl, xh}, a3; tanh.approx.f16 xr, xl; cvt.u32.u16 lo1, xr; tanh.approx.f16 xr, xh; cvt.u32.u16 hi1, xr; mul.rn.f16x2 a0, qz24, p0; fma.rn.f16x2 p1, qz25, qz25, c; fma.rn.f16x2 g5, qz21, h1, qz21; prmt.b32 h0, lo0, hi0, 0x5410;\n"
        "mov.b32 {xl, xh}, a0; tanh.approx.f16 xr, xl; cvt.u32.u16 lo0, xr; tanh.approx.f16 xr, xh; cvt.u32.u16 hi0, xr; mul.rn.f16x2 a1, qz25, p1; fma.rn.f16x2 p0, qz26, qz26, c; fma.rn.f16x2 g6, qz22, h0, qz22; prmt.b32 h1, lo1, hi1, 0x5410;\n"
        "mov.b32 {xl, xh}, a1; tanh.approx.f16 xr, xl; cvt.u32.u16 lo1, xr; tanh.approx.f16 xr, xh; cvt.u32.u16 hi1, xr; mul.rn.f16x2 a2, qz26, p0; fma.rn.f16x2 p1, qz27, qz27, c; fma.rn.f16x2 g7, qz23, h1, qz23; prmt.b32 h0, lo0, hi0, 0x5410;\n"
        "B26:\n"
        "wgmma.wait_group.sync.aligned 2;\n"
        "wgmma.fence.sync.aligned;\n"
        "add.s64 dt, w2d, 256; wgmma.mma_async.sync.aligned.m64n96k16.f16.f16.f16 {o0,o1,o2,o3,o4,o5,o6,o7,o8,o9,o10,o11,o12,o13,o14,o15,o16,o17,o18,o19,o20,o21,o22,o23}, {g0,g1,g2,g3}, dt, pt, 1, 1, 1;\n"
        "add.s64 dt, w2d, 320; wgmma.mma_async.sync.aligned.m64n96k16.f16.f16.f16 {o0,o1,o2,o3,o4,o5,o6,o7,o8,o9,o10,o11,o12,o13,o14,o15,o16,o17,o18,o19,o20,o21,o22,o23}, {g4,g5,g6,g7}, dt, pt, 1, 1, 1;\n"
        "wgmma.commit_group.sync.aligned;\n"
        "@pz bra.uni B30;\n"
        "mov.b32 {xl, xh}, a2; tanh.approx.f16 xr, xl; cvt.u32.u16 lo0, xr; tanh.approx.f16 xr, xh; cvt.u32.u16 hi0, xr; mul.rn.f16x2 a3, qz27, p1; fma.rn.f16x2 p0, qz28, qz28, c; fma.rn.f16x2 g8, qz24, h0, qz24; prmt.b32 h1, lo1, hi1, 0x5410;\n"
        "mov.b32 {xl, xh}, a3; tanh.approx.f16 xr, xl; cvt.u32.u16 lo1, xr; tanh.approx.f16 xr, xh; cvt.u32.u16 hi1, xr; mul.rn.f16x2 a0, qz28, p0; fma.rn.f16x2 p1, qz29, qz29, c; fma.rn.f16x2 g9, qz25, h1, qz25; prmt.b32 h0, lo0, hi0, 0x5410;\n"
        "mov.b32 {xl, xh}, a0; tanh.approx.f16 xr, xl; cvt.u32.u16 lo0, xr; tanh.approx.f16 xr, xh; cvt.u32.u16 hi0, xr; mul.rn.f16x2 a1, qz29, p1; fma.rn.f16x2 p0, qz30, qz30, c; fma.rn.f16x2 g10, qz26, h0, qz26; prmt.b32 h1, lo1, hi1, 0x5410;\n"
        "mov.b32 {xl, xh}, a1; tanh.approx.f16 xr, xl; cvt.u32.u16 lo1, xr; tanh.approx.f16 xr, xh; cvt.u32.u16 hi1, xr; mul.rn.f16x2 a2, qz30, p0; fma.rn.f16x2 p1, qz31, qz31, c; fma.rn.f16x2 g11, qz27, h1, qz27; prmt.b32 h0, lo0, hi0, 0x5410;\n"
        "B30:\n"
        "wgmma.wait_group.sync.aligned 1;\n"
        "wgmma.fence.sync.aligned;\n"
        "add.s64 dt, w2d, 384; wgmma.mma_async.sync.aligned.m64n96k16.f16.f16.f16 {o0,o1,o2,o3,o4,o5,o6,o7,o8,o9,o10,o11,o12,o13,o14,o15,o16,o17,o18,o19,o20,o21,o22,o23}, {g8,g9,g10,g11}, dt, pt, 1, 1, 1;\n"
        "wgmma.commit_group.sync.aligned;\n"
        "@pz bra.uni B34;\n"
        "mov.b32 {xl, xh}, a2; tanh.approx.f16 xr, xl; cvt.u32.u16 lo0, xr; tanh.approx.f16 xr, xh; cvt.u32.u16 hi0, xr; mul.rn.f16x2 a3, qz31, p1; fma.rn.f16x2 p0, qz0, qz0, c; fma.rn.f16x2 g12, qz28, h0, qz28; prmt.b32 h1, lo1, hi1, 0x5410;\n"
        "mov.b32 {xl, xh}, a3; tanh.approx.f16 xr, xl; cvt.u32.u16 lo1, xr; tanh.approx.f16 xr, xh; cvt.u32.u16 hi1, xr; mul.rn.f16x2 a0, qz0, p0; fma.rn.f16x2 p1, qz1, qz1, c; fma.rn.f16x2 g13, qz29, h1, qz29; prmt.b32 h0, lo0, hi0, 0x5410;\n"
        "mov.b32 {xl, xh}, a0; tanh.approx.f16 xr, xl; cvt.u32.u16 lo0, xr; tanh.approx.f16 xr, xh; cvt.u32.u16 hi0, xr; mul.rn.f16x2 a1, qz1, p1; fma.rn.f16x2 p0, qz2, qz2, c; fma.rn.f16x2 g14, qz30, h0, qz30; prmt.b32 h1, lo1, hi1, 0x5410;\n"
        "mov.b32 {xl, xh}, a1; tanh.approx.f16 xr, xl; cvt.u32.u16 lo1, xr; tanh.approx.f16 xr, xh; cvt.u32.u16 hi1, xr; mul.rn.f16x2 a2, qz2, p0; fma.rn.f16x2 p1, qz3, qz3, c; fma.rn.f16x2 g15, qz31, h1, qz31; prmt.b32 h0, lo0, hi0, 0x5410;\n"
        "B34:\n"
        "wgmma.wait_group.sync.aligned 1;\n"
        "wgmma.fence.sync.aligned;\n"
        "add.s64 dt, w2d, 448; wgmma.mma_async.sync.aligned.m64n96k16.f16.f16.f16 {o0,o1,o2,o3,o4,o5,o6,o7,o8,o9,o10,o11,o12,o13,o14,o15,o16,o17,o18,o19,o20,o21,o22,o23}, {g12,g13,g14,g15}, dt, pt, 1, 1, 1;\n"
        "add.s64 dt, w1d, 2304; wgmma.mma_async.sync.aligned.m64n64k16.f16.f16.f16 {qz16,qz17,qz18,qz19,qz20,qz21,qz22,qz23,qz24,qz25,qz26,qz27,qz28,qz29,qz30,qz31}, {qa0,qa1,qa2,qa3}, dt, pf, 1, 1, 1;\n"
        "add.s64 dt, w1d, 2432; wgmma.mma_async.sync.aligned.m64n64k16.f16.f16.f16 {qz16,qz17,qz18,qz19,qz20,qz21,qz22,qz23,qz24,qz25,qz26,qz27,qz28,qz29,qz30,qz31}, {qa4,qa5,qa6,qa7}, dt, pt, 1, 1, 1;\n"
        "add.s64 dt, w1d, 2560; wgmma.mma_async.sync.aligned.m64n64k16.f16.f16.f16 {qz16,qz17,qz18,qz19,qz20,qz21,qz22,qz23,qz24,qz25,qz26,qz27,qz28,qz29,qz30,qz31}, {qa8,qa9,qa10,qa11}, dt, pt, 1, 1, 1;\n"
        "wgmma.commit_group.sync.aligned;\n"
        "@pz bra.uni B38;\n"
        "mov.b32 {xl, xh}, a2; tanh.approx.f16 xr, xl; cvt.u32.u16 lo0, xr; tanh.approx.f16 xr, xh; cvt.u32.u16 hi0, xr; mul.rn.f16x2 a3, qz3, p1; fma.rn.f16x2 p0, qz4, qz4, c; fma.rn.f16x2 g0, qz0, h0, qz0; prmt.b32 h1, lo1, hi1, 0x5410;\n"
        "mov.b32 {xl, xh}, a3; tanh.approx.f16 xr, xl; cvt.u32.u16 lo1, xr; tanh.approx.f16 xr, xh; cvt.u32.u16 hi1, xr; mul.rn.f16x2 a0, qz4, p0; fma.rn.f16x2 p1, qz5, qz5, c; fma.rn.f16x2 g1, qz1, h1, qz1; prmt.b32 h0, lo0, hi0, 0x5410;\n"
        "mov.b32 {xl, xh}, a0; tanh.approx.f16 xr, xl; cvt.u32.u16 lo0, xr; tanh.approx.f16 xr, xh; cvt.u32.u16 hi0, xr; mul.rn.f16x2 a1, qz5, p1; fma.rn.f16x2 p0, qz6, qz6, c; fma.rn.f16x2 g2, qz2, h0, qz2; prmt.b32 h1, lo1, hi1, 0x5410;\n"
        "mov.b32 {xl, xh}, a1; tanh.approx.f16 xr, xl; cvt.u32.u16 lo1, xr; tanh.approx.f16 xr, xh; cvt.u32.u16 hi1, xr; mul.rn.f16x2 a2, qz6, p0; fma.rn.f16x2 p1, qz7, qz7, c; fma.rn.f16x2 g3, qz3, h1, qz3; prmt.b32 h0, lo0, hi0, 0x5410;\n"
        "B38:\n"
        "wgmma.fence.sync.aligned;\n"
        "add.s64 dt, w1d, 2688; wgmma.mma_async.sync.aligned.m64n64k16.f16.f16.f16 {qz16,qz17,qz18,qz19,qz20,qz21,qz22,qz23,qz24,qz25,qz26,qz27,qz28,qz29,qz30,qz31}, {qa12,qa13,qa14,qa15}, dt, pt, 1, 1, 1;\n"
        "add.s64 dt, w1d, 2816; wgmma.mma_async.sync.aligned.m64n64k16.f16.f16.f16 {qz16,qz17,qz18,qz19,qz20,qz21,qz22,qz23,qz24,qz25,qz26,qz27,qz28,qz29,qz30,qz31}, {qa16,qa17,qa18,qa19}, dt, pt, 1, 1, 1;\n"
        "add.s64 dt, w1d, 2944; wgmma.mma_async.sync.aligned.m64n64k16.f16.f16.f16 {qz16,qz17,qz18,qz19,qz20,qz21,qz22,qz23,qz24,qz25,qz26,qz27,qz28,qz29,qz30,qz31}, {qa20,qa21,qa22,qa23}, dt, pt, 1, 1, 1;\n"
        "wgmma.commit_group.sync.aligned;\n"
        "@pz bra.uni B42;\n"
        "mov.b32 {xl, xh}, a2; tanh.approx.f16 xr, xl; cvt.u32.u16 lo0, xr; tanh.approx.f16 xr, xh; cvt.u32.u16 hi0, xr; mul.rn.f16x2 a3, qz7, p1; fma.rn.f16x2 p0, qz8, qz8, c; fma.rn.f16x2 g4, qz4, h0, qz4; prmt.b32 h1, lo1, hi1, 0x5410;\n"
        "mov.b32 {xl, xh}, a3; tanh.approx.f16 xr, xl; cvt.u32.u16 lo1, xr; tanh.approx.f16 xr, xh; cvt.u32.u16 hi1, xr; mul.rn.f16x2 a0, qz8, p0; fma.rn.f16x2 p1, qz9, qz9, c; fma.rn.f16x2 g5, qz5, h1, qz5; prmt.b32 h0, lo0, hi0, 0x5410;\n"
        "mov.b32 {xl, xh}, a0; tanh.approx.f16 xr, xl; cvt.u32.u16 lo0, xr; tanh.approx.f16 xr, xh; cvt.u32.u16 hi0, xr; mul.rn.f16x2 a1, qz9, p1; fma.rn.f16x2 p0, qz10, qz10, c; fma.rn.f16x2 g6, qz6, h0, qz6; prmt.b32 h1, lo1, hi1, 0x5410;\n"
        "mov.b32 {xl, xh}, a1; tanh.approx.f16 xr, xl; cvt.u32.u16 lo1, xr; tanh.approx.f16 xr, xh; cvt.u32.u16 hi1, xr; mul.rn.f16x2 a2, qz10, p0; fma.rn.f16x2 p1, qz11, qz11, c; fma.rn.f16x2 g7, qz7, h1, qz7; prmt.b32 h0, lo0, hi0, 0x5410;\n"
        "B42:\n"
        "wgmma.wait_group.sync.aligned 2;\n"
        "setp.eq.s32 pr, n, 0;\n"
        "@pr bra.uni SPINW1;\n"
        "BACKW1:\n"
        "wgmma.fence.sync.aligned;\n"
        "add.s64 dt, w2d, 512; wgmma.mma_async.sync.aligned.m64n96k16.f16.f16.f16 {o0,o1,o2,o3,o4,o5,o6,o7,o8,o9,o10,o11,o12,o13,o14,o15,o16,o17,o18,o19,o20,o21,o22,o23}, {g0,g1,g2,g3}, dt, pt, 1, 1, 1;\n"
        "add.s64 dt, w2d, 576; wgmma.mma_async.sync.aligned.m64n96k16.f16.f16.f16 {o0,o1,o2,o3,o4,o5,o6,o7,o8,o9,o10,o11,o12,o13,o14,o15,o16,o17,o18,o19,o20,o21,o22,o23}, {g4,g5,g6,g7}, dt, pt, 1, 1, 1;\n"
        "wgmma.commit_group.sync.aligned;\n"
        "@pz bra.uni B46;\n"
        "mov.b32 {xl, xh}, a2; tanh.approx.f16 xr, xl; cvt.u32.u16 lo0, xr; tanh.approx.f16 xr, xh; cvt.u32.u16 hi0, xr; mul.rn.f16x2 a3, qz11, p1; fma.rn.f16x2 p0, qz12, qz12, c; fma.rn.f16x2 g8, qz8, h0, qz8; prmt.b32 h1, lo1, hi1, 0x5410;\n"
        "mov.b32 {xl, xh}, a3; tanh.approx.f16 xr, xl; cvt.u32.u16 lo1, xr; tanh.approx.f16 xr, xh; cvt.u32.u16 hi1, xr; mul.rn.f16x2 a0, qz12, p0; fma.rn.f16x2 p1, qz13, qz13, c; fma.rn.f16x2 g9, qz9, h1, qz9; prmt.b32 h0, lo0, hi0, 0x5410;\n"
        "mov.b32 {xl, xh}, a0; tanh.approx.f16 xr, xl; cvt.u32.u16 lo0, xr; tanh.approx.f16 xr, xh; cvt.u32.u16 hi0, xr; mul.rn.f16x2 a1, qz13, p1; fma.rn.f16x2 p0, qz14, qz14, c; fma.rn.f16x2 g10, qz10, h0, qz10; prmt.b32 h1, lo1, hi1, 0x5410;\n"
        "mov.b32 {xl, xh}, a1; tanh.approx.f16 xr, xl; cvt.u32.u16 lo1, xr; tanh.approx.f16 xr, xh; cvt.u32.u16 hi1, xr; mul.rn.f16x2 a2, qz14, p0; fma.rn.f16x2 p1, qz15, qz15, c; fma.rn.f16x2 g11, qz11, h1, qz11; prmt.b32 h0, lo0, hi0, 0x5410;\n"
        "B46:\n"
        "wgmma.wait_group.sync.aligned 1;\n"
        "wgmma.fence.sync.aligned;\n"
        "add.s64 dt, w2d, 640; wgmma.mma_async.sync.aligned.m64n96k16.f16.f16.f16 {o0,o1,o2,o3,o4,o5,o6,o7,o8,o9,o10,o11,o12,o13,o14,o15,o16,o17,o18,o19,o20,o21,o22,o23}, {g8,g9,g10,g11}, dt, pt, 1, 1, 1;\n"
        "wgmma.commit_group.sync.aligned;\n"
        "mad.lo.u32 tt, n, 8, tbar;\n"
        "@pn mbarrier.arrive.shared::cta.b64 _, [tt+64];\n"
        "@pz bra.uni B50;\n"
        "mov.b32 {xl, xh}, a2; tanh.approx.f16 xr, xl; cvt.u32.u16 lo0, xr; tanh.approx.f16 xr, xh; cvt.u32.u16 hi0, xr; mul.rn.f16x2 a3, qz15, p1; fma.rn.f16x2 p0, qz16, qz16, c; fma.rn.f16x2 g12, qz12, h0, qz12; prmt.b32 h1, lo1, hi1, 0x5410;\n"
        "mov.b32 {xl, xh}, a3; tanh.approx.f16 xr, xl; cvt.u32.u16 lo1, xr; tanh.approx.f16 xr, xh; cvt.u32.u16 hi1, xr; mul.rn.f16x2 a0, qz16, p0; fma.rn.f16x2 p1, qz17, qz17, c; fma.rn.f16x2 g13, qz13, h1, qz13; prmt.b32 h0, lo0, hi0, 0x5410;\n"
        "mov.b32 {xl, xh}, a0; tanh.approx.f16 xr, xl; cvt.u32.u16 lo0, xr; tanh.approx.f16 xr, xh; cvt.u32.u16 hi0, xr; mul.rn.f16x2 a1, qz17, p1; fma.rn.f16x2 p0, qz18, qz18, c; fma.rn.f16x2 g14, qz14, h0, qz14; prmt.b32 h1, lo1, hi1, 0x5410;\n"
        "mov.b32 {xl, xh}, a1; tanh.approx.f16 xr, xl; cvt.u32.u16 lo1, xr; tanh.approx.f16 xr, xh; cvt.u32.u16 hi1, xr; mul.rn.f16x2 a2, qz18, p0; fma.rn.f16x2 p1, qz19, qz19, c; fma.rn.f16x2 g15, qz15, h1, qz15; prmt.b32 h0, lo0, hi0, 0x5410;\n"
        "B50:\n"
        "wgmma.wait_group.sync.aligned 1;\n"
        "wgmma.fence.sync.aligned;\n"
        "add.s64 dt, w2d, 704; wgmma.mma_async.sync.aligned.m64n96k16.f16.f16.f16 {o0,o1,o2,o3,o4,o5,o6,o7,o8,o9,o10,o11,o12,o13,o14,o15,o16,o17,o18,o19,o20,o21,o22,o23}, {g12,g13,g14,g15}, dt, pt, 1, 1, 1;\n"
        "add.s64 dt, w1d, 3072; wgmma.mma_async.sync.aligned.m64n64k16.f16.f16.f16 {qz0,qz1,qz2,qz3,qz4,qz5,qz6,qz7,qz8,qz9,qz10,qz11,qz12,qz13,qz14,qz15}, {qa0,qa1,qa2,qa3}, dt, pf, 1, 1, 1;\n"
        "add.s64 dt, w1d, 3200; wgmma.mma_async.sync.aligned.m64n64k16.f16.f16.f16 {qz0,qz1,qz2,qz3,qz4,qz5,qz6,qz7,qz8,qz9,qz10,qz11,qz12,qz13,qz14,qz15}, {qa4,qa5,qa6,qa7}, dt, pt, 1, 1, 1;\n"
        "add.s64 dt, w1d, 3328; wgmma.mma_async.sync.aligned.m64n64k16.f16.f16.f16 {qz0,qz1,qz2,qz3,qz4,qz5,qz6,qz7,qz8,qz9,qz10,qz11,qz12,qz13,qz14,qz15}, {qa8,qa9,qa10,qa11}, dt, pt, 1, 1, 1;\n"
        "wgmma.commit_group.sync.aligned;\n"
        "@pz bra.uni B54;\n"
        "mov.b32 {xl, xh}, a2; tanh.approx.f16 xr, xl; cvt.u32.u16 lo0, xr; tanh.approx.f16 xr, xh; cvt.u32.u16 hi0, xr; mul.rn.f16x2 a3, qz19, p1; fma.rn.f16x2 p0, qz20, qz20, c; fma.rn.f16x2 g0, qz16, h0, qz16; prmt.b32 h1, lo1, hi1, 0x5410;\n"
        "mov.b32 {xl, xh}, a3; tanh.approx.f16 xr, xl; cvt.u32.u16 lo1, xr; tanh.approx.f16 xr, xh; cvt.u32.u16 hi1, xr; mul.rn.f16x2 a0, qz20, p0; fma.rn.f16x2 p1, qz21, qz21, c; fma.rn.f16x2 g1, qz17, h1, qz17; prmt.b32 h0, lo0, hi0, 0x5410;\n"
        "mov.b32 {xl, xh}, a0; tanh.approx.f16 xr, xl; cvt.u32.u16 lo0, xr; tanh.approx.f16 xr, xh; cvt.u32.u16 hi0, xr; mul.rn.f16x2 a1, qz21, p1; fma.rn.f16x2 p0, qz22, qz22, c; fma.rn.f16x2 g2, qz18, h0, qz18; prmt.b32 h1, lo1, hi1, 0x5410;\n"
        "mov.b32 {xl, xh}, a1; tanh.approx.f16 xr, xl; cvt.u32.u16 lo1, xr; tanh.approx.f16 xr, xh; cvt.u32.u16 hi1, xr; mul.rn.f16x2 a2, qz22, p0; fma.rn.f16x2 p1, qz23, qz23, c; fma.rn.f16x2 g3, qz19, h1, qz19; prmt.b32 h0, lo0, hi0, 0x5410;\n"
        "B54:\n"
        "wgmma.fence.sync.aligned;\n"
        "add.s64 dt, w1d, 3456; wgmma.mma_async.sync.aligned.m64n64k16.f16.f16.f16 {qz0,qz1,qz2,qz3,qz4,qz5,qz6,qz7,qz8,qz9,qz10,qz11,qz12,qz13,qz14,qz15}, {qa12,qa13,qa14,qa15}, dt, pt, 1, 1, 1;\n"
        "add.s64 dt, w1d, 3584; wgmma.mma_async.sync.aligned.m64n64k16.f16.f16.f16 {qz0,qz1,qz2,qz3,qz4,qz5,qz6,qz7,qz8,qz9,qz10,qz11,qz12,qz13,qz14,qz15}, {qa16,qa17,qa18,qa19}, dt, pt, 1, 1, 1;\n"
        "add.s64 dt, w1d, 3712; wgmma.mma_async.sync.aligned.m64n64k16.f16.f16.f16 {qz0,qz1,qz2,qz3,qz4,qz5,qz6,qz7,qz8,qz9,qz10,qz11,qz12,qz13,qz14,qz15}, {qa20,qa21,qa22,qa23}, dt, pt, 1, 1, 1;\n"
        "wgmma.commit_group.sync.aligned;\n"
        "@pz bra.uni B58;\n"
        "mov.b32 {xl, xh}, a2; tanh.approx.f16 xr, xl; cvt.u32.u16 lo0, xr; tanh.approx.f16 xr, xh; cvt.u32.u16 hi0, xr; mul.rn.f16x2 a3, qz23, p1; fma.rn.f16x2 p0, qz24, qz24, c; fma.rn.f16x2 g4, qz20, h0, qz20; prmt.b32 h1, lo1, hi1, 0x5410;\n"
        "mov.b32 {xl, xh}, a3; tanh.approx.f16 xr, xl; cvt.u32.u16 lo1, xr; tanh.approx.f16 xr, xh; cvt.u32.u16 hi1, xr; mul.rn.f16x2 a0, qz24, p0; fma.rn.f16x2 p1, qz25, qz25, c; fma.rn.f16x2 g5, qz21, h1, qz21; prmt.b32 h0, lo0, hi0, 0x5410;\n"
        "mov.b32 {xl, xh}, a0; tanh.approx.f16 xr, xl; cvt.u32.u16 lo0, xr; tanh.approx.f16 xr, xh; cvt.u32.u16 hi0, xr; mul.rn.f16x2 a1, qz25, p1; fma.rn.f16x2 p0, qz26, qz26, c; fma.rn.f16x2 g6, qz22, h0, qz22; prmt.b32 h1, lo1, hi1, 0x5410;\n"
        "mov.b32 {xl, xh}, a1; tanh.approx.f16 xr, xl; cvt.u32.u16 lo1, xr; tanh.approx.f16 xr, xh; cvt.u32.u16 hi1, xr; mul.rn.f16x2 a2, qz26, p0; fma.rn.f16x2 p1, qz27, qz27, c; fma.rn.f16x2 g7, qz23, h1, qz23; prmt.b32 h0, lo0, hi0, 0x5410;\n"
        "B58:\n"
        "wgmma.wait_group.sync.aligned 2;\n"
        "wgmma.fence.sync.aligned;\n"
        "add.s64 dt, w2d, 768; wgmma.mma_async.sync.aligned.m64n96k16.f16.f16.f16 {o0,o1,o2,o3,o4,o5,o6,o7,o8,o9,o10,o11,o12,o13,o14,o15,o16,o17,o18,o19,o20,o21,o22,o23}, {g0,g1,g2,g3}, dt, pt, 1, 1, 1;\n"
        "add.s64 dt, w2d, 832; wgmma.mma_async.sync.aligned.m64n96k16.f16.f16.f16 {o0,o1,o2,o3,o4,o5,o6,o7,o8,o9,o10,o11,o12,o13,o14,o15,o16,o17,o18,o19,o20,o21,o22,o23}, {g4,g5,g6,g7}, dt, pt, 1, 1, 1;\n"
        "wgmma.commit_group.sync.aligned;\n"
        "@pz bra.uni B62;\n"
        "mov.b32 {xl, xh}, a2; tanh.approx.f16 xr, xl; cvt.u32.u16 lo0, xr; tanh.approx.f16 xr, xh; cvt.u32.u16 hi0, xr; mul.rn.f16x2 a3, qz27, p1; fma.rn.f16x2 p0, qz28, qz28, c; fma.rn.f16x2 g8, qz24, h0, qz24; prmt.b32 h1, lo1, hi1, 0x5410;\n"
        "mov.b32 {xl, xh}, a3; tanh.approx.f16 xr, xl; cvt.u32.u16 lo1, xr; tanh.approx.f16 xr, xh; cvt.u32.u16 hi1, xr; mul.rn.f16x2 a0, qz28, p0; fma.rn.f16x2 p1, qz29, qz29, c; fma.rn.f16x2 g9, qz25, h1, qz25; prmt.b32 h0, lo0, hi0, 0x5410;\n"
        "mov.b32 {xl, xh}, a0; tanh.approx.f16 xr, xl; cvt.u32.u16 lo0, xr; tanh.approx.f16 xr, xh; cvt.u32.u16 hi0, xr; mul.rn.f16x2 a1, qz29, p1; fma.rn.f16x2 p0, qz30, qz30, c; fma.rn.f16x2 g10, qz26, h0, qz26; prmt.b32 h1, lo1, hi1, 0x5410;\n"
        "mov.b32 {xl, xh}, a1; tanh.approx.f16 xr, xl; cvt.u32.u16 lo1, xr; tanh.approx.f16 xr, xh; cvt.u32.u16 hi1, xr; mul.rn.f16x2 a2, qz30, p0; fma.rn.f16x2 p1, qz31, qz31, c; fma.rn.f16x2 g11, qz27, h1, qz27; prmt.b32 h0, lo0, hi0, 0x5410;\n"
        "B62:\n"
        "wgmma.wait_group.sync.aligned 1;\n"
        "wgmma.fence.sync.aligned;\n"
        "add.s64 dt, w2d, 896; wgmma.mma_async.sync.aligned.m64n96k16.f16.f16.f16 {o0,o1,o2,o3,o4,o5,o6,o7,o8,o9,o10,o11,o12,o13,o14,o15,o16,o17,o18,o19,o20,o21,o22,o23}, {g8,g9,g10,g11}, dt, pt, 1, 1, 1;\n"
        "wgmma.commit_group.sync.aligned;\n"
        "@pz bra.uni B66;\n"
        "mov.b32 {xl, xh}, a2; tanh.approx.f16 xr, xl; cvt.u32.u16 lo0, xr; tanh.approx.f16 xr, xh; cvt.u32.u16 hi0, xr; mul.rn.f16x2 a3, qz31, p1; fma.rn.f16x2 p0, qz0, qz0, c; fma.rn.f16x2 g12, qz28, h0, qz28; prmt.b32 h1, lo1, hi1, 0x5410;\n"
        "mov.b32 {xl, xh}, a3; tanh.approx.f16 xr, xl; cvt.u32.u16 lo1, xr; tanh.approx.f16 xr, xh; cvt.u32.u16 hi1, xr; mul.rn.f16x2 a0, qz0, p0; fma.rn.f16x2 p1, qz1, qz1, c; fma.rn.f16x2 g13, qz29, h1, qz29; prmt.b32 h0, lo0, hi0, 0x5410;\n"
        "mov.b32 {xl, xh}, a0; tanh.approx.f16 xr, xl; cvt.u32.u16 lo0, xr; tanh.approx.f16 xr, xh; cvt.u32.u16 hi0, xr; mul.rn.f16x2 a1, qz1, p1; fma.rn.f16x2 p0, qz2, qz2, c; fma.rn.f16x2 g14, qz30, h0, qz30; prmt.b32 h1, lo1, hi1, 0x5410;\n"
        "mov.b32 {xl, xh}, a1; tanh.approx.f16 xr, xl; cvt.u32.u16 lo1, xr; tanh.approx.f16 xr, xh; cvt.u32.u16 hi1, xr; mul.rn.f16x2 a2, qz2, p0; fma.rn.f16x2 p1, qz3, qz3, c; fma.rn.f16x2 g15, qz31, h1, qz31; prmt.b32 h0, lo0, hi0, 0x5410;\n"
        "B66:\n"
        "wgmma.wait_group.sync.aligned 1;\n"
        "wgmma.fence.sync.aligned;\n"
        "add.s64 dt, w2d, 960; wgmma.mma_async.sync.aligned.m64n96k16.f16.f16.f16 {o0,o1,o2,o3,o4,o5,o6,o7,o8,o9,o10,o11,o12,o13,o14,o15,o16,o17,o18,o19,o20,o21,o22,o23}, {g12,g13,g14,g15}, dt, pt, 1, 1, 1;\n"
        "add.s64 dt, w1d, 3840; wgmma.mma_async.sync.aligned.m64n64k16.f16.f16.f16 {qz16,qz17,qz18,qz19,qz20,qz21,qz22,qz23,qz24,qz25,qz26,qz27,qz28,qz29,qz30,qz31}, {qa0,qa1,qa2,qa3}, dt, pf, 1, 1, 1;\n"
        "add.s64 dt, w1d, 3968; wgmma.mma_async.sync.aligned.m64n64k16.f16.f16.f16 {qz16,qz17,qz18,qz19,qz20,qz21,qz22,qz23,qz24,qz25,qz26,qz27,qz28,qz29,qz30,qz31}, {qa4,qa5,qa6,qa7}, dt, pt, 1, 1, 1;\n"
        "add.s64 dt, w1d, 4096; wgmma.mma_async.sync.aligned.m64n64k16.f16.f16.f16 {qz16,qz17,qz18,qz19,qz20,qz21,qz22,qz23,qz24,qz25,qz26,qz27,qz28,qz29,qz30,qz31}, {qa8,qa9,qa10,qa11}, dt, pt, 1, 1, 1;\n"
        "wgmma.commit_group.sync.aligned;\n"
        "@pz bra.uni B70;\n"
        "mov.b32 {xl, xh}, a2; tanh.approx.f16 xr, xl; cvt.u32.u16 lo0, xr; tanh.approx.f16 xr, xh; cvt.u32.u16 hi0, xr; mul.rn.f16x2 a3, qz3, p1; fma.rn.f16x2 p0, qz4, qz4, c; fma.rn.f16x2 g0, qz0, h0, qz0; prmt.b32 h1, lo1, hi1, 0x5410;\n"
        "mov.b32 {xl, xh}, a3; tanh.approx.f16 xr, xl; cvt.u32.u16 lo1, xr; tanh.approx.f16 xr, xh; cvt.u32.u16 hi1, xr; mul.rn.f16x2 a0, qz4, p0; fma.rn.f16x2 p1, qz5, qz5, c; fma.rn.f16x2 g1, qz1, h1, qz1; prmt.b32 h0, lo0, hi0, 0x5410;\n"
        "mov.b32 {xl, xh}, a0; tanh.approx.f16 xr, xl; cvt.u32.u16 lo0, xr; tanh.approx.f16 xr, xh; cvt.u32.u16 hi0, xr; mul.rn.f16x2 a1, qz5, p1; fma.rn.f16x2 p0, qz6, qz6, c; fma.rn.f16x2 g2, qz2, h0, qz2; prmt.b32 h1, lo1, hi1, 0x5410;\n"
        "mov.b32 {xl, xh}, a1; tanh.approx.f16 xr, xl; cvt.u32.u16 lo1, xr; tanh.approx.f16 xr, xh; cvt.u32.u16 hi1, xr; mul.rn.f16x2 a2, qz6, p0; fma.rn.f16x2 p1, qz7, qz7, c; fma.rn.f16x2 g3, qz3, h1, qz3; prmt.b32 h0, lo0, hi0, 0x5410;\n"
        "B70:\n"
        "wgmma.fence.sync.aligned;\n"
        "add.s64 dt, w1d, 4224; wgmma.mma_async.sync.aligned.m64n64k16.f16.f16.f16 {qz16,qz17,qz18,qz19,qz20,qz21,qz22,qz23,qz24,qz25,qz26,qz27,qz28,qz29,qz30,qz31}, {qa12,qa13,qa14,qa15}, dt, pt, 1, 1, 1;\n"
        "add.s64 dt, w1d, 4352; wgmma.mma_async.sync.aligned.m64n64k16.f16.f16.f16 {qz16,qz17,qz18,qz19,qz20,qz21,qz22,qz23,qz24,qz25,qz26,qz27,qz28,qz29,qz30,qz31}, {qa16,qa17,qa18,qa19}, dt, pt, 1, 1, 1;\n"
        "add.s64 dt, w1d, 4480; wgmma.mma_async.sync.aligned.m64n64k16.f16.f16.f16 {qz16,qz17,qz18,qz19,qz20,qz21,qz22,qz23,qz24,qz25,qz26,qz27,qz28,qz29,qz30,qz31}, {qa20,qa21,qa22,qa23}, dt, pt, 1, 1, 1;\n"
        "wgmma.commit_group.sync.aligned;\n"
        "@pz bra.uni B74;\n"
        "mov.b32 {xl, xh}, a2; tanh.approx.f16 xr, xl; cvt.u32.u16 lo0, xr; tanh.approx.f16 xr, xh; cvt.u32.u16 hi0, xr; mul.rn.f16x2 a3, qz7, p1; fma.rn.f16x2 p0, qz8, qz8, c; fma.rn.f16x2 g4, qz4, h0, qz4; prmt.b32 h1, lo1, hi1, 0x5410;\n"
        "mov.b32 {xl, xh}, a3; tanh.approx.f16 xr, xl; cvt.u32.u16 lo1, xr; tanh.approx.f16 xr, xh; cvt.u32.u16 hi1, xr; mul.rn.f16x2 a0, qz8, p0; fma.rn.f16x2 p1, qz9, qz9, c; fma.rn.f16x2 g5, qz5, h1, qz5; prmt.b32 h0, lo0, hi0, 0x5410;\n"
        "mov.b32 {xl, xh}, a0; tanh.approx.f16 xr, xl; cvt.u32.u16 lo0, xr; tanh.approx.f16 xr, xh; cvt.u32.u16 hi0, xr; mul.rn.f16x2 a1, qz9, p1; fma.rn.f16x2 p0, qz10, qz10, c; fma.rn.f16x2 g6, qz6, h0, qz6; prmt.b32 h1, lo1, hi1, 0x5410;\n"
        "mov.b32 {xl, xh}, a1; tanh.approx.f16 xr, xl; cvt.u32.u16 lo1, xr; tanh.approx.f16 xr, xh; cvt.u32.u16 hi1, xr; mul.rn.f16x2 a2, qz10, p0; fma.rn.f16x2 p1, qz11, qz11, c; fma.rn.f16x2 g7, qz7, h1, qz7; prmt.b32 h0, lo0, hi0, 0x5410;\n"
        "B74:\n"
        "wgmma.wait_group.sync.aligned 2;\n"
        "wgmma.fence.sync.aligned;\n"
        "add.s64 dt, w2d, 1024; wgmma.mma_async.sync.aligned.m64n96k16.f16.f16.f16 {o0,o1,o2,o3,o4,o5,o6,o7,o8,o9,o10,o11,o12,o13,o14,o15,o16,o17,o18,o19,o20,o21,o22,o23}, {g0,g1,g2,g3}, dt, pt, 1, 1, 1;\n"
        "add.s64 dt, w2d, 1088; wgmma.mma_async.sync.aligned.m64n96k16.f16.f16.f16 {o0,o1,o2,o3,o4,o5,o6,o7,o8,o9,o10,o11,o12,o13,o14,o15,o16,o17,o18,o19,o20,o21,o22,o23}, {g4,g5,g6,g7}, dt, pt, 1, 1, 1;\n"
        "wgmma.commit_group.sync.aligned;\n"
        "@pz bra.uni B78;\n"
        "mov.b32 {xl, xh}, a2; tanh.approx.f16 xr, xl; cvt.u32.u16 lo0, xr; tanh.approx.f16 xr, xh; cvt.u32.u16 hi0, xr; mul.rn.f16x2 a3, qz11, p1; fma.rn.f16x2 p0, qz12, qz12, c; fma.rn.f16x2 g8, qz8, h0, qz8; prmt.b32 h1, lo1, hi1, 0x5410;\n"
        "mov.b32 {xl, xh}, a3; tanh.approx.f16 xr, xl; cvt.u32.u16 lo1, xr; tanh.approx.f16 xr, xh; cvt.u32.u16 hi1, xr; mul.rn.f16x2 a0, qz12, p0; fma.rn.f16x2 p1, qz13, qz13, c; fma.rn.f16x2 g9, qz9, h1, qz9; prmt.b32 h0, lo0, hi0, 0x5410;\n"
        "mov.b32 {xl, xh}, a0; tanh.approx.f16 xr, xl; cvt.u32.u16 lo0, xr; tanh.approx.f16 xr, xh; cvt.u32.u16 hi0, xr; mul.rn.f16x2 a1, qz13, p1; fma.rn.f16x2 p0, qz14, qz14, c; fma.rn.f16x2 g10, qz10, h0, qz10; prmt.b32 h1, lo1, hi1, 0x5410;\n"
        "mov.b32 {xl, xh}, a1; tanh.approx.f16 xr, xl; cvt.u32.u16 lo1, xr; tanh.approx.f16 xr, xh; cvt.u32.u16 hi1, xr; mul.rn.f16x2 a2, qz14, p0; fma.rn.f16x2 p1, qz15, qz15, c; fma.rn.f16x2 g11, qz11, h1, qz11; prmt.b32 h0, lo0, hi0, 0x5410;\n"
        "B78:\n"
        "wgmma.wait_group.sync.aligned 1;\n"
        "@!pm bra.uni BACKY;\n"
        "add.u32 tt, n, 1; and.b32 tt, tt, 1; mbarrier.try_wait.parity.shared::cta.b64 pw, [ybar], tt;\n"
        "@!pw bra.uni SPINY;\n"
        "BACKY:\n"
        "@pz bra.uni B80;\n"
        "and.b32 ad, %5, 0xffff; xor.b32 ad, ad, 0; add.u32 ad, ad, %4; ldmatrix.sync.aligned.m8n8.x4.shared.b16 {qa0,qa1,qa2,qa3}, [ad];\n"
        "and.b32 ad, %5, 0xffff; xor.b32 ad, ad, 32; add.u32 ad, ad, %4; ldmatrix.sync.aligned.m8n8.x4.shared.b16 {qa4,qa5,qa6,qa7}, [ad];\n"
        "and.b32 ad, %5, 0xffff; xor.b32 ad, ad, 64; add.u32 ad, ad, %4; ldmatrix.sync.aligned.m8n8.x4.shared.b16 {qa8,qa9,qa10,qa11}, [ad];\n"
        "and.b32 ad, %5, 0xffff; xor.b32 ad, ad, 96; add.u32 ad, ad, %4; ldmatrix.sync.aligned.m8n8.x4.shared.b16 {qa12,qa13,qa14,qa15}, [ad];\n"
        "shr.u32 ad, %5, 16; xor.b32 ad, ad, 0; add.u32 ad, ad, %4; ldmatrix.sync.aligned.m8n8.x4.shared.b16 {qa16,qa17,qa18,qa19}, [ad];\n"
        "shr.u32 ad, %5, 16; xor.b32 ad, ad, 32; add.u32 ad, ad, %4; ldmatrix.sync.aligned.m8n8.x4.shared.b16 {qa20,qa21,qa22,qa23}, [ad];\n"
        "mov.b32 {xl, xh}, a2; tanh.approx.f16 xr, xl; cvt.u32.u16 lo0, xr; tanh.approx.f16 xr, xh; cvt.u32.u16 hi0, xr; mul.rn.f16x2 a3, qz15, p1; fma.rn.f16x2 p0, qz16, qz16, c; fma.rn.f16x2 g12, qz12, h0, qz12; prmt.b32 h1, lo1, hi1, 0x5410;\n"
        "mov.b32 {xl, xh}, a3; tanh.approx.f16 xr, xl; cvt.u32.u16 lo1, xr; tanh.approx.f16 xr, xh; cvt.u32.u16 hi1, xr; mul.rn.f16x2 a0, qz16, p0; fma.rn.f16x2 p1, qz17, qz17, c; fma.rn.f16x2 g13, qz13, h1, qz13; prmt.b32 h0, lo0, hi0, 0x5410;\n"
        "B80:\n"
        "fence.proxy.async.shared::cta;\n"
        "add.u32 tt, id, 0;\n"
        "@pl bra.uni XLOAD;\n"
        "bar.arrive tt, 128;\n"
        "XLOADB:\n"
        "wgmma.fence.sync.aligned;\n"
        "add.s64 dt, w2d, 1152; wgmma.mma_async.sync.aligned.m64n96k16.f16.f16.f16 {o0,o1,o2,o3,o4,o5,o6,o7,o8,o9,o10,o11,o12,o13,o14,o15,o16,o17,o18,o19,o20,o21,o22,o23}, {g8,g9,g10,g11}, dt, pt, 1, 1, 1;\n"
        "wgmma.commit_group.sync.aligned;\n"
        "@pz bra.uni B82;\n"
        "mov.b32 {xl, xh}, a0; tanh.approx.f16 xr, xl; cvt.u32.u16 lo0, xr; tanh.approx.f16 xr, xh; cvt.u32.u16 hi0, xr; mul.rn.f16x2 a1, qz17, p1; fma.rn.f16x2 p0, qz18, qz18, c; fma.rn.f16x2 g14, qz14, h0, qz14; prmt.b32 h1, lo1, hi1, 0x5410;\n"
        "mov.b32 {xl, xh}, a1; tanh.approx.f16 xr, xl; cvt.u32.u16 lo1, xr; tanh.approx.f16 xr, xh; cvt.u32.u16 hi1, xr; mul.rn.f16x2 a2, qz18, p0; fma.rn.f16x2 p1, qz19, qz19, c; fma.rn.f16x2 g15, qz15, h1, qz15; prmt.b32 h0, lo0, hi0, 0x5410;\n"
        "B82:\n"
        "wgmma.wait_group.sync.aligned 1;\n"
        "@!pm bra.uni SKIP1;\n"
        "wgmma.fence.sync.aligned;\n"
        "add.s64 dt, w1d, 0; wgmma.mma_async.sync.aligned.m64n64k16.f16.f16.f16 {qz0,qz1,qz2,qz3,qz4,qz5,qz6,qz7,qz8,qz9,qz10,qz11,qz12,qz13,qz14,qz15}, {qa0,qa1,qa2,qa3}, dt, pf, 1, 1, 1;\n"
        "add.s64 dt, w1d, 128; wgmma.mma_async.sync.aligned.m64n64k16.f16.f16.f16 {qz0,qz1,qz2,qz3,qz4,qz5,qz6,qz7,qz8,qz9,qz10,qz11,qz12,qz13,qz14,qz15}, {qa4,qa5,qa6,qa7}, dt, pt, 1, 1, 1;\n"
        "add.s64 dt, w1d, 256; wgmma.mma_async.sync.aligned.m64n64k16.f16.f16.f16 {qz0,qz1,qz2,qz3,qz4,qz5,qz6,qz7,qz8,qz9,qz10,qz11,qz12,qz13,qz14,qz15}, {qa8,qa9,qa10,qa11}, dt, pt, 1, 1, 1;\n"
        "SKIP1:\n"
        "wgmma.fence.sync.aligned;\n"
        "add.s64 dt, w2d, 1216; wgmma.mma_async.sync.aligned.m64n96k16.f16.f16.f16 {o0,o1,o2,o3,o4,o5,o6,o7,o8,o9,o10,o11,o12,o13,o14,o15,o16,o17,o18,o19,o20,o21,o22,o23}, {g12,g13,g14,g15}, dt, pt, 1, 1, 1;\n"
        "wgmma.commit_group.sync.aligned;\n"
        "@pz bra.uni B86;\n"
        "mov.b32 {xl, xh}, a2; tanh.approx.f16 xr, xl; cvt.u32.u16 lo0, xr; tanh.approx.f16 xr, xh; cvt.u32.u16 hi0, xr; mul.rn.f16x2 a3, qz19, p1; fma.rn.f16x2 p0, qz20, qz20, c; fma.rn.f16x2 g0, qz16, h0, qz16; prmt.b32 h1, lo1, hi1, 0x5410;\n"
        "mov.b32 {xl, xh}, a3; tanh.approx.f16 xr, xl; cvt.u32.u16 lo1, xr; tanh.approx.f16 xr, xh; cvt.u32.u16 hi1, xr; mul.rn.f16x2 a0, qz20, p0; fma.rn.f16x2 p1, qz21, qz21, c; fma.rn.f16x2 g1, qz17, h1, qz17; prmt.b32 h0, lo0, hi0, 0x5410;\n"
        "mov.b32 {xl, xh}, a0; tanh.approx.f16 xr, xl; cvt.u32.u16 lo0, xr; tanh.approx.f16 xr, xh; cvt.u32.u16 hi0, xr; mul.rn.f16x2 a1, qz21, p1; fma.rn.f16x2 p0, qz22, qz22, c; fma.rn.f16x2 g2, qz18, h0, qz18; prmt.b32 h1, lo1, hi1, 0x5410;\n"
        "mov.b32 {xl, xh}, a1; tanh.approx.f16 xr, xl; cvt.u32.u16 lo1, xr; tanh.approx.f16 xr, xh; cvt.u32.u16 hi1, xr; mul.rn.f16x2 a2, qz22, p0; fma.rn.f16x2 p1, qz23, qz23, c; fma.rn.f16x2 g3, qz19, h1, qz19; prmt.b32 h0, lo0, hi0, 0x5410;\n"
        "B86:\n"
        "@!pm bra.uni SKIP2;\n"
        "wgmma.fence.sync.aligned;\n"
        "add.s64 dt, w1d, 384; wgmma.mma_async.sync.aligned.m64n64k16.f16.f16.f16 {qz0,qz1,qz2,qz3,qz4,qz5,qz6,qz7,qz8,qz9,qz10,qz11,qz12,qz13,qz14,qz15}, {qa12,qa13,qa14,qa15}, dt, pt, 1, 1, 1;\n"
        "add.s64 dt, w1d, 512; wgmma.mma_async.sync.aligned.m64n64k16.f16.f16.f16 {qz0,qz1,qz2,qz3,qz4,qz5,qz6,qz7,qz8,qz9,qz10,qz11,qz12,qz13,qz14,qz15}, {qa16,qa17,qa18,qa19}, dt, pt, 1, 1, 1;\n"
        "add.s64 dt, w1d, 640; wgmma.mma_async.sync.aligned.m64n64k16.f16.f16.f16 {qz0,qz1,qz2,qz3,qz4,qz5,qz6,qz7,qz8,qz9,qz10,qz11,qz12,qz13,qz14,qz15}, {qa20,qa21,qa22,qa23}, dt, pt, 1, 1, 1;\n"
        "SKIP2:\n"
        "@pz bra.uni B90;\n"
        "mov.b32 {xl, xh}, a2; tanh.approx.f16 xr, xl; cvt.u32.u16 lo0, xr; tanh.approx.f16 xr, xh; cvt.u32.u16 hi0, xr; mul.rn.f16x2 a3, qz23, p1; fma.rn.f16x2 p0, qz24, qz24, c; fma.rn.f16x2 g4, qz20, h0, qz20; prmt.b32 h1, lo1, hi1, 0x5410;\n"
        "mov.b32 {xl, xh}, a3; tanh.approx.f16 xr, xl; cvt.u32.u16 lo1, xr; tanh.approx.f16 xr, xh; cvt.u32.u16 hi1, xr; mul.rn.f16x2 a0, qz24, p0; fma.rn.f16x2 p1, qz25, qz25, c; fma.rn.f16x2 g5, qz21, h1, qz21; prmt.b32 h0, lo0, hi0, 0x5410;\n"
        "mov.b32 {xl, xh}, a0; tanh.approx.f16 xr, xl; cvt.u32.u16 lo0, xr; tanh.approx.f16 xr, xh; cvt.u32.u16 hi0, xr; mul.rn.f16x2 a1, qz25, p1; fma.rn.f16x2 p0, qz26, qz26, c; fma.rn.f16x2 g6, qz22, h0, qz22; prmt.b32 h1, lo1, hi1, 0x5410;\n"
        "mov.b32 {xl, xh}, a1; tanh.approx.f16 xr, xl; cvt.u32.u16 lo1, xr; tanh.approx.f16 xr, xh; cvt.u32.u16 hi1, xr; mul.rn.f16x2 a2, qz26, p0; fma.rn.f16x2 p1, qz27, qz27, c; fma.rn.f16x2 g7, qz23, h1, qz23; prmt.b32 h0, lo0, hi0, 0x5410;\n"
        "B90:\n"
        "wgmma.wait_group.sync.aligned 1;\n"
        "wgmma.fence.sync.aligned;\n"
        "add.s64 dt, w2d, 1280; wgmma.mma_async.sync.aligned.m64n96k16.f16.f16.f16 {o0,o1,o2,o3,o4,o5,o6,o7,o8,o9,o10,o11,o12,o13,o14,o15,o16,o17,o18,o19,o20,o21,o22,o23}, {g0,g1,g2,g3}, dt, pt, 1, 1, 1;\n"
        "add.s64 dt, w2d, 1344; wgmma.mma_async.sync.aligned.m64n96k16.f16.f16.f16 {o0,o1,o2,o3,o4,o5,o6,o7,o8,o9,o10,o11,o12,o13,o14,o15,o16,o17,o18,o19,o20,o21,o22,o23}, {g4,g5,g6,g7}, dt, pt, 1, 1, 1;\n"
        "wgmma.commit_group.sync.aligned;\n"
        "@pz bra.uni B94;\n"
        "mov.b32 {xl, xh}, a2; tanh.approx.f16 xr, xl; cvt.u32.u16 lo0, xr; tanh.approx.f16 xr, xh; cvt.u32.u16 hi0, xr; mul.rn.f16x2 a3, qz27, p1; fma.rn.f16x2 p0, qz28, qz28, c; fma.rn.f16x2 g8, qz24, h0, qz24; prmt.b32 h1, lo1, hi1, 0x5410;\n"
        "mov.b32 {xl, xh}, a3; tanh.approx.f16 xr, xl; cvt.u32.u16 lo1, xr; tanh.approx.f16 xr, xh; cvt.u32.u16 hi1, xr; mul.rn.f16x2 a0, qz28, p0; fma.rn.f16x2 p1, qz29, qz29, c; fma.rn.f16x2 g9, qz25, h1, qz25; prmt.b32 h0, lo0, hi0, 0x5410;\n"
        "mov.b32 {xl, xh}, a0; tanh.approx.f16 xr, xl; cvt.u32.u16 lo0, xr; tanh.approx.f16 xr, xh; cvt.u32.u16 hi0, xr; mul.rn.f16x2 a1, qz29, p1; fma.rn.f16x2 p0, qz30, qz30, c; fma.rn.f16x2 g10, qz26, h0, qz26; prmt.b32 h1, lo1, hi1, 0x5410;\n"
        "mov.b32 {xl, xh}, a1; tanh.approx.f16 xr, xl; cvt.u32.u16 lo1, xr; tanh.approx.f16 xr, xh; cvt.u32.u16 hi1, xr; mul.rn.f16x2 a2, qz30, p0; fma.rn.f16x2 p1, qz31, qz31, c; fma.rn.f16x2 g11, qz27, h1, qz27; prmt.b32 h0, lo0, hi0, 0x5410;\n"
        "B94:\n"
        "wgmma.wait_group.sync.aligned 0;\n"
        "wgmma.fence.sync.aligned;\n"
        "add.s64 dt, w2d, 1408; wgmma.mma_async.sync.aligned.m64n96k16.f16.f16.f16 {o0,o1,o2,o3,o4,o5,o6,o7,o8,o9,o10,o11,o12,o13,o14,o15,o16,o17,o18,o19,o20,o21,o22,o23}, {g8,g9,g10,g11}, dt, pt, 1, 1, 1;\n"
        "wgmma.commit_group.sync.aligned;\n"
        "@pz bra.uni B2;\n"
        "mov.b32 {xl, xh}, a2; tanh.approx.f16 xr, xl; cvt.u32.u16 lo0, xr; tanh.approx.f16 xr, xh; cvt.u32.u16 hi0, xr; mul.rn.f16x2 a3, qz31, p1; fma.rn.f16x2 p0, qz0, qz0, c; fma.rn.f16x2 g12, qz28, h0, qz28; prmt.b32 h1, lo1, hi1, 0x5410;\n"
        "mov.b32 {xl, xh}, a3; tanh.approx.f16 xr, xl; cvt.u32.u16 lo1, xr; tanh.approx.f16 xr, xh; cvt.u32.u16 hi1, xr; mul.rn.f16x2 a0, qz0, p0; fma.rn.f16x2 p1, qz1, qz1, c; fma.rn.f16x2 g13, qz29, h1, qz29; prmt.b32 h0, lo0, hi0, 0x5410;\n"
        "mov.b32 {xl, xh}, a0; tanh.approx.f16 xr, xl; cvt.u32.u16 lo0, xr; tanh.approx.f16 xr, xh; cvt.u32.u16 hi0, xr; mul.rn.f16x2 a1, qz1, p1; fma.rn.f16x2 p0, qz2, qz2, c; fma.rn.f16x2 g14, qz30, h0, qz30; prmt.b32 h1, lo1, hi1, 0x5410;\n"
        "mov.b32 {xl, xh}, a1; tanh.approx.f16 xr, xl; cvt.u32.u16 lo1, xr; tanh.approx.f16 xr, xh; cvt.u32.u16 hi1, xr; mul.rn.f16x2 a2, qz2, p0; fma.rn.f16x2 p1, qz3, qz3, c; fma.rn.f16x2 g15, qz31, h1, qz31; prmt.b32 h0, lo0, hi0, 0x5410;\n"
        "B2:\n"
        "wgmma.fence.sync.aligned;\n"
        "add.s64 dt, w2d, 1472; wgmma.mma_async.sync.aligned.m64n96k16.f16.f16.f16 {o0,o1,o2,o3,o4,o5,o6,o7,o8,o9,o10,o11,o12,o13,o14,o15,o16,o17,o18,o19,o20,o21,o22,o23}, {g12,g13,g14,g15}, dt, pt, 1, 1, 1;\n"
        "wgmma.commit_group.sync.aligned;\n"
        "@!pm bra.uni BE;\n"
        "mov.b32 {xl, xh}, a2; tanh.approx.f16 xr, xl; cvt.u32.u16 lo0, xr; tanh.approx.f16 xr, xh; cvt.u32.u16 hi0, xr; mul.rn.f16x2 a3, qz3, p1; fma.rn.f16x2 p0, qz4, qz4, c; fma.rn.f16x2 g0, qz0, h0, qz0; prmt.b32 h1, lo1, hi1, 0x5410;\n"
        "mov.b32 {xl, xh}, a3; tanh.approx.f16 xr, xl; cvt.u32.u16 lo1, xr; tanh.approx.f16 xr, xh; cvt.u32.u16 hi1, xr; mul.rn.f16x2 a0, qz4, p0; fma.rn.f16x2 p1, qz5, qz5, c; fma.rn.f16x2 g1, qz1, h1, qz1; prmt.b32 h0, lo0, hi0, 0x5410;\n"
        "mov.b32 {xl, xh}, a0; tanh.approx.f16 xr, xl; cvt.u32.u16 lo0, xr; tanh.approx.f16 xr, xh; cvt.u32.u16 hi0, xr; mul.rn.f16x2 a1, qz5, p1; fma.rn.f16x2 p0, qz6, qz6, c; fma.rn.f16x2 g2, qz2, h0, qz2; prmt.b32 h1, lo1, hi1, 0x5410;\n"
        "mov.b32 {xl, xh}, a1; tanh.approx.f16 xr, xl; cvt.u32.u16 lo1, xr; tanh.approx.f16 xr, xh; cvt.u32.u16 hi1, xr; mul.rn.f16x2 a2, qz6, p0; fma.rn.f16x2 p1, qz7, qz7, c; fma.rn.f16x2 g3, qz3, h1, qz3; prmt.b32 h0, lo0, hi0, 0x5410;\n"
        "BE:\n"
        "wgmma.wait_group.sync.aligned 0;\n"
        "bra.uni LOOP;\n"
        "STORE:\n"
        "bar.sync tt, 128;\n"
        "setp.lt.s32 pr, n, 0;\n"
        "@pr bra.uni STOREB;\n"
        "cvt.u64.u32 gp, off; add.s64 gp, gp, %11;\n"
        "elect.sync _|pr, 0xffffffff;\n"
        "@pr cp.async.bulk.global.shared::cta.bulk_group [gp], [%4], 12288;\n"
        "@pr cp.async.bulk.commit_group;\n"
        "bra.uni STOREB;\n"
        "YLOAD:\n"
        "@!pm bra.uni YLOADP;\n"
        "cp.async.bulk.wait_group.read 0;\n"
        "sub.u32 ad, off, %8; cvt.u64.u32 gp, ad; add.s64 gp, gp, %11;\n"
        "elect.sync _|pr, 0xffffffff;\n"
        "@pr mbarrier.arrive.expect_tx.shared::cta.b64 _, [ybar], 12288;\n"
        "@pr cp.async.bulk.shared::cluster.global.mbarrier::complete_tx::bytes [%4], [gp], 12288, [ybar];\n"
        "YLOADP:\n"
        "cvt.u64.u32 gp, off; add.s64 gp, gp, %10;\n"
        "elect.sync _|pr, 0xffffffff;\n"
        "@pr cp.async.bulk.prefetch.L2.global.L2::cache_hint [gp], 12288, pol;\n"
        "bra.uni YLOADB;\n"
        "XLOAD:\n"
        "bar.sync tt, 128;\n"
        "cp.async.bulk.wait_group.read 0;\n"
        "cvt.u64.u32 gp, off; add.s64 gp, gp, %10;\n"
        "elect.sync _|pr, 0xffffffff;\n"
        "@pr mbarrier.arrive.expect_tx.shared::cta.b64 _, [xbar], 12288;\n"
        "@pr cp.async.bulk.shared::cluster.global.mbarrier::complete_tx::bytes.L2::cache_hint [%4], [gp], 12288, [xbar], pol;\n"
        "bra.uni XLOADB;\n"
        "SPINY: mov.u32 cnt, 0;\n"
        "SPINYL:\n"
        "add.u32 tt, n, 1; and.b32 tt, tt, 1; mbarrier.try_wait.parity.shared::cta.b64 pw, [ybar], tt;\n"
        "@pw bra.uni BACKY;\n"
        "add.u32 cnt, cnt, 1; setp.lt.u32 pw, cnt, 0x100000;\n"
        "@pw bra.uni SPINYL;\n"
        "trap;\n"
        "SPINX: mov.u32 cnt, 0;\n"
        "SPINXL:\n"
        "and.b32 tt, n, 1; mbarrier.try_wait.parity.shared::cta.b64 pw, [xbar], tt;\n"
        "@pw bra.uni BACKX;\n"
        "add.u32 cnt, cnt, 1; setp.lt.u32 pw, cnt, 0x100000;\n"
        "@pw bra.uni SPINXL;\n"
        "trap;\n"
        "SPINT: mov.u32 cnt, 0;\n"
        "SPINTL:\n"
        "mad.lo.u32 tt, n, 8, tbar; mbarrier.try_wait.parity.shared::cta.b64 pw, [tt], tpar;\n"
        "@pw bra.uni BACKT;\n"
        "add.u32 cnt, cnt, 1; setp.lt.u32 pw, cnt, 0x100000;\n"
        "@pw bra.uni SPINTL;\n"
        "trap;\n"
        "SPINW0: mov.u32 cnt, 0;\n"
        "SPINW0L:\n"
        "mov.u32 tt, 231208; mbarrier.try_wait.parity.shared::cta.b64 pw, [tt], 0;\n"
        "@pw bra.uni BACKW0;\n"
        "add.u32 cnt, cnt, 1; setp.lt.u32 pw, cnt, 0x100000;\n"
        "@pw bra.uni SPINW0L;\n"
        "trap;\n"
        "SPINW1: mov.u32 cnt, 0;\n"
        "SPINW1L:\n"
        "mov.u32 tt, 231216; mbarrier.try_wait.parity.shared::cta.b64 pw, [tt], 0;\n"
        "@pw bra.uni BACKW1;\n"
        "add.u32 cnt, cnt, 1; setp.lt.u32 pw, cnt, 0x100000;\n"
        "@pw bra.uni SPINW1L;\n"
        "trap;\n"
        "DONE:\n"
        "wgmma.wait_group.sync.aligned 0;\n"
        "}\n"
        :: "r"(prm.w1desc), "r"(prm.w2desc), "r"(c.wg), "r"(c.off), "r"(c.xs), "r"(c.a_offs), "r"(c.xs_offs), "r"(c.bias_addr),
           "r"(c.step), "r"(c.w), "l"(prm.x), "l"(prm.out)
        : "memory");
}

__device__ __forceinline__ float warp_sum(float v) {
#pragma unroll
    for (int s = 16; s >= 1; s >>= 1) v += __shfl_xor_sync(0xffffffffu, v, s);
    return v;
}
__device__ __forceinline__ float pow2f(int e) { return __uint_as_float((uint32_t)(e + 127) << 23); }
__device__ __forceinline__ int exponent_of(float v) { return (int)(__float_as_uint(v) >> 23) - 127; }
__device__ __forceinline__ float lds_bf16(uint32_t addr) {
    uint16_t v; asm volatile("ld.shared.u16 %0, [%1];" : "=h"(v) : "r"(addr) : "memory"); return bf_lo(v);
}

__device__ __forceinline__ void publish_bias(const Params& prm, uint32_t c, uint32_t tag) {
    const uint32_t lane = fresh_tid() & 31;
    const uint32_t col = sb + SM_W2 + (c >> 5) * 24576 + lane * 64 + ((((c >> 3) ^ (lane >> 1)) & 3) * 16) + (c & 7) * 2;
    float v = 0.0f;
#pragma unroll
    for (int k = 0; k < EX / 32; k++) v = fmaf(lds_bf16(col + k * 2048), lds_bf16(sb + SM_BETA + lane * 2 + k * 64), v);
    v = warp_sum(v);
    if (lane == 0)
        asm volatile("st.relaxed.gpu.global.u64 [%0], %1;" ::"l"(prm.g->bias + c), "l"((uint64_t)tag << 32 | __float_as_uint(v)) : "memory");
}
__device__ __forceinline__ void collect_bias(const Params& prm, uint32_t tag) {
    const uint32_t lane = fresh_tid() & 31;
    if (lane < 24) {
        const unsigned long long* src = prm.g->bias + 32 * (lane >> 3) + 8 * (lane & 3) + (lane & 4);
        uint32_t v[4], t[4], spins = 0;
        for (;;) {
#pragma unroll
            for (int k = 0; k < 4; k++)
                asm volatile("{\n.reg .b64 w;\nld.relaxed.gpu.global.u64 w, [%2];\nmov.b64 {%0, %1}, w;\n}\n"
                             : "=r"(v[k]), "=r"(t[k]) : "l"(src + k) : "memory");
            if (t[0] == tag && t[1] == tag && t[2] == tag && t[3] == tag) break;
            if (++spins > (1u << 22)) __trap();
        }
        sts128(sb + SM_BIAS + lane * 16, v[0], v[1], v[2], v[3]);
    }
    __syncwarp();
}
__device__ __forceinline__ float fetch_w2_row(uint32_t (&u)[12][4], uint32_t row, uint32_t sw) {
    uint32_t mx[4] = {};
#pragma unroll
    for (int a = 0; a < 3; a++)
#pragma unroll
        for (int k = 0; k < 4; k++) {
            asm volatile("ld.shared.v4.b32 {%0,%1,%2,%3}, [%4];"
                         : "=r"(u[a * 4][k]), "=r"(u[a * 4 + 1][k]), "=r"(u[a * 4 + 2][k]), "=r"(u[a * 4 + 3][k])
                         : "r"(row + a * 24576 + ((k * 16) ^ sw)) : "memory");
#pragma unroll
            for (int b = 0; b < 4; b++) asm("max.xorsign.abs.bf16x2 %0, %0, %1;" : "+r"(mx[b]) : "r"(u[a * 4 + b][k]));
        }
#pragma unroll
    for (int b = 1; b < 4; b++) asm("max.xorsign.abs.bf16x2 %0, %0, %1;" : "+r"(mx[0]) : "r"(mx[b]));
    return fmaxf(fabsf(bf_lo(mx[0])), fabsf(bf_hi(mx[0])));
}

template <bool FAST> __device__ __forceinline__ bool grn_stats(float ss, float gm, float bt, float top, int e, float& gx, float& inv, int& eo) {
    gx = sqrt_fast(fmaf(ss, INV_2A * INV_2A, 1e-6f));
    const float rt = sqrt_fast(ss + 1.0f) * INV_2A * top;
    uint32_t r[4] = {FAST ? __reduce_add_sync(0xffffffffu, __float2uint_rn(gx * 128.0f)) : __float_as_uint(warp_sum(gx)),
                     __reduce_max_sync(0xffffffffu, __float_as_uint(fmaf(bt, top, rt))),
                     __reduce_max_sync(0xffffffffu, __float_as_uint(rt * fabsf(gm) * gx)),
                     (uint32_t)__any_sync(0xffffffffu, !(ss >= 16.0f && ss < ACC_LIMIT))};
    if ((e & 31) == 0) sts128(sb + SM_SEL + (e >> 5) * 16, r[0], r[1], r[2], r[3]);
    MARK(6);
    named_sync(10, 512);
    lds128(r, sb + SM_SEL + min(e & 15, 11) * 16);
    if ((e & 31) >= 12) r[0] = 0;
    const float tot = FAST ? __uint2float_rn(__reduce_add_sync(0xffffffffu, r[0])) * (1.0f / 128) : warp_sum(__uint_as_float(r[0]));
    inv = __fdividef(1.0f, fmaf(tot, 1.0f / EX, 1e-6f));
    const float bound = fmaf(__uint_as_float(__reduce_max_sync(0xffffffffu, r[2])), inv,
                             __uint_as_float(__reduce_max_sync(0xffffffffu, r[1]))) * EX;
    eo = min(max(exponent_of(bound), -90), 126) - 14;
    return __any_sync(0xffffffffu, r[3]);
}

__device__ __forceinline__ float exact_sums(const Params& prm) {
    const int lane = fresh_tid() & 31, warp = fresh_warp(), wg = warp >> 2;
    const uint32_t epoch = lds32(sb + SM_RED + (RED_EPOCH + 1) * 4), bar = sb + SM_BAR + BAR_W1 * 8;
    if (wg < 3) {
        uint32_t wa[2][24], d[2][16];
        float acc[2][2] = {};
        const uint32_t yd = prm.ydesc + ((SM_SPARE - SM_Y1) >> 4), wd = prm.w1desc + ((2 * wg * 12288 + 5 * 2048) >> 4);
        load_w1t(wa, wg, warp & 3, lane);
#pragma unroll 1
        for (int n = 0; n < ROWS_PER_CTA; n++) {
            if (warp == 0) {
                expect_tx(bar, TILE_BYTES);
                bulk_load(sb + SM_SPARE, (const char*)prm.out + (cta_tile0(fresh_cta()) + n * cta_stride(fresh_cta())), TILE_BYTES, bar);
            }
            mbar_wait(bar, (n + 1) & 1);
            gemm1_t<0>(d[0], wa[0], yd, wd);
            gemm1_t<1>(d[1], wa[1], yd, wd);
            wg_wait<0>();
            pin(d[0]); pin(d[1]);
            gelu_sumsq_f(d[0], acc[0]);
            gelu_sumsq_f(d[1], acc[1]);
            named_sync(1, 384);
        }
        publish_sums(acc, prm.g->sums[epoch & 1], &prm.g->count[1], wg, warp & 3, lane);
    }
    grid_wait(&prm.g->count[1], (epoch + 1) * NUM_CTAS);
    return __ldcg(prm.g->sums[epoch & 1] + fresh_tid() % EX);
}

template <bool FIRST> __device__ __forceinline__ void prepare_pass2(const Pass2& c, const Params& prm, float ss) {
    const int tid = fresh_tid(), lane = tid & 31, warp = fresh_warp(), wg = warp >> 2;
    const int e = tid >= EX ? tid - EX : tid;
    const uint32_t w2row = sb + SM_W2 + e * 64, sw = ((e >> 1) & 3) * 16;
    pass2_start(c, prm);
    MARK(2);
    if (wg) {
        uint32_t u[12][4];
        mbar_wait_c<0>(sb + SM_BAR + BAR_W2 * 8);
        const float top = fetch_w2_row(u, w2row, sw);
        MARK(3);
        const float gm = lds_bf16(sb + SM_GAMMA + e * 2), bt = fabsf(lds_bf16(sb + SM_BETA + e * 2));
        if (FIRST) {
            const uint32_t epoch = lds32(sb + SM_RED + RED_EPOCH * 4);
            if (wg == 3) named_sync(11, EX);
            if (warp == 12) collect_bias(prm, epoch + 1);
            MARK(4);
            ss = collect_fast(acc_word(prm, epoch, e));
            if (tid == 416 && fresh_cta() == 0) prm.g->count[0] = epoch + 1;
        }
        if (warp == 4) TS(4);
        MARK(5);
        float gx, inv;
        int eo;
        const bool redo = (grn_stats<FIRST>(ss, gm, bt, top, e, gx, inv, eo) || FORCE_EXACT) && FIRST;
        MARK(8);
        const float up = pow2f(eo), dn = pow2f(-eo);
        if (warp == 4) {
            if (lane == 24) sts64(sb + SM_RED + RED_SCALE * 4, pack_bf2(up, up), redo);
            if (lane < 24 && !redo) {
                uint32_t b[4];
                lds128(b, sb + SM_BIAS + lane * 16);
                const uint32_t p0 = pack_h2(__uint_as_float(b[0]) * dn, __uint_as_float(b[1]) * dn);
                const uint32_t p1 = pack_h2(__uint_as_float(b[2]) * dn, __uint_as_float(b[3]) * dn);
                sts128(sb + SM_BIAS + lane * 16, p0, p0, p1, p1);
            }
            __syncwarp();
            mbar_arrive_if(sb + SM_BAR + BAR_STAT * 8, lane == 0);
        }
        if (!redo) {
            float sc = fmaf(gm, gx * inv, 1.0f) * INV_2A;
            if (eo > 6) {
                const uint32_t dn2 = pack_bf2(dn, dn);
#pragma unroll
                for (int k = 0; k < 48; k++) u[k >> 2][k & 3] = bf2_mul(u[k >> 2][k & 3], dn2);
            } else {
                sc *= dn;
            }
            const uint32_t s2 = pack_bf2(sc * 0x1p-112f, sc * 0x1p-112f);
#pragma unroll
            for (int k = 0; k < 12; k++) {
                uint32_t v[4];
#pragma unroll
                for (int b = 0; b < 4; b++) {
                    v[b] = bf2_mul(u[k][b], s2);
                    v[b] += (v[b] & 0x7fff7fffu) * 7u;
                }
                sts128(w2row + (k >> 2) * 24576 + (((k & 3) * 16) ^ sw), v[0], v[1], v[2], v[3]);
            }
            MARK(9);
            fence_async_smem();
            __syncwarp();
            mbar_arrive_if(sb + SM_BAR + (BAR_ROWS + (wg != 3)) * 8, lane == 0);
        }
        if (warp == 4) TS(5);
    } else {
        asm volatile("bar.arrive 10, 512;" ::: "memory");
    }
}

__device__ __forceinline__ void pass2_uniform(Pass2& c) {
    const int warp = fresh_warp(), wg = warp >> 2;
    c.wg = wg;
    c.w = warp & 3;
    c.off = cta_tile0(fresh_cta()) + (ROWS_PER_CTA - 1 - wg) * cta_stride(fresh_cta());
    c.step = 4 * cta_stride(fresh_cta());
    c.xs = wg == 3 ? sb + SM_BUF3 : sb + SM_Y1 + (wg == 2 ? 2 : 1 - wg) * SLOT_BYTES;
    static_assert((ROWS_PER_CTA - 1) % NX == 1, "slot of the last tile");
}
__device__ __forceinline__ Pass2 pass2_setup() {
    Pass2 c;
    pass2_uniform(c);
    const int lane = fresh_tid() & 31, w = c.w, arow = 16 * w + (lane & 15);
    c.a_offs = (arow * 128 + (((lane >> 4) ^ (arow & 7)) * 16)) |
               (8192 + arow * 64 + (((lane >> 4) ^ ((arow >> 1) & 3)) * 16)) << 16;
    const int g = lane >> 2, px = 33 * (g & 1) + 4 * (g >> 1) + 16 * (w >> 1) + 2 * (w & 1);
    c.xs_offs = (px * 192 + (lane & 3) * 16) | ((px ^ 1) * 192 + (lane & 3) * 16) << 16;
    c.bias_addr = sb + SM_BIAS + (lane & 3) * 16;
    return c;
}

__global__ void __launch_bounds__(512, 1) convnext_kernel(const __grid_constant__ Params prm) {
    extern __shared__ __align__(1024) uint8_t smem[];
    if ((uint32_t)__cvta_generic_to_shared(smem) != sb) __trap();
    {
        const uint32_t tid = fresh_tid(), warp = fresh_warp(), lane = tid & 31;
        if (warp == 0) {
            if (lane == 0) {
#pragma unroll
                for (int k = 0; k < NX; k++) mbar_init(sb + SM_GO + k * 8, 2);
                mbar_init(sb + SM_BAR + BAR_DW * 8, 1);
                mbar_init(sb + SM_BAR + BAR_W1 * 8, 1);
                mbar_init(sb + SM_BAR + BAR_W1B * 8, 1);
                fence_async_smem();
            }
            __syncwarp();
            expect_tx(sb + SM_BAR + BAR_DW * 8, 9 * CH * 2);
            bulk_load(sb + SM_Y1, prm.dw, 9 * CH * 2, sb + SM_BAR + BAR_DW * 8);
            const RowCopy rc = row_copy(prm);
#pragma unroll
            for (int k = 0; k < NX; k++) issue_row_load(rc, k, k);
            SMARK(4);
        }
        if (fresh_warp() == 15) {
            const uint32_t cta = fresh_cta();
            bulk_prefetch((const char*)prm.w1 + cta * (CH * EX * 2 / NUM_CTAS), CH * EX * 2 / NUM_CTAS);
            bulk_prefetch(prm.dw, 9 * CH * 2);
            bulk_prefetch((const char*)prm.x + (cta_tile0(cta) - cta_stride(cta)), TILE_BYTES);
        } else if (warp == 2) {
            if (lane < 2) asm volatile("prefetch.tensormap [%0];" ::"l"(&prm.w1_map + lane) : "memory");
        } else if (warp - 6u < 6) {
            if (lane == 0) {
#pragma unroll 1
                for (int k = NX + warp - 6; k < GO_COUNT + ROWS_PER_CTA + 2; k += 6)
                    mbar_init(sb + SM_GO + k * 8, k < 2 * NX ? 2 : k < GO_COUNT ? 14 : 4);
                fence_async_smem();
            }
        } else if (warp == 3) {
            const uint32_t one = (lane & 5) == ((lane & 8) >> 1) + (lane >> 4) ? 0x3f803f80u : 0u;
            sts128(sb + SM_SEL + lane * 16, one, one, one, one);
            fence_async_smem();
        } else if (tid - 128u < NX * 12 && ((fresh_cta() + 1) & 7) < 2) {
            const int k = tid - 128;
            sts128(sb + SM_X + (k / 12) * SLOT_BYTES + ((fresh_cta() & 7) == 0 ? 0 : XHALF_B + 33 * 192) + (k % 12) * 16, 0, 0, 0, 0);
        }
        __syncwarp();
        SMARK(3);
        named_sync(0, 512);
    }
    if (fresh_warp() >= 12) {
        Producer pc;
        SMARK(0);
        asm volatile("setmaxnreg.inc.sync.aligned.u32 %0;" ::"n"(PRODUCER_REGS));
        SMARK(1);
        const int w = fresh_warp() & 3, lane = fresh_tid() & 31;
        const int j = lane & 7, hb = (lane >> 3) & 1, base = 4 * (2 * w + (lane >> 4));
        pc.lane = lane;
        pc.xoff[0] = hb * XHALF_B + base * 192 + j * 16;
        pc.xoff[1] = hb * XHALF_B + base * 192 + 128 + j * 8;
        const int grp = 4 * w + (lane >> 3);
#pragma unroll
        for (int o = 0; o < 2; o++) {
            const int row = (grp & 7) + 8 * (o ^ hb) + 32 * (grp >> 3);
            pc.yoff[0][o] = row * 128 + ((j ^ (row & 7)) * 16);
            pc.yoff[1][o] = 8192 + row * 64 + (((j >> 1) ^ ((row >> 1) & 3)) * 16) + (j & 1) * 8;
        }
        pc.stat = sb + SM_STAT + (8 * w + (lane >> 2)) * 32;
        pc.own = pc.stat + (lane & 3) * 8;
        const int dstep = fresh_cta() & 8 ? 3 * CH * 2 : -3 * CH * 2;
        mbar_wait_c<0>(sb + SM_BAR + BAR_DW * 8);
        SMARK(8);
#pragma unroll
        for (int tap = 0; tap < 9; tap++) {
            const uint32_t dw = sb + SM_Y1 + (3 + tap % 3) * CH * 2 + (tap / 3 - 1) * dstep;
            lds128(pc.w[tap], dw + j * 16);
            asm volatile("ld.shared.v2.b32 {%0,%1}, [%2];" : "=r"(pc.w[tap][4]), "=r"(pc.w[tap][5]) : "r"(dw + 128 + j * 8) : "memory");
        }
#pragma unroll
        for (int tap = 0; tap < 9; tap++)
#pragma unroll
            for (int u = 0; u < 6; u++) pc.w[tap][u] = bf2_mul(pc.w[tap][u], TAP_SCALE_BF2);
        produce(pc, prm);
        TS(9);
        asm volatile("setmaxnreg.dec.sync.aligned.u32 %0;" ::"n"(EVEN_REGS));
        if (fresh_warp() == 12) {
            mbar_wait_c<0>(sb + SM_BAR + BAR_W2 * 8);
            if (fresh_cta() < CH) publish_bias(prm, fresh_cta(), lds32(sb + SM_RED + RED_EPOCH * 4) + 1);
        }
    } else {
        asm volatile("setmaxnreg.dec.sync.aligned.u32 %0;" ::"n"(CONSUMER_REGS));
        {
            const int tid = fresh_tid(), warp = fresh_warp();
            if (warp == 1) {
#pragma unroll
                for (int h = 0; h < 2; h++) {
                    const uint32_t bar = sb + SM_BAR + (h ? BAR_W1B : BAR_W1) * 8;
                    expect_tx(bar, CH * EX);
#pragma unroll
                    for (int q = h; q < 6; q += 2) tma_load_2d(sb + SM_W1 + q * 12288, &prm.w1_map, 64 * q, 0, bar);
                }
            }
            uint32_t cnt[2];
            asm volatile("ld.relaxed.gpu.global.v2.u32 {%0, %1}, [%2];" : "=r"(cnt[0]), "=r"(cnt[1]) : "l"(prm.g->count) : "memory");
            SMARK(0);
            if (warp == 2) {
                const RowCopy rc = row_copy(prm);
#pragma unroll 1
                for (int i = loop_init<0>(); i < NX; i++) {
                    named_sync(6 + i, 160);
                    issue_row_load(rc, i + NX, i);
                }
            }
            if (tid == 256) {
                sts64(sb + SM_RED + RED_EPOCH * 4, cnt[0], cnt[1] / NUM_CTAS);
#pragma unroll
                for (int k = 0; k < BAR_DW; k++)
                    if (k != BAR_W1 && k != BAR_W1B) mbar_init(sb + SM_BAR + k * 8, k < BAR_TURN || k == BAR_STAT ? 1 : k == BAR_ROWS + 1 ? 8 : 4);
#pragma unroll
                for (int k = 0; k < 3; k++) mbar_arrive_if(sb + SM_BAR + (BAR_Y2FULL + k) * 8, true);
            }
            if (fresh_cta() == 0) *acc_word(prm, cnt[0] + 1, tid) = 0;
            if (fresh_cta() == 1) prm.g->sums[~(cnt[1] / NUM_CTAS) & 1][tid] = 0.0f;
            __syncwarp();
            SMARK(1);
            mbar_wait_c<0>(sb + SM_BAR + BAR_W1 * 8);
            SMARK(2);
        }

        const int tid = fresh_tid(), lane = tid & 31, wg = fresh_warp() >> 2, w = fresh_warp() & 3;
        float acc[2][2];
        const int c = 8 * (lane >> 4) + (lane & 7), ck = 2 * w + ((lane >> 3) & 1);
        consume(acc, sb + SM_W1 + 2 * wg * 12288 + c * 128 + ((ck ^ (c & 7)) * 16), prm.ydesc,
                prm.w1desc + (((2 * wg + 1) * 12288 + 5 * 2048) >> 4), wg * SLOT_BYTES, make_duty(prm, wg, w), w, lane, prm);
        publish_fast(prm, acc, lds32(sb + SM_RED + RED_EPOCH * 4), wg, w, lane);
        if (wg) asm volatile("bar.arrive 11, 384;" ::: "memory");
        MARK(0);
        bulk_wait_all();
        if (wg == 0) TS(3);
        asm volatile("setmaxnreg.inc.sync.aligned.u32 %0;" ::"n"(EVEN_REGS));
    }

    {
        asm volatile(PASS2_STATE);
        MARK(1);
        Pass2 c = pass2_setup();
        prepare_pass2<true>(c, prm, 0.0f);
        if (pass2_head(c, 0)) {
            const float ss = exact_sums(prm);
            c = pass2_setup();
            prepare_pass2<false>(c, prm, ss);
            pass2_head(c, 1);
        }

        pass2_uniform(c);
        pass2_tiles(c, prm);
        bulk_wait_read<0>();
        MARK(13);
    }
}

}

extern "C" void kernel_launch(void* const* d_in, const int* in_sizes, int n_in, void* d_out, int out_size) {
    (void)in_sizes; (void)n_in; (void)out_size;
    typedef CUresult (*EncodeFn)(CUtensorMap*, CUtensorMapDataType, cuuint32_t, void*, const cuuint64_t*, const cuuint64_t*,
                                 const cuuint32_t*, const cuuint32_t*, CUtensorMapInterleave, CUtensorMapSwizzle,
                                 CUtensorMapL2promotion, CUtensorMapFloatOOBfill);
    void* fn = nullptr;
    cudaDriverEntryPointQueryResult status;
    cudaGetDriverEntryPoint("cuTensorMapEncodeTiled", &fn, cudaEnableDefault, &status);
    const EncodeFn encode = (EncodeFn)fn;
    const cuuint32_t ones[2] = {1, 1};

    Params p;
    {
        const cuuint64_t dims[2] = {EX, CH}, strides[1] = {EX * 2};
        const cuuint32_t box[2] = {64, CH};
        encode(&p.w1_map, CU_TENSOR_MAP_DATA_TYPE_BFLOAT16, 2, d_in[2], dims, strides, box, ones,
               CU_TENSOR_MAP_INTERLEAVE_NONE, CU_TENSOR_MAP_SWIZZLE_128B, CU_TENSOR_MAP_L2_PROMOTION_NONE,
               CU_TENSOR_MAP_FLOAT_OOB_FILL_NONE);
    }
    {
        const cuuint64_t dims[2] = {CH, EX}, strides[1] = {CH * 2};
        const cuuint32_t box[2] = {32, 192};
        encode(&p.w2_map, CU_TENSOR_MAP_DATA_TYPE_BFLOAT16, 2, d_in[3], dims, strides, box, ones,
               CU_TENSOR_MAP_INTERLEAVE_NONE, CU_TENSOR_MAP_SWIZZLE_64B, CU_TENSOR_MAP_L2_PROMOTION_NONE,
               CU_TENSOR_MAP_FLOAT_OOB_FILL_NONE);
    }
    p.x = (const __nv_bfloat16*)d_in[0];
    p.dw = (const __nv_bfloat16*)d_in[1];
    p.w1 = (const __nv_bfloat16*)d_in[2];
    p.gamma = (const __nv_bfloat16*)d_in[4];
    p.beta = (const __nv_bfloat16*)d_in[5];
    p.out = (__nv_bfloat16*)d_out;
    cudaGetSymbolAddress((void**)&p.g, g_scratch);
    p.w1desc = desc_lo(sb + SM_W1, 12288);
    p.w2desc = desc_lo(sb + SM_W2, 24576);
    p.ydesc = desc_lo(sb + SM_Y1, 16);
    p.ydesc64[0] = (0x40000040ull << 32) | p.ydesc;
    p.ydesc64[1] = (0x80000020ull << 32) | (p.ydesc + 512);
    for (int k = 0; k < 3; k++) p.sel[k] = (8ull << 32) | desc_lo(sb + SM_SEL + k * 128, k == 2 ? 128 : 0);
    constexpr int smem_bytes = SM_TOTAL;
    cudaFuncSetAttribute(convnext_kernel, cudaFuncAttributeMaxDynamicSharedMemorySize, smem_bytes);
    convnext_kernel<<<NUM_CTAS, 512, smem_bytes>>>(p);
}
```

```cpp
#include <cuda.h>
#include <cuda_runtime.h>
#include <cuda_bf16.h>
#include <stdint.h>

namespace {

constexpr int IMG_W = 512, CH = 96, EX = 384;
constexpr int TILE_PX = 64;
constexpr int ROWS_PER_CTA = 32;
constexpr int NUM_CTAS = 128;
constexpr int STEPS = ROWS_PER_CTA + 2;
constexpr int ROW_BYTES = IMG_W * CH * 2;

#define FORCE_EXACT 0
constexpr int PRODUCER_REGS = 200, CONSUMER_REGS = 104, EVEN_REGS = 128;

constexpr int XHALF_BYTES = 34 * 192;
constexpr int XHALF_B = XHALF_BYTES + 64;
constexpr int XROW_BYTES = XHALF_B + XHALF_BYTES + 64;
constexpr int L2_AHEAD = 2;
constexpr int NX = 3;
constexpr int TILE_BYTES = TILE_PX * 192;

constexpr uint32_t sb = 1024;
constexpr int SM_W1 = 0;
constexpr int SM_W2 = 73728;
constexpr int SM_RING = 147456;
constexpr int SLOT_BYTES = 26624;
constexpr int SM_Y1 = SM_RING;
constexpr int SM_X = SM_Y1 + TILE_BYTES;
constexpr int SM_STAT = SM_X + XROW_BYTES;
constexpr int SM_BUF3 = SM_X + SLOT_BYTES, SM_SPARE = SM_X;
constexpr int SM_SEL = SM_RING + NX * SLOT_BYTES;
constexpr int SM_BIAS = SM_SEL + 512;
constexpr int SM_GAMMA = SM_BIAS + 384;
constexpr int SM_BETA = SM_GAMMA + EX * 2;
constexpr int SM_RED = SM_BETA + EX * 2;
constexpr int SM_BAR = SM_RED + 16;
constexpr int BAR_Y2FULL = 0, BAR_XSFULL = 4, BAR_W1 = 8, BAR_W2 = 9, BAR_W1B = 10, BAR_TURN = 11, BAR_ROWS = 51,
              BAR_STAT = 53, BAR_DW = 54, BAR_COUNT = 55;
constexpr int SM_GO = SM_BAR + BAR_COUNT * 8, GO_COUNT = ROWS_PER_CTA + 2 * NX;
constexpr int SM_YFULL = SM_GO + (GO_COUNT + 1) * 8;
constexpr int SM_TOTAL = SM_YFULL + (ROWS_PER_CTA + 1) * 8;
static_assert(SM_STAT + TILE_PX * 16 <= SM_RING + SLOT_BYTES && XROW_BYTES >= TILE_BYTES && SM_X % 1024 == 0, "ring layout");
static_assert(SM_TOTAL <= 232448, "smem budget");
static_assert(SM_STAT % 128 == 0 && SM_BIAS % 16 == 0 && SM_BAR % 8 == 0 && SLOT_BYTES % 1024 == 0, "alignment");

constexpr int RED_EPOCH = 0, RED_SCALE = 2;

constexpr float GELU_A = 0.32920349f;
constexpr uint32_t GELU_C_H2 = 0x40D940D9u;
constexpr float INV_2A = 1.0f / (2.0f * GELU_A);

constexpr uint32_t TAP_SCALE_BF2 = 0x2B802B80u;
constexpr float LN_EPS_SCALED = 1e-5f * 0x1p-80f;
constexpr float RSTD_SCALE = GELU_A * 0x1p-112f;

struct Scratch {
    unsigned long long acc[2][EX / 4 * 32];
    unsigned long long bias[CH];
    float sums[2][EX];
    uint4 zero_row[66 * 192 / 16];
    unsigned int count[2];
};
__device__ __align__(256) Scratch g_scratch;
constexpr float ACC_LIMIT = 0x1p30f;

#define TS(k)
#define ASM_TS
#define MARK(k)
#define SMARK(k)
#define ASM_MARK
#define ASM_SMARK
#define ASM_TRC(it)

__device__ __forceinline__ void mbar_init(uint32_t bar, uint32_t count) {
    asm volatile("mbarrier.init.shared::cta.b64 [%0], %1;" ::"r"(bar), "r"(count) : "memory");
}
__device__ __forceinline__ void mbar_arrive_if(uint32_t bar, bool pred) {
    asm volatile("{\n.reg .pred p;\nsetp.ne.u32 p, %1, 0;\n@p mbarrier.arrive.shared::cta.b64 _, [%0];\n}\n"
                 ::"r"(bar), "r"((uint32_t)pred) : "memory");
}
__device__ __forceinline__ void mbar_wait(uint32_t bar, uint32_t parity) {
    asm volatile(
        "{\n.reg .pred p;\n.reg .u32 n;\n"
        "mbarrier.try_wait.parity.shared::cta.b64 p, [%0], %1;\n"
        "@p bra.uni WAIT_DONE;\n"
        "mov.u32 n, 0;\n"
        "WAIT_LOOP:\n"
        "mbarrier.try_wait.parity.shared::cta.b64 p, [%0], %1;\n"
        "@p bra.uni WAIT_DONE;\n"
        "mbarrier.try_wait.parity.shared::cta.b64 p, [%0], %1;\n"
        "@p bra.uni WAIT_DONE;\n"
        "mbarrier.try_wait.parity.shared::cta.b64 p, [%0], %1;\n"
        "@p bra.uni WAIT_DONE;\n"
        "add.u32 n, n, 1;\nsetp.lt.u32 p, n, 0x40000;\n"
        "@p bra.uni WAIT_LOOP;\n"
        "trap;\n"
        "WAIT_DONE:\n}\n"
        ::"r"(bar), "r"(parity) : "memory");
}
template <int PARITY> __device__ __forceinline__ void mbar_wait_c(uint32_t bar) {
    asm volatile(
        "{\n.reg .pred p;\n.reg .u32 n;\n"
        "mbarrier.try_wait.parity.shared::cta.b64 p, [%0], %1;\n"
        "@p bra.uni WAIT_DONE;\n"
        "mov.u32 n, 0;\n"
        "WAIT_LOOP:\n"
        "mbarrier.try_wait.parity.shared::cta.b64 p, [%0], %1;\n"
        "@p bra.uni WAIT_DONE;\n"
        "mbarrier.try_wait.parity.shared::cta.b64 p, [%0], %1;\n"
        "@p bra.uni WAIT_DONE;\n"
        "mbarrier.try_wait.parity.shared::cta.b64 p, [%0], %1;\n"
        "@p bra.uni WAIT_DONE;\n"
        "add.u32 n, n, 1;\nsetp.lt.u32 p, n, 0x40000;\n"
        "@p bra.uni WAIT_LOOP;\n"
        "trap;\n"
        "WAIT_DONE:\n}\n"
        ::"r"(bar), "n"(PARITY) : "memory");
}
#define ELECTED(body) "{\n.reg .pred p;\nelect.sync _|p, 0xffffffff;\n" body "}\n"
__device__ __forceinline__ void expect_tx(uint32_t bar, uint32_t bytes) {
    asm volatile(ELECTED("@p mbarrier.arrive.expect_tx.shared::cta.b64 _, [%0], %1;\n") ::"r"(bar), "r"(bytes) : "memory");
}
__device__ __forceinline__ void bulk_load(uint32_t dst, const void* src, uint32_t bytes, uint32_t bar) {
    asm volatile(ELECTED("@p cp.async.bulk.shared::cluster.global.mbarrier::complete_tx::bytes [%0], [%1], %2, [%3];\n")
                 ::"r"(dst), "l"(src), "r"(bytes), "r"(bar) : "memory");
}
__device__ __forceinline__ void bulk_prefetch(const void* src, uint32_t bytes) {
    asm volatile(ELECTED("@p cp.async.bulk.prefetch.L2.global [%0], %1;\n") ::"l"(src), "r"(bytes) : "memory");
}
__device__ __forceinline__ void tma_load_2d(uint32_t dst, const CUtensorMap* map, int c0, int c1, uint32_t bar) {
    asm volatile(ELECTED("@p cp.async.bulk.tensor.2d.shared::cluster.global.mbarrier::complete_tx::bytes [%0], [%1, {%2, %3}], [%4];\n")
                 ::"r"(dst), "l"(map), "r"(c0), "r"(c1), "r"(bar) : "memory");
}
template <int N> __device__ __forceinline__ void bulk_wait_read() {
    asm volatile("cp.async.bulk.wait_group.read %0;" ::"n"(N) : "memory");
}
__device__ __forceinline__ void bulk_wait_all() { asm volatile("cp.async.bulk.wait_group 0;" ::: "memory"); }
__device__ __forceinline__ void fence_async_smem() { asm volatile("fence.proxy.async.shared::cta;" ::: "memory"); }
__device__ __forceinline__ void named_sync(int id, int n) { asm volatile("bar.sync %0, %1;" ::"r"(id), "r"(n) : "memory"); }

__device__ __forceinline__ void sts64(uint32_t addr, uint32_t a, uint32_t b) {
    asm volatile("st.shared.v2.b32 [%0], {%1,%2};" ::"r"(addr), "r"(a), "r"(b) : "memory");
}
__device__ __forceinline__ void sts128(uint32_t addr, uint32_t a, uint32_t b, uint32_t c, uint32_t d) {
    asm volatile("st.shared.v4.b32 [%0], {%1,%2,%3,%4};" ::"r"(addr), "r"(a), "r"(b), "r"(c), "r"(d) : "memory");
}
__device__ __forceinline__ void ldsm4_t(uint32_t* r, uint32_t addr) {
    asm volatile("ldmatrix.sync.aligned.m8n8.x4.trans.shared.b16 {%0,%1,%2,%3}, [%4];"
                 : "=r"(r[0]), "=r"(r[1]), "=r"(r[2]), "=r"(r[3]) : "r"(addr) : "memory");
}
__device__ __forceinline__ void lds128(uint32_t* v, uint32_t addr) {
    asm volatile("ld.shared.v4.b32 {%0,%1,%2,%3}, [%4];"
                 : "=r"(v[0]), "=r"(v[1]), "=r"(v[2]), "=r"(v[3]) : "r"(addr) : "memory");
}
__device__ __forceinline__ uint32_t lds32(uint32_t addr) {
    uint32_t v; asm volatile("ld.shared.b32 %0, [%1];" : "=r"(v) : "r"(addr) : "memory"); return v;
}
__device__ __forceinline__ void sts32(uint32_t addr, uint32_t v) {
    asm volatile("st.shared.b32 [%0], %1;" ::"r"(addr), "r"(v) : "memory");
}

__device__ __forceinline__ uint32_t bf2_fma(uint32_t a, uint32_t b, uint32_t c) {
    uint32_t d; asm("fma.rn.bf16x2 %0, %1, %2, %3;" : "=r"(d) : "r"(a), "r"(b), "r"(c)); return d;
}
__device__ __forceinline__ uint32_t bf2_mul(uint32_t a, uint32_t b) {
    uint32_t d; asm("mul.rn.bf16x2 %0, %1, %2;" : "=r"(d) : "r"(a), "r"(b)); return d;
}
__device__ __forceinline__ uint32_t bf2_add(uint32_t a, uint32_t b) {
    uint32_t d; asm("add.rn.bf16x2 %0, %1, %2;" : "=r"(d) : "r"(a), "r"(b)); return d;
}
__device__ __forceinline__ uint32_t h2_fma(uint32_t a, uint32_t b, uint32_t c) {
    uint32_t d; asm("fma.rn.f16x2 %0, %1, %2, %3;" : "=r"(d) : "r"(a), "r"(b), "r"(c)); return d;
}
__device__ __forceinline__ uint32_t h2_mul(uint32_t a, uint32_t b) {
    uint32_t d; asm("mul.rn.f16x2 %0, %1, %2;" : "=r"(d) : "r"(a), "r"(b)); return d;
}
__device__ __forceinline__ uint32_t h2_tanh(uint32_t a) {
    uint32_t d; asm("tanh.approx.f16x2 %0, %1;" : "=r"(d) : "r"(a)); return d;
}
__device__ __forceinline__ float bf_lo(uint32_t v) { return __uint_as_float(v << 16); }
__device__ __forceinline__ float bf_hi(uint32_t v) { return __uint_as_float(v & 0xffff0000u); }
__device__ __forceinline__ uint32_t pack_h2(float lo, float hi) {
    uint32_t d; asm("cvt.rn.f16x2.f32 %0, %1, %2;" : "=r"(d) : "f"(hi), "f"(lo)); return d;
}
__device__ __forceinline__ uint32_t pack_bf2(float lo, float hi) {
    uint32_t d; asm("cvt.rn.bf16x2.f32 %0, %1, %2;" : "=r"(d) : "f"(hi), "f"(lo)); return d;
}
__device__ __forceinline__ void h2_unpack(uint32_t v, float& lo, float& hi) {
    asm("{\n.reg .b16 l, h;\nmov.b32 {l, h}, %2;\ncvt.f32.f16 %0, l;\ncvt.f32.f16 %1, h;\n}\n" : "=f"(lo), "=f"(hi) : "r"(v));
}

__device__ __forceinline__ uint32_t gelu2(uint32_t z) {
    uint32_t p = h2_fma(z, z, GELU_C_H2);
    uint32_t t = h2_tanh(h2_mul(z, p));
    return h2_fma(z, t, z);
}

__device__ __forceinline__ void wg_fence() { asm volatile("wgmma.fence.sync.aligned;" ::: "memory"); }
__device__ __forceinline__ void wg_commit() { asm volatile("wgmma.commit_group.sync.aligned;" ::: "memory"); }
template <int N> __device__ __forceinline__ void wg_wait() {
    asm volatile("wgmma.wait_group.sync.aligned %0;" ::"n"(N) : "memory");
}
template <int N> __device__ __forceinline__ void pin(uint32_t (&r)[N]) {
#pragma unroll
    for (int i = 0; i < N; i++) asm volatile("" : "+r"(r[i])::"memory");
}
constexpr uint32_t desc_lo(uint32_t addr, uint32_t lbo) { return ((addr & 0x3FFFF) >> 4) | ((lbo >> 4) << 16); }
template <uint32_t SBO, uint32_t SWZ> __device__ __forceinline__ uint64_t desc(uint32_t lo, uint32_t bytes) {
    return (((uint64_t)((SBO >> 4) | (SWZ << 30)) << 32) | lo) + (bytes >> 4);
}
__device__ __forceinline__ uint32_t fresh_tid() {
    uint32_t v; asm volatile("mov.u32 %0, %%tid.x;" : "=r"(v));
    return v;
}
template <uint32_t V> __device__ __forceinline__ uint32_t loop_init() {
    uint32_t v; asm volatile("mov.u32 %0, %1;" : "=r"(v) : "n"(V)); return v;
}
__device__ __forceinline__ int fresh_warp() {
    int v; asm volatile("shfl.sync.idx.b32 %0, %1, 0, 0x1f, 0xffffffff;" : "=r"(v) : "r"(fresh_tid() >> 5)); return v;
}
__device__ __forceinline__ uint32_t fresh_cta() {
    uint32_t v; asm volatile("mov.u32 %0, %%ctaid.x;" : "=r"(v)); return v;
}
__device__ __forceinline__ float sqrt_fast(float v) { float r; asm("sqrt.approx.f32 %0, %1;" : "=f"(r) : "f"(v)); return r; }

template <int TB>
__device__ __forceinline__ void wgmma_n64_h_set(uint32_t (&d)[16], const uint32_t* a, uint64_t desc) {
    asm volatile(
        "{\n.reg .pred p;\nsetp.ne.b32 p, 0, 0;\n"
        "wgmma.mma_async.sync.aligned.m64n64k16.f16.f16.f16 "
        "{%0,%1,%2,%3,%4,%5,%6,%7,%8,%9,%10,%11,%12,%13,%14,%15}, {%16,%17,%18,%19}, %20, p, 1, 1, %21;\n}\n"
        : "=r"(d[0]), "=r"(d[1]), "=r"(d[2]), "=r"(d[3]), "=r"(d[4]), "=r"(d[5]), "=r"(d[6]), "=r"(d[7]), "=r"(d[8]), "=r"(d[9]), "=r"(d[10]), "=r"(d[11]), "=r"(d[12]), "=r"(d[13]), "=r"(d[14]), "=r"(d[15])
        : "r"(a[0]), "r"(a[1]), "r"(a[2]), "r"(a[3]), "l"(desc), "n"(TB));
}
template <int TB>
__device__ __forceinline__ void wgmma_n64_h_acc(uint32_t (&d)[16], const uint32_t* a, uint64_t desc) {
    asm volatile(
        "{\n.reg .pred p;\nsetp.ne.b32 p, 1, 0;\n"
        "wgmma.mma_async.sync.aligned.m64n64k16.f16.f16.f16 "
        "{%0,%1,%2,%3,%4,%5,%6,%7,%8,%9,%10,%11,%12,%13,%14,%15}, {%16,%17,%18,%19}, %20, p, 1, 1, %21;\n}\n"
        : "+r"(d[0]), "+r"(d[1]), "+r"(d[2]), "+r"(d[3]), "+r"(d[4]), "+r"(d[5]), "+r"(d[6]), "+r"(d[7]), "+r"(d[8]), "+r"(d[9]), "+r"(d[10]), "+r"(d[11]), "+r"(d[12]), "+r"(d[13]), "+r"(d[14]), "+r"(d[15])
        : "r"(a[0]), "r"(a[1]), "r"(a[2]), "r"(a[3]), "l"(desc), "n"(TB));
}
__device__ __forceinline__ void wgmma_n64_h_acc_ss(uint32_t (&d)[16], uint64_t adesc, uint64_t desc) {
    asm volatile(
        "{\n.reg .pred p;\nsetp.ne.b32 p, 1, 0;\n"
        "wgmma.mma_async.sync.aligned.m64n64k16.f16.f16.f16 "
        "{%0,%1,%2,%3,%4,%5,%6,%7,%8,%9,%10,%11,%12,%13,%14,%15}, %16, %17, p, 1, 1, 1, 0;\n}\n"
        : "+r"(d[0]), "+r"(d[1]), "+r"(d[2]), "+r"(d[3]), "+r"(d[4]), "+r"(d[5]), "+r"(d[6]), "+r"(d[7]), "+r"(d[8]), "+r"(d[9]), "+r"(d[10]), "+r"(d[11]), "+r"(d[12]), "+r"(d[13]), "+r"(d[14]), "+r"(d[15])
        : "l"(adesc), "l"(desc));
}

struct Params {
    CUtensorMap w1_map, w2_map;
    const __nv_bfloat16* x;
    const __nv_bfloat16* dw;
    const __nv_bfloat16* w1;
    const __nv_bfloat16* gamma;
    const __nv_bfloat16* beta;
    __nv_bfloat16* out;
    Scratch* g;
    uint64_t ydesc64[2];
    uint64_t sel[3];
    uint32_t w1desc, w2desc, ydesc;
};

__device__ __forceinline__ int cta_stride(uint32_t cta) { return cta & 8 ? ROW_BYTES : -ROW_BYTES; }
__device__ __forceinline__ uint32_t cta_tile0(uint32_t cta) {
    return ((cta >> 3) * ROWS_PER_CTA + (cta & 8 ? 0 : ROWS_PER_CTA - 1)) * ROW_BYTES + (cta & 7) * TILE_BYTES;
}

struct Producer {
    uint32_t w[9][6];
    uint32_t xoff[2];
    uint32_t yoff[2][2];
    uint32_t stat, own;
    int lane;
};

struct RowCopy {
    const char* x0;
    char* y0;
    const char* zeros;
    uint32_t cut0, cut1;
    int stride, last;
};
__device__ __forceinline__ RowCopy row_copy(const Params& prm) {
    const uint32_t cta = fresh_cta(), strip = cta & 7, t0 = cta_tile0(cta);
    RowCopy r;
    r.stride = cta_stride(cta);
    r.x0 = (const char*)prm.x + (t0 - r.stride) - 192;
    r.y0 = (char*)prm.out + t0;
    r.zeros = (const char*)prm.g->zero_row;
    r.cut0 = strip == 0 ? 192 : 0;
    r.cut1 = strip == 7 ? 192 : 0;
    r.last = cta - 8 >= NUM_CTAS - 16 ? STEPS - 2 : STEPS - 1;
    return r;
}
__device__ __forceinline__ void issue_row_load(const RowCopy& r, int i, uint32_t slot) {
    const char* src = r.x0 + i * r.stride;
    const uint32_t bar = sb + SM_GO + i * 8, dst = sb + SM_X + slot * SLOT_BYTES;
    expect_tx(bar, XHALF_BYTES - r.cut0);
    bulk_load(dst + r.cut0, src + r.cut0, XHALF_BYTES - r.cut0, bar);
    expect_tx(bar, XHALF_BYTES - r.cut1);
    bulk_load(dst + XHALF_B, src + 32 * 192, XHALF_BYTES - r.cut1, bar);
}

__device__ __forceinline__ float quad_sum(float v) {
    v += __shfl_xor_sync(0xffffffffu, v, 1);
    v += __shfl_xor_sync(0xffffffffu, v, 2);
    return v;
}

__device__ __forceinline__ void load_x(uint32_t (&v)[6][6], const Producer& c, uint32_t row) {
#pragma unroll
    for (int k = 0; k < 6; k++) {
        asm volatile("ld.shared.v4.b32 {%0,%1,%2,%3}, [%4];"
                     : "=r"(v[k][0]), "=r"(v[k][1]), "=r"(v[k][2]), "=r"(v[k][3]) : "r"(row + c.xoff[0] + k * 192));
        asm volatile("ld.shared.v2.b32 {%0,%1}, [%2];" : "=r"(v[k][4]), "=r"(v[k][5]) : "r"(row + c.xoff[1] + k * 192));
    }
}
template <int DY, int STRIDE>
__device__ __forceinline__ void conv_row(uint32_t (&dst)[24], const uint32_t* src, const uint32_t (&v)[6][6], const Producer& c) {
#pragma unroll
    for (int o = 0; o < 4; o++)
#pragma unroll
        for (int u = 0; u < 6; u++)
            dst[o * 6 + u] = bf2_fma(v[o + 2][u], c.w[3 * DY + 2][u], bf2_fma(v[o + 1][u], c.w[3 * DY + 1][u],
                             bf2_fma(v[o][u], c.w[3 * DY][u], STRIDE ? src[o * 6 + u] : src[2 * o + 1])));
}
#define HAND_OVER(name, base, r) asm volatile("mov.b32 " name "%6, %0; mov.b32 " name "%7, %1; mov.b32 " name "%8, %2;\n" \
    "mov.b32 " name "%9, %3; mov.b32 " name "%10, %4; mov.b32 " name "%11, %5;" ::"r"((r)[0]), "r"((r)[1]), "r"((r)[2]), \
    "r"((r)[3]), "r"((r)[4]), "r"((r)[5]), "n"(base), "n"(base + 1), "n"(base + 2), "n"(base + 3), "n"(base + 4), "n"(base + 5))
template <int K> __device__ __forceinline__ void hand_over(const Producer& c, const uint32_t (&B)[24], const uint32_t (&C)[24],
                                                           const uint32_t (&v)[6][6]) {
    HAND_OVER("pw", K * 6, c.w[K]);
    if (K < 6) HAND_OVER("pv", K * 6, v[K % 6]);
    if (K < 4) { HAND_OVER("pb", K * 6, B + K % 4 * 6); HAND_OVER("pc", K * 6, C + K % 4 * 6); }
    if constexpr (K < 8) hand_over<K + 1>(c, B, C, v);
}
__device__ __forceinline__ void produce_tiles(const Producer& c, const Params& prm) {
    asm volatile(
        "{\n"
        ".reg .b32 pa<24>, pq<4>, m<6>, y<6>, rr, mm, t, so, ad, tt, cnt;\n"
        ".reg .b16 xl, xh;\n"
        ".reg .f32 d<4>, us, s0, s1, f0, f1, kq;\n"
        ".reg .pred pt, pf, pr, pw, pl, po, pe;\n"
        "setp.ne.b32 pt, 1, 0; setp.ne.b32 pf, 0, 0; setp.eq.u32 pl, %8, 0; and.b32 tt, %8, 1; setp.ne.u32 po, tt, 0;\n"
        "and.b32 tt, %8, 4; setp.ne.u32 pr, tt, 0; selp.f32 kq, 0f3F802D41, 0f3F7FA57E, pr;\n"
        "mov.u32 t, 0; mov.u32 so, 0;\n"
        "setp.eq.u32 pr, %12, 0;\n"
        "@pr bra.uni RARE;\n"
        "LOOP:\n"
        ASM_TRC("t")
        "fma.rn.bf16x2 pa0, pv0, pw36, pb0; fma.rn.bf16x2 pa1, pv1, pw37, pb1; fma.rn.bf16x2 pa2, pv2, pw38, pb2; fma.rn.bf16x2 pa3, pv3, pw39, pb3; fma.rn.bf16x2 pa4, pv4, pw40, pb4; fma.rn.bf16x2 pa5, pv5, pw41, pb5;\n"
        "fma.rn.bf16x2 pa6, pv6, pw36, pb6; fma.rn.bf16x2 pa7, pv7, pw37, pb7; fma.rn.bf16x2 pa8, pv8, pw38, pb8; fma.rn.bf16x2 pa9, pv9, pw39, pb9; fma.rn.bf16x2 pa10, pv10, pw40, pb10; fma.rn.bf16x2 pa11, pv11, pw41, pb11;\n"
        "fma.rn.bf16x2 pa12, pv12, pw36, pb12; fma.rn.bf16x2 pa13, pv13, pw37, pb13; fma.rn.bf16x2 pa14, pv14, pw38, pb14; fma.rn.bf16x2 pa15, pv15, pw39, pb15; fma.rn.bf16x2 pa16, pv16, pw40, pb16; fma.rn.bf16x2 pa17, pv17, pw41, pb17;\n"
        "fma.rn.bf16x2 pa18, pv18, pw36, pb18; fma.rn.bf16x2 pa19, pv19, pw37, pb19; fma.rn.bf16x2 pa20, pv20, pw38, pb20; fma.rn.bf16x2 pa21, pv21, pw39, pb21; fma.rn.bf16x2 pa22, pv22, pw40, pb22; fma.rn.bf16x2 pa23, pv23, pw41, pb23;\n"
        "fma.rn.bf16x2 pa0, pv6, pw42, pa0; fma.rn.bf16x2 pa1, pv7, pw43, pa1; fma.rn.bf16x2 pa2, pv8, pw44, pa2; fma.rn.bf16x2 pa3, pv9, pw45, pa3; fma.rn.bf16x2 pa4, pv10, pw46, pa4; fma.rn.bf16x2 pa5, pv11, pw47, pa5;\n"
        "fma.rn.bf16x2 pa6, pv12, pw42, pa6; fma.rn.bf16x2 pa7, pv13, pw43, pa7; fma.rn.bf16x2 pa8, pv14, pw44, pa8; fma.rn.bf16x2 pa9, pv15, pw45, pa9; fma.rn.bf16x2 pa10, pv16, pw46, pa10; fma.rn.bf16x2 pa11, pv17, pw47, pa11;\n"
        "fma.rn.bf16x2 pa12, pv18, pw42, pa12; fma.rn.bf16x2 pa13, pv19, pw43, pa13; fma.rn.bf16x2 pa14, pv20, pw44, pa14; fma.rn.bf16x2 pa15, pv21, pw45, pa15; fma.rn.bf16x2 pa16, pv22, pw46, pa16; fma.rn.bf16x2 pa17, pv23, pw47, pa17;\n"
        "fma.rn.bf16x2 pa18, pv24, pw42, pa18; fma.rn.bf16x2 pa19, pv25, pw43, pa19; fma.rn.bf16x2 pa20, pv26, pw44, pa20; fma.rn.bf16x2 pa21, pv27, pw45, pa21; fma.rn.bf16x2 pa22, pv28, pw46, pa22; fma.rn.bf16x2 pa23, pv29, pw47, pa23;\n"
        "fma.rn.bf16x2 pa0, pv12, pw48, pa0; fma.rn.bf16x2 pa1, pv13, pw49, pa1; fma.rn.bf16x2 pa2, pv14, pw50, pa2; fma.rn.bf16x2 pa3, pv15, pw51, pa3; fma.rn.bf16x2 pa4, pv16, pw52, pa4; fma.rn.bf16x2 pa5, pv17, pw53, pa5;\n"
        "fma.rn.bf16x2 pa6, pv18, pw48, pa6; fma.rn.bf16x2 pa7, pv19, pw49, pa7; fma.rn.bf16x2 pa8, pv20, pw50, pa8; fma.rn.bf16x2 pa9, pv21, pw51, pa9; fma.rn.bf16x2 pa10, pv22, pw52, pa10; fma.rn.bf16x2 pa11, pv23, pw53, pa11;\n"
        "fma.rn.bf16x2 pa12, pv24, pw48, pa12; fma.rn.bf16x2 pa13, pv25, pw49, pa13; fma.rn.bf16x2 pa14, pv26, pw50, pa14; fma.rn.bf16x2 pa15, pv27, pw51, pa15; fma.rn.bf16x2 pa16, pv28, pw52, pa16; fma.rn.bf16x2 pa17, pv29, pw53, pa17;\n"
        "fma.rn.bf16x2 pa18, pv30, pw48, pa18; fma.rn.bf16x2 pa19, pv31, pw49, pa19; fma.rn.bf16x2 pa20, pv32, pw50, pa20; fma.rn.bf16x2 pa21, pv33, pw51, pa21; fma.rn.bf16x2 pa22, pv34, pw52, pa22; fma.rn.bf16x2 pa23, pv35, pw53, pa23;\n"
        "mul.rn.bf16x2 pq0, pa0, pa0; fma.rn.bf16x2 pq0, pa1, pa1, pq0; fma.rn.bf16x2 pq0, pa2, pa2, pq0; fma.rn.bf16x2 pq0, pa3, pa3, pq0; fma.rn.bf16x2 pq0, pa4, pa4, pq0; fma.rn.bf16x2 pq0, pa5, pa5, pq0;\n"
        "mul.rn.bf16x2 pq1, pa6, pa6; fma.rn.bf16x2 pq1, pa7, pa7, pq1; fma.rn.bf16x2 pq1, pa8, pa8, pq1; fma.rn.bf16x2 pq1, pa9, pa9, pq1; fma.rn.bf16x2 pq1, pa10, pa10, pq1; fma.rn.bf16x2 pq1, pa11, pa11, pq1;\n"
        "mul.rn.bf16x2 pq2, pa12, pa12; fma.rn.bf16x2 pq2, pa13, pa13, pq2; fma.rn.bf16x2 pq2, pa14, pa14, pq2; fma.rn.bf16x2 pq2, pa15, pa15, pq2; fma.rn.bf16x2 pq2, pa16, pa16, pq2; fma.rn.bf16x2 pq2, pa17, pa17, pq2;\n"
        "mul.rn.bf16x2 pq3, pa18, pa18; fma.rn.bf16x2 pq3, pa19, pa19, pq3; fma.rn.bf16x2 pq3, pa20, pa20, pq3; fma.rn.bf16x2 pq3, pa21, pa21, pq3; fma.rn.bf16x2 pq3, pa22, pa22, pq3; fma.rn.bf16x2 pq3, pa23, pa23, pq3;\n"
        "B0:\n"
        "wgmma.fence.sync.aligned;\n"
        "wgmma.mma_async.sync.aligned.m64n8k16.f32.bf16.bf16 {d0,d1,d2,d3}, {pa0,pa6,pa1,pa7}, %9, pf, 1, 1, 0;\n"
        "wgmma.mma_async.sync.aligned.m64n8k16.f32.bf16.bf16 {d0,d1,d2,d3}, {pa2,pa8,pa3,pa9}, %9, pt, 1, 1, 0;\n"
        "wgmma.mma_async.sync.aligned.m64n8k16.f32.bf16.bf16 {d0,d1,d2,d3}, {pa4,pa10,pa5,pa11}, %9, pt, 1, 1, 0;\n"
        "wgmma.mma_async.sync.aligned.m64n8k16.f32.bf16.bf16 {d0,d1,d2,d3}, {pa12,pa18,pa13,pa19}, %10, pt, 1, 1, 0;\n"
        "wgmma.mma_async.sync.aligned.m64n8k16.f32.bf16.bf16 {d0,d1,d2,d3}, {pa14,pa20,pa15,pa21}, %10, pt, 1, 1, 0;\n"
        "wgmma.mma_async.sync.aligned.m64n8k16.f32.bf16.bf16 {d0,d1,d2,d3}, {pa16,pa22,pa17,pa23}, %10, pt, 1, 1, 0;\n"
        "wgmma.mma_async.sync.aligned.m64n8k16.f32.bf16.bf16 {d0,d1,d2,d3}, {pq0,pq1,pq2,pq3}, %11, pt, 1, 1, 0;\n"
        "wgmma.commit_group.sync.aligned;\n"
        "fence.proxy.async.shared::cta;\n"
        "@pl mbarrier.arrive.shared::cta.b64 _, [t+231544];\n"
        "add.u32 ad, %7, so; ld.shared.f32 us, [ad+4];\n"
        "fma.rn.bf16x2 pb0, pv0, pw18, pc0; fma.rn.bf16x2 pb1, pv1, pw19, pc1; fma.rn.bf16x2 pb2, pv2, pw20, pc2; fma.rn.bf16x2 pb3, pv3, pw21, pc3; fma.rn.bf16x2 pb4, pv4, pw22, pc4; fma.rn.bf16x2 pb5, pv5, pw23, pc5;\n"
        "fma.rn.bf16x2 pb6, pv6, pw18, pc6; fma.rn.bf16x2 pb7, pv7, pw19, pc7; fma.rn.bf16x2 pb8, pv8, pw20, pc8; fma.rn.bf16x2 pb9, pv9, pw21, pc9; fma.rn.bf16x2 pb10, pv10, pw22, pc10; fma.rn.bf16x2 pb11, pv11, pw23, pc11;\n"
        "fma.rn.bf16x2 pb0, pv6, pw24, pb0; fma.rn.bf16x2 pb1, pv7, pw25, pb1; fma.rn.bf16x2 pb2, pv8, pw26, pb2; fma.rn.bf16x2 pb3, pv9, pw27, pb3; fma.rn.bf16x2 pb4, pv10, pw28, pb4; fma.rn.bf16x2 pb5, pv11, pw29, pb5;\n"
        "fma.rn.bf16x2 pb6, pv12, pw24, pb6; fma.rn.bf16x2 pb7, pv13, pw25, pb7; fma.rn.bf16x2 pb8, pv14, pw26, pb8; fma.rn.bf16x2 pb9, pv15, pw27, pb9; fma.rn.bf16x2 pb10, pv16, pw28, pb10; fma.rn.bf16x2 pb11, pv17, pw29, pb11;\n"
        "fma.rn.bf16x2 pb0, pv12, pw30, pb0; fma.rn.bf16x2 pb1, pv13, pw31, pb1; fma.rn.bf16x2 pb2, pv14, pw32, pb2; fma.rn.bf16x2 pb3, pv15, pw33, pb3; fma.rn.bf16x2 pb4, pv16, pw34, pb4; fma.rn.bf16x2 pb5, pv17, pw35, pb5;\n"
        "fma.rn.bf16x2 pb6, pv18, pw30, pb6; fma.rn.bf16x2 pb7, pv19, pw31, pb7; fma.rn.bf16x2 pb8, pv20, pw32, pb8; fma.rn.bf16x2 pb9, pv21, pw33, pb9; fma.rn.bf16x2 pb10, pv22, pw34, pb10; fma.rn.bf16x2 pb11, pv23, pw35, pb11;\n"
        "B1:\n"
        "fma.rn.bf16x2 pb12, pv12, pw18, pc12; fma.rn.bf16x2 pb13, pv13, pw19, pc13; fma.rn.bf16x2 pb14, pv14, pw20, pc14; fma.rn.bf16x2 pb15, pv15, pw21, pc15; fma.rn.bf16x2 pb16, pv16, pw22, pc16; fma.rn.bf16x2 pb17, pv17, pw23, pc17;\n"
        "fma.rn.bf16x2 pb18, pv18, pw18, pc18; fma.rn.bf16x2 pb19, pv19, pw19, pc19; fma.rn.bf16x2 pb20, pv20, pw20, pc20; fma.rn.bf16x2 pb21, pv21, pw21, pc21; fma.rn.bf16x2 pb22, pv22, pw22, pc22; fma.rn.bf16x2 pb23, pv23, pw23, pc23;\n"
        "fma.rn.bf16x2 pb12, pv18, pw24, pb12; fma.rn.bf16x2 pb13, pv19, pw25, pb13; fma.rn.bf16x2 pb14, pv20, pw26, pb14; fma.rn.bf16x2 pb15, pv21, pw27, pb15; fma.rn.bf16x2 pb16, pv22, pw28, pb16; fma.rn.bf16x2 pb17, pv23, pw29, pb17;\n"
        "fma.rn.bf16x2 pb18, pv24, pw24, pb18; fma.rn.bf16x2 pb19, pv25, pw25, pb19; fma.rn.bf16x2 pb20, pv26, pw26, pb20; fma.rn.bf16x2 pb21, pv27, pw27, pb21; fma.rn.bf16x2 pb22, pv28, pw28, pb22; fma.rn.bf16x2 pb23, pv29, pw29, pb23;\n"
        "fma.rn.bf16x2 pb12, pv24, pw30, pb12; fma.rn.bf16x2 pb13, pv25, pw31, pb13; fma.rn.bf16x2 pb14, pv26, pw32, pb14; fma.rn.bf16x2 pb15, pv27, pw33, pb15; fma.rn.bf16x2 pb16, pv28, pw34, pb16; fma.rn.bf16x2 pb17, pv29, pw35, pb17;\n"
        "fma.rn.bf16x2 pb18, pv30, pw30, pb18; fma.rn.bf16x2 pb19, pv31, pw31, pb19; fma.rn.bf16x2 pb20, pv32, pw32, pb20; fma.rn.bf16x2 pb21, pv33, pw33, pb21; fma.rn.bf16x2 pb22, pv34, pw34, pb22; fma.rn.bf16x2 pb23, pv35, pw35, pb23;\n"
        "C0:\n"
        "wgmma.wait_group.sync.aligned 0;\n"
        "selp.f32 s0, d2, d0, po; selp.f32 s1, d3, d1, po;\n"
        "shfl.sync.bfly.b32 f0, s0, 4, 0x1f, 0xffffffff; shfl.sync.bfly.b32 f1, s1, 4, 0x1f, 0xffffffff;\n"
        "fma.rn.bf16x2 pc0, pv0, pw0, ps1; fma.rn.bf16x2 pc1, pv1, pw1, ps1; fma.rn.bf16x2 pc2, pv2, pw2, ps1; fma.rn.bf16x2 pc3, pv3, pw3, ps1; fma.rn.bf16x2 pc4, pv4, pw4, ps1; fma.rn.bf16x2 pc5, pv5, pw5, ps1;\n"
        "fma.rn.bf16x2 pc6, pv6, pw0, ps3; fma.rn.bf16x2 pc7, pv7, pw1, ps3; fma.rn.bf16x2 pc8, pv8, pw2, ps3; fma.rn.bf16x2 pc9, pv9, pw3, ps3; fma.rn.bf16x2 pc10, pv10, pw4, ps3; fma.rn.bf16x2 pc11, pv11, pw5, ps3;\n"
        "fma.rn.bf16x2 pc12, pv12, pw0, ps5; fma.rn.bf16x2 pc13, pv13, pw1, ps5; fma.rn.bf16x2 pc14, pv14, pw2, ps5; fma.rn.bf16x2 pc15, pv15, pw3, ps5; fma.rn.bf16x2 pc16, pv16, pw4, ps5; fma.rn.bf16x2 pc17, pv17, pw5, ps5;\n"
        "fma.rn.bf16x2 pc18, pv18, pw0, ps7; fma.rn.bf16x2 pc19, pv19, pw1, ps7; fma.rn.bf16x2 pc20, pv20, pw2, ps7; fma.rn.bf16x2 pc21, pv21, pw3, ps7; fma.rn.bf16x2 pc22, pv22, pw4, ps7; fma.rn.bf16x2 pc23, pv23, pw5, ps7;\n"
        "fma.rn.bf16x2 pc0, pv6, pw6, pc0; fma.rn.bf16x2 pc1, pv7, pw7, pc1; fma.rn.bf16x2 pc2, pv8, pw8, pc2; fma.rn.bf16x2 pc3, pv9, pw9, pc3; fma.rn.bf16x2 pc4, pv10, pw10, pc4; fma.rn.bf16x2 pc5, pv11, pw11, pc5;\n"
        "fma.rn.bf16x2 pc6, pv12, pw6, pc6; fma.rn.bf16x2 pc7, pv13, pw7, pc7; fma.rn.bf16x2 pc8, pv14, pw8, pc8; fma.rn.bf16x2 pc9, pv15, pw9, pc9; fma.rn.bf16x2 pc10, pv16, pw10, pc10; fma.rn.bf16x2 pc11, pv17, pw11, pc11;\n"
        "fma.rn.bf16x2 pc12, pv18, pw6, pc12; fma.rn.bf16x2 pc13, pv19, pw7, pc13; fma.rn.bf16x2 pc14, pv20, pw8, pc14; fma.rn.bf16x2 pc15, pv21, pw9, pc15; fma.rn.bf16x2 pc16, pv22, pw10, pc16; fma.rn.bf16x2 pc17, pv23, pw11, pc17;\n"
        "fma.rn.bf16x2 pc18, pv24, pw6, pc18; fma.rn.bf16x2 pc19, pv25, pw7, pc19; fma.rn.bf16x2 pc20, pv26, pw8, pc20; fma.rn.bf16x2 pc21, pv27, pw9, pc21; fma.rn.bf16x2 pc22, pv28, pw10, pc22; fma.rn.bf16x2 pc23, pv29, pw11, pc23;\n"
        "fma.rn.bf16x2 pc0, pv12, pw12, pc0; fma.rn.bf16x2 pc1, pv13, pw13, pc1; fma.rn.bf16x2 pc2, pv14, pw14, pc2; fma.rn.bf16x2 pc3, pv15, pw15, pc3; fma.rn.bf16x2 pc4, pv16, pw16, pc4; fma.rn.bf16x2 pc5, pv17, pw17, pc5;\n"
        "fma.rn.bf16x2 pc6, pv18, pw12, pc6; fma.rn.bf16x2 pc7, pv19, pw13, pc7; fma.rn.bf16x2 pc8, pv20, pw14, pc8; fma.rn.bf16x2 pc9, pv21, pw15, pc9; fma.rn.bf16x2 pc10, pv22, pw16, pc10; fma.rn.bf16x2 pc11, pv23, pw17, pc11;\n"
        "fma.rn.bf16x2 pc12, pv24, pw12, pc12; fma.rn.bf16x2 pc13, pv25, pw13, pc13; fma.rn.bf16x2 pc14, pv26, pw14, pc14; fma.rn.bf16x2 pc15, pv27, pw15, pc15; fma.rn.bf16x2 pc16, pv28, pw16, pc16; fma.rn.bf16x2 pc17, pv29, pw17, pc17;\n"
        "fma.rn.bf16x2 pc18, pv30, pw12, pc18; fma.rn.bf16x2 pc19, pv31, pw13, pc19; fma.rn.bf16x2 pc20, pv32, pw14, pc20; fma.rn.bf16x2 pc21, pv33, pw15, pc21; fma.rn.bf16x2 pc22, pv34, pw16, pc22; fma.rn.bf16x2 pc23, pv35, pw17, pc23;\n"
        "add.f32 s0, s0, f0; add.f32 s1, s1, f1; mul.f32 s0, s0, 0fBC2AAAAB;\n"
        "neg.f32 f0, s0; fma.rn.f32 f0, f0, s0, %13; fma.rn.f32 f0, s1, 0f3C2AAAAB, f0; max.f32 f0, f0, %13;\n"
        "rsqrt.approx.ftz.f32 f0, f0; mul.f32 f0, f0, %14; cvt.rn.bf16x2.f32 tt, f0, 0f00000000; mov.b32 f0, tt;\n"
        "mul.f32 f1, s0, kq; mul.f32 f1, f1, f0; cvt.rn.bf16x2.f32 tt, f1, f0; add.f32 us, us, s0; cvt.rn.bf16x2.f32 mm, us, us;\n"
        "add.u32 ad, %7, so; st.shared.v2.b32 [ad], {tt, mm};\n"
        "add.u32 ad, %6, so; ld.shared.v4.b32 {ps0,ps1,ps2,ps3}, [ad]; ld.shared.v4.b32 {ps4,ps5,ps6,ps7}, [ad+16];\n"
        "mbarrier.try_wait.parity.shared::cta.b64 pw, [t+231264], 0;\n"
        "N0:\n"
        "@!pw bra.uni SPIN;\n"
        "BACK:\n"
        "add.u32 ad, %0, so; ld.shared.v4.b32 {pv0,pv1,pv2,pv3}, [ad+0];\n"
        "add.u32 ad, %1, so; ld.shared.v2.b32 {pv4,pv5}, [ad+0];\n"
        "add.u32 ad, %0, so; ld.shared.v4.b32 {pv6,pv7,pv8,pv9}, [ad+192];\n"
        "add.u32 ad, %1, so; ld.shared.v2.b32 {pv10,pv11}, [ad+192];\n"
        "mov.b32 {xl, xh}, ps0; mov.b32 rr, {xl, xl}; mov.b32 mm, {xh, xh}; fma.rn.bf16x2 pa0, pa0, rr, mm; fma.rn.bf16x2 pa1, pa1, rr, mm; fma.rn.bf16x2 pa2, pa2, rr, mm; fma.rn.bf16x2 pa3, pa3, rr, mm; fma.rn.bf16x2 pa4, pa4, rr, mm; fma.rn.bf16x2 pa5, pa5, rr, mm;\n"
        "and.b32 m0, pa0, 0x7fff7fff; and.b32 m1, pa1, 0x7fff7fff; and.b32 m2, pa2, 0x7fff7fff; and.b32 m3, pa3, 0x7fff7fff; and.b32 m4, pa4, 0x7fff7fff; and.b32 m5, pa5, 0x7fff7fff;\n"
        "mad.lo.u32 y0, m0, 7, pa0; mad.lo.u32 y1, m1, 7, pa1; mad.lo.u32 y2, m2, 7, pa2; mad.lo.u32 y3, m3, 7, pa3; mad.lo.u32 y4, m4, 7, pa4; mad.lo.u32 y5, m5, 7, pa5;\n"
        "add.u32 ad, %2, so; st.shared.v4.b32 [ad+0], {y0,y1,y2,y3};\n"
        "add.u32 ad, %4, so; st.shared.v2.b32 [ad+0], {y4,y5};\n"
        "N1:\n"
        "add.u32 ad, %0, so; ld.shared.v4.b32 {pv12,pv13,pv14,pv15}, [ad+384];\n"
        "add.u32 ad, %1, so; ld.shared.v2.b32 {pv16,pv17}, [ad+384];\n"
        "add.u32 ad, %0, so; ld.shared.v4.b32 {pv18,pv19,pv20,pv21}, [ad+576];\n"
        "add.u32 ad, %1, so; ld.shared.v2.b32 {pv22,pv23}, [ad+576];\n"
        "mov.b32 {xl, xh}, ps2; mov.b32 rr, {xl, xl}; mov.b32 mm, {xh, xh}; fma.rn.bf16x2 pa6, pa6, rr, mm; fma.rn.bf16x2 pa7, pa7, rr, mm; fma.rn.bf16x2 pa8, pa8, rr, mm; fma.rn.bf16x2 pa9, pa9, rr, mm; fma.rn.bf16x2 pa10, pa10, rr, mm; fma.rn.bf16x2 pa11, pa11, rr, mm;\n"
        "and.b32 m0, pa6, 0x7fff7fff; and.b32 m1, pa7, 0x7fff7fff; and.b32 m2, pa8, 0x7fff7fff; and.b32 m3, pa9, 0x7fff7fff; and.b32 m4, pa10, 0x7fff7fff; and.b32 m5, pa11, 0x7fff7fff;\n"
        "mad.lo.u32 y0, m0, 7, pa6; mad.lo.u32 y1, m1, 7, pa7; mad.lo.u32 y2, m2, 7, pa8; mad.lo.u32 y3, m3, 7, pa9; mad.lo.u32 y4, m4, 7, pa10; mad.lo.u32 y5, m5, 7, pa11;\n"
        "add.u32 ad, %3, so; st.shared.v4.b32 [ad+0], {y0,y1,y2,y3};\n"
        "add.u32 ad, %5, so; st.shared.v2.b32 [ad+0], {y4,y5};\n"
        "N2:\n"
        "add.u32 ad, %0, so; ld.shared.v4.b32 {pv24,pv25,pv26,pv27}, [ad+768];\n"
        "add.u32 ad, %1, so; ld.shared.v2.b32 {pv28,pv29}, [ad+768];\n"
        "mov.b32 {xl, xh}, ps4; mov.b32 rr, {xl, xl}; mov.b32 mm, {xh, xh}; fma.rn.bf16x2 pa12, pa12, rr, mm; fma.rn.bf16x2 pa13, pa13, rr, mm; fma.rn.bf16x2 pa14, pa14, rr, mm; fma.rn.bf16x2 pa15, pa15, rr, mm; fma.rn.bf16x2 pa16, pa16, rr, mm; fma.rn.bf16x2 pa17, pa17, rr, mm;\n"
        "and.b32 m0, pa12, 0x7fff7fff; and.b32 m1, pa13, 0x7fff7fff; and.b32 m2, pa14, 0x7fff7fff; and.b32 m3, pa15, 0x7fff7fff; and.b32 m4, pa16, 0x7fff7fff; and.b32 m5, pa17, 0x7fff7fff;\n"
        "mad.lo.u32 y0, m0, 7, pa12; mad.lo.u32 y1, m1, 7, pa13; mad.lo.u32 y2, m2, 7, pa14; mad.lo.u32 y3, m3, 7, pa15; mad.lo.u32 y4, m4, 7, pa16; mad.lo.u32 y5, m5, 7, pa17;\n"
        "add.u32 ad, %2, so; st.shared.v4.b32 [ad+2048], {y0,y1,y2,y3};\n"
        "add.u32 ad, %4, so; st.shared.v2.b32 [ad+1024], {y4,y5};\n"
        "N3:\n"
        "add.u32 ad, %0, so; ld.shared.v4.b32 {pv30,pv31,pv32,pv33}, [ad+960];\n"
        "add.u32 ad, %1, so; ld.shared.v2.b32 {pv34,pv35}, [ad+960];\n"
        "mov.b32 {xl, xh}, ps6; mov.b32 rr, {xl, xl}; mov.b32 mm, {xh, xh}; fma.rn.bf16x2 pa18, pa18, rr, mm; fma.rn.bf16x2 pa19, pa19, rr, mm; fma.rn.bf16x2 pa20, pa20, rr, mm; fma.rn.bf16x2 pa21, pa21, rr, mm; fma.rn.bf16x2 pa22, pa22, rr, mm; fma.rn.bf16x2 pa23, pa23, rr, mm;\n"
        "and.b32 m0, pa18, 0x7fff7fff; and.b32 m1, pa19, 0x7fff7fff; and.b32 m2, pa20, 0x7fff7fff; and.b32 m3, pa21, 0x7fff7fff; and.b32 m4, pa22, 0x7fff7fff; and.b32 m5, pa23, 0x7fff7fff;\n"
        "mad.lo.u32 y0, m0, 7, pa18; mad.lo.u32 y1, m1, 7, pa19; mad.lo.u32 y2, m2, 7, pa20; mad.lo.u32 y3, m3, 7, pa21; mad.lo.u32 y4, m4, 7, pa22; mad.lo.u32 y5, m5, 7, pa23;\n"
        "add.u32 ad, %3, so; st.shared.v4.b32 [ad+2048], {y0,y1,y2,y3};\n"
        "add.u32 ad, %5, so; st.shared.v2.b32 [ad+1024], {y4,y5};\n"
        "add.u32 so, so, 26624; setp.eq.u32 pr, so, 79872; selp.u32 so, 0, so, pr;\n"
        "add.u32 t, t, 8; setp.lt.u32 pe, t, 256;\n"
        "@pe bra.uni LOOP;\n"
        "bra.uni DONE;\n"
        "SPIN: mov.u32 cnt, 0;\n"
        "SPINL:\n"
        "mbarrier.try_wait.parity.shared::cta.b64 pw, [t+231264], 0;\n"
        "@pw bra.uni BACK;\n"
        "add.u32 cnt, cnt, 1; setp.lt.u32 pw, cnt, 0x100000;\n"
        "@pw bra.uni SPINL;\n"
        "trap;\n"
        "RARE:\n"
        "ld.volatile.shared.u32 tt, [%6];\n"
        "mov.b32 pa0, tt; mov.b32 pa1, tt; mov.b32 pa2, tt; mov.b32 pa3, tt; mov.b32 pa4, tt; mov.b32 pa5, tt; mov.b32 pa6, tt; mov.b32 pa7, tt; mov.b32 pa8, tt; mov.b32 pa9, tt; mov.b32 pa10, tt; mov.b32 pa11, tt;\n"
        "mov.b32 pa12, tt; mov.b32 pa13, tt; mov.b32 pa14, tt; mov.b32 pa15, tt; mov.b32 pa16, tt; mov.b32 pa17, tt; mov.b32 pa18, tt; mov.b32 pa19, tt; mov.b32 pa20, tt; mov.b32 pa21, tt; mov.b32 pa22, tt; mov.b32 pa23, tt;\n"
        "mov.b32 pb0, tt; mov.b32 pb1, tt; mov.b32 pb2, tt; mov.b32 pb3, tt; mov.b32 pb4, tt; mov.b32 pb5, tt; mov.b32 pb6, tt; mov.b32 pb7, tt; mov.b32 pb8, tt; mov.b32 pb9, tt; mov.b32 pb10, tt; mov.b32 pb11, tt;\n"
        "mov.b32 pb12, tt; mov.b32 pb13, tt; mov.b32 pb14, tt; mov.b32 pb15, tt; mov.b32 pb16, tt; mov.b32 pb17, tt; mov.b32 pb18, tt; mov.b32 pb19, tt; mov.b32 pb20, tt; mov.b32 pb21, tt; mov.b32 pb22, tt; mov.b32 pb23, tt;\n"
        "mov.b32 pc0, tt; mov.b32 pc1, tt; mov.b32 pc2, tt; mov.b32 pc3, tt; mov.b32 pc4, tt; mov.b32 pc5, tt; mov.b32 pc6, tt; mov.b32 pc7, tt; mov.b32 pc8, tt; mov.b32 pc9, tt; mov.b32 pc10, tt; mov.b32 pc11, tt;\n"
        "mov.b32 pc12, tt; mov.b32 pc13, tt; mov.b32 pc14, tt; mov.b32 pc15, tt; mov.b32 pc16, tt; mov.b32 pc17, tt; mov.b32 pc18, tt; mov.b32 pc19, tt; mov.b32 pc20, tt; mov.b32 pc21, tt; mov.b32 pc22, tt; mov.b32 pc23, tt;\n"
        "mov.b32 ps0, tt; mov.b32 ps1, tt; mov.b32 ps2, tt; mov.b32 ps3, tt; mov.b32 ps4, tt; mov.b32 ps5, tt; mov.b32 ps6, tt; mov.b32 ps7, tt; mov.b32 pq0, tt; mov.b32 pq1, tt; mov.b32 pq2, tt; mov.b32 pq3, tt;\n"
        "ld.volatile.shared.v2.b32 {pw1, pw0}, [%6]; xor.b32 tt, tt, pw1;\n"
        "ld.volatile.shared.v2.b32 {pw3, pw2}, [%6]; xor.b32 tt, tt, pw3;\n"
        "ld.volatile.shared.v2.b32 {pw5, pw4}, [%6]; xor.b32 tt, tt, pw5;\n"
        "ld.volatile.shared.v2.b32 {pw7, pw6}, [%6]; xor.b32 tt, tt, pw7;\n"
        "ld.volatile.shared.v2.b32 {pw9, pw8}, [%6]; xor.b32 tt, tt, pw9;\n"
        "ld.volatile.shared.v2.b32 {pw11, pw10}, [%6]; xor.b32 tt, tt, pw11;\n"
        "ld.volatile.shared.v2.b32 {pw13, pw12}, [%6]; xor.b32 tt, tt, pw13;\n"
        "ld.volatile.shared.v2.b32 {pw15, pw14}, [%6]; xor.b32 tt, tt, pw15;\n"
        "ld.volatile.shared.v2.b32 {pw17, pw16}, [%6]; xor.b32 tt, tt, pw17;\n"
        "ld.volatile.shared.v2.b32 {pw19, pw18}, [%6]; xor.b32 tt, tt, pw19;\n"
        "ld.volatile.shared.v2.b32 {pw21, pw20}, [%6]; xor.b32 tt, tt, pw21;\n"
        "ld.volatile.shared.v2.b32 {pw23, pw22}, [%6]; xor.b32 tt, tt, pw23;\n"
        "ld.volatile.shared.v2.b32 {pw25, pw24}, [%6]; xor.b32 tt, tt, pw25;\n"
        "ld.volatile.shared.v2.b32 {pw27, pw26}, [%6]; xor.b32 tt, tt, pw27;\n"
        "ld.volatile.shared.v2.b32 {pw29, pw28}, [%6]; xor.b32 tt, tt, pw29;\n"
        "ld.volatile.shared.v2.b32 {pw31, pw30}, [%6]; xor.b32 tt, tt, pw31;\n"
        "ld.volatile.shared.v2.b32 {pw33, pw32}, [%6]; xor.b32 tt, tt, pw33;\n"
        "ld.volatile.shared.v2.b32 {pw35, pw34}, [%6]; xor.b32 tt, tt, pw35;\n"
        "ld.volatile.shared.v2.b32 {pw37, pw36}, [%6]; xor.b32 tt, tt, pw37;\n"
        "ld.volatile.shared.v2.b32 {pw39, pw38}, [%6]; xor.b32 tt, tt, pw39;\n"
        "ld.volatile.shared.v2.b32 {pw41, pw40}, [%6]; xor.b32 tt, tt, pw41;\n"
        "ld.volatile.shared.v2.b32 {pw43, pw42}, [%6]; xor.b32 tt, tt, pw43;\n"
        "ld.volatile.shared.v2.b32 {pw45, pw44}, [%6]; xor.b32 tt, tt, pw45;\n"
        "ld.volatile.shared.v2.b32 {pw47, pw46}, [%6]; xor.b32 tt, tt, pw47;\n"
        "ld.volatile.shared.v2.b32 {pw49, pw48}, [%6]; xor.b32 tt, tt, pw49;\n"
        "ld.volatile.shared.v2.b32 {pw51, pw50}, [%6]; xor.b32 tt, tt, pw51;\n"
        "ld.volatile.shared.v2.b32 {pw53, pw52}, [%6]; xor.b32 tt, tt, pw53;\n"
        "mov.b32 us, tt; setp.ne.u32 pw, %15, 7;\n"
        "wgmma.fence.sync.aligned;\n"
        "setp.eq.u32 pr, %15, 1000; @pr bra.uni B0;\n"
        "setp.eq.u32 pr, %15, 1001; @pr bra.uni B1;\n"
        "setp.eq.u32 pr, %15, 1002; @pr bra.uni C0;\n"
        "setp.eq.u32 pr, %15, 1003; @pr bra.uni N0;\n"
        "setp.eq.u32 pr, %15, 1004; @pr bra.uni N1;\n"
        "setp.eq.u32 pr, %15, 1005; @pr bra.uni N2;\n"
        "setp.eq.u32 pr, %15, 1006; @pr bra.uni N3;\n"
        "trap;\n"
        "DONE:\n"
        ASM_TRC("t")
        "fence.proxy.async.shared::cta;\n"
        "@pl mbarrier.arrive.shared::cta.b64 _, [t+231544];\n"
        "}\n"
        :: "r"(sb + SM_X + c.xoff[0]), "r"(sb + SM_X + c.xoff[1]), "r"(sb + SM_Y1 + c.yoff[0][0]), "r"(sb + SM_Y1 + c.yoff[0][1]),
           "r"(sb + SM_Y1 + c.yoff[1][0]), "r"(sb + SM_Y1 + c.yoff[1][1]), "r"(c.stat), "r"(c.own), "r"(c.lane),
           "l"(prm.sel[0]), "l"(prm.sel[1]), "l"(prm.sel[2]), "r"(prm.ydesc), "f"(LN_EPS_SCALED), "f"(RSTD_SCALE), "r"(prm.w1desc)
        : "memory");
}

__device__ __forceinline__ void produce(const Producer& c, const Params& prm) {
    uint32_t B[24], C[24];
    uint32_t st[8];
    uint32_t v[6][6];
    uint32_t ws[6];
#pragma unroll
    for (int u = 0; u < 6; u++) {
        ws[u] = c.w[0][u];
#pragma unroll
        for (int t = 1; t < 9; t++) ws[u] = bf2_add(ws[u], c.w[t][u]);
    }
    SMARK(2);
#pragma unroll 1
    for (int i = loop_init<0>();; i++) {
        mbar_wait_c<0>(sb + SM_GO + i * 8);
        SMARK(4 + i);
        load_x(v, c, sb + SM_X + i * SLOT_BYTES);
        fence_async_smem();
        asm volatile("bar.arrive %0, 160;" ::"r"(6 + i) : "memory");
        if (i == 2) break;
        if (i == 0) {
            const uint32_t p = bf2_add(bf2_fma(v[2][2], ws[2], bf2_fma(v[2][1], ws[1], bf2_mul(v[2][0], ws[0]))),
                                       bf2_fma(v[2][5], ws[5], bf2_fma(v[2][4], ws[4], bf2_mul(v[2][3], ws[3]))));
            float e = quad_sum(bf_lo(p) + bf_hi(p));
            e = (e + __shfl_xor_sync(0xffffffffu, e, 4)) * (-1.0f / CH);
            st[1] = st[3] = st[5] = st[7] = pack_bf2(e, e);
#pragma unroll
            for (int k = 0; k < NX; k++) sts32(c.own + k * SLOT_BYTES + 4, st[1]);
        } else {
            conv_row<1, 1>(B, C, v, c);
        }
        conv_row<0, 0>(C, st, v, c);
    }
    asm volatile(".reg .b32 pw<54>, pb<24>, pc<24>, pv<36>, ps<8>;");
    hand_over<0>(c, B, C, v);
    asm volatile("mov.b32 ps1, %0; mov.b32 ps3, %1; mov.b32 ps5, %2; mov.b32 ps7, %3;" ::"r"(st[1]), "r"(st[3]), "r"(st[5]), "r"(st[7]));
    SMARK(7);
    produce_tiles(c, prm);
    mbar_arrive_if(sb + SM_YFULL + ROWS_PER_CTA * 8, c.lane == 0);
}

struct Duty {
    const char* g;
    const char* zeros;
    long long step;
    uint32_t s, bytes;
    int end, zero;
};
__device__ __forceinline__ Duty make_duty(const Params& prm, int wg, int w) {
    const RowCopy rc = row_copy(prm);
    Duty d;
    d.g = (w == 2 ? rc.y0 : rc.x0 + (w == 0 ? rc.cut0 : w == 1 ? 32 * 192 : 192)) +
          (wg + (w == 2 ? 0 : w < 2 ? 2 * NX : 2 * NX + L2_AHEAD)) * rc.stride;
    d.step = NX * rc.stride;
    d.s = wg * SLOT_BYTES + (w == 2 ? sb + SM_Y1 : sb + SM_X + (w == 0 ? rc.cut0 : XHALF_B));
    d.bytes = w >= 2 ? TILE_BYTES : XHALF_BYTES - (w == 0 ? rc.cut0 : rc.cut1);
    d.end = w == 2 ? ROWS_PER_CTA : w < 2 ? STEPS + 1 - 2 * NX : rc.last + 1 - 2 * NX - L2_AHEAD;
    d.zero = rc.last + 1 - 2 * NX;
    d.zeros = rc.zeros;
    return d;
}

static_assert(sb + SM_BAR == 230800 && sb + SM_YFULL == 231552 && sb + SM_GO == 231240 && SLOT_BYTES == 26624 && sb + SM_GAMMA == 229248 &&
              SM_BETA == SM_GAMMA + 768 && SM_W2 == 73728 && sb + SM_BUF3 == 187392 && BAR_W2 == 9 && BAR_W1B == 10, "layout");
__device__ __forceinline__ void consume(float (&acc)[2][2], uint32_t w1t, uint32_t yd, uint32_t wd, uint32_t own_slot, const Duty& d,
                                        uint32_t role, uint32_t lane, const Params& prm) {
    asm volatile(
        "{\n"
        ".reg .b32 z<32>, w<44>, p, a<4>, lo<2>, hi<2>, t, g, q<4>, dl, dh, n, so, c, tt, cnt, f0, f1;\n"
        ".reg .b16 xl, xh, xr;\n"
        ".reg .b64 ds<6>, wd, gp, src;\n"
        ".reg .pred pt, pf, pr, pw, pl, pe;\n"
        "setp.ne.b32 pt, 1, 0; setp.ne.b32 pf, 0, 0; setp.eq.u32 pl, %15, 0;\n"
        "mov.b32 c, 0x40D940D9;\n"
        "ldmatrix.sync.aligned.m8n8.x4.trans.shared.b16 {w0,w1,w2,w3}, [%4+0];\n"
        "ldmatrix.sync.aligned.m8n8.x4.trans.shared.b16 {w4,w5,w6,w7}, [%4+2048];\n"
        "ldmatrix.sync.aligned.m8n8.x4.trans.shared.b16 {w8,w9,w10,w11}, [%4+4096];\n"
        "ldmatrix.sync.aligned.m8n8.x4.trans.shared.b16 {w12,w13,w14,w15}, [%4+6144];\n"
        "ldmatrix.sync.aligned.m8n8.x4.trans.shared.b16 {w16,w17,w18,w19}, [%4+8192];\n"
        "ldmatrix.sync.aligned.m8n8.x4.trans.shared.b16 {w20,w21,w22,w23}, [%4+10240];\n"
        "shl.b32 f0, w0, 16; and.b32 f1, w0, 0xffff0000; cvt.rn.f16x2.f32 w0, f1, f0; shl.b32 f0, w1, 16; and.b32 f1, w1, 0xffff0000; cvt.rn.f16x2.f32 w1, f1, f0; shl.b32 f0, w2, 16; and.b32 f1, w2, 0xffff0000; cvt.rn.f16x2.f32 w2, f1, f0; shl.b32 f0, w3, 16; and.b32 f1, w3, 0xffff0000; cvt.rn.f16x2.f32 w3, f1, f0;\n"
        "stmatrix.sync.aligned.m8n8.x4.trans.shared.b16 [%4+0], {w0,w1,w2,w3};\n"
        "shl.b32 f0, w4, 16; and.b32 f1, w4, 0xffff0000; cvt.rn.f16x2.f32 w4, f1, f0; shl.b32 f0, w5, 16; and.b32 f1, w5, 0xffff0000; cvt.rn.f16x2.f32 w5, f1, f0; shl.b32 f0, w6, 16; and.b32 f1, w6, 0xffff0000; cvt.rn.f16x2.f32 w6, f1, f0; shl.b32 f0, w7, 16; and.b32 f1, w7, 0xffff0000; cvt.rn.f16x2.f32 w7, f1, f0;\n"
        "stmatrix.sync.aligned.m8n8.x4.trans.shared.b16 [%4+2048], {w4,w5,w6,w7};\n"
        "shl.b32 f0, w8, 16; and.b32 f1, w8, 0xffff0000; cvt.rn.f16x2.f32 w8, f1, f0; shl.b32 f0, w9, 16; and.b32 f1, w9, 0xffff0000; cvt.rn.f16x2.f32 w9, f1, f0; shl.b32 f0, w10, 16; and.b32 f1, w10, 0xffff0000; cvt.rn.f16x2.f32 w10, f1, f0; shl.b32 f0, w11, 16; and.b32 f1, w11, 0xffff0000; cvt.rn.f16x2.f32 w11, f1, f0;\n"
        "stmatrix.sync.aligned.m8n8.x4.trans.shared.b16 [%4+4096], {w8,w9,w10,w11};\n"
        "shl.b32 f0, w12, 16; and.b32 f1, w12, 0xffff0000; cvt.rn.f16x2.f32 w12, f1, f0; shl.b32 f0, w13, 16; and.b32 f1, w13, 0xffff0000; cvt.rn.f16x2.f32 w13, f1, f0; shl.b32 f0, w14, 16; and.b32 f1, w14, 0xffff0000; cvt.rn.f16x2.f32 w14, f1, f0; shl.b32 f0, w15, 16; and.b32 f1, w15, 0xffff0000; cvt.rn.f16x2.f32 w15, f1, f0;\n"
        "stmatrix.sync.aligned.m8n8.x4.trans.shared.b16 [%4+6144], {w12,w13,w14,w15};\n"
        "shl.b32 f0, w16, 16; and.b32 f1, w16, 0xffff0000; cvt.rn.f16x2.f32 w16, f1, f0; shl.b32 f0, w17, 16; and.b32 f1, w17, 0xffff0000; cvt.rn.f16x2.f32 w17, f1, f0; shl.b32 f0, w18, 16; and.b32 f1, w18, 0xffff0000; cvt.rn.f16x2.f32 w18, f1, f0; shl.b32 f0, w19, 16; and.b32 f1, w19, 0xffff0000; cvt.rn.f16x2.f32 w19, f1, f0;\n"
        "stmatrix.sync.aligned.m8n8.x4.trans.shared.b16 [%4+8192], {w16,w17,w18,w19};\n"
        "shl.b32 f0, w20, 16; and.b32 f1, w20, 0xffff0000; cvt.rn.f16x2.f32 w20, f1, f0; shl.b32 f0, w21, 16; and.b32 f1, w21, 0xffff0000; cvt.rn.f16x2.f32 w21, f1, f0; shl.b32 f0, w22, 16; and.b32 f1, w22, 0xffff0000; cvt.rn.f16x2.f32 w22, f1, f0; shl.b32 f0, w23, 16; and.b32 f1, w23, 0xffff0000; cvt.rn.f16x2.f32 w23, f1, f0;\n"
        "stmatrix.sync.aligned.m8n8.x4.trans.shared.b16 [%4+10240], {w20,w21,w22,w23};\n"
        "mov.u32 tt, 230880; mbarrier.try_wait.parity.shared::cta.b64 pw, [tt], 0;\n"
        "@!pw bra.uni SPINW;\n"
        "BACKW:\n"
        "ldmatrix.sync.aligned.m8n8.x4.trans.shared.b16 {z0,z1,z2,z3}, [%4+22528];\n"
        "ldmatrix.sync.aligned.m8n8.x4.trans.shared.b16 {w24,w25,w26,w27}, [%4+12288];\n"
        "ldmatrix.sync.aligned.m8n8.x4.trans.shared.b16 {w28,w29,w30,w31}, [%4+14336];\n"
        "ldmatrix.sync.aligned.m8n8.x4.trans.shared.b16 {w32,w33,w34,w35}, [%4+16384];\n"
        "ldmatrix.sync.aligned.m8n8.x4.trans.shared.b16 {w36,w37,w38,w39}, [%4+18432];\n"
        "ldmatrix.sync.aligned.m8n8.x4.trans.shared.b16 {w40,w41,w42,w43}, [%4+20480];\n"
        "shl.b32 f0, z0, 16; and.b32 f1, z0, 0xffff0000; cvt.rn.f16x2.f32 z0, f1, f0; shl.b32 f0, z1, 16; and.b32 f1, z1, 0xffff0000; cvt.rn.f16x2.f32 z1, f1, f0; shl.b32 f0, z2, 16; and.b32 f1, z2, 0xffff0000; cvt.rn.f16x2.f32 z2, f1, f0; shl.b32 f0, z3, 16; and.b32 f1, z3, 0xffff0000; cvt.rn.f16x2.f32 z3, f1, f0;\n"
        "stmatrix.sync.aligned.m8n8.x4.trans.shared.b16 [%4+22528], {z0,z1,z2,z3};\n"
        "shl.b32 f0, w24, 16; and.b32 f1, w24, 0xffff0000; cvt.rn.f16x2.f32 w24, f1, f0; shl.b32 f0, w25, 16; and.b32 f1, w25, 0xffff0000; cvt.rn.f16x2.f32 w25, f1, f0; shl.b32 f0, w26, 16; and.b32 f1, w26, 0xffff0000; cvt.rn.f16x2.f32 w26, f1, f0; shl.b32 f0, w27, 16; and.b32 f1, w27, 0xffff0000; cvt.rn.f16x2.f32 w27, f1, f0;\n"
        "stmatrix.sync.aligned.m8n8.x4.trans.shared.b16 [%4+12288], {w24,w25,w26,w27};\n"
        "shl.b32 f0, w28, 16; and.b32 f1, w28, 0xffff0000; cvt.rn.f16x2.f32 w28, f1, f0; shl.b32 f0, w29, 16; and.b32 f1, w29, 0xffff0000; cvt.rn.f16x2.f32 w29, f1, f0; shl.b32 f0, w30, 16; and.b32 f1, w30, 0xffff0000; cvt.rn.f16x2.f32 w30, f1, f0; shl.b32 f0, w31, 16; and.b32 f1, w31, 0xffff0000; cvt.rn.f16x2.f32 w31, f1, f0;\n"
        "stmatrix.sync.aligned.m8n8.x4.trans.shared.b16 [%4+14336], {w28,w29,w30,w31};\n"
        "shl.b32 f0, w32, 16; and.b32 f1, w32, 0xffff0000; cvt.rn.f16x2.f32 w32, f1, f0; shl.b32 f0, w33, 16; and.b32 f1, w33, 0xffff0000; cvt.rn.f16x2.f32 w33, f1, f0; shl.b32 f0, w34, 16; and.b32 f1, w34, 0xffff0000; cvt.rn.f16x2.f32 w34, f1, f0; shl.b32 f0, w35, 16; and.b32 f1, w35, 0xffff0000; cvt.rn.f16x2.f32 w35, f1, f0;\n"
        "stmatrix.sync.aligned.m8n8.x4.trans.shared.b16 [%4+16384], {w32,w33,w34,w35};\n"
        "shl.b32 f0, w36, 16; and.b32 f1, w36, 0xffff0000; cvt.rn.f16x2.f32 w36, f1, f0; shl.b32 f0, w37, 16; and.b32 f1, w37, 0xffff0000; cvt.rn.f16x2.f32 w37, f1, f0; shl.b32 f0, w38, 16; and.b32 f1, w38, 0xffff0000; cvt.rn.f16x2.f32 w38, f1, f0; shl.b32 f0, w39, 16; and.b32 f1, w39, 0xffff0000; cvt.rn.f16x2.f32 w39, f1, f0;\n"
        "stmatrix.sync.aligned.m8n8.x4.trans.shared.b16 [%4+18432], {w36,w37,w38,w39};\n"
        "shl.b32 f0, w40, 16; and.b32 f1, w40, 0xffff0000; cvt.rn.f16x2.f32 w40, f1, f0; shl.b32 f0, w41, 16; and.b32 f1, w41, 0xffff0000; cvt.rn.f16x2.f32 w41, f1, f0; shl.b32 f0, w42, 16; and.b32 f1, w42, 0xffff0000; cvt.rn.f16x2.f32 w42, f1, f0; shl.b32 f0, w43, 16; and.b32 f1, w43, 0xffff0000; cvt.rn.f16x2.f32 w43, f1, f0;\n"
        "stmatrix.sync.aligned.m8n8.x4.trans.shared.b16 [%4+20480], {w40,w41,w42,w43};\n"
        "fence.proxy.async.shared::cta;\n"
        ASM_SMARK
        "mov.b32 p, 0; mov.b32 t, 0; mov.b32 g, 0; mov.b32 a0, 0; mov.b32 a1, 0; mov.b32 a2, 0; mov.b32 a3, 0; mov.b32 lo0, 0; mov.b32 lo1, 0; mov.b32 hi0, 0; mov.b32 hi1, 0; mov.b32 q0, 0; mov.b32 q1, 0; mov.b32 q2, 0; mov.b32 q3, 0;\n"
        "mov.b32 z16, 0; mov.b32 z17, 0; mov.b32 z18, 0; mov.b32 z19, 0; mov.b32 z20, 0; mov.b32 z21, 0; mov.b32 z22, 0; mov.b32 z23, 0; mov.b32 z24, 0; mov.b32 z25, 0; mov.b32 z26, 0; mov.b32 z27, 0; mov.b32 z28, 0; mov.b32 z29, 0; mov.b32 z30, 0; mov.b32 z31, 0;\n"
        "mov.f32 %0, 0f00000000; mov.f32 %1, 0f00000000; mov.f32 %2, 0f00000000; mov.f32 %3, 0f00000000;\n"
        "mov.u32 n, 0; mov.u32 so, 0; mov.b64 gp, %8; mov.b64 wd, {%6, 0x40000040};\n"
        "mov.b64 ds0, %20; add.s64 ds1, ds0, 2; add.s64 ds2, ds0, 4; add.s64 ds3, ds0, 6; mov.b64 ds4, %21; add.s64 ds5, ds4, 2;\n"
        "mbarrier.try_wait.parity.shared::cta.b64 pw, [n+231552], 0;\n"
        "@!pw bra.uni SPIN0;\n"
        "BACK0:\n"
        ASM_TS
        "wgmma.fence.sync.aligned;\n"
        "wgmma.mma_async.sync.aligned.m64n64k16.f16.f16.f16 {z0,z1,z2,z3,z4,z5,z6,z7,z8,z9,z10,z11,z12,z13,z14,z15}, {w0,w1,w2,w3}, ds0, pf, 1, 1, 0;\n"
        "wgmma.mma_async.sync.aligned.m64n64k16.f16.f16.f16 {z0,z1,z2,z3,z4,z5,z6,z7,z8,z9,z10,z11,z12,z13,z14,z15}, {w4,w5,w6,w7}, ds1, pt, 1, 1, 0;\n"
        "wgmma.mma_async.sync.aligned.m64n64k16.f16.f16.f16 {z0,z1,z2,z3,z4,z5,z6,z7,z8,z9,z10,z11,z12,z13,z14,z15}, {w8,w9,w10,w11}, ds2, pt, 1, 1, 0;\n"
        "wgmma.fence.sync.aligned;\n"
        "wgmma.mma_async.sync.aligned.m64n64k16.f16.f16.f16 {z0,z1,z2,z3,z4,z5,z6,z7,z8,z9,z10,z11,z12,z13,z14,z15}, {w12,w13,w14,w15}, ds3, pt, 1, 1, 0;\n"
        "wgmma.mma_async.sync.aligned.m64n64k16.f16.f16.f16 {z0,z1,z2,z3,z4,z5,z6,z7,z8,z9,z10,z11,z12,z13,z14,z15}, {w16,w17,w18,w19}, ds4, pt, 1, 1, 0;\n"
        "wgmma.mma_async.sync.aligned.m64n64k16.f16.f16.f16 {z0,z1,z2,z3,z4,z5,z6,z7,z8,z9,z10,z11,z12,z13,z14,z15}, {w20,w21,w22,w23}, ds5, pt, 1, 1, 0;\n"
        "wgmma.commit_group.sync.aligned;\n"
        "setp.eq.u32 pr, so, %7;\n"
        "@pr bra.uni DUTY;\n"
        "TOP:\n"
        ASM_TRC("n")
        "wgmma.wait_group.sync.aligned 0;\n"
        "mov.b32 {xl, xh}, a2; tanh.approx.f16 xr, xh; cvt.u32.u16 hi0, xr; mul.rn.f16x2 a3, z31, p; fma.rn.f16x2 p, z0, z0, c; fma.rn.f16x2 q3, g, g, q3; fma.rn.f16x2 g, z28, t, z28; prmt.b32 t, lo1, hi1, 0x5410; tanh.approx.f16 xr, xl; cvt.u32.u16 lo0, xr;\n"
        "B31:\n"
        "mov.b32 {xl, xh}, a3; tanh.approx.f16 xr, xh; cvt.u32.u16 hi1, xr; mul.rn.f16x2 a0, z0, p; fma.rn.f16x2 p, z1, z1, c; fma.rn.f16x2 q2, g, g, q2; fma.rn.f16x2 g, z29, t, z29; prmt.b32 t, lo0, hi0, 0x5410; tanh.approx.f16 xr, xl; cvt.u32.u16 lo1, xr;\n"
        "B0:\n"
        "mov.b32 {xl, xh}, a0; tanh.approx.f16 xr, xh; cvt.u32.u16 hi0, xr; mul.rn.f16x2 a1, z1, p; fma.rn.f16x2 p, z2, z2, c; fma.rn.f16x2 q3, g, g, q3; fma.rn.f16x2 g, z30, t, z30; prmt.b32 t, lo1, hi1, 0x5410; tanh.approx.f16 xr, xl; cvt.u32.u16 lo0, xr;\n"
        "B1:\n"
        "mov.b32 {xl, xh}, a1; tanh.approx.f16 xr, xh; cvt.u32.u16 hi1, xr; mul.rn.f16x2 a2, z2, p; fma.rn.f16x2 p, z3, z3, c; fma.rn.f16x2 q2, g, g, q2; fma.rn.f16x2 g, z31, t, z31; prmt.b32 t, lo0, hi0, 0x5410; tanh.approx.f16 xr, xl; cvt.u32.u16 lo1, xr;\n"
        "B2:\n"
        "wgmma.fence.sync.aligned;\n"
        "wgmma.mma_async.sync.aligned.m64n64k16.f16.f16.f16 {z16,z17,z18,z19,z20,z21,z22,z23,z24,z25,z26,z27,z28,z29,z30,z31}, {w24,w25,w26,w27}, ds0, pf, 1, 1, 0;\n"
        "wgmma.mma_async.sync.aligned.m64n64k16.f16.f16.f16 {z16,z17,z18,z19,z20,z21,z22,z23,z24,z25,z26,z27,z28,z29,z30,z31}, {w28,w29,w30,w31}, ds1, pt, 1, 1, 0;\n"
        "wgmma.mma_async.sync.aligned.m64n64k16.f16.f16.f16 {z16,z17,z18,z19,z20,z21,z22,z23,z24,z25,z26,z27,z28,z29,z30,z31}, {w32,w33,w34,w35}, ds2, pt, 1, 1, 0;\n"
        "mov.b32 {xl, xh}, a2; tanh.approx.f16 xr, xh; cvt.u32.u16 hi0, xr; mul.rn.f16x2 a3, z3, p; fma.rn.f16x2 p, z4, z4, c; fma.rn.f16x2 q3, g, g, q3; fma.rn.f16x2 g, z0, t, z0; prmt.b32 t, lo1, hi1, 0x5410; tanh.approx.f16 xr, xl; cvt.u32.u16 lo0, xr;\n"
        "B3:\n"
        "mov.b32 {xl, xh}, a3; tanh.approx.f16 xr, xh; cvt.u32.u16 hi1, xr; mul.rn.f16x2 a0, z4, p; fma.rn.f16x2 p, z5, z5, c; fma.rn.f16x2 q0, g, g, q0; fma.rn.f16x2 g, z1, t, z1; prmt.b32 t, lo0, hi0, 0x5410; tanh.approx.f16 xr, xl; cvt.u32.u16 lo1, xr;\n"
        "B4:\n"
        "mov.b32 {xl, xh}, a0; tanh.approx.f16 xr, xh; cvt.u32.u16 hi0, xr; mul.rn.f16x2 a1, z5, p; fma.rn.f16x2 p, z6, z6, c; fma.rn.f16x2 q1, g, g, q1; fma.rn.f16x2 g, z2, t, z2; prmt.b32 t, lo1, hi1, 0x5410; tanh.approx.f16 xr, xl; cvt.u32.u16 lo0, xr;\n"
        "B5:\n"
        "wgmma.fence.sync.aligned;\n"
        "wgmma.mma_async.sync.aligned.m64n64k16.f16.f16.f16 {z16,z17,z18,z19,z20,z21,z22,z23,z24,z25,z26,z27,z28,z29,z30,z31}, {w36,w37,w38,w39}, ds3, pt, 1, 1, 0;\n"
        "wgmma.mma_async.sync.aligned.m64n64k16.f16.f16.f16 {z16,z17,z18,z19,z20,z21,z22,z23,z24,z25,z26,z27,z28,z29,z30,z31}, {w40,w41,w42,w43}, ds4, pt, 1, 1, 0;\n"
        "wgmma.mma_async.sync.aligned.m64n64k16.f16.f16.f16 {z16,z17,z18,z19,z20,z21,z22,z23,z24,z25,z26,z27,z28,z29,z30,z31}, wd, ds5, pt, 1, 1, 1, 0;\n"
        "wgmma.commit_group.sync.aligned;\n"
        "mov.b32 {xl, xh}, a1; tanh.approx.f16 xr, xh; cvt.u32.u16 hi1, xr; mul.rn.f16x2 a2, z6, p; fma.rn.f16x2 p, z7, z7, c; fma.rn.f16x2 q0, g, g, q0; fma.rn.f16x2 g, z3, t, z3; prmt.b32 t, lo0, hi0, 0x5410; tanh.approx.f16 xr, xl; cvt.u32.u16 lo1, xr;\n"
        "B6:\n"
        "add.u32 so, so, 26624; setp.eq.u32 pr, so, 79872; selp.u32 so, 0, so, pr;\n"
        "mov.b32 {xl, xh}, a2; tanh.approx.f16 xr, xh; cvt.u32.u16 hi0, xr; mul.rn.f16x2 a3, z7, p; fma.rn.f16x2 p, z8, z8, c; fma.rn.f16x2 q1, g, g, q1; fma.rn.f16x2 g, z4, t, z4; prmt.b32 t, lo1, hi1, 0x5410; tanh.approx.f16 xr, xl; cvt.u32.u16 lo0, xr;\n"
        "B7:\n"
        "shr.u32 tt, so, 4;\n"
        "mov.b64 {dl, dh}, ds0; add.u32 dl, tt, 74816; mov.b64 ds0, {dl, dh}; mov.b64 {dl, dh}, ds1; add.u32 dl, tt, 74818; mov.b64 ds1, {dl, dh}; mov.b64 {dl, dh}, ds2; add.u32 dl, tt, 74820; mov.b64 ds2, {dl, dh};\n"
        "mov.b32 {xl, xh}, a3; tanh.approx.f16 xr, xh; cvt.u32.u16 hi1, xr; mul.rn.f16x2 a0, z8, p; fma.rn.f16x2 p, z9, z9, c; fma.rn.f16x2 q0, g, g, q0; fma.rn.f16x2 g, z5, t, z5; prmt.b32 t, lo0, hi0, 0x5410; tanh.approx.f16 xr, xl; cvt.u32.u16 lo1, xr;\n"
        "B8:\n"
        "shr.u32 tt, so, 4;\n"
        "mov.b64 {dl, dh}, ds3; add.u32 dl, tt, 74822; mov.b64 ds3, {dl, dh}; mov.b64 {dl, dh}, ds4; add.u32 dl, tt, 75328; mov.b64 ds4, {dl, dh}; mov.b64 {dl, dh}, ds5; add.u32 dl, tt, 75330; mov.b64 ds5, {dl, dh};\n"
        "mov.b32 {xl, xh}, a0; tanh.approx.f16 xr, xh; cvt.u32.u16 hi0, xr; mul.rn.f16x2 a1, z9, p; fma.rn.f16x2 p, z10, z10, c; fma.rn.f16x2 q1, g, g, q1; fma.rn.f16x2 g, z6, t, z6; prmt.b32 t, lo1, hi1, 0x5410; tanh.approx.f16 xr, xl; cvt.u32.u16 lo0, xr;\n"
        "B9:\n"
        "mov.b32 {xl, xh}, a1; tanh.approx.f16 xr, xh; cvt.u32.u16 hi1, xr; mul.rn.f16x2 a2, z10, p; fma.rn.f16x2 p, z11, z11, c; fma.rn.f16x2 q0, g, g, q0; fma.rn.f16x2 g, z7, t, z7; prmt.b32 t, lo0, hi0, 0x5410; tanh.approx.f16 xr, xl; cvt.u32.u16 lo1, xr;\n"
        "B10:\n"
        "mov.b32 {xl, xh}, a2; tanh.approx.f16 xr, xh; cvt.u32.u16 hi0, xr; mul.rn.f16x2 a3, z11, p; fma.rn.f16x2 p, z12, z12, c; fma.rn.f16x2 q1, g, g, q1; fma.rn.f16x2 g, z8, t, z8; prmt.b32 t, lo1, hi1, 0x5410; tanh.approx.f16 xr, xl; cvt.u32.u16 lo0, xr;\n"
        "B11:\n"
        "mov.b32 {xl, xh}, a3; tanh.approx.f16 xr, xh; cvt.u32.u16 hi1, xr; mul.rn.f16x2 a0, z12, p; fma.rn.f16x2 p, z13, z13, c; fma.rn.f16x2 q0, g, g, q0; fma.rn.f16x2 g, z9, t, z9; prmt.b32 t, lo0, hi0, 0x5410; tanh.approx.f16 xr, xl; cvt.u32.u16 lo1, xr;\n"
        "B12:\n"
        "mov.b32 {xl, xh}, a0; tanh.approx.f16 xr, xh; cvt.u32.u16 hi0, xr; mul.rn.f16x2 a1, z13, p; fma.rn.f16x2 p, z14, z14, c; fma.rn.f16x2 q1, g, g, q1; fma.rn.f16x2 g, z10, t, z10; prmt.b32 t, lo1, hi1, 0x5410; tanh.approx.f16 xr, xl; cvt.u32.u16 lo0, xr;\n"
        "B13:\n"
        "mov.b32 {xl, xh}, a1; tanh.approx.f16 xr, xh; cvt.u32.u16 hi1, xr; mul.rn.f16x2 a2, z14, p; fma.rn.f16x2 p, z15, z15, c; fma.rn.f16x2 q0, g, g, q0; fma.rn.f16x2 g, z11, t, z11; prmt.b32 t, lo0, hi0, 0x5410; tanh.approx.f16 xr, xl; cvt.u32.u16 lo1, xr;\n"
        "B14:\n"
        "wgmma.wait_group.sync.aligned 0;\n"
        "cp.async.bulk.wait_group.read 0;\n"
        "@pl mbarrier.arrive.shared::cta.b64 _, [n+231288];\n"
        "mov.b32 {xl, xh}, a2; tanh.approx.f16 xr, xh; cvt.u32.u16 hi0, xr; mul.rn.f16x2 a3, z15, p; fma.rn.f16x2 p, z16, z16, c; fma.rn.f16x2 q1, g, g, q1; fma.rn.f16x2 g, z12, t, z12; prmt.b32 t, lo1, hi1, 0x5410; tanh.approx.f16 xr, xl; cvt.u32.u16 lo0, xr;\n"
        "B15:\n"
        "mov.b32 {xl, xh}, a3; tanh.approx.f16 xr, xh; cvt.u32.u16 hi1, xr; mul.rn.f16x2 a0, z16, p; fma.rn.f16x2 p, z17, z17, c; fma.rn.f16x2 q0, g, g, q0; fma.rn.f16x2 g, z13, t, z13; prmt.b32 t, lo0, hi0, 0x5410; tanh.approx.f16 xr, xl; cvt.u32.u16 lo1, xr;\n"
        "B16:\n"
        "mbarrier.try_wait.parity.shared::cta.b64 pw, [n+231560], 0;\n"
        "mov.b32 {xl, xh}, a0; tanh.approx.f16 xr, xh; cvt.u32.u16 hi0, xr; mul.rn.f16x2 a1, z17, p; fma.rn.f16x2 p, z18, z18, c; fma.rn.f16x2 q1, g, g, q1; fma.rn.f16x2 g, z14, t, z14; prmt.b32 t, lo1, hi1, 0x5410; tanh.approx.f16 xr, xl; cvt.u32.u16 lo0, xr;\n"
        "B17:\n"
        "mov.b32 {xl, xh}, a1; tanh.approx.f16 xr, xh; cvt.u32.u16 hi1, xr; mul.rn.f16x2 a2, z18, p; fma.rn.f16x2 p, z19, z19, c; fma.rn.f16x2 q0, g, g, q0; fma.rn.f16x2 g, z15, t, z15; prmt.b32 t, lo0, hi0, 0x5410; tanh.approx.f16 xr, xl; cvt.u32.u16 lo1, xr;\n"
        "B18:\n"
        "@!pw bra.uni SPIN;\n"
        "BACK:\n"
        "wgmma.fence.sync.aligned;\n"
        "wgmma.mma_async.sync.aligned.m64n64k16.f16.f16.f16 {z0,z1,z2,z3,z4,z5,z6,z7,z8,z9,z10,z11,z12,z13,z14,z15}, {w0,w1,w2,w3}, ds0, pf, 1, 1, 0;\n"
        "wgmma.mma_async.sync.aligned.m64n64k16.f16.f16.f16 {z0,z1,z2,z3,z4,z5,z6,z7,z8,z9,z10,z11,z12,z13,z14,z15}, {w4,w5,w6,w7}, ds1, pt, 1, 1, 0;\n"
        "wgmma.mma_async.sync.aligned.m64n64k16.f16.f16.f16 {z0,z1,z2,z3,z4,z5,z6,z7,z8,z9,z10,z11,z12,z13,z14,z15}, {w8,w9,w10,w11}, ds2, pt, 1, 1, 0;\n"
        "mov.b32 {xl, xh}, a2; tanh.approx.f16 xr, xh; cvt.u32.u16 hi0, xr; mul.rn.f16x2 a3, z19, p; fma.rn.f16x2 p, z20, z20, c; fma.rn.f16x2 q1, g, g, q1; fma.rn.f16x2 g, z16, t, z16; prmt.b32 t, lo1, hi1, 0x5410; tanh.approx.f16 xr, xl; cvt.u32.u16 lo0, xr;\n"
        "B19:\n"
        "mov.b32 {xl, xh}, a3; tanh.approx.f16 xr, xh; cvt.u32.u16 hi1, xr; mul.rn.f16x2 a0, z20, p; fma.rn.f16x2 p, z21, z21, c; fma.rn.f16x2 q2, g, g, q2; fma.rn.f16x2 g, z17, t, z17; prmt.b32 t, lo0, hi0, 0x5410; tanh.approx.f16 xr, xl; cvt.u32.u16 lo1, xr;\n"
        "B20:\n"
        "mov.b32 {xl, xh}, a0; tanh.approx.f16 xr, xh; cvt.u32.u16 hi0, xr; mul.rn.f16x2 a1, z21, p; fma.rn.f16x2 p, z22, z22, c; fma.rn.f16x2 q3, g, g, q3; fma.rn.f16x2 g, z18, t, z18; prmt.b32 t, lo1, hi1, 0x5410; tanh.approx.f16 xr, xl; cvt.u32.u16 lo0, xr;\n"
        "B21:\n"
        "wgmma.fence.sync.aligned;\n"
        "wgmma.mma_async.sync.aligned.m64n64k16.f16.f16.f16 {z0,z1,z2,z3,z4,z5,z6,z7,z8,z9,z10,z11,z12,z13,z14,z15}, {w12,w13,w14,w15}, ds3, pt, 1, 1, 0;\n"
        "wgmma.mma_async.sync.aligned.m64n64k16.f16.f16.f16 {z0,z1,z2,z3,z4,z5,z6,z7,z8,z9,z10,z11,z12,z13,z14,z15}, {w16,w17,w18,w19}, ds4, pt, 1, 1, 0;\n"
        "wgmma.mma_async.sync.aligned.m64n64k16.f16.f16.f16 {z0,z1,z2,z3,z4,z5,z6,z7,z8,z9,z10,z11,z12,z13,z14,z15}, {w20,w21,w22,w23}, ds5, pt, 1, 1, 0;\n"
        "wgmma.commit_group.sync.aligned;\n"
        "mov.b32 {xl, xh}, a1; tanh.approx.f16 xr, xh; cvt.u32.u16 hi1, xr; mul.rn.f16x2 a2, z22, p; fma.rn.f16x2 p, z23, z23, c; fma.rn.f16x2 q2, g, g, q2; fma.rn.f16x2 g, z19, t, z19; prmt.b32 t, lo0, hi0, 0x5410; tanh.approx.f16 xr, xl; cvt.u32.u16 lo1, xr;\n"
        "B22:\n"
        "mov.b32 {xl, xh}, a2; tanh.approx.f16 xr, xh; cvt.u32.u16 hi0, xr; mul.rn.f16x2 a3, z23, p; fma.rn.f16x2 p, z24, z24, c; fma.rn.f16x2 q3, g, g, q3; fma.rn.f16x2 g, z20, t, z20; prmt.b32 t, lo1, hi1, 0x5410; tanh.approx.f16 xr, xl; cvt.u32.u16 lo0, xr;\n"
        "B23:\n"
        "mov.b32 {xl, xh}, a3; tanh.approx.f16 xr, xh; cvt.u32.u16 hi1, xr; mul.rn.f16x2 a0, z24, p; fma.rn.f16x2 p, z25, z25, c; fma.rn.f16x2 q2, g, g, q2; fma.rn.f16x2 g, z21, t, z21; prmt.b32 t, lo0, hi0, 0x5410; tanh.approx.f16 xr, xl; cvt.u32.u16 lo1, xr;\n"
        "B24:\n"
        "mov.b32 {xl, xh}, a0; tanh.approx.f16 xr, xh; cvt.u32.u16 hi0, xr; mul.rn.f16x2 a1, z25, p; fma.rn.f16x2 p, z26, z26, c; fma.rn.f16x2 q3, g, g, q3; fma.rn.f16x2 g, z22, t, z22; prmt.b32 t, lo1, hi1, 0x5410; tanh.approx.f16 xr, xl; cvt.u32.u16 lo0, xr;\n"
        "B25:\n"
        "mov.b32 {xl, xh}, a1; tanh.approx.f16 xr, xh; cvt.u32.u16 hi1, xr; mul.rn.f16x2 a2, z26, p; fma.rn.f16x2 p, z27, z27, c; fma.rn.f16x2 q2, g, g, q2; fma.rn.f16x2 g, z23, t, z23; prmt.b32 t, lo0, hi0, 0x5410; tanh.approx.f16 xr, xl; cvt.u32.u16 lo1, xr;\n"
        "B26:\n"
        "mov.b32 {xl, xh}, a2; tanh.approx.f16 xr, xh; cvt.u32.u16 hi0, xr; mul.rn.f16x2 a3, z27, p; fma.rn.f16x2 p, z28, z28, c; fma.rn.f16x2 q3, g, g, q3; fma.rn.f16x2 g, z24, t, z24; prmt.b32 t, lo1, hi1, 0x5410; tanh.approx.f16 xr, xl; cvt.u32.u16 lo0, xr;\n"
        "B27:\n"
        "add.u32 n, n, 8; setp.lt.u32 pe, n, 256; setp.ne.and.u32 pe, so, %7, pe;\n"
        "mov.b32 {xl, xh}, a3; tanh.approx.f16 xr, xh; cvt.u32.u16 hi1, xr; mul.rn.f16x2 a0, z28, p; fma.rn.f16x2 p, z29, z29, c; fma.rn.f16x2 q2, g, g, q2; fma.rn.f16x2 g, z25, t, z25; prmt.b32 t, lo0, hi0, 0x5410; tanh.approx.f16 xr, xl; cvt.u32.u16 lo1, xr;\n"
        "B28:\n"
        "mov.b32 {xl, xh}, a0; tanh.approx.f16 xr, xh; cvt.u32.u16 hi0, xr; mul.rn.f16x2 a1, z29, p; fma.rn.f16x2 p, z30, z30, c; fma.rn.f16x2 q3, g, g, q3; fma.rn.f16x2 g, z26, t, z26; prmt.b32 t, lo1, hi1, 0x5410; tanh.approx.f16 xr, xl; cvt.u32.u16 lo0, xr;\n"
        "B29:\n"
        "mov.b32 {xl, xh}, a1; tanh.approx.f16 xr, xh; cvt.u32.u16 hi1, xr; mul.rn.f16x2 a2, z30, p; fma.rn.f16x2 p, z31, z31, c; fma.rn.f16x2 q2, g, g, q2; fma.rn.f16x2 g, z27, t, z27; prmt.b32 t, lo0, hi0, 0x5410; tanh.approx.f16 xr, xl; cvt.u32.u16 lo1, xr;\n"
        "@pe bra.uni TOP;\n"
        "setp.lt.u32 pe, n, 256;\n"
        "@pe bra.uni DUTY;\n"
        "bra.uni DONE;\n"
        "SPINW: mov.u32 cnt, 0;\n"
        "SPINWL:\n"
        "mov.u32 tt, 230880; mbarrier.try_wait.parity.shared::cta.b64 pw, [tt], 0;\n"
        "@pw bra.uni BACKW;\n"
        "add.u32 cnt, cnt, 1; setp.lt.u32 pw, cnt, 0x100000;\n"
        "@pw bra.uni SPINWL;\n"
        "trap;\n"
        "SPIN0: mov.u32 cnt, 0;\n"
        "SPIN0L:\n"
        "mbarrier.try_wait.parity.shared::cta.b64 pw, [n+231552], 0;\n"
        "@pw bra.uni BACK0;\n"
        "add.u32 cnt, cnt, 1; setp.lt.u32 pw, cnt, 0x100000;\n"
        "@pw bra.uni SPIN0L;\n"
        "trap;\n"
        "SPIN: mov.u32 cnt, 0;\n"
        "SPINL:\n"
        "mbarrier.try_wait.parity.shared::cta.b64 pw, [n+231560], 0;\n"
        "@pw bra.uni BACK;\n"
        "add.u32 cnt, cnt, 1; setp.lt.u32 pw, cnt, 0x100000;\n"
        "@pw bra.uni SPINL;\n"
        "trap;\n"
        "DUTY:\n"
        "setp.ge.s32 pr, n, %11;\n"
        "@pr bra.uni FLUSH;\n"
        "setp.ge.u32 pr, %13, 2;\n"
        "@pr bra.uni ROLE2;\n"
        "setp.ge.s32 pr, n, %12; selp.b64 src, %14, gp, pr; add.u32 tt, n, 231288;\n"
        "elect.sync _|pr, 0xffffffff;\n"
        "@pr mbarrier.arrive.expect_tx.shared::cta.b64 _, [tt], %10;\n"
        "@pr cp.async.bulk.shared::cluster.global.mbarrier::complete_tx::bytes [%9], [src], %10, [tt];\n"
        "bra.uni FLUSH;\n"
        "ROLE2:\n"
        "setp.eq.u32 pr, %13, 3;\n"
        "@pr bra.uni ROLE3;\n"
        "setp.ne.s32 pr, n, 248;\n"
        "@pr bra.uni PARK;\n"
        "cp.async.bulk.wait_group 0;\n"
        "sub.s64 src, gp, %16; mov.u32 tt, 230824; mov.u32 cnt, 187392;\n"
        "elect.sync _|pr, 0xffffffff;\n"
        "@pr mbarrier.arrive.expect_tx.shared::cta.b64 _, [tt], 12288;\n"
        "@pr cp.async.bulk.shared::cluster.global.mbarrier::complete_tx::bytes [cnt], [src], 12288, [tt];\n"
        "PARK:\n"
        "elect.sync _|pr, 0xffffffff;\n"
        "@pr cp.async.bulk.global.shared::cta.bulk_group [gp], [%9], 12288;\n"
        "@pr cp.async.bulk.commit_group;\n"
        "bra.uni FLUSH;\n"
        "ROLE3:\n"
        "setp.ne.s32 pr, n, 64;\n"
        "@pr bra.uni AHEAD;\n"
        "mov.u32 tt, 230872;\n"
        "elect.sync _|pr, 0xffffffff;\n"
        "@pr mbarrier.arrive.expect_tx.shared::cta.b64 _, [tt], 75264;\n"
        "mov.u32 cnt, 229248; @pr cp.async.bulk.shared::cluster.global.mbarrier::complete_tx::bytes [cnt], [%18], 768, [tt];\n"
        "mov.u32 cnt, 230016; @pr cp.async.bulk.shared::cluster.global.mbarrier::complete_tx::bytes [cnt], [%19], 768, [tt];\n"
        "mov.u32 cnt, 74752; @pr cp.async.bulk.tensor.2d.shared::cluster.global.mbarrier::complete_tx::bytes [cnt], [%17, {0, 0}], [tt];\n"
        "mov.u32 cnt, 87040; @pr cp.async.bulk.tensor.2d.shared::cluster.global.mbarrier::complete_tx::bytes [cnt], [%17, {0, 192}], [tt];\n"
        "mov.u32 cnt, 99328; @pr cp.async.bulk.tensor.2d.shared::cluster.global.mbarrier::complete_tx::bytes [cnt], [%17, {32, 0}], [tt];\n"
        "mov.u32 cnt, 111616; @pr cp.async.bulk.tensor.2d.shared::cluster.global.mbarrier::complete_tx::bytes [cnt], [%17, {32, 192}], [tt];\n"
        "mov.u32 cnt, 123904; @pr cp.async.bulk.tensor.2d.shared::cluster.global.mbarrier::complete_tx::bytes [cnt], [%17, {64, 0}], [tt];\n"
        "mov.u32 cnt, 136192; @pr cp.async.bulk.tensor.2d.shared::cluster.global.mbarrier::complete_tx::bytes [cnt], [%17, {64, 192}], [tt];\n"
        "AHEAD:\n"
        "elect.sync _|pr, 0xffffffff;\n"
        "@pr cp.async.bulk.prefetch.L2.global [gp], 12288;\n"
        "FLUSH:\n"
        "add.s64 gp, gp, %16;\n"
        "mov.b32 {xl, xh}, q0; cvt.f32.f16 f0, xl; cvt.f32.f16 f1, xh; add.f32 f0, f0, f1; add.f32 %0, %0, f0; mov.b32 q0, 0;\n"
        "mov.b32 {xl, xh}, q1; cvt.f32.f16 f0, xl; cvt.f32.f16 f1, xh; add.f32 f0, f0, f1; add.f32 %1, %1, f0; mov.b32 q1, 0;\n"
        "mov.b32 {xl, xh}, q2; cvt.f32.f16 f0, xl; cvt.f32.f16 f1, xh; add.f32 f0, f0, f1; add.f32 %2, %2, f0; mov.b32 q2, 0;\n"
        "mov.b32 {xl, xh}, q3; cvt.f32.f16 f0, xl; cvt.f32.f16 f1, xh; add.f32 f0, f0, f1; add.f32 %3, %3, f0; mov.b32 q3, 0;\n"
        "setp.ne.u32 pr, %5, 0;\n"
        "@pr bra.uni TOP;\n"
        "wgmma.wait_group.sync.aligned 0;\n"
        "wgmma.fence.sync.aligned;\n"
        "ld.volatile.shared.v2.b32 {lo0, hi0}, [so]; xor.b32 f0, f0, lo0;\n"
        "ld.volatile.shared.v2.b32 {lo1, hi1}, [so]; xor.b32 f0, f0, lo1;\n"
        "ld.volatile.shared.v2.b32 {q1, a0}, [so]; xor.b32 f0, f0, q1;\n"
        "ld.volatile.shared.v2.b32 {q2, a1}, [so]; xor.b32 f0, f0, q2;\n"
        "ld.volatile.shared.v2.b32 {q3, a2}, [so]; xor.b32 f0, f0, q3;\n"
        "ld.volatile.shared.v2.b32 {q0, a3}, [so]; xor.b32 f0, f0, q0;\n"
        "ld.volatile.shared.v2.b32 {t, g}, [so]; xor.b32 f0, f0, t;\n"
        "ld.volatile.shared.v2.b32 {p, f1}, [so]; xor.b32 f0, f0, p;\n"
        "add.f32 %0, %0, f0;\n"
        "setp.eq.u32 pr, n, 1000; @pr bra.uni B31;\n"
        "setp.eq.u32 pr, n, 1001; @pr bra.uni B0;\n"
        "setp.eq.u32 pr, n, 1002; @pr bra.uni B1;\n"
        "setp.eq.u32 pr, n, 1003; @pr bra.uni B2;\n"
        "setp.eq.u32 pr, n, 1004; @pr bra.uni B3;\n"
        "setp.eq.u32 pr, n, 1005; @pr bra.uni B4;\n"
        "setp.eq.u32 pr, n, 1006; @pr bra.uni B5;\n"
        "setp.eq.u32 pr, n, 1007; @pr bra.uni B6;\n"
        "setp.eq.u32 pr, n, 1008; @pr bra.uni B7;\n"
        "setp.eq.u32 pr, n, 1009; @pr bra.uni B8;\n"
        "setp.eq.u32 pr, n, 1010; @pr bra.uni B9;\n"
        "setp.eq.u32 pr, n, 1011; @pr bra.uni B10;\n"
        "setp.eq.u32 pr, n, 1012; @pr bra.uni B11;\n"
        "setp.eq.u32 pr, n, 1013; @pr bra.uni B12;\n"
        "setp.eq.u32 pr, n, 1014; @pr bra.uni B13;\n"
        "setp.eq.u32 pr, n, 1015; @pr bra.uni B14;\n"
        "setp.eq.u32 pr, n, 1016; @pr bra.uni B15;\n"
        "setp.eq.u32 pr, n, 1017; @pr bra.uni B16;\n"
        "setp.eq.u32 pr, n, 1018; @pr bra.uni B17;\n"
        "setp.eq.u32 pr, n, 1019; @pr bra.uni B18;\n"
        "setp.eq.u32 pr, n, 1020; @pr bra.uni B19;\n"
        "setp.eq.u32 pr, n, 1021; @pr bra.uni B20;\n"
        "setp.eq.u32 pr, n, 1022; @pr bra.uni B21;\n"
        "setp.eq.u32 pr, n, 1023; @pr bra.uni B22;\n"
        "setp.eq.u32 pr, n, 1024; @pr bra.uni B23;\n"
        "setp.eq.u32 pr, n, 1025; @pr bra.uni B24;\n"
        "setp.eq.u32 pr, n, 1026; @pr bra.uni B25;\n"
        "setp.eq.u32 pr, n, 1027; @pr bra.uni B26;\n"
        "setp.eq.u32 pr, n, 1028; @pr bra.uni B27;\n"
        "setp.eq.u32 pr, n, 1029; @pr bra.uni B28;\n"
        "setp.eq.u32 pr, n, 1030; @pr bra.uni B29;\n"
        "setp.eq.u32 pr, n, 1031; @pr bra.uni TOP;\n"
        "trap;\n"
        "DONE:\n"
        ASM_TRC("n")
        "mov.b32 {xl, xh}, a2; tanh.approx.f16 xr, xh; cvt.u32.u16 hi0, xr; mul.rn.f16x2 a3, z31, p; fma.rn.f16x2 q3, g, g, q3; fma.rn.f16x2 g, z28, t, z28; prmt.b32 t, lo1, hi1, 0x5410; tanh.approx.f16 xr, xl; cvt.u32.u16 lo0, xr;\n"
        "mov.b32 {xl, xh}, a3; tanh.approx.f16 xr, xh; cvt.u32.u16 hi1, xr; fma.rn.f16x2 q2, g, g, q2; fma.rn.f16x2 g, z29, t, z29; prmt.b32 t, lo0, hi0, 0x5410; tanh.approx.f16 xr, xl; cvt.u32.u16 lo1, xr;\n"
        "fma.rn.f16x2 q3, g, g, q3; fma.rn.f16x2 g, z30, t, z30; prmt.b32 t, lo1, hi1, 0x5410;\n"
        "fma.rn.f16x2 q2, g, g, q2; fma.rn.f16x2 g, z31, t, z31;\n"
        "fma.rn.f16x2 q3, g, g, q3;\n"
        "mov.b32 {xl, xh}, q0; cvt.f32.f16 f0, xl; cvt.f32.f16 f1, xh; add.f32 f0, f0, f1; add.f32 %0, %0, f0; mov.b32 q0, 0;\n"
        "mov.b32 {xl, xh}, q1; cvt.f32.f16 f0, xl; cvt.f32.f16 f1, xh; add.f32 f0, f0, f1; add.f32 %1, %1, f0; mov.b32 q1, 0;\n"
        "mov.b32 {xl, xh}, q2; cvt.f32.f16 f0, xl; cvt.f32.f16 f1, xh; add.f32 f0, f0, f1; add.f32 %2, %2, f0; mov.b32 q2, 0;\n"
        "mov.b32 {xl, xh}, q3; cvt.f32.f16 f0, xl; cvt.f32.f16 f1, xh; add.f32 f0, f0, f1; add.f32 %3, %3, f0; mov.b32 q3, 0;\n"
        "wgmma.wait_group.sync.aligned 0;\n"
        "}\n"
        : "=f"(acc[0][0]), "=f"(acc[0][1]), "=f"(acc[1][0]), "=f"(acc[1][1])
        : "r"(w1t), "r"(yd), "r"(wd), "r"(own_slot), "l"(d.g), "r"(d.s), "r"(d.bytes), "r"(8 * d.end), "r"(8 * d.zero), "r"(role),
          "l"(d.zeros), "r"(lane), "l"(d.step), "l"(&prm.w2_map), "l"(prm.gamma), "l"(prm.beta), "l"(prm.ydesc64[0]), "l"(prm.ydesc64[1])
        : "memory");
}

template <int M>
__device__ __forceinline__ void gemm1_t(uint32_t (&d)[16], const uint32_t* wa, uint32_t yd, uint32_t wd) {
    wg_fence();
    wgmma_n64_h_set<0>(d, wa, desc<1024, 1>(yd, 0));
#pragma unroll
    for (int kk = 1; kk < 5; kk++)
        wgmma_n64_h_acc<0>(d, wa + kk * 4, kk < 4 ? desc<1024, 1>(yd, kk * 32) : desc<512, 2>(yd, 8192 + (kk - 4) * 32));
    wgmma_n64_h_acc_ss(d, desc<1024, 1>(wd, M * 12288), desc<512, 2>(yd, 8192 + 32));
    wg_commit();
}

__device__ __forceinline__ void gelu_sumsq_f(const uint32_t (&d)[16], float (&acc)[2]) {
#pragma unroll
    for (int r = 0; r < 16; r++) {
        float lo, hi;
        h2_unpack(gelu2(d[r]), lo, hi);
        acc[r & 1] = fmaf(lo, lo, acc[r & 1]);
        acc[r & 1] = fmaf(hi, hi, acc[r & 1]);
    }
}
__device__ __forceinline__ void load_w1t(uint32_t (&wa)[2][24], int wg, int w, int lane) {
#pragma unroll
    for (int m = 0; m < 2; m++)
#pragma unroll
        for (int kk = 0; kk < 5; kk++) {
            const int q = lane >> 3, c = 16 * kk + 8 * (q >> 1) + (lane & 7), ck = 2 * w + (q & 1);
            ldsm4_t(wa[m] + kk * 4, sb + SM_W1 + (2 * wg + m) * 12288 + c * 128 + ((ck ^ (c & 7)) * 16));
        }
}
__device__ __forceinline__ unsigned long long* acc_word(const Params& prm, uint32_t epoch, uint32_t e) {
    return &prm.g->acc[epoch & 1][(e >> 2) * 32 + (e & 3)];
}
__device__ __forceinline__ void publish_fast(const Params& prm, const float (&acc)[2][2], uint32_t epoch, int wg, int w, int lane) {
    const bool m = lane & 2, h = lane & 1;
    const float a = (m ? acc[1][0] : acc[0][0]) + __shfl_xor_sync(0xffffffffu, m ? acc[0][0] : acc[1][0], 2);
    const float b = (m ? acc[1][1] : acc[0][1]) + __shfl_xor_sync(0xffffffffu, m ? acc[0][1] : acc[1][1], 2);
    const float v = (h ? b : a) + __shfl_xor_sync(0xffffffffu, h ? a : b, 1);
    const unsigned long long q = (__float2ull_rn(fminf(v, ACC_LIMIT) * 0x1p16f) << 8) + 1;
    asm volatile("red.relaxed.gpu.global.add.u64 [%0], %1;"
                 ::"l"(acc_word(prm, epoch, 128 * wg + 32 * (lane & 2) + 16 * w + (lane >> 2) + 8 * (lane & 1))), "l"(q) : "memory");
}
__device__ __forceinline__ float collect_fast(const unsigned long long* word, unsigned long long v) {
    asm volatile(
        "{\n.reg .pred p;\n.reg .u32 n, lo, hi;\nmov.u32 n, 0;\n"
        "POLL:\nmov.b64 {lo, hi}, %0;\nand.b32 lo, lo, 255;\n"
        "setp.eq.u32 p, lo, %2;\nvote.sync.all.pred p, p, 0xffffffff;\n@p bra.uni POLL_DONE;\n"
        "ld.relaxed.gpu.global.u64 %0, [%1];\n"
        "add.u32 n, n, 1;\nsetp.lt.u32 p, n, 0x400000;\n@p bra.uni POLL;\ntrap;\nPOLL_DONE:\n}\n"
        : "+l"(v) : "l"(word), "n"(NUM_CTAS) : "memory");
    return __ull2float_rn(v >> 8) * 0x1p-16f;
}
__device__ __forceinline__ void publish_sums(const float (&acc)[2][2], float* sums, unsigned int* counter, int wg, int w, int lane) {
#pragma unroll
    for (int m = 0; m < 2; m++)
#pragma unroll
        for (int h = 0; h < 2; h++) {
            const float v = quad_sum(acc[m][h]);
            if ((lane & 3) == 0) atomicAdd(sums + 64 * (2 * wg + m) + 16 * w + (lane >> 2) + 8 * h, v);
        }
    named_sync(1, 384);
    if (fresh_tid() == 0) asm volatile("red.release.gpu.global.add.u32 [%0], 1;" ::"l"(counter) : "memory");
}
__device__ __forceinline__ void grid_wait(const unsigned int* counter, unsigned int target) {
    if (fresh_tid() == 0) {
        unsigned int v, spins = 0;
        do {
            asm volatile("ld.acquire.gpu.global.u32 %0, [%1];" : "=r"(v) : "l"(counter) : "memory");
            if (++spins > (1u << 22)) __trap();
        } while ((int)(v - target) < 0);
    }
    __syncthreads();
}

struct Pass2 {
    uint32_t wg;
    uint32_t off;
    int step;
    uint32_t xs;
    uint32_t a_offs, xs_offs, bias_addr;
    uint32_t w;
};

static_assert(BAR_Y2FULL == 0 && BAR_XSFULL == 4 && BAR_TURN == 11 && BAR_ROWS == 51 && BAR_STAT == 53 &&
              sb + SM_RED + RED_SCALE * 4 == 230792, "layout");
#define PASS2_STATE ".reg .b32 qa<24>, qz<32>, o<24>, g<16>, p<2>, a<4>, lo<2>, hi<2>, h<2>, osc;"
__device__ __forceinline__ void pass2_start(const Pass2& c, const Params& prm) {
    asm volatile(
        "{\n"
        ".reg .b32 t<2>, c, ad, cnt, ybar;\n"
        ".reg .b16 xl, xh, xr;\n"
        ".reg .b64 w1d, dt;\n"
        ".reg .pred pt, pf, pw;\n"
        "setp.ne.b32 pt, 1, 0; setp.ne.b32 pf, 0, 0; mov.b32 c, 0x40D940D9; mov.b64 w1d, {%0, 0x40000040}; mad.lo.u32 ybar, %1, 8, 230800;\n"
        "mbarrier.try_wait.parity.shared::cta.b64 pw, [ybar], 0;\n"
        "@!pw bra.uni SPINY0;\n"
        "BACKY0:\n"
        "and.b32 t0, %3, 0xffff; shr.u32 t1, %3, 16;\n"
        "xor.b32 ad, t0, 0; add.u32 ad, ad, %2; ldmatrix.sync.aligned.m8n8.x4.shared.b16 {qa0,qa1,qa2,qa3}, [ad];\n"
        "xor.b32 ad, t0, 32; add.u32 ad, ad, %2; ldmatrix.sync.aligned.m8n8.x4.shared.b16 {qa4,qa5,qa6,qa7}, [ad];\n"
        "xor.b32 ad, t0, 64; add.u32 ad, ad, %2; ldmatrix.sync.aligned.m8n8.x4.shared.b16 {qa8,qa9,qa10,qa11}, [ad];\n"
        "xor.b32 ad, t0, 96; add.u32 ad, ad, %2; ldmatrix.sync.aligned.m8n8.x4.shared.b16 {qa12,qa13,qa14,qa15}, [ad];\n"
        "xor.b32 ad, t1, 0; add.u32 ad, ad, %2; ldmatrix.sync.aligned.m8n8.x4.shared.b16 {qa16,qa17,qa18,qa19}, [ad];\n"
        "xor.b32 ad, t1, 32; add.u32 ad, ad, %2; ldmatrix.sync.aligned.m8n8.x4.shared.b16 {qa20,qa21,qa22,qa23}, [ad];\n"
        "wgmma.fence.sync.aligned;\n"
        "add.s64 dt, w1d, 0; wgmma.mma_async.sync.aligned.m64n64k16.f16.f16.f16 {qz0,qz1,qz2,qz3,qz4,qz5,qz6,qz7,qz8,qz9,qz10,qz11,qz12,qz13,qz14,qz15}, {qa0,qa1,qa2,qa3}, dt, pf, 1, 1, 1;\n"
        "add.s64 dt, w1d, 128; wgmma.mma_async.sync.aligned.m64n64k16.f16.f16.f16 {qz0,qz1,qz2,qz3,qz4,qz5,qz6,qz7,qz8,qz9,qz10,qz11,qz12,qz13,qz14,qz15}, {qa4,qa5,qa6,qa7}, dt, pt, 1, 1, 1;\n"
        "add.s64 dt, w1d, 256; wgmma.mma_async.sync.aligned.m64n64k16.f16.f16.f16 {qz0,qz1,qz2,qz3,qz4,qz5,qz6,qz7,qz8,qz9,qz10,qz11,qz12,qz13,qz14,qz15}, {qa8,qa9,qa10,qa11}, dt, pt, 1, 1, 1;\n"
        "add.s64 dt, w1d, 384; wgmma.mma_async.sync.aligned.m64n64k16.f16.f16.f16 {qz0,qz1,qz2,qz3,qz4,qz5,qz6,qz7,qz8,qz9,qz10,qz11,qz12,qz13,qz14,qz15}, {qa12,qa13,qa14,qa15}, dt, pt, 1, 1, 1;\n"
        "add.s64 dt, w1d, 512; wgmma.mma_async.sync.aligned.m64n64k16.f16.f16.f16 {qz0,qz1,qz2,qz3,qz4,qz5,qz6,qz7,qz8,qz9,qz10,qz11,qz12,qz13,qz14,qz15}, {qa16,qa17,qa18,qa19}, dt, pt, 1, 1, 1;\n"
        "add.s64 dt, w1d, 640; wgmma.mma_async.sync.aligned.m64n64k16.f16.f16.f16 {qz0,qz1,qz2,qz3,qz4,qz5,qz6,qz7,qz8,qz9,qz10,qz11,qz12,qz13,qz14,qz15}, {qa20,qa21,qa22,qa23}, dt, pt, 1, 1, 1;\n"
        "wgmma.commit_group.sync.aligned;\n"
        "wgmma.fence.sync.aligned;\n"
        "add.s64 dt, w1d, 768; wgmma.mma_async.sync.aligned.m64n64k16.f16.f16.f16 {qz16,qz17,qz18,qz19,qz20,qz21,qz22,qz23,qz24,qz25,qz26,qz27,qz28,qz29,qz30,qz31}, {qa0,qa1,qa2,qa3}, dt, pf, 1, 1, 1;\n"
        "add.s64 dt, w1d, 896; wgmma.mma_async.sync.aligned.m64n64k16.f16.f16.f16 {qz16,qz17,qz18,qz19,qz20,qz21,qz22,qz23,qz24,qz25,qz26,qz27,qz28,qz29,qz30,qz31}, {qa4,qa5,qa6,qa7}, dt, pt, 1, 1, 1;\n"
        "add.s64 dt, w1d, 1024; wgmma.mma_async.sync.aligned.m64n64k16.f16.f16.f16 {qz16,qz17,qz18,qz19,qz20,qz21,qz22,qz23,qz24,qz25,qz26,qz27,qz28,qz29,qz30,qz31}, {qa8,qa9,qa10,qa11}, dt, pt, 1, 1, 1;\n"
        "add.s64 dt, w1d, 1152; wgmma.mma_async.sync.aligned.m64n64k16.f16.f16.f16 {qz16,qz17,qz18,qz19,qz20,qz21,qz22,qz23,qz24,qz25,qz26,qz27,qz28,qz29,qz30,qz31}, {qa12,qa13,qa14,qa15}, dt, pt, 1, 1, 1;\n"
        "add.s64 dt, w1d, 1280; wgmma.mma_async.sync.aligned.m64n64k16.f16.f16.f16 {qz16,qz17,qz18,qz19,qz20,qz21,qz22,qz23,qz24,qz25,qz26,qz27,qz28,qz29,qz30,qz31}, {qa16,qa17,qa18,qa19}, dt, pt, 1, 1, 1;\n"
        "add.s64 dt, w1d, 1408; wgmma.mma_async.sync.aligned.m64n64k16.f16.f16.f16 {qz16,qz17,qz18,qz19,qz20,qz21,qz22,qz23,qz24,qz25,qz26,qz27,qz28,qz29,qz30,qz31}, {qa20,qa21,qa22,qa23}, dt, pt, 1, 1, 1;\n"
        "wgmma.commit_group.sync.aligned;\n"
        "mov.b32 g0, 0; mov.b32 g1, 0; mov.b32 g2, 0; mov.b32 g3, 0; mov.b32 p0, 0; mov.b32 p1, 0; mov.b32 a0, 0; mov.b32 a1, 0; mov.b32 a2, 0; mov.b32 a3, 0; mov.b32 lo0, 0; mov.b32 lo1, 0; mov.b32 hi0, 0; mov.b32 hi1, 0; mov.b32 h0, 0; mov.b32 h1, 0;\n"
        "wgmma.wait_group.sync.aligned 1;\n"
        "setp.eq.u32 pw, %0, 0;\n"
        "@pw bra.uni HEADE;\n"
        "fma.rn.f16x2 p0, qz0, qz0, c;\n"
        "mul.rn.f16x2 a0, qz0, p0; fma.rn.f16x2 p1, qz1, qz1, c;\n"
        "mov.b32 {xl, xh}, a0; tanh.approx.f16 xr, xl; cvt.u32.u16 lo0, xr; tanh.approx.f16 xr, xh; cvt.u32.u16 hi0, xr; mul.rn.f16x2 a1, qz1, p1; fma.rn.f16x2 p0, qz2, qz2, c;\n"
        "mov.b32 {xl, xh}, a1; tanh.approx.f16 xr, xl; cvt.u32.u16 lo1, xr; tanh.approx.f16 xr, xh; cvt.u32.u16 hi1, xr; mul.rn.f16x2 a2, qz2, p0; fma.rn.f16x2 p1, qz3, qz3, c; prmt.b32 h0, lo0, hi0, 0x5410;\n"
        "mov.b32 {xl, xh}, a2; tanh.approx.f16 xr, xl; cvt.u32.u16 lo0, xr; tanh.approx.f16 xr, xh; cvt.u32.u16 hi0, xr; mul.rn.f16x2 a3, qz3, p1; fma.rn.f16x2 p0, qz4, qz4, c; fma.rn.f16x2 g0, qz0, h0, qz0; prmt.b32 h1, lo1, hi1, 0x5410;\n"
        "mov.b32 {xl, xh}, a3; tanh.approx.f16 xr, xl; cvt.u32.u16 lo1, xr; tanh.approx.f16 xr, xh; cvt.u32.u16 hi1, xr; mul.rn.f16x2 a0, qz4, p0; fma.rn.f16x2 p1, qz5, qz5, c; fma.rn.f16x2 g1, qz1, h1, qz1; prmt.b32 h0, lo0, hi0, 0x5410;\n"
        "mov.b32 {xl, xh}, a0; tanh.approx.f16 xr, xl; cvt.u32.u16 lo0, xr; tanh.approx.f16 xr, xh; cvt.u32.u16 hi0, xr; mul.rn.f16x2 a1, qz5, p1; fma.rn.f16x2 p0, qz6, qz6, c; fma.rn.f16x2 g2, qz2, h0, qz2; prmt.b32 h1, lo1, hi1, 0x5410;\n"
        "mov.b32 {xl, xh}, a1; tanh.approx.f16 xr, xl; cvt.u32.u16 lo1, xr; tanh.approx.f16 xr, xh; cvt.u32.u16 hi1, xr; mul.rn.f16x2 a2, qz6, p0; fma.rn.f16x2 p1, qz7, qz7, c; fma.rn.f16x2 g3, qz3, h1, qz3; prmt.b32 h0, lo0, hi0, 0x5410;\n"
        "HEADE:\n"
        "wgmma.wait_group.sync.aligned 0;\n"
        "bra.uni DONE;\n"
        "SPINY0: mov.u32 cnt, 0;\n"
        "SPINY0L:\n"
        "mbarrier.try_wait.parity.shared::cta.b64 pw, [ybar], 0;\n"
        "@pw bra.uni BACKY0;\n"
        "add.u32 cnt, cnt, 1; setp.lt.u32 pw, cnt, 0x100000;\n"
        "@pw bra.uni SPINY0L;\n"
        "trap;\n"
        "DONE:\n"
        "}\n"
        :: "r"(prm.w1desc), "r"(c.wg), "r"(c.xs), "r"(c.a_offs) : "memory");
}
__device__ __forceinline__ bool pass2_head(const Pass2& c, uint32_t round) {
    uint32_t retry;
    asm volatile(
        "{\n"
        ".reg .b32 t<2>, tt, ad, cnt;\n"
        ".reg .pred pw;\n"
        "and.b32 t0, %3, 0xffff; shr.u32 t1, %3, 16;\n"
        "xor.b32 ad, t0, 0; add.u32 ad, ad, %4; ldmatrix.sync.aligned.m8n8.x4.shared.b16 {qa0,qa1,qa2,qa3}, [ad];\n"
        "xor.b32 ad, t0, 32; add.u32 ad, ad, %4; ldmatrix.sync.aligned.m8n8.x4.shared.b16 {qa4,qa5,qa6,qa7}, [ad];\n"
        "xor.b32 ad, t0, 64; add.u32 ad, ad, %4; ldmatrix.sync.aligned.m8n8.x4.shared.b16 {qa8,qa9,qa10,qa11}, [ad];\n"
        "xor.b32 ad, t0, 96; add.u32 ad, ad, %4; ldmatrix.sync.aligned.m8n8.x4.shared.b16 {qa12,qa13,qa14,qa15}, [ad];\n"
        "xor.b32 ad, t1, 0; add.u32 ad, ad, %4; ldmatrix.sync.aligned.m8n8.x4.shared.b16 {qa16,qa17,qa18,qa19}, [ad];\n"
        "xor.b32 ad, t1, 32; add.u32 ad, ad, %4; ldmatrix.sync.aligned.m8n8.x4.shared.b16 {qa20,qa21,qa22,qa23}, [ad];\n"
        "mov.b32 g4, 0; mov.b32 g5, 0; mov.b32 g6, 0; mov.b32 g7, 0; mov.b32 g8, 0; mov.b32 g9, 0; mov.b32 g10, 0; mov.b32 g11, 0; mov.b32 g12, 0; mov.b32 g13, 0; mov.b32 g14, 0; mov.b32 g15, 0;\n"
        "mov.u32 tt, 231224; mbarrier.try_wait.parity.shared::cta.b64 pw, [tt], %1;\n"
        "@!pw bra.uni SPINR;\n"
        "BACKR:\n"
        "mov.u32 tt, 230792; ld.shared.v2.b32 {osc, %0}, [tt];\n"
        "ld.shared.v4.b32 {o0,o1,o2,o3}, [%2+0];\n"
        "ld.shared.v4.b32 {o4,o5,o6,o7}, [%2+64];\n"
        "ld.shared.v4.b32 {o8,o9,o10,o11}, [%2+128];\n"
        "ld.shared.v4.b32 {o12,o13,o14,o15}, [%2+192];\n"
        "ld.shared.v4.b32 {o16,o17,o18,o19}, [%2+256];\n"
        "ld.shared.v4.b32 {o20,o21,o22,o23}, [%2+320];\n"
        "bra.uni DONE;\n"
        "SPINR: mov.u32 cnt, 0;\n"
        "SPINRL:\n"
        "mov.u32 tt, 231224; mbarrier.try_wait.parity.shared::cta.b64 pw, [tt], %1;\n"
        "@pw bra.uni BACKR;\n"
        "add.u32 cnt, cnt, 1; setp.lt.u32 pw, cnt, 0x100000;\n"
        "@pw bra.uni SPINRL;\n"
        "trap;\n"
        "DONE:\n"
        "}\n"
        : "=r"(retry) : "r"(round), "r"(c.bias_addr), "r"(c.a_offs), "r"(c.xs) : "memory");
    return __any_sync(0xffffffffu, retry);
}
__device__ __forceinline__ void pass2_tiles(const Pass2& c, const Params& prm) {
    asm volatile(
        "{\n"
        ".reg .b32 v<8>, n, off, c, tt, ad, cnt, ybar, xbar, tbar, tpar, id;\n"
        ".reg .b16 xl, xh, xr;\n"
        ".reg .f32 f0, f1;\n"
        ".reg .b64 w1d, w2d, dt, gp, pol;\n"
        ".reg .pred pt, pf, pr, pw, pl, pm, pz, pn;\n"
        "setp.ne.b32 pt, 1, 0; setp.ne.b32 pf, 0, 0; setp.eq.u32 pl, %9, 0; setp.eq.u32 pz, %0, 0;\n"
        "mov.b32 c, 0x40D940D9;\n"
        "mov.b64 w1d, {%0, 0x40000040}; mov.b64 w2d, {%1, 0x80000020};\n"
        "mad.lo.u32 ybar, %2, 8, 230800; mad.lo.u32 xbar, %2, 8, 230832; add.u32 id, %2, 2;\n"
        "mad.lo.u32 tbar, %2, 64, 230888; setp.eq.u32 pr, %2, 0; selp.u32 tpar, 1, 0, pr; mov.u32 tt, %laneid; setp.eq.u32 pn, tt, 0;\n"
        "mov.u32 n, -1; add.u32 off, %3, %8; mov.pred pm, pt; createpolicy.fractional.L2::evict_first.b64 pol, 1.0;\n"
        "LOOP:\n"
        "setp.ge.u32 pr, n, 7;\n"
        "@pr bra.uni SKIP0;\n"
        "wgmma.fence.sync.aligned;\n"
        "add.s64 dt, w1d, 768; wgmma.mma_async.sync.aligned.m64n64k16.f16.f16.f16 {qz16,qz17,qz18,qz19,qz20,qz21,qz22,qz23,qz24,qz25,qz26,qz27,qz28,qz29,qz30,qz31}, {qa0,qa1,qa2,qa3}, dt, pf, 1, 1, 1;\n"
        "add.s64 dt, w1d, 896; wgmma.mma_async.sync.aligned.m64n64k16.f16.f16.f16 {qz16,qz17,qz18,qz19,qz20,qz21,qz22,qz23,qz24,qz25,qz26,qz27,qz28,qz29,qz30,qz31}, {qa4,qa5,qa6,qa7}, dt, pt, 1, 1, 1;\n"
        "add.s64 dt, w1d, 1024; wgmma.mma_async.sync.aligned.m64n64k16.f16.f16.f16 {qz16,qz17,qz18,qz19,qz20,qz21,qz22,qz23,qz24,qz25,qz26,qz27,qz28,qz29,qz30,qz31}, {qa8,qa9,qa10,qa11}, dt, pt, 1, 1, 1;\n"
        "add.s64 dt, w1d, 1152; wgmma.mma_async.sync.aligned.m64n64k16.f16.f16.f16 {qz16,qz17,qz18,qz19,qz20,qz21,qz22,qz23,qz24,qz25,qz26,qz27,qz28,qz29,qz30,qz31}, {qa12,qa13,qa14,qa15}, dt, pt, 1, 1, 1;\n"
        "add.s64 dt, w1d, 1280; wgmma.mma_async.sync.aligned.m64n64k16.f16.f16.f16 {qz16,qz17,qz18,qz19,qz20,qz21,qz22,qz23,qz24,qz25,qz26,qz27,qz28,qz29,qz30,qz31}, {qa16,qa17,qa18,qa19}, dt, pt, 1, 1, 1;\n"
        "add.s64 dt, w1d, 1408; wgmma.mma_async.sync.aligned.m64n64k16.f16.f16.f16 {qz16,qz17,qz18,qz19,qz20,qz21,qz22,qz23,qz24,qz25,qz26,qz27,qz28,qz29,qz30,qz31}, {qa20,qa21,qa22,qa23}, dt, pt, 1, 1, 1;\n"
        "SKIP0:\n"
        "setp.lt.s32 pr, n, 0;\n"
        "@pr bra.uni FIRST;\n"
        "and.b32 tt, n, 1; mbarrier.try_wait.parity.shared::cta.b64 pw, [xbar], tt;\n"
        "@!pw bra.uni SPINX;\n"
        "BACKX:\n"
        "and.b32 ad, %6, 0xffff; add.u32 ad, ad, %4; ld.shared.v4.b32 {v0,v1,v2,v3}, [ad+0];\n"
        "shr.u32 ad, %6, 16; add.u32 ad, ad, %4; ld.shared.v4.b32 {v4,v5,v6,v7}, [ad+0];\n"
        "mov.b32 {xl, xh}, o0; cvt.f32.f16 f0, xl; cvt.f32.f16 f1, xh; cvt.rn.bf16x2.f32 tt, f1, f0; fma.rn.bf16x2 v0, tt, osc, v0;\n"
        "mov.b32 {xl, xh}, o2; cvt.f32.f16 f0, xl; cvt.f32.f16 f1, xh; cvt.rn.bf16x2.f32 tt, f1, f0; fma.rn.bf16x2 v1, tt, osc, v1;\n"
        "mov.b32 {xl, xh}, o4; cvt.f32.f16 f0, xl; cvt.f32.f16 f1, xh; cvt.rn.bf16x2.f32 tt, f1, f0; fma.rn.bf16x2 v2, tt, osc, v2;\n"
        "mov.b32 {xl, xh}, o6; cvt.f32.f16 f0, xl; cvt.f32.f16 f1, xh; cvt.rn.bf16x2.f32 tt, f1, f0; fma.rn.bf16x2 v3, tt, osc, v3;\n"
        "and.b32 ad, %6, 0xffff; add.u32 ad, ad, %4; st.shared.v4.b32 [ad+0], {v0,v1,v2,v3};\n"
        "and.b32 ad, %6, 0xffff; add.u32 ad, ad, %4; ld.shared.v4.b32 {v0,v1,v2,v3}, [ad+64];\n"
        "mov.b32 {xl, xh}, o1; cvt.f32.f16 f0, xl; cvt.f32.f16 f1, xh; cvt.rn.bf16x2.f32 tt, f1, f0; fma.rn.bf16x2 v4, tt, osc, v4;\n"
        "mov.b32 {xl, xh}, o3; cvt.f32.f16 f0, xl; cvt.f32.f16 f1, xh; cvt.rn.bf16x2.f32 tt, f1, f0; fma.rn.bf16x2 v5, tt, osc, v5;\n"
        "mov.b32 {xl, xh}, o5; cvt.f32.f16 f0, xl; cvt.f32.f16 f1, xh; cvt.rn.bf16x2.f32 tt, f1, f0; fma.rn.bf16x2 v6, tt, osc, v6;\n"
        "mov.b32 {xl, xh}, o7; cvt.f32.f16 f0, xl; cvt.f32.f16 f1, xh; cvt.rn.bf16x2.f32 tt, f1, f0; fma.rn.bf16x2 v7, tt, osc, v7;\n"
        "shr.u32 ad, %6, 16; add.u32 ad, ad, %4; st.shared.v4.b32 [ad+0], {v4,v5,v6,v7};\n"
        "shr.u32 ad, %6, 16; add.u32 ad, ad, %4; ld.shared.v4.b32 {v4,v5,v6,v7}, [ad+64];\n"
        "ld.shared.v4.b32 {o0,o1,o2,o3}, [%7+0];\n"
        "ld.shared.v4.b32 {o4,o5,o6,o7}, [%7+64];\n"
        "mov.b32 {xl, xh}, o8; cvt.f32.f16 f0, xl; cvt.f32.f16 f1, xh; cvt.rn.bf16x2.f32 tt, f1, f0; fma.rn.bf16x2 v0, tt, osc, v0;\n"
        "mov.b32 {xl, xh}, o10; cvt.f32.f16 f0, xl; cvt.f32.f16 f1, xh; cvt.rn.bf16x2.f32 tt, f1, f0; fma.rn.bf16x2 v1, tt, osc, v1;\n"
        "mov.b32 {xl, xh}, o12; cvt.f32.f16 f0, xl; cvt.f32.f16 f1, xh; cvt.rn.bf16x2.f32 tt, f1, f0; fma.rn.bf16x2 v2, tt, osc, v2;\n"
        "mov.b32 {xl, xh}, o14; cvt.f32.f16 f0, xl; cvt.f32.f16 f1, xh; cvt.rn.bf16x2.f32 tt, f1, f0; fma.rn.bf16x2 v3, tt, osc, v3;\n"
        "and.b32 ad, %6, 0xffff; add.u32 ad, ad, %4; st.shared.v4.b32 [ad+64], {v0,v1,v2,v3};\n"
        "and.b32 ad, %6, 0xffff; add.u32 ad, ad, %4; ld.shared.v4.b32 {v0,v1,v2,v3}, [ad+128];\n"
        "mov.b32 {xl, xh}, o9; cvt.f32.f16 f0, xl; cvt.f32.f16 f1, xh; cvt.rn.bf16x2.f32 tt, f1, f0; fma.rn.bf16x2 v4, tt, osc, v4;\n"
        "mov.b32 {xl, xh}, o11; cvt.f32.f16 f0, xl; cvt.f32.f16 f1, xh; cvt.rn.bf16x2.f32 tt, f1, f0; fma.rn.bf16x2 v5, tt, osc, v5;\n"
        "mov.b32 {xl, xh}, o13; cvt.f32.f16 f0, xl; cvt.f32.f16 f1, xh; cvt.rn.bf16x2.f32 tt, f1, f0; fma.rn.bf16x2 v6, tt, osc, v6;\n"
        "mov.b32 {xl, xh}, o15; cvt.f32.f16 f0, xl; cvt.f32.f16 f1, xh; cvt.rn.bf16x2.f32 tt, f1, f0; fma.rn.bf16x2 v7, tt, osc, v7;\n"
        "shr.u32 ad, %6, 16; add.u32 ad, ad, %4; st.shared.v4.b32 [ad+64], {v4,v5,v6,v7};\n"
        "shr.u32 ad, %6, 16; add.u32 ad, ad, %4; ld.shared.v4.b32 {v4,v5,v6,v7}, [ad+128];\n"
        "ld.shared.v4.b32 {o8,o9,o10,o11}, [%7+128];\n"
        "ld.shared.v4.b32 {o12,o13,o14,o15}, [%7+192];\n"
        "mov.b32 {xl, xh}, o16; cvt.f32.f16 f0, xl; cvt.f32.f16 f1, xh; cvt.rn.bf16x2.f32 tt, f1, f0; fma.rn.bf16x2 v0, tt, osc, v0;\n"
        "mov.b32 {xl, xh}, o18; cvt.f32.f16 f0, xl; cvt.f32.f16 f1, xh; cvt.rn.bf16x2.f32 tt, f1, f0; fma.rn.bf16x2 v1, tt, osc, v1;\n"
        "mov.b32 {xl, xh}, o20; cvt.f32.f16 f0, xl; cvt.f32.f16 f1, xh; cvt.rn.bf16x2.f32 tt, f1, f0; fma.rn.bf16x2 v2, tt, osc, v2;\n"
        "mov.b32 {xl, xh}, o22; cvt.f32.f16 f0, xl; cvt.f32.f16 f1, xh; cvt.rn.bf16x2.f32 tt, f1, f0; fma.rn.bf16x2 v3, tt, osc, v3;\n"
        "and.b32 ad, %6, 0xffff; add.u32 ad, ad, %4; st.shared.v4.b32 [ad+128], {v0,v1,v2,v3};\n"
        "mov.b32 {xl, xh}, o17; cvt.f32.f16 f0, xl; cvt.f32.f16 f1, xh; cvt.rn.bf16x2.f32 tt, f1, f0; fma.rn.bf16x2 v4, tt, osc, v4;\n"
        "mov.b32 {xl, xh}, o19; cvt.f32.f16 f0, xl; cvt.f32.f16 f1, xh; cvt.rn.bf16x2.f32 tt, f1, f0; fma.rn.bf16x2 v5, tt, osc, v5;\n"
        "mov.b32 {xl, xh}, o21; cvt.f32.f16 f0, xl; cvt.f32.f16 f1, xh; cvt.rn.bf16x2.f32 tt, f1, f0; fma.rn.bf16x2 v6, tt, osc, v6;\n"
        "mov.b32 {xl, xh}, o23; cvt.f32.f16 f0, xl; cvt.f32.f16 f1, xh; cvt.rn.bf16x2.f32 tt, f1, f0; fma.rn.bf16x2 v7, tt, osc, v7;\n"
        "shr.u32 ad, %6, 16; add.u32 ad, ad, %4; st.shared.v4.b32 [ad+128], {v4,v5,v6,v7};\n"
        "ld.shared.v4.b32 {o16,o17,o18,o19}, [%7+256];\n"
        "ld.shared.v4.b32 {o20,o21,o22,o23}, [%7+320];\n"
        "FIRST:\n"
        "@pz bra.uni B7;\n"
        "mov.b32 {xl, xh}, a2; tanh.approx.f16 xr, xl; cvt.u32.u16 lo0, xr; tanh.approx.f16 xr, xh; cvt.u32.u16 hi0, xr; mul.rn.f16x2 a3, qz7, p1; fma.rn.f16x2 p0, qz8, qz8, c; fma.rn.f16x2 g4, qz4, h0, qz4; prmt.b32 h1, lo1, hi1, 0x5410;\n"
        "B7:\n"
        "fence.proxy.async.shared::cta;\n"
        "add.u32 tt, id, 4;\n"
        "@pl bra.uni STORE;\n"
        "bar.arrive tt, 128;\n"
        "STOREB:\n"
        ASM_MARK
        "@!pm bra.uni DONE;\n"
        "add.s32 n, n, 1; sub.u32 off, off, %8; setp.lt.s32 pm, n, 7;\n"
        "@pz bra.uni B10;\n"
        "mov.b32 {xl, xh}, a3; tanh.approx.f16 xr, xl; cvt.u32.u16 lo1, xr; tanh.approx.f16 xr, xh; cvt.u32.u16 hi1, xr; mul.rn.f16x2 a0, qz8, p0; fma.rn.f16x2 p1, qz9, qz9, c; fma.rn.f16x2 g5, qz5, h1, qz5; prmt.b32 h0, lo0, hi0, 0x5410;\n"
        "mov.b32 {xl, xh}, a0; tanh.approx.f16 xr, xl; cvt.u32.u16 lo0, xr; tanh.approx.f16 xr, xh; cvt.u32.u16 hi0, xr; mul.rn.f16x2 a1, qz9, p1; fma.rn.f16x2 p0, qz10, qz10, c; fma.rn.f16x2 g6, qz6, h0, qz6; prmt.b32 h1, lo1, hi1, 0x5410;\n"
        "mov.b32 {xl, xh}, a1; tanh.approx.f16 xr, xl; cvt.u32.u16 lo1, xr; tanh.approx.f16 xr, xh; cvt.u32.u16 hi1, xr; mul.rn.f16x2 a2, qz10, p0; fma.rn.f16x2 p1, qz11, qz11, c; fma.rn.f16x2 g7, qz7, h1, qz7; prmt.b32 h0, lo0, hi0, 0x5410;\n"
        "B10:\n"
        "setp.eq.s32 pr, n, 0;\n"
        "@pr bra.uni SPINW0;\n"
        "BACKW0:\n"
        "wgmma.fence.sync.aligned;\n"
        "add.s64 dt, w2d, 0; wgmma.mma_async.sync.aligned.m64n96k16.f16.f16.f16 {o0,o1,o2,o3,o4,o5,o6,o7,o8,o9,o10,o11,o12,o13,o14,o15,o16,o17,o18,o19,o20,o21,o22,o23}, {g0,g1,g2,g3}, dt, pt, 1, 1, 1;\n"
        "add.s64 dt, w2d, 64; wgmma.mma_async.sync.aligned.m64n96k16.f16.f16.f16 {o0,o1,o2,o3,o4,o5,o6,o7,o8,o9,o10,o11,o12,o13,o14,o15,o16,o17,o18,o19,o20,o21,o22,o23}, {g4,g5,g6,g7}, dt, pt, 1, 1, 1;\n"
        "wgmma.commit_group.sync.aligned;\n"
        "@pz bra.uni B14;\n"
        "mov.b32 {xl, xh}, a2; tanh.approx.f16 xr, xl; cvt.u32.u16 lo0, xr; tanh.approx.f16 xr, xh; cvt.u32.u16 hi0, xr; mul.rn.f16x2 a3, qz11, p1; fma.rn.f16x2 p0, qz12, qz12, c; fma.rn.f16x2 g8, qz8, h0, qz8; prmt.b32 h1, lo1, hi1, 0x5410;\n"
        "mov.b32 {xl, xh}, a3; tanh.approx.f16 xr, xl; cvt.u32.u16 lo1, xr; tanh.approx.f16 xr, xh; cvt.u32.u16 hi1, xr; mul.rn.f16x2 a0, qz12, p0; fma.rn.f16x2 p1, qz13, qz13, c; fma.rn.f16x2 g9, qz9, h1, qz9; prmt.b32 h0, lo0, hi0, 0x5410;\n"
        "mov.b32 {xl, xh}, a0; tanh.approx.f16 xr, xl; cvt.u32.u16 lo0, xr; tanh.approx.f16 xr, xh; cvt.u32.u16 hi0, xr; mul.rn.f16x2 a1, qz13, p1; fma.rn.f16x2 p0, qz14, qz14, c; fma.rn.f16x2 g10, qz10, h0, qz10; prmt.b32 h1, lo1, hi1, 0x5410;\n"
        "mov.b32 {xl, xh}, a1; tanh.approx.f16 xr, xl; cvt.u32.u16 lo1, xr; tanh.approx.f16 xr, xh; cvt.u32.u16 hi1, xr; mul.rn.f16x2 a2, qz14, p0; fma.rn.f16x2 p1, qz15, qz15, c; fma.rn.f16x2 g11, qz11, h1, qz11; prmt.b32 h0, lo0, hi0, 0x5410;\n"
        "B14:\n"
        "wgmma.wait_group.sync.aligned 0;\n"
        "wgmma.fence.sync.aligned;\n"
        "add.s64 dt, w2d, 128; wgmma.mma_async.sync.aligned.m64n96k16.f16.f16.f16 {o0,o1,o2,o3,o4,o5,o6,o7,o8,o9,o10,o11,o12,o13,o14,o15,o16,o17,o18,o19,o20,o21,o22,o23}, {g8,g9,g10,g11}, dt, pt, 1, 1, 1;\n"
        "wgmma.commit_group.sync.aligned;\n"
        "@pz bra.uni B18;\n"
        "mov.b32 {xl, xh}, a2; tanh.approx.f16 xr, xl; cvt.u32.u16 lo0, xr; tanh.approx.f16 xr, xh; cvt.u32.u16 hi0, xr; mul.rn.f16x2 a3, qz15, p1; fma.rn.f16x2 p0, qz16, qz16, c; fma.rn.f16x2 g12, qz12, h0, qz12; prmt.b32 h1, lo1, hi1, 0x5410;\n"
        "mov.b32 {xl, xh}, a3; tanh.approx.f16 xr, xl; cvt.u32.u16 lo1, xr; tanh.approx.f16 xr, xh; cvt.u32.u16 hi1, xr; mul.rn.f16x2 a0, qz16, p0; fma.rn.f16x2 p1, qz17, qz17, c; fma.rn.f16x2 g13, qz13, h1, qz13; prmt.b32 h0, lo0, hi0, 0x5410;\n"
        "mov.b32 {xl, xh}, a0; tanh.approx.f16 xr, xl; cvt.u32.u16 lo0, xr; tanh.approx.f16 xr, xh; cvt.u32.u16 hi0, xr; mul.rn.f16x2 a1, qz17, p1; fma.rn.f16x2 p0, qz18, qz18, c; fma.rn.f16x2 g14, qz14, h0, qz14; prmt.b32 h1, lo1, hi1, 0x5410;\n"
        "mov.b32 {xl, xh}, a1; tanh.approx.f16 xr, xl; cvt.u32.u16 lo1, xr; tanh.approx.f16 xr, xh; cvt.u32.u16 hi1, xr; mul.rn.f16x2 a2, qz18, p0; fma.rn.f16x2 p1, qz19, qz19, c; fma.rn.f16x2 g15, qz15, h1, qz15; prmt.b32 h0, lo0, hi0, 0x5410;\n"
        "B18:\n"
        "mad.lo.u32 tt, n, 8, tbar; mbarrier.try_wait.parity.shared::cta.b64 pw, [tt], tpar;\n"
        "@!pw bra.uni SPINT;\n"
        "BACKT:\n"
        "wgmma.fence.sync.aligned;\n"
        "add.s64 dt, w2d, 192; wgmma.mma_async.sync.aligned.m64n96k16.f16.f16.f16 {o0,o1,o2,o3,o4,o5,o6,o7,o8,o9,o10,o11,o12,o13,o14,o15,o16,o17,o18,o19,o20,o21,o22,o23}, {g12,g13,g14,g15}, dt, pt, 1, 1, 1;\n"
        "add.s64 dt, w1d, 1536; wgmma.mma_async.sync.aligned.m64n64k16.f16.f16.f16 {qz0,qz1,qz2,qz3,qz4,qz5,qz6,qz7,qz8,qz9,qz10,qz11,qz12,qz13,qz14,qz15}, {qa0,qa1,qa2,qa3}, dt, pf, 1, 1, 1;\n"
        "add.s64 dt, w1d, 1664; wgmma.mma_async.sync.aligned.m64n64k16.f16.f16.f16 {qz0,qz1,qz2,qz3,qz4,qz5,qz6,qz7,qz8,qz9,qz10,qz11,qz12,qz13,qz14,qz15}, {qa4,qa5,qa6,qa7}, dt, pt, 1, 1, 1;\n"
        "add.s64 dt, w1d, 1792; wgmma.mma_async.sync.aligned.m64n64k16.f16.f16.f16 {qz0,qz1,qz2,qz3,qz4,qz5,qz6,qz7,qz8,qz9,qz10,qz11,qz12,qz13,qz14,qz15}, {qa8,qa9,qa10,qa11}, dt, pt, 1, 1, 1;\n"
        "wgmma.commit_group.sync.aligned;\n"
        "@pl bra.uni YLOAD;\n"
        "YLOADB:\n"
        "@pz bra.uni B22;\n"
        "mov.b32 {xl, xh}, a2; tanh.approx.f16 xr, xl; cvt.u32.u16 lo0, xr; tanh.approx.f16 xr, xh; cvt.u32.u16 hi0, xr; mul.rn.f16x2 a3, qz19, p1; fma.rn.f16x2 p0, qz20, qz20, c; fma.rn.f16x2 g0, qz16, h0, qz16; prmt.b32 h1, lo1, hi1, 0x5410;\n"
        "mov.b32 {xl, xh}, a3; tanh.approx.f16 xr, xl; cvt.u32.u16 lo1, xr; tanh.approx.f16 xr, xh; cvt.u32.u16 hi1, xr; mul.rn.f16x2 a0, qz20, p0; fma.rn.f16x2 p1, qz21, qz21, c; fma.rn.f16x2 g1, qz17, h1, qz17; prmt.b32 h0, lo0, hi0, 0x5410;\n"
        "mov.b32 {xl, xh}, a0; tanh.approx.f16 xr, xl; cvt.u32.u16 lo0, xr; tanh.approx.f16 xr, xh; cvt.u32.u16 hi0, xr; mul.rn.f16x2 a1, qz21, p1; fma.rn.f16x2 p0, qz22, qz22, c; fma.rn.f16x2 g2, qz18, h0, qz18; prmt.b32 h1, lo1, hi1, 0x5410;\n"
        "mov.b32 {xl, xh}, a1; tanh.approx.f16 xr, xl; cvt.u32.u16 lo1, xr; tanh.approx.f16 xr, xh; cvt.u32.u16 hi1, xr; mul.rn.f16x2 a2, qz22, p0; fma.rn.f16x2 p1, qz23, qz23, c; fma.rn.f16x2 g3, qz19, h1, qz19; prmt.b32 h0, lo0, hi0, 0x5410;\n"
        "B22:\n"
        "wgmma.fence.sync.aligned;\n"
        "add.s64 dt, w1d, 1920; wgmma.mma_async.sync.aligned.m64n64k16.f16.f16.f16 {qz0,qz1,qz2,qz3,qz4,qz5,qz6,qz7,qz8,qz9,qz10,qz11,qz12,qz13,qz14,qz15}, {qa12,qa13,qa14,qa15}, dt, pt, 1, 1, 1;\n"
        "add.s64 dt, w1d, 2048; wgmma.mma_async.sync.aligned.m64n64k16.f16.f16.f16 {qz0,qz1,qz2,qz3,qz4,qz5,qz6,qz7,qz8,qz9,qz10,qz11,qz12,qz13,qz14,qz15}, {qa16,qa17,qa18,qa19}, dt, pt, 1, 1, 1;\n"
        "add.s64 dt, w1d, 2176; wgmma.mma_async.sync.aligned.m64n64k16.f16.f16.f16 {qz0,qz1,qz2,qz3,qz4,qz5,qz6,qz7,qz8,qz9,qz10,qz11,qz12,qz13,qz14,qz15}, {qa20,qa21,qa22,qa23}, dt, pt, 1, 1, 1;\n"
        "wgmma.commit_group.sync.aligned;\n"
        "@pz bra.uni B26;\n"
        "mov.b32 {xl, xh}, a2; tanh.approx.f16 xr, xl; cvt.u32.u16 lo0, xr; tanh.approx.f16 xr, xh; cvt.u32.u16 hi0, xr; mul.rn.f16x2 a3, qz23, p1; fma.rn.f16x2 p0, qz24, qz24, c; fma.rn.f16x2 g4, qz20, h0, qz20; prmt.b32 h1, lo1, hi1, 0x5410;\n"
        "mov.b32 {xl, xh}, a3; tanh.approx.f16 xr, xl; cvt.u32.u16 lo1, xr; tanh.approx.f16 xr, xh; cvt.u32.u16 hi1, xr; mul.rn.f16x2 a0, qz24, p0; fma.rn.f16x2 p1, qz25, qz25, c; fma.rn.f16x2 g5, qz21, h1, qz21; prmt.b32 h0, lo0, hi0, 0x5410;\n"
        "mov.b32 {xl, xh}, a0; tanh.approx.f16 xr, xl; cvt.u32.u16 lo0, xr; tanh.approx.f16 xr, xh; cvt.u32.u16 hi0, xr; mul.rn.f16x2 a1, qz25, p1; fma.rn.f16x2 p0, qz26, qz26, c; fma.rn.f16x2 g6, qz22, h0, qz22; prmt.b32 h1, lo1, hi1, 0x5410;\n"
        "mov.b32 {xl, xh}, a1; tanh.approx.f16 xr, xl; cvt.u32.u16 lo1, xr; tanh.approx.f16 xr, xh; cvt.u32.u16 hi1, xr; mul.rn.f16x2 a2, qz26, p0; fma.rn.f16x2 p1, qz27, qz27, c; fma.rn.f16x2 g7, qz23, h1, qz23; prmt.b32 h0, lo0, hi0, 0x5410;\n"
        "B26:\n"
        "wgmma.wait_group.sync.aligned 2;\n"
        "wgmma.fence.sync.aligned;\n"
        "add.s64 dt, w2d, 256; wgmma.mma_async.sync.aligned.m64n96k16.f16.f16.f16 {o0,o1,o2,o3,o4,o5,o6,o7,o8,o9,o10,o11,o12,o13,o14,o15,o16,o17,o18,o19,o20,o21,o22,o23}, {g0,g1,g2,g3}, dt, pt, 1, 1, 1;\n"
        "add.s64 dt, w2d, 320; wgmma.mma_async.sync.aligned.m64n96k16.f16.f16.f16 {o0,o1,o2,o3,o4,o5,o6,o7,o8,o9,o10,o11,o12,o13,o14,o15,o16,o17,o18,o19,o20,o21,o22,o23}, {g4,g5,g6,g7}, dt, pt, 1, 1, 1;\n"
        "wgmma.commit_group.sync.aligned;\n"
        "@pz bra.uni B30;\n"
        "mov.b32 {xl, xh}, a2; tanh.approx.f16 xr, xl; cvt.u32.u16 lo0, xr; tanh.approx.f16 xr, xh; cvt.u32.u16 hi0, xr; mul.rn.f16x2 a3, qz27, p1; fma.rn.f16x2 p0, qz28, qz28, c; fma.rn.f16x2 g8, qz24, h0, qz24; prmt.b32 h1, lo1, hi1, 0x5410;\n"
        "mov.b32 {xl, xh}, a3; tanh.approx.f16 xr, xl; cvt.u32.u16 lo1, xr; tanh.approx.f16 xr, xh; cvt.u32.u16 hi1, xr; mul.rn.f16x2 a0, qz28, p0; fma.rn.f16x2 p1, qz29, qz29, c; fma.rn.f16x2 g9, qz25, h1, qz25; prmt.b32 h0, lo0, hi0, 0x5410;\n"
        "mov.b32 {xl, xh}, a0; tanh.approx.f16 xr, xl; cvt.u32.u16 lo0, xr; tanh.approx.f16 xr, xh; cvt.u32.u16 hi0, xr; mul.rn.f16x2 a1, qz29, p1; fma.rn.f16x2 p0, qz30, qz30, c; fma.rn.f16x2 g10, qz26, h0, qz26; prmt.b32 h1, lo1, hi1, 0x5410;\n"
        "mov.b32 {xl, xh}, a1; tanh.approx.f16 xr, xl; cvt.u32.u16 lo1, xr; tanh.approx.f16 xr, xh; cvt.u32.u16 hi1, xr; mul.rn.f16x2 a2, qz30, p0; fma.rn.f16x2 p1, qz31, qz31, c; fma.rn.f16x2 g11, qz27, h1, qz27; prmt.b32 h0, lo0, hi0, 0x5410;\n"
        "B30:\n"
        "wgmma.wait_group.sync.aligned 1;\n"
        "wgmma.fence.sync.aligned;\n"
        "add.s64 dt, w2d, 384; wgmma.mma_async.sync.aligned.m64n96k16.f16.f16.f16 {o0,o1,o2,o3,o4,o5,o6,o7,o8,o9,o10,o11,o12,o13,o14,o15,o16,o17,o18,o19,o20,o21,o22,o23}, {g8,g9,g10,g11}, dt, pt, 1, 1, 1;\n"
        "wgmma.commit_group.sync.aligned;\n"
        "@pz bra.uni B34;\n"
        "mov.b32 {xl, xh}, a2; tanh.approx.f16 xr, xl; cvt.u32.u16 lo0, xr; tanh.approx.f16 xr, xh; cvt.u32.u16 hi0, xr; mul.rn.f16x2 a3, qz31, p1; fma.rn.f16x2 p0, qz0, qz0, c; fma.rn.f16x2 g12, qz28, h0, qz28; prmt.b32 h1, lo1, hi1, 0x5410;\n"
        "mov.b32 {xl, xh}, a3; tanh.approx.f16 xr, xl; cvt.u32.u16 lo1, xr; tanh.approx.f16 xr, xh; cvt.u32.u16 hi1, xr; mul.rn.f16x2 a0, qz0, p0; fma.rn.f16x2 p1, qz1, qz1, c; fma.rn.f16x2 g13, qz29, h1, qz29; prmt.b32 h0, lo0, hi0, 0x5410;\n"
        "mov.b32 {xl, xh}, a0; tanh.approx.f16 xr, xl; cvt.u32.u16 lo0, xr; tanh.approx.f16 xr, xh; cvt.u32.u16 hi0, xr; mul.rn.f16x2 a1, qz1, p1; fma.rn.f16x2 p0, qz2, qz2, c; fma.rn.f16x2 g14, qz30, h0, qz30; prmt.b32 h1, lo1, hi1, 0x5410;\n"
        "mov.b32 {xl, xh}, a1; tanh.approx.f16 xr, xl; cvt.u32.u16 lo1, xr; tanh.approx.f16 xr, xh; cvt.u32.u16 hi1, xr; mul.rn.f16x2 a2, qz2, p0; fma.rn.f16x2 p1, qz3, qz3, c; fma.rn.f16x2 g15, qz31, h1, qz31; prmt.b32 h0, lo0, hi0, 0x5410;\n"
        "B34:\n"
        "wgmma.wait_group.sync.aligned 1;\n"
        "wgmma.fence.sync.aligned;\n"
        "add.s64 dt, w2d, 448; wgmma.mma_async.sync.aligned.m64n96k16.f16.f16.f16 {o0,o1,o2,o3,o4,o5,o6,o7,o8,o9,o10,o11,o12,o13,o14,o15,o16,o17,o18,o19,o20,o21,o22,o23}, {g12,g13,g14,g15}, dt, pt, 1, 1, 1;\n"
        "add.s64 dt, w1d, 2304; wgmma.mma_async.sync.aligned.m64n64k16.f16.f16.f16 {qz16,qz17,qz18,qz19,qz20,qz21,qz22,qz23,qz24,qz25,qz26,qz27,qz28,qz29,qz30,qz31}, {qa0,qa1,qa2,qa3}, dt, pf, 1, 1, 1;\n"
        "add.s64 dt, w1d, 2432; wgmma.mma_async.sync.aligned.m64n64k16.f16.f16.f16 {qz16,qz17,qz18,qz19,qz20,qz21,qz22,qz23,qz24,qz25,qz26,qz27,qz28,qz29,qz30,qz31}, {qa4,qa5,qa6,qa7}, dt, pt, 1, 1, 1;\n"
        "add.s64 dt, w1d, 2560; wgmma.mma_async.sync.aligned.m64n64k16.f16.f16.f16 {qz16,qz17,qz18,qz19,qz20,qz21,qz22,qz23,qz24,qz25,qz26,qz27,qz28,qz29,qz30,qz31}, {qa8,qa9,qa10,qa11}, dt, pt, 1, 1, 1;\n"
        "wgmma.commit_group.sync.aligned;\n"
        "@pz bra.uni B38;\n"
        "mov.b32 {xl, xh}, a2; tanh.approx.f16 xr, xl; cvt.u32.u16 lo0, xr; tanh.approx.f16 xr, xh; cvt.u32.u16 hi0, xr; mul.rn.f16x2 a3, qz3, p1; fma.rn.f16x2 p0, qz4, qz4, c; fma.rn.f16x2 g0, qz0, h0, qz0; prmt.b32 h1, lo1, hi1, 0x5410;\n"
        "mov.b32 {xl, xh}, a3; tanh.approx.f16 xr, xl; cvt.u32.u16 lo1, xr; tanh.approx.f16 xr, xh; cvt.u32.u16 hi1, xr; mul.rn.f16x2 a0, qz4, p0; fma.rn.f16x2 p1, qz5, qz5, c; fma.rn.f16x2 g1, qz1, h1, qz1; prmt.b32 h0, lo0, hi0, 0x5410;\n"
        "mov.b32 {xl, xh}, a0; tanh.approx.f16 xr, xl; cvt.u32.u16 lo0, xr; tanh.approx.f16 xr, xh; cvt.u32.u16 hi0, xr; mul.rn.f16x2 a1, qz5, p1; fma.rn.f16x2 p0, qz6, qz6, c; fma.rn.f16x2 g2, qz2, h0, qz2; prmt.b32 h1, lo1, hi1, 0x5410;\n"
        "mov.b32 {xl, xh}, a1; tanh.approx.f16 xr, xl; cvt.u32.u16 lo1, xr; tanh.approx.f16 xr, xh; cvt.u32.u16 hi1, xr; mul.rn.f16x2 a2, qz6, p0; fma.rn.f16x2 p1, qz7, qz7, c; fma.rn.f16x2 g3, qz3, h1, qz3; prmt.b32 h0, lo0, hi0, 0x5410;\n"
        "B38:\n"
        "wgmma.fence.sync.aligned;\n"
        "add.s64 dt, w1d, 2688; wgmma.mma_async.sync.aligned.m64n64k16.f16.f16.f16 {qz16,qz17,qz18,qz19,qz20,qz21,qz22,qz23,qz24,qz25,qz26,qz27,qz28,qz29,qz30,qz31}, {qa12,qa13,qa14,qa15}, dt, pt, 1, 1, 1;\n"
        "add.s64 dt, w1d, 2816; wgmma.mma_async.sync.aligned.m64n64k16.f16.f16.f16 {qz16,qz17,qz18,qz19,qz20,qz21,qz22,qz23,qz24,qz25,qz26,qz27,qz28,qz29,qz30,qz31}, {qa16,qa17,qa18,qa19}, dt, pt, 1, 1, 1;\n"
        "add.s64 dt, w1d, 2944; wgmma.mma_async.sync.aligned.m64n64k16.f16.f16.f16 {qz16,qz17,qz18,qz19,qz20,qz21,qz22,qz23,qz24,qz25,qz26,qz27,qz28,qz29,qz30,qz31}, {qa20,qa21,qa22,qa23}, dt, pt, 1, 1, 1;\n"
        "wgmma.commit_group.sync.aligned;\n"
        "@pz bra.uni B42;\n"
        "mov.b32 {xl, xh}, a2; tanh.approx.f16 xr, xl; cvt.u32.u16 lo0, xr; tanh.approx.f16 xr, xh; cvt.u32.u16 hi0, xr; mul.rn.f16x2 a3, qz7, p1; fma.rn.f16x2 p0, qz8, qz8, c; fma.rn.f16x2 g4, qz4, h0, qz4; prmt.b32 h1, lo1, hi1, 0x5410;\n"
        "mov.b32 {xl, xh}, a3; tanh.approx.f16 xr, xl; cvt.u32.u16 lo1, xr; tanh.approx.f16 xr, xh; cvt.u32.u16 hi1, xr; mul.rn.f16x2 a0, qz8, p0; fma.rn.f16x2 p1, qz9, qz9, c; fma.rn.f16x2 g5, qz5, h1, qz5; prmt.b32 h0, lo0, hi0, 0x5410;\n"
        "mov.b32 {xl, xh}, a0; tanh.approx.f16 xr, xl; cvt.u32.u16 lo0, xr; tanh.approx.f16 xr, xh; cvt.u32.u16 hi0, xr; mul.rn.f16x2 a1, qz9, p1; fma.rn.f16x2 p0, qz10, qz10, c; fma.rn.f16x2 g6, qz6, h0, qz6; prmt.b32 h1, lo1, hi1, 0x5410;\n"
        "mov.b32 {xl, xh}, a1; tanh.approx.f16 xr, xl; cvt.u32.u16 lo1, xr; tanh.approx.f16 xr, xh; cvt.u32.u16 hi1, xr; mul.rn.f16x2 a2, qz10, p0; fma.rn.f16x2 p1, qz11, qz11, c; fma.rn.f16x2 g7, qz7, h1, qz7; prmt.b32 h0, lo0, hi0, 0x5410;\n"
        "B42:\n"
        "wgmma.wait_group.sync.aligned 2;\n"
        "setp.eq.s32 pr, n, 0;\n"
        "@pr bra.uni SPINW1;\n"
        "BACKW1:\n"
        "wgmma.fence.sync.aligned;\n"
        "add.s64 dt, w2d, 512; wgmma.mma_async.sync.aligned.m64n96k16.f16.f16.f16 {o0,o1,o2,o3,o4,o5,o6,o7,o8,o9,o10,o11,o12,o13,o14,o15,o16,o17,o18,o19,o20,o21,o22,o23}, {g0,g1,g2,g3}, dt, pt, 1, 1, 1;\n"
        "add.s64 dt, w2d, 576; wgmma.mma_async.sync.aligned.m64n96k16.f16.f16.f16 {o0,o1,o2,o3,o4,o5,o6,o7,o8,o9,o10,o11,o12,o13,o14,o15,o16,o17,o18,o19,o20,o21,o22,o23}, {g4,g5,g6,g7}, dt, pt, 1, 1, 1;\n"
        "wgmma.commit_group.sync.aligned;\n"
        "@pz bra.uni B46;\n"
        "mov.b32 {xl, xh}, a2; tanh.approx.f16 xr, xl; cvt.u32.u16 lo0, xr; tanh.approx.f16 xr, xh; cvt.u32.u16 hi0, xr; mul.rn.f16x2 a3, qz11, p1; fma.rn.f16x2 p0, qz12, qz12, c; fma.rn.f16x2 g8, qz8, h0, qz8; prmt.b32 h1, lo1, hi1, 0x5410;\n"
        "mov.b32 {xl, xh}, a3; tanh.approx.f16 xr, xl; cvt.u32.u16 lo1, xr; tanh.approx.f16 xr, xh; cvt.u32.u16 hi1, xr; mul.rn.f16x2 a0, qz12, p0; fma.rn.f16x2 p1, qz13, qz13, c; fma.rn.f16x2 g9, qz9, h1, qz9; prmt.b32 h0, lo0, hi0, 0x5410;\n"
        "mov.b32 {xl, xh}, a0; tanh.approx.f16 xr, xl; cvt.u32.u16 lo0, xr; tanh.approx.f16 xr, xh; cvt.u32.u16 hi0, xr; mul.rn.f16x2 a1, qz13, p1; fma.rn.f16x2 p0, qz14, qz14, c; fma.rn.f16x2 g10, qz10, h0, qz10; prmt.b32 h1, lo1, hi1, 0x5410;\n"
        "mov.b32 {xl, xh}, a1; tanh.approx.f16 xr, xl; cvt.u32.u16 lo1, xr; tanh.approx.f16 xr, xh; cvt.u32.u16 hi1, xr; mul.rn.f16x2 a2, qz14, p0; fma.rn.f16x2 p1, qz15, qz15, c; fma.rn.f16x2 g11, qz11, h1, qz11; prmt.b32 h0, lo0, hi0, 0x5410;\n"
        "B46:\n"
        "wgmma.wait_group.sync.aligned 1;\n"
        "wgmma.fence.sync.aligned;\n"
        "add.s64 dt, w2d, 640; wgmma.mma_async.sync.aligned.m64n96k16.f16.f16.f16 {o0,o1,o2,o3,o4,o5,o6,o7,o8,o9,o10,o11,o12,o13,o14,o15,o16,o17,o18,o19,o20,o21,o22,o23}, {g8,g9,g10,g11}, dt, pt, 1, 1, 1;\n"
        "wgmma.commit_group.sync.aligned;\n"
        "mad.lo.u32 tt, n, 8, tbar;\n"
        "@pn mbarrier.arrive.shared::cta.b64 _, [tt+64];\n"
        "@pz bra.uni B50;\n"
        "mov.b32 {xl, xh}, a2; tanh.approx.f16 xr, xl; cvt.u32.u16 lo0, xr; tanh.approx.f16 xr, xh; cvt.u32.u16 hi0, xr; mul.rn.f16x2 a3, qz15, p1; fma.rn.f16x2 p0, qz16, qz16, c; fma.rn.f16x2 g12, qz12, h0, qz12; prmt.b32 h1, lo1, hi1, 0x5410;\n"
        "mov.b32 {xl, xh}, a3; tanh.approx.f16 xr, xl; cvt.u32.u16 lo1, xr; tanh.approx.f16 xr, xh; cvt.u32.u16 hi1, xr; mul.rn.f16x2 a0, qz16, p0; fma.rn.f16x2 p1, qz17, qz17, c; fma.rn.f16x2 g13, qz13, h1, qz13; prmt.b32 h0, lo0, hi0, 0x5410;\n"
        "mov.b32 {xl, xh}, a0; tanh.approx.f16 xr, xl; cvt.u32.u16 lo0, xr; tanh.approx.f16 xr, xh; cvt.u32.u16 hi0, xr; mul.rn.f16x2 a1, qz17, p1; fma.rn.f16x2 p0, qz18, qz18, c; fma.rn.f16x2 g14, qz14, h0, qz14; prmt.b32 h1, lo1, hi1, 0x5410;\n"
        "mov.b32 {xl, xh}, a1; tanh.approx.f16 xr, xl; cvt.u32.u16 lo1, xr; tanh.approx.f16 xr, xh; cvt.u32.u16 hi1, xr; mul.rn.f16x2 a2, qz18, p0; fma.rn.f16x2 p1, qz19, qz19, c; fma.rn.f16x2 g15, qz15, h1, qz15; prmt.b32 h0, lo0, hi0, 0x5410;\n"
        "B50:\n"
        "wgmma.wait_group.sync.aligned 1;\n"
        "wgmma.fence.sync.aligned;\n"
        "add.s64 dt, w2d, 704; wgmma.mma_async.sync.aligned.m64n96k16.f16.f16.f16 {o0,o1,o2,o3,o4,o5,o6,o7,o8,o9,o10,o11,o12,o13,o14,o15,o16,o17,o18,o19,o20,o21,o22,o23}, {g12,g13,g14,g15}, dt, pt, 1, 1, 1;\n"
        "add.s64 dt, w1d, 3072; wgmma.mma_async.sync.aligned.m64n64k16.f16.f16.f16 {qz0,qz1,qz2,qz3,qz4,qz5,qz6,qz7,qz8,qz9,qz10,qz11,qz12,qz13,qz14,qz15}, {qa0,qa1,qa2,qa3}, dt, pf, 1, 1, 1;\n"
        "add.s64 dt, w1d, 3200; wgmma.mma_async.sync.aligned.m64n64k16.f16.f16.f16 {qz0,qz1,qz2,qz3,qz4,qz5,qz6,qz7,qz8,qz9,qz10,qz11,qz12,qz13,qz14,qz15}, {qa4,qa5,qa6,qa7}, dt, pt, 1, 1, 1;\n"
        "add.s64 dt, w1d, 3328; wgmma.mma_async.sync.aligned.m64n64k16.f16.f16.f16 {qz0,qz1,qz2,qz3,qz4,qz5,qz6,qz7,qz8,qz9,qz10,qz11,qz12,qz13,qz14,qz15}, {qa8,qa9,qa10,qa11}, dt, pt, 1, 1, 1;\n"
        "wgmma.commit_group.sync.aligned;\n"
        "@pz bra.uni B54;\n"
        "mov.b32 {xl, xh}, a2; tanh.approx.f16 xr, xl; cvt.u32.u16 lo0, xr; tanh.approx.f16 xr, xh; cvt.u32.u16 hi0, xr; mul.rn.f16x2 a3, qz19, p1; fma.rn.f16x2 p0, qz20, qz20, c; fma.rn.f16x2 g0, qz16, h0, qz16; prmt.b32 h1, lo1, hi1, 0x5410;\n"
        "mov.b32 {xl, xh}, a3; tanh.approx.f16 xr, xl; cvt.u32.u16 lo1, xr; tanh.approx.f16 xr, xh; cvt.u32.u16 hi1, xr; mul.rn.f16x2 a0, qz20, p0; fma.rn.f16x2 p1, qz21, qz21, c; fma.rn.f16x2 g1, qz17, h1, qz17; prmt.b32 h0, lo0, hi0, 0x5410;\n"
        "mov.b32 {xl, xh}, a0; tanh.approx.f16 xr, xl; cvt.u32.u16 lo0, xr; tanh.approx.f16 xr, xh; cvt.u32.u16 hi0, xr; mul.rn.f16x2 a1, qz21, p1; fma.rn.f16x2 p0, qz22, qz22, c; fma.rn.f16x2 g2, qz18, h0, qz18; prmt.b32 h1, lo1, hi1, 0x5410;\n"
        "mov.b32 {xl, xh}, a1; tanh.approx.f16 xr, xl; cvt.u32.u16 lo1, xr; tanh.approx.f16 xr, xh; cvt.u32.u16 hi1, xr; mul.rn.f16x2 a2, qz22, p0; fma.rn.f16x2 p1, qz23, qz23, c; fma.rn.f16x2 g3, qz19, h1, qz19; prmt.b32 h0, lo0, hi0, 0x5410;\n"
        "B54:\n"
        "wgmma.fence.sync.aligned;\n"
        "add.s64 dt, w1d, 3456; wgmma.mma_async.sync.aligned.m64n64k16.f16.f16.f16 {qz0,qz1,qz2,qz3,qz4,qz5,qz6,qz7,qz8,qz9,qz10,qz11,qz12,qz13,qz14,qz15}, {qa12,qa13,qa14,qa15}, dt, pt, 1, 1, 1;\n"
        "add.s64 dt, w1d, 3584; wgmma.mma_async.sync.aligned.m64n64k16.f16.f16.f16 {qz0,qz1,qz2,qz3,qz4,qz5,qz6,qz7,qz8,qz9,qz10,qz11,qz12,qz13,qz14,qz15}, {qa16,qa17,qa18,qa19}, dt, pt, 1, 1, 1;\n"
        "add.s64 dt, w1d, 3712; wgmma.mma_async.sync.aligned.m64n64k16.f16.f16.f16 {qz0,qz1,qz2,qz3,qz4,qz5,qz6,qz7,qz8,qz9,qz10,qz11,qz12,qz13,qz14,qz15}, {qa20,qa21,qa22,qa23}, dt, pt, 1, 1, 1;\n"
        "wgmma.commit_group.sync.aligned;\n"
        "@pz bra.uni B58;\n"
        "mov.b32 {xl, xh}, a2; tanh.approx.f16 xr, xl; cvt.u32.u16 lo0, xr; tanh.approx.f16 xr, xh; cvt.u32.u16 hi0, xr; mul.rn.f16x2 a3, qz23, p1; fma.rn.f16x2 p0, qz24, qz24, c; fma.rn.f16x2 g4, qz20, h0, qz20; prmt.b32 h1, lo1, hi1, 0x5410;\n"
        "mov.b32 {xl, xh}, a3; tanh.approx.f16 xr, xl; cvt.u32.u16 lo1, xr; tanh.approx.f16 xr, xh; cvt.u32.u16 hi1, xr; mul.rn.f16x2 a0, qz24, p0; fma.rn.f16x2 p1, qz25, qz25, c; fma.rn.f16x2 g5, qz21, h1, qz21; prmt.b32 h0, lo0, hi0, 0x5410;\n"
        "mov.b32 {xl, xh}, a0; tanh.approx.f16 xr, xl; cvt.u32.u16 lo0, xr; tanh.approx.f16 xr, xh; cvt.u32.u16 hi0, xr; mul.rn.f16x2 a1, qz25, p1; fma.rn.f16x2 p0, qz26, qz26, c; fma.rn.f16x2 g6, qz22, h0, qz22; prmt.b32 h1, lo1, hi1, 0x5410;\n"
        "mov.b32 {xl, xh}, a1; tanh.approx.f16 xr, xl; cvt.u32.u16 lo1, xr; tanh.approx.f16 xr, xh; cvt.u32.u16 hi1, xr; mul.rn.f16x2 a2, qz26, p0; fma.rn.f16x2 p1, qz27, qz27, c; fma.rn.f16x2 g7, qz23, h1, qz23; prmt.b32 h0, lo0, hi0, 0x5410;\n"
        "B58:\n"
        "wgmma.wait_group.sync.aligned 2;\n"
        "wgmma.fence.sync.aligned;\n"
        "add.s64 dt, w2d, 768; wgmma.mma_async.sync.aligned.m64n96k16.f16.f16.f16 {o0,o1,o2,o3,o4,o5,o6,o7,o8,o9,o10,o11,o12,o13,o14,o15,o16,o17,o18,o19,o20,o21,o22,o23}, {g0,g1,g2,g3}, dt, pt, 1, 1, 1;\n"
        "add.s64 dt, w2d, 832; wgmma.mma_async.sync.aligned.m64n96k16.f16.f16.f16 {o0,o1,o2,o3,o4,o5,o6,o7,o8,o9,o10,o11,o12,o13,o14,o15,o16,o17,o18,o19,o20,o21,o22,o23}, {g4,g5,g6,g7}, dt, pt, 1, 1, 1;\n"
        "wgmma.commit_group.sync.aligned;\n"
        "@pz bra.uni B62;\n"
        "mov.b32 {xl, xh}, a2; tanh.approx.f16 xr, xl; cvt.u32.u16 lo0, xr; tanh.approx.f16 xr, xh; cvt.u32.u16 hi0, xr; mul.rn.f16x2 a3, qz27, p1; fma.rn.f16x2 p0, qz28, qz28, c; fma.rn.f16x2 g8, qz24, h0, qz24; prmt.b32 h1, lo1, hi1, 0x5410;\n"
        "mov.b32 {xl, xh}, a3; tanh.approx.f16 xr, xl; cvt.u32.u16 lo1, xr; tanh.approx.f16 xr, xh; cvt.u32.u16 hi1, xr; mul.rn.f16x2 a0, qz28, p0; fma.rn.f16x2 p1, qz29, qz29, c; fma.rn.f16x2 g9, qz25, h1, qz25; prmt.b32 h0, lo0, hi0, 0x5410;\n"
        "mov.b32 {xl, xh}, a0; tanh.approx.f16 xr, xl; cvt.u32.u16 lo0, xr; tanh.approx.f16 xr, xh; cvt.u32.u16 hi0, xr; mul.rn.f16x2 a1, qz29, p1; fma.rn.f16x2 p0, qz30, qz30, c; fma.rn.f16x2 g10, qz26, h0, qz26; prmt.b32 h1, lo1, hi1, 0x5410;\n"
        "mov.b32 {xl, xh}, a1; tanh.approx.f16 xr, xl; cvt.u32.u16 lo1, xr; tanh.approx.f16 xr, xh; cvt.u32.u16 hi1, xr; mul.rn.f16x2 a2, qz30, p0; fma.rn.f16x2 p1, qz31, qz31, c; fma.rn.f16x2 g11, qz27, h1, qz27; prmt.b32 h0, lo0, hi0, 0x5410;\n"
        "B62:\n"
        "wgmma.wait_group.sync.aligned 1;\n"
        "wgmma.fence.sync.aligned;\n"
        "add.s64 dt, w2d, 896; wgmma.mma_async.sync.aligned.m64n96k16.f16.f16.f16 {o0,o1,o2,o3,o4,o5,o6,o7,o8,o9,o10,o11,o12,o13,o14,o15,o16,o17,o18,o19,o20,o21,o22,o23}, {g8,g9,g10,g11}, dt, pt, 1, 1, 1;\n"
        "wgmma.commit_group.sync.aligned;\n"
        "@pz bra.uni B66;\n"
        "mov.b32 {xl, xh}, a2; tanh.approx.f16 xr, xl; cvt.u32.u16 lo0, xr; tanh.approx.f16 xr, xh; cvt.u32.u16 hi0, xr; mul.rn.f16x2 a3, qz31, p1; fma.rn.f16x2 p0, qz0, qz0, c; fma.rn.f16x2 g12, qz28, h0, qz28; prmt.b32 h1, lo1, hi1, 0x5410;\n"
        "mov.b32 {xl, xh}, a3; tanh.approx.f16 xr, xl; cvt.u32.u16 lo1, xr; tanh.approx.f16 xr, xh; cvt.u32.u16 hi1, xr; mul.rn.f16x2 a0, qz0, p0; fma.rn.f16x2 p1, qz1, qz1, c; fma.rn.f16x2 g13, qz29, h1, qz29; prmt.b32 h0, lo0, hi0, 0x5410;\n"
        "mov.b32 {xl, xh}, a0; tanh.approx.f16 xr, xl; cvt.u32.u16 lo0, xr; tanh.approx.f16 xr, xh; cvt.u32.u16 hi0, xr; mul.rn.f16x2 a1, qz1, p1; fma.rn.f16x2 p0, qz2, qz2, c; fma.rn.f16x2 g14, qz30, h0, qz30; prmt.b32 h1, lo1, hi1, 0x5410;\n"
        "mov.b32 {xl, xh}, a1; tanh.approx.f16 xr, xl; cvt.u32.u16 lo1, xr; tanh.approx.f16 xr, xh; cvt.u32.u16 hi1, xr; mul.rn.f16x2 a2, qz2, p0; fma.rn.f16x2 p1, qz3, qz3, c; fma.rn.f16x2 g15, qz31, h1, qz31; prmt.b32 h0, lo0, hi0, 0x5410;\n"
        "B66:\n"
        "wgmma.wait_group.sync.aligned 1;\n"
        "wgmma.fence.sync.aligned;\n"
        "add.s64 dt, w2d, 960; wgmma.mma_async.sync.aligned.m64n96k16.f16.f16.f16 {o0,o1,o2,o3,o4,o5,o6,o7,o8,o9,o10,o11,o12,o13,o14,o15,o16,o17,o18,o19,o20,o21,o22,o23}, {g12,g13,g14,g15}, dt, pt, 1, 1, 1;\n"
        "add.s64 dt, w1d, 3840; wgmma.mma_async.sync.aligned.m64n64k16.f16.f16.f16 {qz16,qz17,qz18,qz19,qz20,qz21,qz22,qz23,qz24,qz25,qz26,qz27,qz28,qz29,qz30,qz31}, {qa0,qa1,qa2,qa3}, dt, pf, 1, 1, 1;\n"
        "add.s64 dt, w1d, 3968; wgmma.mma_async.sync.aligned.m64n64k16.f16.f16.f16 {qz16,qz17,qz18,qz19,qz20,qz21,qz22,qz23,qz24,qz25,qz26,qz27,qz28,qz29,qz30,qz31}, {qa4,qa5,qa6,qa7}, dt, pt, 1, 1, 1;\n"
        "add.s64 dt, w1d, 4096; wgmma.mma_async.sync.aligned.m64n64k16.f16.f16.f16 {qz16,qz17,qz18,qz19,qz20,qz21,qz22,qz23,qz24,qz25,qz26,qz27,qz28,qz29,qz30,qz31}, {qa8,qa9,qa10,qa11}, dt, pt, 1, 1, 1;\n"
        "wgmma.commit_group.sync.aligned;\n"
        "@pz bra.uni B70;\n"
        "mov.b32 {xl, xh}, a2; tanh.approx.f16 xr, xl; cvt.u32.u16 lo0, xr; tanh.approx.f16 xr, xh; cvt.u32.u16 hi0, xr; mul.rn.f16x2 a3, qz3, p1; fma.rn.f16x2 p0, qz4, qz4, c; fma.rn.f16x2 g0, qz0, h0, qz0; prmt.b32 h1, lo1, hi1, 0x5410;\n"
        "mov.b32 {xl, xh}, a3; tanh.approx.f16 xr, xl; cvt.u32.u16 lo1, xr; tanh.approx.f16 xr, xh; cvt.u32.u16 hi1, xr; mul.rn.f16x2 a0, qz4, p0; fma.rn.f16x2 p1, qz5, qz5, c; fma.rn.f16x2 g1, qz1, h1, qz1; prmt.b32 h0, lo0, hi0, 0x5410;\n"
        "mov.b32 {xl, xh}, a0; tanh.approx.f16 xr, xl; cvt.u32.u16 lo0, xr; tanh.approx.f16 xr, xh; cvt.u32.u16 hi0, xr; mul.rn.f16x2 a1, qz5, p1; fma.rn.f16x2 p0, qz6, qz6, c; fma.rn.f16x2 g2, qz2, h0, qz2; prmt.b32 h1, lo1, hi1, 0x5410;\n"
        "mov.b32 {xl, xh}, a1; tanh.approx.f16 xr, xl; cvt.u32.u16 lo1, xr; tanh.approx.f16 xr, xh; cvt.u32.u16 hi1, xr; mul.rn.f16x2 a2, qz6, p0; fma.rn.f16x2 p1, qz7, qz7, c; fma.rn.f16x2 g3, qz3, h1, qz3; prmt.b32 h0, lo0, hi0, 0x5410;\n"
        "B70:\n"
        "wgmma.fence.sync.aligned;\n"
        "add.s64 dt, w1d, 4224; wgmma.mma_async.sync.aligned.m64n64k16.f16.f16.f16 {qz16,qz17,qz18,qz19,qz20,qz21,qz22,qz23,qz24,qz25,qz26,qz27,qz28,qz29,qz30,qz31}, {qa12,qa13,qa14,qa15}, dt, pt, 1, 1, 1;\n"
        "add.s64 dt, w1d, 4352; wgmma.mma_async.sync.aligned.m64n64k16.f16.f16.f16 {qz16,qz17,qz18,qz19,qz20,qz21,qz22,qz23,qz24,qz25,qz26,qz27,qz28,qz29,qz30,qz31}, {qa16,qa17,qa18,qa19}, dt, pt, 1, 1, 1;\n"
        "add.s64 dt, w1d, 4480; wgmma.mma_async.sync.aligned.m64n64k16.f16.f16.f16 {qz16,qz17,qz18,qz19,qz20,qz21,qz22,qz23,qz24,qz25,qz26,qz27,qz28,qz29,qz30,qz31}, {qa20,qa21,qa22,qa23}, dt, pt, 1, 1, 1;\n"
        "wgmma.commit_group.sync.aligned;\n"
        "@pz bra.uni B74;\n"
        "mov.b32 {xl, xh}, a2; tanh.approx.f16 xr, xl; cvt.u32.u16 lo0, xr; tanh.approx.f16 xr, xh; cvt.u32.u16 hi0, xr; mul.rn.f16x2 a3, qz7, p1; fma.rn.f16x2 p0, qz8, qz8, c; fma.rn.f16x2 g4, qz4, h0, qz4; prmt.b32 h1, lo1, hi1, 0x5410;\n"
        "mov.b32 {xl, xh}, a3; tanh.approx.f16 xr, xl; cvt.u32.u16 lo1, xr; tanh.approx.f16 xr, xh; cvt.u32.u16 hi1, xr; mul.rn.f16x2 a0, qz8, p0; fma.rn.f16x2 p1, qz9, qz9, c; fma.rn.f16x2 g5, qz5, h1, qz5; prmt.b32 h0, lo0, hi0, 0x5410;\n"
        "mov.b32 {xl, xh}, a0; tanh.approx.f16 xr, xl; cvt.u32.u16 lo0, xr; tanh.approx.f16 xr, xh; cvt.u32.u16 hi0, xr; mul.rn.f16x2 a1, qz9, p1; fma.rn.f16x2 p0, qz10, qz10, c; fma.rn.f16x2 g6, qz6, h0, qz6; prmt.b32 h1, lo1, hi1, 0x5410;\n"
        "mov.b32 {xl, xh}, a1; tanh.approx.f16 xr, xl; cvt.u32.u16 lo1, xr; tanh.approx.f16 xr, xh; cvt.u32.u16 hi1, xr; mul.rn.f16x2 a2, qz10, p0; fma.rn.f16x2 p1, qz11, qz11, c; fma.rn.f16x2 g7, qz7, h1, qz7; prmt.b32 h0, lo0, hi0, 0x5410;\n"
        "B74:\n"
        "wgmma.wait_group.sync.aligned 2;\n"
        "wgmma.fence.sync.aligned;\n"
        "add.s64 dt, w2d, 1024; wgmma.mma_async.sync.aligned.m64n96k16.f16.f16.f16 {o0,o1,o2,o3,o4,o5,o6,o7,o8,o9,o10,o11,o12,o13,o14,o15,o16,o17,o18,o19,o20,o21,o22,o23}, {g0,g1,g2,g3}, dt, pt, 1, 1, 1;\n"
        "add.s64 dt, w2d, 1088; wgmma.mma_async.sync.aligned.m64n96k16.f16.f16.f16 {o0,o1,o2,o3,o4,o5,o6,o7,o8,o9,o10,o11,o12,o13,o14,o15,o16,o17,o18,o19,o20,o21,o22,o23}, {g4,g5,g6,g7}, dt, pt, 1, 1, 1;\n"
        "wgmma.commit_group.sync.aligned;\n"
        "@pz bra.uni B78;\n"
        "mov.b32 {xl, xh}, a2; tanh.approx.f16 xr, xl; cvt.u32.u16 lo0, xr; tanh.approx.f16 xr, xh; cvt.u32.u16 hi0, xr; mul.rn.f16x2 a3, qz11, p1; fma.rn.f16x2 p0, qz12, qz12, c; fma.rn.f16x2 g8, qz8, h0, qz8; prmt.b32 h1, lo1, hi1, 0x5410;\n"
        "mov.b32 {xl, xh}, a3; tanh.approx.f16 xr, xl; cvt.u32.u16 lo1, xr; tanh.approx.f16 xr, xh; cvt.u32.u16 hi1, xr; mul.rn.f16x2 a0, qz12, p0; fma.rn.f16x2 p1, qz13, qz13, c; fma.rn.f16x2 g9, qz9, h1, qz9; prmt.b32 h0, lo0, hi0, 0x5410;\n"
        "mov.b32 {xl, xh}, a0; tanh.approx.f16 xr, xl; cvt.u32.u16 lo0, xr; tanh.approx.f16 xr, xh; cvt.u32.u16 hi0, xr; mul.rn.f16x2 a1, qz13, p1; fma.rn.f16x2 p0, qz14, qz14, c; fma.rn.f16x2 g10, qz10, h0, qz10; prmt.b32 h1, lo1, hi1, 0x5410;\n"
        "mov.b32 {xl, xh}, a1; tanh.approx.f16 xr, xl; cvt.u32.u16 lo1, xr; tanh.approx.f16 xr, xh; cvt.u32.u16 hi1, xr; mul.rn.f16x2 a2, qz14, p0; fma.rn.f16x2 p1, qz15, qz15, c; fma.rn.f16x2 g11, qz11, h1, qz11; prmt.b32 h0, lo0, hi0, 0x5410;\n"
        "B78:\n"
        "wgmma.wait_group.sync.aligned 1;\n"
        "@!pm bra.uni BACKY;\n"
        "add.u32 tt, n, 1; and.b32 tt, tt, 1; mbarrier.try_wait.parity.shared::cta.b64 pw, [ybar], tt;\n"
        "@!pw bra.uni SPINY;\n"
        "BACKY:\n"
        "@pz bra.uni B80;\n"
        "and.b32 ad, %5, 0xffff; xor.b32 ad, ad, 0; add.u32 ad, ad, %4; ldmatrix.sync.aligned.m8n8.x4.shared.b16 {qa0,qa1,qa2,qa3}, [ad];\n"
        "and.b32 ad, %5, 0xffff; xor.b32 ad, ad, 32; add.u32 ad, ad, %4; ldmatrix.sync.aligned.m8n8.x4.shared.b16 {qa4,qa5,qa6,qa7}, [ad];\n"
        "and.b32 ad, %5, 0xffff; xor.b32 ad, ad, 64; add.u32 ad, ad, %4; ldmatrix.sync.aligned.m8n8.x4.shared.b16 {qa8,qa9,qa10,qa11}, [ad];\n"
        "and.b32 ad, %5, 0xffff; xor.b32 ad, ad, 96; add.u32 ad, ad, %4; ldmatrix.sync.aligned.m8n8.x4.shared.b16 {qa12,qa13,qa14,qa15}, [ad];\n"
        "shr.u32 ad, %5, 16; xor.b32 ad, ad, 0; add.u32 ad, ad, %4; ldmatrix.sync.aligned.m8n8.x4.shared.b16 {qa16,qa17,qa18,qa19}, [ad];\n"
        "shr.u32 ad, %5, 16; xor.b32 ad, ad, 32; add.u32 ad, ad, %4; ldmatrix.sync.aligned.m8n8.x4.shared.b16 {qa20,qa21,qa22,qa23}, [ad];\n"
        "mov.b32 {xl, xh}, a2; tanh.approx.f16 xr, xl; cvt.u32.u16 lo0, xr; tanh.approx.f16 xr, xh; cvt.u32.u16 hi0, xr; mul.rn.f16x2 a3, qz15, p1; fma.rn.f16x2 p0, qz16, qz16, c; fma.rn.f16x2 g12, qz12, h0, qz12; prmt.b32 h1, lo1, hi1, 0x5410;\n"
        "mov.b32 {xl, xh}, a3; tanh.approx.f16 xr, xl; cvt.u32.u16 lo1, xr; tanh.approx.f16 xr, xh; cvt.u32.u16 hi1, xr; mul.rn.f16x2 a0, qz16, p0; fma.rn.f16x2 p1, qz17, qz17, c; fma.rn.f16x2 g13, qz13, h1, qz13; prmt.b32 h0, lo0, hi0, 0x5410;\n"
        "B80:\n"
        "fence.proxy.async.shared::cta;\n"
        "add.u32 tt, id, 0;\n"
        "@pl bra.uni XLOAD;\n"
        "bar.arrive tt, 128;\n"
        "XLOADB:\n"
        "wgmma.fence.sync.aligned;\n"
        "add.s64 dt, w2d, 1152; wgmma.mma_async.sync.aligned.m64n96k16.f16.f16.f16 {o0,o1,o2,o3,o4,o5,o6,o7,o8,o9,o10,o11,o12,o13,o14,o15,o16,o17,o18,o19,o20,o21,o22,o23}, {g8,g9,g10,g11}, dt, pt, 1, 1, 1;\n"
        "wgmma.commit_group.sync.aligned;\n"
        "@pz bra.uni B82;\n"
        "mov.b32 {xl, xh}, a0; tanh.approx.f16 xr, xl; cvt.u32.u16 lo0, xr; tanh.approx.f16 xr, xh; cvt.u32.u16 hi0, xr; mul.rn.f16x2 a1, qz17, p1; fma.rn.f16x2 p0, qz18, qz18, c; fma.rn.f16x2 g14, qz14, h0, qz14; prmt.b32 h1, lo1, hi1, 0x5410;\n"
        "mov.b32 {xl, xh}, a1; tanh.approx.f16 xr, xl; cvt.u32.u16 lo1, xr; tanh.approx.f16 xr, xh; cvt.u32.u16 hi1, xr; mul.rn.f16x2 a2, qz18, p0; fma.rn.f16x2 p1, qz19, qz19, c; fma.rn.f16x2 g15, qz15, h1, qz15; prmt.b32 h0, lo0, hi0, 0x5410;\n"
        "B82:\n"
        "wgmma.wait_group.sync.aligned 1;\n"
        "@!pm bra.uni SKIP1;\n"
        "wgmma.fence.sync.aligned;\n"
        "add.s64 dt, w1d, 0; wgmma.mma_async.sync.aligned.m64n64k16.f16.f16.f16 {qz0,qz1,qz2,qz3,qz4,qz5,qz6,qz7,qz8,qz9,qz10,qz11,qz12,qz13,qz14,qz15}, {qa0,qa1,qa2,qa3}, dt, pf, 1, 1, 1;\n"
        "add.s64 dt, w1d, 128; wgmma.mma_async.sync.aligned.m64n64k16.f16.f16.f16 {qz0,qz1,qz2,qz3,qz4,qz5,qz6,qz7,qz8,qz9,qz10,qz11,qz12,qz13,qz14,qz15}, {qa4,qa5,qa6,qa7}, dt, pt, 1, 1, 1;\n"
        "add.s64 dt, w1d, 256; wgmma.mma_async.sync.aligned.m64n64k16.f16.f16.f16 {qz0,qz1,qz2,qz3,qz4,qz5,qz6,qz7,qz8,qz9,qz10,qz11,qz12,qz13,qz14,qz15}, {qa8,qa9,qa10,qa11}, dt, pt, 1, 1, 1;\n"
        "SKIP1:\n"
        "wgmma.fence.sync.aligned;\n"
        "add.s64 dt, w2d, 1216; wgmma.mma_async.sync.aligned.m64n96k16.f16.f16.f16 {o0,o1,o2,o3,o4,o5,o6,o7,o8,o9,o10,o11,o12,o13,o14,o15,o16,o17,o18,o19,o20,o21,o22,o23}, {g12,g13,g14,g15}, dt, pt, 1, 1, 1;\n"
        "wgmma.commit_group.sync.aligned;\n"
        "@pz bra.uni B86;\n"
        "mov.b32 {xl, xh}, a2; tanh.approx.f16 xr, xl; cvt.u32.u16 lo0, xr; tanh.approx.f16 xr, xh; cvt.u32.u16 hi0, xr; mul.rn.f16x2 a3, qz19, p1; fma.rn.f16x2 p0, qz20, qz20, c; fma.rn.f16x2 g0, qz16, h0, qz16; prmt.b32 h1, lo1, hi1, 0x5410;\n"
        "mov.b32 {xl, xh}, a3; tanh.approx.f16 xr, xl; cvt.u32.u16 lo1, xr; tanh.approx.f16 xr, xh; cvt.u32.u16 hi1, xr; mul.rn.f16x2 a0, qz20, p0; fma.rn.f16x2 p1, qz21, qz21, c; fma.rn.f16x2 g1, qz17, h1, qz17; prmt.b32 h0, lo0, hi0, 0x5410;\n"
        "mov.b32 {xl, xh}, a0; tanh.approx.f16 xr, xl; cvt.u32.u16 lo0, xr; tanh.approx.f16 xr, xh; cvt.u32.u16 hi0, xr; mul.rn.f16x2 a1, qz21, p1; fma.rn.f16x2 p0, qz22, qz22, c; fma.rn.f16x2 g2, qz18, h0, qz18; prmt.b32 h1, lo1, hi1, 0x5410;\n"
        "mov.b32 {xl, xh}, a1; tanh.approx.f16 xr, xl; cvt.u32.u16 lo1, xr; tanh.approx.f16 xr, xh; cvt.u32.u16 hi1, xr; mul.rn.f16x2 a2, qz22, p0; fma.rn.f16x2 p1, qz23, qz23, c; fma.rn.f16x2 g3, qz19, h1, qz19; prmt.b32 h0, lo0, hi0, 0x5410;\n"
        "B86:\n"
        "@!pm bra.uni SKIP2;\n"
        "wgmma.fence.sync.aligned;\n"
        "add.s64 dt, w1d, 384; wgmma.mma_async.sync.aligned.m64n64k16.f16.f16.f16 {qz0,qz1,qz2,qz3,qz4,qz5,qz6,qz7,qz8,qz9,qz10,qz11,qz12,qz13,qz14,qz15}, {qa12,qa13,qa14,qa15}, dt, pt, 1, 1, 1;\n"
        "add.s64 dt, w1d, 512; wgmma.mma_async.sync.aligned.m64n64k16.f16.f16.f16 {qz0,qz1,qz2,qz3,qz4,qz5,qz6,qz7,qz8,qz9,qz10,qz11,qz12,qz13,qz14,qz15}, {qa16,qa17,qa18,qa19}, dt, pt, 1, 1, 1;\n"
        "add.s64 dt, w1d, 640; wgmma.mma_async.sync.aligned.m64n64k16.f16.f16.f16 {qz0,qz1,qz2,qz3,qz4,qz5,qz6,qz7,qz8,qz9,qz10,qz11,qz12,qz13,qz14,qz15}, {qa20,qa21,qa22,qa23}, dt, pt, 1, 1, 1;\n"
        "SKIP2:\n"
        "@pz bra.uni B90;\n"
        "mov.b32 {xl, xh}, a2; tanh.approx.f16 xr, xl; cvt.u32.u16 lo0, xr; tanh.approx.f16 xr, xh; cvt.u32.u16 hi0, xr; mul.rn.f16x2 a3, qz23, p1; fma.rn.f16x2 p0, qz24, qz24, c; fma.rn.f16x2 g4, qz20, h0, qz20; prmt.b32 h1, lo1, hi1, 0x5410;\n"
        "mov.b32 {xl, xh}, a3; tanh.approx.f16 xr, xl; cvt.u32.u16 lo1, xr; tanh.approx.f16 xr, xh; cvt.u32.u16 hi1, xr; mul.rn.f16x2 a0, qz24, p0; fma.rn.f16x2 p1, qz25, qz25, c; fma.rn.f16x2 g5, qz21, h1, qz21; prmt.b32 h0, lo0, hi0, 0x5410;\n"
        "mov.b32 {xl, xh}, a0; tanh.approx.f16 xr, xl; cvt.u32.u16 lo0, xr; tanh.approx.f16 xr, xh; cvt.u32.u16 hi0, xr; mul.rn.f16x2 a1, qz25, p1; fma.rn.f16x2 p0, qz26, qz26, c; fma.rn.f16x2 g6, qz22, h0, qz22; prmt.b32 h1, lo1, hi1, 0x5410;\n"
        "mov.b32 {xl, xh}, a1; tanh.approx.f16 xr, xl; cvt.u32.u16 lo1, xr; tanh.approx.f16 xr, xh; cvt.u32.u16 hi1, xr; mul.rn.f16x2 a2, qz26, p0; fma.rn.f16x2 p1, qz27, qz27, c; fma.rn.f16x2 g7, qz23, h1, qz23; prmt.b32 h0, lo0, hi0, 0x5410;\n"
        "B90:\n"
        "wgmma.wait_group.sync.aligned 1;\n"
        "wgmma.fence.sync.aligned;\n"
        "add.s64 dt, w2d, 1280; wgmma.mma_async.sync.aligned.m64n96k16.f16.f16.f16 {o0,o1,o2,o3,o4,o5,o6,o7,o8,o9,o10,o11,o12,o13,o14,o15,o16,o17,o18,o19,o20,o21,o22,o23}, {g0,g1,g2,g3}, dt, pt, 1, 1, 1;\n"
        "add.s64 dt, w2d, 1344; wgmma.mma_async.sync.aligned.m64n96k16.f16.f16.f16 {o0,o1,o2,o3,o4,o5,o6,o7,o8,o9,o10,o11,o12,o13,o14,o15,o16,o17,o18,o19,o20,o21,o22,o23}, {g4,g5,g6,g7}, dt, pt, 1, 1, 1;\n"
        "wgmma.commit_group.sync.aligned;\n"
        "@pz bra.uni B94;\n"
        "mov.b32 {xl, xh}, a2; tanh.approx.f16 xr, xl; cvt.u32.u16 lo0, xr; tanh.approx.f16 xr, xh; cvt.u32.u16 hi0, xr; mul.rn.f16x2 a3, qz27, p1; fma.rn.f16x2 p0, qz28, qz28, c; fma.rn.f16x2 g8, qz24, h0, qz24; prmt.b32 h1, lo1, hi1, 0x5410;\n"
        "mov.b32 {xl, xh}, a3; tanh.approx.f16 xr, xl; cvt.u32.u16 lo1, xr; tanh.approx.f16 xr, xh; cvt.u32.u16 hi1, xr; mul.rn.f16x2 a0, qz28, p0; fma.rn.f16x2 p1, qz29, qz29, c; fma.rn.f16x2 g9, qz25, h1, qz25; prmt.b32 h0, lo0, hi0, 0x5410;\n"
        "mov.b32 {xl, xh}, a0; tanh.approx.f16 xr, xl; cvt.u32.u16 lo0, xr; tanh.approx.f16 xr, xh; cvt.u32.u16 hi0, xr; mul.rn.f16x2 a1, qz29, p1; fma.rn.f16x2 p0, qz30, qz30, c; fma.rn.f16x2 g10, qz26, h0, qz26; prmt.b32 h1, lo1, hi1, 0x5410;\n"
        "mov.b32 {xl, xh}, a1; tanh.approx.f16 xr, xl; cvt.u32.u16 lo1, xr; tanh.approx.f16 xr, xh; cvt.u32.u16 hi1, xr; mul.rn.f16x2 a2, qz30, p0; fma.rn.f16x2 p1, qz31, qz31, c; fma.rn.f16x2 g11, qz27, h1, qz27; prmt.b32 h0, lo0, hi0, 0x5410;\n"
        "B94:\n"
        "wgmma.wait_group.sync.aligned 0;\n"
        "wgmma.fence.sync.aligned;\n"
        "add.s64 dt, w2d, 1408; wgmma.mma_async.sync.aligned.m64n96k16.f16.f16.f16 {o0,o1,o2,o3,o4,o5,o6,o7,o8,o9,o10,o11,o12,o13,o14,o15,o16,o17,o18,o19,o20,o21,o22,o23}, {g8,g9,g10,g11}, dt, pt, 1, 1, 1;\n"
        "wgmma.commit_group.sync.aligned;\n"
        "@pz bra.uni B2;\n"
        "mov.b32 {xl, xh}, a2; tanh.approx.f16 xr, xl; cvt.u32.u16 lo0, xr; tanh.approx.f16 xr, xh; cvt.u32.u16 hi0, xr; mul.rn.f16x2 a3, qz31, p1; fma.rn.f16x2 p0, qz0, qz0, c; fma.rn.f16x2 g12, qz28, h0, qz28; prmt.b32 h1, lo1, hi1, 0x5410;\n"
        "mov.b32 {xl, xh}, a3; tanh.approx.f16 xr, xl; cvt.u32.u16 lo1, xr; tanh.approx.f16 xr, xh; cvt.u32.u16 hi1, xr; mul.rn.f16x2 a0, qz0, p0; fma.rn.f16x2 p1, qz1, qz1, c; fma.rn.f16x2 g13, qz29, h1, qz29; prmt.b32 h0, lo0, hi0, 0x5410;\n"
        "mov.b32 {xl, xh}, a0; tanh.approx.f16 xr, xl; cvt.u32.u16 lo0, xr; tanh.approx.f16 xr, xh; cvt.u32.u16 hi0, xr; mul.rn.f16x2 a1, qz1, p1; fma.rn.f16x2 p0, qz2, qz2, c; fma.rn.f16x2 g14, qz30, h0, qz30; prmt.b32 h1, lo1, hi1, 0x5410;\n"
        "mov.b32 {xl, xh}, a1; tanh.approx.f16 xr, xl; cvt.u32.u16 lo1, xr; tanh.approx.f16 xr, xh; cvt.u32.u16 hi1, xr; mul.rn.f16x2 a2, qz2, p0; fma.rn.f16x2 p1, qz3, qz3, c; fma.rn.f16x2 g15, qz31, h1, qz31; prmt.b32 h0, lo0, hi0, 0x5410;\n"
        "B2:\n"
        "wgmma.fence.sync.aligned;\n"
        "add.s64 dt, w2d, 1472; wgmma.mma_async.sync.aligned.m64n96k16.f16.f16.f16 {o0,o1,o2,o3,o4,o5,o6,o7,o8,o9,o10,o11,o12,o13,o14,o15,o16,o17,o18,o19,o20,o21,o22,o23}, {g12,g13,g14,g15}, dt, pt, 1, 1, 1;\n"
        "wgmma.commit_group.sync.aligned;\n"
        "@!pm bra.uni BE;\n"
        "mov.b32 {xl, xh}, a2; tanh.approx.f16 xr, xl; cvt.u32.u16 lo0, xr; tanh.approx.f16 xr, xh; cvt.u32.u16 hi0, xr; mul.rn.f16x2 a3, qz3, p1; fma.rn.f16x2 p0, qz4, qz4, c; fma.rn.f16x2 g0, qz0, h0, qz0; prmt.b32 h1, lo1, hi1, 0x5410;\n"
        "mov.b32 {xl, xh}, a3; tanh.approx.f16 xr, xl; cvt.u32.u16 lo1, xr; tanh.approx.f16 xr, xh; cvt.u32.u16 hi1, xr; mul.rn.f16x2 a0, qz4, p0; fma.rn.f16x2 p1, qz5, qz5, c; fma.rn.f16x2 g1, qz1, h1, qz1; prmt.b32 h0, lo0, hi0, 0x5410;\n"
        "mov.b32 {xl, xh}, a0; tanh.approx.f16 xr, xl; cvt.u32.u16 lo0, xr; tanh.approx.f16 xr, xh; cvt.u32.u16 hi0, xr; mul.rn.f16x2 a1, qz5, p1; fma.rn.f16x2 p0, qz6, qz6, c; fma.rn.f16x2 g2, qz2, h0, qz2; prmt.b32 h1, lo1, hi1, 0x5410;\n"
        "mov.b32 {xl, xh}, a1; tanh.approx.f16 xr, xl; cvt.u32.u16 lo1, xr; tanh.approx.f16 xr, xh; cvt.u32.u16 hi1, xr; mul.rn.f16x2 a2, qz6, p0; fma.rn.f16x2 p1, qz7, qz7, c; fma.rn.f16x2 g3, qz3, h1, qz3; prmt.b32 h0, lo0, hi0, 0x5410;\n"
        "BE:\n"
        "wgmma.wait_group.sync.aligned 0;\n"
        "bra.uni LOOP;\n"
        "STORE:\n"
        "bar.sync tt, 128;\n"
        "setp.lt.s32 pr, n, 0;\n"
        "@pr bra.uni STOREB;\n"
        "cvt.u64.u32 gp, off; add.s64 gp, gp, %11;\n"
        "elect.sync _|pr, 0xffffffff;\n"
        "@pr cp.async.bulk.global.shared::cta.bulk_group [gp], [%4], 12288;\n"
        "@pr cp.async.bulk.commit_group;\n"
        "bra.uni STOREB;\n"
        "YLOAD:\n"
        "@!pm bra.uni YLOADP;\n"
        "cp.async.bulk.wait_group.read 0;\n"
        "sub.u32 ad, off, %8; cvt.u64.u32 gp, ad; add.s64 gp, gp, %11;\n"
        "elect.sync _|pr, 0xffffffff;\n"
        "@pr mbarrier.arrive.expect_tx.shared::cta.b64 _, [ybar], 12288;\n"
        "@pr cp.async.bulk.shared::cluster.global.mbarrier::complete_tx::bytes [%4], [gp], 12288, [ybar];\n"
        "YLOADP:\n"
        "cvt.u64.u32 gp, off; add.s64 gp, gp, %10;\n"
        "elect.sync _|pr, 0xffffffff;\n"
        "@pr cp.async.bulk.prefetch.L2.global.L2::cache_hint [gp], 12288, pol;\n"
        "bra.uni YLOADB;\n"
        "XLOAD:\n"
        "bar.sync tt, 128;\n"
        "cp.async.bulk.wait_group.read 0;\n"
        "cvt.u64.u32 gp, off; add.s64 gp, gp, %10;\n"
        "elect.sync _|pr, 0xffffffff;\n"
        "@pr mbarrier.arrive.expect_tx.shared::cta.b64 _, [xbar], 12288;\n"
        "@pr cp.async.bulk.shared::cluster.global.mbarrier::complete_tx::bytes.L2::cache_hint [%4], [gp], 12288, [xbar], pol;\n"
        "bra.uni XLOADB;\n"
        "SPINY: mov.u32 cnt, 0;\n"
        "SPINYL:\n"
        "add.u32 tt, n, 1; and.b32 tt, tt, 1; mbarrier.try_wait.parity.shared::cta.b64 pw, [ybar], tt;\n"
        "@pw bra.uni BACKY;\n"
        "add.u32 cnt, cnt, 1; setp.lt.u32 pw, cnt, 0x100000;\n"
        "@pw bra.uni SPINYL;\n"
        "trap;\n"
        "SPINX: mov.u32 cnt, 0;\n"
        "SPINXL:\n"
        "and.b32 tt, n, 1; mbarrier.try_wait.parity.shared::cta.b64 pw, [xbar], tt;\n"
        "@pw bra.uni BACKX;\n"
        "add.u32 cnt, cnt, 1; setp.lt.u32 pw, cnt, 0x100000;\n"
        "@pw bra.uni SPINXL;\n"
        "trap;\n"
        "SPINT: mov.u32 cnt, 0;\n"
        "SPINTL:\n"
        "mad.lo.u32 tt, n, 8, tbar; mbarrier.try_wait.parity.shared::cta.b64 pw, [tt], tpar;\n"
        "@pw bra.uni BACKT;\n"
        "add.u32 cnt, cnt, 1; setp.lt.u32 pw, cnt, 0x100000;\n"
        "@pw bra.uni SPINTL;\n"
        "trap;\n"
        "SPINW0: mov.u32 cnt, 0;\n"
        "SPINW0L:\n"
        "mov.u32 tt, 231208; mbarrier.try_wait.parity.shared::cta.b64 pw, [tt], 0;\n"
        "@pw bra.uni BACKW0;\n"
        "add.u32 cnt, cnt, 1; setp.lt.u32 pw, cnt, 0x100000;\n"
        "@pw bra.uni SPINW0L;\n"
        "trap;\n"
        "SPINW1: mov.u32 cnt, 0;\n"
        "SPINW1L:\n"
        "mov.u32 tt, 231216; mbarrier.try_wait.parity.shared::cta.b64 pw, [tt], 0;\n"
        "@pw bra.uni BACKW1;\n"
        "add.u32 cnt, cnt, 1; setp.lt.u32 pw, cnt, 0x100000;\n"
        "@pw bra.uni SPINW1L;\n"
        "trap;\n"
        "DONE:\n"
        "wgmma.wait_group.sync.aligned 0;\n"
        "}\n"
        :: "r"(prm.w1desc), "r"(prm.w2desc), "r"(c.wg), "r"(c.off), "r"(c.xs), "r"(c.a_offs), "r"(c.xs_offs), "r"(c.bias_addr),
           "r"(c.step), "r"(c.w), "l"(prm.x), "l"(prm.out)
        : "memory");
}

__device__ __forceinline__ float warp_sum(float v) {
#pragma unroll
    for (int s = 16; s >= 1; s >>= 1) v += __shfl_xor_sync(0xffffffffu, v, s);
    return v;
}
__device__ __forceinline__ float pow2f(int e) { return __uint_as_float((uint32_t)(e + 127) << 23); }
__device__ __forceinline__ int exponent_of(float v) { return (int)(__float_as_uint(v) >> 23) - 127; }
__device__ __forceinline__ float lds_bf16(uint32_t addr) {
    uint16_t v; asm volatile("ld.shared.u16 %0, [%1];" : "=h"(v) : "r"(addr) : "memory"); return bf_lo(v);
}

__device__ __forceinline__ void publish_bias(const Params& prm, uint32_t c, uint32_t tag) {
    const uint32_t lane = fresh_tid() & 31;
    const uint32_t col = sb + SM_W2 + (c >> 5) * 24576 + lane * 64 + ((((c >> 3) ^ (lane >> 1)) & 3) * 16) + (c & 7) * 2;
    float v = 0.0f;
#pragma unroll
    for (int k = 0; k < EX / 32; k++) v = fmaf(lds_bf16(col + k * 2048), lds_bf16(sb + SM_BETA + lane * 2 + k * 64), v);
    v = warp_sum(v);
    if (lane == 0)
        asm volatile("st.relaxed.gpu.global.u64 [%0], %1;" ::"l"(prm.g->bias + c), "l"((uint64_t)tag << 32 | __float_as_uint(v)) : "memory");
}
__device__ __forceinline__ void collect_bias(const Params& prm, uint32_t tag) {
    const uint32_t lane = fresh_tid() & 31;
    if (lane < 24) {
        const unsigned long long* src = prm.g->bias + 32 * (lane >> 3) + 8 * (lane & 3) + (lane & 4);
        uint32_t v[4], t[4], spins = 0;
        for (;;) {
#pragma unroll
            for (int k = 0; k < 4; k++)
                asm volatile("{\n.reg .b64 w;\nld.relaxed.gpu.global.u64 w, [%2];\nmov.b64 {%0, %1}, w;\n}\n"
                             : "=r"(v[k]), "=r"(t[k]) : "l"(src + k) : "memory");
            if (t[0] == tag && t[1] == tag && t[2] == tag && t[3] == tag) break;
            if (++spins > (1u << 22)) __trap();
        }
        sts128(sb + SM_BIAS + lane * 16, v[0], v[1], v[2], v[3]);
    }
    __syncwarp();
}
__device__ __forceinline__ float fetch_w2_row(uint32_t (&u)[12][4], uint32_t row, uint32_t sw) {
    uint32_t mx[4] = {};
#pragma unroll
    for (int a = 0; a < 3; a++)
#pragma unroll
        for (int k = 0; k < 4; k++) {
            asm volatile("ld.shared.v4.b32 {%0,%1,%2,%3}, [%4];"
                         : "=r"(u[a * 4][k]), "=r"(u[a * 4 + 1][k]), "=r"(u[a * 4 + 2][k]), "=r"(u[a * 4 + 3][k])
                         : "r"(row + a * 24576 + ((k * 16) ^ sw)) : "memory");
#pragma unroll
            for (int b = 0; b < 4; b++) asm("max.xorsign.abs.bf16x2 %0, %0, %1;" : "+r"(mx[b]) : "r"(u[a * 4 + b][k]));
        }
#pragma unroll
    for (int b = 1; b < 4; b++) asm("max.xorsign.abs.bf16x2 %0, %0, %1;" : "+r"(mx[0]) : "r"(mx[b]));
    return fmaxf(fabsf(bf_lo(mx[0])), fabsf(bf_hi(mx[0])));
}

template <bool FAST> __device__ __forceinline__ bool grn_stats(float ss, float gm, float bt, float top, int e, float& gx, float& inv, int& eo) {
    gx = sqrt_fast(fmaf(ss, INV_2A * INV_2A, 1e-6f));
    const float rt = sqrt_fast(ss + 1.0f) * INV_2A * top;
    uint32_t r[4] = {FAST ? __reduce_add_sync(0xffffffffu, __float2uint_rn(gx * 128.0f)) : __float_as_uint(warp_sum(gx)),
                     __reduce_max_sync(0xffffffffu, __float_as_uint(fmaf(bt, top, rt))),
                     __reduce_max_sync(0xffffffffu, __float_as_uint(rt * fabsf(gm) * gx)),
                     (uint32_t)__any_sync(0xffffffffu, !(ss >= 16.0f && ss < ACC_LIMIT))};
    if ((e & 31) == 0) sts128(sb + SM_SEL + (e >> 5) * 16, r[0], r[1], r[2], r[3]);
    MARK(6);
    named_sync(10, 512);
    lds128(r, sb + SM_SEL + min(e & 15, 11) * 16);
    if ((e & 31) >= 12) r[0] = 0;
    const float tot = FAST ? __uint2float_rn(__reduce_add_sync(0xffffffffu, r[0])) * (1.0f / 128) : warp_sum(__uint_as_float(r[0]));
    inv = __fdividef(1.0f, fmaf(tot, 1.0f / EX, 1e-6f));
    const float bound = fmaf(__uint_as_float(__reduce_max_sync(0xffffffffu, r[2])), inv,
                             __uint_as_float(__reduce_max_sync(0xffffffffu, r[1]))) * EX;
    eo = min(max(exponent_of(bound), -90), 126) - 14;
    return __any_sync(0xffffffffu, r[3]);
}

__device__ __forceinline__ float exact_sums(const Params& prm) {
    const int lane = fresh_tid() & 31, warp = fresh_warp(), wg = warp >> 2;
    const uint32_t epoch = lds32(sb + SM_RED + (RED_EPOCH + 1) * 4), bar = sb + SM_BAR + BAR_W1 * 8;
    if (wg < 3) {
        uint32_t wa[2][24], d[2][16];
        float acc[2][2] = {};
        const uint32_t yd = prm.ydesc + ((SM_SPARE - SM_Y1) >> 4), wd = prm.w1desc + ((2 * wg * 12288 + 5 * 2048) >> 4);
        load_w1t(wa, wg, warp & 3, lane);
#pragma unroll 1
        for (int n = 0; n < ROWS_PER_CTA; n++) {
            if (warp == 0) {
                expect_tx(bar, TILE_BYTES);
                bulk_load(sb + SM_SPARE, (const char*)prm.out + (cta_tile0(fresh_cta()) + n * cta_stride(fresh_cta())), TILE_BYTES, bar);
            }
            mbar_wait(bar, (n + 1) & 1);
            gemm1_t<0>(d[0], wa[0], yd, wd);
            gemm1_t<1>(d[1], wa[1], yd, wd);
            wg_wait<0>();
            pin(d[0]); pin(d[1]);
            gelu_sumsq_f(d[0], acc[0]);
            gelu_sumsq_f(d[1], acc[1]);
            named_sync(1, 384);
        }
        publish_sums(acc, prm.g->sums[epoch & 1], &prm.g->count[1], wg, warp & 3, lane);
    }
    grid_wait(&prm.g->count[1], (epoch + 1) * NUM_CTAS);
    return __ldcg(prm.g->sums[epoch & 1] + fresh_tid() % EX);
}

template <bool FIRST> __device__ __forceinline__ void prepare_pass2(const Pass2& c, const Params& prm, float ss) {
    const int tid = fresh_tid(), lane = tid & 31, warp = fresh_warp(), wg = warp >> 2;
    const int e = tid >= EX ? tid - EX : tid;
    const uint32_t w2row = sb + SM_W2 + e * 64, sw = ((e >> 1) & 3) * 16;
    pass2_start(c, prm);
    MARK(2);
    if (wg) {
        uint32_t u[12][4];
        mbar_wait_c<0>(sb + SM_BAR + BAR_W2 * 8);
        const uint32_t epoch = lds32(sb + SM_RED + RED_EPOCH * 4);
        unsigned long long seen = 0;
        if (FIRST) asm volatile("ld.relaxed.gpu.global.u64 %0, [%1];" : "=l"(seen) : "l"(acc_word(prm, epoch, e)) : "memory");
        const float top = fetch_w2_row(u, w2row, sw);
        MARK(3);
        const float gm = lds_bf16(sb + SM_GAMMA + e * 2), bt = fabsf(lds_bf16(sb + SM_BETA + e * 2));
        if (FIRST) {
            if (wg == 3) named_sync(11, EX);
            if (warp == 12) collect_bias(prm, epoch + 1);
            MARK(4);
            ss = collect_fast(acc_word(prm, epoch, e), seen);
            if (tid == 416 && fresh_cta() == 0) prm.g->count[0] = epoch + 1;
        }
        if (warp == 4) TS(4);
        MARK(5);
        float gx, inv;
        int eo;
        const bool redo = (grn_stats<FIRST>(ss, gm, bt, top, e, gx, inv, eo) || FORCE_EXACT) && FIRST;
        MARK(8);
        const float up = pow2f(eo), dn = pow2f(-eo);
        if (warp == 4) {
            if (lane == 24) sts64(sb + SM_RED + RED_SCALE * 4, pack_bf2(up, up), redo);
            if (lane < 24 && !redo) {
                uint32_t b[4];
                lds128(b, sb + SM_BIAS + lane * 16);
                const uint32_t p0 = pack_h2(__uint_as_float(b[0]) * dn, __uint_as_float(b[1]) * dn);
                const uint32_t p1 = pack_h2(__uint_as_float(b[2]) * dn, __uint_as_float(b[3]) * dn);
                sts128(sb + SM_BIAS + lane * 16, p0, p0, p1, p1);
            }
            __syncwarp();
            mbar_arrive_if(sb + SM_BAR + BAR_STAT * 8, lane == 0);
        }
        if (!redo) {
            float sc = fmaf(gm, gx * inv, 1.0f) * INV_2A;
            if (eo > 6) {
                const uint32_t dn2 = pack_bf2(dn, dn);
#pragma unroll
                for (int k = 0; k < 48; k++) u[k >> 2][k & 3] = bf2_mul(u[k >> 2][k & 3], dn2);
            } else {
                sc *= dn;
            }
            const uint32_t s2 = pack_bf2(sc * 0x1p-112f, sc * 0x1p-112f);
#pragma unroll
            for (int k = 0; k < 12; k++) {
                uint32_t v[4];
#pragma unroll
                for (int b = 0; b < 4; b++) {
                    v[b] = bf2_mul(u[k][b], s2);
                    v[b] += (v[b] & 0x7fff7fffu) * 7u;
                }
                sts128(w2row + (k >> 2) * 24576 + (((k & 3) * 16) ^ sw), v[0], v[1], v[2], v[3]);
            }
            MARK(9);
            fence_async_smem();
            __syncwarp();
            mbar_arrive_if(sb + SM_BAR + (BAR_ROWS + (wg != 3)) * 8, lane == 0);
        }
        if (warp == 4) TS(5);
    } else {
        asm volatile("bar.arrive 10, 512;" ::: "memory");
    }
}

__device__ __forceinline__ void pass2_uniform(Pass2& c) {
    const int warp = fresh_warp(), wg = warp >> 2;
    c.wg = wg;
    c.w = warp & 3;
    c.off = cta_tile0(fresh_cta()) + (ROWS_PER_CTA - 1 - wg) * cta_stride(fresh_cta());
    c.step = 4 * cta_stride(fresh_cta());
    c.xs = wg == 3 ? sb + SM_BUF3 : sb + SM_Y1 + (wg == 2 ? 2 : 1 - wg) * SLOT_BYTES;
    static_assert((ROWS_PER_CTA - 1) % NX == 1, "slot of the last tile");
}
__device__ __forceinline__ Pass2 pass2_setup() {
    Pass2 c;
    pass2_uniform(c);
    const int lane = fresh_tid() & 31, w = c.w, arow = 16 * w + (lane & 15);
    c.a_offs = (arow * 128 + (((lane >> 4) ^ (arow & 7)) * 16)) |
               (8192 + arow * 64 + (((lane >> 4) ^ ((arow >> 1) & 3)) * 16)) << 16;
    const int g = lane >> 2, px = 33 * (g & 1) + 4 * (g >> 1) + 16 * (w >> 1) + 2 * (w & 1);
    c.xs_offs = (px * 192 + (lane & 3) * 16) | ((px ^ 1) * 192 + (lane & 3) * 16) << 16;
    c.bias_addr = sb + SM_BIAS + (lane & 3) * 16;
    return c;
}

__global__ void __launch_bounds__(512, 1) convnext_kernel(const __grid_constant__ Params prm) {
    extern __shared__ __align__(1024) uint8_t smem[];
    if ((uint32_t)__cvta_generic_to_shared(smem) != sb) __trap();
    {
        const uint32_t tid = fresh_tid(), warp = fresh_warp(), lane = tid & 31;
        if (warp == 0) {
            if (lane == 0) {
#pragma unroll
                for (int k = 0; k < NX; k++) mbar_init(sb + SM_GO + k * 8, 2);
                mbar_init(sb + SM_BAR + BAR_DW * 8, 1);
                mbar_init(sb + SM_BAR + BAR_W1 * 8, 1);
                mbar_init(sb + SM_BAR + BAR_W1B * 8, 1);
                fence_async_smem();
            }
            __syncwarp();
            expect_tx(sb + SM_BAR + BAR_DW * 8, 9 * CH * 2);
            bulk_load(sb + SM_Y1, prm.dw, 9 * CH * 2, sb + SM_BAR + BAR_DW * 8);
            const RowCopy rc = row_copy(prm);
#pragma unroll
            for (int k = 0; k < NX; k++) issue_row_load(rc, k, k);
            SMARK(4);
        }
        if (fresh_warp() == 15) {
            const uint32_t cta = fresh_cta();
            bulk_prefetch((const char*)prm.w1 + cta * (CH * EX * 2 / NUM_CTAS), CH * EX * 2 / NUM_CTAS);
            bulk_prefetch(prm.dw, 9 * CH * 2);
            bulk_prefetch((const char*)prm.x + (cta_tile0(cta) - cta_stride(cta)), TILE_BYTES);
        } else if (warp == 2) {
            if (lane < 2) asm volatile("prefetch.tensormap [%0];" ::"l"(&prm.w1_map + lane) : "memory");
        } else if (warp - 6u < 6) {
            if (lane == 0) {
#pragma unroll 1
                for (int k = NX + warp - 6; k < GO_COUNT + ROWS_PER_CTA + 2; k += 6)
                    mbar_init(sb + SM_GO + k * 8, k < 2 * NX ? 2 : k < GO_COUNT ? 14 : 4);
                fence_async_smem();
            }
        } else if (warp == 3) {
            const uint32_t one = (lane & 5) == ((lane & 8) >> 1) + (lane >> 4) ? 0x3f803f80u : 0u;
            sts128(sb + SM_SEL + lane * 16, one, one, one, one);
            fence_async_smem();
        } else if (tid - 128u < NX * 12 && ((fresh_cta() + 1) & 7) < 2) {
            const int k = tid - 128;
            sts128(sb + SM_X + (k / 12) * SLOT_BYTES + ((fresh_cta() & 7) == 0 ? 0 : XHALF_B + 33 * 192) + (k % 12) * 16, 0, 0, 0, 0);
        }
        __syncwarp();
        SMARK(3);
        named_sync(0, 512);
    }
    if (fresh_warp() >= 12) {
        Producer pc;
        SMARK(0);
        asm volatile("setmaxnreg.inc.sync.aligned.u32 %0;" ::"n"(PRODUCER_REGS));
        SMARK(1);
        const int w = fresh_warp() & 3, lane = fresh_tid() & 31;
        const int j = lane & 7, hb = (lane >> 3) & 1, base = 4 * (2 * w + (lane >> 4));
        pc.lane = lane;
        pc.xoff[0] = hb * XHALF_B + base * 192 + j * 16;
        pc.xoff[1] = hb * XHALF_B + base * 192 + 128 + j * 8;
        const int grp = 4 * w + (lane >> 3);
#pragma unroll
        for (int o = 0; o < 2; o++) {
            const int row = (grp & 7) + 8 * (o ^ hb) + 32 * (grp >> 3);
            pc.yoff[0][o] = row * 128 + ((j ^ (row & 7)) * 16);
            pc.yoff[1][o] = 8192 + row * 64 + (((j >> 1) ^ ((row >> 1) & 3)) * 16) + (j & 1) * 8;
        }
        pc.stat = sb + SM_STAT + (8 * w + (lane >> 2)) * 32;
        pc.own = pc.stat + (lane & 3) * 8;
        const int dstep = fresh_cta() & 8 ? 3 * CH * 2 : -3 * CH * 2;
        mbar_wait_c<0>(sb + SM_BAR + BAR_DW * 8);
        SMARK(8);
#pragma unroll
        for (int tap = 0; tap < 9; tap++) {
            const uint32_t dw = sb + SM_Y1 + (3 + tap % 3) * CH * 2 + (tap / 3 - 1) * dstep;
            lds128(pc.w[tap], dw + j * 16);
            asm volatile("ld.shared.v2.b32 {%0,%1}, [%2];" : "=r"(pc.w[tap][4]), "=r"(pc.w[tap][5]) : "r"(dw + 128 + j * 8) : "memory");
        }
#pragma unroll
        for (int tap = 0; tap < 9; tap++)
#pragma unroll
            for (int u = 0; u < 6; u++) pc.w[tap][u] = bf2_mul(pc.w[tap][u], TAP_SCALE_BF2);
        produce(pc, prm);
        TS(9);
        asm volatile("setmaxnreg.dec.sync.aligned.u32 %0;" ::"n"(EVEN_REGS));
        if (fresh_warp() == 12) {
            mbar_wait_c<0>(sb + SM_BAR + BAR_W2 * 8);
            if (fresh_cta() < CH) publish_bias(prm, fresh_cta(), lds32(sb + SM_RED + RED_EPOCH * 4) + 1);
        }
    } else {
        asm volatile("setmaxnreg.dec.sync.aligned.u32 %0;" ::"n"(CONSUMER_REGS));
        {
            const int tid = fresh_tid(), warp = fresh_warp();
            if (warp == 1) {
#pragma unroll
                for (int h = 0; h < 2; h++) {
                    const uint32_t bar = sb + SM_BAR + (h ? BAR_W1B : BAR_W1) * 8;
                    expect_tx(bar, CH * EX);
#pragma unroll
                    for (int q = h; q < 6; q += 2) tma_load_2d(sb + SM_W1 + q * 12288, &prm.w1_map, 64 * q, 0, bar);
                }
            }
            uint32_t cnt[2];
            asm volatile("ld.relaxed.gpu.global.v2.u32 {%0, %1}, [%2];" : "=r"(cnt[0]), "=r"(cnt[1]) : "l"(prm.g->count) : "memory");
            SMARK(0);
            if (warp == 2) {
                const RowCopy rc = row_copy(prm);
#pragma unroll 1
                for (int i = loop_init<0>(); i < NX; i++) {
                    named_sync(6 + i, 160);
                    issue_row_load(rc, i + NX, i);
                }
            }
            if (tid == 256) {
                sts64(sb + SM_RED + RED_EPOCH * 4, cnt[0], cnt[1] / NUM_CTAS);
#pragma unroll
                for (int k = 0; k < BAR_DW; k++)
                    if (k != BAR_W1 && k != BAR_W1B) mbar_init(sb + SM_BAR + k * 8, k < BAR_TURN || k == BAR_STAT ? 1 : k == BAR_ROWS + 1 ? 8 : 4);
#pragma unroll
                for (int k = 0; k < 3; k++) mbar_arrive_if(sb + SM_BAR + (BAR_Y2FULL + k) * 8, true);
            }
            if (fresh_cta() == 0) *acc_word(prm, cnt[0] + 1, tid) = 0;
            if (fresh_cta() == 1) prm.g->sums[~(cnt[1] / NUM_CTAS) & 1][tid] = 0.0f;
            __syncwarp();
            SMARK(1);
            mbar_wait_c<0>(sb + SM_BAR + BAR_W1 * 8);
            SMARK(2);
        }

        const int tid = fresh_tid(), lane = tid & 31, wg = fresh_warp() >> 2, w = fresh_warp() & 3;
        float acc[2][2];
        const int c = 8 * (lane >> 4) + (lane & 7), ck = 2 * w + ((lane >> 3) & 1);
        consume(acc, sb + SM_W1 + 2 * wg * 12288 + c * 128 + ((ck ^ (c & 7)) * 16), prm.ydesc,
                prm.w1desc + (((2 * wg + 1) * 12288 + 5 * 2048) >> 4), wg * SLOT_BYTES, make_duty(prm, wg, w), w, lane, prm);
        publish_fast(prm, acc, lds32(sb + SM_RED + RED_EPOCH * 4), wg, w, lane);
        if (wg) asm volatile("bar.arrive 11, 384;" ::: "memory");
        MARK(0);
        bulk_wait_all();
        if (wg == 0) TS(3);
        asm volatile("setmaxnreg.inc.sync.aligned.u32 %0;" ::"n"(EVEN_REGS));
    }

    {
        asm volatile(PASS2_STATE);
        MARK(1);
        Pass2 c = pass2_setup();
        prepare_pass2<true>(c, prm, 0.0f);
        if (pass2_head(c, 0)) {
            const float ss = exact_sums(prm);
            c = pass2_setup();
            prepare_pass2<false>(c, prm, ss);
            pass2_head(c, 1);
        }

        pass2_uniform(c);
        pass2_tiles(c, prm);
        bulk_wait_read<0>();
        MARK(13);
    }
}

}

extern "C" void kernel_launch(void* const* d_in, const int* in_sizes, int n_in, void* d_out, int out_size) {
    (void)in_sizes; (void)n_in; (void)out_size;
    typedef CUresult (*EncodeFn)(CUtensorMap*, CUtensorMapDataType, cuuint32_t, void*, const cuuint64_t*, const cuuint64_t*,
                                 const cuuint32_t*, const cuuint32_t*, CUtensorMapInterleave, CUtensorMapSwizzle,
                                 CUtensorMapL2promotion, CUtensorMapFloatOOBfill);
    void* fn = nullptr;
    cudaDriverEntryPointQueryResult status;
    cudaGetDriverEntryPoint("cuTensorMapEncodeTiled", &fn, cudaEnableDefault, &status);
    const EncodeFn encode = (EncodeFn)fn;
    const cuuint32_t ones[2] = {1, 1};

    Params p;
    {
        const cuuint64_t dims[2] = {EX, CH}, strides[1] = {EX * 2};
        const cuuint32_t box[2] = {64, CH};
        encode(&p.w1_map, CU_TENSOR_MAP_DATA_TYPE_BFLOAT16, 2, d_in[2], dims, strides, box, ones,
               CU_TENSOR_MAP_INTERLEAVE_NONE, CU_TENSOR_MAP_SWIZZLE_128B, CU_TENSOR_MAP_L2_PROMOTION_NONE,
               CU_TENSOR_MAP_FLOAT_OOB_FILL_NONE);
    }
    {
        const cuuint64_t dims[2] = {CH, EX}, strides[1] = {CH * 2};
        const cuuint32_t box[2] = {32, 192};
        encode(&p.w2_map, CU_TENSOR_MAP_DATA_TYPE_BFLOAT16, 2, d_in[3], dims, strides, box, ones,
               CU_TENSOR_MAP_INTERLEAVE_NONE, CU_TENSOR_MAP_SWIZZLE_64B, CU_TENSOR_MAP_L2_PROMOTION_NONE,
               CU_TENSOR_MAP_FLOAT_OOB_FILL_NONE);
    }
    p.x = (const __nv_bfloat16*)d_in[0];
    p.dw = (const __nv_bfloat16*)d_in[1];
    p.w1 = (const __nv_bfloat16*)d_in[2];
    p.gamma = (const __nv_bfloat16*)d_in[4];
    p.beta = (const __nv_bfloat16*)d_in[5];
    p.out = (__nv_bfloat16*)d_out;
    cudaGetSymbolAddress((void**)&p.g, g_scratch);
    p.w1desc = desc_lo(sb + SM_W1, 12288);
    p.w2desc = desc_lo(sb + SM_W2, 24576);
    p.ydesc = desc_lo(sb + SM_Y1, 16);
    p.ydesc64[0] = (0x40000040ull << 32) | p.ydesc;
    p.ydesc64[1] = (0x80000020ull << 32) | (p.ydesc + 512);
    for (int k = 0; k < 3; k++) p.sel[k] = (8ull << 32) | desc_lo(sb + SM_SEL + k * 128, k == 2 ? 128 : 0);
    constexpr int smem_bytes = SM_TOTAL;
    cudaFuncSetAttribute(convnext_kernel, cudaFuncAttributeMaxDynamicSharedMemorySize, smem_bytes);
    convnext_kernel<<<NUM_CTAS, 512, smem_bytes>>>(p);
}
```

```cpp
#include <cuda.h>
#include <cuda_runtime.h>
#include <cuda_bf16.h>
#include <stdint.h>

namespace {

constexpr int IMG_W = 512, CH = 96, EX = 384;
constexpr int TILE_PX = 64;
constexpr int ROWS_PER_CTA = 32;
constexpr int NUM_CTAS = 128;
constexpr int STEPS = ROWS_PER_CTA + 2;
constexpr int ROW_BYTES = IMG_W * CH * 2;

#define FORCE_EXACT 0
constexpr int PRODUCER_REGS = 200, CONSUMER_REGS = 104, EVEN_REGS = 128;

constexpr int XHALF_BYTES = 34 * 192;
constexpr int XHALF_B = XHALF_BYTES + 64;
constexpr int XROW_BYTES = XHALF_B + XHALF_BYTES + 64;
constexpr int L2_AHEAD = 2;
constexpr int NX = 3;
constexpr int TILE_BYTES = TILE_PX * 192;

constexpr uint32_t sb = 1024;
constexpr int SM_W1 = 0;
constexpr int SM_W2 = 73728;
constexpr int SM_RING = 147456;
constexpr int SLOT_BYTES = 26624;
constexpr int SM_Y1 = SM_RING;
constexpr int SM_X = SM_Y1 + TILE_BYTES;
constexpr int SM_STAT = SM_X + XROW_BYTES;
constexpr int SM_BUF3 = SM_X + SLOT_BYTES, SM_SPARE = SM_X;
constexpr int SM_SEL = SM_RING + NX * SLOT_BYTES;
constexpr int SM_BIAS = SM_SEL + 512;
constexpr int SM_GAMMA = SM_BIAS + 384;
constexpr int SM_BETA = SM_GAMMA + EX * 2;
constexpr int SM_RED = SM_BETA + EX * 2;
constexpr int SM_BAR = SM_RED + 16;
constexpr int BAR_Y2FULL = 0, BAR_XSFULL = 4, BAR_W1 = 8, BAR_W2 = 9, BAR_W1B = 10, BAR_TURN = 11, BAR_ROWS = 51,
              BAR_STAT = 53, BAR_DW = 54, BAR_COUNT = 55;
constexpr int SM_GO = SM_BAR + BAR_COUNT * 8, GO_COUNT = ROWS_PER_CTA + 2 * NX;
constexpr int SM_YFULL = SM_GO + (GO_COUNT + 1) * 8;
constexpr int SM_TOTAL = SM_YFULL + (ROWS_PER_CTA + 1) * 8;
static_assert(SM_STAT + TILE_PX * 16 <= SM_RING + SLOT_BYTES && XROW_BYTES >= TILE_BYTES && SM_X % 1024 == 0, "ring layout");
static_assert(SM_TOTAL <= 232448, "smem budget");
static_assert(SM_STAT % 128 == 0 && SM_BIAS % 16 == 0 && SM_BAR % 8 == 0 && SLOT_BYTES % 1024 == 0, "alignment");

constexpr int RED_EPOCH = 0, RED_SCALE = 2;

constexpr float GELU_A = 0.32920349f;
constexpr uint32_t GELU_C_H2 = 0x40D940D9u;
constexpr float INV_2A = 1.0f / (2.0f * GELU_A);

constexpr uint32_t TAP_SCALE_BF2 = 0x2B802B80u;
constexpr float LN_EPS_SCALED = 1e-5f * 0x1p-80f;
constexpr float RSTD_SCALE = GELU_A * 0x1p-112f;

struct Scratch {
    unsigned long long acc[2][EX / 4 * 32];
    unsigned long long bias[CH];
    float sums[2][EX];
    uint4 zero_row[66 * 192 / 16];
    unsigned int count[2];
};
__device__ __align__(256) Scratch g_scratch;
constexpr float ACC_LIMIT = 0x1p30f;

#define TS(k)
#define ASM_TS
#define MARK(k)
#define SMARK(k)
#define ASM_MARK
#define ASM_SMARK
#define ASM_TRC(it)

__device__ __forceinline__ void mbar_init(uint32_t bar, uint32_t count) {
    asm volatile("mbarrier.init.shared::cta.b64 [%0], %1;" ::"r"(bar), "r"(count) : "memory");
}
__device__ __forceinline__ void mbar_arrive_if(uint32_t bar, bool pred) {
    asm volatile("{\n.reg .pred p;\nsetp.ne.u32 p, %1, 0;\n@p mbarrier.arrive.shared::cta.b64 _, [%0];\n}\n"
                 ::"r"(bar), "r"((uint32_t)pred) : "memory");
}
__device__ __forceinline__ void mbar_wait(uint32_t bar, uint32_t parity) {
    asm volatile(
        "{\n.reg .pred p;\n.reg .u32 n;\n"
        "mbarrier.try_wait.parity.shared::cta.b64 p, [%0], %1;\n"
        "@p bra.uni WAIT_DONE;\n"
        "mov.u32 n, 0;\n"
        "WAIT_LOOP:\n"
        "mbarrier.try_wait.parity.shared::cta.b64 p, [%0], %1;\n"
        "@p bra.uni WAIT_DONE;\n"
        "mbarrier.try_wait.parity.shared::cta.b64 p, [%0], %1;\n"
        "@p bra.uni WAIT_DONE;\n"
        "mbarrier.try_wait.parity.shared::cta.b64 p, [%0], %1;\n"
        "@p bra.uni WAIT_DONE;\n"
        "add.u32 n, n, 1;\nsetp.lt.u32 p, n, 0x40000;\n"
        "@p bra.uni WAIT_LOOP;\n"
        "trap;\n"
        "WAIT_DONE:\n}\n"
        ::"r"(bar), "r"(parity) : "memory");
}
template <int PARITY> __device__ __forceinline__ void mbar_wait_c(uint32_t bar) {
    asm volatile(
        "{\n.reg .pred p;\n.reg .u32 n;\n"
        "mbarrier.try_wait.parity.shared::cta.b64 p, [%0], %1;\n"
        "@p bra.uni WAIT_DONE;\n"
        "mov.u32 n, 0;\n"
        "WAIT_LOOP:\n"
        "mbarrier.try_wait.parity.shared::cta.b64 p, [%0], %1;\n"
        "@p bra.uni WAIT_DONE;\n"
        "mbarrier.try_wait.parity.shared::cta.b64 p, [%0], %1;\n"
        "@p bra.uni WAIT_DONE;\n"
        "mbarrier.try_wait.parity.shared::cta.b64 p, [%0], %1;\n"
        "@p bra.uni WAIT_DONE;\n"
        "add.u32 n, n, 1;\nsetp.lt.u32 p, n, 0x40000;\n"
        "@p bra.uni WAIT_LOOP;\n"
        "trap;\n"
        "WAIT_DONE:\n}\n"
        ::"r"(bar), "n"(PARITY) : "memory");
}
#define ELECTED(body) "{\n.reg .pred p;\nelect.sync _|p, 0xffffffff;\n" body "}\n"
__device__ __forceinline__ void expect_tx(uint32_t bar, uint32_t bytes) {
    asm volatile(ELECTED("@p mbarrier.arrive.expect_tx.shared::cta.b64 _, [%0], %1;\n") ::"r"(bar), "r"(bytes) : "memory");
}
__device__ __forceinline__ void bulk_load(uint32_t dst, const void* src, uint32_t bytes, uint32_t bar) {
    asm volatile(ELECTED("@p cp.async.bulk.shared::cluster.global.mbarrier::complete_tx::bytes [%0], [%1], %2, [%3];\n")
                 ::"r"(dst), "l"(src), "r"(bytes), "r"(bar) : "memory");
}
__device__ __forceinline__ void bulk_prefetch(const void* src, uint32_t bytes) {
    asm volatile(ELECTED("@p cp.async.bulk.prefetch.L2.global [%0], %1;\n") ::"l"(src), "r"(bytes) : "memory");
}
__device__ __forceinline__ void tma_load_2d(uint32_t dst, const CUtensorMap* map, int c0, int c1, uint32_t bar) {
    asm volatile(ELECTED("@p cp.async.bulk.tensor.2d.shared::cluster.global.mbarrier::complete_tx::bytes [%0], [%1, {%2, %3}], [%4];\n")
                 ::"r"(dst), "l"(map), "r"(c0), "r"(c1), "r"(bar) : "memory");
}
template <int N> __device__ __forceinline__ void bulk_wait_read() {
    asm volatile("cp.async.bulk.wait_group.read %0;" ::"n"(N) : "memory");
}
__device__ __forceinline__ void bulk_wait_all() { asm volatile("cp.async.bulk.wait_group 0;" ::: "memory"); }
__device__ __forceinline__ void fence_async_smem() { asm volatile("fence.proxy.async.shared::cta;" ::: "memory"); }
__device__ __forceinline__ void named_sync(int id, int n) { asm volatile("bar.sync %0, %1;" ::"r"(id), "r"(n) : "memory"); }

__device__ __forceinline__ void sts64(uint32_t addr, uint32_t a, uint32_t b) {
    asm volatile("st.shared.v2.b32 [%0], {%1,%2};" ::"r"(addr), "r"(a), "r"(b) : "memory");
}
__device__ __forceinline__ void sts128(uint32_t addr, uint32_t a, uint32_t b, uint32_t c, uint32_t d) {
    asm volatile("st.shared.v4.b32 [%0], {%1,%2,%3,%4};" ::"r"(addr), "r"(a), "r"(b), "r"(c), "r"(d) : "memory");
}
__device__ __forceinline__ void ldsm4_t(uint32_t* r, uint32_t addr) {
    asm volatile("ldmatrix.sync.aligned.m8n8.x4.trans.shared.b16 {%0,%1,%2,%3}, [%4];"
                 : "=r"(r[0]), "=r"(r[1]), "=r"(r[2]), "=r"(r[3]) : "r"(addr) : "memory");
}
__device__ __forceinline__ void lds128(uint32_t* v, uint32_t addr) {
    asm volatile("ld.shared.v4.b32 {%0,%1,%2,%3}, [%4];"
                 : "=r"(v[0]), "=r"(v[1]), "=r"(v[2]), "=r"(v[3]) : "r"(addr) : "memory");
}
__device__ __forceinline__ uint32_t lds32(uint32_t addr) {
    uint32_t v; asm volatile("ld.shared.b32 %0, [%1];" : "=r"(v) : "r"(addr) : "memory"); return v;
}
__device__ __forceinline__ void sts32(uint32_t addr, uint32_t v) {
    asm volatile("st.shared.b32 [%0], %1;" ::"r"(addr), "r"(v) : "memory");
}

__device__ __forceinline__ uint32_t bf2_fma(uint32_t a, uint32_t b, uint32_t c) {
    uint32_t d; asm("fma.rn.bf16x2 %0, %1, %2, %3;" : "=r"(d) : "r"(a), "r"(b), "r"(c)); return d;
}
__device__ __forceinline__ uint32_t bf2_mul(uint32_t a, uint32_t b) {
    uint32_t d; asm("mul.rn.bf16x2 %0, %1, %2;" : "=r"(d) : "r"(a), "r"(b)); return d;
}
__device__ __forceinline__ uint32_t bf2_add(uint32_t a, uint32_t b) {
    uint32_t d; asm("add.rn.bf16x2 %0, %1, %2;" : "=r"(d) : "r"(a), "r"(b)); return d;
}
__device__ __forceinline__ uint32_t h2_fma(uint32_t a, uint32_t b, uint32_t c) {
    uint32_t d; asm("fma.rn.f16x2 %0, %1, %2, %3;" : "=r"(d) : "r"(a), "r"(b), "r"(c)); return d;
}
__device__ __forceinline__ uint32_t h2_mul(uint32_t a, uint32_t b) {
    uint32_t d; asm("mul.rn.f16x2 %0, %1, %2;" : "=r"(d) : "r"(a), "r"(b)); return d;
}
__device__ __forceinline__ uint32_t h2_tanh(uint32_t a) {
    uint32_t d; asm("tanh.approx.f16x2 %0, %1;" : "=r"(d) : "r"(a)); return d;
}
__device__ __forceinline__ float bf_lo(uint32_t v) { return __uint_as_float(v << 16); }
__device__ __forceinline__ float bf_hi(uint32_t v) { return __uint_as_float(v & 0xffff0000u); }
__device__ __forceinline__ uint32_t pack_h2(float lo, float hi) {
    uint32_t d; asm("cvt.rn.f16x2.f32 %0, %1, %2;" : "=r"(d) : "f"(hi), "f"(lo)); return d;
}
__device__ __forceinline__ uint32_t pack_bf2(float lo, float hi) {
    uint32_t d; asm("cvt.rn.bf16x2.f32 %0, %1, %2;" : "=r"(d) : "f"(hi), "f"(lo)); return d;
}
__device__ __forceinline__ void h2_unpack(uint32_t v, float& lo, float& hi) {
    asm("{\n.reg .b16 l, h;\nmov.b32 {l, h}, %2;\ncvt.f32.f16 %0, l;\ncvt.f32.f16 %1, h;\n}\n" : "=f"(lo), "=f"(hi) : "r"(v));
}

__device__ __forceinline__ uint32_t gelu2(uint32_t z) {
    uint32_t p = h2_fma(z, z, GELU_C_H2);
    uint32_t t = h2_tanh(h2_mul(z, p));
    return h2_fma(z, t, z);
}

__device__ __forceinline__ void wg_fence() { asm volatile("wgmma.fence.sync.aligned;" ::: "memory"); }
__device__ __forceinline__ void wg_commit() { asm volatile("wgmma.commit_group.sync.aligned;" ::: "memory"); }
template <int N> __device__ __forceinline__ void wg_wait() {
    asm volatile("wgmma.wait_group.sync.aligned %0;" ::"n"(N) : "memory");
}
template <int N> __device__ __forceinline__ void pin(uint32_t (&r)[N]) {
#pragma unroll
    for (int i = 0; i < N; i++) asm volatile("" : "+r"(r[i])::"memory");
}
constexpr uint32_t desc_lo(uint32_t addr, uint32_t lbo) { return ((addr & 0x3FFFF) >> 4) | ((lbo >> 4) << 16); }
template <uint32_t SBO, uint32_t SWZ> __device__ __forceinline__ uint64_t desc(uint32_t lo, uint32_t bytes) {
    return (((uint64_t)((SBO >> 4) | (SWZ << 30)) << 32) | lo) + (bytes >> 4);
}
__device__ __forceinline__ uint32_t fresh_tid() {
    uint32_t v; asm volatile("mov.u32 %0, %%tid.x;" : "=r"(v));
    return v;
}
template <uint32_t V> __device__ __forceinline__ uint32_t loop_init() {
    uint32_t v; asm volatile("mov.u32 %0, %1;" : "=r"(v) : "n"(V)); return v;
}
__device__ __forceinline__ int fresh_warp() {
    int v; asm volatile("shfl.sync.idx.b32 %0, %1, 0, 0x1f, 0xffffffff;" : "=r"(v) : "r"(fresh_tid() >> 5)); return v;
}
__device__ __forceinline__ uint32_t fresh_cta() {
    uint32_t v; asm volatile("mov.u32 %0, %%ctaid.x;" : "=r"(v)); return v;
}
__device__ __forceinline__ float sqrt_fast(float v) { float r; asm("sqrt.approx.f32 %0, %1;" : "=f"(r) : "f"(v)); return r; }

template <int TB>
__device__ __forceinline__ void wgmma_n64_h_set(uint32_t (&d)[16], const uint32_t* a, uint64_t desc) {
    asm volatile(
        "{\n.reg .pred p;\nsetp.ne.b32 p, 0, 0;\n"
        "wgmma.mma_async.sync.aligned.m64n64k16.f16.f16.f16 "
        "{%0,%1,%2,%3,%4,%5,%6,%7,%8,%9,%10,%11,%12,%13,%14,%15}, {%16,%17,%18,%19}, %20, p, 1, 1, %21;\n}\n"
        : "=r"(d[0]), "=r"(d[1]), "=r"(d[2]), "=r"(d[3]), "=r"(d[4]), "=r"(d[5]), "=r"(d[6]), "=r"(d[7]), "=r"(d[8]), "=r"(d[9]), "=r"(d[10]), "=r"(d[11]), "=r"(d[12]), "=r"(d[13]), "=r"(d[14]), "=r"(d[15])
        : "r"(a[0]), "r"(a[1]), "r"(a[2]), "r"(a[3]), "l"(desc), "n"(TB));
}
template <int TB>
__device__ __forceinline__ void wgmma_n64_h_acc(uint32_t (&d)[16], const uint32_t* a, uint64_t desc) {
    asm volatile(
        "{\n.reg .pred p;\nsetp.ne.b32 p, 1, 0;\n"
        "wgmma.mma_async.sync.aligned.m64n64k16.f16.f16.f16 "
        "{%0,%1,%2,%3,%4,%5,%6,%7,%8,%9,%10,%11,%12,%13,%14,%15}, {%16,%17,%18,%19}, %20, p, 1, 1, %21;\n}\n"
        : "+r"(d[0]), "+r"(d[1]), "+r"(d[2]), "+r"(d[3]), "+r"(d[4]), "+r"(d[5]), "+r"(d[6]), "+r"(d[7]), "+r"(d[8]), "+r"(d[9]), "+r"(d[10]), "+r"(d[11]), "+r"(d[12]), "+r"(d[13]), "+r"(d[14]), "+r"(d[15])
        : "r"(a[0]), "r"(a[1]), "r"(a[2]), "r"(a[3]), "l"(desc), "n"(TB));
}
__device__ __forceinline__ void wgmma_n64_h_acc_ss(uint32_t (&d)[16], uint64_t adesc, uint64_t desc) {
    asm volatile(
        "{\n.reg .pred p;\nsetp.ne.b32 p, 1, 0;\n"
        "wgmma.mma_async.sync.aligned.m64n64k16.f16.f16.f16 "
        "{%0,%1,%2,%3,%4,%5,%6,%7,%8,%9,%10,%11,%12,%13,%14,%15}, %16, %17, p, 1, 1, 1, 0;\n}\n"
        : "+r"(d[0]), "+r"(d[1]), "+r"(d[2]), "+r"(d[3]), "+r"(d[4]), "+r"(d[5]), "+r"(d[6]), "+r"(d[7]), "+r"(d[8]), "+r"(d[9]), "+r"(d[10]), "+r"(d[11]), "+r"(d[12]), "+r"(d[13]), "+r"(d[14]), "+r"(d[15])
        : "l"(adesc), "l"(desc));
}

struct Params {
    CUtensorMap w1_map, w2_map;
    const __nv_bfloat16* x;
    const __nv_bfloat16* dw;
    const __nv_bfloat16* w1;
    const __nv_bfloat16* gamma;
    const __nv_bfloat16* beta;
    __nv_bfloat16* out;
    Scratch* g;
    uint64_t ydesc64[2];
    uint64_t sel[3];
    uint32_t w1desc, w2desc, ydesc;
};

__device__ __forceinline__ int cta_stride(uint32_t cta) { return cta & 8 ? ROW_BYTES : -ROW_BYTES; }
__device__ __forceinline__ uint32_t cta_tile0(uint32_t cta) {
    return ((cta >> 3) * ROWS_PER_CTA + (cta & 8 ? 0 : ROWS_PER_CTA - 1)) * ROW_BYTES + (cta & 7) * TILE_BYTES;
}

struct Producer {
    uint32_t w[9][6];
    uint32_t xoff[2];
    uint32_t yoff[2][2];
    uint32_t stat, own;
    int lane;
};

struct RowCopy {
    const char* x0;
    char* y0;
    const char* zeros;
    uint32_t cut0, cut1;
    int stride, last;
};
__device__ __forceinline__ RowCopy row_copy(const Params& prm) {
    const uint32_t cta = fresh_cta(), strip = cta & 7, t0 = cta_tile0(cta);
    RowCopy r;
    r.stride = cta_stride(cta);
    r.x0 = (const char*)prm.x + (t0 - r.stride) - 192;
    r.y0 = (char*)prm.out + t0;
    r.zeros = (const char*)prm.g->zero_row;
    r.cut0 = strip == 0 ? 192 : 0;
    r.cut1 = strip == 7 ? 192 : 0;
    r.last = cta - 8 >= NUM_CTAS - 16 ? STEPS - 2 : STEPS - 1;
    return r;
}
__device__ __forceinline__ void issue_row_load(const RowCopy& r, int i, uint32_t slot) {
    const char* src = r.x0 + i * r.stride;
    const uint32_t bar = sb + SM_GO + i * 8, dst = sb + SM_X + slot * SLOT_BYTES;
    expect_tx(bar, XHALF_BYTES - r.cut0);
    bulk_load(dst + r.cut0, src + r.cut0, XHALF_BYTES - r.cut0, bar);
    expect_tx(bar, XHALF_BYTES - r.cut1);
    bulk_load(dst + XHALF_B, src + 32 * 192, XHALF_BYTES - r.cut1, bar);
}

__device__ __forceinline__ float quad_sum(float v) {
    v += __shfl_xor_sync(0xffffffffu, v, 1);
    v += __shfl_xor_sync(0xffffffffu, v, 2);
    return v;
}

__device__ __forceinline__ void load_x(uint32_t (&v)[6][6], const Producer& c, uint32_t row) {
#pragma unroll
    for (int k = 0; k < 6; k++) {
        asm volatile("ld.shared.v4.b32 {%0,%1,%2,%3}, [%4];"
                     : "=r"(v[k][0]), "=r"(v[k][1]), "=r"(v[k][2]), "=r"(v[k][3]) : "r"(row + c.xoff[0] + k * 192));
        asm volatile("ld.shared.v2.b32 {%0,%1}, [%2];" : "=r"(v[k][4]), "=r"(v[k][5]) : "r"(row + c.xoff[1] + k * 192));
    }
}
template <int DY, int STRIDE>
__device__ __forceinline__ void conv_row(uint32_t (&dst)[24], const uint32_t* src, const uint32_t (&v)[6][6], const Producer& c) {
#pragma unroll
    for (int o = 0; o < 4; o++)
#pragma unroll
        for (int u = 0; u < 6; u++)
            dst[o * 6 + u] = bf2_fma(v[o + 2][u], c.w[3 * DY + 2][u], bf2_fma(v[o + 1][u], c.w[3 * DY + 1][u],
                             bf2_fma(v[o][u], c.w[3 * DY][u], STRIDE ? src[o * 6 + u] : src[2 * o + 1])));
}
#define HAND_OVER(name, base, r) asm volatile("mov.b32 " name "%6, %0; mov.b32 " name "%7, %1; mov.b32 " name "%8, %2;\n" \
    "mov.b32 " name "%9, %3; mov.b32 " name "%10, %4; mov.b32 " name "%11, %5;" ::"r"((r)[0]), "r"((r)[1]), "r"((r)[2]), \
    "r"((r)[3]), "r"((r)[4]), "r"((r)[5]), "n"(base), "n"(base + 1), "n"(base + 2), "n"(base + 3), "n"(base + 4), "n"(base + 5))
template <int K> __device__ __forceinline__ void hand_over(const Producer& c, const uint32_t (&B)[24], const uint32_t (&C)[24],
                                                           const uint32_t (&v)[6][6]) {
    HAND_OVER("pw", K * 6, c.w[K]);
    if (K < 6) HAND_OVER("pv", K * 6, v[K % 6]);
    if (K < 4) { HAND_OVER("pb", K * 6, B + K % 4 * 6); HAND_OVER("pc", K * 6, C + K % 4 * 6); }
    if constexpr (K < 8) hand_over<K + 1>(c, B, C, v);
}
__device__ __forceinline__ void produce_tiles(const Producer& c, const Params& prm) {
    asm volatile(
        "{\n"
        ".reg .b32 pa<24>, pq<4>, m<6>, y<6>, rr, mm, t, so, ad, tt, cnt;\n"
        ".reg .b16 xl, xh;\n"
        ".reg .f32 d<4>, us, s0, s1, f0, f1, kq;\n"
        ".reg .pred pt, pf, pr, pw, pl, po, pe;\n"
        "setp.ne.b32 pt, 1, 0; setp.ne.b32 pf, 0, 0; setp.eq.u32 pl, %8, 0; and.b32 tt, %8, 1; setp.ne.u32 po, tt, 0;\n"
        "and.b32 tt, %8, 4; setp.ne.u32 pr, tt, 0; selp.f32 kq, 0f3F802D41, 0f3F7FA57E, pr;\n"
        "mov.u32 t, 0; mov.u32 so, 0;\n"
        "setp.eq.u32 pr, %12, 0;\n"
        "@pr bra.uni RARE;\n"
        "LOOP:\n"
        ASM_TRC("t")
        "fma.rn.bf16x2 pa0, pv0, pw36, pb0; fma.rn.bf16x2 pa1, pv1, pw37, pb1; fma.rn.bf16x2 pa2, pv2, pw38, pb2; fma.rn.bf16x2 pa3, pv3, pw39, pb3; fma.rn.bf16x2 pa4, pv4, pw40, pb4; fma.rn.bf16x2 pa5, pv5, pw41, pb5;\n"
        "fma.rn.bf16x2 pa6, pv6, pw36, pb6; fma.rn.bf16x2 pa7, pv7, pw37, pb7; fma.rn.bf16x2 pa8, pv8, pw38, pb8; fma.rn.bf16x2 pa9, pv9, pw39, pb9; fma.rn.bf16x2 pa10, pv10, pw40, pb10; fma.rn.bf16x2 pa11, pv11, pw41, pb11;\n"
        "fma.rn.bf16x2 pa12, pv12, pw36, pb12; fma.rn.bf16x2 pa13, pv13, pw37, pb13; fma.rn.bf16x2 pa14, pv14, pw38, pb14; fma.rn.bf16x2 pa15, pv15, pw39, pb15; fma.rn.bf16x2 pa16, pv16, pw40, pb16; fma.rn.bf16x2 pa17, pv17, pw41, pb17;\n"
        "fma.rn.bf16x2 pa18, pv18, pw36, pb18; fma.rn.bf16x2 pa19, pv19, pw37, pb19; fma.rn.bf16x2 pa20, pv20, pw38, pb20; fma.rn.bf16x2 pa21, pv21, pw39, pb21; fma.rn.bf16x2 pa22, pv22, pw40, pb22; fma.rn.bf16x2 pa23, pv23, pw41, pb23;\n"
        "fma.rn.bf16x2 pa0, pv6, pw42, pa0; fma.rn.bf16x2 pa1, pv7, pw43, pa1; fma.rn.bf16x2 pa2, pv8, pw44, pa2; fma.rn.bf16x2 pa3, pv9, pw45, pa3; fma.rn.bf16x2 pa4, pv10, pw46, pa4; fma.rn.bf16x2 pa5, pv11, pw47, pa5;\n"
        "fma.rn.bf16x2 pa6, pv12, pw42, pa6; fma.rn.bf16x2 pa7, pv13, pw43, pa7; fma.rn.bf16x2 pa8, pv14, pw44, pa8; fma.rn.bf16x2 pa9, pv15, pw45, pa9; fma.rn.bf16x2 pa10, pv16, pw46, pa10; fma.rn.bf16x2 pa11, pv17, pw47, pa11;\n"
        "fma.rn.bf16x2 pa12, pv18, pw42, pa12; fma.rn.bf16x2 pa13, pv19, pw43, pa13; fma.rn.bf16x2 pa14, pv20, pw44, pa14; fma.rn.bf16x2 pa15, pv21, pw45, pa15; fma.rn.bf16x2 pa16, pv22, pw46, pa16; fma.rn.bf16x2 pa17, pv23, pw47, pa17;\n"
        "fma.rn.bf16x2 pa18, pv24, pw42, pa18; fma.rn.bf16x2 pa19, pv25, pw43, pa19; fma.rn.bf16x2 pa20, pv26, pw44, pa20; fma.rn.bf16x2 pa21, pv27, pw45, pa21; fma.rn.bf16x2 pa22, pv28, pw46, pa22; fma.rn.bf16x2 pa23, pv29, pw47, pa23;\n"
        "fma.rn.bf16x2 pa0, pv12, pw48, pa0; fma.rn.bf16x2 pa1, pv13, pw49, pa1; fma.rn.bf16x2 pa2, pv14, pw50, pa2; fma.rn.bf16x2 pa3, pv15, pw51, pa3; fma.rn.bf16x2 pa4, pv16, pw52, pa4; fma.rn.bf16x2 pa5, pv17, pw53, pa5;\n"
        "fma.rn.bf16x2 pa6, pv18, pw48, pa6; fma.rn.bf16x2 pa7, pv19, pw49, pa7; fma.rn.bf16x2 pa8, pv20, pw50, pa8; fma.rn.bf16x2 pa9, pv21, pw51, pa9; fma.rn.bf16x2 pa10, pv22, pw52, pa10; fma.rn.bf16x2 pa11, pv23, pw53, pa11;\n"
        "fma.rn.bf16x2 pa12, pv24, pw48, pa12; fma.rn.bf16x2 pa13, pv25, pw49, pa13; fma.rn.bf16x2 pa14, pv26, pw50, pa14; fma.rn.bf16x2 pa15, pv27, pw51, pa15; fma.rn.bf16x2 pa16, pv28, pw52, pa16; fma.rn.bf16x2 pa17, pv29, pw53, pa17;\n"
        "fma.rn.bf16x2 pa18, pv30, pw48, pa18; fma.rn.bf16x2 pa19, pv31, pw49, pa19; fma.rn.bf16x2 pa20, pv32, pw50, pa20; fma.rn.bf16x2 pa21, pv33, pw51, pa21; fma.rn.bf16x2 pa22, pv34, pw52, pa22; fma.rn.bf16x2 pa23, pv35, pw53, pa23;\n"
        "mul.rn.bf16x2 pq0, pa0, pa0; fma.rn.bf16x2 pq0, pa1, pa1, pq0; fma.rn.bf16x2 pq0, pa2, pa2, pq0; fma.rn.bf16x2 pq0, pa3, pa3, pq0; fma.rn.bf16x2 pq0, pa4, pa4, pq0; fma.rn.bf16x2 pq0, pa5, pa5, pq0;\n"
        "mul.rn.bf16x2 pq1, pa6, pa6; fma.rn.bf16x2 pq1, pa7, pa7, pq1; fma.rn.bf16x2 pq1, pa8, pa8, pq1; fma.rn.bf16x2 pq1, pa9, pa9, pq1; fma.rn.bf16x2 pq1, pa10, pa10, pq1; fma.rn.bf16x2 pq1, pa11, pa11, pq1;\n"
        "mul.rn.bf16x2 pq2, pa12, pa12; fma.rn.bf16x2 pq2, pa13, pa13, pq2; fma.rn.bf16x2 pq2, pa14, pa14, pq2; fma.rn.bf16x2 pq2, pa15, pa15, pq2; fma.rn.bf16x2 pq2, pa16, pa16, pq2; fma.rn.bf16x2 pq2, pa17, pa17, pq2;\n"
        "mul.rn.bf16x2 pq3, pa18, pa18; fma.rn.bf16x2 pq3, pa19, pa19, pq3; fma.rn.bf16x2 pq3, pa20, pa20, pq3; fma.rn.bf16x2 pq3, pa21, pa21, pq3; fma.rn.bf16x2 pq3, pa22, pa22, pq3; fma.rn.bf16x2 pq3, pa23, pa23, pq3;\n"
        "B0:\n"
        "wgmma.fence.sync.aligned;\n"
        "wgmma.mma_async.sync.aligned.m64n8k16.f32.bf16.bf16 {d0,d1,d2,d3}, {pa0,pa6,pa1,pa7}, %9, pf, 1, 1, 0;\n"
        "wgmma.mma_async.sync.aligned.m64n8k16.f32.bf16.bf16 {d0,d1,d2,d3}, {pa2,pa8,pa3,pa9}, %9, pt, 1, 1, 0;\n"
        "wgmma.mma_async.sync.aligned.m64n8k16.f32.bf16.bf16 {d0,d1,d2,d3}, {pa4,pa10,pa5,pa11}, %9, pt, 1, 1, 0;\n"
        "wgmma.mma_async.sync.aligned.m64n8k16.f32.bf16.bf16 {d0,d1,d2,d3}, {pa12,pa18,pa13,pa19}, %10, pt, 1, 1, 0;\n"
        "wgmma.mma_async.sync.aligned.m64n8k16.f32.bf16.bf16 {d0,d1,d2,d3}, {pa14,pa20,pa15,pa21}, %10, pt, 1, 1, 0;\n"
        "wgmma.mma_async.sync.aligned.m64n8k16.f32.bf16.bf16 {d0,d1,d2,d3}, {pa16,pa22,pa17,pa23}, %10, pt, 1, 1, 0;\n"
        "wgmma.mma_async.sync.aligned.m64n8k16.f32.bf16.bf16 {d0,d1,d2,d3}, {pq0,pq1,pq2,pq3}, %11, pt, 1, 1, 0;\n"
        "wgmma.commit_group.sync.aligned;\n"
        "fence.proxy.async.shared::cta;\n"
        "@pl mbarrier.arrive.shared::cta.b64 _, [t+231544];\n"
        "add.u32 ad, %7, so; ld.shared.f32 us, [ad+4];\n"
        "fma.rn.bf16x2 pb0, pv0, pw18, pc0; fma.rn.bf16x2 pb1, pv1, pw19, pc1; fma.rn.bf16x2 pb2, pv2, pw20, pc2; fma.rn.bf16x2 pb3, pv3, pw21, pc3; fma.rn.bf16x2 pb4, pv4, pw22, pc4; fma.rn.bf16x2 pb5, pv5, pw23, pc5;\n"
        "fma.rn.bf16x2 pb6, pv6, pw18, pc6; fma.rn.bf16x2 pb7, pv7, pw19, pc7; fma.rn.bf16x2 pb8, pv8, pw20, pc8; fma.rn.bf16x2 pb9, pv9, pw21, pc9; fma.rn.bf16x2 pb10, pv10, pw22, pc10; fma.rn.bf16x2 pb11, pv11, pw23, pc11;\n"
        "fma.rn.bf16x2 pb0, pv6, pw24, pb0; fma.rn.bf16x2 pb1, pv7, pw25, pb1; fma.rn.bf16x2 pb2, pv8, pw26, pb2; fma.rn.bf16x2 pb3, pv9, pw27, pb3; fma.rn.bf16x2 pb4, pv10, pw28, pb4; fma.rn.bf16x2 pb5, pv11, pw29, pb5;\n"
        "fma.rn.bf16x2 pb6, pv12, pw24, pb6; fma.rn.bf16x2 pb7, pv13, pw25, pb7; fma.rn.bf16x2 pb8, pv14, pw26, pb8; fma.rn.bf16x2 pb9, pv15, pw27, pb9; fma.rn.bf16x2 pb10, pv16, pw28, pb10; fma.rn.bf16x2 pb11, pv17, pw29, pb11;\n"
        "fma.rn.bf16x2 pb0, pv12, pw30, pb0; fma.rn.bf16x2 pb1, pv13, pw31, pb1; fma.rn.bf16x2 pb2, pv14, pw32, pb2; fma.rn.bf16x2 pb3, pv15, pw33, pb3; fma.rn.bf16x2 pb4, pv16, pw34, pb4; fma.rn.bf16x2 pb5, pv17, pw35, pb5;\n"
        "fma.rn.bf16x2 pb6, pv18, pw30, pb6; fma.rn.bf16x2 pb7, pv19, pw31, pb7; fma.rn.bf16x2 pb8, pv20, pw32, pb8; fma.rn.bf16x2 pb9, pv21, pw33, pb9; fma.rn.bf16x2 pb10, pv22, pw34, pb10; fma.rn.bf16x2 pb11, pv23, pw35, pb11;\n"
        "B1:\n"
        "fma.rn.bf16x2 pb12, pv12, pw18, pc12; fma.rn.bf16x2 pb13, pv13, pw19, pc13; fma.rn.bf16x2 pb14, pv14, pw20, pc14; fma.rn.bf16x2 pb15, pv15, pw21, pc15; fma.rn.bf16x2 pb16, pv16, pw22, pc16; fma.rn.bf16x2 pb17, pv17, pw23, pc17;\n"
        "fma.rn.bf16x2 pb18, pv18, pw18, pc18; fma.rn.bf16x2 pb19, pv19, pw19, pc19; fma.rn.bf16x2 pb20, pv20, pw20, pc20; fma.rn.bf16x2 pb21, pv21, pw21, pc21; fma.rn.bf16x2 pb22, pv22, pw22, pc22; fma.rn.bf16x2 pb23, pv23, pw23, pc23;\n"
        "fma.rn.bf16x2 pb12, pv18, pw24, pb12; fma.rn.bf16x2 pb13, pv19, pw25, pb13; fma.rn.bf16x2 pb14, pv20, pw26, pb14; fma.rn.bf16x2 pb15, pv21, pw27, pb15; fma.rn.bf16x2 pb16, pv22, pw28, pb16; fma.rn.bf16x2 pb17, pv23, pw29, pb17;\n"
        "fma.rn.bf16x2 pb18, pv24, pw24, pb18; fma.rn.bf16x2 pb19, pv25, pw25, pb19; fma.rn.bf16x2 pb20, pv26, pw26, pb20; fma.rn.bf16x2 pb21, pv27, pw27, pb21; fma.rn.bf16x2 pb22, pv28, pw28, pb22; fma.rn.bf16x2 pb23, pv29, pw29, pb23;\n"
        "fma.rn.bf16x2 pb12, pv24, pw30, pb12; fma.rn.bf16x2 pb13, pv25, pw31, pb13; fma.rn.bf16x2 pb14, pv26, pw32, pb14; fma.rn.bf16x2 pb15, pv27, pw33, pb15; fma.rn.bf16x2 pb16, pv28, pw34, pb16; fma.rn.bf16x2 pb17, pv29, pw35, pb17;\n"
        "fma.rn.bf16x2 pb18, pv30, pw30, pb18; fma.rn.bf16x2 pb19, pv31, pw31, pb19; fma.rn.bf16x2 pb20, pv32, pw32, pb20; fma.rn.bf16x2 pb21, pv33, pw33, pb21; fma.rn.bf16x2 pb22, pv34, pw34, pb22; fma.rn.bf16x2 pb23, pv35, pw35, pb23;\n"
        "C0:\n"
        "wgmma.wait_group.sync.aligned 0;\n"
        "selp.f32 s0, d2, d0, po; selp.f32 s1, d3, d1, po;\n"
        "shfl.sync.bfly.b32 f0, s0, 4, 0x1f, 0xffffffff; shfl.sync.bfly.b32 f1, s1, 4, 0x1f, 0xffffffff;\n"
        "fma.rn.bf16x2 pc0, pv0, pw0, ps1; fma.rn.bf16x2 pc1, pv1, pw1, ps1; fma.rn.bf16x2 pc2, pv2, pw2, ps1; fma.rn.bf16x2 pc3, pv3, pw3, ps1; fma.rn.bf16x2 pc4, pv4, pw4, ps1; fma.rn.bf16x2 pc5, pv5, pw5, ps1;\n"
        "fma.rn.bf16x2 pc6, pv6, pw0, ps3; fma.rn.bf16x2 pc7, pv7, pw1, ps3; fma.rn.bf16x2 pc8, pv8, pw2, ps3; fma.rn.bf16x2 pc9, pv9, pw3, ps3; fma.rn.bf16x2 pc10, pv10, pw4, ps3; fma.rn.bf16x2 pc11, pv11, pw5, ps3;\n"
        "fma.rn.bf16x2 pc12, pv12, pw0, ps5; fma.rn.bf16x2 pc13, pv13, pw1, ps5; fma.rn.bf16x2 pc14, pv14, pw2, ps5; fma.rn.bf16x2 pc15, pv15, pw3, ps5; fma.rn.bf16x2 pc16, pv16, pw4, ps5; fma.rn.bf16x2 pc17, pv17, pw5, ps5;\n"
        "fma.rn.bf16x2 pc18, pv18, pw0, ps7; fma.rn.bf16x2 pc19, pv19, pw1, ps7; fma.rn.bf16x2 pc20, pv20, pw2, ps7; fma.rn.bf16x2 pc21, pv21, pw3, ps7; fma.rn.bf16x2 pc22, pv22, pw4, ps7; fma.rn.bf16x2 pc23, pv23, pw5, ps7;\n"
        "fma.rn.bf16x2 pc0, pv6, pw6, pc0; fma.rn.bf16x2 pc1, pv7, pw7, pc1; fma.rn.bf16x2 pc2, pv8, pw8, pc2; fma.rn.bf16x2 pc3, pv9, pw9, pc3; fma.rn.bf16x2 pc4, pv10, pw10, pc4; fma.rn.bf16x2 pc5, pv11, pw11, pc5;\n"
        "fma.rn.bf16x2 pc6, pv12, pw6, pc6; fma.rn.bf16x2 pc7, pv13, pw7, pc7; fma.rn.bf16x2 pc8, pv14, pw8, pc8; fma.rn.bf16x2 pc9, pv15, pw9, pc9; fma.rn.bf16x2 pc10, pv16, pw10, pc10; fma.rn.bf16x2 pc11, pv17, pw11, pc11;\n"
        "fma.rn.bf16x2 pc12, pv18, pw6, pc12; fma.rn.bf16x2 pc13, pv19, pw7, pc13; fma.rn.bf16x2 pc14, pv20, pw8, pc14; fma.rn.bf16x2 pc15, pv21, pw9, pc15; fma.rn.bf16x2 pc16, pv22, pw10, pc16; fma.rn.bf16x2 pc17, pv23, pw11, pc17;\n"
        "fma.rn.bf16x2 pc18, pv24, pw6, pc18; fma.rn.bf16x2 pc19, pv25, pw7, pc19; fma.rn.bf16x2 pc20, pv26, pw8, pc20; fma.rn.bf16x2 pc21, pv27, pw9, pc21; fma.rn.bf16x2 pc22, pv28, pw10, pc22; fma.rn.bf16x2 pc23, pv29, pw11, pc23;\n"
        "fma.rn.bf16x2 pc0, pv12, pw12, pc0; fma.rn.bf16x2 pc1, pv13, pw13, pc1; fma.rn.bf16x2 pc2, pv14, pw14, pc2; fma.rn.bf16x2 pc3, pv15, pw15, pc3; fma.rn.bf16x2 pc4, pv16, pw16, pc4; fma.rn.bf16x2 pc5, pv17, pw17, pc5;\n"
        "fma.rn.bf16x2 pc6, pv18, pw12, pc6; fma.rn.bf16x2 pc7, pv19, pw13, pc7; fma.rn.bf16x2 pc8, pv20, pw14, pc8; fma.rn.bf16x2 pc9, pv21, pw15, pc9; fma.rn.bf16x2 pc10, pv22, pw16, pc10; fma.rn.bf16x2 pc11, pv23, pw17, pc11;\n"
        "fma.rn.bf16x2 pc12, pv24, pw12, pc12; fma.rn.bf16x2 pc13, pv25, pw13, pc13; fma.rn.bf16x2 pc14, pv26, pw14, pc14; fma.rn.bf16x2 pc15, pv27, pw15, pc15; fma.rn.bf16x2 pc16, pv28, pw16, pc16; fma.rn.bf16x2 pc17, pv29, pw17, pc17;\n"
        "fma.rn.bf16x2 pc18, pv30, pw12, pc18; fma.rn.bf16x2 pc19, pv31, pw13, pc19; fma.rn.bf16x2 pc20, pv32, pw14, pc20; fma.rn.bf16x2 pc21, pv33, pw15, pc21; fma.rn.bf16x2 pc22, pv34, pw16, pc22; fma.rn.bf16x2 pc23, pv35, pw17, pc23;\n"
        "add.f32 s0, s0, f0; add.f32 s1, s1, f1; mul.f32 s0, s0, 0fBC2AAAAB;\n"
        "neg.f32 f0, s0; fma.rn.f32 f0, f0, s0, %13; fma.rn.f32 f0, s1, 0f3C2AAAAB, f0; max.f32 f0, f0, %13;\n"
        "rsqrt.approx.ftz.f32 f0, f0; mul.f32 f0, f0, %14; cvt.rn.bf16x2.f32 tt, f0, 0f00000000; mov.b32 f0, tt;\n"
        "mul.f32 f1, s0, kq; mul.f32 f1, f1, f0; cvt.rn.bf16x2.f32 tt, f1, f0; add.f32 us, us, s0; cvt.rn.bf16x2.f32 mm, us, us;\n"
        "add.u32 ad, %7, so; st.shared.v2.b32 [ad], {tt, mm};\n"
        "add.u32 ad, %6, so; ld.shared.v4.b32 {ps0,ps1,ps2,ps3}, [ad]; ld.shared.v4.b32 {ps4,ps5,ps6,ps7}, [ad+16];\n"
        "mbarrier.try_wait.parity.shared::cta.b64 pw, [t+231264], 0;\n"
        "N0:\n"
        "@!pw bra.uni SPIN;\n"
        "BACK:\n"
        "add.u32 ad, %0, so; ld.shared.v4.b32 {pv0,pv1,pv2,pv3}, [ad+0];\n"
        "add.u32 ad, %1, so; ld.shared.v2.b32 {pv4,pv5}, [ad+0];\n"
        "add.u32 ad, %0, so; ld.shared.v4.b32 {pv6,pv7,pv8,pv9}, [ad+192];\n"
        "add.u32 ad, %1, so; ld.shared.v2.b32 {pv10,pv11}, [ad+192];\n"
        "mov.b32 {xl, xh}, ps0; mov.b32 rr, {xl, xl}; mov.b32 mm, {xh, xh}; fma.rn.bf16x2 pa0, pa0, rr, mm; fma.rn.bf16x2 pa1, pa1, rr, mm; fma.rn.bf16x2 pa2, pa2, rr, mm; fma.rn.bf16x2 pa3, pa3, rr, mm; fma.rn.bf16x2 pa4, pa4, rr, mm; fma.rn.bf16x2 pa5, pa5, rr, mm;\n"
        "and.b32 m0, pa0, 0x7fff7fff; and.b32 m1, pa1, 0x7fff7fff; and.b32 m2, pa2, 0x7fff7fff; and.b32 m3, pa3, 0x7fff7fff; and.b32 m4, pa4, 0x7fff7fff; and.b32 m5, pa5, 0x7fff7fff;\n"
        "mad.lo.u32 y0, m0, 7, pa0; mad.lo.u32 y1, m1, 7, pa1; mad.lo.u32 y2, m2, 7, pa2; mad.lo.u32 y3, m3, 7, pa3; mad.lo.u32 y4, m4, 7, pa4; mad.lo.u32 y5, m5, 7, pa5;\n"
        "add.u32 ad, %2, so; st.shared.v4.b32 [ad+0], {y0,y1,y2,y3};\n"
        "add.u32 ad, %4, so; st.shared.v2.b32 [ad+0], {y4,y5};\n"
        "N1:\n"
        "add.u32 ad, %0, so; ld.shared.v4.b32 {pv12,pv13,pv14,pv15}, [ad+384];\n"
        "add.u32 ad, %1, so; ld.shared.v2.b32 {pv16,pv17}, [ad+384];\n"
        "add.u32 ad, %0, so; ld.shared.v4.b32 {pv18,pv19,pv20,pv21}, [ad+576];\n"
        "add.u32 ad, %1, so; ld.shared.v2.b32 {pv22,pv23}, [ad+576];\n"
        "mov.b32 {xl, xh}, ps2; mov.b32 rr, {xl, xl}; mov.b32 mm, {xh, xh}; fma.rn.bf16x2 pa6, pa6, rr, mm; fma.rn.bf16x2 pa7, pa7, rr, mm; fma.rn.bf16x2 pa8, pa8, rr, mm; fma.rn.bf16x2 pa9, pa9, rr, mm; fma.rn.bf16x2 pa10, pa10, rr, mm; fma.rn.bf16x2 pa11, pa11, rr, mm;\n"
        "and.b32 m0, pa6, 0x7fff7fff; and.b32 m1, pa7, 0x7fff7fff; and.b32 m2, pa8, 0x7fff7fff; and.b32 m3, pa9, 0x7fff7fff; and.b32 m4, pa10, 0x7fff7fff; and.b32 m5, pa11, 0x7fff7fff;\n"
        "mad.lo.u32 y0, m0, 7, pa6; mad.lo.u32 y1, m1, 7, pa7; mad.lo.u32 y2, m2, 7, pa8; mad.lo.u32 y3, m3, 7, pa9; mad.lo.u32 y4, m4, 7, pa10; mad.lo.u32 y5, m5, 7, pa11;\n"
        "add.u32 ad, %3, so; st.shared.v4.b32 [ad+0], {y0,y1,y2,y3};\n"
        "add.u32 ad, %5, so; st.shared.v2.b32 [ad+0], {y4,y5};\n"
        "N2:\n"
        "add.u32 ad, %0, so; ld.shared.v4.b32 {pv24,pv25,pv26,pv27}, [ad+768];\n"
        "add.u32 ad, %1, so; ld.shared.v2.b32 {pv28,pv29}, [ad+768];\n"
        "mov.b32 {xl, xh}, ps4; mov.b32 rr, {xl, xl}; mov.b32 mm, {xh, xh}; fma.rn.bf16x2 pa12, pa12, rr, mm; fma.rn.bf16x2 pa13, pa13, rr, mm; fma.rn.bf16x2 pa14, pa14, rr, mm; fma.rn.bf16x2 pa15, pa15, rr, mm; fma.rn.bf16x2 pa16, pa16, rr, mm; fma.rn.bf16x2 pa17, pa17, rr, mm;\n"
        "and.b32 m0, pa12, 0x7fff7fff; and.b32 m1, pa13, 0x7fff7fff; and.b32 m2, pa14, 0x7fff7fff; and.b32 m3, pa15, 0x7fff7fff; and.b32 m4, pa16, 0x7fff7fff; and.b32 m5, pa17, 0x7fff7fff;\n"
        "mad.lo.u32 y0, m0, 7, pa12; mad.lo.u32 y1, m1, 7, pa13; mad.lo.u32 y2, m2, 7, pa14; mad.lo.u32 y3, m3, 7, pa15; mad.lo.u32 y4, m4, 7, pa16; mad.lo.u32 y5, m5, 7, pa17;\n"
        "add.u32 ad, %2, so; st.shared.v4.b32 [ad+2048], {y0,y1,y2,y3};\n"
        "add.u32 ad, %4, so; st.shared.v2.b32 [ad+1024], {y4,y5};\n"
        "N3:\n"
        "add.u32 ad, %0, so; ld.shared.v4.b32 {pv30,pv31,pv32,pv33}, [ad+960];\n"
        "add.u32 ad, %1, so; ld.shared.v2.b32 {pv34,pv35}, [ad+960];\n"
        "mov.b32 {xl, xh}, ps6; mov.b32 rr, {xl, xl}; mov.b32 mm, {xh, xh}; fma.rn.bf16x2 pa18, pa18, rr, mm; fma.rn.bf16x2 pa19, pa19, rr, mm; fma.rn.bf16x2 pa20, pa20, rr, mm; fma.rn.bf16x2 pa21, pa21, rr, mm; fma.rn.bf16x2 pa22, pa22, rr, mm; fma.rn.bf16x2 pa23, pa23, rr, mm;\n"
        "and.b32 m0, pa18, 0x7fff7fff; and.b32 m1, pa19, 0x7fff7fff; and.b32 m2, pa20, 0x7fff7fff; and.b32 m3, pa21, 0x7fff7fff; and.b32 m4, pa22, 0x7fff7fff; and.b32 m5, pa23, 0x7fff7fff;\n"
        "mad.lo.u32 y0, m0, 7, pa18; mad.lo.u32 y1, m1, 7, pa19; mad.lo.u32 y2, m2, 7, pa20; mad.lo.u32 y3, m3, 7, pa21; mad.lo.u32 y4, m4, 7, pa22; mad.lo.u32 y5, m5, 7, pa23;\n"
        "add.u32 ad, %3, so; st.shared.v4.b32 [ad+2048], {y0,y1,y2,y3};\n"
        "add.u32 ad, %5, so; st.shared.v2.b32 [ad+1024], {y4,y5};\n"
        "add.u32 so, so, 26624; setp.eq.u32 pr, so, 79872; selp.u32 so, 0, so, pr;\n"
        "add.u32 t, t, 8; setp.lt.u32 pe, t, 256;\n"
        "@pe bra.uni LOOP;\n"
        "bra.uni DONE;\n"
        "SPIN: mov.u32 cnt, 0;\n"
        "SPINL:\n"
        "mbarrier.try_wait.parity.shared::cta.b64 pw, [t+231264], 0;\n"
        "@pw bra.uni BACK;\n"
        "add.u32 cnt, cnt, 1; setp.lt.u32 pw, cnt, 0x100000;\n"
        "@pw bra.uni SPINL;\n"
        "trap;\n"
        "RARE:\n"
        "ld.volatile.shared.u32 tt, [%6];\n"
        "mov.b32 pa0, tt; mov.b32 pa1, tt; mov.b32 pa2, tt; mov.b32 pa3, tt; mov.b32 pa4, tt; mov.b32 pa5, tt; mov.b32 pa6, tt; mov.b32 pa7, tt; mov.b32 pa8, tt; mov.b32 pa9, tt; mov.b32 pa10, tt; mov.b32 pa11, tt;\n"
        "mov.b32 pa12, tt; mov.b32 pa13, tt; mov.b32 pa14, tt; mov.b32 pa15, tt; mov.b32 pa16, tt; mov.b32 pa17, tt; mov.b32 pa18, tt; mov.b32 pa19, tt; mov.b32 pa20, tt; mov.b32 pa21, tt; mov.b32 pa22, tt; mov.b32 pa23, tt;\n"
        "mov.b32 pb0, tt; mov.b32 pb1, tt; mov.b32 pb2, tt; mov.b32 pb3, tt; mov.b32 pb4, tt; mov.b32 pb5, tt; mov.b32 pb6, tt; mov.b32 pb7, tt; mov.b32 pb8, tt; mov.b32 pb9, tt; mov.b32 pb10, tt; mov.b32 pb11, tt;\n"
        "mov.b32 pb12, tt; mov.b32 pb13, tt; mov.b32 pb14, tt; mov.b32 pb15, tt; mov.b32 pb16, tt; mov.b32 pb17, tt; mov.b32 pb18, tt; mov.b32 pb19, tt; mov.b32 pb20, tt; mov.b32 pb21, tt; mov.b32 pb22, tt; mov.b32 pb23, tt;\n"
        "mov.b32 pc0, tt; mov.b32 pc1, tt; mov.b32 pc2, tt; mov.b32 pc3, tt; mov.b32 pc4, tt; mov.b32 pc5, tt; mov.b32 pc6, tt; mov.b32 pc7, tt; mov.b32 pc8, tt; mov.b32 pc9, tt; mov.b32 pc10, tt; mov.b32 pc11, tt;\n"
        "mov.b32 pc12, tt; mov.b32 pc13, tt; mov.b32 pc14, tt; mov.b32 pc15, tt; mov.b32 pc16, tt; mov.b32 pc17, tt; mov.b32 pc18, tt; mov.b32 pc19, tt; mov.b32 pc20, tt; mov.b32 pc21, tt; mov.b32 pc22, tt; mov.b32 pc23, tt;\n"
        "mov.b32 ps0, tt; mov.b32 ps1, tt; mov.b32 ps2, tt; mov.b32 ps3, tt; mov.b32 ps4, tt; mov.b32 ps5, tt; mov.b32 ps6, tt; mov.b32 ps7, tt; mov.b32 pq0, tt; mov.b32 pq1, tt; mov.b32 pq2, tt; mov.b32 pq3, tt;\n"
        "ld.volatile.shared.v2.b32 {pw1, pw0}, [%6]; xor.b32 tt, tt, pw1;\n"
        "ld.volatile.shared.v2.b32 {pw3, pw2}, [%6]; xor.b32 tt, tt, pw3;\n"
        "ld.volatile.shared.v2.b32 {pw5, pw4}, [%6]; xor.b32 tt, tt, pw5;\n"
        "ld.volatile.shared.v2.b32 {pw7, pw6}, [%6]; xor.b32 tt, tt, pw7;\n"
        "ld.volatile.shared.v2.b32 {pw9, pw8}, [%6]; xor.b32 tt, tt, pw9;\n"
        "ld.volatile.shared.v2.b32 {pw11, pw10}, [%6]; xor.b32 tt, tt, pw11;\n"
        "ld.volatile.shared.v2.b32 {pw13, pw12}, [%6]; xor.b32 tt, tt, pw13;\n"
        "ld.volatile.shared.v2.b32 {pw15, pw14}, [%6]; xor.b32 tt, tt, pw15;\n"
        "ld.volatile.shared.v2.b32 {pw17, pw16}, [%6]; xor.b32 tt, tt, pw17;\n"
        "ld.volatile.shared.v2.b32 {pw19, pw18}, [%6]; xor.b32 tt, tt, pw19;\n"
        "ld.volatile.shared.v2.b32 {pw21, pw20}, [%6]; xor.b32 tt, tt, pw21;\n"
        "ld.volatile.shared.v2.b32 {pw23, pw22}, [%6]; xor.b32 tt, tt, pw23;\n"
        "ld.volatile.shared.v2.b32 {pw25, pw24}, [%6]; xor.b32 tt, tt, pw25;\n"
        "ld.volatile.shared.v2.b32 {pw27, pw26}, [%6]; xor.b32 tt, tt, pw27;\n"
        "ld.volatile.shared.v2.b32 {pw29, pw28}, [%6]; xor.b32 tt, tt, pw29;\n"
        "ld.volatile.shared.v2.b32 {pw31, pw30}, [%6]; xor.b32 tt, tt, pw31;\n"
        "ld.volatile.shared.v2.b32 {pw33, pw32}, [%6]; xor.b32 tt, tt, pw33;\n"
        "ld.volatile.shared.v2.b32 {pw35, pw34}, [%6]; xor.b32 tt, tt, pw35;\n"
        "ld.volatile.shared.v2.b32 {pw37, pw36}, [%6]; xor.b32 tt, tt, pw37;\n"
        "ld.volatile.shared.v2.b32 {pw39, pw38}, [%6]; xor.b32 tt, tt, pw39;\n"
        "ld.volatile.shared.v2.b32 {pw41, pw40}, [%6]; xor.b32 tt, tt, pw41;\n"
        "ld.volatile.shared.v2.b32 {pw43, pw42}, [%6]; xor.b32 tt, tt, pw43;\n"
        "ld.volatile.shared.v2.b32 {pw45, pw44}, [%6]; xor.b32 tt, tt, pw45;\n"
        "ld.volatile.shared.v2.b32 {pw47, pw46}, [%6]; xor.b32 tt, tt, pw47;\n"
        "ld.volatile.shared.v2.b32 {pw49, pw48}, [%6]; xor.b32 tt, tt, pw49;\n"
        "ld.volatile.shared.v2.b32 {pw51, pw50}, [%6]; xor.b32 tt, tt, pw51;\n"
        "ld.volatile.shared.v2.b32 {pw53, pw52}, [%6]; xor.b32 tt, tt, pw53;\n"
        "mov.b32 us, tt; setp.ne.u32 pw, %15, 7;\n"
        "wgmma.fence.sync.aligned;\n"
        "setp.eq.u32 pr, %15, 1000; @pr bra.uni B0;\n"
        "setp.eq.u32 pr, %15, 1001; @pr bra.uni B1;\n"
        "setp.eq.u32 pr, %15, 1002; @pr bra.uni C0;\n"
        "setp.eq.u32 pr, %15, 1003; @pr bra.uni N0;\n"
        "setp.eq.u32 pr, %15, 1004; @pr bra.uni N1;\n"
        "setp.eq.u32 pr, %15, 1005; @pr bra.uni N2;\n"
        "setp.eq.u32 pr, %15, 1006; @pr bra.uni N3;\n"
        "trap;\n"
        "DONE:\n"
        ASM_TRC("t")
        "fence.proxy.async.shared::cta;\n"
        "@pl mbarrier.arrive.shared::cta.b64 _, [t+231544];\n"
        "}\n"
        :: "r"(sb + SM_X + c.xoff[0]), "r"(sb + SM_X + c.xoff[1]), "r"(sb + SM_Y1 + c.yoff[0][0]), "r"(sb + SM_Y1 + c.yoff[0][1]),
           "r"(sb + SM_Y1 + c.yoff[1][0]), "r"(sb + SM_Y1 + c.yoff[1][1]), "r"(c.stat), "r"(c.own), "r"(c.lane),
           "l"(prm.sel[0]), "l"(prm.sel[1]), "l"(prm.sel[2]), "r"(prm.ydesc), "f"(LN_EPS_SCALED), "f"(RSTD_SCALE), "r"(prm.w1desc)
        : "memory");
}

__device__ __forceinline__ void produce(const Producer& c, const Params& prm) {
    uint32_t B[24], C[24];
    uint32_t st[8];
    uint32_t v[6][6];
    uint32_t ws[6];
#pragma unroll
    for (int u = 0; u < 6; u++) {
        ws[u] = c.w[0][u];
#pragma unroll
        for (int t = 1; t < 9; t++) ws[u] = bf2_add(ws[u], c.w[t][u]);
    }
    SMARK(2);
#pragma unroll 1
    for (int i = loop_init<0>();; i++) {
        mbar_wait_c<0>(sb + SM_GO + i * 8);
        SMARK(4 + i);
        load_x(v, c, sb + SM_X + i * SLOT_BYTES);
        fence_async_smem();
        asm volatile("bar.arrive %0, 160;" ::"r"(6 + i) : "memory");
        if (i == 2) break;
        if (i == 0) {
            const uint32_t p = bf2_add(bf2_fma(v[2][2], ws[2], bf2_fma(v[2][1], ws[1], bf2_mul(v[2][0], ws[0]))),
                                       bf2_fma(v[2][5], ws[5], bf2_fma(v[2][4], ws[4], bf2_mul(v[2][3], ws[3]))));
            float e = quad_sum(bf_lo(p) + bf_hi(p));
            e = (e + __shfl_xor_sync(0xffffffffu, e, 4)) * (-1.0f / CH);
            st[1] = st[3] = st[5] = st[7] = pack_bf2(e, e);
#pragma unroll
            for (int k = 0; k < NX; k++) sts32(c.own + k * SLOT_BYTES + 4, st[1]);
        } else {
            conv_row<1, 1>(B, C, v, c);
        }
        conv_row<0, 0>(C, st, v, c);
    }
    asm volatile(".reg .b32 pw<54>, pb<24>, pc<24>, pv<36>, ps<8>;");
    hand_over<0>(c, B, C, v);
    asm volatile("mov.b32 ps1, %0; mov.b32 ps3, %1; mov.b32 ps5, %2; mov.b32 ps7, %3;" ::"r"(st[1]), "r"(st[3]), "r"(st[5]), "r"(st[7]));
    SMARK(7);
    produce_tiles(c, prm);
    mbar_arrive_if(sb + SM_YFULL + ROWS_PER_CTA * 8, c.lane == 0);
}

struct Duty {
    const char* g;
    const char* zeros;
    long long step;
    uint32_t s, bytes;
    int end, zero;
};
__device__ __forceinline__ Duty make_duty(const Params& prm, int wg, int w) {
    const RowCopy rc = row_copy(prm);
    Duty d;
    d.g = (w == 2 ? rc.y0 : rc.x0 + (w == 0 ? rc.cut0 : w == 1 ? 32 * 192 : 192)) +
          (wg + (w == 2 ? 0 : w < 2 ? 2 * NX : 2 * NX + L2_AHEAD)) * rc.stride;
    d.step = NX * rc.stride;
    d.s = wg * SLOT_BYTES + (w == 2 ? sb + SM_Y1 : sb + SM_X + (w == 0 ? rc.cut0 : XHALF_B));
    d.bytes = w >= 2 ? TILE_BYTES : XHALF_BYTES - (w == 0 ? rc.cut0 : rc.cut1);
    d.end = w == 2 ? ROWS_PER_CTA : w < 2 ? STEPS + 1 - 2 * NX : rc.last + 1 - 2 * NX - L2_AHEAD;
    d.zero = rc.last + 1 - 2 * NX;
    d.zeros = rc.zeros;
    return d;
}

static_assert(sb + SM_BAR == 230800 && sb + SM_YFULL == 231552 && sb + SM_GO == 231240 && SLOT_BYTES == 26624 && sb + SM_GAMMA == 229248 &&
              SM_BETA == SM_GAMMA + 768 && SM_W2 == 73728 && sb + SM_BUF3 == 187392 && BAR_W2 == 9 && BAR_W1B == 10, "layout");
__device__ __forceinline__ void consume(float (&acc)[2][2], uint32_t w1t, uint32_t yd, uint32_t wd, uint32_t own_slot, const Duty& d,
                                        uint32_t role, uint32_t lane, const Params& prm) {
    asm volatile(
        "{\n"
        ".reg .b32 z<32>, w<44>, p, a<4>, lo<2>, hi<2>, t, g, q<4>, dl, dh, n, so, c, tt, cnt, f0, f1;\n"
        ".reg .b16 xl, xh, xr;\n"
        ".reg .b64 ds<6>, wd, gp, src;\n"
        ".reg .pred pt, pf, pr, pw, pl, pe;\n"
        "setp.ne.b32 pt, 1, 0; setp.ne.b32 pf, 0, 0; setp.eq.u32 pl, %15, 0;\n"
        "mov.b32 c, 0x40D940D9;\n"
        "ldmatrix.sync.aligned.m8n8.x4.trans.shared.b16 {w0,w1,w2,w3}, [%4+0];\n"
        "ldmatrix.sync.aligned.m8n8.x4.trans.shared.b16 {w4,w5,w6,w7}, [%4+2048];\n"
        "ldmatrix.sync.aligned.m8n8.x4.trans.shared.b16 {w8,w9,w10,w11}, [%4+4096];\n"
        "ldmatrix.sync.aligned.m8n8.x4.trans.shared.b16 {w12,w13,w14,w15}, [%4+6144];\n"
        "ldmatrix.sync.aligned.m8n8.x4.trans.shared.b16 {w16,w17,w18,w19}, [%4+8192];\n"
        "ldmatrix.sync.aligned.m8n8.x4.trans.shared.b16 {w20,w21,w22,w23}, [%4+10240];\n"
        "shl.b32 f0, w0, 16; and.b32 f1, w0, 0xffff0000; cvt.rn.f16x2.f32 w0, f1, f0; shl.b32 f0, w1, 16; and.b32 f1, w1, 0xffff0000; cvt.rn.f16x2.f32 w1, f1, f0; shl.b32 f0, w2, 16; and.b32 f1, w2, 0xffff0000; cvt.rn.f16x2.f32 w2, f1, f0; shl.b32 f0, w3, 16; and.b32 f1, w3, 0xffff0000; cvt.rn.f16x2.f32 w3, f1, f0;\n"
        "stmatrix.sync.aligned.m8n8.x4.trans.shared.b16 [%4+0], {w0,w1,w2,w3};\n"
        "shl.b32 f0, w4, 16; and.b32 f1, w4, 0xffff0000; cvt.rn.f16x2.f32 w4, f1, f0; shl.b32 f0, w5, 16; and.b32 f1, w5, 0xffff0000; cvt.rn.f16x2.f32 w5, f1, f0; shl.b32 f0, w6, 16; and.b32 f1, w6, 0xffff0000; cvt.rn.f16x2.f32 w6, f1, f0; shl.b32 f0, w7, 16; and.b32 f1, w7, 0xffff0000; cvt.rn.f16x2.f32 w7, f1, f0;\n"
        "stmatrix.sync.aligned.m8n8.x4.trans.shared.b16 [%4+2048], {w4,w5,w6,w7};\n"
        "shl.b32 f0, w8, 16; and.b32 f1, w8, 0xffff0000; cvt.rn.f16x2.f32 w8, f1, f0; shl.b32 f0, w9, 16; and.b32 f1, w9, 0xffff0000; cvt.rn.f16x2.f32 w9, f1, f0; shl.b32 f0, w10, 16; and.b32 f1, w10, 0xffff0000; cvt.rn.f16x2.f32 w10, f1, f0; shl.b32 f0, w11, 16; and.b32 f1, w11, 0xffff0000; cvt.rn.f16x2.f32 w11, f1, f0;\n"
        "stmatrix.sync.aligned.m8n8.x4.trans.shared.b16 [%4+4096], {w8,w9,w10,w11};\n"
        "shl.b32 f0, w12, 16; and.b32 f1, w12, 0xffff0000; cvt.rn.f16x2.f32 w12, f1, f0; shl.b32 f0, w13, 16; and.b32 f1, w13, 0xffff0000; cvt.rn.f16x2.f32 w13, f1, f0; shl.b32 f0, w14, 16; and.b32 f1, w14, 0xffff0000; cvt.rn.f16x2.f32 w14, f1, f0; shl.b32 f0, w15, 16; and.b32 f1, w15, 0xffff0000; cvt.rn.f16x2.f32 w15, f1, f0;\n"
        "stmatrix.sync.aligned.m8n8.x4.trans.shared.b16 [%4+6144], {w12,w13,w14,w15};\n"
        "shl.b32 f0, w16, 16; and.b32 f1, w16, 0xffff0000; cvt.rn.f16x2.f32 w16, f1, f0; shl.b32 f0, w17, 16; and.b32 f1, w17, 0xffff0000; cvt.rn.f16x2.f32 w17, f1, f0; shl.b32 f0, w18, 16; and.b32 f1, w18, 0xffff0000; cvt.rn.f16x2.f32 w18, f1, f0; shl.b32 f0, w19, 16; and.b32 f1, w19, 0xffff0000; cvt.rn.f16x2.f32 w19, f1, f0;\n"
        "stmatrix.sync.aligned.m8n8.x4.trans.shared.b16 [%4+8192], {w16,w17,w18,w19};\n"
        "shl.b32 f0, w20, 16; and.b32 f1, w20, 0xffff0000; cvt.rn.f16x2.f32 w20, f1, f0; shl.b32 f0, w21, 16; and.b32 f1, w21, 0xffff0000; cvt.rn.f16x2.f32 w21, f1, f0; shl.b32 f0, w22, 16; and.b32 f1, w22, 0xffff0000; cvt.rn.f16x2.f32 w22, f1, f0; shl.b32 f0, w23, 16; and.b32 f1, w23, 0xffff0000; cvt.rn.f16x2.f32 w23, f1, f0;\n"
        "stmatrix.sync.aligned.m8n8.x4.trans.shared.b16 [%4+10240], {w20,w21,w22,w23};\n"
        "mov.u32 tt, 230880; mbarrier.try_wait.parity.shared::cta.b64 pw, [tt], 0;\n"
        "@!pw bra.uni SPINW;\n"
        "BACKW:\n"
        "ldmatrix.sync.aligned.m8n8.x4.trans.shared.b16 {z0,z1,z2,z3}, [%4+22528];\n"
        "ldmatrix.sync.aligned.m8n8.x4.trans.shared.b16 {w24,w25,w26,w27}, [%4+12288];\n"
        "ldmatrix.sync.aligned.m8n8.x4.trans.shared.b16 {w28,w29,w30,w31}, [%4+14336];\n"
        "ldmatrix.sync.aligned.m8n8.x4.trans.shared.b16 {w32,w33,w34,w35}, [%4+16384];\n"
        "ldmatrix.sync.aligned.m8n8.x4.trans.shared.b16 {w36,w37,w38,w39}, [%4+18432];\n"
        "ldmatrix.sync.aligned.m8n8.x4.trans.shared.b16 {w40,w41,w42,w43}, [%4+20480];\n"
        "shl.b32 f0, z0, 16; and.b32 f1, z0, 0xffff0000; cvt.rn.f16x2.f32 z0, f1, f0; shl.b32 f0, z1, 16; and.b32 f1, z1, 0xffff0000; cvt.rn.f16x2.f32 z1, f1, f0; shl.b32 f0, z2, 16; and.b32 f1, z2, 0xffff0000; cvt.rn.f16x2.f32 z2, f1, f0; shl.b32 f0, z3, 16; and.b32 f1, z3, 0xffff0000; cvt.rn.f16x2.f32 z3, f1, f0;\n"
        "stmatrix.sync.aligned.m8n8.x4.trans.shared.b16 [%4+22528], {z0,z1,z2,z3};\n"
        "shl.b32 f0, w24, 16; and.b32 f1, w24, 0xffff0000; cvt.rn.f16x2.f32 w24, f1, f0; shl.b32 f0, w25, 16; and.b32 f1, w25, 0xffff0000; cvt.rn.f16x2.f32 w25, f1, f0; shl.b32 f0, w26, 16; and.b32 f1, w26, 0xffff0000; cvt.rn.f16x2.f32 w26, f1, f0; shl.b32 f0, w27, 16; and.b32 f1, w27, 0xffff0000; cvt.rn.f16x2.f32 w27, f1, f0;\n"
        "stmatrix.sync.aligned.m8n8.x4.trans.shared.b16 [%4+12288], {w24,w25,w26,w27};\n"
        "shl.b32 f0, w28, 16; and.b32 f1, w28, 0xffff0000; cvt.rn.f16x2.f32 w28, f1, f0; shl.b32 f0, w29, 16; and.b32 f1, w29, 0xffff0000; cvt.rn.f16x2.f32 w29, f1, f0; shl.b32 f0, w30, 16; and.b32 f1, w30, 0xffff0000; cvt.rn.f16x2.f32 w30, f1, f0; shl.b32 f0, w31, 16; and.b32 f1, w31, 0xffff0000; cvt.rn.f16x2.f32 w31, f1, f0;\n"
        "stmatrix.sync.aligned.m8n8.x4.trans.shared.b16 [%4+14336], {w28,w29,w30,w31};\n"
        "shl.b32 f0, w32, 16; and.b32 f1, w32, 0xffff0000; cvt.rn.f16x2.f32 w32, f1, f0; shl.b32 f0, w33, 16; and.b32 f1, w33, 0xffff0000; cvt.rn.f16x2.f32 w33, f1, f0; shl.b32 f0, w34, 16; and.b32 f1, w34, 0xffff0000; cvt.rn.f16x2.f32 w34, f1, f0; shl.b32 f0, w35, 16; and.b32 f1, w35, 0xffff0000; cvt.rn.f16x2.f32 w35, f1, f0;\n"
        "stmatrix.sync.aligned.m8n8.x4.trans.shared.b16 [%4+16384], {w32,w33,w34,w35};\n"
        "shl.b32 f0, w36, 16; and.b32 f1, w36, 0xffff0000; cvt.rn.f16x2.f32 w36, f1, f0; shl.b32 f0, w37, 16; and.b32 f1, w37, 0xffff0000; cvt.rn.f16x2.f32 w37, f1, f0; shl.b32 f0, w38, 16; and.b32 f1, w38, 0xffff0000; cvt.rn.f16x2.f32 w38, f1, f0; shl.b32 f0, w39, 16; and.b32 f1, w39, 0xffff0000; cvt.rn.f16x2.f32 w39, f1, f0;\n"
        "stmatrix.sync.aligned.m8n8.x4.trans.shared.b16 [%4+18432], {w36,w37,w38,w39};\n"
        "shl.b32 f0, w40, 16; and.b32 f1, w40, 0xffff0000; cvt.rn.f16x2.f32 w40, f1, f0; shl.b32 f0, w41, 16; and.b32 f1, w41, 0xffff0000; cvt.rn.f16x2.f32 w41, f1, f0; shl.b32 f0, w42, 16; and.b32 f1, w42, 0xffff0000; cvt.rn.f16x2.f32 w42, f1, f0; shl.b32 f0, w43, 16; and.b32 f1, w43, 0xffff0000; cvt.rn.f16x2.f32 w43, f1, f0;\n"
        "stmatrix.sync.aligned.m8n8.x4.trans.shared.b16 [%4+20480], {w40,w41,w42,w43};\n"
        "fence.proxy.async.shared::cta;\n"
        ASM_SMARK
        "mov.b32 p, 0; mov.b32 t, 0; mov.b32 g, 0; mov.b32 a0, 0; mov.b32 a1, 0; mov.b32 a2, 0; mov.b32 a3, 0; mov.b32 lo0, 0; mov.b32 lo1, 0; mov.b32 hi0, 0; mov.b32 hi1, 0; mov.b32 q0, 0; mov.b32 q1, 0; mov.b32 q2, 0; mov.b32 q3, 0;\n"
        "mov.b32 z16, 0; mov.b32 z17, 0; mov.b32 z18, 0; mov.b32 z19, 0; mov.b32 z20, 0; mov.b32 z21, 0; mov.b32 z22, 0; mov.b32 z23, 0; mov.b32 z24, 0; mov.b32 z25, 0; mov.b32 z26, 0; mov.b32 z27, 0; mov.b32 z28, 0; mov.b32 z29, 0; mov.b32 z30, 0; mov.b32 z31, 0;\n"
        "mov.f32 %0, 0f00000000; mov.f32 %1, 0f00000000; mov.f32 %2, 0f00000000; mov.f32 %3, 0f00000000;\n"
        "mov.u32 n, 0; mov.u32 so, 0; mov.b64 gp, %8; mov.b64 wd, {%6, 0x40000040};\n"
        "mov.b64 ds0, %20; add.s64 ds1, ds0, 2; add.s64 ds2, ds0, 4; add.s64 ds3, ds0, 6; mov.b64 ds4, %21; add.s64 ds5, ds4, 2;\n"
        "mbarrier.try_wait.parity.shared::cta.b64 pw, [n+231552], 0;\n"
        "@!pw bra.uni SPIN0;\n"
        "BACK0:\n"
        ASM_TS
        "wgmma.fence.sync.aligned;\n"
        "wgmma.mma_async.sync.aligned.m64n64k16.f16.f16.f16 {z0,z1,z2,z3,z4,z5,z6,z7,z8,z9,z10,z11,z12,z13,z14,z15}, {w0,w1,w2,w3}, ds0, pf, 1, 1, 0;\n"
        "wgmma.mma_async.sync.aligned.m64n64k16.f16.f16.f16 {z0,z1,z2,z3,z4,z5,z6,z7,z8,z9,z10,z11,z12,z13,z14,z15}, {w4,w5,w6,w7}, ds1, pt, 1, 1, 0;\n"
        "wgmma.mma_async.sync.aligned.m64n64k16.f16.f16.f16 {z0,z1,z2,z3,z4,z5,z6,z7,z8,z9,z10,z11,z12,z13,z14,z15}, {w8,w9,w10,w11}, ds2, pt, 1, 1, 0;\n"
        "wgmma.fence.sync.aligned;\n"
        "wgmma.mma_async.sync.aligned.m64n64k16.f16.f16.f16 {z0,z1,z2,z3,z4,z5,z6,z7,z8,z9,z10,z11,z12,z13,z14,z15}, {w12,w13,w14,w15}, ds3, pt, 1, 1, 0;\n"
        "wgmma.mma_async.sync.aligned.m64n64k16.f16.f16.f16 {z0,z1,z2,z3,z4,z5,z6,z7,z8,z9,z10,z11,z12,z13,z14,z15}, {w16,w17,w18,w19}, ds4, pt, 1, 1, 0;\n"
        "wgmma.mma_async.sync.aligned.m64n64k16.f16.f16.f16 {z0,z1,z2,z3,z4,z5,z6,z7,z8,z9,z10,z11,z12,z13,z14,z15}, {w20,w21,w22,w23}, ds5, pt, 1, 1, 0;\n"
        "wgmma.commit_group.sync.aligned;\n"
        "setp.eq.u32 pr, so, %7;\n"
        "@pr bra.uni DUTY;\n"
        "TOP:\n"
        ASM_TRC("n")
        "wgmma.wait_group.sync.aligned 0;\n"
        "mov.b32 {xl, xh}, a2; tanh.approx.f16 xr, xh; cvt.u32.u16 hi0, xr; mul.rn.f16x2 a3, z31, p; fma.rn.f16x2 p, z0, z0, c; fma.rn.f16x2 q3, g, g, q3; fma.rn.f16x2 g, z28, t, z28; prmt.b32 t, lo1, hi1, 0x5410; tanh.approx.f16 xr, xl; cvt.u32.u16 lo0, xr;\n"
        "B31:\n"
        "mov.b32 {xl, xh}, a3; tanh.approx.f16 xr, xh; cvt.u32.u16 hi1, xr; mul.rn.f16x2 a0, z0, p; fma.rn.f16x2 p, z1, z1, c; fma.rn.f16x2 q2, g, g, q2; fma.rn.f16x2 g, z29, t, z29; prmt.b32 t, lo0, hi0, 0x5410; tanh.approx.f16 xr, xl; cvt.u32.u16 lo1, xr;\n"
        "B0:\n"
        "mov.b32 {xl, xh}, a0; tanh.approx.f16 xr, xh; cvt.u32.u16 hi0, xr; mul.rn.f16x2 a1, z1, p; fma.rn.f16x2 p, z2, z2, c; fma.rn.f16x2 q3, g, g, q3; fma.rn.f16x2 g, z30, t, z30; prmt.b32 t, lo1, hi1, 0x5410; tanh.approx.f16 xr, xl; cvt.u32.u16 lo0, xr;\n"
        "B1:\n"
        "mov.b32 {xl, xh}, a1; tanh.approx.f16 xr, xh; cvt.u32.u16 hi1, xr; mul.rn.f16x2 a2, z2, p; fma.rn.f16x2 p, z3, z3, c; fma.rn.f16x2 q2, g, g, q2; fma.rn.f16x2 g, z31, t, z31; prmt.b32 t, lo0, hi0, 0x5410; tanh.approx.f16 xr, xl; cvt.u32.u16 lo1, xr;\n"
        "B2:\n"
        "wgmma.fence.sync.aligned;\n"
        "wgmma.mma_async.sync.aligned.m64n64k16.f16.f16.f16 {z16,z17,z18,z19,z20,z21,z22,z23,z24,z25,z26,z27,z28,z29,z30,z31}, {w24,w25,w26,w27}, ds0, pf, 1, 1, 0;\n"
        "wgmma.mma_async.sync.aligned.m64n64k16.f16.f16.f16 {z16,z17,z18,z19,z20,z21,z22,z23,z24,z25,z26,z27,z28,z29,z30,z31}, {w28,w29,w30,w31}, ds1, pt, 1, 1, 0;\n"
        "wgmma.mma_async.sync.aligned.m64n64k16.f16.f16.f16 {z16,z17,z18,z19,z20,z21,z22,z23,z24,z25,z26,z27,z28,z29,z30,z31}, {w32,w33,w34,w35}, ds2, pt, 1, 1, 0;\n"
        "mov.b32 {xl, xh}, a2; tanh.approx.f16 xr, xh; cvt.u32.u16 hi0, xr; mul.rn.f16x2 a3, z3, p; fma.rn.f16x2 p, z4, z4, c; fma.rn.f16x2 q3, g, g, q3; fma.rn.f16x2 g, z0, t, z0; prmt.b32 t, lo1, hi1, 0x5410; tanh.approx.f16 xr, xl; cvt.u32.u16 lo0, xr;\n"
        "B3:\n"
        "mov.b32 {xl, xh}, a3; tanh.approx.f16 xr, xh; cvt.u32.u16 hi1, xr; mul.rn.f16x2 a0, z4, p; fma.rn.f16x2 p, z5, z5, c; fma.rn.f16x2 q0, g, g, q0; fma.rn.f16x2 g, z1, t, z1; prmt.b32 t, lo0, hi0, 0x5410; tanh.approx.f16 xr, xl; cvt.u32.u16 lo1, xr;\n"
        "B4:\n"
        "mov.b32 {xl, xh}, a0; tanh.approx.f16 xr, xh; cvt.u32.u16 hi0, xr; mul.rn.f16x2 a1, z5, p; fma.rn.f16x2 p, z6, z6, c; fma.rn.f16x2 q1, g, g, q1; fma.rn.f16x2 g, z2, t, z2; prmt.b32 t, lo1, hi1, 0x5410; tanh.approx.f16 xr, xl; cvt.u32.u16 lo0, xr;\n"
        "B5:\n"
        "wgmma.fence.sync.aligned;\n"
        "wgmma.mma_async.sync.aligned.m64n64k16.f16.f16.f16 {z16,z17,z18,z19,z20,z21,z22,z23,z24,z25,z26,z27,z28,z29,z30,z31}, {w36,w37,w38,w39}, ds3, pt, 1, 1, 0;\n"
        "wgmma.mma_async.sync.aligned.m64n64k16.f16.f16.f16 {z16,z17,z18,z19,z20,z21,z22,z23,z24,z25,z26,z27,z28,z29,z30,z31}, {w40,w41,w42,w43}, ds4, pt, 1, 1, 0;\n"
        "wgmma.mma_async.sync.aligned.m64n64k16.f16.f16.f16 {z16,z17,z18,z19,z20,z21,z22,z23,z24,z25,z26,z27,z28,z29,z30,z31}, wd, ds5, pt, 1, 1, 1, 0;\n"
        "wgmma.commit_group.sync.aligned;\n"
        "mov.b32 {xl, xh}, a1; tanh.approx.f16 xr, xh; cvt.u32.u16 hi1, xr; mul.rn.f16x2 a2, z6, p; fma.rn.f16x2 p, z7, z7, c; fma.rn.f16x2 q0, g, g, q0; fma.rn.f16x2 g, z3, t, z3; prmt.b32 t, lo0, hi0, 0x5410; tanh.approx.f16 xr, xl; cvt.u32.u16 lo1, xr;\n"
        "B6:\n"
        "add.u32 so, so, 26624; setp.eq.u32 pr, so, 79872; selp.u32 so, 0, so, pr;\n"
        "mov.b32 {xl, xh}, a2; tanh.approx.f16 xr, xh; cvt.u32.u16 hi0, xr; mul.rn.f16x2 a3, z7, p; fma.rn.f16x2 p, z8, z8, c; fma.rn.f16x2 q1, g, g, q1; fma.rn.f16x2 g, z4, t, z4; prmt.b32 t, lo1, hi1, 0x5410; tanh.approx.f16 xr, xl; cvt.u32.u16 lo0, xr;\n"
        "B7:\n"
        "shr.u32 tt, so, 4;\n"
        "mov.b64 {dl, dh}, ds0; add.u32 dl, tt, 74816; mov.b64 ds0, {dl, dh}; mov.b64 {dl, dh}, ds1; add.u32 dl, tt, 74818; mov.b64 ds1, {dl, dh}; mov.b64 {dl, dh}, ds2; add.u32 dl, tt, 74820; mov.b64 ds2, {dl, dh};\n"
        "mov.b32 {xl, xh}, a3; tanh.approx.f16 xr, xh; cvt.u32.u16 hi1, xr; mul.rn.f16x2 a0, z8, p; fma.rn.f16x2 p, z9, z9, c; fma.rn.f16x2 q0, g, g, q0; fma.rn.f16x2 g, z5, t, z5; prmt.b32 t, lo0, hi0, 0x5410; tanh.approx.f16 xr, xl; cvt.u32.u16 lo1, xr;\n"
        "B8:\n"
        "shr.u32 tt, so, 4;\n"
        "mov.b64 {dl, dh}, ds3; add.u32 dl, tt, 74822; mov.b64 ds3, {dl, dh}; mov.b64 {dl, dh}, ds4; add.u32 dl, tt, 75328; mov.b64 ds4, {dl, dh}; mov.b64 {dl, dh}, ds5; add.u32 dl, tt, 75330; mov.b64 ds5, {dl, dh};\n"
        "mov.b32 {xl, xh}, a0; tanh.approx.f16 xr, xh; cvt.u32.u16 hi0, xr; mul.rn.f16x2 a1, z9, p; fma.rn.f16x2 p, z10, z10, c; fma.rn.f16x2 q1, g, g, q1; fma.rn.f16x2 g, z6, t, z6; prmt.b32 t, lo1, hi1, 0x5410; tanh.approx.f16 xr, xl; cvt.u32.u16 lo0, xr;\n"
        "B9:\n"
        "mov.b32 {xl, xh}, a1; tanh.approx.f16 xr, xh; cvt.u32.u16 hi1, xr; mul.rn.f16x2 a2, z10, p; fma.rn.f16x2 p, z11, z11, c; fma.rn.f16x2 q0, g, g, q0; fma.rn.f16x2 g, z7, t, z7; prmt.b32 t, lo0, hi0, 0x5410; tanh.approx.f16 xr, xl; cvt.u32.u16 lo1, xr;\n"
        "B10:\n"
        "mov.b32 {xl, xh}, a2; tanh.approx.f16 xr, xh; cvt.u32.u16 hi0, xr; mul.rn.f16x2 a3, z11, p; fma.rn.f16x2 p, z12, z12, c; fma.rn.f16x2 q1, g, g, q1; fma.rn.f16x2 g, z8, t, z8; prmt.b32 t, lo1, hi1, 0x5410; tanh.approx.f16 xr, xl; cvt.u32.u16 lo0, xr;\n"
        "B11:\n"
        "mov.b32 {xl, xh}, a3; tanh.approx.f16 xr, xh; cvt.u32.u16 hi1, xr; mul.rn.f16x2 a0, z12, p; fma.rn.f16x2 p, z13, z13, c; fma.rn.f16x2 q0, g, g, q0; fma.rn.f16x2 g, z9, t, z9; prmt.b32 t, lo0, hi0, 0x5410; tanh.approx.f16 xr, xl; cvt.u32.u16 lo1, xr;\n"
        "B12:\n"
        "mov.b32 {xl, xh}, a0; tanh.approx.f16 xr, xh; cvt.u32.u16 hi0, xr; mul.rn.f16x2 a1, z13, p; fma.rn.f16x2 p, z14, z14, c; fma.rn.f16x2 q1, g, g, q1; fma.rn.f16x2 g, z10, t, z10; prmt.b32 t, lo1, hi1, 0x5410; tanh.approx.f16 xr, xl; cvt.u32.u16 lo0, xr;\n"
        "B13:\n"
        "mov.b32 {xl, xh}, a1; tanh.approx.f16 xr, xh; cvt.u32.u16 hi1, xr; mul.rn.f16x2 a2, z14, p; fma.rn.f16x2 p, z15, z15, c; fma.rn.f16x2 q0, g, g, q0; fma.rn.f16x2 g, z11, t, z11; prmt.b32 t, lo0, hi0, 0x5410; tanh.approx.f16 xr, xl; cvt.u32.u16 lo1, xr;\n"
        "B14:\n"
        "wgmma.wait_group.sync.aligned 0;\n"
        "cp.async.bulk.wait_group.read 0;\n"
        "@pl mbarrier.arrive.shared::cta.b64 _, [n+231288];\n"
        "mov.b32 {xl, xh}, a2; tanh.approx.f16 xr, xh; cvt.u32.u16 hi0, xr; mul.rn.f16x2 a3, z15, p; fma.rn.f16x2 p, z16, z16, c; fma.rn.f16x2 q1, g, g, q1; fma.rn.f16x2 g, z12, t, z12; prmt.b32 t, lo1, hi1, 0x5410; tanh.approx.f16 xr, xl; cvt.u32.u16 lo0, xr;\n"
        "B15:\n"
        "mov.b32 {xl, xh}, a3; tanh.approx.f16 xr, xh; cvt.u32.u16 hi1, xr; mul.rn.f16x2 a0, z16, p; fma.rn.f16x2 p, z17, z17, c; fma.rn.f16x2 q0, g, g, q0; fma.rn.f16x2 g, z13, t, z13; prmt.b32 t, lo0, hi0, 0x5410; tanh.approx.f16 xr, xl; cvt.u32.u16 lo1, xr;\n"
        "B16:\n"
        "mbarrier.try_wait.parity.shared::cta.b64 pw, [n+231560], 0;\n"
        "mov.b32 {xl, xh}, a0; tanh.approx.f16 xr, xh; cvt.u32.u16 hi0, xr; mul.rn.f16x2 a1, z17, p; fma.rn.f16x2 p, z18, z18, c; fma.rn.f16x2 q1, g, g, q1; fma.rn.f16x2 g, z14, t, z14; prmt.b32 t, lo1, hi1, 0x5410; tanh.approx.f16 xr, xl; cvt.u32.u16 lo0, xr;\n"
        "B17:\n"
        "mov.b32 {xl, xh}, a1; tanh.approx.f16 xr, xh; cvt.u32.u16 hi1, xr; mul.rn.f16x2 a2, z18, p; fma.rn.f16x2 p, z19, z19, c; fma.rn.f16x2 q0, g, g, q0; fma.rn.f16x2 g, z15, t, z15; prmt.b32 t, lo0, hi0, 0x5410; tanh.approx.f16 xr, xl; cvt.u32.u16 lo1, xr;\n"
        "B18:\n"
        "@!pw bra.uni SPIN;\n"
        "BACK:\n"
        "wgmma.fence.sync.aligned;\n"
        "wgmma.mma_async.sync.aligned.m64n64k16.f16.f16.f16 {z0,z1,z2,z3,z4,z5,z6,z7,z8,z9,z10,z11,z12,z13,z14,z15}, {w0,w1,w2,w3}, ds0, pf, 1, 1, 0;\n"
        "wgmma.mma_async.sync.aligned.m64n64k16.f16.f16.f16 {z0,z1,z2,z3,z4,z5,z6,z7,z8,z9,z10,z11,z12,z13,z14,z15}, {w4,w5,w6,w7}, ds1, pt, 1, 1, 0;\n"
        "wgmma.mma_async.sync.aligned.m64n64k16.f16.f16.f16 {z0,z1,z2,z3,z4,z5,z6,z7,z8,z9,z10,z11,z12,z13,z14,z15}, {w8,w9,w10,w11}, ds2, pt, 1, 1, 0;\n"
        "mov.b32 {xl, xh}, a2; tanh.approx.f16 xr, xh; cvt.u32.u16 hi0, xr; mul.rn.f16x2 a3, z19, p; fma.rn.f16x2 p, z20, z20, c; fma.rn.f16x2 q1, g, g, q1; fma.rn.f16x2 g, z16, t, z16; prmt.b32 t, lo1, hi1, 0x5410; tanh.approx.f16 xr, xl; cvt.u32.u16 lo0, xr;\n"
        "B19:\n"
        "mov.b32 {xl, xh}, a3; tanh.approx.f16 xr, xh; cvt.u32.u16 hi1, xr; mul.rn.f16x2 a0, z20, p; fma.rn.f16x2 p, z21, z21, c; fma.rn.f16x2 q2, g, g, q2; fma.rn.f16x2 g, z17, t, z17; prmt.b32 t, lo0, hi0, 0x5410; tanh.approx.f16 xr, xl; cvt.u32.u16 lo1, xr;\n"
        "B20:\n"
        "mov.b32 {xl, xh}, a0; tanh.approx.f16 xr, xh; cvt.u32.u16 hi0, xr; mul.rn.f16x2 a1, z21, p; fma.rn.f16x2 p, z22, z22, c; fma.rn.f16x2 q3, g, g, q3; fma.rn.f16x2 g, z18, t, z18; prmt.b32 t, lo1, hi1, 0x5410; tanh.approx.f16 xr, xl; cvt.u32.u16 lo0, xr;\n"
        "B21:\n"
        "wgmma.fence.sync.aligned;\n"
        "wgmma.mma_async.sync.aligned.m64n64k16.f16.f16.f16 {z0,z1,z2,z3,z4,z5,z6,z7,z8,z9,z10,z11,z12,z13,z14,z15}, {w12,w13,w14,w15}, ds3, pt, 1, 1, 0;\n"
        "wgmma.mma_async.sync.aligned.m64n64k16.f16.f16.f16 {z0,z1,z2,z3,z4,z5,z6,z7,z8,z9,z10,z11,z12,z13,z14,z15}, {w16,w17,w18,w19}, ds4, pt, 1, 1, 0;\n"
        "wgmma.mma_async.sync.aligned.m64n64k16.f16.f16.f16 {z0,z1,z2,z3,z4,z5,z6,z7,z8,z9,z10,z11,z12,z13,z14,z15}, {w20,w21,w22,w23}, ds5, pt, 1, 1, 0;\n"
        "wgmma.commit_group.sync.aligned;\n"
        "mov.b32 {xl, xh}, a1; tanh.approx.f16 xr, xh; cvt.u32.u16 hi1, xr; mul.rn.f16x2 a2, z22, p; fma.rn.f16x2 p, z23, z23, c; fma.rn.f16x2 q2, g, g, q2; fma.rn.f16x2 g, z19, t, z19; prmt.b32 t, lo0, hi0, 0x5410; tanh.approx.f16 xr, xl; cvt.u32.u16 lo1, xr;\n"
        "B22:\n"
        "mov.b32 {xl, xh}, a2; tanh.approx.f16 xr, xh; cvt.u32.u16 hi0, xr; mul.rn.f16x2 a3, z23, p; fma.rn.f16x2 p, z24, z24, c; fma.rn.f16x2 q3, g, g, q3; fma.rn.f16x2 g, z20, t, z20; prmt.b32 t, lo1, hi1, 0x5410; tanh.approx.f16 xr, xl; cvt.u32.u16 lo0, xr;\n"
        "B23:\n"
        "mov.b32 {xl, xh}, a3; tanh.approx.f16 xr, xh; cvt.u32.u16 hi1, xr; mul.rn.f16x2 a0, z24, p; fma.rn.f16x2 p, z25, z25, c; fma.rn.f16x2 q2, g, g, q2; fma.rn.f16x2 g, z21, t, z21; prmt.b32 t, lo0, hi0, 0x5410; tanh.approx.f16 xr, xl; cvt.u32.u16 lo1, xr;\n"
        "B24:\n"
        "mov.b32 {xl, xh}, a0; tanh.approx.f16 xr, xh; cvt.u32.u16 hi0, xr; mul.rn.f16x2 a1, z25, p; fma.rn.f16x2 p, z26, z26, c; fma.rn.f16x2 q3, g, g, q3; fma.rn.f16x2 g, z22, t, z22; prmt.b32 t, lo1, hi1, 0x5410; tanh.approx.f16 xr, xl; cvt.u32.u16 lo0, xr;\n"
        "B25:\n"
        "mov.b32 {xl, xh}, a1; tanh.approx.f16 xr, xh; cvt.u32.u16 hi1, xr; mul.rn.f16x2 a2, z26, p; fma.rn.f16x2 p, z27, z27, c; fma.rn.f16x2 q2, g, g, q2; fma.rn.f16x2 g, z23, t, z23; prmt.b32 t, lo0, hi0, 0x5410; tanh.approx.f16 xr, xl; cvt.u32.u16 lo1, xr;\n"
        "B26:\n"
        "mov.b32 {xl, xh}, a2; tanh.approx.f16 xr, xh; cvt.u32.u16 hi0, xr; mul.rn.f16x2 a3, z27, p; fma.rn.f16x2 p, z28, z28, c; fma.rn.f16x2 q3, g, g, q3; fma.rn.f16x2 g, z24, t, z24; prmt.b32 t, lo1, hi1, 0x5410; tanh.approx.f16 xr, xl; cvt.u32.u16 lo0, xr;\n"
        "B27:\n"
        "add.u32 n, n, 8; setp.lt.u32 pe, n, 256; setp.ne.and.u32 pe, so, %7, pe;\n"
        "mov.b32 {xl, xh}, a3; tanh.approx.f16 xr, xh; cvt.u32.u16 hi1, xr; mul.rn.f16x2 a0, z28, p; fma.rn.f16x2 p, z29, z29, c; fma.rn.f16x2 q2, g, g, q2; fma.rn.f16x2 g, z25, t, z25; prmt.b32 t, lo0, hi0, 0x5410; tanh.approx.f16 xr, xl; cvt.u32.u16 lo1, xr;\n"
        "B28:\n"
        "mov.b32 {xl, xh}, a0; tanh.approx.f16 xr, xh; cvt.u32.u16 hi0, xr; mul.rn.f16x2 a1, z29, p; fma.rn.f16x2 p, z30, z30, c; fma.rn.f16x2 q3, g, g, q3; fma.rn.f16x2 g, z26, t, z26; prmt.b32 t, lo1, hi1, 0x5410; tanh.approx.f16 xr, xl; cvt.u32.u16 lo0, xr;\n"
        "B29:\n"
        "mov.b32 {xl, xh}, a1; tanh.approx.f16 xr, xh; cvt.u32.u16 hi1, xr; mul.rn.f16x2 a2, z30, p; fma.rn.f16x2 p, z31, z31, c; fma.rn.f16x2 q2, g, g, q2; fma.rn.f16x2 g, z27, t, z27; prmt.b32 t, lo0, hi0, 0x5410; tanh.approx.f16 xr, xl; cvt.u32.u16 lo1, xr;\n"
        "@pe bra.uni TOP;\n"
        "setp.lt.u32 pe, n, 256;\n"
        "@pe bra.uni DUTY;\n"
        "bra.uni DONE;\n"
        "SPINW: mov.u32 cnt, 0;\n"
        "SPINWL:\n"
        "mov.u32 tt, 230880; mbarrier.try_wait.parity.shared::cta.b64 pw, [tt], 0;\n"
        "@pw bra.uni BACKW;\n"
        "add.u32 cnt, cnt, 1; setp.lt.u32 pw, cnt, 0x100000;\n"
        "@pw bra.uni SPINWL;\n"
        "trap;\n"
        "SPIN0: mov.u32 cnt, 0;\n"
        "SPIN0L:\n"
        "mbarrier.try_wait.parity.shared::cta.b64 pw, [n+231552], 0;\n"
        "@pw bra.uni BACK0;\n"
        "add.u32 cnt, cnt, 1; setp.lt.u32 pw, cnt, 0x100000;\n"
        "@pw bra.uni SPIN0L;\n"
        "trap;\n"
        "SPIN: mov.u32 cnt, 0;\n"
        "SPINL:\n"
        "mbarrier.try_wait.parity.shared::cta.b64 pw, [n+231560], 0;\n"
        "@pw bra.uni BACK;\n"
        "add.u32 cnt, cnt, 1; setp.lt.u32 pw, cnt, 0x100000;\n"
        "@pw bra.uni SPINL;\n"
        "trap;\n"
        "DUTY:\n"
        "setp.ge.s32 pr, n, %11;\n"
        "@pr bra.uni FLUSH;\n"
        "setp.ge.u32 pr, %13, 2;\n"
        "@pr bra.uni ROLE2;\n"
        "setp.ge.s32 pr, n, %12; selp.b64 src, %14, gp, pr; add.u32 tt, n, 231288;\n"
        "elect.sync _|pr, 0xffffffff;\n"
        "@pr mbarrier.arrive.expect_tx.shared::cta.b64 _, [tt], %10;\n"
        "@pr cp.async.bulk.shared::cluster.global.mbarrier::complete_tx::bytes [%9], [src], %10, [tt];\n"
        "bra.uni FLUSH;\n"
        "ROLE2:\n"
        "setp.eq.u32 pr, %13, 3;\n"
        "@pr bra.uni ROLE3;\n"
        "setp.ne.s32 pr, n, 248;\n"
        "@pr bra.uni PARK;\n"
        "cp.async.bulk.wait_group 0;\n"
        "sub.s64 src, gp, %16; mov.u32 tt, 230824; mov.u32 cnt, 187392;\n"
        "elect.sync _|pr, 0xffffffff;\n"
        "@pr mbarrier.arrive.expect_tx.shared::cta.b64 _, [tt], 12288;\n"
        "@pr cp.async.bulk.shared::cluster.global.mbarrier::complete_tx::bytes [cnt], [src], 12288, [tt];\n"
        "PARK:\n"
        "elect.sync _|pr, 0xffffffff;\n"
        "@pr cp.async.bulk.global.shared::cta.bulk_group [gp], [%9], 12288;\n"
        "@pr cp.async.bulk.commit_group;\n"
        "bra.uni FLUSH;\n"
        "ROLE3:\n"
        "setp.ne.s32 pr, n, 64;\n"
        "@pr bra.uni AHEAD;\n"
        "mov.u32 tt, 230872;\n"
        "elect.sync _|pr, 0xffffffff;\n"
        "@pr mbarrier.arrive.expect_tx.shared::cta.b64 _, [tt], 75264;\n"
        "mov.u32 cnt, 229248; @pr cp.async.bulk.shared::cluster.global.mbarrier::complete_tx::bytes [cnt], [%18], 768, [tt];\n"
        "mov.u32 cnt, 230016; @pr cp.async.bulk.shared::cluster.global.mbarrier::complete_tx::bytes [cnt], [%19], 768, [tt];\n"
        "mov.u32 cnt, 74752; @pr cp.async.bulk.tensor.2d.shared::cluster.global.mbarrier::complete_tx::bytes [cnt], [%17, {0, 0}], [tt];\n"
        "mov.u32 cnt, 87040; @pr cp.async.bulk.tensor.2d.shared::cluster.global.mbarrier::complete_tx::bytes [cnt], [%17, {0, 192}], [tt];\n"
        "mov.u32 cnt, 99328; @pr cp.async.bulk.tensor.2d.shared::cluster.global.mbarrier::complete_tx::bytes [cnt], [%17, {32, 0}], [tt];\n"
        "mov.u32 cnt, 111616; @pr cp.async.bulk.tensor.2d.shared::cluster.global.mbarrier::complete_tx::bytes [cnt], [%17, {32, 192}], [tt];\n"
        "mov.u32 cnt, 123904; @pr cp.async.bulk.tensor.2d.shared::cluster.global.mbarrier::complete_tx::bytes [cnt], [%17, {64, 0}], [tt];\n"
        "mov.u32 cnt, 136192; @pr cp.async.bulk.tensor.2d.shared::cluster.global.mbarrier::complete_tx::bytes [cnt], [%17, {64, 192}], [tt];\n"
        "AHEAD:\n"
        "elect.sync _|pr, 0xffffffff;\n"
        "@pr cp.async.bulk.prefetch.L2.global [gp], 12288;\n"
        "FLUSH:\n"
        "add.s64 gp, gp, %16;\n"
        "mov.b32 {xl, xh}, q0; cvt.f32.f16 f0, xl; cvt.f32.f16 f1, xh; add.f32 f0, f0, f1; add.f32 %0, %0, f0; mov.b32 q0, 0;\n"
        "mov.b32 {xl, xh}, q1; cvt.f32.f16 f0, xl; cvt.f32.f16 f1, xh; add.f32 f0, f0, f1; add.f32 %1, %1, f0; mov.b32 q1, 0;\n"
        "mov.b32 {xl, xh}, q2; cvt.f32.f16 f0, xl; cvt.f32.f16 f1, xh; add.f32 f0, f0, f1; add.f32 %2, %2, f0; mov.b32 q2, 0;\n"
        "mov.b32 {xl, xh}, q3; cvt.f32.f16 f0, xl; cvt.f32.f16 f1, xh; add.f32 f0, f0, f1; add.f32 %3, %3, f0; mov.b32 q3, 0;\n"
        "setp.ne.u32 pr, %5, 0;\n"
        "@pr bra.uni TOP;\n"
        "wgmma.wait_group.sync.aligned 0;\n"
        "wgmma.fence.sync.aligned;\n"
        "ld.volatile.shared.v2.b32 {lo0, hi0}, [so]; xor.b32 f0, f0, lo0;\n"
        "ld.volatile.shared.v2.b32 {lo1, hi1}, [so]; xor.b32 f0, f0, lo1;\n"
        "ld.volatile.shared.v2.b32 {q1, a0}, [so]; xor.b32 f0, f0, q1;\n"
        "ld.volatile.shared.v2.b32 {q2, a1}, [so]; xor.b32 f0, f0, q2;\n"
        "ld.volatile.shared.v2.b32 {q3, a2}, [so]; xor.b32 f0, f0, q3;\n"
        "ld.volatile.shared.v2.b32 {q0, a3}, [so]; xor.b32 f0, f0, q0;\n"
        "ld.volatile.shared.v2.b32 {t, g}, [so]; xor.b32 f0, f0, t;\n"
        "ld.volatile.shared.v2.b32 {p, f1}, [so]; xor.b32 f0, f0, p;\n"
        "add.f32 %0, %0, f0;\n"
        "setp.eq.u32 pr, n, 1000; @pr bra.uni B31;\n"
        "setp.eq.u32 pr, n, 1001; @pr bra.uni B0;\n"
        "setp.eq.u32 pr, n, 1002; @pr bra.uni B1;\n"
        "setp.eq.u32 pr, n, 1003; @pr bra.uni B2;\n"
        "setp.eq.u32 pr, n, 1004; @pr bra.uni B3;\n"
        "setp.eq.u32 pr, n, 1005; @pr bra.uni B4;\n"
        "setp.eq.u32 pr, n, 1006; @pr bra.uni B5;\n"
        "setp.eq.u32 pr, n, 1007; @pr bra.uni B6;\n"
        "setp.eq.u32 pr, n, 1008; @pr bra.uni B7;\n"
        "setp.eq.u32 pr, n, 1009; @pr bra.uni B8;\n"
        "setp.eq.u32 pr, n, 1010; @pr bra.uni B9;\n"
        "setp.eq.u32 pr, n, 1011; @pr bra.uni B10;\n"
        "setp.eq.u32 pr, n, 1012; @pr bra.uni B11;\n"
        "setp.eq.u32 pr, n, 1013; @pr bra.uni B12;\n"
        "setp.eq.u32 pr, n, 1014; @pr bra.uni B13;\n"
        "setp.eq.u32 pr, n, 1015; @pr bra.uni B14;\n"
        "setp.eq.u32 pr, n, 1016; @pr bra.uni B15;\n"
        "setp.eq.u32 pr, n, 1017; @pr bra.uni B16;\n"
        "setp.eq.u32 pr, n, 1018; @pr bra.uni B17;\n"
        "setp.eq.u32 pr, n, 1019; @pr bra.uni B18;\n"
        "setp.eq.u32 pr, n, 1020; @pr bra.uni B19;\n"
        "setp.eq.u32 pr, n, 1021; @pr bra.uni B20;\n"
        "setp.eq.u32 pr, n, 1022; @pr bra.uni B21;\n"
        "setp.eq.u32 pr, n, 1023; @pr bra.uni B22;\n"
        "setp.eq.u32 pr, n, 1024; @pr bra.uni B23;\n"
        "setp.eq.u32 pr, n, 1025; @pr bra.uni B24;\n"
        "setp.eq.u32 pr, n, 1026; @pr bra.uni B25;\n"
        "setp.eq.u32 pr, n, 1027; @pr bra.uni B26;\n"
        "setp.eq.u32 pr, n, 1028; @pr bra.uni B27;\n"
        "setp.eq.u32 pr, n, 1029; @pr bra.uni B28;\n"
        "setp.eq.u32 pr, n, 1030; @pr bra.uni B29;\n"
        "setp.eq.u32 pr, n, 1031; @pr bra.uni TOP;\n"
        "trap;\n"
        "DONE:\n"
        ASM_TRC("n")
        "mov.b32 {xl, xh}, a2; tanh.approx.f16 xr, xh; cvt.u32.u16 hi0, xr; mul.rn.f16x2 a3, z31, p; fma.rn.f16x2 q3, g, g, q3; fma.rn.f16x2 g, z28, t, z28; prmt.b32 t, lo1, hi1, 0x5410; tanh.approx.f16 xr, xl; cvt.u32.u16 lo0, xr;\n"
        "mov.b32 {xl, xh}, a3; tanh.approx.f16 xr, xh; cvt.u32.u16 hi1, xr; fma.rn.f16x2 q2, g, g, q2; fma.rn.f16x2 g, z29, t, z29; prmt.b32 t, lo0, hi0, 0x5410; tanh.approx.f16 xr, xl; cvt.u32.u16 lo1, xr;\n"
        "fma.rn.f16x2 q3, g, g, q3; fma.rn.f16x2 g, z30, t, z30; prmt.b32 t, lo1, hi1, 0x5410;\n"
        "fma.rn.f16x2 q2, g, g, q2; fma.rn.f16x2 g, z31, t, z31;\n"
        "fma.rn.f16x2 q3, g, g, q3;\n"
        "mov.b32 {xl, xh}, q0; cvt.f32.f16 f0, xl; cvt.f32.f16 f1, xh; add.f32 f0, f0, f1; add.f32 %0, %0, f0; mov.b32 q0, 0;\n"
        "mov.b32 {xl, xh}, q1; cvt.f32.f16 f0, xl; cvt.f32.f16 f1, xh; add.f32 f0, f0, f1; add.f32 %1, %1, f0; mov.b32 q1, 0;\n"
        "mov.b32 {xl, xh}, q2; cvt.f32.f16 f0, xl; cvt.f32.f16 f1, xh; add.f32 f0, f0, f1; add.f32 %2, %2, f0; mov.b32 q2, 0;\n"
        "mov.b32 {xl, xh}, q3; cvt.f32.f16 f0, xl; cvt.f32.f16 f1, xh; add.f32 f0, f0, f1; add.f32 %3, %3, f0; mov.b32 q3, 0;\n"
        "wgmma.wait_group.sync.aligned 0;\n"
        "}\n"
        : "=f"(acc[0][0]), "=f"(acc[0][1]), "=f"(acc[1][0]), "=f"(acc[1][1])
        : "r"(w1t), "r"(yd), "r"(wd), "r"(own_slot), "l"(d.g), "r"(d.s), "r"(d.bytes), "r"(8 * d.end), "r"(8 * d.zero), "r"(role),
          "l"(d.zeros), "r"(lane), "l"(d.step), "l"(&prm.w2_map), "l"(prm.gamma), "l"(prm.beta), "l"(prm.ydesc64[0]), "l"(prm.ydesc64[1])
        : "memory");
}

template <int M>
__device__ __forceinline__ void gemm1_t(uint32_t (&d)[16], const uint32_t* wa, uint32_t yd, uint32_t wd) {
    wg_fence();
    wgmma_n64_h_set<0>(d, wa, desc<1024, 1>(yd, 0));
#pragma unroll
    for (int kk = 1; kk < 5; kk++)
        wgmma_n64_h_acc<0>(d, wa + kk * 4, kk < 4 ? desc<1024, 1>(yd, kk * 32) : desc<512, 2>(yd, 8192 + (kk - 4) * 32));
    wgmma_n64_h_acc_ss(d, desc<1024, 1>(wd, M * 12288), desc<512, 2>(yd, 8192 + 32));
    wg_commit();
}

__device__ __forceinline__ void gelu_sumsq_f(const uint32_t (&d)[16], float (&acc)[2]) {
#pragma unroll
    for (int r = 0; r < 16; r++) {
        float lo, hi;
        h2_unpack(gelu2(d[r]), lo, hi);
        acc[r & 1] = fmaf(lo, lo, acc[r & 1]);
        acc[r & 1] = fmaf(hi, hi, acc[r & 1]);
    }
}
__device__ __forceinline__ void load_w1t(uint32_t (&wa)[2][24], int wg, int w, int lane) {
#pragma unroll
    for (int m = 0; m < 2; m++)
#pragma unroll
        for (int kk = 0; kk < 5; kk++) {
            const int q = lane >> 3, c = 16 * kk + 8 * (q >> 1) + (lane & 7), ck = 2 * w + (q & 1);
            ldsm4_t(wa[m] + kk * 4, sb + SM_W1 + (2 * wg + m) * 12288 + c * 128 + ((ck ^ (c & 7)) * 16));
        }
}
__device__ __forceinline__ unsigned long long* acc_word(const Params& prm, uint32_t epoch, uint32_t e) {
    return &prm.g->acc[epoch & 1][(e >> 2) * 32 + (e & 3)];
}
__device__ __forceinline__ void publish_fast(const Params& prm, const float (&acc)[2][2], uint32_t epoch, int wg, int w, int lane) {
    const bool m = lane & 2, h = lane & 1;
    const float a = (m ? acc[1][0] : acc[0][0]) + __shfl_xor_sync(0xffffffffu, m ? acc[0][0] : acc[1][0], 2);
    const float b = (m ? acc[1][1] : acc[0][1]) + __shfl_xor_sync(0xffffffffu, m ? acc[0][1] : acc[1][1], 2);
    const float v = (h ? b : a) + __shfl_xor_sync(0xffffffffu, h ? a : b, 1);
    const unsigned long long q = (__float2ull_rn(fminf(v, ACC_LIMIT) * 0x1p16f) << 8) + 1;
    asm volatile("red.relaxed.gpu.global.add.u64 [%0], %1;"
                 ::"l"(acc_word(prm, epoch, 128 * wg + 32 * (lane & 2) + 16 * w + (lane >> 2) + 8 * (lane & 1))), "l"(q) : "memory");
}
__device__ __forceinline__ float collect_fast(const unsigned long long* word, unsigned long long v) {
    asm volatile(
        "{\n.reg .pred p;\n.reg .u32 n, lo, hi;\nmov.u32 n, 0;\n"
        "POLL:\nmov.b64 {lo, hi}, %0;\nand.b32 lo, lo, 255;\n"
        "setp.eq.u32 p, lo, %2;\nvote.sync.all.pred p, p, 0xffffffff;\n@p bra.uni POLL_DONE;\n"
        "ld.relaxed.gpu.global.u64 %0, [%1];\n"
        "add.u32 n, n, 1;\nsetp.lt.u32 p, n, 0x400000;\n@p bra.uni POLL;\ntrap;\nPOLL_DONE:\n}\n"
        : "+l"(v) : "l"(word), "n"(NUM_CTAS) : "memory");
    return __ull2float_rn(v >> 8) * 0x1p-16f;
}
__device__ __forceinline__ void publish_sums(const float (&acc)[2][2], float* sums, unsigned int* counter, int wg, int w, int lane) {
#pragma unroll
    for (int m = 0; m < 2; m++)
#pragma unroll
        for (int h = 0; h < 2; h++) {
            const float v = quad_sum(acc[m][h]);
            if ((lane & 3) == 0) atomicAdd(sums + 64 * (2 * wg + m) + 16 * w + (lane >> 2) + 8 * h, v);
        }
    named_sync(1, 384);
    if (fresh_tid() == 0) asm volatile("red.release.gpu.global.add.u32 [%0], 1;" ::"l"(counter) : "memory");
}
__device__ __forceinline__ void grid_wait(const unsigned int* counter, unsigned int target) {
    if (fresh_tid() == 0) {
        unsigned int v, spins = 0;
        do {
            asm volatile("ld.acquire.gpu.global.u32 %0, [%1];" : "=r"(v) : "l"(counter) : "memory");
            if (++spins > (1u << 22)) __trap();
        } while ((int)(v - target) < 0);
    }
    __syncthreads();
}

struct Pass2 {
    uint32_t wg;
    uint32_t off;
    int step;
    uint32_t xs;
    uint32_t a_offs, xs_offs, bias_addr;
    uint32_t w;
};

static_assert(BAR_Y2FULL == 0 && BAR_XSFULL == 4 && BAR_TURN == 11 && BAR_ROWS == 51 && BAR_STAT == 53 &&
              sb + SM_RED + RED_SCALE * 4 == 230792, "layout");
#define PASS2_STATE ".reg .b32 qa<24>, qz<32>, o<24>, g<16>, p<2>, a<4>, lo<2>, hi<2>, h<2>, osc;"
__device__ __forceinline__ void pass2_start(const Pass2& c, const Params& prm) {
    asm volatile(
        "{\n"
        ".reg .b32 t<2>, c, ad, cnt, ybar;\n"
        ".reg .b16 xl, xh, xr;\n"
        ".reg .b64 w1d, dt;\n"
        ".reg .pred pt, pf, pw;\n"
        "setp.ne.b32 pt, 1, 0; setp.ne.b32 pf, 0, 0; mov.b32 c, 0x40D940D9; mov.b64 w1d, {%0, 0x40000040}; mad.lo.u32 ybar, %1, 8, 230800;\n"
        "mbarrier.try_wait.parity.shared::cta.b64 pw, [ybar], 0;\n"
        "@!pw bra.uni SPINY0;\n"
        "BACKY0:\n"
        "and.b32 t0, %3, 0xffff; shr.u32 t1, %3, 16;\n"
        "xor.b32 ad, t0, 0; add.u32 ad, ad, %2; ldmatrix.sync.aligned.m8n8.x4.shared.b16 {qa0,qa1,qa2,qa3}, [ad];\n"
        "xor.b32 ad, t0, 32; add.u32 ad, ad, %2; ldmatrix.sync.aligned.m8n8.x4.shared.b16 {qa4,qa5,qa6,qa7}, [ad];\n"
        "xor.b32 ad, t0, 64; add.u32 ad, ad, %2; ldmatrix.sync.aligned.m8n8.x4.shared.b16 {qa8,qa9,qa10,qa11}, [ad];\n"
        "xor.b32 ad, t0, 96; add.u32 ad, ad, %2; ldmatrix.sync.aligned.m8n8.x4.shared.b16 {qa12,qa13,qa14,qa15}, [ad];\n"
        "xor.b32 ad, t1, 0; add.u32 ad, ad, %2; ldmatrix.sync.aligned.m8n8.x4.shared.b16 {qa16,qa17,qa18,qa19}, [ad];\n"
        "xor.b32 ad, t1, 32; add.u32 ad, ad, %2; ldmatrix.sync.aligned.m8n8.x4.shared.b16 {qa20,qa21,qa22,qa23}, [ad];\n"
        "wgmma.fence.sync.aligned;\n"
        "add.s64 dt, w1d, 0; wgmma.mma_async.sync.aligned.m64n64k16.f16.f16.f16 {qz0,qz1,qz2,qz3,qz4,qz5,qz6,qz7,qz8,qz9,qz10,qz11,qz12,qz13,qz14,qz15}, {qa0,qa1,qa2,qa3}, dt, pf, 1, 1, 1;\n"
        "add.s64 dt, w1d, 128; wgmma.mma_async.sync.aligned.m64n64k16.f16.f16.f16 {qz0,qz1,qz2,qz3,qz4,qz5,qz6,qz7,qz8,qz9,qz10,qz11,qz12,qz13,qz14,qz15}, {qa4,qa5,qa6,qa7}, dt, pt, 1, 1, 1;\n"
        "add.s64 dt, w1d, 256; wgmma.mma_async.sync.aligned.m64n64k16.f16.f16.f16 {qz0,qz1,qz2,qz3,qz4,qz5,qz6,qz7,qz8,qz9,qz10,qz11,qz12,qz13,qz14,qz15}, {qa8,qa9,qa10,qa11}, dt, pt, 1, 1, 1;\n"
        "add.s64 dt, w1d, 384; wgmma.mma_async.sync.aligned.m64n64k16.f16.f16.f16 {qz0,qz1,qz2,qz3,qz4,qz5,qz6,qz7,qz8,qz9,qz10,qz11,qz12,qz13,qz14,qz15}, {qa12,qa13,qa14,qa15}, dt, pt, 1, 1, 1;\n"
        "add.s64 dt, w1d, 512; wgmma.mma_async.sync.aligned.m64n64k16.f16.f16.f16 {qz0,qz1,qz2,qz3,qz4,qz5,qz6,qz7,qz8,qz9,qz10,qz11,qz12,qz13,qz14,qz15}, {qa16,qa17,qa18,qa19}, dt, pt, 1, 1, 1;\n"
        "add.s64 dt, w1d, 640; wgmma.mma_async.sync.aligned.m64n64k16.f16.f16.f16 {qz0,qz1,qz2,qz3,qz4,qz5,qz6,qz7,qz8,qz9,qz10,qz11,qz12,qz13,qz14,qz15}, {qa20,qa21,qa22,qa23}, dt, pt, 1, 1, 1;\n"
        "wgmma.commit_group.sync.aligned;\n"
        "wgmma.fence.sync.aligned;\n"
        "add.s64 dt, w1d, 768; wgmma.mma_async.sync.aligned.m64n64k16.f16.f16.f16 {qz16,qz17,qz18,qz19,qz20,qz21,qz22,qz23,qz24,qz25,qz26,qz27,qz28,qz29,qz30,qz31}, {qa0,qa1,qa2,qa3}, dt, pf, 1, 1, 1;\n"
        "add.s64 dt, w1d, 896; wgmma.mma_async.sync.aligned.m64n64k16.f16.f16.f16 {qz16,qz17,qz18,qz19,qz20,qz21,qz22,qz23,qz24,qz25,qz26,qz27,qz28,qz29,qz30,qz31}, {qa4,qa5,qa6,qa7}, dt, pt, 1, 1, 1;\n"
        "add.s64 dt, w1d, 1024; wgmma.mma_async.sync.aligned.m64n64k16.f16.f16.f16 {qz16,qz17,qz18,qz19,qz20,qz21,qz22,qz23,qz24,qz25,qz26,qz27,qz28,qz29,qz30,qz31}, {qa8,qa9,qa10,qa11}, dt, pt, 1, 1, 1;\n"
        "add.s64 dt, w1d, 1152; wgmma.mma_async.sync.aligned.m64n64k16.f16.f16.f16 {qz16,qz17,qz18,qz19,qz20,qz21,qz22,qz23,qz24,qz25,qz26,qz27,qz28,qz29,qz30,qz31}, {qa12,qa13,qa14,qa15}, dt, pt, 1, 1, 1;\n"
        "add.s64 dt, w1d, 1280; wgmma.mma_async.sync.aligned.m64n64k16.f16.f16.f16 {qz16,qz17,qz18,qz19,qz20,qz21,qz22,qz23,qz24,qz25,qz26,qz27,qz28,qz29,qz30,qz31}, {qa16,qa17,qa18,qa19}, dt, pt, 1, 1, 1;\n"
        "add.s64 dt, w1d, 1408; wgmma.mma_async.sync.aligned.m64n64k16.f16.f16.f16 {qz16,qz17,qz18,qz19,qz20,qz21,qz22,qz23,qz24,qz25,qz26,qz27,qz28,qz29,qz30,qz31}, {qa20,qa21,qa22,qa23}, dt, pt, 1, 1, 1;\n"
        "wgmma.commit_group.sync.aligned;\n"
        "mov.b32 g0, 0; mov.b32 g1, 0; mov.b32 g2, 0; mov.b32 g3, 0; mov.b32 p0, 0; mov.b32 p1, 0; mov.b32 a0, 0; mov.b32 a1, 0; mov.b32 a2, 0; mov.b32 a3, 0; mov.b32 lo0, 0; mov.b32 lo1, 0; mov.b32 hi0, 0; mov.b32 hi1, 0; mov.b32 h0, 0; mov.b32 h1, 0;\n"
        "wgmma.wait_group.sync.aligned 1;\n"
        "setp.eq.u32 pw, %0, 0;\n"
        "@pw bra.uni HEADE;\n"
        "fma.rn.f16x2 p0, qz0, qz0, c;\n"
        "mul.rn.f16x2 a0, qz0, p0; fma.rn.f16x2 p1, qz1, qz1, c;\n"
        "mov.b32 {xl, xh}, a0; tanh.approx.f16 xr, xl; cvt.u32.u16 lo0, xr; tanh.approx.f16 xr, xh; cvt.u32.u16 hi0, xr; mul.rn.f16x2 a1, qz1, p1; fma.rn.f16x2 p0, qz2, qz2, c;\n"
        "mov.b32 {xl, xh}, a1; tanh.approx.f16 xr, xl; cvt.u32.u16 lo1, xr; tanh.approx.f16 xr, xh; cvt.u32.u16 hi1, xr; mul.rn.f16x2 a2, qz2, p0; fma.rn.f16x2 p1, qz3, qz3, c; prmt.b32 h0, lo0, hi0, 0x5410;\n"
        "mov.b32 {xl, xh}, a2; tanh.approx.f16 xr, xl; cvt.u32.u16 lo0, xr; tanh.approx.f16 xr, xh; cvt.u32.u16 hi0, xr; mul.rn.f16x2 a3, qz3, p1; fma.rn.f16x2 p0, qz4, qz4, c; fma.rn.f16x2 g0, qz0, h0, qz0; prmt.b32 h1, lo1, hi1, 0x5410;\n"
        "mov.b32 {xl, xh}, a3; tanh.approx.f16 xr, xl; cvt.u32.u16 lo1, xr; tanh.approx.f16 xr, xh; cvt.u32.u16 hi1, xr; mul.rn.f16x2 a0, qz4, p0; fma.rn.f16x2 p1, qz5, qz5, c; fma.rn.f16x2 g1, qz1, h1, qz1; prmt.b32 h0, lo0, hi0, 0x5410;\n"
        "mov.b32 {xl, xh}, a0; tanh.approx.f16 xr, xl; cvt.u32.u16 lo0, xr; tanh.approx.f16 xr, xh; cvt.u32.u16 hi0, xr; mul.rn.f16x2 a1, qz5, p1; fma.rn.f16x2 p0, qz6, qz6, c; fma.rn.f16x2 g2, qz2, h0, qz2; prmt.b32 h1, lo1, hi1, 0x5410;\n"
        "mov.b32 {xl, xh}, a1; tanh.approx.f16 xr, xl; cvt.u32.u16 lo1, xr; tanh.approx.f16 xr, xh; cvt.u32.u16 hi1, xr; mul.rn.f16x2 a2, qz6, p0; fma.rn.f16x2 p1, qz7, qz7, c; fma.rn.f16x2 g3, qz3, h1, qz3; prmt.b32 h0, lo0, hi0, 0x5410;\n"
        "HEADE:\n"
        "wgmma.wait_group.sync.aligned 0;\n"
        "bra.uni DONE;\n"
        "SPINY0: mov.u32 cnt, 0;\n"
        "SPINY0L:\n"
        "mbarrier.try_wait.parity.shared::cta.b64 pw, [ybar], 0;\n"
        "@pw bra.uni BACKY0;\n"
        "add.u32 cnt, cnt, 1; setp.lt.u32 pw, cnt, 0x100000;\n"
        "@pw bra.uni SPINY0L;\n"
        "trap;\n"
        "DONE:\n"
        "}\n"
        :: "r"(prm.w1desc), "r"(c.wg), "r"(c.xs), "r"(c.a_offs) : "memory");
}
__device__ __forceinline__ bool pass2_head(const Pass2& c, uint32_t round) {
    uint32_t retry;
    asm volatile(
        "{\n"
        ".reg .b32 t<2>, tt, ad, cnt;\n"
        ".reg .pred pw;\n"
        "and.b32 t0, %3, 0xffff; shr.u32 t1, %3, 16;\n"
        "xor.b32 ad, t0, 0; add.u32 ad, ad, %4; ldmatrix.sync.aligned.m8n8.x4.shared.b16 {qa0,qa1,qa2,qa3}, [ad];\n"
        "xor.b32 ad, t0, 32; add.u32 ad, ad, %4; ldmatrix.sync.aligned.m8n8.x4.shared.b16 {qa4,qa5,qa6,qa7}, [ad];\n"
        "xor.b32 ad, t0, 64; add.u32 ad, ad, %4; ldmatrix.sync.aligned.m8n8.x4.shared.b16 {qa8,qa9,qa10,qa11}, [ad];\n"
        "xor.b32 ad, t0, 96; add.u32 ad, ad, %4; ldmatrix.sync.aligned.m8n8.x4.shared.b16 {qa12,qa13,qa14,qa15}, [ad];\n"
        "xor.b32 ad, t1, 0; add.u32 ad, ad, %4; ldmatrix.sync.aligned.m8n8.x4.shared.b16 {qa16,qa17,qa18,qa19}, [ad];\n"
        "xor.b32 ad, t1, 32; add.u32 ad, ad, %4; ldmatrix.sync.aligned.m8n8.x4.shared.b16 {qa20,qa21,qa22,qa23}, [ad];\n"
        "mov.b32 g4, 0; mov.b32 g5, 0; mov.b32 g6, 0; mov.b32 g7, 0; mov.b32 g8, 0; mov.b32 g9, 0; mov.b32 g10, 0; mov.b32 g11, 0; mov.b32 g12, 0; mov.b32 g13, 0; mov.b32 g14, 0; mov.b32 g15, 0;\n"
        "mov.u32 tt, 231224; mbarrier.try_wait.parity.shared::cta.b64 pw, [tt], %1;\n"
        "@!pw bra.uni SPINR;\n"
        "BACKR:\n"
        "mov.u32 tt, 230792; ld.shared.v2.b32 {osc, %0}, [tt];\n"
        "ld.shared.v4.b32 {o0,o1,o2,o3}, [%2+0];\n"
        "ld.shared.v4.b32 {o4,o5,o6,o7}, [%2+64];\n"
        "ld.shared.v4.b32 {o8,o9,o10,o11}, [%2+128];\n"
        "ld.shared.v4.b32 {o12,o13,o14,o15}, [%2+192];\n"
        "ld.shared.v4.b32 {o16,o17,o18,o19}, [%2+256];\n"
        "ld.shared.v4.b32 {o20,o21,o22,o23}, [%2+320];\n"
        "bra.uni DONE;\n"
        "SPINR: mov.u32 cnt, 0;\n"
        "SPINRL:\n"
        "mov.u32 tt, 231224; mbarrier.try_wait.parity.shared::cta.b64 pw, [tt], %1;\n"
        "@pw bra.uni BACKR;\n"
        "add.u32 cnt, cnt, 1; setp.lt.u32 pw, cnt, 0x100000;\n"
        "@pw bra.uni SPINRL;\n"
        "trap;\n"
        "DONE:\n"
        "}\n"
        : "=r"(retry) : "r"(round), "r"(c.bias_addr), "r"(c.a_offs), "r"(c.xs) : "memory");
    return __any_sync(0xffffffffu, retry);
}
__device__ __forceinline__ void pass2_tiles(const Pass2& c, const Params& prm) {
    asm volatile(
        "{\n"
        ".reg .b32 v<8>, r<24>, n, off, c, tt, ad, cnt, ybar, xbar, tbar, tpar, id;\n"
        ".reg .b16 xl, xh, xr;\n"
        ".reg .f32 f0, f1;\n"
        ".reg .b64 w1d, w2d, dt, gp, pol;\n"
        ".reg .pred pt, pf, pr, pw, pl, pm, pz, pn;\n"
        "setp.ne.b32 pt, 1, 0; setp.ne.b32 pf, 0, 0; setp.eq.u32 pl, %9, 0; setp.eq.u32 pz, %0, 0;\n"
        "mov.b32 c, 0x40D940D9;\n"
        "mov.b64 w1d, {%0, 0x40000040}; mov.b64 w2d, {%1, 0x80000020};\n"
        "mad.lo.u32 ybar, %2, 8, 230800; mad.lo.u32 xbar, %2, 8, 230832; add.u32 id, %2, 2;\n"
        "mad.lo.u32 tbar, %2, 64, 230888; setp.eq.u32 pr, %2, 0; selp.u32 tpar, 1, 0, pr; mov.u32 tt, %laneid; setp.eq.u32 pn, tt, 0;\n"
        "mov.u32 n, -1; add.u32 off, %3, %8; mov.pred pm, pt; createpolicy.fractional.L2::evict_first.b64 pol, 1.0;\n"
        "LOOP:\n"
        "setp.lt.s32 pr, n, 0;\n"
        "@pr bra.uni SKIP0;\n"
        "wgmma.fence.sync.aligned;\n"
        "add.s64 dt, w1d, 768; wgmma.mma_async.sync.aligned.m64n64k16.f16.f16.f16 {qz16,qz17,qz18,qz19,qz20,qz21,qz22,qz23,qz24,qz25,qz26,qz27,qz28,qz29,qz30,qz31}, {qa0,qa1,qa2,qa3}, dt, pf, 1, 1, 1;\n"
        "add.s64 dt, w1d, 896; wgmma.mma_async.sync.aligned.m64n64k16.f16.f16.f16 {qz16,qz17,qz18,qz19,qz20,qz21,qz22,qz23,qz24,qz25,qz26,qz27,qz28,qz29,qz30,qz31}, {qa4,qa5,qa6,qa7}, dt, pt, 1, 1, 1;\n"
        "add.s64 dt, w1d, 1024; wgmma.mma_async.sync.aligned.m64n64k16.f16.f16.f16 {qz16,qz17,qz18,qz19,qz20,qz21,qz22,qz23,qz24,qz25,qz26,qz27,qz28,qz29,qz30,qz31}, {qa8,qa9,qa10,qa11}, dt, pt, 1, 1, 1;\n"
        "add.s64 dt, w1d, 1152; wgmma.mma_async.sync.aligned.m64n64k16.f16.f16.f16 {qz16,qz17,qz18,qz19,qz20,qz21,qz22,qz23,qz24,qz25,qz26,qz27,qz28,qz29,qz30,qz31}, {qa12,qa13,qa14,qa15}, dt, pt, 1, 1, 1;\n"
        "add.s64 dt, w1d, 1280; wgmma.mma_async.sync.aligned.m64n64k16.f16.f16.f16 {qz16,qz17,qz18,qz19,qz20,qz21,qz22,qz23,qz24,qz25,qz26,qz27,qz28,qz29,qz30,qz31}, {qa16,qa17,qa18,qa19}, dt, pt, 1, 1, 1;\n"
        "add.s64 dt, w1d, 1408; wgmma.mma_async.sync.aligned.m64n64k16.f16.f16.f16 {qz16,qz17,qz18,qz19,qz20,qz21,qz22,qz23,qz24,qz25,qz26,qz27,qz28,qz29,qz30,qz31}, {qa20,qa21,qa22,qa23}, dt, pt, 1, 1, 1;\n"
        "SKIP0:\n"
        "setp.lt.s32 pr, n, 0;\n"
        "@pr bra.uni FIRST;\n"
        "and.b32 tt, n, 1; mbarrier.try_wait.parity.shared::cta.b64 pw, [xbar], tt;\n"
        "@!pw bra.uni SPINX;\n"
        "BACKX:\n"
        "and.b32 ad, %6, 0xffff; add.u32 ad, ad, %4; ld.shared.v4.b32 {v0,v1,v2,v3}, [ad+0];\n"
        "shr.u32 ad, %6, 16; add.u32 ad, ad, %4; ld.shared.v4.b32 {v4,v5,v6,v7}, [ad+0];\n"
        "mov.b32 {xl, xh}, o0; cvt.f32.f16 f0, xl; cvt.f32.f16 f1, xh; cvt.rn.bf16x2.f32 tt, f1, f0; fma.rn.bf16x2 v0, tt, osc, v0;\n"
        "mov.b32 {xl, xh}, o2; cvt.f32.f16 f0, xl; cvt.f32.f16 f1, xh; cvt.rn.bf16x2.f32 tt, f1, f0; fma.rn.bf16x2 v1, tt, osc, v1;\n"
        "mov.b32 {xl, xh}, o4; cvt.f32.f16 f0, xl; cvt.f32.f16 f1, xh; cvt.rn.bf16x2.f32 tt, f1, f0; fma.rn.bf16x2 v2, tt, osc, v2;\n"
        "mov.b32 {xl, xh}, o6; cvt.f32.f16 f0, xl; cvt.f32.f16 f1, xh; cvt.rn.bf16x2.f32 tt, f1, f0; fma.rn.bf16x2 v3, tt, osc, v3;\n"
        "and.b32 ad, %6, 0xffff; add.u32 ad, ad, %4; st.shared.v4.b32 [ad+0], {v0,v1,v2,v3};\n"
        "and.b32 ad, %6, 0xffff; add.u32 ad, ad, %4; ld.shared.v4.b32 {v0,v1,v2,v3}, [ad+64];\n"
        "mov.b32 {xl, xh}, o1; cvt.f32.f16 f0, xl; cvt.f32.f16 f1, xh; cvt.rn.bf16x2.f32 tt, f1, f0; fma.rn.bf16x2 v4, tt, osc, v4;\n"
        "mov.b32 {xl, xh}, o3; cvt.f32.f16 f0, xl; cvt.f32.f16 f1, xh; cvt.rn.bf16x2.f32 tt, f1, f0; fma.rn.bf16x2 v5, tt, osc, v5;\n"
        "mov.b32 {xl, xh}, o5; cvt.f32.f16 f0, xl; cvt.f32.f16 f1, xh; cvt.rn.bf16x2.f32 tt, f1, f0; fma.rn.bf16x2 v6, tt, osc, v6;\n"
        "mov.b32 {xl, xh}, o7; cvt.f32.f16 f0, xl; cvt.f32.f16 f1, xh; cvt.rn.bf16x2.f32 tt, f1, f0; fma.rn.bf16x2 v7, tt, osc, v7;\n"
        "shr.u32 ad, %6, 16; add.u32 ad, ad, %4; st.shared.v4.b32 [ad+0], {v4,v5,v6,v7};\n"
        "shr.u32 ad, %6, 16; add.u32 ad, ad, %4; ld.shared.v4.b32 {v4,v5,v6,v7}, [ad+64];\n"
        "ld.shared.v4.b32 {o0,o1,o2,o3}, [%7+0];\n"
        "ld.shared.v4.b32 {o4,o5,o6,o7}, [%7+64];\n"
        "mov.b32 {xl, xh}, o8; cvt.f32.f16 f0, xl; cvt.f32.f16 f1, xh; cvt.rn.bf16x2.f32 tt, f1, f0; fma.rn.bf16x2 v0, tt, osc, v0;\n"
        "mov.b32 {xl, xh}, o10; cvt.f32.f16 f0, xl; cvt.f32.f16 f1, xh; cvt.rn.bf16x2.f32 tt, f1, f0; fma.rn.bf16x2 v1, tt, osc, v1;\n"
        "mov.b32 {xl, xh}, o12; cvt.f32.f16 f0, xl; cvt.f32.f16 f1, xh; cvt.rn.bf16x2.f32 tt, f1, f0; fma.rn.bf16x2 v2, tt, osc, v2;\n"
        "mov.b32 {xl, xh}, o14; cvt.f32.f16 f0, xl; cvt.f32.f16 f1, xh; cvt.rn.bf16x2.f32 tt, f1, f0; fma.rn.bf16x2 v3, tt, osc, v3;\n"
        "and.b32 ad, %6, 0xffff; add.u32 ad, ad, %4; st.shared.v4.b32 [ad+64], {v0,v1,v2,v3};\n"
        "and.b32 ad, %6, 0xffff; add.u32 ad, ad, %4; ld.shared.v4.b32 {v0,v1,v2,v3}, [ad+128];\n"
        "mov.b32 {xl, xh}, o9; cvt.f32.f16 f0, xl; cvt.f32.f16 f1, xh; cvt.rn.bf16x2.f32 tt, f1, f0; fma.rn.bf16x2 v4, tt, osc, v4;\n"
        "mov.b32 {xl, xh}, o11; cvt.f32.f16 f0, xl; cvt.f32.f16 f1, xh; cvt.rn.bf16x2.f32 tt, f1, f0; fma.rn.bf16x2 v5, tt, osc, v5;\n"
        "mov.b32 {xl, xh}, o13; cvt.f32.f16 f0, xl; cvt.f32.f16 f1, xh; cvt.rn.bf16x2.f32 tt, f1, f0; fma.rn.bf16x2 v6, tt, osc, v6;\n"
        "mov.b32 {xl, xh}, o15; cvt.f32.f16 f0, xl; cvt.f32.f16 f1, xh; cvt.rn.bf16x2.f32 tt, f1, f0; fma.rn.bf16x2 v7, tt, osc, v7;\n"
        "shr.u32 ad, %6, 16; add.u32 ad, ad, %4; st.shared.v4.b32 [ad+64], {v4,v5,v6,v7};\n"
        "shr.u32 ad, %6, 16; add.u32 ad, ad, %4; ld.shared.v4.b32 {v4,v5,v6,v7}, [ad+128];\n"
        "ld.shared.v4.b32 {o8,o9,o10,o11}, [%7+128];\n"
        "ld.shared.v4.b32 {o12,o13,o14,o15}, [%7+192];\n"
        "mov.b32 {xl, xh}, o16; cvt.f32.f16 f0, xl; cvt.f32.f16 f1, xh; cvt.rn.bf16x2.f32 tt, f1, f0; fma.rn.bf16x2 v0, tt, osc, v0;\n"
        "mov.b32 {xl, xh}, o18; cvt.f32.f16 f0, xl; cvt.f32.f16 f1, xh; cvt.rn.bf16x2.f32 tt, f1, f0; fma.rn.bf16x2 v1, tt, osc, v1;\n"
        "mov.b32 {xl, xh}, o20; cvt.f32.f16 f0, xl; cvt.f32.f16 f1, xh; cvt.rn.bf16x2.f32 tt, f1, f0; fma.rn.bf16x2 v2, tt, osc, v2;\n"
        "mov.b32 {xl, xh}, o22; cvt.f32.f16 f0, xl; cvt.f32.f16 f1, xh; cvt.rn.bf16x2.f32 tt, f1, f0; fma.rn.bf16x2 v3, tt, osc, v3;\n"
        "and.b32 ad, %6, 0xffff; add.u32 ad, ad, %4; st.shared.v4.b32 [ad+128], {v0,v1,v2,v3};\n"
        "mov.b32 {xl, xh}, o17; cvt.f32.f16 f0, xl; cvt.f32.f16 f1, xh; cvt.rn.bf16x2.f32 tt, f1, f0; fma.rn.bf16x2 v4, tt, osc, v4;\n"
        "mov.b32 {xl, xh}, o19; cvt.f32.f16 f0, xl; cvt.f32.f16 f1, xh; cvt.rn.bf16x2.f32 tt, f1, f0; fma.rn.bf16x2 v5, tt, osc, v5;\n"
        "mov.b32 {xl, xh}, o21; cvt.f32.f16 f0, xl; cvt.f32.f16 f1, xh; cvt.rn.bf16x2.f32 tt, f1, f0; fma.rn.bf16x2 v6, tt, osc, v6;\n"
        "mov.b32 {xl, xh}, o23; cvt.f32.f16 f0, xl; cvt.f32.f16 f1, xh; cvt.rn.bf16x2.f32 tt, f1, f0; fma.rn.bf16x2 v7, tt, osc, v7;\n"
        "shr.u32 ad, %6, 16; add.u32 ad, ad, %4; st.shared.v4.b32 [ad+128], {v4,v5,v6,v7};\n"
        "ld.shared.v4.b32 {o16,o17,o18,o19}, [%7+256];\n"
        "ld.shared.v4.b32 {o20,o21,o22,o23}, [%7+320];\n"
        "FIRST:\n"
        "@pz bra.uni B7;\n"
        "mov.b32 {xl, xh}, a2; tanh.approx.f16 xr, xl; cvt.u32.u16 lo0, xr; tanh.approx.f16 xr, xh; cvt.u32.u16 hi0, xr; mul.rn.f16x2 a3, qz7, p1; fma.rn.f16x2 p0, qz8, qz8, c; fma.rn.f16x2 g4, qz4, h0, qz4; prmt.b32 h1, lo1, hi1, 0x5410;\n"
        "B7:\n"
        "fence.proxy.async.shared::cta;\n"
        "add.u32 tt, id, 4;\n"
        "@pl bra.uni STORE;\n"
        "bar.arrive tt, 128;\n"
        "STOREB:\n"
        ASM_MARK
        "add.s32 n, n, 1; sub.u32 off, off, %8; setp.lt.s32 pm, n, 7;\n"
        "@pz bra.uni B10;\n"
        "mov.b32 {xl, xh}, a3; tanh.approx.f16 xr, xl; cvt.u32.u16 lo1, xr; tanh.approx.f16 xr, xh; cvt.u32.u16 hi1, xr; mul.rn.f16x2 a0, qz8, p0; fma.rn.f16x2 p1, qz9, qz9, c; fma.rn.f16x2 g5, qz5, h1, qz5; prmt.b32 h0, lo0, hi0, 0x5410;\n"
        "mov.b32 {xl, xh}, a0; tanh.approx.f16 xr, xl; cvt.u32.u16 lo0, xr; tanh.approx.f16 xr, xh; cvt.u32.u16 hi0, xr; mul.rn.f16x2 a1, qz9, p1; fma.rn.f16x2 p0, qz10, qz10, c; fma.rn.f16x2 g6, qz6, h0, qz6; prmt.b32 h1, lo1, hi1, 0x5410;\n"
        "mov.b32 {xl, xh}, a1; tanh.approx.f16 xr, xl; cvt.u32.u16 lo1, xr; tanh.approx.f16 xr, xh; cvt.u32.u16 hi1, xr; mul.rn.f16x2 a2, qz10, p0; fma.rn.f16x2 p1, qz11, qz11, c; fma.rn.f16x2 g7, qz7, h1, qz7; prmt.b32 h0, lo0, hi0, 0x5410;\n"
        "B10:\n"
        "setp.eq.s32 pr, n, 0;\n"
        "@pr bra.uni SPINW0;\n"
        "BACKW0:\n"
        "wgmma.fence.sync.aligned;\n"
        "add.s64 dt, w2d, 0; wgmma.mma_async.sync.aligned.m64n96k16.f16.f16.f16 {o0,o1,o2,o3,o4,o5,o6,o7,o8,o9,o10,o11,o12,o13,o14,o15,o16,o17,o18,o19,o20,o21,o22,o23}, {g0,g1,g2,g3}, dt, pt, 1, 1, 1;\n"
        "add.s64 dt, w2d, 64; wgmma.mma_async.sync.aligned.m64n96k16.f16.f16.f16 {o0,o1,o2,o3,o4,o5,o6,o7,o8,o9,o10,o11,o12,o13,o14,o15,o16,o17,o18,o19,o20,o21,o22,o23}, {g4,g5,g6,g7}, dt, pt, 1, 1, 1;\n"
        "wgmma.commit_group.sync.aligned;\n"
        "@pz bra.uni B14;\n"
        "mov.b32 {xl, xh}, a2; tanh.approx.f16 xr, xl; cvt.u32.u16 lo0, xr; tanh.approx.f16 xr, xh; cvt.u32.u16 hi0, xr; mul.rn.f16x2 a3, qz11, p1; fma.rn.f16x2 p0, qz12, qz12, c; fma.rn.f16x2 g8, qz8, h0, qz8; prmt.b32 h1, lo1, hi1, 0x5410;\n"
        "mov.b32 {xl, xh}, a3; tanh.approx.f16 xr, xl; cvt.u32.u16 lo1, xr; tanh.approx.f16 xr, xh; cvt.u32.u16 hi1, xr; mul.rn.f16x2 a0, qz12, p0; fma.rn.f16x2 p1, qz13, qz13, c; fma.rn.f16x2 g9, qz9, h1, qz9; prmt.b32 h0, lo0, hi0, 0x5410;\n"
        "mov.b32 {xl, xh}, a0; tanh.approx.f16 xr, xl; cvt.u32.u16 lo0, xr; tanh.approx.f16 xr, xh; cvt.u32.u16 hi0, xr; mul.rn.f16x2 a1, qz13, p1; fma.rn.f16x2 p0, qz14, qz14, c; fma.rn.f16x2 g10, qz10, h0, qz10; prmt.b32 h1, lo1, hi1, 0x5410;\n"
        "mov.b32 {xl, xh}, a1; tanh.approx.f16 xr, xl; cvt.u32.u16 lo1, xr; tanh.approx.f16 xr, xh; cvt.u32.u16 hi1, xr; mul.rn.f16x2 a2, qz14, p0; fma.rn.f16x2 p1, qz15, qz15, c; fma.rn.f16x2 g11, qz11, h1, qz11; prmt.b32 h0, lo0, hi0, 0x5410;\n"
        "B14:\n"
        "wgmma.wait_group.sync.aligned 0;\n"
        "mad.lo.u32 tt, n, 8, tbar; mbarrier.try_wait.parity.shared::cta.b64 pw, [tt], tpar;\n"
        "@!pw bra.uni SPINT;\n"
        "BACKT:\n"
        "wgmma.fence.sync.aligned;\n"
        "add.s64 dt, w2d, 128; wgmma.mma_async.sync.aligned.m64n96k16.f16.f16.f16 {o0,o1,o2,o3,o4,o5,o6,o7,o8,o9,o10,o11,o12,o13,o14,o15,o16,o17,o18,o19,o20,o21,o22,o23}, {g8,g9,g10,g11}, dt, pt, 1, 1, 1;\n"
        "wgmma.commit_group.sync.aligned;\n"
        "@pz bra.uni B18;\n"
        "mov.b32 {xl, xh}, a2; tanh.approx.f16 xr, xl; cvt.u32.u16 lo0, xr; tanh.approx.f16 xr, xh; cvt.u32.u16 hi0, xr; mul.rn.f16x2 a3, qz15, p1; fma.rn.f16x2 p0, qz16, qz16, c; fma.rn.f16x2 g12, qz12, h0, qz12; prmt.b32 h1, lo1, hi1, 0x5410;\n"
        "mov.b32 {xl, xh}, a3; tanh.approx.f16 xr, xl; cvt.u32.u16 lo1, xr; tanh.approx.f16 xr, xh; cvt.u32.u16 hi1, xr; mul.rn.f16x2 a0, qz16, p0; fma.rn.f16x2 p1, qz17, qz17, c; fma.rn.f16x2 g13, qz13, h1, qz13; prmt.b32 h0, lo0, hi0, 0x5410;\n"
        "mov.b32 {xl, xh}, a0; tanh.approx.f16 xr, xl; cvt.u32.u16 lo0, xr; tanh.approx.f16 xr, xh; cvt.u32.u16 hi0, xr; mul.rn.f16x2 a1, qz17, p1; fma.rn.f16x2 p0, qz18, qz18, c; fma.rn.f16x2 g14, qz14, h0, qz14; prmt.b32 h1, lo1, hi1, 0x5410;\n"
        "mov.b32 {xl, xh}, a1; tanh.approx.f16 xr, xl; cvt.u32.u16 lo1, xr; tanh.approx.f16 xr, xh; cvt.u32.u16 hi1, xr; mul.rn.f16x2 a2, qz18, p0; fma.rn.f16x2 p1, qz19, qz19, c; fma.rn.f16x2 g15, qz15, h1, qz15; prmt.b32 h0, lo0, hi0, 0x5410;\n"
        "B18:\n"
        "wgmma.fence.sync.aligned;\n"
        "add.s64 dt, w2d, 192; wgmma.mma_async.sync.aligned.m64n96k16.f16.f16.f16 {o0,o1,o2,o3,o4,o5,o6,o7,o8,o9,o10,o11,o12,o13,o14,o15,o16,o17,o18,o19,o20,o21,o22,o23}, {g12,g13,g14,g15}, dt, pt, 1, 1, 1;\n"
        "add.s64 dt, w1d, 1536; wgmma.mma_async.sync.aligned.m64n64k16.f16.f16.f16 {qz0,qz1,qz2,qz3,qz4,qz5,qz6,qz7,qz8,qz9,qz10,qz11,qz12,qz13,qz14,qz15}, {qa0,qa1,qa2,qa3}, dt, pf, 1, 1, 1;\n"
        "add.s64 dt, w1d, 1664; wgmma.mma_async.sync.aligned.m64n64k16.f16.f16.f16 {qz0,qz1,qz2,qz3,qz4,qz5,qz6,qz7,qz8,qz9,qz10,qz11,qz12,qz13,qz14,qz15}, {qa4,qa5,qa6,qa7}, dt, pt, 1, 1, 1;\n"
        "add.s64 dt, w1d, 1792; wgmma.mma_async.sync.aligned.m64n64k16.f16.f16.f16 {qz0,qz1,qz2,qz3,qz4,qz5,qz6,qz7,qz8,qz9,qz10,qz11,qz12,qz13,qz14,qz15}, {qa8,qa9,qa10,qa11}, dt, pt, 1, 1, 1;\n"
        "wgmma.commit_group.sync.aligned;\n"
        "@pl bra.uni YLOAD;\n"
        "YLOADB:\n"
        "@pz bra.uni B22;\n"
        "mov.b32 {xl, xh}, a2; tanh.approx.f16 xr, xl; cvt.u32.u16 lo0, xr; tanh.approx.f16 xr, xh; cvt.u32.u16 hi0, xr; mul.rn.f16x2 a3, qz19, p1; fma.rn.f16x2 p0, qz20, qz20, c; fma.rn.f16x2 g0, qz16, h0, qz16; prmt.b32 h1, lo1, hi1, 0x5410;\n"
        "mov.b32 {xl, xh}, a3; tanh.approx.f16 xr, xl; cvt.u32.u16 lo1, xr; tanh.approx.f16 xr, xh; cvt.u32.u16 hi1, xr; mul.rn.f16x2 a0, qz20, p0; fma.rn.f16x2 p1, qz21, qz21, c; fma.rn.f16x2 g1, qz17, h1, qz17; prmt.b32 h0, lo0, hi0, 0x5410;\n"
        "mov.b32 {xl, xh}, a0; tanh.approx.f16 xr, xl; cvt.u32.u16 lo0, xr; tanh.approx.f16 xr, xh; cvt.u32.u16 hi0, xr; mul.rn.f16x2 a1, qz21, p1; fma.rn.f16x2 p0, qz22, qz22, c; fma.rn.f16x2 g2, qz18, h0, qz18; prmt.b32 h1, lo1, hi1, 0x5410;\n"
        "mov.b32 {xl, xh}, a1; tanh.approx.f16 xr, xl; cvt.u32.u16 lo1, xr; tanh.approx.f16 xr, xh; cvt.u32.u16 hi1, xr; mul.rn.f16x2 a2, qz22, p0; fma.rn.f16x2 p1, qz23, qz23, c; fma.rn.f16x2 g3, qz19, h1, qz19; prmt.b32 h0, lo0, hi0, 0x5410;\n"
        "B22:\n"
        "wgmma.fence.sync.aligned;\n"
        "add.s64 dt, w1d, 1920; wgmma.mma_async.sync.aligned.m64n64k16.f16.f16.f16 {qz0,qz1,qz2,qz3,qz4,qz5,qz6,qz7,qz8,qz9,qz10,qz11,qz12,qz13,qz14,qz15}, {qa12,qa13,qa14,qa15}, dt, pt, 1, 1, 1;\n"
        "add.s64 dt, w1d, 2048; wgmma.mma_async.sync.aligned.m64n64k16.f16.f16.f16 {qz0,qz1,qz2,qz3,qz4,qz5,qz6,qz7,qz8,qz9,qz10,qz11,qz12,qz13,qz14,qz15}, {qa16,qa17,qa18,qa19}, dt, pt, 1, 1, 1;\n"
        "add.s64 dt, w1d, 2176; wgmma.mma_async.sync.aligned.m64n64k16.f16.f16.f16 {qz0,qz1,qz2,qz3,qz4,qz5,qz6,qz7,qz8,qz9,qz10,qz11,qz12,qz13,qz14,qz15}, {qa20,qa21,qa22,qa23}, dt, pt, 1, 1, 1;\n"
        "wgmma.commit_group.sync.aligned;\n"
        "@pz bra.uni B26;\n"
        "mov.b32 {xl, xh}, a2; tanh.approx.f16 xr, xl; cvt.u32.u16 lo0, xr; tanh.approx.f16 xr, xh; cvt.u32.u16 hi0, xr; mul.rn.f16x2 a3, qz23, p1; fma.rn.f16x2 p0, qz24, qz24, c; fma.rn.f16x2 g4, qz20, h0, qz20; prmt.b32 h1, lo1, hi1, 0x5410;\n"
        "mov.b32 {xl, xh}, a3; tanh.approx.f16 xr, xl; cvt.u32.u16 lo1, xr; tanh.approx.f16 xr, xh; cvt.u32.u16 hi1, xr; mul.rn.f16x2 a0, qz24, p0; fma.rn.f16x2 p1, qz25, qz25, c; fma.rn.f16x2 g5, qz21, h1, qz21; prmt.b32 h0, lo0, hi0, 0x5410;\n"
        "mov.b32 {xl, xh}, a0; tanh.approx.f16 xr, xl; cvt.u32.u16 lo0, xr; tanh.approx.f16 xr, xh; cvt.u32.u16 hi0, xr; mul.rn.f16x2 a1, qz25, p1; fma.rn.f16x2 p0, qz26, qz26, c; fma.rn.f16x2 g6, qz22, h0, qz22; prmt.b32 h1, lo1, hi1, 0x5410;\n"
        "mov.b32 {xl, xh}, a1; tanh.approx.f16 xr, xl; cvt.u32.u16 lo1, xr; tanh.approx.f16 xr, xh; cvt.u32.u16 hi1, xr; mul.rn.f16x2 a2, qz26, p0; fma.rn.f16x2 p1, qz27, qz27, c; fma.rn.f16x2 g7, qz23, h1, qz23; prmt.b32 h0, lo0, hi0, 0x5410;\n"
        "B26:\n"
        "wgmma.wait_group.sync.aligned 2;\n"
        "wgmma.fence.sync.aligned;\n"
        "add.s64 dt, w2d, 256; wgmma.mma_async.sync.aligned.m64n96k16.f16.f16.f16 {o0,o1,o2,o3,o4,o5,o6,o7,o8,o9,o10,o11,o12,o13,o14,o15,o16,o17,o18,o19,o20,o21,o22,o23}, {g0,g1,g2,g3}, dt, pt, 1, 1, 1;\n"
        "add.s64 dt, w2d, 320; wgmma.mma_async.sync.aligned.m64n96k16.f16.f16.f16 {o0,o1,o2,o3,o4,o5,o6,o7,o8,o9,o10,o11,o12,o13,o14,o15,o16,o17,o18,o19,o20,o21,o22,o23}, {g4,g5,g6,g7}, dt, pt, 1, 1, 1;\n"
        "wgmma.commit_group.sync.aligned;\n"
        "@pz bra.uni B30;\n"
        "mov.b32 {xl, xh}, a2; tanh.approx.f16 xr, xl; cvt.u32.u16 lo0, xr; tanh.approx.f16 xr, xh; cvt.u32.u16 hi0, xr; mul.rn.f16x2 a3, qz27, p1; fma.rn.f16x2 p0, qz28, qz28, c; fma.rn.f16x2 g8, qz24, h0, qz24; prmt.b32 h1, lo1, hi1, 0x5410;\n"
        "mov.b32 {xl, xh}, a3; tanh.approx.f16 xr, xl; cvt.u32.u16 lo1, xr; tanh.approx.f16 xr, xh; cvt.u32.u16 hi1, xr; mul.rn.f16x2 a0, qz28, p0; fma.rn.f16x2 p1, qz29, qz29, c; fma.rn.f16x2 g9, qz25, h1, qz25; prmt.b32 h0, lo0, hi0, 0x5410;\n"
        "mov.b32 {xl, xh}, a0; tanh.approx.f16 xr, xl; cvt.u32.u16 lo0, xr; tanh.approx.f16 xr, xh; cvt.u32.u16 hi0, xr; mul.rn.f16x2 a1, qz29, p1; fma.rn.f16x2 p0, qz30, qz30, c; fma.rn.f16x2 g10, qz26, h0, qz26; prmt.b32 h1, lo1, hi1, 0x5410;\n"
        "mov.b32 {xl, xh}, a1; tanh.approx.f16 xr, xl; cvt.u32.u16 lo1, xr; tanh.approx.f16 xr, xh; cvt.u32.u16 hi1, xr; mul.rn.f16x2 a2, qz30, p0; fma.rn.f16x2 p1, qz31, qz31, c; fma.rn.f16x2 g11, qz27, h1, qz27; prmt.b32 h0, lo0, hi0, 0x5410;\n"
        "B30:\n"
        "wgmma.wait_group.sync.aligned 1;\n"
        "wgmma.fence.sync.aligned;\n"
        "add.s64 dt, w2d, 384; wgmma.mma_async.sync.aligned.m64n96k16.f16.f16.f16 {o0,o1,o2,o3,o4,o5,o6,o7,o8,o9,o10,o11,o12,o13,o14,o15,o16,o17,o18,o19,o20,o21,o22,o23}, {g8,g9,g10,g11}, dt, pt, 1, 1, 1;\n"
        "wgmma.commit_group.sync.aligned;\n"
        "@pz bra.uni B34;\n"
        "mov.b32 {xl, xh}, a2; tanh.approx.f16 xr, xl; cvt.u32.u16 lo0, xr; tanh.approx.f16 xr, xh; cvt.u32.u16 hi0, xr; mul.rn.f16x2 a3, qz31, p1; fma.rn.f16x2 p0, qz0, qz0, c; fma.rn.f16x2 g12, qz28, h0, qz28; prmt.b32 h1, lo1, hi1, 0x5410;\n"
        "mov.b32 {xl, xh}, a3; tanh.approx.f16 xr, xl; cvt.u32.u16 lo1, xr; tanh.approx.f16 xr, xh; cvt.u32.u16 hi1, xr; mul.rn.f16x2 a0, qz0, p0; fma.rn.f16x2 p1, qz1, qz1, c; fma.rn.f16x2 g13, qz29, h1, qz29; prmt.b32 h0, lo0, hi0, 0x5410;\n"
        "mov.b32 {xl, xh}, a0; tanh.approx.f16 xr, xl; cvt.u32.u16 lo0, xr; tanh.approx.f16 xr, xh; cvt.u32.u16 hi0, xr; mul.rn.f16x2 a1, qz1, p1; fma.rn.f16x2 p0, qz2, qz2, c; fma.rn.f16x2 g14, qz30, h0, qz30; prmt.b32 h1, lo1, hi1, 0x5410;\n"
        "mov.b32 {xl, xh}, a1; tanh.approx.f16 xr, xl; cvt.u32.u16 lo1, xr; tanh.approx.f16 xr, xh; cvt.u32.u16 hi1, xr; mul.rn.f16x2 a2, qz2, p0; fma.rn.f16x2 p1, qz3, qz3, c; fma.rn.f16x2 g15, qz31, h1, qz31; prmt.b32 h0, lo0, hi0, 0x5410;\n"
        "B34:\n"
        "wgmma.wait_group.sync.aligned 1;\n"
        "wgmma.fence.sync.aligned;\n"
        "add.s64 dt, w2d, 448; wgmma.mma_async.sync.aligned.m64n96k16.f16.f16.f16 {o0,o1,o2,o3,o4,o5,o6,o7,o8,o9,o10,o11,o12,o13,o14,o15,o16,o17,o18,o19,o20,o21,o22,o23}, {g12,g13,g14,g15}, dt, pt, 1, 1, 1;\n"
        "add.s64 dt, w1d, 2304; wgmma.mma_async.sync.aligned.m64n64k16.f16.f16.f16 {qz16,qz17,qz18,qz19,qz20,qz21,qz22,qz23,qz24,qz25,qz26,qz27,qz28,qz29,qz30,qz31}, {qa0,qa1,qa2,qa3}, dt, pf, 1, 1, 1;\n"
        "add.s64 dt, w1d, 2432; wgmma.mma_async.sync.aligned.m64n64k16.f16.f16.f16 {qz16,qz17,qz18,qz19,qz20,qz21,qz22,qz23,qz24,qz25,qz26,qz27,qz28,qz29,qz30,qz31}, {qa4,qa5,qa6,qa7}, dt, pt, 1, 1, 1;\n"
        "add.s64 dt, w1d, 2560; wgmma.mma_async.sync.aligned.m64n64k16.f16.f16.f16 {qz16,qz17,qz18,qz19,qz20,qz21,qz22,qz23,qz24,qz25,qz26,qz27,qz28,qz29,qz30,qz31}, {qa8,qa9,qa10,qa11}, dt, pt, 1, 1, 1;\n"
        "wgmma.commit_group.sync.aligned;\n"
        "@pz bra.uni B38;\n"
        "mov.b32 {xl, xh}, a2; tanh.approx.f16 xr, xl; cvt.u32.u16 lo0, xr; tanh.approx.f16 xr, xh; cvt.u32.u16 hi0, xr; mul.rn.f16x2 a3, qz3, p1; fma.rn.f16x2 p0, qz4, qz4, c; fma.rn.f16x2 g0, qz0, h0, qz0; prmt.b32 h1, lo1, hi1, 0x5410;\n"
        "mov.b32 {xl, xh}, a3; tanh.approx.f16 xr, xl; cvt.u32.u16 lo1, xr; tanh.approx.f16 xr, xh; cvt.u32.u16 hi1, xr; mul.rn.f16x2 a0, qz4, p0; fma.rn.f16x2 p1, qz5, qz5, c; fma.rn.f16x2 g1, qz1, h1, qz1; prmt.b32 h0, lo0, hi0, 0x5410;\n"
        "mov.b32 {xl, xh}, a0; tanh.approx.f16 xr, xl; cvt.u32.u16 lo0, xr; tanh.approx.f16 xr, xh; cvt.u32.u16 hi0, xr; mul.rn.f16x2 a1, qz5, p1; fma.rn.f16x2 p0, qz6, qz6, c; fma.rn.f16x2 g2, qz2, h0, qz2; prmt.b32 h1, lo1, hi1, 0x5410;\n"
        "mov.b32 {xl, xh}, a1; tanh.approx.f16 xr, xl; cvt.u32.u16 lo1, xr; tanh.approx.f16 xr, xh; cvt.u32.u16 hi1, xr; mul.rn.f16x2 a2, qz6, p0; fma.rn.f16x2 p1, qz7, qz7, c; fma.rn.f16x2 g3, qz3, h1, qz3; prmt.b32 h0, lo0, hi0, 0x5410;\n"
        "B38:\n"
        "wgmma.fence.sync.aligned;\n"
        "add.s64 dt, w1d, 2688; wgmma.mma_async.sync.aligned.m64n64k16.f16.f16.f16 {qz16,qz17,qz18,qz19,qz20,qz21,qz22,qz23,qz24,qz25,qz26,qz27,qz28,qz29,qz30,qz31}, {qa12,qa13,qa14,qa15}, dt, pt, 1, 1, 1;\n"
        "add.s64 dt, w1d, 2816; wgmma.mma_async.sync.aligned.m64n64k16.f16.f16.f16 {qz16,qz17,qz18,qz19,qz20,qz21,qz22,qz23,qz24,qz25,qz26,qz27,qz28,qz29,qz30,qz31}, {qa16,qa17,qa18,qa19}, dt, pt, 1, 1, 1;\n"
        "add.s64 dt, w1d, 2944; wgmma.mma_async.sync.aligned.m64n64k16.f16.f16.f16 {qz16,qz17,qz18,qz19,qz20,qz21,qz22,qz23,qz24,qz25,qz26,qz27,qz28,qz29,qz30,qz31}, {qa20,qa21,qa22,qa23}, dt, pt, 1, 1, 1;\n"
        "wgmma.commit_group.sync.aligned;\n"
        "@pz bra.uni B42;\n"
        "mov.b32 {xl, xh}, a2; tanh.approx.f16 xr, xl; cvt.u32.u16 lo0, xr; tanh.approx.f16 xr, xh; cvt.u32.u16 hi0, xr; mul.rn.f16x2 a3, qz7, p1; fma.rn.f16x2 p0, qz8, qz8, c; fma.rn.f16x2 g4, qz4, h0, qz4; prmt.b32 h1, lo1, hi1, 0x5410;\n"
        "mov.b32 {xl, xh}, a3; tanh.approx.f16 xr, xl; cvt.u32.u16 lo1, xr; tanh.approx.f16 xr, xh; cvt.u32.u16 hi1, xr; mul.rn.f16x2 a0, qz8, p0; fma.rn.f16x2 p1, qz9, qz9, c; fma.rn.f16x2 g5, qz5, h1, qz5; prmt.b32 h0, lo0, hi0, 0x5410;\n"
        "mov.b32 {xl, xh}, a0; tanh.approx.f16 xr, xl; cvt.u32.u16 lo0, xr; tanh.approx.f16 xr, xh; cvt.u32.u16 hi0, xr; mul.rn.f16x2 a1, qz9, p1; fma.rn.f16x2 p0, qz10, qz10, c; fma.rn.f16x2 g6, qz6, h0, qz6; prmt.b32 h1, lo1, hi1, 0x5410;\n"
        "mov.b32 {xl, xh}, a1; tanh.approx.f16 xr, xl; cvt.u32.u16 lo1, xr; tanh.approx.f16 xr, xh; cvt.u32.u16 hi1, xr; mul.rn.f16x2 a2, qz10, p0; fma.rn.f16x2 p1, qz11, qz11, c; fma.rn.f16x2 g7, qz7, h1, qz7; prmt.b32 h0, lo0, hi0, 0x5410;\n"
        "B42:\n"
        "wgmma.wait_group.sync.aligned 2;\n"
        "setp.eq.s32 pr, n, 0;\n"
        "@pr bra.uni SPINW1;\n"
        "BACKW1:\n"
        "wgmma.fence.sync.aligned;\n"
        "add.s64 dt, w2d, 512; wgmma.mma_async.sync.aligned.m64n96k16.f16.f16.f16 {o0,o1,o2,o3,o4,o5,o6,o7,o8,o9,o10,o11,o12,o13,o14,o15,o16,o17,o18,o19,o20,o21,o22,o23}, {g0,g1,g2,g3}, dt, pt, 1, 1, 1;\n"
        "add.s64 dt, w2d, 576; wgmma.mma_async.sync.aligned.m64n96k16.f16.f16.f16 {o0,o1,o2,o3,o4,o5,o6,o7,o8,o9,o10,o11,o12,o13,o14,o15,o16,o17,o18,o19,o20,o21,o22,o23}, {g4,g5,g6,g7}, dt, pt, 1, 1, 1;\n"
        "wgmma.commit_group.sync.aligned;\n"
        "mad.lo.u32 tt, n, 8, tbar;\n"
        "@pn mbarrier.arrive.shared::cta.b64 _, [tt+64];\n"
        "@pz bra.uni B46;\n"
        "mov.b32 {xl, xh}, a2; tanh.approx.f16 xr, xl; cvt.u32.u16 lo0, xr; tanh.approx.f16 xr, xh; cvt.u32.u16 hi0, xr; mul.rn.f16x2 a3, qz11, p1; fma.rn.f16x2 p0, qz12, qz12, c; fma.rn.f16x2 g8, qz8, h0, qz8; prmt.b32 h1, lo1, hi1, 0x5410;\n"
        "mov.b32 {xl, xh}, a3; tanh.approx.f16 xr, xl; cvt.u32.u16 lo1, xr; tanh.approx.f16 xr, xh; cvt.u32.u16 hi1, xr; mul.rn.f16x2 a0, qz12, p0; fma.rn.f16x2 p1, qz13, qz13, c; fma.rn.f16x2 g9, qz9, h1, qz9; prmt.b32 h0, lo0, hi0, 0x5410;\n"
        "mov.b32 {xl, xh}, a0; tanh.approx.f16 xr, xl; cvt.u32.u16 lo0, xr; tanh.approx.f16 xr, xh; cvt.u32.u16 hi0, xr; mul.rn.f16x2 a1, qz13, p1; fma.rn.f16x2 p0, qz14, qz14, c; fma.rn.f16x2 g10, qz10, h0, qz10; prmt.b32 h1, lo1, hi1, 0x5410;\n"
        "mov.b32 {xl, xh}, a1; tanh.approx.f16 xr, xl; cvt.u32.u16 lo1, xr; tanh.approx.f16 xr, xh; cvt.u32.u16 hi1, xr; mul.rn.f16x2 a2, qz14, p0; fma.rn.f16x2 p1, qz15, qz15, c; fma.rn.f16x2 g11, qz11, h1, qz11; prmt.b32 h0, lo0, hi0, 0x5410;\n"
        "B46:\n"
        "wgmma.wait_group.sync.aligned 1;\n"
        "wgmma.fence.sync.aligned;\n"
        "add.s64 dt, w2d, 640; wgmma.mma_async.sync.aligned.m64n96k16.f16.f16.f16 {o0,o1,o2,o3,o4,o5,o6,o7,o8,o9,o10,o11,o12,o13,o14,o15,o16,o17,o18,o19,o20,o21,o22,o23}, {g8,g9,g10,g11}, dt, pt, 1, 1, 1;\n"
        "wgmma.commit_group.sync.aligned;\n"
        "@pz bra.uni B50;\n"
        "mov.b32 {xl, xh}, a2; tanh.approx.f16 xr, xl; cvt.u32.u16 lo0, xr; tanh.approx.f16 xr, xh; cvt.u32.u16 hi0, xr; mul.rn.f16x2 a3, qz15, p1; fma.rn.f16x2 p0, qz16, qz16, c; fma.rn.f16x2 g12, qz12, h0, qz12; prmt.b32 h1, lo1, hi1, 0x5410;\n"
        "mov.b32 {xl, xh}, a3; tanh.approx.f16 xr, xl; cvt.u32.u16 lo1, xr; tanh.approx.f16 xr, xh; cvt.u32.u16 hi1, xr; mul.rn.f16x2 a0, qz16, p0; fma.rn.f16x2 p1, qz17, qz17, c; fma.rn.f16x2 g13, qz13, h1, qz13; prmt.b32 h0, lo0, hi0, 0x5410;\n"
        "mov.b32 {xl, xh}, a0; tanh.approx.f16 xr, xl; cvt.u32.u16 lo0, xr; tanh.approx.f16 xr, xh; cvt.u32.u16 hi0, xr; mul.rn.f16x2 a1, qz17, p1; fma.rn.f16x2 p0, qz18, qz18, c; fma.rn.f16x2 g14, qz14, h0, qz14; prmt.b32 h1, lo1, hi1, 0x5410;\n"
        "mov.b32 {xl, xh}, a1; tanh.approx.f16 xr, xl; cvt.u32.u16 lo1, xr; tanh.approx.f16 xr, xh; cvt.u32.u16 hi1, xr; mul.rn.f16x2 a2, qz18, p0; fma.rn.f16x2 p1, qz19, qz19, c; fma.rn.f16x2 g15, qz15, h1, qz15; prmt.b32 h0, lo0, hi0, 0x5410;\n"
        "B50:\n"
        "wgmma.wait_group.sync.aligned 1;\n"
        "wgmma.fence.sync.aligned;\n"
        "add.s64 dt, w2d, 704; wgmma.mma_async.sync.aligned.m64n96k16.f16.f16.f16 {o0,o1,o2,o3,o4,o5,o6,o7,o8,o9,o10,o11,o12,o13,o14,o15,o16,o17,o18,o19,o20,o21,o22,o23}, {g12,g13,g14,g15}, dt, pt, 1, 1, 1;\n"
        "add.s64 dt, w1d, 3072; wgmma.mma_async.sync.aligned.m64n64k16.f16.f16.f16 {qz0,qz1,qz2,qz3,qz4,qz5,qz6,qz7,qz8,qz9,qz10,qz11,qz12,qz13,qz14,qz15}, {qa0,qa1,qa2,qa3}, dt, pf, 1, 1, 1;\n"
        "add.s64 dt, w1d, 3200; wgmma.mma_async.sync.aligned.m64n64k16.f16.f16.f16 {qz0,qz1,qz2,qz3,qz4,qz5,qz6,qz7,qz8,qz9,qz10,qz11,qz12,qz13,qz14,qz15}, {qa4,qa5,qa6,qa7}, dt, pt, 1, 1, 1;\n"
        "add.s64 dt, w1d, 3328; wgmma.mma_async.sync.aligned.m64n64k16.f16.f16.f16 {qz0,qz1,qz2,qz3,qz4,qz5,qz6,qz7,qz8,qz9,qz10,qz11,qz12,qz13,qz14,qz15}, {qa8,qa9,qa10,qa11}, dt, pt, 1, 1, 1;\n"
        "wgmma.commit_group.sync.aligned;\n"
        "@pz bra.uni B54;\n"
        "mov.b32 {xl, xh}, a2; tanh.approx.f16 xr, xl; cvt.u32.u16 lo0, xr; tanh.approx.f16 xr, xh; cvt.u32.u16 hi0, xr; mul.rn.f16x2 a3, qz19, p1; fma.rn.f16x2 p0, qz20, qz20, c; fma.rn.f16x2 g0, qz16, h0, qz16; prmt.b32 h1, lo1, hi1, 0x5410;\n"
        "mov.b32 {xl, xh}, a3; tanh.approx.f16 xr, xl; cvt.u32.u16 lo1, xr; tanh.approx.f16 xr, xh; cvt.u32.u16 hi1, xr; mul.rn.f16x2 a0, qz20, p0; fma.rn.f16x2 p1, qz21, qz21, c; fma.rn.f16x2 g1, qz17, h1, qz17; prmt.b32 h0, lo0, hi0, 0x5410;\n"
        "mov.b32 {xl, xh}, a0; tanh.approx.f16 xr, xl; cvt.u32.u16 lo0, xr; tanh.approx.f16 xr, xh; cvt.u32.u16 hi0, xr; mul.rn.f16x2 a1, qz21, p1; fma.rn.f16x2 p0, qz22, qz22, c; fma.rn.f16x2 g2, qz18, h0, qz18; prmt.b32 h1, lo1, hi1, 0x5410;\n"
        "mov.b32 {xl, xh}, a1; tanh.approx.f16 xr, xl; cvt.u32.u16 lo1, xr; tanh.approx.f16 xr, xh; cvt.u32.u16 hi1, xr; mul.rn.f16x2 a2, qz22, p0; fma.rn.f16x2 p1, qz23, qz23, c; fma.rn.f16x2 g3, qz19, h1, qz19; prmt.b32 h0, lo0, hi0, 0x5410;\n"
        "B54:\n"
        "wgmma.fence.sync.aligned;\n"
        "add.s64 dt, w1d, 3456; wgmma.mma_async.sync.aligned.m64n64k16.f16.f16.f16 {qz0,qz1,qz2,qz3,qz4,qz5,qz6,qz7,qz8,qz9,qz10,qz11,qz12,qz13,qz14,qz15}, {qa12,qa13,qa14,qa15}, dt, pt, 1, 1, 1;\n"
        "add.s64 dt, w1d, 3584; wgmma.mma_async.sync.aligned.m64n64k16.f16.f16.f16 {qz0,qz1,qz2,qz3,qz4,qz5,qz6,qz7,qz8,qz9,qz10,qz11,qz12,qz13,qz14,qz15}, {qa16,qa17,qa18,qa19}, dt, pt, 1, 1, 1;\n"
        "add.s64 dt, w1d, 3712; wgmma.mma_async.sync.aligned.m64n64k16.f16.f16.f16 {qz0,qz1,qz2,qz3,qz4,qz5,qz6,qz7,qz8,qz9,qz10,qz11,qz12,qz13,qz14,qz15}, {qa20,qa21,qa22,qa23}, dt, pt, 1, 1, 1;\n"
        "wgmma.commit_group.sync.aligned;\n"
        "@pz bra.uni B58;\n"
        "mov.b32 {xl, xh}, a2; tanh.approx.f16 xr, xl; cvt.u32.u16 lo0, xr; tanh.approx.f16 xr, xh; cvt.u32.u16 hi0, xr; mul.rn.f16x2 a3, qz23, p1; fma.rn.f16x2 p0, qz24, qz24, c; fma.rn.f16x2 g4, qz20, h0, qz20; prmt.b32 h1, lo1, hi1, 0x5410;\n"
        "mov.b32 {xl, xh}, a3; tanh.approx.f16 xr, xl; cvt.u32.u16 lo1, xr; tanh.approx.f16 xr, xh; cvt.u32.u16 hi1, xr; mul.rn.f16x2 a0, qz24, p0; fma.rn.f16x2 p1, qz25, qz25, c; fma.rn.f16x2 g5, qz21, h1, qz21; prmt.b32 h0, lo0, hi0, 0x5410;\n"
        "mov.b32 {xl, xh}, a0; tanh.approx.f16 xr, xl; cvt.u32.u16 lo0, xr; tanh.approx.f16 xr, xh; cvt.u32.u16 hi0, xr; mul.rn.f16x2 a1, qz25, p1; fma.rn.f16x2 p0, qz26, qz26, c; fma.rn.f16x2 g6, qz22, h0, qz22; prmt.b32 h1, lo1, hi1, 0x5410;\n"
        "mov.b32 {xl, xh}, a1; tanh.approx.f16 xr, xl; cvt.u32.u16 lo1, xr; tanh.approx.f16 xr, xh; cvt.u32.u16 hi1, xr; mul.rn.f16x2 a2, qz26, p0; fma.rn.f16x2 p1, qz27, qz27, c; fma.rn.f16x2 g7, qz23, h1, qz23; prmt.b32 h0, lo0, hi0, 0x5410;\n"
        "B58:\n"
        "wgmma.wait_group.sync.aligned 2;\n"
        "wgmma.fence.sync.aligned;\n"
        "add.s64 dt, w2d, 768; wgmma.mma_async.sync.aligned.m64n96k16.f16.f16.f16 {o0,o1,o2,o3,o4,o5,o6,o7,o8,o9,o10,o11,o12,o13,o14,o15,o16,o17,o18,o19,o20,o21,o22,o23}, {g0,g1,g2,g3}, dt, pt, 1, 1, 1;\n"
        "add.s64 dt, w2d, 832; wgmma.mma_async.sync.aligned.m64n96k16.f16.f16.f16 {o0,o1,o2,o3,o4,o5,o6,o7,o8,o9,o10,o11,o12,o13,o14,o15,o16,o17,o18,o19,o20,o21,o22,o23}, {g4,g5,g6,g7}, dt, pt, 1, 1, 1;\n"
        "wgmma.commit_group.sync.aligned;\n"
        "@pz bra.uni B62;\n"
        "mov.b32 {xl, xh}, a2; tanh.approx.f16 xr, xl; cvt.u32.u16 lo0, xr; tanh.approx.f16 xr, xh; cvt.u32.u16 hi0, xr; mul.rn.f16x2 a3, qz27, p1; fma.rn.f16x2 p0, qz28, qz28, c; fma.rn.f16x2 g8, qz24, h0, qz24; prmt.b32 h1, lo1, hi1, 0x5410;\n"
        "mov.b32 {xl, xh}, a3; tanh.approx.f16 xr, xl; cvt.u32.u16 lo1, xr; tanh.approx.f16 xr, xh; cvt.u32.u16 hi1, xr; mul.rn.f16x2 a0, qz28, p0; fma.rn.f16x2 p1, qz29, qz29, c; fma.rn.f16x2 g9, qz25, h1, qz25; prmt.b32 h0, lo0, hi0, 0x5410;\n"
        "mov.b32 {xl, xh}, a0; tanh.approx.f16 xr, xl; cvt.u32.u16 lo0, xr; tanh.approx.f16 xr, xh; cvt.u32.u16 hi0, xr; mul.rn.f16x2 a1, qz29, p1; fma.rn.f16x2 p0, qz30, qz30, c; fma.rn.f16x2 g10, qz26, h0, qz26; prmt.b32 h1, lo1, hi1, 0x5410;\n"
        "mov.b32 {xl, xh}, a1; tanh.approx.f16 xr, xl; cvt.u32.u16 lo1, xr; tanh.approx.f16 xr, xh; cvt.u32.u16 hi1, xr; mul.rn.f16x2 a2, qz30, p0; fma.rn.f16x2 p1, qz31, qz31, c; fma.rn.f16x2 g11, qz27, h1, qz27; prmt.b32 h0, lo0, hi0, 0x5410;\n"
        "B62:\n"
        "wgmma.wait_group.sync.aligned 1;\n"
        "wgmma.fence.sync.aligned;\n"
        "add.s64 dt, w2d, 896; wgmma.mma_async.sync.aligned.m64n96k16.f16.f16.f16 {o0,o1,o2,o3,o4,o5,o6,o7,o8,o9,o10,o11,o12,o13,o14,o15,o16,o17,o18,o19,o20,o21,o22,o23}, {g8,g9,g10,g11}, dt, pt, 1, 1, 1;\n"
        "wgmma.commit_group.sync.aligned;\n"
        "@pz bra.uni B66;\n"
        "mov.b32 {xl, xh}, a2; tanh.approx.f16 xr, xl; cvt.u32.u16 lo0, xr; tanh.approx.f16 xr, xh; cvt.u32.u16 hi0, xr; mul.rn.f16x2 a3, qz31, p1; fma.rn.f16x2 p0, qz0, qz0, c; fma.rn.f16x2 g12, qz28, h0, qz28; prmt.b32 h1, lo1, hi1, 0x5410;\n"
        "mov.b32 {xl, xh}, a3; tanh.approx.f16 xr, xl; cvt.u32.u16 lo1, xr; tanh.approx.f16 xr, xh; cvt.u32.u16 hi1, xr; mul.rn.f16x2 a0, qz0, p0; fma.rn.f16x2 p1, qz1, qz1, c; fma.rn.f16x2 g13, qz29, h1, qz29; prmt.b32 h0, lo0, hi0, 0x5410;\n"
        "mov.b32 {xl, xh}, a0; tanh.approx.f16 xr, xl; cvt.u32.u16 lo0, xr; tanh.approx.f16 xr, xh; cvt.u32.u16 hi0, xr; mul.rn.f16x2 a1, qz1, p1; fma.rn.f16x2 p0, qz2, qz2, c; fma.rn.f16x2 g14, qz30, h0, qz30; prmt.b32 h1, lo1, hi1, 0x5410;\n"
        "mov.b32 {xl, xh}, a1; tanh.approx.f16 xr, xl; cvt.u32.u16 lo1, xr; tanh.approx.f16 xr, xh; cvt.u32.u16 hi1, xr; mul.rn.f16x2 a2, qz2, p0; fma.rn.f16x2 p1, qz3, qz3, c; fma.rn.f16x2 g15, qz31, h1, qz31; prmt.b32 h0, lo0, hi0, 0x5410;\n"
        "B66:\n"
        "wgmma.wait_group.sync.aligned 1;\n"
        "wgmma.fence.sync.aligned;\n"
        "add.s64 dt, w2d, 960; wgmma.mma_async.sync.aligned.m64n96k16.f16.f16.f16 {o0,o1,o2,o3,o4,o5,o6,o7,o8,o9,o10,o11,o12,o13,o14,o15,o16,o17,o18,o19,o20,o21,o22,o23}, {g12,g13,g14,g15}, dt, pt, 1, 1, 1;\n"
        "add.s64 dt, w1d, 3840; wgmma.mma_async.sync.aligned.m64n64k16.f16.f16.f16 {qz16,qz17,qz18,qz19,qz20,qz21,qz22,qz23,qz24,qz25,qz26,qz27,qz28,qz29,qz30,qz31}, {qa0,qa1,qa2,qa3}, dt, pf, 1, 1, 1;\n"
        "add.s64 dt, w1d, 3968; wgmma.mma_async.sync.aligned.m64n64k16.f16.f16.f16 {qz16,qz17,qz18,qz19,qz20,qz21,qz22,qz23,qz24,qz25,qz26,qz27,qz28,qz29,qz30,qz31}, {qa4,qa5,qa6,qa7}, dt, pt, 1, 1, 1;\n"
        "add.s64 dt, w1d, 4096; wgmma.mma_async.sync.aligned.m64n64k16.f16.f16.f16 {qz16,qz17,qz18,qz19,qz20,qz21,qz22,qz23,qz24,qz25,qz26,qz27,qz28,qz29,qz30,qz31}, {qa8,qa9,qa10,qa11}, dt, pt, 1, 1, 1;\n"
        "wgmma.commit_group.sync.aligned;\n"
        "@pz bra.uni B70;\n"
        "mov.b32 {xl, xh}, a2; tanh.approx.f16 xr, xl; cvt.u32.u16 lo0, xr; tanh.approx.f16 xr, xh; cvt.u32.u16 hi0, xr; mul.rn.f16x2 a3, qz3, p1; fma.rn.f16x2 p0, qz4, qz4, c; fma.rn.f16x2 g0, qz0, h0, qz0; prmt.b32 h1, lo1, hi1, 0x5410;\n"
        "mov.b32 {xl, xh}, a3; tanh.approx.f16 xr, xl; cvt.u32.u16 lo1, xr; tanh.approx.f16 xr, xh; cvt.u32.u16 hi1, xr; mul.rn.f16x2 a0, qz4, p0; fma.rn.f16x2 p1, qz5, qz5, c; fma.rn.f16x2 g1, qz1, h1, qz1; prmt.b32 h0, lo0, hi0, 0x5410;\n"
        "mov.b32 {xl, xh}, a0; tanh.approx.f16 xr, xl; cvt.u32.u16 lo0, xr; tanh.approx.f16 xr, xh; cvt.u32.u16 hi0, xr; mul.rn.f16x2 a1, qz5, p1; fma.rn.f16x2 p0, qz6, qz6, c; fma.rn.f16x2 g2, qz2, h0, qz2; prmt.b32 h1, lo1, hi1, 0x5410;\n"
        "mov.b32 {xl, xh}, a1; tanh.approx.f16 xr, xl; cvt.u32.u16 lo1, xr; tanh.approx.f16 xr, xh; cvt.u32.u16 hi1, xr; mul.rn.f16x2 a2, qz6, p0; fma.rn.f16x2 p1, qz7, qz7, c; fma.rn.f16x2 g3, qz3, h1, qz3; prmt.b32 h0, lo0, hi0, 0x5410;\n"
        "B70:\n"
        "wgmma.fence.sync.aligned;\n"
        "add.s64 dt, w1d, 4224; wgmma.mma_async.sync.aligned.m64n64k16.f16.f16.f16 {qz16,qz17,qz18,qz19,qz20,qz21,qz22,qz23,qz24,qz25,qz26,qz27,qz28,qz29,qz30,qz31}, {qa12,qa13,qa14,qa15}, dt, pt, 1, 1, 1;\n"
        "add.s64 dt, w1d, 4352; wgmma.mma_async.sync.aligned.m64n64k16.f16.f16.f16 {qz16,qz17,qz18,qz19,qz20,qz21,qz22,qz23,qz24,qz25,qz26,qz27,qz28,qz29,qz30,qz31}, {qa16,qa17,qa18,qa19}, dt, pt, 1, 1, 1;\n"
        "add.s64 dt, w1d, 4480; wgmma.mma_async.sync.aligned.m64n64k16.f16.f16.f16 {qz16,qz17,qz18,qz19,qz20,qz21,qz22,qz23,qz24,qz25,qz26,qz27,qz28,qz29,qz30,qz31}, {qa20,qa21,qa22,qa23}, dt, pt, 1, 1, 1;\n"
        "wgmma.commit_group.sync.aligned;\n"
        "@pz bra.uni B74;\n"
        "mov.b32 {xl, xh}, a2; tanh.approx.f16 xr, xl; cvt.u32.u16 lo0, xr; tanh.approx.f16 xr, xh; cvt.u32.u16 hi0, xr; mul.rn.f16x2 a3, qz7, p1; fma.rn.f16x2 p0, qz8, qz8, c; fma.rn.f16x2 g4, qz4, h0, qz4; prmt.b32 h1, lo1, hi1, 0x5410;\n"
        "mov.b32 {xl, xh}, a3; tanh.approx.f16 xr, xl; cvt.u32.u16 lo1, xr; tanh.approx.f16 xr, xh; cvt.u32.u16 hi1, xr; mul.rn.f16x2 a0, qz8, p0; fma.rn.f16x2 p1, qz9, qz9, c; fma.rn.f16x2 g5, qz5, h1, qz5; prmt.b32 h0, lo0, hi0, 0x5410;\n"
        "mov.b32 {xl, xh}, a0; tanh.approx.f16 xr, xl; cvt.u32.u16 lo0, xr; tanh.approx.f16 xr, xh; cvt.u32.u16 hi0, xr; mul.rn.f16x2 a1, qz9, p1; fma.rn.f16x2 p0, qz10, qz10, c; fma.rn.f16x2 g6, qz6, h0, qz6; prmt.b32 h1, lo1, hi1, 0x5410;\n"
        "mov.b32 {xl, xh}, a1; tanh.approx.f16 xr, xl; cvt.u32.u16 lo1, xr; tanh.approx.f16 xr, xh; cvt.u32.u16 hi1, xr; mul.rn.f16x2 a2, qz10, p0; fma.rn.f16x2 p1, qz11, qz11, c; fma.rn.f16x2 g7, qz7, h1, qz7; prmt.b32 h0, lo0, hi0, 0x5410;\n"
        "B74:\n"
        "wgmma.wait_group.sync.aligned 2;\n"
        "wgmma.fence.sync.aligned;\n"
        "add.s64 dt, w2d, 1024; wgmma.mma_async.sync.aligned.m64n96k16.f16.f16.f16 {o0,o1,o2,o3,o4,o5,o6,o7,o8,o9,o10,o11,o12,o13,o14,o15,o16,o17,o18,o19,o20,o21,o22,o23}, {g0,g1,g2,g3}, dt, pt, 1, 1, 1;\n"
        "add.s64 dt, w2d, 1088; wgmma.mma_async.sync.aligned.m64n96k16.f16.f16.f16 {o0,o1,o2,o3,o4,o5,o6,o7,o8,o9,o10,o11,o12,o13,o14,o15,o16,o17,o18,o19,o20,o21,o22,o23}, {g4,g5,g6,g7}, dt, pt, 1, 1, 1;\n"
        "wgmma.commit_group.sync.aligned;\n"
        "@pz bra.uni B78;\n"
        "mov.b32 {xl, xh}, a2; tanh.approx.f16 xr, xl; cvt.u32.u16 lo0, xr; tanh.approx.f16 xr, xh; cvt.u32.u16 hi0, xr; mul.rn.f16x2 a3, qz11, p1; fma.rn.f16x2 p0, qz12, qz12, c; fma.rn.f16x2 g8, qz8, h0, qz8; prmt.b32 h1, lo1, hi1, 0x5410;\n"
        "mov.b32 {xl, xh}, a3; tanh.approx.f16 xr, xl; cvt.u32.u16 lo1, xr; tanh.approx.f16 xr, xh; cvt.u32.u16 hi1, xr; mul.rn.f16x2 a0, qz12, p0; fma.rn.f16x2 p1, qz13, qz13, c; fma.rn.f16x2 g9, qz9, h1, qz9; prmt.b32 h0, lo0, hi0, 0x5410;\n"
        "mov.b32 {xl, xh}, a0; tanh.approx.f16 xr, xl; cvt.u32.u16 lo0, xr; tanh.approx.f16 xr, xh; cvt.u32.u16 hi0, xr; mul.rn.f16x2 a1, qz13, p1; fma.rn.f16x2 p0, qz14, qz14, c; fma.rn.f16x2 g10, qz10, h0, qz10; prmt.b32 h1, lo1, hi1, 0x5410;\n"
        "mov.b32 {xl, xh}, a1; tanh.approx.f16 xr, xl; cvt.u32.u16 lo1, xr; tanh.approx.f16 xr, xh; cvt.u32.u16 hi1, xr; mul.rn.f16x2 a2, qz14, p0; fma.rn.f16x2 p1, qz15, qz15, c; fma.rn.f16x2 g11, qz11, h1, qz11; prmt.b32 h0, lo0, hi0, 0x5410;\n"
        "B78:\n"
        "wgmma.wait_group.sync.aligned 1;\n"
        "@!pm bra.uni BACKY;\n"
        "add.u32 tt, n, 1; and.b32 tt, tt, 1; mbarrier.try_wait.parity.shared::cta.b64 pw, [ybar], tt;\n"
        "@!pw bra.uni SPINY;\n"
        "BACKY:\n"
        "@pz bra.uni B80;\n"
        "and.b32 ad, %5, 0xffff; xor.b32 ad, ad, 0; add.u32 ad, ad, %4; ldmatrix.sync.aligned.m8n8.x4.shared.b16 {qa0,qa1,qa2,qa3}, [ad];\n"
        "and.b32 ad, %5, 0xffff; xor.b32 ad, ad, 32; add.u32 ad, ad, %4; ldmatrix.sync.aligned.m8n8.x4.shared.b16 {qa4,qa5,qa6,qa7}, [ad];\n"
        "and.b32 ad, %5, 0xffff; xor.b32 ad, ad, 64; add.u32 ad, ad, %4; ldmatrix.sync.aligned.m8n8.x4.shared.b16 {qa8,qa9,qa10,qa11}, [ad];\n"
        "and.b32 ad, %5, 0xffff; xor.b32 ad, ad, 96; add.u32 ad, ad, %4; ldmatrix.sync.aligned.m8n8.x4.shared.b16 {qa12,qa13,qa14,qa15}, [ad];\n"
        "shr.u32 ad, %5, 16; xor.b32 ad, ad, 0; add.u32 ad, ad, %4; ldmatrix.sync.aligned.m8n8.x4.shared.b16 {qa16,qa17,qa18,qa19}, [ad];\n"
        "shr.u32 ad, %5, 16; xor.b32 ad, ad, 32; add.u32 ad, ad, %4; ldmatrix.sync.aligned.m8n8.x4.shared.b16 {qa20,qa21,qa22,qa23}, [ad];\n"
        "mov.b32 {xl, xh}, a2; tanh.approx.f16 xr, xl; cvt.u32.u16 lo0, xr; tanh.approx.f16 xr, xh; cvt.u32.u16 hi0, xr; mul.rn.f16x2 a3, qz15, p1; fma.rn.f16x2 p0, qz16, qz16, c; fma.rn.f16x2 g12, qz12, h0, qz12; prmt.b32 h1, lo1, hi1, 0x5410;\n"
        "mov.b32 {xl, xh}, a3; tanh.approx.f16 xr, xl; cvt.u32.u16 lo1, xr; tanh.approx.f16 xr, xh; cvt.u32.u16 hi1, xr; mul.rn.f16x2 a0, qz16, p0; fma.rn.f16x2 p1, qz17, qz17, c; fma.rn.f16x2 g13, qz13, h1, qz13; prmt.b32 h0, lo0, hi0, 0x5410;\n"
        "B80:\n"
        "@!pm bra.uni XLOADB;\n"
        "fence.proxy.async.shared::cta;\n"
        "add.u32 tt, id, 0;\n"
        "@pl bra.uni XLOAD;\n"
        "bar.arrive tt, 128;\n"
        "XLOADB:\n"
        "wgmma.fence.sync.aligned;\n"
        "add.s64 dt, w2d, 1152; wgmma.mma_async.sync.aligned.m64n96k16.f16.f16.f16 {o0,o1,o2,o3,o4,o5,o6,o7,o8,o9,o10,o11,o12,o13,o14,o15,o16,o17,o18,o19,o20,o21,o22,o23}, {g8,g9,g10,g11}, dt, pt, 1, 1, 1;\n"
        "wgmma.commit_group.sync.aligned;\n"
        "@pz bra.uni B82;\n"
        "mov.b32 {xl, xh}, a0; tanh.approx.f16 xr, xl; cvt.u32.u16 lo0, xr; tanh.approx.f16 xr, xh; cvt.u32.u16 hi0, xr; mul.rn.f16x2 a1, qz17, p1; fma.rn.f16x2 p0, qz18, qz18, c; fma.rn.f16x2 g14, qz14, h0, qz14; prmt.b32 h1, lo1, hi1, 0x5410;\n"
        "mov.b32 {xl, xh}, a1; tanh.approx.f16 xr, xl; cvt.u32.u16 lo1, xr; tanh.approx.f16 xr, xh; cvt.u32.u16 hi1, xr; mul.rn.f16x2 a2, qz18, p0; fma.rn.f16x2 p1, qz19, qz19, c; fma.rn.f16x2 g15, qz15, h1, qz15; prmt.b32 h0, lo0, hi0, 0x5410;\n"
        "B82:\n"
        "wgmma.wait_group.sync.aligned 1;\n"
        "@!pm bra.uni SKIP1;\n"
        "wgmma.fence.sync.aligned;\n"
        "add.s64 dt, w1d, 0; wgmma.mma_async.sync.aligned.m64n64k16.f16.f16.f16 {qz0,qz1,qz2,qz3,qz4,qz5,qz6,qz7,qz8,qz9,qz10,qz11,qz12,qz13,qz14,qz15}, {qa0,qa1,qa2,qa3}, dt, pf, 1, 1, 1;\n"
        "add.s64 dt, w1d, 128; wgmma.mma_async.sync.aligned.m64n64k16.f16.f16.f16 {qz0,qz1,qz2,qz3,qz4,qz5,qz6,qz7,qz8,qz9,qz10,qz11,qz12,qz13,qz14,qz15}, {qa4,qa5,qa6,qa7}, dt, pt, 1, 1, 1;\n"
        "add.s64 dt, w1d, 256; wgmma.mma_async.sync.aligned.m64n64k16.f16.f16.f16 {qz0,qz1,qz2,qz3,qz4,qz5,qz6,qz7,qz8,qz9,qz10,qz11,qz12,qz13,qz14,qz15}, {qa8,qa9,qa10,qa11}, dt, pt, 1, 1, 1;\n"
        "SKIP1:\n"
        "wgmma.fence.sync.aligned;\n"
        "add.s64 dt, w2d, 1216; wgmma.mma_async.sync.aligned.m64n96k16.f16.f16.f16 {o0,o1,o2,o3,o4,o5,o6,o7,o8,o9,o10,o11,o12,o13,o14,o15,o16,o17,o18,o19,o20,o21,o22,o23}, {g12,g13,g14,g15}, dt, pt, 1, 1, 1;\n"
        "wgmma.commit_group.sync.aligned;\n"
        "@pz bra.uni B86;\n"
        "mov.b32 {xl, xh}, a2; tanh.approx.f16 xr, xl; cvt.u32.u16 lo0, xr; tanh.approx.f16 xr, xh; cvt.u32.u16 hi0, xr; mul.rn.f16x2 a3, qz19, p1; fma.rn.f16x2 p0, qz20, qz20, c; fma.rn.f16x2 g0, qz16, h0, qz16; prmt.b32 h1, lo1, hi1, 0x5410;\n"
        "mov.b32 {xl, xh}, a3; tanh.approx.f16 xr, xl; cvt.u32.u16 lo1, xr; tanh.approx.f16 xr, xh; cvt.u32.u16 hi1, xr; mul.rn.f16x2 a0, qz20, p0; fma.rn.f16x2 p1, qz21, qz21, c; fma.rn.f16x2 g1, qz17, h1, qz17; prmt.b32 h0, lo0, hi0, 0x5410;\n"
        "mov.b32 {xl, xh}, a0; tanh.approx.f16 xr, xl; cvt.u32.u16 lo0, xr; tanh.approx.f16 xr, xh; cvt.u32.u16 hi0, xr; mul.rn.f16x2 a1, qz21, p1; fma.rn.f16x2 p0, qz22, qz22, c; fma.rn.f16x2 g2, qz18, h0, qz18; prmt.b32 h1, lo1, hi1, 0x5410;\n"
        "mov.b32 {xl, xh}, a1; tanh.approx.f16 xr, xl; cvt.u32.u16 lo1, xr; tanh.approx.f16 xr, xh; cvt.u32.u16 hi1, xr; mul.rn.f16x2 a2, qz22, p0; fma.rn.f16x2 p1, qz23, qz23, c; fma.rn.f16x2 g3, qz19, h1, qz19; prmt.b32 h0, lo0, hi0, 0x5410;\n"
        "B86:\n"
        "@!pm bra.uni SKIP2;\n"
        "wgmma.fence.sync.aligned;\n"
        "add.s64 dt, w1d, 384; wgmma.mma_async.sync.aligned.m64n64k16.f16.f16.f16 {qz0,qz1,qz2,qz3,qz4,qz5,qz6,qz7,qz8,qz9,qz10,qz11,qz12,qz13,qz14,qz15}, {qa12,qa13,qa14,qa15}, dt, pt, 1, 1, 1;\n"
        "add.s64 dt, w1d, 512; wgmma.mma_async.sync.aligned.m64n64k16.f16.f16.f16 {qz0,qz1,qz2,qz3,qz4,qz5,qz6,qz7,qz8,qz9,qz10,qz11,qz12,qz13,qz14,qz15}, {qa16,qa17,qa18,qa19}, dt, pt, 1, 1, 1;\n"
        "add.s64 dt, w1d, 640; wgmma.mma_async.sync.aligned.m64n64k16.f16.f16.f16 {qz0,qz1,qz2,qz3,qz4,qz5,qz6,qz7,qz8,qz9,qz10,qz11,qz12,qz13,qz14,qz15}, {qa20,qa21,qa22,qa23}, dt, pt, 1, 1, 1;\n"
        "SKIP2:\n"
        "@pz bra.uni B90;\n"
        "mov.b32 {xl, xh}, a2; tanh.approx.f16 xr, xl; cvt.u32.u16 lo0, xr; tanh.approx.f16 xr, xh; cvt.u32.u16 hi0, xr; mul.rn.f16x2 a3, qz23, p1; fma.rn.f16x2 p0, qz24, qz24, c; fma.rn.f16x2 g4, qz20, h0, qz20; prmt.b32 h1, lo1, hi1, 0x5410;\n"
        "mov.b32 {xl, xh}, a3; tanh.approx.f16 xr, xl; cvt.u32.u16 lo1, xr; tanh.approx.f16 xr, xh; cvt.u32.u16 hi1, xr; mul.rn.f16x2 a0, qz24, p0; fma.rn.f16x2 p1, qz25, qz25, c; fma.rn.f16x2 g5, qz21, h1, qz21; prmt.b32 h0, lo0, hi0, 0x5410;\n"
        "mov.b32 {xl, xh}, a0; tanh.approx.f16 xr, xl; cvt.u32.u16 lo0, xr; tanh.approx.f16 xr, xh; cvt.u32.u16 hi0, xr; mul.rn.f16x2 a1, qz25, p1; fma.rn.f16x2 p0, qz26, qz26, c; fma.rn.f16x2 g6, qz22, h0, qz22; prmt.b32 h1, lo1, hi1, 0x5410;\n"
        "mov.b32 {xl, xh}, a1; tanh.approx.f16 xr, xl; cvt.u32.u16 lo1, xr; tanh.approx.f16 xr, xh; cvt.u32.u16 hi1, xr; mul.rn.f16x2 a2, qz26, p0; fma.rn.f16x2 p1, qz27, qz27, c; fma.rn.f16x2 g7, qz23, h1, qz23; prmt.b32 h0, lo0, hi0, 0x5410;\n"
        "B90:\n"
        "wgmma.wait_group.sync.aligned 1;\n"
        "wgmma.fence.sync.aligned;\n"
        "add.s64 dt, w2d, 1280; wgmma.mma_async.sync.aligned.m64n96k16.f16.f16.f16 {o0,o1,o2,o3,o4,o5,o6,o7,o8,o9,o10,o11,o12,o13,o14,o15,o16,o17,o18,o19,o20,o21,o22,o23}, {g0,g1,g2,g3}, dt, pt, 1, 1, 1;\n"
        "add.s64 dt, w2d, 1344; wgmma.mma_async.sync.aligned.m64n96k16.f16.f16.f16 {o0,o1,o2,o3,o4,o5,o6,o7,o8,o9,o10,o11,o12,o13,o14,o15,o16,o17,o18,o19,o20,o21,o22,o23}, {g4,g5,g6,g7}, dt, pt, 1, 1, 1;\n"
        "wgmma.commit_group.sync.aligned;\n"
        "@pz bra.uni B94;\n"
        "mov.b32 {xl, xh}, a2; tanh.approx.f16 xr, xl; cvt.u32.u16 lo0, xr; tanh.approx.f16 xr, xh; cvt.u32.u16 hi0, xr; mul.rn.f16x2 a3, qz27, p1; fma.rn.f16x2 p0, qz28, qz28, c; fma.rn.f16x2 g8, qz24, h0, qz24; prmt.b32 h1, lo1, hi1, 0x5410;\n"
        "mov.b32 {xl, xh}, a3; tanh.approx.f16 xr, xl; cvt.u32.u16 lo1, xr; tanh.approx.f16 xr, xh; cvt.u32.u16 hi1, xr; mul.rn.f16x2 a0, qz28, p0; fma.rn.f16x2 p1, qz29, qz29, c; fma.rn.f16x2 g9, qz25, h1, qz25; prmt.b32 h0, lo0, hi0, 0x5410;\n"
        "mov.b32 {xl, xh}, a0; tanh.approx.f16 xr, xl; cvt.u32.u16 lo0, xr; tanh.approx.f16 xr, xh; cvt.u32.u16 hi0, xr; mul.rn.f16x2 a1, qz29, p1; fma.rn.f16x2 p0, qz30, qz30, c; fma.rn.f16x2 g10, qz26, h0, qz26; prmt.b32 h1, lo1, hi1, 0x5410;\n"
        "mov.b32 {xl, xh}, a1; tanh.approx.f16 xr, xl; cvt.u32.u16 lo1, xr; tanh.approx.f16 xr, xh; cvt.u32.u16 hi1, xr; mul.rn.f16x2 a2, qz30, p0; fma.rn.f16x2 p1, qz31, qz31, c; fma.rn.f16x2 g11, qz27, h1, qz27; prmt.b32 h0, lo0, hi0, 0x5410;\n"
        "B94:\n"
        "wgmma.wait_group.sync.aligned 0;\n"
        "wgmma.fence.sync.aligned;\n"
        "add.s64 dt, w2d, 1408; wgmma.mma_async.sync.aligned.m64n96k16.f16.f16.f16 {o0,o1,o2,o3,o4,o5,o6,o7,o8,o9,o10,o11,o12,o13,o14,o15,o16,o17,o18,o19,o20,o21,o22,o23}, {g8,g9,g10,g11}, dt, pt, 1, 1, 1;\n"
        "wgmma.commit_group.sync.aligned;\n"
        "@pz bra.uni B2;\n"
        "mov.b32 {xl, xh}, a2; tanh.approx.f16 xr, xl; cvt.u32.u16 lo0, xr; tanh.approx.f16 xr, xh; cvt.u32.u16 hi0, xr; mul.rn.f16x2 a3, qz31, p1; fma.rn.f16x2 p0, qz0, qz0, c; fma.rn.f16x2 g12, qz28, h0, qz28; prmt.b32 h1, lo1, hi1, 0x5410;\n"
        "mov.b32 {xl, xh}, a3; tanh.approx.f16 xr, xl; cvt.u32.u16 lo1, xr; tanh.approx.f16 xr, xh; cvt.u32.u16 hi1, xr; mul.rn.f16x2 a0, qz0, p0; fma.rn.f16x2 p1, qz1, qz1, c; fma.rn.f16x2 g13, qz29, h1, qz29; prmt.b32 h0, lo0, hi0, 0x5410;\n"
        "mov.b32 {xl, xh}, a0; tanh.approx.f16 xr, xl; cvt.u32.u16 lo0, xr; tanh.approx.f16 xr, xh; cvt.u32.u16 hi0, xr; mul.rn.f16x2 a1, qz1, p1; fma.rn.f16x2 p0, qz2, qz2, c; fma.rn.f16x2 g14, qz30, h0, qz30; prmt.b32 h1, lo1, hi1, 0x5410;\n"
        "mov.b32 {xl, xh}, a1; tanh.approx.f16 xr, xl; cvt.u32.u16 lo1, xr; tanh.approx.f16 xr, xh; cvt.u32.u16 hi1, xr; mul.rn.f16x2 a2, qz2, p0; fma.rn.f16x2 p1, qz3, qz3, c; fma.rn.f16x2 g15, qz31, h1, qz31; prmt.b32 h0, lo0, hi0, 0x5410;\n"
        "B2:\n"
        "wgmma.fence.sync.aligned;\n"
        "add.s64 dt, w2d, 1472; wgmma.mma_async.sync.aligned.m64n96k16.f16.f16.f16 {o0,o1,o2,o3,o4,o5,o6,o7,o8,o9,o10,o11,o12,o13,o14,o15,o16,o17,o18,o19,o20,o21,o22,o23}, {g12,g13,g14,g15}, dt, pt, 1, 1, 1;\n"
        "wgmma.commit_group.sync.aligned;\n"
        "@!pm bra.uni LAST;\n"
        "@pz bra.uni BE;\n"
        "mov.b32 {xl, xh}, a2; tanh.approx.f16 xr, xl; cvt.u32.u16 lo0, xr; tanh.approx.f16 xr, xh; cvt.u32.u16 hi0, xr; mul.rn.f16x2 a3, qz3, p1; fma.rn.f16x2 p0, qz4, qz4, c; fma.rn.f16x2 g0, qz0, h0, qz0; prmt.b32 h1, lo1, hi1, 0x5410;\n"
        "mov.b32 {xl, xh}, a3; tanh.approx.f16 xr, xl; cvt.u32.u16 lo1, xr; tanh.approx.f16 xr, xh; cvt.u32.u16 hi1, xr; mul.rn.f16x2 a0, qz4, p0; fma.rn.f16x2 p1, qz5, qz5, c; fma.rn.f16x2 g1, qz1, h1, qz1; prmt.b32 h0, lo0, hi0, 0x5410;\n"
        "mov.b32 {xl, xh}, a0; tanh.approx.f16 xr, xl; cvt.u32.u16 lo0, xr; tanh.approx.f16 xr, xh; cvt.u32.u16 hi0, xr; mul.rn.f16x2 a1, qz5, p1; fma.rn.f16x2 p0, qz6, qz6, c; fma.rn.f16x2 g2, qz2, h0, qz2; prmt.b32 h1, lo1, hi1, 0x5410;\n"
        "mov.b32 {xl, xh}, a1; tanh.approx.f16 xr, xl; cvt.u32.u16 lo1, xr; tanh.approx.f16 xr, xh; cvt.u32.u16 hi1, xr; mul.rn.f16x2 a2, qz6, p0; fma.rn.f16x2 p1, qz7, qz7, c; fma.rn.f16x2 g3, qz3, h1, qz3; prmt.b32 h0, lo0, hi0, 0x5410;\n"
        "BE:\n"
        "wgmma.wait_group.sync.aligned 0;\n"
        "bra.uni LOOP;\n"
        "STORE:\n"
        "bar.sync tt, 128;\n"
        "setp.lt.s32 pr, n, 0;\n"
        "@pr bra.uni STOREB;\n"
        "cvt.u64.u32 gp, off; add.s64 gp, gp, %11;\n"
        "elect.sync _|pr, 0xffffffff;\n"
        "@pr cp.async.bulk.global.shared::cta.bulk_group [gp], [%4], 12288;\n"
        "@pr cp.async.bulk.commit_group;\n"
        "bra.uni STOREB;\n"
        "YLOAD:\n"
        "cp.async.bulk.wait_group.read 0;\n"
        "@!pm bra.uni XLAST;\n"
        "sub.u32 ad, off, %8; cvt.u64.u32 gp, ad; add.s64 gp, gp, %11;\n"
        "elect.sync _|pr, 0xffffffff;\n"
        "@pr mbarrier.arrive.expect_tx.shared::cta.b64 _, [ybar], 12288;\n"
        "@pr cp.async.bulk.shared::cluster.global.mbarrier::complete_tx::bytes [%4], [gp], 12288, [ybar];\n"
        "cvt.u64.u32 gp, off; add.s64 gp, gp, %10;\n"
        "@pr cp.async.bulk.prefetch.L2.global.L2::cache_hint [gp], 12288, pol;\n"
        "bra.uni YLOADB;\n"
        "XLAST:\n"
        "cvt.u64.u32 gp, off; add.s64 gp, gp, %10;\n"
        "elect.sync _|pr, 0xffffffff;\n"
        "@pr mbarrier.arrive.expect_tx.shared::cta.b64 _, [xbar], 12288;\n"
        "@pr cp.async.bulk.shared::cluster.global.mbarrier::complete_tx::bytes.L2::cache_hint [%4], [gp], 12288, [xbar], pol;\n"
        "bra.uni YLOADB;\n"
        "XLOAD:\n"
        "bar.sync tt, 128;\n"
        "cvt.u64.u32 gp, off; add.s64 gp, gp, %10;\n"
        "elect.sync _|pr, 0xffffffff;\n"
        "@pr mbarrier.arrive.expect_tx.shared::cta.b64 _, [xbar], 12288;\n"
        "@pr cp.async.bulk.shared::cluster.global.mbarrier::complete_tx::bytes.L2::cache_hint [%4], [gp], 12288, [xbar], pol;\n"
        "bra.uni XLOADB;\n"
        "SPINY: mov.u32 cnt, 0;\n"
        "SPINYL:\n"
        "add.u32 tt, n, 1; and.b32 tt, tt, 1; mbarrier.try_wait.parity.shared::cta.b64 pw, [ybar], tt;\n"
        "@pw bra.uni BACKY;\n"
        "add.u32 cnt, cnt, 1; setp.lt.u32 pw, cnt, 0x100000;\n"
        "@pw bra.uni SPINYL;\n"
        "trap;\n"
        "SPINX: mov.u32 cnt, 0;\n"
        "SPINXL:\n"
        "and.b32 tt, n, 1; mbarrier.try_wait.parity.shared::cta.b64 pw, [xbar], tt;\n"
        "@pw bra.uni BACKX;\n"
        "add.u32 cnt, cnt, 1; setp.lt.u32 pw, cnt, 0x100000;\n"
        "@pw bra.uni SPINXL;\n"
        "trap;\n"
        "SPINT: mov.u32 cnt, 0;\n"
        "SPINTL:\n"
        "mad.lo.u32 tt, n, 8, tbar; mbarrier.try_wait.parity.shared::cta.b64 pw, [tt], tpar;\n"
        "@pw bra.uni BACKT;\n"
        "add.u32 cnt, cnt, 1; setp.lt.u32 pw, cnt, 0x100000;\n"
        "@pw bra.uni SPINTL;\n"
        "trap;\n"
        "SPINW0: mov.u32 cnt, 0;\n"
        "SPINW0L:\n"
        "mov.u32 tt, 231208; mbarrier.try_wait.parity.shared::cta.b64 pw, [tt], 0;\n"
        "@pw bra.uni BACKW0;\n"
        "add.u32 cnt, cnt, 1; setp.lt.u32 pw, cnt, 0x100000;\n"
        "@pw bra.uni SPINW0L;\n"
        "trap;\n"
        "SPINW1: mov.u32 cnt, 0;\n"
        "SPINW1L:\n"
        "mov.u32 tt, 231216; mbarrier.try_wait.parity.shared::cta.b64 pw, [tt], 0;\n"
        "@pw bra.uni BACKW1;\n"
        "add.u32 cnt, cnt, 1; setp.lt.u32 pw, cnt, 0x100000;\n"
        "@pw bra.uni SPINW1L;\n"
        "trap;\n"
        "SPINL: mov.u32 cnt, 0;\n"
        "SPINLL:\n"
        "and.b32 tt, n, 1; mbarrier.try_wait.parity.shared::cta.b64 pw, [xbar], tt;\n"
        "@pw bra.uni BACKL;\n"
        "add.u32 cnt, cnt, 1; setp.lt.u32 pw, cnt, 0x100000;\n"
        "@pw bra.uni SPINLL;\n"
        "trap;\n"
        "LAST:\n"
        "and.b32 tt, n, 1; mbarrier.try_wait.parity.shared::cta.b64 pw, [xbar], tt;\n"
        "@!pw bra.uni SPINL;\n"
        "BACKL:\n"
        "and.b32 ad, %6, 0xffff; add.u32 ad, ad, %4; ld.shared.v4.b32 {r0,r1,r2,r3}, [ad+0];\n"
        "shr.u32 ad, %6, 16; add.u32 ad, ad, %4; ld.shared.v4.b32 {r4,r5,r6,r7}, [ad+0];\n"
        "and.b32 ad, %6, 0xffff; add.u32 ad, ad, %4; ld.shared.v4.b32 {r8,r9,r10,r11}, [ad+64];\n"
        "shr.u32 ad, %6, 16; add.u32 ad, ad, %4; ld.shared.v4.b32 {r12,r13,r14,r15}, [ad+64];\n"
        "and.b32 ad, %6, 0xffff; add.u32 ad, ad, %4; ld.shared.v4.b32 {r16,r17,r18,r19}, [ad+128];\n"
        "shr.u32 ad, %6, 16; add.u32 ad, ad, %4; ld.shared.v4.b32 {r20,r21,r22,r23}, [ad+128];\n"
        "wgmma.wait_group.sync.aligned 0;\n"
        "mov.b32 {xl, xh}, o0; cvt.f32.f16 f0, xl; cvt.f32.f16 f1, xh; cvt.rn.bf16x2.f32 tt, f1, f0; fma.rn.bf16x2 r0, tt, osc, r0;\n"
        "mov.b32 {xl, xh}, o2; cvt.f32.f16 f0, xl; cvt.f32.f16 f1, xh; cvt.rn.bf16x2.f32 tt, f1, f0; fma.rn.bf16x2 r1, tt, osc, r1;\n"
        "mov.b32 {xl, xh}, o4; cvt.f32.f16 f0, xl; cvt.f32.f16 f1, xh; cvt.rn.bf16x2.f32 tt, f1, f0; fma.rn.bf16x2 r2, tt, osc, r2;\n"
        "mov.b32 {xl, xh}, o6; cvt.f32.f16 f0, xl; cvt.f32.f16 f1, xh; cvt.rn.bf16x2.f32 tt, f1, f0; fma.rn.bf16x2 r3, tt, osc, r3;\n"
        "and.b32 ad, %6, 0xffff; add.u32 ad, ad, off; cvt.u64.u32 gp, ad; add.s64 gp, gp, %11; st.global.v4.b32 [gp+0], {r0,r1,r2,r3};\n"
        "mov.b32 {xl, xh}, o1; cvt.f32.f16 f0, xl; cvt.f32.f16 f1, xh; cvt.rn.bf16x2.f32 tt, f1, f0; fma.rn.bf16x2 r4, tt, osc, r4;\n"
        "mov.b32 {xl, xh}, o3; cvt.f32.f16 f0, xl; cvt.f32.f16 f1, xh; cvt.rn.bf16x2.f32 tt, f1, f0; fma.rn.bf16x2 r5, tt, osc, r5;\n"
        "mov.b32 {xl, xh}, o5; cvt.f32.f16 f0, xl; cvt.f32.f16 f1, xh; cvt.rn.bf16x2.f32 tt, f1, f0; fma.rn.bf16x2 r6, tt, osc, r6;\n"
        "mov.b32 {xl, xh}, o7; cvt.f32.f16 f0, xl; cvt.f32.f16 f1, xh; cvt.rn.bf16x2.f32 tt, f1, f0; fma.rn.bf16x2 r7, tt, osc, r7;\n"
        "shr.u32 ad, %6, 16; add.u32 ad, ad, off; cvt.u64.u32 gp, ad; add.s64 gp, gp, %11; st.global.v4.b32 [gp+0], {r4,r5,r6,r7};\n"
        "mov.b32 {xl, xh}, o8; cvt.f32.f16 f0, xl; cvt.f32.f16 f1, xh; cvt.rn.bf16x2.f32 tt, f1, f0; fma.rn.bf16x2 r8, tt, osc, r8;\n"
        "mov.b32 {xl, xh}, o10; cvt.f32.f16 f0, xl; cvt.f32.f16 f1, xh; cvt.rn.bf16x2.f32 tt, f1, f0; fma.rn.bf16x2 r9, tt, osc, r9;\n"
        "mov.b32 {xl, xh}, o12; cvt.f32.f16 f0, xl; cvt.f32.f16 f1, xh; cvt.rn.bf16x2.f32 tt, f1, f0; fma.rn.bf16x2 r10, tt, osc, r10;\n"
        "mov.b32 {xl, xh}, o14; cvt.f32.f16 f0, xl; cvt.f32.f16 f1, xh; cvt.rn.bf16x2.f32 tt, f1, f0; fma.rn.bf16x2 r11, tt, osc, r11;\n"
        "and.b32 ad, %6, 0xffff; add.u32 ad, ad, off; cvt.u64.u32 gp, ad; add.s64 gp, gp, %11; st.global.v4.b32 [gp+64], {r8,r9,r10,r11};\n"
        "mov.b32 {xl, xh}, o9; cvt.f32.f16 f0, xl; cvt.f32.f16 f1, xh; cvt.rn.bf16x2.f32 tt, f1, f0; fma.rn.bf16x2 r12, tt, osc, r12;\n"
        "mov.b32 {xl, xh}, o11; cvt.f32.f16 f0, xl; cvt.f32.f16 f1, xh; cvt.rn.bf16x2.f32 tt, f1, f0; fma.rn.bf16x2 r13, tt, osc, r13;\n"
        "mov.b32 {xl, xh}, o13; cvt.f32.f16 f0, xl; cvt.f32.f16 f1, xh; cvt.rn.bf16x2.f32 tt, f1, f0; fma.rn.bf16x2 r14, tt, osc, r14;\n"
        "mov.b32 {xl, xh}, o15; cvt.f32.f16 f0, xl; cvt.f32.f16 f1, xh; cvt.rn.bf16x2.f32 tt, f1, f0; fma.rn.bf16x2 r15, tt, osc, r15;\n"
        "shr.u32 ad, %6, 16; add.u32 ad, ad, off; cvt.u64.u32 gp, ad; add.s64 gp, gp, %11; st.global.v4.b32 [gp+64], {r12,r13,r14,r15};\n"
        "mov.b32 {xl, xh}, o16; cvt.f32.f16 f0, xl; cvt.f32.f16 f1, xh; cvt.rn.bf16x2.f32 tt, f1, f0; fma.rn.bf16x2 r16, tt, osc, r16;\n"
        "mov.b32 {xl, xh}, o18; cvt.f32.f16 f0, xl; cvt.f32.f16 f1, xh; cvt.rn.bf16x2.f32 tt, f1, f0; fma.rn.bf16x2 r17, tt, osc, r17;\n"
        "mov.b32 {xl, xh}, o20; cvt.f32.f16 f0, xl; cvt.f32.f16 f1, xh; cvt.rn.bf16x2.f32 tt, f1, f0; fma.rn.bf16x2 r18, tt, osc, r18;\n"
        "mov.b32 {xl, xh}, o22; cvt.f32.f16 f0, xl; cvt.f32.f16 f1, xh; cvt.rn.bf16x2.f32 tt, f1, f0; fma.rn.bf16x2 r19, tt, osc, r19;\n"
        "and.b32 ad, %6, 0xffff; add.u32 ad, ad, off; cvt.u64.u32 gp, ad; add.s64 gp, gp, %11; st.global.v4.b32 [gp+128], {r16,r17,r18,r19};\n"
        "mov.b32 {xl, xh}, o17; cvt.f32.f16 f0, xl; cvt.f32.f16 f1, xh; cvt.rn.bf16x2.f32 tt, f1, f0; fma.rn.bf16x2 r20, tt, osc, r20;\n"
        "mov.b32 {xl, xh}, o19; cvt.f32.f16 f0, xl; cvt.f32.f16 f1, xh; cvt.rn.bf16x2.f32 tt, f1, f0; fma.rn.bf16x2 r21, tt, osc, r21;\n"
        "mov.b32 {xl, xh}, o21; cvt.f32.f16 f0, xl; cvt.f32.f16 f1, xh; cvt.rn.bf16x2.f32 tt, f1, f0; fma.rn.bf16x2 r22, tt, osc, r22;\n"
        "mov.b32 {xl, xh}, o23; cvt.f32.f16 f0, xl; cvt.f32.f16 f1, xh; cvt.rn.bf16x2.f32 tt, f1, f0; fma.rn.bf16x2 r23, tt, osc, r23;\n"
        "shr.u32 ad, %6, 16; add.u32 ad, ad, off; cvt.u64.u32 gp, ad; add.s64 gp, gp, %11; st.global.v4.b32 [gp+128], {r20,r21,r22,r23};\n"
        ASM_MARK
        "}\n"
        :: "r"(prm.w1desc), "r"(prm.w2desc), "r"(c.wg), "r"(c.off), "r"(c.xs), "r"(c.a_offs), "r"(c.xs_offs), "r"(c.bias_addr),
           "r"(c.step), "r"(c.w), "l"(prm.x), "l"(prm.out)
        : "memory");
}

__device__ __forceinline__ float warp_sum(float v) {
#pragma unroll
    for (int s = 16; s >= 1; s >>= 1) v += __shfl_xor_sync(0xffffffffu, v, s);
    return v;
}
__device__ __forceinline__ float pow2f(int e) { return __uint_as_float((uint32_t)(e + 127) << 23); }
__device__ __forceinline__ int exponent_of(float v) { return (int)(__float_as_uint(v) >> 23) - 127; }
__device__ __forceinline__ float lds_bf16(uint32_t addr) {
    uint16_t v; asm volatile("ld.shared.u16 %0, [%1];" : "=h"(v) : "r"(addr) : "memory"); return bf_lo(v);
}

__device__ __forceinline__ void publish_bias(const Params& prm, uint32_t c, uint32_t tag) {
    const uint32_t lane = fresh_tid() & 31;
    const uint32_t col = sb + SM_W2 + (c >> 5) * 24576 + lane * 64 + ((((c >> 3) ^ (lane >> 1)) & 3) * 16) + (c & 7) * 2;
    float v = 0.0f;
#pragma unroll
    for (int k = 0; k < EX / 32; k++) v = fmaf(lds_bf16(col + k * 2048), lds_bf16(sb + SM_BETA + lane * 2 + k * 64), v);
    v = warp_sum(v);
    if (lane == 0)
        asm volatile("st.relaxed.gpu.global.u64 [%0], %1;" ::"l"(prm.g->bias + c), "l"((uint64_t)tag << 32 | __float_as_uint(v)) : "memory");
}
__device__ __forceinline__ void collect_bias(const Params& prm, uint32_t tag) {
    const uint32_t lane = fresh_tid() & 31;
    if (lane < 24) {
        const unsigned long long* src = prm.g->bias + 32 * (lane >> 3) + 8 * (lane & 3) + (lane & 4);
        uint32_t v[4], t[4], spins = 0;
        for (;;) {
#pragma unroll
            for (int k = 0; k < 4; k++)
                asm volatile("{\n.reg .b64 w;\nld.relaxed.gpu.global.u64 w, [%2];\nmov.b64 {%0, %1}, w;\n}\n"
                             : "=r"(v[k]), "=r"(t[k]) : "l"(src + k) : "memory");
            if (t[0] == tag && t[1] == tag && t[2] == tag && t[3] == tag) break;
            if (++spins > (1u << 22)) __trap();
        }
        sts128(sb + SM_BIAS + lane * 16, v[0], v[1], v[2], v[3]);
    }
    __syncwarp();
}
__device__ __forceinline__ float fetch_w2_row(uint32_t (&u)[12][4], uint32_t row, uint32_t sw) {
    uint32_t mx[4] = {};
#pragma unroll
    for (int a = 0; a < 3; a++)
#pragma unroll
        for (int k = 0; k < 4; k++) {
            asm volatile("ld.shared.v4.b32 {%0,%1,%2,%3}, [%4];"
                         : "=r"(u[a * 4][k]), "=r"(u[a * 4 + 1][k]), "=r"(u[a * 4 + 2][k]), "=r"(u[a * 4 + 3][k])
                         : "r"(row + a * 24576 + ((k * 16) ^ sw)) : "memory");
#pragma unroll
            for (int b = 0; b < 4; b++) asm("max.xorsign.abs.bf16x2 %0, %0, %1;" : "+r"(mx[b]) : "r"(u[a * 4 + b][k]));
        }
#pragma unroll
    for (int b = 1; b < 4; b++) asm("max.xorsign.abs.bf16x2 %0, %0, %1;" : "+r"(mx[0]) : "r"(mx[b]));
    return fmaxf(fabsf(bf_lo(mx[0])), fabsf(bf_hi(mx[0])));
}

template <bool FAST> __device__ __forceinline__ bool grn_stats(float ss, float gm, float bt, float top, int e, float& gx, float& inv, int& eo) {
    gx = sqrt_fast(fmaf(ss, INV_2A * INV_2A, 1e-6f));
    const float rt = sqrt_fast(ss + 1.0f) * INV_2A * top;
    uint32_t r[4] = {FAST ? __reduce_add_sync(0xffffffffu, __float2uint_rn(gx * 128.0f)) : __float_as_uint(warp_sum(gx)),
                     __reduce_max_sync(0xffffffffu, __float_as_uint(fmaf(bt, top, rt))),
                     __reduce_max_sync(0xffffffffu, __float_as_uint(rt * fabsf(gm) * gx)),
                     (uint32_t)__any_sync(0xffffffffu, !(ss >= 16.0f && ss < ACC_LIMIT))};
    if ((e & 31) == 0) sts128(sb + SM_SEL + (e >> 5) * 16, r[0], r[1], r[2], r[3]);
    MARK(6);
    named_sync(10, 512);
    lds128(r, sb + SM_SEL + min(e & 15, 11) * 16);
    if ((e & 31) >= 12) r[0] = 0;
    const float tot = FAST ? __uint2float_rn(__reduce_add_sync(0xffffffffu, r[0])) * (1.0f / 128) : warp_sum(__uint_as_float(r[0]));
    inv = __fdividef(1.0f, fmaf(tot, 1.0f / EX, 1e-6f));
    const float bound = fmaf(__uint_as_float(__reduce_max_sync(0xffffffffu, r[2])), inv,
                             __uint_as_float(__reduce_max_sync(0xffffffffu, r[1]))) * EX;
    eo = min(max(exponent_of(bound), -90), 126) - 14;
    return __any_sync(0xffffffffu, r[3]);
}

__device__ __forceinline__ float exact_sums(const Params& prm) {
    const int lane = fresh_tid() & 31, warp = fresh_warp(), wg = warp >> 2;
    const uint32_t epoch = lds32(sb + SM_RED + (RED_EPOCH + 1) * 4), bar = sb + SM_BAR + BAR_W1 * 8;
    if (wg < 3) {
        uint32_t wa[2][24], d[2][16];
        float acc[2][2] = {};
        const uint32_t yd = prm.ydesc + ((SM_SPARE - SM_Y1) >> 4), wd = prm.w1desc + ((2 * wg * 12288 + 5 * 2048) >> 4);
        load_w1t(wa, wg, warp & 3, lane);
#pragma unroll 1
        for (int n = 0; n < ROWS_PER_CTA; n++) {
            if (warp == 0) {
                expect_tx(bar, TILE_BYTES);
                bulk_load(sb + SM_SPARE, (const char*)prm.out + (cta_tile0(fresh_cta()) + n * cta_stride(fresh_cta())), TILE_BYTES, bar);
            }
            mbar_wait(bar, (n + 1) & 1);
            gemm1_t<0>(d[0], wa[0], yd, wd);
            gemm1_t<1>(d[1], wa[1], yd, wd);
            wg_wait<0>();
            pin(d[0]); pin(d[1]);
            gelu_sumsq_f(d[0], acc[0]);
            gelu_sumsq_f(d[1], acc[1]);
            named_sync(1, 384);
        }
        publish_sums(acc, prm.g->sums[epoch & 1], &prm.g->count[1], wg, warp & 3, lane);
    }
    grid_wait(&prm.g->count[1], (epoch + 1) * NUM_CTAS);
    return __ldcg(prm.g->sums[epoch & 1] + fresh_tid() % EX);
}

template <bool FIRST> __device__ __forceinline__ void prepare_pass2(const Pass2& c, const Params& prm, float ss) {
    const int tid = fresh_tid(), lane = tid & 31, warp = fresh_warp(), wg = warp >> 2;
    const int e = tid >= EX ? tid - EX : tid;
    const uint32_t w2row = sb + SM_W2 + e * 64, sw = ((e >> 1) & 3) * 16;
    pass2_start(c, prm);
    MARK(2);
    if (wg) {
        uint32_t u[12][4];
        mbar_wait_c<0>(sb + SM_BAR + BAR_W2 * 8);
        const uint32_t epoch = lds32(sb + SM_RED + RED_EPOCH * 4);
        unsigned long long seen = 0;
        if (FIRST) asm volatile("ld.relaxed.gpu.global.u64 %0, [%1];" : "=l"(seen) : "l"(acc_word(prm, epoch, e)) : "memory");
        const float top = fetch_w2_row(u, w2row, sw);
        MARK(3);
        const float gm = lds_bf16(sb + SM_GAMMA + e * 2), bt = fabsf(lds_bf16(sb + SM_BETA + e * 2));
        if (FIRST) {
            if (wg == 3) named_sync(11, EX);
            if (warp == 12) collect_bias(prm, epoch + 1);
            MARK(4);
            ss = collect_fast(acc_word(prm, epoch, e), seen);
            if (tid == 416 && fresh_cta() == 0) prm.g->count[0] = epoch + 1;
        }
        if (warp == 4) TS(4);
        MARK(5);
        float gx, inv;
        int eo;
        const bool redo = (grn_stats<FIRST>(ss, gm, bt, top, e, gx, inv, eo) || FORCE_EXACT) && FIRST;
        MARK(8);
        const float up = pow2f(eo), dn = pow2f(-eo);
        if (warp == 4) {
            if (lane == 24) sts64(sb + SM_RED + RED_SCALE * 4, pack_bf2(up, up), redo);
            if (lane < 24 && !redo) {
                uint32_t b[4];
                lds128(b, sb + SM_BIAS + lane * 16);
                const uint32_t p0 = pack_h2(__uint_as_float(b[0]) * dn, __uint_as_float(b[1]) * dn);
                const uint32_t p1 = pack_h2(__uint_as_float(b[2]) * dn, __uint_as_float(b[3]) * dn);
                sts128(sb + SM_BIAS + lane * 16, p0, p0, p1, p1);
            }
            __syncwarp();
            mbar_arrive_if(sb + SM_BAR + BAR_STAT * 8, lane == 0);
        }
        if (!redo) {
            float sc = fmaf(gm, gx * inv, 1.0f) * INV_2A;
            if (eo > 6) {
                const uint32_t dn2 = pack_bf2(dn, dn);
#pragma unroll
                for (int k = 0; k < 48; k++) u[k >> 2][k & 3] = bf2_mul(u[k >> 2][k & 3], dn2);
            } else {
                sc *= dn;
            }
            const uint32_t s2 = pack_bf2(sc * 0x1p-112f, sc * 0x1p-112f);
#pragma unroll
            for (int k = 0; k < 12; k++) {
                uint32_t v[4];
#pragma unroll
                for (int b = 0; b < 4; b++) {
                    v[b] = bf2_mul(u[k][b], s2);
                    v[b] += (v[b] & 0x7fff7fffu) * 7u;
                }
                sts128(w2row + (k >> 2) * 24576 + (((k & 3) * 16) ^ sw), v[0], v[1], v[2], v[3]);
            }
            MARK(9);
            fence_async_smem();
            __syncwarp();
            mbar_arrive_if(sb + SM_BAR + (BAR_ROWS + (wg != 3)) * 8, lane == 0);
        }
        if (warp == 4) TS(5);
    } else {
        asm volatile("bar.arrive 10, 512;" ::: "memory");
    }
}

__device__ __forceinline__ void pass2_uniform(Pass2& c) {
    const int warp = fresh_warp(), wg = warp >> 2;
    c.wg = wg;
    c.w = warp & 3;
    c.off = cta_tile0(fresh_cta()) + (ROWS_PER_CTA - 1 - wg) * cta_stride(fresh_cta());
    c.step = 4 * cta_stride(fresh_cta());
    c.xs = wg == 3 ? sb + SM_BUF3 : sb + SM_Y1 + (wg == 2 ? 2 : 1 - wg) * SLOT_BYTES;
    static_assert((ROWS_PER_CTA - 1) % NX == 1, "slot of the last tile");
}
__device__ __forceinline__ Pass2 pass2_setup() {
    Pass2 c;
    pass2_uniform(c);
    const int lane = fresh_tid() & 31, w = c.w, arow = 16 * w + (lane & 15);
    c.a_offs = (arow * 128 + (((lane >> 4) ^ (arow & 7)) * 16)) |
               (8192 + arow * 64 + (((lane >> 4) ^ ((arow >> 1) & 3)) * 16)) << 16;
    const int g = lane >> 2, px = 33 * (g & 1) + 4 * (g >> 1) + 16 * (w >> 1) + 2 * (w & 1);
    c.xs_offs = (px * 192 + (lane & 3) * 16) | ((px ^ 1) * 192 + (lane & 3) * 16) << 16;
    c.bias_addr = sb + SM_BIAS + (lane & 3) * 16;
    return c;
}

__global__ void __launch_bounds__(512, 1) convnext_kernel(const __grid_constant__ Params prm) {
    extern __shared__ __align__(1024) uint8_t smem[];
    if ((uint32_t)__cvta_generic_to_shared(smem) != sb) __trap();
    {
        const uint32_t tid = fresh_tid(), warp = fresh_warp(), lane = tid & 31;
        if (warp == 0) {
            if (lane == 0) {
#pragma unroll
                for (int k = 0; k < NX; k++) mbar_init(sb + SM_GO + k * 8, 2);
                mbar_init(sb + SM_BAR + BAR_DW * 8, 1);
                mbar_init(sb + SM_BAR + BAR_W1 * 8, 1);
                mbar_init(sb + SM_BAR + BAR_W1B * 8, 1);
                fence_async_smem();
            }
            __syncwarp();
            expect_tx(sb + SM_BAR + BAR_DW * 8, 9 * CH * 2);
            bulk_load(sb + SM_Y1, prm.dw, 9 * CH * 2, sb + SM_BAR + BAR_DW * 8);
            const RowCopy rc = row_copy(prm);
#pragma unroll
            for (int k = 0; k < NX; k++) issue_row_load(rc, k, k);
            SMARK(4);
        }
        if (fresh_warp() == 15) {
            const uint32_t cta = fresh_cta();
            bulk_prefetch((const char*)prm.w1 + cta * (CH * EX * 2 / NUM_CTAS), CH * EX * 2 / NUM_CTAS);
            bulk_prefetch(prm.dw, 9 * CH * 2);
            bulk_prefetch((const char*)prm.x + (cta_tile0(cta) - cta_stride(cta)), TILE_BYTES);
        } else if (warp == 2) {
            if (lane < 2) asm volatile("prefetch.tensormap [%0];" ::"l"(&prm.w1_map + lane) : "memory");
        } else if (warp - 6u < 6) {
            if (lane == 0) {
#pragma unroll 1
                for (int k = NX + warp - 6; k < GO_COUNT + ROWS_PER_CTA + 2; k += 6)
                    mbar_init(sb + SM_GO + k * 8, k < 2 * NX ? 2 : k < GO_COUNT ? 14 : 4);
                fence_async_smem();
            }
        } else if (warp == 3) {
            const uint32_t one = (lane & 5) == ((lane & 8) >> 1) + (lane >> 4) ? 0x3f803f80u : 0u;
            sts128(sb + SM_SEL + lane * 16, one, one, one, one);
            fence_async_smem();
        } else if (tid - 128u < NX * 12 && ((fresh_cta() + 1) & 7) < 2) {
            const int k = tid - 128;
            sts128(sb + SM_X + (k / 12) * SLOT_BYTES + ((fresh_cta() & 7) == 0 ? 0 : XHALF_B + 33 * 192) + (k % 12) * 16, 0, 0, 0, 0);
        }
        __syncwarp();
        SMARK(3);
        named_sync(0, 512);
    }
    if (fresh_warp() >= 12) {
        Producer pc;
        SMARK(0);
        asm volatile("setmaxnreg.inc.sync.aligned.u32 %0;" ::"n"(PRODUCER_REGS));
        SMARK(1);
        const int w = fresh_warp() & 3, lane = fresh_tid() & 31;
        const int j = lane & 7, hb = (lane >> 3) & 1, base = 4 * (2 * w + (lane >> 4));
        pc.lane = lane;
        pc.xoff[0] = hb * XHALF_B + base * 192 + j * 16;
        pc.xoff[1] = hb * XHALF_B + base * 192 + 128 + j * 8;
        const int grp = 4 * w + (lane >> 3);
#pragma unroll
        for (int o = 0; o < 2; o++) {
            const int row = (grp & 7) + 8 * (o ^ hb) + 32 * (grp >> 3);
            pc.yoff[0][o] = row * 128 + ((j ^ (row & 7)) * 16);
            pc.yoff[1][o] = 8192 + row * 64 + (((j >> 1) ^ ((row >> 1) & 3)) * 16) + (j & 1) * 8;
        }
        pc.stat = sb + SM_STAT + (8 * w + (lane >> 2)) * 32;
        pc.own = pc.stat + (lane & 3) * 8;
        const int dstep = fresh_cta() & 8 ? 3 * CH * 2 : -3 * CH * 2;
        mbar_wait_c<0>(sb + SM_BAR + BAR_DW * 8);
        SMARK(8);
#pragma unroll
        for (int tap = 0; tap < 9; tap++) {
            const uint32_t dw = sb + SM_Y1 + (3 + tap % 3) * CH * 2 + (tap / 3 - 1) * dstep;
            lds128(pc.w[tap], dw + j * 16);
            asm volatile("ld.shared.v2.b32 {%0,%1}, [%2];" : "=r"(pc.w[tap][4]), "=r"(pc.w[tap][5]) : "r"(dw + 128 + j * 8) : "memory");
        }
#pragma unroll
        for (int tap = 0; tap < 9; tap++)
#pragma unroll
            for (int u = 0; u < 6; u++) pc.w[tap][u] = bf2_mul(pc.w[tap][u], TAP_SCALE_BF2);
        produce(pc, prm);
        TS(9);
        asm volatile("setmaxnreg.dec.sync.aligned.u32 %0;" ::"n"(EVEN_REGS));
        if (fresh_warp() == 12) {
            mbar_wait_c<0>(sb + SM_BAR + BAR_W2 * 8);
            if (fresh_cta() < CH) publish_bias(prm, fresh_cta(), lds32(sb + SM_RED + RED_EPOCH * 4) + 1);
        }
    } else {
        asm volatile("setmaxnreg.dec.sync.aligned.u32 %0;" ::"n"(CONSUMER_REGS));
        {
            const int tid = fresh_tid(), warp = fresh_warp();
            if (warp == 1) {
#pragma unroll
                for (int h = 0; h < 2; h++) {
                    const uint32_t bar = sb + SM_BAR + (h ? BAR_W1B : BAR_W1) * 8;
                    expect_tx(bar, CH * EX);
#pragma unroll
                    for (int q = h; q < 6; q += 2) tma_load_2d(sb + SM_W1 + q * 12288, &prm.w1_map, 64 * q, 0, bar);
                }
            }
            uint32_t cnt[2];
            asm volatile("ld.relaxed.gpu.global.v2.u32 {%0, %1}, [%2];" : "=r"(cnt[0]), "=r"(cnt[1]) : "l"(prm.g->count) : "memory");
            SMARK(0);
            if (warp == 2) {
                const RowCopy rc = row_copy(prm);
#pragma unroll 1
                for (int i = loop_init<0>(); i < NX; i++) {
                    named_sync(6 + i, 160);
                    issue_row_load(rc, i + NX, i);
                }
            }
            if (tid == 256) {
                sts64(sb + SM_RED + RED_EPOCH * 4, cnt[0], cnt[1] / NUM_CTAS);
#pragma unroll
                for (int k = 0; k < BAR_DW; k++)
                    if (k != BAR_W1 && k != BAR_W1B) mbar_init(sb + SM_BAR + k * 8, k < BAR_TURN || k == BAR_STAT ? 1 : k == BAR_ROWS + 1 ? 8 : 4);
#pragma unroll
                for (int k = 0; k < 3; k++) mbar_arrive_if(sb + SM_BAR + (BAR_Y2FULL + k) * 8, true);
            }
            if (fresh_cta() == 0) *acc_word(prm, cnt[0] + 1, tid) = 0;
            if (fresh_cta() == 1) prm.g->sums[~(cnt[1] / NUM_CTAS) & 1][tid] = 0.0f;
            __syncwarp();
            SMARK(1);
            mbar_wait_c<0>(sb + SM_BAR + BAR_W1 * 8);
            SMARK(2);
        }

        const int tid = fresh_tid(), lane = tid & 31, wg = fresh_warp() >> 2, w = fresh_warp() & 3;
        float acc[2][2];
        const int c = 8 * (lane >> 4) + (lane & 7), ck = 2 * w + ((lane >> 3) & 1);
        consume(acc, sb + SM_W1 + 2 * wg * 12288 + c * 128 + ((ck ^ (c & 7)) * 16), prm.ydesc,
                prm.w1desc + (((2 * wg + 1) * 12288 + 5 * 2048) >> 4), wg * SLOT_BYTES, make_duty(prm, wg, w), w, lane, prm);
        publish_fast(prm, acc, lds32(sb + SM_RED + RED_EPOCH * 4), wg, w, lane);
        if (wg) asm volatile("bar.arrive 11, 384;" ::: "memory");
        MARK(0);
        bulk_wait_all();
        if (wg == 0) TS(3);
        asm volatile("setmaxnreg.inc.sync.aligned.u32 %0;" ::"n"(EVEN_REGS));
    }

    {
        asm volatile(PASS2_STATE);
        MARK(1);
        Pass2 c = pass2_setup();
        prepare_pass2<true>(c, prm, 0.0f);
        if (pass2_head(c, 0)) {
            const float ss = exact_sums(prm);
            c = pass2_setup();
            prepare_pass2<false>(c, prm, ss);
            pass2_head(c, 1);
        }

        pass2_uniform(c);
        pass2_tiles(c, prm);
        bulk_wait_read<0>();
        MARK(13);
    }
}

}

extern "C" void kernel_launch(void* const* d_in, const int* in_sizes, int n_in, void* d_out, int out_size) {
    (void)in_sizes; (void)n_in; (void)out_size;
    typedef CUresult (*EncodeFn)(CUtensorMap*, CUtensorMapDataType, cuuint32_t, void*, const cuuint64_t*, const cuuint64_t*,
                                 const cuuint32_t*, const cuuint32_t*, CUtensorMapInterleave, CUtensorMapSwizzle,
                                 CUtensorMapL2promotion, CUtensorMapFloatOOBfill);
    void* fn = nullptr;
    cudaDriverEntryPointQueryResult status;
    cudaGetDriverEntryPoint("cuTensorMapEncodeTiled", &fn, cudaEnableDefault, &status);
    const EncodeFn encode = (EncodeFn)fn;
    const cuuint32_t ones[2] = {1, 1};

    Params p;
    {
        const cuuint64_t dims[2] = {EX, CH}, strides[1] = {EX * 2};
        const cuuint32_t box[2] = {64, CH};
        encode(&p.w1_map, CU_TENSOR_MAP_DATA_TYPE_BFLOAT16, 2, d_in[2], dims, strides, box, ones,
               CU_TENSOR_MAP_INTERLEAVE_NONE, CU_TENSOR_MAP_SWIZZLE_128B, CU_TENSOR_MAP_L2_PROMOTION_NONE,
               CU_TENSOR_MAP_FLOAT_OOB_FILL_NONE);
    }
    {
        const cuuint64_t dims[2] = {CH, EX}, strides[1] = {CH * 2};
        const cuuint32_t box[2] = {32, 192};
        encode(&p.w2_map, CU_TENSOR_MAP_DATA_TYPE_BFLOAT16, 2, d_in[3], dims, strides, box, ones,
               CU_TENSOR_MAP_INTERLEAVE_NONE, CU_TENSOR_MAP_SWIZZLE_64B, CU_TENSOR_MAP_L2_PROMOTION_NONE,
               CU_TENSOR_MAP_FLOAT_OOB_FILL_NONE);
    }
    p.x = (const __nv_bfloat16*)d_in[0];
    p.dw = (const __nv_bfloat16*)d_in[1];
    p.w1 = (const __nv_bfloat16*)d_in[2];
    p.gamma = (const __nv_bfloat16*)d_in[4];
    p.beta = (const __nv_bfloat16*)d_in[5];
    p.out = (__nv_bfloat16*)d_out;
    cudaGetSymbolAddress((void**)&p.g, g_scratch);
    p.w1desc = desc_lo(sb + SM_W1, 12288);
    p.w2desc = desc_lo(sb + SM_W2, 24576);
    p.ydesc = desc_lo(sb + SM_Y1, 16);
    p.ydesc64[0] = (0x40000040ull << 32) | p.ydesc;
    p.ydesc64[1] = (0x80000020ull << 32) | (p.ydesc + 512);
    for (int k = 0; k < 3; k++) p.sel[k] = (8ull << 32) | desc_lo(sb + SM_SEL + k * 128, k == 2 ? 128 : 0);
    constexpr int smem_bytes = SM_TOTAL;
    cudaFuncSetAttribute(convnext_kernel, cudaFuncAttributeMaxDynamicSharedMemorySize, smem_bytes);
    convnext_kernel<<<NUM_CTAS, 512, smem_bytes>>>(p);
}
```

```cpp
#include <cuda.h>
#include <cuda_runtime.h>
#include <cuda_bf16.h>
#include <stdint.h>

namespace {

constexpr int IMG_W = 512, CH = 96, EX = 384;
constexpr int TILE_PX = 64;
constexpr int ROWS_PER_CTA = 32;
constexpr int NUM_CTAS = 128;
constexpr int STEPS = ROWS_PER_CTA + 2;
constexpr int ROW_BYTES = IMG_W * CH * 2;

#define FORCE_EXACT 0
constexpr int PRODUCER_REGS = 200, CONSUMER_REGS = 104, EVEN_REGS = 128;

constexpr int XHALF_BYTES = 34 * 192;
constexpr int XHALF_B = XHALF_BYTES + 64;
constexpr int XROW_BYTES = XHALF_B + XHALF_BYTES + 64;
constexpr int L2_AHEAD = 2;
constexpr int NX = 3;
constexpr int TILE_BYTES = TILE_PX * 192;

constexpr uint32_t sb = 1024;
constexpr int SM_W1 = 0;
constexpr int SM_W2 = 73728;
constexpr int SM_RING = 147456;
constexpr int SLOT_BYTES = 26624;
constexpr int SM_Y1 = SM_RING;
constexpr int SM_X = SM_Y1 + TILE_BYTES;
constexpr int SM_STAT = SM_X + XROW_BYTES;
constexpr int SM_BUF3 = SM_X + SLOT_BYTES, SM_SPARE = SM_X;
constexpr int SM_SEL = SM_RING + NX * SLOT_BYTES;
constexpr int SM_BIAS = SM_SEL + 512;
constexpr int SM_GAMMA = SM_BIAS + 384;
constexpr int SM_BETA = SM_GAMMA + EX * 2;
constexpr int SM_RED = SM_BETA + EX * 2;
constexpr int SM_BAR = SM_RED + 16;
constexpr int BAR_Y2FULL = 0, BAR_XSFULL = 4, BAR_W1 = 8, BAR_W2 = 9, BAR_W1B = 10, BAR_TURN = 11, BAR_ROWS = 51,
              BAR_STAT = 53, BAR_DW = 54, BAR_COUNT = 55;
constexpr int SM_GO = SM_BAR + BAR_COUNT * 8, GO_COUNT = ROWS_PER_CTA + 2 * NX;
constexpr int SM_YFULL = SM_GO + (GO_COUNT + 1) * 8;
constexpr int SM_TOTAL = SM_YFULL + (ROWS_PER_CTA + 1) * 8;
static_assert(SM_STAT + TILE_PX * 16 <= SM_RING + SLOT_BYTES && XROW_BYTES >= TILE_BYTES && SM_X % 1024 == 0, "ring layout");
static_assert(SM_TOTAL <= 232448, "smem budget");
static_assert(SM_STAT % 128 == 0 && SM_BIAS % 16 == 0 && SM_BAR % 8 == 0 && SLOT_BYTES % 1024 == 0, "alignment");

constexpr int RED_EPOCH = 0, RED_SCALE = 2;

constexpr float GELU_A = 0.32920349f;
constexpr uint32_t GELU_C_H2 = 0x40D940D9u;
constexpr float INV_2A = 1.0f / (2.0f * GELU_A);

constexpr uint32_t TAP_SCALE_BF2 = 0x2B802B80u;
constexpr float LN_EPS_SCALED = 1e-5f * 0x1p-80f;
constexpr float RSTD_SCALE = GELU_A * 0x1p-112f;

struct Scratch {
    unsigned long long acc[2][EX / 4 * 32];
    unsigned long long bias[CH];
    float sums[2][EX];
    uint4 zero_row[66 * 192 / 16];
    unsigned int count[2];
};
__device__ __align__(256) Scratch g_scratch;
constexpr float ACC_LIMIT = 0x1p30f;

#define TS(k)
#define ASM_TS
#define MARK(k)
#define SMARK(k)
#define ASM_MARK
#define ASM_SMARK
#define ASM_TRC(it)

__device__ __forceinline__ void mbar_init(uint32_t bar, uint32_t count) {
    asm volatile("mbarrier.init.shared::cta.b64 [%0], %1;" ::"r"(bar), "r"(count) : "memory");
}
__device__ __forceinline__ void mbar_arrive_if(uint32_t bar, bool pred) {
    asm volatile("{\n.reg .pred p;\nsetp.ne.u32 p, %1, 0;\n@p mbarrier.arrive.shared::cta.b64 _, [%0];\n}\n"
                 ::"r"(bar), "r"((uint32_t)pred) : "memory");
}
__device__ __forceinline__ void mbar_wait(uint32_t bar, uint32_t parity) {
    asm volatile(
        "{\n.reg .pred p;\n.reg .u32 n;\n"
        "mbarrier.try_wait.parity.shared::cta.b64 p, [%0], %1;\n"
        "@p bra.uni WAIT_DONE;\n"
        "mov.u32 n, 0;\n"
        "WAIT_LOOP:\n"
        "mbarrier.try_wait.parity.shared::cta.b64 p, [%0], %1;\n"
        "@p bra.uni WAIT_DONE;\n"
        "mbarrier.try_wait.parity.shared::cta.b64 p, [%0], %1;\n"
        "@p bra.uni WAIT_DONE;\n"
        "mbarrier.try_wait.parity.shared::cta.b64 p, [%0], %1;\n"
        "@p bra.uni WAIT_DONE;\n"
        "add.u32 n, n, 1;\nsetp.lt.u32 p, n, 0x40000;\n"
        "@p bra.uni WAIT_LOOP;\n"
        "trap;\n"
        "WAIT_DONE:\n}\n"
        ::"r"(bar), "r"(parity) : "memory");
}
template <int PARITY> __device__ __forceinline__ void mbar_wait_c(uint32_t bar) {
    asm volatile(
        "{\n.reg .pred p;\n.reg .u32 n;\n"
        "mbarrier.try_wait.parity.shared::cta.b64 p, [%0], %1;\n"
        "@p bra.uni WAIT_DONE;\n"
        "mov.u32 n, 0;\n"
        "WAIT_LOOP:\n"
        "mbarrier.try_wait.parity.shared::cta.b64 p, [%0], %1;\n"
        "@p bra.uni WAIT_DONE;\n"
        "mbarrier.try_wait.parity.shared::cta.b64 p, [%0], %1;\n"
        "@p bra.uni WAIT_DONE;\n"
        "mbarrier.try_wait.parity.shared::cta.b64 p, [%0], %1;\n"
        "@p bra.uni WAIT_DONE;\n"
        "add.u32 n, n, 1;\nsetp.lt.u32 p, n, 0x40000;\n"
        "@p bra.uni WAIT_LOOP;\n"
        "trap;\n"
        "WAIT_DONE:\n}\n"
        ::"r"(bar), "n"(PARITY) : "memory");
}
#define ELECTED(body) "{\n.reg .pred p;\nelect.sync _|p, 0xffffffff;\n" body "}\n"
__device__ __forceinline__ void expect_tx(uint32_t bar, uint32_t bytes) {
    asm volatile(ELECTED("@p mbarrier.arrive.expect_tx.shared::cta.b64 _, [%0], %1;\n") ::"r"(bar), "r"(bytes) : "memory");
}
__device__ __forceinline__ void bulk_load(uint32_t dst, const void* src, uint32_t bytes, uint32_t bar) {
    asm volatile(ELECTED("@p cp.async.bulk.shared::cluster.global.mbarrier::complete_tx::bytes [%0], [%1], %2, [%3];\n")
                 ::"r"(dst), "l"(src), "r"(bytes), "r"(bar) : "memory");
}
__device__ __forceinline__ void bulk_prefetch(const void* src, uint32_t bytes) {
    asm volatile(ELECTED("@p cp.async.bulk.prefetch.L2.global [%0], %1;\n") ::"l"(src), "r"(bytes) : "memory");
}
__device__ __forceinline__ void tma_load_2d(uint32_t dst, const CUtensorMap* map, int c0, int c1, uint32_t bar) {
    asm volatile(ELECTED("@p cp.async.bulk.tensor.2d.shared::cluster.global.mbarrier::complete_tx::bytes [%0], [%1, {%2, %3}], [%4];\n")
                 ::"r"(dst), "l"(map), "r"(c0), "r"(c1), "r"(bar) : "memory");
}
template <int N> __device__ __forceinline__ void bulk_wait_read() {
    asm volatile("cp.async.bulk.wait_group.read %0;" ::"n"(N) : "memory");
}
__device__ __forceinline__ void bulk_wait_all() { asm volatile("cp.async.bulk.wait_group 0;" ::: "memory"); }
__device__ __forceinline__ void fence_async_smem() { asm volatile("fence.proxy.async.shared::cta;" ::: "memory"); }
__device__ __forceinline__ void named_sync(int id, int n) { asm volatile("bar.sync %0, %1;" ::"r"(id), "r"(n) : "memory"); }

__device__ __forceinline__ void sts64(uint32_t addr, uint32_t a, uint32_t b) {
    asm volatile("st.shared.v2.b32 [%0], {%1,%2};" ::"r"(addr), "r"(a), "r"(b) : "memory");
}
__device__ __forceinline__ void sts128(uint32_t addr, uint32_t a, uint32_t b, uint32_t c, uint32_t d) {
    asm volatile("st.shared.v4.b32 [%0], {%1,%2,%3,%4};" ::"r"(addr), "r"(a), "r"(b), "r"(c), "r"(d) : "memory");
}
__device__ __forceinline__ void ldsm4_t(uint32_t* r, uint32_t addr) {
    asm volatile("ldmatrix.sync.aligned.m8n8.x4.trans.shared.b16 {%0,%1,%2,%3}, [%4];"
                 : "=r"(r[0]), "=r"(r[1]), "=r"(r[2]), "=r"(r[3]) : "r"(addr) : "memory");
}
__device__ __forceinline__ void lds128(uint32_t* v, uint32_t addr) {
    asm volatile("ld.shared.v4.b32 {%0,%1,%2,%3}, [%4];"
                 : "=r"(v[0]), "=r"(v[1]), "=r"(v[2]), "=r"(v[3]) : "r"(addr) : "memory");
}
__device__ __forceinline__ uint32_t lds32(uint32_t addr) {
    uint32_t v; asm volatile("ld.shared.b32 %0, [%1];" : "=r"(v) : "r"(addr) : "memory"); return v;
}
__device__ __forceinline__ void sts32(uint32_t addr, uint32_t v) {
    asm volatile("st.shared.b32 [%0], %1;" ::"r"(addr), "r"(v) : "memory");
}

__device__ __forceinline__ uint32_t bf2_fma(uint32_t a, uint32_t b, uint32_t c) {
    uint32_t d; asm("fma.rn.bf16x2 %0, %1, %2, %3;" : "=r"(d) : "r"(a), "r"(b), "r"(c)); return d;
}
__device__ __forceinline__ uint32_t bf2_mul(uint32_t a, uint32_t b) {
    uint32_t d; asm("mul.rn.bf16x2 %0, %1, %2;" : "=r"(d) : "r"(a), "r"(b)); return d;
}
__device__ __forceinline__ uint32_t bf2_add(uint32_t a, uint32_t b) {
    uint32_t d; asm("add.rn.bf16x2 %0, %1, %2;" : "=r"(d) : "r"(a), "r"(b)); return d;
}
__device__ __forceinline__ uint32_t h2_fma(uint32_t a, uint32_t b, uint32_t c) {
    uint32_t d; asm("fma.rn.f16x2 %0, %1, %2, %3;" : "=r"(d) : "r"(a), "r"(b), "r"(c)); return d;
}
__device__ __forceinline__ uint32_t h2_mul(uint32_t a, uint32_t b) {
    uint32_t d; asm("mul.rn.f16x2 %0, %1, %2;" : "=r"(d) : "r"(a), "r"(b)); return d;
}
__device__ __forceinline__ uint32_t h2_tanh(uint32_t a) {
    uint32_t d; asm("tanh.approx.f16x2 %0, %1;" : "=r"(d) : "r"(a)); return d;
}
__device__ __forceinline__ float bf_lo(uint32_t v) { return __uint_as_float(v << 16); }
__device__ __forceinline__ float bf_hi(uint32_t v) { return __uint_as_float(v & 0xffff0000u); }
__device__ __forceinline__ uint32_t pack_h2(float lo, float hi) {
    uint32_t d; asm("cvt.rn.f16x2.f32 %0, %1, %2;" : "=r"(d) : "f"(hi), "f"(lo)); return d;
}
__device__ __forceinline__ uint32_t pack_bf2(float lo, float hi) {
    uint32_t d; asm("cvt.rn.bf16x2.f32 %0, %1, %2;" : "=r"(d) : "f"(hi), "f"(lo)); return d;
}
__device__ __forceinline__ void h2_unpack(uint32_t v, float& lo, float& hi) {
    asm("{\n.reg .b16 l, h;\nmov.b32 {l, h}, %2;\ncvt.f32.f16 %0, l;\ncvt.f32.f16 %1, h;\n}\n" : "=f"(lo), "=f"(hi) : "r"(v));
}

__device__ __forceinline__ uint32_t gelu2(uint32_t z) {
    uint32_t p = h2_fma(z, z, GELU_C_H2);
    uint32_t t = h2_tanh(h2_mul(z, p));
    return h2_fma(z, t, z);
}

__device__ __forceinline__ void wg_fence() { asm volatile("wgmma.fence.sync.aligned;" ::: "memory"); }
__device__ __forceinline__ void wg_commit() { asm volatile("wgmma.commit_group.sync.aligned;" ::: "memory"); }
template <int N> __device__ __forceinline__ void wg_wait() {
    asm volatile("wgmma.wait_group.sync.aligned %0;" ::"n"(N) : "memory");
}
template <int N> __device__ __forceinline__ void pin(uint32_t (&r)[N]) {
#pragma unroll
    for (int i = 0; i < N; i++) asm volatile("" : "+r"(r[i])::"memory");
}
constexpr uint32_t desc_lo(uint32_t addr, uint32_t lbo) { return ((addr & 0x3FFFF) >> 4) | ((lbo >> 4) << 16); }
template <uint32_t SBO, uint32_t SWZ> __device__ __forceinline__ uint64_t desc(uint32_t lo, uint32_t bytes) {
    return (((uint64_t)((SBO >> 4) | (SWZ << 30)) << 32) | lo) + (bytes >> 4);
}
__device__ __forceinline__ uint32_t fresh_tid() {
    uint32_t v; asm volatile("mov.u32 %0, %%tid.x;" : "=r"(v));
    return v;
}
template <uint32_t V> __device__ __forceinline__ uint32_t loop_init() {
    uint32_t v; asm volatile("mov.u32 %0, %1;" : "=r"(v) : "n"(V)); return v;
}
__device__ __forceinline__ int fresh_warp() {
    int v; asm volatile("shfl.sync.idx.b32 %0, %1, 0, 0x1f, 0xffffffff;" : "=r"(v) : "r"(fresh_tid() >> 5)); return v;
}
__device__ __forceinline__ uint32_t fresh_cta() {
    uint32_t v; asm volatile("mov.u32 %0, %%ctaid.x;" : "=r"(v)); return v;
}
__device__ __forceinline__ float sqrt_fast(float v) { float r; asm("sqrt.approx.f32 %0, %1;" : "=f"(r) : "f"(v)); return r; }

template <int TB>
__device__ __forceinline__ void wgmma_n64_h_set(uint32_t (&d)[16], const uint32_t* a, uint64_t desc) {
    asm volatile(
        "{\n.reg .pred p;\nsetp.ne.b32 p, 0, 0;\n"
        "wgmma.mma_async.sync.aligned.m64n64k16.f16.f16.f16 "
        "{%0,%1,%2,%3,%4,%5,%6,%7,%8,%9,%10,%11,%12,%13,%14,%15}, {%16,%17,%18,%19}, %20, p, 1, 1, %21;\n}\n"
        : "=r"(d[0]), "=r"(d[1]), "=r"(d[2]), "=r"(d[3]), "=r"(d[4]), "=r"(d[5]), "=r"(d[6]), "=r"(d[7]), "=r"(d[8]), "=r"(d[9]), "=r"(d[10]), "=r"(d[11]), "=r"(d[12]), "=r"(d[13]), "=r"(d[14]), "=r"(d[15])
        : "r"(a[0]), "r"(a[1]), "r"(a[2]), "r"(a[3]), "l"(desc), "n"(TB));
}
template <int TB>
__device__ __forceinline__ void wgmma_n64_h_acc(uint32_t (&d)[16], const uint32_t* a, uint64_t desc) {
    asm volatile(
        "{\n.reg .pred p;\nsetp.ne.b32 p, 1, 0;\n"
        "wgmma.mma_async.sync.aligned.m64n64k16.f16.f16.f16 "
        "{%0,%1,%2,%3,%4,%5,%6,%7,%8,%9,%10,%11,%12,%13,%14,%15}, {%16,%17,%18,%19}, %20, p, 1, 1, %21;\n}\n"
        : "+r"(d[0]), "+r"(d[1]), "+r"(d[2]), "+r"(d[3]), "+r"(d[4]), "+r"(d[5]), "+r"(d[6]), "+r"(d[7]), "+r"(d[8]), "+r"(d[9]), "+r"(d[10]), "+r"(d[11]), "+r"(d[12]), "+r"(d[13]), "+r"(d[14]), "+r"(d[15])
        : "r"(a[0]), "r"(a[1]), "r"(a[2]), "r"(a[3]), "l"(desc), "n"(TB));
}
__device__ __forceinline__ void wgmma_n64_h_acc_ss(uint32_t (&d)[16], uint64_t adesc, uint64_t desc) {
    asm volatile(
        "{\n.reg .pred p;\nsetp.ne.b32 p, 1, 0;\n"
        "wgmma.mma_async.sync.aligned.m64n64k16.f16.f16.f16 "
        "{%0,%1,%2,%3,%4,%5,%6,%7,%8,%9,%10,%11,%12,%13,%14,%15}, %16, %17, p, 1, 1, 1, 0;\n}\n"
        : "+r"(d[0]), "+r"(d[1]), "+r"(d[2]), "+r"(d[3]), "+r"(d[4]), "+r"(d[5]), "+r"(d[6]), "+r"(d[7]), "+r"(d[8]), "+r"(d[9]), "+r"(d[10]), "+r"(d[11]), "+r"(d[12]), "+r"(d[13]), "+r"(d[14]), "+r"(d[15])
        : "l"(adesc), "l"(desc));
}

struct Params {
    CUtensorMap w1_map, w2_map;
    const __nv_bfloat16* x;
    const __nv_bfloat16* dw;
    const __nv_bfloat16* w1;
    const __nv_bfloat16* gamma;
    const __nv_bfloat16* beta;
    __nv_bfloat16* out;
    Scratch* g;
    uint64_t ydesc64[2];
    uint64_t sel[3];
    uint32_t w1desc, w2desc, ydesc;
};

__device__ __forceinline__ int cta_stride(uint32_t cta) { return cta & 8 ? ROW_BYTES : -ROW_BYTES; }
__device__ __forceinline__ uint32_t cta_tile0(uint32_t cta) {
    return ((cta >> 3) * ROWS_PER_CTA + (cta & 8 ? 0 : ROWS_PER_CTA - 1)) * ROW_BYTES + (cta & 7) * TILE_BYTES;
}

struct Producer {
    uint32_t w[9][6];
    uint32_t xoff[2];
    uint32_t yoff[2][2];
    uint32_t stat, own;
    int lane;
};

struct RowCopy {
    const char* x0;
    char* y0;
    const char* zeros;
    uint32_t cut0, cut1;
    int stride, last;
};
__device__ __forceinline__ RowCopy row_copy(const Params& prm) {
    const uint32_t cta = fresh_cta(), strip = cta & 7, t0 = cta_tile0(cta);
    RowCopy r;
    r.stride = cta_stride(cta);
    r.x0 = (const char*)prm.x + (t0 - r.stride) - 192;
    r.y0 = (char*)prm.out + t0;
    r.zeros = (const char*)prm.g->zero_row;
    r.cut0 = strip == 0 ? 192 : 0;
    r.cut1 = strip == 7 ? 192 : 0;
    r.last = cta - 8 >= NUM_CTAS - 16 ? STEPS - 2 : STEPS - 1;
    return r;
}
__device__ __forceinline__ void issue_row_load(const RowCopy& r, int i, uint32_t slot) {
    const char* src = r.x0 + i * r.stride;
    const uint32_t bar = sb + SM_GO + i * 8, dst = sb + SM_X + slot * SLOT_BYTES;
    expect_tx(bar, XHALF_BYTES - r.cut0);
    bulk_load(dst + r.cut0, src + r.cut0, XHALF_BYTES - r.cut0, bar);
    expect_tx(bar, XHALF_BYTES - r.cut1);
    bulk_load(dst + XHALF_B, src + 32 * 192, XHALF_BYTES - r.cut1, bar);
}

__device__ __forceinline__ float quad_sum(float v) {
    v += __shfl_xor_sync(0xffffffffu, v, 1);
    v += __shfl_xor_sync(0xffffffffu, v, 2);
    return v;
}

__device__ __forceinline__ void load_x(uint32_t (&v)[6][6], const Producer& c, uint32_t row) {
#pragma unroll
    for (int k = 0; k < 6; k++) {
        asm volatile("ld.shared.v4.b32 {%0,%1,%2,%3}, [%4];"
                     : "=r"(v[k][0]), "=r"(v[k][1]), "=r"(v[k][2]), "=r"(v[k][3]) : "r"(row + c.xoff[0] + k * 192));
        asm volatile("ld.shared.v2.b32 {%0,%1}, [%2];" : "=r"(v[k][4]), "=r"(v[k][5]) : "r"(row + c.xoff[1] + k * 192));
    }
}
template <int DY, int STRIDE>
__device__ __forceinline__ void conv_row(uint32_t (&dst)[24], const uint32_t* src, const uint32_t (&v)[6][6], const Producer& c) {
#pragma unroll
    for (int o = 0; o < 4; o++)
#pragma unroll
        for (int u = 0; u < 6; u++)
            dst[o * 6 + u] = bf2_fma(v[o + 2][u], c.w[3 * DY + 2][u], bf2_fma(v[o + 1][u], c.w[3 * DY + 1][u],
                             bf2_fma(v[o][u], c.w[3 * DY][u], STRIDE ? src[o * 6 + u] : src[2 * o + 1])));
}
#define HAND_OVER(name, base, r) asm volatile("mov.b32 " name "%6, %0; mov.b32 " name "%7, %1; mov.b32 " name "%8, %2;\n" \
    "mov.b32 " name "%9, %3; mov.b32 " name "%10, %4; mov.b32 " name "%11, %5;" ::"r"((r)[0]), "r"((r)[1]), "r"((r)[2]), \
    "r"((r)[3]), "r"((r)[4]), "r"((r)[5]), "n"(base), "n"(base + 1), "n"(base + 2), "n"(base + 3), "n"(base + 4), "n"(base + 5))
template <int K> __device__ __forceinline__ void hand_over(const Producer& c, const uint32_t (&B)[24], const uint32_t (&C)[24],
                                                           const uint32_t (&v)[6][6]) {
    HAND_OVER("pw", K * 6, c.w[K]);
    if (K < 6) HAND_OVER("pv", K * 6, v[K % 6]);
    if (K < 4) { HAND_OVER("pb", K * 6, B + K % 4 * 6); HAND_OVER("pc", K * 6, C + K % 4 * 6); }
    if constexpr (K < 8) hand_over<K + 1>(c, B, C, v);
}
__device__ __forceinline__ void produce_tiles(const Producer& c, const Params& prm) {
    asm volatile(
        "{\n"
        ".reg .b32 pa<24>, pq<4>, m<6>, y<6>, rr, mm, t, so, ad, tt, cnt;\n"
        ".reg .b16 xl, xh;\n"
        ".reg .f32 d<4>, us, s0, s1, f0, f1, kq;\n"
        ".reg .pred pt, pf, pr, pw, pl, po, pe;\n"
        "setp.ne.b32 pt, 1, 0; setp.ne.b32 pf, 0, 0; setp.eq.u32 pl, %8, 0; and.b32 tt, %8, 1; setp.ne.u32 po, tt, 0;\n"
        "and.b32 tt, %8, 4; setp.ne.u32 pr, tt, 0; selp.f32 kq, 0f3F802D41, 0f3F7FA57E, pr;\n"
        "mov.u32 t, 0; mov.u32 so, 0;\n"
        "setp.eq.u32 pr, %12, 0;\n"
        "@pr bra.uni RARE;\n"
        "LOOP:\n"
        ASM_TRC("t")
        "fma.rn.bf16x2 pa0, pv0, pw36, pb0; fma.rn.bf16x2 pa1, pv1, pw37, pb1; fma.rn.bf16x2 pa2, pv2, pw38, pb2; fma.rn.bf16x2 pa3, pv3, pw39, pb3; fma.rn.bf16x2 pa4, pv4, pw40, pb4; fma.rn.bf16x2 pa5, pv5, pw41, pb5;\n"
        "fma.rn.bf16x2 pa6, pv6, pw36, pb6; fma.rn.bf16x2 pa7, pv7, pw37, pb7; fma.rn.bf16x2 pa8, pv8, pw38, pb8; fma.rn.bf16x2 pa9, pv9, pw39, pb9; fma.rn.bf16x2 pa10, pv10, pw40, pb10; fma.rn.bf16x2 pa11, pv11, pw41, pb11;\n"
        "fma.rn.bf16x2 pa12, pv12, pw36, pb12; fma.rn.bf16x2 pa13, pv13, pw37, pb13; fma.rn.bf16x2 pa14, pv14, pw38, pb14; fma.rn.bf16x2 pa15, pv15, pw39, pb15; fma.rn.bf16x2 pa16, pv16, pw40, pb16; fma.rn.bf16x2 pa17, pv17, pw41, pb17;\n"
        "fma.rn.bf16x2 pa18, pv18, pw36, pb18; fma.rn.bf16x2 pa19, pv19, pw37, pb19; fma.rn.bf16x2 pa20, pv20, pw38, pb20; fma.rn.bf16x2 pa21, pv21, pw39, pb21; fma.rn.bf16x2 pa22, pv22, pw40, pb22; fma.rn.bf16x2 pa23, pv23, pw41, pb23;\n"
        "fma.rn.bf16x2 pa0, pv6, pw42, pa0; fma.rn.bf16x2 pa1, pv7, pw43, pa1; fma.rn.bf16x2 pa2, pv8, pw44, pa2; fma.rn.bf16x2 pa3, pv9, pw45, pa3; fma.rn.bf16x2 pa4, pv10, pw46, pa4; fma.rn.bf16x2 pa5, pv11, pw47, pa5;\n"
        "fma.rn.bf16x2 pa6, pv12, pw42, pa6; fma.rn.bf16x2 pa7, pv13, pw43, pa7; fma.rn.bf16x2 pa8, pv14, pw44, pa8; fma.rn.bf16x2 pa9, pv15, pw45, pa9; fma.rn.bf16x2 pa10, pv16, pw46, pa10; fma.rn.bf16x2 pa11, pv17, pw47, pa11;\n"
        "fma.rn.bf16x2 pa12, pv18, pw42, pa12; fma.rn.bf16x2 pa13, pv19, pw43, pa13; fma.rn.bf16x2 pa14, pv20, pw44, pa14; fma.rn.bf16x2 pa15, pv21, pw45, pa15; fma.rn.bf16x2 pa16, pv22, pw46, pa16; fma.rn.bf16x2 pa17, pv23, pw47, pa17;\n"
        "fma.rn.bf16x2 pa18, pv24, pw42, pa18; fma.rn.bf16x2 pa19, pv25, pw43, pa19; fma.rn.bf16x2 pa20, pv26, pw44, pa20; fma.rn.bf16x2 pa21, pv27, pw45, pa21; fma.rn.bf16x2 pa22, pv28, pw46, pa22; fma.rn.bf16x2 pa23, pv29, pw47, pa23;\n"
        "fma.rn.bf16x2 pa0, pv12, pw48, pa0; fma.rn.bf16x2 pa1, pv13, pw49, pa1; fma.rn.bf16x2 pa2, pv14, pw50, pa2; fma.rn.bf16x2 pa3, pv15, pw51, pa3; fma.rn.bf16x2 pa4, pv16, pw52, pa4; fma.rn.bf16x2 pa5, pv17, pw53, pa5;\n"
        "fma.rn.bf16x2 pa6, pv18, pw48, pa6; fma.rn.bf16x2 pa7, pv19, pw49, pa7; fma.rn.bf16x2 pa8, pv20, pw50, pa8; fma.rn.bf16x2 pa9, pv21, pw51, pa9; fma.rn.bf16x2 pa10, pv22, pw52, pa10; fma.rn.bf16x2 pa11, pv23, pw53, pa11;\n"
        "fma.rn.bf16x2 pa12, pv24, pw48, pa12; fma.rn.bf16x2 pa13, pv25, pw49, pa13; fma.rn.bf16x2 pa14, pv26, pw50, pa14; fma.rn.bf16x2 pa15, pv27, pw51, pa15; fma.rn.bf16x2 pa16, pv28, pw52, pa16; fma.rn.bf16x2 pa17, pv29, pw53, pa17;\n"
        "fma.rn.bf16x2 pa18, pv30, pw48, pa18; fma.rn.bf16x2 pa19, pv31, pw49, pa19; fma.rn.bf16x2 pa20, pv32, pw50, pa20; fma.rn.bf16x2 pa21, pv33, pw51, pa21; fma.rn.bf16x2 pa22, pv34, pw52, pa22; fma.rn.bf16x2 pa23, pv35, pw53, pa23;\n"
        "mul.rn.bf16x2 pq0, pa0, pa0; fma.rn.bf16x2 pq0, pa1, pa1, pq0; fma.rn.bf16x2 pq0, pa2, pa2, pq0; fma.rn.bf16x2 pq0, pa3, pa3, pq0; fma.rn.bf16x2 pq0, pa4, pa4, pq0; fma.rn.bf16x2 pq0, pa5, pa5, pq0;\n"
        "mul.rn.bf16x2 pq1, pa6, pa6; fma.rn.bf16x2 pq1, pa7, pa7, pq1; fma.rn.bf16x2 pq1, pa8, pa8, pq1; fma.rn.bf16x2 pq1, pa9, pa9, pq1; fma.rn.bf16x2 pq1, pa10, pa10, pq1; fma.rn.bf16x2 pq1, pa11, pa11, pq1;\n"
        "mul.rn.bf16x2 pq2, pa12, pa12; fma.rn.bf16x2 pq2, pa13, pa13, pq2; fma.rn.bf16x2 pq2, pa14, pa14, pq2; fma.rn.bf16x2 pq2, pa15, pa15, pq2; fma.rn.bf16x2 pq2, pa16, pa16, pq2; fma.rn.bf16x2 pq2, pa17, pa17, pq2;\n"
        "mul.rn.bf16x2 pq3, pa18, pa18; fma.rn.bf16x2 pq3, pa19, pa19, pq3; fma.rn.bf16x2 pq3, pa20, pa20, pq3; fma.rn.bf16x2 pq3, pa21, pa21, pq3; fma.rn.bf16x2 pq3, pa22, pa22, pq3; fma.rn.bf16x2 pq3, pa23, pa23, pq3;\n"
        "B0:\n"
        "wgmma.fence.sync.aligned;\n"
        "wgmma.mma_async.sync.aligned.m64n8k16.f32.bf16.bf16 {d0,d1,d2,d3}, {pa0,pa6,pa1,pa7}, %9, pf, 1, 1, 0;\n"
        "wgmma.mma_async.sync.aligned.m64n8k16.f32.bf16.bf16 {d0,d1,d2,d3}, {pa2,pa8,pa3,pa9}, %9, pt, 1, 1, 0;\n"
        "wgmma.mma_async.sync.aligned.m64n8k16.f32.bf16.bf16 {d0,d1,d2,d3}, {pa4,pa10,pa5,pa11}, %9, pt, 1, 1, 0;\n"
        "wgmma.mma_async.sync.aligned.m64n8k16.f32.bf16.bf16 {d0,d1,d2,d3}, {pa12,pa18,pa13,pa19}, %10, pt, 1, 1, 0;\n"
        "wgmma.mma_async.sync.aligned.m64n8k16.f32.bf16.bf16 {d0,d1,d2,d3}, {pa14,pa20,pa15,pa21}, %10, pt, 1, 1, 0;\n"
        "wgmma.mma_async.sync.aligned.m64n8k16.f32.bf16.bf16 {d0,d1,d2,d3}, {pa16,pa22,pa17,pa23}, %10, pt, 1, 1, 0;\n"
        "wgmma.mma_async.sync.aligned.m64n8k16.f32.bf16.bf16 {d0,d1,d2,d3}, {pq0,pq1,pq2,pq3}, %11, pt, 1, 1, 0;\n"
        "wgmma.commit_group.sync.aligned;\n"
        "fence.proxy.async.shared::cta;\n"
        "@pl mbarrier.arrive.shared::cta.b64 _, [t+231544];\n"
        "add.u32 ad, %7, so; ld.shared.f32 us, [ad+4];\n"
        "fma.rn.bf16x2 pb0, pv0, pw18, pc0; fma.rn.bf16x2 pb1, pv1, pw19, pc1; fma.rn.bf16x2 pb2, pv2, pw20, pc2; fma.rn.bf16x2 pb3, pv3, pw21, pc3; fma.rn.bf16x2 pb4, pv4, pw22, pc4; fma.rn.bf16x2 pb5, pv5, pw23, pc5;\n"
        "fma.rn.bf16x2 pb6, pv6, pw18, pc6; fma.rn.bf16x2 pb7, pv7, pw19, pc7; fma.rn.bf16x2 pb8, pv8, pw20, pc8; fma.rn.bf16x2 pb9, pv9, pw21, pc9; fma.rn.bf16x2 pb10, pv10, pw22, pc10; fma.rn.bf16x2 pb11, pv11, pw23, pc11;\n"
        "fma.rn.bf16x2 pb0, pv6, pw24, pb0; fma.rn.bf16x2 pb1, pv7, pw25, pb1; fma.rn.bf16x2 pb2, pv8, pw26, pb2; fma.rn.bf16x2 pb3, pv9, pw27, pb3; fma.rn.bf16x2 pb4, pv10, pw28, pb4; fma.rn.bf16x2 pb5, pv11, pw29, pb5;\n"
        "fma.rn.bf16x2 pb6, pv12, pw24, pb6; fma.rn.bf16x2 pb7, pv13, pw25, pb7; fma.rn.bf16x2 pb8, pv14, pw26, pb8; fma.rn.bf16x2 pb9, pv15, pw27, pb9; fma.rn.bf16x2 pb10, pv16, pw28, pb10; fma.rn.bf16x2 pb11, pv17, pw29, pb11;\n"
        "fma.rn.bf16x2 pb0, pv12, pw30, pb0; fma.rn.bf16x2 pb1, pv13, pw31, pb1; fma.rn.bf16x2 pb2, pv14, pw32, pb2; fma.rn.bf16x2 pb3, pv15, pw33, pb3; fma.rn.bf16x2 pb4, pv16, pw34, pb4; fma.rn.bf16x2 pb5, pv17, pw35, pb5;\n"
        "fma.rn.bf16x2 pb6, pv18, pw30, pb6; fma.rn.bf16x2 pb7, pv19, pw31, pb7; fma.rn.bf16x2 pb8, pv20, pw32, pb8; fma.rn.bf16x2 pb9, pv21, pw33, pb9; fma.rn.bf16x2 pb10, pv22, pw34, pb10; fma.rn.bf16x2 pb11, pv23, pw35, pb11;\n"
        "B1:\n"
        "fma.rn.bf16x2 pb12, pv12, pw18, pc12; fma.rn.bf16x2 pb13, pv13, pw19, pc13; fma.rn.bf16x2 pb14, pv14, pw20, pc14; fma.rn.bf16x2 pb15, pv15, pw21, pc15; fma.rn.bf16x2 pb16, pv16, pw22, pc16; fma.rn.bf16x2 pb17, pv17, pw23, pc17;\n"
        "fma.rn.bf16x2 pb18, pv18, pw18, pc18; fma.rn.bf16x2 pb19, pv19, pw19, pc19; fma.rn.bf16x2 pb20, pv20, pw20, pc20; fma.rn.bf16x2 pb21, pv21, pw21, pc21; fma.rn.bf16x2 pb22, pv22, pw22, pc22; fma.rn.bf16x2 pb23, pv23, pw23, pc23;\n"
        "fma.rn.bf16x2 pb12, pv18, pw24, pb12; fma.rn.bf16x2 pb13, pv19, pw25, pb13; fma.rn.bf16x2 pb14, pv20, pw26, pb14; fma.rn.bf16x2 pb15, pv21, pw27, pb15; fma.rn.bf16x2 pb16, pv22, pw28, pb16; fma.rn.bf16x2 pb17, pv23, pw29, pb17;\n"
        "fma.rn.bf16x2 pb18, pv24, pw24, pb18; fma.rn.bf16x2 pb19, pv25, pw25, pb19; fma.rn.bf16x2 pb20, pv26, pw26, pb20; fma.rn.bf16x2 pb21, pv27, pw27, pb21; fma.rn.bf16x2 pb22, pv28, pw28, pb22; fma.rn.bf16x2 pb23, pv29, pw29, pb23;\n"
        "fma.rn.bf16x2 pb12, pv24, pw30, pb12; fma.rn.bf16x2 pb13, pv25, pw31, pb13; fma.rn.bf16x2 pb14, pv26, pw32, pb14; fma.rn.bf16x2 pb15, pv27, pw33, pb15; fma.rn.bf16x2 pb16, pv28, pw34, pb16; fma.rn.bf16x2 pb17, pv29, pw35, pb17;\n"
        "fma.rn.bf16x2 pb18, pv30, pw30, pb18; fma.rn.bf16x2 pb19, pv31, pw31, pb19; fma.rn.bf16x2 pb20, pv32, pw32, pb20; fma.rn.bf16x2 pb21, pv33, pw33, pb21; fma.rn.bf16x2 pb22, pv34, pw34, pb22; fma.rn.bf16x2 pb23, pv35, pw35, pb23;\n"
        "C0:\n"
        "wgmma.wait_group.sync.aligned 0;\n"
        "selp.f32 s0, d2, d0, po; selp.f32 s1, d3, d1, po;\n"
        "shfl.sync.bfly.b32 f0, s0, 4, 0x1f, 0xffffffff; shfl.sync.bfly.b32 f1, s1, 4, 0x1f, 0xffffffff;\n"
        "fma.rn.bf16x2 pc0, pv0, pw0, ps1; fma.rn.bf16x2 pc1, pv1, pw1, ps1; fma.rn.bf16x2 pc2, pv2, pw2, ps1; fma.rn.bf16x2 pc3, pv3, pw3, ps1; fma.rn.bf16x2 pc4, pv4, pw4, ps1; fma.rn.bf16x2 pc5, pv5, pw5, ps1;\n"
        "fma.rn.bf16x2 pc6, pv6, pw0, ps3; fma.rn.bf16x2 pc7, pv7, pw1, ps3; fma.rn.bf16x2 pc8, pv8, pw2, ps3; fma.rn.bf16x2 pc9, pv9, pw3, ps3; fma.rn.bf16x2 pc10, pv10, pw4, ps3; fma.rn.bf16x2 pc11, pv11, pw5, ps3;\n"
        "fma.rn.bf16x2 pc12, pv12, pw0, ps5; fma.rn.bf16x2 pc13, pv13, pw1, ps5; fma.rn.bf16x2 pc14, pv14, pw2, ps5; fma.rn.bf16x2 pc15, pv15, pw3, ps5; fma.rn.bf16x2 pc16, pv16, pw4, ps5; fma.rn.bf16x2 pc17, pv17, pw5, ps5;\n"
        "fma.rn.bf16x2 pc18, pv18, pw0, ps7; fma.rn.bf16x2 pc19, pv19, pw1, ps7; fma.rn.bf16x2 pc20, pv20, pw2, ps7; fma.rn.bf16x2 pc21, pv21, pw3, ps7; fma.rn.bf16x2 pc22, pv22, pw4, ps7; fma.rn.bf16x2 pc23, pv23, pw5, ps7;\n"
        "fma.rn.bf16x2 pc0, pv6, pw6, pc0; fma.rn.bf16x2 pc1, pv7, pw7, pc1; fma.rn.bf16x2 pc2, pv8, pw8, pc2; fma.rn.bf16x2 pc3, pv9, pw9, pc3; fma.rn.bf16x2 pc4, pv10, pw10, pc4; fma.rn.bf16x2 pc5, pv11, pw11, pc5;\n"
        "fma.rn.bf16x2 pc6, pv12, pw6, pc6; fma.rn.bf16x2 pc7, pv13, pw7, pc7; fma.rn.bf16x2 pc8, pv14, pw8, pc8; fma.rn.bf16x2 pc9, pv15, pw9, pc9; fma.rn.bf16x2 pc10, pv16, pw10, pc10; fma.rn.bf16x2 pc11, pv17, pw11, pc11;\n"
        "fma.rn.bf16x2 pc12, pv18, pw6, pc12; fma.rn.bf16x2 pc13, pv19, pw7, pc13; fma.rn.bf16x2 pc14, pv20, pw8, pc14; fma.rn.bf16x2 pc15, pv21, pw9, pc15; fma.rn.bf16x2 pc16, pv22, pw10, pc16; fma.rn.bf16x2 pc17, pv23, pw11, pc17;\n"
        "fma.rn.bf16x2 pc18, pv24, pw6, pc18; fma.rn.bf16x2 pc19, pv25, pw7, pc19; fma.rn.bf16x2 pc20, pv26, pw8, pc20; fma.rn.bf16x2 pc21, pv27, pw9, pc21; fma.rn.bf16x2 pc22, pv28, pw10, pc22; fma.rn.bf16x2 pc23, pv29, pw11, pc23;\n"
        "fma.rn.bf16x2 pc0, pv12, pw12, pc0; fma.rn.bf16x2 pc1, pv13, pw13, pc1; fma.rn.bf16x2 pc2, pv14, pw14, pc2; fma.rn.bf16x2 pc3, pv15, pw15, pc3; fma.rn.bf16x2 pc4, pv16, pw16, pc4; fma.rn.bf16x2 pc5, pv17, pw17, pc5;\n"
        "fma.rn.bf16x2 pc6, pv18, pw12, pc6; fma.rn.bf16x2 pc7, pv19, pw13, pc7; fma.rn.bf16x2 pc8, pv20, pw14, pc8; fma.rn.bf16x2 pc9, pv21, pw15, pc9; fma.rn.bf16x2 pc10, pv22, pw16, pc10; fma.rn.bf16x2 pc11, pv23, pw17, pc11;\n"
        "fma.rn.bf16x2 pc12, pv24, pw12, pc12; fma.rn.bf16x2 pc13, pv25, pw13, pc13; fma.rn.bf16x2 pc14, pv26, pw14, pc14; fma.rn.bf16x2 pc15, pv27, pw15, pc15; fma.rn.bf16x2 pc16, pv28, pw16, pc16; fma.rn.bf16x2 pc17, pv29, pw17, pc17;\n"
        "fma.rn.bf16x2 pc18, pv30, pw12, pc18; fma.rn.bf16x2 pc19, pv31, pw13, pc19; fma.rn.bf16x2 pc20, pv32, pw14, pc20; fma.rn.bf16x2 pc21, pv33, pw15, pc21; fma.rn.bf16x2 pc22, pv34, pw16, pc22; fma.rn.bf16x2 pc23, pv35, pw17, pc23;\n"
        "add.f32 s0, s0, f0; add.f32 s1, s1, f1; mul.f32 s0, s0, 0fBC2AAAAB;\n"
        "neg.f32 f0, s0; fma.rn.f32 f0, f0, s0, %13; fma.rn.f32 f0, s1, 0f3C2AAAAB, f0; max.f32 f0, f0, %13;\n"
        "rsqrt.approx.ftz.f32 f0, f0; mul.f32 f0, f0, %14; cvt.rn.bf16x2.f32 tt, f0, 0f00000000; mov.b32 f0, tt;\n"
        "mul.f32 f1, s0, kq; mul.f32 f1, f1, f0; cvt.rn.bf16x2.f32 tt, f1, f0; add.f32 us, us, s0; cvt.rn.bf16x2.f32 mm, us, us;\n"
        "add.u32 ad, %7, so; st.shared.v2.b32 [ad], {tt, mm};\n"
        "add.u32 ad, %6, so; ld.shared.v4.b32 {ps0,ps1,ps2,ps3}, [ad]; ld.shared.v4.b32 {ps4,ps5,ps6,ps7}, [ad+16];\n"
        "mbarrier.try_wait.parity.shared::cta.b64 pw, [t+231264], 0;\n"
        "N0:\n"
        "@!pw bra.uni SPIN;\n"
        "BACK:\n"
        "add.u32 ad, %0, so; ld.shared.v4.b32 {pv0,pv1,pv2,pv3}, [ad+0];\n"
        "add.u32 ad, %1, so; ld.shared.v2.b32 {pv4,pv5}, [ad+0];\n"
        "add.u32 ad, %0, so; ld.shared.v4.b32 {pv6,pv7,pv8,pv9}, [ad+192];\n"
        "add.u32 ad, %1, so; ld.shared.v2.b32 {pv10,pv11}, [ad+192];\n"
        "mov.b32 {xl, xh}, ps0; mov.b32 rr, {xl, xl}; mov.b32 mm, {xh, xh}; fma.rn.bf16x2 pa0, pa0, rr, mm; fma.rn.bf16x2 pa1, pa1, rr, mm; fma.rn.bf16x2 pa2, pa2, rr, mm; fma.rn.bf16x2 pa3, pa3, rr, mm; fma.rn.bf16x2 pa4, pa4, rr, mm; fma.rn.bf16x2 pa5, pa5, rr, mm;\n"
        "and.b32 m0, pa0, 0x7fff7fff; and.b32 m1, pa1, 0x7fff7fff; and.b32 m2, pa2, 0x7fff7fff; and.b32 m3, pa3, 0x7fff7fff; and.b32 m4, pa4, 0x7fff7fff; and.b32 m5, pa5, 0x7fff7fff;\n"
        "mad.lo.u32 y0, m0, 7, pa0; mad.lo.u32 y1, m1, 7, pa1; mad.lo.u32 y2, m2, 7, pa2; mad.lo.u32 y3, m3, 7, pa3; mad.lo.u32 y4, m4, 7, pa4; mad.lo.u32 y5, m5, 7, pa5;\n"
        "add.u32 ad, %2, so; st.shared.v4.b32 [ad+0], {y0,y1,y2,y3};\n"
        "add.u32 ad, %4, so; st.shared.v2.b32 [ad+0], {y4,y5};\n"
        "N1:\n"
        "add.u32 ad, %0, so; ld.shared.v4.b32 {pv12,pv13,pv14,pv15}, [ad+384];\n"
        "add.u32 ad, %1, so; ld.shared.v2.b32 {pv16,pv17}, [ad+384];\n"
        "add.u32 ad, %0, so; ld.shared.v4.b32 {pv18,pv19,pv20,pv21}, [ad+576];\n"
        "add.u32 ad, %1, so; ld.shared.v2.b32 {pv22,pv23}, [ad+576];\n"
        "mov.b32 {xl, xh}, ps2; mov.b32 rr, {xl, xl}; mov.b32 mm, {xh, xh}; fma.rn.bf16x2 pa6, pa6, rr, mm; fma.rn.bf16x2 pa7, pa7, rr, mm; fma.rn.bf16x2 pa8, pa8, rr, mm; fma.rn.bf16x2 pa9, pa9, rr, mm; fma.rn.bf16x2 pa10, pa10, rr, mm; fma.rn.bf16x2 pa11, pa11, rr, mm;\n"
        "and.b32 m0, pa6, 0x7fff7fff; and.b32 m1, pa7, 0x7fff7fff; and.b32 m2, pa8, 0x7fff7fff; and.b32 m3, pa9, 0x7fff7fff; and.b32 m4, pa10, 0x7fff7fff; and.b32 m5, pa11, 0x7fff7fff;\n"
        "mad.lo.u32 y0, m0, 7, pa6; mad.lo.u32 y1, m1, 7, pa7; mad.lo.u32 y2, m2, 7, pa8; mad.lo.u32 y3, m3, 7, pa9; mad.lo.u32 y4, m4, 7, pa10; mad.lo.u32 y5, m5, 7, pa11;\n"
        "add.u32 ad, %3, so; st.shared.v4.b32 [ad+0], {y0,y1,y2,y3};\n"
        "add.u32 ad, %5, so; st.shared.v2.b32 [ad+0], {y4,y5};\n"
        "N2:\n"
        "add.u32 ad, %0, so; ld.shared.v4.b32 {pv24,pv25,pv26,pv27}, [ad+768];\n"
        "add.u32 ad, %1, so; ld.shared.v2.b32 {pv28,pv29}, [ad+768];\n"
        "mov.b32 {xl, xh}, ps4; mov.b32 rr, {xl, xl}; mov.b32 mm, {xh, xh}; fma.rn.bf16x2 pa12, pa12, rr, mm; fma.rn.bf16x2 pa13, pa13, rr, mm; fma.rn.bf16x2 pa14, pa14, rr, mm; fma.rn.bf16x2 pa15, pa15, rr, mm; fma.rn.bf16x2 pa16, pa16, rr, mm; fma.rn.bf16x2 pa17, pa17, rr, mm;\n"
        "and.b32 m0, pa12, 0x7fff7fff; and.b32 m1, pa13, 0x7fff7fff; and.b32 m2, pa14, 0x7fff7fff; and.b32 m3, pa15, 0x7fff7fff; and.b32 m4, pa16, 0x7fff7fff; and.b32 m5, pa17, 0x7fff7fff;\n"
        "mad.lo.u32 y0, m0, 7, pa12; mad.lo.u32 y1, m1, 7, pa13; mad.lo.u32 y2, m2, 7, pa14; mad.lo.u32 y3, m3, 7, pa15; mad.lo.u32 y4, m4, 7, pa16; mad.lo.u32 y5, m5, 7, pa17;\n"
        "add.u32 ad, %2, so; st.shared.v4.b32 [ad+2048], {y0,y1,y2,y3};\n"
        "add.u32 ad, %4, so; st.shared.v2.b32 [ad+1024], {y4,y5};\n"
        "N3:\n"
        "add.u32 ad, %0, so; ld.shared.v4.b32 {pv30,pv31,pv32,pv33}, [ad+960];\n"
        "add.u32 ad, %1, so; ld.shared.v2.b32 {pv34,pv35}, [ad+960];\n"
        "mov.b32 {xl, xh}, ps6; mov.b32 rr, {xl, xl}; mov.b32 mm, {xh, xh}; fma.rn.bf16x2 pa18, pa18, rr, mm; fma.rn.bf16x2 pa19, pa19, rr, mm; fma.rn.bf16x2 pa20, pa20, rr, mm; fma.rn.bf16x2 pa21, pa21, rr, mm; fma.rn.bf16x2 pa22, pa22, rr, mm; fma.rn.bf16x2 pa23, pa23, rr, mm;\n"
        "and.b32 m0, pa18, 0x7fff7fff; and.b32 m1, pa19, 0x7fff7fff; and.b32 m2, pa20, 0x7fff7fff; and.b32 m3, pa21, 0x7fff7fff; and.b32 m4, pa22, 0x7fff7fff; and.b32 m5, pa23, 0x7fff7fff;\n"
        "mad.lo.u32 y0, m0, 7, pa18; mad.lo.u32 y1, m1, 7, pa19; mad.lo.u32 y2, m2, 7, pa20; mad.lo.u32 y3, m3, 7, pa21; mad.lo.u32 y4, m4, 7, pa22; mad.lo.u32 y5, m5, 7, pa23;\n"
        "add.u32 ad, %3, so; st.shared.v4.b32 [ad+2048], {y0,y1,y2,y3};\n"
        "add.u32 ad, %5, so; st.shared.v2.b32 [ad+1024], {y4,y5};\n"
        "add.u32 so, so, 26624; setp.eq.u32 pr, so, 79872; selp.u32 so, 0, so, pr;\n"
        "add.u32 t, t, 8; setp.lt.u32 pe, t, 256;\n"
        "@pe bra.uni LOOP;\n"
        "bra.uni DONE;\n"
        "SPIN: mov.u32 cnt, 0;\n"
        "SPINL:\n"
        "mbarrier.try_wait.parity.shared::cta.b64 pw, [t+231264], 0;\n"
        "@pw bra.uni BACK;\n"
        "add.u32 cnt, cnt, 1; setp.lt.u32 pw, cnt, 0x100000;\n"
        "@pw bra.uni SPINL;\n"
        "trap;\n"
        "RARE:\n"
        "ld.volatile.shared.u32 tt, [%6];\n"
        "mov.b32 pa0, tt; mov.b32 pa1, tt; mov.b32 pa2, tt; mov.b32 pa3, tt; mov.b32 pa4, tt; mov.b32 pa5, tt; mov.b32 pa6, tt; mov.b32 pa7, tt; mov.b32 pa8, tt; mov.b32 pa9, tt; mov.b32 pa10, tt; mov.b32 pa11, tt;\n"
        "mov.b32 pa12, tt; mov.b32 pa13, tt; mov.b32 pa14, tt; mov.b32 pa15, tt; mov.b32 pa16, tt; mov.b32 pa17, tt; mov.b32 pa18, tt; mov.b32 pa19, tt; mov.b32 pa20, tt; mov.b32 pa21, tt; mov.b32 pa22, tt; mov.b32 pa23, tt;\n"
        "mov.b32 pb0, tt; mov.b32 pb1, tt; mov.b32 pb2, tt; mov.b32 pb3, tt; mov.b32 pb4, tt; mov.b32 pb5, tt; mov.b32 pb6, tt; mov.b32 pb7, tt; mov.b32 pb8, tt; mov.b32 pb9, tt; mov.b32 pb10, tt; mov.b32 pb11, tt;\n"
        "mov.b32 pb12, tt; mov.b32 pb13, tt; mov.b32 pb14, tt; mov.b32 pb15, tt; mov.b32 pb16, tt; mov.b32 pb17, tt; mov.b32 pb18, tt; mov.b32 pb19, tt; mov.b32 pb20, tt; mov.b32 pb21, tt; mov.b32 pb22, tt; mov.b32 pb23, tt;\n"
        "mov.b32 pc0, tt; mov.b32 pc1, tt; mov.b32 pc2, tt; mov.b32 pc3, tt; mov.b32 pc4, tt; mov.b32 pc5, tt; mov.b32 pc6, tt; mov.b32 pc7, tt; mov.b32 pc8, tt; mov.b32 pc9, tt; mov.b32 pc10, tt; mov.b32 pc11, tt;\n"
        "mov.b32 pc12, tt; mov.b32 pc13, tt; mov.b32 pc14, tt; mov.b32 pc15, tt; mov.b32 pc16, tt; mov.b32 pc17, tt; mov.b32 pc18, tt; mov.b32 pc19, tt; mov.b32 pc20, tt; mov.b32 pc21, tt; mov.b32 pc22, tt; mov.b32 pc23, tt;\n"
        "mov.b32 ps0, tt; mov.b32 ps1, tt; mov.b32 ps2, tt; mov.b32 ps3, tt; mov.b32 ps4, tt; mov.b32 ps5, tt; mov.b32 ps6, tt; mov.b32 ps7, tt; mov.b32 pq0, tt; mov.b32 pq1, tt; mov.b32 pq2, tt; mov.b32 pq3, tt;\n"
        "ld.volatile.shared.v2.b32 {pw1, pw0}, [%6]; xor.b32 tt, tt, pw1;\n"
        "ld.volatile.shared.v2.b32 {pw3, pw2}, [%6]; xor.b32 tt, tt, pw3;\n"
        "ld.volatile.shared.v2.b32 {pw5, pw4}, [%6]; xor.b32 tt, tt, pw5;\n"
        "ld.volatile.shared.v2.b32 {pw7, pw6}, [%6]; xor.b32 tt, tt, pw7;\n"
        "ld.volatile.shared.v2.b32 {pw9, pw8}, [%6]; xor.b32 tt, tt, pw9;\n"
        "ld.volatile.shared.v2.b32 {pw11, pw10}, [%6]; xor.b32 tt, tt, pw11;\n"
        "ld.volatile.shared.v2.b32 {pw13, pw12}, [%6]; xor.b32 tt, tt, pw13;\n"
        "ld.volatile.shared.v2.b32 {pw15, pw14}, [%6]; xor.b32 tt, tt, pw15;\n"
        "ld.volatile.shared.v2.b32 {pw17, pw16}, [%6]; xor.b32 tt, tt, pw17;\n"
        "ld.volatile.shared.v2.b32 {pw19, pw18}, [%6]; xor.b32 tt, tt, pw19;\n"
        "ld.volatile.shared.v2.b32 {pw21, pw20}, [%6]; xor.b32 tt, tt, pw21;\n"
        "ld.volatile.shared.v2.b32 {pw23, pw22}, [%6]; xor.b32 tt, tt, pw23;\n"
        "ld.volatile.shared.v2.b32 {pw25, pw24}, [%6]; xor.b32 tt, tt, pw25;\n"
        "ld.volatile.shared.v2.b32 {pw27, pw26}, [%6]; xor.b32 tt, tt, pw27;\n"
        "ld.volatile.shared.v2.b32 {pw29, pw28}, [%6]; xor.b32 tt, tt, pw29;\n"
        "ld.volatile.shared.v2.b32 {pw31, pw30}, [%6]; xor.b32 tt, tt, pw31;\n"
        "ld.volatile.shared.v2.b32 {pw33, pw32}, [%6]; xor.b32 tt, tt, pw33;\n"
        "ld.volatile.shared.v2.b32 {pw35, pw34}, [%6]; xor.b32 tt, tt, pw35;\n"
        "ld.volatile.shared.v2.b32 {pw37, pw36}, [%6]; xor.b32 tt, tt, pw37;\n"
        "ld.volatile.shared.v2.b32 {pw39, pw38}, [%6]; xor.b32 tt, tt, pw39;\n"
        "ld.volatile.shared.v2.b32 {pw41, pw40}, [%6]; xor.b32 tt, tt, pw41;\n"
        "ld.volatile.shared.v2.b32 {pw43, pw42}, [%6]; xor.b32 tt, tt, pw43;\n"
        "ld.volatile.shared.v2.b32 {pw45, pw44}, [%6]; xor.b32 tt, tt, pw45;\n"
        "ld.volatile.shared.v2.b32 {pw47, pw46}, [%6]; xor.b32 tt, tt, pw47;\n"
        "ld.volatile.shared.v2.b32 {pw49, pw48}, [%6]; xor.b32 tt, tt, pw49;\n"
        "ld.volatile.shared.v2.b32 {pw51, pw50}, [%6]; xor.b32 tt, tt, pw51;\n"
        "ld.volatile.shared.v2.b32 {pw53, pw52}, [%6]; xor.b32 tt, tt, pw53;\n"
        "mov.b32 us, tt; setp.ne.u32 pw, %15, 7;\n"
        "wgmma.fence.sync.aligned;\n"
        "setp.eq.u32 pr, %15, 1000; @pr bra.uni B0;\n"
        "setp.eq.u32 pr, %15, 1001; @pr bra.uni B1;\n"
        "setp.eq.u32 pr, %15, 1002; @pr bra.uni C0;\n"
        "setp.eq.u32 pr, %15, 1003; @pr bra.uni N0;\n"
        "setp.eq.u32 pr, %15, 1004; @pr bra.uni N1;\n"
        "setp.eq.u32 pr, %15, 1005; @pr bra.uni N2;\n"
        "setp.eq.u32 pr, %15, 1006; @pr bra.uni N3;\n"
        "trap;\n"
        "DONE:\n"
        ASM_TRC("t")
        "fence.proxy.async.shared::cta;\n"
        "@pl mbarrier.arrive.shared::cta.b64 _, [t+231544];\n"
        "}\n"
        :: "r"(sb + SM_X + c.xoff[0]), "r"(sb + SM_X + c.xoff[1]), "r"(sb + SM_Y1 + c.yoff[0][0]), "r"(sb + SM_Y1 + c.yoff[0][1]),
           "r"(sb + SM_Y1 + c.yoff[1][0]), "r"(sb + SM_Y1 + c.yoff[1][1]), "r"(c.stat), "r"(c.own), "r"(c.lane),
           "l"(prm.sel[0]), "l"(prm.sel[1]), "l"(prm.sel[2]), "r"(prm.ydesc), "f"(LN_EPS_SCALED), "f"(RSTD_SCALE), "r"(prm.w1desc)
        : "memory");
}

__device__ __forceinline__ void produce(const Producer& c, const Params& prm) {
    uint32_t B[24], C[24];
    uint32_t st[8];
    uint32_t v[6][6];
    uint32_t ws[6];
#pragma unroll
    for (int u = 0; u < 6; u++) {
        ws[u] = c.w[0][u];
#pragma unroll
        for (int t = 1; t < 9; t++) ws[u] = bf2_add(ws[u], c.w[t][u]);
    }
    SMARK(2);
#pragma unroll 1
    for (int i = loop_init<0>(), so = loop_init<0>();; i++, so += SLOT_BYTES) {
        mbar_wait_c<0>(sb + SM_GO + i * 8);
        SMARK(4 + i);
        load_x(v, c, sb + SM_X + so);
        if (i == 2) break;
        if (so == 0) {
            const uint32_t p = bf2_add(bf2_fma(v[2][2], ws[2], bf2_fma(v[2][1], ws[1], bf2_mul(v[2][0], ws[0]))),
                                       bf2_fma(v[2][5], ws[5], bf2_fma(v[2][4], ws[4], bf2_mul(v[2][3], ws[3]))));
            float e = quad_sum(bf_lo(p) + bf_hi(p));
            e = (e + __shfl_xor_sync(0xffffffffu, e, 4)) * (-1.0f / CH);
            st[1] = st[3] = st[5] = st[7] = pack_bf2(e, e);
#pragma unroll
            for (int k = 0; k < NX; k++) sts32(c.own + k * SLOT_BYTES + 4, st[1]);
        } else {
            conv_row<1, 1>(B, C, v, c);
        }
        conv_row<0, 0>(C, st, v, c);
        fence_async_smem();
        asm volatile("bar.arrive %0, 160;" ::"r"(6 + i) : "memory");
    }
    asm volatile(".reg .b32 pw<54>, pb<24>, pc<24>, pv<36>, ps<8>;");
    hand_over<0>(c, B, C, v);
    asm volatile("mov.b32 ps1, %0; mov.b32 ps3, %1; mov.b32 ps5, %2; mov.b32 ps7, %3;" ::"r"(st[1]), "r"(st[3]), "r"(st[5]), "r"(st[7]));
    SMARK(7);
    produce_tiles(c, prm);
    mbar_arrive_if(sb + SM_YFULL + ROWS_PER_CTA * 8, c.lane == 0);
}

struct Duty {
    const char* g;
    const char* zeros;
    long long step;
    uint32_t s, bytes;
    int end, zero;
};
__device__ __forceinline__ Duty make_duty(const Params& prm, int wg, int w) {
    const RowCopy rc = row_copy(prm);
    Duty d;
    d.g = (w == 2 ? rc.y0 : rc.x0 + (w == 0 ? rc.cut0 : w == 1 ? 32 * 192 : 192)) +
          (wg + (w == 2 ? 0 : w < 2 ? 2 * NX : 2 * NX + L2_AHEAD)) * rc.stride;
    d.step = NX * rc.stride;
    d.s = wg * SLOT_BYTES + (w == 2 ? sb + SM_Y1 : sb + SM_X + (w == 0 ? rc.cut0 : XHALF_B));
    d.bytes = w >= 2 ? TILE_BYTES : XHALF_BYTES - (w == 0 ? rc.cut0 : rc.cut1);
    d.end = w == 2 ? ROWS_PER_CTA : w < 2 ? STEPS + 1 - 2 * NX : rc.last + 1 - 2 * NX - L2_AHEAD;
    d.zero = rc.last + 1 - 2 * NX;
    d.zeros = rc.zeros;
    return d;
}

static_assert(sb + SM_BAR == 230800 && sb + SM_YFULL == 231552 && sb + SM_GO == 231240 && SLOT_BYTES == 26624 && sb + SM_GAMMA == 229248 &&
              SM_BETA == SM_GAMMA + 768 && SM_W2 == 73728 && sb + SM_BUF3 == 187392 && BAR_W2 == 9 && BAR_W1B == 10, "layout");
__device__ __forceinline__ void consume(float (&acc)[2][2], uint32_t w1t, uint32_t yd, uint32_t wd, uint32_t own_slot, const Duty& d,
                                        uint32_t role, uint32_t lane, const Params& prm) {
    asm volatile(
        "{\n"
        ".reg .b32 z<32>, w<44>, p, a<4>, lo<2>, hi<2>, t, g, q<4>, dl, dh, n, so, c, tt, cnt, f0, f1;\n"
        ".reg .b16 xl, xh, xr;\n"
        ".reg .b64 ds<6>, wd, gp, src;\n"
        ".reg .pred pt, pf, pr, pw, pl, pe;\n"
        "setp.ne.b32 pt, 1, 0; setp.ne.b32 pf, 0, 0; setp.eq.u32 pl, %15, 0;\n"
        "mov.b32 c, 0x40D940D9;\n"
        "ldmatrix.sync.aligned.m8n8.x4.trans.shared.b16 {w0,w1,w2,w3}, [%4+0];\n"
        "ldmatrix.sync.aligned.m8n8.x4.trans.shared.b16 {w4,w5,w6,w7}, [%4+2048];\n"
        "ldmatrix.sync.aligned.m8n8.x4.trans.shared.b16 {w8,w9,w10,w11}, [%4+4096];\n"
        "ldmatrix.sync.aligned.m8n8.x4.trans.shared.b16 {w12,w13,w14,w15}, [%4+6144];\n"
        "ldmatrix.sync.aligned.m8n8.x4.trans.shared.b16 {w16,w17,w18,w19}, [%4+8192];\n"
        "ldmatrix.sync.aligned.m8n8.x4.trans.shared.b16 {w20,w21,w22,w23}, [%4+10240];\n"
        "shl.b32 f0, w0, 16; and.b32 f1, w0, 0xffff0000; cvt.rn.f16x2.f32 w0, f1, f0; shl.b32 f0, w1, 16; and.b32 f1, w1, 0xffff0000; cvt.rn.f16x2.f32 w1, f1, f0; shl.b32 f0, w2, 16; and.b32 f1, w2, 0xffff0000; cvt.rn.f16x2.f32 w2, f1, f0; shl.b32 f0, w3, 16; and.b32 f1, w3, 0xffff0000; cvt.rn.f16x2.f32 w3, f1, f0;\n"
        "stmatrix.sync.aligned.m8n8.x4.trans.shared.b16 [%4+0], {w0,w1,w2,w3};\n"
        "shl.b32 f0, w4, 16; and.b32 f1, w4, 0xffff0000; cvt.rn.f16x2.f32 w4, f1, f0; shl.b32 f0, w5, 16; and.b32 f1, w5, 0xffff0000; cvt.rn.f16x2.f32 w5, f1, f0; shl.b32 f0, w6, 16; and.b32 f1, w6, 0xffff0000; cvt.rn.f16x2.f32 w6, f1, f0; shl.b32 f0, w7, 16; and.b32 f1, w7, 0xffff0000; cvt.rn.f16x2.f32 w7, f1, f0;\n"
        "stmatrix.sync.aligned.m8n8.x4.trans.shared.b16 [%4+2048], {w4,w5,w6,w7};\n"
        "shl.b32 f0, w8, 16; and.b32 f1, w8, 0xffff0000; cvt.rn.f16x2.f32 w8, f1, f0; shl.b32 f0, w9, 16; and.b32 f1, w9, 0xffff0000; cvt.rn.f16x2.f32 w9, f1, f0; shl.b32 f0, w10, 16; and.b32 f1, w10, 0xffff0000; cvt.rn.f16x2.f32 w10, f1, f0; shl.b32 f0, w11, 16; and.b32 f1, w11, 0xffff0000; cvt.rn.f16x2.f32 w11, f1, f0;\n"
        "stmatrix.sync.aligned.m8n8.x4.trans.shared.b16 [%4+4096], {w8,w9,w10,w11};\n"
        "shl.b32 f0, w12, 16; and.b32 f1, w12, 0xffff0000; cvt.rn.f16x2.f32 w12, f1, f0; shl.b32 f0, w13, 16; and.b32 f1, w13, 0xffff0000; cvt.rn.f16x2.f32 w13, f1, f0; shl.b32 f0, w14, 16; and.b32 f1, w14, 0xffff0000; cvt.rn.f16x2.f32 w14, f1, f0; shl.b32 f0, w15, 16; and.b32 f1, w15, 0xffff0000; cvt.rn.f16x2.f32 w15, f1, f0;\n"
        "stmatrix.sync.aligned.m8n8.x4.trans.shared.b16 [%4+6144], {w12,w13,w14,w15};\n"
        "shl.b32 f0, w16, 16; and.b32 f1, w16, 0xffff0000; cvt.rn.f16x2.f32 w16, f1, f0; shl.b32 f0, w17, 16; and.b32 f1, w17, 0xffff0000; cvt.rn.f16x2.f32 w17, f1, f0; shl.b32 f0, w18, 16; and.b32 f1, w18, 0xffff0000; cvt.rn.f16x2.f32 w18, f1, f0; shl.b32 f0, w19, 16; and.b32 f1, w19, 0xffff0000; cvt.rn.f16x2.f32 w19, f1, f0;\n"
        "stmatrix.sync.aligned.m8n8.x4.trans.shared.b16 [%4+8192], {w16,w17,w18,w19};\n"
        "shl.b32 f0, w20, 16; and.b32 f1, w20, 0xffff0000; cvt.rn.f16x2.f32 w20, f1, f0; shl.b32 f0, w21, 16; and.b32 f1, w21, 0xffff0000; cvt.rn.f16x2.f32 w21, f1, f0; shl.b32 f0, w22, 16; and.b32 f1, w22, 0xffff0000; cvt.rn.f16x2.f32 w22, f1, f0; shl.b32 f0, w23, 16; and.b32 f1, w23, 0xffff0000; cvt.rn.f16x2.f32 w23, f1, f0;\n"
        "stmatrix.sync.aligned.m8n8.x4.trans.shared.b16 [%4+10240], {w20,w21,w22,w23};\n"
        "mov.u32 tt, 230880; mbarrier.try_wait.parity.shared::cta.b64 pw, [tt], 0;\n"
        "@!pw bra.uni SPINW;\n"
        "BACKW:\n"
        "ldmatrix.sync.aligned.m8n8.x4.trans.shared.b16 {z0,z1,z2,z3}, [%4+22528];\n"
        "ldmatrix.sync.aligned.m8n8.x4.trans.shared.b16 {w24,w25,w26,w27}, [%4+12288];\n"
        "ldmatrix.sync.aligned.m8n8.x4.trans.shared.b16 {w28,w29,w30,w31}, [%4+14336];\n"
        "ldmatrix.sync.aligned.m8n8.x4.trans.shared.b16 {w32,w33,w34,w35}, [%4+16384];\n"
        "ldmatrix.sync.aligned.m8n8.x4.trans.shared.b16 {w36,w37,w38,w39}, [%4+18432];\n"
        "ldmatrix.sync.aligned.m8n8.x4.trans.shared.b16 {w40,w41,w42,w43}, [%4+20480];\n"
        "shl.b32 f0, z0, 16; and.b32 f1, z0, 0xffff0000; cvt.rn.f16x2.f32 z0, f1, f0; shl.b32 f0, z1, 16; and.b32 f1, z1, 0xffff0000; cvt.rn.f16x2.f32 z1, f1, f0; shl.b32 f0, z2, 16; and.b32 f1, z2, 0xffff0000; cvt.rn.f16x2.f32 z2, f1, f0; shl.b32 f0, z3, 16; and.b32 f1, z3, 0xffff0000; cvt.rn.f16x2.f32 z3, f1, f0;\n"
        "stmatrix.sync.aligned.m8n8.x4.trans.shared.b16 [%4+22528], {z0,z1,z2,z3};\n"
        "shl.b32 f0, w24, 16; and.b32 f1, w24, 0xffff0000; cvt.rn.f16x2.f32 w24, f1, f0; shl.b32 f0, w25, 16; and.b32 f1, w25, 0xffff0000; cvt.rn.f16x2.f32 w25, f1, f0; shl.b32 f0, w26, 16; and.b32 f1, w26, 0xffff0000; cvt.rn.f16x2.f32 w26, f1, f0; shl.b32 f0, w27, 16; and.b32 f1, w27, 0xffff0000; cvt.rn.f16x2.f32 w27, f1, f0;\n"
        "stmatrix.sync.aligned.m8n8.x4.trans.shared.b16 [%4+12288], {w24,w25,w26,w27};\n"
        "shl.b32 f0, w28, 16; and.b32 f1, w28, 0xffff0000; cvt.rn.f16x2.f32 w28, f1, f0; shl.b32 f0, w29, 16; and.b32 f1, w29, 0xffff0000; cvt.rn.f16x2.f32 w29, f1, f0; shl.b32 f0, w30, 16; and.b32 f1, w30, 0xffff0000; cvt.rn.f16x2.f32 w30, f1, f0; shl.b32 f0, w31, 16; and.b32 f1, w31, 0xffff0000; cvt.rn.f16x2.f32 w31, f1, f0;\n"
        "stmatrix.sync.aligned.m8n8.x4.trans.shared.b16 [%4+14336], {w28,w29,w30,w31};\n"
        "shl.b32 f0, w32, 16; and.b32 f1, w32, 0xffff0000; cvt.rn.f16x2.f32 w32, f1, f0; shl.b32 f0, w33, 16; and.b32 f1, w33, 0xffff0000; cvt.rn.f16x2.f32 w33, f1, f0; shl.b32 f0, w34, 16; and.b32 f1, w34, 0xffff0000; cvt.rn.f16x2.f32 w34, f1, f0; shl.b32 f0, w35, 16; and.b32 f1, w35, 0xffff0000; cvt.rn.f16x2.f32 w35, f1, f0;\n"
        "stmatrix.sync.aligned.m8n8.x4.trans.shared.b16 [%4+16384], {w32,w33,w34,w35};\n"
        "shl.b32 f0, w36, 16; and.b32 f1, w36, 0xffff0000; cvt.rn.f16x2.f32 w36, f1, f0; shl.b32 f0, w37, 16; and.b32 f1, w37, 0xffff0000; cvt.rn.f16x2.f32 w37, f1, f0; shl.b32 f0, w38, 16; and.b32 f1, w38, 0xffff0000; cvt.rn.f16x2.f32 w38, f1, f0; shl.b32 f0, w39, 16; and.b32 f1, w39, 0xffff0000; cvt.rn.f16x2.f32 w39, f1, f0;\n"
        "stmatrix.sync.aligned.m8n8.x4.trans.shared.b16 [%4+18432], {w36,w37,w38,w39};\n"
        "shl.b32 f0, w40, 16; and.b32 f1, w40, 0xffff0000; cvt.rn.f16x2.f32 w40, f1, f0; shl.b32 f0, w41, 16; and.b32 f1, w41, 0xffff0000; cvt.rn.f16x2.f32 w41, f1, f0; shl.b32 f0, w42, 16; and.b32 f1, w42, 0xffff0000; cvt.rn.f16x2.f32 w42, f1, f0; shl.b32 f0, w43, 16; and.b32 f1, w43, 0xffff0000; cvt.rn.f16x2.f32 w43, f1, f0;\n"
        "stmatrix.sync.aligned.m8n8.x4.trans.shared.b16 [%4+20480], {w40,w41,w42,w43};\n"
        "fence.proxy.async.shared::cta;\n"
        ASM_SMARK
        "mov.b32 p, 0; mov.b32 t, 0; mov.b32 g, 0; mov.b32 a0, 0; mov.b32 a1, 0; mov.b32 a2, 0; mov.b32 a3, 0; mov.b32 lo0, 0; mov.b32 lo1, 0; mov.b32 hi0, 0; mov.b32 hi1, 0; mov.b32 q0, 0; mov.b32 q1, 0; mov.b32 q2, 0; mov.b32 q3, 0;\n"
        "mov.b32 z16, 0; mov.b32 z17, 0; mov.b32 z18, 0; mov.b32 z19, 0; mov.b32 z20, 0; mov.b32 z21, 0; mov.b32 z22, 0; mov.b32 z23, 0; mov.b32 z24, 0; mov.b32 z25, 0; mov.b32 z26, 0; mov.b32 z27, 0; mov.b32 z28, 0; mov.b32 z29, 0; mov.b32 z30, 0; mov.b32 z31, 0;\n"
        "mov.f32 %0, 0f00000000; mov.f32 %1, 0f00000000; mov.f32 %2, 0f00000000; mov.f32 %3, 0f00000000;\n"
        "mov.u32 n, 0; mov.u32 so, 0; mov.b64 gp, %8; mov.b64 wd, {%6, 0x40000040};\n"
        "mov.b64 ds0, %20; add.s64 ds1, ds0, 2; add.s64 ds2, ds0, 4; add.s64 ds3, ds0, 6; mov.b64 ds4, %21; add.s64 ds5, ds4, 2;\n"
        "setp.eq.u32 pr, %7, 53248; setp.lt.and.u32 pr, %13, 2, pr;\n"
        "@!pr bra.uni ROW5;\n"
        "mbarrier.try_wait.parity.shared::cta.b64 pw, [n+231544], 0;\n"
        "@!pw bra.uni SPIN5;\n"
        "BACK5:\n"
        "sub.s64 src, gp, %16; mov.u32 tt, 231280;\n"
        "elect.sync _|pr, 0xffffffff;\n"
        "@pr mbarrier.arrive.expect_tx.shared::cta.b64 _, [tt], %10;\n"
        "@pr cp.async.bulk.shared::cluster.global.mbarrier::complete_tx::bytes [%9], [src], %10, [tt];\n"
        "ROW5:\n"
        "mbarrier.try_wait.parity.shared::cta.b64 pw, [n+231552], 0;\n"
        "@!pw bra.uni SPIN0;\n"
        "BACK0:\n"
        ASM_TS
        "wgmma.fence.sync.aligned;\n"
        "wgmma.mma_async.sync.aligned.m64n64k16.f16.f16.f16 {z0,z1,z2,z3,z4,z5,z6,z7,z8,z9,z10,z11,z12,z13,z14,z15}, {w0,w1,w2,w3}, ds0, pf, 1, 1, 0;\n"
        "wgmma.mma_async.sync.aligned.m64n64k16.f16.f16.f16 {z0,z1,z2,z3,z4,z5,z6,z7,z8,z9,z10,z11,z12,z13,z14,z15}, {w4,w5,w6,w7}, ds1, pt, 1, 1, 0;\n"
        "wgmma.mma_async.sync.aligned.m64n64k16.f16.f16.f16 {z0,z1,z2,z3,z4,z5,z6,z7,z8,z9,z10,z11,z12,z13,z14,z15}, {w8,w9,w10,w11}, ds2, pt, 1, 1, 0;\n"
        "wgmma.fence.sync.aligned;\n"
        "wgmma.mma_async.sync.aligned.m64n64k16.f16.f16.f16 {z0,z1,z2,z3,z4,z5,z6,z7,z8,z9,z10,z11,z12,z13,z14,z15}, {w12,w13,w14,w15}, ds3, pt, 1, 1, 0;\n"
        "wgmma.mma_async.sync.aligned.m64n64k16.f16.f16.f16 {z0,z1,z2,z3,z4,z5,z6,z7,z8,z9,z10,z11,z12,z13,z14,z15}, {w16,w17,w18,w19}, ds4, pt, 1, 1, 0;\n"
        "wgmma.mma_async.sync.aligned.m64n64k16.f16.f16.f16 {z0,z1,z2,z3,z4,z5,z6,z7,z8,z9,z10,z11,z12,z13,z14,z15}, {w20,w21,w22,w23}, ds5, pt, 1, 1, 0;\n"
        "wgmma.commit_group.sync.aligned;\n"
        "setp.eq.u32 pr, so, %7;\n"
        "@pr bra.uni DUTY;\n"
        "TOP:\n"
        ASM_TRC("n")
        "wgmma.wait_group.sync.aligned 0;\n"
        "mov.b32 {xl, xh}, a2; tanh.approx.f16 xr, xh; cvt.u32.u16 hi0, xr; mul.rn.f16x2 a3, z31, p; fma.rn.f16x2 p, z0, z0, c; fma.rn.f16x2 q3, g, g, q3; fma.rn.f16x2 g, z28, t, z28; prmt.b32 t, lo1, hi1, 0x5410; tanh.approx.f16 xr, xl; cvt.u32.u16 lo0, xr;\n"
        "B31:\n"
        "mov.b32 {xl, xh}, a3; tanh.approx.f16 xr, xh; cvt.u32.u16 hi1, xr; mul.rn.f16x2 a0, z0, p; fma.rn.f16x2 p, z1, z1, c; fma.rn.f16x2 q2, g, g, q2; fma.rn.f16x2 g, z29, t, z29; prmt.b32 t, lo0, hi0, 0x5410; tanh.approx.f16 xr, xl; cvt.u32.u16 lo1, xr;\n"
        "B0:\n"
        "mov.b32 {xl, xh}, a0; tanh.approx.f16 xr, xh; cvt.u32.u16 hi0, xr; mul.rn.f16x2 a1, z1, p; fma.rn.f16x2 p, z2, z2, c; fma.rn.f16x2 q3, g, g, q3; fma.rn.f16x2 g, z30, t, z30; prmt.b32 t, lo1, hi1, 0x5410; tanh.approx.f16 xr, xl; cvt.u32.u16 lo0, xr;\n"
        "B1:\n"
        "mov.b32 {xl, xh}, a1; tanh.approx.f16 xr, xh; cvt.u32.u16 hi1, xr; mul.rn.f16x2 a2, z2, p; fma.rn.f16x2 p, z3, z3, c; fma.rn.f16x2 q2, g, g, q2; fma.rn.f16x2 g, z31, t, z31; prmt.b32 t, lo0, hi0, 0x5410; tanh.approx.f16 xr, xl; cvt.u32.u16 lo1, xr;\n"
        "B2:\n"
        "wgmma.fence.sync.aligned;\n"
        "wgmma.mma_async.sync.aligned.m64n64k16.f16.f16.f16 {z16,z17,z18,z19,z20,z21,z22,z23,z24,z25,z26,z27,z28,z29,z30,z31}, {w24,w25,w26,w27}, ds0, pf, 1, 1, 0;\n"
        "wgmma.mma_async.sync.aligned.m64n64k16.f16.f16.f16 {z16,z17,z18,z19,z20,z21,z22,z23,z24,z25,z26,z27,z28,z29,z30,z31}, {w28,w29,w30,w31}, ds1, pt, 1, 1, 0;\n"
        "wgmma.mma_async.sync.aligned.m64n64k16.f16.f16.f16 {z16,z17,z18,z19,z20,z21,z22,z23,z24,z25,z26,z27,z28,z29,z30,z31}, {w32,w33,w34,w35}, ds2, pt, 1, 1, 0;\n"
        "mov.b32 {xl, xh}, a2; tanh.approx.f16 xr, xh; cvt.u32.u16 hi0, xr; mul.rn.f16x2 a3, z3, p; fma.rn.f16x2 p, z4, z4, c; fma.rn.f16x2 q3, g, g, q3; fma.rn.f16x2 g, z0, t, z0; prmt.b32 t, lo1, hi1, 0x5410; tanh.approx.f16 xr, xl; cvt.u32.u16 lo0, xr;\n"
        "B3:\n"
        "mov.b32 {xl, xh}, a3; tanh.approx.f16 xr, xh; cvt.u32.u16 hi1, xr; mul.rn.f16x2 a0, z4, p; fma.rn.f16x2 p, z5, z5, c; fma.rn.f16x2 q0, g, g, q0; fma.rn.f16x2 g, z1, t, z1; prmt.b32 t, lo0, hi0, 0x5410; tanh.approx.f16 xr, xl; cvt.u32.u16 lo1, xr;\n"
        "B4:\n"
        "mov.b32 {xl, xh}, a0; tanh.approx.f16 xr, xh; cvt.u32.u16 hi0, xr; mul.rn.f16x2 a1, z5, p; fma.rn.f16x2 p, z6, z6, c; fma.rn.f16x2 q1, g, g, q1; fma.rn.f16x2 g, z2, t, z2; prmt.b32 t, lo1, hi1, 0x5410; tanh.approx.f16 xr, xl; cvt.u32.u16 lo0, xr;\n"
        "B5:\n"
        "wgmma.fence.sync.aligned;\n"
        "wgmma.mma_async.sync.aligned.m64n64k16.f16.f16.f16 {z16,z17,z18,z19,z20,z21,z22,z23,z24,z25,z26,z27,z28,z29,z30,z31}, {w36,w37,w38,w39}, ds3, pt, 1, 1, 0;\n"
        "wgmma.mma_async.sync.aligned.m64n64k16.f16.f16.f16 {z16,z17,z18,z19,z20,z21,z22,z23,z24,z25,z26,z27,z28,z29,z30,z31}, {w40,w41,w42,w43}, ds4, pt, 1, 1, 0;\n"
        "wgmma.mma_async.sync.aligned.m64n64k16.f16.f16.f16 {z16,z17,z18,z19,z20,z21,z22,z23,z24,z25,z26,z27,z28,z29,z30,z31}, wd, ds5, pt, 1, 1, 1, 0;\n"
        "wgmma.commit_group.sync.aligned;\n"
        "mov.b32 {xl, xh}, a1; tanh.approx.f16 xr, xh; cvt.u32.u16 hi1, xr; mul.rn.f16x2 a2, z6, p; fma.rn.f16x2 p, z7, z7, c; fma.rn.f16x2 q0, g, g, q0; fma.rn.f16x2 g, z3, t, z3; prmt.b32 t, lo0, hi0, 0x5410; tanh.approx.f16 xr, xl; cvt.u32.u16 lo1, xr;\n"
        "B6:\n"
        "add.u32 so, so, 26624; setp.eq.u32 pr, so, 79872; selp.u32 so, 0, so, pr;\n"
        "mov.b32 {xl, xh}, a2; tanh.approx.f16 xr, xh; cvt.u32.u16 hi0, xr; mul.rn.f16x2 a3, z7, p; fma.rn.f16x2 p, z8, z8, c; fma.rn.f16x2 q1, g, g, q1; fma.rn.f16x2 g, z4, t, z4; prmt.b32 t, lo1, hi1, 0x5410; tanh.approx.f16 xr, xl; cvt.u32.u16 lo0, xr;\n"
        "B7:\n"
        "shr.u32 tt, so, 4;\n"
        "mov.b64 {dl, dh}, ds0; add.u32 dl, tt, 74816; mov.b64 ds0, {dl, dh}; mov.b64 {dl, dh}, ds1; add.u32 dl, tt, 74818; mov.b64 ds1, {dl, dh}; mov.b64 {dl, dh}, ds2; add.u32 dl, tt, 74820; mov.b64 ds2, {dl, dh};\n"
        "mov.b32 {xl, xh}, a3; tanh.approx.f16 xr, xh; cvt.u32.u16 hi1, xr; mul.rn.f16x2 a0, z8, p; fma.rn.f16x2 p, z9, z9, c; fma.rn.f16x2 q0, g, g, q0; fma.rn.f16x2 g, z5, t, z5; prmt.b32 t, lo0, hi0, 0x5410; tanh.approx.f16 xr, xl; cvt.u32.u16 lo1, xr;\n"
        "B8:\n"
        "shr.u32 tt, so, 4;\n"
        "mov.b64 {dl, dh}, ds3; add.u32 dl, tt, 74822; mov.b64 ds3, {dl, dh}; mov.b64 {dl, dh}, ds4; add.u32 dl, tt, 75328; mov.b64 ds4, {dl, dh}; mov.b64 {dl, dh}, ds5; add.u32 dl, tt, 75330; mov.b64 ds5, {dl, dh};\n"
        "mov.b32 {xl, xh}, a0; tanh.approx.f16 xr, xh; cvt.u32.u16 hi0, xr; mul.rn.f16x2 a1, z9, p; fma.rn.f16x2 p, z10, z10, c; fma.rn.f16x2 q1, g, g, q1; fma.rn.f16x2 g, z6, t, z6; prmt.b32 t, lo1, hi1, 0x5410; tanh.approx.f16 xr, xl; cvt.u32.u16 lo0, xr;\n"
        "B9:\n"
        "mov.b32 {xl, xh}, a1; tanh.approx.f16 xr, xh; cvt.u32.u16 hi1, xr; mul.rn.f16x2 a2, z10, p; fma.rn.f16x2 p, z11, z11, c; fma.rn.f16x2 q0, g, g, q0; fma.rn.f16x2 g, z7, t, z7; prmt.b32 t, lo0, hi0, 0x5410; tanh.approx.f16 xr, xl; cvt.u32.u16 lo1, xr;\n"
        "B10:\n"
        "mov.b32 {xl, xh}, a2; tanh.approx.f16 xr, xh; cvt.u32.u16 hi0, xr; mul.rn.f16x2 a3, z11, p; fma.rn.f16x2 p, z12, z12, c; fma.rn.f16x2 q1, g, g, q1; fma.rn.f16x2 g, z8, t, z8; prmt.b32 t, lo1, hi1, 0x5410; tanh.approx.f16 xr, xl; cvt.u32.u16 lo0, xr;\n"
        "B11:\n"
        "mov.b32 {xl, xh}, a3; tanh.approx.f16 xr, xh; cvt.u32.u16 hi1, xr; mul.rn.f16x2 a0, z12, p; fma.rn.f16x2 p, z13, z13, c; fma.rn.f16x2 q0, g, g, q0; fma.rn.f16x2 g, z9, t, z9; prmt.b32 t, lo0, hi0, 0x5410; tanh.approx.f16 xr, xl; cvt.u32.u16 lo1, xr;\n"
        "B12:\n"
        "mov.b32 {xl, xh}, a0; tanh.approx.f16 xr, xh; cvt.u32.u16 hi0, xr; mul.rn.f16x2 a1, z13, p; fma.rn.f16x2 p, z14, z14, c; fma.rn.f16x2 q1, g, g, q1; fma.rn.f16x2 g, z10, t, z10; prmt.b32 t, lo1, hi1, 0x5410; tanh.approx.f16 xr, xl; cvt.u32.u16 lo0, xr;\n"
        "B13:\n"
        "mov.b32 {xl, xh}, a1; tanh.approx.f16 xr, xh; cvt.u32.u16 hi1, xr; mul.rn.f16x2 a2, z14, p; fma.rn.f16x2 p, z15, z15, c; fma.rn.f16x2 q0, g, g, q0; fma.rn.f16x2 g, z11, t, z11; prmt.b32 t, lo0, hi0, 0x5410; tanh.approx.f16 xr, xl; cvt.u32.u16 lo1, xr;\n"
        "B14:\n"
        "wgmma.wait_group.sync.aligned 0;\n"
        "cp.async.bulk.wait_group.read 0;\n"
        "@pl mbarrier.arrive.shared::cta.b64 _, [n+231288];\n"
        "mov.b32 {xl, xh}, a2; tanh.approx.f16 xr, xh; cvt.u32.u16 hi0, xr; mul.rn.f16x2 a3, z15, p; fma.rn.f16x2 p, z16, z16, c; fma.rn.f16x2 q1, g, g, q1; fma.rn.f16x2 g, z12, t, z12; prmt.b32 t, lo1, hi1, 0x5410; tanh.approx.f16 xr, xl; cvt.u32.u16 lo0, xr;\n"
        "B15:\n"
        "mov.b32 {xl, xh}, a3; tanh.approx.f16 xr, xh; cvt.u32.u16 hi1, xr; mul.rn.f16x2 a0, z16, p; fma.rn.f16x2 p, z17, z17, c; fma.rn.f16x2 q0, g, g, q0; fma.rn.f16x2 g, z13, t, z13; prmt.b32 t, lo0, hi0, 0x5410; tanh.approx.f16 xr, xl; cvt.u32.u16 lo1, xr;\n"
        "B16:\n"
        "mbarrier.try_wait.parity.shared::cta.b64 pw, [n+231560], 0;\n"
        "mov.b32 {xl, xh}, a0; tanh.approx.f16 xr, xh; cvt.u32.u16 hi0, xr; mul.rn.f16x2 a1, z17, p; fma.rn.f16x2 p, z18, z18, c; fma.rn.f16x2 q1, g, g, q1; fma.rn.f16x2 g, z14, t, z14; prmt.b32 t, lo1, hi1, 0x5410; tanh.approx.f16 xr, xl; cvt.u32.u16 lo0, xr;\n"
        "B17:\n"
        "mov.b32 {xl, xh}, a1; tanh.approx.f16 xr, xh; cvt.u32.u16 hi1, xr; mul.rn.f16x2 a2, z18, p; fma.rn.f16x2 p, z19, z19, c; fma.rn.f16x2 q0, g, g, q0; fma.rn.f16x2 g, z15, t, z15; prmt.b32 t, lo0, hi0, 0x5410; tanh.approx.f16 xr, xl; cvt.u32.u16 lo1, xr;\n"
        "B18:\n"
        "@!pw bra.uni SPIN;\n"
        "BACK:\n"
        "wgmma.fence.sync.aligned;\n"
        "wgmma.mma_async.sync.aligned.m64n64k16.f16.f16.f16 {z0,z1,z2,z3,z4,z5,z6,z7,z8,z9,z10,z11,z12,z13,z14,z15}, {w0,w1,w2,w3}, ds0, pf, 1, 1, 0;\n"
        "wgmma.mma_async.sync.aligned.m64n64k16.f16.f16.f16 {z0,z1,z2,z3,z4,z5,z6,z7,z8,z9,z10,z11,z12,z13,z14,z15}, {w4,w5,w6,w7}, ds1, pt, 1, 1, 0;\n"
        "wgmma.mma_async.sync.aligned.m64n64k16.f16.f16.f16 {z0,z1,z2,z3,z4,z5,z6,z7,z8,z9,z10,z11,z12,z13,z14,z15}, {w8,w9,w10,w11}, ds2, pt, 1, 1, 0;\n"
        "mov.b32 {xl, xh}, a2; tanh.approx.f16 xr, xh; cvt.u32.u16 hi0, xr; mul.rn.f16x2 a3, z19, p; fma.rn.f16x2 p, z20, z20, c; fma.rn.f16x2 q1, g, g, q1; fma.rn.f16x2 g, z16, t, z16; prmt.b32 t, lo1, hi1, 0x5410; tanh.approx.f16 xr, xl; cvt.u32.u16 lo0, xr;\n"
        "B19:\n"
        "mov.b32 {xl, xh}, a3; tanh.approx.f16 xr, xh; cvt.u32.u16 hi1, xr; mul.rn.f16x2 a0, z20, p; fma.rn.f16x2 p, z21, z21, c; fma.rn.f16x2 q2, g, g, q2; fma.rn.f16x2 g, z17, t, z17; prmt.b32 t, lo0, hi0, 0x5410; tanh.approx.f16 xr, xl; cvt.u32.u16 lo1, xr;\n"
        "B20:\n"
        "mov.b32 {xl, xh}, a0; tanh.approx.f16 xr, xh; cvt.u32.u16 hi0, xr; mul.rn.f16x2 a1, z21, p; fma.rn.f16x2 p, z22, z22, c; fma.rn.f16x2 q3, g, g, q3; fma.rn.f16x2 g, z18, t, z18; prmt.b32 t, lo1, hi1, 0x5410; tanh.approx.f16 xr, xl; cvt.u32.u16 lo0, xr;\n"
        "B21:\n"
        "wgmma.fence.sync.aligned;\n"
        "wgmma.mma_async.sync.aligned.m64n64k16.f16.f16.f16 {z0,z1,z2,z3,z4,z5,z6,z7,z8,z9,z10,z11,z12,z13,z14,z15}, {w12,w13,w14,w15}, ds3, pt, 1, 1, 0;\n"
        "wgmma.mma_async.sync.aligned.m64n64k16.f16.f16.f16 {z0,z1,z2,z3,z4,z5,z6,z7,z8,z9,z10,z11,z12,z13,z14,z15}, {w16,w17,w18,w19}, ds4, pt, 1, 1, 0;\n"
        "wgmma.mma_async.sync.aligned.m64n64k16.f16.f16.f16 {z0,z1,z2,z3,z4,z5,z6,z7,z8,z9,z10,z11,z12,z13,z14,z15}, {w20,w21,w22,w23}, ds5, pt, 1, 1, 0;\n"
        "wgmma.commit_group.sync.aligned;\n"
        "mov.b32 {xl, xh}, a1; tanh.approx.f16 xr, xh; cvt.u32.u16 hi1, xr; mul.rn.f16x2 a2, z22, p; fma.rn.f16x2 p, z23, z23, c; fma.rn.f16x2 q2, g, g, q2; fma.rn.f16x2 g, z19, t, z19; prmt.b32 t, lo0, hi0, 0x5410; tanh.approx.f16 xr, xl; cvt.u32.u16 lo1, xr;\n"
        "B22:\n"
        "mov.b32 {xl, xh}, a2; tanh.approx.f16 xr, xh; cvt.u32.u16 hi0, xr; mul.rn.f16x2 a3, z23, p; fma.rn.f16x2 p, z24, z24, c; fma.rn.f16x2 q3, g, g, q3; fma.rn.f16x2 g, z20, t, z20; prmt.b32 t, lo1, hi1, 0x5410; tanh.approx.f16 xr, xl; cvt.u32.u16 lo0, xr;\n"
        "B23:\n"
        "mov.b32 {xl, xh}, a3; tanh.approx.f16 xr, xh; cvt.u32.u16 hi1, xr; mul.rn.f16x2 a0, z24, p; fma.rn.f16x2 p, z25, z25, c; fma.rn.f16x2 q2, g, g, q2; fma.rn.f16x2 g, z21, t, z21; prmt.b32 t, lo0, hi0, 0x5410; tanh.approx.f16 xr, xl; cvt.u32.u16 lo1, xr;\n"
        "B24:\n"
        "mov.b32 {xl, xh}, a0; tanh.approx.f16 xr, xh; cvt.u32.u16 hi0, xr; mul.rn.f16x2 a1, z25, p; fma.rn.f16x2 p, z26, z26, c; fma.rn.f16x2 q3, g, g, q3; fma.rn.f16x2 g, z22, t, z22; prmt.b32 t, lo1, hi1, 0x5410; tanh.approx.f16 xr, xl; cvt.u32.u16 lo0, xr;\n"
        "B25:\n"
        "mov.b32 {xl, xh}, a1; tanh.approx.f16 xr, xh; cvt.u32.u16 hi1, xr; mul.rn.f16x2 a2, z26, p; fma.rn.f16x2 p, z27, z27, c; fma.rn.f16x2 q2, g, g, q2; fma.rn.f16x2 g, z23, t, z23; prmt.b32 t, lo0, hi0, 0x5410; tanh.approx.f16 xr, xl; cvt.u32.u16 lo1, xr;\n"
        "B26:\n"
        "mov.b32 {xl, xh}, a2; tanh.approx.f16 xr, xh; cvt.u32.u16 hi0, xr; mul.rn.f16x2 a3, z27, p; fma.rn.f16x2 p, z28, z28, c; fma.rn.f16x2 q3, g, g, q3; fma.rn.f16x2 g, z24, t, z24; prmt.b32 t, lo1, hi1, 0x5410; tanh.approx.f16 xr, xl; cvt.u32.u16 lo0, xr;\n"
        "B27:\n"
        "add.u32 n, n, 8; setp.lt.u32 pe, n, 256; setp.ne.and.u32 pe, so, %7, pe;\n"
        "mov.b32 {xl, xh}, a3; tanh.approx.f16 xr, xh; cvt.u32.u16 hi1, xr; mul.rn.f16x2 a0, z28, p; fma.rn.f16x2 p, z29, z29, c; fma.rn.f16x2 q2, g, g, q2; fma.rn.f16x2 g, z25, t, z25; prmt.b32 t, lo0, hi0, 0x5410; tanh.approx.f16 xr, xl; cvt.u32.u16 lo1, xr;\n"
        "B28:\n"
        "mov.b32 {xl, xh}, a0; tanh.approx.f16 xr, xh; cvt.u32.u16 hi0, xr; mul.rn.f16x2 a1, z29, p; fma.rn.f16x2 p, z30, z30, c; fma.rn.f16x2 q3, g, g, q3; fma.rn.f16x2 g, z26, t, z26; prmt.b32 t, lo1, hi1, 0x5410; tanh.approx.f16 xr, xl; cvt.u32.u16 lo0, xr;\n"
        "B29:\n"
        "mov.b32 {xl, xh}, a1; tanh.approx.f16 xr, xh; cvt.u32.u16 hi1, xr; mul.rn.f16x2 a2, z30, p; fma.rn.f16x2 p, z31, z31, c; fma.rn.f16x2 q2, g, g, q2; fma.rn.f16x2 g, z27, t, z27; prmt.b32 t, lo0, hi0, 0x5410; tanh.approx.f16 xr, xl; cvt.u32.u16 lo1, xr;\n"
        "@pe bra.uni TOP;\n"
        "setp.lt.u32 pe, n, 256;\n"
        "@pe bra.uni DUTY;\n"
        "bra.uni DONE;\n"
        "SPINW: mov.u32 cnt, 0;\n"
        "SPINWL:\n"
        "mov.u32 tt, 230880; mbarrier.try_wait.parity.shared::cta.b64 pw, [tt], 0;\n"
        "@pw bra.uni BACKW;\n"
        "add.u32 cnt, cnt, 1; setp.lt.u32 pw, cnt, 0x100000;\n"
        "@pw bra.uni SPINWL;\n"
        "trap;\n"
        "SPIN5: mov.u32 cnt, 0;\n"
        "SPIN5L:\n"
        "mbarrier.try_wait.parity.shared::cta.b64 pw, [n+231544], 0;\n"
        "@pw bra.uni BACK5;\n"
        "add.u32 cnt, cnt, 1; setp.lt.u32 pw, cnt, 0x100000;\n"
        "@pw bra.uni SPIN5L;\n"
        "trap;\n"
        "SPIN0: mov.u32 cnt, 0;\n"
        "SPIN0L:\n"
        "mbarrier.try_wait.parity.shared::cta.b64 pw, [n+231552], 0;\n"
        "@pw bra.uni BACK0;\n"
        "add.u32 cnt, cnt, 1; setp.lt.u32 pw, cnt, 0x100000;\n"
        "@pw bra.uni SPIN0L;\n"
        "trap;\n"
        "SPIN: mov.u32 cnt, 0;\n"
        "SPINL:\n"
        "mbarrier.try_wait.parity.shared::cta.b64 pw, [n+231560], 0;\n"
        "@pw bra.uni BACK;\n"
        "add.u32 cnt, cnt, 1; setp.lt.u32 pw, cnt, 0x100000;\n"
        "@pw bra.uni SPINL;\n"
        "trap;\n"
        "DUTY:\n"
        "setp.ge.s32 pr, n, %11;\n"
        "@pr bra.uni FLUSH;\n"
        "setp.ge.u32 pr, %13, 2;\n"
        "@pr bra.uni ROLE2;\n"
        "setp.ge.s32 pr, n, %12; selp.b64 src, %14, gp, pr; add.u32 tt, n, 231288;\n"
        "elect.sync _|pr, 0xffffffff;\n"
        "@pr mbarrier.arrive.expect_tx.shared::cta.b64 _, [tt], %10;\n"
        "@pr cp.async.bulk.shared::cluster.global.mbarrier::complete_tx::bytes [%9], [src], %10, [tt];\n"
        "bra.uni FLUSH;\n"
        "ROLE2:\n"
        "setp.eq.u32 pr, %13, 3;\n"
        "@pr bra.uni ROLE3;\n"
        "setp.ne.s32 pr, n, 248;\n"
        "@pr bra.uni PARK;\n"
        "cp.async.bulk.wait_group 0;\n"
        "sub.s64 src, gp, %16; mov.u32 tt, 230824; mov.u32 cnt, 187392;\n"
        "elect.sync _|pr, 0xffffffff;\n"
        "@pr mbarrier.arrive.expect_tx.shared::cta.b64 _, [tt], 12288;\n"
        "@pr cp.async.bulk.shared::cluster.global.mbarrier::complete_tx::bytes [cnt], [src], 12288, [tt];\n"
        "PARK:\n"
        "elect.sync _|pr, 0xffffffff;\n"
        "@pr cp.async.bulk.global.shared::cta.bulk_group [gp], [%9], 12288;\n"
        "@pr cp.async.bulk.commit_group;\n"
        "bra.uni FLUSH;\n"
        "ROLE3:\n"
        "setp.ne.s32 pr, n, 64;\n"
        "@pr bra.uni AHEAD;\n"
        "mov.u32 tt, 230872;\n"
        "elect.sync _|pr, 0xffffffff;\n"
        "@pr mbarrier.arrive.expect_tx.shared::cta.b64 _, [tt], 75264;\n"
        "mov.u32 cnt, 229248; @pr cp.async.bulk.shared::cluster.global.mbarrier::complete_tx::bytes [cnt], [%18], 768, [tt];\n"
        "mov.u32 cnt, 230016; @pr cp.async.bulk.shared::cluster.global.mbarrier::complete_tx::bytes [cnt], [%19], 768, [tt];\n"
        "mov.u32 cnt, 74752; @pr cp.async.bulk.tensor.2d.shared::cluster.global.mbarrier::complete_tx::bytes [cnt], [%17, {0, 0}], [tt];\n"
        "mov.u32 cnt, 87040; @pr cp.async.bulk.tensor.2d.shared::cluster.global.mbarrier::complete_tx::bytes [cnt], [%17, {0, 192}], [tt];\n"
        "mov.u32 cnt, 99328; @pr cp.async.bulk.tensor.2d.shared::cluster.global.mbarrier::complete_tx::bytes [cnt], [%17, {32, 0}], [tt];\n"
        "mov.u32 cnt, 111616; @pr cp.async.bulk.tensor.2d.shared::cluster.global.mbarrier::complete_tx::bytes [cnt], [%17, {32, 192}], [tt];\n"
        "mov.u32 cnt, 123904; @pr cp.async.bulk.tensor.2d.shared::cluster.global.mbarrier::complete_tx::bytes [cnt], [%17, {64, 0}], [tt];\n"
        "mov.u32 cnt, 136192; @pr cp.async.bulk.tensor.2d.shared::cluster.global.mbarrier::complete_tx::bytes [cnt], [%17, {64, 192}], [tt];\n"
        "AHEAD:\n"
        "elect.sync _|pr, 0xffffffff;\n"
        "@pr cp.async.bulk.prefetch.L2.global [gp], 12288;\n"
        "FLUSH:\n"
        "add.s64 gp, gp, %16;\n"
        "mov.b32 {xl, xh}, q0; cvt.f32.f16 f0, xl; cvt.f32.f16 f1, xh; add.f32 f0, f0, f1; add.f32 %0, %0, f0; mov.b32 q0, 0;\n"
        "mov.b32 {xl, xh}, q1; cvt.f32.f16 f0, xl; cvt.f32.f16 f1, xh; add.f32 f0, f0, f1; add.f32 %1, %1, f0; mov.b32 q1, 0;\n"
        "mov.b32 {xl, xh}, q2; cvt.f32.f16 f0, xl; cvt.f32.f16 f1, xh; add.f32 f0, f0, f1; add.f32 %2, %2, f0; mov.b32 q2, 0;\n"
        "mov.b32 {xl, xh}, q3; cvt.f32.f16 f0, xl; cvt.f32.f16 f1, xh; add.f32 f0, f0, f1; add.f32 %3, %3, f0; mov.b32 q3, 0;\n"
        "setp.ne.u32 pr, %5, 0;\n"
        "@pr bra.uni TOP;\n"
        "wgmma.wait_group.sync.aligned 0;\n"
        "wgmma.fence.sync.aligned;\n"
        "ld.volatile.shared.v2.b32 {lo0, hi0}, [so]; xor.b32 f0, f0, lo0;\n"
        "ld.volatile.shared.v2.b32 {lo1, hi1}, [so]; xor.b32 f0, f0, lo1;\n"
        "ld.volatile.shared.v2.b32 {q1, a0}, [so]; xor.b32 f0, f0, q1;\n"
        "ld.volatile.shared.v2.b32 {q2, a1}, [so]; xor.b32 f0, f0, q2;\n"
        "ld.volatile.shared.v2.b32 {q3, a2}, [so]; xor.b32 f0, f0, q3;\n"
        "ld.volatile.shared.v2.b32 {q0, a3}, [so]; xor.b32 f0, f0, q0;\n"
        "ld.volatile.shared.v2.b32 {t, g}, [so]; xor.b32 f0, f0, t;\n"
        "ld.volatile.shared.v2.b32 {p, f1}, [so]; xor.b32 f0, f0, p;\n"
        "add.f32 %0, %0, f0;\n"
        "setp.eq.u32 pr, n, 1000; @pr bra.uni B31;\n"
        "setp.eq.u32 pr, n, 1001; @pr bra.uni B0;\n"
        "setp.eq.u32 pr, n, 1002; @pr bra.uni B1;\n"
        "setp.eq.u32 pr, n, 1003; @pr bra.uni B2;\n"
        "setp.eq.u32 pr, n, 1004; @pr bra.uni B3;\n"
        "setp.eq.u32 pr, n, 1005; @pr bra.uni B4;\n"
        "setp.eq.u32 pr, n, 1006; @pr bra.uni B5;\n"
        "setp.eq.u32 pr, n, 1007; @pr bra.uni B6;\n"
        "setp.eq.u32 pr, n, 1008; @pr bra.uni B7;\n"
        "setp.eq.u32 pr, n, 1009; @pr bra.uni B8;\n"
        "setp.eq.u32 pr, n, 1010; @pr bra.uni B9;\n"
        "setp.eq.u32 pr, n, 1011; @pr bra.uni B10;\n"
        "setp.eq.u32 pr, n, 1012; @pr bra.uni B11;\n"
        "setp.eq.u32 pr, n, 1013; @pr bra.uni B12;\n"
        "setp.eq.u32 pr, n, 1014; @pr bra.uni B13;\n"
        "setp.eq.u32 pr, n, 1015; @pr bra.uni B14;\n"
        "setp.eq.u32 pr, n, 1016; @pr bra.uni B15;\n"
        "setp.eq.u32 pr, n, 1017; @pr bra.uni B16;\n"
        "setp.eq.u32 pr, n, 1018; @pr bra.uni B17;\n"
        "setp.eq.u32 pr, n, 1019; @pr bra.uni B18;\n"
        "setp.eq.u32 pr, n, 1020; @pr bra.uni B19;\n"
        "setp.eq.u32 pr, n, 1021; @pr bra.uni B20;\n"
        "setp.eq.u32 pr, n, 1022; @pr bra.uni B21;\n"
        "setp.eq.u32 pr, n, 1023; @pr bra.uni B22;\n"
        "setp.eq.u32 pr, n, 1024; @pr bra.uni B23;\n"
        "setp.eq.u32 pr, n, 1025; @pr bra.uni B24;\n"
        "setp.eq.u32 pr, n, 1026; @pr bra.uni B25;\n"
        "setp.eq.u32 pr, n, 1027; @pr bra.uni B26;\n"
        "setp.eq.u32 pr, n, 1028; @pr bra.uni B27;\n"
        "setp.eq.u32 pr, n, 1029; @pr bra.uni B28;\n"
        "setp.eq.u32 pr, n, 1030; @pr bra.uni B29;\n"
        "setp.eq.u32 pr, n, 1031; @pr bra.uni TOP;\n"
        "trap;\n"
        "DONE:\n"
        ASM_TRC("n")
        "mov.b32 {xl, xh}, a2; tanh.approx.f16 xr, xh; cvt.u32.u16 hi0, xr; mul.rn.f16x2 a3, z31, p; fma.rn.f16x2 q3, g, g, q3; fma.rn.f16x2 g, z28, t, z28; prmt.b32 t, lo1, hi1, 0x5410; tanh.approx.f16 xr, xl; cvt.u32.u16 lo0, xr;\n"
        "mov.b32 {xl, xh}, a3; tanh.approx.f16 xr, xh; cvt.u32.u16 hi1, xr; fma.rn.f16x2 q2, g, g, q2; fma.rn.f16x2 g, z29, t, z29; prmt.b32 t, lo0, hi0, 0x5410; tanh.approx.f16 xr, xl; cvt.u32.u16 lo1, xr;\n"
        "fma.rn.f16x2 q3, g, g, q3; fma.rn.f16x2 g, z30, t, z30; prmt.b32 t, lo1, hi1, 0x5410;\n"
        "fma.rn.f16x2 q2, g, g, q2; fma.rn.f16x2 g, z31, t, z31;\n"
        "fma.rn.f16x2 q3, g, g, q3;\n"
        "mov.b32 {xl, xh}, q0; cvt.f32.f16 f0, xl; cvt.f32.f16 f1, xh; add.f32 f0, f0, f1; add.f32 %0, %0, f0; mov.b32 q0, 0;\n"
        "mov.b32 {xl, xh}, q1; cvt.f32.f16 f0, xl; cvt.f32.f16 f1, xh; add.f32 f0, f0, f1; add.f32 %1, %1, f0; mov.b32 q1, 0;\n"
        "mov.b32 {xl, xh}, q2; cvt.f32.f16 f0, xl; cvt.f32.f16 f1, xh; add.f32 f0, f0, f1; add.f32 %2, %2, f0; mov.b32 q2, 0;\n"
        "mov.b32 {xl, xh}, q3; cvt.f32.f16 f0, xl; cvt.f32.f16 f1, xh; add.f32 f0, f0, f1; add.f32 %3, %3, f0; mov.b32 q3, 0;\n"
        "wgmma.wait_group.sync.aligned 0;\n"
        "}\n"
        : "=f"(acc[0][0]), "=f"(acc[0][1]), "=f"(acc[1][0]), "=f"(acc[1][1])
        : "r"(w1t), "r"(yd), "r"(wd), "r"(own_slot), "l"(d.g), "r"(d.s), "r"(d.bytes), "r"(8 * d.end), "r"(8 * d.zero), "r"(role),
          "l"(d.zeros), "r"(lane), "l"(d.step), "l"(&prm.w2_map), "l"(prm.gamma), "l"(prm.beta), "l"(prm.ydesc64[0]), "l"(prm.ydesc64[1])
        : "memory");
}

template <int M>
__device__ __forceinline__ void gemm1_t(uint32_t (&d)[16], const uint32_t* wa, uint32_t yd, uint32_t wd) {
    wg_fence();
    wgmma_n64_h_set<0>(d, wa, desc<1024, 1>(yd, 0));
#pragma unroll
    for (int kk = 1; kk < 5; kk++)
        wgmma_n64_h_acc<0>(d, wa + kk * 4, kk < 4 ? desc<1024, 1>(yd, kk * 32) : desc<512, 2>(yd, 8192 + (kk - 4) * 32));
    wgmma_n64_h_acc_ss(d, desc<1024, 1>(wd, M * 12288), desc<512, 2>(yd, 8192 + 32));
    wg_commit();
}

__device__ __forceinline__ void gelu_sumsq_f(const uint32_t (&d)[16], float (&acc)[2]) {
#pragma unroll
    for (int r = 0; r < 16; r++) {
        float lo, hi;
        h2_unpack(gelu2(d[r]), lo, hi);
        acc[r & 1] = fmaf(lo, lo, acc[r & 1]);
        acc[r & 1] = fmaf(hi, hi, acc[r & 1]);
    }
}
__device__ __forceinline__ void load_w1t(uint32_t (&wa)[2][24], int wg, int w, int lane) {
#pragma unroll
    for (int m = 0; m < 2; m++)
#pragma unroll
        for (int kk = 0; kk < 5; kk++) {
            const int q = lane >> 3, c = 16 * kk + 8 * (q >> 1) + (lane & 7), ck = 2 * w + (q & 1);
            ldsm4_t(wa[m] + kk * 4, sb + SM_W1 + (2 * wg + m) * 12288 + c * 128 + ((ck ^ (c & 7)) * 16));
        }
}
__device__ __forceinline__ unsigned long long* acc_word(const Params& prm, uint32_t epoch, uint32_t e) {
    return &prm.g->acc[epoch & 1][(e >> 2) * 32 + (e & 3)];
}
__device__ __forceinline__ void publish_fast(const Params& prm, const float (&acc)[2][2], uint32_t epoch, int wg, int w, int lane) {
    const bool m = lane & 2, h = lane & 1;
    const float a = (m ? acc[1][0] : acc[0][0]) + __shfl_xor_sync(0xffffffffu, m ? acc[0][0] : acc[1][0], 2);
    const float b = (m ? acc[1][1] : acc[0][1]) + __shfl_xor_sync(0xffffffffu, m ? acc[0][1] : acc[1][1], 2);
    const float v = (h ? b : a) + __shfl_xor_sync(0xffffffffu, h ? a : b, 1);
    const unsigned long long q = (__float2ull_rn(fminf(v, ACC_LIMIT) * 0x1p16f) << 8) + 1;
    asm volatile("red.relaxed.gpu.global.add.u64 [%0], %1;"
                 ::"l"(acc_word(prm, epoch, 128 * wg + 32 * (lane & 2) + 16 * w + (lane >> 2) + 8 * (lane & 1))), "l"(q) : "memory");
}
__device__ __forceinline__ float collect_fast(const unsigned long long* word, unsigned long long v) {
    asm volatile(
        "{\n.reg .pred p;\n.reg .u32 n, lo, hi;\nmov.u32 n, 0;\n"
        "POLL:\nmov.b64 {lo, hi}, %0;\nand.b32 lo, lo, 255;\n"
        "setp.eq.u32 p, lo, %2;\nvote.sync.all.pred p, p, 0xffffffff;\n@p bra.uni POLL_DONE;\n"
        "ld.relaxed.gpu.global.u64 %0, [%1];\n"
        "add.u32 n, n, 1;\nsetp.lt.u32 p, n, 0x400000;\n@p bra.uni POLL;\ntrap;\nPOLL_DONE:\n}\n"
        : "+l"(v) : "l"(word), "n"(NUM_CTAS) : "memory");
    return __ull2float_rn(v >> 8) * 0x1p-16f;
}
__device__ __forceinline__ void publish_sums(const float (&acc)[2][2], float* sums, unsigned int* counter, int wg, int w, int lane) {
#pragma unroll
    for (int m = 0; m < 2; m++)
#pragma unroll
        for (int h = 0; h < 2; h++) {
            const float v = quad_sum(acc[m][h]);
            if ((lane & 3) == 0) atomicAdd(sums + 64 * (2 * wg + m) + 16 * w + (lane >> 2) + 8 * h, v);
        }
    named_sync(1, 384);
    if (fresh_tid() == 0) asm volatile("red.release.gpu.global.add.u32 [%0], 1;" ::"l"(counter) : "memory");
}
__device__ __forceinline__ void grid_wait(const unsigned int* counter, unsigned int target) {
    if (fresh_tid() == 0) {
        unsigned int v, spins = 0;
        do {
            asm volatile("ld.acquire.gpu.global.u32 %0, [%1];" : "=r"(v) : "l"(counter) : "memory");
            if (++spins > (1u << 22)) __trap();
        } while ((int)(v - target) < 0);
    }
    __syncthreads();
}

struct Pass2 {
    uint32_t wg;
    uint32_t off;
    int step;
    uint32_t xs;
    uint32_t a_offs, xs_offs, bias_addr;
    uint32_t w;
};

static_assert(BAR_Y2FULL == 0 && BAR_XSFULL == 4 && BAR_TURN == 11 && BAR_ROWS == 51 && BAR_STAT == 53 &&
              sb + SM_RED + RED_SCALE * 4 == 230792, "layout");
#define PASS2_STATE ".reg .b32 qa<24>, qz<32>, o<24>, g<16>, p<2>, a<4>, lo<2>, hi<2>, h<2>, osc;"
__device__ __forceinline__ void pass2_start(const Pass2& c, const Params& prm) {
    asm volatile(
        "{\n"
        ".reg .b32 t<2>, c, ad, cnt, ybar;\n"
        ".reg .b16 xl, xh, xr;\n"
        ".reg .b64 w1d, dt;\n"
        ".reg .pred pt, pf, pw;\n"
        "setp.ne.b32 pt, 1, 0; setp.ne.b32 pf, 0, 0; mov.b32 c, 0x40D940D9; mov.b64 w1d, {%0, 0x40000040}; mad.lo.u32 ybar, %1, 8, 230800;\n"
        "mbarrier.try_wait.parity.shared::cta.b64 pw, [ybar], 0;\n"
        "@!pw bra.uni SPINY0;\n"
        "BACKY0:\n"
        "and.b32 t0, %3, 0xffff; shr.u32 t1, %3, 16;\n"
        "xor.b32 ad, t0, 0; add.u32 ad, ad, %2; ldmatrix.sync.aligned.m8n8.x4.shared.b16 {qa0,qa1,qa2,qa3}, [ad];\n"
        "xor.b32 ad, t0, 32; add.u32 ad, ad, %2; ldmatrix.sync.aligned.m8n8.x4.shared.b16 {qa4,qa5,qa6,qa7}, [ad];\n"
        "xor.b32 ad, t0, 64; add.u32 ad, ad, %2; ldmatrix.sync.aligned.m8n8.x4.shared.b16 {qa8,qa9,qa10,qa11}, [ad];\n"
        "xor.b32 ad, t0, 96; add.u32 ad, ad, %2; ldmatrix.sync.aligned.m8n8.x4.shared.b16 {qa12,qa13,qa14,qa15}, [ad];\n"
        "xor.b32 ad, t1, 0; add.u32 ad, ad, %2; ldmatrix.sync.aligned.m8n8.x4.shared.b16 {qa16,qa17,qa18,qa19}, [ad];\n"
        "xor.b32 ad, t1, 32; add.u32 ad, ad, %2; ldmatrix.sync.aligned.m8n8.x4.shared.b16 {qa20,qa21,qa22,qa23}, [ad];\n"
        "wgmma.fence.sync.aligned;\n"
        "add.s64 dt, w1d, 0; wgmma.mma_async.sync.aligned.m64n64k16.f16.f16.f16 {qz0,qz1,qz2,qz3,qz4,qz5,qz6,qz7,qz8,qz9,qz10,qz11,qz12,qz13,qz14,qz15}, {qa0,qa1,qa2,qa3}, dt, pf, 1, 1, 1;\n"
        "add.s64 dt, w1d, 128; wgmma.mma_async.sync.aligned.m64n64k16.f16.f16.f16 {qz0,qz1,qz2,qz3,qz4,qz5,qz6,qz7,qz8,qz9,qz10,qz11,qz12,qz13,qz14,qz15}, {qa4,qa5,qa6,qa7}, dt, pt, 1, 1, 1;\n"
        "add.s64 dt, w1d, 256; wgmma.mma_async.sync.aligned.m64n64k16.f16.f16.f16 {qz0,qz1,qz2,qz3,qz4,qz5,qz6,qz7,qz8,qz9,qz10,qz11,qz12,qz13,qz14,qz15}, {qa8,qa9,qa10,qa11}, dt, pt, 1, 1, 1;\n"
        "add.s64 dt, w1d, 384; wgmma.mma_async.sync.aligned.m64n64k16.f16.f16.f16 {qz0,qz1,qz2,qz3,qz4,qz5,qz6,qz7,qz8,qz9,qz10,qz11,qz12,qz13,qz14,qz15}, {qa12,qa13,qa14,qa15}, dt, pt, 1, 1, 1;\n"
        "add.s64 dt, w1d, 512; wgmma.mma_async.sync.aligned.m64n64k16.f16.f16.f16 {qz0,qz1,qz2,qz3,qz4,qz5,qz6,qz7,qz8,qz9,qz10,qz11,qz12,qz13,qz14,qz15}, {qa16,qa17,qa18,qa19}, dt, pt, 1, 1, 1;\n"
        "add.s64 dt, w1d, 640; wgmma.mma_async.sync.aligned.m64n64k16.f16.f16.f16 {qz0,qz1,qz2,qz3,qz4,qz5,qz6,qz7,qz8,qz9,qz10,qz11,qz12,qz13,qz14,qz15}, {qa20,qa21,qa22,qa23}, dt, pt, 1, 1, 1;\n"
        "wgmma.commit_group.sync.aligned;\n"
        "wgmma.fence.sync.aligned;\n"
        "add.s64 dt, w1d, 768; wgmma.mma_async.sync.aligned.m64n64k16.f16.f16.f16 {qz16,qz17,qz18,qz19,qz20,qz21,qz22,qz23,qz24,qz25,qz26,qz27,qz28,qz29,qz30,qz31}, {qa0,qa1,qa2,qa3}, dt, pf, 1, 1, 1;\n"
        "add.s64 dt, w1d, 896; wgmma.mma_async.sync.aligned.m64n64k16.f16.f16.f16 {qz16,qz17,qz18,qz19,qz20,qz21,qz22,qz23,qz24,qz25,qz26,qz27,qz28,qz29,qz30,qz31}, {qa4,qa5,qa6,qa7}, dt, pt, 1, 1, 1;\n"
        "add.s64 dt, w1d, 1024; wgmma.mma_async.sync.aligned.m64n64k16.f16.f16.f16 {qz16,qz17,qz18,qz19,qz20,qz21,qz22,qz23,qz24,qz25,qz26,qz27,qz28,qz29,qz30,qz31}, {qa8,qa9,qa10,qa11}, dt, pt, 1, 1, 1;\n"
        "add.s64 dt, w1d, 1152; wgmma.mma_async.sync.aligned.m64n64k16.f16.f16.f16 {qz16,qz17,qz18,qz19,qz20,qz21,qz22,qz23,qz24,qz25,qz26,qz27,qz28,qz29,qz30,qz31}, {qa12,qa13,qa14,qa15}, dt, pt, 1, 1, 1;\n"
        "add.s64 dt, w1d, 1280; wgmma.mma_async.sync.aligned.m64n64k16.f16.f16.f16 {qz16,qz17,qz18,qz19,qz20,qz21,qz22,qz23,qz24,qz25,qz26,qz27,qz28,qz29,qz30,qz31}, {qa16,qa17,qa18,qa19}, dt, pt, 1, 1, 1;\n"
        "add.s64 dt, w1d, 1408; wgmma.mma_async.sync.aligned.m64n64k16.f16.f16.f16 {qz16,qz17,qz18,qz19,qz20,qz21,qz22,qz23,qz24,qz25,qz26,qz27,qz28,qz29,qz30,qz31}, {qa20,qa21,qa22,qa23}, dt, pt, 1, 1, 1;\n"
        "wgmma.commit_group.sync.aligned;\n"
        "mov.b32 g0, 0; mov.b32 g1, 0; mov.b32 g2, 0; mov.b32 g3, 0; mov.b32 p0, 0; mov.b32 p1, 0; mov.b32 a0, 0; mov.b32 a1, 0; mov.b32 a2, 0; mov.b32 a3, 0; mov.b32 lo0, 0; mov.b32 lo1, 0; mov.b32 hi0, 0; mov.b32 hi1, 0; mov.b32 h0, 0; mov.b32 h1, 0;\n"
        "wgmma.wait_group.sync.aligned 1;\n"
        "setp.eq.u32 pw, %0, 0;\n"
        "@pw bra.uni HEADE;\n"
        "fma.rn.f16x2 p0, qz0, qz0, c;\n"
        "mul.rn.f16x2 a0, qz0, p0; fma.rn.f16x2 p1, qz1, qz1, c;\n"
        "mov.b32 {xl, xh}, a0; tanh.approx.f16 xr, xl; cvt.u32.u16 lo0, xr; tanh.approx.f16 xr, xh; cvt.u32.u16 hi0, xr; mul.rn.f16x2 a1, qz1, p1; fma.rn.f16x2 p0, qz2, qz2, c;\n"
        "mov.b32 {xl, xh}, a1; tanh.approx.f16 xr, xl; cvt.u32.u16 lo1, xr; tanh.approx.f16 xr, xh; cvt.u32.u16 hi1, xr; mul.rn.f16x2 a2, qz2, p0; fma.rn.f16x2 p1, qz3, qz3, c; prmt.b32 h0, lo0, hi0, 0x5410;\n"
        "mov.b32 {xl, xh}, a2; tanh.approx.f16 xr, xl; cvt.u32.u16 lo0, xr; tanh.approx.f16 xr, xh; cvt.u32.u16 hi0, xr; mul.rn.f16x2 a3, qz3, p1; fma.rn.f16x2 p0, qz4, qz4, c; fma.rn.f16x2 g0, qz0, h0, qz0; prmt.b32 h1, lo1, hi1, 0x5410;\n"
        "mov.b32 {xl, xh}, a3; tanh.approx.f16 xr, xl; cvt.u32.u16 lo1, xr; tanh.approx.f16 xr, xh; cvt.u32.u16 hi1, xr; mul.rn.f16x2 a0, qz4, p0; fma.rn.f16x2 p1, qz5, qz5, c; fma.rn.f16x2 g1, qz1, h1, qz1; prmt.b32 h0, lo0, hi0, 0x5410;\n"
        "mov.b32 {xl, xh}, a0; tanh.approx.f16 xr, xl; cvt.u32.u16 lo0, xr; tanh.approx.f16 xr, xh; cvt.u32.u16 hi0, xr; mul.rn.f16x2 a1, qz5, p1; fma.rn.f16x2 p0, qz6, qz6, c; fma.rn.f16x2 g2, qz2, h0, qz2; prmt.b32 h1, lo1, hi1, 0x5410;\n"
        "mov.b32 {xl, xh}, a1; tanh.approx.f16 xr, xl; cvt.u32.u16 lo1, xr; tanh.approx.f16 xr, xh; cvt.u32.u16 hi1, xr; mul.rn.f16x2 a2, qz6, p0; fma.rn.f16x2 p1, qz7, qz7, c; fma.rn.f16x2 g3, qz3, h1, qz3; prmt.b32 h0, lo0, hi0, 0x5410;\n"
        "HEADE:\n"
        "wgmma.wait_group.sync.aligned 0;\n"
        "bra.uni DONE;\n"
        "SPINY0: mov.u32 cnt, 0;\n"
        "SPINY0L:\n"
        "mbarrier.try_wait.parity.shared::cta.b64 pw, [ybar], 0;\n"
        "@pw bra.uni BACKY0;\n"
        "add.u32 cnt, cnt, 1; setp.lt.u32 pw, cnt, 0x100000;\n"
        "@pw bra.uni SPINY0L;\n"
        "trap;\n"
        "DONE:\n"
        "}\n"
        :: "r"(prm.w1desc), "r"(c.wg), "r"(c.xs), "r"(c.a_offs) : "memory");
}
__device__ __forceinline__ bool pass2_head(const Pass2& c, uint32_t round) {
    uint32_t retry;
    asm volatile(
        "{\n"
        ".reg .b32 t<2>, tt, ad, cnt;\n"
        ".reg .pred pw;\n"
        "and.b32 t0, %3, 0xffff; shr.u32 t1, %3, 16;\n"
        "xor.b32 ad, t0, 0; add.u32 ad, ad, %4; ldmatrix.sync.aligned.m8n8.x4.shared.b16 {qa0,qa1,qa2,qa3}, [ad];\n"
        "xor.b32 ad, t0, 32; add.u32 ad, ad, %4; ldmatrix.sync.aligned.m8n8.x4.shared.b16 {qa4,qa5,qa6,qa7}, [ad];\n"
        "xor.b32 ad, t0, 64; add.u32 ad, ad, %4; ldmatrix.sync.aligned.m8n8.x4.shared.b16 {qa8,qa9,qa10,qa11}, [ad];\n"
        "xor.b32 ad, t0, 96; add.u32 ad, ad, %4; ldmatrix.sync.aligned.m8n8.x4.shared.b16 {qa12,qa13,qa14,qa15}, [ad];\n"
        "xor.b32 ad, t1, 0; add.u32 ad, ad, %4; ldmatrix.sync.aligned.m8n8.x4.shared.b16 {qa16,qa17,qa18,qa19}, [ad];\n"
        "xor.b32 ad, t1, 32; add.u32 ad, ad, %4; ldmatrix.sync.aligned.m8n8.x4.shared.b16 {qa20,qa21,qa22,qa23}, [ad];\n"
        "mov.b32 g4, 0; mov.b32 g5, 0; mov.b32 g6, 0; mov.b32 g7, 0; mov.b32 g8, 0; mov.b32 g9, 0; mov.b32 g10, 0; mov.b32 g11, 0; mov.b32 g12, 0; mov.b32 g13, 0; mov.b32 g14, 0; mov.b32 g15, 0;\n"
        "mov.u32 tt, 231224; mbarrier.try_wait.parity.shared::cta.b64 pw, [tt], %1;\n"
        "@!pw bra.uni SPINR;\n"
        "BACKR:\n"
        "mov.u32 tt, 230792; ld.shared.v2.b32 {osc, %0}, [tt];\n"
        "ld.shared.v4.b32 {o0,o1,o2,o3}, [%2+0];\n"
        "ld.shared.v4.b32 {o4,o5,o6,o7}, [%2+64];\n"
        "ld.shared.v4.b32 {o8,o9,o10,o11}, [%2+128];\n"
        "ld.shared.v4.b32 {o12,o13,o14,o15}, [%2+192];\n"
        "ld.shared.v4.b32 {o16,o17,o18,o19}, [%2+256];\n"
        "ld.shared.v4.b32 {o20,o21,o22,o23}, [%2+320];\n"
        "bra.uni DONE;\n"
        "SPINR: mov.u32 cnt, 0;\n"
        "SPINRL:\n"
        "mov.u32 tt, 231224; mbarrier.try_wait.parity.shared::cta.b64 pw, [tt], %1;\n"
        "@pw bra.uni BACKR;\n"
        "add.u32 cnt, cnt, 1; setp.lt.u32 pw, cnt, 0x100000;\n"
        "@pw bra.uni SPINRL;\n"
        "trap;\n"
        "DONE:\n"
        "}\n"
        : "=r"(retry) : "r"(round), "r"(c.bias_addr), "r"(c.a_offs), "r"(c.xs) : "memory");
    return __any_sync(0xffffffffu, retry);
}
__device__ __forceinline__ void pass2_tiles(const Pass2& c, const Params& prm) {
    asm volatile(
        "{\n"
        ".reg .b32 v<8>, r<24>, n, off, c, tt, ad, cnt, ybar, xbar, tbar, tpar, id;\n"
        ".reg .b16 xl, xh, xr;\n"
        ".reg .f32 f0, f1;\n"
        ".reg .b64 w1d, w2d, dt, gp, pol;\n"
        ".reg .pred pt, pf, pr, pw, pl, pm, pz, pn;\n"
        "setp.ne.b32 pt, 1, 0; setp.ne.b32 pf, 0, 0; setp.eq.u32 pl, %9, 0; setp.eq.u32 pz, %0, 0;\n"
        "mov.b32 c, 0x40D940D9;\n"
        "mov.b64 w1d, {%0, 0x40000040}; mov.b64 w2d, {%1, 0x80000020};\n"
        "mad.lo.u32 ybar, %2, 8, 230800; mad.lo.u32 xbar, %2, 8, 230832; add.u32 id, %2, 2;\n"
        "mad.lo.u32 tbar, %2, 64, 230888; setp.eq.u32 pr, %2, 0; selp.u32 tpar, 1, 0, pr; mov.u32 tt, %laneid; setp.eq.u32 pn, tt, 0;\n"
        "mov.u32 n, -1; add.u32 off, %3, %8; mov.pred pm, pt; createpolicy.fractional.L2::evict_first.b64 pol, 1.0;\n"
        "LOOP:\n"
        "setp.lt.s32 pr, n, 0;\n"
        "@pr bra.uni SKIP0;\n"
        "wgmma.fence.sync.aligned;\n"
        "add.s64 dt, w1d, 768; wgmma.mma_async.sync.aligned.m64n64k16.f16.f16.f16 {qz16,qz17,qz18,qz19,qz20,qz21,qz22,qz23,qz24,qz25,qz26,qz27,qz28,qz29,qz30,qz31}, {qa0,qa1,qa2,qa3}, dt, pf, 1, 1, 1;\n"
        "add.s64 dt, w1d, 896; wgmma.mma_async.sync.aligned.m64n64k16.f16.f16.f16 {qz16,qz17,qz18,qz19,qz20,qz21,qz22,qz23,qz24,qz25,qz26,qz27,qz28,qz29,qz30,qz31}, {qa4,qa5,qa6,qa7}, dt, pt, 1, 1, 1;\n"
        "add.s64 dt, w1d, 1024; wgmma.mma_async.sync.aligned.m64n64k16.f16.f16.f16 {qz16,qz17,qz18,qz19,qz20,qz21,qz22,qz23,qz24,qz25,qz26,qz27,qz28,qz29,qz30,qz31}, {qa8,qa9,qa10,qa11}, dt, pt, 1, 1, 1;\n"
        "add.s64 dt, w1d, 1152; wgmma.mma_async.sync.aligned.m64n64k16.f16.f16.f16 {qz16,qz17,qz18,qz19,qz20,qz21,qz22,qz23,qz24,qz25,qz26,qz27,qz28,qz29,qz30,qz31}, {qa12,qa13,qa14,qa15}, dt, pt, 1, 1, 1;\n"
        "add.s64 dt, w1d, 1280; wgmma.mma_async.sync.aligned.m64n64k16.f16.f16.f16 {qz16,qz17,qz18,qz19,qz20,qz21,qz22,qz23,qz24,qz25,qz26,qz27,qz28,qz29,qz30,qz31}, {qa16,qa17,qa18,qa19}, dt, pt, 1, 1, 1;\n"
        "add.s64 dt, w1d, 1408; wgmma.mma_async.sync.aligned.m64n64k16.f16.f16.f16 {qz16,qz17,qz18,qz19,qz20,qz21,qz22,qz23,qz24,qz25,qz26,qz27,qz28,qz29,qz30,qz31}, {qa20,qa21,qa22,qa23}, dt, pt, 1, 1, 1;\n"
        "SKIP0:\n"
        "setp.lt.s32 pr, n, 0;\n"
        "@pr bra.uni FIRST;\n"
        "and.b32 tt, n, 1; mbarrier.try_wait.parity.shared::cta.b64 pw, [xbar], tt;\n"
        "@!pw bra.uni SPINX;\n"
        "BACKX:\n"
        "and.b32 ad, %6, 0xffff; add.u32 ad, ad, %4; ld.shared.v4.b32 {v0,v1,v2,v3}, [ad+0];\n"
        "shr.u32 ad, %6, 16; add.u32 ad, ad, %4; ld.shared.v4.b32 {v4,v5,v6,v7}, [ad+0];\n"
        "mov.b32 {xl, xh}, o0; cvt.f32.f16 f0, xl; cvt.f32.f16 f1, xh; cvt.rn.bf16x2.f32 tt, f1, f0; fma.rn.bf16x2 v0, tt, osc, v0;\n"
        "mov.b32 {xl, xh}, o2; cvt.f32.f16 f0, xl; cvt.f32.f16 f1, xh; cvt.rn.bf16x2.f32 tt, f1, f0; fma.rn.bf16x2 v1, tt, osc, v1;\n"
        "mov.b32 {xl, xh}, o4; cvt.f32.f16 f0, xl; cvt.f32.f16 f1, xh; cvt.rn.bf16x2.f32 tt, f1, f0; fma.rn.bf16x2 v2, tt, osc, v2;\n"
        "mov.b32 {xl, xh}, o6; cvt.f32.f16 f0, xl; cvt.f32.f16 f1, xh; cvt.rn.bf16x2.f32 tt, f1, f0; fma.rn.bf16x2 v3, tt, osc, v3;\n"
        "and.b32 ad, %6, 0xffff; add.u32 ad, ad, %4; st.shared.v4.b32 [ad+0], {v0,v1,v2,v3};\n"
        "and.b32 ad, %6, 0xffff; add.u32 ad, ad, %4; ld.shared.v4.b32 {v0,v1,v2,v3}, [ad+64];\n"
        "mov.b32 {xl, xh}, o1; cvt.f32.f16 f0, xl; cvt.f32.f16 f1, xh; cvt.rn.bf16x2.f32 tt, f1, f0; fma.rn.bf16x2 v4, tt, osc, v4;\n"
        "mov.b32 {xl, xh}, o3; cvt.f32.f16 f0, xl; cvt.f32.f16 f1, xh; cvt.rn.bf16x2.f32 tt, f1, f0; fma.rn.bf16x2 v5, tt, osc, v5;\n"
        "mov.b32 {xl, xh}, o5; cvt.f32.f16 f0, xl; cvt.f32.f16 f1, xh; cvt.rn.bf16x2.f32 tt, f1, f0; fma.rn.bf16x2 v6, tt, osc, v6;\n"
        "mov.b32 {xl, xh}, o7; cvt.f32.f16 f0, xl; cvt.f32.f16 f1, xh; cvt.rn.bf16x2.f32 tt, f1, f0; fma.rn.bf16x2 v7, tt, osc, v7;\n"
        "shr.u32 ad, %6, 16; add.u32 ad, ad, %4; st.shared.v4.b32 [ad+0], {v4,v5,v6,v7};\n"
        "shr.u32 ad, %6, 16; add.u32 ad, ad, %4; ld.shared.v4.b32 {v4,v5,v6,v7}, [ad+64];\n"
        "ld.shared.v4.b32 {o0,o1,o2,o3}, [%7+0];\n"
        "ld.shared.v4.b32 {o4,o5,o6,o7}, [%7+64];\n"
        "mov.b32 {xl, xh}, o8; cvt.f32.f16 f0, xl; cvt.f32.f16 f1, xh; cvt.rn.bf16x2.f32 tt, f1, f0; fma.rn.bf16x2 v0, tt, osc, v0;\n"
        "mov.b32 {xl, xh}, o10; cvt.f32.f16 f0, xl; cvt.f32.f16 f1, xh; cvt.rn.bf16x2.f32 tt, f1, f0; fma.rn.bf16x2 v1, tt, osc, v1;\n"
        "mov.b32 {xl, xh}, o12; cvt.f32.f16 f0, xl; cvt.f32.f16 f1, xh; cvt.rn.bf16x2.f32 tt, f1, f0; fma.rn.bf16x2 v2, tt, osc, v2;\n"
        "mov.b32 {xl, xh}, o14; cvt.f32.f16 f0, xl; cvt.f32.f16 f1, xh; cvt.rn.bf16x2.f32 tt, f1, f0; fma.rn.bf16x2 v3, tt, osc, v3;\n"
        "and.b32 ad, %6, 0xffff; add.u32 ad, ad, %4; st.shared.v4.b32 [ad+64], {v0,v1,v2,v3};\n"
        "and.b32 ad, %6, 0xffff; add.u32 ad, ad, %4; ld.shared.v4.b32 {v0,v1,v2,v3}, [ad+128];\n"
        "mov.b32 {xl, xh}, o9; cvt.f32.f16 f0, xl; cvt.f32.f16 f1, xh; cvt.rn.bf16x2.f32 tt, f1, f0; fma.rn.bf16x2 v4, tt, osc, v4;\n"
        "mov.b32 {xl, xh}, o11; cvt.f32.f16 f0, xl; cvt.f32.f16 f1, xh; cvt.rn.bf16x2.f32 tt, f1, f0; fma.rn.bf16x2 v5, tt, osc, v5;\n"
        "mov.b32 {xl, xh}, o13; cvt.f32.f16 f0, xl; cvt.f32.f16 f1, xh; cvt.rn.bf16x2.f32 tt, f1, f0; fma.rn.bf16x2 v6, tt, osc, v6;\n"
        "mov.b32 {xl, xh}, o15; cvt.f32.f16 f0, xl; cvt.f32.f16 f1, xh; cvt.rn.bf16x2.f32 tt, f1, f0; fma.rn.bf16x2 v7, tt, osc, v7;\n"
        "shr.u32 ad, %6, 16; add.u32 ad, ad, %4; st.shared.v4.b32 [ad+64], {v4,v5,v6,v7};\n"
        "shr.u32 ad, %6, 16; add.u32 ad, ad, %4; ld.shared.v4.b32 {v4,v5,v6,v7}, [ad+128];\n"
        "ld.shared.v4.b32 {o8,o9,o10,o11}, [%7+128];\n"
        "ld.shared.v4.b32 {o12,o13,o14,o15}, [%7+192];\n"
        "mov.b32 {xl, xh}, o16; cvt.f32.f16 f0, xl; cvt.f32.f16 f1, xh; cvt.rn.bf16x2.f32 tt, f1, f0; fma.rn.bf16x2 v0, tt, osc, v0;\n"
        "mov.b32 {xl, xh}, o18; cvt.f32.f16 f0, xl; cvt.f32.f16 f1, xh; cvt.rn.bf16x2.f32 tt, f1, f0; fma.rn.bf16x2 v1, tt, osc, v1;\n"
        "mov.b32 {xl, xh}, o20; cvt.f32.f16 f0, xl; cvt.f32.f16 f1, xh; cvt.rn.bf16x2.f32 tt, f1, f0; fma.rn.bf16x2 v2, tt, osc, v2;\n"
        "mov.b32 {xl, xh}, o22; cvt.f32.f16 f0, xl; cvt.f32.f16 f1, xh; cvt.rn.bf16x2.f32 tt, f1, f0; fma.rn.bf16x2 v3, tt, osc, v3;\n"
        "and.b32 ad, %6, 0xffff; add.u32 ad, ad, %4; st.shared.v4.b32 [ad+128], {v0,v1,v2,v3};\n"
        "mov.b32 {xl, xh}, o17; cvt.f32.f16 f0, xl; cvt.f32.f16 f1, xh; cvt.rn.bf16x2.f32 tt, f1, f0; fma.rn.bf16x2 v4, tt, osc, v4;\n"
        "mov.b32 {xl, xh}, o19; cvt.f32.f16 f0, xl; cvt.f32.f16 f1, xh; cvt.rn.bf16x2.f32 tt, f1, f0; fma.rn.bf16x2 v5, tt, osc, v5;\n"
        "mov.b32 {xl, xh}, o21; cvt.f32.f16 f0, xl; cvt.f32.f16 f1, xh; cvt.rn.bf16x2.f32 tt, f1, f0; fma.rn.bf16x2 v6, tt, osc, v6;\n"
        "mov.b32 {xl, xh}, o23; cvt.f32.f16 f0, xl; cvt.f32.f16 f1, xh; cvt.rn.bf16x2.f32 tt, f1, f0; fma.rn.bf16x2 v7, tt, osc, v7;\n"
        "shr.u32 ad, %6, 16; add.u32 ad, ad, %4; st.shared.v4.b32 [ad+128], {v4,v5,v6,v7};\n"
        "ld.shared.v4.b32 {o16,o17,o18,o19}, [%7+256];\n"
        "ld.shared.v4.b32 {o20,o21,o22,o23}, [%7+320];\n"
        "FIRST:\n"
        "@pz bra.uni B7;\n"
        "mov.b32 {xl, xh}, a2; tanh.approx.f16 xr, xl; cvt.u32.u16 lo0, xr; tanh.approx.f16 xr, xh; cvt.u32.u16 hi0, xr; mul.rn.f16x2 a3, qz7, p1; fma.rn.f16x2 p0, qz8, qz8, c; fma.rn.f16x2 g4, qz4, h0, qz4; prmt.b32 h1, lo1, hi1, 0x5410;\n"
        "B7:\n"
        "fence.proxy.async.shared::cta;\n"
        "add.u32 tt, id, 4;\n"
        "@pl bra.uni STORE;\n"
        "bar.arrive tt, 128;\n"
        "STOREB:\n"
        ASM_MARK
        "add.s32 n, n, 1; sub.u32 off, off, %8; setp.lt.s32 pm, n, 7;\n"
        "@pz bra.uni B10;\n"
        "mov.b32 {xl, xh}, a3; tanh.approx.f16 xr, xl; cvt.u32.u16 lo1, xr; tanh.approx.f16 xr, xh; cvt.u32.u16 hi1, xr; mul.rn.f16x2 a0, qz8, p0; fma.rn.f16x2 p1, qz9, qz9, c; fma.rn.f16x2 g5, qz5, h1, qz5; prmt.b32 h0, lo0, hi0, 0x5410;\n"
        "mov.b32 {xl, xh}, a0; tanh.approx.f16 xr, xl; cvt.u32.u16 lo0, xr; tanh.approx.f16 xr, xh; cvt.u32.u16 hi0, xr; mul.rn.f16x2 a1, qz9, p1; fma.rn.f16x2 p0, qz10, qz10, c; fma.rn.f16x2 g6, qz6, h0, qz6; prmt.b32 h1, lo1, hi1, 0x5410;\n"
        "mov.b32 {xl, xh}, a1; tanh.approx.f16 xr, xl; cvt.u32.u16 lo1, xr; tanh.approx.f16 xr, xh; cvt.u32.u16 hi1, xr; mul.rn.f16x2 a2, qz10, p0; fma.rn.f16x2 p1, qz11, qz11, c; fma.rn.f16x2 g7, qz7, h1, qz7; prmt.b32 h0, lo0, hi0, 0x5410;\n"
        "B10:\n"
        "setp.eq.s32 pr, n, 0;\n"
        "@pr bra.uni SPINW0;\n"
        "BACKW0:\n"
        "wgmma.fence.sync.aligned;\n"
        "add.s64 dt, w2d, 0; wgmma.mma_async.sync.aligned.m64n96k16.f16.f16.f16 {o0,o1,o2,o3,o4,o5,o6,o7,o8,o9,o10,o11,o12,o13,o14,o15,o16,o17,o18,o19,o20,o21,o22,o23}, {g0,g1,g2,g3}, dt, pt, 1, 1, 1;\n"
        "add.s64 dt, w2d, 64; wgmma.mma_async.sync.aligned.m64n96k16.f16.f16.f16 {o0,o1,o2,o3,o4,o5,o6,o7,o8,o9,o10,o11,o12,o13,o14,o15,o16,o17,o18,o19,o20,o21,o22,o23}, {g4,g5,g6,g7}, dt, pt, 1, 1, 1;\n"
        "wgmma.commit_group.sync.aligned;\n"
        "@pz bra.uni B14;\n"
        "mov.b32 {xl, xh}, a2; tanh.approx.f16 xr, xl; cvt.u32.u16 lo0, xr; tanh.approx.f16 xr, xh; cvt.u32.u16 hi0, xr; mul.rn.f16x2 a3, qz11, p1; fma.rn.f16x2 p0, qz12, qz12, c; fma.rn.f16x2 g8, qz8, h0, qz8; prmt.b32 h1, lo1, hi1, 0x5410;\n"
        "mov.b32 {xl, xh}, a3; tanh.approx.f16 xr, xl; cvt.u32.u16 lo1, xr; tanh.approx.f16 xr, xh; cvt.u32.u16 hi1, xr; mul.rn.f16x2 a0, qz12, p0; fma.rn.f16x2 p1, qz13, qz13, c; fma.rn.f16x2 g9, qz9, h1, qz9; prmt.b32 h0, lo0, hi0, 0x5410;\n"
        "mov.b32 {xl, xh}, a0; tanh.approx.f16 xr, xl; cvt.u32.u16 lo0, xr; tanh.approx.f16 xr, xh; cvt.u32.u16 hi0, xr; mul.rn.f16x2 a1, qz13, p1; fma.rn.f16x2 p0, qz14, qz14, c; fma.rn.f16x2 g10, qz10, h0, qz10; prmt.b32 h1, lo1, hi1, 0x5410;\n"
        "mov.b32 {xl, xh}, a1; tanh.approx.f16 xr, xl; cvt.u32.u16 lo1, xr; tanh.approx.f16 xr, xh; cvt.u32.u16 hi1, xr; mul.rn.f16x2 a2, qz14, p0; fma.rn.f16x2 p1, qz15, qz15, c; fma.rn.f16x2 g11, qz11, h1, qz11; prmt.b32 h0, lo0, hi0, 0x5410;\n"
        "B14:\n"
        "wgmma.wait_group.sync.aligned 0;\n"
        "mad.lo.u32 tt, n, 8, tbar; mbarrier.try_wait.parity.shared::cta.b64 pw, [tt], tpar;\n"
        "@!pw bra.uni SPINT;\n"
        "BACKT:\n"
        "wgmma.fence.sync.aligned;\n"
        "add.s64 dt, w2d, 128; wgmma.mma_async.sync.aligned.m64n96k16.f16.f16.f16 {o0,o1,o2,o3,o4,o5,o6,o7,o8,o9,o10,o11,o12,o13,o14,o15,o16,o17,o18,o19,o20,o21,o22,o23}, {g8,g9,g10,g11}, dt, pt, 1, 1, 1;\n"
        "wgmma.commit_group.sync.aligned;\n"
        "@pz bra.uni B18;\n"
        "mov.b32 {xl, xh}, a2; tanh.approx.f16 xr, xl; cvt.u32.u16 lo0, xr; tanh.approx.f16 xr, xh; cvt.u32.u16 hi0, xr; mul.rn.f16x2 a3, qz15, p1; fma.rn.f16x2 p0, qz16, qz16, c; fma.rn.f16x2 g12, qz12, h0, qz12; prmt.b32 h1, lo1, hi1, 0x5410;\n"
        "mov.b32 {xl, xh}, a3; tanh.approx.f16 xr, xl; cvt.u32.u16 lo1, xr; tanh.approx.f16 xr, xh; cvt.u32.u16 hi1, xr; mul.rn.f16x2 a0, qz16, p0; fma.rn.f16x2 p1, qz17, qz17, c; fma.rn.f16x2 g13, qz13, h1, qz13; prmt.b32 h0, lo0, hi0, 0x5410;\n"
        "mov.b32 {xl, xh}, a0; tanh.approx.f16 xr, xl; cvt.u32.u16 lo0, xr; tanh.approx.f16 xr, xh; cvt.u32.u16 hi0, xr; mul.rn.f16x2 a1, qz17, p1; fma.rn.f16x2 p0, qz18, qz18, c; fma.rn.f16x2 g14, qz14, h0, qz14; prmt.b32 h1, lo1, hi1, 0x5410;\n"
        "mov.b32 {xl, xh}, a1; tanh.approx.f16 xr, xl; cvt.u32.u16 lo1, xr; tanh.approx.f16 xr, xh; cvt.u32.u16 hi1, xr; mul.rn.f16x2 a2, qz18, p0; fma.rn.f16x2 p1, qz19, qz19, c; fma.rn.f16x2 g15, qz15, h1, qz15; prmt.b32 h0, lo0, hi0, 0x5410;\n"
        "B18:\n"
        "wgmma.fence.sync.aligned;\n"
        "add.s64 dt, w2d, 192; wgmma.mma_async.sync.aligned.m64n96k16.f16.f16.f16 {o0,o1,o2,o3,o4,o5,o6,o7,o8,o9,o10,o11,o12,o13,o14,o15,o16,o17,o18,o19,o20,o21,o22,o23}, {g12,g13,g14,g15}, dt, pt, 1, 1, 1;\n"
        "add.s64 dt, w1d, 1536; wgmma.mma_async.sync.aligned.m64n64k16.f16.f16.f16 {qz0,qz1,qz2,qz3,qz4,qz5,qz6,qz7,qz8,qz9,qz10,qz11,qz12,qz13,qz14,qz15}, {qa0,qa1,qa2,qa3}, dt, pf, 1, 1, 1;\n"
        "add.s64 dt, w1d, 1664; wgmma.mma_async.sync.aligned.m64n64k16.f16.f16.f16 {qz0,qz1,qz2,qz3,qz4,qz5,qz6,qz7,qz8,qz9,qz10,qz11,qz12,qz13,qz14,qz15}, {qa4,qa5,qa6,qa7}, dt, pt, 1, 1, 1;\n"
        "add.s64 dt, w1d, 1792; wgmma.mma_async.sync.aligned.m64n64k16.f16.f16.f16 {qz0,qz1,qz2,qz3,qz4,qz5,qz6,qz7,qz8,qz9,qz10,qz11,qz12,qz13,qz14,qz15}, {qa8,qa9,qa10,qa11}, dt, pt, 1, 1, 1;\n"
        "wgmma.commit_group.sync.aligned;\n"
        "@pl bra.uni YLOAD;\n"
        "YLOADB:\n"
        "@pz bra.uni B22;\n"
        "mov.b32 {xl, xh}, a2; tanh.approx.f16 xr, xl; cvt.u32.u16 lo0, xr; tanh.approx.f16 xr, xh; cvt.u32.u16 hi0, xr; mul.rn.f16x2 a3, qz19, p1; fma.rn.f16x2 p0, qz20, qz20, c; fma.rn.f16x2 g0, qz16, h0, qz16; prmt.b32 h1, lo1, hi1, 0x5410;\n"
        "mov.b32 {xl, xh}, a3; tanh.approx.f16 xr, xl; cvt.u32.u16 lo1, xr; tanh.approx.f16 xr, xh; cvt.u32.u16 hi1, xr; mul.rn.f16x2 a0, qz20, p0; fma.rn.f16x2 p1, qz21, qz21, c; fma.rn.f16x2 g1, qz17, h1, qz17; prmt.b32 h0, lo0, hi0, 0x5410;\n"
        "mov.b32 {xl, xh}, a0; tanh.approx.f16 xr, xl; cvt.u32.u16 lo0, xr; tanh.approx.f16 xr, xh; cvt.u32.u16 hi0, xr; mul.rn.f16x2 a1, qz21, p1; fma.rn.f16x2 p0, qz22, qz22, c; fma.rn.f16x2 g2, qz18, h0, qz18; prmt.b32 h1, lo1, hi1, 0x5410;\n"
        "mov.b32 {xl, xh}, a1; tanh.approx.f16 xr, xl; cvt.u32.u16 lo1, xr; tanh.approx.f16 xr, xh; cvt.u32.u16 hi1, xr; mul.rn.f16x2 a2, qz22, p0; fma.rn.f16x2 p1, qz23, qz23, c; fma.rn.f16x2 g3, qz19, h1, qz19; prmt.b32 h0, lo0, hi0, 0x5410;\n"
        "B22:\n"
        "wgmma.fence.sync.aligned;\n"
        "add.s64 dt, w1d, 1920; wgmma.mma_async.sync.aligned.m64n64k16.f16.f16.f16 {qz0,qz1,qz2,qz3,qz4,qz5,qz6,qz7,qz8,qz9,qz10,qz11,qz12,qz13,qz14,qz15}, {qa12,qa13,qa14,qa15}, dt, pt, 1, 1, 1;\n"
        "add.s64 dt, w1d, 2048; wgmma.mma_async.sync.aligned.m64n64k16.f16.f16.f16 {qz0,qz1,qz2,qz3,qz4,qz5,qz6,qz7,qz8,qz9,qz10,qz11,qz12,qz13,qz14,qz15}, {qa16,qa17,qa18,qa19}, dt, pt, 1, 1, 1;\n"
        "add.s64 dt, w1d, 2176; wgmma.mma_async.sync.aligned.m64n64k16.f16.f16.f16 {qz0,qz1,qz2,qz3,qz4,qz5,qz6,qz7,qz8,qz9,qz10,qz11,qz12,qz13,qz14,qz15}, {qa20,qa21,qa22,qa23}, dt, pt, 1, 1, 1;\n"
        "wgmma.commit_group.sync.aligned;\n"
        "@pz bra.uni B26;\n"
        "mov.b32 {xl, xh}, a2; tanh.approx.f16 xr, xl; cvt.u32.u16 lo0, xr; tanh.approx.f16 xr, xh; cvt.u32.u16 hi0, xr; mul.rn.f16x2 a3, qz23, p1; fma.rn.f16x2 p0, qz24, qz24, c; fma.rn.f16x2 g4, qz20, h0, qz20; prmt.b32 h1, lo1, hi1, 0x5410;\n"
        "mov.b32 {xl, xh}, a3; tanh.approx.f16 xr, xl; cvt.u32.u16 lo1, xr; tanh.approx.f16 xr, xh; cvt.u32.u16 hi1, xr; mul.rn.f16x2 a0, qz24, p0; fma.rn.f16x2 p1, qz25, qz25, c; fma.rn.f16x2 g5, qz21, h1, qz21; prmt.b32 h0, lo0, hi0, 0x5410;\n"
        "mov.b32 {xl, xh}, a0; tanh.approx.f16 xr, xl; cvt.u32.u16 lo0, xr; tanh.approx.f16 xr, xh; cvt.u32.u16 hi0, xr; mul.rn.f16x2 a1, qz25, p1; fma.rn.f16x2 p0, qz26, qz26, c; fma.rn.f16x2 g6, qz22, h0, qz22; prmt.b32 h1, lo1, hi1, 0x5410;\n"
        "mov.b32 {xl, xh}, a1; tanh.approx.f16 xr, xl; cvt.u32.u16 lo1, xr; tanh.approx.f16 xr, xh; cvt.u32.u16 hi1, xr; mul.rn.f16x2 a2, qz26, p0; fma.rn.f16x2 p1, qz27, qz27, c; fma.rn.f16x2 g7, qz23, h1, qz23; prmt.b32 h0, lo0, hi0, 0x5410;\n"
        "B26:\n"
        "wgmma.wait_group.sync.aligned 2;\n"
        "wgmma.fence.sync.aligned;\n"
        "add.s64 dt, w2d, 256; wgmma.mma_async.sync.aligned.m64n96k16.f16.f16.f16 {o0,o1,o2,o3,o4,o5,o6,o7,o8,o9,o10,o11,o12,o13,o14,o15,o16,o17,o18,o19,o20,o21,o22,o23}, {g0,g1,g2,g3}, dt, pt, 1, 1, 1;\n"
        "add.s64 dt, w2d, 320; wgmma.mma_async.sync.aligned.m64n96k16.f16.f16.f16 {o0,o1,o2,o3,o4,o5,o6,o7,o8,o9,o10,o11,o12,o13,o14,o15,o16,o17,o18,o19,o20,o21,o22,o23}, {g4,g5,g6,g7}, dt, pt, 1, 1, 1;\n"
        "wgmma.commit_group.sync.aligned;\n"
        "@pz bra.uni B30;\n"
        "mov.b32 {xl, xh}, a2; tanh.approx.f16 xr, xl; cvt.u32.u16 lo0, xr; tanh.approx.f16 xr, xh; cvt.u32.u16 hi0, xr; mul.rn.f16x2 a3, qz27, p1; fma.rn.f16x2 p0, qz28, qz28, c; fma.rn.f16x2 g8, qz24, h0, qz24; prmt.b32 h1, lo1, hi1, 0x5410;\n"
        "mov.b32 {xl, xh}, a3; tanh.approx.f16 xr, xl; cvt.u32.u16 lo1, xr; tanh.approx.f16 xr, xh; cvt.u32.u16 hi1, xr; mul.rn.f16x2 a0, qz28, p0; fma.rn.f16x2 p1, qz29, qz29, c; fma.rn.f16x2 g9, qz25, h1, qz25; prmt.b32 h0, lo0, hi0, 0x5410;\n"
        "mov.b32 {xl, xh}, a0; tanh.approx.f16 xr, xl; cvt.u32.u16 lo0, xr; tanh.approx.f16 xr, xh; cvt.u32.u16 hi0, xr; mul.rn.f16x2 a1, qz29, p1; fma.rn.f16x2 p0, qz30, qz30, c; fma.rn.f16x2 g10, qz26, h0, qz26; prmt.b32 h1, lo1, hi1, 0x5410;\n"
        "mov.b32 {xl, xh}, a1; tanh.approx.f16 xr, xl; cvt.u32.u16 lo1, xr; tanh.approx.f16 xr, xh; cvt.u32.u16 hi1, xr; mul.rn.f16x2 a2, qz30, p0; fma.rn.f16x2 p1, qz31, qz31, c; fma.rn.f16x2 g11, qz27, h1, qz27; prmt.b32 h0, lo0, hi0, 0x5410;\n"
        "B30:\n"
        "wgmma.wait_group.sync.aligned 1;\n"
        "wgmma.fence.sync.aligned;\n"
        "add.s64 dt, w2d, 384; wgmma.mma_async.sync.aligned.m64n96k16.f16.f16.f16 {o0,o1,o2,o3,o4,o5,o6,o7,o8,o9,o10,o11,o12,o13,o14,o15,o16,o17,o18,o19,o20,o21,o22,o23}, {g8,g9,g10,g11}, dt, pt, 1, 1, 1;\n"
        "wgmma.commit_group.sync.aligned;\n"
        "@pz bra.uni B34;\n"
        "mov.b32 {xl, xh}, a2; tanh.approx.f16 xr, xl; cvt.u32.u16 lo0, xr; tanh.approx.f16 xr, xh; cvt.u32.u16 hi0, xr; mul.rn.f16x2 a3, qz31, p1; fma.rn.f16x2 p0, qz0, qz0, c; fma.rn.f16x2 g12, qz28, h0, qz28; prmt.b32 h1, lo1, hi1, 0x5410;\n"
        "mov.b32 {xl, xh}, a3; tanh.approx.f16 xr, xl; cvt.u32.u16 lo1, xr; tanh.approx.f16 xr, xh; cvt.u32.u16 hi1, xr; mul.rn.f16x2 a0, qz0, p0; fma.rn.f16x2 p1, qz1, qz1, c; fma.rn.f16x2 g13, qz29, h1, qz29; prmt.b32 h0, lo0, hi0, 0x5410;\n"
        "mov.b32 {xl, xh}, a0; tanh.approx.f16 xr, xl; cvt.u32.u16 lo0, xr; tanh.approx.f16 xr, xh; cvt.u32.u16 hi0, xr; mul.rn.f16x2 a1, qz1, p1; fma.rn.f16x2 p0, qz2, qz2, c; fma.rn.f16x2 g14, qz30, h0, qz30; prmt.b32 h1, lo1, hi1, 0x5410;\n"
        "mov.b32 {xl, xh}, a1; tanh.approx.f16 xr, xl; cvt.u32.u16 lo1, xr; tanh.approx.f16 xr, xh; cvt.u32.u16 hi1, xr; mul.rn.f16x2 a2, qz2, p0; fma.rn.f16x2 p1, qz3, qz3, c; fma.rn.f16x2 g15, qz31, h1, qz31; prmt.b32 h0, lo0, hi0, 0x5410;\n"
        "B34:\n"
        "wgmma.wait_group.sync.aligned 1;\n"
        "wgmma.fence.sync.aligned;\n"
        "add.s64 dt, w2d, 448; wgmma.mma_async.sync.aligned.m64n96k16.f16.f16.f16 {o0,o1,o2,o3,o4,o5,o6,o7,o8,o9,o10,o11,o12,o13,o14,o15,o16,o17,o18,o19,o20,o21,o22,o23}, {g12,g13,g14,g15}, dt, pt, 1, 1, 1;\n"
        "add.s64 dt, w1d, 2304; wgmma.mma_async.sync.aligned.m64n64k16.f16.f16.f16 {qz16,qz17,qz18,qz19,qz20,qz21,qz22,qz23,qz24,qz25,qz26,qz27,qz28,qz29,qz30,qz31}, {qa0,qa1,qa2,qa3}, dt, pf, 1, 1, 1;\n"
        "add.s64 dt, w1d, 2432; wgmma.mma_async.sync.aligned.m64n64k16.f16.f16.f16 {qz16,qz17,qz18,qz19,qz20,qz21,qz22,qz23,qz24,qz25,qz26,qz27,qz28,qz29,qz30,qz31}, {qa4,qa5,qa6,qa7}, dt, pt, 1, 1, 1;\n"
        "add.s64 dt, w1d, 2560; wgmma.mma_async.sync.aligned.m64n64k16.f16.f16.f16 {qz16,qz17,qz18,qz19,qz20,qz21,qz22,qz23,qz24,qz25,qz26,qz27,qz28,qz29,qz30,qz31}, {qa8,qa9,qa10,qa11}, dt, pt, 1, 1, 1;\n"
        "wgmma.commit_group.sync.aligned;\n"
        "@pz bra.uni B38;\n"
        "mov.b32 {xl, xh}, a2; tanh.approx.f16 xr, xl; cvt.u32.u16 lo0, xr; tanh.approx.f16 xr, xh; cvt.u32.u16 hi0, xr; mul.rn.f16x2 a3, qz3, p1; fma.rn.f16x2 p0, qz4, qz4, c; fma.rn.f16x2 g0, qz0, h0, qz0; prmt.b32 h1, lo1, hi1, 0x5410;\n"
        "mov.b32 {xl, xh}, a3; tanh.approx.f16 xr, xl; cvt.u32.u16 lo1, xr; tanh.approx.f16 xr, xh; cvt.u32.u16 hi1, xr; mul.rn.f16x2 a0, qz4, p0; fma.rn.f16x2 p1, qz5, qz5, c; fma.rn.f16x2 g1, qz1, h1, qz1; prmt.b32 h0, lo0, hi0, 0x5410;\n"
        "mov.b32 {xl, xh}, a0; tanh.approx.f16 xr, xl; cvt.u32.u16 lo0, xr; tanh.approx.f16 xr, xh; cvt.u32.u16 hi0, xr; mul.rn.f16x2 a1, qz5, p1; fma.rn.f16x2 p0, qz6, qz6, c; fma.rn.f16x2 g2, qz2, h0, qz2; prmt.b32 h1, lo1, hi1, 0x5410;\n"
        "mov.b32 {xl, xh}, a1; tanh.approx.f16 xr, xl; cvt.u32.u16 lo1, xr; tanh.approx.f16 xr, xh; cvt.u32.u16 hi1, xr; mul.rn.f16x2 a2, qz6, p0; fma.rn.f16x2 p1, qz7, qz7, c; fma.rn.f16x2 g3, qz3, h1, qz3; prmt.b32 h0, lo0, hi0, 0x5410;\n"
        "B38:\n"
        "wgmma.fence.sync.aligned;\n"
        "add.s64 dt, w1d, 2688; wgmma.mma_async.sync.aligned.m64n64k16.f16.f16.f16 {qz16,qz17,qz18,qz19,qz20,qz21,qz22,qz23,qz24,qz25,qz26,qz27,qz28,qz29,qz30,qz31}, {qa12,qa13,qa14,qa15}, dt, pt, 1, 1, 1;\n"
        "add.s64 dt, w1d, 2816; wgmma.mma_async.sync.aligned.m64n64k16.f16.f16.f16 {qz16,qz17,qz18,qz19,qz20,qz21,qz22,qz23,qz24,qz25,qz26,qz27,qz28,qz29,qz30,qz31}, {qa16,qa17,qa18,qa19}, dt, pt, 1, 1, 1;\n"
        "add.s64 dt, w1d, 2944; wgmma.mma_async.sync.aligned.m64n64k16.f16.f16.f16 {qz16,qz17,qz18,qz19,qz20,qz21,qz22,qz23,qz24,qz25,qz26,qz27,qz28,qz29,qz30,qz31}, {qa20,qa21,qa22,qa23}, dt, pt, 1, 1, 1;\n"
        "wgmma.commit_group.sync.aligned;\n"
        "@pz bra.uni B42;\n"
        "mov.b32 {xl, xh}, a2; tanh.approx.f16 xr, xl; cvt.u32.u16 lo0, xr; tanh.approx.f16 xr, xh; cvt.u32.u16 hi0, xr; mul.rn.f16x2 a3, qz7, p1; fma.rn.f16x2 p0, qz8, qz8, c; fma.rn.f16x2 g4, qz4, h0, qz4; prmt.b32 h1, lo1, hi1, 0x5410;\n"
        "mov.b32 {xl, xh}, a3; tanh.approx.f16 xr, xl; cvt.u32.u16 lo1, xr; tanh.approx.f16 xr, xh; cvt.u32.u16 hi1, xr; mul.rn.f16x2 a0, qz8, p0; fma.rn.f16x2 p1, qz9, qz9, c; fma.rn.f16x2 g5, qz5, h1, qz5; prmt.b32 h0, lo0, hi0, 0x5410;\n"
        "mov.b32 {xl, xh}, a0; tanh.approx.f16 xr, xl; cvt.u32.u16 lo0, xr; tanh.approx.f16 xr, xh; cvt.u32.u16 hi0, xr; mul.rn.f16x2 a1, qz9, p1; fma.rn.f16x2 p0, qz10, qz10, c; fma.rn.f16x2 g6, qz6, h0, qz6; prmt.b32 h1, lo1, hi1, 0x5410;\n"
        "mov.b32 {xl, xh}, a1; tanh.approx.f16 xr, xl; cvt.u32.u16 lo1, xr; tanh.approx.f16 xr, xh; cvt.u32.u16 hi1, xr; mul.rn.f16x2 a2, qz10, p0; fma.rn.f16x2 p1, qz11, qz11, c; fma.rn.f16x2 g7, qz7, h1, qz7; prmt.b32 h0, lo0, hi0, 0x5410;\n"
        "B42:\n"
        "wgmma.wait_group.sync.aligned 2;\n"
        "setp.eq.s32 pr, n, 0;\n"
        "@pr bra.uni SPINW1;\n"
        "BACKW1:\n"
        "wgmma.fence.sync.aligned;\n"
        "add.s64 dt, w2d, 512; wgmma.mma_async.sync.aligned.m64n96k16.f16.f16.f16 {o0,o1,o2,o3,o4,o5,o6,o7,o8,o9,o10,o11,o12,o13,o14,o15,o16,o17,o18,o19,o20,o21,o22,o23}, {g0,g1,g2,g3}, dt, pt, 1, 1, 1;\n"
        "add.s64 dt, w2d, 576; wgmma.mma_async.sync.aligned.m64n96k16.f16.f16.f16 {o0,o1,o2,o3,o4,o5,o6,o7,o8,o9,o10,o11,o12,o13,o14,o15,o16,o17,o18,o19,o20,o21,o22,o23}, {g4,g5,g6,g7}, dt, pt, 1, 1, 1;\n"
        "wgmma.commit_group.sync.aligned;\n"
        "mad.lo.u32 tt, n, 8, tbar;\n"
        "@pn mbarrier.arrive.shared::cta.b64 _, [tt+64];\n"
        "@pz bra.uni B46;\n"
        "mov.b32 {xl, xh}, a2; tanh.approx.f16 xr, xl; cvt.u32.u16 lo0, xr; tanh.approx.f16 xr, xh; cvt.u32.u16 hi0, xr; mul.rn.f16x2 a3, qz11, p1; fma.rn.f16x2 p0, qz12, qz12, c; fma.rn.f16x2 g8, qz8, h0, qz8; prmt.b32 h1, lo1, hi1, 0x5410;\n"
        "mov.b32 {xl, xh}, a3; tanh.approx.f16 xr, xl; cvt.u32.u16 lo1, xr; tanh.approx.f16 xr, xh; cvt.u32.u16 hi1, xr; mul.rn.f16x2 a0, qz12, p0; fma.rn.f16x2 p1, qz13, qz13, c; fma.rn.f16x2 g9, qz9, h1, qz9; prmt.b32 h0, lo0, hi0, 0x5410;\n"
        "mov.b32 {xl, xh}, a0; tanh.approx.f16 xr, xl; cvt.u32.u16 lo0, xr; tanh.approx.f16 xr, xh; cvt.u32.u16 hi0, xr; mul.rn.f16x2 a1, qz13, p1; fma.rn.f16x2 p0, qz14, qz14, c; fma.rn.f16x2 g10, qz10, h0, qz10; prmt.b32 h1, lo1, hi1, 0x5410;\n"
        "mov.b32 {xl, xh}, a1; tanh.approx.f16 xr, xl; cvt.u32.u16 lo1, xr; tanh.approx.f16 xr, xh; cvt.u32.u16 hi1, xr; mul.rn.f16x2 a2, qz14, p0; fma.rn.f16x2 p1, qz15, qz15, c; fma.rn.f16x2 g11, qz11, h1, qz11; prmt.b32 h0, lo0, hi0, 0x5410;\n"
        "B46:\n"
        "wgmma.wait_group.sync.aligned 1;\n"
        "wgmma.fence.sync.aligned;\n"
        "add.s64 dt, w2d, 640; wgmma.mma_async.sync.aligned.m64n96k16.f16.f16.f16 {o0,o1,o2,o3,o4,o5,o6,o7,o8,o9,o10,o11,o12,o13,o14,o15,o16,o17,o18,o19,o20,o21,o22,o23}, {g8,g9,g10,g11}, dt, pt, 1, 1, 1;\n"
        "wgmma.commit_group.sync.aligned;\n"
        "@pz bra.uni B50;\n"
        "mov.b32 {xl, xh}, a2; tanh.approx.f16 xr, xl; cvt.u32.u16 lo0, xr; tanh.approx.f16 xr, xh; cvt.u32.u16 hi0, xr; mul.rn.f16x2 a3, qz15, p1; fma.rn.f16x2 p0, qz16, qz16, c; fma.rn.f16x2 g12, qz12, h0, qz12; prmt.b32 h1, lo1, hi1, 0x5410;\n"
        "mov.b32 {xl, xh}, a3; tanh.approx.f16 xr, xl; cvt.u32.u16 lo1, xr; tanh.approx.f16 xr, xh; cvt.u32.u16 hi1, xr; mul.rn.f16x2 a0, qz16, p0; fma.rn.f16x2 p1, qz17, qz17, c; fma.rn.f16x2 g13, qz13, h1, qz13; prmt.b32 h0, lo0, hi0, 0x5410;\n"
        "mov.b32 {xl, xh}, a0; tanh.approx.f16 xr, xl; cvt.u32.u16 lo0, xr; tanh.approx.f16 xr, xh; cvt.u32.u16 hi0, xr; mul.rn.f16x2 a1, qz17, p1; fma.rn.f16x2 p0, qz18, qz18, c; fma.rn.f16x2 g14, qz14, h0, qz14; prmt.b32 h1, lo1, hi1, 0x5410;\n"
        "mov.b32 {xl, xh}, a1; tanh.approx.f16 xr, xl; cvt.u32.u16 lo1, xr; tanh.approx.f16 xr, xh; cvt.u32.u16 hi1, xr; mul.rn.f16x2 a2, qz18, p0; fma.rn.f16x2 p1, qz19, qz19, c; fma.rn.f16x2 g15, qz15, h1, qz15; prmt.b32 h0, lo0, hi0, 0x5410;\n"
        "B50:\n"
        "wgmma.wait_group.sync.aligned 1;\n"
        "wgmma.fence.sync.aligned;\n"
        "add.s64 dt, w2d, 704; wgmma.mma_async.sync.aligned.m64n96k16.f16.f16.f16 {o0,o1,o2,o3,o4,o5,o6,o7,o8,o9,o10,o11,o12,o13,o14,o15,o16,o17,o18,o19,o20,o21,o22,o23}, {g12,g13,g14,g15}, dt, pt, 1, 1, 1;\n"
        "add.s64 dt, w1d, 3072; wgmma.mma_async.sync.aligned.m64n64k16.f16.f16.f16 {qz0,qz1,qz2,qz3,qz4,qz5,qz6,qz7,qz8,qz9,qz10,qz11,qz12,qz13,qz14,qz15}, {qa0,qa1,qa2,qa3}, dt, pf, 1, 1, 1;\n"
        "add.s64 dt, w1d, 3200; wgmma.mma_async.sync.aligned.m64n64k16.f16.f16.f16 {qz0,qz1,qz2,qz3,qz4,qz5,qz6,qz7,qz8,qz9,qz10,qz11,qz12,qz13,qz14,qz15}, {qa4,qa5,qa6,qa7}, dt, pt, 1, 1, 1;\n"
        "add.s64 dt, w1d, 3328; wgmma.mma_async.sync.aligned.m64n64k16.f16.f16.f16 {qz0,qz1,qz2,qz3,qz4,qz5,qz6,qz7,qz8,qz9,qz10,qz11,qz12,qz13,qz14,qz15}, {qa8,qa9,qa10,qa11}, dt, pt, 1, 1, 1;\n"
        "wgmma.commit_group.sync.aligned;\n"
        "@pz bra.uni B54;\n"
        "mov.b32 {xl, xh}, a2; tanh.approx.f16 xr, xl; cvt.u32.u16 lo0, xr; tanh.approx.f16 xr, xh; cvt.u32.u16 hi0, xr; mul.rn.f16x2 a3, qz19, p1; fma.rn.f16x2 p0, qz20, qz20, c; fma.rn.f16x2 g0, qz16, h0, qz16; prmt.b32 h1, lo1, hi1, 0x5410;\n"
        "mov.b32 {xl, xh}, a3; tanh.approx.f16 xr, xl; cvt.u32.u16 lo1, xr; tanh.approx.f16 xr, xh; cvt.u32.u16 hi1, xr; mul.rn.f16x2 a0, qz20, p0; fma.rn.f16x2 p1, qz21, qz21, c; fma.rn.f16x2 g1, qz17, h1, qz17; prmt.b32 h0, lo0, hi0, 0x5410;\n"
        "mov.b32 {xl, xh}, a0; tanh.approx.f16 xr, xl; cvt.u32.u16 lo0, xr; tanh.approx.f16 xr, xh; cvt.u32.u16 hi0, xr; mul.rn.f16x2 a1, qz21, p1; fma.rn.f16x2 p0, qz22, qz22, c; fma.rn.f16x2 g2, qz18, h0, qz18; prmt.b32 h1, lo1, hi1, 0x5410;\n"
        "mov.b32 {xl, xh}, a1; tanh.approx.f16 xr, xl; cvt.u32.u16 lo1, xr; tanh.approx.f16 xr, xh; cvt.u32.u16 hi1, xr; mul.rn.f16x2 a2, qz22, p0; fma.rn.f16x2 p1, qz23, qz23, c; fma.rn.f16x2 g3, qz19, h1, qz19; prmt.b32 h0, lo0, hi0, 0x5410;\n"
        "B54:\n"
        "wgmma.fence.sync.aligned;\n"
        "add.s64 dt, w1d, 3456; wgmma.mma_async.sync.aligned.m64n64k16.f16.f16.f16 {qz0,qz1,qz2,qz3,qz4,qz5,qz6,qz7,qz8,qz9,qz10,qz11,qz12,qz13,qz14,qz15}, {qa12,qa13,qa14,qa15}, dt, pt, 1, 1, 1;\n"
        "add.s64 dt, w1d, 3584; wgmma.mma_async.sync.aligned.m64n64k16.f16.f16.f16 {qz0,qz1,qz2,qz3,qz4,qz5,qz6,qz7,qz8,qz9,qz10,qz11,qz12,qz13,qz14,qz15}, {qa16,qa17,qa18,qa19}, dt, pt, 1, 1, 1;\n"
        "add.s64 dt, w1d, 3712; wgmma.mma_async.sync.aligned.m64n64k16.f16.f16.f16 {qz0,qz1,qz2,qz3,qz4,qz5,qz6,qz7,qz8,qz9,qz10,qz11,qz12,qz13,qz14,qz15}, {qa20,qa21,qa22,qa23}, dt, pt, 1, 1, 1;\n"
        "wgmma.commit_group.sync.aligned;\n"
        "@pz bra.uni B58;\n"
        "mov.b32 {xl, xh}, a2; tanh.approx.f16 xr, xl; cvt.u32.u16 lo0, xr; tanh.approx.f16 xr, xh; cvt.u32.u16 hi0, xr; mul.rn.f16x2 a3, qz23, p1; fma.rn.f16x2 p0, qz24, qz24, c; fma.rn.f16x2 g4, qz20, h0, qz20; prmt.b32 h1, lo1, hi1, 0x5410;\n"
        "mov.b32 {xl, xh}, a3; tanh.approx.f16 xr, xl; cvt.u32.u16 lo1, xr; tanh.approx.f16 xr, xh; cvt.u32.u16 hi1, xr; mul.rn.f16x2 a0, qz24, p0; fma.rn.f16x2 p1, qz25, qz25, c; fma.rn.f16x2 g5, qz21, h1, qz21; prmt.b32 h0, lo0, hi0, 0x5410;\n"
        "mov.b32 {xl, xh}, a0; tanh.approx.f16 xr, xl; cvt.u32.u16 lo0, xr; tanh.approx.f16 xr, xh; cvt.u32.u16 hi0, xr; mul.rn.f16x2 a1, qz25, p1; fma.rn.f16x2 p0, qz26, qz26, c; fma.rn.f16x2 g6, qz22, h0, qz22; prmt.b32 h1, lo1, hi1, 0x5410;\n"
        "mov.b32 {xl, xh}, a1; tanh.approx.f16 xr, xl; cvt.u32.u16 lo1, xr; tanh.approx.f16 xr, xh; cvt.u32.u16 hi1, xr; mul.rn.f16x2 a2, qz26, p0; fma.rn.f16x2 p1, qz27, qz27, c; fma.rn.f16x2 g7, qz23, h1, qz23; prmt.b32 h0, lo0, hi0, 0x5410;\n"
        "B58:\n"
        "wgmma.wait_group.sync.aligned 2;\n"
        "wgmma.fence.sync.aligned;\n"
        "add.s64 dt, w2d, 768; wgmma.mma_async.sync.aligned.m64n96k16.f16.f16.f16 {o0,o1,o2,o3,o4,o5,o6,o7,o8,o9,o10,o11,o12,o13,o14,o15,o16,o17,o18,o19,o20,o21,o22,o23}, {g0,g1,g2,g3}, dt, pt, 1, 1, 1;\n"
        "add.s64 dt, w2d, 832; wgmma.mma_async.sync.aligned.m64n96k16.f16.f16.f16 {o0,o1,o2,o3,o4,o5,o6,o7,o8,o9,o10,o11,o12,o13,o14,o15,o16,o17,o18,o19,o20,o21,o22,o23}, {g4,g5,g6,g7}, dt, pt, 1, 1, 1;\n"
        "wgmma.commit_group.sync.aligned;\n"
        "@pz bra.uni B62;\n"
        "mov.b32 {xl, xh}, a2; tanh.approx.f16 xr, xl; cvt.u32.u16 lo0, xr; tanh.approx.f16 xr, xh; cvt.u32.u16 hi0, xr; mul.rn.f16x2 a3, qz27, p1; fma.rn.f16x2 p0, qz28, qz28, c; fma.rn.f16x2 g8, qz24, h0, qz24; prmt.b32 h1, lo1, hi1, 0x5410;\n"
        "mov.b32 {xl, xh}, a3; tanh.approx.f16 xr, xl; cvt.u32.u16 lo1, xr; tanh.approx.f16 xr, xh; cvt.u32.u16 hi1, xr; mul.rn.f16x2 a0, qz28, p0; fma.rn.f16x2 p1, qz29, qz29, c; fma.rn.f16x2 g9, qz25, h1, qz25; prmt.b32 h0, lo0, hi0, 0x5410;\n"
        "mov.b32 {xl, xh}, a0; tanh.approx.f16 xr, xl; cvt.u32.u16 lo0, xr; tanh.approx.f16 xr, xh; cvt.u32.u16 hi0, xr; mul.rn.f16x2 a1, qz29, p1; fma.rn.f16x2 p0, qz30, qz30, c; fma.rn.f16x2 g10, qz26, h0, qz26; prmt.b32 h1, lo1, hi1, 0x5410;\n"
        "mov.b32 {xl, xh}, a1; tanh.approx.f16 xr, xl; cvt.u32.u16 lo1, xr; tanh.approx.f16 xr, xh; cvt.u32.u16 hi1, xr; mul.rn.f16x2 a2, qz30, p0; fma.rn.f16x2 p1, qz31, qz31, c; fma.rn.f16x2 g11, qz27, h1, qz27; prmt.b32 h0, lo0, hi0, 0x5410;\n"
        "B62:\n"
        "wgmma.wait_group.sync.aligned 1;\n"
        "wgmma.fence.sync.aligned;\n"
        "add.s64 dt, w2d, 896; wgmma.mma_async.sync.aligned.m64n96k16.f16.f16.f16 {o0,o1,o2,o3,o4,o5,o6,o7,o8,o9,o10,o11,o12,o13,o14,o15,o16,o17,o18,o19,o20,o21,o22,o23}, {g8,g9,g10,g11}, dt, pt, 1, 1, 1;\n"
        "wgmma.commit_group.sync.aligned;\n"
        "@pz bra.uni B66;\n"
        "mov.b32 {xl, xh}, a2; tanh.approx.f16 xr, xl; cvt.u32.u16 lo0, xr; tanh.approx.f16 xr, xh; cvt.u32.u16 hi0, xr; mul.rn.f16x2 a3, qz31, p1; fma.rn.f16x2 p0, qz0, qz0, c; fma.rn.f16x2 g12, qz28, h0, qz28; prmt.b32 h1, lo1, hi1, 0x5410;\n"
        "mov.b32 {xl, xh}, a3; tanh.approx.f16 xr, xl; cvt.u32.u16 lo1, xr; tanh.approx.f16 xr, xh; cvt.u32.u16 hi1, xr; mul.rn.f16x2 a0, qz0, p0; fma.rn.f16x2 p1, qz1, qz1, c; fma.rn.f16x2 g13, qz29, h1, qz29; prmt.b32 h0, lo0, hi0, 0x5410;\n"
        "mov.b32 {xl, xh}, a0; tanh.approx.f16 xr, xl; cvt.u32.u16 lo0, xr; tanh.approx.f16 xr, xh; cvt.u32.u16 hi0, xr; mul.rn.f16x2 a1, qz1, p1; fma.rn.f16x2 p0, qz2, qz2, c; fma.rn.f16x2 g14, qz30, h0, qz30; prmt.b32 h1, lo1, hi1, 0x5410;\n"
        "mov.b32 {xl, xh}, a1; tanh.approx.f16 xr, xl; cvt.u32.u16 lo1, xr; tanh.approx.f16 xr, xh; cvt.u32.u16 hi1, xr; mul.rn.f16x2 a2, qz2, p0; fma.rn.f16x2 p1, qz3, qz3, c; fma.rn.f16x2 g15, qz31, h1, qz31; prmt.b32 h0, lo0, hi0, 0x5410;\n"
        "B66:\n"
        "wgmma.wait_group.sync.aligned 1;\n"
        "wgmma.fence.sync.aligned;\n"
        "add.s64 dt, w2d, 960; wgmma.mma_async.sync.aligned.m64n96k16.f16.f16.f16 {o0,o1,o2,o3,o4,o5,o6,o7,o8,o9,o10,o11,o12,o13,o14,o15,o16,o17,o18,o19,o20,o21,o22,o23}, {g12,g13,g14,g15}, dt, pt, 1, 1, 1;\n"
        "add.s64 dt, w1d, 3840; wgmma.mma_async.sync.aligned.m64n64k16.f16.f16.f16 {qz16,qz17,qz18,qz19,qz20,qz21,qz22,qz23,qz24,qz25,qz26,qz27,qz28,qz29,qz30,qz31}, {qa0,qa1,qa2,qa3}, dt, pf, 1, 1, 1;\n"
        "add.s64 dt, w1d, 3968; wgmma.mma_async.sync.aligned.m64n64k16.f16.f16.f16 {qz16,qz17,qz18,qz19,qz20,qz21,qz22,qz23,qz24,qz25,qz26,qz27,qz28,qz29,qz30,qz31}, {qa4,qa5,qa6,qa7}, dt, pt, 1, 1, 1;\n"
        "add.s64 dt, w1d, 4096; wgmma.mma_async.sync.aligned.m64n64k16.f16.f16.f16 {qz16,qz17,qz18,qz19,qz20,qz21,qz22,qz23,qz24,qz25,qz26,qz27,qz28,qz29,qz30,qz31}, {qa8,qa9,qa10,qa11}, dt, pt, 1, 1, 1;\n"
        "wgmma.commit_group.sync.aligned;\n"
        "@pz bra.uni B70;\n"
        "mov.b32 {xl, xh}, a2; tanh.approx.f16 xr, xl; cvt.u32.u16 lo0, xr; tanh.approx.f16 xr, xh; cvt.u32.u16 hi0, xr; mul.rn.f16x2 a3, qz3, p1; fma.rn.f16x2 p0, qz4, qz4, c; fma.rn.f16x2 g0, qz0, h0, qz0; prmt.b32 h1, lo1, hi1, 0x5410;\n"
        "mov.b32 {xl, xh}, a3; tanh.approx.f16 xr, xl; cvt.u32.u16 lo1, xr; tanh.approx.f16 xr, xh; cvt.u32.u16 hi1, xr; mul.rn.f16x2 a0, qz4, p0; fma.rn.f16x2 p1, qz5, qz5, c; fma.rn.f16x2 g1, qz1, h1, qz1; prmt.b32 h0, lo0, hi0, 0x5410;\n"
        "mov.b32 {xl, xh}, a0; tanh.approx.f16 xr, xl; cvt.u32.u16 lo0, xr; tanh.approx.f16 xr, xh; cvt.u32.u16 hi0, xr; mul.rn.f16x2 a1, qz5, p1; fma.rn.f16x2 p0, qz6, qz6, c; fma.rn.f16x2 g2, qz2, h0, qz2; prmt.b32 h1, lo1, hi1, 0x5410;\n"
        "mov.b32 {xl, xh}, a1; tanh.approx.f16 xr, xl; cvt.u32.u16 lo1, xr; tanh.approx.f16 xr, xh; cvt.u32.u16 hi1, xr; mul.rn.f16x2 a2, qz6, p0; fma.rn.f16x2 p1, qz7, qz7, c; fma.rn.f16x2 g3, qz3, h1, qz3; prmt.b32 h0, lo0, hi0, 0x5410;\n"
        "B70:\n"
        "wgmma.fence.sync.aligned;\n"
        "add.s64 dt, w1d, 4224; wgmma.mma_async.sync.aligned.m64n64k16.f16.f16.f16 {qz16,qz17,qz18,qz19,qz20,qz21,qz22,qz23,qz24,qz25,qz26,qz27,qz28,qz29,qz30,qz31}, {qa12,qa13,qa14,qa15}, dt, pt, 1, 1, 1;\n"
        "add.s64 dt, w1d, 4352; wgmma.mma_async.sync.aligned.m64n64k16.f16.f16.f16 {qz16,qz17,qz18,qz19,qz20,qz21,qz22,qz23,qz24,qz25,qz26,qz27,qz28,qz29,qz30,qz31}, {qa16,qa17,qa18,qa19}, dt, pt, 1, 1, 1;\n"
        "add.s64 dt, w1d, 4480; wgmma.mma_async.sync.aligned.m64n64k16.f16.f16.f16 {qz16,qz17,qz18,qz19,qz20,qz21,qz22,qz23,qz24,qz25,qz26,qz27,qz28,qz29,qz30,qz31}, {qa20,qa21,qa22,qa23}, dt, pt, 1, 1, 1;\n"
        "wgmma.commit_group.sync.aligned;\n"
        "@pz bra.uni B74;\n"
        "mov.b32 {xl, xh}, a2; tanh.approx.f16 xr, xl; cvt.u32.u16 lo0, xr; tanh.approx.f16 xr, xh; cvt.u32.u16 hi0, xr; mul.rn.f16x2 a3, qz7, p1; fma.rn.f16x2 p0, qz8, qz8, c; fma.rn.f16x2 g4, qz4, h0, qz4; prmt.b32 h1, lo1, hi1, 0x5410;\n"
        "mov.b32 {xl, xh}, a3; tanh.approx.f16 xr, xl; cvt.u32.u16 lo1, xr; tanh.approx.f16 xr, xh; cvt.u32.u16 hi1, xr; mul.rn.f16x2 a0, qz8, p0; fma.rn.f16x2 p1, qz9, qz9, c; fma.rn.f16x2 g5, qz5, h1, qz5; prmt.b32 h0, lo0, hi0, 0x5410;\n"
        "mov.b32 {xl, xh}, a0; tanh.approx.f16 xr, xl; cvt.u32.u16 lo0, xr; tanh.approx.f16 xr, xh; cvt.u32.u16 hi0, xr; mul.rn.f16x2 a1, qz9, p1; fma.rn.f16x2 p0, qz10, qz10, c; fma.rn.f16x2 g6, qz6, h0, qz6; prmt.b32 h1, lo1, hi1, 0x5410;\n"
        "mov.b32 {xl, xh}, a1; tanh.approx.f16 xr, xl; cvt.u32.u16 lo1, xr; tanh.approx.f16 xr, xh; cvt.u32.u16 hi1, xr; mul.rn.f16x2 a2, qz10, p0; fma.rn.f16x2 p1, qz11, qz11, c; fma.rn.f16x2 g7, qz7, h1, qz7; prmt.b32 h0, lo0, hi0, 0x5410;\n"
        "B74:\n"
        "wgmma.wait_group.sync.aligned 2;\n"
        "wgmma.fence.sync.aligned;\n"
        "add.s64 dt, w2d, 1024; wgmma.mma_async.sync.aligned.m64n96k16.f16.f16.f16 {o0,o1,o2,o3,o4,o5,o6,o7,o8,o9,o10,o11,o12,o13,o14,o15,o16,o17,o18,o19,o20,o21,o22,o23}, {g0,g1,g2,g3}, dt, pt, 1, 1, 1;\n"
        "add.s64 dt, w2d, 1088; wgmma.mma_async.sync.aligned.m64n96k16.f16.f16.f16 {o0,o1,o2,o3,o4,o5,o6,o7,o8,o9,o10,o11,o12,o13,o14,o15,o16,o17,o18,o19,o20,o21,o22,o23}, {g4,g5,g6,g7}, dt, pt, 1, 1, 1;\n"
        "wgmma.commit_group.sync.aligned;\n"
        "@pz bra.uni B78;\n"
        "mov.b32 {xl, xh}, a2; tanh.approx.f16 xr, xl; cvt.u32.u16 lo0, xr; tanh.approx.f16 xr, xh; cvt.u32.u16 hi0, xr; mul.rn.f16x2 a3, qz11, p1; fma.rn.f16x2 p0, qz12, qz12, c; fma.rn.f16x2 g8, qz8, h0, qz8; prmt.b32 h1, lo1, hi1, 0x5410;\n"
        "mov.b32 {xl, xh}, a3; tanh.approx.f16 xr, xl; cvt.u32.u16 lo1, xr; tanh.approx.f16 xr, xh; cvt.u32.u16 hi1, xr; mul.rn.f16x2 a0, qz12, p0; fma.rn.f16x2 p1, qz13, qz13, c; fma.rn.f16x2 g9, qz9, h1, qz9; prmt.b32 h0, lo0, hi0, 0x5410;\n"
        "mov.b32 {xl, xh}, a0; tanh.approx.f16 xr, xl; cvt.u32.u16 lo0, xr; tanh.approx.f16 xr, xh; cvt.u32.u16 hi0, xr; mul.rn.f16x2 a1, qz13, p1; fma.rn.f16x2 p0, qz14, qz14, c; fma.rn.f16x2 g10, qz10, h0, qz10; prmt.b32 h1, lo1, hi1, 0x5410;\n"
        "mov.b32 {xl, xh}, a1; tanh.approx.f16 xr, xl; cvt.u32.u16 lo1, xr; tanh.approx.f16 xr, xh; cvt.u32.u16 hi1, xr; mul.rn.f16x2 a2, qz14, p0; fma.rn.f16x2 p1, qz15, qz15, c; fma.rn.f16x2 g11, qz11, h1, qz11; prmt.b32 h0, lo0, hi0, 0x5410;\n"
        "B78:\n"
        "wgmma.wait_group.sync.aligned 1;\n"
        "@!pm bra.uni BACKY;\n"
        "add.u32 tt, n, 1; and.b32 tt, tt, 1; mbarrier.try_wait.parity.shared::cta.b64 pw, [ybar], tt;\n"
        "@!pw bra.uni SPINY;\n"
        "BACKY:\n"
        "@pz bra.uni B80;\n"
        "and.b32 ad, %5, 0xffff; xor.b32 ad, ad, 0; add.u32 ad, ad, %4; ldmatrix.sync.aligned.m8n8.x4.shared.b16 {qa0,qa1,qa2,qa3}, [ad];\n"
        "and.b32 ad, %5, 0xffff; xor.b32 ad, ad, 32; add.u32 ad, ad, %4; ldmatrix.sync.aligned.m8n8.x4.shared.b16 {qa4,qa5,qa6,qa7}, [ad];\n"
        "and.b32 ad, %5, 0xffff; xor.b32 ad, ad, 64; add.u32 ad, ad, %4; ldmatrix.sync.aligned.m8n8.x4.shared.b16 {qa8,qa9,qa10,qa11}, [ad];\n"
        "and.b32 ad, %5, 0xffff; xor.b32 ad, ad, 96; add.u32 ad, ad, %4; ldmatrix.sync.aligned.m8n8.x4.shared.b16 {qa12,qa13,qa14,qa15}, [ad];\n"
        "shr.u32 ad, %5, 16; xor.b32 ad, ad, 0; add.u32 ad, ad, %4; ldmatrix.sync.aligned.m8n8.x4.shared.b16 {qa16,qa17,qa18,qa19}, [ad];\n"
        "shr.u32 ad, %5, 16; xor.b32 ad, ad, 32; add.u32 ad, ad, %4; ldmatrix.sync.aligned.m8n8.x4.shared.b16 {qa20,qa21,qa22,qa23}, [ad];\n"
        "mov.b32 {xl, xh}, a2; tanh.approx.f16 xr, xl; cvt.u32.u16 lo0, xr; tanh.approx.f16 xr, xh; cvt.u32.u16 hi0, xr; mul.rn.f16x2 a3, qz15, p1; fma.rn.f16x2 p0, qz16, qz16, c; fma.rn.f16x2 g12, qz12, h0, qz12; prmt.b32 h1, lo1, hi1, 0x5410;\n"
        "mov.b32 {xl, xh}, a3; tanh.approx.f16 xr, xl; cvt.u32.u16 lo1, xr; tanh.approx.f16 xr, xh; cvt.u32.u16 hi1, xr; mul.rn.f16x2 a0, qz16, p0; fma.rn.f16x2 p1, qz17, qz17, c; fma.rn.f16x2 g13, qz13, h1, qz13; prmt.b32 h0, lo0, hi0, 0x5410;\n"
        "B80:\n"
        "@!pm bra.uni XLOADB;\n"
        "fence.proxy.async.shared::cta;\n"
        "add.u32 tt, id, 0;\n"
        "@pl bra.uni XLOAD;\n"
        "bar.arrive tt, 128;\n"
        "XLOADB:\n"
        "wgmma.fence.sync.aligned;\n"
        "add.s64 dt, w2d, 1152; wgmma.mma_async.sync.aligned.m64n96k16.f16.f16.f16 {o0,o1,o2,o3,o4,o5,o6,o7,o8,o9,o10,o11,o12,o13,o14,o15,o16,o17,o18,o19,o20,o21,o22,o23}, {g8,g9,g10,g11}, dt, pt, 1, 1, 1;\n"
        "wgmma.commit_group.sync.aligned;\n"
        "@pz bra.uni B82;\n"
        "mov.b32 {xl, xh}, a0; tanh.approx.f16 xr, xl; cvt.u32.u16 lo0, xr; tanh.approx.f16 xr, xh; cvt.u32.u16 hi0, xr; mul.rn.f16x2 a1, qz17, p1; fma.rn.f16x2 p0, qz18, qz18, c; fma.rn.f16x2 g14, qz14, h0, qz14; prmt.b32 h1, lo1, hi1, 0x5410;\n"
        "mov.b32 {xl, xh}, a1; tanh.approx.f16 xr, xl; cvt.u32.u16 lo1, xr; tanh.approx.f16 xr, xh; cvt.u32.u16 hi1, xr; mul.rn.f16x2 a2, qz18, p0; fma.rn.f16x2 p1, qz19, qz19, c; fma.rn.f16x2 g15, qz15, h1, qz15; prmt.b32 h0, lo0, hi0, 0x5410;\n"
        "B82:\n"
        "wgmma.wait_group.sync.aligned 1;\n"
        "@!pm bra.uni SKIP1;\n"
        "wgmma.fence.sync.aligned;\n"
        "add.s64 dt, w1d, 0; wgmma.mma_async.sync.aligned.m64n64k16.f16.f16.f16 {qz0,qz1,qz2,qz3,qz4,qz5,qz6,qz7,qz8,qz9,qz10,qz11,qz12,qz13,qz14,qz15}, {qa0,qa1,qa2,qa3}, dt, pf, 1, 1, 1;\n"
        "add.s64 dt, w1d, 128; wgmma.mma_async.sync.aligned.m64n64k16.f16.f16.f16 {qz0,qz1,qz2,qz3,qz4,qz5,qz6,qz7,qz8,qz9,qz10,qz11,qz12,qz13,qz14,qz15}, {qa4,qa5,qa6,qa7}, dt, pt, 1, 1, 1;\n"
        "add.s64 dt, w1d, 256; wgmma.mma_async.sync.aligned.m64n64k16.f16.f16.f16 {qz0,qz1,qz2,qz3,qz4,qz5,qz6,qz7,qz8,qz9,qz10,qz11,qz12,qz13,qz14,qz15}, {qa8,qa9,qa10,qa11}, dt, pt, 1, 1, 1;\n"
        "SKIP1:\n"
        "wgmma.fence.sync.aligned;\n"
        "add.s64 dt, w2d, 1216; wgmma.mma_async.sync.aligned.m64n96k16.f16.f16.f16 {o0,o1,o2,o3,o4,o5,o6,o7,o8,o9,o10,o11,o12,o13,o14,o15,o16,o17,o18,o19,o20,o21,o22,o23}, {g12,g13,g14,g15}, dt, pt, 1, 1, 1;\n"
        "wgmma.commit_group.sync.aligned;\n"
        "@pz bra.uni B86;\n"
        "mov.b32 {xl, xh}, a2; tanh.approx.f16 xr, xl; cvt.u32.u16 lo0, xr; tanh.approx.f16 xr, xh; cvt.u32.u16 hi0, xr; mul.rn.f16x2 a3, qz19, p1; fma.rn.f16x2 p0, qz20, qz20, c; fma.rn.f16x2 g0, qz16, h0, qz16; prmt.b32 h1, lo1, hi1, 0x5410;\n"
        "mov.b32 {xl, xh}, a3; tanh.approx.f16 xr, xl; cvt.u32.u16 lo1, xr; tanh.approx.f16 xr, xh; cvt.u32.u16 hi1, xr; mul.rn.f16x2 a0, qz20, p0; fma.rn.f16x2 p1, qz21, qz21, c; fma.rn.f16x2 g1, qz17, h1, qz17; prmt.b32 h0, lo0, hi0, 0x5410;\n"
        "mov.b32 {xl, xh}, a0; tanh.approx.f16 xr, xl; cvt.u32.u16 lo0, xr; tanh.approx.f16 xr, xh; cvt.u32.u16 hi0, xr; mul.rn.f16x2 a1, qz21, p1; fma.rn.f16x2 p0, qz22, qz22, c; fma.rn.f16x2 g2, qz18, h0, qz18; prmt.b32 h1, lo1, hi1, 0x5410;\n"
        "mov.b32 {xl, xh}, a1; tanh.approx.f16 xr, xl; cvt.u32.u16 lo1, xr; tanh.approx.f16 xr, xh; cvt.u32.u16 hi1, xr; mul.rn.f16x2 a2, qz22, p0; fma.rn.f16x2 p1, qz23, qz23, c; fma.rn.f16x2 g3, qz19, h1, qz19; prmt.b32 h0, lo0, hi0, 0x5410;\n"
        "B86:\n"
        "@!pm bra.uni SKIP2;\n"
        "wgmma.fence.sync.aligned;\n"
        "add.s64 dt, w1d, 384; wgmma.mma_async.sync.aligned.m64n64k16.f16.f16.f16 {qz0,qz1,qz2,qz3,qz4,qz5,qz6,qz7,qz8,qz9,qz10,qz11,qz12,qz13,qz14,qz15}, {qa12,qa13,qa14,qa15}, dt, pt, 1, 1, 1;\n"
        "add.s64 dt, w1d, 512; wgmma.mma_async.sync.aligned.m64n64k16.f16.f16.f16 {qz0,qz1,qz2,qz3,qz4,qz5,qz6,qz7,qz8,qz9,qz10,qz11,qz12,qz13,qz14,qz15}, {qa16,qa17,qa18,qa19}, dt, pt, 1, 1, 1;\n"
        "add.s64 dt, w1d, 640; wgmma.mma_async.sync.aligned.m64n64k16.f16.f16.f16 {qz0,qz1,qz2,qz3,qz4,qz5,qz6,qz7,qz8,qz9,qz10,qz11,qz12,qz13,qz14,qz15}, {qa20,qa21,qa22,qa23}, dt, pt, 1, 1, 1;\n"
        "SKIP2:\n"
        "@pz bra.uni B90;\n"
        "mov.b32 {xl, xh}, a2; tanh.approx.f16 xr, xl; cvt.u32.u16 lo0, xr; tanh.approx.f16 xr, xh; cvt.u32.u16 hi0, xr; mul.rn.f16x2 a3, qz23, p1; fma.rn.f16x2 p0, qz24, qz24, c; fma.rn.f16x2 g4, qz20, h0, qz20; prmt.b32 h1, lo1, hi1, 0x5410;\n"
        "mov.b32 {xl, xh}, a3; tanh.approx.f16 xr, xl; cvt.u32.u16 lo1, xr; tanh.approx.f16 xr, xh; cvt.u32.u16 hi1, xr; mul.rn.f16x2 a0, qz24, p0; fma.rn.f16x2 p1, qz25, qz25, c; fma.rn.f16x2 g5, qz21, h1, qz21; prmt.b32 h0, lo0, hi0, 0x5410;\n"
        "mov.b32 {xl, xh}, a0; tanh.approx.f16 xr, xl; cvt.u32.u16 lo0, xr; tanh.approx.f16 xr, xh; cvt.u32.u16 hi0, xr; mul.rn.f16x2 a1, qz25, p1; fma.rn.f16x2 p0, qz26, qz26, c; fma.rn.f16x2 g6, qz22, h0, qz22; prmt.b32 h1, lo1, hi1, 0x5410;\n"
        "mov.b32 {xl, xh}, a1; tanh.approx.f16 xr, xl; cvt.u32.u16 lo1, xr; tanh.approx.f16 xr, xh; cvt.u32.u16 hi1, xr; mul.rn.f16x2 a2, qz26, p0; fma.rn.f16x2 p1, qz27, qz27, c; fma.rn.f16x2 g7, qz23, h1, qz23; prmt.b32 h0, lo0, hi0, 0x5410;\n"
        "B90:\n"
        "wgmma.wait_group.sync.aligned 1;\n"
        "wgmma.fence.sync.aligned;\n"
        "add.s64 dt, w2d, 1280; wgmma.mma_async.sync.aligned.m64n96k16.f16.f16.f16 {o0,o1,o2,o3,o4,o5,o6,o7,o8,o9,o10,o11,o12,o13,o14,o15,o16,o17,o18,o19,o20,o21,o22,o23}, {g0,g1,g2,g3}, dt, pt, 1, 1, 1;\n"
        "add.s64 dt, w2d, 1344; wgmma.mma_async.sync.aligned.m64n96k16.f16.f16.f16 {o0,o1,o2,o3,o4,o5,o6,o7,o8,o9,o10,o11,o12,o13,o14,o15,o16,o17,o18,o19,o20,o21,o22,o23}, {g4,g5,g6,g7}, dt, pt, 1, 1, 1;\n"
        "wgmma.commit_group.sync.aligned;\n"
        "@pz bra.uni B94;\n"
        "mov.b32 {xl, xh}, a2; tanh.approx.f16 xr, xl; cvt.u32.u16 lo0, xr; tanh.approx.f16 xr, xh; cvt.u32.u16 hi0, xr; mul.rn.f16x2 a3, qz27, p1; fma.rn.f16x2 p0, qz28, qz28, c; fma.rn.f16x2 g8, qz24, h0, qz24; prmt.b32 h1, lo1, hi1, 0x5410;\n"
        "mov.b32 {xl, xh}, a3; tanh.approx.f16 xr, xl; cvt.u32.u16 lo1, xr; tanh.approx.f16 xr, xh; cvt.u32.u16 hi1, xr; mul.rn.f16x2 a0, qz28, p0; fma.rn.f16x2 p1, qz29, qz29, c; fma.rn.f16x2 g9, qz25, h1, qz25; prmt.b32 h0, lo0, hi0, 0x5410;\n"
        "mov.b32 {xl, xh}, a0; tanh.approx.f16 xr, xl; cvt.u32.u16 lo0, xr; tanh.approx.f16 xr, xh; cvt.u32.u16 hi0, xr; mul.rn.f16x2 a1, qz29, p1; fma.rn.f16x2 p0, qz30, qz30, c; fma.rn.f16x2 g10, qz26, h0, qz26; prmt.b32 h1, lo1, hi1, 0x5410;\n"
        "mov.b32 {xl, xh}, a1; tanh.approx.f16 xr, xl; cvt.u32.u16 lo1, xr; tanh.approx.f16 xr, xh; cvt.u32.u16 hi1, xr; mul.rn.f16x2 a2, qz30, p0; fma.rn.f16x2 p1, qz31, qz31, c; fma.rn.f16x2 g11, qz27, h1, qz27; prmt.b32 h0, lo0, hi0, 0x5410;\n"
        "B94:\n"
        "wgmma.wait_group.sync.aligned 0;\n"
        "wgmma.fence.sync.aligned;\n"
        "add.s64 dt, w2d, 1408; wgmma.mma_async.sync.aligned.m64n96k16.f16.f16.f16 {o0,o1,o2,o3,o4,o5,o6,o7,o8,o9,o10,o11,o12,o13,o14,o15,o16,o17,o18,o19,o20,o21,o22,o23}, {g8,g9,g10,g11}, dt, pt, 1, 1, 1;\n"
        "wgmma.commit_group.sync.aligned;\n"
        "@pz bra.uni B2;\n"
        "mov.b32 {xl, xh}, a2; tanh.approx.f16 xr, xl; cvt.u32.u16 lo0, xr; tanh.approx.f16 xr, xh; cvt.u32.u16 hi0, xr; mul.rn.f16x2 a3, qz31, p1; fma.rn.f16x2 p0, qz0, qz0, c; fma.rn.f16x2 g12, qz28, h0, qz28; prmt.b32 h1, lo1, hi1, 0x5410;\n"
        "mov.b32 {xl, xh}, a3; tanh.approx.f16 xr, xl; cvt.u32.u16 lo1, xr; tanh.approx.f16 xr, xh; cvt.u32.u16 hi1, xr; mul.rn.f16x2 a0, qz0, p0; fma.rn.f16x2 p1, qz1, qz1, c; fma.rn.f16x2 g13, qz29, h1, qz29; prmt.b32 h0, lo0, hi0, 0x5410;\n"
        "mov.b32 {xl, xh}, a0; tanh.approx.f16 xr, xl; cvt.u32.u16 lo0, xr; tanh.approx.f16 xr, xh; cvt.u32.u16 hi0, xr; mul.rn.f16x2 a1, qz1, p1; fma.rn.f16x2 p0, qz2, qz2, c; fma.rn.f16x2 g14, qz30, h0, qz30; prmt.b32 h1, lo1, hi1, 0x5410;\n"
        "mov.b32 {xl, xh}, a1; tanh.approx.f16 xr, xl; cvt.u32.u16 lo1, xr; tanh.approx.f16 xr, xh; cvt.u32.u16 hi1, xr; mul.rn.f16x2 a2, qz2, p0; fma.rn.f16x2 p1, qz3, qz3, c; fma.rn.f16x2 g15, qz31, h1, qz31; prmt.b32 h0, lo0, hi0, 0x5410;\n"
        "B2:\n"
        "wgmma.fence.sync.aligned;\n"
        "add.s64 dt, w2d, 1472; wgmma.mma_async.sync.aligned.m64n96k16.f16.f16.f16 {o0,o1,o2,o3,o4,o5,o6,o7,o8,o9,o10,o11,o12,o13,o14,o15,o16,o17,o18,o19,o20,o21,o22,o23}, {g12,g13,g14,g15}, dt, pt, 1, 1, 1;\n"
        "wgmma.commit_group.sync.aligned;\n"
        "@!pm bra.uni LAST;\n"
        "@pz bra.uni BE;\n"
        "mov.b32 {xl, xh}, a2; tanh.approx.f16 xr, xl; cvt.u32.u16 lo0, xr; tanh.approx.f16 xr, xh; cvt.u32.u16 hi0, xr; mul.rn.f16x2 a3, qz3, p1; fma.rn.f16x2 p0, qz4, qz4, c; fma.rn.f16x2 g0, qz0, h0, qz0; prmt.b32 h1, lo1, hi1, 0x5410;\n"
        "mov.b32 {xl, xh}, a3; tanh.approx.f16 xr, xl; cvt.u32.u16 lo1, xr; tanh.approx.f16 xr, xh; cvt.u32.u16 hi1, xr; mul.rn.f16x2 a0, qz4, p0; fma.rn.f16x2 p1, qz5, qz5, c; fma.rn.f16x2 g1, qz1, h1, qz1; prmt.b32 h0, lo0, hi0, 0x5410;\n"
        "mov.b32 {xl, xh}, a0; tanh.approx.f16 xr, xl; cvt.u32.u16 lo0, xr; tanh.approx.f16 xr, xh; cvt.u32.u16 hi0, xr; mul.rn.f16x2 a1, qz5, p1; fma.rn.f16x2 p0, qz6, qz6, c; fma.rn.f16x2 g2, qz2, h0, qz2; prmt.b32 h1, lo1, hi1, 0x5410;\n"
        "mov.b32 {xl, xh}, a1; tanh.approx.f16 xr, xl; cvt.u32.u16 lo1, xr; tanh.approx.f16 xr, xh; cvt.u32.u16 hi1, xr; mul.rn.f16x2 a2, qz6, p0; fma.rn.f16x2 p1, qz7, qz7, c; fma.rn.f16x2 g3, qz3, h1, qz3; prmt.b32 h0, lo0, hi0, 0x5410;\n"
        "BE:\n"
        "wgmma.wait_group.sync.aligned 0;\n"
        "bra.uni LOOP;\n"
        "STORE:\n"
        "bar.sync tt, 128;\n"
        "setp.lt.s32 pr, n, 0;\n"
        "@pr bra.uni STOREB;\n"
        "cvt.u64.u32 gp, off; add.s64 gp, gp, %11;\n"
        "elect.sync _|pr, 0xffffffff;\n"
        "@pr cp.async.bulk.global.shared::cta.bulk_group [gp], [%4], 12288;\n"
        "@pr cp.async.bulk.commit_group;\n"
        "bra.uni STOREB;\n"
        "YLOAD:\n"
        "cp.async.bulk.wait_group.read 0;\n"
        "@!pm bra.uni XLAST;\n"
        "sub.u32 ad, off, %8; cvt.u64.u32 gp, ad; add.s64 gp, gp, %11;\n"
        "elect.sync _|pr, 0xffffffff;\n"
        "@pr mbarrier.arrive.expect_tx.shared::cta.b64 _, [ybar], 12288;\n"
        "@pr cp.async.bulk.shared::cluster.global.mbarrier::complete_tx::bytes [%4], [gp], 12288, [ybar];\n"
        "cvt.u64.u32 gp, off; add.s64 gp, gp, %10;\n"
        "@pr cp.async.bulk.prefetch.L2.global.L2::cache_hint [gp], 12288, pol;\n"
        "bra.uni YLOADB;\n"
        "XLAST:\n"
        "cvt.u64.u32 gp, off; add.s64 gp, gp, %10;\n"
        "elect.sync _|pr, 0xffffffff;\n"
        "@pr mbarrier.arrive.expect_tx.shared::cta.b64 _, [xbar], 12288;\n"
        "@pr cp.async.bulk.shared::cluster.global.mbarrier::complete_tx::bytes.L2::cache_hint [%4], [gp], 12288, [xbar], pol;\n"
        "bra.uni YLOADB;\n"
        "XLOAD:\n"
        "bar.sync tt, 128;\n"
        "cvt.u64.u32 gp, off; add.s64 gp, gp, %10;\n"
        "elect.sync _|pr, 0xffffffff;\n"
        "@pr mbarrier.arrive.expect_tx.shared::cta.b64 _, [xbar], 12288;\n"
        "@pr cp.async.bulk.shared::cluster.global.mbarrier::complete_tx::bytes.L2::cache_hint [%4], [gp], 12288, [xbar], pol;\n"
        "bra.uni XLOADB;\n"
        "SPINY: mov.u32 cnt, 0;\n"
        "SPINYL:\n"
        "add.u32 tt, n, 1; and.b32 tt, tt, 1; mbarrier.try_wait.parity.shared::cta.b64 pw, [ybar], tt;\n"
        "@pw bra.uni BACKY;\n"
        "add.u32 cnt, cnt, 1; setp.lt.u32 pw, cnt, 0x100000;\n"
        "@pw bra.uni SPINYL;\n"
        "trap;\n"
        "SPINX: mov.u32 cnt, 0;\n"
        "SPINXL:\n"
        "and.b32 tt, n, 1; mbarrier.try_wait.parity.shared::cta.b64 pw, [xbar], tt;\n"
        "@pw bra.uni BACKX;\n"
        "add.u32 cnt, cnt, 1; setp.lt.u32 pw, cnt, 0x100000;\n"
        "@pw bra.uni SPINXL;\n"
        "trap;\n"
        "SPINT: mov.u32 cnt, 0;\n"
        "SPINTL:\n"
        "mad.lo.u32 tt, n, 8, tbar; mbarrier.try_wait.parity.shared::cta.b64 pw, [tt], tpar;\n"
        "@pw bra.uni BACKT;\n"
        "add.u32 cnt, cnt, 1; setp.lt.u32 pw, cnt, 0x100000;\n"
        "@pw bra.uni SPINTL;\n"
        "trap;\n"
        "SPINW0: mov.u32 cnt, 0;\n"
        "SPINW0L:\n"
        "mov.u32 tt, 231208; mbarrier.try_wait.parity.shared::cta.b64 pw, [tt], 0;\n"
        "@pw bra.uni BACKW0;\n"
        "add.u32 cnt, cnt, 1; setp.lt.u32 pw, cnt, 0x100000;\n"
        "@pw bra.uni SPINW0L;\n"
        "trap;\n"
        "SPINW1: mov.u32 cnt, 0;\n"
        "SPINW1L:\n"
        "mov.u32 tt, 231216; mbarrier.try_wait.parity.shared::cta.b64 pw, [tt], 0;\n"
        "@pw bra.uni BACKW1;\n"
        "add.u32 cnt, cnt, 1; setp.lt.u32 pw, cnt, 0x100000;\n"
        "@pw bra.uni SPINW1L;\n"
        "trap;\n"
        "SPINL: mov.u32 cnt, 0;\n"
        "SPINLL:\n"
        "and.b32 tt, n, 1; mbarrier.try_wait.parity.shared::cta.b64 pw, [xbar], tt;\n"
        "@pw bra.uni BACKL;\n"
        "add.u32 cnt, cnt, 1; setp.lt.u32 pw, cnt, 0x100000;\n"
        "@pw bra.uni SPINLL;\n"
        "trap;\n"
        "LAST:\n"
        "and.b32 tt, n, 1; mbarrier.try_wait.parity.shared::cta.b64 pw, [xbar], tt;\n"
        "@!pw bra.uni SPINL;\n"
        "BACKL:\n"
        "and.b32 ad, %6, 0xffff; add.u32 ad, ad, %4; ld.shared.v4.b32 {r0,r1,r2,r3}, [ad+0];\n"
        "shr.u32 ad, %6, 16; add.u32 ad, ad, %4; ld.shared.v4.b32 {r4,r5,r6,r7}, [ad+0];\n"
        "and.b32 ad, %6, 0xffff; add.u32 ad, ad, %4; ld.shared.v4.b32 {r8,r9,r10,r11}, [ad+64];\n"
        "shr.u32 ad, %6, 16; add.u32 ad, ad, %4; ld.shared.v4.b32 {r12,r13,r14,r15}, [ad+64];\n"
        "and.b32 ad, %6, 0xffff; add.u32 ad, ad, %4; ld.shared.v4.b32 {r16,r17,r18,r19}, [ad+128];\n"
        "shr.u32 ad, %6, 16; add.u32 ad, ad, %4; ld.shared.v4.b32 {r20,r21,r22,r23}, [ad+128];\n"
        "wgmma.wait_group.sync.aligned 0;\n"
        "mov.b32 {xl, xh}, o0; cvt.f32.f16 f0, xl; cvt.f32.f16 f1, xh; cvt.rn.bf16x2.f32 tt, f1, f0; fma.rn.bf16x2 r0, tt, osc, r0;\n"
        "mov.b32 {xl, xh}, o2; cvt.f32.f16 f0, xl; cvt.f32.f16 f1, xh; cvt.rn.bf16x2.f32 tt, f1, f0; fma.rn.bf16x2 r1, tt, osc, r1;\n"
        "mov.b32 {xl, xh}, o4; cvt.f32.f16 f0, xl; cvt.f32.f16 f1, xh; cvt.rn.bf16x2.f32 tt, f1, f0; fma.rn.bf16x2 r2, tt, osc, r2;\n"
        "mov.b32 {xl, xh}, o6; cvt.f32.f16 f0, xl; cvt.f32.f16 f1, xh; cvt.rn.bf16x2.f32 tt, f1, f0; fma.rn.bf16x2 r3, tt, osc, r3;\n"
        "and.b32 ad, %6, 0xffff; add.u32 ad, ad, off; cvt.u64.u32 gp, ad; add.s64 gp, gp, %11; st.global.v4.b32 [gp+0], {r0,r1,r2,r3};\n"
        "mov.b32 {xl, xh}, o1; cvt.f32.f16 f0, xl; cvt.f32.f16 f1, xh; cvt.rn.bf16x2.f32 tt, f1, f0; fma.rn.bf16x2 r4, tt, osc, r4;\n"
        "mov.b32 {xl, xh}, o3; cvt.f32.f16 f0, xl; cvt.f32.f16 f1, xh; cvt.rn.bf16x2.f32 tt, f1, f0; fma.rn.bf16x2 r5, tt, osc, r5;\n"
        "mov.b32 {xl, xh}, o5; cvt.f32.f16 f0, xl; cvt.f32.f16 f1, xh; cvt.rn.bf16x2.f32 tt, f1, f0; fma.rn.bf16x2 r6, tt, osc, r6;\n"
        "mov.b32 {xl, xh}, o7; cvt.f32.f16 f0, xl; cvt.f32.f16 f1, xh; cvt.rn.bf16x2.f32 tt, f1, f0; fma.rn.bf16x2 r7, tt, osc, r7;\n"
        "shr.u32 ad, %6, 16; add.u32 ad, ad, off; cvt.u64.u32 gp, ad; add.s64 gp, gp, %11; st.global.v4.b32 [gp+0], {r4,r5,r6,r7};\n"
        "mov.b32 {xl, xh}, o8; cvt.f32.f16 f0, xl; cvt.f32.f16 f1, xh; cvt.rn.bf16x2.f32 tt, f1, f0; fma.rn.bf16x2 r8, tt, osc, r8;\n"
        "mov.b32 {xl, xh}, o10; cvt.f32.f16 f0, xl; cvt.f32.f16 f1, xh; cvt.rn.bf16x2.f32 tt, f1, f0; fma.rn.bf16x2 r9, tt, osc, r9;\n"
        "mov.b32 {xl, xh}, o12; cvt.f32.f16 f0, xl; cvt.f32.f16 f1, xh; cvt.rn.bf16x2.f32 tt, f1, f0; fma.rn.bf16x2 r10, tt, osc, r10;\n"
        "mov.b32 {xl, xh}, o14; cvt.f32.f16 f0, xl; cvt.f32.f16 f1, xh; cvt.rn.bf16x2.f32 tt, f1, f0; fma.rn.bf16x2 r11, tt, osc, r11;\n"
        "and.b32 ad, %6, 0xffff; add.u32 ad, ad, off; cvt.u64.u32 gp, ad; add.s64 gp, gp, %11; st.global.v4.b32 [gp+64], {r8,r9,r10,r11};\n"
        "mov.b32 {xl, xh}, o9; cvt.f32.f16 f0, xl; cvt.f32.f16 f1, xh; cvt.rn.bf16x2.f32 tt, f1, f0; fma.rn.bf16x2 r12, tt, osc, r12;\n"
        "mov.b32 {xl, xh}, o11; cvt.f32.f16 f0, xl; cvt.f32.f16 f1, xh; cvt.rn.bf16x2.f32 tt, f1, f0; fma.rn.bf16x2 r13, tt, osc, r13;\n"
        "mov.b32 {xl, xh}, o13; cvt.f32.f16 f0, xl; cvt.f32.f16 f1, xh; cvt.rn.bf16x2.f32 tt, f1, f0; fma.rn.bf16x2 r14, tt, osc, r14;\n"
        "mov.b32 {xl, xh}, o15; cvt.f32.f16 f0, xl; cvt.f32.f16 f1, xh; cvt.rn.bf16x2.f32 tt, f1, f0; fma.rn.bf16x2 r15, tt, osc, r15;\n"
        "shr.u32 ad, %6, 16; add.u32 ad, ad, off; cvt.u64.u32 gp, ad; add.s64 gp, gp, %11; st.global.v4.b32 [gp+64], {r12,r13,r14,r15};\n"
        "mov.b32 {xl, xh}, o16; cvt.f32.f16 f0, xl; cvt.f32.f16 f1, xh; cvt.rn.bf16x2.f32 tt, f1, f0; fma.rn.bf16x2 r16, tt, osc, r16;\n"
        "mov.b32 {xl, xh}, o18; cvt.f32.f16 f0, xl; cvt.f32.f16 f1, xh; cvt.rn.bf16x2.f32 tt, f1, f0; fma.rn.bf16x2 r17, tt, osc, r17;\n"
        "mov.b32 {xl, xh}, o20; cvt.f32.f16 f0, xl; cvt.f32.f16 f1, xh; cvt.rn.bf16x2.f32 tt, f1, f0; fma.rn.bf16x2 r18, tt, osc, r18;\n"
        "mov.b32 {xl, xh}, o22; cvt.f32.f16 f0, xl; cvt.f32.f16 f1, xh; cvt.rn.bf16x2.f32 tt, f1, f0; fma.rn.bf16x2 r19, tt, osc, r19;\n"
        "and.b32 ad, %6, 0xffff; add.u32 ad, ad, off; cvt.u64.u32 gp, ad; add.s64 gp, gp, %11; st.global.v4.b32 [gp+128], {r16,r17,r18,r19};\n"
        "mov.b32 {xl, xh}, o17; cvt.f32.f16 f0, xl; cvt.f32.f16 f1, xh; cvt.rn.bf16x2.f32 tt, f1, f0; fma.rn.bf16x2 r20, tt, osc, r20;\n"
        "mov.b32 {xl, xh}, o19; cvt.f32.f16 f0, xl; cvt.f32.f16 f1, xh; cvt.rn.bf16x2.f32 tt, f1, f0; fma.rn.bf16x2 r21, tt, osc, r21;\n"
        "mov.b32 {xl, xh}, o21; cvt.f32.f16 f0, xl; cvt.f32.f16 f1, xh; cvt.rn.bf16x2.f32 tt, f1, f0; fma.rn.bf16x2 r22, tt, osc, r22;\n"
        "mov.b32 {xl, xh}, o23; cvt.f32.f16 f0, xl; cvt.f32.f16 f1, xh; cvt.rn.bf16x2.f32 tt, f1, f0; fma.rn.bf16x2 r23, tt, osc, r23;\n"
        "shr.u32 ad, %6, 16; add.u32 ad, ad, off; cvt.u64.u32 gp, ad; add.s64 gp, gp, %11; st.global.v4.b32 [gp+128], {r20,r21,r22,r23};\n"
        ASM_MARK
        "}\n"
        :: "r"(prm.w1desc), "r"(prm.w2desc), "r"(c.wg), "r"(c.off), "r"(c.xs), "r"(c.a_offs), "r"(c.xs_offs), "r"(c.bias_addr),
           "r"(c.step), "r"(c.w), "l"(prm.x), "l"(prm.out)
        : "memory");
}

__device__ __forceinline__ float warp_sum(float v) {
#pragma unroll
    for (int s = 16; s >= 1; s >>= 1) v += __shfl_xor_sync(0xffffffffu, v, s);
    return v;
}
__device__ __forceinline__ float pow2f(int e) { return __uint_as_float((uint32_t)(e + 127) << 23); }
__device__ __forceinline__ int exponent_of(float v) { return (int)(__float_as_uint(v) >> 23) - 127; }
__device__ __forceinline__ float lds_bf16(uint32_t addr) {
    uint16_t v; asm volatile("ld.shared.u16 %0, [%1];" : "=h"(v) : "r"(addr) : "memory"); return bf_lo(v);
}

__device__ __forceinline__ void publish_bias(const Params& prm, uint32_t c, uint32_t tag) {
    const uint32_t lane = fresh_tid() & 31;
    const uint32_t col = sb + SM_W2 + (c >> 5) * 24576 + lane * 64 + ((((c >> 3) ^ (lane >> 1)) & 3) * 16) + (c & 7) * 2;
    float v = 0.0f;
#pragma unroll
    for (int k = 0; k < EX / 32; k++) v = fmaf(lds_bf16(col + k * 2048), lds_bf16(sb + SM_BETA + lane * 2 + k * 64), v);
    v = warp_sum(v);
    if (lane == 0)
        asm volatile("st.relaxed.gpu.global.u64 [%0], %1;" ::"l"(prm.g->bias + c), "l"((uint64_t)tag << 32 | __float_as_uint(v)) : "memory");
}
__device__ __forceinline__ void collect_bias(const Params& prm, uint32_t tag) {
    const uint32_t lane = fresh_tid() & 31;
    if (lane < 24) {
        const unsigned long long* src = prm.g->bias + 32 * (lane >> 3) + 8 * (lane & 3) + (lane & 4);
        uint32_t v[4], t[4], spins = 0;
        for (;;) {
#pragma unroll
            for (int k = 0; k < 4; k++)
                asm volatile("{\n.reg .b64 w;\nld.relaxed.gpu.global.u64 w, [%2];\nmov.b64 {%0, %1}, w;\n}\n"
                             : "=r"(v[k]), "=r"(t[k]) : "l"(src + k) : "memory");
            if (t[0] == tag && t[1] == tag && t[2] == tag && t[3] == tag) break;
            if (++spins > (1u << 22)) __trap();
        }
        sts128(sb + SM_BIAS + lane * 16, v[0], v[1], v[2], v[3]);
    }
    __syncwarp();
}
__device__ __forceinline__ float fetch_w2_row(uint32_t (&u)[12][4], uint32_t row, uint32_t sw) {
    uint32_t mx[4] = {};
#pragma unroll
    for (int a = 0; a < 3; a++)
#pragma unroll
        for (int k = 0; k < 4; k++) {
            asm volatile("ld.shared.v4.b32 {%0,%1,%2,%3}, [%4];"
                         : "=r"(u[a * 4][k]), "=r"(u[a * 4 + 1][k]), "=r"(u[a * 4 + 2][k]), "=r"(u[a * 4 + 3][k])
                         : "r"(row + a * 24576 + ((k * 16) ^ sw)) : "memory");
#pragma unroll
            for (int b = 0; b < 4; b++) asm("max.xorsign.abs.bf16x2 %0, %0, %1;" : "+r"(mx[b]) : "r"(u[a * 4 + b][k]));
        }
#pragma unroll
    for (int b = 1; b < 4; b++) asm("max.xorsign.abs.bf16x2 %0, %0, %1;" : "+r"(mx[0]) : "r"(mx[b]));
    return fmaxf(fabsf(bf_lo(mx[0])), fabsf(bf_hi(mx[0])));
}

template <bool FAST> __device__ __forceinline__ bool grn_stats(float ss, float gm, float bt, float top, int e, float& gx, float& inv, int& eo) {
    gx = sqrt_fast(fmaf(ss, INV_2A * INV_2A, 1e-6f));
    const float rt = sqrt_fast(ss + 1.0f) * INV_2A * top;
    uint32_t r[4] = {FAST ? __reduce_add_sync(0xffffffffu, __float2uint_rn(gx * 128.0f)) : __float_as_uint(warp_sum(gx)),
                     __reduce_max_sync(0xffffffffu, __float_as_uint(fmaf(bt, top, rt))),
                     __reduce_max_sync(0xffffffffu, __float_as_uint(rt * fabsf(gm) * gx)),
                     (uint32_t)__any_sync(0xffffffffu, !(ss >= 16.0f && ss < ACC_LIMIT))};
    if ((e & 31) == 0) sts128(sb + SM_SEL + (e >> 5) * 16, r[0], r[1], r[2], r[3]);
    MARK(6);
    named_sync(10, 512);
    lds128(r, sb + SM_SEL + min(e & 15, 11) * 16);
    if ((e & 31) >= 12) r[0] = 0;
    const float tot = FAST ? __uint2float_rn(__reduce_add_sync(0xffffffffu, r[0])) * (1.0f / 128) : warp_sum(__uint_as_float(r[0]));
    inv = __fdividef(1.0f, fmaf(tot, 1.0f / EX, 1e-6f));
    const float bound = fmaf(__uint_as_float(__reduce_max_sync(0xffffffffu, r[2])), inv,
                             __uint_as_float(__reduce_max_sync(0xffffffffu, r[1]))) * EX;
    eo = min(max(exponent_of(bound), -90), 126) - 14;
    return __any_sync(0xffffffffu, r[3]);
}

__device__ __forceinline__ float exact_sums(const Params& prm) {
    const int lane = fresh_tid() & 31, warp = fresh_warp(), wg = warp >> 2;
    const uint32_t epoch = lds32(sb + SM_RED + (RED_EPOCH + 1) * 4), bar = sb + SM_BAR + BAR_W1 * 8;
    if (wg < 3) {
        uint32_t wa[2][24], d[2][16];
        float acc[2][2] = {};
        const uint32_t yd = prm.ydesc + ((SM_SPARE - SM_Y1) >> 4), wd = prm.w1desc + ((2 * wg * 12288 + 5 * 2048) >> 4);
        load_w1t(wa, wg, warp & 3, lane);
#pragma unroll 1
        for (int n = 0; n < ROWS_PER_CTA; n++) {
            if (warp == 0) {
                expect_tx(bar, TILE_BYTES);
                bulk_load(sb + SM_SPARE, (const char*)prm.out + (cta_tile0(fresh_cta()) + n * cta_stride(fresh_cta())), TILE_BYTES, bar);
            }
            mbar_wait(bar, (n + 1) & 1);
            gemm1_t<0>(d[0], wa[0], yd, wd);
            gemm1_t<1>(d[1], wa[1], yd, wd);
            wg_wait<0>();
            pin(d[0]); pin(d[1]);
            gelu_sumsq_f(d[0], acc[0]);
            gelu_sumsq_f(d[1], acc[1]);
            named_sync(1, 384);
        }
        publish_sums(acc, prm.g->sums[epoch & 1], &prm.g->count[1], wg, warp & 3, lane);
    }
    grid_wait(&prm.g->count[1], (epoch + 1) * NUM_CTAS);
    return __ldcg(prm.g->sums[epoch & 1] + fresh_tid() % EX);
}

template <bool FIRST> __device__ __forceinline__ void prepare_pass2(const Pass2& c, const Params& prm, float ss) {
    const int tid = fresh_tid(), lane = tid & 31, warp = fresh_warp(), wg = warp >> 2;
    const int e = tid >= EX ? tid - EX : tid;
    const uint32_t w2row = sb + SM_W2 + e * 64, sw = ((e >> 1) & 3) * 16;
    pass2_start(c, prm);
    MARK(2);
    if (wg) {
        uint32_t u[12][4];
        mbar_wait_c<0>(sb + SM_BAR + BAR_W2 * 8);
        const uint32_t epoch = lds32(sb + SM_RED + RED_EPOCH * 4);
        unsigned long long seen = 0;
        if (FIRST) asm volatile("ld.relaxed.gpu.global.u64 %0, [%1];" : "=l"(seen) : "l"(acc_word(prm, epoch, e)) : "memory");
        const float top = fetch_w2_row(u, w2row, sw);
        MARK(3);
        const float gm = lds_bf16(sb + SM_GAMMA + e * 2), bt = fabsf(lds_bf16(sb + SM_BETA + e * 2));
        if (FIRST) {
            if (wg == 3) named_sync(11, EX);
            if (warp == 12) collect_bias(prm, epoch + 1);
            MARK(4);
            ss = collect_fast(acc_word(prm, epoch, e), seen);
            if (tid == 416 && fresh_cta() == 0) prm.g->count[0] = epoch + 1;
        }
        if (warp == 4) TS(4);
        MARK(5);
        float gx, inv;
        int eo;
        const bool redo = (grn_stats<FIRST>(ss, gm, bt, top, e, gx, inv, eo) || FORCE_EXACT) && FIRST;
        MARK(8);
        const float up = pow2f(eo), dn = pow2f(-eo);
        if (warp == 4) {
            if (lane == 24) sts64(sb + SM_RED + RED_SCALE * 4, pack_bf2(up, up), redo);
            if (lane < 24 && !redo) {
                uint32_t b[4];
                lds128(b, sb + SM_BIAS + lane * 16);
                const uint32_t p0 = pack_h2(__uint_as_float(b[0]) * dn, __uint_as_float(b[1]) * dn);
                const uint32_t p1 = pack_h2(__uint_as_float(b[2]) * dn, __uint_as_float(b[3]) * dn);
                sts128(sb + SM_BIAS + lane * 16, p0, p0, p1, p1);
            }
            __syncwarp();
            mbar_arrive_if(sb + SM_BAR + BAR_STAT * 8, lane == 0);
        }
        if (!redo) {
            float sc = fmaf(gm, gx * inv, 1.0f) * INV_2A;
            if (eo > 6) {
                const uint32_t dn2 = pack_bf2(dn, dn);
#pragma unroll
                for (int k = 0; k < 48; k++) u[k >> 2][k & 3] = bf2_mul(u[k >> 2][k & 3], dn2);
            } else {
                sc *= dn;
            }
            const uint32_t s2 = pack_bf2(sc * 0x1p-112f, sc * 0x1p-112f);
#pragma unroll
            for (int k = 0; k < 12; k++) {
                uint32_t v[4];
#pragma unroll
                for (int b = 0; b < 4; b++) {
                    v[b] = bf2_mul(u[k][b], s2);
                    v[b] += (v[b] & 0x7fff7fffu) * 7u;
                }
                sts128(w2row + (k >> 2) * 24576 + (((k & 3) * 16) ^ sw), v[0], v[1], v[2], v[3]);
            }
            MARK(9);
            fence_async_smem();
            __syncwarp();
            mbar_arrive_if(sb + SM_BAR + (BAR_ROWS + (wg != 3)) * 8, lane == 0);
        }
        if (warp == 4) TS(5);
    } else {
        asm volatile("bar.arrive 10, 512;" ::: "memory");
    }
}

__device__ __forceinline__ void pass2_uniform(Pass2& c) {
    const int warp = fresh_warp(), wg = warp >> 2;
    c.wg = wg;
    c.w = warp & 3;
    c.off = cta_tile0(fresh_cta()) + (ROWS_PER_CTA - 1 - wg) * cta_stride(fresh_cta());
    c.step = 4 * cta_stride(fresh_cta());
    c.xs = wg == 3 ? sb + SM_BUF3 : sb + SM_Y1 + (wg == 2 ? 2 : 1 - wg) * SLOT_BYTES;
    static_assert((ROWS_PER_CTA - 1) % NX == 1, "slot of the last tile");
}
__device__ __forceinline__ Pass2 pass2_setup() {
    Pass2 c;
    pass2_uniform(c);
    const int lane = fresh_tid() & 31, w = c.w, arow = 16 * w + (lane & 15);
    c.a_offs = (arow * 128 + (((lane >> 4) ^ (arow & 7)) * 16)) |
               (8192 + arow * 64 + (((lane >> 4) ^ ((arow >> 1) & 3)) * 16)) << 16;
    const int g = lane >> 2, px = 33 * (g & 1) + 4 * (g >> 1) + 16 * (w >> 1) + 2 * (w & 1);
    c.xs_offs = (px * 192 + (lane & 3) * 16) | ((px ^ 1) * 192 + (lane & 3) * 16) << 16;
    c.bias_addr = sb + SM_BIAS + (lane & 3) * 16;
    return c;
}

__global__ void __launch_bounds__(512, 1) convnext_kernel(const __grid_constant__ Params prm) {
    extern __shared__ __align__(1024) uint8_t smem[];
    if ((uint32_t)__cvta_generic_to_shared(smem) != sb) __trap();
    {
        const uint32_t tid = fresh_tid(), warp = fresh_warp(), lane = tid & 31;
        if (warp == 0) {
            if (lane == 0) {
#pragma unroll
                for (int k = 0; k < NX; k++) mbar_init(sb + SM_GO + k * 8, 2);
                mbar_init(sb + SM_BAR + BAR_DW * 8, 1);
                mbar_init(sb + SM_BAR + BAR_W1 * 8, 1);
                mbar_init(sb + SM_BAR + BAR_W1B * 8, 1);
                fence_async_smem();
            }
            __syncwarp();
            expect_tx(sb + SM_BAR + BAR_DW * 8, 9 * CH * 2);
            bulk_load(sb + SM_Y1, prm.dw, 9 * CH * 2, sb + SM_BAR + BAR_DW * 8);
            const RowCopy rc = row_copy(prm);
#pragma unroll
            for (int k = 0; k < NX; k++) issue_row_load(rc, k, k);
            SMARK(4);
        }
        if (fresh_warp() == 15) {
            const uint32_t cta = fresh_cta();
            bulk_prefetch((const char*)prm.w1 + cta * (CH * EX * 2 / NUM_CTAS), CH * EX * 2 / NUM_CTAS);
            bulk_prefetch(prm.dw, 9 * CH * 2);
            bulk_prefetch((const char*)prm.x + (cta_tile0(cta) - cta_stride(cta)), TILE_BYTES);
        } else if (warp == 2) {
            if (lane < 2) asm volatile("prefetch.tensormap [%0];" ::"l"(&prm.w1_map + lane) : "memory");
        } else if (warp - 6u < 6) {
            if (lane == 0) {
#pragma unroll 1
                for (int k = NX + warp - 6; k < GO_COUNT + ROWS_PER_CTA + 2; k += 6)
                    mbar_init(sb + SM_GO + k * 8, k < 2 * NX ? 2 : k < GO_COUNT ? 14 : 4);
                fence_async_smem();
            }
        } else if (warp == 3) {
            const uint32_t one = (lane & 5) == ((lane & 8) >> 1) + (lane >> 4) ? 0x3f803f80u : 0u;
            sts128(sb + SM_SEL + lane * 16, one, one, one, one);
            fence_async_smem();
        } else if (tid - 128u < NX * 12 && ((fresh_cta() + 1) & 7) < 2) {
            const int k = tid - 128;
            sts128(sb + SM_X + (k / 12) * SLOT_BYTES + ((fresh_cta() & 7) == 0 ? 0 : XHALF_B + 33 * 192) + (k % 12) * 16, 0, 0, 0, 0);
        }
        __syncwarp();
        SMARK(3);
        named_sync(0, 512);
    }
    if (fresh_warp() >= 12) {
        Producer pc;
        SMARK(0);
        asm volatile("setmaxnreg.inc.sync.aligned.u32 %0;" ::"n"(PRODUCER_REGS));
        SMARK(1);
        const int w = fresh_warp() & 3, lane = fresh_tid() & 31;
        const int j = lane & 7, hb = (lane >> 3) & 1, base = 4 * (2 * w + (lane >> 4));
        pc.lane = lane;
        pc.xoff[0] = hb * XHALF_B + base * 192 + j * 16;
        pc.xoff[1] = hb * XHALF_B + base * 192 + 128 + j * 8;
        const int grp = 4 * w + (lane >> 3);
#pragma unroll
        for (int o = 0; o < 2; o++) {
            const int row = (grp & 7) + 8 * (o ^ hb) + 32 * (grp >> 3);
            pc.yoff[0][o] = row * 128 + ((j ^ (row & 7)) * 16);
            pc.yoff[1][o] = 8192 + row * 64 + (((j >> 1) ^ ((row >> 1) & 3)) * 16) + (j & 1) * 8;
        }
        pc.stat = sb + SM_STAT + (8 * w + (lane >> 2)) * 32;
        pc.own = pc.stat + (lane & 3) * 8;
        const int dstep = fresh_cta() & 8 ? 3 * CH * 2 : -3 * CH * 2;
        mbar_wait_c<0>(sb + SM_BAR + BAR_DW * 8);
        SMARK(8);
#pragma unroll
        for (int tap = 0; tap < 9; tap++) {
            const uint32_t dw = sb + SM_Y1 + (3 + tap % 3) * CH * 2 + (tap / 3 - 1) * dstep;
            lds128(pc.w[tap], dw + j * 16);
            asm volatile("ld.shared.v2.b32 {%0,%1}, [%2];" : "=r"(pc.w[tap][4]), "=r"(pc.w[tap][5]) : "r"(dw + 128 + j * 8) : "memory");
        }
#pragma unroll
        for (int tap = 0; tap < 9; tap++)
#pragma unroll
            for (int u = 0; u < 6; u++) pc.w[tap][u] = bf2_mul(pc.w[tap][u], TAP_SCALE_BF2);
        produce(pc, prm);
        TS(9);
        asm volatile("setmaxnreg.dec.sync.aligned.u32 %0;" ::"n"(EVEN_REGS));
        if (fresh_warp() == 12) {
            mbar_wait_c<0>(sb + SM_BAR + BAR_W2 * 8);
            if (fresh_cta() < CH) publish_bias(prm, fresh_cta(), lds32(sb + SM_RED + RED_EPOCH * 4) + 1);
        }
    } else {
        asm volatile("setmaxnreg.dec.sync.aligned.u32 %0;" ::"n"(CONSUMER_REGS));
        {
            const int tid = fresh_tid(), warp = fresh_warp();
            if (warp == 1) {
#pragma unroll
                for (int h = 0; h < 2; h++) {
                    const uint32_t bar = sb + SM_BAR + (h ? BAR_W1B : BAR_W1) * 8;
                    expect_tx(bar, CH * EX);
#pragma unroll
                    for (int q = h; q < 6; q += 2) tma_load_2d(sb + SM_W1 + q * 12288, &prm.w1_map, 64 * q, 0, bar);
                }
            }
            uint32_t cnt[2];
            asm volatile("ld.relaxed.gpu.global.v2.u32 {%0, %1}, [%2];" : "=r"(cnt[0]), "=r"(cnt[1]) : "l"(prm.g->count) : "memory");
            SMARK(0);
            if (warp == 2) {
                const RowCopy rc = row_copy(prm);
#pragma unroll 1
                for (int i = loop_init<0>(); i < NX - 1; i++) {
                    named_sync(6 + i, 160);
                    issue_row_load(rc, i + NX, i);
                }
            }
            if (tid == 256) {
                sts64(sb + SM_RED + RED_EPOCH * 4, cnt[0], cnt[1] / NUM_CTAS);
#pragma unroll
                for (int k = 0; k < BAR_DW; k++)
                    if (k != BAR_W1 && k != BAR_W1B) mbar_init(sb + SM_BAR + k * 8, k < BAR_TURN || k == BAR_STAT ? 1 : k == BAR_ROWS + 1 ? 8 : 4);
#pragma unroll
                for (int k = 0; k < 3; k++) mbar_arrive_if(sb + SM_BAR + (BAR_Y2FULL + k) * 8, true);
            }
            if (fresh_cta() == 0) *acc_word(prm, cnt[0] + 1, tid) = 0;
            if (fresh_cta() == 1) prm.g->sums[~(cnt[1] / NUM_CTAS) & 1][tid] = 0.0f;
            __syncwarp();
            SMARK(1);
            mbar_wait_c<0>(sb + SM_BAR + BAR_W1 * 8);
            SMARK(2);
        }

        const int tid = fresh_tid(), lane = tid & 31, wg = fresh_warp() >> 2, w = fresh_warp() & 3;
        float acc[2][2];
        const int c = 8 * (lane >> 4) + (lane & 7), ck = 2 * w + ((lane >> 3) & 1);
        consume(acc, sb + SM_W1 + 2 * wg * 12288 + c * 128 + ((ck ^ (c & 7)) * 16), prm.ydesc,
                prm.w1desc + (((2 * wg + 1) * 12288 + 5 * 2048) >> 4), wg * SLOT_BYTES, make_duty(prm, wg, w), w, lane, prm);
        publish_fast(prm, acc, lds32(sb + SM_RED + RED_EPOCH * 4), wg, w, lane);
        if (wg) asm volatile("bar.arrive 11, 384;" ::: "memory");
        MARK(0);
        bulk_wait_all();
        if (wg == 0) TS(3);
        asm volatile("setmaxnreg.inc.sync.aligned.u32 %0;" ::"n"(EVEN_REGS));
    }

    {
        asm volatile(PASS2_STATE);
        MARK(1);
        Pass2 c = pass2_setup();
        prepare_pass2<true>(c, prm, 0.0f);
        if (pass2_head(c, 0)) {
            const float ss = exact_sums(prm);
            c = pass2_setup();
            prepare_pass2<false>(c, prm, ss);
            pass2_head(c, 1);
        }

        pass2_uniform(c);
        pass2_tiles(c, prm);
        bulk_wait_read<0>();
        MARK(13);
    }
}

}

extern "C" void kernel_launch(void* const* d_in, const int* in_sizes, int n_in, void* d_out, int out_size) {
    (void)in_sizes; (void)n_in; (void)out_size;
    typedef CUresult (*EncodeFn)(CUtensorMap*, CUtensorMapDataType, cuuint32_t, void*, const cuuint64_t*, const cuuint64_t*,
                                 const cuuint32_t*, const cuuint32_t*, CUtensorMapInterleave, CUtensorMapSwizzle,
                                 CUtensorMapL2promotion, CUtensorMapFloatOOBfill);
    void* fn = nullptr;
    cudaDriverEntryPointQueryResult status;
    cudaGetDriverEntryPoint("cuTensorMapEncodeTiled", &fn, cudaEnableDefault, &status);
    const EncodeFn encode = (EncodeFn)fn;
    const cuuint32_t ones[2] = {1, 1};

    Params p;
    {
        const cuuint64_t dims[2] = {EX, CH}, strides[1] = {EX * 2};
        const cuuint32_t box[2] = {64, CH};
        encode(&p.w1_map, CU_TENSOR_MAP_DATA_TYPE_BFLOAT16, 2, d_in[2], dims, strides, box, ones,
               CU_TENSOR_MAP_INTERLEAVE_NONE, CU_TENSOR_MAP_SWIZZLE_128B, CU_TENSOR_MAP_L2_PROMOTION_NONE,
               CU_TENSOR_MAP_FLOAT_OOB_FILL_NONE);
    }
    {
        const cuuint64_t dims[2] = {CH, EX}, strides[1] = {CH * 2};
        const cuuint32_t box[2] = {32, 192};
        encode(&p.w2_map, CU_TENSOR_MAP_DATA_TYPE_BFLOAT16, 2, d_in[3], dims, strides, box, ones,
               CU_TENSOR_MAP_INTERLEAVE_NONE, CU_TENSOR_MAP_SWIZZLE_64B, CU_TENSOR_MAP_L2_PROMOTION_NONE,
               CU_TENSOR_MAP_FLOAT_OOB_FILL_NONE);
    }
    p.x = (const __nv_bfloat16*)d_in[0];
    p.dw = (const __nv_bfloat16*)d_in[1];
    p.w1 = (const __nv_bfloat16*)d_in[2];
    p.gamma = (const __nv_bfloat16*)d_in[4];
    p.beta = (const __nv_bfloat16*)d_in[5];
    p.out = (__nv_bfloat16*)d_out;
    cudaGetSymbolAddress((void**)&p.g, g_scratch);
    p.w1desc = desc_lo(sb + SM_W1, 12288);
    p.w2desc = desc_lo(sb + SM_W2, 24576);
    p.ydesc = desc_lo(sb + SM_Y1, 16);
    p.ydesc64[0] = (0x40000040ull << 32) | p.ydesc;
    p.ydesc64[1] = (0x80000020ull << 32) | (p.ydesc + 512);
    for (int k = 0; k < 3; k++) p.sel[k] = (8ull << 32) | desc_lo(sb + SM_SEL + k * 128, k == 2 ? 128 : 0);
    constexpr int smem_bytes = SM_TOTAL;
    cudaFuncSetAttribute(convnext_kernel, cudaFuncAttributeMaxDynamicSharedMemorySize, smem_bytes);
    convnext_kernel<<<NUM_CTAS, 512, smem_bytes>>>(p);
}
```

```cpp
#include <cuda.h>
#include <cuda_runtime.h>
#include <cuda_bf16.h>
#include <stdint.h>

namespace {

constexpr int IMG_W = 512, CH = 96, EX = 384;
constexpr int TILE_PX = 64;
constexpr int ROWS_PER_CTA = 32;
constexpr int NUM_CTAS = 128;
constexpr int STEPS = ROWS_PER_CTA + 2;
constexpr int ROW_BYTES = IMG_W * CH * 2;

#define FORCE_EXACT 0
constexpr int PRODUCER_REGS = 200, CONSUMER_REGS = 104, EVEN_REGS = 128;

constexpr int XHALF_BYTES = 34 * 192;
constexpr int XHALF_B = XHALF_BYTES + 64;
constexpr int XROW_BYTES = XHALF_B + XHALF_BYTES + 64;
constexpr int L2_AHEAD = 2;
constexpr int NX = 3;
constexpr int TILE_BYTES = TILE_PX * 192;

constexpr uint32_t sb = 1024;
constexpr int SM_W1 = 0;
constexpr int SM_W2 = 73728;
constexpr int SM_RING = 147456;
constexpr int SLOT_BYTES = 26624;
constexpr int SM_Y1 = SM_RING;
constexpr int SM_X = SM_Y1 + TILE_BYTES;
constexpr int SM_STAT = SM_X + XROW_BYTES;
constexpr int SM_BUF3 = SM_X + SLOT_BYTES, SM_SPARE = SM_X;
constexpr int SM_SEL = SM_RING + NX * SLOT_BYTES;
constexpr int SM_BIAS = SM_SEL + 512;
constexpr int SM_GAMMA = SM_BIAS + 384;
constexpr int SM_BETA = SM_GAMMA + EX * 2;
constexpr int SM_RED = SM_BETA + EX * 2;
constexpr int SM_BAR = SM_RED + 16;
constexpr int BAR_Y2FULL = 0, BAR_XSFULL = 4, BAR_W1 = 8, BAR_W2 = 9, BAR_W1B = 10, BAR_TURN = 11, BAR_ROWS = 51,
              BAR_STAT = 54, BAR_DW = 55, BAR_COUNT = 56;
constexpr int SM_GO = SM_BAR + BAR_COUNT * 8, GO_COUNT = ROWS_PER_CTA + 2 * NX;
constexpr int SM_YFULL = SM_GO + (GO_COUNT + 1) * 8;
constexpr int SM_TOTAL = SM_YFULL + (ROWS_PER_CTA + 1) * 8;
static_assert(SM_STAT + TILE_PX * 16 <= SM_RING + SLOT_BYTES && XROW_BYTES >= TILE_BYTES && SM_X % 1024 == 0, "ring layout");
static_assert(SM_TOTAL <= 232448, "smem budget");
static_assert(SM_STAT % 128 == 0 && SM_BIAS % 16 == 0 && SM_BAR % 8 == 0 && SLOT_BYTES % 1024 == 0, "alignment");

constexpr int RED_EPOCH = 0, RED_SCALE = 2;

constexpr float GELU_A = 0.32920349f;
constexpr uint32_t GELU_C_H2 = 0x40D940D9u;
constexpr float INV_2A = 1.0f / (2.0f * GELU_A);

constexpr uint32_t TAP_SCALE_BF2 = 0x2B802B80u;
constexpr float LN_EPS_SCALED = 1e-5f * 0x1p-80f;
constexpr float RSTD_SCALE = GELU_A * 0x1p-112f;

struct Scratch {
    unsigned long long acc[2][EX / 4 * 32];
    unsigned long long bias[CH];
    float sums[2][EX];
    uint4 zero_row[66 * 192 / 16];
    unsigned int count[2];
};
__device__ __align__(256) Scratch g_scratch;
constexpr float ACC_LIMIT = 0x1p30f;

#define TS(k)
#define ASM_TS
#define MARK(k)
#define SMARK(k)
#define ASM_MARK
#define ASM_SMARK
#define ASM_TRC(it)

__device__ __forceinline__ void mbar_init(uint32_t bar, uint32_t count) {
    asm volatile("mbarrier.init.shared::cta.b64 [%0], %1;" ::"r"(bar), "r"(count) : "memory");
}
__device__ __forceinline__ void mbar_arrive_if(uint32_t bar, bool pred) {
    asm volatile("{\n.reg .pred p;\nsetp.ne.u32 p, %1, 0;\n@p mbarrier.arrive.shared::cta.b64 _, [%0];\n}\n"
                 ::"r"(bar), "r"((uint32_t)pred) : "memory");
}
__device__ __forceinline__ void mbar_wait(uint32_t bar, uint32_t parity) {
    asm volatile(
        "{\n.reg .pred p;\n.reg .u32 n;\n"
        "mbarrier.try_wait.parity.shared::cta.b64 p, [%0], %1;\n"
        "@p bra.uni WAIT_DONE;\n"
        "mov.u32 n, 0;\n"
        "WAIT_LOOP:\n"
        "mbarrier.try_wait.parity.shared::cta.b64 p, [%0], %1;\n"
        "@p bra.uni WAIT_DONE;\n"
        "mbarrier.try_wait.parity.shared::cta.b64 p, [%0], %1;\n"
        "@p bra.uni WAIT_DONE;\n"
        "mbarrier.try_wait.parity.shared::cta.b64 p, [%0], %1;\n"
        "@p bra.uni WAIT_DONE;\n"
        "add.u32 n, n, 1;\nsetp.lt.u32 p, n, 0x40000;\n"
        "@p bra.uni WAIT_LOOP;\n"
        "trap;\n"
        "WAIT_DONE:\n}\n"
        ::"r"(bar), "r"(parity) : "memory");
}
template <int PARITY> __device__ __forceinline__ void mbar_wait_c(uint32_t bar) {
    asm volatile(
        "{\n.reg .pred p;\n.reg .u32 n;\n"
        "mbarrier.try_wait.parity.shared::cta.b64 p, [%0], %1;\n"
        "@p bra.uni WAIT_DONE;\n"
        "mov.u32 n, 0;\n"
        "WAIT_LOOP:\n"
        "mbarrier.try_wait.parity.shared::cta.b64 p, [%0], %1;\n"
        "@p bra.uni WAIT_DONE;\n"
        "mbarrier.try_wait.parity.shared::cta.b64 p, [%0], %1;\n"
        "@p bra.uni WAIT_DONE;\n"
        "mbarrier.try_wait.parity.shared::cta.b64 p, [%0], %1;\n"
        "@p bra.uni WAIT_DONE;\n"
        "add.u32 n, n, 1;\nsetp.lt.u32 p, n, 0x40000;\n"
        "@p bra.uni WAIT_LOOP;\n"
        "trap;\n"
        "WAIT_DONE:\n}\n"
        ::"r"(bar), "n"(PARITY) : "memory");
}
#define ELECTED(body) "{\n.reg .pred p;\nelect.sync _|p, 0xffffffff;\n" body "}\n"
__device__ __forceinline__ void expect_tx(uint32_t bar, uint32_t bytes) {
    asm volatile(ELECTED("@p mbarrier.arrive.expect_tx.shared::cta.b64 _, [%0], %1;\n") ::"r"(bar), "r"(bytes) : "memory");
}
__device__ __forceinline__ void bulk_load(uint32_t dst, const void* src, uint32_t bytes, uint32_t bar) {
    asm volatile(ELECTED("@p cp.async.bulk.shared::cluster.global.mbarrier::complete_tx::bytes [%0], [%1], %2, [%3];\n")
                 ::"r"(dst), "l"(src), "r"(bytes), "r"(bar) : "memory");
}
__device__ __forceinline__ void bulk_prefetch(const void* src, uint32_t bytes) {
    asm volatile(ELECTED("@p cp.async.bulk.prefetch.L2.global [%0], %1;\n") ::"l"(src), "r"(bytes) : "memory");
}
__device__ __forceinline__ void tma_load_2d(uint32_t dst, const CUtensorMap* map, int c0, int c1, uint32_t bar) {
    asm volatile(ELECTED("@p cp.async.bulk.tensor.2d.shared::cluster.global.mbarrier::complete_tx::bytes [%0], [%1, {%2, %3}], [%4];\n")
                 ::"r"(dst), "l"(map), "r"(c0), "r"(c1), "r"(bar) : "memory");
}
template <int N> __device__ __forceinline__ void bulk_wait_read() {
    asm volatile("cp.async.bulk.wait_group.read %0;" ::"n"(N) : "memory");
}
__device__ __forceinline__ void bulk_wait_all() { asm volatile("cp.async.bulk.wait_group 0;" ::: "memory"); }
__device__ __forceinline__ void fence_async_smem() { asm volatile("fence.proxy.async.shared::cta;" ::: "memory"); }
__device__ __forceinline__ void named_sync(int id, int n) { asm volatile("bar.sync %0, %1;" ::"r"(id), "r"(n) : "memory"); }

__device__ __forceinline__ void sts64(uint32_t addr, uint32_t a, uint32_t b) {
    asm volatile("st.shared.v2.b32 [%0], {%1,%2};" ::"r"(addr), "r"(a), "r"(b) : "memory");
}
__device__ __forceinline__ void sts128(uint32_t addr, uint32_t a, uint32_t b, uint32_t c, uint32_t d) {
    asm volatile("st.shared.v4.b32 [%0], {%1,%2,%3,%4};" ::"r"(addr), "r"(a), "r"(b), "r"(c), "r"(d) : "memory");
}
__device__ __forceinline__ void ldsm4_t(uint32_t* r, uint32_t addr) {
    asm volatile("ldmatrix.sync.aligned.m8n8.x4.trans.shared.b16 {%0,%1,%2,%3}, [%4];"
                 : "=r"(r[0]), "=r"(r[1]), "=r"(r[2]), "=r"(r[3]) : "r"(addr) : "memory");
}
__device__ __forceinline__ void lds128(uint32_t* v, uint32_t addr) {
    asm volatile("ld.shared.v4.b32 {%0,%1,%2,%3}, [%4];"
                 : "=r"(v[0]), "=r"(v[1]), "=r"(v[2]), "=r"(v[3]) : "r"(addr) : "memory");
}
__device__ __forceinline__ uint32_t lds32(uint32_t addr) {
    uint32_t v; asm volatile("ld.shared.b32 %0, [%1];" : "=r"(v) : "r"(addr) : "memory"); return v;
}
__device__ __forceinline__ void sts32(uint32_t addr, uint32_t v) {
    asm volatile("st.shared.b32 [%0], %1;" ::"r"(addr), "r"(v) : "memory");
}

__device__ __forceinline__ uint32_t bf2_fma(uint32_t a, uint32_t b, uint32_t c) {
    uint32_t d; asm("fma.rn.bf16x2 %0, %1, %2, %3;" : "=r"(d) : "r"(a), "r"(b), "r"(c)); return d;
}
__device__ __forceinline__ uint32_t bf2_mul(uint32_t a, uint32_t b) {
    uint32_t d; asm("mul.rn.bf16x2 %0, %1, %2;" : "=r"(d) : "r"(a), "r"(b)); return d;
}
__device__ __forceinline__ uint32_t bf2_add(uint32_t a, uint32_t b) {
    uint32_t d; asm("add.rn.bf16x2 %0, %1, %2;" : "=r"(d) : "r"(a), "r"(b)); return d;
}
__device__ __forceinline__ uint32_t h2_fma(uint32_t a, uint32_t b, uint32_t c) {
    uint32_t d; asm("fma.rn.f16x2 %0, %1, %2, %3;" : "=r"(d) : "r"(a), "r"(b), "r"(c)); return d;
}
__device__ __forceinline__ uint32_t h2_mul(uint32_t a, uint32_t b) {
    uint32_t d; asm("mul.rn.f16x2 %0, %1, %2;" : "=r"(d) : "r"(a), "r"(b)); return d;
}
__device__ __forceinline__ uint32_t h2_tanh(uint32_t a) {
    uint32_t d; asm("tanh.approx.f16x2 %0, %1;" : "=r"(d) : "r"(a)); return d;
}
__device__ __forceinline__ float bf_lo(uint32_t v) { return __uint_as_float(v << 16); }
__device__ __forceinline__ float bf_hi(uint32_t v) { return __uint_as_float(v & 0xffff0000u); }
__device__ __forceinline__ uint32_t pack_h2(float lo, float hi) {
    uint32_t d; asm("cvt.rn.f16x2.f32 %0, %1, %2;" : "=r"(d) : "f"(hi), "f"(lo)); return d;
}
__device__ __forceinline__ uint32_t pack_bf2(float lo, float hi) {
    uint32_t d; asm("cvt.rn.bf16x2.f32 %0, %1, %2;" : "=r"(d) : "f"(hi), "f"(lo)); return d;
}
__device__ __forceinline__ void h2_unpack(uint32_t v, float& lo, float& hi) {
    asm("{\n.reg .b16 l, h;\nmov.b32 {l, h}, %2;\ncvt.f32.f16 %0, l;\ncvt.f32.f16 %1, h;\n}\n" : "=f"(lo), "=f"(hi) : "r"(v));
}

__device__ __forceinline__ uint32_t gelu2(uint32_t z) {
    uint32_t p = h2_fma(z, z, GELU_C_H2);
    uint32_t t = h2_tanh(h2_mul(z, p));
    return h2_fma(z, t, z);
}

__device__ __forceinline__ void wg_fence() { asm volatile("wgmma.fence.sync.aligned;" ::: "memory"); }
__device__ __forceinline__ void wg_commit() { asm volatile("wgmma.commit_group.sync.aligned;" ::: "memory"); }
template <int N> __device__ __forceinline__ void wg_wait() {
    asm volatile("wgmma.wait_group.sync.aligned %0;" ::"n"(N) : "memory");
}
template <int N> __device__ __forceinline__ void pin(uint32_t (&r)[N]) {
#pragma unroll
    for (int i = 0; i < N; i++) asm volatile("" : "+r"(r[i])::"memory");
}
constexpr uint32_t desc_lo(uint32_t addr, uint32_t lbo) { return ((addr & 0x3FFFF) >> 4) | ((lbo >> 4) << 16); }
template <uint32_t SBO, uint32_t SWZ> __device__ __forceinline__ uint64_t desc(uint32_t lo, uint32_t bytes) {
    return (((uint64_t)((SBO >> 4) | (SWZ << 30)) << 32) | lo) + (bytes >> 4);
}
__device__ __forceinline__ uint32_t fresh_tid() {
    uint32_t v; asm volatile("mov.u32 %0, %%tid.x;" : "=r"(v));
    return v;
}
template <uint32_t V> __device__ __forceinline__ uint32_t loop_init() {
    uint32_t v; asm volatile("mov.u32 %0, %1;" : "=r"(v) : "n"(V)); return v;
}
__device__ __forceinline__ int fresh_warp() {
    int v; asm volatile("shfl.sync.idx.b32 %0, %1, 0, 0x1f, 0xffffffff;" : "=r"(v) : "r"(fresh_tid() >> 5)); return v;
}
__device__ __forceinline__ uint32_t fresh_cta() {
    uint32_t v; asm volatile("mov.u32 %0, %%ctaid.x;" : "=r"(v)); return v;
}
__device__ __forceinline__ float sqrt_fast(float v) { float r; asm("sqrt.approx.f32 %0, %1;" : "=f"(r) : "f"(v)); return r; }

template <int TB>
__device__ __forceinline__ void wgmma_n64_h_set(uint32_t (&d)[16], const uint32_t* a, uint64_t desc) {
    asm volatile(
        "{\n.reg .pred p;\nsetp.ne.b32 p, 0, 0;\n"
        "wgmma.mma_async.sync.aligned.m64n64k16.f16.f16.f16 "
        "{%0,%1,%2,%3,%4,%5,%6,%7,%8,%9,%10,%11,%12,%13,%14,%15}, {%16,%17,%18,%19}, %20, p, 1, 1, %21;\n}\n"
        : "=r"(d[0]), "=r"(d[1]), "=r"(d[2]), "=r"(d[3]), "=r"(d[4]), "=r"(d[5]), "=r"(d[6]), "=r"(d[7]), "=r"(d[8]), "=r"(d[9]), "=r"(d[10]), "=r"(d[11]), "=r"(d[12]), "=r"(d[13]), "=r"(d[14]), "=r"(d[15])
        : "r"(a[0]), "r"(a[1]), "r"(a[2]), "r"(a[3]), "l"(desc), "n"(TB));
}
template <int TB>
__device__ __forceinline__ void wgmma_n64_h_acc(uint32_t (&d)[16], const uint32_t* a, uint64_t desc) {
    asm volatile(
        "{\n.reg .pred p;\nsetp.ne.b32 p, 1, 0;\n"
        "wgmma.mma_async.sync.aligned.m64n64k16.f16.f16.f16 "
        "{%0,%1,%2,%3,%4,%5,%6,%7,%8,%9,%10,%11,%12,%13,%14,%15}, {%16,%17,%18,%19}, %20, p, 1, 1, %21;\n}\n"
        : "+r"(d[0]), "+r"(d[1]), "+r"(d[2]), "+r"(d[3]), "+r"(d[4]), "+r"(d[5]), "+r"(d[6]), "+r"(d[7]), "+r"(d[8]), "+r"(d[9]), "+r"(d[10]), "+r"(d[11]), "+r"(d[12]), "+r"(d[13]), "+r"(d[14]), "+r"(d[15])
        : "r"(a[0]), "r"(a[1]), "r"(a[2]), "r"(a[3]), "l"(desc), "n"(TB));
}
__device__ __forceinline__ void wgmma_n64_h_acc_ss(uint32_t (&d)[16], uint64_t adesc, uint64_t desc) {
    asm volatile(
        "{\n.reg .pred p;\nsetp.ne.b32 p, 1, 0;\n"
        "wgmma.mma_async.sync.aligned.m64n64k16.f16.f16.f16 "
        "{%0,%1,%2,%3,%4,%5,%6,%7,%8,%9,%10,%11,%12,%13,%14,%15}, %16, %17, p, 1, 1, 1, 0;\n}\n"
        : "+r"(d[0]), "+r"(d[1]), "+r"(d[2]), "+r"(d[3]), "+r"(d[4]), "+r"(d[5]), "+r"(d[6]), "+r"(d[7]), "+r"(d[8]), "+r"(d[9]), "+r"(d[10]), "+r"(d[11]), "+r"(d[12]), "+r"(d[13]), "+r"(d[14]), "+r"(d[15])
        : "l"(adesc), "l"(desc));
}

struct Params {
    CUtensorMap w1_map, w2_map;
    const __nv_bfloat16* x;
    const __nv_bfloat16* dw;
    const __nv_bfloat16* w1;
    const __nv_bfloat16* gamma;
    const __nv_bfloat16* beta;
    __nv_bfloat16* out;
    Scratch* g;
    uint64_t ydesc64[2];
    uint64_t sel[3];
    uint32_t w1desc, w2desc, ydesc;
};

__device__ __forceinline__ int cta_stride(uint32_t cta) { return cta & 8 ? ROW_BYTES : -ROW_BYTES; }
__device__ __forceinline__ uint32_t cta_tile0(uint32_t cta) {
    return ((cta >> 3) * ROWS_PER_CTA + (cta & 8 ? 0 : ROWS_PER_CTA - 1)) * ROW_BYTES + (cta & 7) * TILE_BYTES;
}

struct Producer {
    uint32_t w[9][6];
    uint32_t xoff[2];
    uint32_t yoff[2][2];
    uint32_t stat, own;
    int lane;
};

struct RowCopy {
    const char* x0;
    char* y0;
    const char* zeros;
    uint32_t cut0, cut1;
    int stride, last;
};
__device__ __forceinline__ RowCopy row_copy(const Params& prm) {
    const uint32_t cta = fresh_cta(), strip = cta & 7, t0 = cta_tile0(cta);
    RowCopy r;
    r.stride = cta_stride(cta);
    r.x0 = (const char*)prm.x + (t0 - r.stride) - 192;
    r.y0 = (char*)prm.out + t0;
    r.zeros = (const char*)prm.g->zero_row;
    r.cut0 = strip == 0 ? 192 : 0;
    r.cut1 = strip == 7 ? 192 : 0;
    r.last = cta - 8 >= NUM_CTAS - 16 ? STEPS - 2 : STEPS - 1;
    return r;
}
__device__ __forceinline__ void issue_row_load(const RowCopy& r, int i, uint32_t slot) {
    const char* src = r.x0 + i * r.stride;
    const uint32_t bar = sb + SM_GO + i * 8, dst = sb + SM_X + slot * SLOT_BYTES;
    expect_tx(bar, XHALF_BYTES - r.cut0);
    bulk_load(dst + r.cut0, src + r.cut0, XHALF_BYTES - r.cut0, bar);
    expect_tx(bar, XHALF_BYTES - r.cut1);
    bulk_load(dst + XHALF_B, src + 32 * 192, XHALF_BYTES - r.cut1, bar);
}

__device__ __forceinline__ float quad_sum(float v) {
    v += __shfl_xor_sync(0xffffffffu, v, 1);
    v += __shfl_xor_sync(0xffffffffu, v, 2);
    return v;
}

__device__ __forceinline__ void load_x(uint32_t (&v)[6][6], const Producer& c, uint32_t row) {
#pragma unroll
    for (int k = 0; k < 6; k++) {
        asm volatile("ld.shared.v4.b32 {%0,%1,%2,%3}, [%4];"
                     : "=r"(v[k][0]), "=r"(v[k][1]), "=r"(v[k][2]), "=r"(v[k][3]) : "r"(row + c.xoff[0] + k * 192));
        asm volatile("ld.shared.v2.b32 {%0,%1}, [%2];" : "=r"(v[k][4]), "=r"(v[k][5]) : "r"(row + c.xoff[1] + k * 192));
    }
}
template <int DY, int STRIDE>
__device__ __forceinline__ void conv_row(uint32_t (&dst)[24], const uint32_t* src, const uint32_t (&v)[6][6], const Producer& c) {
#pragma unroll
    for (int o = 0; o < 4; o++)
#pragma unroll
        for (int u = 0; u < 6; u++)
            dst[o * 6 + u] = bf2_fma(v[o + 2][u], c.w[3 * DY + 2][u], bf2_fma(v[o + 1][u], c.w[3 * DY + 1][u],
                             bf2_fma(v[o][u], c.w[3 * DY][u], STRIDE ? src[o * 6 + u] : src[2 * o + 1])));
}
#define HAND_OVER(name, base, r) asm volatile("mov.b32 " name "%6, %0; mov.b32 " name "%7, %1; mov.b32 " name "%8, %2;\n" \
    "mov.b32 " name "%9, %3; mov.b32 " name "%10, %4; mov.b32 " name "%11, %5;" ::"r"((r)[0]), "r"((r)[1]), "r"((r)[2]), \
    "r"((r)[3]), "r"((r)[4]), "r"((r)[5]), "n"(base), "n"(base + 1), "n"(base + 2), "n"(base + 3), "n"(base + 4), "n"(base + 5))
template <int K> __device__ __forceinline__ void hand_over(const Producer& c, const uint32_t (&B)[24], const uint32_t (&C)[24],
                                                           const uint32_t (&v)[6][6]) {
    HAND_OVER("pw", K * 6, c.w[K]);
    if (K < 6) HAND_OVER("pv", K * 6, v[K % 6]);
    if (K < 4) { HAND_OVER("pb", K * 6, B + K % 4 * 6); HAND_OVER("pc", K * 6, C + K % 4 * 6); }
    if constexpr (K < 8) hand_over<K + 1>(c, B, C, v);
}
__device__ __forceinline__ void produce_tiles(const Producer& c, const Params& prm) {
    asm volatile(
        "{\n"
        ".reg .b32 pa<24>, pq<4>, m<6>, y<6>, rr, mm, t, so, ad, tt, cnt;\n"
        ".reg .b16 xl, xh;\n"
        ".reg .f32 d<4>, us, s0, s1, f0, f1, kq;\n"
        ".reg .pred pt, pf, pr, pw, pl, po, pe;\n"
        "setp.ne.b32 pt, 1, 0; setp.ne.b32 pf, 0, 0; setp.eq.u32 pl, %8, 0; and.b32 tt, %8, 1; setp.ne.u32 po, tt, 0;\n"
        "and.b32 tt, %8, 4; setp.ne.u32 pr, tt, 0; selp.f32 kq, 0f3F802D41, 0f3F7FA57E, pr;\n"
        "mov.u32 t, 0; mov.u32 so, 0;\n"
        "setp.eq.u32 pr, %12, 0;\n"
        "@pr bra.uni RARE;\n"
        "LOOP:\n"
        ASM_TRC("t")
        "fma.rn.bf16x2 pa0, pv0, pw36, pb0; fma.rn.bf16x2 pa1, pv1, pw37, pb1; fma.rn.bf16x2 pa2, pv2, pw38, pb2; fma.rn.bf16x2 pa3, pv3, pw39, pb3; fma.rn.bf16x2 pa4, pv4, pw40, pb4; fma.rn.bf16x2 pa5, pv5, pw41, pb5;\n"
        "fma.rn.bf16x2 pa6, pv6, pw36, pb6; fma.rn.bf16x2 pa7, pv7, pw37, pb7; fma.rn.bf16x2 pa8, pv8, pw38, pb8; fma.rn.bf16x2 pa9, pv9, pw39, pb9; fma.rn.bf16x2 pa10, pv10, pw40, pb10; fma.rn.bf16x2 pa11, pv11, pw41, pb11;\n"
        "fma.rn.bf16x2 pa12, pv12, pw36, pb12; fma.rn.bf16x2 pa13, pv13, pw37, pb13; fma.rn.bf16x2 pa14, pv14, pw38, pb14; fma.rn.bf16x2 pa15, pv15, pw39, pb15; fma.rn.bf16x2 pa16, pv16, pw40, pb16; fma.rn.bf16x2 pa17, pv17, pw41, pb17;\n"
        "fma.rn.bf16x2 pa18, pv18, pw36, pb18; fma.rn.bf16x2 pa19, pv19, pw37, pb19; fma.rn.bf16x2 pa20, pv20, pw38, pb20; fma.rn.bf16x2 pa21, pv21, pw39, pb21; fma.rn.bf16x2 pa22, pv22, pw40, pb22; fma.rn.bf16x2 pa23, pv23, pw41, pb23;\n"
        "fma.rn.bf16x2 pa0, pv6, pw42, pa0; fma.rn.bf16x2 pa1, pv7, pw43, pa1; fma.rn.bf16x2 pa2, pv8, pw44, pa2; fma.rn.bf16x2 pa3, pv9, pw45, pa3; fma.rn.bf16x2 pa4, pv10, pw46, pa4; fma.rn.bf16x2 pa5, pv11, pw47, pa5;\n"
        "fma.rn.bf16x2 pa6, pv12, pw42, pa6; fma.rn.bf16x2 pa7, pv13, pw43, pa7; fma.rn.bf16x2 pa8, pv14, pw44, pa8; fma.rn.bf16x2 pa9, pv15, pw45, pa9; fma.rn.bf16x2 pa10, pv16, pw46, pa10; fma.rn.bf16x2 pa11, pv17, pw47, pa11;\n"
        "fma.rn.bf16x2 pa12, pv18, pw42, pa12; fma.rn.bf16x2 pa13, pv19, pw43, pa13; fma.rn.bf16x2 pa14, pv20, pw44, pa14; fma.rn.bf16x2 pa15, pv21, pw45, pa15; fma.rn.bf16x2 pa16, pv22, pw46, pa16; fma.rn.bf16x2 pa17, pv23, pw47, pa17;\n"
        "fma.rn.bf16x2 pa18, pv24, pw42, pa18; fma.rn.bf16x2 pa19, pv25, pw43, pa19; fma.rn.bf16x2 pa20, pv26, pw44, pa20; fma.rn.bf16x2 pa21, pv27, pw45, pa21; fma.rn.bf16x2 pa22, pv28, pw46, pa22; fma.rn.bf16x2 pa23, pv29, pw47, pa23;\n"
        "fma.rn.bf16x2 pa0, pv12, pw48, pa0; fma.rn.bf16x2 pa1, pv13, pw49, pa1; fma.rn.bf16x2 pa2, pv14, pw50, pa2; fma.rn.bf16x2 pa3, pv15, pw51, pa3; fma.rn.bf16x2 pa4, pv16, pw52, pa4; fma.rn.bf16x2 pa5, pv17, pw53, pa5;\n"
        "fma.rn.bf16x2 pa6, pv18, pw48, pa6; fma.rn.bf16x2 pa7, pv19, pw49, pa7; fma.rn.bf16x2 pa8, pv20, pw50, pa8; fma.rn.bf16x2 pa9, pv21, pw51, pa9; fma.rn.bf16x2 pa10, pv22, pw52, pa10; fma.rn.bf16x2 pa11, pv23, pw53, pa11;\n"
        "fma.rn.bf16x2 pa12, pv24, pw48, pa12; fma.rn.bf16x2 pa13, pv25, pw49, pa13; fma.rn.bf16x2 pa14, pv26, pw50, pa14; fma.rn.bf16x2 pa15, pv27, pw51, pa15; fma.rn.bf16x2 pa16, pv28, pw52, pa16; fma.rn.bf16x2 pa17, pv29, pw53, pa17;\n"
        "fma.rn.bf16x2 pa18, pv30, pw48, pa18; fma.rn.bf16x2 pa19, pv31, pw49, pa19; fma.rn.bf16x2 pa20, pv32, pw50, pa20; fma.rn.bf16x2 pa21, pv33, pw51, pa21; fma.rn.bf16x2 pa22, pv34, pw52, pa22; fma.rn.bf16x2 pa23, pv35, pw53, pa23;\n"
        "mul.rn.bf16x2 pq0, pa0, pa0; fma.rn.bf16x2 pq0, pa1, pa1, pq0; fma.rn.bf16x2 pq0, pa2, pa2, pq0; fma.rn.bf16x2 pq0, pa3, pa3, pq0; fma.rn.bf16x2 pq0, pa4, pa4, pq0; fma.rn.bf16x2 pq0, pa5, pa5, pq0;\n"
        "mul.rn.bf16x2 pq1, pa6, pa6; fma.rn.bf16x2 pq1, pa7, pa7, pq1; fma.rn.bf16x2 pq1, pa8, pa8, pq1; fma.rn.bf16x2 pq1, pa9, pa9, pq1; fma.rn.bf16x2 pq1, pa10, pa10, pq1; fma.rn.bf16x2 pq1, pa11, pa11, pq1;\n"
        "mul.rn.bf16x2 pq2, pa12, pa12; fma.rn.bf16x2 pq2, pa13, pa13, pq2; fma.rn.bf16x2 pq2, pa14, pa14, pq2; fma.rn.bf16x2 pq2, pa15, pa15, pq2; fma.rn.bf16x2 pq2, pa16, pa16, pq2; fma.rn.bf16x2 pq2, pa17, pa17, pq2;\n"
        "mul.rn.bf16x2 pq3, pa18, pa18; fma.rn.bf16x2 pq3, pa19, pa19, pq3; fma.rn.bf16x2 pq3, pa20, pa20, pq3; fma.rn.bf16x2 pq3, pa21, pa21, pq3; fma.rn.bf16x2 pq3, pa22, pa22, pq3; fma.rn.bf16x2 pq3, pa23, pa23, pq3;\n"
        "B0:\n"
        "wgmma.fence.sync.aligned;\n"
        "wgmma.mma_async.sync.aligned.m64n8k16.f32.bf16.bf16 {d0,d1,d2,d3}, {pa0,pa6,pa1,pa7}, %9, pf, 1, 1, 0;\n"
        "wgmma.mma_async.sync.aligned.m64n8k16.f32.bf16.bf16 {d0,d1,d2,d3}, {pa2,pa8,pa3,pa9}, %9, pt, 1, 1, 0;\n"
        "wgmma.mma_async.sync.aligned.m64n8k16.f32.bf16.bf16 {d0,d1,d2,d3}, {pa4,pa10,pa5,pa11}, %9, pt, 1, 1, 0;\n"
        "wgmma.mma_async.sync.aligned.m64n8k16.f32.bf16.bf16 {d0,d1,d2,d3}, {pa12,pa18,pa13,pa19}, %10, pt, 1, 1, 0;\n"
        "wgmma.mma_async.sync.aligned.m64n8k16.f32.bf16.bf16 {d0,d1,d2,d3}, {pa14,pa20,pa15,pa21}, %10, pt, 1, 1, 0;\n"
        "wgmma.mma_async.sync.aligned.m64n8k16.f32.bf16.bf16 {d0,d1,d2,d3}, {pa16,pa22,pa17,pa23}, %10, pt, 1, 1, 0;\n"
        "wgmma.mma_async.sync.aligned.m64n8k16.f32.bf16.bf16 {d0,d1,d2,d3}, {pq0,pq1,pq2,pq3}, %11, pt, 1, 1, 0;\n"
        "wgmma.commit_group.sync.aligned;\n"
        "fence.proxy.async.shared::cta;\n"
        "@pl mbarrier.arrive.shared::cta.b64 _, [t+231552];\n"
        "add.u32 ad, %7, so; ld.shared.f32 us, [ad+4];\n"
        "fma.rn.bf16x2 pb0, pv0, pw18, pc0; fma.rn.bf16x2 pb1, pv1, pw19, pc1; fma.rn.bf16x2 pb2, pv2, pw20, pc2; fma.rn.bf16x2 pb3, pv3, pw21, pc3; fma.rn.bf16x2 pb4, pv4, pw22, pc4; fma.rn.bf16x2 pb5, pv5, pw23, pc5;\n"
        "fma.rn.bf16x2 pb6, pv6, pw18, pc6; fma.rn.bf16x2 pb7, pv7, pw19, pc7; fma.rn.bf16x2 pb8, pv8, pw20, pc8; fma.rn.bf16x2 pb9, pv9, pw21, pc9; fma.rn.bf16x2 pb10, pv10, pw22, pc10; fma.rn.bf16x2 pb11, pv11, pw23, pc11;\n"
        "fma.rn.bf16x2 pb0, pv6, pw24, pb0; fma.rn.bf16x2 pb1, pv7, pw25, pb1; fma.rn.bf16x2 pb2, pv8, pw26, pb2; fma.rn.bf16x2 pb3, pv9, pw27, pb3; fma.rn.bf16x2 pb4, pv10, pw28, pb4; fma.rn.bf16x2 pb5, pv11, pw29, pb5;\n"
        "fma.rn.bf16x2 pb6, pv12, pw24, pb6; fma.rn.bf16x2 pb7, pv13, pw25, pb7; fma.rn.bf16x2 pb8, pv14, pw26, pb8; fma.rn.bf16x2 pb9, pv15, pw27, pb9; fma.rn.bf16x2 pb10, pv16, pw28, pb10; fma.rn.bf16x2 pb11, pv17, pw29, pb11;\n"
        "fma.rn.bf16x2 pb0, pv12, pw30, pb0; fma.rn.bf16x2 pb1, pv13, pw31, pb1; fma.rn.bf16x2 pb2, pv14, pw32, pb2; fma.rn.bf16x2 pb3, pv15, pw33, pb3; fma.rn.bf16x2 pb4, pv16, pw34, pb4; fma.rn.bf16x2 pb5, pv17, pw35, pb5;\n"
        "fma.rn.bf16x2 pb6, pv18, pw30, pb6; fma.rn.bf16x2 pb7, pv19, pw31, pb7; fma.rn.bf16x2 pb8, pv20, pw32, pb8; fma.rn.bf16x2 pb9, pv21, pw33, pb9; fma.rn.bf16x2 pb10, pv22, pw34, pb10; fma.rn.bf16x2 pb11, pv23, pw35, pb11;\n"
        "B1:\n"
        "fma.rn.bf16x2 pb12, pv12, pw18, pc12; fma.rn.bf16x2 pb13, pv13, pw19, pc13; fma.rn.bf16x2 pb14, pv14, pw20, pc14; fma.rn.bf16x2 pb15, pv15, pw21, pc15; fma.rn.bf16x2 pb16, pv16, pw22, pc16; fma.rn.bf16x2 pb17, pv17, pw23, pc17;\n"
        "fma.rn.bf16x2 pb18, pv18, pw18, pc18; fma.rn.bf16x2 pb19, pv19, pw19, pc19; fma.rn.bf16x2 pb20, pv20, pw20, pc20; fma.rn.bf16x2 pb21, pv21, pw21, pc21; fma.rn.bf16x2 pb22, pv22, pw22, pc22; fma.rn.bf16x2 pb23, pv23, pw23, pc23;\n"
        "fma.rn.bf16x2 pb12, pv18, pw24, pb12; fma.rn.bf16x2 pb13, pv19, pw25, pb13; fma.rn.bf16x2 pb14, pv20, pw26, pb14; fma.rn.bf16x2 pb15, pv21, pw27, pb15; fma.rn.bf16x2 pb16, pv22, pw28, pb16; fma.rn.bf16x2 pb17, pv23, pw29, pb17;\n"
        "fma.rn.bf16x2 pb18, pv24, pw24, pb18; fma.rn.bf16x2 pb19, pv25, pw25, pb19; fma.rn.bf16x2 pb20, pv26, pw26, pb20; fma.rn.bf16x2 pb21, pv27, pw27, pb21; fma.rn.bf16x2 pb22, pv28, pw28, pb22; fma.rn.bf16x2 pb23, pv29, pw29, pb23;\n"
        "fma.rn.bf16x2 pb12, pv24, pw30, pb12; fma.rn.bf16x2 pb13, pv25, pw31, pb13; fma.rn.bf16x2 pb14, pv26, pw32, pb14; fma.rn.bf16x2 pb15, pv27, pw33, pb15; fma.rn.bf16x2 pb16, pv28, pw34, pb16; fma.rn.bf16x2 pb17, pv29, pw35, pb17;\n"
        "fma.rn.bf16x2 pb18, pv30, pw30, pb18; fma.rn.bf16x2 pb19, pv31, pw31, pb19; fma.rn.bf16x2 pb20, pv32, pw32, pb20; fma.rn.bf16x2 pb21, pv33, pw33, pb21; fma.rn.bf16x2 pb22, pv34, pw34, pb22; fma.rn.bf16x2 pb23, pv35, pw35, pb23;\n"
        "C0:\n"
        "wgmma.wait_group.sync.aligned 0;\n"
        "selp.f32 s0, d2, d0, po; selp.f32 s1, d3, d1, po;\n"
        "shfl.sync.bfly.b32 f0, s0, 4, 0x1f, 0xffffffff; shfl.sync.bfly.b32 f1, s1, 4, 0x1f, 0xffffffff;\n"
        "fma.rn.bf16x2 pc0, pv0, pw0, ps1; fma.rn.bf16x2 pc1, pv1, pw1, ps1; fma.rn.bf16x2 pc2, pv2, pw2, ps1; fma.rn.bf16x2 pc3, pv3, pw3, ps1; fma.rn.bf16x2 pc4, pv4, pw4, ps1; fma.rn.bf16x2 pc5, pv5, pw5, ps1;\n"
        "fma.rn.bf16x2 pc6, pv6, pw0, ps3; fma.rn.bf16x2 pc7, pv7, pw1, ps3; fma.rn.bf16x2 pc8, pv8, pw2, ps3; fma.rn.bf16x2 pc9, pv9, pw3, ps3; fma.rn.bf16x2 pc10, pv10, pw4, ps3; fma.rn.bf16x2 pc11, pv11, pw5, ps3;\n"
        "fma.rn.bf16x2 pc12, pv12, pw0, ps5; fma.rn.bf16x2 pc13, pv13, pw1, ps5; fma.rn.bf16x2 pc14, pv14, pw2, ps5; fma.rn.bf16x2 pc15, pv15, pw3, ps5; fma.rn.bf16x2 pc16, pv16, pw4, ps5; fma.rn.bf16x2 pc17, pv17, pw5, ps5;\n"
        "fma.rn.bf16x2 pc18, pv18, pw0, ps7; fma.rn.bf16x2 pc19, pv19, pw1, ps7; fma.rn.bf16x2 pc20, pv20, pw2, ps7; fma.rn.bf16x2 pc21, pv21, pw3, ps7; fma.rn.bf16x2 pc22, pv22, pw4, ps7; fma.rn.bf16x2 pc23, pv23, pw5, ps7;\n"
        "fma.rn.bf16x2 pc0, pv6, pw6, pc0; fma.rn.bf16x2 pc1, pv7, pw7, pc1; fma.rn.bf16x2 pc2, pv8, pw8, pc2; fma.rn.bf16x2 pc3, pv9, pw9, pc3; fma.rn.bf16x2 pc4, pv10, pw10, pc4; fma.rn.bf16x2 pc5, pv11, pw11, pc5;\n"
        "fma.rn.bf16x2 pc6, pv12, pw6, pc6; fma.rn.bf16x2 pc7, pv13, pw7, pc7; fma.rn.bf16x2 pc8, pv14, pw8, pc8; fma.rn.bf16x2 pc9, pv15, pw9, pc9; fma.rn.bf16x2 pc10, pv16, pw10, pc10; fma.rn.bf16x2 pc11, pv17, pw11, pc11;\n"
        "fma.rn.bf16x2 pc12, pv18, pw6, pc12; fma.rn.bf16x2 pc13, pv19, pw7, pc13; fma.rn.bf16x2 pc14, pv20, pw8, pc14; fma.rn.bf16x2 pc15, pv21, pw9, pc15; fma.rn.bf16x2 pc16, pv22, pw10, pc16; fma.rn.bf16x2 pc17, pv23, pw11, pc17;\n"
        "fma.rn.bf16x2 pc18, pv24, pw6, pc18; fma.rn.bf16x2 pc19, pv25, pw7, pc19; fma.rn.bf16x2 pc20, pv26, pw8, pc20; fma.rn.bf16x2 pc21, pv27, pw9, pc21; fma.rn.bf16x2 pc22, pv28, pw10, pc22; fma.rn.bf16x2 pc23, pv29, pw11, pc23;\n"
        "fma.rn.bf16x2 pc0, pv12, pw12, pc0; fma.rn.bf16x2 pc1, pv13, pw13, pc1; fma.rn.bf16x2 pc2, pv14, pw14, pc2; fma.rn.bf16x2 pc3, pv15, pw15, pc3; fma.rn.bf16x2 pc4, pv16, pw16, pc4; fma.rn.bf16x2 pc5, pv17, pw17, pc5;\n"
        "fma.rn.bf16x2 pc6, pv18, pw12, pc6; fma.rn.bf16x2 pc7, pv19, pw13, pc7; fma.rn.bf16x2 pc8, pv20, pw14, pc8; fma.rn.bf16x2 pc9, pv21, pw15, pc9; fma.rn.bf16x2 pc10, pv22, pw16, pc10; fma.rn.bf16x2 pc11, pv23, pw17, pc11;\n"
        "fma.rn.bf16x2 pc12, pv24, pw12, pc12; fma.rn.bf16x2 pc13, pv25, pw13, pc13; fma.rn.bf16x2 pc14, pv26, pw14, pc14; fma.rn.bf16x2 pc15, pv27, pw15, pc15; fma.rn.bf16x2 pc16, pv28, pw16, pc16; fma.rn.bf16x2 pc17, pv29, pw17, pc17;\n"
        "fma.rn.bf16x2 pc18, pv30, pw12, pc18; fma.rn.bf16x2 pc19, pv31, pw13, pc19; fma.rn.bf16x2 pc20, pv32, pw14, pc20; fma.rn.bf16x2 pc21, pv33, pw15, pc21; fma.rn.bf16x2 pc22, pv34, pw16, pc22; fma.rn.bf16x2 pc23, pv35, pw17, pc23;\n"
        "add.f32 s0, s0, f0; add.f32 s1, s1, f1; mul.f32 s0, s0, 0fBC2AAAAB;\n"
        "neg.f32 f0, s0; fma.rn.f32 f0, f0, s0, %13; fma.rn.f32 f0, s1, 0f3C2AAAAB, f0; max.f32 f0, f0, %13;\n"
        "rsqrt.approx.ftz.f32 f0, f0; mul.f32 f0, f0, %14; cvt.rn.bf16x2.f32 tt, f0, 0f00000000; mov.b32 f0, tt;\n"
        "mul.f32 f1, s0, kq; mul.f32 f1, f1, f0; cvt.rn.bf16x2.f32 tt, f1, f0; add.f32 us, us, s0; cvt.rn.bf16x2.f32 mm, us, us;\n"
        "add.u32 ad, %7, so; st.shared.v2.b32 [ad], {tt, mm};\n"
        "add.u32 ad, %6, so; ld.shared.v4.b32 {ps0,ps1,ps2,ps3}, [ad]; ld.shared.v4.b32 {ps4,ps5,ps6,ps7}, [ad+16];\n"
        "mbarrier.try_wait.parity.shared::cta.b64 pw, [t+231272], 0;\n"
        "N0:\n"
        "@!pw bra.uni SPIN;\n"
        "BACK:\n"
        "add.u32 ad, %0, so; ld.shared.v4.b32 {pv0,pv1,pv2,pv3}, [ad+0];\n"
        "add.u32 ad, %1, so; ld.shared.v2.b32 {pv4,pv5}, [ad+0];\n"
        "add.u32 ad, %0, so; ld.shared.v4.b32 {pv6,pv7,pv8,pv9}, [ad+192];\n"
        "add.u32 ad, %1, so; ld.shared.v2.b32 {pv10,pv11}, [ad+192];\n"
        "mov.b32 {xl, xh}, ps0; mov.b32 rr, {xl, xl}; mov.b32 mm, {xh, xh}; fma.rn.bf16x2 pa0, pa0, rr, mm; fma.rn.bf16x2 pa1, pa1, rr, mm; fma.rn.bf16x2 pa2, pa2, rr, mm; fma.rn.bf16x2 pa3, pa3, rr, mm; fma.rn.bf16x2 pa4, pa4, rr, mm; fma.rn.bf16x2 pa5, pa5, rr, mm;\n"
        "and.b32 m0, pa0, 0x7fff7fff; and.b32 m1, pa1, 0x7fff7fff; and.b32 m2, pa2, 0x7fff7fff; and.b32 m3, pa3, 0x7fff7fff; and.b32 m4, pa4, 0x7fff7fff; and.b32 m5, pa5, 0x7fff7fff;\n"
        "mad.lo.u32 y0, m0, 7, pa0; mad.lo.u32 y1, m1, 7, pa1; mad.lo.u32 y2, m2, 7, pa2; mad.lo.u32 y3, m3, 7, pa3; mad.lo.u32 y4, m4, 7, pa4; mad.lo.u32 y5, m5, 7, pa5;\n"
        "add.u32 ad, %2, so; st.shared.v4.b32 [ad+0], {y0,y1,y2,y3};\n"
        "add.u32 ad, %4, so; st.shared.v2.b32 [ad+0], {y4,y5};\n"
        "N1:\n"
        "add.u32 ad, %0, so; ld.shared.v4.b32 {pv12,pv13,pv14,pv15}, [ad+384];\n"
        "add.u32 ad, %1, so; ld.shared.v2.b32 {pv16,pv17}, [ad+384];\n"
        "add.u32 ad, %0, so; ld.shared.v4.b32 {pv18,pv19,pv20,pv21}, [ad+576];\n"
        "add.u32 ad, %1, so; ld.shared.v2.b32 {pv22,pv23}, [ad+576];\n"
        "mov.b32 {xl, xh}, ps2; mov.b32 rr, {xl, xl}; mov.b32 mm, {xh, xh}; fma.rn.bf16x2 pa6, pa6, rr, mm; fma.rn.bf16x2 pa7, pa7, rr, mm; fma.rn.bf16x2 pa8, pa8, rr, mm; fma.rn.bf16x2 pa9, pa9, rr, mm; fma.rn.bf16x2 pa10, pa10, rr, mm; fma.rn.bf16x2 pa11, pa11, rr, mm;\n"
        "and.b32 m0, pa6, 0x7fff7fff; and.b32 m1, pa7, 0x7fff7fff; and.b32 m2, pa8, 0x7fff7fff; and.b32 m3, pa9, 0x7fff7fff; and.b32 m4, pa10, 0x7fff7fff; and.b32 m5, pa11, 0x7fff7fff;\n"
        "mad.lo.u32 y0, m0, 7, pa6; mad.lo.u32 y1, m1, 7, pa7; mad.lo.u32 y2, m2, 7, pa8; mad.lo.u32 y3, m3, 7, pa9; mad.lo.u32 y4, m4, 7, pa10; mad.lo.u32 y5, m5, 7, pa11;\n"
        "add.u32 ad, %3, so; st.shared.v4.b32 [ad+0], {y0,y1,y2,y3};\n"
        "add.u32 ad, %5, so; st.shared.v2.b32 [ad+0], {y4,y5};\n"
        "N2:\n"
        "add.u32 ad, %0, so; ld.shared.v4.b32 {pv24,pv25,pv26,pv27}, [ad+768];\n"
        "add.u32 ad, %1, so; ld.shared.v2.b32 {pv28,pv29}, [ad+768];\n"
        "mov.b32 {xl, xh}, ps4; mov.b32 rr, {xl, xl}; mov.b32 mm, {xh, xh}; fma.rn.bf16x2 pa12, pa12, rr, mm; fma.rn.bf16x2 pa13, pa13, rr, mm; fma.rn.bf16x2 pa14, pa14, rr, mm; fma.rn.bf16x2 pa15, pa15, rr, mm; fma.rn.bf16x2 pa16, pa16, rr, mm; fma.rn.bf16x2 pa17, pa17, rr, mm;\n"
        "and.b32 m0, pa12, 0x7fff7fff; and.b32 m1, pa13, 0x7fff7fff; and.b32 m2, pa14, 0x7fff7fff; and.b32 m3, pa15, 0x7fff7fff; and.b32 m4, pa16, 0x7fff7fff; and.b32 m5, pa17, 0x7fff7fff;\n"
        "mad.lo.u32 y0, m0, 7, pa12; mad.lo.u32 y1, m1, 7, pa13; mad.lo.u32 y2, m2, 7, pa14; mad.lo.u32 y3, m3, 7, pa15; mad.lo.u32 y4, m4, 7, pa16; mad.lo.u32 y5, m5, 7, pa17;\n"
        "add.u32 ad, %2, so; st.shared.v4.b32 [ad+2048], {y0,y1,y2,y3};\n"
        "add.u32 ad, %4, so; st.shared.v2.b32 [ad+1024], {y4,y5};\n"
        "N3:\n"
        "add.u32 ad, %0, so; ld.shared.v4.b32 {pv30,pv31,pv32,pv33}, [ad+960];\n"
        "add.u32 ad, %1, so; ld.shared.v2.b32 {pv34,pv35}, [ad+960];\n"
        "mov.b32 {xl, xh}, ps6; mov.b32 rr, {xl, xl}; mov.b32 mm, {xh, xh}; fma.rn.bf16x2 pa18, pa18, rr, mm; fma.rn.bf16x2 pa19, pa19, rr, mm; fma.rn.bf16x2 pa20, pa20, rr, mm; fma.rn.bf16x2 pa21, pa21, rr, mm; fma.rn.bf16x2 pa22, pa22, rr, mm; fma.rn.bf16x2 pa23, pa23, rr, mm;\n"
        "and.b32 m0, pa18, 0x7fff7fff; and.b32 m1, pa19, 0x7fff7fff; and.b32 m2, pa20, 0x7fff7fff; and.b32 m3, pa21, 0x7fff7fff; and.b32 m4, pa22, 0x7fff7fff; and.b32 m5, pa23, 0x7fff7fff;\n"
        "mad.lo.u32 y0, m0, 7, pa18; mad.lo.u32 y1, m1, 7, pa19; mad.lo.u32 y2, m2, 7, pa20; mad.lo.u32 y3, m3, 7, pa21; mad.lo.u32 y4, m4, 7, pa22; mad.lo.u32 y5, m5, 7, pa23;\n"
        "add.u32 ad, %3, so; st.shared.v4.b32 [ad+2048], {y0,y1,y2,y3};\n"
        "add.u32 ad, %5, so; st.shared.v2.b32 [ad+1024], {y4,y5};\n"
        "add.u32 so, so, 26624; setp.eq.u32 pr, so, 79872; selp.u32 so, 0, so, pr;\n"
        "add.u32 t, t, 8; setp.lt.u32 pe, t, 256;\n"
        "@pe bra.uni LOOP;\n"
        "bra.uni DONE;\n"
        "SPIN: mov.u32 cnt, 0;\n"
        "SPINL:\n"
        "mbarrier.try_wait.parity.shared::cta.b64 pw, [t+231272], 0;\n"
        "@pw bra.uni BACK;\n"
        "add.u32 cnt, cnt, 1; setp.lt.u32 pw, cnt, 0x100000;\n"
        "@pw bra.uni SPINL;\n"
        "trap;\n"
        "RARE:\n"
        "ld.volatile.shared.u32 tt, [%6];\n"
        "mov.b32 pa0, tt; mov.b32 pa1, tt; mov.b32 pa2, tt; mov.b32 pa3, tt; mov.b32 pa4, tt; mov.b32 pa5, tt; mov.b32 pa6, tt; mov.b32 pa7, tt; mov.b32 pa8, tt; mov.b32 pa9, tt; mov.b32 pa10, tt; mov.b32 pa11, tt;\n"
        "mov.b32 pa12, tt; mov.b32 pa13, tt; mov.b32 pa14, tt; mov.b32 pa15, tt; mov.b32 pa16, tt; mov.b32 pa17, tt; mov.b32 pa18, tt; mov.b32 pa19, tt; mov.b32 pa20, tt; mov.b32 pa21, tt; mov.b32 pa22, tt; mov.b32 pa23, tt;\n"
        "mov.b32 pb0, tt; mov.b32 pb1, tt; mov.b32 pb2, tt; mov.b32 pb3, tt; mov.b32 pb4, tt; mov.b32 pb5, tt; mov.b32 pb6, tt; mov.b32 pb7, tt; mov.b32 pb8, tt; mov.b32 pb9, tt; mov.b32 pb10, tt; mov.b32 pb11, tt;\n"
        "mov.b32 pb12, tt; mov.b32 pb13, tt; mov.b32 pb14, tt; mov.b32 pb15, tt; mov.b32 pb16, tt; mov.b32 pb17, tt; mov.b32 pb18, tt; mov.b32 pb19, tt; mov.b32 pb20, tt; mov.b32 pb21, tt; mov.b32 pb22, tt; mov.b32 pb23, tt;\n"
        "mov.b32 pc0, tt; mov.b32 pc1, tt; mov.b32 pc2, tt; mov.b32 pc3, tt; mov.b32 pc4, tt; mov.b32 pc5, tt; mov.b32 pc6, tt; mov.b32 pc7, tt; mov.b32 pc8, tt; mov.b32 pc9, tt; mov.b32 pc10, tt; mov.b32 pc11, tt;\n"
        "mov.b32 pc12, tt; mov.b32 pc13, tt; mov.b32 pc14, tt; mov.b32 pc15, tt; mov.b32 pc16, tt; mov.b32 pc17, tt; mov.b32 pc18, tt; mov.b32 pc19, tt; mov.b32 pc20, tt; mov.b32 pc21, tt; mov.b32 pc22, tt; mov.b32 pc23, tt;\n"
        "mov.b32 ps0, tt; mov.b32 ps1, tt; mov.b32 ps2, tt; mov.b32 ps3, tt; mov.b32 ps4, tt; mov.b32 ps5, tt; mov.b32 ps6, tt; mov.b32 ps7, tt; mov.b32 pq0, tt; mov.b32 pq1, tt; mov.b32 pq2, tt; mov.b32 pq3, tt;\n"
        "ld.volatile.shared.v2.b32 {pw1, pw0}, [%6]; xor.b32 tt, tt, pw1;\n"
        "ld.volatile.shared.v2.b32 {pw3, pw2}, [%6]; xor.b32 tt, tt, pw3;\n"
        "ld.volatile.shared.v2.b32 {pw5, pw4}, [%6]; xor.b32 tt, tt, pw5;\n"
        "ld.volatile.shared.v2.b32 {pw7, pw6}, [%6]; xor.b32 tt, tt, pw7;\n"
        "ld.volatile.shared.v2.b32 {pw9, pw8}, [%6]; xor.b32 tt, tt, pw9;\n"
        "ld.volatile.shared.v2.b32 {pw11, pw10}, [%6]; xor.b32 tt, tt, pw11;\n"
        "ld.volatile.shared.v2.b32 {pw13, pw12}, [%6]; xor.b32 tt, tt, pw13;\n"
        "ld.volatile.shared.v2.b32 {pw15, pw14}, [%6]; xor.b32 tt, tt, pw15;\n"
        "ld.volatile.shared.v2.b32 {pw17, pw16}, [%6]; xor.b32 tt, tt, pw17;\n"
        "ld.volatile.shared.v2.b32 {pw19, pw18}, [%6]; xor.b32 tt, tt, pw19;\n"
        "ld.volatile.shared.v2.b32 {pw21, pw20}, [%6]; xor.b32 tt, tt, pw21;\n"
        "ld.volatile.shared.v2.b32 {pw23, pw22}, [%6]; xor.b32 tt, tt, pw23;\n"
        "ld.volatile.shared.v2.b32 {pw25, pw24}, [%6]; xor.b32 tt, tt, pw25;\n"
        "ld.volatile.shared.v2.b32 {pw27, pw26}, [%6]; xor.b32 tt, tt, pw27;\n"
        "ld.volatile.shared.v2.b32 {pw29, pw28}, [%6]; xor.b32 tt, tt, pw29;\n"
        "ld.volatile.shared.v2.b32 {pw31, pw30}, [%6]; xor.b32 tt, tt, pw31;\n"
        "ld.volatile.shared.v2.b32 {pw33, pw32}, [%6]; xor.b32 tt, tt, pw33;\n"
        "ld.volatile.shared.v2.b32 {pw35, pw34}, [%6]; xor.b32 tt, tt, pw35;\n"
        "ld.volatile.shared.v2.b32 {pw37, pw36}, [%6]; xor.b32 tt, tt, pw37;\n"
        "ld.volatile.shared.v2.b32 {pw39, pw38}, [%6]; xor.b32 tt, tt, pw39;\n"
        "ld.volatile.shared.v2.b32 {pw41, pw40}, [%6]; xor.b32 tt, tt, pw41;\n"
        "ld.volatile.shared.v2.b32 {pw43, pw42}, [%6]; xor.b32 tt, tt, pw43;\n"
        "ld.volatile.shared.v2.b32 {pw45, pw44}, [%6]; xor.b32 tt, tt, pw45;\n"
        "ld.volatile.shared.v2.b32 {pw47, pw46}, [%6]; xor.b32 tt, tt, pw47;\n"
        "ld.volatile.shared.v2.b32 {pw49, pw48}, [%6]; xor.b32 tt, tt, pw49;\n"
        "ld.volatile.shared.v2.b32 {pw51, pw50}, [%6]; xor.b32 tt, tt, pw51;\n"
        "ld.volatile.shared.v2.b32 {pw53, pw52}, [%6]; xor.b32 tt, tt, pw53;\n"
        "mov.b32 us, tt; setp.ne.u32 pw, %15, 7;\n"
        "wgmma.fence.sync.aligned;\n"
        "setp.eq.u32 pr, %15, 1000; @pr bra.uni B0;\n"
        "setp.eq.u32 pr, %15, 1001; @pr bra.uni B1;\n"
        "setp.eq.u32 pr, %15, 1002; @pr bra.uni C0;\n"
        "setp.eq.u32 pr, %15, 1003; @pr bra.uni N0;\n"
        "setp.eq.u32 pr, %15, 1004; @pr bra.uni N1;\n"
        "setp.eq.u32 pr, %15, 1005; @pr bra.uni N2;\n"
        "setp.eq.u32 pr, %15, 1006; @pr bra.uni N3;\n"
        "trap;\n"
        "DONE:\n"
        ASM_TRC("t")
        "fence.proxy.async.shared::cta;\n"
        "@pl mbarrier.arrive.shared::cta.b64 _, [t+231552];\n"
        "}\n"
        :: "r"(sb + SM_X + c.xoff[0]), "r"(sb + SM_X + c.xoff[1]), "r"(sb + SM_Y1 + c.yoff[0][0]), "r"(sb + SM_Y1 + c.yoff[0][1]),
           "r"(sb + SM_Y1 + c.yoff[1][0]), "r"(sb + SM_Y1 + c.yoff[1][1]), "r"(c.stat), "r"(c.own), "r"(c.lane),
           "l"(prm.sel[0]), "l"(prm.sel[1]), "l"(prm.sel[2]), "r"(prm.ydesc), "f"(LN_EPS_SCALED), "f"(RSTD_SCALE), "r"(prm.w1desc)
        : "memory");
}

__device__ __forceinline__ void produce(const Producer& c, const Params& prm) {
    uint32_t B[24], C[24];
    uint32_t st[8];
    uint32_t v[6][6];
    uint32_t ws[6];
#pragma unroll
    for (int u = 0; u < 6; u++) {
        ws[u] = c.w[0][u];
#pragma unroll
        for (int t = 1; t < 9; t++) ws[u] = bf2_add(ws[u], c.w[t][u]);
    }
    SMARK(2);
#pragma unroll 1
    for (int i = loop_init<0>(), so = loop_init<0>();; i++, so += SLOT_BYTES) {
        mbar_wait_c<0>(sb + SM_GO + i * 8);
        SMARK(4 + i);
        load_x(v, c, sb + SM_X + so);
        if (i == 2) break;
        if (so == 0) {
            const uint32_t p = bf2_add(bf2_fma(v[2][2], ws[2], bf2_fma(v[2][1], ws[1], bf2_mul(v[2][0], ws[0]))),
                                       bf2_fma(v[2][5], ws[5], bf2_fma(v[2][4], ws[4], bf2_mul(v[2][3], ws[3]))));
            float e = quad_sum(bf_lo(p) + bf_hi(p));
            e = (e + __shfl_xor_sync(0xffffffffu, e, 4)) * (-1.0f / CH);
            st[1] = st[3] = st[5] = st[7] = pack_bf2(e, e);
#pragma unroll
            for (int k = 0; k < NX; k++) sts32(c.own + k * SLOT_BYTES + 4, st[1]);
        } else {
            conv_row<1, 1>(B, C, v, c);
        }
        conv_row<0, 0>(C, st, v, c);
        fence_async_smem();
        asm volatile("bar.arrive %0, 160;" ::"r"(6 + i) : "memory");
    }
    asm volatile(".reg .b32 pw<54>, pb<24>, pc<24>, pv<36>, ps<8>;");
    hand_over<0>(c, B, C, v);
    asm volatile("mov.b32 ps1, %0; mov.b32 ps3, %1; mov.b32 ps5, %2; mov.b32 ps7, %3;" ::"r"(st[1]), "r"(st[3]), "r"(st[5]), "r"(st[7]));
    SMARK(7);
    produce_tiles(c, prm);
    mbar_arrive_if(sb + SM_YFULL + ROWS_PER_CTA * 8, c.lane == 0);
}

struct Duty {
    const char* g;
    const char* zeros;
    long long step;
    uint32_t s, bytes;
    int end, zero;
};
__device__ __forceinline__ Duty make_duty(const Params& prm, int wg, int w) {
    const RowCopy rc = row_copy(prm);
    Duty d;
    d.g = (w == 2 ? rc.y0 : rc.x0 + (w == 0 ? rc.cut0 : w == 1 ? 32 * 192 : 192)) +
          (wg + (w == 2 ? 0 : w < 2 ? 2 * NX : 2 * NX + L2_AHEAD)) * rc.stride;
    d.step = NX * rc.stride;
    d.s = wg * SLOT_BYTES + (w == 2 ? sb + SM_Y1 : sb + SM_X + (w == 0 ? rc.cut0 : XHALF_B));
    d.bytes = w >= 2 ? TILE_BYTES : XHALF_BYTES - (w == 0 ? rc.cut0 : rc.cut1);
    d.end = w == 2 ? ROWS_PER_CTA : w < 2 ? STEPS + 1 - 2 * NX : rc.last + 1 - 2 * NX - L2_AHEAD;
    d.zero = rc.last + 1 - 2 * NX;
    d.zeros = rc.zeros;
    return d;
}

static_assert(sb + SM_BAR == 230800 && sb + SM_YFULL == 231560 && sb + SM_GO == 231248 && SLOT_BYTES == 26624 && sb + SM_GAMMA == 229248 &&
              SM_BETA == SM_GAMMA + 768 && SM_W2 == 73728 && sb + SM_BUF3 == 187392 && BAR_W2 == 9 && BAR_W1B == 10, "layout");
__device__ __forceinline__ void consume(float (&acc)[2][2], uint32_t w1t, uint32_t yd, uint32_t wd, uint32_t own_slot, const Duty& d,
                                        uint32_t role, uint32_t lane, const Params& prm) {
    asm volatile(
        "{\n"
        ".reg .b32 z<32>, w<44>, p, a<4>, lo<2>, hi<2>, t, g, q<4>, dl, dh, n, so, c, tt, cnt, f0, f1;\n"
        ".reg .b16 xl, xh, xr;\n"
        ".reg .b64 ds<6>, wd, gp, src;\n"
        ".reg .pred pt, pf, pr, pw, pl, pe;\n"
        "setp.ne.b32 pt, 1, 0; setp.ne.b32 pf, 0, 0; setp.eq.u32 pl, %15, 0;\n"
        "mov.b32 c, 0x40D940D9;\n"
        "ldmatrix.sync.aligned.m8n8.x4.trans.shared.b16 {w0,w1,w2,w3}, [%4+0];\n"
        "ldmatrix.sync.aligned.m8n8.x4.trans.shared.b16 {w4,w5,w6,w7}, [%4+2048];\n"
        "ldmatrix.sync.aligned.m8n8.x4.trans.shared.b16 {w8,w9,w10,w11}, [%4+4096];\n"
        "ldmatrix.sync.aligned.m8n8.x4.trans.shared.b16 {w12,w13,w14,w15}, [%4+6144];\n"
        "ldmatrix.sync.aligned.m8n8.x4.trans.shared.b16 {w16,w17,w18,w19}, [%4+8192];\n"
        "ldmatrix.sync.aligned.m8n8.x4.trans.shared.b16 {w20,w21,w22,w23}, [%4+10240];\n"
        "shl.b32 f0, w0, 16; and.b32 f1, w0, 0xffff0000; cvt.rn.f16x2.f32 w0, f1, f0; shl.b32 f0, w1, 16; and.b32 f1, w1, 0xffff0000; cvt.rn.f16x2.f32 w1, f1, f0; shl.b32 f0, w2, 16; and.b32 f1, w2, 0xffff0000; cvt.rn.f16x2.f32 w2, f1, f0; shl.b32 f0, w3, 16; and.b32 f1, w3, 0xffff0000; cvt.rn.f16x2.f32 w3, f1, f0;\n"
        "stmatrix.sync.aligned.m8n8.x4.trans.shared.b16 [%4+0], {w0,w1,w2,w3};\n"
        "shl.b32 f0, w4, 16; and.b32 f1, w4, 0xffff0000; cvt.rn.f16x2.f32 w4, f1, f0; shl.b32 f0, w5, 16; and.b32 f1, w5, 0xffff0000; cvt.rn.f16x2.f32 w5, f1, f0; shl.b32 f0, w6, 16; and.b32 f1, w6, 0xffff0000; cvt.rn.f16x2.f32 w6, f1, f0; shl.b32 f0, w7, 16; and.b32 f1, w7, 0xffff0000; cvt.rn.f16x2.f32 w7, f1, f0;\n"
        "stmatrix.sync.aligned.m8n8.x4.trans.shared.b16 [%4+2048], {w4,w5,w6,w7};\n"
        "shl.b32 f0, w8, 16; and.b32 f1, w8, 0xffff0000; cvt.rn.f16x2.f32 w8, f1, f0; shl.b32 f0, w9, 16; and.b32 f1, w9, 0xffff0000; cvt.rn.f16x2.f32 w9, f1, f0; shl.b32 f0, w10, 16; and.b32 f1, w10, 0xffff0000; cvt.rn.f16x2.f32 w10, f1, f0; shl.b32 f0, w11, 16; and.b32 f1, w11, 0xffff0000; cvt.rn.f16x2.f32 w11, f1, f0;\n"
        "stmatrix.sync.aligned.m8n8.x4.trans.shared.b16 [%4+4096], {w8,w9,w10,w11};\n"
        "shl.b32 f0, w12, 16; and.b32 f1, w12, 0xffff0000; cvt.rn.f16x2.f32 w12, f1, f0; shl.b32 f0, w13, 16; and.b32 f1, w13, 0xffff0000; cvt.rn.f16x2.f32 w13, f1, f0; shl.b32 f0, w14, 16; and.b32 f1, w14, 0xffff0000; cvt.rn.f16x2.f32 w14, f1, f0; shl.b32 f0, w15, 16; and.b32 f1, w15, 0xffff0000; cvt.rn.f16x2.f32 w15, f1, f0;\n"
        "stmatrix.sync.aligned.m8n8.x4.trans.shared.b16 [%4+6144], {w12,w13,w14,w15};\n"
        "shl.b32 f0, w16, 16; and.b32 f1, w16, 0xffff0000; cvt.rn.f16x2.f32 w16, f1, f0; shl.b32 f0, w17, 16; and.b32 f1, w17, 0xffff0000; cvt.rn.f16x2.f32 w17, f1, f0; shl.b32 f0, w18, 16; and.b32 f1, w18, 0xffff0000; cvt.rn.f16x2.f32 w18, f1, f0; shl.b32 f0, w19, 16; and.b32 f1, w19, 0xffff0000; cvt.rn.f16x2.f32 w19, f1, f0;\n"
        "stmatrix.sync.aligned.m8n8.x4.trans.shared.b16 [%4+8192], {w16,w17,w18,w19};\n"
        "shl.b32 f0, w20, 16; and.b32 f1, w20, 0xffff0000; cvt.rn.f16x2.f32 w20, f1, f0; shl.b32 f0, w21, 16; and.b32 f1, w21, 0xffff0000; cvt.rn.f16x2.f32 w21, f1, f0; shl.b32 f0, w22, 16; and.b32 f1, w22, 0xffff0000; cvt.rn.f16x2.f32 w22, f1, f0; shl.b32 f0, w23, 16; and.b32 f1, w23, 0xffff0000; cvt.rn.f16x2.f32 w23, f1, f0;\n"
        "stmatrix.sync.aligned.m8n8.x4.trans.shared.b16 [%4+10240], {w20,w21,w22,w23};\n"
        "mov.u32 tt, 230880; mbarrier.try_wait.parity.shared::cta.b64 pw, [tt], 0;\n"
        "@!pw bra.uni SPINW;\n"
        "BACKW:\n"
        "ldmatrix.sync.aligned.m8n8.x4.trans.shared.b16 {z0,z1,z2,z3}, [%4+22528];\n"
        "ldmatrix.sync.aligned.m8n8.x4.trans.shared.b16 {w24,w25,w26,w27}, [%4+12288];\n"
        "ldmatrix.sync.aligned.m8n8.x4.trans.shared.b16 {w28,w29,w30,w31}, [%4+14336];\n"
        "ldmatrix.sync.aligned.m8n8.x4.trans.shared.b16 {w32,w33,w34,w35}, [%4+16384];\n"
        "ldmatrix.sync.aligned.m8n8.x4.trans.shared.b16 {w36,w37,w38,w39}, [%4+18432];\n"
        "ldmatrix.sync.aligned.m8n8.x4.trans.shared.b16 {w40,w41,w42,w43}, [%4+20480];\n"
        "shl.b32 f0, z0, 16; and.b32 f1, z0, 0xffff0000; cvt.rn.f16x2.f32 z0, f1, f0; shl.b32 f0, z1, 16; and.b32 f1, z1, 0xffff0000; cvt.rn.f16x2.f32 z1, f1, f0; shl.b32 f0, z2, 16; and.b32 f1, z2, 0xffff0000; cvt.rn.f16x2.f32 z2, f1, f0; shl.b32 f0, z3, 16; and.b32 f1, z3, 0xffff0000; cvt.rn.f16x2.f32 z3, f1, f0;\n"
        "stmatrix.sync.aligned.m8n8.x4.trans.shared.b16 [%4+22528], {z0,z1,z2,z3};\n"
        "shl.b32 f0, w24, 16; and.b32 f1, w24, 0xffff0000; cvt.rn.f16x2.f32 w24, f1, f0; shl.b32 f0, w25, 16; and.b32 f1, w25, 0xffff0000; cvt.rn.f16x2.f32 w25, f1, f0; shl.b32 f0, w26, 16; and.b32 f1, w26, 0xffff0000; cvt.rn.f16x2.f32 w26, f1, f0; shl.b32 f0, w27, 16; and.b32 f1, w27, 0xffff0000; cvt.rn.f16x2.f32 w27, f1, f0;\n"
        "stmatrix.sync.aligned.m8n8.x4.trans.shared.b16 [%4+12288], {w24,w25,w26,w27};\n"
        "shl.b32 f0, w28, 16; and.b32 f1, w28, 0xffff0000; cvt.rn.f16x2.f32 w28, f1, f0; shl.b32 f0, w29, 16; and.b32 f1, w29, 0xffff0000; cvt.rn.f16x2.f32 w29, f1, f0; shl.b32 f0, w30, 16; and.b32 f1, w30, 0xffff0000; cvt.rn.f16x2.f32 w30, f1, f0; shl.b32 f0, w31, 16; and.b32 f1, w31, 0xffff0000; cvt.rn.f16x2.f32 w31, f1, f0;\n"
        "stmatrix.sync.aligned.m8n8.x4.trans.shared.b16 [%4+14336], {w28,w29,w30,w31};\n"
        "shl.b32 f0, w32, 16; and.b32 f1, w32, 0xffff0000; cvt.rn.f16x2.f32 w32, f1, f0; shl.b32 f0, w33, 16; and.b32 f1, w33, 0xffff0000; cvt.rn.f16x2.f32 w33, f1, f0; shl.b32 f0, w34, 16; and.b32 f1, w34, 0xffff0000; cvt.rn.f16x2.f32 w34, f1, f0; shl.b32 f0, w35, 16; and.b32 f1, w35, 0xffff0000; cvt.rn.f16x2.f32 w35, f1, f0;\n"
        "stmatrix.sync.aligned.m8n8.x4.trans.shared.b16 [%4+16384], {w32,w33,w34,w35};\n"
        "shl.b32 f0, w36, 16; and.b32 f1, w36, 0xffff0000; cvt.rn.f16x2.f32 w36, f1, f0; shl.b32 f0, w37, 16; and.b32 f1, w37, 0xffff0000; cvt.rn.f16x2.f32 w37, f1, f0; shl.b32 f0, w38, 16; and.b32 f1, w38, 0xffff0000; cvt.rn.f16x2.f32 w38, f1, f0; shl.b32 f0, w39, 16; and.b32 f1, w39, 0xffff0000; cvt.rn.f16x2.f32 w39, f1, f0;\n"
        "stmatrix.sync.aligned.m8n8.x4.trans.shared.b16 [%4+18432], {w36,w37,w38,w39};\n"
        "shl.b32 f0, w40, 16; and.b32 f1, w40, 0xffff0000; cvt.rn.f16x2.f32 w40, f1, f0; shl.b32 f0, w41, 16; and.b32 f1, w41, 0xffff0000; cvt.rn.f16x2.f32 w41, f1, f0; shl.b32 f0, w42, 16; and.b32 f1, w42, 0xffff0000; cvt.rn.f16x2.f32 w42, f1, f0; shl.b32 f0, w43, 16; and.b32 f1, w43, 0xffff0000; cvt.rn.f16x2.f32 w43, f1, f0;\n"
        "stmatrix.sync.aligned.m8n8.x4.trans.shared.b16 [%4+20480], {w40,w41,w42,w43};\n"
        "fence.proxy.async.shared::cta;\n"
        ASM_SMARK
        "mov.b32 p, 0; mov.b32 t, 0; mov.b32 g, 0; mov.b32 a0, 0; mov.b32 a1, 0; mov.b32 a2, 0; mov.b32 a3, 0; mov.b32 lo0, 0; mov.b32 lo1, 0; mov.b32 hi0, 0; mov.b32 hi1, 0; mov.b32 q0, 0; mov.b32 q1, 0; mov.b32 q2, 0; mov.b32 q3, 0;\n"
        "mov.b32 z16, 0; mov.b32 z17, 0; mov.b32 z18, 0; mov.b32 z19, 0; mov.b32 z20, 0; mov.b32 z21, 0; mov.b32 z22, 0; mov.b32 z23, 0; mov.b32 z24, 0; mov.b32 z25, 0; mov.b32 z26, 0; mov.b32 z27, 0; mov.b32 z28, 0; mov.b32 z29, 0; mov.b32 z30, 0; mov.b32 z31, 0;\n"
        "mov.f32 %0, 0f00000000; mov.f32 %1, 0f00000000; mov.f32 %2, 0f00000000; mov.f32 %3, 0f00000000;\n"
        "mov.u32 n, 0; mov.u32 so, 0; mov.b64 gp, %8; mov.b64 wd, {%6, 0x40000040};\n"
        "mov.b64 ds0, %20; add.s64 ds1, ds0, 2; add.s64 ds2, ds0, 4; add.s64 ds3, ds0, 6; mov.b64 ds4, %21; add.s64 ds5, ds4, 2;\n"
        "setp.eq.u32 pr, %7, 53248; setp.lt.and.u32 pr, %13, 2, pr;\n"
        "@!pr bra.uni ROW5;\n"
        "mbarrier.try_wait.parity.shared::cta.b64 pw, [n+231552], 0;\n"
        "@!pw bra.uni SPIN5;\n"
        "BACK5:\n"
        "sub.s64 src, gp, %16; mov.u32 tt, 231288;\n"
        "elect.sync _|pr, 0xffffffff;\n"
        "@pr mbarrier.arrive.expect_tx.shared::cta.b64 _, [tt], %10;\n"
        "@pr cp.async.bulk.shared::cluster.global.mbarrier::complete_tx::bytes [%9], [src], %10, [tt];\n"
        "ROW5:\n"
        "mbarrier.try_wait.parity.shared::cta.b64 pw, [n+231560], 0;\n"
        "@!pw bra.uni SPIN0;\n"
        "BACK0:\n"
        ASM_TS
        "wgmma.fence.sync.aligned;\n"
        "wgmma.mma_async.sync.aligned.m64n64k16.f16.f16.f16 {z0,z1,z2,z3,z4,z5,z6,z7,z8,z9,z10,z11,z12,z13,z14,z15}, {w0,w1,w2,w3}, ds0, pf, 1, 1, 0;\n"
        "wgmma.mma_async.sync.aligned.m64n64k16.f16.f16.f16 {z0,z1,z2,z3,z4,z5,z6,z7,z8,z9,z10,z11,z12,z13,z14,z15}, {w4,w5,w6,w7}, ds1, pt, 1, 1, 0;\n"
        "wgmma.mma_async.sync.aligned.m64n64k16.f16.f16.f16 {z0,z1,z2,z3,z4,z5,z6,z7,z8,z9,z10,z11,z12,z13,z14,z15}, {w8,w9,w10,w11}, ds2, pt, 1, 1, 0;\n"
        "wgmma.fence.sync.aligned;\n"
        "wgmma.mma_async.sync.aligned.m64n64k16.f16.f16.f16 {z0,z1,z2,z3,z4,z5,z6,z7,z8,z9,z10,z11,z12,z13,z14,z15}, {w12,w13,w14,w15}, ds3, pt, 1, 1, 0;\n"
        "wgmma.mma_async.sync.aligned.m64n64k16.f16.f16.f16 {z0,z1,z2,z3,z4,z5,z6,z7,z8,z9,z10,z11,z12,z13,z14,z15}, {w16,w17,w18,w19}, ds4, pt, 1, 1, 0;\n"
        "wgmma.mma_async.sync.aligned.m64n64k16.f16.f16.f16 {z0,z1,z2,z3,z4,z5,z6,z7,z8,z9,z10,z11,z12,z13,z14,z15}, {w20,w21,w22,w23}, ds5, pt, 1, 1, 0;\n"
        "wgmma.commit_group.sync.aligned;\n"
        "setp.eq.u32 pr, so, %7;\n"
        "@pr bra.uni DUTY;\n"
        "TOP:\n"
        ASM_TRC("n")
        "wgmma.wait_group.sync.aligned 0;\n"
        "mov.b32 {xl, xh}, a2; tanh.approx.f16 xr, xh; cvt.u32.u16 hi0, xr; mul.rn.f16x2 a3, z31, p; fma.rn.f16x2 p, z0, z0, c; fma.rn.f16x2 q3, g, g, q3; fma.rn.f16x2 g, z28, t, z28; prmt.b32 t, lo1, hi1, 0x5410; tanh.approx.f16 xr, xl; cvt.u32.u16 lo0, xr;\n"
        "B31:\n"
        "mov.b32 {xl, xh}, a3; tanh.approx.f16 xr, xh; cvt.u32.u16 hi1, xr; mul.rn.f16x2 a0, z0, p; fma.rn.f16x2 p, z1, z1, c; fma.rn.f16x2 q2, g, g, q2; fma.rn.f16x2 g, z29, t, z29; prmt.b32 t, lo0, hi0, 0x5410; tanh.approx.f16 xr, xl; cvt.u32.u16 lo1, xr;\n"
        "B0:\n"
        "mov.b32 {xl, xh}, a0; tanh.approx.f16 xr, xh; cvt.u32.u16 hi0, xr; mul.rn.f16x2 a1, z1, p; fma.rn.f16x2 p, z2, z2, c; fma.rn.f16x2 q3, g, g, q3; fma.rn.f16x2 g, z30, t, z30; prmt.b32 t, lo1, hi1, 0x5410; tanh.approx.f16 xr, xl; cvt.u32.u16 lo0, xr;\n"
        "B1:\n"
        "mov.b32 {xl, xh}, a1; tanh.approx.f16 xr, xh; cvt.u32.u16 hi1, xr; mul.rn.f16x2 a2, z2, p; fma.rn.f16x2 p, z3, z3, c; fma.rn.f16x2 q2, g, g, q2; fma.rn.f16x2 g, z31, t, z31; prmt.b32 t, lo0, hi0, 0x5410; tanh.approx.f16 xr, xl; cvt.u32.u16 lo1, xr;\n"
        "B2:\n"
        "wgmma.fence.sync.aligned;\n"
        "wgmma.mma_async.sync.aligned.m64n64k16.f16.f16.f16 {z16,z17,z18,z19,z20,z21,z22,z23,z24,z25,z26,z27,z28,z29,z30,z31}, {w24,w25,w26,w27}, ds0, pf, 1, 1, 0;\n"
        "wgmma.mma_async.sync.aligned.m64n64k16.f16.f16.f16 {z16,z17,z18,z19,z20,z21,z22,z23,z24,z25,z26,z27,z28,z29,z30,z31}, {w28,w29,w30,w31}, ds1, pt, 1, 1, 0;\n"
        "wgmma.mma_async.sync.aligned.m64n64k16.f16.f16.f16 {z16,z17,z18,z19,z20,z21,z22,z23,z24,z25,z26,z27,z28,z29,z30,z31}, {w32,w33,w34,w35}, ds2, pt, 1, 1, 0;\n"
        "mov.b32 {xl, xh}, a2; tanh.approx.f16 xr, xh; cvt.u32.u16 hi0, xr; mul.rn.f16x2 a3, z3, p; fma.rn.f16x2 p, z4, z4, c; fma.rn.f16x2 q3, g, g, q3; fma.rn.f16x2 g, z0, t, z0; prmt.b32 t, lo1, hi1, 0x5410; tanh.approx.f16 xr, xl; cvt.u32.u16 lo0, xr;\n"
        "B3:\n"
        "mov.b32 {xl, xh}, a3; tanh.approx.f16 xr, xh; cvt.u32.u16 hi1, xr; mul.rn.f16x2 a0, z4, p; fma.rn.f16x2 p, z5, z5, c; fma.rn.f16x2 q0, g, g, q0; fma.rn.f16x2 g, z1, t, z1; prmt.b32 t, lo0, hi0, 0x5410; tanh.approx.f16 xr, xl; cvt.u32.u16 lo1, xr;\n"
        "B4:\n"
        "mov.b32 {xl, xh}, a0; tanh.approx.f16 xr, xh; cvt.u32.u16 hi0, xr; mul.rn.f16x2 a1, z5, p; fma.rn.f16x2 p, z6, z6, c; fma.rn.f16x2 q1, g, g, q1; fma.rn.f16x2 g, z2, t, z2; prmt.b32 t, lo1, hi1, 0x5410; tanh.approx.f16 xr, xl; cvt.u32.u16 lo0, xr;\n"
        "B5:\n"
        "wgmma.fence.sync.aligned;\n"
        "wgmma.mma_async.sync.aligned.m64n64k16.f16.f16.f16 {z16,z17,z18,z19,z20,z21,z22,z23,z24,z25,z26,z27,z28,z29,z30,z31}, {w36,w37,w38,w39}, ds3, pt, 1, 1, 0;\n"
        "wgmma.mma_async.sync.aligned.m64n64k16.f16.f16.f16 {z16,z17,z18,z19,z20,z21,z22,z23,z24,z25,z26,z27,z28,z29,z30,z31}, {w40,w41,w42,w43}, ds4, pt, 1, 1, 0;\n"
        "wgmma.mma_async.sync.aligned.m64n64k16.f16.f16.f16 {z16,z17,z18,z19,z20,z21,z22,z23,z24,z25,z26,z27,z28,z29,z30,z31}, wd, ds5, pt, 1, 1, 1, 0;\n"
        "wgmma.commit_group.sync.aligned;\n"
        "mov.b32 {xl, xh}, a1; tanh.approx.f16 xr, xh; cvt.u32.u16 hi1, xr; mul.rn.f16x2 a2, z6, p; fma.rn.f16x2 p, z7, z7, c; fma.rn.f16x2 q0, g, g, q0; fma.rn.f16x2 g, z3, t, z3; prmt.b32 t, lo0, hi0, 0x5410; tanh.approx.f16 xr, xl; cvt.u32.u16 lo1, xr;\n"
        "B6:\n"
        "add.u32 so, so, 26624; setp.eq.u32 pr, so, 79872; selp.u32 so, 0, so, pr;\n"
        "mov.b32 {xl, xh}, a2; tanh.approx.f16 xr, xh; cvt.u32.u16 hi0, xr; mul.rn.f16x2 a3, z7, p; fma.rn.f16x2 p, z8, z8, c; fma.rn.f16x2 q1, g, g, q1; fma.rn.f16x2 g, z4, t, z4; prmt.b32 t, lo1, hi1, 0x5410; tanh.approx.f16 xr, xl; cvt.u32.u16 lo0, xr;\n"
        "B7:\n"
        "shr.u32 tt, so, 4;\n"
        "mov.b64 {dl, dh}, ds0; add.u32 dl, tt, 74816; mov.b64 ds0, {dl, dh}; mov.b64 {dl, dh}, ds1; add.u32 dl, tt, 74818; mov.b64 ds1, {dl, dh}; mov.b64 {dl, dh}, ds2; add.u32 dl, tt, 74820; mov.b64 ds2, {dl, dh};\n"
        "mov.b32 {xl, xh}, a3; tanh.approx.f16 xr, xh; cvt.u32.u16 hi1, xr; mul.rn.f16x2 a0, z8, p; fma.rn.f16x2 p, z9, z9, c; fma.rn.f16x2 q0, g, g, q0; fma.rn.f16x2 g, z5, t, z5; prmt.b32 t, lo0, hi0, 0x5410; tanh.approx.f16 xr, xl; cvt.u32.u16 lo1, xr;\n"
        "B8:\n"
        "shr.u32 tt, so, 4;\n"
        "mov.b64 {dl, dh}, ds3; add.u32 dl, tt, 74822; mov.b64 ds3, {dl, dh}; mov.b64 {dl, dh}, ds4; add.u32 dl, tt, 75328; mov.b64 ds4, {dl, dh}; mov.b64 {dl, dh}, ds5; add.u32 dl, tt, 75330; mov.b64 ds5, {dl, dh};\n"
        "mov.b32 {xl, xh}, a0; tanh.approx.f16 xr, xh; cvt.u32.u16 hi0, xr; mul.rn.f16x2 a1, z9, p; fma.rn.f16x2 p, z10, z10, c; fma.rn.f16x2 q1, g, g, q1; fma.rn.f16x2 g, z6, t, z6; prmt.b32 t, lo1, hi1, 0x5410; tanh.approx.f16 xr, xl; cvt.u32.u16 lo0, xr;\n"
        "B9:\n"
        "mov.b32 {xl, xh}, a1; tanh.approx.f16 xr, xh; cvt.u32.u16 hi1, xr; mul.rn.f16x2 a2, z10, p; fma.rn.f16x2 p, z11, z11, c; fma.rn.f16x2 q0, g, g, q0; fma.rn.f16x2 g, z7, t, z7; prmt.b32 t, lo0, hi0, 0x5410; tanh.approx.f16 xr, xl; cvt.u32.u16 lo1, xr;\n"
        "B10:\n"
        "mov.b32 {xl, xh}, a2; tanh.approx.f16 xr, xh; cvt.u32.u16 hi0, xr; mul.rn.f16x2 a3, z11, p; fma.rn.f16x2 p, z12, z12, c; fma.rn.f16x2 q1, g, g, q1; fma.rn.f16x2 g, z8, t, z8; prmt.b32 t, lo1, hi1, 0x5410; tanh.approx.f16 xr, xl; cvt.u32.u16 lo0, xr;\n"
        "B11:\n"
        "mov.b32 {xl, xh}, a3; tanh.approx.f16 xr, xh; cvt.u32.u16 hi1, xr; mul.rn.f16x2 a0, z12, p; fma.rn.f16x2 p, z13, z13, c; fma.rn.f16x2 q0, g, g, q0; fma.rn.f16x2 g, z9, t, z9; prmt.b32 t, lo0, hi0, 0x5410; tanh.approx.f16 xr, xl; cvt.u32.u16 lo1, xr;\n"
        "B12:\n"
        "mov.b32 {xl, xh}, a0; tanh.approx.f16 xr, xh; cvt.u32.u16 hi0, xr; mul.rn.f16x2 a1, z13, p; fma.rn.f16x2 p, z14, z14, c; fma.rn.f16x2 q1, g, g, q1; fma.rn.f16x2 g, z10, t, z10; prmt.b32 t, lo1, hi1, 0x5410; tanh.approx.f16 xr, xl; cvt.u32.u16 lo0, xr;\n"
        "B13:\n"
        "mov.b32 {xl, xh}, a1; tanh.approx.f16 xr, xh; cvt.u32.u16 hi1, xr; mul.rn.f16x2 a2, z14, p; fma.rn.f16x2 p, z15, z15, c; fma.rn.f16x2 q0, g, g, q0; fma.rn.f16x2 g, z11, t, z11; prmt.b32 t, lo0, hi0, 0x5410; tanh.approx.f16 xr, xl; cvt.u32.u16 lo1, xr;\n"
        "B14:\n"
        "wgmma.wait_group.sync.aligned 0;\n"
        "cp.async.bulk.wait_group.read 0;\n"
        "@pl mbarrier.arrive.shared::cta.b64 _, [n+231296];\n"
        "mov.b32 {xl, xh}, a2; tanh.approx.f16 xr, xh; cvt.u32.u16 hi0, xr; mul.rn.f16x2 a3, z15, p; fma.rn.f16x2 p, z16, z16, c; fma.rn.f16x2 q1, g, g, q1; fma.rn.f16x2 g, z12, t, z12; prmt.b32 t, lo1, hi1, 0x5410; tanh.approx.f16 xr, xl; cvt.u32.u16 lo0, xr;\n"
        "B15:\n"
        "mov.b32 {xl, xh}, a3; tanh.approx.f16 xr, xh; cvt.u32.u16 hi1, xr; mul.rn.f16x2 a0, z16, p; fma.rn.f16x2 p, z17, z17, c; fma.rn.f16x2 q0, g, g, q0; fma.rn.f16x2 g, z13, t, z13; prmt.b32 t, lo0, hi0, 0x5410; tanh.approx.f16 xr, xl; cvt.u32.u16 lo1, xr;\n"
        "B16:\n"
        "mbarrier.try_wait.parity.shared::cta.b64 pw, [n+231568], 0;\n"
        "mov.b32 {xl, xh}, a0; tanh.approx.f16 xr, xh; cvt.u32.u16 hi0, xr; mul.rn.f16x2 a1, z17, p; fma.rn.f16x2 p, z18, z18, c; fma.rn.f16x2 q1, g, g, q1; fma.rn.f16x2 g, z14, t, z14; prmt.b32 t, lo1, hi1, 0x5410; tanh.approx.f16 xr, xl; cvt.u32.u16 lo0, xr;\n"
        "B17:\n"
        "mov.b32 {xl, xh}, a1; tanh.approx.f16 xr, xh; cvt.u32.u16 hi1, xr; mul.rn.f16x2 a2, z18, p; fma.rn.f16x2 p, z19, z19, c; fma.rn.f16x2 q0, g, g, q0; fma.rn.f16x2 g, z15, t, z15; prmt.b32 t, lo0, hi0, 0x5410; tanh.approx.f16 xr, xl; cvt.u32.u16 lo1, xr;\n"
        "B18:\n"
        "@!pw bra.uni SPIN;\n"
        "BACK:\n"
        "wgmma.fence.sync.aligned;\n"
        "wgmma.mma_async.sync.aligned.m64n64k16.f16.f16.f16 {z0,z1,z2,z3,z4,z5,z6,z7,z8,z9,z10,z11,z12,z13,z14,z15}, {w0,w1,w2,w3}, ds0, pf, 1, 1, 0;\n"
        "wgmma.mma_async.sync.aligned.m64n64k16.f16.f16.f16 {z0,z1,z2,z3,z4,z5,z6,z7,z8,z9,z10,z11,z12,z13,z14,z15}, {w4,w5,w6,w7}, ds1, pt, 1, 1, 0;\n"
        "wgmma.mma_async.sync.aligned.m64n64k16.f16.f16.f16 {z0,z1,z2,z3,z4,z5,z6,z7,z8,z9,z10,z11,z12,z13,z14,z15}, {w8,w9,w10,w11}, ds2, pt, 1, 1, 0;\n"
        "mov.b32 {xl, xh}, a2; tanh.approx.f16 xr, xh; cvt.u32.u16 hi0, xr; mul.rn.f16x2 a3, z19, p; fma.rn.f16x2 p, z20, z20, c; fma.rn.f16x2 q1, g, g, q1; fma.rn.f16x2 g, z16, t, z16; prmt.b32 t, lo1, hi1, 0x5410; tanh.approx.f16 xr, xl; cvt.u32.u16 lo0, xr;\n"
        "B19:\n"
        "mov.b32 {xl, xh}, a3; tanh.approx.f16 xr, xh; cvt.u32.u16 hi1, xr; mul.rn.f16x2 a0, z20, p; fma.rn.f16x2 p, z21, z21, c; fma.rn.f16x2 q2, g, g, q2; fma.rn.f16x2 g, z17, t, z17; prmt.b32 t, lo0, hi0, 0x5410; tanh.approx.f16 xr, xl; cvt.u32.u16 lo1, xr;\n"
        "B20:\n"
        "mov.b32 {xl, xh}, a0; tanh.approx.f16 xr, xh; cvt.u32.u16 hi0, xr; mul.rn.f16x2 a1, z21, p; fma.rn.f16x2 p, z22, z22, c; fma.rn.f16x2 q3, g, g, q3; fma.rn.f16x2 g, z18, t, z18; prmt.b32 t, lo1, hi1, 0x5410; tanh.approx.f16 xr, xl; cvt.u32.u16 lo0, xr;\n"
        "B21:\n"
        "wgmma.fence.sync.aligned;\n"
        "wgmma.mma_async.sync.aligned.m64n64k16.f16.f16.f16 {z0,z1,z2,z3,z4,z5,z6,z7,z8,z9,z10,z11,z12,z13,z14,z15}, {w12,w13,w14,w15}, ds3, pt, 1, 1, 0;\n"
        "wgmma.mma_async.sync.aligned.m64n64k16.f16.f16.f16 {z0,z1,z2,z3,z4,z5,z6,z7,z8,z9,z10,z11,z12,z13,z14,z15}, {w16,w17,w18,w19}, ds4, pt, 1, 1, 0;\n"
        "wgmma.mma_async.sync.aligned.m64n64k16.f16.f16.f16 {z0,z1,z2,z3,z4,z5,z6,z7,z8,z9,z10,z11,z12,z13,z14,z15}, {w20,w21,w22,w23}, ds5, pt, 1, 1, 0;\n"
        "wgmma.commit_group.sync.aligned;\n"
        "mov.b32 {xl, xh}, a1; tanh.approx.f16 xr, xh; cvt.u32.u16 hi1, xr; mul.rn.f16x2 a2, z22, p; fma.rn.f16x2 p, z23, z23, c; fma.rn.f16x2 q2, g, g, q2; fma.rn.f16x2 g, z19, t, z19; prmt.b32 t, lo0, hi0, 0x5410; tanh.approx.f16 xr, xl; cvt.u32.u16 lo1, xr;\n"
        "B22:\n"
        "mov.b32 {xl, xh}, a2; tanh.approx.f16 xr, xh; cvt.u32.u16 hi0, xr; mul.rn.f16x2 a3, z23, p; fma.rn.f16x2 p, z24, z24, c; fma.rn.f16x2 q3, g, g, q3; fma.rn.f16x2 g, z20, t, z20; prmt.b32 t, lo1, hi1, 0x5410; tanh.approx.f16 xr, xl; cvt.u32.u16 lo0, xr;\n"
        "B23:\n"
        "mov.b32 {xl, xh}, a3; tanh.approx.f16 xr, xh; cvt.u32.u16 hi1, xr; mul.rn.f16x2 a0, z24, p; fma.rn.f16x2 p, z25, z25, c; fma.rn.f16x2 q2, g, g, q2; fma.rn.f16x2 g, z21, t, z21; prmt.b32 t, lo0, hi0, 0x5410; tanh.approx.f16 xr, xl; cvt.u32.u16 lo1, xr;\n"
        "B24:\n"
        "mov.b32 {xl, xh}, a0; tanh.approx.f16 xr, xh; cvt.u32.u16 hi0, xr; mul.rn.f16x2 a1, z25, p; fma.rn.f16x2 p, z26, z26, c; fma.rn.f16x2 q3, g, g, q3; fma.rn.f16x2 g, z22, t, z22; prmt.b32 t, lo1, hi1, 0x5410; tanh.approx.f16 xr, xl; cvt.u32.u16 lo0, xr;\n"
        "B25:\n"
        "mov.b32 {xl, xh}, a1; tanh.approx.f16 xr, xh; cvt.u32.u16 hi1, xr; mul.rn.f16x2 a2, z26, p; fma.rn.f16x2 p, z27, z27, c; fma.rn.f16x2 q2, g, g, q2; fma.rn.f16x2 g, z23, t, z23; prmt.b32 t, lo0, hi0, 0x5410; tanh.approx.f16 xr, xl; cvt.u32.u16 lo1, xr;\n"
        "B26:\n"
        "mov.b32 {xl, xh}, a2; tanh.approx.f16 xr, xh; cvt.u32.u16 hi0, xr; mul.rn.f16x2 a3, z27, p; fma.rn.f16x2 p, z28, z28, c; fma.rn.f16x2 q3, g, g, q3; fma.rn.f16x2 g, z24, t, z24; prmt.b32 t, lo1, hi1, 0x5410; tanh.approx.f16 xr, xl; cvt.u32.u16 lo0, xr;\n"
        "B27:\n"
        "add.u32 n, n, 8; setp.lt.u32 pe, n, 256; setp.ne.and.u32 pe, so, %7, pe;\n"
        "mov.b32 {xl, xh}, a3; tanh.approx.f16 xr, xh; cvt.u32.u16 hi1, xr; mul.rn.f16x2 a0, z28, p; fma.rn.f16x2 p, z29, z29, c; fma.rn.f16x2 q2, g, g, q2; fma.rn.f16x2 g, z25, t, z25; prmt.b32 t, lo0, hi0, 0x5410; tanh.approx.f16 xr, xl; cvt.u32.u16 lo1, xr;\n"
        "B28:\n"
        "mov.b32 {xl, xh}, a0; tanh.approx.f16 xr, xh; cvt.u32.u16 hi0, xr; mul.rn.f16x2 a1, z29, p; fma.rn.f16x2 p, z30, z30, c; fma.rn.f16x2 q3, g, g, q3; fma.rn.f16x2 g, z26, t, z26; prmt.b32 t, lo1, hi1, 0x5410; tanh.approx.f16 xr, xl; cvt.u32.u16 lo0, xr;\n"
        "B29:\n"
        "mov.b32 {xl, xh}, a1; tanh.approx.f16 xr, xh; cvt.u32.u16 hi1, xr; mul.rn.f16x2 a2, z30, p; fma.rn.f16x2 p, z31, z31, c; fma.rn.f16x2 q2, g, g, q2; fma.rn.f16x2 g, z27, t, z27; prmt.b32 t, lo0, hi0, 0x5410; tanh.approx.f16 xr, xl; cvt.u32.u16 lo1, xr;\n"
        "@pe bra.uni TOP;\n"
        "setp.lt.u32 pe, n, 256;\n"
        "@pe bra.uni DUTY;\n"
        "bra.uni DONE;\n"
        "SPINW: mov.u32 cnt, 0;\n"
        "SPINWL:\n"
        "mov.u32 tt, 230880; mbarrier.try_wait.parity.shared::cta.b64 pw, [tt], 0;\n"
        "@pw bra.uni BACKW;\n"
        "add.u32 cnt, cnt, 1; setp.lt.u32 pw, cnt, 0x100000;\n"
        "@pw bra.uni SPINWL;\n"
        "trap;\n"
        "SPIN5: mov.u32 cnt, 0;\n"
        "SPIN5L:\n"
        "mbarrier.try_wait.parity.shared::cta.b64 pw, [n+231552], 0;\n"
        "@pw bra.uni BACK5;\n"
        "add.u32 cnt, cnt, 1; setp.lt.u32 pw, cnt, 0x100000;\n"
        "@pw bra.uni SPIN5L;\n"
        "trap;\n"
        "SPIN0: mov.u32 cnt, 0;\n"
        "SPIN0L:\n"
        "mbarrier.try_wait.parity.shared::cta.b64 pw, [n+231560], 0;\n"
        "@pw bra.uni BACK0;\n"
        "add.u32 cnt, cnt, 1; setp.lt.u32 pw, cnt, 0x100000;\n"
        "@pw bra.uni SPIN0L;\n"
        "trap;\n"
        "SPIN: mov.u32 cnt, 0;\n"
        "SPINL:\n"
        "mbarrier.try_wait.parity.shared::cta.b64 pw, [n+231568], 0;\n"
        "@pw bra.uni BACK;\n"
        "add.u32 cnt, cnt, 1; setp.lt.u32 pw, cnt, 0x100000;\n"
        "@pw bra.uni SPINL;\n"
        "trap;\n"
        "DUTY:\n"
        "setp.ge.s32 pr, n, %11;\n"
        "@pr bra.uni FLUSH;\n"
        "setp.ge.u32 pr, %13, 2;\n"
        "@pr bra.uni ROLE2;\n"
        "setp.ge.s32 pr, n, %12; selp.b64 src, %14, gp, pr; add.u32 tt, n, 231296;\n"
        "elect.sync _|pr, 0xffffffff;\n"
        "@pr mbarrier.arrive.expect_tx.shared::cta.b64 _, [tt], %10;\n"
        "@pr cp.async.bulk.shared::cluster.global.mbarrier::complete_tx::bytes [%9], [src], %10, [tt];\n"
        "bra.uni FLUSH;\n"
        "ROLE2:\n"
        "setp.eq.u32 pr, %13, 3;\n"
        "@pr bra.uni ROLE3;\n"
        "setp.ne.s32 pr, n, 248;\n"
        "@pr bra.uni PARK;\n"
        "cp.async.bulk.wait_group 0;\n"
        "sub.s64 src, gp, %16; mov.u32 tt, 230824; mov.u32 cnt, 187392;\n"
        "elect.sync _|pr, 0xffffffff;\n"
        "@pr mbarrier.arrive.expect_tx.shared::cta.b64 _, [tt], 12288;\n"
        "@pr cp.async.bulk.shared::cluster.global.mbarrier::complete_tx::bytes [cnt], [src], 12288, [tt];\n"
        "PARK:\n"
        "elect.sync _|pr, 0xffffffff;\n"
        "@pr cp.async.bulk.global.shared::cta.bulk_group [gp], [%9], 12288;\n"
        "@pr cp.async.bulk.commit_group;\n"
        "bra.uni FLUSH;\n"
        "ROLE3:\n"
        "setp.ne.s32 pr, n, 64;\n"
        "@pr bra.uni AHEAD;\n"
        "mov.u32 tt, 230872;\n"
        "elect.sync _|pr, 0xffffffff;\n"
        "@pr mbarrier.arrive.expect_tx.shared::cta.b64 _, [tt], 75264;\n"
        "mov.u32 cnt, 229248; @pr cp.async.bulk.shared::cluster.global.mbarrier::complete_tx::bytes [cnt], [%18], 768, [tt];\n"
        "mov.u32 cnt, 230016; @pr cp.async.bulk.shared::cluster.global.mbarrier::complete_tx::bytes [cnt], [%19], 768, [tt];\n"
        "mov.u32 cnt, 74752; @pr cp.async.bulk.tensor.2d.shared::cluster.global.mbarrier::complete_tx::bytes [cnt], [%17, {0, 0}], [tt];\n"
        "mov.u32 cnt, 87040; @pr cp.async.bulk.tensor.2d.shared::cluster.global.mbarrier::complete_tx::bytes [cnt], [%17, {0, 192}], [tt];\n"
        "mov.u32 cnt, 99328; @pr cp.async.bulk.tensor.2d.shared::cluster.global.mbarrier::complete_tx::bytes [cnt], [%17, {32, 0}], [tt];\n"
        "mov.u32 cnt, 111616; @pr cp.async.bulk.tensor.2d.shared::cluster.global.mbarrier::complete_tx::bytes [cnt], [%17, {32, 192}], [tt];\n"
        "mov.u32 cnt, 123904; @pr cp.async.bulk.tensor.2d.shared::cluster.global.mbarrier::complete_tx::bytes [cnt], [%17, {64, 0}], [tt];\n"
        "mov.u32 cnt, 136192; @pr cp.async.bulk.tensor.2d.shared::cluster.global.mbarrier::complete_tx::bytes [cnt], [%17, {64, 192}], [tt];\n"
        "AHEAD:\n"
        "elect.sync _|pr, 0xffffffff;\n"
        "@pr cp.async.bulk.prefetch.L2.global [gp], 12288;\n"
        "FLUSH:\n"
        "add.s64 gp, gp, %16;\n"
        "mov.b32 {xl, xh}, q0; cvt.f32.f16 f0, xl; cvt.f32.f16 f1, xh; add.f32 f0, f0, f1; add.f32 %0, %0, f0; mov.b32 q0, 0;\n"
        "mov.b32 {xl, xh}, q1; cvt.f32.f16 f0, xl; cvt.f32.f16 f1, xh; add.f32 f0, f0, f1; add.f32 %1, %1, f0; mov.b32 q1, 0;\n"
        "mov.b32 {xl, xh}, q2; cvt.f32.f16 f0, xl; cvt.f32.f16 f1, xh; add.f32 f0, f0, f1; add.f32 %2, %2, f0; mov.b32 q2, 0;\n"
        "mov.b32 {xl, xh}, q3; cvt.f32.f16 f0, xl; cvt.f32.f16 f1, xh; add.f32 f0, f0, f1; add.f32 %3, %3, f0; mov.b32 q3, 0;\n"
        "setp.ne.u32 pr, %5, 0;\n"
        "@pr bra.uni TOP;\n"
        "wgmma.wait_group.sync.aligned 0;\n"
        "wgmma.fence.sync.aligned;\n"
        "ld.volatile.shared.v2.b32 {lo0, hi0}, [so]; xor.b32 f0, f0, lo0;\n"
        "ld.volatile.shared.v2.b32 {lo1, hi1}, [so]; xor.b32 f0, f0, lo1;\n"
        "ld.volatile.shared.v2.b32 {q1, a0}, [so]; xor.b32 f0, f0, q1;\n"
        "ld.volatile.shared.v2.b32 {q2, a1}, [so]; xor.b32 f0, f0, q2;\n"
        "ld.volatile.shared.v2.b32 {q3, a2}, [so]; xor.b32 f0, f0, q3;\n"
        "ld.volatile.shared.v2.b32 {q0, a3}, [so]; xor.b32 f0, f0, q0;\n"
        "ld.volatile.shared.v2.b32 {t, g}, [so]; xor.b32 f0, f0, t;\n"
        "ld.volatile.shared.v2.b32 {p, f1}, [so]; xor.b32 f0, f0, p;\n"
        "add.f32 %0, %0, f0;\n"
        "setp.eq.u32 pr, n, 1000; @pr bra.uni B31;\n"
        "setp.eq.u32 pr, n, 1001; @pr bra.uni B0;\n"
        "setp.eq.u32 pr, n, 1002; @pr bra.uni B1;\n"
        "setp.eq.u32 pr, n, 1003; @pr bra.uni B2;\n"
        "setp.eq.u32 pr, n, 1004; @pr bra.uni B3;\n"
        "setp.eq.u32 pr, n, 1005; @pr bra.uni B4;\n"
        "setp.eq.u32 pr, n, 1006; @pr bra.uni B5;\n"
        "setp.eq.u32 pr, n, 1007; @pr bra.uni B6;\n"
        "setp.eq.u32 pr, n, 1008; @pr bra.uni B7;\n"
        "setp.eq.u32 pr, n, 1009; @pr bra.uni B8;\n"
        "setp.eq.u32 pr, n, 1010; @pr bra.uni B9;\n"
        "setp.eq.u32 pr, n, 1011; @pr bra.uni B10;\n"
        "setp.eq.u32 pr, n, 1012; @pr bra.uni B11;\n"
        "setp.eq.u32 pr, n, 1013; @pr bra.uni B12;\n"
        "setp.eq.u32 pr, n, 1014; @pr bra.uni B13;\n"
        "setp.eq.u32 pr, n, 1015; @pr bra.uni B14;\n"
        "setp.eq.u32 pr, n, 1016; @pr bra.uni B15;\n"
        "setp.eq.u32 pr, n, 1017; @pr bra.uni B16;\n"
        "setp.eq.u32 pr, n, 1018; @pr bra.uni B17;\n"
        "setp.eq.u32 pr, n, 1019; @pr bra.uni B18;\n"
        "setp.eq.u32 pr, n, 1020; @pr bra.uni B19;\n"
        "setp.eq.u32 pr, n, 1021; @pr bra.uni B20;\n"
        "setp.eq.u32 pr, n, 1022; @pr bra.uni B21;\n"
        "setp.eq.u32 pr, n, 1023; @pr bra.uni B22;\n"
        "setp.eq.u32 pr, n, 1024; @pr bra.uni B23;\n"
        "setp.eq.u32 pr, n, 1025; @pr bra.uni B24;\n"
        "setp.eq.u32 pr, n, 1026; @pr bra.uni B25;\n"
        "setp.eq.u32 pr, n, 1027; @pr bra.uni B26;\n"
        "setp.eq.u32 pr, n, 1028; @pr bra.uni B27;\n"
        "setp.eq.u32 pr, n, 1029; @pr bra.uni B28;\n"
        "setp.eq.u32 pr, n, 1030; @pr bra.uni B29;\n"
        "setp.eq.u32 pr, n, 1031; @pr bra.uni TOP;\n"
        "trap;\n"
        "DONE:\n"
        ASM_TRC("n")
        "mov.b32 {xl, xh}, a2; tanh.approx.f16 xr, xh; cvt.u32.u16 hi0, xr; mul.rn.f16x2 a3, z31, p; fma.rn.f16x2 q3, g, g, q3; fma.rn.f16x2 g, z28, t, z28; prmt.b32 t, lo1, hi1, 0x5410; tanh.approx.f16 xr, xl; cvt.u32.u16 lo0, xr;\n"
        "mov.b32 {xl, xh}, a3; tanh.approx.f16 xr, xh; cvt.u32.u16 hi1, xr; fma.rn.f16x2 q2, g, g, q2; fma.rn.f16x2 g, z29, t, z29; prmt.b32 t, lo0, hi0, 0x5410; tanh.approx.f16 xr, xl; cvt.u32.u16 lo1, xr;\n"
        "fma.rn.f16x2 q3, g, g, q3; fma.rn.f16x2 g, z30, t, z30; prmt.b32 t, lo1, hi1, 0x5410;\n"
        "fma.rn.f16x2 q2, g, g, q2; fma.rn.f16x2 g, z31, t, z31;\n"
        "fma.rn.f16x2 q3, g, g, q3;\n"
        "mov.b32 {xl, xh}, q0; cvt.f32.f16 f0, xl; cvt.f32.f16 f1, xh; add.f32 f0, f0, f1; add.f32 %0, %0, f0; mov.b32 q0, 0;\n"
        "mov.b32 {xl, xh}, q1; cvt.f32.f16 f0, xl; cvt.f32.f16 f1, xh; add.f32 f0, f0, f1; add.f32 %1, %1, f0; mov.b32 q1, 0;\n"
        "mov.b32 {xl, xh}, q2; cvt.f32.f16 f0, xl; cvt.f32.f16 f1, xh; add.f32 f0, f0, f1; add.f32 %2, %2, f0; mov.b32 q2, 0;\n"
        "mov.b32 {xl, xh}, q3; cvt.f32.f16 f0, xl; cvt.f32.f16 f1, xh; add.f32 f0, f0, f1; add.f32 %3, %3, f0; mov.b32 q3, 0;\n"
        "wgmma.wait_group.sync.aligned 0;\n"
        "}\n"
        : "=f"(acc[0][0]), "=f"(acc[0][1]), "=f"(acc[1][0]), "=f"(acc[1][1])
        : "r"(w1t), "r"(yd), "r"(wd), "r"(own_slot), "l"(d.g), "r"(d.s), "r"(d.bytes), "r"(8 * d.end), "r"(8 * d.zero), "r"(role),
          "l"(d.zeros), "r"(lane), "l"(d.step), "l"(&prm.w2_map), "l"(prm.gamma), "l"(prm.beta), "l"(prm.ydesc64[0]), "l"(prm.ydesc64[1])
        : "memory");
}

template <int M>
__device__ __forceinline__ void gemm1_t(uint32_t (&d)[16], const uint32_t* wa, uint32_t yd, uint32_t wd) {
    wg_fence();
    wgmma_n64_h_set<0>(d, wa, desc<1024, 1>(yd, 0));
#pragma unroll
    for (int kk = 1; kk < 5; kk++)
        wgmma_n64_h_acc<0>(d, wa + kk * 4, kk < 4 ? desc<1024, 1>(yd, kk * 32) : desc<512, 2>(yd, 8192 + (kk - 4) * 32));
    wgmma_n64_h_acc_ss(d, desc<1024, 1>(wd, M * 12288), desc<512, 2>(yd, 8192 + 32));
    wg_commit();
}

__device__ __forceinline__ void gelu_sumsq_f(const uint32_t (&d)[16], float (&acc)[2]) {
#pragma unroll
    for (int r = 0; r < 16; r++) {
        float lo, hi;
        h2_unpack(gelu2(d[r]), lo, hi);
        acc[r & 1] = fmaf(lo, lo, acc[r & 1]);
        acc[r & 1] = fmaf(hi, hi, acc[r & 1]);
    }
}
__device__ __forceinline__ void load_w1t(uint32_t (&wa)[2][24], int wg, int w, int lane) {
#pragma unroll
    for (int m = 0; m < 2; m++)
#pragma unroll
        for (int kk = 0; kk < 5; kk++) {
            const int q = lane >> 3, c = 16 * kk + 8 * (q >> 1) + (lane & 7), ck = 2 * w + (q & 1);
            ldsm4_t(wa[m] + kk * 4, sb + SM_W1 + (2 * wg + m) * 12288 + c * 128 + ((ck ^ (c & 7)) * 16));
        }
}
__device__ __forceinline__ unsigned long long* acc_word(const Params& prm, uint32_t epoch, uint32_t e) {
    return &prm.g->acc[epoch & 1][(e >> 2) * 32 + (e & 3)];
}
__device__ __forceinline__ void publish_fast(const Params& prm, const float (&acc)[2][2], uint32_t epoch, int wg, int w, int lane) {
    const bool m = lane & 2, h = lane & 1;
    const float a = (m ? acc[1][0] : acc[0][0]) + __shfl_xor_sync(0xffffffffu, m ? acc[0][0] : acc[1][0], 2);
    const float b = (m ? acc[1][1] : acc[0][1]) + __shfl_xor_sync(0xffffffffu, m ? acc[0][1] : acc[1][1], 2);
    const float v = (h ? b : a) + __shfl_xor_sync(0xffffffffu, h ? a : b, 1);
    const unsigned long long q = (__float2ull_rn(fminf(v, ACC_LIMIT) * 0x1p16f) << 8) + 1;
    asm volatile("red.relaxed.gpu.global.add.u64 [%0], %1;"
                 ::"l"(acc_word(prm, epoch, 128 * wg + 32 * (lane & 2) + 16 * w + (lane >> 2) + 8 * (lane & 1))), "l"(q) : "memory");
}
__device__ __forceinline__ void collect_fast(const unsigned long long* word, float (&ss)[3]) {
    unsigned long long v[3];
    asm volatile(
        "{\n.reg .pred p;\n.reg .u32 n, lo, hi;\n.reg .b64 w;\nmov.u32 n, 0;\n"
        "POLL:\nld.relaxed.gpu.global.u64 %0, [%3];\nld.relaxed.gpu.global.u64 %1, [%3+8192];\nld.relaxed.gpu.global.u64 %2, [%3+16384];\n"
        "and.b64 w, %0, %1;\nand.b64 w, w, %2;\nmov.b64 {lo, hi}, w;\nand.b32 lo, lo, 128;\n"
        "setp.ne.u32 p, lo, 0;\nvote.sync.all.pred p, p, 0xffffffff;\n@p bra.uni POLL_DONE;\n"
        "add.u32 n, n, 1;\nsetp.lt.u32 p, n, 0x400000;\n@p bra.uni POLL;\ntrap;\nPOLL_DONE:\n}\n"
        : "=&l"(v[0]), "=&l"(v[1]), "=&l"(v[2]) : "l"(word) : "memory");
    static_assert(NUM_CTAS == 128, "the count is complete when bit 7 is set");
#pragma unroll
    for (int k = 0; k < 3; k++) ss[k] = __ull2float_rn(v[k] >> 8) * 0x1p-16f;
}
__device__ __forceinline__ void publish_sums(const float (&acc)[2][2], float* sums, unsigned int* counter, int wg, int w, int lane) {
#pragma unroll
    for (int m = 0; m < 2; m++)
#pragma unroll
        for (int h = 0; h < 2; h++) {
            const float v = quad_sum(acc[m][h]);
            if ((lane & 3) == 0) atomicAdd(sums + 64 * (2 * wg + m) + 16 * w + (lane >> 2) + 8 * h, v);
        }
    named_sync(1, 384);
    if (fresh_tid() == 0) asm volatile("red.release.gpu.global.add.u32 [%0], 1;" ::"l"(counter) : "memory");
}
__device__ __forceinline__ void grid_wait(const unsigned int* counter, unsigned int target) {
    if (fresh_tid() == 0) {
        unsigned int v, spins = 0;
        do {
            asm volatile("ld.acquire.gpu.global.u32 %0, [%1];" : "=r"(v) : "l"(counter) : "memory");
            if (++spins > (1u << 22)) __trap();
        } while ((int)(v - target) < 0);
    }
    __syncthreads();
}

struct Pass2 {
    uint32_t wg;
    uint32_t off;
    int step;
    uint32_t xs;
    uint32_t a_offs, xs_offs, bias_addr;
    uint32_t w;
};

static_assert(BAR_Y2FULL == 0 && BAR_XSFULL == 4 && BAR_TURN == 11 && BAR_ROWS == 51 && BAR_STAT == 54 &&
              sb + SM_RED + RED_SCALE * 4 == 230792, "layout");
__device__ __forceinline__ bool pass2_tiles(const Pass2& c, const Params& prm, uint32_t round) {
    uint32_t retry;
    asm volatile(
        "{\n"
        ".reg .b32 qa<24>, qz<32>, o<24>, g<16>, p<2>, a<4>, lo<2>, hi<2>, h<2>, osc, v<8>, r<24>, t<2>;\n"
        ".reg .b32 n, off, c, tt, ad, cnt, ybar, xbar, tbar, tpar, id;\n"
        ".reg .b16 xl, xh, xr;\n"
        ".reg .f32 f0, f1;\n"
        ".reg .b64 w1d, w2d, dt, gp, pol;\n"
        ".reg .pred pt, pf, pr, pw, pl, pm, pz, pn;\n"
        "setp.ne.b32 pt, 1, 0; setp.ne.b32 pf, 0, 0; setp.eq.u32 pl, %10, 0; setp.eq.u32 pz, %1, 0;\n"
        "mov.b32 c, 0x40D940D9;\n"
        "mov.b64 w1d, {%1, 0x40000040}; mov.b64 w2d, {%2, 0x80000020};\n"
        "mad.lo.u32 ybar, %3, 8, 230800; mad.lo.u32 xbar, %3, 8, 230832; add.u32 id, %3, 2;\n"
        "mad.lo.u32 tbar, %3, 64, 230888; setp.eq.u32 pr, %3, 0; selp.u32 tpar, 1, 0, pr; mov.u32 tt, %laneid; setp.eq.u32 pn, tt, 0;\n"
        "mov.u32 n, -1; add.u32 off, %4, %9; mov.pred pm, pt; createpolicy.fractional.L2::evict_first.b64 pol, 1.0;\n"
        "mbarrier.try_wait.parity.shared::cta.b64 pw, [ybar], 0;\n"
        "@!pw bra.uni SPINY0;\n"
        "BACKY0:\n"
        "and.b32 t0, %6, 0xffff; shr.u32 t1, %6, 16;\n"
        "xor.b32 ad, t0, 0; add.u32 ad, ad, %5; ldmatrix.sync.aligned.m8n8.x4.shared.b16 {qa0,qa1,qa2,qa3}, [ad];\n"
        "xor.b32 ad, t0, 32; add.u32 ad, ad, %5; ldmatrix.sync.aligned.m8n8.x4.shared.b16 {qa4,qa5,qa6,qa7}, [ad];\n"
        "xor.b32 ad, t0, 64; add.u32 ad, ad, %5; ldmatrix.sync.aligned.m8n8.x4.shared.b16 {qa8,qa9,qa10,qa11}, [ad];\n"
        "xor.b32 ad, t0, 96; add.u32 ad, ad, %5; ldmatrix.sync.aligned.m8n8.x4.shared.b16 {qa12,qa13,qa14,qa15}, [ad];\n"
        "xor.b32 ad, t1, 0; add.u32 ad, ad, %5; ldmatrix.sync.aligned.m8n8.x4.shared.b16 {qa16,qa17,qa18,qa19}, [ad];\n"
        "xor.b32 ad, t1, 32; add.u32 ad, ad, %5; ldmatrix.sync.aligned.m8n8.x4.shared.b16 {qa20,qa21,qa22,qa23}, [ad];\n"
        "wgmma.fence.sync.aligned;\n"
        "add.s64 dt, w1d, 0; wgmma.mma_async.sync.aligned.m64n64k16.f16.f16.f16 {qz0,qz1,qz2,qz3,qz4,qz5,qz6,qz7,qz8,qz9,qz10,qz11,qz12,qz13,qz14,qz15}, {qa0,qa1,qa2,qa3}, dt, pf, 1, 1, 1;\n"
        "add.s64 dt, w1d, 128; wgmma.mma_async.sync.aligned.m64n64k16.f16.f16.f16 {qz0,qz1,qz2,qz3,qz4,qz5,qz6,qz7,qz8,qz9,qz10,qz11,qz12,qz13,qz14,qz15}, {qa4,qa5,qa6,qa7}, dt, pt, 1, 1, 1;\n"
        "add.s64 dt, w1d, 256; wgmma.mma_async.sync.aligned.m64n64k16.f16.f16.f16 {qz0,qz1,qz2,qz3,qz4,qz5,qz6,qz7,qz8,qz9,qz10,qz11,qz12,qz13,qz14,qz15}, {qa8,qa9,qa10,qa11}, dt, pt, 1, 1, 1;\n"
        "add.s64 dt, w1d, 384; wgmma.mma_async.sync.aligned.m64n64k16.f16.f16.f16 {qz0,qz1,qz2,qz3,qz4,qz5,qz6,qz7,qz8,qz9,qz10,qz11,qz12,qz13,qz14,qz15}, {qa12,qa13,qa14,qa15}, dt, pt, 1, 1, 1;\n"
        "add.s64 dt, w1d, 512; wgmma.mma_async.sync.aligned.m64n64k16.f16.f16.f16 {qz0,qz1,qz2,qz3,qz4,qz5,qz6,qz7,qz8,qz9,qz10,qz11,qz12,qz13,qz14,qz15}, {qa16,qa17,qa18,qa19}, dt, pt, 1, 1, 1;\n"
        "add.s64 dt, w1d, 640; wgmma.mma_async.sync.aligned.m64n64k16.f16.f16.f16 {qz0,qz1,qz2,qz3,qz4,qz5,qz6,qz7,qz8,qz9,qz10,qz11,qz12,qz13,qz14,qz15}, {qa20,qa21,qa22,qa23}, dt, pt, 1, 1, 1;\n"
        "wgmma.commit_group.sync.aligned;\n"
        "mov.b32 g0, 0; mov.b32 g1, 0; mov.b32 g2, 0; mov.b32 g3, 0; mov.b32 g4, 0; mov.b32 g5, 0; mov.b32 g6, 0; mov.b32 g7, 0; mov.b32 g8, 0; mov.b32 g9, 0; mov.b32 g10, 0; mov.b32 g11, 0; mov.b32 g12, 0; mov.b32 g13, 0; mov.b32 g14, 0; mov.b32 g15, 0; mov.b32 o0, 0; mov.b32 o1, 0; mov.b32 o2, 0; mov.b32 o3, 0; mov.b32 o4, 0; mov.b32 o5, 0; mov.b32 o6, 0; mov.b32 o7, 0; mov.b32 o8, 0; mov.b32 o9, 0; mov.b32 o10, 0; mov.b32 o11, 0; mov.b32 o12, 0; mov.b32 o13, 0; mov.b32 o14, 0; mov.b32 o15, 0; mov.b32 o16, 0; mov.b32 o17, 0; mov.b32 o18, 0; mov.b32 o19, 0; mov.b32 o20, 0; mov.b32 o21, 0; mov.b32 o22, 0; mov.b32 o23, 0;\n"
        "mov.b32 osc, 0;\n"
        "wgmma.wait_group.sync.aligned 0;\n"
        "fma.rn.f16x2 p0, qz0, qz0, c;\n"
        "mul.rn.f16x2 a0, qz0, p0; fma.rn.f16x2 p1, qz1, qz1, c;\n"
        "mov.b32 {xl, xh}, a0; tanh.approx.f16 xr, xl; cvt.u32.u16 lo0, xr; tanh.approx.f16 xr, xh; cvt.u32.u16 hi0, xr; mul.rn.f16x2 a1, qz1, p1; fma.rn.f16x2 p0, qz2, qz2, c;\n"
        "mov.b32 {xl, xh}, a1; tanh.approx.f16 xr, xl; cvt.u32.u16 lo1, xr; tanh.approx.f16 xr, xh; cvt.u32.u16 hi1, xr; mul.rn.f16x2 a2, qz2, p0; fma.rn.f16x2 p1, qz3, qz3, c; prmt.b32 h0, lo0, hi0, 0x5410;\n"
        "mov.b32 {xl, xh}, a2; tanh.approx.f16 xr, xl; cvt.u32.u16 lo0, xr; tanh.approx.f16 xr, xh; cvt.u32.u16 hi0, xr; mul.rn.f16x2 a3, qz3, p1; fma.rn.f16x2 p0, qz4, qz4, c; fma.rn.f16x2 g0, qz0, h0, qz0; prmt.b32 h1, lo1, hi1, 0x5410;\n"
        "mov.b32 {xl, xh}, a3; tanh.approx.f16 xr, xl; cvt.u32.u16 lo1, xr; tanh.approx.f16 xr, xh; cvt.u32.u16 hi1, xr; mul.rn.f16x2 a0, qz4, p0; fma.rn.f16x2 p1, qz5, qz5, c; fma.rn.f16x2 g1, qz1, h1, qz1; prmt.b32 h0, lo0, hi0, 0x5410;\n"
        "mov.b32 {xl, xh}, a0; tanh.approx.f16 xr, xl; cvt.u32.u16 lo0, xr; tanh.approx.f16 xr, xh; cvt.u32.u16 hi0, xr; mul.rn.f16x2 a1, qz5, p1; fma.rn.f16x2 p0, qz6, qz6, c; fma.rn.f16x2 g2, qz2, h0, qz2; prmt.b32 h1, lo1, hi1, 0x5410;\n"
        "mov.b32 {xl, xh}, a1; tanh.approx.f16 xr, xl; cvt.u32.u16 lo1, xr; tanh.approx.f16 xr, xh; cvt.u32.u16 hi1, xr; mul.rn.f16x2 a2, qz6, p0; fma.rn.f16x2 p1, qz7, qz7, c; fma.rn.f16x2 g3, qz3, h1, qz3; prmt.b32 h0, lo0, hi0, 0x5410;\n"
        "LOOP:\n"
        "wgmma.fence.sync.aligned;\n"
        "add.s64 dt, w1d, 768; wgmma.mma_async.sync.aligned.m64n64k16.f16.f16.f16 {qz16,qz17,qz18,qz19,qz20,qz21,qz22,qz23,qz24,qz25,qz26,qz27,qz28,qz29,qz30,qz31}, {qa0,qa1,qa2,qa3}, dt, pf, 1, 1, 1;\n"
        "add.s64 dt, w1d, 896; wgmma.mma_async.sync.aligned.m64n64k16.f16.f16.f16 {qz16,qz17,qz18,qz19,qz20,qz21,qz22,qz23,qz24,qz25,qz26,qz27,qz28,qz29,qz30,qz31}, {qa4,qa5,qa6,qa7}, dt, pt, 1, 1, 1;\n"
        "add.s64 dt, w1d, 1024; wgmma.mma_async.sync.aligned.m64n64k16.f16.f16.f16 {qz16,qz17,qz18,qz19,qz20,qz21,qz22,qz23,qz24,qz25,qz26,qz27,qz28,qz29,qz30,qz31}, {qa8,qa9,qa10,qa11}, dt, pt, 1, 1, 1;\n"
        "add.s64 dt, w1d, 1152; wgmma.mma_async.sync.aligned.m64n64k16.f16.f16.f16 {qz16,qz17,qz18,qz19,qz20,qz21,qz22,qz23,qz24,qz25,qz26,qz27,qz28,qz29,qz30,qz31}, {qa12,qa13,qa14,qa15}, dt, pt, 1, 1, 1;\n"
        "add.s64 dt, w1d, 1280; wgmma.mma_async.sync.aligned.m64n64k16.f16.f16.f16 {qz16,qz17,qz18,qz19,qz20,qz21,qz22,qz23,qz24,qz25,qz26,qz27,qz28,qz29,qz30,qz31}, {qa16,qa17,qa18,qa19}, dt, pt, 1, 1, 1;\n"
        "add.s64 dt, w1d, 1408; wgmma.mma_async.sync.aligned.m64n64k16.f16.f16.f16 {qz16,qz17,qz18,qz19,qz20,qz21,qz22,qz23,qz24,qz25,qz26,qz27,qz28,qz29,qz30,qz31}, {qa20,qa21,qa22,qa23}, dt, pt, 1, 1, 1;\n"
        "setp.lt.s32 pr, n, 0;\n"
        "@pr bra.uni FIRST;\n"
        "and.b32 tt, n, 1; mbarrier.try_wait.parity.shared::cta.b64 pw, [xbar], tt;\n"
        "@!pw bra.uni SPINX;\n"
        "BACKX:\n"
        "and.b32 ad, %7, 0xffff; add.u32 ad, ad, %5; ld.shared.v4.b32 {v0,v1,v2,v3}, [ad+0];\n"
        "shr.u32 ad, %7, 16; add.u32 ad, ad, %5; ld.shared.v4.b32 {v4,v5,v6,v7}, [ad+0];\n"
        "mov.b32 {xl, xh}, o0; cvt.f32.f16 f0, xl; cvt.f32.f16 f1, xh; cvt.rn.bf16x2.f32 tt, f1, f0; fma.rn.bf16x2 v0, tt, osc, v0;\n"
        "mov.b32 {xl, xh}, o2; cvt.f32.f16 f0, xl; cvt.f32.f16 f1, xh; cvt.rn.bf16x2.f32 tt, f1, f0; fma.rn.bf16x2 v1, tt, osc, v1;\n"
        "mov.b32 {xl, xh}, o4; cvt.f32.f16 f0, xl; cvt.f32.f16 f1, xh; cvt.rn.bf16x2.f32 tt, f1, f0; fma.rn.bf16x2 v2, tt, osc, v2;\n"
        "mov.b32 {xl, xh}, o6; cvt.f32.f16 f0, xl; cvt.f32.f16 f1, xh; cvt.rn.bf16x2.f32 tt, f1, f0; fma.rn.bf16x2 v3, tt, osc, v3;\n"
        "and.b32 ad, %7, 0xffff; add.u32 ad, ad, %5; st.shared.v4.b32 [ad+0], {v0,v1,v2,v3};\n"
        "and.b32 ad, %7, 0xffff; add.u32 ad, ad, %5; ld.shared.v4.b32 {v0,v1,v2,v3}, [ad+64];\n"
        "mov.b32 {xl, xh}, o1; cvt.f32.f16 f0, xl; cvt.f32.f16 f1, xh; cvt.rn.bf16x2.f32 tt, f1, f0; fma.rn.bf16x2 v4, tt, osc, v4;\n"
        "mov.b32 {xl, xh}, o3; cvt.f32.f16 f0, xl; cvt.f32.f16 f1, xh; cvt.rn.bf16x2.f32 tt, f1, f0; fma.rn.bf16x2 v5, tt, osc, v5;\n"
        "mov.b32 {xl, xh}, o5; cvt.f32.f16 f0, xl; cvt.f32.f16 f1, xh; cvt.rn.bf16x2.f32 tt, f1, f0; fma.rn.bf16x2 v6, tt, osc, v6;\n"
        "mov.b32 {xl, xh}, o7; cvt.f32.f16 f0, xl; cvt.f32.f16 f1, xh; cvt.rn.bf16x2.f32 tt, f1, f0; fma.rn.bf16x2 v7, tt, osc, v7;\n"
        "shr.u32 ad, %7, 16; add.u32 ad, ad, %5; st.shared.v4.b32 [ad+0], {v4,v5,v6,v7};\n"
        "shr.u32 ad, %7, 16; add.u32 ad, ad, %5; ld.shared.v4.b32 {v4,v5,v6,v7}, [ad+64];\n"
        "ld.shared.v4.b32 {o0,o1,o2,o3}, [%8+0];\n"
        "ld.shared.v4.b32 {o4,o5,o6,o7}, [%8+64];\n"
        "mov.b32 {xl, xh}, o8; cvt.f32.f16 f0, xl; cvt.f32.f16 f1, xh; cvt.rn.bf16x2.f32 tt, f1, f0; fma.rn.bf16x2 v0, tt, osc, v0;\n"
        "mov.b32 {xl, xh}, o10; cvt.f32.f16 f0, xl; cvt.f32.f16 f1, xh; cvt.rn.bf16x2.f32 tt, f1, f0; fma.rn.bf16x2 v1, tt, osc, v1;\n"
        "mov.b32 {xl, xh}, o12; cvt.f32.f16 f0, xl; cvt.f32.f16 f1, xh; cvt.rn.bf16x2.f32 tt, f1, f0; fma.rn.bf16x2 v2, tt, osc, v2;\n"
        "mov.b32 {xl, xh}, o14; cvt.f32.f16 f0, xl; cvt.f32.f16 f1, xh; cvt.rn.bf16x2.f32 tt, f1, f0; fma.rn.bf16x2 v3, tt, osc, v3;\n"
        "and.b32 ad, %7, 0xffff; add.u32 ad, ad, %5; st.shared.v4.b32 [ad+64], {v0,v1,v2,v3};\n"
        "and.b32 ad, %7, 0xffff; add.u32 ad, ad, %5; ld.shared.v4.b32 {v0,v1,v2,v3}, [ad+128];\n"
        "mov.b32 {xl, xh}, o9; cvt.f32.f16 f0, xl; cvt.f32.f16 f1, xh; cvt.rn.bf16x2.f32 tt, f1, f0; fma.rn.bf16x2 v4, tt, osc, v4;\n"
        "mov.b32 {xl, xh}, o11; cvt.f32.f16 f0, xl; cvt.f32.f16 f1, xh; cvt.rn.bf16x2.f32 tt, f1, f0; fma.rn.bf16x2 v5, tt, osc, v5;\n"
        "mov.b32 {xl, xh}, o13; cvt.f32.f16 f0, xl; cvt.f32.f16 f1, xh; cvt.rn.bf16x2.f32 tt, f1, f0; fma.rn.bf16x2 v6, tt, osc, v6;\n"
        "mov.b32 {xl, xh}, o15; cvt.f32.f16 f0, xl; cvt.f32.f16 f1, xh; cvt.rn.bf16x2.f32 tt, f1, f0; fma.rn.bf16x2 v7, tt, osc, v7;\n"
        "shr.u32 ad, %7, 16; add.u32 ad, ad, %5; st.shared.v4.b32 [ad+64], {v4,v5,v6,v7};\n"
        "shr.u32 ad, %7, 16; add.u32 ad, ad, %5; ld.shared.v4.b32 {v4,v5,v6,v7}, [ad+128];\n"
        "ld.shared.v4.b32 {o8,o9,o10,o11}, [%8+128];\n"
        "ld.shared.v4.b32 {o12,o13,o14,o15}, [%8+192];\n"
        "mov.b32 {xl, xh}, o16; cvt.f32.f16 f0, xl; cvt.f32.f16 f1, xh; cvt.rn.bf16x2.f32 tt, f1, f0; fma.rn.bf16x2 v0, tt, osc, v0;\n"
        "mov.b32 {xl, xh}, o18; cvt.f32.f16 f0, xl; cvt.f32.f16 f1, xh; cvt.rn.bf16x2.f32 tt, f1, f0; fma.rn.bf16x2 v1, tt, osc, v1;\n"
        "mov.b32 {xl, xh}, o20; cvt.f32.f16 f0, xl; cvt.f32.f16 f1, xh; cvt.rn.bf16x2.f32 tt, f1, f0; fma.rn.bf16x2 v2, tt, osc, v2;\n"
        "mov.b32 {xl, xh}, o22; cvt.f32.f16 f0, xl; cvt.f32.f16 f1, xh; cvt.rn.bf16x2.f32 tt, f1, f0; fma.rn.bf16x2 v3, tt, osc, v3;\n"
        "and.b32 ad, %7, 0xffff; add.u32 ad, ad, %5; st.shared.v4.b32 [ad+128], {v0,v1,v2,v3};\n"
        "mov.b32 {xl, xh}, o17; cvt.f32.f16 f0, xl; cvt.f32.f16 f1, xh; cvt.rn.bf16x2.f32 tt, f1, f0; fma.rn.bf16x2 v4, tt, osc, v4;\n"
        "mov.b32 {xl, xh}, o19; cvt.f32.f16 f0, xl; cvt.f32.f16 f1, xh; cvt.rn.bf16x2.f32 tt, f1, f0; fma.rn.bf16x2 v5, tt, osc, v5;\n"
        "mov.b32 {xl, xh}, o21; cvt.f32.f16 f0, xl; cvt.f32.f16 f1, xh; cvt.rn.bf16x2.f32 tt, f1, f0; fma.rn.bf16x2 v6, tt, osc, v6;\n"
        "mov.b32 {xl, xh}, o23; cvt.f32.f16 f0, xl; cvt.f32.f16 f1, xh; cvt.rn.bf16x2.f32 tt, f1, f0; fma.rn.bf16x2 v7, tt, osc, v7;\n"
        "shr.u32 ad, %7, 16; add.u32 ad, ad, %5; st.shared.v4.b32 [ad+128], {v4,v5,v6,v7};\n"
        "ld.shared.v4.b32 {o16,o17,o18,o19}, [%8+256];\n"
        "ld.shared.v4.b32 {o20,o21,o22,o23}, [%8+320];\n"
        "FIRST:\n"
        "@pz bra.uni B7;\n"
        "mov.b32 {xl, xh}, a2; tanh.approx.f16 xr, xl; cvt.u32.u16 lo0, xr; tanh.approx.f16 xr, xh; cvt.u32.u16 hi0, xr; mul.rn.f16x2 a3, qz7, p1; fma.rn.f16x2 p0, qz8, qz8, c; fma.rn.f16x2 g4, qz4, h0, qz4; prmt.b32 h1, lo1, hi1, 0x5410;\n"
        "B7:\n"
        "fence.proxy.async.shared::cta;\n"
        "add.u32 tt, id, 4;\n"
        "@pl bra.uni STORE;\n"
        "bar.arrive tt, 128;\n"
        "STOREB:\n"
        ASM_MARK
        "add.s32 n, n, 1; sub.u32 off, off, %9; setp.lt.s32 pm, n, 7;\n"
        "@pz bra.uni B10;\n"
        "mov.b32 {xl, xh}, a3; tanh.approx.f16 xr, xl; cvt.u32.u16 lo1, xr; tanh.approx.f16 xr, xh; cvt.u32.u16 hi1, xr; mul.rn.f16x2 a0, qz8, p0; fma.rn.f16x2 p1, qz9, qz9, c; fma.rn.f16x2 g5, qz5, h1, qz5; prmt.b32 h0, lo0, hi0, 0x5410;\n"
        "mov.b32 {xl, xh}, a0; tanh.approx.f16 xr, xl; cvt.u32.u16 lo0, xr; tanh.approx.f16 xr, xh; cvt.u32.u16 hi0, xr; mul.rn.f16x2 a1, qz9, p1; fma.rn.f16x2 p0, qz10, qz10, c; fma.rn.f16x2 g6, qz6, h0, qz6; prmt.b32 h1, lo1, hi1, 0x5410;\n"
        "mov.b32 {xl, xh}, a1; tanh.approx.f16 xr, xl; cvt.u32.u16 lo1, xr; tanh.approx.f16 xr, xh; cvt.u32.u16 hi1, xr; mul.rn.f16x2 a2, qz10, p0; fma.rn.f16x2 p1, qz11, qz11, c; fma.rn.f16x2 g7, qz7, h1, qz7; prmt.b32 h0, lo0, hi0, 0x5410;\n"
        "B10:\n"
        "setp.eq.s32 pr, n, 0;\n"
        "@pr bra.uni SPINR;\n"
        "BACKW0:\n"
        "wgmma.fence.sync.aligned;\n"
        "add.s64 dt, w2d, 0; wgmma.mma_async.sync.aligned.m64n96k16.f16.f16.f16 {o0,o1,o2,o3,o4,o5,o6,o7,o8,o9,o10,o11,o12,o13,o14,o15,o16,o17,o18,o19,o20,o21,o22,o23}, {g0,g1,g2,g3}, dt, pt, 1, 1, 1;\n"
        "add.s64 dt, w2d, 64; wgmma.mma_async.sync.aligned.m64n96k16.f16.f16.f16 {o0,o1,o2,o3,o4,o5,o6,o7,o8,o9,o10,o11,o12,o13,o14,o15,o16,o17,o18,o19,o20,o21,o22,o23}, {g4,g5,g6,g7}, dt, pt, 1, 1, 1;\n"
        "wgmma.commit_group.sync.aligned;\n"
        "@pz bra.uni B14;\n"
        "mov.b32 {xl, xh}, a2; tanh.approx.f16 xr, xl; cvt.u32.u16 lo0, xr; tanh.approx.f16 xr, xh; cvt.u32.u16 hi0, xr; mul.rn.f16x2 a3, qz11, p1; fma.rn.f16x2 p0, qz12, qz12, c; fma.rn.f16x2 g8, qz8, h0, qz8; prmt.b32 h1, lo1, hi1, 0x5410;\n"
        "mov.b32 {xl, xh}, a3; tanh.approx.f16 xr, xl; cvt.u32.u16 lo1, xr; tanh.approx.f16 xr, xh; cvt.u32.u16 hi1, xr; mul.rn.f16x2 a0, qz12, p0; fma.rn.f16x2 p1, qz13, qz13, c; fma.rn.f16x2 g9, qz9, h1, qz9; prmt.b32 h0, lo0, hi0, 0x5410;\n"
        "mov.b32 {xl, xh}, a0; tanh.approx.f16 xr, xl; cvt.u32.u16 lo0, xr; tanh.approx.f16 xr, xh; cvt.u32.u16 hi0, xr; mul.rn.f16x2 a1, qz13, p1; fma.rn.f16x2 p0, qz14, qz14, c; fma.rn.f16x2 g10, qz10, h0, qz10; prmt.b32 h1, lo1, hi1, 0x5410;\n"
        "mov.b32 {xl, xh}, a1; tanh.approx.f16 xr, xl; cvt.u32.u16 lo1, xr; tanh.approx.f16 xr, xh; cvt.u32.u16 hi1, xr; mul.rn.f16x2 a2, qz14, p0; fma.rn.f16x2 p1, qz15, qz15, c; fma.rn.f16x2 g11, qz11, h1, qz11; prmt.b32 h0, lo0, hi0, 0x5410;\n"
        "B14:\n"
        "wgmma.wait_group.sync.aligned 0;\n"
        "mad.lo.u32 tt, n, 8, tbar; mbarrier.try_wait.parity.shared::cta.b64 pw, [tt], tpar;\n"
        "@!pw bra.uni SPINT;\n"
        "BACKT:\n"
        "wgmma.fence.sync.aligned;\n"
        "add.s64 dt, w2d, 128; wgmma.mma_async.sync.aligned.m64n96k16.f16.f16.f16 {o0,o1,o2,o3,o4,o5,o6,o7,o8,o9,o10,o11,o12,o13,o14,o15,o16,o17,o18,o19,o20,o21,o22,o23}, {g8,g9,g10,g11}, dt, pt, 1, 1, 1;\n"
        "wgmma.commit_group.sync.aligned;\n"
        "@pz bra.uni B18;\n"
        "mov.b32 {xl, xh}, a2; tanh.approx.f16 xr, xl; cvt.u32.u16 lo0, xr; tanh.approx.f16 xr, xh; cvt.u32.u16 hi0, xr; mul.rn.f16x2 a3, qz15, p1; fma.rn.f16x2 p0, qz16, qz16, c; fma.rn.f16x2 g12, qz12, h0, qz12; prmt.b32 h1, lo1, hi1, 0x5410;\n"
        "mov.b32 {xl, xh}, a3; tanh.approx.f16 xr, xl; cvt.u32.u16 lo1, xr; tanh.approx.f16 xr, xh; cvt.u32.u16 hi1, xr; mul.rn.f16x2 a0, qz16, p0; fma.rn.f16x2 p1, qz17, qz17, c; fma.rn.f16x2 g13, qz13, h1, qz13; prmt.b32 h0, lo0, hi0, 0x5410;\n"
        "mov.b32 {xl, xh}, a0; tanh.approx.f16 xr, xl; cvt.u32.u16 lo0, xr; tanh.approx.f16 xr, xh; cvt.u32.u16 hi0, xr; mul.rn.f16x2 a1, qz17, p1; fma.rn.f16x2 p0, qz18, qz18, c; fma.rn.f16x2 g14, qz14, h0, qz14; prmt.b32 h1, lo1, hi1, 0x5410;\n"
        "mov.b32 {xl, xh}, a1; tanh.approx.f16 xr, xl; cvt.u32.u16 lo1, xr; tanh.approx.f16 xr, xh; cvt.u32.u16 hi1, xr; mul.rn.f16x2 a2, qz18, p0; fma.rn.f16x2 p1, qz19, qz19, c; fma.rn.f16x2 g15, qz15, h1, qz15; prmt.b32 h0, lo0, hi0, 0x5410;\n"
        "B18:\n"
        "wgmma.fence.sync.aligned;\n"
        "add.s64 dt, w2d, 192; wgmma.mma_async.sync.aligned.m64n96k16.f16.f16.f16 {o0,o1,o2,o3,o4,o5,o6,o7,o8,o9,o10,o11,o12,o13,o14,o15,o16,o17,o18,o19,o20,o21,o22,o23}, {g12,g13,g14,g15}, dt, pt, 1, 1, 1;\n"
        "add.s64 dt, w1d, 1536; wgmma.mma_async.sync.aligned.m64n64k16.f16.f16.f16 {qz0,qz1,qz2,qz3,qz4,qz5,qz6,qz7,qz8,qz9,qz10,qz11,qz12,qz13,qz14,qz15}, {qa0,qa1,qa2,qa3}, dt, pf, 1, 1, 1;\n"
        "add.s64 dt, w1d, 1664; wgmma.mma_async.sync.aligned.m64n64k16.f16.f16.f16 {qz0,qz1,qz2,qz3,qz4,qz5,qz6,qz7,qz8,qz9,qz10,qz11,qz12,qz13,qz14,qz15}, {qa4,qa5,qa6,qa7}, dt, pt, 1, 1, 1;\n"
        "add.s64 dt, w1d, 1792; wgmma.mma_async.sync.aligned.m64n64k16.f16.f16.f16 {qz0,qz1,qz2,qz3,qz4,qz5,qz6,qz7,qz8,qz9,qz10,qz11,qz12,qz13,qz14,qz15}, {qa8,qa9,qa10,qa11}, dt, pt, 1, 1, 1;\n"
        "wgmma.commit_group.sync.aligned;\n"
        "@pl bra.uni YLOAD;\n"
        "YLOADB:\n"
        "@pz bra.uni B22;\n"
        "mov.b32 {xl, xh}, a2; tanh.approx.f16 xr, xl; cvt.u32.u16 lo0, xr; tanh.approx.f16 xr, xh; cvt.u32.u16 hi0, xr; mul.rn.f16x2 a3, qz19, p1; fma.rn.f16x2 p0, qz20, qz20, c; fma.rn.f16x2 g0, qz16, h0, qz16; prmt.b32 h1, lo1, hi1, 0x5410;\n"
        "mov.b32 {xl, xh}, a3; tanh.approx.f16 xr, xl; cvt.u32.u16 lo1, xr; tanh.approx.f16 xr, xh; cvt.u32.u16 hi1, xr; mul.rn.f16x2 a0, qz20, p0; fma.rn.f16x2 p1, qz21, qz21, c; fma.rn.f16x2 g1, qz17, h1, qz17; prmt.b32 h0, lo0, hi0, 0x5410;\n"
        "mov.b32 {xl, xh}, a0; tanh.approx.f16 xr, xl; cvt.u32.u16 lo0, xr; tanh.approx.f16 xr, xh; cvt.u32.u16 hi0, xr; mul.rn.f16x2 a1, qz21, p1; fma.rn.f16x2 p0, qz22, qz22, c; fma.rn.f16x2 g2, qz18, h0, qz18; prmt.b32 h1, lo1, hi1, 0x5410;\n"
        "mov.b32 {xl, xh}, a1; tanh.approx.f16 xr, xl; cvt.u32.u16 lo1, xr; tanh.approx.f16 xr, xh; cvt.u32.u16 hi1, xr; mul.rn.f16x2 a2, qz22, p0; fma.rn.f16x2 p1, qz23, qz23, c; fma.rn.f16x2 g3, qz19, h1, qz19; prmt.b32 h0, lo0, hi0, 0x5410;\n"
        "B22:\n"
        "wgmma.fence.sync.aligned;\n"
        "add.s64 dt, w1d, 1920; wgmma.mma_async.sync.aligned.m64n64k16.f16.f16.f16 {qz0,qz1,qz2,qz3,qz4,qz5,qz6,qz7,qz8,qz9,qz10,qz11,qz12,qz13,qz14,qz15}, {qa12,qa13,qa14,qa15}, dt, pt, 1, 1, 1;\n"
        "add.s64 dt, w1d, 2048; wgmma.mma_async.sync.aligned.m64n64k16.f16.f16.f16 {qz0,qz1,qz2,qz3,qz4,qz5,qz6,qz7,qz8,qz9,qz10,qz11,qz12,qz13,qz14,qz15}, {qa16,qa17,qa18,qa19}, dt, pt, 1, 1, 1;\n"
        "add.s64 dt, w1d, 2176; wgmma.mma_async.sync.aligned.m64n64k16.f16.f16.f16 {qz0,qz1,qz2,qz3,qz4,qz5,qz6,qz7,qz8,qz9,qz10,qz11,qz12,qz13,qz14,qz15}, {qa20,qa21,qa22,qa23}, dt, pt, 1, 1, 1;\n"
        "wgmma.commit_group.sync.aligned;\n"
        "@pz bra.uni B26;\n"
        "mov.b32 {xl, xh}, a2; tanh.approx.f16 xr, xl; cvt.u32.u16 lo0, xr; tanh.approx.f16 xr, xh; cvt.u32.u16 hi0, xr; mul.rn.f16x2 a3, qz23, p1; fma.rn.f16x2 p0, qz24, qz24, c; fma.rn.f16x2 g4, qz20, h0, qz20; prmt.b32 h1, lo1, hi1, 0x5410;\n"
        "mov.b32 {xl, xh}, a3; tanh.approx.f16 xr, xl; cvt.u32.u16 lo1, xr; tanh.approx.f16 xr, xh; cvt.u32.u16 hi1, xr; mul.rn.f16x2 a0, qz24, p0; fma.rn.f16x2 p1, qz25, qz25, c; fma.rn.f16x2 g5, qz21, h1, qz21; prmt.b32 h0, lo0, hi0, 0x5410;\n"
        "mov.b32 {xl, xh}, a0; tanh.approx.f16 xr, xl; cvt.u32.u16 lo0, xr; tanh.approx.f16 xr, xh; cvt.u32.u16 hi0, xr; mul.rn.f16x2 a1, qz25, p1; fma.rn.f16x2 p0, qz26, qz26, c; fma.rn.f16x2 g6, qz22, h0, qz22; prmt.b32 h1, lo1, hi1, 0x5410;\n"
        "mov.b32 {xl, xh}, a1; tanh.approx.f16 xr, xl; cvt.u32.u16 lo1, xr; tanh.approx.f16 xr, xh; cvt.u32.u16 hi1, xr; mul.rn.f16x2 a2, qz26, p0; fma.rn.f16x2 p1, qz27, qz27, c; fma.rn.f16x2 g7, qz23, h1, qz23; prmt.b32 h0, lo0, hi0, 0x5410;\n"
        "B26:\n"
        "wgmma.wait_group.sync.aligned 2;\n"
        "wgmma.fence.sync.aligned;\n"
        "add.s64 dt, w2d, 256; wgmma.mma_async.sync.aligned.m64n96k16.f16.f16.f16 {o0,o1,o2,o3,o4,o5,o6,o7,o8,o9,o10,o11,o12,o13,o14,o15,o16,o17,o18,o19,o20,o21,o22,o23}, {g0,g1,g2,g3}, dt, pt, 1, 1, 1;\n"
        "add.s64 dt, w2d, 320; wgmma.mma_async.sync.aligned.m64n96k16.f16.f16.f16 {o0,o1,o2,o3,o4,o5,o6,o7,o8,o9,o10,o11,o12,o13,o14,o15,o16,o17,o18,o19,o20,o21,o22,o23}, {g4,g5,g6,g7}, dt, pt, 1, 1, 1;\n"
        "wgmma.commit_group.sync.aligned;\n"
        "@pz bra.uni B30;\n"
        "mov.b32 {xl, xh}, a2; tanh.approx.f16 xr, xl; cvt.u32.u16 lo0, xr; tanh.approx.f16 xr, xh; cvt.u32.u16 hi0, xr; mul.rn.f16x2 a3, qz27, p1; fma.rn.f16x2 p0, qz28, qz28, c; fma.rn.f16x2 g8, qz24, h0, qz24; prmt.b32 h1, lo1, hi1, 0x5410;\n"
        "mov.b32 {xl, xh}, a3; tanh.approx.f16 xr, xl; cvt.u32.u16 lo1, xr; tanh.approx.f16 xr, xh; cvt.u32.u16 hi1, xr; mul.rn.f16x2 a0, qz28, p0; fma.rn.f16x2 p1, qz29, qz29, c; fma.rn.f16x2 g9, qz25, h1, qz25; prmt.b32 h0, lo0, hi0, 0x5410;\n"
        "mov.b32 {xl, xh}, a0; tanh.approx.f16 xr, xl; cvt.u32.u16 lo0, xr; tanh.approx.f16 xr, xh; cvt.u32.u16 hi0, xr; mul.rn.f16x2 a1, qz29, p1; fma.rn.f16x2 p0, qz30, qz30, c; fma.rn.f16x2 g10, qz26, h0, qz26; prmt.b32 h1, lo1, hi1, 0x5410;\n"
        "mov.b32 {xl, xh}, a1; tanh.approx.f16 xr, xl; cvt.u32.u16 lo1, xr; tanh.approx.f16 xr, xh; cvt.u32.u16 hi1, xr; mul.rn.f16x2 a2, qz30, p0; fma.rn.f16x2 p1, qz31, qz31, c; fma.rn.f16x2 g11, qz27, h1, qz27; prmt.b32 h0, lo0, hi0, 0x5410;\n"
        "B30:\n"
        "wgmma.wait_group.sync.aligned 1;\n"
        "wgmma.fence.sync.aligned;\n"
        "add.s64 dt, w2d, 384; wgmma.mma_async.sync.aligned.m64n96k16.f16.f16.f16 {o0,o1,o2,o3,o4,o5,o6,o7,o8,o9,o10,o11,o12,o13,o14,o15,o16,o17,o18,o19,o20,o21,o22,o23}, {g8,g9,g10,g11}, dt, pt, 1, 1, 1;\n"
        "wgmma.commit_group.sync.aligned;\n"
        "@pz bra.uni B34;\n"
        "mov.b32 {xl, xh}, a2; tanh.approx.f16 xr, xl; cvt.u32.u16 lo0, xr; tanh.approx.f16 xr, xh; cvt.u32.u16 hi0, xr; mul.rn.f16x2 a3, qz31, p1; fma.rn.f16x2 p0, qz0, qz0, c; fma.rn.f16x2 g12, qz28, h0, qz28; prmt.b32 h1, lo1, hi1, 0x5410;\n"
        "mov.b32 {xl, xh}, a3; tanh.approx.f16 xr, xl; cvt.u32.u16 lo1, xr; tanh.approx.f16 xr, xh; cvt.u32.u16 hi1, xr; mul.rn.f16x2 a0, qz0, p0; fma.rn.f16x2 p1, qz1, qz1, c; fma.rn.f16x2 g13, qz29, h1, qz29; prmt.b32 h0, lo0, hi0, 0x5410;\n"
        "mov.b32 {xl, xh}, a0; tanh.approx.f16 xr, xl; cvt.u32.u16 lo0, xr; tanh.approx.f16 xr, xh; cvt.u32.u16 hi0, xr; mul.rn.f16x2 a1, qz1, p1; fma.rn.f16x2 p0, qz2, qz2, c; fma.rn.f16x2 g14, qz30, h0, qz30; prmt.b32 h1, lo1, hi1, 0x5410;\n"
        "mov.b32 {xl, xh}, a1; tanh.approx.f16 xr, xl; cvt.u32.u16 lo1, xr; tanh.approx.f16 xr, xh; cvt.u32.u16 hi1, xr; mul.rn.f16x2 a2, qz2, p0; fma.rn.f16x2 p1, qz3, qz3, c; fma.rn.f16x2 g15, qz31, h1, qz31; prmt.b32 h0, lo0, hi0, 0x5410;\n"
        "B34:\n"
        "wgmma.wait_group.sync.aligned 1;\n"
        "wgmma.fence.sync.aligned;\n"
        "add.s64 dt, w2d, 448; wgmma.mma_async.sync.aligned.m64n96k16.f16.f16.f16 {o0,o1,o2,o3,o4,o5,o6,o7,o8,o9,o10,o11,o12,o13,o14,o15,o16,o17,o18,o19,o20,o21,o22,o23}, {g12,g13,g14,g15}, dt, pt, 1, 1, 1;\n"
        "add.s64 dt, w1d, 2304; wgmma.mma_async.sync.aligned.m64n64k16.f16.f16.f16 {qz16,qz17,qz18,qz19,qz20,qz21,qz22,qz23,qz24,qz25,qz26,qz27,qz28,qz29,qz30,qz31}, {qa0,qa1,qa2,qa3}, dt, pf, 1, 1, 1;\n"
        "add.s64 dt, w1d, 2432; wgmma.mma_async.sync.aligned.m64n64k16.f16.f16.f16 {qz16,qz17,qz18,qz19,qz20,qz21,qz22,qz23,qz24,qz25,qz26,qz27,qz28,qz29,qz30,qz31}, {qa4,qa5,qa6,qa7}, dt, pt, 1, 1, 1;\n"
        "add.s64 dt, w1d, 2560; wgmma.mma_async.sync.aligned.m64n64k16.f16.f16.f16 {qz16,qz17,qz18,qz19,qz20,qz21,qz22,qz23,qz24,qz25,qz26,qz27,qz28,qz29,qz30,qz31}, {qa8,qa9,qa10,qa11}, dt, pt, 1, 1, 1;\n"
        "wgmma.commit_group.sync.aligned;\n"
        "@pz bra.uni B38;\n"
        "mov.b32 {xl, xh}, a2; tanh.approx.f16 xr, xl; cvt.u32.u16 lo0, xr; tanh.approx.f16 xr, xh; cvt.u32.u16 hi0, xr; mul.rn.f16x2 a3, qz3, p1; fma.rn.f16x2 p0, qz4, qz4, c; fma.rn.f16x2 g0, qz0, h0, qz0; prmt.b32 h1, lo1, hi1, 0x5410;\n"
        "mov.b32 {xl, xh}, a3; tanh.approx.f16 xr, xl; cvt.u32.u16 lo1, xr; tanh.approx.f16 xr, xh; cvt.u32.u16 hi1, xr; mul.rn.f16x2 a0, qz4, p0; fma.rn.f16x2 p1, qz5, qz5, c; fma.rn.f16x2 g1, qz1, h1, qz1; prmt.b32 h0, lo0, hi0, 0x5410;\n"
        "mov.b32 {xl, xh}, a0; tanh.approx.f16 xr, xl; cvt.u32.u16 lo0, xr; tanh.approx.f16 xr, xh; cvt.u32.u16 hi0, xr; mul.rn.f16x2 a1, qz5, p1; fma.rn.f16x2 p0, qz6, qz6, c; fma.rn.f16x2 g2, qz2, h0, qz2; prmt.b32 h1, lo1, hi1, 0x5410;\n"
        "mov.b32 {xl, xh}, a1; tanh.approx.f16 xr, xl; cvt.u32.u16 lo1, xr; tanh.approx.f16 xr, xh; cvt.u32.u16 hi1, xr; mul.rn.f16x2 a2, qz6, p0; fma.rn.f16x2 p1, qz7, qz7, c; fma.rn.f16x2 g3, qz3, h1, qz3; prmt.b32 h0, lo0, hi0, 0x5410;\n"
        "B38:\n"
        "wgmma.fence.sync.aligned;\n"
        "add.s64 dt, w1d, 2688; wgmma.mma_async.sync.aligned.m64n64k16.f16.f16.f16 {qz16,qz17,qz18,qz19,qz20,qz21,qz22,qz23,qz24,qz25,qz26,qz27,qz28,qz29,qz30,qz31}, {qa12,qa13,qa14,qa15}, dt, pt, 1, 1, 1;\n"
        "add.s64 dt, w1d, 2816; wgmma.mma_async.sync.aligned.m64n64k16.f16.f16.f16 {qz16,qz17,qz18,qz19,qz20,qz21,qz22,qz23,qz24,qz25,qz26,qz27,qz28,qz29,qz30,qz31}, {qa16,qa17,qa18,qa19}, dt, pt, 1, 1, 1;\n"
        "add.s64 dt, w1d, 2944; wgmma.mma_async.sync.aligned.m64n64k16.f16.f16.f16 {qz16,qz17,qz18,qz19,qz20,qz21,qz22,qz23,qz24,qz25,qz26,qz27,qz28,qz29,qz30,qz31}, {qa20,qa21,qa22,qa23}, dt, pt, 1, 1, 1;\n"
        "wgmma.commit_group.sync.aligned;\n"
        "@pz bra.uni B42;\n"
        "mov.b32 {xl, xh}, a2; tanh.approx.f16 xr, xl; cvt.u32.u16 lo0, xr; tanh.approx.f16 xr, xh; cvt.u32.u16 hi0, xr; mul.rn.f16x2 a3, qz7, p1; fma.rn.f16x2 p0, qz8, qz8, c; fma.rn.f16x2 g4, qz4, h0, qz4; prmt.b32 h1, lo1, hi1, 0x5410;\n"
        "mov.b32 {xl, xh}, a3; tanh.approx.f16 xr, xl; cvt.u32.u16 lo1, xr; tanh.approx.f16 xr, xh; cvt.u32.u16 hi1, xr; mul.rn.f16x2 a0, qz8, p0; fma.rn.f16x2 p1, qz9, qz9, c; fma.rn.f16x2 g5, qz5, h1, qz5; prmt.b32 h0, lo0, hi0, 0x5410;\n"
        "mov.b32 {xl, xh}, a0; tanh.approx.f16 xr, xl; cvt.u32.u16 lo0, xr; tanh.approx.f16 xr, xh; cvt.u32.u16 hi0, xr; mul.rn.f16x2 a1, qz9, p1; fma.rn.f16x2 p0, qz10, qz10, c; fma.rn.f16x2 g6, qz6, h0, qz6; prmt.b32 h1, lo1, hi1, 0x5410;\n"
        "mov.b32 {xl, xh}, a1; tanh.approx.f16 xr, xl; cvt.u32.u16 lo1, xr; tanh.approx.f16 xr, xh; cvt.u32.u16 hi1, xr; mul.rn.f16x2 a2, qz10, p0; fma.rn.f16x2 p1, qz11, qz11, c; fma.rn.f16x2 g7, qz7, h1, qz7; prmt.b32 h0, lo0, hi0, 0x5410;\n"
        "B42:\n"
        "wgmma.wait_group.sync.aligned 2;\n"
        "setp.eq.s32 pr, n, 0;\n"
        "@pr bra.uni SPINW1;\n"
        "BACKW1:\n"
        "wgmma.fence.sync.aligned;\n"
        "add.s64 dt, w2d, 512; wgmma.mma_async.sync.aligned.m64n96k16.f16.f16.f16 {o0,o1,o2,o3,o4,o5,o6,o7,o8,o9,o10,o11,o12,o13,o14,o15,o16,o17,o18,o19,o20,o21,o22,o23}, {g0,g1,g2,g3}, dt, pt, 1, 1, 1;\n"
        "add.s64 dt, w2d, 576; wgmma.mma_async.sync.aligned.m64n96k16.f16.f16.f16 {o0,o1,o2,o3,o4,o5,o6,o7,o8,o9,o10,o11,o12,o13,o14,o15,o16,o17,o18,o19,o20,o21,o22,o23}, {g4,g5,g6,g7}, dt, pt, 1, 1, 1;\n"
        "wgmma.commit_group.sync.aligned;\n"
        "mad.lo.u32 tt, n, 8, tbar;\n"
        "@pn mbarrier.arrive.shared::cta.b64 _, [tt+64];\n"
        "@pz bra.uni B46;\n"
        "mov.b32 {xl, xh}, a2; tanh.approx.f16 xr, xl; cvt.u32.u16 lo0, xr; tanh.approx.f16 xr, xh; cvt.u32.u16 hi0, xr; mul.rn.f16x2 a3, qz11, p1; fma.rn.f16x2 p0, qz12, qz12, c; fma.rn.f16x2 g8, qz8, h0, qz8; prmt.b32 h1, lo1, hi1, 0x5410;\n"
        "mov.b32 {xl, xh}, a3; tanh.approx.f16 xr, xl; cvt.u32.u16 lo1, xr; tanh.approx.f16 xr, xh; cvt.u32.u16 hi1, xr; mul.rn.f16x2 a0, qz12, p0; fma.rn.f16x2 p1, qz13, qz13, c; fma.rn.f16x2 g9, qz9, h1, qz9; prmt.b32 h0, lo0, hi0, 0x5410;\n"
        "mov.b32 {xl, xh}, a0; tanh.approx.f16 xr, xl; cvt.u32.u16 lo0, xr; tanh.approx.f16 xr, xh; cvt.u32.u16 hi0, xr; mul.rn.f16x2 a1, qz13, p1; fma.rn.f16x2 p0, qz14, qz14, c; fma.rn.f16x2 g10, qz10, h0, qz10; prmt.b32 h1, lo1, hi1, 0x5410;\n"
        "mov.b32 {xl, xh}, a1; tanh.approx.f16 xr, xl; cvt.u32.u16 lo1, xr; tanh.approx.f16 xr, xh; cvt.u32.u16 hi1, xr; mul.rn.f16x2 a2, qz14, p0; fma.rn.f16x2 p1, qz15, qz15, c; fma.rn.f16x2 g11, qz11, h1, qz11; prmt.b32 h0, lo0, hi0, 0x5410;\n"
        "B46:\n"
        "wgmma.wait_group.sync.aligned 1;\n"
        "wgmma.fence.sync.aligned;\n"
        "add.s64 dt, w2d, 640; wgmma.mma_async.sync.aligned.m64n96k16.f16.f16.f16 {o0,o1,o2,o3,o4,o5,o6,o7,o8,o9,o10,o11,o12,o13,o14,o15,o16,o17,o18,o19,o20,o21,o22,o23}, {g8,g9,g10,g11}, dt, pt, 1, 1, 1;\n"
        "wgmma.commit_group.sync.aligned;\n"
        "@pz bra.uni B50;\n"
        "mov.b32 {xl, xh}, a2; tanh.approx.f16 xr, xl; cvt.u32.u16 lo0, xr; tanh.approx.f16 xr, xh; cvt.u32.u16 hi0, xr; mul.rn.f16x2 a3, qz15, p1; fma.rn.f16x2 p0, qz16, qz16, c; fma.rn.f16x2 g12, qz12, h0, qz12; prmt.b32 h1, lo1, hi1, 0x5410;\n"
        "mov.b32 {xl, xh}, a3; tanh.approx.f16 xr, xl; cvt.u32.u16 lo1, xr; tanh.approx.f16 xr, xh; cvt.u32.u16 hi1, xr; mul.rn.f16x2 a0, qz16, p0; fma.rn.f16x2 p1, qz17, qz17, c; fma.rn.f16x2 g13, qz13, h1, qz13; prmt.b32 h0, lo0, hi0, 0x5410;\n"
        "mov.b32 {xl, xh}, a0; tanh.approx.f16 xr, xl; cvt.u32.u16 lo0, xr; tanh.approx.f16 xr, xh; cvt.u32.u16 hi0, xr; mul.rn.f16x2 a1, qz17, p1; fma.rn.f16x2 p0, qz18, qz18, c; fma.rn.f16x2 g14, qz14, h0, qz14; prmt.b32 h1, lo1, hi1, 0x5410;\n"
        "mov.b32 {xl, xh}, a1; tanh.approx.f16 xr, xl; cvt.u32.u16 lo1, xr; tanh.approx.f16 xr, xh; cvt.u32.u16 hi1, xr; mul.rn.f16x2 a2, qz18, p0; fma.rn.f16x2 p1, qz19, qz19, c; fma.rn.f16x2 g15, qz15, h1, qz15; prmt.b32 h0, lo0, hi0, 0x5410;\n"
        "B50:\n"
        "wgmma.wait_group.sync.aligned 1;\n"
        "wgmma.fence.sync.aligned;\n"
        "add.s64 dt, w2d, 704; wgmma.mma_async.sync.aligned.m64n96k16.f16.f16.f16 {o0,o1,o2,o3,o4,o5,o6,o7,o8,o9,o10,o11,o12,o13,o14,o15,o16,o17,o18,o19,o20,o21,o22,o23}, {g12,g13,g14,g15}, dt, pt, 1, 1, 1;\n"
        "add.s64 dt, w1d, 3072; wgmma.mma_async.sync.aligned.m64n64k16.f16.f16.f16 {qz0,qz1,qz2,qz3,qz4,qz5,qz6,qz7,qz8,qz9,qz10,qz11,qz12,qz13,qz14,qz15}, {qa0,qa1,qa2,qa3}, dt, pf, 1, 1, 1;\n"
        "add.s64 dt, w1d, 3200; wgmma.mma_async.sync.aligned.m64n64k16.f16.f16.f16 {qz0,qz1,qz2,qz3,qz4,qz5,qz6,qz7,qz8,qz9,qz10,qz11,qz12,qz13,qz14,qz15}, {qa4,qa5,qa6,qa7}, dt, pt, 1, 1, 1;\n"
        "add.s64 dt, w1d, 3328; wgmma.mma_async.sync.aligned.m64n64k16.f16.f16.f16 {qz0,qz1,qz2,qz3,qz4,qz5,qz6,qz7,qz8,qz9,qz10,qz11,qz12,qz13,qz14,qz15}, {qa8,qa9,qa10,qa11}, dt, pt, 1, 1, 1;\n"
        "wgmma.commit_group.sync.aligned;\n"
        "@pz bra.uni B54;\n"
        "mov.b32 {xl, xh}, a2; tanh.approx.f16 xr, xl; cvt.u32.u16 lo0, xr; tanh.approx.f16 xr, xh; cvt.u32.u16 hi0, xr; mul.rn.f16x2 a3, qz19, p1; fma.rn.f16x2 p0, qz20, qz20, c; fma.rn.f16x2 g0, qz16, h0, qz16; prmt.b32 h1, lo1, hi1, 0x5410;\n"
        "mov.b32 {xl, xh}, a3; tanh.approx.f16 xr, xl; cvt.u32.u16 lo1, xr; tanh.approx.f16 xr, xh; cvt.u32.u16 hi1, xr; mul.rn.f16x2 a0, qz20, p0; fma.rn.f16x2 p1, qz21, qz21, c; fma.rn.f16x2 g1, qz17, h1, qz17; prmt.b32 h0, lo0, hi0, 0x5410;\n"
        "mov.b32 {xl, xh}, a0; tanh.approx.f16 xr, xl; cvt.u32.u16 lo0, xr; tanh.approx.f16 xr, xh; cvt.u32.u16 hi0, xr; mul.rn.f16x2 a1, qz21, p1; fma.rn.f16x2 p0, qz22, qz22, c; fma.rn.f16x2 g2, qz18, h0, qz18; prmt.b32 h1, lo1, hi1, 0x5410;\n"
        "mov.b32 {xl, xh}, a1; tanh.approx.f16 xr, xl; cvt.u32.u16 lo1, xr; tanh.approx.f16 xr, xh; cvt.u32.u16 hi1, xr; mul.rn.f16x2 a2, qz22, p0; fma.rn.f16x2 p1, qz23, qz23, c; fma.rn.f16x2 g3, qz19, h1, qz19; prmt.b32 h0, lo0, hi0, 0x5410;\n"
        "B54:\n"
        "wgmma.fence.sync.aligned;\n"
        "add.s64 dt, w1d, 3456; wgmma.mma_async.sync.aligned.m64n64k16.f16.f16.f16 {qz0,qz1,qz2,qz3,qz4,qz5,qz6,qz7,qz8,qz9,qz10,qz11,qz12,qz13,qz14,qz15}, {qa12,qa13,qa14,qa15}, dt, pt, 1, 1, 1;\n"
        "add.s64 dt, w1d, 3584; wgmma.mma_async.sync.aligned.m64n64k16.f16.f16.f16 {qz0,qz1,qz2,qz3,qz4,qz5,qz6,qz7,qz8,qz9,qz10,qz11,qz12,qz13,qz14,qz15}, {qa16,qa17,qa18,qa19}, dt, pt, 1, 1, 1;\n"
        "add.s64 dt, w1d, 3712; wgmma.mma_async.sync.aligned.m64n64k16.f16.f16.f16 {qz0,qz1,qz2,qz3,qz4,qz5,qz6,qz7,qz8,qz9,qz10,qz11,qz12,qz13,qz14,qz15}, {qa20,qa21,qa22,qa23}, dt, pt, 1, 1, 1;\n"
        "wgmma.commit_group.sync.aligned;\n"
        "@pz bra.uni B58;\n"
        "mov.b32 {xl, xh}, a2; tanh.approx.f16 xr, xl; cvt.u32.u16 lo0, xr; tanh.approx.f16 xr, xh; cvt.u32.u16 hi0, xr; mul.rn.f16x2 a3, qz23, p1; fma.rn.f16x2 p0, qz24, qz24, c; fma.rn.f16x2 g4, qz20, h0, qz20; prmt.b32 h1, lo1, hi1, 0x5410;\n"
        "mov.b32 {xl, xh}, a3; tanh.approx.f16 xr, xl; cvt.u32.u16 lo1, xr; tanh.approx.f16 xr, xh; cvt.u32.u16 hi1, xr; mul.rn.f16x2 a0, qz24, p0; fma.rn.f16x2 p1, qz25, qz25, c; fma.rn.f16x2 g5, qz21, h1, qz21; prmt.b32 h0, lo0, hi0, 0x5410;\n"
        "mov.b32 {xl, xh}, a0; tanh.approx.f16 xr, xl; cvt.u32.u16 lo0, xr; tanh.approx.f16 xr, xh; cvt.u32.u16 hi0, xr; mul.rn.f16x2 a1, qz25, p1; fma.rn.f16x2 p0, qz26, qz26, c; fma.rn.f16x2 g6, qz22, h0, qz22; prmt.b32 h1, lo1, hi1, 0x5410;\n"
        "mov.b32 {xl, xh}, a1; tanh.approx.f16 xr, xl; cvt.u32.u16 lo1, xr; tanh.approx.f16 xr, xh; cvt.u32.u16 hi1, xr; mul.rn.f16x2 a2, qz26, p0; fma.rn.f16x2 p1, qz27, qz27, c; fma.rn.f16x2 g7, qz23, h1, qz23; prmt.b32 h0, lo0, hi0, 0x5410;\n"
        "B58:\n"
        "wgmma.wait_group.sync.aligned 2;\n"
        "wgmma.fence.sync.aligned;\n"
        "add.s64 dt, w2d, 768; wgmma.mma_async.sync.aligned.m64n96k16.f16.f16.f16 {o0,o1,o2,o3,o4,o5,o6,o7,o8,o9,o10,o11,o12,o13,o14,o15,o16,o17,o18,o19,o20,o21,o22,o23}, {g0,g1,g2,g3}, dt, pt, 1, 1, 1;\n"
        "add.s64 dt, w2d, 832; wgmma.mma_async.sync.aligned.m64n96k16.f16.f16.f16 {o0,o1,o2,o3,o4,o5,o6,o7,o8,o9,o10,o11,o12,o13,o14,o15,o16,o17,o18,o19,o20,o21,o22,o23}, {g4,g5,g6,g7}, dt, pt, 1, 1, 1;\n"
        "wgmma.commit_group.sync.aligned;\n"
        "@pz bra.uni B62;\n"
        "mov.b32 {xl, xh}, a2; tanh.approx.f16 xr, xl; cvt.u32.u16 lo0, xr; tanh.approx.f16 xr, xh; cvt.u32.u16 hi0, xr; mul.rn.f16x2 a3, qz27, p1; fma.rn.f16x2 p0, qz28, qz28, c; fma.rn.f16x2 g8, qz24, h0, qz24; prmt.b32 h1, lo1, hi1, 0x5410;\n"
        "mov.b32 {xl, xh}, a3; tanh.approx.f16 xr, xl; cvt.u32.u16 lo1, xr; tanh.approx.f16 xr, xh; cvt.u32.u16 hi1, xr; mul.rn.f16x2 a0, qz28, p0; fma.rn.f16x2 p1, qz29, qz29, c; fma.rn.f16x2 g9, qz25, h1, qz25; prmt.b32 h0, lo0, hi0, 0x5410;\n"
        "mov.b32 {xl, xh}, a0; tanh.approx.f16 xr, xl; cvt.u32.u16 lo0, xr; tanh.approx.f16 xr, xh; cvt.u32.u16 hi0, xr; mul.rn.f16x2 a1, qz29, p1; fma.rn.f16x2 p0, qz30, qz30, c; fma.rn.f16x2 g10, qz26, h0, qz26; prmt.b32 h1, lo1, hi1, 0x5410;\n"
        "mov.b32 {xl, xh}, a1; tanh.approx.f16 xr, xl; cvt.u32.u16 lo1, xr; tanh.approx.f16 xr, xh; cvt.u32.u16 hi1, xr; mul.rn.f16x2 a2, qz30, p0; fma.rn.f16x2 p1, qz31, qz31, c; fma.rn.f16x2 g11, qz27, h1, qz27; prmt.b32 h0, lo0, hi0, 0x5410;\n"
        "B62:\n"
        "wgmma.wait_group.sync.aligned 1;\n"
        "wgmma.fence.sync.aligned;\n"
        "add.s64 dt, w2d, 896; wgmma.mma_async.sync.aligned.m64n96k16.f16.f16.f16 {o0,o1,o2,o3,o4,o5,o6,o7,o8,o9,o10,o11,o12,o13,o14,o15,o16,o17,o18,o19,o20,o21,o22,o23}, {g8,g9,g10,g11}, dt, pt, 1, 1, 1;\n"
        "wgmma.commit_group.sync.aligned;\n"
        "@pz bra.uni B66;\n"
        "mov.b32 {xl, xh}, a2; tanh.approx.f16 xr, xl; cvt.u32.u16 lo0, xr; tanh.approx.f16 xr, xh; cvt.u32.u16 hi0, xr; mul.rn.f16x2 a3, qz31, p1; fma.rn.f16x2 p0, qz0, qz0, c; fma.rn.f16x2 g12, qz28, h0, qz28; prmt.b32 h1, lo1, hi1, 0x5410;\n"
        "mov.b32 {xl, xh}, a3; tanh.approx.f16 xr, xl; cvt.u32.u16 lo1, xr; tanh.approx.f16 xr, xh; cvt.u32.u16 hi1, xr; mul.rn.f16x2 a0, qz0, p0; fma.rn.f16x2 p1, qz1, qz1, c; fma.rn.f16x2 g13, qz29, h1, qz29; prmt.b32 h0, lo0, hi0, 0x5410;\n"
        "mov.b32 {xl, xh}, a0; tanh.approx.f16 xr, xl; cvt.u32.u16 lo0, xr; tanh.approx.f16 xr, xh; cvt.u32.u16 hi0, xr; mul.rn.f16x2 a1, qz1, p1; fma.rn.f16x2 p0, qz2, qz2, c; fma.rn.f16x2 g14, qz30, h0, qz30; prmt.b32 h1, lo1, hi1, 0x5410;\n"
        "mov.b32 {xl, xh}, a1; tanh.approx.f16 xr, xl; cvt.u32.u16 lo1, xr; tanh.approx.f16 xr, xh; cvt.u32.u16 hi1, xr; mul.rn.f16x2 a2, qz2, p0; fma.rn.f16x2 p1, qz3, qz3, c; fma.rn.f16x2 g15, qz31, h1, qz31; prmt.b32 h0, lo0, hi0, 0x5410;\n"
        "B66:\n"
        "wgmma.wait_group.sync.aligned 1;\n"
        "wgmma.fence.sync.aligned;\n"
        "add.s64 dt, w2d, 960; wgmma.mma_async.sync.aligned.m64n96k16.f16.f16.f16 {o0,o1,o2,o3,o4,o5,o6,o7,o8,o9,o10,o11,o12,o13,o14,o15,o16,o17,o18,o19,o20,o21,o22,o23}, {g12,g13,g14,g15}, dt, pt, 1, 1, 1;\n"
        "add.s64 dt, w1d, 3840; wgmma.mma_async.sync.aligned.m64n64k16.f16.f16.f16 {qz16,qz17,qz18,qz19,qz20,qz21,qz22,qz23,qz24,qz25,qz26,qz27,qz28,qz29,qz30,qz31}, {qa0,qa1,qa2,qa3}, dt, pf, 1, 1, 1;\n"
        "add.s64 dt, w1d, 3968; wgmma.mma_async.sync.aligned.m64n64k16.f16.f16.f16 {qz16,qz17,qz18,qz19,qz20,qz21,qz22,qz23,qz24,qz25,qz26,qz27,qz28,qz29,qz30,qz31}, {qa4,qa5,qa6,qa7}, dt, pt, 1, 1, 1;\n"
        "add.s64 dt, w1d, 4096; wgmma.mma_async.sync.aligned.m64n64k16.f16.f16.f16 {qz16,qz17,qz18,qz19,qz20,qz21,qz22,qz23,qz24,qz25,qz26,qz27,qz28,qz29,qz30,qz31}, {qa8,qa9,qa10,qa11}, dt, pt, 1, 1, 1;\n"
        "wgmma.commit_group.sync.aligned;\n"
        "@pz bra.uni B70;\n"
        "mov.b32 {xl, xh}, a2; tanh.approx.f16 xr, xl; cvt.u32.u16 lo0, xr; tanh.approx.f16 xr, xh; cvt.u32.u16 hi0, xr; mul.rn.f16x2 a3, qz3, p1; fma.rn.f16x2 p0, qz4, qz4, c; fma.rn.f16x2 g0, qz0, h0, qz0; prmt.b32 h1, lo1, hi1, 0x5410;\n"
        "mov.b32 {xl, xh}, a3; tanh.approx.f16 xr, xl; cvt.u32.u16 lo1, xr; tanh.approx.f16 xr, xh; cvt.u32.u16 hi1, xr; mul.rn.f16x2 a0, qz4, p0; fma.rn.f16x2 p1, qz5, qz5, c; fma.rn.f16x2 g1, qz1, h1, qz1; prmt.b32 h0, lo0, hi0, 0x5410;\n"
        "mov.b32 {xl, xh}, a0; tanh.approx.f16 xr, xl; cvt.u32.u16 lo0, xr; tanh.approx.f16 xr, xh; cvt.u32.u16 hi0, xr; mul.rn.f16x2 a1, qz5, p1; fma.rn.f16x2 p0, qz6, qz6, c; fma.rn.f16x2 g2, qz2, h0, qz2; prmt.b32 h1, lo1, hi1, 0x5410;\n"
        "mov.b32 {xl, xh}, a1; tanh.approx.f16 xr, xl; cvt.u32.u16 lo1, xr; tanh.approx.f16 xr, xh; cvt.u32.u16 hi1, xr; mul.rn.f16x2 a2, qz6, p0; fma.rn.f16x2 p1, qz7, qz7, c; fma.rn.f16x2 g3, qz3, h1, qz3; prmt.b32 h0, lo0, hi0, 0x5410;\n"
        "B70:\n"
        "wgmma.fence.sync.aligned;\n"
        "add.s64 dt, w1d, 4224; wgmma.mma_async.sync.aligned.m64n64k16.f16.f16.f16 {qz16,qz17,qz18,qz19,qz20,qz21,qz22,qz23,qz24,qz25,qz26,qz27,qz28,qz29,qz30,qz31}, {qa12,qa13,qa14,qa15}, dt, pt, 1, 1, 1;\n"
        "add.s64 dt, w1d, 4352; wgmma.mma_async.sync.aligned.m64n64k16.f16.f16.f16 {qz16,qz17,qz18,qz19,qz20,qz21,qz22,qz23,qz24,qz25,qz26,qz27,qz28,qz29,qz30,qz31}, {qa16,qa17,qa18,qa19}, dt, pt, 1, 1, 1;\n"
        "add.s64 dt, w1d, 4480; wgmma.mma_async.sync.aligned.m64n64k16.f16.f16.f16 {qz16,qz17,qz18,qz19,qz20,qz21,qz22,qz23,qz24,qz25,qz26,qz27,qz28,qz29,qz30,qz31}, {qa20,qa21,qa22,qa23}, dt, pt, 1, 1, 1;\n"
        "wgmma.commit_group.sync.aligned;\n"
        "@pz bra.uni B74;\n"
        "mov.b32 {xl, xh}, a2; tanh.approx.f16 xr, xl; cvt.u32.u16 lo0, xr; tanh.approx.f16 xr, xh; cvt.u32.u16 hi0, xr; mul.rn.f16x2 a3, qz7, p1; fma.rn.f16x2 p0, qz8, qz8, c; fma.rn.f16x2 g4, qz4, h0, qz4; prmt.b32 h1, lo1, hi1, 0x5410;\n"
        "mov.b32 {xl, xh}, a3; tanh.approx.f16 xr, xl; cvt.u32.u16 lo1, xr; tanh.approx.f16 xr, xh; cvt.u32.u16 hi1, xr; mul.rn.f16x2 a0, qz8, p0; fma.rn.f16x2 p1, qz9, qz9, c; fma.rn.f16x2 g5, qz5, h1, qz5; prmt.b32 h0, lo0, hi0, 0x5410;\n"
        "mov.b32 {xl, xh}, a0; tanh.approx.f16 xr, xl; cvt.u32.u16 lo0, xr; tanh.approx.f16 xr, xh; cvt.u32.u16 hi0, xr; mul.rn.f16x2 a1, qz9, p1; fma.rn.f16x2 p0, qz10, qz10, c; fma.rn.f16x2 g6, qz6, h0, qz6; prmt.b32 h1, lo1, hi1, 0x5410;\n"
        "mov.b32 {xl, xh}, a1; tanh.approx.f16 xr, xl; cvt.u32.u16 lo1, xr; tanh.approx.f16 xr, xh; cvt.u32.u16 hi1, xr; mul.rn.f16x2 a2, qz10, p0; fma.rn.f16x2 p1, qz11, qz11, c; fma.rn.f16x2 g7, qz7, h1, qz7; prmt.b32 h0, lo0, hi0, 0x5410;\n"
        "B74:\n"
        "wgmma.wait_group.sync.aligned 2;\n"
        "setp.eq.s32 pr, n, 0;\n"
        "@pr bra.uni SPINW2;\n"
        "BACKW2:\n"
        "wgmma.fence.sync.aligned;\n"
        "add.s64 dt, w2d, 1024; wgmma.mma_async.sync.aligned.m64n96k16.f16.f16.f16 {o0,o1,o2,o3,o4,o5,o6,o7,o8,o9,o10,o11,o12,o13,o14,o15,o16,o17,o18,o19,o20,o21,o22,o23}, {g0,g1,g2,g3}, dt, pt, 1, 1, 1;\n"
        "add.s64 dt, w2d, 1088; wgmma.mma_async.sync.aligned.m64n96k16.f16.f16.f16 {o0,o1,o2,o3,o4,o5,o6,o7,o8,o9,o10,o11,o12,o13,o14,o15,o16,o17,o18,o19,o20,o21,o22,o23}, {g4,g5,g6,g7}, dt, pt, 1, 1, 1;\n"
        "wgmma.commit_group.sync.aligned;\n"
        "@pz bra.uni B78;\n"
        "mov.b32 {xl, xh}, a2; tanh.approx.f16 xr, xl; cvt.u32.u16 lo0, xr; tanh.approx.f16 xr, xh; cvt.u32.u16 hi0, xr; mul.rn.f16x2 a3, qz11, p1; fma.rn.f16x2 p0, qz12, qz12, c; fma.rn.f16x2 g8, qz8, h0, qz8; prmt.b32 h1, lo1, hi1, 0x5410;\n"
        "mov.b32 {xl, xh}, a3; tanh.approx.f16 xr, xl; cvt.u32.u16 lo1, xr; tanh.approx.f16 xr, xh; cvt.u32.u16 hi1, xr; mul.rn.f16x2 a0, qz12, p0; fma.rn.f16x2 p1, qz13, qz13, c; fma.rn.f16x2 g9, qz9, h1, qz9; prmt.b32 h0, lo0, hi0, 0x5410;\n"
        "mov.b32 {xl, xh}, a0; tanh.approx.f16 xr, xl; cvt.u32.u16 lo0, xr; tanh.approx.f16 xr, xh; cvt.u32.u16 hi0, xr; mul.rn.f16x2 a1, qz13, p1; fma.rn.f16x2 p0, qz14, qz14, c; fma.rn.f16x2 g10, qz10, h0, qz10; prmt.b32 h1, lo1, hi1, 0x5410;\n"
        "mov.b32 {xl, xh}, a1; tanh.approx.f16 xr, xl; cvt.u32.u16 lo1, xr; tanh.approx.f16 xr, xh; cvt.u32.u16 hi1, xr; mul.rn.f16x2 a2, qz14, p0; fma.rn.f16x2 p1, qz15, qz15, c; fma.rn.f16x2 g11, qz11, h1, qz11; prmt.b32 h0, lo0, hi0, 0x5410;\n"
        "B78:\n"
        "wgmma.wait_group.sync.aligned 1;\n"
        "@!pm bra.uni BACKY;\n"
        "add.u32 tt, n, 1; and.b32 tt, tt, 1; mbarrier.try_wait.parity.shared::cta.b64 pw, [ybar], tt;\n"
        "@!pw bra.uni SPINY;\n"
        "BACKY:\n"
        "@pz bra.uni B80;\n"
        "and.b32 ad, %6, 0xffff; xor.b32 ad, ad, 0; add.u32 ad, ad, %5; ldmatrix.sync.aligned.m8n8.x4.shared.b16 {qa0,qa1,qa2,qa3}, [ad];\n"
        "and.b32 ad, %6, 0xffff; xor.b32 ad, ad, 32; add.u32 ad, ad, %5; ldmatrix.sync.aligned.m8n8.x4.shared.b16 {qa4,qa5,qa6,qa7}, [ad];\n"
        "and.b32 ad, %6, 0xffff; xor.b32 ad, ad, 64; add.u32 ad, ad, %5; ldmatrix.sync.aligned.m8n8.x4.shared.b16 {qa8,qa9,qa10,qa11}, [ad];\n"
        "and.b32 ad, %6, 0xffff; xor.b32 ad, ad, 96; add.u32 ad, ad, %5; ldmatrix.sync.aligned.m8n8.x4.shared.b16 {qa12,qa13,qa14,qa15}, [ad];\n"
        "shr.u32 ad, %6, 16; xor.b32 ad, ad, 0; add.u32 ad, ad, %5; ldmatrix.sync.aligned.m8n8.x4.shared.b16 {qa16,qa17,qa18,qa19}, [ad];\n"
        "shr.u32 ad, %6, 16; xor.b32 ad, ad, 32; add.u32 ad, ad, %5; ldmatrix.sync.aligned.m8n8.x4.shared.b16 {qa20,qa21,qa22,qa23}, [ad];\n"
        "mov.b32 {xl, xh}, a2; tanh.approx.f16 xr, xl; cvt.u32.u16 lo0, xr; tanh.approx.f16 xr, xh; cvt.u32.u16 hi0, xr; mul.rn.f16x2 a3, qz15, p1; fma.rn.f16x2 p0, qz16, qz16, c; fma.rn.f16x2 g12, qz12, h0, qz12; prmt.b32 h1, lo1, hi1, 0x5410;\n"
        "mov.b32 {xl, xh}, a3; tanh.approx.f16 xr, xl; cvt.u32.u16 lo1, xr; tanh.approx.f16 xr, xh; cvt.u32.u16 hi1, xr; mul.rn.f16x2 a0, qz16, p0; fma.rn.f16x2 p1, qz17, qz17, c; fma.rn.f16x2 g13, qz13, h1, qz13; prmt.b32 h0, lo0, hi0, 0x5410;\n"
        "B80:\n"
        "@!pm bra.uni XLOADB;\n"
        "fence.proxy.async.shared::cta;\n"
        "add.u32 tt, id, 0;\n"
        "@pl bra.uni XLOAD;\n"
        "bar.arrive tt, 128;\n"
        "XLOADB:\n"
        "wgmma.fence.sync.aligned;\n"
        "add.s64 dt, w2d, 1152; wgmma.mma_async.sync.aligned.m64n96k16.f16.f16.f16 {o0,o1,o2,o3,o4,o5,o6,o7,o8,o9,o10,o11,o12,o13,o14,o15,o16,o17,o18,o19,o20,o21,o22,o23}, {g8,g9,g10,g11}, dt, pt, 1, 1, 1;\n"
        "wgmma.commit_group.sync.aligned;\n"
        "@pz bra.uni B82;\n"
        "mov.b32 {xl, xh}, a0; tanh.approx.f16 xr, xl; cvt.u32.u16 lo0, xr; tanh.approx.f16 xr, xh; cvt.u32.u16 hi0, xr; mul.rn.f16x2 a1, qz17, p1; fma.rn.f16x2 p0, qz18, qz18, c; fma.rn.f16x2 g14, qz14, h0, qz14; prmt.b32 h1, lo1, hi1, 0x5410;\n"
        "mov.b32 {xl, xh}, a1; tanh.approx.f16 xr, xl; cvt.u32.u16 lo1, xr; tanh.approx.f16 xr, xh; cvt.u32.u16 hi1, xr; mul.rn.f16x2 a2, qz18, p0; fma.rn.f16x2 p1, qz19, qz19, c; fma.rn.f16x2 g15, qz15, h1, qz15; prmt.b32 h0, lo0, hi0, 0x5410;\n"
        "B82:\n"
        "wgmma.wait_group.sync.aligned 1;\n"
        "@!pm bra.uni SKIP0;\n"
        "wgmma.fence.sync.aligned;\n"
        "add.s64 dt, w1d, 0; wgmma.mma_async.sync.aligned.m64n64k16.f16.f16.f16 {qz0,qz1,qz2,qz3,qz4,qz5,qz6,qz7,qz8,qz9,qz10,qz11,qz12,qz13,qz14,qz15}, {qa0,qa1,qa2,qa3}, dt, pf, 1, 1, 1;\n"
        "add.s64 dt, w1d, 128; wgmma.mma_async.sync.aligned.m64n64k16.f16.f16.f16 {qz0,qz1,qz2,qz3,qz4,qz5,qz6,qz7,qz8,qz9,qz10,qz11,qz12,qz13,qz14,qz15}, {qa4,qa5,qa6,qa7}, dt, pt, 1, 1, 1;\n"
        "add.s64 dt, w1d, 256; wgmma.mma_async.sync.aligned.m64n64k16.f16.f16.f16 {qz0,qz1,qz2,qz3,qz4,qz5,qz6,qz7,qz8,qz9,qz10,qz11,qz12,qz13,qz14,qz15}, {qa8,qa9,qa10,qa11}, dt, pt, 1, 1, 1;\n"
        "SKIP0:\n"
        "wgmma.fence.sync.aligned;\n"
        "add.s64 dt, w2d, 1216; wgmma.mma_async.sync.aligned.m64n96k16.f16.f16.f16 {o0,o1,o2,o3,o4,o5,o6,o7,o8,o9,o10,o11,o12,o13,o14,o15,o16,o17,o18,o19,o20,o21,o22,o23}, {g12,g13,g14,g15}, dt, pt, 1, 1, 1;\n"
        "wgmma.commit_group.sync.aligned;\n"
        "@pz bra.uni B86;\n"
        "mov.b32 {xl, xh}, a2; tanh.approx.f16 xr, xl; cvt.u32.u16 lo0, xr; tanh.approx.f16 xr, xh; cvt.u32.u16 hi0, xr; mul.rn.f16x2 a3, qz19, p1; fma.rn.f16x2 p0, qz20, qz20, c; fma.rn.f16x2 g0, qz16, h0, qz16; prmt.b32 h1, lo1, hi1, 0x5410;\n"
        "mov.b32 {xl, xh}, a3; tanh.approx.f16 xr, xl; cvt.u32.u16 lo1, xr; tanh.approx.f16 xr, xh; cvt.u32.u16 hi1, xr; mul.rn.f16x2 a0, qz20, p0; fma.rn.f16x2 p1, qz21, qz21, c; fma.rn.f16x2 g1, qz17, h1, qz17; prmt.b32 h0, lo0, hi0, 0x5410;\n"
        "mov.b32 {xl, xh}, a0; tanh.approx.f16 xr, xl; cvt.u32.u16 lo0, xr; tanh.approx.f16 xr, xh; cvt.u32.u16 hi0, xr; mul.rn.f16x2 a1, qz21, p1; fma.rn.f16x2 p0, qz22, qz22, c; fma.rn.f16x2 g2, qz18, h0, qz18; prmt.b32 h1, lo1, hi1, 0x5410;\n"
        "mov.b32 {xl, xh}, a1; tanh.approx.f16 xr, xl; cvt.u32.u16 lo1, xr; tanh.approx.f16 xr, xh; cvt.u32.u16 hi1, xr; mul.rn.f16x2 a2, qz22, p0; fma.rn.f16x2 p1, qz23, qz23, c; fma.rn.f16x2 g3, qz19, h1, qz19; prmt.b32 h0, lo0, hi0, 0x5410;\n"
        "B86:\n"
        "@!pm bra.uni SKIP1;\n"
        "wgmma.fence.sync.aligned;\n"
        "add.s64 dt, w1d, 384; wgmma.mma_async.sync.aligned.m64n64k16.f16.f16.f16 {qz0,qz1,qz2,qz3,qz4,qz5,qz6,qz7,qz8,qz9,qz10,qz11,qz12,qz13,qz14,qz15}, {qa12,qa13,qa14,qa15}, dt, pt, 1, 1, 1;\n"
        "add.s64 dt, w1d, 512; wgmma.mma_async.sync.aligned.m64n64k16.f16.f16.f16 {qz0,qz1,qz2,qz3,qz4,qz5,qz6,qz7,qz8,qz9,qz10,qz11,qz12,qz13,qz14,qz15}, {qa16,qa17,qa18,qa19}, dt, pt, 1, 1, 1;\n"
        "add.s64 dt, w1d, 640; wgmma.mma_async.sync.aligned.m64n64k16.f16.f16.f16 {qz0,qz1,qz2,qz3,qz4,qz5,qz6,qz7,qz8,qz9,qz10,qz11,qz12,qz13,qz14,qz15}, {qa20,qa21,qa22,qa23}, dt, pt, 1, 1, 1;\n"
        "SKIP1:\n"
        "@pz bra.uni B90;\n"
        "mov.b32 {xl, xh}, a2; tanh.approx.f16 xr, xl; cvt.u32.u16 lo0, xr; tanh.approx.f16 xr, xh; cvt.u32.u16 hi0, xr; mul.rn.f16x2 a3, qz23, p1; fma.rn.f16x2 p0, qz24, qz24, c; fma.rn.f16x2 g4, qz20, h0, qz20; prmt.b32 h1, lo1, hi1, 0x5410;\n"
        "mov.b32 {xl, xh}, a3; tanh.approx.f16 xr, xl; cvt.u32.u16 lo1, xr; tanh.approx.f16 xr, xh; cvt.u32.u16 hi1, xr; mul.rn.f16x2 a0, qz24, p0; fma.rn.f16x2 p1, qz25, qz25, c; fma.rn.f16x2 g5, qz21, h1, qz21; prmt.b32 h0, lo0, hi0, 0x5410;\n"
        "mov.b32 {xl, xh}, a0; tanh.approx.f16 xr, xl; cvt.u32.u16 lo0, xr; tanh.approx.f16 xr, xh; cvt.u32.u16 hi0, xr; mul.rn.f16x2 a1, qz25, p1; fma.rn.f16x2 p0, qz26, qz26, c; fma.rn.f16x2 g6, qz22, h0, qz22; prmt.b32 h1, lo1, hi1, 0x5410;\n"
        "mov.b32 {xl, xh}, a1; tanh.approx.f16 xr, xl; cvt.u32.u16 lo1, xr; tanh.approx.f16 xr, xh; cvt.u32.u16 hi1, xr; mul.rn.f16x2 a2, qz26, p0; fma.rn.f16x2 p1, qz27, qz27, c; fma.rn.f16x2 g7, qz23, h1, qz23; prmt.b32 h0, lo0, hi0, 0x5410;\n"
        "B90:\n"
        "wgmma.wait_group.sync.aligned 1;\n"
        "wgmma.fence.sync.aligned;\n"
        "add.s64 dt, w2d, 1280; wgmma.mma_async.sync.aligned.m64n96k16.f16.f16.f16 {o0,o1,o2,o3,o4,o5,o6,o7,o8,o9,o10,o11,o12,o13,o14,o15,o16,o17,o18,o19,o20,o21,o22,o23}, {g0,g1,g2,g3}, dt, pt, 1, 1, 1;\n"
        "add.s64 dt, w2d, 1344; wgmma.mma_async.sync.aligned.m64n96k16.f16.f16.f16 {o0,o1,o2,o3,o4,o5,o6,o7,o8,o9,o10,o11,o12,o13,o14,o15,o16,o17,o18,o19,o20,o21,o22,o23}, {g4,g5,g6,g7}, dt, pt, 1, 1, 1;\n"
        "wgmma.commit_group.sync.aligned;\n"
        "@pz bra.uni B94;\n"
        "mov.b32 {xl, xh}, a2; tanh.approx.f16 xr, xl; cvt.u32.u16 lo0, xr; tanh.approx.f16 xr, xh; cvt.u32.u16 hi0, xr; mul.rn.f16x2 a3, qz27, p1; fma.rn.f16x2 p0, qz28, qz28, c; fma.rn.f16x2 g8, qz24, h0, qz24; prmt.b32 h1, lo1, hi1, 0x5410;\n"
        "mov.b32 {xl, xh}, a3; tanh.approx.f16 xr, xl; cvt.u32.u16 lo1, xr; tanh.approx.f16 xr, xh; cvt.u32.u16 hi1, xr; mul.rn.f16x2 a0, qz28, p0; fma.rn.f16x2 p1, qz29, qz29, c; fma.rn.f16x2 g9, qz25, h1, qz25; prmt.b32 h0, lo0, hi0, 0x5410;\n"
        "mov.b32 {xl, xh}, a0; tanh.approx.f16 xr, xl; cvt.u32.u16 lo0, xr; tanh.approx.f16 xr, xh; cvt.u32.u16 hi0, xr; mul.rn.f16x2 a1, qz29, p1; fma.rn.f16x2 p0, qz30, qz30, c; fma.rn.f16x2 g10, qz26, h0, qz26; prmt.b32 h1, lo1, hi1, 0x5410;\n"
        "mov.b32 {xl, xh}, a1; tanh.approx.f16 xr, xl; cvt.u32.u16 lo1, xr; tanh.approx.f16 xr, xh; cvt.u32.u16 hi1, xr; mul.rn.f16x2 a2, qz30, p0; fma.rn.f16x2 p1, qz31, qz31, c; fma.rn.f16x2 g11, qz27, h1, qz27; prmt.b32 h0, lo0, hi0, 0x5410;\n"
        "B94:\n"
        "wgmma.wait_group.sync.aligned 0;\n"
        "wgmma.fence.sync.aligned;\n"
        "add.s64 dt, w2d, 1408; wgmma.mma_async.sync.aligned.m64n96k16.f16.f16.f16 {o0,o1,o2,o3,o4,o5,o6,o7,o8,o9,o10,o11,o12,o13,o14,o15,o16,o17,o18,o19,o20,o21,o22,o23}, {g8,g9,g10,g11}, dt, pt, 1, 1, 1;\n"
        "wgmma.commit_group.sync.aligned;\n"
        "@pz bra.uni B2;\n"
        "mov.b32 {xl, xh}, a2; tanh.approx.f16 xr, xl; cvt.u32.u16 lo0, xr; tanh.approx.f16 xr, xh; cvt.u32.u16 hi0, xr; mul.rn.f16x2 a3, qz31, p1; fma.rn.f16x2 p0, qz0, qz0, c; fma.rn.f16x2 g12, qz28, h0, qz28; prmt.b32 h1, lo1, hi1, 0x5410;\n"
        "mov.b32 {xl, xh}, a3; tanh.approx.f16 xr, xl; cvt.u32.u16 lo1, xr; tanh.approx.f16 xr, xh; cvt.u32.u16 hi1, xr; mul.rn.f16x2 a0, qz0, p0; fma.rn.f16x2 p1, qz1, qz1, c; fma.rn.f16x2 g13, qz29, h1, qz29; prmt.b32 h0, lo0, hi0, 0x5410;\n"
        "mov.b32 {xl, xh}, a0; tanh.approx.f16 xr, xl; cvt.u32.u16 lo0, xr; tanh.approx.f16 xr, xh; cvt.u32.u16 hi0, xr; mul.rn.f16x2 a1, qz1, p1; fma.rn.f16x2 p0, qz2, qz2, c; fma.rn.f16x2 g14, qz30, h0, qz30; prmt.b32 h1, lo1, hi1, 0x5410;\n"
        "mov.b32 {xl, xh}, a1; tanh.approx.f16 xr, xl; cvt.u32.u16 lo1, xr; tanh.approx.f16 xr, xh; cvt.u32.u16 hi1, xr; mul.rn.f16x2 a2, qz2, p0; fma.rn.f16x2 p1, qz3, qz3, c; fma.rn.f16x2 g15, qz31, h1, qz31; prmt.b32 h0, lo0, hi0, 0x5410;\n"
        "B2:\n"
        "wgmma.fence.sync.aligned;\n"
        "add.s64 dt, w2d, 1472; wgmma.mma_async.sync.aligned.m64n96k16.f16.f16.f16 {o0,o1,o2,o3,o4,o5,o6,o7,o8,o9,o10,o11,o12,o13,o14,o15,o16,o17,o18,o19,o20,o21,o22,o23}, {g12,g13,g14,g15}, dt, pt, 1, 1, 1;\n"
        "wgmma.commit_group.sync.aligned;\n"
        "@!pm bra.uni LAST;\n"
        "@pz bra.uni BE;\n"
        "mov.b32 {xl, xh}, a2; tanh.approx.f16 xr, xl; cvt.u32.u16 lo0, xr; tanh.approx.f16 xr, xh; cvt.u32.u16 hi0, xr; mul.rn.f16x2 a3, qz3, p1; fma.rn.f16x2 p0, qz4, qz4, c; fma.rn.f16x2 g0, qz0, h0, qz0; prmt.b32 h1, lo1, hi1, 0x5410;\n"
        "mov.b32 {xl, xh}, a3; tanh.approx.f16 xr, xl; cvt.u32.u16 lo1, xr; tanh.approx.f16 xr, xh; cvt.u32.u16 hi1, xr; mul.rn.f16x2 a0, qz4, p0; fma.rn.f16x2 p1, qz5, qz5, c; fma.rn.f16x2 g1, qz1, h1, qz1; prmt.b32 h0, lo0, hi0, 0x5410;\n"
        "mov.b32 {xl, xh}, a0; tanh.approx.f16 xr, xl; cvt.u32.u16 lo0, xr; tanh.approx.f16 xr, xh; cvt.u32.u16 hi0, xr; mul.rn.f16x2 a1, qz5, p1; fma.rn.f16x2 p0, qz6, qz6, c; fma.rn.f16x2 g2, qz2, h0, qz2; prmt.b32 h1, lo1, hi1, 0x5410;\n"
        "mov.b32 {xl, xh}, a1; tanh.approx.f16 xr, xl; cvt.u32.u16 lo1, xr; tanh.approx.f16 xr, xh; cvt.u32.u16 hi1, xr; mul.rn.f16x2 a2, qz6, p0; fma.rn.f16x2 p1, qz7, qz7, c; fma.rn.f16x2 g3, qz3, h1, qz3; prmt.b32 h0, lo0, hi0, 0x5410;\n"
        "BE:\n"
        "wgmma.wait_group.sync.aligned 0;\n"
        "bra.uni LOOP;\n"
        "STORE:\n"
        "bar.sync tt, 128;\n"
        "setp.lt.s32 pr, n, 0;\n"
        "@pr bra.uni STOREB;\n"
        "cvt.u64.u32 gp, off; add.s64 gp, gp, %12;\n"
        "elect.sync _|pr, 0xffffffff;\n"
        "@pr cp.async.bulk.global.shared::cta.bulk_group [gp], [%5], 12288;\n"
        "@pr cp.async.bulk.commit_group;\n"
        "bra.uni STOREB;\n"
        "YLOAD:\n"
        "cp.async.bulk.wait_group.read 0;\n"
        "@!pm bra.uni XLAST;\n"
        "sub.u32 ad, off, %9; cvt.u64.u32 gp, ad; add.s64 gp, gp, %12;\n"
        "elect.sync _|pr, 0xffffffff;\n"
        "@pr mbarrier.arrive.expect_tx.shared::cta.b64 _, [ybar], 12288;\n"
        "@pr cp.async.bulk.shared::cluster.global.mbarrier::complete_tx::bytes [%5], [gp], 12288, [ybar];\n"
        "cvt.u64.u32 gp, off; add.s64 gp, gp, %11;\n"
        "@pr cp.async.bulk.prefetch.L2.global.L2::cache_hint [gp], 12288, pol;\n"
        "bra.uni YLOADB;\n"
        "XLAST:\n"
        "cvt.u64.u32 gp, off; add.s64 gp, gp, %11;\n"
        "elect.sync _|pr, 0xffffffff;\n"
        "@pr mbarrier.arrive.expect_tx.shared::cta.b64 _, [xbar], 12288;\n"
        "@pr cp.async.bulk.shared::cluster.global.mbarrier::complete_tx::bytes.L2::cache_hint [%5], [gp], 12288, [xbar], pol;\n"
        "bra.uni YLOADB;\n"
        "XLOAD:\n"
        "bar.sync tt, 128;\n"
        "cvt.u64.u32 gp, off; add.s64 gp, gp, %11;\n"
        "elect.sync _|pr, 0xffffffff;\n"
        "@pr mbarrier.arrive.expect_tx.shared::cta.b64 _, [xbar], 12288;\n"
        "@pr cp.async.bulk.shared::cluster.global.mbarrier::complete_tx::bytes.L2::cache_hint [%5], [gp], 12288, [xbar], pol;\n"
        "bra.uni XLOADB;\n"
        "SPINY: mov.u32 cnt, 0;\n"
        "SPINYL:\n"
        "add.u32 tt, n, 1; and.b32 tt, tt, 1; mbarrier.try_wait.parity.shared::cta.b64 pw, [ybar], tt;\n"
        "@pw bra.uni BACKY;\n"
        "add.u32 cnt, cnt, 1; setp.lt.u32 pw, cnt, 0x100000;\n"
        "@pw bra.uni SPINYL;\n"
        "trap;\n"
        "SPINX: mov.u32 cnt, 0;\n"
        "SPINXL:\n"
        "and.b32 tt, n, 1; mbarrier.try_wait.parity.shared::cta.b64 pw, [xbar], tt;\n"
        "@pw bra.uni BACKX;\n"
        "add.u32 cnt, cnt, 1; setp.lt.u32 pw, cnt, 0x100000;\n"
        "@pw bra.uni SPINXL;\n"
        "trap;\n"
        "SPINT: mov.u32 cnt, 0;\n"
        "SPINTL:\n"
        "mad.lo.u32 tt, n, 8, tbar; mbarrier.try_wait.parity.shared::cta.b64 pw, [tt], tpar;\n"
        "@pw bra.uni BACKT;\n"
        "add.u32 cnt, cnt, 1; setp.lt.u32 pw, cnt, 0x100000;\n"
        "@pw bra.uni SPINTL;\n"
        "trap;\n"
        "SPINW0: mov.u32 cnt, 0;\n"
        "SPINW0L:\n"
        "mov.u32 tt, 231208; mbarrier.try_wait.parity.shared::cta.b64 pw, [tt], 0;\n"
        "@pw bra.uni BACKW0;\n"
        "add.u32 cnt, cnt, 1; setp.lt.u32 pw, cnt, 0x100000;\n"
        "@pw bra.uni SPINW0L;\n"
        "trap;\n"
        "SPINW1: mov.u32 cnt, 0;\n"
        "SPINW1L:\n"
        "mov.u32 tt, 231216; mbarrier.try_wait.parity.shared::cta.b64 pw, [tt], 0;\n"
        "@pw bra.uni BACKW1;\n"
        "add.u32 cnt, cnt, 1; setp.lt.u32 pw, cnt, 0x100000;\n"
        "@pw bra.uni SPINW1L;\n"
        "trap;\n"
        "SPINW2: mov.u32 cnt, 0;\n"
        "SPINW2L:\n"
        "mov.u32 tt, 231224; mbarrier.try_wait.parity.shared::cta.b64 pw, [tt], 0;\n"
        "@pw bra.uni BACKW2;\n"
        "add.u32 cnt, cnt, 1; setp.lt.u32 pw, cnt, 0x100000;\n"
        "@pw bra.uni SPINW2L;\n"
        "trap;\n"
        "SPINY0: mov.u32 cnt, 0;\n"
        "SPINY0L:\n"
        "mbarrier.try_wait.parity.shared::cta.b64 pw, [ybar], 0;\n"
        "@pw bra.uni BACKY0;\n"
        "add.u32 cnt, cnt, 1; setp.lt.u32 pw, cnt, 0x100000;\n"
        "@pw bra.uni SPINY0L;\n"
        "trap;\n"
        "SPINR: mov.u32 cnt, 0;\n"
        "SPINRL:\n"
        "mov.u32 tt, 231232; mbarrier.try_wait.parity.shared::cta.b64 pw, [tt], %13;\n"
        "@pw bra.uni BACKR;\n"
        "add.u32 cnt, cnt, 1; setp.lt.u32 pw, cnt, 0x100000;\n"
        "@pw bra.uni SPINRL;\n"
        "trap;\n"
        "BACKR:\n"
        "mov.u32 tt, 230792; ld.shared.v2.b32 {osc, tt}, [tt];\n"
        "setp.ne.u32 pr, tt, 0; vote.sync.any.pred pr, pr, 0xffffffff;\n"
        "@pr bra.uni RETRY;\n"
        "setp.eq.u32 pr, %3, 0;\n"
        "@pr bra.uni BACKB;\n"
        "SPINB: mov.u32 cnt, 0;\n"
        "SPINBL:\n"
        "mov.u32 tt, 231208; mbarrier.try_wait.parity.shared::cta.b64 pw, [tt], 0;\n"
        "@pw bra.uni BACKB;\n"
        "add.u32 cnt, cnt, 1; setp.lt.u32 pw, cnt, 0x100000;\n"
        "@pw bra.uni SPINBL;\n"
        "trap;\n"
        "BACKB:\n"
        "ld.shared.v4.b32 {o0,o1,o2,o3}, [%8+0];\n"
        "ld.shared.v4.b32 {o4,o5,o6,o7}, [%8+64];\n"
        "ld.shared.v4.b32 {o8,o9,o10,o11}, [%8+128];\n"
        "ld.shared.v4.b32 {o12,o13,o14,o15}, [%8+192];\n"
        "ld.shared.v4.b32 {o16,o17,o18,o19}, [%8+256];\n"
        "ld.shared.v4.b32 {o20,o21,o22,o23}, [%8+320];\n"
        "bra.uni SPINW0;\n"
        "RETRY:\n"
        "wgmma.fence.sync.aligned;\n"
        "wgmma.commit_group.sync.aligned;\n"
        "wgmma.wait_group.sync.aligned 0;\n"
        "mov.u32 %0, 1;\n"
        "bra.uni OUT;\n"
        "SPINL: mov.u32 cnt, 0;\n"
        "SPINLL:\n"
        "and.b32 tt, n, 1; mbarrier.try_wait.parity.shared::cta.b64 pw, [xbar], tt;\n"
        "@pw bra.uni BACKL;\n"
        "add.u32 cnt, cnt, 1; setp.lt.u32 pw, cnt, 0x100000;\n"
        "@pw bra.uni SPINLL;\n"
        "trap;\n"
        "LAST:\n"
        "and.b32 tt, n, 1; mbarrier.try_wait.parity.shared::cta.b64 pw, [xbar], tt;\n"
        "@!pw bra.uni SPINL;\n"
        "BACKL:\n"
        "and.b32 ad, %7, 0xffff; add.u32 ad, ad, %5; ld.shared.v4.b32 {r0,r1,r2,r3}, [ad+0];\n"
        "shr.u32 ad, %7, 16; add.u32 ad, ad, %5; ld.shared.v4.b32 {r4,r5,r6,r7}, [ad+0];\n"
        "and.b32 ad, %7, 0xffff; add.u32 ad, ad, %5; ld.shared.v4.b32 {r8,r9,r10,r11}, [ad+64];\n"
        "shr.u32 ad, %7, 16; add.u32 ad, ad, %5; ld.shared.v4.b32 {r12,r13,r14,r15}, [ad+64];\n"
        "and.b32 ad, %7, 0xffff; add.u32 ad, ad, %5; ld.shared.v4.b32 {r16,r17,r18,r19}, [ad+128];\n"
        "shr.u32 ad, %7, 16; add.u32 ad, ad, %5; ld.shared.v4.b32 {r20,r21,r22,r23}, [ad+128];\n"
        "wgmma.wait_group.sync.aligned 0;\n"
        "mov.b32 {xl, xh}, o0; cvt.f32.f16 f0, xl; cvt.f32.f16 f1, xh; cvt.rn.bf16x2.f32 tt, f1, f0; fma.rn.bf16x2 r0, tt, osc, r0;\n"
        "mov.b32 {xl, xh}, o2; cvt.f32.f16 f0, xl; cvt.f32.f16 f1, xh; cvt.rn.bf16x2.f32 tt, f1, f0; fma.rn.bf16x2 r1, tt, osc, r1;\n"
        "mov.b32 {xl, xh}, o4; cvt.f32.f16 f0, xl; cvt.f32.f16 f1, xh; cvt.rn.bf16x2.f32 tt, f1, f0; fma.rn.bf16x2 r2, tt, osc, r2;\n"
        "mov.b32 {xl, xh}, o6; cvt.f32.f16 f0, xl; cvt.f32.f16 f1, xh; cvt.rn.bf16x2.f32 tt, f1, f0; fma.rn.bf16x2 r3, tt, osc, r3;\n"
        "and.b32 ad, %7, 0xffff; add.u32 ad, ad, off; cvt.u64.u32 gp, ad; add.s64 gp, gp, %12; st.global.v4.b32 [gp+0], {r0,r1,r2,r3};\n"
        "mov.b32 {xl, xh}, o1; cvt.f32.f16 f0, xl; cvt.f32.f16 f1, xh; cvt.rn.bf16x2.f32 tt, f1, f0; fma.rn.bf16x2 r4, tt, osc, r4;\n"
        "mov.b32 {xl, xh}, o3; cvt.f32.f16 f0, xl; cvt.f32.f16 f1, xh; cvt.rn.bf16x2.f32 tt, f1, f0; fma.rn.bf16x2 r5, tt, osc, r5;\n"
        "mov.b32 {xl, xh}, o5; cvt.f32.f16 f0, xl; cvt.f32.f16 f1, xh; cvt.rn.bf16x2.f32 tt, f1, f0; fma.rn.bf16x2 r6, tt, osc, r6;\n"
        "mov.b32 {xl, xh}, o7; cvt.f32.f16 f0, xl; cvt.f32.f16 f1, xh; cvt.rn.bf16x2.f32 tt, f1, f0; fma.rn.bf16x2 r7, tt, osc, r7;\n"
        "shr.u32 ad, %7, 16; add.u32 ad, ad, off; cvt.u64.u32 gp, ad; add.s64 gp, gp, %12; st.global.v4.b32 [gp+0], {r4,r5,r6,r7};\n"
        "mov.b32 {xl, xh}, o8; cvt.f32.f16 f0, xl; cvt.f32.f16 f1, xh; cvt.rn.bf16x2.f32 tt, f1, f0; fma.rn.bf16x2 r8, tt, osc, r8;\n"
        "mov.b32 {xl, xh}, o10; cvt.f32.f16 f0, xl; cvt.f32.f16 f1, xh; cvt.rn.bf16x2.f32 tt, f1, f0; fma.rn.bf16x2 r9, tt, osc, r9;\n"
        "mov.b32 {xl, xh}, o12; cvt.f32.f16 f0, xl; cvt.f32.f16 f1, xh; cvt.rn.bf16x2.f32 tt, f1, f0; fma.rn.bf16x2 r10, tt, osc, r10;\n"
        "mov.b32 {xl, xh}, o14; cvt.f32.f16 f0, xl; cvt.f32.f16 f1, xh; cvt.rn.bf16x2.f32 tt, f1, f0; fma.rn.bf16x2 r11, tt, osc, r11;\n"
        "and.b32 ad, %7, 0xffff; add.u32 ad, ad, off; cvt.u64.u32 gp, ad; add.s64 gp, gp, %12; st.global.v4.b32 [gp+64], {r8,r9,r10,r11};\n"
        "mov.b32 {xl, xh}, o9; cvt.f32.f16 f0, xl; cvt.f32.f16 f1, xh; cvt.rn.bf16x2.f32 tt, f1, f0; fma.rn.bf16x2 r12, tt, osc, r12;\n"
        "mov.b32 {xl, xh}, o11; cvt.f32.f16 f0, xl; cvt.f32.f16 f1, xh; cvt.rn.bf16x2.f32 tt, f1, f0; fma.rn.bf16x2 r13, tt, osc, r13;\n"
        "mov.b32 {xl, xh}, o13; cvt.f32.f16 f0, xl; cvt.f32.f16 f1, xh; cvt.rn.bf16x2.f32 tt, f1, f0; fma.rn.bf16x2 r14, tt, osc, r14;\n"
        "mov.b32 {xl, xh}, o15; cvt.f32.f16 f0, xl; cvt.f32.f16 f1, xh; cvt.rn.bf16x2.f32 tt, f1, f0; fma.rn.bf16x2 r15, tt, osc, r15;\n"
        "shr.u32 ad, %7, 16; add.u32 ad, ad, off; cvt.u64.u32 gp, ad; add.s64 gp, gp, %12; st.global.v4.b32 [gp+64], {r12,r13,r14,r15};\n"
        "mov.b32 {xl, xh}, o16; cvt.f32.f16 f0, xl; cvt.f32.f16 f1, xh; cvt.rn.bf16x2.f32 tt, f1, f0; fma.rn.bf16x2 r16, tt, osc, r16;\n"
        "mov.b32 {xl, xh}, o18; cvt.f32.f16 f0, xl; cvt.f32.f16 f1, xh; cvt.rn.bf16x2.f32 tt, f1, f0; fma.rn.bf16x2 r17, tt, osc, r17;\n"
        "mov.b32 {xl, xh}, o20; cvt.f32.f16 f0, xl; cvt.f32.f16 f1, xh; cvt.rn.bf16x2.f32 tt, f1, f0; fma.rn.bf16x2 r18, tt, osc, r18;\n"
        "mov.b32 {xl, xh}, o22; cvt.f32.f16 f0, xl; cvt.f32.f16 f1, xh; cvt.rn.bf16x2.f32 tt, f1, f0; fma.rn.bf16x2 r19, tt, osc, r19;\n"
        "and.b32 ad, %7, 0xffff; add.u32 ad, ad, off; cvt.u64.u32 gp, ad; add.s64 gp, gp, %12; st.global.v4.b32 [gp+128], {r16,r17,r18,r19};\n"
        "mov.b32 {xl, xh}, o17; cvt.f32.f16 f0, xl; cvt.f32.f16 f1, xh; cvt.rn.bf16x2.f32 tt, f1, f0; fma.rn.bf16x2 r20, tt, osc, r20;\n"
        "mov.b32 {xl, xh}, o19; cvt.f32.f16 f0, xl; cvt.f32.f16 f1, xh; cvt.rn.bf16x2.f32 tt, f1, f0; fma.rn.bf16x2 r21, tt, osc, r21;\n"
        "mov.b32 {xl, xh}, o21; cvt.f32.f16 f0, xl; cvt.f32.f16 f1, xh; cvt.rn.bf16x2.f32 tt, f1, f0; fma.rn.bf16x2 r22, tt, osc, r22;\n"
        "mov.b32 {xl, xh}, o23; cvt.f32.f16 f0, xl; cvt.f32.f16 f1, xh; cvt.rn.bf16x2.f32 tt, f1, f0; fma.rn.bf16x2 r23, tt, osc, r23;\n"
        "shr.u32 ad, %7, 16; add.u32 ad, ad, off; cvt.u64.u32 gp, ad; add.s64 gp, gp, %12; st.global.v4.b32 [gp+128], {r20,r21,r22,r23};\n"
        ASM_MARK
        "mov.u32 %0, 0;\n"
        "OUT:\n"
        "}\n"
        : "=r"(retry)
        : "r"(prm.w1desc), "r"(prm.w2desc), "r"(c.wg), "r"(c.off), "r"(c.xs), "r"(c.a_offs), "r"(c.xs_offs), "r"(c.bias_addr),
          "r"(c.step), "r"(c.w), "l"(prm.x), "l"(prm.out), "r"(round)
        : "memory");
    return retry;
}

__device__ __forceinline__ float warp_sum(float v) {
#pragma unroll
    for (int s = 16; s >= 1; s >>= 1) v += __shfl_xor_sync(0xffffffffu, v, s);
    return v;
}
__device__ __forceinline__ float pow2f(int e) { return __uint_as_float((uint32_t)(e + 127) << 23); }
__device__ __forceinline__ int exponent_of(float v) { return (int)(__float_as_uint(v) >> 23) - 127; }
__device__ __forceinline__ float lds_bf16(uint32_t addr) {
    uint16_t v; asm volatile("ld.shared.u16 %0, [%1];" : "=h"(v) : "r"(addr) : "memory"); return bf_lo(v);
}

__device__ __forceinline__ void publish_bias(const Params& prm, uint32_t c, uint32_t tag) {
    const uint32_t lane = fresh_tid() & 31;
    const uint32_t col = sb + SM_W2 + (c >> 5) * 24576 + lane * 64 + ((((c >> 3) ^ (lane >> 1)) & 3) * 16) + (c & 7) * 2;
    float v = 0.0f;
#pragma unroll
    for (int k = 0; k < EX / 32; k++) v = fmaf(lds_bf16(col + k * 2048), lds_bf16(sb + SM_BETA + lane * 2 + k * 64), v);
    v = warp_sum(v);
    if (lane == 0)
        asm volatile("st.relaxed.gpu.global.u64 [%0], %1;" ::"l"(prm.g->bias + c), "l"((uint64_t)tag << 32 | __float_as_uint(v)) : "memory");
}
__device__ __forceinline__ void collect_bias(const Params& prm, uint32_t tag) {
    const uint32_t lane = fresh_tid() & 31;
    if (lane < 24) {
        const unsigned long long* src = prm.g->bias + 32 * (lane >> 3) + 8 * (lane & 3) + (lane & 4);
        uint32_t v[4], t[4], spins = 0;
        for (;;) {
#pragma unroll
            for (int k = 0; k < 4; k++)
                asm volatile("{\n.reg .b64 w;\nld.relaxed.gpu.global.u64 w, [%2];\nmov.b64 {%0, %1}, w;\n}\n"
                             : "=r"(v[k]), "=r"(t[k]) : "l"(src + k) : "memory");
            if (t[0] == tag && t[1] == tag && t[2] == tag && t[3] == tag) break;
            if (++spins > (1u << 22)) __trap();
        }
        sts128(sb + SM_BIAS + lane * 16, v[0], v[1], v[2], v[3]);
    }
    __syncwarp();
}
__device__ __forceinline__ float fetch_w2_row(uint32_t (&u)[12][4], uint32_t row, uint32_t sw) {
    uint32_t mx[4] = {};
#pragma unroll
    for (int a = 0; a < 3; a++)
#pragma unroll
        for (int k = 0; k < 4; k++) {
            asm volatile("ld.shared.v4.b32 {%0,%1,%2,%3}, [%4];"
                         : "=r"(u[a * 4][k]), "=r"(u[a * 4 + 1][k]), "=r"(u[a * 4 + 2][k]), "=r"(u[a * 4 + 3][k])
                         : "r"(row + a * 24576 + ((k * 16) ^ sw)) : "memory");
#pragma unroll
            for (int b = 0; b < 4; b++) asm("max.xorsign.abs.bf16x2 %0, %0, %1;" : "+r"(mx[b]) : "r"(u[a * 4 + b][k]));
        }
#pragma unroll
    for (int b = 1; b < 4; b++) asm("max.xorsign.abs.bf16x2 %0, %0, %1;" : "+r"(mx[0]) : "r"(mx[b]));
    return fmaxf(fabsf(bf_lo(mx[0])), fabsf(bf_hi(mx[0])));
}

template <bool FAST> __device__ __forceinline__ bool grn_stats(const float (&ss)[3], const float (&gm)[3], const float (&bt)[3],
                                                               const float (&top)[3], int e, float (&gx)[3], float& inv, int& eo) {
    float b0 = 0.0f, b1 = 0.0f;
    bool bad = false;
#pragma unroll
    for (int k = 0; k < 3; k++) {
        gx[k] = sqrt_fast(fmaf(ss[k], INV_2A * INV_2A, 1e-6f));
        const float rt = sqrt_fast(ss[k] + 1.0f) * INV_2A * top[k];
        b0 += fmaf(bt[k], top[k], rt);
        b1 += rt * fabsf(gm[k]) * gx[k];
        bad |= !(ss[k] >= 16.0f && ss[k] < ACC_LIMIT);
    }
    const float sum = gx[0] + gx[1] + gx[2];
    uint32_t r[4] = {FAST ? __reduce_add_sync(0xffffffffu, __float2uint_rn(sum * 128.0f)) : __float_as_uint(warp_sum(sum)),
                     __reduce_max_sync(0xffffffffu, __float_as_uint(b0)), __reduce_max_sync(0xffffffffu, __float_as_uint(b1)),
                     (uint32_t)__any_sync(0xffffffffu, bad)};
    if ((e & 31) == 0) sts128(sb + SM_SEL + (e >> 5) * 16, r[0], r[1], r[2], r[3]);
    MARK(6);
    named_sync(10, 128);
    lds128(r, sb + SM_SEL + (e & 3) * 16);
    if ((e & 31) >= 4) r[0] = 0;
    const float tot = FAST ? __uint2float_rn(__reduce_add_sync(0xffffffffu, r[0])) * (1.0f / 128) : warp_sum(__uint_as_float(r[0]));
    inv = __fdividef(1.0f, fmaf(tot, 1.0f / EX, 1e-6f));
    const float bound = fmaf(__uint_as_float(__reduce_max_sync(0xffffffffu, r[2])), inv,
                             __uint_as_float(__reduce_max_sync(0xffffffffu, r[1]))) * (EX / 3);
    eo = min(max(exponent_of(bound), -90), 126) - 14;
    return __any_sync(0xffffffffu, r[3]);
}

__device__ __forceinline__ const float* exact_sums(const Params& prm) {
    const int lane = fresh_tid() & 31, warp = fresh_warp(), wg = warp >> 2;
    const uint32_t epoch = lds32(sb + SM_RED + (RED_EPOCH + 1) * 4), bar = sb + SM_BAR + BAR_W1 * 8;
    if (wg < 3) {
        uint32_t wa[2][24], d[2][16];
        float acc[2][2] = {};
        const uint32_t yd = prm.ydesc + ((SM_SPARE - SM_Y1) >> 4), wd = prm.w1desc + ((2 * wg * 12288 + 5 * 2048) >> 4);
        load_w1t(wa, wg, warp & 3, lane);
#pragma unroll 1
        for (int n = 0; n < ROWS_PER_CTA; n++) {
            if (warp == 0) {
                expect_tx(bar, TILE_BYTES);
                bulk_load(sb + SM_SPARE, (const char*)prm.out + (cta_tile0(fresh_cta()) + n * cta_stride(fresh_cta())), TILE_BYTES, bar);
            }
            mbar_wait(bar, (n + 1) & 1);
            gemm1_t<0>(d[0], wa[0], yd, wd);
            gemm1_t<1>(d[1], wa[1], yd, wd);
            wg_wait<0>();
            pin(d[0]); pin(d[1]);
            gelu_sumsq_f(d[0], acc[0]);
            gelu_sumsq_f(d[1], acc[1]);
            named_sync(1, 384);
        }
        publish_sums(acc, prm.g->sums[epoch & 1], &prm.g->count[1], wg, warp & 3, lane);
    }
    grid_wait(&prm.g->count[1], (epoch + 1) * NUM_CTAS);
    return prm.g->sums[epoch & 1];
}

__device__ __forceinline__ void scale_w2_row(uint32_t (&u)[12][4], uint32_t row, uint32_t sw, float sc, int eo, uint32_t bar) {
    const float dn = pow2f(-eo);
    if (eo > 6) {
        const uint32_t dn2 = pack_bf2(dn, dn);
#pragma unroll
        for (int k = 0; k < 48; k++) u[k >> 2][k & 3] = bf2_mul(u[k >> 2][k & 3], dn2);
    } else {
        sc *= dn;
    }
    const uint32_t s2 = pack_bf2(sc * 0x1p-112f, sc * 0x1p-112f);
#pragma unroll
    for (int k = 0; k < 12; k++) {
        uint32_t v[4];
#pragma unroll
        for (int b = 0; b < 4; b++) {
            v[b] = bf2_mul(u[k][b], s2);
            v[b] += (v[b] & 0x7fff7fffu) * 7u;
        }
        sts128(row + (k >> 2) * 24576 + (((k & 3) * 16) ^ sw), v[0], v[1], v[2], v[3]);
    }
    fence_async_smem();
    __syncwarp();
    mbar_arrive_if(bar, (fresh_tid() & 31) == 0);
}
template <bool FIRST> __device__ __forceinline__ void prepare_w2(const Params& prm, const float* exact) {
    const int e = fresh_tid() - EX, lane = e & 31, warp = fresh_warp();
    const uint32_t row = sb + SM_W2 + e * 64, sw = ((e >> 1) & 3) * 16;
    uint32_t u[2][12][4];
    float top[3], gm[3], bt[3], ss[3], gx[3], inv;
    mbar_wait_c<0>(sb + SM_BAR + BAR_W2 * 8);
    top[2] = fetch_w2_row(u[0], row + 16384, sw);
    top[0] = fetch_w2_row(u[0], row, sw);
    top[1] = fetch_w2_row(u[1], row + 8192, sw);
#pragma unroll
    for (int k = 0; k < 3; k++) {
        gm[k] = lds_bf16(sb + SM_GAMMA + e * 2 + k * 256);
        bt[k] = fabsf(lds_bf16(sb + SM_BETA + e * 2 + k * 256));
    }
    MARK(3);
    if (FIRST) {
        const uint32_t epoch = lds32(sb + SM_RED + RED_EPOCH * 4);
        named_sync(11, 512);
        if (warp == 12) collect_bias(prm, epoch + 1);
        MARK(4);
        collect_fast(acc_word(prm, epoch, e), ss);
        if (e == 32 && fresh_cta() == 0) prm.g->count[0] = epoch + 1;
    } else {
#pragma unroll
        for (int k = 0; k < 3; k++) ss[k] = __ldcg(exact + e + 128 * k);
    }
    MARK(5);
    int eo;
    const bool redo = (grn_stats<FIRST>(ss, gm, bt, top, e, gx, inv, eo) || FORCE_EXACT) && FIRST;
    MARK(8);
    if (warp == 12) {
        const float up = pow2f(eo), dn = pow2f(-eo);
        if (lane == 24) sts64(sb + SM_RED + RED_SCALE * 4, pack_bf2(up, up), redo);
        if (lane < 24 && !redo) {
            uint32_t b[4];
            lds128(b, sb + SM_BIAS + lane * 16);
            const uint32_t p0 = pack_h2(__uint_as_float(b[0]) * dn, __uint_as_float(b[1]) * dn);
            const uint32_t p1 = pack_h2(__uint_as_float(b[2]) * dn, __uint_as_float(b[3]) * dn);
            sts128(sb + SM_BIAS + lane * 16, p0, p0, p1, p1);
        }
        __syncwarp();
        mbar_arrive_if(sb + SM_BAR + BAR_STAT * 8, lane == 0);
    }
    if (redo) return;
#pragma unroll
    for (int k = 0; k < 3; k++) gx[k] = fmaf(gm[k], gx[k] * inv, 1.0f) * INV_2A;
    scale_w2_row(u[0], row, sw, gx[0], eo, sb + SM_BAR + BAR_ROWS * 8);
    MARK(7);
    fetch_w2_row(u[0], row + 16384, sw);
    scale_w2_row(u[1], row + 8192, sw, gx[1], eo, sb + SM_BAR + (BAR_ROWS + 1) * 8);
    scale_w2_row(u[0], row + 16384, sw, gx[2], eo, sb + SM_BAR + (BAR_ROWS + 2) * 8);
    MARK(9);
    TS(4); TS(5);
}

__device__ __forceinline__ Pass2 pass2_setup() {
    const int warp = fresh_warp(), wg = warp >> 2, w = warp & 3, lane = fresh_tid() & 31, arow = 16 * w + (lane & 15);
    Pass2 c;
    c.wg = wg;
    c.w = w;
    c.off = cta_tile0(fresh_cta()) + (ROWS_PER_CTA - 1 - wg) * cta_stride(fresh_cta());
    c.step = 4 * cta_stride(fresh_cta());
    c.xs = wg == 3 ? sb + SM_BUF3 : sb + SM_Y1 + (wg == 2 ? 2 : 1 - wg) * SLOT_BYTES;
    static_assert((ROWS_PER_CTA - 1) % NX == 1, "slot of the last tile");
    c.a_offs = (arow * 128 + (((lane >> 4) ^ (arow & 7)) * 16)) |
               (8192 + arow * 64 + (((lane >> 4) ^ ((arow >> 1) & 3)) * 16)) << 16;
    const int g = lane >> 2, px = 33 * (g & 1) + 4 * (g >> 1) + 16 * (w >> 1) + 2 * (w & 1);
    c.xs_offs = (px * 192 + (lane & 3) * 16) | ((px ^ 1) * 192 + (lane & 3) * 16) << 16;
    c.bias_addr = sb + SM_BIAS + (lane & 3) * 16;
    return c;
}

__global__ void __launch_bounds__(512, 1) convnext_kernel(const __grid_constant__ Params prm) {
    extern __shared__ __align__(1024) uint8_t smem[];
    if ((uint32_t)__cvta_generic_to_shared(smem) != sb) __trap();
    {
        const uint32_t tid = fresh_tid(), warp = fresh_warp(), lane = tid & 31;
        if (warp == 0) {
            if (lane == 0) {
#pragma unroll
                for (int k = 0; k < NX; k++) mbar_init(sb + SM_GO + k * 8, 2);
                mbar_init(sb + SM_BAR + BAR_DW * 8, 1);
                mbar_init(sb + SM_BAR + BAR_W1 * 8, 1);
                mbar_init(sb + SM_BAR + BAR_W1B * 8, 1);
                fence_async_smem();
            }
            __syncwarp();
            expect_tx(sb + SM_BAR + BAR_DW * 8, 9 * CH * 2);
            bulk_load(sb + SM_Y1, prm.dw, 9 * CH * 2, sb + SM_BAR + BAR_DW * 8);
            const RowCopy rc = row_copy(prm);
#pragma unroll
            for (int k = 0; k < NX; k++) issue_row_load(rc, k, k);
            SMARK(4);
        }
        if (fresh_warp() == 15) {
            const uint32_t cta = fresh_cta();
            bulk_prefetch((const char*)prm.w1 + cta * (CH * EX * 2 / NUM_CTAS), CH * EX * 2 / NUM_CTAS);
            bulk_prefetch(prm.dw, 9 * CH * 2);
            bulk_prefetch((const char*)prm.x + (cta_tile0(cta) - cta_stride(cta)), TILE_BYTES);
        } else if (warp == 2) {
            if (lane < 2) asm volatile("prefetch.tensormap [%0];" ::"l"(&prm.w1_map + lane) : "memory");
        } else if (warp - 6u < 6) {
            if (lane == 0) {
#pragma unroll 1
                for (int k = NX + warp - 6; k < GO_COUNT + ROWS_PER_CTA + 2; k += 6)
                    mbar_init(sb + SM_GO + k * 8, k < 2 * NX ? 2 : k < GO_COUNT ? 14 : 4);
                fence_async_smem();
            }
        } else if (warp == 3) {
            const uint32_t one = (lane & 5) == ((lane & 8) >> 1) + (lane >> 4) ? 0x3f803f80u : 0u;
            sts128(sb + SM_SEL + lane * 16, one, one, one, one);
            fence_async_smem();
        } else if (tid - 128u < NX * 12 && ((fresh_cta() + 1) & 7) < 2) {
            const int k = tid - 128;
            sts128(sb + SM_X + (k / 12) * SLOT_BYTES + ((fresh_cta() & 7) == 0 ? 0 : XHALF_B + 33 * 192) + (k % 12) * 16, 0, 0, 0, 0);
        }
        __syncwarp();
        SMARK(3);
        named_sync(0, 512);
    }
    if (fresh_warp() >= 12) {
        Producer pc;
        SMARK(0);
        asm volatile("setmaxnreg.inc.sync.aligned.u32 %0;" ::"n"(PRODUCER_REGS));
        SMARK(1);
        const int w = fresh_warp() & 3, lane = fresh_tid() & 31;
        const int j = lane & 7, hb = (lane >> 3) & 1, base = 4 * (2 * w + (lane >> 4));
        pc.lane = lane;
        pc.xoff[0] = hb * XHALF_B + base * 192 + j * 16;
        pc.xoff[1] = hb * XHALF_B + base * 192 + 128 + j * 8;
        const int grp = 4 * w + (lane >> 3);
#pragma unroll
        for (int o = 0; o < 2; o++) {
            const int row = (grp & 7) + 8 * (o ^ hb) + 32 * (grp >> 3);
            pc.yoff[0][o] = row * 128 + ((j ^ (row & 7)) * 16);
            pc.yoff[1][o] = 8192 + row * 64 + (((j >> 1) ^ ((row >> 1) & 3)) * 16) + (j & 1) * 8;
        }
        pc.stat = sb + SM_STAT + (8 * w + (lane >> 2)) * 32;
        pc.own = pc.stat + (lane & 3) * 8;
        const int dstep = fresh_cta() & 8 ? 3 * CH * 2 : -3 * CH * 2;
        mbar_wait_c<0>(sb + SM_BAR + BAR_DW * 8);
        SMARK(8);
#pragma unroll
        for (int tap = 0; tap < 9; tap++) {
            const uint32_t dw = sb + SM_Y1 + (3 + tap % 3) * CH * 2 + (tap / 3 - 1) * dstep;
            lds128(pc.w[tap], dw + j * 16);
            asm volatile("ld.shared.v2.b32 {%0,%1}, [%2];" : "=r"(pc.w[tap][4]), "=r"(pc.w[tap][5]) : "r"(dw + 128 + j * 8) : "memory");
        }
#pragma unroll
        for (int tap = 0; tap < 9; tap++)
#pragma unroll
            for (int u = 0; u < 6; u++) pc.w[tap][u] = bf2_mul(pc.w[tap][u], TAP_SCALE_BF2);
        produce(pc, prm);
        TS(9);
        asm volatile("setmaxnreg.dec.sync.aligned.u32 %0;" ::"n"(EVEN_REGS));
        if (fresh_warp() == 12) {
            mbar_wait_c<0>(sb + SM_BAR + BAR_W2 * 8);
            if (fresh_cta() < CH) publish_bias(prm, fresh_cta(), lds32(sb + SM_RED + RED_EPOCH * 4) + 1);
        }
    } else {
        asm volatile("setmaxnreg.dec.sync.aligned.u32 %0;" ::"n"(CONSUMER_REGS));
        {
            const int tid = fresh_tid(), warp = fresh_warp();
            if (warp == 1) {
#pragma unroll
                for (int h = 0; h < 2; h++) {
                    const uint32_t bar = sb + SM_BAR + (h ? BAR_W1B : BAR_W1) * 8;
                    expect_tx(bar, CH * EX);
#pragma unroll
                    for (int q = h; q < 6; q += 2) tma_load_2d(sb + SM_W1 + q * 12288, &prm.w1_map, 64 * q, 0, bar);
                }
            }
            uint32_t cnt[2];
            asm volatile("ld.relaxed.gpu.global.v2.u32 {%0, %1}, [%2];" : "=r"(cnt[0]), "=r"(cnt[1]) : "l"(prm.g->count) : "memory");
            SMARK(0);
            if (warp == 2) {
                const RowCopy rc = row_copy(prm);
#pragma unroll 1
                for (int i = loop_init<0>(); i < NX - 1; i++) {
                    named_sync(6 + i, 160);
                    issue_row_load(rc, i + NX, i);
                }
            }
            if (tid == 256) {
                sts64(sb + SM_RED + RED_EPOCH * 4, cnt[0], cnt[1] / NUM_CTAS);
#pragma unroll
                for (int k = 0; k < BAR_DW; k++)
                    if (k != BAR_W1 && k != BAR_W1B) mbar_init(sb + SM_BAR + k * 8, k < BAR_TURN || k == BAR_STAT ? 1 : 4);
#pragma unroll
                for (int k = 0; k < 3; k++) mbar_arrive_if(sb + SM_BAR + (BAR_Y2FULL + k) * 8, true);
            }
            if (fresh_cta() == 0) *acc_word(prm, cnt[0] + 1, tid) = 0;
            if (fresh_cta() == 1) prm.g->sums[~(cnt[1] / NUM_CTAS) & 1][tid] = 0.0f;
            __syncwarp();
            SMARK(1);
            mbar_wait_c<0>(sb + SM_BAR + BAR_W1 * 8);
            SMARK(2);
        }

        const int tid = fresh_tid(), lane = tid & 31, wg = fresh_warp() >> 2, w = fresh_warp() & 3;
        float acc[2][2];
        const int c = 8 * (lane >> 4) + (lane & 7), ck = 2 * w + ((lane >> 3) & 1);
        consume(acc, sb + SM_W1 + 2 * wg * 12288 + c * 128 + ((ck ^ (c & 7)) * 16), prm.ydesc,
                prm.w1desc + (((2 * wg + 1) * 12288 + 5 * 2048) >> 4), wg * SLOT_BYTES, make_duty(prm, wg, w), w, lane, prm);
        publish_fast(prm, acc, lds32(sb + SM_RED + RED_EPOCH * 4), wg, w, lane);
        MARK(0);
        bulk_wait_all();
        asm volatile("bar.arrive 11, 512;" ::: "memory");
        if (wg == 0) TS(3);
        asm volatile("setmaxnreg.inc.sync.aligned.u32 %0;" ::"n"(EVEN_REGS));
    }

    {
        MARK(1);
        if (fresh_warp() >= 12) prepare_w2<true>(prm, nullptr);

        if (pass2_tiles(pass2_setup(), prm, 0)) {
            const float* exact = exact_sums(prm);
            if (fresh_warp() >= 12) prepare_w2<false>(prm, exact);
            pass2_tiles(pass2_setup(), prm, 1);
        }
        bulk_wait_read<0>();
        MARK(13);
    }
}

}

extern "C" void kernel_launch(void* const* d_in, const int* in_sizes, int n_in, void* d_out, int out_size) {
    (void)in_sizes; (void)n_in; (void)out_size;
    typedef CUresult (*EncodeFn)(CUtensorMap*, CUtensorMapDataType, cuuint32_t, void*, const cuuint64_t*, const cuuint64_t*,
                                 const cuuint32_t*, const cuuint32_t*, CUtensorMapInterleave, CUtensorMapSwizzle,
                                 CUtensorMapL2promotion, CUtensorMapFloatOOBfill);
    void* fn = nullptr;
    cudaDriverEntryPointQueryResult status;
    cudaGetDriverEntryPoint("cuTensorMapEncodeTiled", &fn, cudaEnableDefault, &status);
    const EncodeFn encode = (EncodeFn)fn;
    const cuuint32_t ones[2] = {1, 1};

    Params p;
    {
        const cuuint64_t dims[2] = {EX, CH}, strides[1] = {EX * 2};
        const cuuint32_t box[2] = {64, CH};
        encode(&p.w1_map, CU_TENSOR_MAP_DATA_TYPE_BFLOAT16, 2, d_in[2], dims, strides, box, ones,
               CU_TENSOR_MAP_INTERLEAVE_NONE, CU_TENSOR_MAP_SWIZZLE_128B, CU_TENSOR_MAP_L2_PROMOTION_NONE,
               CU_TENSOR_MAP_FLOAT_OOB_FILL_NONE);
    }
    {
        const cuuint64_t dims[2] = {CH, EX}, strides[1] = {CH * 2};
        const cuuint32_t box[2] = {32, 192};
        encode(&p.w2_map, CU_TENSOR_MAP_DATA_TYPE_BFLOAT16, 2, d_in[3], dims, strides, box, ones,
               CU_TENSOR_MAP_INTERLEAVE_NONE, CU_TENSOR_MAP_SWIZZLE_64B, CU_TENSOR_MAP_L2_PROMOTION_NONE,
               CU_TENSOR_MAP_FLOAT_OOB_FILL_NONE);
    }
    p.x = (const __nv_bfloat16*)d_in[0];
    p.dw = (const __nv_bfloat16*)d_in[1];
    p.w1 = (const __nv_bfloat16*)d_in[2];
    p.gamma = (const __nv_bfloat16*)d_in[4];
    p.beta = (const __nv_bfloat16*)d_in[5];
    p.out = (__nv_bfloat16*)d_out;
    cudaGetSymbolAddress((void**)&p.g, g_scratch);
    p.w1desc = desc_lo(sb + SM_W1, 12288);
    p.w2desc = desc_lo(sb + SM_W2, 24576);
    p.ydesc = desc_lo(sb + SM_Y1, 16);
    p.ydesc64[0] = (0x40000040ull << 32) | p.ydesc;
    p.ydesc64[1] = (0x80000020ull << 32) | (p.ydesc + 512);
    for (int k = 0; k < 3; k++) p.sel[k] = (8ull << 32) | desc_lo(sb + SM_SEL + k * 128, k == 2 ? 128 : 0);
    constexpr int smem_bytes = SM_TOTAL;
    cudaFuncSetAttribute(convnext_kernel, cudaFuncAttributeMaxDynamicSharedMemorySize, smem_bytes);
    convnext_kernel<<<NUM_CTAS, 512, smem_bytes>>>(p);
}
```

```cpp
#include <cuda.h>
#include <cuda_runtime.h>
#include <cuda_bf16.h>
#include <stdint.h>

namespace {

constexpr int IMG_W = 512, CH = 96, EX = 384;
constexpr int TILE_PX = 64;
constexpr int ROWS_PER_CTA = 32;
constexpr int NUM_CTAS = 128;
constexpr int HELPERS = 4;
constexpr int STEPS = ROWS_PER_CTA + 2;
constexpr int ROW_BYTES = IMG_W * CH * 2;

#define USE_HELPERS 1
#define FORCE_EXACT 0
constexpr int PRODUCER_REGS = 200, CONSUMER_REGS = 104, EVEN_REGS = 128;

constexpr int XHALF_BYTES = 34 * 192;
constexpr int XHALF_B = XHALF_BYTES + 64;
constexpr int XROW_BYTES = XHALF_B + XHALF_BYTES + 64;
constexpr int L2_AHEAD = 2;
constexpr int NX = 3;
constexpr int TILE_BYTES = TILE_PX * 192;

constexpr uint32_t sb = 1024;
constexpr int SM_W1 = 0;
constexpr int SM_W2 = 73728;
constexpr int SM_RING = 147456;
constexpr int SLOT_BYTES = 26624;
constexpr int SM_Y1 = SM_RING;
constexpr int SM_X = SM_Y1 + TILE_BYTES;
constexpr int SM_STAT = SM_X + XROW_BYTES;
constexpr int SM_BUF3 = SM_X + SLOT_BYTES, SM_SPARE = SM_X;
constexpr int SM_SEL = SM_RING + NX * SLOT_BYTES;
constexpr int SM_BIAS = SM_SEL + 512;
constexpr int SM_GAMMA = SM_BIAS + 384;
constexpr int SM_BETA = SM_GAMMA + EX * 2;
constexpr int SM_RED = SM_BETA + EX * 2;
constexpr int SM_BAR = SM_RED + 16;
constexpr int BAR_Y2FULL = 0, BAR_XSFULL = 4, BAR_W1 = 8, BAR_W2 = 9, BAR_W1B = 10, BAR_TURN = 11, BAR_ROWS = 51,
              BAR_STAT = 54, BAR_DW = 55, BAR_COUNT = 56;
constexpr int SM_GO = SM_BAR + BAR_COUNT * 8, GO_COUNT = ROWS_PER_CTA + 2 * NX;
constexpr int SM_YFULL = SM_GO + (GO_COUNT + 1) * 8;
constexpr int SM_TOTAL = SM_YFULL + (ROWS_PER_CTA + 1) * 8;
static_assert(SM_STAT + TILE_PX * 16 <= SM_RING + SLOT_BYTES && XROW_BYTES >= TILE_BYTES && SM_X % 1024 == 0, "ring layout");
static_assert(SM_TOTAL <= 232448, "smem budget");
static_assert(SM_STAT % 128 == 0 && SM_BIAS % 16 == 0 && SM_BAR % 8 == 0 && SLOT_BYTES % 1024 == 0, "alignment");

constexpr int RED_EPOCH = 0, RED_SCALE = 2;

constexpr float GELU_A = 0.32920349f;
constexpr uint32_t GELU_C_H2 = 0x40D940D9u;
constexpr float INV_2A = 1.0f / (2.0f * GELU_A);

constexpr uint32_t TAP_SCALE_BF2 = 0x2B802B80u;
constexpr float LN_EPS_SCALED = 1e-5f * 0x1p-80f;
constexpr float RSTD_SCALE = GELU_A * 0x1p-112f;

struct Scratch {
    unsigned long long acc[2][EX / 4 * 32];
    unsigned long long bias[CH];
    float sums[2][EX];
    uint4 zero_row[66 * 192 / 16];
    uint4 park[HELPERS][3][16][128];
    unsigned int count[2];
    unsigned int parked[NUM_CTAS];
};
__device__ __align__(256) Scratch g_scratch;
constexpr float ACC_LIMIT = 0x1p30f;

#define TS(k)
#define ASM_TS
#define MARK(k)
#define SMARK(k)
#define ASM_MARK
#define ASM_SMARK
#define ASM_TRC(it)

__device__ __forceinline__ void mbar_init(uint32_t bar, uint32_t count) {
    asm volatile("mbarrier.init.shared::cta.b64 [%0], %1;" ::"r"(bar), "r"(count) : "memory");
}
__device__ __forceinline__ void mbar_arrive_if(uint32_t bar, bool pred) {
    asm volatile("{\n.reg .pred p;\nsetp.ne.u32 p, %1, 0;\n@p mbarrier.arrive.shared::cta.b64 _, [%0];\n}\n"
                 ::"r"(bar), "r"((uint32_t)pred) : "memory");
}
__device__ __forceinline__ void mbar_wait(uint32_t bar, uint32_t parity) {
    asm volatile(
        "{\n.reg .pred p;\n.reg .u32 n;\n"
        "mbarrier.try_wait.parity.shared::cta.b64 p, [%0], %1;\n"
        "@p bra.uni WAIT_DONE;\n"
        "mov.u32 n, 0;\n"
        "WAIT_LOOP:\n"
        "mbarrier.try_wait.parity.shared::cta.b64 p, [%0], %1;\n"
        "@p bra.uni WAIT_DONE;\n"
        "mbarrier.try_wait.parity.shared::cta.b64 p, [%0], %1;\n"
        "@p bra.uni WAIT_DONE;\n"
        "mbarrier.try_wait.parity.shared::cta.b64 p, [%0], %1;\n"
        "@p bra.uni WAIT_DONE;\n"
        "add.u32 n, n, 1;\nsetp.lt.u32 p, n, 0x40000;\n"
        "@p bra.uni WAIT_LOOP;\n"
        "trap;\n"
        "WAIT_DONE:\n}\n"
        ::"r"(bar), "r"(parity) : "memory");
}
template <int PARITY> __device__ __forceinline__ void mbar_wait_c(uint32_t bar) {
    asm volatile(
        "{\n.reg .pred p;\n.reg .u32 n;\n"
        "mbarrier.try_wait.parity.shared::cta.b64 p, [%0], %1;\n"
        "@p bra.uni WAIT_DONE;\n"
        "mov.u32 n, 0;\n"
        "WAIT_LOOP:\n"
        "mbarrier.try_wait.parity.shared::cta.b64 p, [%0], %1;\n"
        "@p bra.uni WAIT_DONE;\n"
        "mbarrier.try_wait.parity.shared::cta.b64 p, [%0], %1;\n"
        "@p bra.uni WAIT_DONE;\n"
        "mbarrier.try_wait.parity.shared::cta.b64 p, [%0], %1;\n"
        "@p bra.uni WAIT_DONE;\n"
        "add.u32 n, n, 1;\nsetp.lt.u32 p, n, 0x40000;\n"
        "@p bra.uni WAIT_LOOP;\n"
        "trap;\n"
        "WAIT_DONE:\n}\n"
        ::"r"(bar), "n"(PARITY) : "memory");
}
#define ELECTED(body) "{\n.reg .pred p;\nelect.sync _|p, 0xffffffff;\n" body "}\n"
__device__ __forceinline__ void expect_tx(uint32_t bar, uint32_t bytes) {
    asm volatile(ELECTED("@p mbarrier.arrive.expect_tx.shared::cta.b64 _, [%0], %1;\n") ::"r"(bar), "r"(bytes) : "memory");
}
__device__ __forceinline__ void bulk_load(uint32_t dst, const void* src, uint32_t bytes, uint32_t bar) {
    asm volatile(ELECTED("@p cp.async.bulk.shared::cluster.global.mbarrier::complete_tx::bytes [%0], [%1], %2, [%3];\n")
                 ::"r"(dst), "l"(src), "r"(bytes), "r"(bar) : "memory");
}
__device__ __forceinline__ void bulk_prefetch(const void* src, uint32_t bytes) {
    asm volatile(ELECTED("@p cp.async.bulk.prefetch.L2.global [%0], %1;\n") ::"l"(src), "r"(bytes) : "memory");
}
__device__ __forceinline__ void tma_load_2d(uint32_t dst, const CUtensorMap* map, int c0, int c1, uint32_t bar) {
    asm volatile(ELECTED("@p cp.async.bulk.tensor.2d.shared::cluster.global.mbarrier::complete_tx::bytes [%0], [%1, {%2, %3}], [%4];\n")
                 ::"r"(dst), "l"(map), "r"(c0), "r"(c1), "r"(bar) : "memory");
}
template <int N> __device__ __forceinline__ void bulk_wait_read() {
    asm volatile("cp.async.bulk.wait_group.read %0;" ::"n"(N) : "memory");
}
__device__ __forceinline__ void bulk_wait_all() { asm volatile("cp.async.bulk.wait_group 0;" ::: "memory"); }
__device__ __forceinline__ void fence_async_smem() { asm volatile("fence.proxy.async.shared::cta;" ::: "memory"); }
__device__ __forceinline__ void named_sync(int id, int n) { asm volatile("bar.sync %0, %1;" ::"r"(id), "r"(n) : "memory"); }

__device__ __forceinline__ void sts64(uint32_t addr, uint32_t a, uint32_t b) {
    asm volatile("st.shared.v2.b32 [%0], {%1,%2};" ::"r"(addr), "r"(a), "r"(b) : "memory");
}
__device__ __forceinline__ void sts128(uint32_t addr, uint32_t a, uint32_t b, uint32_t c, uint32_t d) {
    asm volatile("st.shared.v4.b32 [%0], {%1,%2,%3,%4};" ::"r"(addr), "r"(a), "r"(b), "r"(c), "r"(d) : "memory");
}
__device__ __forceinline__ void ldsm4_t(uint32_t* r, uint32_t addr) {
    asm volatile("ldmatrix.sync.aligned.m8n8.x4.trans.shared.b16 {%0,%1,%2,%3}, [%4];"
                 : "=r"(r[0]), "=r"(r[1]), "=r"(r[2]), "=r"(r[3]) : "r"(addr) : "memory");
}
__device__ __forceinline__ void lds128(uint32_t* v, uint32_t addr) {
    asm volatile("ld.shared.v4.b32 {%0,%1,%2,%3}, [%4];"
                 : "=r"(v[0]), "=r"(v[1]), "=r"(v[2]), "=r"(v[3]) : "r"(addr) : "memory");
}
__device__ __forceinline__ uint32_t lds32(uint32_t addr) {
    uint32_t v; asm volatile("ld.shared.b32 %0, [%1];" : "=r"(v) : "r"(addr) : "memory"); return v;
}
__device__ __forceinline__ void sts32(uint32_t addr, uint32_t v) {
    asm volatile("st.shared.b32 [%0], %1;" ::"r"(addr), "r"(v) : "memory");
}

__device__ __forceinline__ uint32_t bf2_fma(uint32_t a, uint32_t b, uint32_t c) {
    uint32_t d; asm("fma.rn.bf16x2 %0, %1, %2, %3;" : "=r"(d) : "r"(a), "r"(b), "r"(c)); return d;
}
__device__ __forceinline__ uint32_t bf2_mul(uint32_t a, uint32_t b) {
    uint32_t d; asm("mul.rn.bf16x2 %0, %1, %2;" : "=r"(d) : "r"(a), "r"(b)); return d;
}
__device__ __forceinline__ uint32_t bf2_add(uint32_t a, uint32_t b) {
    uint32_t d; asm("add.rn.bf16x2 %0, %1, %2;" : "=r"(d) : "r"(a), "r"(b)); return d;
}
__device__ __forceinline__ uint32_t h2_fma(uint32_t a, uint32_t b, uint32_t c) {
    uint32_t d; asm("fma.rn.f16x2 %0, %1, %2, %3;" : "=r"(d) : "r"(a), "r"(b), "r"(c)); return d;
}
__device__ __forceinline__ uint32_t h2_mul(uint32_t a, uint32_t b) {
    uint32_t d; asm("mul.rn.f16x2 %0, %1, %2;" : "=r"(d) : "r"(a), "r"(b)); return d;
}
__device__ __forceinline__ uint32_t h2_tanh(uint32_t a) {
    uint32_t d; asm("tanh.approx.f16x2 %0, %1;" : "=r"(d) : "r"(a)); return d;
}
__device__ __forceinline__ float bf_lo(uint32_t v) { return __uint_as_float(v << 16); }
__device__ __forceinline__ float bf_hi(uint32_t v) { return __uint_as_float(v & 0xffff0000u); }
__device__ __forceinline__ uint32_t pack_h2(float lo, float hi) {
    uint32_t d; asm("cvt.rn.f16x2.f32 %0, %1, %2;" : "=r"(d) : "f"(hi), "f"(lo)); return d;
}
__device__ __forceinline__ uint32_t pack_bf2(float lo, float hi) {
    uint32_t d; asm("cvt.rn.bf16x2.f32 %0, %1, %2;" : "=r"(d) : "f"(hi), "f"(lo)); return d;
}
__device__ __forceinline__ void h2_unpack(uint32_t v, float& lo, float& hi) {
    asm("{\n.reg .b16 l, h;\nmov.b32 {l, h}, %2;\ncvt.f32.f16 %0, l;\ncvt.f32.f16 %1, h;\n}\n" : "=f"(lo), "=f"(hi) : "r"(v));
}

__device__ __forceinline__ uint32_t gelu2(uint32_t z) {
    uint32_t p = h2_fma(z, z, GELU_C_H2);
    uint32_t t = h2_tanh(h2_mul(z, p));
    return h2_fma(z, t, z);
}

__device__ __forceinline__ void wg_fence() { asm volatile("wgmma.fence.sync.aligned;" ::: "memory"); }
__device__ __forceinline__ void wg_commit() { asm volatile("wgmma.commit_group.sync.aligned;" ::: "memory"); }
template <int N> __device__ __forceinline__ void wg_wait() {
    asm volatile("wgmma.wait_group.sync.aligned %0;" ::"n"(N) : "memory");
}
template <int N> __device__ __forceinline__ void pin(uint32_t (&r)[N]) {
#pragma unroll
    for (int i = 0; i < N; i++) asm volatile("" : "+r"(r[i])::"memory");
}
constexpr uint32_t desc_lo(uint32_t addr, uint32_t lbo) { return ((addr & 0x3FFFF) >> 4) | ((lbo >> 4) << 16); }
template <uint32_t SBO, uint32_t SWZ> __device__ __forceinline__ uint64_t desc(uint32_t lo, uint32_t bytes) {
    return (((uint64_t)((SBO >> 4) | (SWZ << 30)) << 32) | lo) + (bytes >> 4);
}
__device__ __forceinline__ uint32_t fresh_tid() {
    uint32_t v; asm volatile("mov.u32 %0, %%tid.x;" : "=r"(v));
    return v;
}
template <uint32_t V> __device__ __forceinline__ uint32_t loop_init() {
    uint32_t v; asm volatile("mov.u32 %0, %1;" : "=r"(v) : "n"(V)); return v;
}
__device__ __forceinline__ int fresh_warp() {
    int v; asm volatile("shfl.sync.idx.b32 %0, %1, 0, 0x1f, 0xffffffff;" : "=r"(v) : "r"(fresh_tid() >> 5)); return v;
}
__device__ __forceinline__ uint32_t fresh_cta() {
    uint32_t v; asm volatile("mov.u32 %0, %%ctaid.x;" : "=r"(v)); return v;
}
__device__ __forceinline__ float sqrt_fast(float v) { float r; asm("sqrt.approx.f32 %0, %1;" : "=f"(r) : "f"(v)); return r; }

template <int TB>
__device__ __forceinline__ void wgmma_n64_h_set(uint32_t (&d)[16], const uint32_t* a, uint64_t desc) {
    asm volatile(
        "{\n.reg .pred p;\nsetp.ne.b32 p, 0, 0;\n"
        "wgmma.mma_async.sync.aligned.m64n64k16.f16.f16.f16 "
        "{%0,%1,%2,%3,%4,%5,%6,%7,%8,%9,%10,%11,%12,%13,%14,%15}, {%16,%17,%18,%19}, %20, p, 1, 1, %21;\n}\n"
        : "=r"(d[0]), "=r"(d[1]), "=r"(d[2]), "=r"(d[3]), "=r"(d[4]), "=r"(d[5]), "=r"(d[6]), "=r"(d[7]), "=r"(d[8]), "=r"(d[9]), "=r"(d[10]), "=r"(d[11]), "=r"(d[12]), "=r"(d[13]), "=r"(d[14]), "=r"(d[15])
        : "r"(a[0]), "r"(a[1]), "r"(a[2]), "r"(a[3]), "l"(desc), "n"(TB));
}
template <int TB>
__device__ __forceinline__ void wgmma_n64_h_acc(uint32_t (&d)[16], const uint32_t* a, uint64_t desc) {
    asm volatile(
        "{\n.reg .pred p;\nsetp.ne.b32 p, 1, 0;\n"
        "wgmma.mma_async.sync.aligned.m64n64k16.f16.f16.f16 "
        "{%0,%1,%2,%3,%4,%5,%6,%7,%8,%9,%10,%11,%12,%13,%14,%15}, {%16,%17,%18,%19}, %20, p, 1, 1, %21;\n}\n"
        : "+r"(d[0]), "+r"(d[1]), "+r"(d[2]), "+r"(d[3]), "+r"(d[4]), "+r"(d[5]), "+r"(d[6]), "+r"(d[7]), "+r"(d[8]), "+r"(d[9]), "+r"(d[10]), "+r"(d[11]), "+r"(d[12]), "+r"(d[13]), "+r"(d[14]), "+r"(d[15])
        : "r"(a[0]), "r"(a[1]), "r"(a[2]), "r"(a[3]), "l"(desc), "n"(TB));
}
__device__ __forceinline__ void wgmma_n64_h_acc_ss(uint32_t (&d)[16], uint64_t adesc, uint64_t desc) {
    asm volatile(
        "{\n.reg .pred p;\nsetp.ne.b32 p, 1, 0;\n"
        "wgmma.mma_async.sync.aligned.m64n64k16.f16.f16.f16 "
        "{%0,%1,%2,%3,%4,%5,%6,%7,%8,%9,%10,%11,%12,%13,%14,%15}, %16, %17, p, 1, 1, 1, 0;\n}\n"
        : "+r"(d[0]), "+r"(d[1]), "+r"(d[2]), "+r"(d[3]), "+r"(d[4]), "+r"(d[5]), "+r"(d[6]), "+r"(d[7]), "+r"(d[8]), "+r"(d[9]), "+r"(d[10]), "+r"(d[11]), "+r"(d[12]), "+r"(d[13]), "+r"(d[14]), "+r"(d[15])
        : "l"(adesc), "l"(desc));
}

struct Params {
    CUtensorMap w1_map, w2_map;
    const __nv_bfloat16* x;
    const __nv_bfloat16* dw;
    const __nv_bfloat16* w1;
    const __nv_bfloat16* gamma;
    const __nv_bfloat16* beta;
    __nv_bfloat16* out;
    Scratch* g;
    uint64_t ydesc64[2];
    uint64_t sel[3];
    uint32_t w1desc, w2desc, ydesc;
    uint32_t helper_desc[2];
    uint32_t ctas;
};

__device__ __forceinline__ int cta_stride(uint32_t cta) { return cta & 8 ? ROW_BYTES : -ROW_BYTES; }
__device__ __forceinline__ uint32_t cta_tile0(uint32_t cta) {
    return ((cta >> 3) * ROWS_PER_CTA + (cta & 8 ? 0 : ROWS_PER_CTA - 1)) * ROW_BYTES + (cta & 7) * TILE_BYTES;
}

struct Producer {
    uint32_t w[9][6];
    uint32_t xoff[2];
    uint32_t yoff[2][2];
    uint32_t stat, own;
    int lane;
};

struct RowCopy {
    const char* x0;
    char* y0;
    const char* zeros;
    uint32_t cut0, cut1;
    int stride, last;
};
__device__ __forceinline__ RowCopy row_copy(const Params& prm) {
    const uint32_t cta = fresh_cta(), strip = cta & 7, t0 = cta_tile0(cta);
    RowCopy r;
    r.stride = cta_stride(cta);
    r.x0 = (const char*)prm.x + (t0 - r.stride) - 192;
    r.y0 = (char*)prm.out + t0;
    r.zeros = (const char*)prm.g->zero_row;
    r.cut0 = strip == 0 ? 192 : 0;
    r.cut1 = strip == 7 ? 192 : 0;
    r.last = cta - 8 >= NUM_CTAS - 16 ? STEPS - 2 : STEPS - 1;
    return r;
}
__device__ __forceinline__ void issue_row_load(const RowCopy& r, int i, uint32_t slot) {
    const char* src = r.x0 + i * r.stride;
    const uint32_t bar = sb + SM_GO + i * 8, dst = sb + SM_X + slot * SLOT_BYTES;
    expect_tx(bar, XHALF_BYTES - r.cut0);
    bulk_load(dst + r.cut0, src + r.cut0, XHALF_BYTES - r.cut0, bar);
    expect_tx(bar, XHALF_BYTES - r.cut1);
    bulk_load(dst + XHALF_B, src + 32 * 192, XHALF_BYTES - r.cut1, bar);
}

__device__ __forceinline__ float quad_sum(float v) {
    v += __shfl_xor_sync(0xffffffffu, v, 1);
    v += __shfl_xor_sync(0xffffffffu, v, 2);
    return v;
}

__device__ __forceinline__ void load_x(uint32_t (&v)[6][6], const Producer& c, uint32_t row) {
#pragma unroll
    for (int k = 0; k < 6; k++) {
        asm volatile("ld.shared.v4.b32 {%0,%1,%2,%3}, [%4];"
                     : "=r"(v[k][0]), "=r"(v[k][1]), "=r"(v[k][2]), "=r"(v[k][3]) : "r"(row + c.xoff[0] + k * 192));
        asm volatile("ld.shared.v2.b32 {%0,%1}, [%2];" : "=r"(v[k][4]), "=r"(v[k][5]) : "r"(row + c.xoff[1] + k * 192));
    }
}
template <int DY, int STRIDE>
__device__ __forceinline__ void conv_row(uint32_t (&dst)[24], const uint32_t* src, const uint32_t (&v)[6][6], const Producer& c) {
#pragma unroll
    for (int o = 0; o < 4; o++)
#pragma unroll
        for (int u = 0; u < 6; u++)
            dst[o * 6 + u] = bf2_fma(v[o + 2][u], c.w[3 * DY + 2][u], bf2_fma(v[o + 1][u], c.w[3 * DY + 1][u],
                             bf2_fma(v[o][u], c.w[3 * DY][u], STRIDE ? src[o * 6 + u] : src[2 * o + 1])));
}
#define HAND_OVER(name, base, r) asm volatile("mov.b32 " name "%6, %0; mov.b32 " name "%7, %1; mov.b32 " name "%8, %2;\n" \
    "mov.b32 " name "%9, %3; mov.b32 " name "%10, %4; mov.b32 " name "%11, %5;" ::"r"((r)[0]), "r"((r)[1]), "r"((r)[2]), \
    "r"((r)[3]), "r"((r)[4]), "r"((r)[5]), "n"(base), "n"(base + 1), "n"(base + 2), "n"(base + 3), "n"(base + 4), "n"(base + 5))
template <int K> __device__ __forceinline__ void hand_over(const Producer& c, const uint32_t (&B)[24], const uint32_t (&C)[24],
                                                           const uint32_t (&v)[6][6]) {
    HAND_OVER("pw", K * 6, c.w[K]);
    if (K < 6) HAND_OVER("pv", K * 6, v[K % 6]);
    if (K < 4) { HAND_OVER("pb", K * 6, B + K % 4 * 6); HAND_OVER("pc", K * 6, C + K % 4 * 6); }
    if constexpr (K < 8) hand_over<K + 1>(c, B, C, v);
}
__device__ __forceinline__ void produce_tiles(const Producer& c, const Params& prm) {
    asm volatile(
        "{\n"
        ".reg .b32 pa<24>, pq<4>, m<6>, y<6>, rr, mm, t, so, ad, tt, cnt;\n"
        ".reg .b16 xl, xh;\n"
        ".reg .f32 d<4>, us, s0, s1, f0, f1, kq;\n"
        ".reg .pred pt, pf, pr, pw, pl, po, pe;\n"
        "setp.ne.b32 pt, 1, 0; setp.ne.b32 pf, 0, 0; setp.eq.u32 pl, %8, 0; and.b32 tt, %8, 1; setp.ne.u32 po, tt, 0;\n"
        "and.b32 tt, %8, 4; setp.ne.u32 pr, tt, 0; selp.f32 kq, 0f3F802D41, 0f3F7FA57E, pr;\n"
        "mov.u32 t, 0; mov.u32 so, 0;\n"
        "setp.eq.u32 pr, %12, 0;\n"
        "@pr bra.uni RARE;\n"
        "LOOP:\n"
        ASM_TRC("t")
        "fma.rn.bf16x2 pa0, pv0, pw36, pb0; fma.rn.bf16x2 pa1, pv1, pw37, pb1; fma.rn.bf16x2 pa2, pv2, pw38, pb2; fma.rn.bf16x2 pa3, pv3, pw39, pb3; fma.rn.bf16x2 pa4, pv4, pw40, pb4; fma.rn.bf16x2 pa5, pv5, pw41, pb5;\n"
        "fma.rn.bf16x2 pa6, pv6, pw36, pb6; fma.rn.bf16x2 pa7, pv7, pw37, pb7; fma.rn.bf16x2 pa8, pv8, pw38, pb8; fma.rn.bf16x2 pa9, pv9, pw39, pb9; fma.rn.bf16x2 pa10, pv10, pw40, pb10; fma.rn.bf16x2 pa11, pv11, pw41, pb11;\n"
        "fma.rn.bf16x2 pa12, pv12, pw36, pb12; fma.rn.bf16x2 pa13, pv13, pw37, pb13; fma.rn.bf16x2 pa14, pv14, pw38, pb14; fma.rn.bf16x2 pa15, pv15, pw39, pb15; fma.rn.bf16x2 pa16, pv16, pw40, pb16; fma.rn.bf16x2 pa17, pv17, pw41, pb17;\n"
        "fma.rn.bf16x2 pa18, pv18, pw36, pb18; fma.rn.bf16x2 pa19, pv19, pw37, pb19; fma.rn.bf16x2 pa20, pv20, pw38, pb20; fma.rn.bf16x2 pa21, pv21, pw39, pb21; fma.rn.bf16x2 pa22, pv22, pw40, pb22; fma.rn.bf16x2 pa23, pv23, pw41, pb23;\n"
        "fma.rn.bf16x2 pa0, pv6, pw42, pa0; fma.rn.bf16x2 pa1, pv7, pw43, pa1; fma.rn.bf16x2 pa2, pv8, pw44, pa2; fma.rn.bf16x2 pa3, pv9, pw45, pa3; fma.rn.bf16x2 pa4, pv10, pw46, pa4; fma.rn.bf16x2 pa5, pv11, pw47, pa5;\n"
        "fma.rn.bf16x2 pa6, pv12, pw42, pa6; fma.rn.bf16x2 pa7, pv13, pw43, pa7; fma.rn.bf16x2 pa8, pv14, pw44, pa8; fma.rn.bf16x2 pa9, pv15, pw45, pa9; fma.rn.bf16x2 pa10, pv16, pw46, pa10; fma.rn.bf16x2 pa11, pv17, pw47, pa11;\n"
        "fma.rn.bf16x2 pa12, pv18, pw42, pa12; fma.rn.bf16x2 pa13, pv19, pw43, pa13; fma.rn.bf16x2 pa14, pv20, pw44, pa14; fma.rn.bf16x2 pa15, pv21, pw45, pa15; fma.rn.bf16x2 pa16, pv22, pw46, pa16; fma.rn.bf16x2 pa17, pv23, pw47, pa17;\n"
        "fma.rn.bf16x2 pa18, pv24, pw42, pa18; fma.rn.bf16x2 pa19, pv25, pw43, pa19; fma.rn.bf16x2 pa20, pv26, pw44, pa20; fma.rn.bf16x2 pa21, pv27, pw45, pa21; fma.rn.bf16x2 pa22, pv28, pw46, pa22; fma.rn.bf16x2 pa23, pv29, pw47, pa23;\n"
        "fma.rn.bf16x2 pa0, pv12, pw48, pa0; fma.rn.bf16x2 pa1, pv13, pw49, pa1; fma.rn.bf16x2 pa2, pv14, pw50, pa2; fma.rn.bf16x2 pa3, pv15, pw51, pa3; fma.rn.bf16x2 pa4, pv16, pw52, pa4; fma.rn.bf16x2 pa5, pv17, pw53, pa5;\n"
        "fma.rn.bf16x2 pa6, pv18, pw48, pa6; fma.rn.bf16x2 pa7, pv19, pw49, pa7; fma.rn.bf16x2 pa8, pv20, pw50, pa8; fma.rn.bf16x2 pa9, pv21, pw51, pa9; fma.rn.bf16x2 pa10, pv22, pw52, pa10; fma.rn.bf16x2 pa11, pv23, pw53, pa11;\n"
        "fma.rn.bf16x2 pa12, pv24, pw48, pa12; fma.rn.bf16x2 pa13, pv25, pw49, pa13; fma.rn.bf16x2 pa14, pv26, pw50, pa14; fma.rn.bf16x2 pa15, pv27, pw51, pa15; fma.rn.bf16x2 pa16, pv28, pw52, pa16; fma.rn.bf16x2 pa17, pv29, pw53, pa17;\n"
        "fma.rn.bf16x2 pa18, pv30, pw48, pa18; fma.rn.bf16x2 pa19, pv31, pw49, pa19; fma.rn.bf16x2 pa20, pv32, pw50, pa20; fma.rn.bf16x2 pa21, pv33, pw51, pa21; fma.rn.bf16x2 pa22, pv34, pw52, pa22; fma.rn.bf16x2 pa23, pv35, pw53, pa23;\n"
        "mul.rn.bf16x2 pq0, pa0, pa0; fma.rn.bf16x2 pq0, pa1, pa1, pq0; fma.rn.bf16x2 pq0, pa2, pa2, pq0; fma.rn.bf16x2 pq0, pa3, pa3, pq0; fma.rn.bf16x2 pq0, pa4, pa4, pq0; fma.rn.bf16x2 pq0, pa5, pa5, pq0;\n"
        "mul.rn.bf16x2 pq1, pa6, pa6; fma.rn.bf16x2 pq1, pa7, pa7, pq1; fma.rn.bf16x2 pq1, pa8, pa8, pq1; fma.rn.bf16x2 pq1, pa9, pa9, pq1; fma.rn.bf16x2 pq1, pa10, pa10, pq1; fma.rn.bf16x2 pq1, pa11, pa11, pq1;\n"
        "mul.rn.bf16x2 pq2, pa12, pa12; fma.rn.bf16x2 pq2, pa13, pa13, pq2; fma.rn.bf16x2 pq2, pa14, pa14, pq2; fma.rn.bf16x2 pq2, pa15, pa15, pq2; fma.rn.bf16x2 pq2, pa16, pa16, pq2; fma.rn.bf16x2 pq2, pa17, pa17, pq2;\n"
        "mul.rn.bf16x2 pq3, pa18, pa18; fma.rn.bf16x2 pq3, pa19, pa19, pq3; fma.rn.bf16x2 pq3, pa20, pa20, pq3; fma.rn.bf16x2 pq3, pa21, pa21, pq3; fma.rn.bf16x2 pq3, pa22, pa22, pq3; fma.rn.bf16x2 pq3, pa23, pa23, pq3;\n"
        "B0:\n"
        "wgmma.fence.sync.aligned;\n"
        "wgmma.mma_async.sync.aligned.m64n8k16.f32.bf16.bf16 {d0,d1,d2,d3}, {pa0,pa6,pa1,pa7}, %9, pf, 1, 1, 0;\n"
        "wgmma.mma_async.sync.aligned.m64n8k16.f32.bf16.bf16 {d0,d1,d2,d3}, {pa2,pa8,pa3,pa9}, %9, pt, 1, 1, 0;\n"
        "wgmma.mma_async.sync.aligned.m64n8k16.f32.bf16.bf16 {d0,d1,d2,d3}, {pa4,pa10,pa5,pa11}, %9, pt, 1, 1, 0;\n"
        "wgmma.mma_async.sync.aligned.m64n8k16.f32.bf16.bf16 {d0,d1,d2,d3}, {pa12,pa18,pa13,pa19}, %10, pt, 1, 1, 0;\n"
        "wgmma.mma_async.sync.aligned.m64n8k16.f32.bf16.bf16 {d0,d1,d2,d3}, {pa14,pa20,pa15,pa21}, %10, pt, 1, 1, 0;\n"
        "wgmma.mma_async.sync.aligned.m64n8k16.f32.bf16.bf16 {d0,d1,d2,d3}, {pa16,pa22,pa17,pa23}, %10, pt, 1, 1, 0;\n"
        "wgmma.mma_async.sync.aligned.m64n8k16.f32.bf16.bf16 {d0,d1,d2,d3}, {pq0,pq1,pq2,pq3}, %11, pt, 1, 1, 0;\n"
        "wgmma.commit_group.sync.aligned;\n"
        "fence.proxy.async.shared::cta;\n"
        "@pl mbarrier.arrive.shared::cta.b64 _, [t+231552];\n"
        "add.u32 ad, %7, so; ld.shared.f32 us, [ad+4];\n"
        "fma.rn.bf16x2 pb0, pv0, pw18, pc0; fma.rn.bf16x2 pb1, pv1, pw19, pc1; fma.rn.bf16x2 pb2, pv2, pw20, pc2; fma.rn.bf16x2 pb3, pv3, pw21, pc3; fma.rn.bf16x2 pb4, pv4, pw22, pc4; fma.rn.bf16x2 pb5, pv5, pw23, pc5;\n"
        "fma.rn.bf16x2 pb6, pv6, pw18, pc6; fma.rn.bf16x2 pb7, pv7, pw19, pc7; fma.rn.bf16x2 pb8, pv8, pw20, pc8; fma.rn.bf16x2 pb9, pv9, pw21, pc9; fma.rn.bf16x2 pb10, pv10, pw22, pc10; fma.rn.bf16x2 pb11, pv11, pw23, pc11;\n"
        "fma.rn.bf16x2 pb0, pv6, pw24, pb0; fma.rn.bf16x2 pb1, pv7, pw25, pb1; fma.rn.bf16x2 pb2, pv8, pw26, pb2; fma.rn.bf16x2 pb3, pv9, pw27, pb3; fma.rn.bf16x2 pb4, pv10, pw28, pb4; fma.rn.bf16x2 pb5, pv11, pw29, pb5;\n"
        "fma.rn.bf16x2 pb6, pv12, pw24, pb6; fma.rn.bf16x2 pb7, pv13, pw25, pb7; fma.rn.bf16x2 pb8, pv14, pw26, pb8; fma.rn.bf16x2 pb9, pv15, pw27, pb9; fma.rn.bf16x2 pb10, pv16, pw28, pb10; fma.rn.bf16x2 pb11, pv17, pw29, pb11;\n"
        "fma.rn.bf16x2 pb0, pv12, pw30, pb0; fma.rn.bf16x2 pb1, pv13, pw31, pb1; fma.rn.bf16x2 pb2, pv14, pw32, pb2; fma.rn.bf16x2 pb3, pv15, pw33, pb3; fma.rn.bf16x2 pb4, pv16, pw34, pb4; fma.rn.bf16x2 pb5, pv17, pw35, pb5;\n"
        "fma.rn.bf16x2 pb6, pv18, pw30, pb6; fma.rn.bf16x2 pb7, pv19, pw31, pb7; fma.rn.bf16x2 pb8, pv20, pw32, pb8; fma.rn.bf16x2 pb9, pv21, pw33, pb9; fma.rn.bf16x2 pb10, pv22, pw34, pb10; fma.rn.bf16x2 pb11, pv23, pw35, pb11;\n"
        "B1:\n"
        "fma.rn.bf16x2 pb12, pv12, pw18, pc12; fma.rn.bf16x2 pb13, pv13, pw19, pc13; fma.rn.bf16x2 pb14, pv14, pw20, pc14; fma.rn.bf16x2 pb15, pv15, pw21, pc15; fma.rn.bf16x2 pb16, pv16, pw22, pc16; fma.rn.bf16x2 pb17, pv17, pw23, pc17;\n"
        "fma.rn.bf16x2 pb18, pv18, pw18, pc18; fma.rn.bf16x2 pb19, pv19, pw19, pc19; fma.rn.bf16x2 pb20, pv20, pw20, pc20; fma.rn.bf16x2 pb21, pv21, pw21, pc21; fma.rn.bf16x2 pb22, pv22, pw22, pc22; fma.rn.bf16x2 pb23, pv23, pw23, pc23;\n"
        "fma.rn.bf16x2 pb12, pv18, pw24, pb12; fma.rn.bf16x2 pb13, pv19, pw25, pb13; fma.rn.bf16x2 pb14, pv20, pw26, pb14; fma.rn.bf16x2 pb15, pv21, pw27, pb15; fma.rn.bf16x2 pb16, pv22, pw28, pb16; fma.rn.bf16x2 pb17, pv23, pw29, pb17;\n"
        "fma.rn.bf16x2 pb18, pv24, pw24, pb18; fma.rn.bf16x2 pb19, pv25, pw25, pb19; fma.rn.bf16x2 pb20, pv26, pw26, pb20; fma.rn.bf16x2 pb21, pv27, pw27, pb21; fma.rn.bf16x2 pb22, pv28, pw28, pb22; fma.rn.bf16x2 pb23, pv29, pw29, pb23;\n"
        "fma.rn.bf16x2 pb12, pv24, pw30, pb12; fma.rn.bf16x2 pb13, pv25, pw31, pb13; fma.rn.bf16x2 pb14, pv26, pw32, pb14; fma.rn.bf16x2 pb15, pv27, pw33, pb15; fma.rn.bf16x2 pb16, pv28, pw34, pb16; fma.rn.bf16x2 pb17, pv29, pw35, pb17;\n"
        "fma.rn.bf16x2 pb18, pv30, pw30, pb18; fma.rn.bf16x2 pb19, pv31, pw31, pb19; fma.rn.bf16x2 pb20, pv32, pw32, pb20; fma.rn.bf16x2 pb21, pv33, pw33, pb21; fma.rn.bf16x2 pb22, pv34, pw34, pb22; fma.rn.bf16x2 pb23, pv35, pw35, pb23;\n"
        "C0:\n"
        "wgmma.wait_group.sync.aligned 0;\n"
        "selp.f32 s0, d2, d0, po; selp.f32 s1, d3, d1, po;\n"
        "shfl.sync.bfly.b32 f0, s0, 4, 0x1f, 0xffffffff; shfl.sync.bfly.b32 f1, s1, 4, 0x1f, 0xffffffff;\n"
        "fma.rn.bf16x2 pc0, pv0, pw0, ps1; fma.rn.bf16x2 pc1, pv1, pw1, ps1; fma.rn.bf16x2 pc2, pv2, pw2, ps1; fma.rn.bf16x2 pc3, pv3, pw3, ps1; fma.rn.bf16x2 pc4, pv4, pw4, ps1; fma.rn.bf16x2 pc5, pv5, pw5, ps1;\n"
        "fma.rn.bf16x2 pc6, pv6, pw0, ps3; fma.rn.bf16x2 pc7, pv7, pw1, ps3; fma.rn.bf16x2 pc8, pv8, pw2, ps3; fma.rn.bf16x2 pc9, pv9, pw3, ps3; fma.rn.bf16x2 pc10, pv10, pw4, ps3; fma.rn.bf16x2 pc11, pv11, pw5, ps3;\n"
        "fma.rn.bf16x2 pc12, pv12, pw0, ps5; fma.rn.bf16x2 pc13, pv13, pw1, ps5; fma.rn.bf16x2 pc14, pv14, pw2, ps5; fma.rn.bf16x2 pc15, pv15, pw3, ps5; fma.rn.bf16x2 pc16, pv16, pw4, ps5; fma.rn.bf16x2 pc17, pv17, pw5, ps5;\n"
        "fma.rn.bf16x2 pc18, pv18, pw0, ps7; fma.rn.bf16x2 pc19, pv19, pw1, ps7; fma.rn.bf16x2 pc20, pv20, pw2, ps7; fma.rn.bf16x2 pc21, pv21, pw3, ps7; fma.rn.bf16x2 pc22, pv22, pw4, ps7; fma.rn.bf16x2 pc23, pv23, pw5, ps7;\n"
        "fma.rn.bf16x2 pc0, pv6, pw6, pc0; fma.rn.bf16x2 pc1, pv7, pw7, pc1; fma.rn.bf16x2 pc2, pv8, pw8, pc2; fma.rn.bf16x2 pc3, pv9, pw9, pc3; fma.rn.bf16x2 pc4, pv10, pw10, pc4; fma.rn.bf16x2 pc5, pv11, pw11, pc5;\n"
        "fma.rn.bf16x2 pc6, pv12, pw6, pc6; fma.rn.bf16x2 pc7, pv13, pw7, pc7; fma.rn.bf16x2 pc8, pv14, pw8, pc8; fma.rn.bf16x2 pc9, pv15, pw9, pc9; fma.rn.bf16x2 pc10, pv16, pw10, pc10; fma.rn.bf16x2 pc11, pv17, pw11, pc11;\n"
        "fma.rn.bf16x2 pc12, pv18, pw6, pc12; fma.rn.bf16x2 pc13, pv19, pw7, pc13; fma.rn.bf16x2 pc14, pv20, pw8, pc14; fma.rn.bf16x2 pc15, pv21, pw9, pc15; fma.rn.bf16x2 pc16, pv22, pw10, pc16; fma.rn.bf16x2 pc17, pv23, pw11, pc17;\n"
        "fma.rn.bf16x2 pc18, pv24, pw6, pc18; fma.rn.bf16x2 pc19, pv25, pw7, pc19; fma.rn.bf16x2 pc20, pv26, pw8, pc20; fma.rn.bf16x2 pc21, pv27, pw9, pc21; fma.rn.bf16x2 pc22, pv28, pw10, pc22; fma.rn.bf16x2 pc23, pv29, pw11, pc23;\n"
        "fma.rn.bf16x2 pc0, pv12, pw12, pc0; fma.rn.bf16x2 pc1, pv13, pw13, pc1; fma.rn.bf16x2 pc2, pv14, pw14, pc2; fma.rn.bf16x2 pc3, pv15, pw15, pc3; fma.rn.bf16x2 pc4, pv16, pw16, pc4; fma.rn.bf16x2 pc5, pv17, pw17, pc5;\n"
        "fma.rn.bf16x2 pc6, pv18, pw12, pc6; fma.rn.bf16x2 pc7, pv19, pw13, pc7; fma.rn.bf16x2 pc8, pv20, pw14, pc8; fma.rn.bf16x2 pc9, pv21, pw15, pc9; fma.rn.bf16x2 pc10, pv22, pw16, pc10; fma.rn.bf16x2 pc11, pv23, pw17, pc11;\n"
        "fma.rn.bf16x2 pc12, pv24, pw12, pc12; fma.rn.bf16x2 pc13, pv25, pw13, pc13; fma.rn.bf16x2 pc14, pv26, pw14, pc14; fma.rn.bf16x2 pc15, pv27, pw15, pc15; fma.rn.bf16x2 pc16, pv28, pw16, pc16; fma.rn.bf16x2 pc17, pv29, pw17, pc17;\n"
        "fma.rn.bf16x2 pc18, pv30, pw12, pc18; fma.rn.bf16x2 pc19, pv31, pw13, pc19; fma.rn.bf16x2 pc20, pv32, pw14, pc20; fma.rn.bf16x2 pc21, pv33, pw15, pc21; fma.rn.bf16x2 pc22, pv34, pw16, pc22; fma.rn.bf16x2 pc23, pv35, pw17, pc23;\n"
        "add.f32 s0, s0, f0; add.f32 s1, s1, f1; mul.f32 s0, s0, 0fBC2AAAAB;\n"
        "neg.f32 f0, s0; fma.rn.f32 f0, f0, s0, %13; fma.rn.f32 f0, s1, 0f3C2AAAAB, f0; max.f32 f0, f0, %13;\n"
        "rsqrt.approx.ftz.f32 f0, f0; mul.f32 f0, f0, %14; cvt.rn.bf16x2.f32 tt, f0, 0f00000000; mov.b32 f0, tt;\n"
        "mul.f32 f1, s0, kq; mul.f32 f1, f1, f0; cvt.rn.bf16x2.f32 tt, f1, f0; add.f32 us, us, s0; cvt.rn.bf16x2.f32 mm, us, us;\n"
        "add.u32 ad, %7, so; st.shared.v2.b32 [ad], {tt, mm};\n"
        "add.u32 ad, %6, so; ld.shared.v4.b32 {ps0,ps1,ps2,ps3}, [ad]; ld.shared.v4.b32 {ps4,ps5,ps6,ps7}, [ad+16];\n"
        "mbarrier.try_wait.parity.shared::cta.b64 pw, [t+231272], 0;\n"
        "N0:\n"
        "@!pw bra.uni SPIN;\n"
        "BACK:\n"
        "add.u32 ad, %0, so; ld.shared.v4.b32 {pv0,pv1,pv2,pv3}, [ad+0];\n"
        "add.u32 ad, %1, so; ld.shared.v2.b32 {pv4,pv5}, [ad+0];\n"
        "add.u32 ad, %0, so; ld.shared.v4.b32 {pv6,pv7,pv8,pv9}, [ad+192];\n"
        "add.u32 ad, %1, so; ld.shared.v2.b32 {pv10,pv11}, [ad+192];\n"
        "mov.b32 {xl, xh}, ps0; mov.b32 rr, {xl, xl}; mov.b32 mm, {xh, xh}; fma.rn.bf16x2 pa0, pa0, rr, mm; fma.rn.bf16x2 pa1, pa1, rr, mm; fma.rn.bf16x2 pa2, pa2, rr, mm; fma.rn.bf16x2 pa3, pa3, rr, mm; fma.rn.bf16x2 pa4, pa4, rr, mm; fma.rn.bf16x2 pa5, pa5, rr, mm;\n"
        "and.b32 m0, pa0, 0x7fff7fff; and.b32 m1, pa1, 0x7fff7fff; and.b32 m2, pa2, 0x7fff7fff; and.b32 m3, pa3, 0x7fff7fff; and.b32 m4, pa4, 0x7fff7fff; and.b32 m5, pa5, 0x7fff7fff;\n"
        "mad.lo.u32 y0, m0, 7, pa0; mad.lo.u32 y1, m1, 7, pa1; mad.lo.u32 y2, m2, 7, pa2; mad.lo.u32 y3, m3, 7, pa3; mad.lo.u32 y4, m4, 7, pa4; mad.lo.u32 y5, m5, 7, pa5;\n"
        "add.u32 ad, %2, so; st.shared.v4.b32 [ad+0], {y0,y1,y2,y3};\n"
        "add.u32 ad, %4, so; st.shared.v2.b32 [ad+0], {y4,y5};\n"
        "N1:\n"
        "add.u32 ad, %0, so; ld.shared.v4.b32 {pv12,pv13,pv14,pv15}, [ad+384];\n"
        "add.u32 ad, %1, so; ld.shared.v2.b32 {pv16,pv17}, [ad+384];\n"
        "add.u32 ad, %0, so; ld.shared.v4.b32 {pv18,pv19,pv20,pv21}, [ad+576];\n"
        "add.u32 ad, %1, so; ld.shared.v2.b32 {pv22,pv23}, [ad+576];\n"
        "mov.b32 {xl, xh}, ps2; mov.b32 rr, {xl, xl}; mov.b32 mm, {xh, xh}; fma.rn.bf16x2 pa6, pa6, rr, mm; fma.rn.bf16x2 pa7, pa7, rr, mm; fma.rn.bf16x2 pa8, pa8, rr, mm; fma.rn.bf16x2 pa9, pa9, rr, mm; fma.rn.bf16x2 pa10, pa10, rr, mm; fma.rn.bf16x2 pa11, pa11, rr, mm;\n"
        "and.b32 m0, pa6, 0x7fff7fff; and.b32 m1, pa7, 0x7fff7fff; and.b32 m2, pa8, 0x7fff7fff; and.b32 m3, pa9, 0x7fff7fff; and.b32 m4, pa10, 0x7fff7fff; and.b32 m5, pa11, 0x7fff7fff;\n"
        "mad.lo.u32 y0, m0, 7, pa6; mad.lo.u32 y1, m1, 7, pa7; mad.lo.u32 y2, m2, 7, pa8; mad.lo.u32 y3, m3, 7, pa9; mad.lo.u32 y4, m4, 7, pa10; mad.lo.u32 y5, m5, 7, pa11;\n"
        "add.u32 ad, %3, so; st.shared.v4.b32 [ad+0], {y0,y1,y2,y3};\n"
        "add.u32 ad, %5, so; st.shared.v2.b32 [ad+0], {y4,y5};\n"
        "N2:\n"
        "add.u32 ad, %0, so; ld.shared.v4.b32 {pv24,pv25,pv26,pv27}, [ad+768];\n"
        "add.u32 ad, %1, so; ld.shared.v2.b32 {pv28,pv29}, [ad+768];\n"
        "mov.b32 {xl, xh}, ps4; mov.b32 rr, {xl, xl}; mov.b32 mm, {xh, xh}; fma.rn.bf16x2 pa12, pa12, rr, mm; fma.rn.bf16x2 pa13, pa13, rr, mm; fma.rn.bf16x2 pa14, pa14, rr, mm; fma.rn.bf16x2 pa15, pa15, rr, mm; fma.rn.bf16x2 pa16, pa16, rr, mm; fma.rn.bf16x2 pa17, pa17, rr, mm;\n"
        "and.b32 m0, pa12, 0x7fff7fff; and.b32 m1, pa13, 0x7fff7fff; and.b32 m2, pa14, 0x7fff7fff; and.b32 m3, pa15, 0x7fff7fff; and.b32 m4, pa16, 0x7fff7fff; and.b32 m5, pa17, 0x7fff7fff;\n"
        "mad.lo.u32 y0, m0, 7, pa12; mad.lo.u32 y1, m1, 7, pa13; mad.lo.u32 y2, m2, 7, pa14; mad.lo.u32 y3, m3, 7, pa15; mad.lo.u32 y4, m4, 7, pa16; mad.lo.u32 y5, m5, 7, pa17;\n"
        "add.u32 ad, %2, so; st.shared.v4.b32 [ad+2048], {y0,y1,y2,y3};\n"
        "add.u32 ad, %4, so; st.shared.v2.b32 [ad+1024], {y4,y5};\n"
        "N3:\n"
        "add.u32 ad, %0, so; ld.shared.v4.b32 {pv30,pv31,pv32,pv33}, [ad+960];\n"
        "add.u32 ad, %1, so; ld.shared.v2.b32 {pv34,pv35}, [ad+960];\n"
        "mov.b32 {xl, xh}, ps6; mov.b32 rr, {xl, xl}; mov.b32 mm, {xh, xh}; fma.rn.bf16x2 pa18, pa18, rr, mm; fma.rn.bf16x2 pa19, pa19, rr, mm; fma.rn.bf16x2 pa20, pa20, rr, mm; fma.rn.bf16x2 pa21, pa21, rr, mm; fma.rn.bf16x2 pa22, pa22, rr, mm; fma.rn.bf16x2 pa23, pa23, rr, mm;\n"
        "and.b32 m0, pa18, 0x7fff7fff; and.b32 m1, pa19, 0x7fff7fff; and.b32 m2, pa20, 0x7fff7fff; and.b32 m3, pa21, 0x7fff7fff; and.b32 m4, pa22, 0x7fff7fff; and.b32 m5, pa23, 0x7fff7fff;\n"
        "mad.lo.u32 y0, m0, 7, pa18; mad.lo.u32 y1, m1, 7, pa19; mad.lo.u32 y2, m2, 7, pa20; mad.lo.u32 y3, m3, 7, pa21; mad.lo.u32 y4, m4, 7, pa22; mad.lo.u32 y5, m5, 7, pa23;\n"
        "add.u32 ad, %3, so; st.shared.v4.b32 [ad+2048], {y0,y1,y2,y3};\n"
        "add.u32 ad, %5, so; st.shared.v2.b32 [ad+1024], {y4,y5};\n"
        "add.u32 so, so, 26624; setp.eq.u32 pr, so, 79872; selp.u32 so, 0, so, pr;\n"
        "add.u32 t, t, 8; setp.lt.u32 pe, t, 256;\n"
        "@pe bra.uni LOOP;\n"
        "bra.uni DONE;\n"
        "SPIN: mov.u32 cnt, 0;\n"
        "SPINL:\n"
        "mbarrier.try_wait.parity.shared::cta.b64 pw, [t+231272], 0;\n"
        "@pw bra.uni BACK;\n"
        "add.u32 cnt, cnt, 1; setp.lt.u32 pw, cnt, 0x100000;\n"
        "@pw bra.uni SPINL;\n"
        "trap;\n"
        "RARE:\n"
        "ld.volatile.shared.u32 tt, [%6];\n"
        "mov.b32 pa0, tt; mov.b32 pa1, tt; mov.b32 pa2, tt; mov.b32 pa3, tt; mov.b32 pa4, tt; mov.b32 pa5, tt; mov.b32 pa6, tt; mov.b32 pa7, tt; mov.b32 pa8, tt; mov.b32 pa9, tt; mov.b32 pa10, tt; mov.b32 pa11, tt;\n"
        "mov.b32 pa12, tt; mov.b32 pa13, tt; mov.b32 pa14, tt; mov.b32 pa15, tt; mov.b32 pa16, tt; mov.b32 pa17, tt; mov.b32 pa18, tt; mov.b32 pa19, tt; mov.b32 pa20, tt; mov.b32 pa21, tt; mov.b32 pa22, tt; mov.b32 pa23, tt;\n"
        "mov.b32 pb0, tt; mov.b32 pb1, tt; mov.b32 pb2, tt; mov.b32 pb3, tt; mov.b32 pb4, tt; mov.b32 pb5, tt; mov.b32 pb6, tt; mov.b32 pb7, tt; mov.b32 pb8, tt; mov.b32 pb9, tt; mov.b32 pb10, tt; mov.b32 pb11, tt;\n"
        "mov.b32 pb12, tt; mov.b32 pb13, tt; mov.b32 pb14, tt; mov.b32 pb15, tt; mov.b32 pb16, tt; mov.b32 pb17, tt; mov.b32 pb18, tt; mov.b32 pb19, tt; mov.b32 pb20, tt; mov.b32 pb21, tt; mov.b32 pb22, tt; mov.b32 pb23, tt;\n"
        "mov.b32 pc0, tt; mov.b32 pc1, tt; mov.b32 pc2, tt; mov.b32 pc3, tt; mov.b32 pc4, tt; mov.b32 pc5, tt; mov.b32 pc6, tt; mov.b32 pc7, tt; mov.b32 pc8, tt; mov.b32 pc9, tt; mov.b32 pc10, tt; mov.b32 pc11, tt;\n"
        "mov.b32 pc12, tt; mov.b32 pc13, tt; mov.b32 pc14, tt; mov.b32 pc15, tt; mov.b32 pc16, tt; mov.b32 pc17, tt; mov.b32 pc18, tt; mov.b32 pc19, tt; mov.b32 pc20, tt; mov.b32 pc21, tt; mov.b32 pc22, tt; mov.b32 pc23, tt;\n"
        "mov.b32 ps0, tt; mov.b32 ps1, tt; mov.b32 ps2, tt; mov.b32 ps3, tt; mov.b32 ps4, tt; mov.b32 ps5, tt; mov.b32 ps6, tt; mov.b32 ps7, tt; mov.b32 pq0, tt; mov.b32 pq1, tt; mov.b32 pq2, tt; mov.b32 pq3, tt;\n"
        "ld.volatile.shared.v2.b32 {pw1, pw0}, [%6]; xor.b32 tt, tt, pw1;\n"
        "ld.volatile.shared.v2.b32 {pw3, pw2}, [%6]; xor.b32 tt, tt, pw3;\n"
        "ld.volatile.shared.v2.b32 {pw5, pw4}, [%6]; xor.b32 tt, tt, pw5;\n"
        "ld.volatile.shared.v2.b32 {pw7, pw6}, [%6]; xor.b32 tt, tt, pw7;\n"
        "ld.volatile.shared.v2.b32 {pw9, pw8}, [%6]; xor.b32 tt, tt, pw9;\n"
        "ld.volatile.shared.v2.b32 {pw11, pw10}, [%6]; xor.b32 tt, tt, pw11;\n"
        "ld.volatile.shared.v2.b32 {pw13, pw12}, [%6]; xor.b32 tt, tt, pw13;\n"
        "ld.volatile.shared.v2.b32 {pw15, pw14}, [%6]; xor.b32 tt, tt, pw15;\n"
        "ld.volatile.shared.v2.b32 {pw17, pw16}, [%6]; xor.b32 tt, tt, pw17;\n"
        "ld.volatile.shared.v2.b32 {pw19, pw18}, [%6]; xor.b32 tt, tt, pw19;\n"
        "ld.volatile.shared.v2.b32 {pw21, pw20}, [%6]; xor.b32 tt, tt, pw21;\n"
        "ld.volatile.shared.v2.b32 {pw23, pw22}, [%6]; xor.b32 tt, tt, pw23;\n"
        "ld.volatile.shared.v2.b32 {pw25, pw24}, [%6]; xor.b32 tt, tt, pw25;\n"
        "ld.volatile.shared.v2.b32 {pw27, pw26}, [%6]; xor.b32 tt, tt, pw27;\n"
        "ld.volatile.shared.v2.b32 {pw29, pw28}, [%6]; xor.b32 tt, tt, pw29;\n"
        "ld.volatile.shared.v2.b32 {pw31, pw30}, [%6]; xor.b32 tt, tt, pw31;\n"
        "ld.volatile.shared.v2.b32 {pw33, pw32}, [%6]; xor.b32 tt, tt, pw33;\n"
        "ld.volatile.shared.v2.b32 {pw35, pw34}, [%6]; xor.b32 tt, tt, pw35;\n"
        "ld.volatile.shared.v2.b32 {pw37, pw36}, [%6]; xor.b32 tt, tt, pw37;\n"
        "ld.volatile.shared.v2.b32 {pw39, pw38}, [%6]; xor.b32 tt, tt, pw39;\n"
        "ld.volatile.shared.v2.b32 {pw41, pw40}, [%6]; xor.b32 tt, tt, pw41;\n"
        "ld.volatile.shared.v2.b32 {pw43, pw42}, [%6]; xor.b32 tt, tt, pw43;\n"
        "ld.volatile.shared.v2.b32 {pw45, pw44}, [%6]; xor.b32 tt, tt, pw45;\n"
        "ld.volatile.shared.v2.b32 {pw47, pw46}, [%6]; xor.b32 tt, tt, pw47;\n"
        "ld.volatile.shared.v2.b32 {pw49, pw48}, [%6]; xor.b32 tt, tt, pw49;\n"
        "ld.volatile.shared.v2.b32 {pw51, pw50}, [%6]; xor.b32 tt, tt, pw51;\n"
        "ld.volatile.shared.v2.b32 {pw53, pw52}, [%6]; xor.b32 tt, tt, pw53;\n"
        "mov.b32 us, tt; setp.ne.u32 pw, %15, 7;\n"
        "wgmma.fence.sync.aligned;\n"
        "setp.eq.u32 pr, %15, 1000; @pr bra.uni B0;\n"
        "setp.eq.u32 pr, %15, 1001; @pr bra.uni B1;\n"
        "setp.eq.u32 pr, %15, 1002; @pr bra.uni C0;\n"
        "setp.eq.u32 pr, %15, 1003; @pr bra.uni N0;\n"
        "setp.eq.u32 pr, %15, 1004; @pr bra.uni N1;\n"
        "setp.eq.u32 pr, %15, 1005; @pr bra.uni N2;\n"
        "setp.eq.u32 pr, %15, 1006; @pr bra.uni N3;\n"
        "trap;\n"
        "DONE:\n"
        ASM_TRC("t")
        "fence.proxy.async.shared::cta;\n"
        "@pl mbarrier.arrive.shared::cta.b64 _, [t+231552];\n"
        "}\n"
        :: "r"(sb + SM_X + c.xoff[0]), "r"(sb + SM_X + c.xoff[1]), "r"(sb + SM_Y1 + c.yoff[0][0]), "r"(sb + SM_Y1 + c.yoff[0][1]),
           "r"(sb + SM_Y1 + c.yoff[1][0]), "r"(sb + SM_Y1 + c.yoff[1][1]), "r"(c.stat), "r"(c.own), "r"(c.lane),
           "l"(prm.sel[0]), "l"(prm.sel[1]), "l"(prm.sel[2]), "r"(prm.ydesc), "f"(LN_EPS_SCALED), "f"(RSTD_SCALE), "r"(prm.w1desc)
        : "memory");
}

__device__ __forceinline__ void produce(const Producer& c, const Params& prm) {
    uint32_t B[24], C[24];
    uint32_t st[8];
    uint32_t v[6][6];
    uint32_t ws[6];
#pragma unroll
    for (int u = 0; u < 6; u++) {
        ws[u] = c.w[0][u];
#pragma unroll
        for (int t = 1; t < 9; t++) ws[u] = bf2_add(ws[u], c.w[t][u]);
    }
    SMARK(2);
#pragma unroll 1
    for (int i = loop_init<0>(), so = loop_init<0>();; i++, so += SLOT_BYTES) {
        mbar_wait_c<0>(sb + SM_GO + i * 8);
        SMARK(4 + i);
        load_x(v, c, sb + SM_X + so);
        if (i == 2) break;
        if (so == 0) {
            const uint32_t p = bf2_add(bf2_fma(v[2][2], ws[2], bf2_fma(v[2][1], ws[1], bf2_mul(v[2][0], ws[0]))),
                                       bf2_fma(v[2][5], ws[5], bf2_fma(v[2][4], ws[4], bf2_mul(v[2][3], ws[3]))));
            float e = quad_sum(bf_lo(p) + bf_hi(p));
            e = (e + __shfl_xor_sync(0xffffffffu, e, 4)) * (-1.0f / CH);
            st[1] = st[3] = st[5] = st[7] = pack_bf2(e, e);
#pragma unroll
            for (int k = 0; k < NX; k++) sts32(c.own + k * SLOT_BYTES + 4, st[1]);
        } else {
            conv_row<1, 1>(B, C, v, c);
        }
        conv_row<0, 0>(C, st, v, c);
        fence_async_smem();
        asm volatile("bar.arrive %0, 160;" ::"r"(6 + i) : "memory");
    }
    asm volatile(".reg .b32 pw<54>, pb<24>, pc<24>, pv<36>, ps<8>;");
    hand_over<0>(c, B, C, v);
    asm volatile("mov.b32 ps1, %0; mov.b32 ps3, %1; mov.b32 ps5, %2; mov.b32 ps7, %3;" ::"r"(st[1]), "r"(st[3]), "r"(st[5]), "r"(st[7]));
    SMARK(7);
    produce_tiles(c, prm);
    mbar_arrive_if(sb + SM_YFULL + ROWS_PER_CTA * 8, c.lane == 0);
}

struct Duty {
    const char* g;
    const char* zeros;
    long long step;
    uint32_t s, bytes;
    int end, zero;
};
__device__ __forceinline__ Duty make_duty(const Params& prm, int wg, int w) {
    const RowCopy rc = row_copy(prm);
    Duty d;
    d.g = (w == 2 ? rc.y0 : rc.x0 + (w == 0 ? rc.cut0 : w == 1 ? 32 * 192 : 192)) +
          (wg + (w == 2 ? 0 : w < 2 ? 2 * NX : 2 * NX + L2_AHEAD)) * rc.stride;
    d.step = NX * rc.stride;
    d.s = wg * SLOT_BYTES + (w == 2 ? sb + SM_Y1 : sb + SM_X + (w == 0 ? rc.cut0 : XHALF_B));
    d.bytes = w >= 2 ? TILE_BYTES : XHALF_BYTES - (w == 0 ? rc.cut0 : rc.cut1);
    d.end = w == 2 ? ROWS_PER_CTA : w < 2 ? STEPS + 1 - 2 * NX : rc.last + 1 - 2 * NX - L2_AHEAD;
    d.zero = rc.last + 1 - 2 * NX;
    d.zeros = rc.zeros;
    return d;
}

static_assert(sb + SM_BAR == 230800 && sb + SM_YFULL == 231560 && sb + SM_GO == 231248 && SLOT_BYTES == 26624 && sb + SM_GAMMA == 229248 &&
              SM_BETA == SM_GAMMA + 768 && SM_W2 == 73728 && sb + SM_BUF3 == 187392 && BAR_W2 == 9 && BAR_W1B == 10, "layout");
__device__ __forceinline__ void consume(float (&acc)[2][2], uint32_t w1t, uint32_t yd, uint32_t wd, uint32_t own_slot, const Duty& d,
                                        uint32_t role, uint32_t lane, const Params& prm) {
    asm volatile(
        "{\n"
        ".reg .b32 z<32>, w<44>, p, a<4>, lo<2>, hi<2>, t, g, q<4>, dl, dh, n, so, c, tt, cnt, f0, f1;\n"
        ".reg .b16 xl, xh, xr;\n"
        ".reg .b64 ds<6>, wd, gp, src;\n"
        ".reg .pred pt, pf, pr, pw, pl, pe;\n"
        "setp.ne.b32 pt, 1, 0; setp.ne.b32 pf, 0, 0; setp.eq.u32 pl, %15, 0;\n"
        "mov.b32 c, 0x40D940D9;\n"
        "ldmatrix.sync.aligned.m8n8.x4.trans.shared.b16 {w0,w1,w2,w3}, [%4+0];\n"
        "ldmatrix.sync.aligned.m8n8.x4.trans.shared.b16 {w4,w5,w6,w7}, [%4+2048];\n"
        "ldmatrix.sync.aligned.m8n8.x4.trans.shared.b16 {w8,w9,w10,w11}, [%4+4096];\n"
        "ldmatrix.sync.aligned.m8n8.x4.trans.shared.b16 {w12,w13,w14,w15}, [%4+6144];\n"
        "ldmatrix.sync.aligned.m8n8.x4.trans.shared.b16 {w16,w17,w18,w19}, [%4+8192];\n"
        "ldmatrix.sync.aligned.m8n8.x4.trans.shared.b16 {w20,w21,w22,w23}, [%4+10240];\n"
        "shl.b32 f0, w0, 16; and.b32 f1, w0, 0xffff0000; cvt.rn.f16x2.f32 w0, f1, f0; shl.b32 f0, w1, 16; and.b32 f1, w1, 0xffff0000; cvt.rn.f16x2.f32 w1, f1, f0; shl.b32 f0, w2, 16; and.b32 f1, w2, 0xffff0000; cvt.rn.f16x2.f32 w2, f1, f0; shl.b32 f0, w3, 16; and.b32 f1, w3, 0xffff0000; cvt.rn.f16x2.f32 w3, f1, f0;\n"
        "stmatrix.sync.aligned.m8n8.x4.trans.shared.b16 [%4+0], {w0,w1,w2,w3};\n"
        "shl.b32 f0, w4, 16; and.b32 f1, w4, 0xffff0000; cvt.rn.f16x2.f32 w4, f1, f0; shl.b32 f0, w5, 16; and.b32 f1, w5, 0xffff0000; cvt.rn.f16x2.f32 w5, f1, f0; shl.b32 f0, w6, 16; and.b32 f1, w6, 0xffff0000; cvt.rn.f16x2.f32 w6, f1, f0; shl.b32 f0, w7, 16; and.b32 f1, w7, 0xffff0000; cvt.rn.f16x2.f32 w7, f1, f0;\n"
        "stmatrix.sync.aligned.m8n8.x4.trans.shared.b16 [%4+2048], {w4,w5,w6,w7};\n"
        "shl.b32 f0, w8, 16; and.b32 f1, w8, 0xffff0000; cvt.rn.f16x2.f32 w8, f1, f0; shl.b32 f0, w9, 16; and.b32 f1, w9, 0xffff0000; cvt.rn.f16x2.f32 w9, f1, f0; shl.b32 f0, w10, 16; and.b32 f1, w10, 0xffff0000; cvt.rn.f16x2.f32 w10, f1, f0; shl.b32 f0, w11, 16; and.b32 f1, w11, 0xffff0000; cvt.rn.f16x2.f32 w11, f1, f0;\n"
        "stmatrix.sync.aligned.m8n8.x4.trans.shared.b16 [%4+4096], {w8,w9,w10,w11};\n"
        "shl.b32 f0, w12, 16; and.b32 f1, w12, 0xffff0000; cvt.rn.f16x2.f32 w12, f1, f0; shl.b32 f0, w13, 16; and.b32 f1, w13, 0xffff0000; cvt.rn.f16x2.f32 w13, f1, f0; shl.b32 f0, w14, 16; and.b32 f1, w14, 0xffff0000; cvt.rn.f16x2.f32 w14, f1, f0; shl.b32 f0, w15, 16; and.b32 f1, w15, 0xffff0000; cvt.rn.f16x2.f32 w15, f1, f0;\n"
        "stmatrix.sync.aligned.m8n8.x4.trans.shared.b16 [%4+6144], {w12,w13,w14,w15};\n"
        "shl.b32 f0, w16, 16; and.b32 f1, w16, 0xffff0000; cvt.rn.f16x2.f32 w16, f1, f0; shl.b32 f0, w17, 16; and.b32 f1, w17, 0xffff0000; cvt.rn.f16x2.f32 w17, f1, f0; shl.b32 f0, w18, 16; and.b32 f1, w18, 0xffff0000; cvt.rn.f16x2.f32 w18, f1, f0; shl.b32 f0, w19, 16; and.b32 f1, w19, 0xffff0000; cvt.rn.f16x2.f32 w19, f1, f0;\n"
        "stmatrix.sync.aligned.m8n8.x4.trans.shared.b16 [%4+8192], {w16,w17,w18,w19};\n"
        "shl.b32 f0, w20, 16; and.b32 f1, w20, 0xffff0000; cvt.rn.f16x2.f32 w20, f1, f0; shl.b32 f0, w21, 16; and.b32 f1, w21, 0xffff0000; cvt.rn.f16x2.f32 w21, f1, f0; shl.b32 f0, w22, 16; and.b32 f1, w22, 0xffff0000; cvt.rn.f16x2.f32 w22, f1, f0; shl.b32 f0, w23, 16; and.b32 f1, w23, 0xffff0000; cvt.rn.f16x2.f32 w23, f1, f0;\n"
        "stmatrix.sync.aligned.m8n8.x4.trans.shared.b16 [%4+10240], {w20,w21,w22,w23};\n"
        "mov.u32 tt, 230880; mbarrier.try_wait.parity.shared::cta.b64 pw, [tt], 0;\n"
        "@!pw bra.uni SPINW;\n"
        "BACKW:\n"
        "ldmatrix.sync.aligned.m8n8.x4.trans.shared.b16 {z0,z1,z2,z3}, [%4+22528];\n"
        "ldmatrix.sync.aligned.m8n8.x4.trans.shared.b16 {w24,w25,w26,w27}, [%4+12288];\n"
        "ldmatrix.sync.aligned.m8n8.x4.trans.shared.b16 {w28,w29,w30,w31}, [%4+14336];\n"
        "ldmatrix.sync.aligned.m8n8.x4.trans.shared.b16 {w32,w33,w34,w35}, [%4+16384];\n"
        "ldmatrix.sync.aligned.m8n8.x4.trans.shared.b16 {w36,w37,w38,w39}, [%4+18432];\n"
        "ldmatrix.sync.aligned.m8n8.x4.trans.shared.b16 {w40,w41,w42,w43}, [%4+20480];\n"
        "shl.b32 f0, z0, 16; and.b32 f1, z0, 0xffff0000; cvt.rn.f16x2.f32 z0, f1, f0; shl.b32 f0, z1, 16; and.b32 f1, z1, 0xffff0000; cvt.rn.f16x2.f32 z1, f1, f0; shl.b32 f0, z2, 16; and.b32 f1, z2, 0xffff0000; cvt.rn.f16x2.f32 z2, f1, f0; shl.b32 f0, z3, 16; and.b32 f1, z3, 0xffff0000; cvt.rn.f16x2.f32 z3, f1, f0;\n"
        "stmatrix.sync.aligned.m8n8.x4.trans.shared.b16 [%4+22528], {z0,z1,z2,z3};\n"
        "shl.b32 f0, w24, 16; and.b32 f1, w24, 0xffff0000; cvt.rn.f16x2.f32 w24, f1, f0; shl.b32 f0, w25, 16; and.b32 f1, w25, 0xffff0000; cvt.rn.f16x2.f32 w25, f1, f0; shl.b32 f0, w26, 16; and.b32 f1, w26, 0xffff0000; cvt.rn.f16x2.f32 w26, f1, f0; shl.b32 f0, w27, 16; and.b32 f1, w27, 0xffff0000; cvt.rn.f16x2.f32 w27, f1, f0;\n"
        "stmatrix.sync.aligned.m8n8.x4.trans.shared.b16 [%4+12288], {w24,w25,w26,w27};\n"
        "shl.b32 f0, w28, 16; and.b32 f1, w28, 0xffff0000; cvt.rn.f16x2.f32 w28, f1, f0; shl.b32 f0, w29, 16; and.b32 f1, w29, 0xffff0000; cvt.rn.f16x2.f32 w29, f1, f0; shl.b32 f0, w30, 16; and.b32 f1, w30, 0xffff0000; cvt.rn.f16x2.f32 w30, f1, f0; shl.b32 f0, w31, 16; and.b32 f1, w31, 0xffff0000; cvt.rn.f16x2.f32 w31, f1, f0;\n"
        "stmatrix.sync.aligned.m8n8.x4.trans.shared.b16 [%4+14336], {w28,w29,w30,w31};\n"
        "shl.b32 f0, w32, 16; and.b32 f1, w32, 0xffff0000; cvt.rn.f16x2.f32 w32, f1, f0; shl.b32 f0, w33, 16; and.b32 f1, w33, 0xffff0000; cvt.rn.f16x2.f32 w33, f1, f0; shl.b32 f0, w34, 16; and.b32 f1, w34, 0xffff0000; cvt.rn.f16x2.f32 w34, f1, f0; shl.b32 f0, w35, 16; and.b32 f1, w35, 0xffff0000; cvt.rn.f16x2.f32 w35, f1, f0;\n"
        "stmatrix.sync.aligned.m8n8.x4.trans.shared.b16 [%4+16384], {w32,w33,w34,w35};\n"
        "shl.b32 f0, w36, 16; and.b32 f1, w36, 0xffff0000; cvt.rn.f16x2.f32 w36, f1, f0; shl.b32 f0, w37, 16; and.b32 f1, w37, 0xffff0000; cvt.rn.f16x2.f32 w37, f1, f0; shl.b32 f0, w38, 16; and.b32 f1, w38, 0xffff0000; cvt.rn.f16x2.f32 w38, f1, f0; shl.b32 f0, w39, 16; and.b32 f1, w39, 0xffff0000; cvt.rn.f16x2.f32 w39, f1, f0;\n"
        "stmatrix.sync.aligned.m8n8.x4.trans.shared.b16 [%4+18432], {w36,w37,w38,w39};\n"
        "shl.b32 f0, w40, 16; and.b32 f1, w40, 0xffff0000; cvt.rn.f16x2.f32 w40, f1, f0; shl.b32 f0, w41, 16; and.b32 f1, w41, 0xffff0000; cvt.rn.f16x2.f32 w41, f1, f0; shl.b32 f0, w42, 16; and.b32 f1, w42, 0xffff0000; cvt.rn.f16x2.f32 w42, f1, f0; shl.b32 f0, w43, 16; and.b32 f1, w43, 0xffff0000; cvt.rn.f16x2.f32 w43, f1, f0;\n"
        "stmatrix.sync.aligned.m8n8.x4.trans.shared.b16 [%4+20480], {w40,w41,w42,w43};\n"
        "fence.proxy.async.shared::cta;\n"
        ASM_SMARK
        "mov.b32 p, 0; mov.b32 t, 0; mov.b32 g, 0; mov.b32 a0, 0; mov.b32 a1, 0; mov.b32 a2, 0; mov.b32 a3, 0; mov.b32 lo0, 0; mov.b32 lo1, 0; mov.b32 hi0, 0; mov.b32 hi1, 0; mov.b32 q0, 0; mov.b32 q1, 0; mov.b32 q2, 0; mov.b32 q3, 0;\n"
        "mov.b32 z16, 0; mov.b32 z17, 0; mov.b32 z18, 0; mov.b32 z19, 0; mov.b32 z20, 0; mov.b32 z21, 0; mov.b32 z22, 0; mov.b32 z23, 0; mov.b32 z24, 0; mov.b32 z25, 0; mov.b32 z26, 0; mov.b32 z27, 0; mov.b32 z28, 0; mov.b32 z29, 0; mov.b32 z30, 0; mov.b32 z31, 0;\n"
        "mov.f32 %0, 0f00000000; mov.f32 %1, 0f00000000; mov.f32 %2, 0f00000000; mov.f32 %3, 0f00000000;\n"
        "mov.u32 n, 0; mov.u32 so, 0; mov.b64 gp, %8; mov.b64 wd, {%6, 0x40000040};\n"
        "mov.b64 ds0, %20; add.s64 ds1, ds0, 2; add.s64 ds2, ds0, 4; add.s64 ds3, ds0, 6; mov.b64 ds4, %21; add.s64 ds5, ds4, 2;\n"
        "setp.eq.u32 pr, %7, 53248; setp.lt.and.u32 pr, %13, 2, pr;\n"
        "@!pr bra.uni ROW5;\n"
        "mbarrier.try_wait.parity.shared::cta.b64 pw, [n+231552], 0;\n"
        "@!pw bra.uni SPIN5;\n"
        "BACK5:\n"
        "sub.s64 src, gp, %16; mov.u32 tt, 231288;\n"
        "elect.sync _|pr, 0xffffffff;\n"
        "@pr mbarrier.arrive.expect_tx.shared::cta.b64 _, [tt], %10;\n"
        "@pr cp.async.bulk.shared::cluster.global.mbarrier::complete_tx::bytes [%9], [src], %10, [tt];\n"
        "ROW5:\n"
        "mbarrier.try_wait.parity.shared::cta.b64 pw, [n+231560], 0;\n"
        "@!pw bra.uni SPIN0;\n"
        "BACK0:\n"
        ASM_TS
        "wgmma.fence.sync.aligned;\n"
        "wgmma.mma_async.sync.aligned.m64n64k16.f16.f16.f16 {z0,z1,z2,z3,z4,z5,z6,z7,z8,z9,z10,z11,z12,z13,z14,z15}, {w0,w1,w2,w3}, ds0, pf, 1, 1, 0;\n"
        "wgmma.mma_async.sync.aligned.m64n64k16.f16.f16.f16 {z0,z1,z2,z3,z4,z5,z6,z7,z8,z9,z10,z11,z12,z13,z14,z15}, {w4,w5,w6,w7}, ds1, pt, 1, 1, 0;\n"
        "wgmma.mma_async.sync.aligned.m64n64k16.f16.f16.f16 {z0,z1,z2,z3,z4,z5,z6,z7,z8,z9,z10,z11,z12,z13,z14,z15}, {w8,w9,w10,w11}, ds2, pt, 1, 1, 0;\n"
        "wgmma.fence.sync.aligned;\n"
        "wgmma.mma_async.sync.aligned.m64n64k16.f16.f16.f16 {z0,z1,z2,z3,z4,z5,z6,z7,z8,z9,z10,z11,z12,z13,z14,z15}, {w12,w13,w14,w15}, ds3, pt, 1, 1, 0;\n"
        "wgmma.mma_async.sync.aligned.m64n64k16.f16.f16.f16 {z0,z1,z2,z3,z4,z5,z6,z7,z8,z9,z10,z11,z12,z13,z14,z15}, {w16,w17,w18,w19}, ds4, pt, 1, 1, 0;\n"
        "wgmma.mma_async.sync.aligned.m64n64k16.f16.f16.f16 {z0,z1,z2,z3,z4,z5,z6,z7,z8,z9,z10,z11,z12,z13,z14,z15}, {w20,w21,w22,w23}, ds5, pt, 1, 1, 0;\n"
        "wgmma.commit_group.sync.aligned;\n"
        "setp.eq.u32 pr, so, %7;\n"
        "@pr bra.uni DUTY;\n"
        "TOP:\n"
        ASM_TRC("n")
        "wgmma.wait_group.sync.aligned 0;\n"
        "mov.b32 {xl, xh}, a2; tanh.approx.f16 xr, xh; cvt.u32.u16 hi0, xr; mul.rn.f16x2 a3, z31, p; fma.rn.f16x2 p, z0, z0, c; fma.rn.f16x2 q3, g, g, q3; fma.rn.f16x2 g, z28, t, z28; prmt.b32 t, lo1, hi1, 0x5410; tanh.approx.f16 xr, xl; cvt.u32.u16 lo0, xr;\n"
        "B31:\n"
        "mov.b32 {xl, xh}, a3; tanh.approx.f16 xr, xh; cvt.u32.u16 hi1, xr; mul.rn.f16x2 a0, z0, p; fma.rn.f16x2 p, z1, z1, c; fma.rn.f16x2 q2, g, g, q2; fma.rn.f16x2 g, z29, t, z29; prmt.b32 t, lo0, hi0, 0x5410; tanh.approx.f16 xr, xl; cvt.u32.u16 lo1, xr;\n"
        "B0:\n"
        "mov.b32 {xl, xh}, a0; tanh.approx.f16 xr, xh; cvt.u32.u16 hi0, xr; mul.rn.f16x2 a1, z1, p; fma.rn.f16x2 p, z2, z2, c; fma.rn.f16x2 q3, g, g, q3; fma.rn.f16x2 g, z30, t, z30; prmt.b32 t, lo1, hi1, 0x5410; tanh.approx.f16 xr, xl; cvt.u32.u16 lo0, xr;\n"
        "B1:\n"
        "mov.b32 {xl, xh}, a1; tanh.approx.f16 xr, xh; cvt.u32.u16 hi1, xr; mul.rn.f16x2 a2, z2, p; fma.rn.f16x2 p, z3, z3, c; fma.rn.f16x2 q2, g, g, q2; fma.rn.f16x2 g, z31, t, z31; prmt.b32 t, lo0, hi0, 0x5410; tanh.approx.f16 xr, xl; cvt.u32.u16 lo1, xr;\n"
        "B2:\n"
        "wgmma.fence.sync.aligned;\n"
        "wgmma.mma_async.sync.aligned.m64n64k16.f16.f16.f16 {z16,z17,z18,z19,z20,z21,z22,z23,z24,z25,z26,z27,z28,z29,z30,z31}, {w24,w25,w26,w27}, ds0, pf, 1, 1, 0;\n"
        "wgmma.mma_async.sync.aligned.m64n64k16.f16.f16.f16 {z16,z17,z18,z19,z20,z21,z22,z23,z24,z25,z26,z27,z28,z29,z30,z31}, {w28,w29,w30,w31}, ds1, pt, 1, 1, 0;\n"
        "wgmma.mma_async.sync.aligned.m64n64k16.f16.f16.f16 {z16,z17,z18,z19,z20,z21,z22,z23,z24,z25,z26,z27,z28,z29,z30,z31}, {w32,w33,w34,w35}, ds2, pt, 1, 1, 0;\n"
        "mov.b32 {xl, xh}, a2; tanh.approx.f16 xr, xh; cvt.u32.u16 hi0, xr; mul.rn.f16x2 a3, z3, p; fma.rn.f16x2 p, z4, z4, c; fma.rn.f16x2 q3, g, g, q3; fma.rn.f16x2 g, z0, t, z0; prmt.b32 t, lo1, hi1, 0x5410; tanh.approx.f16 xr, xl; cvt.u32.u16 lo0, xr;\n"
        "B3:\n"
        "mov.b32 {xl, xh}, a3; tanh.approx.f16 xr, xh; cvt.u32.u16 hi1, xr; mul.rn.f16x2 a0, z4, p; fma.rn.f16x2 p, z5, z5, c; fma.rn.f16x2 q0, g, g, q0; fma.rn.f16x2 g, z1, t, z1; prmt.b32 t, lo0, hi0, 0x5410; tanh.approx.f16 xr, xl; cvt.u32.u16 lo1, xr;\n"
        "B4:\n"
        "mov.b32 {xl, xh}, a0; tanh.approx.f16 xr, xh; cvt.u32.u16 hi0, xr; mul.rn.f16x2 a1, z5, p; fma.rn.f16x2 p, z6, z6, c; fma.rn.f16x2 q1, g, g, q1; fma.rn.f16x2 g, z2, t, z2; prmt.b32 t, lo1, hi1, 0x5410; tanh.approx.f16 xr, xl; cvt.u32.u16 lo0, xr;\n"
        "B5:\n"
        "wgmma.fence.sync.aligned;\n"
        "wgmma.mma_async.sync.aligned.m64n64k16.f16.f16.f16 {z16,z17,z18,z19,z20,z21,z22,z23,z24,z25,z26,z27,z28,z29,z30,z31}, {w36,w37,w38,w39}, ds3, pt, 1, 1, 0;\n"
        "wgmma.mma_async.sync.aligned.m64n64k16.f16.f16.f16 {z16,z17,z18,z19,z20,z21,z22,z23,z24,z25,z26,z27,z28,z29,z30,z31}, {w40,w41,w42,w43}, ds4, pt, 1, 1, 0;\n"
        "wgmma.mma_async.sync.aligned.m64n64k16.f16.f16.f16 {z16,z17,z18,z19,z20,z21,z22,z23,z24,z25,z26,z27,z28,z29,z30,z31}, wd, ds5, pt, 1, 1, 1, 0;\n"
        "wgmma.commit_group.sync.aligned;\n"
        "mov.b32 {xl, xh}, a1; tanh.approx.f16 xr, xh; cvt.u32.u16 hi1, xr; mul.rn.f16x2 a2, z6, p; fma.rn.f16x2 p, z7, z7, c; fma.rn.f16x2 q0, g, g, q0; fma.rn.f16x2 g, z3, t, z3; prmt.b32 t, lo0, hi0, 0x5410; tanh.approx.f16 xr, xl; cvt.u32.u16 lo1, xr;\n"
        "B6:\n"
        "add.u32 so, so, 26624; setp.eq.u32 pr, so, 79872; selp.u32 so, 0, so, pr;\n"
        "mov.b32 {xl, xh}, a2; tanh.approx.f16 xr, xh; cvt.u32.u16 hi0, xr; mul.rn.f16x2 a3, z7, p; fma.rn.f16x2 p, z8, z8, c; fma.rn.f16x2 q1, g, g, q1; fma.rn.f16x2 g, z4, t, z4; prmt.b32 t, lo1, hi1, 0x5410; tanh.approx.f16 xr, xl; cvt.u32.u16 lo0, xr;\n"
        "B7:\n"
        "shr.u32 tt, so, 4;\n"
        "mov.b64 {dl, dh}, ds0; add.u32 dl, tt, 74816; mov.b64 ds0, {dl, dh}; mov.b64 {dl, dh}, ds1; add.u32 dl, tt, 74818; mov.b64 ds1, {dl, dh}; mov.b64 {dl, dh}, ds2; add.u32 dl, tt, 74820; mov.b64 ds2, {dl, dh};\n"
        "mov.b32 {xl, xh}, a3; tanh.approx.f16 xr, xh; cvt.u32.u16 hi1, xr; mul.rn.f16x2 a0, z8, p; fma.rn.f16x2 p, z9, z9, c; fma.rn.f16x2 q0, g, g, q0; fma.rn.f16x2 g, z5, t, z5; prmt.b32 t, lo0, hi0, 0x5410; tanh.approx.f16 xr, xl; cvt.u32.u16 lo1, xr;\n"
        "B8:\n"
        "shr.u32 tt, so, 4;\n"
        "mov.b64 {dl, dh}, ds3; add.u32 dl, tt, 74822; mov.b64 ds3, {dl, dh}; mov.b64 {dl, dh}, ds4; add.u32 dl, tt, 75328; mov.b64 ds4, {dl, dh}; mov.b64 {dl, dh}, ds5; add.u32 dl, tt, 75330; mov.b64 ds5, {dl, dh};\n"
        "mov.b32 {xl, xh}, a0; tanh.approx.f16 xr, xh; cvt.u32.u16 hi0, xr; mul.rn.f16x2 a1, z9, p; fma.rn.f16x2 p, z10, z10, c; fma.rn.f16x2 q1, g, g, q1; fma.rn.f16x2 g, z6, t, z6; prmt.b32 t, lo1, hi1, 0x5410; tanh.approx.f16 xr, xl; cvt.u32.u16 lo0, xr;\n"
        "B9:\n"
        "mov.b32 {xl, xh}, a1; tanh.approx.f16 xr, xh; cvt.u32.u16 hi1, xr; mul.rn.f16x2 a2, z10, p; fma.rn.f16x2 p, z11, z11, c; fma.rn.f16x2 q0, g, g, q0; fma.rn.f16x2 g, z7, t, z7; prmt.b32 t, lo0, hi0, 0x5410; tanh.approx.f16 xr, xl; cvt.u32.u16 lo1, xr;\n"
        "B10:\n"
        "mov.b32 {xl, xh}, a2; tanh.approx.f16 xr, xh; cvt.u32.u16 hi0, xr; mul.rn.f16x2 a3, z11, p; fma.rn.f16x2 p, z12, z12, c; fma.rn.f16x2 q1, g, g, q1; fma.rn.f16x2 g, z8, t, z8; prmt.b32 t, lo1, hi1, 0x5410; tanh.approx.f16 xr, xl; cvt.u32.u16 lo0, xr;\n"
        "B11:\n"
        "mov.b32 {xl, xh}, a3; tanh.approx.f16 xr, xh; cvt.u32.u16 hi1, xr; mul.rn.f16x2 a0, z12, p; fma.rn.f16x2 p, z13, z13, c; fma.rn.f16x2 q0, g, g, q0; fma.rn.f16x2 g, z9, t, z9; prmt.b32 t, lo0, hi0, 0x5410; tanh.approx.f16 xr, xl; cvt.u32.u16 lo1, xr;\n"
        "B12:\n"
        "mov.b32 {xl, xh}, a0; tanh.approx.f16 xr, xh; cvt.u32.u16 hi0, xr; mul.rn.f16x2 a1, z13, p; fma.rn.f16x2 p, z14, z14, c; fma.rn.f16x2 q1, g, g, q1; fma.rn.f16x2 g, z10, t, z10; prmt.b32 t, lo1, hi1, 0x5410; tanh.approx.f16 xr, xl; cvt.u32.u16 lo0, xr;\n"
        "B13:\n"
        "mov.b32 {xl, xh}, a1; tanh.approx.f16 xr, xh; cvt.u32.u16 hi1, xr; mul.rn.f16x2 a2, z14, p; fma.rn.f16x2 p, z15, z15, c; fma.rn.f16x2 q0, g, g, q0; fma.rn.f16x2 g, z11, t, z11; prmt.b32 t, lo0, hi0, 0x5410; tanh.approx.f16 xr, xl; cvt.u32.u16 lo1, xr;\n"
        "B14:\n"
        "wgmma.wait_group.sync.aligned 0;\n"
        "cp.async.bulk.wait_group.read 0;\n"
        "@pl mbarrier.arrive.shared::cta.b64 _, [n+231296];\n"
        "mov.b32 {xl, xh}, a2; tanh.approx.f16 xr, xh; cvt.u32.u16 hi0, xr; mul.rn.f16x2 a3, z15, p; fma.rn.f16x2 p, z16, z16, c; fma.rn.f16x2 q1, g, g, q1; fma.rn.f16x2 g, z12, t, z12; prmt.b32 t, lo1, hi1, 0x5410; tanh.approx.f16 xr, xl; cvt.u32.u16 lo0, xr;\n"
        "B15:\n"
        "mov.b32 {xl, xh}, a3; tanh.approx.f16 xr, xh; cvt.u32.u16 hi1, xr; mul.rn.f16x2 a0, z16, p; fma.rn.f16x2 p, z17, z17, c; fma.rn.f16x2 q0, g, g, q0; fma.rn.f16x2 g, z13, t, z13; prmt.b32 t, lo0, hi0, 0x5410; tanh.approx.f16 xr, xl; cvt.u32.u16 lo1, xr;\n"
        "B16:\n"
        "mbarrier.try_wait.parity.shared::cta.b64 pw, [n+231568], 0;\n"
        "mov.b32 {xl, xh}, a0; tanh.approx.f16 xr, xh; cvt.u32.u16 hi0, xr; mul.rn.f16x2 a1, z17, p; fma.rn.f16x2 p, z18, z18, c; fma.rn.f16x2 q1, g, g, q1; fma.rn.f16x2 g, z14, t, z14; prmt.b32 t, lo1, hi1, 0x5410; tanh.approx.f16 xr, xl; cvt.u32.u16 lo0, xr;\n"
        "B17:\n"
        "mov.b32 {xl, xh}, a1; tanh.approx.f16 xr, xh; cvt.u32.u16 hi1, xr; mul.rn.f16x2 a2, z18, p; fma.rn.f16x2 p, z19, z19, c; fma.rn.f16x2 q0, g, g, q0; fma.rn.f16x2 g, z15, t, z15; prmt.b32 t, lo0, hi0, 0x5410; tanh.approx.f16 xr, xl; cvt.u32.u16 lo1, xr;\n"
        "B18:\n"
        "@!pw bra.uni SPIN;\n"
        "BACK:\n"
        "wgmma.fence.sync.aligned;\n"
        "wgmma.mma_async.sync.aligned.m64n64k16.f16.f16.f16 {z0,z1,z2,z3,z4,z5,z6,z7,z8,z9,z10,z11,z12,z13,z14,z15}, {w0,w1,w2,w3}, ds0, pf, 1, 1, 0;\n"
        "wgmma.mma_async.sync.aligned.m64n64k16.f16.f16.f16 {z0,z1,z2,z3,z4,z5,z6,z7,z8,z9,z10,z11,z12,z13,z14,z15}, {w4,w5,w6,w7}, ds1, pt, 1, 1, 0;\n"
        "wgmma.mma_async.sync.aligned.m64n64k16.f16.f16.f16 {z0,z1,z2,z3,z4,z5,z6,z7,z8,z9,z10,z11,z12,z13,z14,z15}, {w8,w9,w10,w11}, ds2, pt, 1, 1, 0;\n"
        "mov.b32 {xl, xh}, a2; tanh.approx.f16 xr, xh; cvt.u32.u16 hi0, xr; mul.rn.f16x2 a3, z19, p; fma.rn.f16x2 p, z20, z20, c; fma.rn.f16x2 q1, g, g, q1; fma.rn.f16x2 g, z16, t, z16; prmt.b32 t, lo1, hi1, 0x5410; tanh.approx.f16 xr, xl; cvt.u32.u16 lo0, xr;\n"
        "B19:\n"
        "mov.b32 {xl, xh}, a3; tanh.approx.f16 xr, xh; cvt.u32.u16 hi1, xr; mul.rn.f16x2 a0, z20, p; fma.rn.f16x2 p, z21, z21, c; fma.rn.f16x2 q2, g, g, q2; fma.rn.f16x2 g, z17, t, z17; prmt.b32 t, lo0, hi0, 0x5410; tanh.approx.f16 xr, xl; cvt.u32.u16 lo1, xr;\n"
        "B20:\n"
        "mov.b32 {xl, xh}, a0; tanh.approx.f16 xr, xh; cvt.u32.u16 hi0, xr; mul.rn.f16x2 a1, z21, p; fma.rn.f16x2 p, z22, z22, c; fma.rn.f16x2 q3, g, g, q3; fma.rn.f16x2 g, z18, t, z18; prmt.b32 t, lo1, hi1, 0x5410; tanh.approx.f16 xr, xl; cvt.u32.u16 lo0, xr;\n"
        "B21:\n"
        "wgmma.fence.sync.aligned;\n"
        "wgmma.mma_async.sync.aligned.m64n64k16.f16.f16.f16 {z0,z1,z2,z3,z4,z5,z6,z7,z8,z9,z10,z11,z12,z13,z14,z15}, {w12,w13,w14,w15}, ds3, pt, 1, 1, 0;\n"
        "wgmma.mma_async.sync.aligned.m64n64k16.f16.f16.f16 {z0,z1,z2,z3,z4,z5,z6,z7,z8,z9,z10,z11,z12,z13,z14,z15}, {w16,w17,w18,w19}, ds4, pt, 1, 1, 0;\n"
        "wgmma.mma_async.sync.aligned.m64n64k16.f16.f16.f16 {z0,z1,z2,z3,z4,z5,z6,z7,z8,z9,z10,z11,z12,z13,z14,z15}, {w20,w21,w22,w23}, ds5, pt, 1, 1, 0;\n"
        "wgmma.commit_group.sync.aligned;\n"
        "mov.b32 {xl, xh}, a1; tanh.approx.f16 xr, xh; cvt.u32.u16 hi1, xr; mul.rn.f16x2 a2, z22, p; fma.rn.f16x2 p, z23, z23, c; fma.rn.f16x2 q2, g, g, q2; fma.rn.f16x2 g, z19, t, z19; prmt.b32 t, lo0, hi0, 0x5410; tanh.approx.f16 xr, xl; cvt.u32.u16 lo1, xr;\n"
        "B22:\n"
        "mov.b32 {xl, xh}, a2; tanh.approx.f16 xr, xh; cvt.u32.u16 hi0, xr; mul.rn.f16x2 a3, z23, p; fma.rn.f16x2 p, z24, z24, c; fma.rn.f16x2 q3, g, g, q3; fma.rn.f16x2 g, z20, t, z20; prmt.b32 t, lo1, hi1, 0x5410; tanh.approx.f16 xr, xl; cvt.u32.u16 lo0, xr;\n"
        "B23:\n"
        "mov.b32 {xl, xh}, a3; tanh.approx.f16 xr, xh; cvt.u32.u16 hi1, xr; mul.rn.f16x2 a0, z24, p; fma.rn.f16x2 p, z25, z25, c; fma.rn.f16x2 q2, g, g, q2; fma.rn.f16x2 g, z21, t, z21; prmt.b32 t, lo0, hi0, 0x5410; tanh.approx.f16 xr, xl; cvt.u32.u16 lo1, xr;\n"
        "B24:\n"
        "mov.b32 {xl, xh}, a0; tanh.approx.f16 xr, xh; cvt.u32.u16 hi0, xr; mul.rn.f16x2 a1, z25, p; fma.rn.f16x2 p, z26, z26, c; fma.rn.f16x2 q3, g, g, q3; fma.rn.f16x2 g, z22, t, z22; prmt.b32 t, lo1, hi1, 0x5410; tanh.approx.f16 xr, xl; cvt.u32.u16 lo0, xr;\n"
        "B25:\n"
        "mov.b32 {xl, xh}, a1; tanh.approx.f16 xr, xh; cvt.u32.u16 hi1, xr; mul.rn.f16x2 a2, z26, p; fma.rn.f16x2 p, z27, z27, c; fma.rn.f16x2 q2, g, g, q2; fma.rn.f16x2 g, z23, t, z23; prmt.b32 t, lo0, hi0, 0x5410; tanh.approx.f16 xr, xl; cvt.u32.u16 lo1, xr;\n"
        "B26:\n"
        "mov.b32 {xl, xh}, a2; tanh.approx.f16 xr, xh; cvt.u32.u16 hi0, xr; mul.rn.f16x2 a3, z27, p; fma.rn.f16x2 p, z28, z28, c; fma.rn.f16x2 q3, g, g, q3; fma.rn.f16x2 g, z24, t, z24; prmt.b32 t, lo1, hi1, 0x5410; tanh.approx.f16 xr, xl; cvt.u32.u16 lo0, xr;\n"
        "B27:\n"
        "add.u32 n, n, 8; setp.lt.u32 pe, n, 256; setp.ne.and.u32 pe, so, %7, pe;\n"
        "mov.b32 {xl, xh}, a3; tanh.approx.f16 xr, xh; cvt.u32.u16 hi1, xr; mul.rn.f16x2 a0, z28, p; fma.rn.f16x2 p, z29, z29, c; fma.rn.f16x2 q2, g, g, q2; fma.rn.f16x2 g, z25, t, z25; prmt.b32 t, lo0, hi0, 0x5410; tanh.approx.f16 xr, xl; cvt.u32.u16 lo1, xr;\n"
        "B28:\n"
        "mov.b32 {xl, xh}, a0; tanh.approx.f16 xr, xh; cvt.u32.u16 hi0, xr; mul.rn.f16x2 a1, z29, p; fma.rn.f16x2 p, z30, z30, c; fma.rn.f16x2 q3, g, g, q3; fma.rn.f16x2 g, z26, t, z26; prmt.b32 t, lo1, hi1, 0x5410; tanh.approx.f16 xr, xl; cvt.u32.u16 lo0, xr;\n"
        "B29:\n"
        "mov.b32 {xl, xh}, a1; tanh.approx.f16 xr, xh; cvt.u32.u16 hi1, xr; mul.rn.f16x2 a2, z30, p; fma.rn.f16x2 p, z31, z31, c; fma.rn.f16x2 q2, g, g, q2; fma.rn.f16x2 g, z27, t, z27; prmt.b32 t, lo0, hi0, 0x5410; tanh.approx.f16 xr, xl; cvt.u32.u16 lo1, xr;\n"
        "@pe bra.uni TOP;\n"
        "setp.lt.u32 pe, n, 256;\n"
        "@pe bra.uni DUTY;\n"
        "bra.uni DONE;\n"
        "SPINW: mov.u32 cnt, 0;\n"
        "SPINWL:\n"
        "mov.u32 tt, 230880; mbarrier.try_wait.parity.shared::cta.b64 pw, [tt], 0;\n"
        "@pw bra.uni BACKW;\n"
        "add.u32 cnt, cnt, 1; setp.lt.u32 pw, cnt, 0x100000;\n"
        "@pw bra.uni SPINWL;\n"
        "trap;\n"
        "SPIN5: mov.u32 cnt, 0;\n"
        "SPIN5L:\n"
        "mbarrier.try_wait.parity.shared::cta.b64 pw, [n+231552], 0;\n"
        "@pw bra.uni BACK5;\n"
        "add.u32 cnt, cnt, 1; setp.lt.u32 pw, cnt, 0x100000;\n"
        "@pw bra.uni SPIN5L;\n"
        "trap;\n"
        "SPIN0: mov.u32 cnt, 0;\n"
        "SPIN0L:\n"
        "mbarrier.try_wait.parity.shared::cta.b64 pw, [n+231560], 0;\n"
        "@pw bra.uni BACK0;\n"
        "add.u32 cnt, cnt, 1; setp.lt.u32 pw, cnt, 0x100000;\n"
        "@pw bra.uni SPIN0L;\n"
        "trap;\n"
        "SPIN: mov.u32 cnt, 0;\n"
        "SPINL:\n"
        "mbarrier.try_wait.parity.shared::cta.b64 pw, [n+231568], 0;\n"
        "@pw bra.uni BACK;\n"
        "add.u32 cnt, cnt, 1; setp.lt.u32 pw, cnt, 0x100000;\n"
        "@pw bra.uni SPINL;\n"
        "trap;\n"
        "DUTY:\n"
        "setp.ge.s32 pr, n, %11;\n"
        "@pr bra.uni FLUSH;\n"
        "setp.ge.u32 pr, %13, 2;\n"
        "@pr bra.uni ROLE2;\n"
        "setp.ge.s32 pr, n, %12; selp.b64 src, %14, gp, pr; add.u32 tt, n, 231296;\n"
        "elect.sync _|pr, 0xffffffff;\n"
        "@pr mbarrier.arrive.expect_tx.shared::cta.b64 _, [tt], %10;\n"
        "@pr cp.async.bulk.shared::cluster.global.mbarrier::complete_tx::bytes [%9], [src], %10, [tt];\n"
        "bra.uni FLUSH;\n"
        "ROLE2:\n"
        "setp.eq.u32 pr, %13, 3;\n"
        "@pr bra.uni ROLE3;\n"
        "setp.ne.s32 pr, n, 192;\n"
        "@pr bra.uni NOFLAG;\n"
        "cp.async.bulk.wait_group 0;\n"
        "mov.u32 tt, 230784; ld.shared.u32 tt, [tt]; add.u32 tt, tt, 1;\n"
        "@pl st.relaxed.gpu.global.u32 [%22], tt;\n"
        "NOFLAG:\n"
        "setp.ne.s32 pr, n, 248;\n"
        "@pr bra.uni PARK;\n"
        "cp.async.bulk.wait_group 0;\n"
        "sub.s64 src, gp, %16; mov.u32 tt, 230824; mov.u32 cnt, 187392;\n"
        "elect.sync _|pr, 0xffffffff;\n"
        "@pr mbarrier.arrive.expect_tx.shared::cta.b64 _, [tt], 12288;\n"
        "@pr cp.async.bulk.shared::cluster.global.mbarrier::complete_tx::bytes [cnt], [src], 12288, [tt];\n"
        "PARK:\n"
        "elect.sync _|pr, 0xffffffff;\n"
        "@pr cp.async.bulk.global.shared::cta.bulk_group [gp], [%9], 12288;\n"
        "@pr cp.async.bulk.commit_group;\n"
        "bra.uni FLUSH;\n"
        "ROLE3:\n"
        "setp.ne.s32 pr, n, 64;\n"
        "@pr bra.uni AHEAD;\n"
        "mov.u32 tt, 230872;\n"
        "elect.sync _|pr, 0xffffffff;\n"
        "@pr mbarrier.arrive.expect_tx.shared::cta.b64 _, [tt], 75264;\n"
        "mov.u32 cnt, 229248; @pr cp.async.bulk.shared::cluster.global.mbarrier::complete_tx::bytes [cnt], [%18], 768, [tt];\n"
        "mov.u32 cnt, 230016; @pr cp.async.bulk.shared::cluster.global.mbarrier::complete_tx::bytes [cnt], [%19], 768, [tt];\n"
        "mov.u32 cnt, 74752; @pr cp.async.bulk.tensor.2d.shared::cluster.global.mbarrier::complete_tx::bytes [cnt], [%17, {0, 0}], [tt];\n"
        "mov.u32 cnt, 87040; @pr cp.async.bulk.tensor.2d.shared::cluster.global.mbarrier::complete_tx::bytes [cnt], [%17, {0, 192}], [tt];\n"
        "mov.u32 cnt, 99328; @pr cp.async.bulk.tensor.2d.shared::cluster.global.mbarrier::complete_tx::bytes [cnt], [%17, {32, 0}], [tt];\n"
        "mov.u32 cnt, 111616; @pr cp.async.bulk.tensor.2d.shared::cluster.global.mbarrier::complete_tx::bytes [cnt], [%17, {32, 192}], [tt];\n"
        "mov.u32 cnt, 123904; @pr cp.async.bulk.tensor.2d.shared::cluster.global.mbarrier::complete_tx::bytes [cnt], [%17, {64, 0}], [tt];\n"
        "mov.u32 cnt, 136192; @pr cp.async.bulk.tensor.2d.shared::cluster.global.mbarrier::complete_tx::bytes [cnt], [%17, {64, 192}], [tt];\n"
        "AHEAD:\n"
        "elect.sync _|pr, 0xffffffff;\n"
        "@pr cp.async.bulk.prefetch.L2.global [gp], 12288;\n"
        "FLUSH:\n"
        "add.s64 gp, gp, %16;\n"
        "mov.b32 {xl, xh}, q0; cvt.f32.f16 f0, xl; cvt.f32.f16 f1, xh; add.f32 f0, f0, f1; add.f32 %0, %0, f0; mov.b32 q0, 0;\n"
        "mov.b32 {xl, xh}, q1; cvt.f32.f16 f0, xl; cvt.f32.f16 f1, xh; add.f32 f0, f0, f1; add.f32 %1, %1, f0; mov.b32 q1, 0;\n"
        "mov.b32 {xl, xh}, q2; cvt.f32.f16 f0, xl; cvt.f32.f16 f1, xh; add.f32 f0, f0, f1; add.f32 %2, %2, f0; mov.b32 q2, 0;\n"
        "mov.b32 {xl, xh}, q3; cvt.f32.f16 f0, xl; cvt.f32.f16 f1, xh; add.f32 f0, f0, f1; add.f32 %3, %3, f0; mov.b32 q3, 0;\n"
        "setp.ne.u32 pr, %5, 0;\n"
        "@pr bra.uni TOP;\n"
        "wgmma.wait_group.sync.aligned 0;\n"
        "wgmma.fence.sync.aligned;\n"
        "ld.volatile.shared.v2.b32 {lo0, hi0}, [so]; xor.b32 f0, f0, lo0;\n"
        "ld.volatile.shared.v2.b32 {lo1, hi1}, [so]; xor.b32 f0, f0, lo1;\n"
        "ld.volatile.shared.v2.b32 {q1, a0}, [so]; xor.b32 f0, f0, q1;\n"
        "ld.volatile.shared.v2.b32 {q2, a1}, [so]; xor.b32 f0, f0, q2;\n"
        "ld.volatile.shared.v2.b32 {q3, a2}, [so]; xor.b32 f0, f0, q3;\n"
        "ld.volatile.shared.v2.b32 {q0, a3}, [so]; xor.b32 f0, f0, q0;\n"
        "ld.volatile.shared.v2.b32 {t, g}, [so]; xor.b32 f0, f0, t;\n"
        "ld.volatile.shared.v2.b32 {p, f1}, [so]; xor.b32 f0, f0, p;\n"
        "add.f32 %0, %0, f0;\n"
        "setp.eq.u32 pr, n, 1000; @pr bra.uni B31;\n"
        "setp.eq.u32 pr, n, 1001; @pr bra.uni B0;\n"
        "setp.eq.u32 pr, n, 1002; @pr bra.uni B1;\n"
        "setp.eq.u32 pr, n, 1003; @pr bra.uni B2;\n"
        "setp.eq.u32 pr, n, 1004; @pr bra.uni B3;\n"
        "setp.eq.u32 pr, n, 1005; @pr bra.uni B4;\n"
        "setp.eq.u32 pr, n, 1006; @pr bra.uni B5;\n"
        "setp.eq.u32 pr, n, 1007; @pr bra.uni B6;\n"
        "setp.eq.u32 pr, n, 1008; @pr bra.uni B7;\n"
        "setp.eq.u32 pr, n, 1009; @pr bra.uni B8;\n"
        "setp.eq.u32 pr, n, 1010; @pr bra.uni B9;\n"
        "setp.eq.u32 pr, n, 1011; @pr bra.uni B10;\n"
        "setp.eq.u32 pr, n, 1012; @pr bra.uni B11;\n"
        "setp.eq.u32 pr, n, 1013; @pr bra.uni B12;\n"
        "setp.eq.u32 pr, n, 1014; @pr bra.uni B13;\n"
        "setp.eq.u32 pr, n, 1015; @pr bra.uni B14;\n"
        "setp.eq.u32 pr, n, 1016; @pr bra.uni B15;\n"
        "setp.eq.u32 pr, n, 1017; @pr bra.uni B16;\n"
        "setp.eq.u32 pr, n, 1018; @pr bra.uni B17;\n"
        "setp.eq.u32 pr, n, 1019; @pr bra.uni B18;\n"
        "setp.eq.u32 pr, n, 1020; @pr bra.uni B19;\n"
        "setp.eq.u32 pr, n, 1021; @pr bra.uni B20;\n"
        "setp.eq.u32 pr, n, 1022; @pr bra.uni B21;\n"
        "setp.eq.u32 pr, n, 1023; @pr bra.uni B22;\n"
        "setp.eq.u32 pr, n, 1024; @pr bra.uni B23;\n"
        "setp.eq.u32 pr, n, 1025; @pr bra.uni B24;\n"
        "setp.eq.u32 pr, n, 1026; @pr bra.uni B25;\n"
        "setp.eq.u32 pr, n, 1027; @pr bra.uni B26;\n"
        "setp.eq.u32 pr, n, 1028; @pr bra.uni B27;\n"
        "setp.eq.u32 pr, n, 1029; @pr bra.uni B28;\n"
        "setp.eq.u32 pr, n, 1030; @pr bra.uni B29;\n"
        "setp.eq.u32 pr, n, 1031; @pr bra.uni TOP;\n"
        "trap;\n"
        "DONE:\n"
        ASM_TRC("n")
        "mov.b32 {xl, xh}, a2; tanh.approx.f16 xr, xh; cvt.u32.u16 hi0, xr; mul.rn.f16x2 a3, z31, p; fma.rn.f16x2 q3, g, g, q3; fma.rn.f16x2 g, z28, t, z28; prmt.b32 t, lo1, hi1, 0x5410; tanh.approx.f16 xr, xl; cvt.u32.u16 lo0, xr;\n"
        "mov.b32 {xl, xh}, a3; tanh.approx.f16 xr, xh; cvt.u32.u16 hi1, xr; fma.rn.f16x2 q2, g, g, q2; fma.rn.f16x2 g, z29, t, z29; prmt.b32 t, lo0, hi0, 0x5410; tanh.approx.f16 xr, xl; cvt.u32.u16 lo1, xr;\n"
        "fma.rn.f16x2 q3, g, g, q3; fma.rn.f16x2 g, z30, t, z30; prmt.b32 t, lo1, hi1, 0x5410;\n"
        "fma.rn.f16x2 q2, g, g, q2; fma.rn.f16x2 g, z31, t, z31;\n"
        "fma.rn.f16x2 q3, g, g, q3;\n"
        "mov.b32 {xl, xh}, q0; cvt.f32.f16 f0, xl; cvt.f32.f16 f1, xh; add.f32 f0, f0, f1; add.f32 %0, %0, f0; mov.b32 q0, 0;\n"
        "mov.b32 {xl, xh}, q1; cvt.f32.f16 f0, xl; cvt.f32.f16 f1, xh; add.f32 f0, f0, f1; add.f32 %1, %1, f0; mov.b32 q1, 0;\n"
        "mov.b32 {xl, xh}, q2; cvt.f32.f16 f0, xl; cvt.f32.f16 f1, xh; add.f32 f0, f0, f1; add.f32 %2, %2, f0; mov.b32 q2, 0;\n"
        "mov.b32 {xl, xh}, q3; cvt.f32.f16 f0, xl; cvt.f32.f16 f1, xh; add.f32 f0, f0, f1; add.f32 %3, %3, f0; mov.b32 q3, 0;\n"
        "wgmma.wait_group.sync.aligned 0;\n"
        "}\n"
        : "=f"(acc[0][0]), "=f"(acc[0][1]), "=f"(acc[1][0]), "=f"(acc[1][1])
        : "r"(w1t), "r"(yd), "r"(wd), "r"(own_slot), "l"(d.g), "r"(d.s), "r"(d.bytes), "r"(8 * d.end), "r"(8 * d.zero), "r"(role),
          "l"(d.zeros), "r"(lane), "l"(d.step), "l"(&prm.w2_map), "l"(prm.gamma), "l"(prm.beta), "l"(prm.ydesc64[0]), "l"(prm.ydesc64[1]),
          "l"(prm.g->parked + fresh_cta())
        : "memory");
}

template <int M>
__device__ __forceinline__ void gemm1_t(uint32_t (&d)[16], const uint32_t* wa, uint32_t yd, uint32_t wd) {
    wg_fence();
    wgmma_n64_h_set<0>(d, wa, desc<1024, 1>(yd, 0));
#pragma unroll
    for (int kk = 1; kk < 5; kk++)
        wgmma_n64_h_acc<0>(d, wa + kk * 4, kk < 4 ? desc<1024, 1>(yd, kk * 32) : desc<512, 2>(yd, 8192 + (kk - 4) * 32));
    wgmma_n64_h_acc_ss(d, desc<1024, 1>(wd, M * 12288), desc<512, 2>(yd, 8192 + 32));
    wg_commit();
}

__device__ __forceinline__ void gelu_sumsq_f(const uint32_t (&d)[16], float (&acc)[2]) {
#pragma unroll
    for (int r = 0; r < 16; r++) {
        float lo, hi;
        h2_unpack(gelu2(d[r]), lo, hi);
        acc[r & 1] = fmaf(lo, lo, acc[r & 1]);
        acc[r & 1] = fmaf(hi, hi, acc[r & 1]);
    }
}
__device__ __forceinline__ void load_w1t(uint32_t (&wa)[2][24], int wg, int w, int lane) {
#pragma unroll
    for (int m = 0; m < 2; m++)
#pragma unroll
        for (int kk = 0; kk < 5; kk++) {
            const int q = lane >> 3, c = 16 * kk + 8 * (q >> 1) + (lane & 7), ck = 2 * w + (q & 1);
            ldsm4_t(wa[m] + kk * 4, sb + SM_W1 + (2 * wg + m) * 12288 + c * 128 + ((ck ^ (c & 7)) * 16));
        }
}
__device__ __forceinline__ unsigned long long* acc_word(const Params& prm, uint32_t epoch, uint32_t e) {
    return &prm.g->acc[epoch & 1][(e >> 2) * 32 + (e & 3)];
}
__device__ __forceinline__ void publish_fast(const Params& prm, const float (&acc)[2][2], uint32_t epoch, int wg, int w, int lane) {
    const bool m = lane & 2, h = lane & 1;
    const float a = (m ? acc[1][0] : acc[0][0]) + __shfl_xor_sync(0xffffffffu, m ? acc[0][0] : acc[1][0], 2);
    const float b = (m ? acc[1][1] : acc[0][1]) + __shfl_xor_sync(0xffffffffu, m ? acc[0][1] : acc[1][1], 2);
    const float v = (h ? b : a) + __shfl_xor_sync(0xffffffffu, h ? a : b, 1);
    const unsigned long long q = (__float2ull_rn(fminf(v, ACC_LIMIT) * 0x1p16f) << 8) + 1;
    asm volatile("red.relaxed.gpu.global.add.u64 [%0], %1;"
                 ::"l"(acc_word(prm, epoch, 128 * wg + 32 * (lane & 2) + 16 * w + (lane >> 2) + 8 * (lane & 1))), "l"(q) : "memory");
}
__device__ __forceinline__ void collect_fast(const unsigned long long* word, uint32_t ctas, float (&ss)[3]) {
    unsigned long long v[3];
    asm volatile(
        "{\n.reg .pred p;\n.reg .u32 n, lo, hi;\n.reg .b64 w;\nmov.u32 n, 0;\n"
        "POLL:\nld.relaxed.gpu.global.u64 %0, [%3];\nld.relaxed.gpu.global.u64 %1, [%3+8192];\nld.relaxed.gpu.global.u64 %2, [%3+16384];\n"
        "and.b64 w, %0, %1;\nand.b64 w, w, %2;\nmov.b64 {lo, hi}, w;\nand.b32 lo, lo, 255;\n"
        "setp.eq.u32 p, lo, %4;\nvote.sync.all.pred p, p, 0xffffffff;\n@p bra.uni POLL_DONE;\n"
        "add.u32 n, n, 1;\nsetp.lt.u32 p, n, 0x400000;\n@p bra.uni POLL;\ntrap;\nPOLL_DONE:\n}\n"
        : "=&l"(v[0]), "=&l"(v[1]), "=&l"(v[2]) : "l"(word), "r"(ctas) : "memory");
#pragma unroll
    for (int k = 0; k < 3; k++) ss[k] = __ull2float_rn(v[k] >> 8) * 0x1p-16f;
}
__device__ __forceinline__ void publish_sums(const float (&acc)[2][2], float* sums, unsigned int* counter, int wg, int w, int lane) {
#pragma unroll
    for (int m = 0; m < 2; m++)
#pragma unroll
        for (int h = 0; h < 2; h++) {
            const float v = quad_sum(acc[m][h]);
            if ((lane & 3) == 0) atomicAdd(sums + 64 * (2 * wg + m) + 16 * w + (lane >> 2) + 8 * h, v);
        }
    named_sync(1, 384);
    if (fresh_tid() == 0) asm volatile("red.release.gpu.global.add.u32 [%0], 1;" ::"l"(counter) : "memory");
}
__device__ __forceinline__ void grid_wait(const unsigned int* counter, unsigned int target) {
    if (fresh_tid() == 0) {
        unsigned int v, spins = 0;
        do {
            asm volatile("ld.acquire.gpu.global.u32 %0, [%1];" : "=r"(v) : "l"(counter) : "memory");
            if (++spins > (1u << 22)) __trap();
        } while ((int)(v - target) < 0);
    }
    __syncthreads();
}

struct Pass2 {
    uint32_t wg;
    uint32_t off;
    int step;
    uint32_t xs;
    uint32_t a_offs, xs_offs, bias_addr;
    uint32_t w;
    int last;
    const void* park;
};

static_assert(BAR_Y2FULL == 0 && BAR_XSFULL == 4 && BAR_TURN == 11 && BAR_ROWS == 51 && BAR_STAT == 54 &&
              sb + SM_RED + RED_SCALE * 4 == 230792, "layout");
__device__ __forceinline__ bool pass2_tiles(const Pass2& c, const Params& prm, uint32_t round) {
    uint32_t retry;
    asm volatile(
        "{\n"
        ".reg .b32 qa<24>, qz<32>, o<24>, g<16>, p<2>, a<4>, lo<2>, hi<2>, h<2>, osc, v<8>, r<24>, t<2>;\n"
        ".reg .b32 n, off, c, tt, ad, cnt, ybar, xbar, tbar, tpar, id;\n"
        ".reg .b16 xl, xh, xr;\n"
        ".reg .f32 f0, f1;\n"
        ".reg .b64 w1d, w2d, dt, gp, gq, pol;\n"
        ".reg .pred pt, pf, pr, pw, pl, pm, pz, pn;\n"
        "setp.ne.b32 pt, 1, 0; setp.ne.b32 pf, 0, 0; setp.eq.u32 pl, %10, 0; setp.eq.u32 pz, %1, 0;\n"
        "mov.b32 c, 0x40D940D9;\n"
        "mov.b64 w1d, {%1, 0x40000040}; mov.b64 w2d, {%2, 0x80000020};\n"
        "mad.lo.u32 ybar, %3, 8, 230800; mad.lo.u32 xbar, %3, 8, 230832; add.u32 id, %3, 2;\n"
        "mad.lo.u32 tbar, %3, 64, 230888; setp.eq.u32 pr, %3, 0; selp.u32 tpar, 1, 0, pr; mov.u32 tt, %laneid; setp.eq.u32 pn, tt, 0;\n"
        "mov.u32 n, -1; add.u32 off, %4, %9; mov.pred pm, pt; createpolicy.fractional.L2::evict_first.b64 pol, 1.0;\n"
        "mbarrier.try_wait.parity.shared::cta.b64 pw, [ybar], 0;\n"
        "@!pw bra.uni SPINY0;\n"
        "BACKY0:\n"
        "and.b32 t0, %6, 0xffff; shr.u32 t1, %6, 16;\n"
        "xor.b32 ad, t0, 0; add.u32 ad, ad, %5; ldmatrix.sync.aligned.m8n8.x4.shared.b16 {qa0,qa1,qa2,qa3}, [ad];\n"
        "xor.b32 ad, t0, 32; add.u32 ad, ad, %5; ldmatrix.sync.aligned.m8n8.x4.shared.b16 {qa4,qa5,qa6,qa7}, [ad];\n"
        "xor.b32 ad, t0, 64; add.u32 ad, ad, %5; ldmatrix.sync.aligned.m8n8.x4.shared.b16 {qa8,qa9,qa10,qa11}, [ad];\n"
        "xor.b32 ad, t0, 96; add.u32 ad, ad, %5; ldmatrix.sync.aligned.m8n8.x4.shared.b16 {qa12,qa13,qa14,qa15}, [ad];\n"
        "xor.b32 ad, t1, 0; add.u32 ad, ad, %5; ldmatrix.sync.aligned.m8n8.x4.shared.b16 {qa16,qa17,qa18,qa19}, [ad];\n"
        "xor.b32 ad, t1, 32; add.u32 ad, ad, %5; ldmatrix.sync.aligned.m8n8.x4.shared.b16 {qa20,qa21,qa22,qa23}, [ad];\n"
        "wgmma.fence.sync.aligned;\n"
        "add.s64 dt, w1d, 0; wgmma.mma_async.sync.aligned.m64n64k16.f16.f16.f16 {qz0,qz1,qz2,qz3,qz4,qz5,qz6,qz7,qz8,qz9,qz10,qz11,qz12,qz13,qz14,qz15}, {qa0,qa1,qa2,qa3}, dt, pf, 1, 1, 1;\n"
        "add.s64 dt, w1d, 128; wgmma.mma_async.sync.aligned.m64n64k16.f16.f16.f16 {qz0,qz1,qz2,qz3,qz4,qz5,qz6,qz7,qz8,qz9,qz10,qz11,qz12,qz13,qz14,qz15}, {qa4,qa5,qa6,qa7}, dt, pt, 1, 1, 1;\n"
        "add.s64 dt, w1d, 256; wgmma.mma_async.sync.aligned.m64n64k16.f16.f16.f16 {qz0,qz1,qz2,qz3,qz4,qz5,qz6,qz7,qz8,qz9,qz10,qz11,qz12,qz13,qz14,qz15}, {qa8,qa9,qa10,qa11}, dt, pt, 1, 1, 1;\n"
        "add.s64 dt, w1d, 384; wgmma.mma_async.sync.aligned.m64n64k16.f16.f16.f16 {qz0,qz1,qz2,qz3,qz4,qz5,qz6,qz7,qz8,qz9,qz10,qz11,qz12,qz13,qz14,qz15}, {qa12,qa13,qa14,qa15}, dt, pt, 1, 1, 1;\n"
        "add.s64 dt, w1d, 512; wgmma.mma_async.sync.aligned.m64n64k16.f16.f16.f16 {qz0,qz1,qz2,qz3,qz4,qz5,qz6,qz7,qz8,qz9,qz10,qz11,qz12,qz13,qz14,qz15}, {qa16,qa17,qa18,qa19}, dt, pt, 1, 1, 1;\n"
        "add.s64 dt, w1d, 640; wgmma.mma_async.sync.aligned.m64n64k16.f16.f16.f16 {qz0,qz1,qz2,qz3,qz4,qz5,qz6,qz7,qz8,qz9,qz10,qz11,qz12,qz13,qz14,qz15}, {qa20,qa21,qa22,qa23}, dt, pt, 1, 1, 1;\n"
        "wgmma.commit_group.sync.aligned;\n"
        "mov.b32 g0, 0; mov.b32 g1, 0; mov.b32 g2, 0; mov.b32 g3, 0; mov.b32 g4, 0; mov.b32 g5, 0; mov.b32 g6, 0; mov.b32 g7, 0; mov.b32 g8, 0; mov.b32 g9, 0; mov.b32 g10, 0; mov.b32 g11, 0; mov.b32 g12, 0; mov.b32 g13, 0; mov.b32 g14, 0; mov.b32 g15, 0; mov.b32 o0, 0; mov.b32 o1, 0; mov.b32 o2, 0; mov.b32 o3, 0; mov.b32 o4, 0; mov.b32 o5, 0; mov.b32 o6, 0; mov.b32 o7, 0; mov.b32 o8, 0; mov.b32 o9, 0; mov.b32 o10, 0; mov.b32 o11, 0; mov.b32 o12, 0; mov.b32 o13, 0; mov.b32 o14, 0; mov.b32 o15, 0; mov.b32 o16, 0; mov.b32 o17, 0; mov.b32 o18, 0; mov.b32 o19, 0; mov.b32 o20, 0; mov.b32 o21, 0; mov.b32 o22, 0; mov.b32 o23, 0;\n"
        "mov.b32 osc, 0;\n"
        "wgmma.wait_group.sync.aligned 0;\n"
        "fma.rn.f16x2 p0, qz0, qz0, c;\n"
        "mul.rn.f16x2 a0, qz0, p0; fma.rn.f16x2 p1, qz1, qz1, c;\n"
        "mov.b32 {xl, xh}, a0; tanh.approx.f16 xr, xl; cvt.u32.u16 lo0, xr; tanh.approx.f16 xr, xh; cvt.u32.u16 hi0, xr; mul.rn.f16x2 a1, qz1, p1; fma.rn.f16x2 p0, qz2, qz2, c;\n"
        "mov.b32 {xl, xh}, a1; tanh.approx.f16 xr, xl; cvt.u32.u16 lo1, xr; tanh.approx.f16 xr, xh; cvt.u32.u16 hi1, xr; mul.rn.f16x2 a2, qz2, p0; fma.rn.f16x2 p1, qz3, qz3, c; prmt.b32 h0, lo0, hi0, 0x5410;\n"
        "mov.b32 {xl, xh}, a2; tanh.approx.f16 xr, xl; cvt.u32.u16 lo0, xr; tanh.approx.f16 xr, xh; cvt.u32.u16 hi0, xr; mul.rn.f16x2 a3, qz3, p1; fma.rn.f16x2 p0, qz4, qz4, c; fma.rn.f16x2 g0, qz0, h0, qz0; prmt.b32 h1, lo1, hi1, 0x5410;\n"
        "mov.b32 {xl, xh}, a3; tanh.approx.f16 xr, xl; cvt.u32.u16 lo1, xr; tanh.approx.f16 xr, xh; cvt.u32.u16 hi1, xr; mul.rn.f16x2 a0, qz4, p0; fma.rn.f16x2 p1, qz5, qz5, c; fma.rn.f16x2 g1, qz1, h1, qz1; prmt.b32 h0, lo0, hi0, 0x5410;\n"
        "mov.b32 {xl, xh}, a0; tanh.approx.f16 xr, xl; cvt.u32.u16 lo0, xr; tanh.approx.f16 xr, xh; cvt.u32.u16 hi0, xr; mul.rn.f16x2 a1, qz5, p1; fma.rn.f16x2 p0, qz6, qz6, c; fma.rn.f16x2 g2, qz2, h0, qz2; prmt.b32 h1, lo1, hi1, 0x5410;\n"
        "mov.b32 {xl, xh}, a1; tanh.approx.f16 xr, xl; cvt.u32.u16 lo1, xr; tanh.approx.f16 xr, xh; cvt.u32.u16 hi1, xr; mul.rn.f16x2 a2, qz6, p0; fma.rn.f16x2 p1, qz7, qz7, c; fma.rn.f16x2 g3, qz3, h1, qz3; prmt.b32 h0, lo0, hi0, 0x5410;\n"
        "LOOP:\n"
        "wgmma.fence.sync.aligned;\n"
        "add.s64 dt, w1d, 768; wgmma.mma_async.sync.aligned.m64n64k16.f16.f16.f16 {qz16,qz17,qz18,qz19,qz20,qz21,qz22,qz23,qz24,qz25,qz26,qz27,qz28,qz29,qz30,qz31}, {qa0,qa1,qa2,qa3}, dt, pf, 1, 1, 1;\n"
        "add.s64 dt, w1d, 896; wgmma.mma_async.sync.aligned.m64n64k16.f16.f16.f16 {qz16,qz17,qz18,qz19,qz20,qz21,qz22,qz23,qz24,qz25,qz26,qz27,qz28,qz29,qz30,qz31}, {qa4,qa5,qa6,qa7}, dt, pt, 1, 1, 1;\n"
        "add.s64 dt, w1d, 1024; wgmma.mma_async.sync.aligned.m64n64k16.f16.f16.f16 {qz16,qz17,qz18,qz19,qz20,qz21,qz22,qz23,qz24,qz25,qz26,qz27,qz28,qz29,qz30,qz31}, {qa8,qa9,qa10,qa11}, dt, pt, 1, 1, 1;\n"
        "add.s64 dt, w1d, 1152; wgmma.mma_async.sync.aligned.m64n64k16.f16.f16.f16 {qz16,qz17,qz18,qz19,qz20,qz21,qz22,qz23,qz24,qz25,qz26,qz27,qz28,qz29,qz30,qz31}, {qa12,qa13,qa14,qa15}, dt, pt, 1, 1, 1;\n"
        "add.s64 dt, w1d, 1280; wgmma.mma_async.sync.aligned.m64n64k16.f16.f16.f16 {qz16,qz17,qz18,qz19,qz20,qz21,qz22,qz23,qz24,qz25,qz26,qz27,qz28,qz29,qz30,qz31}, {qa16,qa17,qa18,qa19}, dt, pt, 1, 1, 1;\n"
        "add.s64 dt, w1d, 1408; wgmma.mma_async.sync.aligned.m64n64k16.f16.f16.f16 {qz16,qz17,qz18,qz19,qz20,qz21,qz22,qz23,qz24,qz25,qz26,qz27,qz28,qz29,qz30,qz31}, {qa20,qa21,qa22,qa23}, dt, pt, 1, 1, 1;\n"
        "setp.lt.s32 pr, n, 0;\n"
        "@pr bra.uni FIRST;\n"
        "and.b32 tt, n, 1; mbarrier.try_wait.parity.shared::cta.b64 pw, [xbar], tt;\n"
        "@!pw bra.uni SPINX;\n"
        "BACKX:\n"
        "and.b32 ad, %7, 0xffff; add.u32 ad, ad, %5; ld.shared.v4.b32 {v0,v1,v2,v3}, [ad+0];\n"
        "shr.u32 ad, %7, 16; add.u32 ad, ad, %5; ld.shared.v4.b32 {v4,v5,v6,v7}, [ad+0];\n"
        "mov.b32 {xl, xh}, o0; cvt.f32.f16 f0, xl; cvt.f32.f16 f1, xh; cvt.rn.bf16x2.f32 tt, f1, f0; fma.rn.bf16x2 v0, tt, osc, v0;\n"
        "mov.b32 {xl, xh}, o2; cvt.f32.f16 f0, xl; cvt.f32.f16 f1, xh; cvt.rn.bf16x2.f32 tt, f1, f0; fma.rn.bf16x2 v1, tt, osc, v1;\n"
        "mov.b32 {xl, xh}, o4; cvt.f32.f16 f0, xl; cvt.f32.f16 f1, xh; cvt.rn.bf16x2.f32 tt, f1, f0; fma.rn.bf16x2 v2, tt, osc, v2;\n"
        "mov.b32 {xl, xh}, o6; cvt.f32.f16 f0, xl; cvt.f32.f16 f1, xh; cvt.rn.bf16x2.f32 tt, f1, f0; fma.rn.bf16x2 v3, tt, osc, v3;\n"
        "and.b32 ad, %7, 0xffff; add.u32 ad, ad, %5; st.shared.v4.b32 [ad+0], {v0,v1,v2,v3};\n"
        "and.b32 ad, %7, 0xffff; add.u32 ad, ad, %5; ld.shared.v4.b32 {v0,v1,v2,v3}, [ad+64];\n"
        "mov.b32 {xl, xh}, o1; cvt.f32.f16 f0, xl; cvt.f32.f16 f1, xh; cvt.rn.bf16x2.f32 tt, f1, f0; fma.rn.bf16x2 v4, tt, osc, v4;\n"
        "mov.b32 {xl, xh}, o3; cvt.f32.f16 f0, xl; cvt.f32.f16 f1, xh; cvt.rn.bf16x2.f32 tt, f1, f0; fma.rn.bf16x2 v5, tt, osc, v5;\n"
        "mov.b32 {xl, xh}, o5; cvt.f32.f16 f0, xl; cvt.f32.f16 f1, xh; cvt.rn.bf16x2.f32 tt, f1, f0; fma.rn.bf16x2 v6, tt, osc, v6;\n"
        "mov.b32 {xl, xh}, o7; cvt.f32.f16 f0, xl; cvt.f32.f16 f1, xh; cvt.rn.bf16x2.f32 tt, f1, f0; fma.rn.bf16x2 v7, tt, osc, v7;\n"
        "shr.u32 ad, %7, 16; add.u32 ad, ad, %5; st.shared.v4.b32 [ad+0], {v4,v5,v6,v7};\n"
        "shr.u32 ad, %7, 16; add.u32 ad, ad, %5; ld.shared.v4.b32 {v4,v5,v6,v7}, [ad+64];\n"
        "ld.shared.v4.b32 {o0,o1,o2,o3}, [%8+0];\n"
        "ld.shared.v4.b32 {o4,o5,o6,o7}, [%8+64];\n"
        "mov.b32 {xl, xh}, o8; cvt.f32.f16 f0, xl; cvt.f32.f16 f1, xh; cvt.rn.bf16x2.f32 tt, f1, f0; fma.rn.bf16x2 v0, tt, osc, v0;\n"
        "mov.b32 {xl, xh}, o10; cvt.f32.f16 f0, xl; cvt.f32.f16 f1, xh; cvt.rn.bf16x2.f32 tt, f1, f0; fma.rn.bf16x2 v1, tt, osc, v1;\n"
        "mov.b32 {xl, xh}, o12; cvt.f32.f16 f0, xl; cvt.f32.f16 f1, xh; cvt.rn.bf16x2.f32 tt, f1, f0; fma.rn.bf16x2 v2, tt, osc, v2;\n"
        "mov.b32 {xl, xh}, o14; cvt.f32.f16 f0, xl; cvt.f32.f16 f1, xh; cvt.rn.bf16x2.f32 tt, f1, f0; fma.rn.bf16x2 v3, tt, osc, v3;\n"
        "and.b32 ad, %7, 0xffff; add.u32 ad, ad, %5; st.shared.v4.b32 [ad+64], {v0,v1,v2,v3};\n"
        "and.b32 ad, %7, 0xffff; add.u32 ad, ad, %5; ld.shared.v4.b32 {v0,v1,v2,v3}, [ad+128];\n"
        "mov.b32 {xl, xh}, o9; cvt.f32.f16 f0, xl; cvt.f32.f16 f1, xh; cvt.rn.bf16x2.f32 tt, f1, f0; fma.rn.bf16x2 v4, tt, osc, v4;\n"
        "mov.b32 {xl, xh}, o11; cvt.f32.f16 f0, xl; cvt.f32.f16 f1, xh; cvt.rn.bf16x2.f32 tt, f1, f0; fma.rn.bf16x2 v5, tt, osc, v5;\n"
        "mov.b32 {xl, xh}, o13; cvt.f32.f16 f0, xl; cvt.f32.f16 f1, xh; cvt.rn.bf16x2.f32 tt, f1, f0; fma.rn.bf16x2 v6, tt, osc, v6;\n"
        "mov.b32 {xl, xh}, o15; cvt.f32.f16 f0, xl; cvt.f32.f16 f1, xh; cvt.rn.bf16x2.f32 tt, f1, f0; fma.rn.bf16x2 v7, tt, osc, v7;\n"
        "shr.u32 ad, %7, 16; add.u32 ad, ad, %5; st.shared.v4.b32 [ad+64], {v4,v5,v6,v7};\n"
        "shr.u32 ad, %7, 16; add.u32 ad, ad, %5; ld.shared.v4.b32 {v4,v5,v6,v7}, [ad+128];\n"
        "ld.shared.v4.b32 {o8,o9,o10,o11}, [%8+128];\n"
        "ld.shared.v4.b32 {o12,o13,o14,o15}, [%8+192];\n"
        "mov.b32 {xl, xh}, o16; cvt.f32.f16 f0, xl; cvt.f32.f16 f1, xh; cvt.rn.bf16x2.f32 tt, f1, f0; fma.rn.bf16x2 v0, tt, osc, v0;\n"
        "mov.b32 {xl, xh}, o18; cvt.f32.f16 f0, xl; cvt.f32.f16 f1, xh; cvt.rn.bf16x2.f32 tt, f1, f0; fma.rn.bf16x2 v1, tt, osc, v1;\n"
        "mov.b32 {xl, xh}, o20; cvt.f32.f16 f0, xl; cvt.f32.f16 f1, xh; cvt.rn.bf16x2.f32 tt, f1, f0; fma.rn.bf16x2 v2, tt, osc, v2;\n"
        "mov.b32 {xl, xh}, o22; cvt.f32.f16 f0, xl; cvt.f32.f16 f1, xh; cvt.rn.bf16x2.f32 tt, f1, f0; fma.rn.bf16x2 v3, tt, osc, v3;\n"
        "and.b32 ad, %7, 0xffff; add.u32 ad, ad, %5; st.shared.v4.b32 [ad+128], {v0,v1,v2,v3};\n"
        "mov.b32 {xl, xh}, o17; cvt.f32.f16 f0, xl; cvt.f32.f16 f1, xh; cvt.rn.bf16x2.f32 tt, f1, f0; fma.rn.bf16x2 v4, tt, osc, v4;\n"
        "mov.b32 {xl, xh}, o19; cvt.f32.f16 f0, xl; cvt.f32.f16 f1, xh; cvt.rn.bf16x2.f32 tt, f1, f0; fma.rn.bf16x2 v5, tt, osc, v5;\n"
        "mov.b32 {xl, xh}, o21; cvt.f32.f16 f0, xl; cvt.f32.f16 f1, xh; cvt.rn.bf16x2.f32 tt, f1, f0; fma.rn.bf16x2 v6, tt, osc, v6;\n"
        "mov.b32 {xl, xh}, o23; cvt.f32.f16 f0, xl; cvt.f32.f16 f1, xh; cvt.rn.bf16x2.f32 tt, f1, f0; fma.rn.bf16x2 v7, tt, osc, v7;\n"
        "shr.u32 ad, %7, 16; add.u32 ad, ad, %5; st.shared.v4.b32 [ad+128], {v4,v5,v6,v7};\n"
        "ld.shared.v4.b32 {o16,o17,o18,o19}, [%8+256];\n"
        "ld.shared.v4.b32 {o20,o21,o22,o23}, [%8+320];\n"
        "FIRST:\n"
        "@pz bra.uni B7;\n"
        "mov.b32 {xl, xh}, a2; tanh.approx.f16 xr, xl; cvt.u32.u16 lo0, xr; tanh.approx.f16 xr, xh; cvt.u32.u16 hi0, xr; mul.rn.f16x2 a3, qz7, p1; fma.rn.f16x2 p0, qz8, qz8, c; fma.rn.f16x2 g4, qz4, h0, qz4; prmt.b32 h1, lo1, hi1, 0x5410;\n"
        "B7:\n"
        "fence.proxy.async.shared::cta;\n"
        "add.u32 tt, id, 4;\n"
        "@pl bra.uni STORE;\n"
        "bar.arrive tt, 128;\n"
        "STOREB:\n"
        ASM_MARK
        "add.s32 n, n, 1; sub.u32 off, off, %9; setp.lt.s32 pm, n, %14;\n"
        "@pz bra.uni B10;\n"
        "mov.b32 {xl, xh}, a3; tanh.approx.f16 xr, xl; cvt.u32.u16 lo1, xr; tanh.approx.f16 xr, xh; cvt.u32.u16 hi1, xr; mul.rn.f16x2 a0, qz8, p0; fma.rn.f16x2 p1, qz9, qz9, c; fma.rn.f16x2 g5, qz5, h1, qz5; prmt.b32 h0, lo0, hi0, 0x5410;\n"
        "mov.b32 {xl, xh}, a0; tanh.approx.f16 xr, xl; cvt.u32.u16 lo0, xr; tanh.approx.f16 xr, xh; cvt.u32.u16 hi0, xr; mul.rn.f16x2 a1, qz9, p1; fma.rn.f16x2 p0, qz10, qz10, c; fma.rn.f16x2 g6, qz6, h0, qz6; prmt.b32 h1, lo1, hi1, 0x5410;\n"
        "mov.b32 {xl, xh}, a1; tanh.approx.f16 xr, xl; cvt.u32.u16 lo1, xr; tanh.approx.f16 xr, xh; cvt.u32.u16 hi1, xr; mul.rn.f16x2 a2, qz10, p0; fma.rn.f16x2 p1, qz11, qz11, c; fma.rn.f16x2 g7, qz7, h1, qz7; prmt.b32 h0, lo0, hi0, 0x5410;\n"
        "B10:\n"
        "setp.eq.s32 pr, n, 0;\n"
        "@pr bra.uni SPINR;\n"
        "BACKW0:\n"
        "wgmma.fence.sync.aligned;\n"
        "add.s64 dt, w2d, 0; wgmma.mma_async.sync.aligned.m64n96k16.f16.f16.f16 {o0,o1,o2,o3,o4,o5,o6,o7,o8,o9,o10,o11,o12,o13,o14,o15,o16,o17,o18,o19,o20,o21,o22,o23}, {g0,g1,g2,g3}, dt, pt, 1, 1, 1;\n"
        "add.s64 dt, w2d, 64; wgmma.mma_async.sync.aligned.m64n96k16.f16.f16.f16 {o0,o1,o2,o3,o4,o5,o6,o7,o8,o9,o10,o11,o12,o13,o14,o15,o16,o17,o18,o19,o20,o21,o22,o23}, {g4,g5,g6,g7}, dt, pt, 1, 1, 1;\n"
        "wgmma.commit_group.sync.aligned;\n"
        "@pz bra.uni B14;\n"
        "mov.b32 {xl, xh}, a2; tanh.approx.f16 xr, xl; cvt.u32.u16 lo0, xr; tanh.approx.f16 xr, xh; cvt.u32.u16 hi0, xr; mul.rn.f16x2 a3, qz11, p1; fma.rn.f16x2 p0, qz12, qz12, c; fma.rn.f16x2 g8, qz8, h0, qz8; prmt.b32 h1, lo1, hi1, 0x5410;\n"
        "mov.b32 {xl, xh}, a3; tanh.approx.f16 xr, xl; cvt.u32.u16 lo1, xr; tanh.approx.f16 xr, xh; cvt.u32.u16 hi1, xr; mul.rn.f16x2 a0, qz12, p0; fma.rn.f16x2 p1, qz13, qz13, c; fma.rn.f16x2 g9, qz9, h1, qz9; prmt.b32 h0, lo0, hi0, 0x5410;\n"
        "mov.b32 {xl, xh}, a0; tanh.approx.f16 xr, xl; cvt.u32.u16 lo0, xr; tanh.approx.f16 xr, xh; cvt.u32.u16 hi0, xr; mul.rn.f16x2 a1, qz13, p1; fma.rn.f16x2 p0, qz14, qz14, c; fma.rn.f16x2 g10, qz10, h0, qz10; prmt.b32 h1, lo1, hi1, 0x5410;\n"
        "mov.b32 {xl, xh}, a1; tanh.approx.f16 xr, xl; cvt.u32.u16 lo1, xr; tanh.approx.f16 xr, xh; cvt.u32.u16 hi1, xr; mul.rn.f16x2 a2, qz14, p0; fma.rn.f16x2 p1, qz15, qz15, c; fma.rn.f16x2 g11, qz11, h1, qz11; prmt.b32 h0, lo0, hi0, 0x5410;\n"
        "B14:\n"
        "wgmma.wait_group.sync.aligned 0;\n"
        "mad.lo.u32 tt, n, 8, tbar; mbarrier.try_wait.parity.shared::cta.b64 pw, [tt], tpar;\n"
        "@!pw bra.uni SPINT;\n"
        "BACKT:\n"
        "wgmma.fence.sync.aligned;\n"
        "add.s64 dt, w2d, 128; wgmma.mma_async.sync.aligned.m64n96k16.f16.f16.f16 {o0,o1,o2,o3,o4,o5,o6,o7,o8,o9,o10,o11,o12,o13,o14,o15,o16,o17,o18,o19,o20,o21,o22,o23}, {g8,g9,g10,g11}, dt, pt, 1, 1, 1;\n"
        "wgmma.commit_group.sync.aligned;\n"
        "@pz bra.uni B18;\n"
        "mov.b32 {xl, xh}, a2; tanh.approx.f16 xr, xl; cvt.u32.u16 lo0, xr; tanh.approx.f16 xr, xh; cvt.u32.u16 hi0, xr; mul.rn.f16x2 a3, qz15, p1; fma.rn.f16x2 p0, qz16, qz16, c; fma.rn.f16x2 g12, qz12, h0, qz12; prmt.b32 h1, lo1, hi1, 0x5410;\n"
        "mov.b32 {xl, xh}, a3; tanh.approx.f16 xr, xl; cvt.u32.u16 lo1, xr; tanh.approx.f16 xr, xh; cvt.u32.u16 hi1, xr; mul.rn.f16x2 a0, qz16, p0; fma.rn.f16x2 p1, qz17, qz17, c; fma.rn.f16x2 g13, qz13, h1, qz13; prmt.b32 h0, lo0, hi0, 0x5410;\n"
        "mov.b32 {xl, xh}, a0; tanh.approx.f16 xr, xl; cvt.u32.u16 lo0, xr; tanh.approx.f16 xr, xh; cvt.u32.u16 hi0, xr; mul.rn.f16x2 a1, qz17, p1; fma.rn.f16x2 p0, qz18, qz18, c; fma.rn.f16x2 g14, qz14, h0, qz14; prmt.b32 h1, lo1, hi1, 0x5410;\n"
        "mov.b32 {xl, xh}, a1; tanh.approx.f16 xr, xl; cvt.u32.u16 lo1, xr; tanh.approx.f16 xr, xh; cvt.u32.u16 hi1, xr; mul.rn.f16x2 a2, qz18, p0; fma.rn.f16x2 p1, qz19, qz19, c; fma.rn.f16x2 g15, qz15, h1, qz15; prmt.b32 h0, lo0, hi0, 0x5410;\n"
        "B18:\n"
        "wgmma.fence.sync.aligned;\n"
        "add.s64 dt, w2d, 192; wgmma.mma_async.sync.aligned.m64n96k16.f16.f16.f16 {o0,o1,o2,o3,o4,o5,o6,o7,o8,o9,o10,o11,o12,o13,o14,o15,o16,o17,o18,o19,o20,o21,o22,o23}, {g12,g13,g14,g15}, dt, pt, 1, 1, 1;\n"
        "add.s64 dt, w1d, 1536; wgmma.mma_async.sync.aligned.m64n64k16.f16.f16.f16 {qz0,qz1,qz2,qz3,qz4,qz5,qz6,qz7,qz8,qz9,qz10,qz11,qz12,qz13,qz14,qz15}, {qa0,qa1,qa2,qa3}, dt, pf, 1, 1, 1;\n"
        "add.s64 dt, w1d, 1664; wgmma.mma_async.sync.aligned.m64n64k16.f16.f16.f16 {qz0,qz1,qz2,qz3,qz4,qz5,qz6,qz7,qz8,qz9,qz10,qz11,qz12,qz13,qz14,qz15}, {qa4,qa5,qa6,qa7}, dt, pt, 1, 1, 1;\n"
        "add.s64 dt, w1d, 1792; wgmma.mma_async.sync.aligned.m64n64k16.f16.f16.f16 {qz0,qz1,qz2,qz3,qz4,qz5,qz6,qz7,qz8,qz9,qz10,qz11,qz12,qz13,qz14,qz15}, {qa8,qa9,qa10,qa11}, dt, pt, 1, 1, 1;\n"
        "wgmma.commit_group.sync.aligned;\n"
        "@pl bra.uni YLOAD;\n"
        "YLOADB:\n"
        "@pz bra.uni B22;\n"
        "mov.b32 {xl, xh}, a2; tanh.approx.f16 xr, xl; cvt.u32.u16 lo0, xr; tanh.approx.f16 xr, xh; cvt.u32.u16 hi0, xr; mul.rn.f16x2 a3, qz19, p1; fma.rn.f16x2 p0, qz20, qz20, c; fma.rn.f16x2 g0, qz16, h0, qz16; prmt.b32 h1, lo1, hi1, 0x5410;\n"
        "mov.b32 {xl, xh}, a3; tanh.approx.f16 xr, xl; cvt.u32.u16 lo1, xr; tanh.approx.f16 xr, xh; cvt.u32.u16 hi1, xr; mul.rn.f16x2 a0, qz20, p0; fma.rn.f16x2 p1, qz21, qz21, c; fma.rn.f16x2 g1, qz17, h1, qz17; prmt.b32 h0, lo0, hi0, 0x5410;\n"
        "mov.b32 {xl, xh}, a0; tanh.approx.f16 xr, xl; cvt.u32.u16 lo0, xr; tanh.approx.f16 xr, xh; cvt.u32.u16 hi0, xr; mul.rn.f16x2 a1, qz21, p1; fma.rn.f16x2 p0, qz22, qz22, c; fma.rn.f16x2 g2, qz18, h0, qz18; prmt.b32 h1, lo1, hi1, 0x5410;\n"
        "mov.b32 {xl, xh}, a1; tanh.approx.f16 xr, xl; cvt.u32.u16 lo1, xr; tanh.approx.f16 xr, xh; cvt.u32.u16 hi1, xr; mul.rn.f16x2 a2, qz22, p0; fma.rn.f16x2 p1, qz23, qz23, c; fma.rn.f16x2 g3, qz19, h1, qz19; prmt.b32 h0, lo0, hi0, 0x5410;\n"
        "B22:\n"
        "wgmma.fence.sync.aligned;\n"
        "add.s64 dt, w1d, 1920; wgmma.mma_async.sync.aligned.m64n64k16.f16.f16.f16 {qz0,qz1,qz2,qz3,qz4,qz5,qz6,qz7,qz8,qz9,qz10,qz11,qz12,qz13,qz14,qz15}, {qa12,qa13,qa14,qa15}, dt, pt, 1, 1, 1;\n"
        "add.s64 dt, w1d, 2048; wgmma.mma_async.sync.aligned.m64n64k16.f16.f16.f16 {qz0,qz1,qz2,qz3,qz4,qz5,qz6,qz7,qz8,qz9,qz10,qz11,qz12,qz13,qz14,qz15}, {qa16,qa17,qa18,qa19}, dt, pt, 1, 1, 1;\n"
        "add.s64 dt, w1d, 2176; wgmma.mma_async.sync.aligned.m64n64k16.f16.f16.f16 {qz0,qz1,qz2,qz3,qz4,qz5,qz6,qz7,qz8,qz9,qz10,qz11,qz12,qz13,qz14,qz15}, {qa20,qa21,qa22,qa23}, dt, pt, 1, 1, 1;\n"
        "wgmma.commit_group.sync.aligned;\n"
        "@pz bra.uni B26;\n"
        "mov.b32 {xl, xh}, a2; tanh.approx.f16 xr, xl; cvt.u32.u16 lo0, xr; tanh.approx.f16 xr, xh; cvt.u32.u16 hi0, xr; mul.rn.f16x2 a3, qz23, p1; fma.rn.f16x2 p0, qz24, qz24, c; fma.rn.f16x2 g4, qz20, h0, qz20; prmt.b32 h1, lo1, hi1, 0x5410;\n"
        "mov.b32 {xl, xh}, a3; tanh.approx.f16 xr, xl; cvt.u32.u16 lo1, xr; tanh.approx.f16 xr, xh; cvt.u32.u16 hi1, xr; mul.rn.f16x2 a0, qz24, p0; fma.rn.f16x2 p1, qz25, qz25, c; fma.rn.f16x2 g5, qz21, h1, qz21; prmt.b32 h0, lo0, hi0, 0x5410;\n"
        "mov.b32 {xl, xh}, a0; tanh.approx.f16 xr, xl; cvt.u32.u16 lo0, xr; tanh.approx.f16 xr, xh; cvt.u32.u16 hi0, xr; mul.rn.f16x2 a1, qz25, p1; fma.rn.f16x2 p0, qz26, qz26, c; fma.rn.f16x2 g6, qz22, h0, qz22; prmt.b32 h1, lo1, hi1, 0x5410;\n"
        "mov.b32 {xl, xh}, a1; tanh.approx.f16 xr, xl; cvt.u32.u16 lo1, xr; tanh.approx.f16 xr, xh; cvt.u32.u16 hi1, xr; mul.rn.f16x2 a2, qz26, p0; fma.rn.f16x2 p1, qz27, qz27, c; fma.rn.f16x2 g7, qz23, h1, qz23; prmt.b32 h0, lo0, hi0, 0x5410;\n"
        "B26:\n"
        "wgmma.wait_group.sync.aligned 2;\n"
        "wgmma.fence.sync.aligned;\n"
        "add.s64 dt, w2d, 256; wgmma.mma_async.sync.aligned.m64n96k16.f16.f16.f16 {o0,o1,o2,o3,o4,o5,o6,o7,o8,o9,o10,o11,o12,o13,o14,o15,o16,o17,o18,o19,o20,o21,o22,o23}, {g0,g1,g2,g3}, dt, pt, 1, 1, 1;\n"
        "add.s64 dt, w2d, 320; wgmma.mma_async.sync.aligned.m64n96k16.f16.f16.f16 {o0,o1,o2,o3,o4,o5,o6,o7,o8,o9,o10,o11,o12,o13,o14,o15,o16,o17,o18,o19,o20,o21,o22,o23}, {g4,g5,g6,g7}, dt, pt, 1, 1, 1;\n"
        "wgmma.commit_group.sync.aligned;\n"
        "@pz bra.uni B30;\n"
        "mov.b32 {xl, xh}, a2; tanh.approx.f16 xr, xl; cvt.u32.u16 lo0, xr; tanh.approx.f16 xr, xh; cvt.u32.u16 hi0, xr; mul.rn.f16x2 a3, qz27, p1; fma.rn.f16x2 p0, qz28, qz28, c; fma.rn.f16x2 g8, qz24, h0, qz24; prmt.b32 h1, lo1, hi1, 0x5410;\n"
        "mov.b32 {xl, xh}, a3; tanh.approx.f16 xr, xl; cvt.u32.u16 lo1, xr; tanh.approx.f16 xr, xh; cvt.u32.u16 hi1, xr; mul.rn.f16x2 a0, qz28, p0; fma.rn.f16x2 p1, qz29, qz29, c; fma.rn.f16x2 g9, qz25, h1, qz25; prmt.b32 h0, lo0, hi0, 0x5410;\n"
        "mov.b32 {xl, xh}, a0; tanh.approx.f16 xr, xl; cvt.u32.u16 lo0, xr; tanh.approx.f16 xr, xh; cvt.u32.u16 hi0, xr; mul.rn.f16x2 a1, qz29, p1; fma.rn.f16x2 p0, qz30, qz30, c; fma.rn.f16x2 g10, qz26, h0, qz26; prmt.b32 h1, lo1, hi1, 0x5410;\n"
        "mov.b32 {xl, xh}, a1; tanh.approx.f16 xr, xl; cvt.u32.u16 lo1, xr; tanh.approx.f16 xr, xh; cvt.u32.u16 hi1, xr; mul.rn.f16x2 a2, qz30, p0; fma.rn.f16x2 p1, qz31, qz31, c; fma.rn.f16x2 g11, qz27, h1, qz27; prmt.b32 h0, lo0, hi0, 0x5410;\n"
        "B30:\n"
        "wgmma.wait_group.sync.aligned 1;\n"
        "wgmma.fence.sync.aligned;\n"
        "add.s64 dt, w2d, 384; wgmma.mma_async.sync.aligned.m64n96k16.f16.f16.f16 {o0,o1,o2,o3,o4,o5,o6,o7,o8,o9,o10,o11,o12,o13,o14,o15,o16,o17,o18,o19,o20,o21,o22,o23}, {g8,g9,g10,g11}, dt, pt, 1, 1, 1;\n"
        "wgmma.commit_group.sync.aligned;\n"
        "@pz bra.uni B34;\n"
        "mov.b32 {xl, xh}, a2; tanh.approx.f16 xr, xl; cvt.u32.u16 lo0, xr; tanh.approx.f16 xr, xh; cvt.u32.u16 hi0, xr; mul.rn.f16x2 a3, qz31, p1; fma.rn.f16x2 p0, qz0, qz0, c; fma.rn.f16x2 g12, qz28, h0, qz28; prmt.b32 h1, lo1, hi1, 0x5410;\n"
        "mov.b32 {xl, xh}, a3; tanh.approx.f16 xr, xl; cvt.u32.u16 lo1, xr; tanh.approx.f16 xr, xh; cvt.u32.u16 hi1, xr; mul.rn.f16x2 a0, qz0, p0; fma.rn.f16x2 p1, qz1, qz1, c; fma.rn.f16x2 g13, qz29, h1, qz29; prmt.b32 h0, lo0, hi0, 0x5410;\n"
        "mov.b32 {xl, xh}, a0; tanh.approx.f16 xr, xl; cvt.u32.u16 lo0, xr; tanh.approx.f16 xr, xh; cvt.u32.u16 hi0, xr; mul.rn.f16x2 a1, qz1, p1; fma.rn.f16x2 p0, qz2, qz2, c; fma.rn.f16x2 g14, qz30, h0, qz30; prmt.b32 h1, lo1, hi1, 0x5410;\n"
        "mov.b32 {xl, xh}, a1; tanh.approx.f16 xr, xl; cvt.u32.u16 lo1, xr; tanh.approx.f16 xr, xh; cvt.u32.u16 hi1, xr; mul.rn.f16x2 a2, qz2, p0; fma.rn.f16x2 p1, qz3, qz3, c; fma.rn.f16x2 g15, qz31, h1, qz31; prmt.b32 h0, lo0, hi0, 0x5410;\n"
        "B34:\n"
        "wgmma.wait_group.sync.aligned 1;\n"
        "wgmma.fence.sync.aligned;\n"
        "add.s64 dt, w2d, 448; wgmma.mma_async.sync.aligned.m64n96k16.f16.f16.f16 {o0,o1,o2,o3,o4,o5,o6,o7,o8,o9,o10,o11,o12,o13,o14,o15,o16,o17,o18,o19,o20,o21,o22,o23}, {g12,g13,g14,g15}, dt, pt, 1, 1, 1;\n"
        "add.s64 dt, w1d, 2304; wgmma.mma_async.sync.aligned.m64n64k16.f16.f16.f16 {qz16,qz17,qz18,qz19,qz20,qz21,qz22,qz23,qz24,qz25,qz26,qz27,qz28,qz29,qz30,qz31}, {qa0,qa1,qa2,qa3}, dt, pf, 1, 1, 1;\n"
        "add.s64 dt, w1d, 2432; wgmma.mma_async.sync.aligned.m64n64k16.f16.f16.f16 {qz16,qz17,qz18,qz19,qz20,qz21,qz22,qz23,qz24,qz25,qz26,qz27,qz28,qz29,qz30,qz31}, {qa4,qa5,qa6,qa7}, dt, pt, 1, 1, 1;\n"
        "add.s64 dt, w1d, 2560; wgmma.mma_async.sync.aligned.m64n64k16.f16.f16.f16 {qz16,qz17,qz18,qz19,qz20,qz21,qz22,qz23,qz24,qz25,qz26,qz27,qz28,qz29,qz30,qz31}, {qa8,qa9,qa10,qa11}, dt, pt, 1, 1, 1;\n"
        "wgmma.commit_group.sync.aligned;\n"
        "@pz bra.uni B38;\n"
        "mov.b32 {xl, xh}, a2; tanh.approx.f16 xr, xl; cvt.u32.u16 lo0, xr; tanh.approx.f16 xr, xh; cvt.u32.u16 hi0, xr; mul.rn.f16x2 a3, qz3, p1; fma.rn.f16x2 p0, qz4, qz4, c; fma.rn.f16x2 g0, qz0, h0, qz0; prmt.b32 h1, lo1, hi1, 0x5410;\n"
        "mov.b32 {xl, xh}, a3; tanh.approx.f16 xr, xl; cvt.u32.u16 lo1, xr; tanh.approx.f16 xr, xh; cvt.u32.u16 hi1, xr; mul.rn.f16x2 a0, qz4, p0; fma.rn.f16x2 p1, qz5, qz5, c; fma.rn.f16x2 g1, qz1, h1, qz1; prmt.b32 h0, lo0, hi0, 0x5410;\n"
        "mov.b32 {xl, xh}, a0; tanh.approx.f16 xr, xl; cvt.u32.u16 lo0, xr; tanh.approx.f16 xr, xh; cvt.u32.u16 hi0, xr; mul.rn.f16x2 a1, qz5, p1; fma.rn.f16x2 p0, qz6, qz6, c; fma.rn.f16x2 g2, qz2, h0, qz2; prmt.b32 h1, lo1, hi1, 0x5410;\n"
        "mov.b32 {xl, xh}, a1; tanh.approx.f16 xr, xl; cvt.u32.u16 lo1, xr; tanh.approx.f16 xr, xh; cvt.u32.u16 hi1, xr; mul.rn.f16x2 a2, qz6, p0; fma.rn.f16x2 p1, qz7, qz7, c; fma.rn.f16x2 g3, qz3, h1, qz3; prmt.b32 h0, lo0, hi0, 0x5410;\n"
        "B38:\n"
        "wgmma.fence.sync.aligned;\n"
        "add.s64 dt, w1d, 2688; wgmma.mma_async.sync.aligned.m64n64k16.f16.f16.f16 {qz16,qz17,qz18,qz19,qz20,qz21,qz22,qz23,qz24,qz25,qz26,qz27,qz28,qz29,qz30,qz31}, {qa12,qa13,qa14,qa15}, dt, pt, 1, 1, 1;\n"
        "add.s64 dt, w1d, 2816; wgmma.mma_async.sync.aligned.m64n64k16.f16.f16.f16 {qz16,qz17,qz18,qz19,qz20,qz21,qz22,qz23,qz24,qz25,qz26,qz27,qz28,qz29,qz30,qz31}, {qa16,qa17,qa18,qa19}, dt, pt, 1, 1, 1;\n"
        "add.s64 dt, w1d, 2944; wgmma.mma_async.sync.aligned.m64n64k16.f16.f16.f16 {qz16,qz17,qz18,qz19,qz20,qz21,qz22,qz23,qz24,qz25,qz26,qz27,qz28,qz29,qz30,qz31}, {qa20,qa21,qa22,qa23}, dt, pt, 1, 1, 1;\n"
        "wgmma.commit_group.sync.aligned;\n"
        "@pz bra.uni B42;\n"
        "mov.b32 {xl, xh}, a2; tanh.approx.f16 xr, xl; cvt.u32.u16 lo0, xr; tanh.approx.f16 xr, xh; cvt.u32.u16 hi0, xr; mul.rn.f16x2 a3, qz7, p1; fma.rn.f16x2 p0, qz8, qz8, c; fma.rn.f16x2 g4, qz4, h0, qz4; prmt.b32 h1, lo1, hi1, 0x5410;\n"
        "mov.b32 {xl, xh}, a3; tanh.approx.f16 xr, xl; cvt.u32.u16 lo1, xr; tanh.approx.f16 xr, xh; cvt.u32.u16 hi1, xr; mul.rn.f16x2 a0, qz8, p0; fma.rn.f16x2 p1, qz9, qz9, c; fma.rn.f16x2 g5, qz5, h1, qz5; prmt.b32 h0, lo0, hi0, 0x5410;\n"
        "mov.b32 {xl, xh}, a0; tanh.approx.f16 xr, xl; cvt.u32.u16 lo0, xr; tanh.approx.f16 xr, xh; cvt.u32.u16 hi0, xr; mul.rn.f16x2 a1, qz9, p1; fma.rn.f16x2 p0, qz10, qz10, c; fma.rn.f16x2 g6, qz6, h0, qz6; prmt.b32 h1, lo1, hi1, 0x5410;\n"
        "mov.b32 {xl, xh}, a1; tanh.approx.f16 xr, xl; cvt.u32.u16 lo1, xr; tanh.approx.f16 xr, xh; cvt.u32.u16 hi1, xr; mul.rn.f16x2 a2, qz10, p0; fma.rn.f16x2 p1, qz11, qz11, c; fma.rn.f16x2 g7, qz7, h1, qz7; prmt.b32 h0, lo0, hi0, 0x5410;\n"
        "B42:\n"
        "wgmma.wait_group.sync.aligned 2;\n"
        "setp.eq.s32 pr, n, 0;\n"
        "@pr bra.uni SPINW1;\n"
        "BACKW1:\n"
        "wgmma.fence.sync.aligned;\n"
        "add.s64 dt, w2d, 512; wgmma.mma_async.sync.aligned.m64n96k16.f16.f16.f16 {o0,o1,o2,o3,o4,o5,o6,o7,o8,o9,o10,o11,o12,o13,o14,o15,o16,o17,o18,o19,o20,o21,o22,o23}, {g0,g1,g2,g3}, dt, pt, 1, 1, 1;\n"
        "add.s64 dt, w2d, 576; wgmma.mma_async.sync.aligned.m64n96k16.f16.f16.f16 {o0,o1,o2,o3,o4,o5,o6,o7,o8,o9,o10,o11,o12,o13,o14,o15,o16,o17,o18,o19,o20,o21,o22,o23}, {g4,g5,g6,g7}, dt, pt, 1, 1, 1;\n"
        "wgmma.commit_group.sync.aligned;\n"
        "mad.lo.u32 tt, n, 8, tbar;\n"
        "@pn mbarrier.arrive.shared::cta.b64 _, [tt+64];\n"
        "@pz bra.uni B46;\n"
        "mov.b32 {xl, xh}, a2; tanh.approx.f16 xr, xl; cvt.u32.u16 lo0, xr; tanh.approx.f16 xr, xh; cvt.u32.u16 hi0, xr; mul.rn.f16x2 a3, qz11, p1; fma.rn.f16x2 p0, qz12, qz12, c; fma.rn.f16x2 g8, qz8, h0, qz8; prmt.b32 h1, lo1, hi1, 0x5410;\n"
        "mov.b32 {xl, xh}, a3; tanh.approx.f16 xr, xl; cvt.u32.u16 lo1, xr; tanh.approx.f16 xr, xh; cvt.u32.u16 hi1, xr; mul.rn.f16x2 a0, qz12, p0; fma.rn.f16x2 p1, qz13, qz13, c; fma.rn.f16x2 g9, qz9, h1, qz9; prmt.b32 h0, lo0, hi0, 0x5410;\n"
        "mov.b32 {xl, xh}, a0; tanh.approx.f16 xr, xl; cvt.u32.u16 lo0, xr; tanh.approx.f16 xr, xh; cvt.u32.u16 hi0, xr; mul.rn.f16x2 a1, qz13, p1; fma.rn.f16x2 p0, qz14, qz14, c; fma.rn.f16x2 g10, qz10, h0, qz10; prmt.b32 h1, lo1, hi1, 0x5410;\n"
        "mov.b32 {xl, xh}, a1; tanh.approx.f16 xr, xl; cvt.u32.u16 lo1, xr; tanh.approx.f16 xr, xh; cvt.u32.u16 hi1, xr; mul.rn.f16x2 a2, qz14, p0; fma.rn.f16x2 p1, qz15, qz15, c; fma.rn.f16x2 g11, qz11, h1, qz11; prmt.b32 h0, lo0, hi0, 0x5410;\n"
        "B46:\n"
        "wgmma.wait_group.sync.aligned 1;\n"
        "wgmma.fence.sync.aligned;\n"
        "add.s64 dt, w2d, 640; wgmma.mma_async.sync.aligned.m64n96k16.f16.f16.f16 {o0,o1,o2,o3,o4,o5,o6,o7,o8,o9,o10,o11,o12,o13,o14,o15,o16,o17,o18,o19,o20,o21,o22,o23}, {g8,g9,g10,g11}, dt, pt, 1, 1, 1;\n"
        "wgmma.commit_group.sync.aligned;\n"
        "@pz bra.uni B50;\n"
        "mov.b32 {xl, xh}, a2; tanh.approx.f16 xr, xl; cvt.u32.u16 lo0, xr; tanh.approx.f16 xr, xh; cvt.u32.u16 hi0, xr; mul.rn.f16x2 a3, qz15, p1; fma.rn.f16x2 p0, qz16, qz16, c; fma.rn.f16x2 g12, qz12, h0, qz12; prmt.b32 h1, lo1, hi1, 0x5410;\n"
        "mov.b32 {xl, xh}, a3; tanh.approx.f16 xr, xl; cvt.u32.u16 lo1, xr; tanh.approx.f16 xr, xh; cvt.u32.u16 hi1, xr; mul.rn.f16x2 a0, qz16, p0; fma.rn.f16x2 p1, qz17, qz17, c; fma.rn.f16x2 g13, qz13, h1, qz13; prmt.b32 h0, lo0, hi0, 0x5410;\n"
        "mov.b32 {xl, xh}, a0; tanh.approx.f16 xr, xl; cvt.u32.u16 lo0, xr; tanh.approx.f16 xr, xh; cvt.u32.u16 hi0, xr; mul.rn.f16x2 a1, qz17, p1; fma.rn.f16x2 p0, qz18, qz18, c; fma.rn.f16x2 g14, qz14, h0, qz14; prmt.b32 h1, lo1, hi1, 0x5410;\n"
        "mov.b32 {xl, xh}, a1; tanh.approx.f16 xr, xl; cvt.u32.u16 lo1, xr; tanh.approx.f16 xr, xh; cvt.u32.u16 hi1, xr; mul.rn.f16x2 a2, qz18, p0; fma.rn.f16x2 p1, qz19, qz19, c; fma.rn.f16x2 g15, qz15, h1, qz15; prmt.b32 h0, lo0, hi0, 0x5410;\n"
        "B50:\n"
        "wgmma.wait_group.sync.aligned 1;\n"
        "wgmma.fence.sync.aligned;\n"
        "add.s64 dt, w2d, 704; wgmma.mma_async.sync.aligned.m64n96k16.f16.f16.f16 {o0,o1,o2,o3,o4,o5,o6,o7,o8,o9,o10,o11,o12,o13,o14,o15,o16,o17,o18,o19,o20,o21,o22,o23}, {g12,g13,g14,g15}, dt, pt, 1, 1, 1;\n"
        "add.s64 dt, w1d, 3072; wgmma.mma_async.sync.aligned.m64n64k16.f16.f16.f16 {qz0,qz1,qz2,qz3,qz4,qz5,qz6,qz7,qz8,qz9,qz10,qz11,qz12,qz13,qz14,qz15}, {qa0,qa1,qa2,qa3}, dt, pf, 1, 1, 1;\n"
        "add.s64 dt, w1d, 3200; wgmma.mma_async.sync.aligned.m64n64k16.f16.f16.f16 {qz0,qz1,qz2,qz3,qz4,qz5,qz6,qz7,qz8,qz9,qz10,qz11,qz12,qz13,qz14,qz15}, {qa4,qa5,qa6,qa7}, dt, pt, 1, 1, 1;\n"
        "add.s64 dt, w1d, 3328; wgmma.mma_async.sync.aligned.m64n64k16.f16.f16.f16 {qz0,qz1,qz2,qz3,qz4,qz5,qz6,qz7,qz8,qz9,qz10,qz11,qz12,qz13,qz14,qz15}, {qa8,qa9,qa10,qa11}, dt, pt, 1, 1, 1;\n"
        "wgmma.commit_group.sync.aligned;\n"
        "@pz bra.uni B54;\n"
        "mov.b32 {xl, xh}, a2; tanh.approx.f16 xr, xl; cvt.u32.u16 lo0, xr; tanh.approx.f16 xr, xh; cvt.u32.u16 hi0, xr; mul.rn.f16x2 a3, qz19, p1; fma.rn.f16x2 p0, qz20, qz20, c; fma.rn.f16x2 g0, qz16, h0, qz16; prmt.b32 h1, lo1, hi1, 0x5410;\n"
        "mov.b32 {xl, xh}, a3; tanh.approx.f16 xr, xl; cvt.u32.u16 lo1, xr; tanh.approx.f16 xr, xh; cvt.u32.u16 hi1, xr; mul.rn.f16x2 a0, qz20, p0; fma.rn.f16x2 p1, qz21, qz21, c; fma.rn.f16x2 g1, qz17, h1, qz17; prmt.b32 h0, lo0, hi0, 0x5410;\n"
        "mov.b32 {xl, xh}, a0; tanh.approx.f16 xr, xl; cvt.u32.u16 lo0, xr; tanh.approx.f16 xr, xh; cvt.u32.u16 hi0, xr; mul.rn.f16x2 a1, qz21, p1; fma.rn.f16x2 p0, qz22, qz22, c; fma.rn.f16x2 g2, qz18, h0, qz18; prmt.b32 h1, lo1, hi1, 0x5410;\n"
        "mov.b32 {xl, xh}, a1; tanh.approx.f16 xr, xl; cvt.u32.u16 lo1, xr; tanh.approx.f16 xr, xh; cvt.u32.u16 hi1, xr; mul.rn.f16x2 a2, qz22, p0; fma.rn.f16x2 p1, qz23, qz23, c; fma.rn.f16x2 g3, qz19, h1, qz19; prmt.b32 h0, lo0, hi0, 0x5410;\n"
        "B54:\n"
        "wgmma.fence.sync.aligned;\n"
        "add.s64 dt, w1d, 3456; wgmma.mma_async.sync.aligned.m64n64k16.f16.f16.f16 {qz0,qz1,qz2,qz3,qz4,qz5,qz6,qz7,qz8,qz9,qz10,qz11,qz12,qz13,qz14,qz15}, {qa12,qa13,qa14,qa15}, dt, pt, 1, 1, 1;\n"
        "add.s64 dt, w1d, 3584; wgmma.mma_async.sync.aligned.m64n64k16.f16.f16.f16 {qz0,qz1,qz2,qz3,qz4,qz5,qz6,qz7,qz8,qz9,qz10,qz11,qz12,qz13,qz14,qz15}, {qa16,qa17,qa18,qa19}, dt, pt, 1, 1, 1;\n"
        "add.s64 dt, w1d, 3712; wgmma.mma_async.sync.aligned.m64n64k16.f16.f16.f16 {qz0,qz1,qz2,qz3,qz4,qz5,qz6,qz7,qz8,qz9,qz10,qz11,qz12,qz13,qz14,qz15}, {qa20,qa21,qa22,qa23}, dt, pt, 1, 1, 1;\n"
        "wgmma.commit_group.sync.aligned;\n"
        "@pz bra.uni B58;\n"
        "mov.b32 {xl, xh}, a2; tanh.approx.f16 xr, xl; cvt.u32.u16 lo0, xr; tanh.approx.f16 xr, xh; cvt.u32.u16 hi0, xr; mul.rn.f16x2 a3, qz23, p1; fma.rn.f16x2 p0, qz24, qz24, c; fma.rn.f16x2 g4, qz20, h0, qz20; prmt.b32 h1, lo1, hi1, 0x5410;\n"
        "mov.b32 {xl, xh}, a3; tanh.approx.f16 xr, xl; cvt.u32.u16 lo1, xr; tanh.approx.f16 xr, xh; cvt.u32.u16 hi1, xr; mul.rn.f16x2 a0, qz24, p0; fma.rn.f16x2 p1, qz25, qz25, c; fma.rn.f16x2 g5, qz21, h1, qz21; prmt.b32 h0, lo0, hi0, 0x5410;\n"
        "mov.b32 {xl, xh}, a0; tanh.approx.f16 xr, xl; cvt.u32.u16 lo0, xr; tanh.approx.f16 xr, xh; cvt.u32.u16 hi0, xr; mul.rn.f16x2 a1, qz25, p1; fma.rn.f16x2 p0, qz26, qz26, c; fma.rn.f16x2 g6, qz22, h0, qz22; prmt.b32 h1, lo1, hi1, 0x5410;\n"
        "mov.b32 {xl, xh}, a1; tanh.approx.f16 xr, xl; cvt.u32.u16 lo1, xr; tanh.approx.f16 xr, xh; cvt.u32.u16 hi1, xr; mul.rn.f16x2 a2, qz26, p0; fma.rn.f16x2 p1, qz27, qz27, c; fma.rn.f16x2 g7, qz23, h1, qz23; prmt.b32 h0, lo0, hi0, 0x5410;\n"
        "B58:\n"
        "wgmma.wait_group.sync.aligned 2;\n"
        "wgmma.fence.sync.aligned;\n"
        "add.s64 dt, w2d, 768; wgmma.mma_async.sync.aligned.m64n96k16.f16.f16.f16 {o0,o1,o2,o3,o4,o5,o6,o7,o8,o9,o10,o11,o12,o13,o14,o15,o16,o17,o18,o19,o20,o21,o22,o23}, {g0,g1,g2,g3}, dt, pt, 1, 1, 1;\n"
        "add.s64 dt, w2d, 832; wgmma.mma_async.sync.aligned.m64n96k16.f16.f16.f16 {o0,o1,o2,o3,o4,o5,o6,o7,o8,o9,o10,o11,o12,o13,o14,o15,o16,o17,o18,o19,o20,o21,o22,o23}, {g4,g5,g6,g7}, dt, pt, 1, 1, 1;\n"
        "wgmma.commit_group.sync.aligned;\n"
        "@pz bra.uni B62;\n"
        "mov.b32 {xl, xh}, a2; tanh.approx.f16 xr, xl; cvt.u32.u16 lo0, xr; tanh.approx.f16 xr, xh; cvt.u32.u16 hi0, xr; mul.rn.f16x2 a3, qz27, p1; fma.rn.f16x2 p0, qz28, qz28, c; fma.rn.f16x2 g8, qz24, h0, qz24; prmt.b32 h1, lo1, hi1, 0x5410;\n"
        "mov.b32 {xl, xh}, a3; tanh.approx.f16 xr, xl; cvt.u32.u16 lo1, xr; tanh.approx.f16 xr, xh; cvt.u32.u16 hi1, xr; mul.rn.f16x2 a0, qz28, p0; fma.rn.f16x2 p1, qz29, qz29, c; fma.rn.f16x2 g9, qz25, h1, qz25; prmt.b32 h0, lo0, hi0, 0x5410;\n"
        "mov.b32 {xl, xh}, a0; tanh.approx.f16 xr, xl; cvt.u32.u16 lo0, xr; tanh.approx.f16 xr, xh; cvt.u32.u16 hi0, xr; mul.rn.f16x2 a1, qz29, p1; fma.rn.f16x2 p0, qz30, qz30, c; fma.rn.f16x2 g10, qz26, h0, qz26; prmt.b32 h1, lo1, hi1, 0x5410;\n"
        "mov.b32 {xl, xh}, a1; tanh.approx.f16 xr, xl; cvt.u32.u16 lo1, xr; tanh.approx.f16 xr, xh; cvt.u32.u16 hi1, xr; mul.rn.f16x2 a2, qz30, p0; fma.rn.f16x2 p1, qz31, qz31, c; fma.rn.f16x2 g11, qz27, h1, qz27; prmt.b32 h0, lo0, hi0, 0x5410;\n"
        "B62:\n"
        "wgmma.wait_group.sync.aligned 1;\n"
        "wgmma.fence.sync.aligned;\n"
        "add.s64 dt, w2d, 896; wgmma.mma_async.sync.aligned.m64n96k16.f16.f16.f16 {o0,o1,o2,o3,o4,o5,o6,o7,o8,o9,o10,o11,o12,o13,o14,o15,o16,o17,o18,o19,o20,o21,o22,o23}, {g8,g9,g10,g11}, dt, pt, 1, 1, 1;\n"
        "wgmma.commit_group.sync.aligned;\n"
        "@pz bra.uni B66;\n"
        "mov.b32 {xl, xh}, a2; tanh.approx.f16 xr, xl; cvt.u32.u16 lo0, xr; tanh.approx.f16 xr, xh; cvt.u32.u16 hi0, xr; mul.rn.f16x2 a3, qz31, p1; fma.rn.f16x2 p0, qz0, qz0, c; fma.rn.f16x2 g12, qz28, h0, qz28; prmt.b32 h1, lo1, hi1, 0x5410;\n"
        "mov.b32 {xl, xh}, a3; tanh.approx.f16 xr, xl; cvt.u32.u16 lo1, xr; tanh.approx.f16 xr, xh; cvt.u32.u16 hi1, xr; mul.rn.f16x2 a0, qz0, p0; fma.rn.f16x2 p1, qz1, qz1, c; fma.rn.f16x2 g13, qz29, h1, qz29; prmt.b32 h0, lo0, hi0, 0x5410;\n"
        "mov.b32 {xl, xh}, a0; tanh.approx.f16 xr, xl; cvt.u32.u16 lo0, xr; tanh.approx.f16 xr, xh; cvt.u32.u16 hi0, xr; mul.rn.f16x2 a1, qz1, p1; fma.rn.f16x2 p0, qz2, qz2, c; fma.rn.f16x2 g14, qz30, h0, qz30; prmt.b32 h1, lo1, hi1, 0x5410;\n"
        "mov.b32 {xl, xh}, a1; tanh.approx.f16 xr, xl; cvt.u32.u16 lo1, xr; tanh.approx.f16 xr, xh; cvt.u32.u16 hi1, xr; mul.rn.f16x2 a2, qz2, p0; fma.rn.f16x2 p1, qz3, qz3, c; fma.rn.f16x2 g15, qz31, h1, qz31; prmt.b32 h0, lo0, hi0, 0x5410;\n"
        "B66:\n"
        "wgmma.wait_group.sync.aligned 1;\n"
        "wgmma.fence.sync.aligned;\n"
        "add.s64 dt, w2d, 960; wgmma.mma_async.sync.aligned.m64n96k16.f16.f16.f16 {o0,o1,o2,o3,o4,o5,o6,o7,o8,o9,o10,o11,o12,o13,o14,o15,o16,o17,o18,o19,o20,o21,o22,o23}, {g12,g13,g14,g15}, dt, pt, 1, 1, 1;\n"
        "add.s64 dt, w1d, 3840; wgmma.mma_async.sync.aligned.m64n64k16.f16.f16.f16 {qz16,qz17,qz18,qz19,qz20,qz21,qz22,qz23,qz24,qz25,qz26,qz27,qz28,qz29,qz30,qz31}, {qa0,qa1,qa2,qa3}, dt, pf, 1, 1, 1;\n"
        "add.s64 dt, w1d, 3968; wgmma.mma_async.sync.aligned.m64n64k16.f16.f16.f16 {qz16,qz17,qz18,qz19,qz20,qz21,qz22,qz23,qz24,qz25,qz26,qz27,qz28,qz29,qz30,qz31}, {qa4,qa5,qa6,qa7}, dt, pt, 1, 1, 1;\n"
        "add.s64 dt, w1d, 4096; wgmma.mma_async.sync.aligned.m64n64k16.f16.f16.f16 {qz16,qz17,qz18,qz19,qz20,qz21,qz22,qz23,qz24,qz25,qz26,qz27,qz28,qz29,qz30,qz31}, {qa8,qa9,qa10,qa11}, dt, pt, 1, 1, 1;\n"
        "wgmma.commit_group.sync.aligned;\n"
        "@pz bra.uni B70;\n"
        "mov.b32 {xl, xh}, a2; tanh.approx.f16 xr, xl; cvt.u32.u16 lo0, xr; tanh.approx.f16 xr, xh; cvt.u32.u16 hi0, xr; mul.rn.f16x2 a3, qz3, p1; fma.rn.f16x2 p0, qz4, qz4, c; fma.rn.f16x2 g0, qz0, h0, qz0; prmt.b32 h1, lo1, hi1, 0x5410;\n"
        "mov.b32 {xl, xh}, a3; tanh.approx.f16 xr, xl; cvt.u32.u16 lo1, xr; tanh.approx.f16 xr, xh; cvt.u32.u16 hi1, xr; mul.rn.f16x2 a0, qz4, p0; fma.rn.f16x2 p1, qz5, qz5, c; fma.rn.f16x2 g1, qz1, h1, qz1; prmt.b32 h0, lo0, hi0, 0x5410;\n"
        "mov.b32 {xl, xh}, a0; tanh.approx.f16 xr, xl; cvt.u32.u16 lo0, xr; tanh.approx.f16 xr, xh; cvt.u32.u16 hi0, xr; mul.rn.f16x2 a1, qz5, p1; fma.rn.f16x2 p0, qz6, qz6, c; fma.rn.f16x2 g2, qz2, h0, qz2; prmt.b32 h1, lo1, hi1, 0x5410;\n"
        "mov.b32 {xl, xh}, a1; tanh.approx.f16 xr, xl; cvt.u32.u16 lo1, xr; tanh.approx.f16 xr, xh; cvt.u32.u16 hi1, xr; mul.rn.f16x2 a2, qz6, p0; fma.rn.f16x2 p1, qz7, qz7, c; fma.rn.f16x2 g3, qz3, h1, qz3; prmt.b32 h0, lo0, hi0, 0x5410;\n"
        "B70:\n"
        "wgmma.fence.sync.aligned;\n"
        "add.s64 dt, w1d, 4224; wgmma.mma_async.sync.aligned.m64n64k16.f16.f16.f16 {qz16,qz17,qz18,qz19,qz20,qz21,qz22,qz23,qz24,qz25,qz26,qz27,qz28,qz29,qz30,qz31}, {qa12,qa13,qa14,qa15}, dt, pt, 1, 1, 1;\n"
        "add.s64 dt, w1d, 4352; wgmma.mma_async.sync.aligned.m64n64k16.f16.f16.f16 {qz16,qz17,qz18,qz19,qz20,qz21,qz22,qz23,qz24,qz25,qz26,qz27,qz28,qz29,qz30,qz31}, {qa16,qa17,qa18,qa19}, dt, pt, 1, 1, 1;\n"
        "add.s64 dt, w1d, 4480; wgmma.mma_async.sync.aligned.m64n64k16.f16.f16.f16 {qz16,qz17,qz18,qz19,qz20,qz21,qz22,qz23,qz24,qz25,qz26,qz27,qz28,qz29,qz30,qz31}, {qa20,qa21,qa22,qa23}, dt, pt, 1, 1, 1;\n"
        "wgmma.commit_group.sync.aligned;\n"
        "@pz bra.uni B74;\n"
        "mov.b32 {xl, xh}, a2; tanh.approx.f16 xr, xl; cvt.u32.u16 lo0, xr; tanh.approx.f16 xr, xh; cvt.u32.u16 hi0, xr; mul.rn.f16x2 a3, qz7, p1; fma.rn.f16x2 p0, qz8, qz8, c; fma.rn.f16x2 g4, qz4, h0, qz4; prmt.b32 h1, lo1, hi1, 0x5410;\n"
        "mov.b32 {xl, xh}, a3; tanh.approx.f16 xr, xl; cvt.u32.u16 lo1, xr; tanh.approx.f16 xr, xh; cvt.u32.u16 hi1, xr; mul.rn.f16x2 a0, qz8, p0; fma.rn.f16x2 p1, qz9, qz9, c; fma.rn.f16x2 g5, qz5, h1, qz5; prmt.b32 h0, lo0, hi0, 0x5410;\n"
        "mov.b32 {xl, xh}, a0; tanh.approx.f16 xr, xl; cvt.u32.u16 lo0, xr; tanh.approx.f16 xr, xh; cvt.u32.u16 hi0, xr; mul.rn.f16x2 a1, qz9, p1; fma.rn.f16x2 p0, qz10, qz10, c; fma.rn.f16x2 g6, qz6, h0, qz6; prmt.b32 h1, lo1, hi1, 0x5410;\n"
        "mov.b32 {xl, xh}, a1; tanh.approx.f16 xr, xl; cvt.u32.u16 lo1, xr; tanh.approx.f16 xr, xh; cvt.u32.u16 hi1, xr; mul.rn.f16x2 a2, qz10, p0; fma.rn.f16x2 p1, qz11, qz11, c; fma.rn.f16x2 g7, qz7, h1, qz7; prmt.b32 h0, lo0, hi0, 0x5410;\n"
        "B74:\n"
        "wgmma.wait_group.sync.aligned 2;\n"
        "setp.eq.s32 pr, n, 0;\n"
        "@pr bra.uni SPINW2;\n"
        "BACKW2:\n"
        "wgmma.fence.sync.aligned;\n"
        "add.s64 dt, w2d, 1024; wgmma.mma_async.sync.aligned.m64n96k16.f16.f16.f16 {o0,o1,o2,o3,o4,o5,o6,o7,o8,o9,o10,o11,o12,o13,o14,o15,o16,o17,o18,o19,o20,o21,o22,o23}, {g0,g1,g2,g3}, dt, pt, 1, 1, 1;\n"
        "add.s64 dt, w2d, 1088; wgmma.mma_async.sync.aligned.m64n96k16.f16.f16.f16 {o0,o1,o2,o3,o4,o5,o6,o7,o8,o9,o10,o11,o12,o13,o14,o15,o16,o17,o18,o19,o20,o21,o22,o23}, {g4,g5,g6,g7}, dt, pt, 1, 1, 1;\n"
        "wgmma.commit_group.sync.aligned;\n"
        "@pz bra.uni B78;\n"
        "mov.b32 {xl, xh}, a2; tanh.approx.f16 xr, xl; cvt.u32.u16 lo0, xr; tanh.approx.f16 xr, xh; cvt.u32.u16 hi0, xr; mul.rn.f16x2 a3, qz11, p1; fma.rn.f16x2 p0, qz12, qz12, c; fma.rn.f16x2 g8, qz8, h0, qz8; prmt.b32 h1, lo1, hi1, 0x5410;\n"
        "mov.b32 {xl, xh}, a3; tanh.approx.f16 xr, xl; cvt.u32.u16 lo1, xr; tanh.approx.f16 xr, xh; cvt.u32.u16 hi1, xr; mul.rn.f16x2 a0, qz12, p0; fma.rn.f16x2 p1, qz13, qz13, c; fma.rn.f16x2 g9, qz9, h1, qz9; prmt.b32 h0, lo0, hi0, 0x5410;\n"
        "mov.b32 {xl, xh}, a0; tanh.approx.f16 xr, xl; cvt.u32.u16 lo0, xr; tanh.approx.f16 xr, xh; cvt.u32.u16 hi0, xr; mul.rn.f16x2 a1, qz13, p1; fma.rn.f16x2 p0, qz14, qz14, c; fma.rn.f16x2 g10, qz10, h0, qz10; prmt.b32 h1, lo1, hi1, 0x5410;\n"
        "mov.b32 {xl, xh}, a1; tanh.approx.f16 xr, xl; cvt.u32.u16 lo1, xr; tanh.approx.f16 xr, xh; cvt.u32.u16 hi1, xr; mul.rn.f16x2 a2, qz14, p0; fma.rn.f16x2 p1, qz15, qz15, c; fma.rn.f16x2 g11, qz11, h1, qz11; prmt.b32 h0, lo0, hi0, 0x5410;\n"
        "B78:\n"
        "wgmma.wait_group.sync.aligned 1;\n"
        "@!pm bra.uni BACKY;\n"
        "add.u32 tt, n, 1; and.b32 tt, tt, 1; mbarrier.try_wait.parity.shared::cta.b64 pw, [ybar], tt;\n"
        "@!pw bra.uni SPINY;\n"
        "BACKY:\n"
        "@pz bra.uni B80;\n"
        "and.b32 ad, %6, 0xffff; xor.b32 ad, ad, 0; add.u32 ad, ad, %5; ldmatrix.sync.aligned.m8n8.x4.shared.b16 {qa0,qa1,qa2,qa3}, [ad];\n"
        "and.b32 ad, %6, 0xffff; xor.b32 ad, ad, 32; add.u32 ad, ad, %5; ldmatrix.sync.aligned.m8n8.x4.shared.b16 {qa4,qa5,qa6,qa7}, [ad];\n"
        "and.b32 ad, %6, 0xffff; xor.b32 ad, ad, 64; add.u32 ad, ad, %5; ldmatrix.sync.aligned.m8n8.x4.shared.b16 {qa8,qa9,qa10,qa11}, [ad];\n"
        "and.b32 ad, %6, 0xffff; xor.b32 ad, ad, 96; add.u32 ad, ad, %5; ldmatrix.sync.aligned.m8n8.x4.shared.b16 {qa12,qa13,qa14,qa15}, [ad];\n"
        "shr.u32 ad, %6, 16; xor.b32 ad, ad, 0; add.u32 ad, ad, %5; ldmatrix.sync.aligned.m8n8.x4.shared.b16 {qa16,qa17,qa18,qa19}, [ad];\n"
        "shr.u32 ad, %6, 16; xor.b32 ad, ad, 32; add.u32 ad, ad, %5; ldmatrix.sync.aligned.m8n8.x4.shared.b16 {qa20,qa21,qa22,qa23}, [ad];\n"
        "mov.b32 {xl, xh}, a2; tanh.approx.f16 xr, xl; cvt.u32.u16 lo0, xr; tanh.approx.f16 xr, xh; cvt.u32.u16 hi0, xr; mul.rn.f16x2 a3, qz15, p1; fma.rn.f16x2 p0, qz16, qz16, c; fma.rn.f16x2 g12, qz12, h0, qz12; prmt.b32 h1, lo1, hi1, 0x5410;\n"
        "mov.b32 {xl, xh}, a3; tanh.approx.f16 xr, xl; cvt.u32.u16 lo1, xr; tanh.approx.f16 xr, xh; cvt.u32.u16 hi1, xr; mul.rn.f16x2 a0, qz16, p0; fma.rn.f16x2 p1, qz17, qz17, c; fma.rn.f16x2 g13, qz13, h1, qz13; prmt.b32 h0, lo0, hi0, 0x5410;\n"
        "B80:\n"
        "@!pm bra.uni XLOADB;\n"
        "fence.proxy.async.shared::cta;\n"
        "add.u32 tt, id, 0;\n"
        "@pl bra.uni XLOAD;\n"
        "bar.arrive tt, 128;\n"
        "XLOADB:\n"
        "wgmma.fence.sync.aligned;\n"
        "add.s64 dt, w2d, 1152; wgmma.mma_async.sync.aligned.m64n96k16.f16.f16.f16 {o0,o1,o2,o3,o4,o5,o6,o7,o8,o9,o10,o11,o12,o13,o14,o15,o16,o17,o18,o19,o20,o21,o22,o23}, {g8,g9,g10,g11}, dt, pt, 1, 1, 1;\n"
        "wgmma.commit_group.sync.aligned;\n"
        "@pz bra.uni B82;\n"
        "mov.b32 {xl, xh}, a0; tanh.approx.f16 xr, xl; cvt.u32.u16 lo0, xr; tanh.approx.f16 xr, xh; cvt.u32.u16 hi0, xr; mul.rn.f16x2 a1, qz17, p1; fma.rn.f16x2 p0, qz18, qz18, c; fma.rn.f16x2 g14, qz14, h0, qz14; prmt.b32 h1, lo1, hi1, 0x5410;\n"
        "mov.b32 {xl, xh}, a1; tanh.approx.f16 xr, xl; cvt.u32.u16 lo1, xr; tanh.approx.f16 xr, xh; cvt.u32.u16 hi1, xr; mul.rn.f16x2 a2, qz18, p0; fma.rn.f16x2 p1, qz19, qz19, c; fma.rn.f16x2 g15, qz15, h1, qz15; prmt.b32 h0, lo0, hi0, 0x5410;\n"
        "B82:\n"
        "wgmma.wait_group.sync.aligned 1;\n"
        "@!pm bra.uni SKIP0;\n"
        "wgmma.fence.sync.aligned;\n"
        "add.s64 dt, w1d, 0; wgmma.mma_async.sync.aligned.m64n64k16.f16.f16.f16 {qz0,qz1,qz2,qz3,qz4,qz5,qz6,qz7,qz8,qz9,qz10,qz11,qz12,qz13,qz14,qz15}, {qa0,qa1,qa2,qa3}, dt, pf, 1, 1, 1;\n"
        "add.s64 dt, w1d, 128; wgmma.mma_async.sync.aligned.m64n64k16.f16.f16.f16 {qz0,qz1,qz2,qz3,qz4,qz5,qz6,qz7,qz8,qz9,qz10,qz11,qz12,qz13,qz14,qz15}, {qa4,qa5,qa6,qa7}, dt, pt, 1, 1, 1;\n"
        "add.s64 dt, w1d, 256; wgmma.mma_async.sync.aligned.m64n64k16.f16.f16.f16 {qz0,qz1,qz2,qz3,qz4,qz5,qz6,qz7,qz8,qz9,qz10,qz11,qz12,qz13,qz14,qz15}, {qa8,qa9,qa10,qa11}, dt, pt, 1, 1, 1;\n"
        "SKIP0:\n"
        "wgmma.fence.sync.aligned;\n"
        "add.s64 dt, w2d, 1216; wgmma.mma_async.sync.aligned.m64n96k16.f16.f16.f16 {o0,o1,o2,o3,o4,o5,o6,o7,o8,o9,o10,o11,o12,o13,o14,o15,o16,o17,o18,o19,o20,o21,o22,o23}, {g12,g13,g14,g15}, dt, pt, 1, 1, 1;\n"
        "wgmma.commit_group.sync.aligned;\n"
        "@pz bra.uni B86;\n"
        "mov.b32 {xl, xh}, a2; tanh.approx.f16 xr, xl; cvt.u32.u16 lo0, xr; tanh.approx.f16 xr, xh; cvt.u32.u16 hi0, xr; mul.rn.f16x2 a3, qz19, p1; fma.rn.f16x2 p0, qz20, qz20, c; fma.rn.f16x2 g0, qz16, h0, qz16; prmt.b32 h1, lo1, hi1, 0x5410;\n"
        "mov.b32 {xl, xh}, a3; tanh.approx.f16 xr, xl; cvt.u32.u16 lo1, xr; tanh.approx.f16 xr, xh; cvt.u32.u16 hi1, xr; mul.rn.f16x2 a0, qz20, p0; fma.rn.f16x2 p1, qz21, qz21, c; fma.rn.f16x2 g1, qz17, h1, qz17; prmt.b32 h0, lo0, hi0, 0x5410;\n"
        "mov.b32 {xl, xh}, a0; tanh.approx.f16 xr, xl; cvt.u32.u16 lo0, xr; tanh.approx.f16 xr, xh; cvt.u32.u16 hi0, xr; mul.rn.f16x2 a1, qz21, p1; fma.rn.f16x2 p0, qz22, qz22, c; fma.rn.f16x2 g2, qz18, h0, qz18; prmt.b32 h1, lo1, hi1, 0x5410;\n"
        "mov.b32 {xl, xh}, a1; tanh.approx.f16 xr, xl; cvt.u32.u16 lo1, xr; tanh.approx.f16 xr, xh; cvt.u32.u16 hi1, xr; mul.rn.f16x2 a2, qz22, p0; fma.rn.f16x2 p1, qz23, qz23, c; fma.rn.f16x2 g3, qz19, h1, qz19; prmt.b32 h0, lo0, hi0, 0x5410;\n"
        "B86:\n"
        "@!pm bra.uni SKIP1;\n"
        "wgmma.fence.sync.aligned;\n"
        "add.s64 dt, w1d, 384; wgmma.mma_async.sync.aligned.m64n64k16.f16.f16.f16 {qz0,qz1,qz2,qz3,qz4,qz5,qz6,qz7,qz8,qz9,qz10,qz11,qz12,qz13,qz14,qz15}, {qa12,qa13,qa14,qa15}, dt, pt, 1, 1, 1;\n"
        "add.s64 dt, w1d, 512; wgmma.mma_async.sync.aligned.m64n64k16.f16.f16.f16 {qz0,qz1,qz2,qz3,qz4,qz5,qz6,qz7,qz8,qz9,qz10,qz11,qz12,qz13,qz14,qz15}, {qa16,qa17,qa18,qa19}, dt, pt, 1, 1, 1;\n"
        "add.s64 dt, w1d, 640; wgmma.mma_async.sync.aligned.m64n64k16.f16.f16.f16 {qz0,qz1,qz2,qz3,qz4,qz5,qz6,qz7,qz8,qz9,qz10,qz11,qz12,qz13,qz14,qz15}, {qa20,qa21,qa22,qa23}, dt, pt, 1, 1, 1;\n"
        "SKIP1:\n"
        "@pz bra.uni B90;\n"
        "mov.b32 {xl, xh}, a2; tanh.approx.f16 xr, xl; cvt.u32.u16 lo0, xr; tanh.approx.f16 xr, xh; cvt.u32.u16 hi0, xr; mul.rn.f16x2 a3, qz23, p1; fma.rn.f16x2 p0, qz24, qz24, c; fma.rn.f16x2 g4, qz20, h0, qz20; prmt.b32 h1, lo1, hi1, 0x5410;\n"
        "mov.b32 {xl, xh}, a3; tanh.approx.f16 xr, xl; cvt.u32.u16 lo1, xr; tanh.approx.f16 xr, xh; cvt.u32.u16 hi1, xr; mul.rn.f16x2 a0, qz24, p0; fma.rn.f16x2 p1, qz25, qz25, c; fma.rn.f16x2 g5, qz21, h1, qz21; prmt.b32 h0, lo0, hi0, 0x5410;\n"
        "mov.b32 {xl, xh}, a0; tanh.approx.f16 xr, xl; cvt.u32.u16 lo0, xr; tanh.approx.f16 xr, xh; cvt.u32.u16 hi0, xr; mul.rn.f16x2 a1, qz25, p1; fma.rn.f16x2 p0, qz26, qz26, c; fma.rn.f16x2 g6, qz22, h0, qz22; prmt.b32 h1, lo1, hi1, 0x5410;\n"
        "mov.b32 {xl, xh}, a1; tanh.approx.f16 xr, xl; cvt.u32.u16 lo1, xr; tanh.approx.f16 xr, xh; cvt.u32.u16 hi1, xr; mul.rn.f16x2 a2, qz26, p0; fma.rn.f16x2 p1, qz27, qz27, c; fma.rn.f16x2 g7, qz23, h1, qz23; prmt.b32 h0, lo0, hi0, 0x5410;\n"
        "B90:\n"
        "wgmma.wait_group.sync.aligned 1;\n"
        "wgmma.fence.sync.aligned;\n"
        "add.s64 dt, w2d, 1280; wgmma.mma_async.sync.aligned.m64n96k16.f16.f16.f16 {o0,o1,o2,o3,o4,o5,o6,o7,o8,o9,o10,o11,o12,o13,o14,o15,o16,o17,o18,o19,o20,o21,o22,o23}, {g0,g1,g2,g3}, dt, pt, 1, 1, 1;\n"
        "add.s64 dt, w2d, 1344; wgmma.mma_async.sync.aligned.m64n96k16.f16.f16.f16 {o0,o1,o2,o3,o4,o5,o6,o7,o8,o9,o10,o11,o12,o13,o14,o15,o16,o17,o18,o19,o20,o21,o22,o23}, {g4,g5,g6,g7}, dt, pt, 1, 1, 1;\n"
        "wgmma.commit_group.sync.aligned;\n"
        "@pz bra.uni B94;\n"
        "mov.b32 {xl, xh}, a2; tanh.approx.f16 xr, xl; cvt.u32.u16 lo0, xr; tanh.approx.f16 xr, xh; cvt.u32.u16 hi0, xr; mul.rn.f16x2 a3, qz27, p1; fma.rn.f16x2 p0, qz28, qz28, c; fma.rn.f16x2 g8, qz24, h0, qz24; prmt.b32 h1, lo1, hi1, 0x5410;\n"
        "mov.b32 {xl, xh}, a3; tanh.approx.f16 xr, xl; cvt.u32.u16 lo1, xr; tanh.approx.f16 xr, xh; cvt.u32.u16 hi1, xr; mul.rn.f16x2 a0, qz28, p0; fma.rn.f16x2 p1, qz29, qz29, c; fma.rn.f16x2 g9, qz25, h1, qz25; prmt.b32 h0, lo0, hi0, 0x5410;\n"
        "mov.b32 {xl, xh}, a0; tanh.approx.f16 xr, xl; cvt.u32.u16 lo0, xr; tanh.approx.f16 xr, xh; cvt.u32.u16 hi0, xr; mul.rn.f16x2 a1, qz29, p1; fma.rn.f16x2 p0, qz30, qz30, c; fma.rn.f16x2 g10, qz26, h0, qz26; prmt.b32 h1, lo1, hi1, 0x5410;\n"
        "mov.b32 {xl, xh}, a1; tanh.approx.f16 xr, xl; cvt.u32.u16 lo1, xr; tanh.approx.f16 xr, xh; cvt.u32.u16 hi1, xr; mul.rn.f16x2 a2, qz30, p0; fma.rn.f16x2 p1, qz31, qz31, c; fma.rn.f16x2 g11, qz27, h1, qz27; prmt.b32 h0, lo0, hi0, 0x5410;\n"
        "B94:\n"
        "wgmma.wait_group.sync.aligned 0;\n"
        "wgmma.fence.sync.aligned;\n"
        "add.s64 dt, w2d, 1408; wgmma.mma_async.sync.aligned.m64n96k16.f16.f16.f16 {o0,o1,o2,o3,o4,o5,o6,o7,o8,o9,o10,o11,o12,o13,o14,o15,o16,o17,o18,o19,o20,o21,o22,o23}, {g8,g9,g10,g11}, dt, pt, 1, 1, 1;\n"
        "wgmma.commit_group.sync.aligned;\n"
        "@pz bra.uni B2;\n"
        "mov.b32 {xl, xh}, a2; tanh.approx.f16 xr, xl; cvt.u32.u16 lo0, xr; tanh.approx.f16 xr, xh; cvt.u32.u16 hi0, xr; mul.rn.f16x2 a3, qz31, p1; fma.rn.f16x2 p0, qz0, qz0, c; fma.rn.f16x2 g12, qz28, h0, qz28; prmt.b32 h1, lo1, hi1, 0x5410;\n"
        "mov.b32 {xl, xh}, a3; tanh.approx.f16 xr, xl; cvt.u32.u16 lo1, xr; tanh.approx.f16 xr, xh; cvt.u32.u16 hi1, xr; mul.rn.f16x2 a0, qz0, p0; fma.rn.f16x2 p1, qz1, qz1, c; fma.rn.f16x2 g13, qz29, h1, qz29; prmt.b32 h0, lo0, hi0, 0x5410;\n"
        "mov.b32 {xl, xh}, a0; tanh.approx.f16 xr, xl; cvt.u32.u16 lo0, xr; tanh.approx.f16 xr, xh; cvt.u32.u16 hi0, xr; mul.rn.f16x2 a1, qz1, p1; fma.rn.f16x2 p0, qz2, qz2, c; fma.rn.f16x2 g14, qz30, h0, qz30; prmt.b32 h1, lo1, hi1, 0x5410;\n"
        "mov.b32 {xl, xh}, a1; tanh.approx.f16 xr, xl; cvt.u32.u16 lo1, xr; tanh.approx.f16 xr, xh; cvt.u32.u16 hi1, xr; mul.rn.f16x2 a2, qz2, p0; fma.rn.f16x2 p1, qz3, qz3, c; fma.rn.f16x2 g15, qz31, h1, qz31; prmt.b32 h0, lo0, hi0, 0x5410;\n"
        "B2:\n"
        "wgmma.fence.sync.aligned;\n"
        "add.s64 dt, w2d, 1472; wgmma.mma_async.sync.aligned.m64n96k16.f16.f16.f16 {o0,o1,o2,o3,o4,o5,o6,o7,o8,o9,o10,o11,o12,o13,o14,o15,o16,o17,o18,o19,o20,o21,o22,o23}, {g12,g13,g14,g15}, dt, pt, 1, 1, 1;\n"
        "wgmma.commit_group.sync.aligned;\n"
        "@!pm bra.uni LAST;\n"
        "@pz bra.uni BE;\n"
        "mov.b32 {xl, xh}, a2; tanh.approx.f16 xr, xl; cvt.u32.u16 lo0, xr; tanh.approx.f16 xr, xh; cvt.u32.u16 hi0, xr; mul.rn.f16x2 a3, qz3, p1; fma.rn.f16x2 p0, qz4, qz4, c; fma.rn.f16x2 g0, qz0, h0, qz0; prmt.b32 h1, lo1, hi1, 0x5410;\n"
        "mov.b32 {xl, xh}, a3; tanh.approx.f16 xr, xl; cvt.u32.u16 lo1, xr; tanh.approx.f16 xr, xh; cvt.u32.u16 hi1, xr; mul.rn.f16x2 a0, qz4, p0; fma.rn.f16x2 p1, qz5, qz5, c; fma.rn.f16x2 g1, qz1, h1, qz1; prmt.b32 h0, lo0, hi0, 0x5410;\n"
        "mov.b32 {xl, xh}, a0; tanh.approx.f16 xr, xl; cvt.u32.u16 lo0, xr; tanh.approx.f16 xr, xh; cvt.u32.u16 hi0, xr; mul.rn.f16x2 a1, qz5, p1; fma.rn.f16x2 p0, qz6, qz6, c; fma.rn.f16x2 g2, qz2, h0, qz2; prmt.b32 h1, lo1, hi1, 0x5410;\n"
        "mov.b32 {xl, xh}, a1; tanh.approx.f16 xr, xl; cvt.u32.u16 lo1, xr; tanh.approx.f16 xr, xh; cvt.u32.u16 hi1, xr; mul.rn.f16x2 a2, qz6, p0; fma.rn.f16x2 p1, qz7, qz7, c; fma.rn.f16x2 g3, qz3, h1, qz3; prmt.b32 h0, lo0, hi0, 0x5410;\n"
        "BE:\n"
        "wgmma.wait_group.sync.aligned 0;\n"
        "bra.uni LOOP;\n"
        "STORE:\n"
        "bar.sync tt, 128;\n"
        "setp.lt.s32 pr, n, 0;\n"
        "@pr bra.uni STOREB;\n"
        "cvt.u64.u32 gp, off; add.s64 gp, gp, %12;\n"
        "elect.sync _|pr, 0xffffffff;\n"
        "@pr cp.async.bulk.global.shared::cta.bulk_group [gp], [%5], 12288;\n"
        "@pr cp.async.bulk.commit_group;\n"
        "bra.uni STOREB;\n"
        "YLOAD:\n"
        "cp.async.bulk.wait_group.read 0;\n"
        "@!pm bra.uni XLAST;\n"
        "sub.u32 ad, off, %9; cvt.u64.u32 gp, ad; add.s64 gp, gp, %12;\n"
        "elect.sync _|pr, 0xffffffff;\n"
        "@pr mbarrier.arrive.expect_tx.shared::cta.b64 _, [ybar], 12288;\n"
        "@pr cp.async.bulk.shared::cluster.global.mbarrier::complete_tx::bytes [%5], [gp], 12288, [ybar];\n"
        "cvt.u64.u32 gp, off; add.s64 gp, gp, %11;\n"
        "@pr cp.async.bulk.prefetch.L2.global.L2::cache_hint [gp], 12288, pol;\n"
        "bra.uni YLOADB;\n"
        "XLAST:\n"
        "cvt.u64.u32 gp, off; add.s64 gp, gp, %11;\n"
        "elect.sync _|pr, 0xffffffff;\n"
        "@pr mbarrier.arrive.expect_tx.shared::cta.b64 _, [xbar], 12288;\n"
        "@pr cp.async.bulk.shared::cluster.global.mbarrier::complete_tx::bytes.L2::cache_hint [%5], [gp], 12288, [xbar], pol;\n"
        "bra.uni YLOADB;\n"
        "XLOAD:\n"
        "bar.sync tt, 128;\n"
        "cvt.u64.u32 gp, off; add.s64 gp, gp, %11;\n"
        "elect.sync _|pr, 0xffffffff;\n"
        "@pr mbarrier.arrive.expect_tx.shared::cta.b64 _, [xbar], 12288;\n"
        "@pr cp.async.bulk.shared::cluster.global.mbarrier::complete_tx::bytes.L2::cache_hint [%5], [gp], 12288, [xbar], pol;\n"
        "bra.uni XLOADB;\n"
        "SPINY: mov.u32 cnt, 0;\n"
        "SPINYL:\n"
        "add.u32 tt, n, 1; and.b32 tt, tt, 1; mbarrier.try_wait.parity.shared::cta.b64 pw, [ybar], tt;\n"
        "@pw bra.uni BACKY;\n"
        "add.u32 cnt, cnt, 1; setp.lt.u32 pw, cnt, 0x100000;\n"
        "@pw bra.uni SPINYL;\n"
        "trap;\n"
        "SPINX: mov.u32 cnt, 0;\n"
        "SPINXL:\n"
        "and.b32 tt, n, 1; mbarrier.try_wait.parity.shared::cta.b64 pw, [xbar], tt;\n"
        "@pw bra.uni BACKX;\n"
        "add.u32 cnt, cnt, 1; setp.lt.u32 pw, cnt, 0x100000;\n"
        "@pw bra.uni SPINXL;\n"
        "trap;\n"
        "SPINT: mov.u32 cnt, 0;\n"
        "SPINTL:\n"
        "mad.lo.u32 tt, n, 8, tbar; mbarrier.try_wait.parity.shared::cta.b64 pw, [tt], tpar;\n"
        "@pw bra.uni BACKT;\n"
        "add.u32 cnt, cnt, 1; setp.lt.u32 pw, cnt, 0x100000;\n"
        "@pw bra.uni SPINTL;\n"
        "trap;\n"
        "SPINW0: mov.u32 cnt, 0;\n"
        "SPINW0L:\n"
        "mov.u32 tt, 231208; mbarrier.try_wait.parity.shared::cta.b64 pw, [tt], 0;\n"
        "@pw bra.uni BACKW0;\n"
        "add.u32 cnt, cnt, 1; setp.lt.u32 pw, cnt, 0x100000;\n"
        "@pw bra.uni SPINW0L;\n"
        "trap;\n"
        "SPINW1: mov.u32 cnt, 0;\n"
        "SPINW1L:\n"
        "mov.u32 tt, 231216; mbarrier.try_wait.parity.shared::cta.b64 pw, [tt], 0;\n"
        "@pw bra.uni BACKW1;\n"
        "add.u32 cnt, cnt, 1; setp.lt.u32 pw, cnt, 0x100000;\n"
        "@pw bra.uni SPINW1L;\n"
        "trap;\n"
        "SPINW2: mov.u32 cnt, 0;\n"
        "SPINW2L:\n"
        "mov.u32 tt, 231224; mbarrier.try_wait.parity.shared::cta.b64 pw, [tt], 0;\n"
        "@pw bra.uni BACKW2;\n"
        "add.u32 cnt, cnt, 1; setp.lt.u32 pw, cnt, 0x100000;\n"
        "@pw bra.uni SPINW2L;\n"
        "trap;\n"
        "SPINY0: mov.u32 cnt, 0;\n"
        "SPINY0L:\n"
        "mbarrier.try_wait.parity.shared::cta.b64 pw, [ybar], 0;\n"
        "@pw bra.uni BACKY0;\n"
        "add.u32 cnt, cnt, 1; setp.lt.u32 pw, cnt, 0x100000;\n"
        "@pw bra.uni SPINY0L;\n"
        "trap;\n"
        "SPINR: mov.u32 cnt, 0;\n"
        "SPINRL:\n"
        "mov.u32 tt, 231232; mbarrier.try_wait.parity.shared::cta.b64 pw, [tt], %13;\n"
        "@pw bra.uni BACKR;\n"
        "add.u32 cnt, cnt, 1; setp.lt.u32 pw, cnt, 0x100000;\n"
        "@pw bra.uni SPINRL;\n"
        "trap;\n"
        "BACKR:\n"
        "mov.u32 tt, 230792; ld.shared.v2.b32 {osc, tt}, [tt];\n"
        "setp.ne.u32 pr, tt, 0; vote.sync.any.pred pr, pr, 0xffffffff;\n"
        "@pr bra.uni RETRY;\n"
        "setp.eq.u32 pr, %3, 0;\n"
        "@pr bra.uni BACKB;\n"
        "SPINB: mov.u32 cnt, 0;\n"
        "SPINBL:\n"
        "mov.u32 tt, 231208; mbarrier.try_wait.parity.shared::cta.b64 pw, [tt], 0;\n"
        "@pw bra.uni BACKB;\n"
        "add.u32 cnt, cnt, 1; setp.lt.u32 pw, cnt, 0x100000;\n"
        "@pw bra.uni SPINBL;\n"
        "trap;\n"
        "BACKB:\n"
        "ld.shared.v4.b32 {o0,o1,o2,o3}, [%8+0];\n"
        "ld.shared.v4.b32 {o4,o5,o6,o7}, [%8+64];\n"
        "ld.shared.v4.b32 {o8,o9,o10,o11}, [%8+128];\n"
        "ld.shared.v4.b32 {o12,o13,o14,o15}, [%8+192];\n"
        "ld.shared.v4.b32 {o16,o17,o18,o19}, [%8+256];\n"
        "ld.shared.v4.b32 {o20,o21,o22,o23}, [%8+320];\n"
        "bra.uni SPINW0;\n"
        "RETRY:\n"
        "wgmma.fence.sync.aligned;\n"
        "wgmma.commit_group.sync.aligned;\n"
        "wgmma.wait_group.sync.aligned 0;\n"
        "mov.u32 %0, 1;\n"
        "bra.uni OUT;\n"
        "SPINL: mov.u32 cnt, 0;\n"
        "SPINLL:\n"
        "and.b32 tt, n, 1; mbarrier.try_wait.parity.shared::cta.b64 pw, [xbar], tt;\n"
        "@pw bra.uni BACKL;\n"
        "add.u32 cnt, cnt, 1; setp.lt.u32 pw, cnt, 0x100000;\n"
        "@pw bra.uni SPINLL;\n"
        "trap;\n"
        "LAST:\n"
        "and.b32 tt, n, 1; mbarrier.try_wait.parity.shared::cta.b64 pw, [xbar], tt;\n"
        "@!pw bra.uni SPINL;\n"
        "BACKL:\n"
        "and.b32 ad, %7, 0xffff; add.u32 ad, ad, %5; ld.shared.v4.b32 {r0,r1,r2,r3}, [ad+0];\n"
        "shr.u32 ad, %7, 16; add.u32 ad, ad, %5; ld.shared.v4.b32 {r4,r5,r6,r7}, [ad+0];\n"
        "and.b32 ad, %7, 0xffff; add.u32 ad, ad, %5; ld.shared.v4.b32 {r8,r9,r10,r11}, [ad+64];\n"
        "shr.u32 ad, %7, 16; add.u32 ad, ad, %5; ld.shared.v4.b32 {r12,r13,r14,r15}, [ad+64];\n"
        "and.b32 ad, %7, 0xffff; add.u32 ad, ad, %5; ld.shared.v4.b32 {r16,r17,r18,r19}, [ad+128];\n"
        "shr.u32 ad, %7, 16; add.u32 ad, ad, %5; ld.shared.v4.b32 {r20,r21,r22,r23}, [ad+128];\n"
        "wgmma.wait_group.sync.aligned 0;\n"
        "mov.b32 {xl, xh}, o0; cvt.f32.f16 f0, xl; cvt.f32.f16 f1, xh; cvt.rn.bf16x2.f32 tt, f1, f0; fma.rn.bf16x2 r0, tt, osc, r0;\n"
        "mov.b32 {xl, xh}, o2; cvt.f32.f16 f0, xl; cvt.f32.f16 f1, xh; cvt.rn.bf16x2.f32 tt, f1, f0; fma.rn.bf16x2 r1, tt, osc, r1;\n"
        "mov.b32 {xl, xh}, o4; cvt.f32.f16 f0, xl; cvt.f32.f16 f1, xh; cvt.rn.bf16x2.f32 tt, f1, f0; fma.rn.bf16x2 r2, tt, osc, r2;\n"
        "mov.b32 {xl, xh}, o6; cvt.f32.f16 f0, xl; cvt.f32.f16 f1, xh; cvt.rn.bf16x2.f32 tt, f1, f0; fma.rn.bf16x2 r3, tt, osc, r3;\n"
        "and.b32 ad, %7, 0xffff; add.u32 ad, ad, off; cvt.u64.u32 gp, ad; add.s64 gp, gp, %12; st.global.v4.b32 [gp+0], {r0,r1,r2,r3};\n"
        "mov.b32 {xl, xh}, o1; cvt.f32.f16 f0, xl; cvt.f32.f16 f1, xh; cvt.rn.bf16x2.f32 tt, f1, f0; fma.rn.bf16x2 r4, tt, osc, r4;\n"
        "mov.b32 {xl, xh}, o3; cvt.f32.f16 f0, xl; cvt.f32.f16 f1, xh; cvt.rn.bf16x2.f32 tt, f1, f0; fma.rn.bf16x2 r5, tt, osc, r5;\n"
        "mov.b32 {xl, xh}, o5; cvt.f32.f16 f0, xl; cvt.f32.f16 f1, xh; cvt.rn.bf16x2.f32 tt, f1, f0; fma.rn.bf16x2 r6, tt, osc, r6;\n"
        "mov.b32 {xl, xh}, o7; cvt.f32.f16 f0, xl; cvt.f32.f16 f1, xh; cvt.rn.bf16x2.f32 tt, f1, f0; fma.rn.bf16x2 r7, tt, osc, r7;\n"
        "shr.u32 ad, %7, 16; add.u32 ad, ad, off; cvt.u64.u32 gp, ad; add.s64 gp, gp, %12; st.global.v4.b32 [gp+0], {r4,r5,r6,r7};\n"
        "mov.b32 {xl, xh}, o8; cvt.f32.f16 f0, xl; cvt.f32.f16 f1, xh; cvt.rn.bf16x2.f32 tt, f1, f0; fma.rn.bf16x2 r8, tt, osc, r8;\n"
        "mov.b32 {xl, xh}, o10; cvt.f32.f16 f0, xl; cvt.f32.f16 f1, xh; cvt.rn.bf16x2.f32 tt, f1, f0; fma.rn.bf16x2 r9, tt, osc, r9;\n"
        "mov.b32 {xl, xh}, o12; cvt.f32.f16 f0, xl; cvt.f32.f16 f1, xh; cvt.rn.bf16x2.f32 tt, f1, f0; fma.rn.bf16x2 r10, tt, osc, r10;\n"
        "mov.b32 {xl, xh}, o14; cvt.f32.f16 f0, xl; cvt.f32.f16 f1, xh; cvt.rn.bf16x2.f32 tt, f1, f0; fma.rn.bf16x2 r11, tt, osc, r11;\n"
        "and.b32 ad, %7, 0xffff; add.u32 ad, ad, off; cvt.u64.u32 gp, ad; add.s64 gp, gp, %12; st.global.v4.b32 [gp+64], {r8,r9,r10,r11};\n"
        "mov.b32 {xl, xh}, o9; cvt.f32.f16 f0, xl; cvt.f32.f16 f1, xh; cvt.rn.bf16x2.f32 tt, f1, f0; fma.rn.bf16x2 r12, tt, osc, r12;\n"
        "mov.b32 {xl, xh}, o11; cvt.f32.f16 f0, xl; cvt.f32.f16 f1, xh; cvt.rn.bf16x2.f32 tt, f1, f0; fma.rn.bf16x2 r13, tt, osc, r13;\n"
        "mov.b32 {xl, xh}, o13; cvt.f32.f16 f0, xl; cvt.f32.f16 f1, xh; cvt.rn.bf16x2.f32 tt, f1, f0; fma.rn.bf16x2 r14, tt, osc, r14;\n"
        "mov.b32 {xl, xh}, o15; cvt.f32.f16 f0, xl; cvt.f32.f16 f1, xh; cvt.rn.bf16x2.f32 tt, f1, f0; fma.rn.bf16x2 r15, tt, osc, r15;\n"
        "shr.u32 ad, %7, 16; add.u32 ad, ad, off; cvt.u64.u32 gp, ad; add.s64 gp, gp, %12; st.global.v4.b32 [gp+64], {r12,r13,r14,r15};\n"
        "mov.b32 {xl, xh}, o16; cvt.f32.f16 f0, xl; cvt.f32.f16 f1, xh; cvt.rn.bf16x2.f32 tt, f1, f0; fma.rn.bf16x2 r16, tt, osc, r16;\n"
        "mov.b32 {xl, xh}, o18; cvt.f32.f16 f0, xl; cvt.f32.f16 f1, xh; cvt.rn.bf16x2.f32 tt, f1, f0; fma.rn.bf16x2 r17, tt, osc, r17;\n"
        "mov.b32 {xl, xh}, o20; cvt.f32.f16 f0, xl; cvt.f32.f16 f1, xh; cvt.rn.bf16x2.f32 tt, f1, f0; fma.rn.bf16x2 r18, tt, osc, r18;\n"
        "mov.b32 {xl, xh}, o22; cvt.f32.f16 f0, xl; cvt.f32.f16 f1, xh; cvt.rn.bf16x2.f32 tt, f1, f0; fma.rn.bf16x2 r19, tt, osc, r19;\n"
        "and.b32 ad, %7, 0xffff; add.u32 ad, ad, off; cvt.u64.u32 gp, ad; add.s64 gp, gp, %12; st.global.v4.b32 [gp+128], {r16,r17,r18,r19};\n"
        "mov.b32 {xl, xh}, o17; cvt.f32.f16 f0, xl; cvt.f32.f16 f1, xh; cvt.rn.bf16x2.f32 tt, f1, f0; fma.rn.bf16x2 r20, tt, osc, r20;\n"
        "mov.b32 {xl, xh}, o19; cvt.f32.f16 f0, xl; cvt.f32.f16 f1, xh; cvt.rn.bf16x2.f32 tt, f1, f0; fma.rn.bf16x2 r21, tt, osc, r21;\n"
        "mov.b32 {xl, xh}, o21; cvt.f32.f16 f0, xl; cvt.f32.f16 f1, xh; cvt.rn.bf16x2.f32 tt, f1, f0; fma.rn.bf16x2 r22, tt, osc, r22;\n"
        "mov.b32 {xl, xh}, o23; cvt.f32.f16 f0, xl; cvt.f32.f16 f1, xh; cvt.rn.bf16x2.f32 tt, f1, f0; fma.rn.bf16x2 r23, tt, osc, r23;\n"
        "shr.u32 ad, %7, 16; add.u32 ad, ad, off; cvt.u64.u32 gp, ad; add.s64 gp, gp, %12; st.global.v4.b32 [gp+128], {r20,r21,r22,r23};\n"
        ASM_MARK
        "mov.u32 %0, 0;\n"
        "OUT:\n"
        "}\n"
        : "=r"(retry)
        : "r"(prm.w1desc), "r"(prm.w2desc), "r"(c.wg), "r"(c.off), "r"(c.xs), "r"(c.a_offs), "r"(c.xs_offs), "r"(c.bias_addr),
          "r"(c.step), "r"(c.w), "l"(prm.x), "l"(prm.out), "r"(round), "r"(c.last), "l"(c.park)
        : "memory");
    return retry;
}
static_assert(BAR_Y2FULL == 0 && BAR_XSFULL == 4 && BAR_TURN == 11 && BAR_ROWS == 51 && BAR_STAT == 54 &&
              sb + SM_RED + RED_SCALE * 4 == 230792, "layout");
__device__ __forceinline__ bool helper_tiles(const Pass2& c, const Params& prm, uint32_t round) {
    uint32_t retry;
    asm volatile(
        "{\n"
        ".reg .b32 qa<24>, qz<32>, o<24>, g<16>, p<2>, a<4>, lo<2>, hi<2>, h<2>, osc, v<8>, r<24>, t<2>;\n"
        ".reg .b32 n, off, c, tt, ad, cnt, ybar, xbar, tbar, tpar, id;\n"
        ".reg .b16 xl, xh, xr;\n"
        ".reg .f32 f0, f1;\n"
        ".reg .b64 w1d, w2d, dt, gp, gq, pol;\n"
        ".reg .pred pt, pf, pr, pw, pl, pm, pz, pn;\n"
        "setp.ne.b32 pt, 1, 0; setp.ne.b32 pf, 0, 0; setp.eq.u32 pl, %10, 0; setp.eq.u32 pz, %1, 0;\n"
        "mov.b32 c, 0x40D940D9;\n"
        "mov.b64 w1d, {%1, 0x40000040}; mov.b64 w2d, {%2, 0x80000020};\n"
        "mad.lo.u32 ybar, %3, 8, 230800; mad.lo.u32 xbar, %3, 8, 230832; add.u32 id, %3, 2;\n"
        "mad.lo.u32 tbar, %3, 64, 230888; setp.eq.u32 pr, %3, 0; selp.u32 tpar, 1, 0, pr; mov.u32 tt, %laneid; setp.eq.u32 pn, tt, 0;\n"
        "mov.u32 n, -1; add.u32 off, %4, %9; mov.pred pm, pt; createpolicy.fractional.L2::evict_first.b64 pol, 1.0;\n"
        "mbarrier.try_wait.parity.shared::cta.b64 pw, [ybar], 0;\n"
        "@!pw bra.uni SPINY0;\n"
        "BACKY0:\n"
        "and.b32 t0, %6, 0xffff; shr.u32 t1, %6, 16;\n"
        "xor.b32 ad, t0, 0; add.u32 ad, ad, %5; ldmatrix.sync.aligned.m8n8.x4.shared.b16 {qa0,qa1,qa2,qa3}, [ad];\n"
        "xor.b32 ad, t0, 32; add.u32 ad, ad, %5; ldmatrix.sync.aligned.m8n8.x4.shared.b16 {qa4,qa5,qa6,qa7}, [ad];\n"
        "xor.b32 ad, t0, 64; add.u32 ad, ad, %5; ldmatrix.sync.aligned.m8n8.x4.shared.b16 {qa8,qa9,qa10,qa11}, [ad];\n"
        "xor.b32 ad, t0, 96; add.u32 ad, ad, %5; ldmatrix.sync.aligned.m8n8.x4.shared.b16 {qa12,qa13,qa14,qa15}, [ad];\n"
        "xor.b32 ad, t1, 0; add.u32 ad, ad, %5; ldmatrix.sync.aligned.m8n8.x4.shared.b16 {qa16,qa17,qa18,qa19}, [ad];\n"
        "xor.b32 ad, t1, 32; add.u32 ad, ad, %5; ldmatrix.sync.aligned.m8n8.x4.shared.b16 {qa20,qa21,qa22,qa23}, [ad];\n"
        "wgmma.fence.sync.aligned;\n"
        "add.s64 dt, w1d, 0; wgmma.mma_async.sync.aligned.m64n64k16.f16.f16.f16 {qz0,qz1,qz2,qz3,qz4,qz5,qz6,qz7,qz8,qz9,qz10,qz11,qz12,qz13,qz14,qz15}, {qa0,qa1,qa2,qa3}, dt, pf, 1, 1, 1;\n"
        "add.s64 dt, w1d, 128; wgmma.mma_async.sync.aligned.m64n64k16.f16.f16.f16 {qz0,qz1,qz2,qz3,qz4,qz5,qz6,qz7,qz8,qz9,qz10,qz11,qz12,qz13,qz14,qz15}, {qa4,qa5,qa6,qa7}, dt, pt, 1, 1, 1;\n"
        "add.s64 dt, w1d, 256; wgmma.mma_async.sync.aligned.m64n64k16.f16.f16.f16 {qz0,qz1,qz2,qz3,qz4,qz5,qz6,qz7,qz8,qz9,qz10,qz11,qz12,qz13,qz14,qz15}, {qa8,qa9,qa10,qa11}, dt, pt, 1, 1, 1;\n"
        "add.s64 dt, w1d, 384; wgmma.mma_async.sync.aligned.m64n64k16.f16.f16.f16 {qz0,qz1,qz2,qz3,qz4,qz5,qz6,qz7,qz8,qz9,qz10,qz11,qz12,qz13,qz14,qz15}, {qa12,qa13,qa14,qa15}, dt, pt, 1, 1, 1;\n"
        "add.s64 dt, w1d, 512; wgmma.mma_async.sync.aligned.m64n64k16.f16.f16.f16 {qz0,qz1,qz2,qz3,qz4,qz5,qz6,qz7,qz8,qz9,qz10,qz11,qz12,qz13,qz14,qz15}, {qa16,qa17,qa18,qa19}, dt, pt, 1, 1, 1;\n"
        "add.s64 dt, w1d, 640; wgmma.mma_async.sync.aligned.m64n64k16.f16.f16.f16 {qz0,qz1,qz2,qz3,qz4,qz5,qz6,qz7,qz8,qz9,qz10,qz11,qz12,qz13,qz14,qz15}, {qa20,qa21,qa22,qa23}, dt, pt, 1, 1, 1;\n"
        "wgmma.commit_group.sync.aligned;\n"
        "mov.b32 g0, 0; mov.b32 g1, 0; mov.b32 g2, 0; mov.b32 g3, 0; mov.b32 g4, 0; mov.b32 g5, 0; mov.b32 g6, 0; mov.b32 g7, 0; mov.b32 g8, 0; mov.b32 g9, 0; mov.b32 g10, 0; mov.b32 g11, 0; mov.b32 g12, 0; mov.b32 g13, 0; mov.b32 g14, 0; mov.b32 g15, 0; mov.b32 o0, 0; mov.b32 o1, 0; mov.b32 o2, 0; mov.b32 o3, 0; mov.b32 o4, 0; mov.b32 o5, 0; mov.b32 o6, 0; mov.b32 o7, 0; mov.b32 o8, 0; mov.b32 o9, 0; mov.b32 o10, 0; mov.b32 o11, 0; mov.b32 o12, 0; mov.b32 o13, 0; mov.b32 o14, 0; mov.b32 o15, 0; mov.b32 o16, 0; mov.b32 o17, 0; mov.b32 o18, 0; mov.b32 o19, 0; mov.b32 o20, 0; mov.b32 o21, 0; mov.b32 o22, 0; mov.b32 o23, 0;\n"
        "mov.b32 osc, 0;\n"
        "wgmma.wait_group.sync.aligned 0;\n"
        "fma.rn.f16x2 p0, qz0, qz0, c;\n"
        "mul.rn.f16x2 a0, qz0, p0; fma.rn.f16x2 p1, qz1, qz1, c;\n"
        "mov.b32 {xl, xh}, a0; tanh.approx.f16 xr, xl; cvt.u32.u16 lo0, xr; tanh.approx.f16 xr, xh; cvt.u32.u16 hi0, xr; mul.rn.f16x2 a1, qz1, p1; fma.rn.f16x2 p0, qz2, qz2, c;\n"
        "mov.b32 {xl, xh}, a1; tanh.approx.f16 xr, xl; cvt.u32.u16 lo1, xr; tanh.approx.f16 xr, xh; cvt.u32.u16 hi1, xr; mul.rn.f16x2 a2, qz2, p0; fma.rn.f16x2 p1, qz3, qz3, c; prmt.b32 h0, lo0, hi0, 0x5410;\n"
        "mov.b32 {xl, xh}, a2; tanh.approx.f16 xr, xl; cvt.u32.u16 lo0, xr; tanh.approx.f16 xr, xh; cvt.u32.u16 hi0, xr; mul.rn.f16x2 a3, qz3, p1; fma.rn.f16x2 p0, qz4, qz4, c; fma.rn.f16x2 g0, qz0, h0, qz0; prmt.b32 h1, lo1, hi1, 0x5410;\n"
        "mov.b32 {xl, xh}, a3; tanh.approx.f16 xr, xl; cvt.u32.u16 lo1, xr; tanh.approx.f16 xr, xh; cvt.u32.u16 hi1, xr; mul.rn.f16x2 a0, qz4, p0; fma.rn.f16x2 p1, qz5, qz5, c; fma.rn.f16x2 g1, qz1, h1, qz1; prmt.b32 h0, lo0, hi0, 0x5410;\n"
        "mov.b32 {xl, xh}, a0; tanh.approx.f16 xr, xl; cvt.u32.u16 lo0, xr; tanh.approx.f16 xr, xh; cvt.u32.u16 hi0, xr; mul.rn.f16x2 a1, qz5, p1; fma.rn.f16x2 p0, qz6, qz6, c; fma.rn.f16x2 g2, qz2, h0, qz2; prmt.b32 h1, lo1, hi1, 0x5410;\n"
        "mov.b32 {xl, xh}, a1; tanh.approx.f16 xr, xl; cvt.u32.u16 lo1, xr; tanh.approx.f16 xr, xh; cvt.u32.u16 hi1, xr; mul.rn.f16x2 a2, qz6, p0; fma.rn.f16x2 p1, qz7, qz7, c; fma.rn.f16x2 g3, qz3, h1, qz3; prmt.b32 h0, lo0, hi0, 0x5410;\n"
        "setp.ne.u64 pr, %15, 0;\n"
        "@pr bra.uni FAST;\n"
        "LOOP:\n"
        "wgmma.fence.sync.aligned;\n"
        "add.s64 dt, w1d, 768; wgmma.mma_async.sync.aligned.m64n64k16.f16.f16.f16 {qz16,qz17,qz18,qz19,qz20,qz21,qz22,qz23,qz24,qz25,qz26,qz27,qz28,qz29,qz30,qz31}, {qa0,qa1,qa2,qa3}, dt, pf, 1, 1, 1;\n"
        "add.s64 dt, w1d, 896; wgmma.mma_async.sync.aligned.m64n64k16.f16.f16.f16 {qz16,qz17,qz18,qz19,qz20,qz21,qz22,qz23,qz24,qz25,qz26,qz27,qz28,qz29,qz30,qz31}, {qa4,qa5,qa6,qa7}, dt, pt, 1, 1, 1;\n"
        "add.s64 dt, w1d, 1024; wgmma.mma_async.sync.aligned.m64n64k16.f16.f16.f16 {qz16,qz17,qz18,qz19,qz20,qz21,qz22,qz23,qz24,qz25,qz26,qz27,qz28,qz29,qz30,qz31}, {qa8,qa9,qa10,qa11}, dt, pt, 1, 1, 1;\n"
        "add.s64 dt, w1d, 1152; wgmma.mma_async.sync.aligned.m64n64k16.f16.f16.f16 {qz16,qz17,qz18,qz19,qz20,qz21,qz22,qz23,qz24,qz25,qz26,qz27,qz28,qz29,qz30,qz31}, {qa12,qa13,qa14,qa15}, dt, pt, 1, 1, 1;\n"
        "add.s64 dt, w1d, 1280; wgmma.mma_async.sync.aligned.m64n64k16.f16.f16.f16 {qz16,qz17,qz18,qz19,qz20,qz21,qz22,qz23,qz24,qz25,qz26,qz27,qz28,qz29,qz30,qz31}, {qa16,qa17,qa18,qa19}, dt, pt, 1, 1, 1;\n"
        "add.s64 dt, w1d, 1408; wgmma.mma_async.sync.aligned.m64n64k16.f16.f16.f16 {qz16,qz17,qz18,qz19,qz20,qz21,qz22,qz23,qz24,qz25,qz26,qz27,qz28,qz29,qz30,qz31}, {qa20,qa21,qa22,qa23}, dt, pt, 1, 1, 1;\n"
        "setp.lt.s32 pr, n, 0;\n"
        "@pr bra.uni FIRST;\n"
        "and.b32 tt, n, 1; mbarrier.try_wait.parity.shared::cta.b64 pw, [xbar], tt;\n"
        "@!pw bra.uni SPINX;\n"
        "BACKX:\n"
        "and.b32 ad, %7, 0xffff; add.u32 ad, ad, %5; ld.shared.v4.b32 {v0,v1,v2,v3}, [ad+0];\n"
        "shr.u32 ad, %7, 16; add.u32 ad, ad, %5; ld.shared.v4.b32 {v4,v5,v6,v7}, [ad+0];\n"
        "mov.b32 {xl, xh}, o0; cvt.f32.f16 f0, xl; cvt.f32.f16 f1, xh; cvt.rn.bf16x2.f32 tt, f1, f0; fma.rn.bf16x2 v0, tt, osc, v0;\n"
        "mov.b32 {xl, xh}, o2; cvt.f32.f16 f0, xl; cvt.f32.f16 f1, xh; cvt.rn.bf16x2.f32 tt, f1, f0; fma.rn.bf16x2 v1, tt, osc, v1;\n"
        "mov.b32 {xl, xh}, o4; cvt.f32.f16 f0, xl; cvt.f32.f16 f1, xh; cvt.rn.bf16x2.f32 tt, f1, f0; fma.rn.bf16x2 v2, tt, osc, v2;\n"
        "mov.b32 {xl, xh}, o6; cvt.f32.f16 f0, xl; cvt.f32.f16 f1, xh; cvt.rn.bf16x2.f32 tt, f1, f0; fma.rn.bf16x2 v3, tt, osc, v3;\n"
        "and.b32 ad, %7, 0xffff; add.u32 ad, ad, %5; st.shared.v4.b32 [ad+0], {v0,v1,v2,v3};\n"
        "and.b32 ad, %7, 0xffff; add.u32 ad, ad, %5; ld.shared.v4.b32 {v0,v1,v2,v3}, [ad+64];\n"
        "mov.b32 {xl, xh}, o1; cvt.f32.f16 f0, xl; cvt.f32.f16 f1, xh; cvt.rn.bf16x2.f32 tt, f1, f0; fma.rn.bf16x2 v4, tt, osc, v4;\n"
        "mov.b32 {xl, xh}, o3; cvt.f32.f16 f0, xl; cvt.f32.f16 f1, xh; cvt.rn.bf16x2.f32 tt, f1, f0; fma.rn.bf16x2 v5, tt, osc, v5;\n"
        "mov.b32 {xl, xh}, o5; cvt.f32.f16 f0, xl; cvt.f32.f16 f1, xh; cvt.rn.bf16x2.f32 tt, f1, f0; fma.rn.bf16x2 v6, tt, osc, v6;\n"
        "mov.b32 {xl, xh}, o7; cvt.f32.f16 f0, xl; cvt.f32.f16 f1, xh; cvt.rn.bf16x2.f32 tt, f1, f0; fma.rn.bf16x2 v7, tt, osc, v7;\n"
        "shr.u32 ad, %7, 16; add.u32 ad, ad, %5; st.shared.v4.b32 [ad+0], {v4,v5,v6,v7};\n"
        "shr.u32 ad, %7, 16; add.u32 ad, ad, %5; ld.shared.v4.b32 {v4,v5,v6,v7}, [ad+64];\n"
        "ld.shared.v4.b32 {o0,o1,o2,o3}, [%8+0];\n"
        "ld.shared.v4.b32 {o4,o5,o6,o7}, [%8+64];\n"
        "mov.b32 {xl, xh}, o8; cvt.f32.f16 f0, xl; cvt.f32.f16 f1, xh; cvt.rn.bf16x2.f32 tt, f1, f0; fma.rn.bf16x2 v0, tt, osc, v0;\n"
        "mov.b32 {xl, xh}, o10; cvt.f32.f16 f0, xl; cvt.f32.f16 f1, xh; cvt.rn.bf16x2.f32 tt, f1, f0; fma.rn.bf16x2 v1, tt, osc, v1;\n"
        "mov.b32 {xl, xh}, o12; cvt.f32.f16 f0, xl; cvt.f32.f16 f1, xh; cvt.rn.bf16x2.f32 tt, f1, f0; fma.rn.bf16x2 v2, tt, osc, v2;\n"
        "mov.b32 {xl, xh}, o14; cvt.f32.f16 f0, xl; cvt.f32.f16 f1, xh; cvt.rn.bf16x2.f32 tt, f1, f0; fma.rn.bf16x2 v3, tt, osc, v3;\n"
        "and.b32 ad, %7, 0xffff; add.u32 ad, ad, %5; st.shared.v4.b32 [ad+64], {v0,v1,v2,v3};\n"
        "and.b32 ad, %7, 0xffff; add.u32 ad, ad, %5; ld.shared.v4.b32 {v0,v1,v2,v3}, [ad+128];\n"
        "mov.b32 {xl, xh}, o9; cvt.f32.f16 f0, xl; cvt.f32.f16 f1, xh; cvt.rn.bf16x2.f32 tt, f1, f0; fma.rn.bf16x2 v4, tt, osc, v4;\n"
        "mov.b32 {xl, xh}, o11; cvt.f32.f16 f0, xl; cvt.f32.f16 f1, xh; cvt.rn.bf16x2.f32 tt, f1, f0; fma.rn.bf16x2 v5, tt, osc, v5;\n"
        "mov.b32 {xl, xh}, o13; cvt.f32.f16 f0, xl; cvt.f32.f16 f1, xh; cvt.rn.bf16x2.f32 tt, f1, f0; fma.rn.bf16x2 v6, tt, osc, v6;\n"
        "mov.b32 {xl, xh}, o15; cvt.f32.f16 f0, xl; cvt.f32.f16 f1, xh; cvt.rn.bf16x2.f32 tt, f1, f0; fma.rn.bf16x2 v7, tt, osc, v7;\n"
        "shr.u32 ad, %7, 16; add.u32 ad, ad, %5; st.shared.v4.b32 [ad+64], {v4,v5,v6,v7};\n"
        "shr.u32 ad, %7, 16; add.u32 ad, ad, %5; ld.shared.v4.b32 {v4,v5,v6,v7}, [ad+128];\n"
        "ld.shared.v4.b32 {o8,o9,o10,o11}, [%8+128];\n"
        "ld.shared.v4.b32 {o12,o13,o14,o15}, [%8+192];\n"
        "mov.b32 {xl, xh}, o16; cvt.f32.f16 f0, xl; cvt.f32.f16 f1, xh; cvt.rn.bf16x2.f32 tt, f1, f0; fma.rn.bf16x2 v0, tt, osc, v0;\n"
        "mov.b32 {xl, xh}, o18; cvt.f32.f16 f0, xl; cvt.f32.f16 f1, xh; cvt.rn.bf16x2.f32 tt, f1, f0; fma.rn.bf16x2 v1, tt, osc, v1;\n"
        "mov.b32 {xl, xh}, o20; cvt.f32.f16 f0, xl; cvt.f32.f16 f1, xh; cvt.rn.bf16x2.f32 tt, f1, f0; fma.rn.bf16x2 v2, tt, osc, v2;\n"
        "mov.b32 {xl, xh}, o22; cvt.f32.f16 f0, xl; cvt.f32.f16 f1, xh; cvt.rn.bf16x2.f32 tt, f1, f0; fma.rn.bf16x2 v3, tt, osc, v3;\n"
        "and.b32 ad, %7, 0xffff; add.u32 ad, ad, %5; st.shared.v4.b32 [ad+128], {v0,v1,v2,v3};\n"
        "mov.b32 {xl, xh}, o17; cvt.f32.f16 f0, xl; cvt.f32.f16 f1, xh; cvt.rn.bf16x2.f32 tt, f1, f0; fma.rn.bf16x2 v4, tt, osc, v4;\n"
        "mov.b32 {xl, xh}, o19; cvt.f32.f16 f0, xl; cvt.f32.f16 f1, xh; cvt.rn.bf16x2.f32 tt, f1, f0; fma.rn.bf16x2 v5, tt, osc, v5;\n"
        "mov.b32 {xl, xh}, o21; cvt.f32.f16 f0, xl; cvt.f32.f16 f1, xh; cvt.rn.bf16x2.f32 tt, f1, f0; fma.rn.bf16x2 v6, tt, osc, v6;\n"
        "mov.b32 {xl, xh}, o23; cvt.f32.f16 f0, xl; cvt.f32.f16 f1, xh; cvt.rn.bf16x2.f32 tt, f1, f0; fma.rn.bf16x2 v7, tt, osc, v7;\n"
        "shr.u32 ad, %7, 16; add.u32 ad, ad, %5; st.shared.v4.b32 [ad+128], {v4,v5,v6,v7};\n"
        "ld.shared.v4.b32 {o16,o17,o18,o19}, [%8+256];\n"
        "ld.shared.v4.b32 {o20,o21,o22,o23}, [%8+320];\n"
        "FIRST:\n"
        "@pz bra.uni B7;\n"
        "mov.b32 {xl, xh}, a2; tanh.approx.f16 xr, xl; cvt.u32.u16 lo0, xr; tanh.approx.f16 xr, xh; cvt.u32.u16 hi0, xr; mul.rn.f16x2 a3, qz7, p1; fma.rn.f16x2 p0, qz8, qz8, c; fma.rn.f16x2 g4, qz4, h0, qz4; prmt.b32 h1, lo1, hi1, 0x5410;\n"
        "B7:\n"
        "fence.proxy.async.shared::cta;\n"
        "add.u32 tt, id, 4;\n"
        "@pl bra.uni STORE;\n"
        "bar.arrive tt, 128;\n"
        "STOREB:\n"
        ASM_MARK
        "add.s32 n, n, 1; sub.u32 off, off, %9; setp.lt.s32 pm, n, %14;\n"
        "@pz bra.uni B10;\n"
        "mov.b32 {xl, xh}, a3; tanh.approx.f16 xr, xl; cvt.u32.u16 lo1, xr; tanh.approx.f16 xr, xh; cvt.u32.u16 hi1, xr; mul.rn.f16x2 a0, qz8, p0; fma.rn.f16x2 p1, qz9, qz9, c; fma.rn.f16x2 g5, qz5, h1, qz5; prmt.b32 h0, lo0, hi0, 0x5410;\n"
        "mov.b32 {xl, xh}, a0; tanh.approx.f16 xr, xl; cvt.u32.u16 lo0, xr; tanh.approx.f16 xr, xh; cvt.u32.u16 hi0, xr; mul.rn.f16x2 a1, qz9, p1; fma.rn.f16x2 p0, qz10, qz10, c; fma.rn.f16x2 g6, qz6, h0, qz6; prmt.b32 h1, lo1, hi1, 0x5410;\n"
        "mov.b32 {xl, xh}, a1; tanh.approx.f16 xr, xl; cvt.u32.u16 lo1, xr; tanh.approx.f16 xr, xh; cvt.u32.u16 hi1, xr; mul.rn.f16x2 a2, qz10, p0; fma.rn.f16x2 p1, qz11, qz11, c; fma.rn.f16x2 g7, qz7, h1, qz7; prmt.b32 h0, lo0, hi0, 0x5410;\n"
        "B10:\n"
        "setp.eq.s32 pr, n, 0;\n"
        "@pr bra.uni SPINR;\n"
        "BACKW0:\n"
        "wgmma.fence.sync.aligned;\n"
        "add.s64 dt, w2d, 0; wgmma.mma_async.sync.aligned.m64n96k16.f16.f16.f16 {o0,o1,o2,o3,o4,o5,o6,o7,o8,o9,o10,o11,o12,o13,o14,o15,o16,o17,o18,o19,o20,o21,o22,o23}, {g0,g1,g2,g3}, dt, pt, 1, 1, 1;\n"
        "add.s64 dt, w2d, 64; wgmma.mma_async.sync.aligned.m64n96k16.f16.f16.f16 {o0,o1,o2,o3,o4,o5,o6,o7,o8,o9,o10,o11,o12,o13,o14,o15,o16,o17,o18,o19,o20,o21,o22,o23}, {g4,g5,g6,g7}, dt, pt, 1, 1, 1;\n"
        "wgmma.commit_group.sync.aligned;\n"
        "@pz bra.uni B14;\n"
        "mov.b32 {xl, xh}, a2; tanh.approx.f16 xr, xl; cvt.u32.u16 lo0, xr; tanh.approx.f16 xr, xh; cvt.u32.u16 hi0, xr; mul.rn.f16x2 a3, qz11, p1; fma.rn.f16x2 p0, qz12, qz12, c; fma.rn.f16x2 g8, qz8, h0, qz8; prmt.b32 h1, lo1, hi1, 0x5410;\n"
        "mov.b32 {xl, xh}, a3; tanh.approx.f16 xr, xl; cvt.u32.u16 lo1, xr; tanh.approx.f16 xr, xh; cvt.u32.u16 hi1, xr; mul.rn.f16x2 a0, qz12, p0; fma.rn.f16x2 p1, qz13, qz13, c; fma.rn.f16x2 g9, qz9, h1, qz9; prmt.b32 h0, lo0, hi0, 0x5410;\n"
        "mov.b32 {xl, xh}, a0; tanh.approx.f16 xr, xl; cvt.u32.u16 lo0, xr; tanh.approx.f16 xr, xh; cvt.u32.u16 hi0, xr; mul.rn.f16x2 a1, qz13, p1; fma.rn.f16x2 p0, qz14, qz14, c; fma.rn.f16x2 g10, qz10, h0, qz10; prmt.b32 h1, lo1, hi1, 0x5410;\n"
        "mov.b32 {xl, xh}, a1; tanh.approx.f16 xr, xl; cvt.u32.u16 lo1, xr; tanh.approx.f16 xr, xh; cvt.u32.u16 hi1, xr; mul.rn.f16x2 a2, qz14, p0; fma.rn.f16x2 p1, qz15, qz15, c; fma.rn.f16x2 g11, qz11, h1, qz11; prmt.b32 h0, lo0, hi0, 0x5410;\n"
        "B14:\n"
        "wgmma.wait_group.sync.aligned 0;\n"
        "mad.lo.u32 tt, n, 8, tbar; mbarrier.try_wait.parity.shared::cta.b64 pw, [tt], tpar;\n"
        "@!pw bra.uni SPINT;\n"
        "BACKT:\n"
        "wgmma.fence.sync.aligned;\n"
        "add.s64 dt, w2d, 128; wgmma.mma_async.sync.aligned.m64n96k16.f16.f16.f16 {o0,o1,o2,o3,o4,o5,o6,o7,o8,o9,o10,o11,o12,o13,o14,o15,o16,o17,o18,o19,o20,o21,o22,o23}, {g8,g9,g10,g11}, dt, pt, 1, 1, 1;\n"
        "wgmma.commit_group.sync.aligned;\n"
        "@pz bra.uni B18;\n"
        "mov.b32 {xl, xh}, a2; tanh.approx.f16 xr, xl; cvt.u32.u16 lo0, xr; tanh.approx.f16 xr, xh; cvt.u32.u16 hi0, xr; mul.rn.f16x2 a3, qz15, p1; fma.rn.f16x2 p0, qz16, qz16, c; fma.rn.f16x2 g12, qz12, h0, qz12; prmt.b32 h1, lo1, hi1, 0x5410;\n"
        "mov.b32 {xl, xh}, a3; tanh.approx.f16 xr, xl; cvt.u32.u16 lo1, xr; tanh.approx.f16 xr, xh; cvt.u32.u16 hi1, xr; mul.rn.f16x2 a0, qz16, p0; fma.rn.f16x2 p1, qz17, qz17, c; fma.rn.f16x2 g13, qz13, h1, qz13; prmt.b32 h0, lo0, hi0, 0x5410;\n"
        "mov.b32 {xl, xh}, a0; tanh.approx.f16 xr, xl; cvt.u32.u16 lo0, xr; tanh.approx.f16 xr, xh; cvt.u32.u16 hi0, xr; mul.rn.f16x2 a1, qz17, p1; fma.rn.f16x2 p0, qz18, qz18, c; fma.rn.f16x2 g14, qz14, h0, qz14; prmt.b32 h1, lo1, hi1, 0x5410;\n"
        "mov.b32 {xl, xh}, a1; tanh.approx.f16 xr, xl; cvt.u32.u16 lo1, xr; tanh.approx.f16 xr, xh; cvt.u32.u16 hi1, xr; mul.rn.f16x2 a2, qz18, p0; fma.rn.f16x2 p1, qz19, qz19, c; fma.rn.f16x2 g15, qz15, h1, qz15; prmt.b32 h0, lo0, hi0, 0x5410;\n"
        "B18:\n"
        "wgmma.fence.sync.aligned;\n"
        "add.s64 dt, w2d, 192; wgmma.mma_async.sync.aligned.m64n96k16.f16.f16.f16 {o0,o1,o2,o3,o4,o5,o6,o7,o8,o9,o10,o11,o12,o13,o14,o15,o16,o17,o18,o19,o20,o21,o22,o23}, {g12,g13,g14,g15}, dt, pt, 1, 1, 1;\n"
        "add.s64 dt, w1d, 1536; wgmma.mma_async.sync.aligned.m64n64k16.f16.f16.f16 {qz0,qz1,qz2,qz3,qz4,qz5,qz6,qz7,qz8,qz9,qz10,qz11,qz12,qz13,qz14,qz15}, {qa0,qa1,qa2,qa3}, dt, pf, 1, 1, 1;\n"
        "add.s64 dt, w1d, 1664; wgmma.mma_async.sync.aligned.m64n64k16.f16.f16.f16 {qz0,qz1,qz2,qz3,qz4,qz5,qz6,qz7,qz8,qz9,qz10,qz11,qz12,qz13,qz14,qz15}, {qa4,qa5,qa6,qa7}, dt, pt, 1, 1, 1;\n"
        "add.s64 dt, w1d, 1792; wgmma.mma_async.sync.aligned.m64n64k16.f16.f16.f16 {qz0,qz1,qz2,qz3,qz4,qz5,qz6,qz7,qz8,qz9,qz10,qz11,qz12,qz13,qz14,qz15}, {qa8,qa9,qa10,qa11}, dt, pt, 1, 1, 1;\n"
        "wgmma.commit_group.sync.aligned;\n"
        "@pl bra.uni YLOAD;\n"
        "YLOADB:\n"
        "@pz bra.uni B22;\n"
        "mov.b32 {xl, xh}, a2; tanh.approx.f16 xr, xl; cvt.u32.u16 lo0, xr; tanh.approx.f16 xr, xh; cvt.u32.u16 hi0, xr; mul.rn.f16x2 a3, qz19, p1; fma.rn.f16x2 p0, qz20, qz20, c; fma.rn.f16x2 g0, qz16, h0, qz16; prmt.b32 h1, lo1, hi1, 0x5410;\n"
        "mov.b32 {xl, xh}, a3; tanh.approx.f16 xr, xl; cvt.u32.u16 lo1, xr; tanh.approx.f16 xr, xh; cvt.u32.u16 hi1, xr; mul.rn.f16x2 a0, qz20, p0; fma.rn.f16x2 p1, qz21, qz21, c; fma.rn.f16x2 g1, qz17, h1, qz17; prmt.b32 h0, lo0, hi0, 0x5410;\n"
        "mov.b32 {xl, xh}, a0; tanh.approx.f16 xr, xl; cvt.u32.u16 lo0, xr; tanh.approx.f16 xr, xh; cvt.u32.u16 hi0, xr; mul.rn.f16x2 a1, qz21, p1; fma.rn.f16x2 p0, qz22, qz22, c; fma.rn.f16x2 g2, qz18, h0, qz18; prmt.b32 h1, lo1, hi1, 0x5410;\n"
        "mov.b32 {xl, xh}, a1; tanh.approx.f16 xr, xl; cvt.u32.u16 lo1, xr; tanh.approx.f16 xr, xh; cvt.u32.u16 hi1, xr; mul.rn.f16x2 a2, qz22, p0; fma.rn.f16x2 p1, qz23, qz23, c; fma.rn.f16x2 g3, qz19, h1, qz19; prmt.b32 h0, lo0, hi0, 0x5410;\n"
        "B22:\n"
        "wgmma.fence.sync.aligned;\n"
        "add.s64 dt, w1d, 1920; wgmma.mma_async.sync.aligned.m64n64k16.f16.f16.f16 {qz0,qz1,qz2,qz3,qz4,qz5,qz6,qz7,qz8,qz9,qz10,qz11,qz12,qz13,qz14,qz15}, {qa12,qa13,qa14,qa15}, dt, pt, 1, 1, 1;\n"
        "add.s64 dt, w1d, 2048; wgmma.mma_async.sync.aligned.m64n64k16.f16.f16.f16 {qz0,qz1,qz2,qz3,qz4,qz5,qz6,qz7,qz8,qz9,qz10,qz11,qz12,qz13,qz14,qz15}, {qa16,qa17,qa18,qa19}, dt, pt, 1, 1, 1;\n"
        "add.s64 dt, w1d, 2176; wgmma.mma_async.sync.aligned.m64n64k16.f16.f16.f16 {qz0,qz1,qz2,qz3,qz4,qz5,qz6,qz7,qz8,qz9,qz10,qz11,qz12,qz13,qz14,qz15}, {qa20,qa21,qa22,qa23}, dt, pt, 1, 1, 1;\n"
        "wgmma.commit_group.sync.aligned;\n"
        "@pz bra.uni B26;\n"
        "mov.b32 {xl, xh}, a2; tanh.approx.f16 xr, xl; cvt.u32.u16 lo0, xr; tanh.approx.f16 xr, xh; cvt.u32.u16 hi0, xr; mul.rn.f16x2 a3, qz23, p1; fma.rn.f16x2 p0, qz24, qz24, c; fma.rn.f16x2 g4, qz20, h0, qz20; prmt.b32 h1, lo1, hi1, 0x5410;\n"
        "mov.b32 {xl, xh}, a3; tanh.approx.f16 xr, xl; cvt.u32.u16 lo1, xr; tanh.approx.f16 xr, xh; cvt.u32.u16 hi1, xr; mul.rn.f16x2 a0, qz24, p0; fma.rn.f16x2 p1, qz25, qz25, c; fma.rn.f16x2 g5, qz21, h1, qz21; prmt.b32 h0, lo0, hi0, 0x5410;\n"
        "mov.b32 {xl, xh}, a0; tanh.approx.f16 xr, xl; cvt.u32.u16 lo0, xr; tanh.approx.f16 xr, xh; cvt.u32.u16 hi0, xr; mul.rn.f16x2 a1, qz25, p1; fma.rn.f16x2 p0, qz26, qz26, c; fma.rn.f16x2 g6, qz22, h0, qz22; prmt.b32 h1, lo1, hi1, 0x5410;\n"
        "mov.b32 {xl, xh}, a1; tanh.approx.f16 xr, xl; cvt.u32.u16 lo1, xr; tanh.approx.f16 xr, xh; cvt.u32.u16 hi1, xr; mul.rn.f16x2 a2, qz26, p0; fma.rn.f16x2 p1, qz27, qz27, c; fma.rn.f16x2 g7, qz23, h1, qz23; prmt.b32 h0, lo0, hi0, 0x5410;\n"
        "B26:\n"
        "wgmma.wait_group.sync.aligned 2;\n"
        "wgmma.fence.sync.aligned;\n"
        "add.s64 dt, w2d, 256; wgmma.mma_async.sync.aligned.m64n96k16.f16.f16.f16 {o0,o1,o2,o3,o4,o5,o6,o7,o8,o9,o10,o11,o12,o13,o14,o15,o16,o17,o18,o19,o20,o21,o22,o23}, {g0,g1,g2,g3}, dt, pt, 1, 1, 1;\n"
        "add.s64 dt, w2d, 320; wgmma.mma_async.sync.aligned.m64n96k16.f16.f16.f16 {o0,o1,o2,o3,o4,o5,o6,o7,o8,o9,o10,o11,o12,o13,o14,o15,o16,o17,o18,o19,o20,o21,o22,o23}, {g4,g5,g6,g7}, dt, pt, 1, 1, 1;\n"
        "wgmma.commit_group.sync.aligned;\n"
        "@pz bra.uni B30;\n"
        "mov.b32 {xl, xh}, a2; tanh.approx.f16 xr, xl; cvt.u32.u16 lo0, xr; tanh.approx.f16 xr, xh; cvt.u32.u16 hi0, xr; mul.rn.f16x2 a3, qz27, p1; fma.rn.f16x2 p0, qz28, qz28, c; fma.rn.f16x2 g8, qz24, h0, qz24; prmt.b32 h1, lo1, hi1, 0x5410;\n"
        "mov.b32 {xl, xh}, a3; tanh.approx.f16 xr, xl; cvt.u32.u16 lo1, xr; tanh.approx.f16 xr, xh; cvt.u32.u16 hi1, xr; mul.rn.f16x2 a0, qz28, p0; fma.rn.f16x2 p1, qz29, qz29, c; fma.rn.f16x2 g9, qz25, h1, qz25; prmt.b32 h0, lo0, hi0, 0x5410;\n"
        "mov.b32 {xl, xh}, a0; tanh.approx.f16 xr, xl; cvt.u32.u16 lo0, xr; tanh.approx.f16 xr, xh; cvt.u32.u16 hi0, xr; mul.rn.f16x2 a1, qz29, p1; fma.rn.f16x2 p0, qz30, qz30, c; fma.rn.f16x2 g10, qz26, h0, qz26; prmt.b32 h1, lo1, hi1, 0x5410;\n"
        "mov.b32 {xl, xh}, a1; tanh.approx.f16 xr, xl; cvt.u32.u16 lo1, xr; tanh.approx.f16 xr, xh; cvt.u32.u16 hi1, xr; mul.rn.f16x2 a2, qz30, p0; fma.rn.f16x2 p1, qz31, qz31, c; fma.rn.f16x2 g11, qz27, h1, qz27; prmt.b32 h0, lo0, hi0, 0x5410;\n"
        "B30:\n"
        "wgmma.wait_group.sync.aligned 1;\n"
        "wgmma.fence.sync.aligned;\n"
        "add.s64 dt, w2d, 384; wgmma.mma_async.sync.aligned.m64n96k16.f16.f16.f16 {o0,o1,o2,o3,o4,o5,o6,o7,o8,o9,o10,o11,o12,o13,o14,o15,o16,o17,o18,o19,o20,o21,o22,o23}, {g8,g9,g10,g11}, dt, pt, 1, 1, 1;\n"
        "wgmma.commit_group.sync.aligned;\n"
        "@pz bra.uni B34;\n"
        "mov.b32 {xl, xh}, a2; tanh.approx.f16 xr, xl; cvt.u32.u16 lo0, xr; tanh.approx.f16 xr, xh; cvt.u32.u16 hi0, xr; mul.rn.f16x2 a3, qz31, p1; fma.rn.f16x2 p0, qz0, qz0, c; fma.rn.f16x2 g12, qz28, h0, qz28; prmt.b32 h1, lo1, hi1, 0x5410;\n"
        "mov.b32 {xl, xh}, a3; tanh.approx.f16 xr, xl; cvt.u32.u16 lo1, xr; tanh.approx.f16 xr, xh; cvt.u32.u16 hi1, xr; mul.rn.f16x2 a0, qz0, p0; fma.rn.f16x2 p1, qz1, qz1, c; fma.rn.f16x2 g13, qz29, h1, qz29; prmt.b32 h0, lo0, hi0, 0x5410;\n"
        "mov.b32 {xl, xh}, a0; tanh.approx.f16 xr, xl; cvt.u32.u16 lo0, xr; tanh.approx.f16 xr, xh; cvt.u32.u16 hi0, xr; mul.rn.f16x2 a1, qz1, p1; fma.rn.f16x2 p0, qz2, qz2, c; fma.rn.f16x2 g14, qz30, h0, qz30; prmt.b32 h1, lo1, hi1, 0x5410;\n"
        "mov.b32 {xl, xh}, a1; tanh.approx.f16 xr, xl; cvt.u32.u16 lo1, xr; tanh.approx.f16 xr, xh; cvt.u32.u16 hi1, xr; mul.rn.f16x2 a2, qz2, p0; fma.rn.f16x2 p1, qz3, qz3, c; fma.rn.f16x2 g15, qz31, h1, qz31; prmt.b32 h0, lo0, hi0, 0x5410;\n"
        "B34:\n"
        "wgmma.wait_group.sync.aligned 1;\n"
        "wgmma.fence.sync.aligned;\n"
        "add.s64 dt, w2d, 448; wgmma.mma_async.sync.aligned.m64n96k16.f16.f16.f16 {o0,o1,o2,o3,o4,o5,o6,o7,o8,o9,o10,o11,o12,o13,o14,o15,o16,o17,o18,o19,o20,o21,o22,o23}, {g12,g13,g14,g15}, dt, pt, 1, 1, 1;\n"
        "add.s64 dt, w1d, 2304; wgmma.mma_async.sync.aligned.m64n64k16.f16.f16.f16 {qz16,qz17,qz18,qz19,qz20,qz21,qz22,qz23,qz24,qz25,qz26,qz27,qz28,qz29,qz30,qz31}, {qa0,qa1,qa2,qa3}, dt, pf, 1, 1, 1;\n"
        "add.s64 dt, w1d, 2432; wgmma.mma_async.sync.aligned.m64n64k16.f16.f16.f16 {qz16,qz17,qz18,qz19,qz20,qz21,qz22,qz23,qz24,qz25,qz26,qz27,qz28,qz29,qz30,qz31}, {qa4,qa5,qa6,qa7}, dt, pt, 1, 1, 1;\n"
        "add.s64 dt, w1d, 2560; wgmma.mma_async.sync.aligned.m64n64k16.f16.f16.f16 {qz16,qz17,qz18,qz19,qz20,qz21,qz22,qz23,qz24,qz25,qz26,qz27,qz28,qz29,qz30,qz31}, {qa8,qa9,qa10,qa11}, dt, pt, 1, 1, 1;\n"
        "wgmma.commit_group.sync.aligned;\n"
        "@pz bra.uni B38;\n"
        "mov.b32 {xl, xh}, a2; tanh.approx.f16 xr, xl; cvt.u32.u16 lo0, xr; tanh.approx.f16 xr, xh; cvt.u32.u16 hi0, xr; mul.rn.f16x2 a3, qz3, p1; fma.rn.f16x2 p0, qz4, qz4, c; fma.rn.f16x2 g0, qz0, h0, qz0; prmt.b32 h1, lo1, hi1, 0x5410;\n"
        "mov.b32 {xl, xh}, a3; tanh.approx.f16 xr, xl; cvt.u32.u16 lo1, xr; tanh.approx.f16 xr, xh; cvt.u32.u16 hi1, xr; mul.rn.f16x2 a0, qz4, p0; fma.rn.f16x2 p1, qz5, qz5, c; fma.rn.f16x2 g1, qz1, h1, qz1; prmt.b32 h0, lo0, hi0, 0x5410;\n"
        "mov.b32 {xl, xh}, a0; tanh.approx.f16 xr, xl; cvt.u32.u16 lo0, xr; tanh.approx.f16 xr, xh; cvt.u32.u16 hi0, xr; mul.rn.f16x2 a1, qz5, p1; fma.rn.f16x2 p0, qz6, qz6, c; fma.rn.f16x2 g2, qz2, h0, qz2; prmt.b32 h1, lo1, hi1, 0x5410;\n"
        "mov.b32 {xl, xh}, a1; tanh.approx.f16 xr, xl; cvt.u32.u16 lo1, xr; tanh.approx.f16 xr, xh; cvt.u32.u16 hi1, xr; mul.rn.f16x2 a2, qz6, p0; fma.rn.f16x2 p1, qz7, qz7, c; fma.rn.f16x2 g3, qz3, h1, qz3; prmt.b32 h0, lo0, hi0, 0x5410;\n"
        "B38:\n"
        "wgmma.fence.sync.aligned;\n"
        "add.s64 dt, w1d, 2688; wgmma.mma_async.sync.aligned.m64n64k16.f16.f16.f16 {qz16,qz17,qz18,qz19,qz20,qz21,qz22,qz23,qz24,qz25,qz26,qz27,qz28,qz29,qz30,qz31}, {qa12,qa13,qa14,qa15}, dt, pt, 1, 1, 1;\n"
        "add.s64 dt, w1d, 2816; wgmma.mma_async.sync.aligned.m64n64k16.f16.f16.f16 {qz16,qz17,qz18,qz19,qz20,qz21,qz22,qz23,qz24,qz25,qz26,qz27,qz28,qz29,qz30,qz31}, {qa16,qa17,qa18,qa19}, dt, pt, 1, 1, 1;\n"
        "add.s64 dt, w1d, 2944; wgmma.mma_async.sync.aligned.m64n64k16.f16.f16.f16 {qz16,qz17,qz18,qz19,qz20,qz21,qz22,qz23,qz24,qz25,qz26,qz27,qz28,qz29,qz30,qz31}, {qa20,qa21,qa22,qa23}, dt, pt, 1, 1, 1;\n"
        "wgmma.commit_group.sync.aligned;\n"
        "@pz bra.uni B42;\n"
        "mov.b32 {xl, xh}, a2; tanh.approx.f16 xr, xl; cvt.u32.u16 lo0, xr; tanh.approx.f16 xr, xh; cvt.u32.u16 hi0, xr; mul.rn.f16x2 a3, qz7, p1; fma.rn.f16x2 p0, qz8, qz8, c; fma.rn.f16x2 g4, qz4, h0, qz4; prmt.b32 h1, lo1, hi1, 0x5410;\n"
        "mov.b32 {xl, xh}, a3; tanh.approx.f16 xr, xl; cvt.u32.u16 lo1, xr; tanh.approx.f16 xr, xh; cvt.u32.u16 hi1, xr; mul.rn.f16x2 a0, qz8, p0; fma.rn.f16x2 p1, qz9, qz9, c; fma.rn.f16x2 g5, qz5, h1, qz5; prmt.b32 h0, lo0, hi0, 0x5410;\n"
        "mov.b32 {xl, xh}, a0; tanh.approx.f16 xr, xl; cvt.u32.u16 lo0, xr; tanh.approx.f16 xr, xh; cvt.u32.u16 hi0, xr; mul.rn.f16x2 a1, qz9, p1; fma.rn.f16x2 p0, qz10, qz10, c; fma.rn.f16x2 g6, qz6, h0, qz6; prmt.b32 h1, lo1, hi1, 0x5410;\n"
        "mov.b32 {xl, xh}, a1; tanh.approx.f16 xr, xl; cvt.u32.u16 lo1, xr; tanh.approx.f16 xr, xh; cvt.u32.u16 hi1, xr; mul.rn.f16x2 a2, qz10, p0; fma.rn.f16x2 p1, qz11, qz11, c; fma.rn.f16x2 g7, qz7, h1, qz7; prmt.b32 h0, lo0, hi0, 0x5410;\n"
        "B42:\n"
        "wgmma.wait_group.sync.aligned 2;\n"
        "setp.eq.s32 pr, n, 0;\n"
        "@pr bra.uni SPINW1;\n"
        "BACKW1:\n"
        "wgmma.fence.sync.aligned;\n"
        "add.s64 dt, w2d, 512; wgmma.mma_async.sync.aligned.m64n96k16.f16.f16.f16 {o0,o1,o2,o3,o4,o5,o6,o7,o8,o9,o10,o11,o12,o13,o14,o15,o16,o17,o18,o19,o20,o21,o22,o23}, {g0,g1,g2,g3}, dt, pt, 1, 1, 1;\n"
        "add.s64 dt, w2d, 576; wgmma.mma_async.sync.aligned.m64n96k16.f16.f16.f16 {o0,o1,o2,o3,o4,o5,o6,o7,o8,o9,o10,o11,o12,o13,o14,o15,o16,o17,o18,o19,o20,o21,o22,o23}, {g4,g5,g6,g7}, dt, pt, 1, 1, 1;\n"
        "wgmma.commit_group.sync.aligned;\n"
        "mad.lo.u32 tt, n, 8, tbar;\n"
        "@pn mbarrier.arrive.shared::cta.b64 _, [tt+64];\n"
        "@pz bra.uni B46;\n"
        "mov.b32 {xl, xh}, a2; tanh.approx.f16 xr, xl; cvt.u32.u16 lo0, xr; tanh.approx.f16 xr, xh; cvt.u32.u16 hi0, xr; mul.rn.f16x2 a3, qz11, p1; fma.rn.f16x2 p0, qz12, qz12, c; fma.rn.f16x2 g8, qz8, h0, qz8; prmt.b32 h1, lo1, hi1, 0x5410;\n"
        "mov.b32 {xl, xh}, a3; tanh.approx.f16 xr, xl; cvt.u32.u16 lo1, xr; tanh.approx.f16 xr, xh; cvt.u32.u16 hi1, xr; mul.rn.f16x2 a0, qz12, p0; fma.rn.f16x2 p1, qz13, qz13, c; fma.rn.f16x2 g9, qz9, h1, qz9; prmt.b32 h0, lo0, hi0, 0x5410;\n"
        "mov.b32 {xl, xh}, a0; tanh.approx.f16 xr, xl; cvt.u32.u16 lo0, xr; tanh.approx.f16 xr, xh; cvt.u32.u16 hi0, xr; mul.rn.f16x2 a1, qz13, p1; fma.rn.f16x2 p0, qz14, qz14, c; fma.rn.f16x2 g10, qz10, h0, qz10; prmt.b32 h1, lo1, hi1, 0x5410;\n"
        "mov.b32 {xl, xh}, a1; tanh.approx.f16 xr, xl; cvt.u32.u16 lo1, xr; tanh.approx.f16 xr, xh; cvt.u32.u16 hi1, xr; mul.rn.f16x2 a2, qz14, p0; fma.rn.f16x2 p1, qz15, qz15, c; fma.rn.f16x2 g11, qz11, h1, qz11; prmt.b32 h0, lo0, hi0, 0x5410;\n"
        "B46:\n"
        "wgmma.wait_group.sync.aligned 1;\n"
        "wgmma.fence.sync.aligned;\n"
        "add.s64 dt, w2d, 640; wgmma.mma_async.sync.aligned.m64n96k16.f16.f16.f16 {o0,o1,o2,o3,o4,o5,o6,o7,o8,o9,o10,o11,o12,o13,o14,o15,o16,o17,o18,o19,o20,o21,o22,o23}, {g8,g9,g10,g11}, dt, pt, 1, 1, 1;\n"
        "wgmma.commit_group.sync.aligned;\n"
        "@pz bra.uni B50;\n"
        "mov.b32 {xl, xh}, a2; tanh.approx.f16 xr, xl; cvt.u32.u16 lo0, xr; tanh.approx.f16 xr, xh; cvt.u32.u16 hi0, xr; mul.rn.f16x2 a3, qz15, p1; fma.rn.f16x2 p0, qz16, qz16, c; fma.rn.f16x2 g12, qz12, h0, qz12; prmt.b32 h1, lo1, hi1, 0x5410;\n"
        "mov.b32 {xl, xh}, a3; tanh.approx.f16 xr, xl; cvt.u32.u16 lo1, xr; tanh.approx.f16 xr, xh; cvt.u32.u16 hi1, xr; mul.rn.f16x2 a0, qz16, p0; fma.rn.f16x2 p1, qz17, qz17, c; fma.rn.f16x2 g13, qz13, h1, qz13; prmt.b32 h0, lo0, hi0, 0x5410;\n"
        "mov.b32 {xl, xh}, a0; tanh.approx.f16 xr, xl; cvt.u32.u16 lo0, xr; tanh.approx.f16 xr, xh; cvt.u32.u16 hi0, xr; mul.rn.f16x2 a1, qz17, p1; fma.rn.f16x2 p0, qz18, qz18, c; fma.rn.f16x2 g14, qz14, h0, qz14; prmt.b32 h1, lo1, hi1, 0x5410;\n"
        "mov.b32 {xl, xh}, a1; tanh.approx.f16 xr, xl; cvt.u32.u16 lo1, xr; tanh.approx.f16 xr, xh; cvt.u32.u16 hi1, xr; mul.rn.f16x2 a2, qz18, p0; fma.rn.f16x2 p1, qz19, qz19, c; fma.rn.f16x2 g15, qz15, h1, qz15; prmt.b32 h0, lo0, hi0, 0x5410;\n"
        "B50:\n"
        "wgmma.wait_group.sync.aligned 1;\n"
        "wgmma.fence.sync.aligned;\n"
        "add.s64 dt, w2d, 704; wgmma.mma_async.sync.aligned.m64n96k16.f16.f16.f16 {o0,o1,o2,o3,o4,o5,o6,o7,o8,o9,o10,o11,o12,o13,o14,o15,o16,o17,o18,o19,o20,o21,o22,o23}, {g12,g13,g14,g15}, dt, pt, 1, 1, 1;\n"
        "add.s64 dt, w1d, 3072; wgmma.mma_async.sync.aligned.m64n64k16.f16.f16.f16 {qz0,qz1,qz2,qz3,qz4,qz5,qz6,qz7,qz8,qz9,qz10,qz11,qz12,qz13,qz14,qz15}, {qa0,qa1,qa2,qa3}, dt, pf, 1, 1, 1;\n"
        "add.s64 dt, w1d, 3200; wgmma.mma_async.sync.aligned.m64n64k16.f16.f16.f16 {qz0,qz1,qz2,qz3,qz4,qz5,qz6,qz7,qz8,qz9,qz10,qz11,qz12,qz13,qz14,qz15}, {qa4,qa5,qa6,qa7}, dt, pt, 1, 1, 1;\n"
        "add.s64 dt, w1d, 3328; wgmma.mma_async.sync.aligned.m64n64k16.f16.f16.f16 {qz0,qz1,qz2,qz3,qz4,qz5,qz6,qz7,qz8,qz9,qz10,qz11,qz12,qz13,qz14,qz15}, {qa8,qa9,qa10,qa11}, dt, pt, 1, 1, 1;\n"
        "wgmma.commit_group.sync.aligned;\n"
        "@pz bra.uni B54;\n"
        "mov.b32 {xl, xh}, a2; tanh.approx.f16 xr, xl; cvt.u32.u16 lo0, xr; tanh.approx.f16 xr, xh; cvt.u32.u16 hi0, xr; mul.rn.f16x2 a3, qz19, p1; fma.rn.f16x2 p0, qz20, qz20, c; fma.rn.f16x2 g0, qz16, h0, qz16; prmt.b32 h1, lo1, hi1, 0x5410;\n"
        "mov.b32 {xl, xh}, a3; tanh.approx.f16 xr, xl; cvt.u32.u16 lo1, xr; tanh.approx.f16 xr, xh; cvt.u32.u16 hi1, xr; mul.rn.f16x2 a0, qz20, p0; fma.rn.f16x2 p1, qz21, qz21, c; fma.rn.f16x2 g1, qz17, h1, qz17; prmt.b32 h0, lo0, hi0, 0x5410;\n"
        "mov.b32 {xl, xh}, a0; tanh.approx.f16 xr, xl; cvt.u32.u16 lo0, xr; tanh.approx.f16 xr, xh; cvt.u32.u16 hi0, xr; mul.rn.f16x2 a1, qz21, p1; fma.rn.f16x2 p0, qz22, qz22, c; fma.rn.f16x2 g2, qz18, h0, qz18; prmt.b32 h1, lo1, hi1, 0x5410;\n"
        "mov.b32 {xl, xh}, a1; tanh.approx.f16 xr, xl; cvt.u32.u16 lo1, xr; tanh.approx.f16 xr, xh; cvt.u32.u16 hi1, xr; mul.rn.f16x2 a2, qz22, p0; fma.rn.f16x2 p1, qz23, qz23, c; fma.rn.f16x2 g3, qz19, h1, qz19; prmt.b32 h0, lo0, hi0, 0x5410;\n"
        "B54:\n"
        "wgmma.fence.sync.aligned;\n"
        "add.s64 dt, w1d, 3456; wgmma.mma_async.sync.aligned.m64n64k16.f16.f16.f16 {qz0,qz1,qz2,qz3,qz4,qz5,qz6,qz7,qz8,qz9,qz10,qz11,qz12,qz13,qz14,qz15}, {qa12,qa13,qa14,qa15}, dt, pt, 1, 1, 1;\n"
        "add.s64 dt, w1d, 3584; wgmma.mma_async.sync.aligned.m64n64k16.f16.f16.f16 {qz0,qz1,qz2,qz3,qz4,qz5,qz6,qz7,qz8,qz9,qz10,qz11,qz12,qz13,qz14,qz15}, {qa16,qa17,qa18,qa19}, dt, pt, 1, 1, 1;\n"
        "add.s64 dt, w1d, 3712; wgmma.mma_async.sync.aligned.m64n64k16.f16.f16.f16 {qz0,qz1,qz2,qz3,qz4,qz5,qz6,qz7,qz8,qz9,qz10,qz11,qz12,qz13,qz14,qz15}, {qa20,qa21,qa22,qa23}, dt, pt, 1, 1, 1;\n"
        "wgmma.commit_group.sync.aligned;\n"
        "@pz bra.uni B58;\n"
        "mov.b32 {xl, xh}, a2; tanh.approx.f16 xr, xl; cvt.u32.u16 lo0, xr; tanh.approx.f16 xr, xh; cvt.u32.u16 hi0, xr; mul.rn.f16x2 a3, qz23, p1; fma.rn.f16x2 p0, qz24, qz24, c; fma.rn.f16x2 g4, qz20, h0, qz20; prmt.b32 h1, lo1, hi1, 0x5410;\n"
        "mov.b32 {xl, xh}, a3; tanh.approx.f16 xr, xl; cvt.u32.u16 lo1, xr; tanh.approx.f16 xr, xh; cvt.u32.u16 hi1, xr; mul.rn.f16x2 a0, qz24, p0; fma.rn.f16x2 p1, qz25, qz25, c; fma.rn.f16x2 g5, qz21, h1, qz21; prmt.b32 h0, lo0, hi0, 0x5410;\n"
        "mov.b32 {xl, xh}, a0; tanh.approx.f16 xr, xl; cvt.u32.u16 lo0, xr; tanh.approx.f16 xr, xh; cvt.u32.u16 hi0, xr; mul.rn.f16x2 a1, qz25, p1; fma.rn.f16x2 p0, qz26, qz26, c; fma.rn.f16x2 g6, qz22, h0, qz22; prmt.b32 h1, lo1, hi1, 0x5410;\n"
        "mov.b32 {xl, xh}, a1; tanh.approx.f16 xr, xl; cvt.u32.u16 lo1, xr; tanh.approx.f16 xr, xh; cvt.u32.u16 hi1, xr; mul.rn.f16x2 a2, qz26, p0; fma.rn.f16x2 p1, qz27, qz27, c; fma.rn.f16x2 g7, qz23, h1, qz23; prmt.b32 h0, lo0, hi0, 0x5410;\n"
        "B58:\n"
        "wgmma.wait_group.sync.aligned 2;\n"
        "wgmma.fence.sync.aligned;\n"
        "add.s64 dt, w2d, 768; wgmma.mma_async.sync.aligned.m64n96k16.f16.f16.f16 {o0,o1,o2,o3,o4,o5,o6,o7,o8,o9,o10,o11,o12,o13,o14,o15,o16,o17,o18,o19,o20,o21,o22,o23}, {g0,g1,g2,g3}, dt, pt, 1, 1, 1;\n"
        "add.s64 dt, w2d, 832; wgmma.mma_async.sync.aligned.m64n96k16.f16.f16.f16 {o0,o1,o2,o3,o4,o5,o6,o7,o8,o9,o10,o11,o12,o13,o14,o15,o16,o17,o18,o19,o20,o21,o22,o23}, {g4,g5,g6,g7}, dt, pt, 1, 1, 1;\n"
        "wgmma.commit_group.sync.aligned;\n"
        "@pz bra.uni B62;\n"
        "mov.b32 {xl, xh}, a2; tanh.approx.f16 xr, xl; cvt.u32.u16 lo0, xr; tanh.approx.f16 xr, xh; cvt.u32.u16 hi0, xr; mul.rn.f16x2 a3, qz27, p1; fma.rn.f16x2 p0, qz28, qz28, c; fma.rn.f16x2 g8, qz24, h0, qz24; prmt.b32 h1, lo1, hi1, 0x5410;\n"
        "mov.b32 {xl, xh}, a3; tanh.approx.f16 xr, xl; cvt.u32.u16 lo1, xr; tanh.approx.f16 xr, xh; cvt.u32.u16 hi1, xr; mul.rn.f16x2 a0, qz28, p0; fma.rn.f16x2 p1, qz29, qz29, c; fma.rn.f16x2 g9, qz25, h1, qz25; prmt.b32 h0, lo0, hi0, 0x5410;\n"
        "mov.b32 {xl, xh}, a0; tanh.approx.f16 xr, xl; cvt.u32.u16 lo0, xr; tanh.approx.f16 xr, xh; cvt.u32.u16 hi0, xr; mul.rn.f16x2 a1, qz29, p1; fma.rn.f16x2 p0, qz30, qz30, c; fma.rn.f16x2 g10, qz26, h0, qz26; prmt.b32 h1, lo1, hi1, 0x5410;\n"
        "mov.b32 {xl, xh}, a1; tanh.approx.f16 xr, xl; cvt.u32.u16 lo1, xr; tanh.approx.f16 xr, xh; cvt.u32.u16 hi1, xr; mul.rn.f16x2 a2, qz30, p0; fma.rn.f16x2 p1, qz31, qz31, c; fma.rn.f16x2 g11, qz27, h1, qz27; prmt.b32 h0, lo0, hi0, 0x5410;\n"
        "B62:\n"
        "wgmma.wait_group.sync.aligned 1;\n"
        "wgmma.fence.sync.aligned;\n"
        "add.s64 dt, w2d, 896; wgmma.mma_async.sync.aligned.m64n96k16.f16.f16.f16 {o0,o1,o2,o3,o4,o5,o6,o7,o8,o9,o10,o11,o12,o13,o14,o15,o16,o17,o18,o19,o20,o21,o22,o23}, {g8,g9,g10,g11}, dt, pt, 1, 1, 1;\n"
        "wgmma.commit_group.sync.aligned;\n"
        "@pz bra.uni B66;\n"
        "mov.b32 {xl, xh}, a2; tanh.approx.f16 xr, xl; cvt.u32.u16 lo0, xr; tanh.approx.f16 xr, xh; cvt.u32.u16 hi0, xr; mul.rn.f16x2 a3, qz31, p1; fma.rn.f16x2 p0, qz0, qz0, c; fma.rn.f16x2 g12, qz28, h0, qz28; prmt.b32 h1, lo1, hi1, 0x5410;\n"
        "mov.b32 {xl, xh}, a3; tanh.approx.f16 xr, xl; cvt.u32.u16 lo1, xr; tanh.approx.f16 xr, xh; cvt.u32.u16 hi1, xr; mul.rn.f16x2 a0, qz0, p0; fma.rn.f16x2 p1, qz1, qz1, c; fma.rn.f16x2 g13, qz29, h1, qz29; prmt.b32 h0, lo0, hi0, 0x5410;\n"
        "mov.b32 {xl, xh}, a0; tanh.approx.f16 xr, xl; cvt.u32.u16 lo0, xr; tanh.approx.f16 xr, xh; cvt.u32.u16 hi0, xr; mul.rn.f16x2 a1, qz1, p1; fma.rn.f16x2 p0, qz2, qz2, c; fma.rn.f16x2 g14, qz30, h0, qz30; prmt.b32 h1, lo1, hi1, 0x5410;\n"
        "mov.b32 {xl, xh}, a1; tanh.approx.f16 xr, xl; cvt.u32.u16 lo1, xr; tanh.approx.f16 xr, xh; cvt.u32.u16 hi1, xr; mul.rn.f16x2 a2, qz2, p0; fma.rn.f16x2 p1, qz3, qz3, c; fma.rn.f16x2 g15, qz31, h1, qz31; prmt.b32 h0, lo0, hi0, 0x5410;\n"
        "B66:\n"
        "wgmma.wait_group.sync.aligned 1;\n"
        "wgmma.fence.sync.aligned;\n"
        "add.s64 dt, w2d, 960; wgmma.mma_async.sync.aligned.m64n96k16.f16.f16.f16 {o0,o1,o2,o3,o4,o5,o6,o7,o8,o9,o10,o11,o12,o13,o14,o15,o16,o17,o18,o19,o20,o21,o22,o23}, {g12,g13,g14,g15}, dt, pt, 1, 1, 1;\n"
        "add.s64 dt, w1d, 3840; wgmma.mma_async.sync.aligned.m64n64k16.f16.f16.f16 {qz16,qz17,qz18,qz19,qz20,qz21,qz22,qz23,qz24,qz25,qz26,qz27,qz28,qz29,qz30,qz31}, {qa0,qa1,qa2,qa3}, dt, pf, 1, 1, 1;\n"
        "add.s64 dt, w1d, 3968; wgmma.mma_async.sync.aligned.m64n64k16.f16.f16.f16 {qz16,qz17,qz18,qz19,qz20,qz21,qz22,qz23,qz24,qz25,qz26,qz27,qz28,qz29,qz30,qz31}, {qa4,qa5,qa6,qa7}, dt, pt, 1, 1, 1;\n"
        "add.s64 dt, w1d, 4096; wgmma.mma_async.sync.aligned.m64n64k16.f16.f16.f16 {qz16,qz17,qz18,qz19,qz20,qz21,qz22,qz23,qz24,qz25,qz26,qz27,qz28,qz29,qz30,qz31}, {qa8,qa9,qa10,qa11}, dt, pt, 1, 1, 1;\n"
        "wgmma.commit_group.sync.aligned;\n"
        "@pz bra.uni B70;\n"
        "mov.b32 {xl, xh}, a2; tanh.approx.f16 xr, xl; cvt.u32.u16 lo0, xr; tanh.approx.f16 xr, xh; cvt.u32.u16 hi0, xr; mul.rn.f16x2 a3, qz3, p1; fma.rn.f16x2 p0, qz4, qz4, c; fma.rn.f16x2 g0, qz0, h0, qz0; prmt.b32 h1, lo1, hi1, 0x5410;\n"
        "mov.b32 {xl, xh}, a3; tanh.approx.f16 xr, xl; cvt.u32.u16 lo1, xr; tanh.approx.f16 xr, xh; cvt.u32.u16 hi1, xr; mul.rn.f16x2 a0, qz4, p0; fma.rn.f16x2 p1, qz5, qz5, c; fma.rn.f16x2 g1, qz1, h1, qz1; prmt.b32 h0, lo0, hi0, 0x5410;\n"
        "mov.b32 {xl, xh}, a0; tanh.approx.f16 xr, xl; cvt.u32.u16 lo0, xr; tanh.approx.f16 xr, xh; cvt.u32.u16 hi0, xr; mul.rn.f16x2 a1, qz5, p1; fma.rn.f16x2 p0, qz6, qz6, c; fma.rn.f16x2 g2, qz2, h0, qz2; prmt.b32 h1, lo1, hi1, 0x5410;\n"
        "mov.b32 {xl, xh}, a1; tanh.approx.f16 xr, xl; cvt.u32.u16 lo1, xr; tanh.approx.f16 xr, xh; cvt.u32.u16 hi1, xr; mul.rn.f16x2 a2, qz6, p0; fma.rn.f16x2 p1, qz7, qz7, c; fma.rn.f16x2 g3, qz3, h1, qz3; prmt.b32 h0, lo0, hi0, 0x5410;\n"
        "B70:\n"
        "wgmma.fence.sync.aligned;\n"
        "add.s64 dt, w1d, 4224; wgmma.mma_async.sync.aligned.m64n64k16.f16.f16.f16 {qz16,qz17,qz18,qz19,qz20,qz21,qz22,qz23,qz24,qz25,qz26,qz27,qz28,qz29,qz30,qz31}, {qa12,qa13,qa14,qa15}, dt, pt, 1, 1, 1;\n"
        "add.s64 dt, w1d, 4352; wgmma.mma_async.sync.aligned.m64n64k16.f16.f16.f16 {qz16,qz17,qz18,qz19,qz20,qz21,qz22,qz23,qz24,qz25,qz26,qz27,qz28,qz29,qz30,qz31}, {qa16,qa17,qa18,qa19}, dt, pt, 1, 1, 1;\n"
        "add.s64 dt, w1d, 4480; wgmma.mma_async.sync.aligned.m64n64k16.f16.f16.f16 {qz16,qz17,qz18,qz19,qz20,qz21,qz22,qz23,qz24,qz25,qz26,qz27,qz28,qz29,qz30,qz31}, {qa20,qa21,qa22,qa23}, dt, pt, 1, 1, 1;\n"
        "wgmma.commit_group.sync.aligned;\n"
        "@pz bra.uni B74;\n"
        "mov.b32 {xl, xh}, a2; tanh.approx.f16 xr, xl; cvt.u32.u16 lo0, xr; tanh.approx.f16 xr, xh; cvt.u32.u16 hi0, xr; mul.rn.f16x2 a3, qz7, p1; fma.rn.f16x2 p0, qz8, qz8, c; fma.rn.f16x2 g4, qz4, h0, qz4; prmt.b32 h1, lo1, hi1, 0x5410;\n"
        "mov.b32 {xl, xh}, a3; tanh.approx.f16 xr, xl; cvt.u32.u16 lo1, xr; tanh.approx.f16 xr, xh; cvt.u32.u16 hi1, xr; mul.rn.f16x2 a0, qz8, p0; fma.rn.f16x2 p1, qz9, qz9, c; fma.rn.f16x2 g5, qz5, h1, qz5; prmt.b32 h0, lo0, hi0, 0x5410;\n"
        "mov.b32 {xl, xh}, a0; tanh.approx.f16 xr, xl; cvt.u32.u16 lo0, xr; tanh.approx.f16 xr, xh; cvt.u32.u16 hi0, xr; mul.rn.f16x2 a1, qz9, p1; fma.rn.f16x2 p0, qz10, qz10, c; fma.rn.f16x2 g6, qz6, h0, qz6; prmt.b32 h1, lo1, hi1, 0x5410;\n"
        "mov.b32 {xl, xh}, a1; tanh.approx.f16 xr, xl; cvt.u32.u16 lo1, xr; tanh.approx.f16 xr, xh; cvt.u32.u16 hi1, xr; mul.rn.f16x2 a2, qz10, p0; fma.rn.f16x2 p1, qz11, qz11, c; fma.rn.f16x2 g7, qz7, h1, qz7; prmt.b32 h0, lo0, hi0, 0x5410;\n"
        "B74:\n"
        "wgmma.wait_group.sync.aligned 0;\n"
        "setp.eq.s32 pr, n, 0;\n"
        "@pr bra.uni SPINW2;\n"
        "BACKW2:\n"
        "wgmma.fence.sync.aligned;\n"
        "add.s64 dt, w2d, 1024; wgmma.mma_async.sync.aligned.m64n96k16.f16.f16.f16 {o0,o1,o2,o3,o4,o5,o6,o7,o8,o9,o10,o11,o12,o13,o14,o15,o16,o17,o18,o19,o20,o21,o22,o23}, {g0,g1,g2,g3}, dt, pt, 1, 1, 1;\n"
        "add.s64 dt, w2d, 1088; wgmma.mma_async.sync.aligned.m64n96k16.f16.f16.f16 {o0,o1,o2,o3,o4,o5,o6,o7,o8,o9,o10,o11,o12,o13,o14,o15,o16,o17,o18,o19,o20,o21,o22,o23}, {g4,g5,g6,g7}, dt, pt, 1, 1, 1;\n"
        "wgmma.commit_group.sync.aligned;\n"
        "@pz bra.uni B78;\n"
        "mov.b32 {xl, xh}, a2; tanh.approx.f16 xr, xl; cvt.u32.u16 lo0, xr; tanh.approx.f16 xr, xh; cvt.u32.u16 hi0, xr; mul.rn.f16x2 a3, qz11, p1; fma.rn.f16x2 p0, qz12, qz12, c; fma.rn.f16x2 g8, qz8, h0, qz8; prmt.b32 h1, lo1, hi1, 0x5410;\n"
        "mov.b32 {xl, xh}, a3; tanh.approx.f16 xr, xl; cvt.u32.u16 lo1, xr; tanh.approx.f16 xr, xh; cvt.u32.u16 hi1, xr; mul.rn.f16x2 a0, qz12, p0; fma.rn.f16x2 p1, qz13, qz13, c; fma.rn.f16x2 g9, qz9, h1, qz9; prmt.b32 h0, lo0, hi0, 0x5410;\n"
        "mov.b32 {xl, xh}, a0; tanh.approx.f16 xr, xl; cvt.u32.u16 lo0, xr; tanh.approx.f16 xr, xh; cvt.u32.u16 hi0, xr; mul.rn.f16x2 a1, qz13, p1; fma.rn.f16x2 p0, qz14, qz14, c; fma.rn.f16x2 g10, qz10, h0, qz10; prmt.b32 h1, lo1, hi1, 0x5410;\n"
        "mov.b32 {xl, xh}, a1; tanh.approx.f16 xr, xl; cvt.u32.u16 lo1, xr; tanh.approx.f16 xr, xh; cvt.u32.u16 hi1, xr; mul.rn.f16x2 a2, qz14, p0; fma.rn.f16x2 p1, qz15, qz15, c; fma.rn.f16x2 g11, qz11, h1, qz11; prmt.b32 h0, lo0, hi0, 0x5410;\n"
        "B78:\n"
        "@!pm bra.uni BACKY;\n"
        "add.u32 tt, n, 1; and.b32 tt, tt, 1; mbarrier.try_wait.parity.shared::cta.b64 pw, [ybar], tt;\n"
        "@!pw bra.uni SPINY;\n"
        "BACKY:\n"
        "@pz bra.uni B80;\n"
        "and.b32 ad, %6, 0xffff; xor.b32 ad, ad, 0; add.u32 ad, ad, %5; ldmatrix.sync.aligned.m8n8.x4.shared.b16 {qa0,qa1,qa2,qa3}, [ad];\n"
        "and.b32 ad, %6, 0xffff; xor.b32 ad, ad, 32; add.u32 ad, ad, %5; ldmatrix.sync.aligned.m8n8.x4.shared.b16 {qa4,qa5,qa6,qa7}, [ad];\n"
        "and.b32 ad, %6, 0xffff; xor.b32 ad, ad, 64; add.u32 ad, ad, %5; ldmatrix.sync.aligned.m8n8.x4.shared.b16 {qa8,qa9,qa10,qa11}, [ad];\n"
        "and.b32 ad, %6, 0xffff; xor.b32 ad, ad, 96; add.u32 ad, ad, %5; ldmatrix.sync.aligned.m8n8.x4.shared.b16 {qa12,qa13,qa14,qa15}, [ad];\n"
        "shr.u32 ad, %6, 16; xor.b32 ad, ad, 0; add.u32 ad, ad, %5; ldmatrix.sync.aligned.m8n8.x4.shared.b16 {qa16,qa17,qa18,qa19}, [ad];\n"
        "shr.u32 ad, %6, 16; xor.b32 ad, ad, 32; add.u32 ad, ad, %5; ldmatrix.sync.aligned.m8n8.x4.shared.b16 {qa20,qa21,qa22,qa23}, [ad];\n"
        "mov.b32 {xl, xh}, a2; tanh.approx.f16 xr, xl; cvt.u32.u16 lo0, xr; tanh.approx.f16 xr, xh; cvt.u32.u16 hi0, xr; mul.rn.f16x2 a3, qz15, p1; fma.rn.f16x2 p0, qz16, qz16, c; fma.rn.f16x2 g12, qz12, h0, qz12; prmt.b32 h1, lo1, hi1, 0x5410;\n"
        "mov.b32 {xl, xh}, a3; tanh.approx.f16 xr, xl; cvt.u32.u16 lo1, xr; tanh.approx.f16 xr, xh; cvt.u32.u16 hi1, xr; mul.rn.f16x2 a0, qz16, p0; fma.rn.f16x2 p1, qz17, qz17, c; fma.rn.f16x2 g13, qz13, h1, qz13; prmt.b32 h0, lo0, hi0, 0x5410;\n"
        "B80:\n"
        "@!pm bra.uni XLOADB;\n"
        "fence.proxy.async.shared::cta;\n"
        "add.u32 tt, id, 0;\n"
        "@pl bra.uni XLOAD;\n"
        "bar.arrive tt, 128;\n"
        "XLOADB:\n"
        "wgmma.fence.sync.aligned;\n"
        "add.s64 dt, w2d, 1152; wgmma.mma_async.sync.aligned.m64n96k16.f16.f16.f16 {o0,o1,o2,o3,o4,o5,o6,o7,o8,o9,o10,o11,o12,o13,o14,o15,o16,o17,o18,o19,o20,o21,o22,o23}, {g8,g9,g10,g11}, dt, pt, 1, 1, 1;\n"
        "wgmma.commit_group.sync.aligned;\n"
        "@pz bra.uni B82;\n"
        "mov.b32 {xl, xh}, a0; tanh.approx.f16 xr, xl; cvt.u32.u16 lo0, xr; tanh.approx.f16 xr, xh; cvt.u32.u16 hi0, xr; mul.rn.f16x2 a1, qz17, p1; fma.rn.f16x2 p0, qz18, qz18, c; fma.rn.f16x2 g14, qz14, h0, qz14; prmt.b32 h1, lo1, hi1, 0x5410;\n"
        "mov.b32 {xl, xh}, a1; tanh.approx.f16 xr, xl; cvt.u32.u16 lo1, xr; tanh.approx.f16 xr, xh; cvt.u32.u16 hi1, xr; mul.rn.f16x2 a2, qz18, p0; fma.rn.f16x2 p1, qz19, qz19, c; fma.rn.f16x2 g15, qz15, h1, qz15; prmt.b32 h0, lo0, hi0, 0x5410;\n"
        "B82:\n"
        "wgmma.wait_group.sync.aligned 1;\n"
        "@!pm bra.uni SKIP0;\n"
        "wgmma.fence.sync.aligned;\n"
        "add.s64 dt, w1d, 0; wgmma.mma_async.sync.aligned.m64n64k16.f16.f16.f16 {qz0,qz1,qz2,qz3,qz4,qz5,qz6,qz7,qz8,qz9,qz10,qz11,qz12,qz13,qz14,qz15}, {qa0,qa1,qa2,qa3}, dt, pf, 1, 1, 1;\n"
        "add.s64 dt, w1d, 128; wgmma.mma_async.sync.aligned.m64n64k16.f16.f16.f16 {qz0,qz1,qz2,qz3,qz4,qz5,qz6,qz7,qz8,qz9,qz10,qz11,qz12,qz13,qz14,qz15}, {qa4,qa5,qa6,qa7}, dt, pt, 1, 1, 1;\n"
        "add.s64 dt, w1d, 256; wgmma.mma_async.sync.aligned.m64n64k16.f16.f16.f16 {qz0,qz1,qz2,qz3,qz4,qz5,qz6,qz7,qz8,qz9,qz10,qz11,qz12,qz13,qz14,qz15}, {qa8,qa9,qa10,qa11}, dt, pt, 1, 1, 1;\n"
        "SKIP0:\n"
        "wgmma.fence.sync.aligned;\n"
        "add.s64 dt, w2d, 1216; wgmma.mma_async.sync.aligned.m64n96k16.f16.f16.f16 {o0,o1,o2,o3,o4,o5,o6,o7,o8,o9,o10,o11,o12,o13,o14,o15,o16,o17,o18,o19,o20,o21,o22,o23}, {g12,g13,g14,g15}, dt, pt, 1, 1, 1;\n"
        "wgmma.commit_group.sync.aligned;\n"
        "@pz bra.uni B86;\n"
        "mov.b32 {xl, xh}, a2; tanh.approx.f16 xr, xl; cvt.u32.u16 lo0, xr; tanh.approx.f16 xr, xh; cvt.u32.u16 hi0, xr; mul.rn.f16x2 a3, qz19, p1; fma.rn.f16x2 p0, qz20, qz20, c; fma.rn.f16x2 g0, qz16, h0, qz16; prmt.b32 h1, lo1, hi1, 0x5410;\n"
        "mov.b32 {xl, xh}, a3; tanh.approx.f16 xr, xl; cvt.u32.u16 lo1, xr; tanh.approx.f16 xr, xh; cvt.u32.u16 hi1, xr; mul.rn.f16x2 a0, qz20, p0; fma.rn.f16x2 p1, qz21, qz21, c; fma.rn.f16x2 g1, qz17, h1, qz17; prmt.b32 h0, lo0, hi0, 0x5410;\n"
        "mov.b32 {xl, xh}, a0; tanh.approx.f16 xr, xl; cvt.u32.u16 lo0, xr; tanh.approx.f16 xr, xh; cvt.u32.u16 hi0, xr; mul.rn.f16x2 a1, qz21, p1; fma.rn.f16x2 p0, qz22, qz22, c; fma.rn.f16x2 g2, qz18, h0, qz18; prmt.b32 h1, lo1, hi1, 0x5410;\n"
        "mov.b32 {xl, xh}, a1; tanh.approx.f16 xr, xl; cvt.u32.u16 lo1, xr; tanh.approx.f16 xr, xh; cvt.u32.u16 hi1, xr; mul.rn.f16x2 a2, qz22, p0; fma.rn.f16x2 p1, qz23, qz23, c; fma.rn.f16x2 g3, qz19, h1, qz19; prmt.b32 h0, lo0, hi0, 0x5410;\n"
        "B86:\n"
        "@!pm bra.uni SKIP1;\n"
        "wgmma.fence.sync.aligned;\n"
        "add.s64 dt, w1d, 384; wgmma.mma_async.sync.aligned.m64n64k16.f16.f16.f16 {qz0,qz1,qz2,qz3,qz4,qz5,qz6,qz7,qz8,qz9,qz10,qz11,qz12,qz13,qz14,qz15}, {qa12,qa13,qa14,qa15}, dt, pt, 1, 1, 1;\n"
        "add.s64 dt, w1d, 512; wgmma.mma_async.sync.aligned.m64n64k16.f16.f16.f16 {qz0,qz1,qz2,qz3,qz4,qz5,qz6,qz7,qz8,qz9,qz10,qz11,qz12,qz13,qz14,qz15}, {qa16,qa17,qa18,qa19}, dt, pt, 1, 1, 1;\n"
        "add.s64 dt, w1d, 640; wgmma.mma_async.sync.aligned.m64n64k16.f16.f16.f16 {qz0,qz1,qz2,qz3,qz4,qz5,qz6,qz7,qz8,qz9,qz10,qz11,qz12,qz13,qz14,qz15}, {qa20,qa21,qa22,qa23}, dt, pt, 1, 1, 1;\n"
        "SKIP1:\n"
        "@pz bra.uni B90;\n"
        "mov.b32 {xl, xh}, a2; tanh.approx.f16 xr, xl; cvt.u32.u16 lo0, xr; tanh.approx.f16 xr, xh; cvt.u32.u16 hi0, xr; mul.rn.f16x2 a3, qz23, p1; fma.rn.f16x2 p0, qz24, qz24, c; fma.rn.f16x2 g4, qz20, h0, qz20; prmt.b32 h1, lo1, hi1, 0x5410;\n"
        "mov.b32 {xl, xh}, a3; tanh.approx.f16 xr, xl; cvt.u32.u16 lo1, xr; tanh.approx.f16 xr, xh; cvt.u32.u16 hi1, xr; mul.rn.f16x2 a0, qz24, p0; fma.rn.f16x2 p1, qz25, qz25, c; fma.rn.f16x2 g5, qz21, h1, qz21; prmt.b32 h0, lo0, hi0, 0x5410;\n"
        "mov.b32 {xl, xh}, a0; tanh.approx.f16 xr, xl; cvt.u32.u16 lo0, xr; tanh.approx.f16 xr, xh; cvt.u32.u16 hi0, xr; mul.rn.f16x2 a1, qz25, p1; fma.rn.f16x2 p0, qz26, qz26, c; fma.rn.f16x2 g6, qz22, h0, qz22; prmt.b32 h1, lo1, hi1, 0x5410;\n"
        "mov.b32 {xl, xh}, a1; tanh.approx.f16 xr, xl; cvt.u32.u16 lo1, xr; tanh.approx.f16 xr, xh; cvt.u32.u16 hi1, xr; mul.rn.f16x2 a2, qz26, p0; fma.rn.f16x2 p1, qz27, qz27, c; fma.rn.f16x2 g7, qz23, h1, qz23; prmt.b32 h0, lo0, hi0, 0x5410;\n"
        "B90:\n"
        "wgmma.wait_group.sync.aligned 1;\n"
        "wgmma.fence.sync.aligned;\n"
        "add.s64 dt, w2d, 1280; wgmma.mma_async.sync.aligned.m64n96k16.f16.f16.f16 {o0,o1,o2,o3,o4,o5,o6,o7,o8,o9,o10,o11,o12,o13,o14,o15,o16,o17,o18,o19,o20,o21,o22,o23}, {g0,g1,g2,g3}, dt, pt, 1, 1, 1;\n"
        "add.s64 dt, w2d, 1344; wgmma.mma_async.sync.aligned.m64n96k16.f16.f16.f16 {o0,o1,o2,o3,o4,o5,o6,o7,o8,o9,o10,o11,o12,o13,o14,o15,o16,o17,o18,o19,o20,o21,o22,o23}, {g4,g5,g6,g7}, dt, pt, 1, 1, 1;\n"
        "wgmma.commit_group.sync.aligned;\n"
        "@pz bra.uni B94;\n"
        "mov.b32 {xl, xh}, a2; tanh.approx.f16 xr, xl; cvt.u32.u16 lo0, xr; tanh.approx.f16 xr, xh; cvt.u32.u16 hi0, xr; mul.rn.f16x2 a3, qz27, p1; fma.rn.f16x2 p0, qz28, qz28, c; fma.rn.f16x2 g8, qz24, h0, qz24; prmt.b32 h1, lo1, hi1, 0x5410;\n"
        "mov.b32 {xl, xh}, a3; tanh.approx.f16 xr, xl; cvt.u32.u16 lo1, xr; tanh.approx.f16 xr, xh; cvt.u32.u16 hi1, xr; mul.rn.f16x2 a0, qz28, p0; fma.rn.f16x2 p1, qz29, qz29, c; fma.rn.f16x2 g9, qz25, h1, qz25; prmt.b32 h0, lo0, hi0, 0x5410;\n"
        "mov.b32 {xl, xh}, a0; tanh.approx.f16 xr, xl; cvt.u32.u16 lo0, xr; tanh.approx.f16 xr, xh; cvt.u32.u16 hi0, xr; mul.rn.f16x2 a1, qz29, p1; fma.rn.f16x2 p0, qz30, qz30, c; fma.rn.f16x2 g10, qz26, h0, qz26; prmt.b32 h1, lo1, hi1, 0x5410;\n"
        "mov.b32 {xl, xh}, a1; tanh.approx.f16 xr, xl; cvt.u32.u16 lo1, xr; tanh.approx.f16 xr, xh; cvt.u32.u16 hi1, xr; mul.rn.f16x2 a2, qz30, p0; fma.rn.f16x2 p1, qz31, qz31, c; fma.rn.f16x2 g11, qz27, h1, qz27; prmt.b32 h0, lo0, hi0, 0x5410;\n"
        "B94:\n"
        "wgmma.wait_group.sync.aligned 0;\n"
        "wgmma.fence.sync.aligned;\n"
        "add.s64 dt, w2d, 1408; wgmma.mma_async.sync.aligned.m64n96k16.f16.f16.f16 {o0,o1,o2,o3,o4,o5,o6,o7,o8,o9,o10,o11,o12,o13,o14,o15,o16,o17,o18,o19,o20,o21,o22,o23}, {g8,g9,g10,g11}, dt, pt, 1, 1, 1;\n"
        "wgmma.commit_group.sync.aligned;\n"
        "@pz bra.uni B2;\n"
        "mov.b32 {xl, xh}, a2; tanh.approx.f16 xr, xl; cvt.u32.u16 lo0, xr; tanh.approx.f16 xr, xh; cvt.u32.u16 hi0, xr; mul.rn.f16x2 a3, qz31, p1; fma.rn.f16x2 p0, qz0, qz0, c; fma.rn.f16x2 g12, qz28, h0, qz28; prmt.b32 h1, lo1, hi1, 0x5410;\n"
        "mov.b32 {xl, xh}, a3; tanh.approx.f16 xr, xl; cvt.u32.u16 lo1, xr; tanh.approx.f16 xr, xh; cvt.u32.u16 hi1, xr; mul.rn.f16x2 a0, qz0, p0; fma.rn.f16x2 p1, qz1, qz1, c; fma.rn.f16x2 g13, qz29, h1, qz29; prmt.b32 h0, lo0, hi0, 0x5410;\n"
        "mov.b32 {xl, xh}, a0; tanh.approx.f16 xr, xl; cvt.u32.u16 lo0, xr; tanh.approx.f16 xr, xh; cvt.u32.u16 hi0, xr; mul.rn.f16x2 a1, qz1, p1; fma.rn.f16x2 p0, qz2, qz2, c; fma.rn.f16x2 g14, qz30, h0, qz30; prmt.b32 h1, lo1, hi1, 0x5410;\n"
        "mov.b32 {xl, xh}, a1; tanh.approx.f16 xr, xl; cvt.u32.u16 lo1, xr; tanh.approx.f16 xr, xh; cvt.u32.u16 hi1, xr; mul.rn.f16x2 a2, qz2, p0; fma.rn.f16x2 p1, qz3, qz3, c; fma.rn.f16x2 g15, qz31, h1, qz31; prmt.b32 h0, lo0, hi0, 0x5410;\n"
        "B2:\n"
        "wgmma.fence.sync.aligned;\n"
        "add.s64 dt, w2d, 1472; wgmma.mma_async.sync.aligned.m64n96k16.f16.f16.f16 {o0,o1,o2,o3,o4,o5,o6,o7,o8,o9,o10,o11,o12,o13,o14,o15,o16,o17,o18,o19,o20,o21,o22,o23}, {g12,g13,g14,g15}, dt, pt, 1, 1, 1;\n"
        "wgmma.commit_group.sync.aligned;\n"
        "@!pm bra.uni LAST;\n"
        "@pz bra.uni BE;\n"
        "mov.b32 {xl, xh}, a2; tanh.approx.f16 xr, xl; cvt.u32.u16 lo0, xr; tanh.approx.f16 xr, xh; cvt.u32.u16 hi0, xr; mul.rn.f16x2 a3, qz3, p1; fma.rn.f16x2 p0, qz4, qz4, c; fma.rn.f16x2 g0, qz0, h0, qz0; prmt.b32 h1, lo1, hi1, 0x5410;\n"
        "mov.b32 {xl, xh}, a3; tanh.approx.f16 xr, xl; cvt.u32.u16 lo1, xr; tanh.approx.f16 xr, xh; cvt.u32.u16 hi1, xr; mul.rn.f16x2 a0, qz4, p0; fma.rn.f16x2 p1, qz5, qz5, c; fma.rn.f16x2 g1, qz1, h1, qz1; prmt.b32 h0, lo0, hi0, 0x5410;\n"
        "mov.b32 {xl, xh}, a0; tanh.approx.f16 xr, xl; cvt.u32.u16 lo0, xr; tanh.approx.f16 xr, xh; cvt.u32.u16 hi0, xr; mul.rn.f16x2 a1, qz5, p1; fma.rn.f16x2 p0, qz6, qz6, c; fma.rn.f16x2 g2, qz2, h0, qz2; prmt.b32 h1, lo1, hi1, 0x5410;\n"
        "mov.b32 {xl, xh}, a1; tanh.approx.f16 xr, xl; cvt.u32.u16 lo1, xr; tanh.approx.f16 xr, xh; cvt.u32.u16 hi1, xr; mul.rn.f16x2 a2, qz6, p0; fma.rn.f16x2 p1, qz7, qz7, c; fma.rn.f16x2 g3, qz3, h1, qz3; prmt.b32 h0, lo0, hi0, 0x5410;\n"
        "BE:\n"
        "wgmma.wait_group.sync.aligned 0;\n"
        "bra.uni LOOP;\n"
        "STORE:\n"
        "bar.sync tt, 128;\n"
        "setp.lt.s32 pr, n, 0;\n"
        "@pr bra.uni STOREB;\n"
        "cvt.u64.u32 gp, off; add.s64 gp, gp, %12;\n"
        "elect.sync _|pr, 0xffffffff;\n"
        "@pr cp.async.bulk.global.shared::cta.bulk_group [gp], [%5], 12288;\n"
        "@pr cp.async.bulk.commit_group;\n"
        "bra.uni STOREB;\n"
        "YLOAD:\n"
        "cp.async.bulk.wait_group.read 0;\n"
        "@!pm bra.uni XLAST;\n"
        "sub.u32 ad, off, %9; cvt.u64.u32 gp, ad; add.s64 gp, gp, %12;\n"
        "elect.sync _|pr, 0xffffffff;\n"
        "@pr mbarrier.arrive.expect_tx.shared::cta.b64 _, [ybar], 12288;\n"
        "@pr cp.async.bulk.shared::cluster.global.mbarrier::complete_tx::bytes [%5], [gp], 12288, [ybar];\n"
        "cvt.u64.u32 gp, off; add.s64 gp, gp, %11;\n"
        "@pr cp.async.bulk.prefetch.L2.global.L2::cache_hint [gp], 12288, pol;\n"
        "bra.uni YLOADB;\n"
        "XLAST:\n"
        "cvt.u64.u32 gp, off; add.s64 gp, gp, %11;\n"
        "elect.sync _|pr, 0xffffffff;\n"
        "@pr mbarrier.arrive.expect_tx.shared::cta.b64 _, [xbar], 12288;\n"
        "@pr cp.async.bulk.shared::cluster.global.mbarrier::complete_tx::bytes.L2::cache_hint [%5], [gp], 12288, [xbar], pol;\n"
        "bra.uni YLOADB;\n"
        "XLOAD:\n"
        "bar.sync tt, 128;\n"
        "cvt.u64.u32 gp, off; add.s64 gp, gp, %11;\n"
        "elect.sync _|pr, 0xffffffff;\n"
        "@pr mbarrier.arrive.expect_tx.shared::cta.b64 _, [xbar], 12288;\n"
        "@pr cp.async.bulk.shared::cluster.global.mbarrier::complete_tx::bytes.L2::cache_hint [%5], [gp], 12288, [xbar], pol;\n"
        "bra.uni XLOADB;\n"
        "SPINY: mov.u32 cnt, 0;\n"
        "SPINYL:\n"
        "add.u32 tt, n, 1; and.b32 tt, tt, 1; mbarrier.try_wait.parity.shared::cta.b64 pw, [ybar], tt;\n"
        "@pw bra.uni BACKY;\n"
        "add.u32 cnt, cnt, 1; setp.lt.u32 pw, cnt, 0x100000;\n"
        "@pw bra.uni SPINYL;\n"
        "trap;\n"
        "SPINX: mov.u32 cnt, 0;\n"
        "SPINXL:\n"
        "and.b32 tt, n, 1; mbarrier.try_wait.parity.shared::cta.b64 pw, [xbar], tt;\n"
        "@pw bra.uni BACKX;\n"
        "add.u32 cnt, cnt, 1; setp.lt.u32 pw, cnt, 0x100000;\n"
        "@pw bra.uni SPINXL;\n"
        "trap;\n"
        "SPINT: mov.u32 cnt, 0;\n"
        "SPINTL:\n"
        "mad.lo.u32 tt, n, 8, tbar; mbarrier.try_wait.parity.shared::cta.b64 pw, [tt], tpar;\n"
        "@pw bra.uni BACKT;\n"
        "add.u32 cnt, cnt, 1; setp.lt.u32 pw, cnt, 0x100000;\n"
        "@pw bra.uni SPINTL;\n"
        "trap;\n"
        "SPINW0: mov.u32 cnt, 0;\n"
        "SPINW0L:\n"
        "mov.u32 tt, 231208; mbarrier.try_wait.parity.shared::cta.b64 pw, [tt], 0;\n"
        "@pw bra.uni BACKW0;\n"
        "add.u32 cnt, cnt, 1; setp.lt.u32 pw, cnt, 0x100000;\n"
        "@pw bra.uni SPINW0L;\n"
        "trap;\n"
        "SPINW1: mov.u32 cnt, 0;\n"
        "SPINW1L:\n"
        "mov.u32 tt, 231216; mbarrier.try_wait.parity.shared::cta.b64 pw, [tt], 0;\n"
        "@pw bra.uni BACKW1;\n"
        "add.u32 cnt, cnt, 1; setp.lt.u32 pw, cnt, 0x100000;\n"
        "@pw bra.uni SPINW1L;\n"
        "trap;\n"
        "SPINW2: mov.u32 cnt, 0;\n"
        "SPINW2L:\n"
        "mov.u32 tt, 231224; mbarrier.try_wait.parity.shared::cta.b64 pw, [tt], 0;\n"
        "@pw bra.uni BACKW2;\n"
        "add.u32 cnt, cnt, 1; setp.lt.u32 pw, cnt, 0x100000;\n"
        "@pw bra.uni SPINW2L;\n"
        "trap;\n"
        "SPINY0: mov.u32 cnt, 0;\n"
        "SPINY0L:\n"
        "mbarrier.try_wait.parity.shared::cta.b64 pw, [ybar], 0;\n"
        "@pw bra.uni BACKY0;\n"
        "add.u32 cnt, cnt, 1; setp.lt.u32 pw, cnt, 0x100000;\n"
        "@pw bra.uni SPINY0L;\n"
        "trap;\n"
        "SPINR: mov.u32 cnt, 0;\n"
        "SPINRL:\n"
        "mov.u32 tt, 231232; mbarrier.try_wait.parity.shared::cta.b64 pw, [tt], %13;\n"
        "@pw bra.uni BACKR;\n"
        "add.u32 cnt, cnt, 1; setp.lt.u32 pw, cnt, 0x100000;\n"
        "@pw bra.uni SPINRL;\n"
        "trap;\n"
        "BACKR:\n"
        "mov.u32 tt, 230792; ld.shared.v2.b32 {osc, tt}, [tt];\n"
        "setp.ne.u32 pr, tt, 0; vote.sync.any.pred pr, pr, 0xffffffff;\n"
        "@pr bra.uni RETRY;\n"
        "setp.eq.u32 pr, %3, 0;\n"
        "@pr bra.uni BACKB;\n"
        "SPINB: mov.u32 cnt, 0;\n"
        "SPINBL:\n"
        "mov.u32 tt, 231208; mbarrier.try_wait.parity.shared::cta.b64 pw, [tt], 0;\n"
        "@pw bra.uni BACKB;\n"
        "add.u32 cnt, cnt, 1; setp.lt.u32 pw, cnt, 0x100000;\n"
        "@pw bra.uni SPINBL;\n"
        "trap;\n"
        "BACKB:\n"
        "ld.shared.v4.b32 {o0,o1,o2,o3}, [%8+0];\n"
        "ld.shared.v4.b32 {o4,o5,o6,o7}, [%8+64];\n"
        "ld.shared.v4.b32 {o8,o9,o10,o11}, [%8+128];\n"
        "ld.shared.v4.b32 {o12,o13,o14,o15}, [%8+192];\n"
        "ld.shared.v4.b32 {o16,o17,o18,o19}, [%8+256];\n"
        "ld.shared.v4.b32 {o20,o21,o22,o23}, [%8+320];\n"
        "bra.uni SPINW0;\n"
        "RETRY:\n"
        "wgmma.fence.sync.aligned;\n"
        "wgmma.commit_group.sync.aligned;\n"
        "wgmma.wait_group.sync.aligned 0;\n"
        "mov.u32 %0, 1;\n"
        "bra.uni OUT;\n"
        "FAST:\n"
        "mov.u32 n, 0; mov.u32 off, %4;\n"
        "fence.proxy.async.shared::cta;\n"
        "add.u32 tt, id, 4; bar.sync tt, 128;\n"
        "wgmma.fence.sync.aligned;\n"
        "add.s64 dt, w1d, 768; wgmma.mma_async.sync.aligned.m64n64k16.f16.f16.f16 {qz16,qz17,qz18,qz19,qz20,qz21,qz22,qz23,qz24,qz25,qz26,qz27,qz28,qz29,qz30,qz31}, {qa0,qa1,qa2,qa3}, dt, pf, 1, 1, 1;\n"
        "add.s64 dt, w1d, 896; wgmma.mma_async.sync.aligned.m64n64k16.f16.f16.f16 {qz16,qz17,qz18,qz19,qz20,qz21,qz22,qz23,qz24,qz25,qz26,qz27,qz28,qz29,qz30,qz31}, {qa4,qa5,qa6,qa7}, dt, pt, 1, 1, 1;\n"
        "add.s64 dt, w1d, 1024; wgmma.mma_async.sync.aligned.m64n64k16.f16.f16.f16 {qz16,qz17,qz18,qz19,qz20,qz21,qz22,qz23,qz24,qz25,qz26,qz27,qz28,qz29,qz30,qz31}, {qa8,qa9,qa10,qa11}, dt, pt, 1, 1, 1;\n"
        "add.s64 dt, w1d, 1152; wgmma.mma_async.sync.aligned.m64n64k16.f16.f16.f16 {qz16,qz17,qz18,qz19,qz20,qz21,qz22,qz23,qz24,qz25,qz26,qz27,qz28,qz29,qz30,qz31}, {qa12,qa13,qa14,qa15}, dt, pt, 1, 1, 1;\n"
        "add.s64 dt, w1d, 1280; wgmma.mma_async.sync.aligned.m64n64k16.f16.f16.f16 {qz16,qz17,qz18,qz19,qz20,qz21,qz22,qz23,qz24,qz25,qz26,qz27,qz28,qz29,qz30,qz31}, {qa16,qa17,qa18,qa19}, dt, pt, 1, 1, 1;\n"
        "add.s64 dt, w1d, 1408; wgmma.mma_async.sync.aligned.m64n64k16.f16.f16.f16 {qz16,qz17,qz18,qz19,qz20,qz21,qz22,qz23,qz24,qz25,qz26,qz27,qz28,qz29,qz30,qz31}, {qa20,qa21,qa22,qa23}, dt, pt, 1, 1, 1;\n"
        "wgmma.commit_group.sync.aligned;\n"
        "@pz bra.uni L10;\n"
        "mov.u32 ad, %tid.x; and.b32 ad, ad, 127; mad.wide.u32 gq, ad, 16, %15; st.global.v4.b32 [gq+0], {g0,g1,g2,g3};\n"
        "mov.b32 {xl, xh}, a2; tanh.approx.f16 xr, xl; cvt.u32.u16 lo0, xr; tanh.approx.f16 xr, xh; cvt.u32.u16 hi0, xr; mul.rn.f16x2 a3, qz7, p1; fma.rn.f16x2 p0, qz8, qz8, c; fma.rn.f16x2 g4, qz4, h0, qz4; prmt.b32 h1, lo1, hi1, 0x5410;\n"
        "mov.b32 {xl, xh}, a3; tanh.approx.f16 xr, xl; cvt.u32.u16 lo1, xr; tanh.approx.f16 xr, xh; cvt.u32.u16 hi1, xr; mul.rn.f16x2 a0, qz8, p0; fma.rn.f16x2 p1, qz9, qz9, c; fma.rn.f16x2 g5, qz5, h1, qz5; prmt.b32 h0, lo0, hi0, 0x5410;\n"
        "mov.b32 {xl, xh}, a0; tanh.approx.f16 xr, xl; cvt.u32.u16 lo0, xr; tanh.approx.f16 xr, xh; cvt.u32.u16 hi0, xr; mul.rn.f16x2 a1, qz9, p1; fma.rn.f16x2 p0, qz10, qz10, c; fma.rn.f16x2 g6, qz6, h0, qz6; prmt.b32 h1, lo1, hi1, 0x5410;\n"
        "mov.b32 {xl, xh}, a1; tanh.approx.f16 xr, xl; cvt.u32.u16 lo1, xr; tanh.approx.f16 xr, xh; cvt.u32.u16 hi1, xr; mul.rn.f16x2 a2, qz10, p0; fma.rn.f16x2 p1, qz11, qz11, c; fma.rn.f16x2 g7, qz7, h1, qz7; prmt.b32 h0, lo0, hi0, 0x5410;\n"
        "L10:\n"
        "@pz bra.uni L14;\n"
        "mov.u32 ad, %tid.x; and.b32 ad, ad, 127; mad.wide.u32 gq, ad, 16, %15; st.global.v4.b32 [gq+2048], {g4,g5,g6,g7};\n"
        "mov.b32 {xl, xh}, a2; tanh.approx.f16 xr, xl; cvt.u32.u16 lo0, xr; tanh.approx.f16 xr, xh; cvt.u32.u16 hi0, xr; mul.rn.f16x2 a3, qz11, p1; fma.rn.f16x2 p0, qz12, qz12, c; fma.rn.f16x2 g8, qz8, h0, qz8; prmt.b32 h1, lo1, hi1, 0x5410;\n"
        "mov.b32 {xl, xh}, a3; tanh.approx.f16 xr, xl; cvt.u32.u16 lo1, xr; tanh.approx.f16 xr, xh; cvt.u32.u16 hi1, xr; mul.rn.f16x2 a0, qz12, p0; fma.rn.f16x2 p1, qz13, qz13, c; fma.rn.f16x2 g9, qz9, h1, qz9; prmt.b32 h0, lo0, hi0, 0x5410;\n"
        "mov.b32 {xl, xh}, a0; tanh.approx.f16 xr, xl; cvt.u32.u16 lo0, xr; tanh.approx.f16 xr, xh; cvt.u32.u16 hi0, xr; mul.rn.f16x2 a1, qz13, p1; fma.rn.f16x2 p0, qz14, qz14, c; fma.rn.f16x2 g10, qz10, h0, qz10; prmt.b32 h1, lo1, hi1, 0x5410;\n"
        "mov.b32 {xl, xh}, a1; tanh.approx.f16 xr, xl; cvt.u32.u16 lo1, xr; tanh.approx.f16 xr, xh; cvt.u32.u16 hi1, xr; mul.rn.f16x2 a2, qz14, p0; fma.rn.f16x2 p1, qz15, qz15, c; fma.rn.f16x2 g11, qz11, h1, qz11; prmt.b32 h0, lo0, hi0, 0x5410;\n"
        "L14:\n"
        "wgmma.wait_group.sync.aligned 0;\n"
        "@pz bra.uni L18;\n"
        "mov.u32 ad, %tid.x; and.b32 ad, ad, 127; mad.wide.u32 gq, ad, 16, %15; st.global.v4.b32 [gq+4096], {g8,g9,g10,g11};\n"
        "mov.b32 {xl, xh}, a2; tanh.approx.f16 xr, xl; cvt.u32.u16 lo0, xr; tanh.approx.f16 xr, xh; cvt.u32.u16 hi0, xr; mul.rn.f16x2 a3, qz15, p1; fma.rn.f16x2 p0, qz16, qz16, c; fma.rn.f16x2 g12, qz12, h0, qz12; prmt.b32 h1, lo1, hi1, 0x5410;\n"
        "mov.b32 {xl, xh}, a3; tanh.approx.f16 xr, xl; cvt.u32.u16 lo1, xr; tanh.approx.f16 xr, xh; cvt.u32.u16 hi1, xr; mul.rn.f16x2 a0, qz16, p0; fma.rn.f16x2 p1, qz17, qz17, c; fma.rn.f16x2 g13, qz13, h1, qz13; prmt.b32 h0, lo0, hi0, 0x5410;\n"
        "mov.b32 {xl, xh}, a0; tanh.approx.f16 xr, xl; cvt.u32.u16 lo0, xr; tanh.approx.f16 xr, xh; cvt.u32.u16 hi0, xr; mul.rn.f16x2 a1, qz17, p1; fma.rn.f16x2 p0, qz18, qz18, c; fma.rn.f16x2 g14, qz14, h0, qz14; prmt.b32 h1, lo1, hi1, 0x5410;\n"
        "mov.b32 {xl, xh}, a1; tanh.approx.f16 xr, xl; cvt.u32.u16 lo1, xr; tanh.approx.f16 xr, xh; cvt.u32.u16 hi1, xr; mul.rn.f16x2 a2, qz18, p0; fma.rn.f16x2 p1, qz19, qz19, c; fma.rn.f16x2 g15, qz15, h1, qz15; prmt.b32 h0, lo0, hi0, 0x5410;\n"
        "L18:\n"
        "wgmma.fence.sync.aligned;\n"
        "add.s64 dt, w1d, 1536; wgmma.mma_async.sync.aligned.m64n64k16.f16.f16.f16 {qz0,qz1,qz2,qz3,qz4,qz5,qz6,qz7,qz8,qz9,qz10,qz11,qz12,qz13,qz14,qz15}, {qa0,qa1,qa2,qa3}, dt, pf, 1, 1, 1;\n"
        "add.s64 dt, w1d, 1664; wgmma.mma_async.sync.aligned.m64n64k16.f16.f16.f16 {qz0,qz1,qz2,qz3,qz4,qz5,qz6,qz7,qz8,qz9,qz10,qz11,qz12,qz13,qz14,qz15}, {qa4,qa5,qa6,qa7}, dt, pt, 1, 1, 1;\n"
        "add.s64 dt, w1d, 1792; wgmma.mma_async.sync.aligned.m64n64k16.f16.f16.f16 {qz0,qz1,qz2,qz3,qz4,qz5,qz6,qz7,qz8,qz9,qz10,qz11,qz12,qz13,qz14,qz15}, {qa8,qa9,qa10,qa11}, dt, pt, 1, 1, 1;\n"
        "add.s64 dt, w1d, 1920; wgmma.mma_async.sync.aligned.m64n64k16.f16.f16.f16 {qz0,qz1,qz2,qz3,qz4,qz5,qz6,qz7,qz8,qz9,qz10,qz11,qz12,qz13,qz14,qz15}, {qa12,qa13,qa14,qa15}, dt, pt, 1, 1, 1;\n"
        "add.s64 dt, w1d, 2048; wgmma.mma_async.sync.aligned.m64n64k16.f16.f16.f16 {qz0,qz1,qz2,qz3,qz4,qz5,qz6,qz7,qz8,qz9,qz10,qz11,qz12,qz13,qz14,qz15}, {qa16,qa17,qa18,qa19}, dt, pt, 1, 1, 1;\n"
        "add.s64 dt, w1d, 2176; wgmma.mma_async.sync.aligned.m64n64k16.f16.f16.f16 {qz0,qz1,qz2,qz3,qz4,qz5,qz6,qz7,qz8,qz9,qz10,qz11,qz12,qz13,qz14,qz15}, {qa20,qa21,qa22,qa23}, dt, pt, 1, 1, 1;\n"
        "wgmma.commit_group.sync.aligned;\n"
        "@pz bra.uni L22;\n"
        "mov.u32 ad, %tid.x; and.b32 ad, ad, 127; mad.wide.u32 gq, ad, 16, %15; st.global.v4.b32 [gq+6144], {g12,g13,g14,g15};\n"
        "mov.b32 {xl, xh}, a2; tanh.approx.f16 xr, xl; cvt.u32.u16 lo0, xr; tanh.approx.f16 xr, xh; cvt.u32.u16 hi0, xr; mul.rn.f16x2 a3, qz19, p1; fma.rn.f16x2 p0, qz20, qz20, c; fma.rn.f16x2 g0, qz16, h0, qz16; prmt.b32 h1, lo1, hi1, 0x5410;\n"
        "mov.b32 {xl, xh}, a3; tanh.approx.f16 xr, xl; cvt.u32.u16 lo1, xr; tanh.approx.f16 xr, xh; cvt.u32.u16 hi1, xr; mul.rn.f16x2 a0, qz20, p0; fma.rn.f16x2 p1, qz21, qz21, c; fma.rn.f16x2 g1, qz17, h1, qz17; prmt.b32 h0, lo0, hi0, 0x5410;\n"
        "mov.b32 {xl, xh}, a0; tanh.approx.f16 xr, xl; cvt.u32.u16 lo0, xr; tanh.approx.f16 xr, xh; cvt.u32.u16 hi0, xr; mul.rn.f16x2 a1, qz21, p1; fma.rn.f16x2 p0, qz22, qz22, c; fma.rn.f16x2 g2, qz18, h0, qz18; prmt.b32 h1, lo1, hi1, 0x5410;\n"
        "mov.b32 {xl, xh}, a1; tanh.approx.f16 xr, xl; cvt.u32.u16 lo1, xr; tanh.approx.f16 xr, xh; cvt.u32.u16 hi1, xr; mul.rn.f16x2 a2, qz22, p0; fma.rn.f16x2 p1, qz23, qz23, c; fma.rn.f16x2 g3, qz19, h1, qz19; prmt.b32 h0, lo0, hi0, 0x5410;\n"
        "L22:\n"
        "@pz bra.uni L26;\n"
        "mov.u32 ad, %tid.x; and.b32 ad, ad, 127; mad.wide.u32 gq, ad, 16, %15; st.global.v4.b32 [gq+8192], {g0,g1,g2,g3};\n"
        "mov.b32 {xl, xh}, a2; tanh.approx.f16 xr, xl; cvt.u32.u16 lo0, xr; tanh.approx.f16 xr, xh; cvt.u32.u16 hi0, xr; mul.rn.f16x2 a3, qz23, p1; fma.rn.f16x2 p0, qz24, qz24, c; fma.rn.f16x2 g4, qz20, h0, qz20; prmt.b32 h1, lo1, hi1, 0x5410;\n"
        "mov.b32 {xl, xh}, a3; tanh.approx.f16 xr, xl; cvt.u32.u16 lo1, xr; tanh.approx.f16 xr, xh; cvt.u32.u16 hi1, xr; mul.rn.f16x2 a0, qz24, p0; fma.rn.f16x2 p1, qz25, qz25, c; fma.rn.f16x2 g5, qz21, h1, qz21; prmt.b32 h0, lo0, hi0, 0x5410;\n"
        "mov.b32 {xl, xh}, a0; tanh.approx.f16 xr, xl; cvt.u32.u16 lo0, xr; tanh.approx.f16 xr, xh; cvt.u32.u16 hi0, xr; mul.rn.f16x2 a1, qz25, p1; fma.rn.f16x2 p0, qz26, qz26, c; fma.rn.f16x2 g6, qz22, h0, qz22; prmt.b32 h1, lo1, hi1, 0x5410;\n"
        "mov.b32 {xl, xh}, a1; tanh.approx.f16 xr, xl; cvt.u32.u16 lo1, xr; tanh.approx.f16 xr, xh; cvt.u32.u16 hi1, xr; mul.rn.f16x2 a2, qz26, p0; fma.rn.f16x2 p1, qz27, qz27, c; fma.rn.f16x2 g7, qz23, h1, qz23; prmt.b32 h0, lo0, hi0, 0x5410;\n"
        "L26:\n"
        "@pz bra.uni L30;\n"
        "mov.u32 ad, %tid.x; and.b32 ad, ad, 127; mad.wide.u32 gq, ad, 16, %15; st.global.v4.b32 [gq+10240], {g4,g5,g6,g7};\n"
        "mov.b32 {xl, xh}, a2; tanh.approx.f16 xr, xl; cvt.u32.u16 lo0, xr; tanh.approx.f16 xr, xh; cvt.u32.u16 hi0, xr; mul.rn.f16x2 a3, qz27, p1; fma.rn.f16x2 p0, qz28, qz28, c; fma.rn.f16x2 g8, qz24, h0, qz24; prmt.b32 h1, lo1, hi1, 0x5410;\n"
        "mov.b32 {xl, xh}, a3; tanh.approx.f16 xr, xl; cvt.u32.u16 lo1, xr; tanh.approx.f16 xr, xh; cvt.u32.u16 hi1, xr; mul.rn.f16x2 a0, qz28, p0; fma.rn.f16x2 p1, qz29, qz29, c; fma.rn.f16x2 g9, qz25, h1, qz25; prmt.b32 h0, lo0, hi0, 0x5410;\n"
        "mov.b32 {xl, xh}, a0; tanh.approx.f16 xr, xl; cvt.u32.u16 lo0, xr; tanh.approx.f16 xr, xh; cvt.u32.u16 hi0, xr; mul.rn.f16x2 a1, qz29, p1; fma.rn.f16x2 p0, qz30, qz30, c; fma.rn.f16x2 g10, qz26, h0, qz26; prmt.b32 h1, lo1, hi1, 0x5410;\n"
        "mov.b32 {xl, xh}, a1; tanh.approx.f16 xr, xl; cvt.u32.u16 lo1, xr; tanh.approx.f16 xr, xh; cvt.u32.u16 hi1, xr; mul.rn.f16x2 a2, qz30, p0; fma.rn.f16x2 p1, qz31, qz31, c; fma.rn.f16x2 g11, qz27, h1, qz27; prmt.b32 h0, lo0, hi0, 0x5410;\n"
        "L30:\n"
        "wgmma.wait_group.sync.aligned 0;\n"
        "@pz bra.uni L34;\n"
        "mov.u32 ad, %tid.x; and.b32 ad, ad, 127; mad.wide.u32 gq, ad, 16, %15; st.global.v4.b32 [gq+12288], {g8,g9,g10,g11};\n"
        "mov.b32 {xl, xh}, a2; tanh.approx.f16 xr, xl; cvt.u32.u16 lo0, xr; tanh.approx.f16 xr, xh; cvt.u32.u16 hi0, xr; mul.rn.f16x2 a3, qz31, p1; fma.rn.f16x2 p0, qz0, qz0, c; fma.rn.f16x2 g12, qz28, h0, qz28; prmt.b32 h1, lo1, hi1, 0x5410;\n"
        "mov.b32 {xl, xh}, a3; tanh.approx.f16 xr, xl; cvt.u32.u16 lo1, xr; tanh.approx.f16 xr, xh; cvt.u32.u16 hi1, xr; mul.rn.f16x2 a0, qz0, p0; fma.rn.f16x2 p1, qz1, qz1, c; fma.rn.f16x2 g13, qz29, h1, qz29; prmt.b32 h0, lo0, hi0, 0x5410;\n"
        "mov.b32 {xl, xh}, a0; tanh.approx.f16 xr, xl; cvt.u32.u16 lo0, xr; tanh.approx.f16 xr, xh; cvt.u32.u16 hi0, xr; mul.rn.f16x2 a1, qz1, p1; fma.rn.f16x2 p0, qz2, qz2, c; fma.rn.f16x2 g14, qz30, h0, qz30; prmt.b32 h1, lo1, hi1, 0x5410;\n"
        "mov.b32 {xl, xh}, a1; tanh.approx.f16 xr, xl; cvt.u32.u16 lo1, xr; tanh.approx.f16 xr, xh; cvt.u32.u16 hi1, xr; mul.rn.f16x2 a2, qz2, p0; fma.rn.f16x2 p1, qz3, qz3, c; fma.rn.f16x2 g15, qz31, h1, qz31; prmt.b32 h0, lo0, hi0, 0x5410;\n"
        "L34:\n"
        "wgmma.fence.sync.aligned;\n"
        "add.s64 dt, w1d, 2304; wgmma.mma_async.sync.aligned.m64n64k16.f16.f16.f16 {qz16,qz17,qz18,qz19,qz20,qz21,qz22,qz23,qz24,qz25,qz26,qz27,qz28,qz29,qz30,qz31}, {qa0,qa1,qa2,qa3}, dt, pf, 1, 1, 1;\n"
        "add.s64 dt, w1d, 2432; wgmma.mma_async.sync.aligned.m64n64k16.f16.f16.f16 {qz16,qz17,qz18,qz19,qz20,qz21,qz22,qz23,qz24,qz25,qz26,qz27,qz28,qz29,qz30,qz31}, {qa4,qa5,qa6,qa7}, dt, pt, 1, 1, 1;\n"
        "add.s64 dt, w1d, 2560; wgmma.mma_async.sync.aligned.m64n64k16.f16.f16.f16 {qz16,qz17,qz18,qz19,qz20,qz21,qz22,qz23,qz24,qz25,qz26,qz27,qz28,qz29,qz30,qz31}, {qa8,qa9,qa10,qa11}, dt, pt, 1, 1, 1;\n"
        "add.s64 dt, w1d, 2688; wgmma.mma_async.sync.aligned.m64n64k16.f16.f16.f16 {qz16,qz17,qz18,qz19,qz20,qz21,qz22,qz23,qz24,qz25,qz26,qz27,qz28,qz29,qz30,qz31}, {qa12,qa13,qa14,qa15}, dt, pt, 1, 1, 1;\n"
        "add.s64 dt, w1d, 2816; wgmma.mma_async.sync.aligned.m64n64k16.f16.f16.f16 {qz16,qz17,qz18,qz19,qz20,qz21,qz22,qz23,qz24,qz25,qz26,qz27,qz28,qz29,qz30,qz31}, {qa16,qa17,qa18,qa19}, dt, pt, 1, 1, 1;\n"
        "add.s64 dt, w1d, 2944; wgmma.mma_async.sync.aligned.m64n64k16.f16.f16.f16 {qz16,qz17,qz18,qz19,qz20,qz21,qz22,qz23,qz24,qz25,qz26,qz27,qz28,qz29,qz30,qz31}, {qa20,qa21,qa22,qa23}, dt, pt, 1, 1, 1;\n"
        "wgmma.commit_group.sync.aligned;\n"
        "@pz bra.uni L38;\n"
        "mov.u32 ad, %tid.x; and.b32 ad, ad, 127; mad.wide.u32 gq, ad, 16, %15; st.global.v4.b32 [gq+14336], {g12,g13,g14,g15};\n"
        "mov.b32 {xl, xh}, a2; tanh.approx.f16 xr, xl; cvt.u32.u16 lo0, xr; tanh.approx.f16 xr, xh; cvt.u32.u16 hi0, xr; mul.rn.f16x2 a3, qz3, p1; fma.rn.f16x2 p0, qz4, qz4, c; fma.rn.f16x2 g0, qz0, h0, qz0; prmt.b32 h1, lo1, hi1, 0x5410;\n"
        "mov.b32 {xl, xh}, a3; tanh.approx.f16 xr, xl; cvt.u32.u16 lo1, xr; tanh.approx.f16 xr, xh; cvt.u32.u16 hi1, xr; mul.rn.f16x2 a0, qz4, p0; fma.rn.f16x2 p1, qz5, qz5, c; fma.rn.f16x2 g1, qz1, h1, qz1; prmt.b32 h0, lo0, hi0, 0x5410;\n"
        "mov.b32 {xl, xh}, a0; tanh.approx.f16 xr, xl; cvt.u32.u16 lo0, xr; tanh.approx.f16 xr, xh; cvt.u32.u16 hi0, xr; mul.rn.f16x2 a1, qz5, p1; fma.rn.f16x2 p0, qz6, qz6, c; fma.rn.f16x2 g2, qz2, h0, qz2; prmt.b32 h1, lo1, hi1, 0x5410;\n"
        "mov.b32 {xl, xh}, a1; tanh.approx.f16 xr, xl; cvt.u32.u16 lo1, xr; tanh.approx.f16 xr, xh; cvt.u32.u16 hi1, xr; mul.rn.f16x2 a2, qz6, p0; fma.rn.f16x2 p1, qz7, qz7, c; fma.rn.f16x2 g3, qz3, h1, qz3; prmt.b32 h0, lo0, hi0, 0x5410;\n"
        "L38:\n"
        "@pz bra.uni L42;\n"
        "mov.u32 ad, %tid.x; and.b32 ad, ad, 127; mad.wide.u32 gq, ad, 16, %15; st.global.v4.b32 [gq+16384], {g0,g1,g2,g3};\n"
        "mov.b32 {xl, xh}, a2; tanh.approx.f16 xr, xl; cvt.u32.u16 lo0, xr; tanh.approx.f16 xr, xh; cvt.u32.u16 hi0, xr; mul.rn.f16x2 a3, qz7, p1; fma.rn.f16x2 p0, qz8, qz8, c; fma.rn.f16x2 g4, qz4, h0, qz4; prmt.b32 h1, lo1, hi1, 0x5410;\n"
        "mov.b32 {xl, xh}, a3; tanh.approx.f16 xr, xl; cvt.u32.u16 lo1, xr; tanh.approx.f16 xr, xh; cvt.u32.u16 hi1, xr; mul.rn.f16x2 a0, qz8, p0; fma.rn.f16x2 p1, qz9, qz9, c; fma.rn.f16x2 g5, qz5, h1, qz5; prmt.b32 h0, lo0, hi0, 0x5410;\n"
        "mov.b32 {xl, xh}, a0; tanh.approx.f16 xr, xl; cvt.u32.u16 lo0, xr; tanh.approx.f16 xr, xh; cvt.u32.u16 hi0, xr; mul.rn.f16x2 a1, qz9, p1; fma.rn.f16x2 p0, qz10, qz10, c; fma.rn.f16x2 g6, qz6, h0, qz6; prmt.b32 h1, lo1, hi1, 0x5410;\n"
        "mov.b32 {xl, xh}, a1; tanh.approx.f16 xr, xl; cvt.u32.u16 lo1, xr; tanh.approx.f16 xr, xh; cvt.u32.u16 hi1, xr; mul.rn.f16x2 a2, qz10, p0; fma.rn.f16x2 p1, qz11, qz11, c; fma.rn.f16x2 g7, qz7, h1, qz7; prmt.b32 h0, lo0, hi0, 0x5410;\n"
        "L42:\n"
        "@pz bra.uni L46;\n"
        "mov.u32 ad, %tid.x; and.b32 ad, ad, 127; mad.wide.u32 gq, ad, 16, %15; st.global.v4.b32 [gq+18432], {g4,g5,g6,g7};\n"
        "mov.b32 {xl, xh}, a2; tanh.approx.f16 xr, xl; cvt.u32.u16 lo0, xr; tanh.approx.f16 xr, xh; cvt.u32.u16 hi0, xr; mul.rn.f16x2 a3, qz11, p1; fma.rn.f16x2 p0, qz12, qz12, c; fma.rn.f16x2 g8, qz8, h0, qz8; prmt.b32 h1, lo1, hi1, 0x5410;\n"
        "mov.b32 {xl, xh}, a3; tanh.approx.f16 xr, xl; cvt.u32.u16 lo1, xr; tanh.approx.f16 xr, xh; cvt.u32.u16 hi1, xr; mul.rn.f16x2 a0, qz12, p0; fma.rn.f16x2 p1, qz13, qz13, c; fma.rn.f16x2 g9, qz9, h1, qz9; prmt.b32 h0, lo0, hi0, 0x5410;\n"
        "mov.b32 {xl, xh}, a0; tanh.approx.f16 xr, xl; cvt.u32.u16 lo0, xr; tanh.approx.f16 xr, xh; cvt.u32.u16 hi0, xr; mul.rn.f16x2 a1, qz13, p1; fma.rn.f16x2 p0, qz14, qz14, c; fma.rn.f16x2 g10, qz10, h0, qz10; prmt.b32 h1, lo1, hi1, 0x5410;\n"
        "mov.b32 {xl, xh}, a1; tanh.approx.f16 xr, xl; cvt.u32.u16 lo1, xr; tanh.approx.f16 xr, xh; cvt.u32.u16 hi1, xr; mul.rn.f16x2 a2, qz14, p0; fma.rn.f16x2 p1, qz15, qz15, c; fma.rn.f16x2 g11, qz11, h1, qz11; prmt.b32 h0, lo0, hi0, 0x5410;\n"
        "L46:\n"
        "wgmma.wait_group.sync.aligned 0;\n"
        "@pz bra.uni L50;\n"
        "mov.u32 ad, %tid.x; and.b32 ad, ad, 127; mad.wide.u32 gq, ad, 16, %15; st.global.v4.b32 [gq+20480], {g8,g9,g10,g11};\n"
        "mov.b32 {xl, xh}, a2; tanh.approx.f16 xr, xl; cvt.u32.u16 lo0, xr; tanh.approx.f16 xr, xh; cvt.u32.u16 hi0, xr; mul.rn.f16x2 a3, qz15, p1; fma.rn.f16x2 p0, qz16, qz16, c; fma.rn.f16x2 g12, qz12, h0, qz12; prmt.b32 h1, lo1, hi1, 0x5410;\n"
        "mov.b32 {xl, xh}, a3; tanh.approx.f16 xr, xl; cvt.u32.u16 lo1, xr; tanh.approx.f16 xr, xh; cvt.u32.u16 hi1, xr; mul.rn.f16x2 a0, qz16, p0; fma.rn.f16x2 p1, qz17, qz17, c; fma.rn.f16x2 g13, qz13, h1, qz13; prmt.b32 h0, lo0, hi0, 0x5410;\n"
        "mov.b32 {xl, xh}, a0; tanh.approx.f16 xr, xl; cvt.u32.u16 lo0, xr; tanh.approx.f16 xr, xh; cvt.u32.u16 hi0, xr; mul.rn.f16x2 a1, qz17, p1; fma.rn.f16x2 p0, qz18, qz18, c; fma.rn.f16x2 g14, qz14, h0, qz14; prmt.b32 h1, lo1, hi1, 0x5410;\n"
        "mov.b32 {xl, xh}, a1; tanh.approx.f16 xr, xl; cvt.u32.u16 lo1, xr; tanh.approx.f16 xr, xh; cvt.u32.u16 hi1, xr; mul.rn.f16x2 a2, qz18, p0; fma.rn.f16x2 p1, qz19, qz19, c; fma.rn.f16x2 g15, qz15, h1, qz15; prmt.b32 h0, lo0, hi0, 0x5410;\n"
        "L50:\n"
        "wgmma.fence.sync.aligned;\n"
        "add.s64 dt, w1d, 3072; wgmma.mma_async.sync.aligned.m64n64k16.f16.f16.f16 {qz0,qz1,qz2,qz3,qz4,qz5,qz6,qz7,qz8,qz9,qz10,qz11,qz12,qz13,qz14,qz15}, {qa0,qa1,qa2,qa3}, dt, pf, 1, 1, 1;\n"
        "add.s64 dt, w1d, 3200; wgmma.mma_async.sync.aligned.m64n64k16.f16.f16.f16 {qz0,qz1,qz2,qz3,qz4,qz5,qz6,qz7,qz8,qz9,qz10,qz11,qz12,qz13,qz14,qz15}, {qa4,qa5,qa6,qa7}, dt, pt, 1, 1, 1;\n"
        "add.s64 dt, w1d, 3328; wgmma.mma_async.sync.aligned.m64n64k16.f16.f16.f16 {qz0,qz1,qz2,qz3,qz4,qz5,qz6,qz7,qz8,qz9,qz10,qz11,qz12,qz13,qz14,qz15}, {qa8,qa9,qa10,qa11}, dt, pt, 1, 1, 1;\n"
        "add.s64 dt, w1d, 3456; wgmma.mma_async.sync.aligned.m64n64k16.f16.f16.f16 {qz0,qz1,qz2,qz3,qz4,qz5,qz6,qz7,qz8,qz9,qz10,qz11,qz12,qz13,qz14,qz15}, {qa12,qa13,qa14,qa15}, dt, pt, 1, 1, 1;\n"
        "add.s64 dt, w1d, 3584; wgmma.mma_async.sync.aligned.m64n64k16.f16.f16.f16 {qz0,qz1,qz2,qz3,qz4,qz5,qz6,qz7,qz8,qz9,qz10,qz11,qz12,qz13,qz14,qz15}, {qa16,qa17,qa18,qa19}, dt, pt, 1, 1, 1;\n"
        "add.s64 dt, w1d, 3712; wgmma.mma_async.sync.aligned.m64n64k16.f16.f16.f16 {qz0,qz1,qz2,qz3,qz4,qz5,qz6,qz7,qz8,qz9,qz10,qz11,qz12,qz13,qz14,qz15}, {qa20,qa21,qa22,qa23}, dt, pt, 1, 1, 1;\n"
        "wgmma.commit_group.sync.aligned;\n"
        "@pz bra.uni L54;\n"
        "mov.u32 ad, %tid.x; and.b32 ad, ad, 127; mad.wide.u32 gq, ad, 16, %15; st.global.v4.b32 [gq+22528], {g12,g13,g14,g15};\n"
        "mov.b32 {xl, xh}, a2; tanh.approx.f16 xr, xl; cvt.u32.u16 lo0, xr; tanh.approx.f16 xr, xh; cvt.u32.u16 hi0, xr; mul.rn.f16x2 a3, qz19, p1; fma.rn.f16x2 p0, qz20, qz20, c; fma.rn.f16x2 g0, qz16, h0, qz16; prmt.b32 h1, lo1, hi1, 0x5410;\n"
        "mov.b32 {xl, xh}, a3; tanh.approx.f16 xr, xl; cvt.u32.u16 lo1, xr; tanh.approx.f16 xr, xh; cvt.u32.u16 hi1, xr; mul.rn.f16x2 a0, qz20, p0; fma.rn.f16x2 p1, qz21, qz21, c; fma.rn.f16x2 g1, qz17, h1, qz17; prmt.b32 h0, lo0, hi0, 0x5410;\n"
        "mov.b32 {xl, xh}, a0; tanh.approx.f16 xr, xl; cvt.u32.u16 lo0, xr; tanh.approx.f16 xr, xh; cvt.u32.u16 hi0, xr; mul.rn.f16x2 a1, qz21, p1; fma.rn.f16x2 p0, qz22, qz22, c; fma.rn.f16x2 g2, qz18, h0, qz18; prmt.b32 h1, lo1, hi1, 0x5410;\n"
        "mov.b32 {xl, xh}, a1; tanh.approx.f16 xr, xl; cvt.u32.u16 lo1, xr; tanh.approx.f16 xr, xh; cvt.u32.u16 hi1, xr; mul.rn.f16x2 a2, qz22, p0; fma.rn.f16x2 p1, qz23, qz23, c; fma.rn.f16x2 g3, qz19, h1, qz19; prmt.b32 h0, lo0, hi0, 0x5410;\n"
        "L54:\n"
        "@pz bra.uni L58;\n"
        "mov.u32 ad, %tid.x; and.b32 ad, ad, 127; mad.wide.u32 gq, ad, 16, %15; st.global.v4.b32 [gq+24576], {g0,g1,g2,g3};\n"
        "mov.b32 {xl, xh}, a2; tanh.approx.f16 xr, xl; cvt.u32.u16 lo0, xr; tanh.approx.f16 xr, xh; cvt.u32.u16 hi0, xr; mul.rn.f16x2 a3, qz23, p1; fma.rn.f16x2 p0, qz24, qz24, c; fma.rn.f16x2 g4, qz20, h0, qz20; prmt.b32 h1, lo1, hi1, 0x5410;\n"
        "mov.b32 {xl, xh}, a3; tanh.approx.f16 xr, xl; cvt.u32.u16 lo1, xr; tanh.approx.f16 xr, xh; cvt.u32.u16 hi1, xr; mul.rn.f16x2 a0, qz24, p0; fma.rn.f16x2 p1, qz25, qz25, c; fma.rn.f16x2 g5, qz21, h1, qz21; prmt.b32 h0, lo0, hi0, 0x5410;\n"
        "mov.b32 {xl, xh}, a0; tanh.approx.f16 xr, xl; cvt.u32.u16 lo0, xr; tanh.approx.f16 xr, xh; cvt.u32.u16 hi0, xr; mul.rn.f16x2 a1, qz25, p1; fma.rn.f16x2 p0, qz26, qz26, c; fma.rn.f16x2 g6, qz22, h0, qz22; prmt.b32 h1, lo1, hi1, 0x5410;\n"
        "mov.b32 {xl, xh}, a1; tanh.approx.f16 xr, xl; cvt.u32.u16 lo1, xr; tanh.approx.f16 xr, xh; cvt.u32.u16 hi1, xr; mul.rn.f16x2 a2, qz26, p0; fma.rn.f16x2 p1, qz27, qz27, c; fma.rn.f16x2 g7, qz23, h1, qz23; prmt.b32 h0, lo0, hi0, 0x5410;\n"
        "L58:\n"
        "@pz bra.uni L62;\n"
        "mov.u32 ad, %tid.x; and.b32 ad, ad, 127; mad.wide.u32 gq, ad, 16, %15; st.global.v4.b32 [gq+26624], {g4,g5,g6,g7};\n"
        "mov.b32 {xl, xh}, a2; tanh.approx.f16 xr, xl; cvt.u32.u16 lo0, xr; tanh.approx.f16 xr, xh; cvt.u32.u16 hi0, xr; mul.rn.f16x2 a3, qz27, p1; fma.rn.f16x2 p0, qz28, qz28, c; fma.rn.f16x2 g8, qz24, h0, qz24; prmt.b32 h1, lo1, hi1, 0x5410;\n"
        "mov.b32 {xl, xh}, a3; tanh.approx.f16 xr, xl; cvt.u32.u16 lo1, xr; tanh.approx.f16 xr, xh; cvt.u32.u16 hi1, xr; mul.rn.f16x2 a0, qz28, p0; fma.rn.f16x2 p1, qz29, qz29, c; fma.rn.f16x2 g9, qz25, h1, qz25; prmt.b32 h0, lo0, hi0, 0x5410;\n"
        "mov.b32 {xl, xh}, a0; tanh.approx.f16 xr, xl; cvt.u32.u16 lo0, xr; tanh.approx.f16 xr, xh; cvt.u32.u16 hi0, xr; mul.rn.f16x2 a1, qz29, p1; fma.rn.f16x2 p0, qz30, qz30, c; fma.rn.f16x2 g10, qz26, h0, qz26; prmt.b32 h1, lo1, hi1, 0x5410;\n"
        "mov.b32 {xl, xh}, a1; tanh.approx.f16 xr, xl; cvt.u32.u16 lo1, xr; tanh.approx.f16 xr, xh; cvt.u32.u16 hi1, xr; mul.rn.f16x2 a2, qz30, p0; fma.rn.f16x2 p1, qz31, qz31, c; fma.rn.f16x2 g11, qz27, h1, qz27; prmt.b32 h0, lo0, hi0, 0x5410;\n"
        "L62:\n"
        "wgmma.wait_group.sync.aligned 0;\n"
        "@pz bra.uni L66;\n"
        "mov.u32 ad, %tid.x; and.b32 ad, ad, 127; mad.wide.u32 gq, ad, 16, %15; st.global.v4.b32 [gq+28672], {g8,g9,g10,g11};\n"
        "mov.b32 {xl, xh}, a2; tanh.approx.f16 xr, xl; cvt.u32.u16 lo0, xr; tanh.approx.f16 xr, xh; cvt.u32.u16 hi0, xr; mul.rn.f16x2 a3, qz31, p1; fma.rn.f16x2 p0, qz0, qz0, c; fma.rn.f16x2 g12, qz28, h0, qz28; prmt.b32 h1, lo1, hi1, 0x5410;\n"
        "mov.b32 {xl, xh}, a3; tanh.approx.f16 xr, xl; cvt.u32.u16 lo1, xr; tanh.approx.f16 xr, xh; cvt.u32.u16 hi1, xr; mul.rn.f16x2 a0, qz0, p0; fma.rn.f16x2 p1, qz1, qz1, c; fma.rn.f16x2 g13, qz29, h1, qz29; prmt.b32 h0, lo0, hi0, 0x5410;\n"
        "mov.b32 {xl, xh}, a0; tanh.approx.f16 xr, xl; cvt.u32.u16 lo0, xr; tanh.approx.f16 xr, xh; cvt.u32.u16 hi0, xr; mul.rn.f16x2 a1, qz1, p1; fma.rn.f16x2 p0, qz2, qz2, c; fma.rn.f16x2 g14, qz30, h0, qz30; prmt.b32 h1, lo1, hi1, 0x5410;\n"
        "mov.b32 {xl, xh}, a1; tanh.approx.f16 xr, xl; cvt.u32.u16 lo1, xr; tanh.approx.f16 xr, xh; cvt.u32.u16 hi1, xr; mul.rn.f16x2 a2, qz2, p0; fma.rn.f16x2 p1, qz3, qz3, c; fma.rn.f16x2 g15, qz31, h1, qz31; prmt.b32 h0, lo0, hi0, 0x5410;\n"
        "L66:\n"
        "wgmma.fence.sync.aligned;\n"
        "add.s64 dt, w1d, 3840; wgmma.mma_async.sync.aligned.m64n64k16.f16.f16.f16 {qz16,qz17,qz18,qz19,qz20,qz21,qz22,qz23,qz24,qz25,qz26,qz27,qz28,qz29,qz30,qz31}, {qa0,qa1,qa2,qa3}, dt, pf, 1, 1, 1;\n"
        "add.s64 dt, w1d, 3968; wgmma.mma_async.sync.aligned.m64n64k16.f16.f16.f16 {qz16,qz17,qz18,qz19,qz20,qz21,qz22,qz23,qz24,qz25,qz26,qz27,qz28,qz29,qz30,qz31}, {qa4,qa5,qa6,qa7}, dt, pt, 1, 1, 1;\n"
        "add.s64 dt, w1d, 4096; wgmma.mma_async.sync.aligned.m64n64k16.f16.f16.f16 {qz16,qz17,qz18,qz19,qz20,qz21,qz22,qz23,qz24,qz25,qz26,qz27,qz28,qz29,qz30,qz31}, {qa8,qa9,qa10,qa11}, dt, pt, 1, 1, 1;\n"
        "add.s64 dt, w1d, 4224; wgmma.mma_async.sync.aligned.m64n64k16.f16.f16.f16 {qz16,qz17,qz18,qz19,qz20,qz21,qz22,qz23,qz24,qz25,qz26,qz27,qz28,qz29,qz30,qz31}, {qa12,qa13,qa14,qa15}, dt, pt, 1, 1, 1;\n"
        "add.s64 dt, w1d, 4352; wgmma.mma_async.sync.aligned.m64n64k16.f16.f16.f16 {qz16,qz17,qz18,qz19,qz20,qz21,qz22,qz23,qz24,qz25,qz26,qz27,qz28,qz29,qz30,qz31}, {qa16,qa17,qa18,qa19}, dt, pt, 1, 1, 1;\n"
        "add.s64 dt, w1d, 4480; wgmma.mma_async.sync.aligned.m64n64k16.f16.f16.f16 {qz16,qz17,qz18,qz19,qz20,qz21,qz22,qz23,qz24,qz25,qz26,qz27,qz28,qz29,qz30,qz31}, {qa20,qa21,qa22,qa23}, dt, pt, 1, 1, 1;\n"
        "wgmma.commit_group.sync.aligned;\n"
        "@pz bra.uni L70;\n"
        "mov.u32 ad, %tid.x; and.b32 ad, ad, 127; mad.wide.u32 gq, ad, 16, %15; st.global.v4.b32 [gq+30720], {g12,g13,g14,g15};\n"
        "mov.b32 {xl, xh}, a2; tanh.approx.f16 xr, xl; cvt.u32.u16 lo0, xr; tanh.approx.f16 xr, xh; cvt.u32.u16 hi0, xr; mul.rn.f16x2 a3, qz3, p1; fma.rn.f16x2 p0, qz4, qz4, c; fma.rn.f16x2 g0, qz0, h0, qz0; prmt.b32 h1, lo1, hi1, 0x5410;\n"
        "mov.b32 {xl, xh}, a3; tanh.approx.f16 xr, xl; cvt.u32.u16 lo1, xr; tanh.approx.f16 xr, xh; cvt.u32.u16 hi1, xr; mul.rn.f16x2 a0, qz4, p0; fma.rn.f16x2 p1, qz5, qz5, c; fma.rn.f16x2 g1, qz1, h1, qz1; prmt.b32 h0, lo0, hi0, 0x5410;\n"
        "mov.b32 {xl, xh}, a0; tanh.approx.f16 xr, xl; cvt.u32.u16 lo0, xr; tanh.approx.f16 xr, xh; cvt.u32.u16 hi0, xr; mul.rn.f16x2 a1, qz5, p1; fma.rn.f16x2 p0, qz6, qz6, c; fma.rn.f16x2 g2, qz2, h0, qz2; prmt.b32 h1, lo1, hi1, 0x5410;\n"
        "mov.b32 {xl, xh}, a1; tanh.approx.f16 xr, xl; cvt.u32.u16 lo1, xr; tanh.approx.f16 xr, xh; cvt.u32.u16 hi1, xr; mul.rn.f16x2 a2, qz6, p0; fma.rn.f16x2 p1, qz7, qz7, c; fma.rn.f16x2 g3, qz3, h1, qz3; prmt.b32 h0, lo0, hi0, 0x5410;\n"
        "L70:\n"
        "@pz bra.uni L74;\n"
        "mov.b32 {xl, xh}, a2; tanh.approx.f16 xr, xl; cvt.u32.u16 lo0, xr; tanh.approx.f16 xr, xh; cvt.u32.u16 hi0, xr; mul.rn.f16x2 a3, qz7, p1; fma.rn.f16x2 p0, qz8, qz8, c; fma.rn.f16x2 g4, qz4, h0, qz4; prmt.b32 h1, lo1, hi1, 0x5410;\n"
        "mov.b32 {xl, xh}, a3; tanh.approx.f16 xr, xl; cvt.u32.u16 lo1, xr; tanh.approx.f16 xr, xh; cvt.u32.u16 hi1, xr; mul.rn.f16x2 a0, qz8, p0; fma.rn.f16x2 p1, qz9, qz9, c; fma.rn.f16x2 g5, qz5, h1, qz5; prmt.b32 h0, lo0, hi0, 0x5410;\n"
        "mov.b32 {xl, xh}, a0; tanh.approx.f16 xr, xl; cvt.u32.u16 lo0, xr; tanh.approx.f16 xr, xh; cvt.u32.u16 hi0, xr; mul.rn.f16x2 a1, qz9, p1; fma.rn.f16x2 p0, qz10, qz10, c; fma.rn.f16x2 g6, qz6, h0, qz6; prmt.b32 h1, lo1, hi1, 0x5410;\n"
        "mov.b32 {xl, xh}, a1; tanh.approx.f16 xr, xl; cvt.u32.u16 lo1, xr; tanh.approx.f16 xr, xh; cvt.u32.u16 hi1, xr; mul.rn.f16x2 a2, qz10, p0; fma.rn.f16x2 p1, qz11, qz11, c; fma.rn.f16x2 g7, qz7, h1, qz7; prmt.b32 h0, lo0, hi0, 0x5410;\n"
        "L74:\n"
        "wgmma.wait_group.sync.aligned 0;\n"
        "mov.u32 ad, %tid.x; and.b32 ad, ad, 127; mad.wide.u32 gq, ad, 16, %15;\n"
        "ld.global.v4.b32 {qa0,qa1,qa2,qa3}, [gq+0];\n"
        "ld.global.v4.b32 {qa4,qa5,qa6,qa7}, [gq+2048];\n"
        "ld.global.v4.b32 {qa8,qa9,qa10,qa11}, [gq+4096];\n"
        "ld.global.v4.b32 {qa12,qa13,qa14,qa15}, [gq+6144];\n"
        "ld.global.v4.b32 {qa16,qa17,qa18,qa19}, [gq+8192];\n"
        "ld.global.v4.b32 {qa20,qa21,qa22,qa23}, [gq+10240];\n"
        "@!pl bra.uni FPREB;\n"
        "sub.u32 tt, off, %9; cvt.u64.u32 gp, tt; add.s64 gp, gp, %12;\n"
        "elect.sync _|pr, 0xffffffff;\n"
        "@pr cp.async.bulk.prefetch.L2.global [gp], 12288;\n"
        "cvt.u64.u32 gp, off; add.s64 gp, gp, %11;\n"
        "@pr cp.async.bulk.prefetch.L2.global [gp], 12288;\n"
        "FPREB:\n"
        "mov.u32 tt, 231232; mbarrier.try_wait.parity.shared::cta.b64 pw, [tt], %13;\n"
        "@!pw bra.uni SPINFR;\n"
        "BACKFR:\n"
        "mov.u32 tt, 230792; ld.shared.v2.b32 {osc, tt}, [tt];\n"
        "setp.ne.u32 pr, tt, 0; vote.sync.any.pred pr, pr, 0xffffffff;\n"
        "@pr bra.uni RETRY;\n"
        "@!pl bra.uni FLOADB;\n"
        "sub.u32 tt, off, %9; cvt.u64.u32 gp, tt; add.s64 gp, gp, %12;\n"
        "elect.sync _|pr, 0xffffffff;\n"
        "@pr mbarrier.arrive.expect_tx.shared::cta.b64 _, [ybar], 12288;\n"
        "@pr cp.async.bulk.shared::cluster.global.mbarrier::complete_tx::bytes [%5], [gp], 12288, [ybar];\n"
        "FLOADB:\n"
        "mad.lo.u32 tt, n, 8, tbar; mbarrier.try_wait.parity.shared::cta.b64 pw, [tt], tpar;\n"
        "@!pw bra.uni SPINFT;\n"
        "BACKFT:\n"
        "ld.shared.v4.b32 {o0,o1,o2,o3}, [%8+0];\n"
        "ld.shared.v4.b32 {o4,o5,o6,o7}, [%8+64];\n"
        "ld.shared.v4.b32 {o8,o9,o10,o11}, [%8+128];\n"
        "ld.shared.v4.b32 {o12,o13,o14,o15}, [%8+192];\n"
        "ld.shared.v4.b32 {o16,o17,o18,o19}, [%8+256];\n"
        "ld.shared.v4.b32 {o20,o21,o22,o23}, [%8+320];\n"
        "mov.u32 tt, 231208; mbarrier.try_wait.parity.shared::cta.b64 pw, [tt], 0;\n"
        "@!pw bra.uni SPINF0;\n"
        "BACKF0:\n"
        "wgmma.fence.sync.aligned;\n"
        "add.s64 dt, w2d, 0; wgmma.mma_async.sync.aligned.m64n96k16.f16.f16.f16 {o0,o1,o2,o3,o4,o5,o6,o7,o8,o9,o10,o11,o12,o13,o14,o15,o16,o17,o18,o19,o20,o21,o22,o23}, {qa0,qa1,qa2,qa3}, dt, pt, 1, 1, 1;\n"
        "wgmma.commit_group.sync.aligned;\n"
        "wgmma.fence.sync.aligned;\n"
        "add.s64 dt, w2d, 64; wgmma.mma_async.sync.aligned.m64n96k16.f16.f16.f16 {o0,o1,o2,o3,o4,o5,o6,o7,o8,o9,o10,o11,o12,o13,o14,o15,o16,o17,o18,o19,o20,o21,o22,o23}, {qa4,qa5,qa6,qa7}, dt, pt, 1, 1, 1;\n"
        "wgmma.commit_group.sync.aligned;\n"
        "wgmma.wait_group.sync.aligned 1;\n"
        "@pz bra.uni R1;\n"
        "mov.u32 ad, %tid.x; and.b32 ad, ad, 127; mad.wide.u32 gq, ad, 16, %15;\n"
        "ld.volatile.global.v4.b32 {qa0,qa1,qa2,qa3}, [gq+12288];\n"
        "R1:\n"
        "wgmma.fence.sync.aligned;\n"
        "add.s64 dt, w2d, 128; wgmma.mma_async.sync.aligned.m64n96k16.f16.f16.f16 {o0,o1,o2,o3,o4,o5,o6,o7,o8,o9,o10,o11,o12,o13,o14,o15,o16,o17,o18,o19,o20,o21,o22,o23}, {qa8,qa9,qa10,qa11}, dt, pt, 1, 1, 1;\n"
        "wgmma.commit_group.sync.aligned;\n"
        "wgmma.wait_group.sync.aligned 1;\n"
        "@pz bra.uni R2;\n"
        "mov.u32 ad, %tid.x; and.b32 ad, ad, 127; mad.wide.u32 gq, ad, 16, %15;\n"
        "ld.volatile.global.v4.b32 {qa4,qa5,qa6,qa7}, [gq+14336];\n"
        "R2:\n"
        "wgmma.fence.sync.aligned;\n"
        "add.s64 dt, w2d, 192; wgmma.mma_async.sync.aligned.m64n96k16.f16.f16.f16 {o0,o1,o2,o3,o4,o5,o6,o7,o8,o9,o10,o11,o12,o13,o14,o15,o16,o17,o18,o19,o20,o21,o22,o23}, {qa12,qa13,qa14,qa15}, dt, pt, 1, 1, 1;\n"
        "wgmma.commit_group.sync.aligned;\n"
        "wgmma.wait_group.sync.aligned 1;\n"
        "@pz bra.uni R3;\n"
        "mov.u32 ad, %tid.x; and.b32 ad, ad, 127; mad.wide.u32 gq, ad, 16, %15;\n"
        "ld.volatile.global.v4.b32 {qa8,qa9,qa10,qa11}, [gq+16384];\n"
        "R3:\n"
        "wgmma.fence.sync.aligned;\n"
        "add.s64 dt, w2d, 256; wgmma.mma_async.sync.aligned.m64n96k16.f16.f16.f16 {o0,o1,o2,o3,o4,o5,o6,o7,o8,o9,o10,o11,o12,o13,o14,o15,o16,o17,o18,o19,o20,o21,o22,o23}, {qa16,qa17,qa18,qa19}, dt, pt, 1, 1, 1;\n"
        "wgmma.commit_group.sync.aligned;\n"
        "wgmma.wait_group.sync.aligned 1;\n"
        "@pz bra.uni R4;\n"
        "mov.u32 ad, %tid.x; and.b32 ad, ad, 127; mad.wide.u32 gq, ad, 16, %15;\n"
        "ld.volatile.global.v4.b32 {qa12,qa13,qa14,qa15}, [gq+18432];\n"
        "R4:\n"
        "wgmma.fence.sync.aligned;\n"
        "add.s64 dt, w2d, 320; wgmma.mma_async.sync.aligned.m64n96k16.f16.f16.f16 {o0,o1,o2,o3,o4,o5,o6,o7,o8,o9,o10,o11,o12,o13,o14,o15,o16,o17,o18,o19,o20,o21,o22,o23}, {qa20,qa21,qa22,qa23}, dt, pt, 1, 1, 1;\n"
        "wgmma.commit_group.sync.aligned;\n"
        "wgmma.wait_group.sync.aligned 1;\n"
        "@pz bra.uni R5;\n"
        "mov.u32 ad, %tid.x; and.b32 ad, ad, 127; mad.wide.u32 gq, ad, 16, %15;\n"
        "ld.volatile.global.v4.b32 {qa16,qa17,qa18,qa19}, [gq+20480];\n"
        "R5:\n"
        "@pn mbarrier.arrive.shared::cta.b64 _, [tbar+64];\n"
        "wgmma.fence.sync.aligned;\n"
        "add.s64 dt, w2d, 384; wgmma.mma_async.sync.aligned.m64n96k16.f16.f16.f16 {o0,o1,o2,o3,o4,o5,o6,o7,o8,o9,o10,o11,o12,o13,o14,o15,o16,o17,o18,o19,o20,o21,o22,o23}, {qa0,qa1,qa2,qa3}, dt, pt, 1, 1, 1;\n"
        "wgmma.commit_group.sync.aligned;\n"
        "wgmma.wait_group.sync.aligned 1;\n"
        "@pz bra.uni R6;\n"
        "mov.u32 ad, %tid.x; and.b32 ad, ad, 127; mad.wide.u32 gq, ad, 16, %15;\n"
        "ld.volatile.global.v4.b32 {qa20,qa21,qa22,qa23}, [gq+22528];\n"
        "R6:\n"
        "wgmma.fence.sync.aligned;\n"
        "add.s64 dt, w2d, 448; wgmma.mma_async.sync.aligned.m64n96k16.f16.f16.f16 {o0,o1,o2,o3,o4,o5,o6,o7,o8,o9,o10,o11,o12,o13,o14,o15,o16,o17,o18,o19,o20,o21,o22,o23}, {qa4,qa5,qa6,qa7}, dt, pt, 1, 1, 1;\n"
        "wgmma.commit_group.sync.aligned;\n"
        "wgmma.wait_group.sync.aligned 1;\n"
        "@pz bra.uni R7;\n"
        "mov.u32 ad, %tid.x; and.b32 ad, ad, 127; mad.wide.u32 gq, ad, 16, %15;\n"
        "ld.volatile.global.v4.b32 {qa0,qa1,qa2,qa3}, [gq+24576];\n"
        "R7:\n"
        "mov.u32 tt, 231216; mbarrier.try_wait.parity.shared::cta.b64 pw, [tt], 0;\n"
        "@!pw bra.uni SPINF1;\n"
        "BACKF1:\n"
        "wgmma.fence.sync.aligned;\n"
        "add.s64 dt, w2d, 512; wgmma.mma_async.sync.aligned.m64n96k16.f16.f16.f16 {o0,o1,o2,o3,o4,o5,o6,o7,o8,o9,o10,o11,o12,o13,o14,o15,o16,o17,o18,o19,o20,o21,o22,o23}, {qa8,qa9,qa10,qa11}, dt, pt, 1, 1, 1;\n"
        "wgmma.commit_group.sync.aligned;\n"
        "wgmma.wait_group.sync.aligned 1;\n"
        "@pz bra.uni R8;\n"
        "mov.u32 ad, %tid.x; and.b32 ad, ad, 127; mad.wide.u32 gq, ad, 16, %15;\n"
        "ld.volatile.global.v4.b32 {qa4,qa5,qa6,qa7}, [gq+26624];\n"
        "R8:\n"
        "wgmma.fence.sync.aligned;\n"
        "add.s64 dt, w2d, 576; wgmma.mma_async.sync.aligned.m64n96k16.f16.f16.f16 {o0,o1,o2,o3,o4,o5,o6,o7,o8,o9,o10,o11,o12,o13,o14,o15,o16,o17,o18,o19,o20,o21,o22,o23}, {qa12,qa13,qa14,qa15}, dt, pt, 1, 1, 1;\n"
        "wgmma.commit_group.sync.aligned;\n"
        "wgmma.wait_group.sync.aligned 1;\n"
        "@pz bra.uni R9;\n"
        "mov.u32 ad, %tid.x; and.b32 ad, ad, 127; mad.wide.u32 gq, ad, 16, %15;\n"
        "ld.volatile.global.v4.b32 {qa8,qa9,qa10,qa11}, [gq+28672];\n"
        "R9:\n"
        "wgmma.fence.sync.aligned;\n"
        "add.s64 dt, w2d, 640; wgmma.mma_async.sync.aligned.m64n96k16.f16.f16.f16 {o0,o1,o2,o3,o4,o5,o6,o7,o8,o9,o10,o11,o12,o13,o14,o15,o16,o17,o18,o19,o20,o21,o22,o23}, {qa16,qa17,qa18,qa19}, dt, pt, 1, 1, 1;\n"
        "wgmma.commit_group.sync.aligned;\n"
        "wgmma.wait_group.sync.aligned 1;\n"
        "@pz bra.uni R10;\n"
        "mov.u32 ad, %tid.x; and.b32 ad, ad, 127; mad.wide.u32 gq, ad, 16, %15;\n"
        "ld.volatile.global.v4.b32 {qa12,qa13,qa14,qa15}, [gq+30720];\n"
        "R10:\n"
        "wgmma.fence.sync.aligned;\n"
        "add.s64 dt, w2d, 704; wgmma.mma_async.sync.aligned.m64n96k16.f16.f16.f16 {o0,o1,o2,o3,o4,o5,o6,o7,o8,o9,o10,o11,o12,o13,o14,o15,o16,o17,o18,o19,o20,o21,o22,o23}, {qa20,qa21,qa22,qa23}, dt, pt, 1, 1, 1;\n"
        "wgmma.commit_group.sync.aligned;\n"
        "wgmma.fence.sync.aligned;\n"
        "add.s64 dt, w2d, 768; wgmma.mma_async.sync.aligned.m64n96k16.f16.f16.f16 {o0,o1,o2,o3,o4,o5,o6,o7,o8,o9,o10,o11,o12,o13,o14,o15,o16,o17,o18,o19,o20,o21,o22,o23}, {qa0,qa1,qa2,qa3}, dt, pt, 1, 1, 1;\n"
        "wgmma.commit_group.sync.aligned;\n"
        "wgmma.fence.sync.aligned;\n"
        "add.s64 dt, w2d, 832; wgmma.mma_async.sync.aligned.m64n96k16.f16.f16.f16 {o0,o1,o2,o3,o4,o5,o6,o7,o8,o9,o10,o11,o12,o13,o14,o15,o16,o17,o18,o19,o20,o21,o22,o23}, {qa4,qa5,qa6,qa7}, dt, pt, 1, 1, 1;\n"
        "wgmma.commit_group.sync.aligned;\n"
        "wgmma.fence.sync.aligned;\n"
        "add.s64 dt, w2d, 896; wgmma.mma_async.sync.aligned.m64n96k16.f16.f16.f16 {o0,o1,o2,o3,o4,o5,o6,o7,o8,o9,o10,o11,o12,o13,o14,o15,o16,o17,o18,o19,o20,o21,o22,o23}, {qa8,qa9,qa10,qa11}, dt, pt, 1, 1, 1;\n"
        "wgmma.commit_group.sync.aligned;\n"
        "wgmma.fence.sync.aligned;\n"
        "add.s64 dt, w2d, 960; wgmma.mma_async.sync.aligned.m64n96k16.f16.f16.f16 {o0,o1,o2,o3,o4,o5,o6,o7,o8,o9,o10,o11,o12,o13,o14,o15,o16,o17,o18,o19,o20,o21,o22,o23}, {qa12,qa13,qa14,qa15}, dt, pt, 1, 1, 1;\n"
        "wgmma.commit_group.sync.aligned;\n"
        "bra.uni B74;\n"
        "SPINFR: mov.u32 cnt, 0;\n"
        "SPINFRL:\n"
        "mov.u32 tt, 231232; mbarrier.try_wait.parity.shared::cta.b64 pw, [tt], %13;\n"
        "@pw bra.uni BACKFR;\n"
        "add.u32 cnt, cnt, 1; setp.lt.u32 pw, cnt, 0x100000;\n"
        "@pw bra.uni SPINFRL;\n"
        "trap;\n"
        "SPINFT: mov.u32 cnt, 0;\n"
        "SPINFTL:\n"
        "mad.lo.u32 tt, n, 8, tbar; mbarrier.try_wait.parity.shared::cta.b64 pw, [tt], tpar;\n"
        "@pw bra.uni BACKFT;\n"
        "add.u32 cnt, cnt, 1; setp.lt.u32 pw, cnt, 0x100000;\n"
        "@pw bra.uni SPINFTL;\n"
        "trap;\n"
        "SPINF0: mov.u32 cnt, 0;\n"
        "SPINF0L:\n"
        "mov.u32 tt, 231208; mbarrier.try_wait.parity.shared::cta.b64 pw, [tt], 0;\n"
        "@pw bra.uni BACKF0;\n"
        "add.u32 cnt, cnt, 1; setp.lt.u32 pw, cnt, 0x100000;\n"
        "@pw bra.uni SPINF0L;\n"
        "trap;\n"
        "SPINF1: mov.u32 cnt, 0;\n"
        "SPINF1L:\n"
        "mov.u32 tt, 231216; mbarrier.try_wait.parity.shared::cta.b64 pw, [tt], 0;\n"
        "@pw bra.uni BACKF1;\n"
        "add.u32 cnt, cnt, 1; setp.lt.u32 pw, cnt, 0x100000;\n"
        "@pw bra.uni SPINF1L;\n"
        "trap;\n"
        "SPINL: mov.u32 cnt, 0;\n"
        "SPINLL:\n"
        "and.b32 tt, n, 1; mbarrier.try_wait.parity.shared::cta.b64 pw, [xbar], tt;\n"
        "@pw bra.uni BACKL;\n"
        "add.u32 cnt, cnt, 1; setp.lt.u32 pw, cnt, 0x100000;\n"
        "@pw bra.uni SPINLL;\n"
        "trap;\n"
        "LAST:\n"
        "and.b32 tt, n, 1; mbarrier.try_wait.parity.shared::cta.b64 pw, [xbar], tt;\n"
        "@!pw bra.uni SPINL;\n"
        "BACKL:\n"
        "and.b32 ad, %7, 0xffff; add.u32 ad, ad, %5; ld.shared.v4.b32 {r0,r1,r2,r3}, [ad+0];\n"
        "shr.u32 ad, %7, 16; add.u32 ad, ad, %5; ld.shared.v4.b32 {r4,r5,r6,r7}, [ad+0];\n"
        "and.b32 ad, %7, 0xffff; add.u32 ad, ad, %5; ld.shared.v4.b32 {r8,r9,r10,r11}, [ad+64];\n"
        "shr.u32 ad, %7, 16; add.u32 ad, ad, %5; ld.shared.v4.b32 {r12,r13,r14,r15}, [ad+64];\n"
        "and.b32 ad, %7, 0xffff; add.u32 ad, ad, %5; ld.shared.v4.b32 {r16,r17,r18,r19}, [ad+128];\n"
        "shr.u32 ad, %7, 16; add.u32 ad, ad, %5; ld.shared.v4.b32 {r20,r21,r22,r23}, [ad+128];\n"
        "wgmma.wait_group.sync.aligned 0;\n"
        "mov.b32 {xl, xh}, o0; cvt.f32.f16 f0, xl; cvt.f32.f16 f1, xh; cvt.rn.bf16x2.f32 tt, f1, f0; fma.rn.bf16x2 r0, tt, osc, r0;\n"
        "mov.b32 {xl, xh}, o2; cvt.f32.f16 f0, xl; cvt.f32.f16 f1, xh; cvt.rn.bf16x2.f32 tt, f1, f0; fma.rn.bf16x2 r1, tt, osc, r1;\n"
        "mov.b32 {xl, xh}, o4; cvt.f32.f16 f0, xl; cvt.f32.f16 f1, xh; cvt.rn.bf16x2.f32 tt, f1, f0; fma.rn.bf16x2 r2, tt, osc, r2;\n"
        "mov.b32 {xl, xh}, o6; cvt.f32.f16 f0, xl; cvt.f32.f16 f1, xh; cvt.rn.bf16x2.f32 tt, f1, f0; fma.rn.bf16x2 r3, tt, osc, r3;\n"
        "and.b32 ad, %7, 0xffff; add.u32 ad, ad, off; cvt.u64.u32 gp, ad; add.s64 gp, gp, %12; st.global.v4.b32 [gp+0], {r0,r1,r2,r3};\n"
        "mov.b32 {xl, xh}, o1; cvt.f32.f16 f0, xl; cvt.f32.f16 f1, xh; cvt.rn.bf16x2.f32 tt, f1, f0; fma.rn.bf16x2 r4, tt, osc, r4;\n"
        "mov.b32 {xl, xh}, o3; cvt.f32.f16 f0, xl; cvt.f32.f16 f1, xh; cvt.rn.bf16x2.f32 tt, f1, f0; fma.rn.bf16x2 r5, tt, osc, r5;\n"
        "mov.b32 {xl, xh}, o5; cvt.f32.f16 f0, xl; cvt.f32.f16 f1, xh; cvt.rn.bf16x2.f32 tt, f1, f0; fma.rn.bf16x2 r6, tt, osc, r6;\n"
        "mov.b32 {xl, xh}, o7; cvt.f32.f16 f0, xl; cvt.f32.f16 f1, xh; cvt.rn.bf16x2.f32 tt, f1, f0; fma.rn.bf16x2 r7, tt, osc, r7;\n"
        "shr.u32 ad, %7, 16; add.u32 ad, ad, off; cvt.u64.u32 gp, ad; add.s64 gp, gp, %12; st.global.v4.b32 [gp+0], {r4,r5,r6,r7};\n"
        "mov.b32 {xl, xh}, o8; cvt.f32.f16 f0, xl; cvt.f32.f16 f1, xh; cvt.rn.bf16x2.f32 tt, f1, f0; fma.rn.bf16x2 r8, tt, osc, r8;\n"
        "mov.b32 {xl, xh}, o10; cvt.f32.f16 f0, xl; cvt.f32.f16 f1, xh; cvt.rn.bf16x2.f32 tt, f1, f0; fma.rn.bf16x2 r9, tt, osc, r9;\n"
        "mov.b32 {xl, xh}, o12; cvt.f32.f16 f0, xl; cvt.f32.f16 f1, xh; cvt.rn.bf16x2.f32 tt, f1, f0; fma.rn.bf16x2 r10, tt, osc, r10;\n"
        "mov.b32 {xl, xh}, o14; cvt.f32.f16 f0, xl; cvt.f32.f16 f1, xh; cvt.rn.bf16x2.f32 tt, f1, f0; fma.rn.bf16x2 r11, tt, osc, r11;\n"
        "and.b32 ad, %7, 0xffff; add.u32 ad, ad, off; cvt.u64.u32 gp, ad; add.s64 gp, gp, %12; st.global.v4.b32 [gp+64], {r8,r9,r10,r11};\n"
        "mov.b32 {xl, xh}, o9; cvt.f32.f16 f0, xl; cvt.f32.f16 f1, xh; cvt.rn.bf16x2.f32 tt, f1, f0; fma.rn.bf16x2 r12, tt, osc, r12;\n"
        "mov.b32 {xl, xh}, o11; cvt.f32.f16 f0, xl; cvt.f32.f16 f1, xh; cvt.rn.bf16x2.f32 tt, f1, f0; fma.rn.bf16x2 r13, tt, osc, r13;\n"
        "mov.b32 {xl, xh}, o13; cvt.f32.f16 f0, xl; cvt.f32.f16 f1, xh; cvt.rn.bf16x2.f32 tt, f1, f0; fma.rn.bf16x2 r14, tt, osc, r14;\n"
        "mov.b32 {xl, xh}, o15; cvt.f32.f16 f0, xl; cvt.f32.f16 f1, xh; cvt.rn.bf16x2.f32 tt, f1, f0; fma.rn.bf16x2 r15, tt, osc, r15;\n"
        "shr.u32 ad, %7, 16; add.u32 ad, ad, off; cvt.u64.u32 gp, ad; add.s64 gp, gp, %12; st.global.v4.b32 [gp+64], {r12,r13,r14,r15};\n"
        "mov.b32 {xl, xh}, o16; cvt.f32.f16 f0, xl; cvt.f32.f16 f1, xh; cvt.rn.bf16x2.f32 tt, f1, f0; fma.rn.bf16x2 r16, tt, osc, r16;\n"
        "mov.b32 {xl, xh}, o18; cvt.f32.f16 f0, xl; cvt.f32.f16 f1, xh; cvt.rn.bf16x2.f32 tt, f1, f0; fma.rn.bf16x2 r17, tt, osc, r17;\n"
        "mov.b32 {xl, xh}, o20; cvt.f32.f16 f0, xl; cvt.f32.f16 f1, xh; cvt.rn.bf16x2.f32 tt, f1, f0; fma.rn.bf16x2 r18, tt, osc, r18;\n"
        "mov.b32 {xl, xh}, o22; cvt.f32.f16 f0, xl; cvt.f32.f16 f1, xh; cvt.rn.bf16x2.f32 tt, f1, f0; fma.rn.bf16x2 r19, tt, osc, r19;\n"
        "and.b32 ad, %7, 0xffff; add.u32 ad, ad, off; cvt.u64.u32 gp, ad; add.s64 gp, gp, %12; st.global.v4.b32 [gp+128], {r16,r17,r18,r19};\n"
        "mov.b32 {xl, xh}, o17; cvt.f32.f16 f0, xl; cvt.f32.f16 f1, xh; cvt.rn.bf16x2.f32 tt, f1, f0; fma.rn.bf16x2 r20, tt, osc, r20;\n"
        "mov.b32 {xl, xh}, o19; cvt.f32.f16 f0, xl; cvt.f32.f16 f1, xh; cvt.rn.bf16x2.f32 tt, f1, f0; fma.rn.bf16x2 r21, tt, osc, r21;\n"
        "mov.b32 {xl, xh}, o21; cvt.f32.f16 f0, xl; cvt.f32.f16 f1, xh; cvt.rn.bf16x2.f32 tt, f1, f0; fma.rn.bf16x2 r22, tt, osc, r22;\n"
        "mov.b32 {xl, xh}, o23; cvt.f32.f16 f0, xl; cvt.f32.f16 f1, xh; cvt.rn.bf16x2.f32 tt, f1, f0; fma.rn.bf16x2 r23, tt, osc, r23;\n"
        "shr.u32 ad, %7, 16; add.u32 ad, ad, off; cvt.u64.u32 gp, ad; add.s64 gp, gp, %12; st.global.v4.b32 [gp+128], {r20,r21,r22,r23};\n"
        ASM_MARK
        "mov.u32 %0, 0;\n"
        "OUT:\n"
        "}\n"
        : "=r"(retry)
        : "r"(prm.helper_desc[0]), "r"(prm.helper_desc[1]), "r"(c.wg), "r"(c.off), "r"(c.xs), "r"(c.a_offs), "r"(c.xs_offs), "r"(c.bias_addr),
          "r"(c.step), "r"(c.w), "l"(prm.x), "l"(prm.out), "r"(round), "r"(c.last), "l"(c.park)
        : "memory");
    return retry;
}

__device__ __forceinline__ float warp_sum(float v) {
#pragma unroll
    for (int s = 16; s >= 1; s >>= 1) v += __shfl_xor_sync(0xffffffffu, v, s);
    return v;
}
__device__ __forceinline__ float pow2f(int e) { return __uint_as_float((uint32_t)(e + 127) << 23); }
__device__ __forceinline__ int exponent_of(float v) { return (int)(__float_as_uint(v) >> 23) - 127; }
__device__ __forceinline__ float lds_bf16(uint32_t addr) {
    uint16_t v; asm volatile("ld.shared.u16 %0, [%1];" : "=h"(v) : "r"(addr) : "memory"); return bf_lo(v);
}

__device__ __forceinline__ void publish_bias(const Params& prm, uint32_t c, uint32_t tag) {
    const uint32_t lane = fresh_tid() & 31;
    const uint32_t col = sb + SM_W2 + (c >> 5) * 24576 + lane * 64 + ((((c >> 3) ^ (lane >> 1)) & 3) * 16) + (c & 7) * 2;
    float v = 0.0f;
#pragma unroll
    for (int k = 0; k < EX / 32; k++) v = fmaf(lds_bf16(col + k * 2048), lds_bf16(sb + SM_BETA + lane * 2 + k * 64), v);
    v = warp_sum(v);
    if (lane == 0)
        asm volatile("st.relaxed.gpu.global.u64 [%0], %1;" ::"l"(prm.g->bias + c), "l"((uint64_t)tag << 32 | __float_as_uint(v)) : "memory");
}
__device__ __forceinline__ void collect_bias(const Params& prm, uint32_t tag) {
    const uint32_t lane = fresh_tid() & 31;
    if (lane < 24) {
        const unsigned long long* src = prm.g->bias + 32 * (lane >> 3) + 8 * (lane & 3) + (lane & 4);
        uint32_t v[4], t[4], spins = 0;
        for (;;) {
#pragma unroll
            for (int k = 0; k < 4; k++)
                asm volatile("{\n.reg .b64 w;\nld.relaxed.gpu.global.u64 w, [%2];\nmov.b64 {%0, %1}, w;\n}\n"
                             : "=r"(v[k]), "=r"(t[k]) : "l"(src + k) : "memory");
            if (t[0] == tag && t[1] == tag && t[2] == tag && t[3] == tag) break;
            if (++spins > (1u << 22)) __trap();
        }
        sts128(sb + SM_BIAS + lane * 16, v[0], v[1], v[2], v[3]);
    }
    __syncwarp();
}
__device__ __forceinline__ float fetch_w2_row(uint32_t (&u)[12][4], uint32_t row, uint32_t sw) {
    uint32_t mx[4] = {};
#pragma unroll
    for (int a = 0; a < 3; a++)
#pragma unroll
        for (int k = 0; k < 4; k++) {
            asm volatile("ld.shared.v4.b32 {%0,%1,%2,%3}, [%4];"
                         : "=r"(u[a * 4][k]), "=r"(u[a * 4 + 1][k]), "=r"(u[a * 4 + 2][k]), "=r"(u[a * 4 + 3][k])
                         : "r"(row + a * 24576 + ((k * 16) ^ sw)) : "memory");
#pragma unroll
            for (int b = 0; b < 4; b++) asm("max.xorsign.abs.bf16x2 %0, %0, %1;" : "+r"(mx[b]) : "r"(u[a * 4 + b][k]));
        }
#pragma unroll
    for (int b = 1; b < 4; b++) asm("max.xorsign.abs.bf16x2 %0, %0, %1;" : "+r"(mx[0]) : "r"(mx[b]));
    return fmaxf(fabsf(bf_lo(mx[0])), fabsf(bf_hi(mx[0])));
}

template <bool FAST> __device__ __forceinline__ bool grn_stats(const float (&ss)[3], const float (&gm)[3], const float (&bt)[3],
                                                               const float (&top)[3], int e, float (&gx)[3], float& inv, int& eo) {
    float b0 = 0.0f, b1 = 0.0f;
    bool bad = false;
#pragma unroll
    for (int k = 0; k < 3; k++) {
        gx[k] = sqrt_fast(fmaf(ss[k], INV_2A * INV_2A, 1e-6f));
        const float rt = sqrt_fast(ss[k] + 1.0f) * INV_2A * top[k];
        b0 += fmaf(bt[k], top[k], rt);
        b1 += rt * fabsf(gm[k]) * gx[k];
        bad |= !(ss[k] >= 16.0f && ss[k] < ACC_LIMIT);
    }
    const float sum = gx[0] + gx[1] + gx[2];
    uint32_t r[4] = {FAST ? __reduce_add_sync(0xffffffffu, __float2uint_rn(sum * 128.0f)) : __float_as_uint(warp_sum(sum)),
                     __reduce_max_sync(0xffffffffu, __float_as_uint(b0)), __reduce_max_sync(0xffffffffu, __float_as_uint(b1)),
                     (uint32_t)__any_sync(0xffffffffu, bad)};
    if ((e & 31) == 0) sts128(sb + SM_SEL + (e >> 5) * 16, r[0], r[1], r[2], r[3]);
    MARK(6);
    named_sync(10, 128);
    lds128(r, sb + SM_SEL + (e & 3) * 16);
    if ((e & 31) >= 4) r[0] = 0;
    const float tot = FAST ? __uint2float_rn(__reduce_add_sync(0xffffffffu, r[0])) * (1.0f / 128) : warp_sum(__uint_as_float(r[0]));
    inv = __fdividef(1.0f, fmaf(tot, 1.0f / EX, 1e-6f));
    const float bound = fmaf(__uint_as_float(__reduce_max_sync(0xffffffffu, r[2])), inv,
                             __uint_as_float(__reduce_max_sync(0xffffffffu, r[1]))) * (EX / 3);
    eo = min(max(exponent_of(bound), -90), 126) - 14;
    return __any_sync(0xffffffffu, r[3]);
}

__device__ __forceinline__ const float* exact_sums(const Params& prm) {
    const int lane = fresh_tid() & 31, warp = fresh_warp(), wg = warp >> 2;
    const uint32_t epoch = lds32(sb + SM_RED + (RED_EPOCH + 1) * 4), bar = sb + SM_BAR + BAR_W1 * 8;
    if (wg < 3 && fresh_cta() < NUM_CTAS) {
        uint32_t wa[2][24], d[2][16];
        float acc[2][2] = {};
        const uint32_t yd = prm.ydesc + ((SM_SPARE - SM_Y1) >> 4), wd = prm.w1desc + ((2 * wg * 12288 + 5 * 2048) >> 4);
        load_w1t(wa, wg, warp & 3, lane);
#pragma unroll 1
        for (int n = 0; n < ROWS_PER_CTA; n++) {
            if (warp == 0) {
                expect_tx(bar, TILE_BYTES);
                bulk_load(sb + SM_SPARE, (const char*)prm.out + (cta_tile0(fresh_cta()) + n * cta_stride(fresh_cta())), TILE_BYTES, bar);
            }
            mbar_wait(bar, (n + 1) & 1);
            gemm1_t<0>(d[0], wa[0], yd, wd);
            gemm1_t<1>(d[1], wa[1], yd, wd);
            wg_wait<0>();
            pin(d[0]); pin(d[1]);
            gelu_sumsq_f(d[0], acc[0]);
            gelu_sumsq_f(d[1], acc[1]);
            named_sync(1, 384);
        }
        publish_sums(acc, prm.g->sums[epoch & 1], &prm.g->count[1], wg, warp & 3, lane);
    }
    grid_wait(&prm.g->count[1], (epoch + 1) * NUM_CTAS);
    return prm.g->sums[epoch & 1];
}

__device__ __forceinline__ void scale_w2_row(uint32_t (&u)[12][4], uint32_t row, uint32_t sw, float sc, int eo, uint32_t bar) {
    const float dn = pow2f(-eo);
    if (eo > 6) {
        const uint32_t dn2 = pack_bf2(dn, dn);
#pragma unroll
        for (int k = 0; k < 48; k++) u[k >> 2][k & 3] = bf2_mul(u[k >> 2][k & 3], dn2);
    } else {
        sc *= dn;
    }
    const uint32_t s2 = pack_bf2(sc * 0x1p-112f, sc * 0x1p-112f);
#pragma unroll
    for (int k = 0; k < 12; k++) {
        uint32_t v[4];
#pragma unroll
        for (int b = 0; b < 4; b++) {
            v[b] = bf2_mul(u[k][b], s2);
            v[b] += (v[b] & 0x7fff7fffu) * 7u;
        }
        sts128(row + (k >> 2) * 24576 + (((k & 3) * 16) ^ sw), v[0], v[1], v[2], v[3]);
    }
    fence_async_smem();
    __syncwarp();
    mbar_arrive_if(bar, (fresh_tid() & 31) == 0);
}
template <bool FIRST> __device__ __forceinline__ void prepare_w2(const Params& prm, const float* exact) {
    const int e = fresh_tid() - EX, lane = e & 31, warp = fresh_warp();
    const uint32_t row = sb + SM_W2 + e * 64, sw = ((e >> 1) & 3) * 16;
    uint32_t u[2][12][4];
    float top[3], gm[3], bt[3], ss[3], gx[3], inv;
    mbar_wait_c<0>(sb + SM_BAR + BAR_W2 * 8);
    top[2] = fetch_w2_row(u[0], row + 16384, sw);
    top[0] = fetch_w2_row(u[0], row, sw);
    top[1] = fetch_w2_row(u[1], row + 8192, sw);
#pragma unroll
    for (int k = 0; k < 3; k++) {
        gm[k] = lds_bf16(sb + SM_GAMMA + e * 2 + k * 256);
        bt[k] = fabsf(lds_bf16(sb + SM_BETA + e * 2 + k * 256));
    }
    MARK(3);
    if (FIRST) {
        const uint32_t epoch = lds32(sb + SM_RED + RED_EPOCH * 4);
        named_sync(11, 512);
        if (warp == 12) collect_bias(prm, epoch + 1);
        MARK(4);
        collect_fast(acc_word(prm, epoch, e), prm.ctas, ss);
        if (e == 32 && fresh_cta() == 0) prm.g->count[0] = epoch + 1;
    } else {
#pragma unroll
        for (int k = 0; k < 3; k++) ss[k] = __ldcg(exact + e + 128 * k);
    }
    MARK(5);
    int eo;
    const bool redo = (grn_stats<FIRST>(ss, gm, bt, top, e, gx, inv, eo) || FORCE_EXACT) && FIRST;
    MARK(8);
    if (warp == 12) {
        const float up = pow2f(eo), dn = pow2f(-eo);
        if (lane == 24) sts64(sb + SM_RED + RED_SCALE * 4, pack_bf2(up, up), redo);
        if (lane < 24 && !redo) {
            uint32_t b[4];
            lds128(b, sb + SM_BIAS + lane * 16);
            const uint32_t p0 = pack_h2(__uint_as_float(b[0]) * dn, __uint_as_float(b[1]) * dn);
            const uint32_t p1 = pack_h2(__uint_as_float(b[2]) * dn, __uint_as_float(b[3]) * dn);
            sts128(sb + SM_BIAS + lane * 16, p0, p0, p1, p1);
        }
        __syncwarp();
        mbar_arrive_if(sb + SM_BAR + BAR_STAT * 8, lane == 0);
    }
    if (redo) return;
#pragma unroll
    for (int k = 0; k < 3; k++) gx[k] = fmaf(gm[k], gx[k] * inv, 1.0f) * INV_2A;
    scale_w2_row(u[0], row, sw, gx[0], eo, sb + SM_BAR + BAR_ROWS * 8);
    MARK(7);
    fetch_w2_row(u[0], row + 16384, sw);
    scale_w2_row(u[1], row + 8192, sw, gx[1], eo, sb + SM_BAR + (BAR_ROWS + 1) * 8);
    scale_w2_row(u[0], row + 16384, sw, gx[2], eo, sb + SM_BAR + (BAR_ROWS + 2) * 8);
    MARK(9);
    TS(4); TS(5);
}

__device__ __forceinline__ uint32_t helper_source(uint32_t h, uint32_t wg) { return 8 * (wg & 1) + 2 * h + (wg >> 1); }
__device__ __forceinline__ Pass2 pass2_setup(const Params& prm) {
    const int warp = fresh_warp(), wg = warp >> 2, w = warp & 3, lane = fresh_tid() & 31, arow = 16 * w + (lane & 15);
    Pass2 c;
    c.wg = wg;
    c.w = w;
    const uint32_t cta = fresh_cta();
    const bool helper = cta >= NUM_CTAS;
    c.off = helper ? cta_tile0(helper_source(cta - NUM_CTAS, wg)) : cta_tile0(cta) + (ROWS_PER_CTA - 1 - wg) * cta_stride(cta);
    c.step = helper ? -2 * ROWS_PER_CTA * ROW_BYTES : 4 * cta_stride(cta);
    c.last = wg == 3 && !helper && prm.ctas > NUM_CTAS ? 6 : 7;
    c.park = helper && wg < 3 ? prm.g->park[cta - NUM_CTAS][wg] : nullptr;
    c.xs = wg == 3 ? sb + SM_BUF3 : sb + SM_Y1 + (wg == 2 ? 2 : 1 - wg) * SLOT_BYTES;
    static_assert((ROWS_PER_CTA - 1) % NX == 1, "slot of the last tile");
    c.a_offs = (arow * 128 + (((lane >> 4) ^ (arow & 7)) * 16)) |
               (8192 + arow * 64 + (((lane >> 4) ^ ((arow >> 1) & 3)) * 16)) << 16;
    const int g = lane >> 2, px = 33 * (g & 1) + 4 * (g >> 1) + 16 * (w >> 1) + 2 * (w & 1);
    c.xs_offs = (px * 192 + (lane & 3) * 16) | ((px ^ 1) * 192 + (lane & 3) * 16) << 16;
    c.bias_addr = sb + SM_BIAS + (lane & 3) * 16;
    return c;
}

__device__ __forceinline__ void helper_start(const Params& prm) {
    const uint32_t tid = fresh_tid(), warp = fresh_warp(), lane = tid & 31;
    uint32_t cnt[2];
    asm volatile("ld.relaxed.gpu.global.v2.u32 {%0, %1}, [%2];" : "=r"(cnt[0]), "=r"(cnt[1]) : "l"(prm.g->count) : "memory");
    if (tid == 0) {
        sts64(sb + SM_RED + RED_EPOCH * 4, cnt[0], cnt[1] / NUM_CTAS);
#pragma unroll 1
        for (int k = 0; k < BAR_DW; k++) mbar_init(sb + SM_BAR + k * 8, k < BAR_TURN || k == BAR_STAT ? 1 : 4);
        fence_async_smem();
    }
    __syncthreads();
    if (tid < EX) asm volatile("red.relaxed.gpu.global.add.u64 [%0], 1;" ::"l"(acc_word(prm, cnt[0], tid)) : "memory");
    if (warp == 0) {
        expect_tx(sb + SM_BAR + BAR_W1 * 8, CH * EX * 2);
        expect_tx(sb + SM_BAR + BAR_W2 * 8, CH * EX * 2 + EX * 4);
#pragma unroll 1
        for (int q = loop_init<0>(); q < 6; q++) {
            tma_load_2d(sb + SM_W1 + q * 12288, &prm.w1_map, 64 * q, 0, sb + SM_BAR + BAR_W1 * 8);
            tma_load_2d(sb + SM_W2 + q * 12288, &prm.w2_map, 32 * (q >> 1), 192 * (q & 1), sb + SM_BAR + BAR_W2 * 8);
        }
        bulk_load(sb + SM_GAMMA, prm.gamma, EX * 2, sb + SM_BAR + BAR_W2 * 8);
        bulk_load(sb + SM_BETA, prm.beta, EX * 2, sb + SM_BAR + BAR_W2 * 8);
    }
    mbar_wait_c<0>(sb + SM_BAR + BAR_W1 * 8);
#pragma unroll 1
    for (uint32_t a = sb + SM_W1 + tid * 16; a < sb + SM_W2; a += 8192) {
        uint32_t v[4];
        lds128(v, a);
        sts128(a, pack_h2(bf_lo(v[0]), bf_hi(v[0])), pack_h2(bf_lo(v[1]), bf_hi(v[1])), pack_h2(bf_lo(v[2]), bf_hi(v[2])),
               pack_h2(bf_lo(v[3]), bf_hi(v[3])));
    }
    if (warp == 1) {
        const unsigned int* flag = prm.g->parked + helper_source(fresh_cta() - NUM_CTAS, lane & 3) + 16 * (lane >> 2);
        uint32_t v, spins = 0;
        do {
            __nanosleep(500);
            asm volatile("ld.acquire.gpu.global.u32 %0, [%1];" : "=r"(v) : "l"(flag) : "memory");
            if (++spins > (1u << 20)) __trap();
        } while (v != cnt[0] + 1);
    }
    asm volatile("fence.proxy.async;" ::: "memory");
    __syncthreads();
    asm volatile("fence.proxy.async;" ::: "memory");
    const Pass2 c = pass2_setup(prm);
    if (c.w == 0) {
        expect_tx(sb + SM_BAR + (BAR_Y2FULL + c.wg) * 8, TILE_BYTES);
        bulk_load(c.xs, (const char*)prm.out + c.off, TILE_BYTES, sb + SM_BAR + (BAR_Y2FULL + c.wg) * 8);
    }
    if (warp < 12) {
        asm volatile("bar.arrive 11, 512;" ::: "memory");
    } else {
        unsigned long long v;
        uint32_t spins = 0;
        do {
            __nanosleep(200);
            asm volatile("ld.relaxed.gpu.global.u64 %0, [%1];" : "=l"(v) : "l"(acc_word(prm, cnt[0], EX - 1)) : "memory");
            if (++spins > (1u << 20)) __trap();
        } while ((v & 255) <= HELPERS);
        __syncwarp();
    }
}

__global__ void __launch_bounds__(512, 1) convnext_kernel(const __grid_constant__ Params prm) {
    extern __shared__ __align__(1024) uint8_t smem[];
    if ((uint32_t)__cvta_generic_to_shared(smem) != sb) __trap();
    if (fresh_cta() < NUM_CTAS) {
        const uint32_t tid = fresh_tid(), warp = fresh_warp(), lane = tid & 31;
        if (warp == 0) {
            if (lane == 0) {
#pragma unroll
                for (int k = 0; k < NX; k++) mbar_init(sb + SM_GO + k * 8, 2);
                mbar_init(sb + SM_BAR + BAR_DW * 8, 1);
                mbar_init(sb + SM_BAR + BAR_W1 * 8, 1);
                mbar_init(sb + SM_BAR + BAR_W1B * 8, 1);
                fence_async_smem();
            }
            __syncwarp();
            expect_tx(sb + SM_BAR + BAR_DW * 8, 9 * CH * 2);
            bulk_load(sb + SM_Y1, prm.dw, 9 * CH * 2, sb + SM_BAR + BAR_DW * 8);
            const RowCopy rc = row_copy(prm);
#pragma unroll
            for (int k = 0; k < NX; k++) issue_row_load(rc, k, k);
            SMARK(4);
        }
        if (fresh_warp() == 15) {
            const uint32_t cta = fresh_cta();
            bulk_prefetch((const char*)prm.w1 + cta * (CH * EX * 2 / NUM_CTAS), CH * EX * 2 / NUM_CTAS);
            bulk_prefetch(prm.dw, 9 * CH * 2);
            bulk_prefetch((const char*)prm.x + (cta_tile0(cta) - cta_stride(cta)), TILE_BYTES);
        } else if (warp == 2) {
            if (lane < 2) asm volatile("prefetch.tensormap [%0];" ::"l"(&prm.w1_map + lane) : "memory");
        } else if (warp - 6u < 6) {
            if (lane == 0) {
#pragma unroll 1
                for (int k = NX + warp - 6; k < GO_COUNT + ROWS_PER_CTA + 2; k += 6)
                    mbar_init(sb + SM_GO + k * 8, k < 2 * NX ? 2 : k < GO_COUNT ? 14 : 4);
                fence_async_smem();
            }
        } else if (warp == 3) {
            const uint32_t one = (lane & 5) == ((lane & 8) >> 1) + (lane >> 4) ? 0x3f803f80u : 0u;
            sts128(sb + SM_SEL + lane * 16, one, one, one, one);
            fence_async_smem();
        } else if (tid - 128u < NX * 12 && ((fresh_cta() + 1) & 7) < 2) {
            const int k = tid - 128;
            sts128(sb + SM_X + (k / 12) * SLOT_BYTES + ((fresh_cta() & 7) == 0 ? 0 : XHALF_B + 33 * 192) + (k % 12) * 16, 0, 0, 0, 0);
        }
        __syncwarp();
        SMARK(3);
        named_sync(0, 512);
    }
    if (fresh_cta() >= NUM_CTAS) {
        helper_start(prm);
    } else if (fresh_warp() >= 12) {
        Producer pc;
        SMARK(0);
        asm volatile("setmaxnreg.inc.sync.aligned.u32 %0;" ::"n"(PRODUCER_REGS));
        SMARK(1);
        const int w = fresh_warp() & 3, lane = fresh_tid() & 31;
        const int j = lane & 7, hb = (lane >> 3) & 1, base = 4 * (2 * w + (lane >> 4));
        pc.lane = lane;
        pc.xoff[0] = hb * XHALF_B + base * 192 + j * 16;
        pc.xoff[1] = hb * XHALF_B + base * 192 + 128 + j * 8;
        const int grp = 4 * w + (lane >> 3);
#pragma unroll
        for (int o = 0; o < 2; o++) {
            const int row = (grp & 7) + 8 * (o ^ hb) + 32 * (grp >> 3);
            pc.yoff[0][o] = row * 128 + ((j ^ (row & 7)) * 16);
            pc.yoff[1][o] = 8192 + row * 64 + (((j >> 1) ^ ((row >> 1) & 3)) * 16) + (j & 1) * 8;
        }
        pc.stat = sb + SM_STAT + (8 * w + (lane >> 2)) * 32;
        pc.own = pc.stat + (lane & 3) * 8;
        const int dstep = fresh_cta() & 8 ? 3 * CH * 2 : -3 * CH * 2;
        mbar_wait_c<0>(sb + SM_BAR + BAR_DW * 8);
        SMARK(8);
#pragma unroll
        for (int tap = 0; tap < 9; tap++) {
            const uint32_t dw = sb + SM_Y1 + (3 + tap % 3) * CH * 2 + (tap / 3 - 1) * dstep;
            lds128(pc.w[tap], dw + j * 16);
            asm volatile("ld.shared.v2.b32 {%0,%1}, [%2];" : "=r"(pc.w[tap][4]), "=r"(pc.w[tap][5]) : "r"(dw + 128 + j * 8) : "memory");
        }
#pragma unroll
        for (int tap = 0; tap < 9; tap++)
#pragma unroll
            for (int u = 0; u < 6; u++) pc.w[tap][u] = bf2_mul(pc.w[tap][u], TAP_SCALE_BF2);
        produce(pc, prm);
        TS(9);
        asm volatile("setmaxnreg.dec.sync.aligned.u32 %0;" ::"n"(EVEN_REGS));
        if (fresh_warp() == 12) {
            mbar_wait_c<0>(sb + SM_BAR + BAR_W2 * 8);
            if (fresh_cta() < CH) publish_bias(prm, fresh_cta(), lds32(sb + SM_RED + RED_EPOCH * 4) + 1);
        }
    } else {
        asm volatile("setmaxnreg.dec.sync.aligned.u32 %0;" ::"n"(CONSUMER_REGS));
        {
            const int tid = fresh_tid(), warp = fresh_warp();
            if (warp == 1) {
#pragma unroll
                for (int h = 0; h < 2; h++) {
                    const uint32_t bar = sb + SM_BAR + (h ? BAR_W1B : BAR_W1) * 8;
                    expect_tx(bar, CH * EX);
#pragma unroll
                    for (int q = h; q < 6; q += 2) tma_load_2d(sb + SM_W1 + q * 12288, &prm.w1_map, 64 * q, 0, bar);
                }
            }
            uint32_t cnt[2];
            asm volatile("ld.relaxed.gpu.global.v2.u32 {%0, %1}, [%2];" : "=r"(cnt[0]), "=r"(cnt[1]) : "l"(prm.g->count) : "memory");
            SMARK(0);
            if (warp == 2) {
                const RowCopy rc = row_copy(prm);
#pragma unroll 1
                for (int i = loop_init<0>(); i < NX - 1; i++) {
                    named_sync(6 + i, 160);
                    issue_row_load(rc, i + NX, i);
                }
            }
            if (tid == 256) {
                sts64(sb + SM_RED + RED_EPOCH * 4, cnt[0], cnt[1] / NUM_CTAS);
#pragma unroll
                for (int k = 0; k < BAR_DW; k++)
                    if (k != BAR_W1 && k != BAR_W1B) mbar_init(sb + SM_BAR + k * 8, k < BAR_TURN || k == BAR_STAT ? 1 : 4);
#pragma unroll
                for (int k = 0; k < 3; k++) mbar_arrive_if(sb + SM_BAR + (BAR_Y2FULL + k) * 8, true);
            }
            if (fresh_cta() == 0) *acc_word(prm, cnt[0] + 1, tid) = 0;
            if (fresh_cta() == 1) prm.g->sums[~(cnt[1] / NUM_CTAS) & 1][tid] = 0.0f;
            __syncwarp();
            SMARK(1);
            mbar_wait_c<0>(sb + SM_BAR + BAR_W1 * 8);
            SMARK(2);
        }

        const int tid = fresh_tid(), lane = tid & 31, wg = fresh_warp() >> 2, w = fresh_warp() & 3;
        float acc[2][2];
        const int c = 8 * (lane >> 4) + (lane & 7), ck = 2 * w + ((lane >> 3) & 1);
        consume(acc, sb + SM_W1 + 2 * wg * 12288 + c * 128 + ((ck ^ (c & 7)) * 16), prm.ydesc,
                prm.w1desc + (((2 * wg + 1) * 12288 + 5 * 2048) >> 4), wg * SLOT_BYTES, make_duty(prm, wg, w), w, lane, prm);
        publish_fast(prm, acc, lds32(sb + SM_RED + RED_EPOCH * 4), wg, w, lane);
        MARK(0);
        bulk_wait_all();
        asm volatile("bar.arrive 11, 512;" ::: "memory");
        if (wg == 0) TS(3);
        asm volatile("setmaxnreg.inc.sync.aligned.u32 %0;" ::"n"(EVEN_REGS));
    }

    {
        MARK(1);
        if (fresh_warp() >= 12) prepare_w2<true>(prm, nullptr);

        if (fresh_cta() < NUM_CTAS ? pass2_tiles(pass2_setup(prm), prm, 0) : helper_tiles(pass2_setup(prm), prm, 0)) {
            const float* exact = exact_sums(prm);
            if (fresh_warp() >= 12) prepare_w2<false>(prm, exact);
            pass2_tiles(pass2_setup(prm), prm, 1);
        }
        bulk_wait_read<0>();
        MARK(13);
    }
}

}

extern "C" void kernel_launch(void* const* d_in, const int* in_sizes, int n_in, void* d_out, int out_size) {
    (void)in_sizes; (void)n_in; (void)out_size;
    typedef CUresult (*EncodeFn)(CUtensorMap*, CUtensorMapDataType, cuuint32_t, void*, const cuuint64_t*, const cuuint64_t*,
                                 const cuuint32_t*, const cuuint32_t*, CUtensorMapInterleave, CUtensorMapSwizzle,
                                 CUtensorMapL2promotion, CUtensorMapFloatOOBfill);
    void* fn = nullptr;
    cudaDriverEntryPointQueryResult status;
    cudaGetDriverEntryPoint("cuTensorMapEncodeTiled", &fn, cudaEnableDefault, &status);
    const EncodeFn encode = (EncodeFn)fn;
    const cuuint32_t ones[2] = {1, 1};

    Params p;
    {
        const cuuint64_t dims[2] = {EX, CH}, strides[1] = {EX * 2};
        const cuuint32_t box[2] = {64, CH};
        encode(&p.w1_map, CU_TENSOR_MAP_DATA_TYPE_BFLOAT16, 2, d_in[2], dims, strides, box, ones,
               CU_TENSOR_MAP_INTERLEAVE_NONE, CU_TENSOR_MAP_SWIZZLE_128B, CU_TENSOR_MAP_L2_PROMOTION_NONE,
               CU_TENSOR_MAP_FLOAT_OOB_FILL_NONE);
    }
    {
        const cuuint64_t dims[2] = {CH, EX}, strides[1] = {CH * 2};
        const cuuint32_t box[2] = {32, 192};
        encode(&p.w2_map, CU_TENSOR_MAP_DATA_TYPE_BFLOAT16, 2, d_in[3], dims, strides, box, ones,
               CU_TENSOR_MAP_INTERLEAVE_NONE, CU_TENSOR_MAP_SWIZZLE_64B, CU_TENSOR_MAP_L2_PROMOTION_NONE,
               CU_TENSOR_MAP_FLOAT_OOB_FILL_NONE);
    }
    p.x = (const __nv_bfloat16*)d_in[0];
    p.dw = (const __nv_bfloat16*)d_in[1];
    p.w1 = (const __nv_bfloat16*)d_in[2];
    p.gamma = (const __nv_bfloat16*)d_in[4];
    p.beta = (const __nv_bfloat16*)d_in[5];
    p.out = (__nv_bfloat16*)d_out;
    cudaGetSymbolAddress((void**)&p.g, g_scratch);
    p.w1desc = desc_lo(sb + SM_W1, 12288);
    p.w2desc = desc_lo(sb + SM_W2, 24576);
    p.helper_desc[0] = p.w1desc;
    p.helper_desc[1] = p.w2desc;
    p.ydesc = desc_lo(sb + SM_Y1, 16);
    p.ydesc64[0] = (0x40000040ull << 32) | p.ydesc;
    p.ydesc64[1] = (0x80000020ull << 32) | (p.ydesc + 512);
    for (int k = 0; k < 3; k++) p.sel[k] = (8ull << 32) | desc_lo(sb + SM_SEL + k * 128, k == 2 ? 128 : 0);
    constexpr int smem_bytes = SM_TOTAL;
    cudaFuncSetAttribute(convnext_kernel, cudaFuncAttributeMaxDynamicSharedMemorySize, smem_bytes);
    int device = 0, sms = 0;
    cudaGetDevice(&device);
    cudaDeviceGetAttribute(&sms, cudaDevAttrMultiProcessorCount, device);
    p.ctas = USE_HELPERS && sms >= NUM_CTAS + HELPERS ? NUM_CTAS + HELPERS : NUM_CTAS;
    convnext_kernel<<<p.ctas, 512, smem_bytes>>>(p);
}
```

```cpp
#include <cuda.h>
#include <cuda_runtime.h>
#include <cuda_bf16.h>
#include <stdint.h>

namespace {

constexpr int IMG_W = 512, CH = 96, EX = 384;
constexpr int TILE_PX = 64;
constexpr int ROWS_PER_CTA = 32;
constexpr int NUM_CTAS = 128;
constexpr int HELPERS = 4;
constexpr int STEPS = ROWS_PER_CTA + 2;
constexpr int ROW_BYTES = IMG_W * CH * 2;

#define USE_HELPERS 1
#define FORCE_EXACT 0
constexpr int PRODUCER_REGS = 200, CONSUMER_REGS = 104, EVEN_REGS = 128;

constexpr int XHALF_BYTES = 34 * 192;
constexpr int XHALF_B = XHALF_BYTES + 64;
constexpr int XROW_BYTES = XHALF_B + XHALF_BYTES + 64;
constexpr int L2_AHEAD = 2;
constexpr int NX = 3;
constexpr int TILE_BYTES = TILE_PX * 192;

constexpr uint32_t sb = 1024;
constexpr int SM_W1 = 0;
constexpr int SM_W2 = 73728;
constexpr int SM_RING = 147456;
constexpr int SLOT_BYTES = 26624;
constexpr int SM_Y1 = SM_RING;
constexpr int SM_X = SM_Y1 + TILE_BYTES;
constexpr int SM_STAT = SM_X + XROW_BYTES;
constexpr int SM_BUF3 = SM_X + SLOT_BYTES, SM_SPARE = SM_X;
constexpr int SM_SEL = SM_RING + NX * SLOT_BYTES;
constexpr int SM_BIAS = SM_SEL + 512;
constexpr int SM_GAMMA = SM_BIAS + 384;
constexpr int SM_BETA = SM_GAMMA + EX * 2;
constexpr int SM_RED = SM_BETA + EX * 2;
constexpr int SM_BAR = SM_RED + 16;
constexpr int BAR_Y2FULL = 0, BAR_XSFULL = 4, BAR_W1 = 8, BAR_W2 = 9, BAR_W1B = 10, BAR_TURN = 11, BAR_ROWS = 51,
              BAR_STAT = 54, BAR_DW = 55, BAR_COUNT = 56;
constexpr int SM_GO = SM_BAR + BAR_COUNT * 8, GO_COUNT = ROWS_PER_CTA + 2 * NX;
constexpr int SM_YFULL = SM_GO + (GO_COUNT + 1) * 8;
constexpr int SM_TOTAL = SM_YFULL + (ROWS_PER_CTA + 1) * 8;
static_assert(SM_STAT + TILE_PX * 16 <= SM_RING + SLOT_BYTES && XROW_BYTES >= TILE_BYTES && SM_X % 1024 == 0, "ring layout");
static_assert(SM_TOTAL <= 232448, "smem budget");
static_assert(SM_STAT % 128 == 0 && SM_BIAS % 16 == 0 && SM_BAR % 8 == 0 && SLOT_BYTES % 1024 == 0, "alignment");

constexpr int RED_EPOCH = 0, RED_SCALE = 2;

constexpr float GELU_A = 0.32920349f;
constexpr uint32_t GELU_C_H2 = 0x40D940D9u;
constexpr float INV_2A = 1.0f / (2.0f * GELU_A);

constexpr uint32_t TAP_SCALE_BF2 = 0x2B802B80u;
constexpr float LN_EPS_SCALED = 1e-5f * 0x1p-80f;
constexpr float RSTD_SCALE = GELU_A * 0x1p-112f;

struct Scratch {
    unsigned long long acc[2][EX / 4 * 32];
    unsigned long long bias[CH];
    float sums[2][EX];
    uint4 zero_row[66 * 192 / 16];
    uint4 park[HELPERS][3][16][128];
    unsigned int count[2];
    unsigned int parked[NUM_CTAS];
};
__device__ __align__(256) Scratch g_scratch;
constexpr float ACC_LIMIT = 0x1p30f;

#define TS(k)
#define ASM_TS
#define MARK(k)
#define SMARK(k)
#define ASM_MARK
#define ASM_SMARK
#define ASM_TRC(it)

__device__ __forceinline__ void mbar_init(uint32_t bar, uint32_t count) {
    asm volatile("mbarrier.init.shared::cta.b64 [%0], %1;" ::"r"(bar), "r"(count) : "memory");
}
__device__ __forceinline__ void mbar_arrive_if(uint32_t bar, bool pred) {
    asm volatile("{\n.reg .pred p;\nsetp.ne.u32 p, %1, 0;\n@p mbarrier.arrive.shared::cta.b64 _, [%0];\n}\n"
                 ::"r"(bar), "r"((uint32_t)pred) : "memory");
}
__device__ __forceinline__ void mbar_wait(uint32_t bar, uint32_t parity) {
    asm volatile(
        "{\n.reg .pred p;\n.reg .u32 n;\n"
        "mbarrier.try_wait.parity.shared::cta.b64 p, [%0], %1;\n"
        "@p bra.uni WAIT_DONE;\n"
        "mov.u32 n, 0;\n"
        "WAIT_LOOP:\n"
        "mbarrier.try_wait.parity.shared::cta.b64 p, [%0], %1;\n"
        "@p bra.uni WAIT_DONE;\n"
        "mbarrier.try_wait.parity.shared::cta.b64 p, [%0], %1;\n"
        "@p bra.uni WAIT_DONE;\n"
        "mbarrier.try_wait.parity.shared::cta.b64 p, [%0], %1;\n"
        "@p bra.uni WAIT_DONE;\n"
        "add.u32 n, n, 1;\nsetp.lt.u32 p, n, 0x40000;\n"
        "@p bra.uni WAIT_LOOP;\n"
        "trap;\n"
        "WAIT_DONE:\n}\n"
        ::"r"(bar), "r"(parity) : "memory");
}
template <int PARITY> __device__ __forceinline__ void mbar_wait_c(uint32_t bar) {
    asm volatile(
        "{\n.reg .pred p;\n.reg .u32 n;\n"
        "mbarrier.try_wait.parity.shared::cta.b64 p, [%0], %1;\n"
        "@p bra.uni WAIT_DONE;\n"
        "mov.u32 n, 0;\n"
        "WAIT_LOOP:\n"
        "mbarrier.try_wait.parity.shared::cta.b64 p, [%0], %1;\n"
        "@p bra.uni WAIT_DONE;\n"
        "mbarrier.try_wait.parity.shared::cta.b64 p, [%0], %1;\n"
        "@p bra.uni WAIT_DONE;\n"
        "mbarrier.try_wait.parity.shared::cta.b64 p, [%0], %1;\n"
        "@p bra.uni WAIT_DONE;\n"
        "add.u32 n, n, 1;\nsetp.lt.u32 p, n, 0x40000;\n"
        "@p bra.uni WAIT_LOOP;\n"
        "trap;\n"
        "WAIT_DONE:\n}\n"
        ::"r"(bar), "n"(PARITY) : "memory");
}
#define ELECTED(body) "{\n.reg .pred p;\nelect.sync _|p, 0xffffffff;\n" body "}\n"
__device__ __forceinline__ void expect_tx(uint32_t bar, uint32_t bytes) {
    asm volatile(ELECTED("@p mbarrier.arrive.expect_tx.shared::cta.b64 _, [%0], %1;\n") ::"r"(bar), "r"(bytes) : "memory");
}
__device__ __forceinline__ void bulk_load(uint32_t dst, const void* src, uint32_t bytes, uint32_t bar) {
    asm volatile(ELECTED("@p cp.async.bulk.shared::cluster.global.mbarrier::complete_tx::bytes [%0], [%1], %2, [%3];\n")
                 ::"r"(dst), "l"(src), "r"(bytes), "r"(bar) : "memory");
}
__device__ __forceinline__ void bulk_prefetch(const void* src, uint32_t bytes) {
    asm volatile(ELECTED("@p cp.async.bulk.prefetch.L2.global [%0], %1;\n") ::"l"(src), "r"(bytes) : "memory");
}
__device__ __forceinline__ void tma_load_2d(uint32_t dst, const CUtensorMap* map, int c0, int c1, uint32_t bar) {
    asm volatile(ELECTED("@p cp.async.bulk.tensor.2d.shared::cluster.global.mbarrier::complete_tx::bytes [%0], [%1, {%2, %3}], [%4];\n")
                 ::"r"(dst), "l"(map), "r"(c0), "r"(c1), "r"(bar) : "memory");
}
template <int N> __device__ __forceinline__ void bulk_wait_read() {
    asm volatile("cp.async.bulk.wait_group.read %0;" ::"n"(N) : "memory");
}
__device__ __forceinline__ void bulk_wait_all() { asm volatile("cp.async.bulk.wait_group 0;" ::: "memory"); }
__device__ __forceinline__ void fence_async_smem() { asm volatile("fence.proxy.async.shared::cta;" ::: "memory"); }
__device__ __forceinline__ void named_sync(int id, int n) { asm volatile("bar.sync %0, %1;" ::"r"(id), "r"(n) : "memory"); }

__device__ __forceinline__ void sts64(uint32_t addr, uint32_t a, uint32_t b) {
    asm volatile("st.shared.v2.b32 [%0], {%1,%2};" ::"r"(addr), "r"(a), "r"(b) : "memory");
}
__device__ __forceinline__ void sts128(uint32_t addr, uint32_t a, uint32_t b, uint32_t c, uint32_t d) {
    asm volatile("st.shared.v4.b32 [%0], {%1,%2,%3,%4};" ::"r"(addr), "r"(a), "r"(b), "r"(c), "r"(d) : "memory");
}
__device__ __forceinline__ void ldsm4_t(uint32_t* r, uint32_t addr) {
    asm volatile("ldmatrix.sync.aligned.m8n8.x4.trans.shared.b16 {%0,%1,%2,%3}, [%4];"
                 : "=r"(r[0]), "=r"(r[1]), "=r"(r[2]), "=r"(r[3]) : "r"(addr) : "memory");
}
__device__ __forceinline__ void lds128(uint32_t* v, uint32_t addr) {
    asm volatile("ld.shared.v4.b32 {%0,%1,%2,%3}, [%4];"
                 : "=r"(v[0]), "=r"(v[1]), "=r"(v[2]), "=r"(v[3]) : "r"(addr) : "memory");
}
__device__ __forceinline__ uint32_t lds32(uint32_t addr) {
    uint32_t v; asm volatile("ld.shared.b32 %0, [%1];" : "=r"(v) : "r"(addr) : "memory"); return v;
}
__device__ __forceinline__ void sts32(uint32_t addr, uint32_t v) {
    asm volatile("st.shared.b32 [%0], %1;" ::"r"(addr), "r"(v) : "memory");
}

__device__ __forceinline__ uint32_t bf2_fma(uint32_t a, uint32_t b, uint32_t c) {
    uint32_t d; asm("fma.rn.bf16x2 %0, %1, %2, %3;" : "=r"(d) : "r"(a), "r"(b), "r"(c)); return d;
}
__device__ __forceinline__ uint32_t bf2_mul(uint32_t a, uint32_t b) {
    uint32_t d; asm("mul.rn.bf16x2 %0, %1, %2;" : "=r"(d) : "r"(a), "r"(b)); return d;
}
__device__ __forceinline__ uint32_t bf2_add(uint32_t a, uint32_t b) {
    uint32_t d; asm("add.rn.bf16x2 %0, %1, %2;" : "=r"(d) : "r"(a), "r"(b)); return d;
}
__device__ __forceinline__ uint32_t h2_fma(uint32_t a, uint32_t b, uint32_t c) {
    uint32_t d; asm("fma.rn.f16x2 %0, %1, %2, %3;" : "=r"(d) : "r"(a), "r"(b), "r"(c)); return d;
}
__device__ __forceinline__ uint32_t h2_mul(uint32_t a, uint32_t b) {
    uint32_t d; asm("mul.rn.f16x2 %0, %1, %2;" : "=r"(d) : "r"(a), "r"(b)); return d;
}
__device__ __forceinline__ uint32_t h2_tanh(uint32_t a) {
    uint32_t d; asm("tanh.approx.f16x2 %0, %1;" : "=r"(d) : "r"(a)); return d;
}
__device__ __forceinline__ float bf_lo(uint32_t v) { return __uint_as_float(v << 16); }
__device__ __forceinline__ float bf_hi(uint32_t v) { return __uint_as_float(v & 0xffff0000u); }
__device__ __forceinline__ uint32_t pack_h2(float lo, float hi) {
    uint32_t d; asm("cvt.rn.f16x2.f32 %0, %1, %2;" : "=r"(d) : "f"(hi), "f"(lo)); return d;
}
__device__ __forceinline__ uint32_t pack_bf2(float lo, float hi) {
    uint32_t d; asm("cvt.rn.bf16x2.f32 %0, %1, %2;" : "=r"(d) : "f"(hi), "f"(lo)); return d;
}
__device__ __forceinline__ void h2_unpack(uint32_t v, float& lo, float& hi) {
    asm("{\n.reg .b16 l, h;\nmov.b32 {l, h}, %2;\ncvt.f32.f16 %0, l;\ncvt.f32.f16 %1, h;\n}\n" : "=f"(lo), "=f"(hi) : "r"(v));
}

__device__ __forceinline__ uint32_t gelu2(uint32_t z) {
    uint32_t p = h2_fma(z, z, GELU_C_H2);
    uint32_t t = h2_tanh(h2_mul(z, p));
    return h2_fma(z, t, z);
}

__device__ __forceinline__ void wg_fence() { asm volatile("wgmma.fence.sync.aligned;" ::: "memory"); }
__device__ __forceinline__ void wg_commit() { asm volatile("wgmma.commit_group.sync.aligned;" ::: "memory"); }
template <int N> __device__ __forceinline__ void wg_wait() {
    asm volatile("wgmma.wait_group.sync.aligned %0;" ::"n"(N) : "memory");
}
template <int N> __device__ __forceinline__ void pin(uint32_t (&r)[N]) {
#pragma unroll
    for (int i = 0; i < N; i++) asm volatile("" : "+r"(r[i])::"memory");
}
constexpr uint32_t desc_lo(uint32_t addr, uint32_t lbo) { return ((addr & 0x3FFFF) >> 4) | ((lbo >> 4) << 16); }
template <uint32_t SBO, uint32_t SWZ> __device__ __forceinline__ uint64_t desc(uint32_t lo, uint32_t bytes) {
    return (((uint64_t)((SBO >> 4) | (SWZ << 30)) << 32) | lo) + (bytes >> 4);
}
__device__ __forceinline__ uint32_t fresh_tid() {
    uint32_t v; asm volatile("mov.u32 %0, %%tid.x;" : "=r"(v));
    return v;
}
template <uint32_t V> __device__ __forceinline__ uint32_t loop_init() {
    uint32_t v; asm volatile("mov.u32 %0, %1;" : "=r"(v) : "n"(V)); return v;
}
__device__ __forceinline__ int fresh_warp() {
    int v; asm volatile("shfl.sync.idx.b32 %0, %1, 0, 0x1f, 0xffffffff;" : "=r"(v) : "r"(fresh_tid() >> 5)); return v;
}
__device__ __forceinline__ uint32_t fresh_cta() {
    uint32_t v; asm volatile("mov.u32 %0, %%ctaid.x;" : "=r"(v)); return v;
}
__device__ __forceinline__ float sqrt_fast(float v) { float r; asm("sqrt.approx.f32 %0, %1;" : "=f"(r) : "f"(v)); return r; }

template <int TB>
__device__ __forceinline__ void wgmma_n64_h_set(uint32_t (&d)[16], const uint32_t* a, uint64_t desc) {
    asm volatile(
        "{\n.reg .pred p;\nsetp.ne.b32 p, 0, 0;\n"
        "wgmma.mma_async.sync.aligned.m64n64k16.f16.f16.f16 "
        "{%0,%1,%2,%3,%4,%5,%6,%7,%8,%9,%10,%11,%12,%13,%14,%15}, {%16,%17,%18,%19}, %20, p, 1, 1, %21;\n}\n"
        : "=r"(d[0]), "=r"(d[1]), "=r"(d[2]), "=r"(d[3]), "=r"(d[4]), "=r"(d[5]), "=r"(d[6]), "=r"(d[7]), "=r"(d[8]), "=r"(d[9]), "=r"(d[10]), "=r"(d[11]), "=r"(d[12]), "=r"(d[13]), "=r"(d[14]), "=r"(d[15])
        : "r"(a[0]), "r"(a[1]), "r"(a[2]), "r"(a[3]), "l"(desc), "n"(TB));
}
template <int TB>
__device__ __forceinline__ void wgmma_n64_h_acc(uint32_t (&d)[16], const uint32_t* a, uint64_t desc) {
    asm volatile(
        "{\n.reg .pred p;\nsetp.ne.b32 p, 1, 0;\n"
        "wgmma.mma_async.sync.aligned.m64n64k16.f16.f16.f16 "
        "{%0,%1,%2,%3,%4,%5,%6,%7,%8,%9,%10,%11,%12,%13,%14,%15}, {%16,%17,%18,%19}, %20, p, 1, 1, %21;\n}\n"
        : "+r"(d[0]), "+r"(d[1]), "+r"(d[2]), "+r"(d[3]), "+r"(d[4]), "+r"(d[5]), "+r"(d[6]), "+r"(d[7]), "+r"(d[8]), "+r"(d[9]), "+r"(d[10]), "+r"(d[11]), "+r"(d[12]), "+r"(d[13]), "+r"(d[14]), "+r"(d[15])
        : "r"(a[0]), "r"(a[1]), "r"(a[2]), "r"(a[3]), "l"(desc), "n"(TB));
}
__device__ __forceinline__ void wgmma_n64_h_acc_ss(uint32_t (&d)[16], uint64_t adesc, uint64_t desc) {
    asm volatile(
        "{\n.reg .pred p;\nsetp.ne.b32 p, 1, 0;\n"
        "wgmma.mma_async.sync.aligned.m64n64k16.f16.f16.f16 "
        "{%0,%1,%2,%3,%4,%5,%6,%7,%8,%9,%10,%11,%12,%13,%14,%15}, %16, %17, p, 1, 1, 1, 0;\n}\n"
        : "+r"(d[0]), "+r"(d[1]), "+r"(d[2]), "+r"(d[3]), "+r"(d[4]), "+r"(d[5]), "+r"(d[6]), "+r"(d[7]), "+r"(d[8]), "+r"(d[9]), "+r"(d[10]), "+r"(d[11]), "+r"(d[12]), "+r"(d[13]), "+r"(d[14]), "+r"(d[15])
        : "l"(adesc), "l"(desc));
}

struct Params {
    CUtensorMap w1_map, w2_map;
    const __nv_bfloat16* x;
    const __nv_bfloat16* dw;
    const __nv_bfloat16* w1;
    const __nv_bfloat16* gamma;
    const __nv_bfloat16* beta;
    __nv_bfloat16* out;
    Scratch* g;
    uint64_t ydesc64[2];
    uint64_t sel[3];
    uint32_t w1desc, w2desc, ydesc;
    uint32_t helper_desc[2];
    uint32_t ctas;
};

__device__ __forceinline__ int cta_stride(uint32_t cta) { return cta & 8 ? ROW_BYTES : -ROW_BYTES; }
__device__ __forceinline__ uint32_t cta_tile0(uint32_t cta) {
    return ((cta >> 3) * ROWS_PER_CTA + (cta & 8 ? 0 : ROWS_PER_CTA - 1)) * ROW_BYTES + (cta & 7) * TILE_BYTES;
}

struct Producer {
    uint32_t w[9][6];
    uint32_t xoff[2];
    uint32_t yoff[2][2];
    uint32_t stat, own;
    int lane;
};

struct RowCopy {
    const char* x0;
    char* y0;
    const char* zeros;
    uint32_t cut0, cut1;
    int stride, last;
};
__device__ __forceinline__ RowCopy row_copy(const Params& prm) {
    const uint32_t cta = fresh_cta(), strip = cta & 7, t0 = cta_tile0(cta);
    RowCopy r;
    r.stride = cta_stride(cta);
    r.x0 = (const char*)prm.x + (t0 - r.stride) - 192;
    r.y0 = (char*)prm.out + t0;
    r.zeros = (const char*)prm.g->zero_row;
    r.cut0 = strip == 0 ? 192 : 0;
    r.cut1 = strip == 7 ? 192 : 0;
    r.last = cta - 8 >= NUM_CTAS - 16 ? STEPS - 2 : STEPS - 1;
    return r;
}
__device__ __forceinline__ void issue_row_load(const RowCopy& r, int i, uint32_t slot) {
    const char* src = r.x0 + i * r.stride;
    const uint32_t bar = sb + SM_GO + i * 8, dst = sb + SM_X + slot * SLOT_BYTES;
    expect_tx(bar, XHALF_BYTES - r.cut0);
    bulk_load(dst + r.cut0, src + r.cut0, XHALF_BYTES - r.cut0, bar);
    expect_tx(bar, XHALF_BYTES - r.cut1);
    bulk_load(dst + XHALF_B, src + 32 * 192, XHALF_BYTES - r.cut1, bar);
}

__device__ __forceinline__ float quad_sum(float v) {
    v += __shfl_xor_sync(0xffffffffu, v, 1);
    v += __shfl_xor_sync(0xffffffffu, v, 2);
    return v;
}

__device__ __forceinline__ void load_x(uint32_t (&v)[6][6], const Producer& c, uint32_t row) {
#pragma unroll
    for (int k = 0; k < 6; k++) {
        asm volatile("ld.shared.v4.b32 {%0,%1,%2,%3}, [%4];"
                     : "=r"(v[k][0]), "=r"(v[k][1]), "=r"(v[k][2]), "=r"(v[k][3]) : "r"(row + c.xoff[0] + k * 192));
        asm volatile("ld.shared.v2.b32 {%0,%1}, [%2];" : "=r"(v[k][4]), "=r"(v[k][5]) : "r"(row + c.xoff[1] + k * 192));
    }
}
template <int DY, int STRIDE>
__device__ __forceinline__ void conv_row(uint32_t (&dst)[24], const uint32_t* src, const uint32_t (&v)[6][6], const Producer& c) {
#pragma unroll
    for (int o = 0; o < 4; o++)
#pragma unroll
        for (int u = 0; u < 6; u++)
            dst[o * 6 + u] = bf2_fma(v[o + 2][u], c.w[3 * DY + 2][u], bf2_fma(v[o + 1][u], c.w[3 * DY + 1][u],
                             bf2_fma(v[o][u], c.w[3 * DY][u], STRIDE ? src[o * 6 + u] : src[2 * o + 1])));
}
#define HAND_OVER(name, base, r) asm volatile("mov.b32 " name "%6, %0; mov.b32 " name "%7, %1; mov.b32 " name "%8, %2;\n" \
    "mov.b32 " name "%9, %3; mov.b32 " name "%10, %4; mov.b32 " name "%11, %5;" ::"r"((r)[0]), "r"((r)[1]), "r"((r)[2]), \
    "r"((r)[3]), "r"((r)[4]), "r"((r)[5]), "n"(base), "n"(base + 1), "n"(base + 2), "n"(base + 3), "n"(base + 4), "n"(base + 5))
template <int K> __device__ __forceinline__ void hand_over(const Producer& c, const uint32_t (&B)[24], const uint32_t (&C)[24],
                                                           const uint32_t (&v)[6][6]) {
    HAND_OVER("pw", K * 6, c.w[K]);
    if (K < 6) HAND_OVER("pv", K * 6, v[K % 6]);
    if (K < 4) { HAND_OVER("pb", K * 6, B + K % 4 * 6); HAND_OVER("pc", K * 6, C + K % 4 * 6); }
    if constexpr (K < 8) hand_over<K + 1>(c, B, C, v);
}
__device__ __forceinline__ void produce_tiles(const Producer& c, const Params& prm) {
    asm volatile(
        "{\n"
        ".reg .b32 pa<24>, pq<4>, m<6>, y<6>, rr, mm, t, so, ad, tt, cnt;\n"
        ".reg .b16 xl, xh;\n"
        ".reg .f32 d<4>, us, s0, s1, f0, f1, kq;\n"
        ".reg .pred pt, pf, pr, pw, pl, po, pe;\n"
        "setp.ne.b32 pt, 1, 0; setp.ne.b32 pf, 0, 0; setp.eq.u32 pl, %8, 0; and.b32 tt, %8, 1; setp.ne.u32 po, tt, 0;\n"
        "and.b32 tt, %8, 4; setp.ne.u32 pr, tt, 0; selp.f32 kq, 0f3F802D41, 0f3F7FA57E, pr;\n"
        "mov.u32 t, 0; mov.u32 so, 0;\n"
        "setp.eq.u32 pr, %12, 0;\n"
        "@pr bra.uni RARE;\n"
        "LOOP:\n"
        ASM_TRC("t")
        "fma.rn.bf16x2 pa0, pv0, pw36, pb0; fma.rn.bf16x2 pa1, pv1, pw37, pb1; fma.rn.bf16x2 pa2, pv2, pw38, pb2; fma.rn.bf16x2 pa3, pv3, pw39, pb3; fma.rn.bf16x2 pa4, pv4, pw40, pb4; fma.rn.bf16x2 pa5, pv5, pw41, pb5;\n"
        "fma.rn.bf16x2 pa6, pv6, pw36, pb6; fma.rn.bf16x2 pa7, pv7, pw37, pb7; fma.rn.bf16x2 pa8, pv8, pw38, pb8; fma.rn.bf16x2 pa9, pv9, pw39, pb9; fma.rn.bf16x2 pa10, pv10, pw40, pb10; fma.rn.bf16x2 pa11, pv11, pw41, pb11;\n"
        "fma.rn.bf16x2 pa12, pv12, pw36, pb12; fma.rn.bf16x2 pa13, pv13, pw37, pb13; fma.rn.bf16x2 pa14, pv14, pw38, pb14; fma.rn.bf16x2 pa15, pv15, pw39, pb15; fma.rn.bf16x2 pa16, pv16, pw40, pb16; fma.rn.bf16x2 pa17, pv17, pw41, pb17;\n"
        "fma.rn.bf16x2 pa18, pv18, pw36, pb18; fma.rn.bf16x2 pa19, pv19, pw37, pb19; fma.rn.bf16x2 pa20, pv20, pw38, pb20; fma.rn.bf16x2 pa21, pv21, pw39, pb21; fma.rn.bf16x2 pa22, pv22, pw40, pb22; fma.rn.bf16x2 pa23, pv23, pw41, pb23;\n"
        "fma.rn.bf16x2 pa0, pv6, pw42, pa0; fma.rn.bf16x2 pa1, pv7, pw43, pa1; fma.rn.bf16x2 pa2, pv8, pw44, pa2; fma.rn.bf16x2 pa3, pv9, pw45, pa3; fma.rn.bf16x2 pa4, pv10, pw46, pa4; fma.rn.bf16x2 pa5, pv11, pw47, pa5;\n"
        "fma.rn.bf16x2 pa6, pv12, pw42, pa6; fma.rn.bf16x2 pa7, pv13, pw43, pa7; fma.rn.bf16x2 pa8, pv14, pw44, pa8; fma.rn.bf16x2 pa9, pv15, pw45, pa9; fma.rn.bf16x2 pa10, pv16, pw46, pa10; fma.rn.bf16x2 pa11, pv17, pw47, pa11;\n"
        "fma.rn.bf16x2 pa12, pv18, pw42, pa12; fma.rn.bf16x2 pa13, pv19, pw43, pa13; fma.rn.bf16x2 pa14, pv20, pw44, pa14; fma.rn.bf16x2 pa15, pv21, pw45, pa15; fma.rn.bf16x2 pa16, pv22, pw46, pa16; fma.rn.bf16x2 pa17, pv23, pw47, pa17;\n"
        "fma.rn.bf16x2 pa18, pv24, pw42, pa18; fma.rn.bf16x2 pa19, pv25, pw43, pa19; fma.rn.bf16x2 pa20, pv26, pw44, pa20; fma.rn.bf16x2 pa21, pv27, pw45, pa21; fma.rn.bf16x2 pa22, pv28, pw46, pa22; fma.rn.bf16x2 pa23, pv29, pw47, pa23;\n"
        "fma.rn.bf16x2 pa0, pv12, pw48, pa0; fma.rn.bf16x2 pa1, pv13, pw49, pa1; fma.rn.bf16x2 pa2, pv14, pw50, pa2; fma.rn.bf16x2 pa3, pv15, pw51, pa3; fma.rn.bf16x2 pa4, pv16, pw52, pa4; fma.rn.bf16x2 pa5, pv17, pw53, pa5;\n"
        "fma.rn.bf16x2 pa6, pv18, pw48, pa6; fma.rn.bf16x2 pa7, pv19, pw49, pa7; fma.rn.bf16x2 pa8, pv20, pw50, pa8; fma.rn.bf16x2 pa9, pv21, pw51, pa9; fma.rn.bf16x2 pa10, pv22, pw52, pa10; fma.rn.bf16x2 pa11, pv23, pw53, pa11;\n"
        "fma.rn.bf16x2 pa12, pv24, pw48, pa12; fma.rn.bf16x2 pa13, pv25, pw49, pa13; fma.rn.bf16x2 pa14, pv26, pw50, pa14; fma.rn.bf16x2 pa15, pv27, pw51, pa15; fma.rn.bf16x2 pa16, pv28, pw52, pa16; fma.rn.bf16x2 pa17, pv29, pw53, pa17;\n"
        "fma.rn.bf16x2 pa18, pv30, pw48, pa18; fma.rn.bf16x2 pa19, pv31, pw49, pa19; fma.rn.bf16x2 pa20, pv32, pw50, pa20; fma.rn.bf16x2 pa21, pv33, pw51, pa21; fma.rn.bf16x2 pa22, pv34, pw52, pa22; fma.rn.bf16x2 pa23, pv35, pw53, pa23;\n"
        "mul.rn.bf16x2 pq0, pa0, pa0; fma.rn.bf16x2 pq0, pa1, pa1, pq0; fma.rn.bf16x2 pq0, pa2, pa2, pq0; fma.rn.bf16x2 pq0, pa3, pa3, pq0; fma.rn.bf16x2 pq0, pa4, pa4, pq0; fma.rn.bf16x2 pq0, pa5, pa5, pq0;\n"
        "mul.rn.bf16x2 pq1, pa6, pa6; fma.rn.bf16x2 pq1, pa7, pa7, pq1; fma.rn.bf16x2 pq1, pa8, pa8, pq1; fma.rn.bf16x2 pq1, pa9, pa9, pq1; fma.rn.bf16x2 pq1, pa10, pa10, pq1; fma.rn.bf16x2 pq1, pa11, pa11, pq1;\n"
        "mul.rn.bf16x2 pq2, pa12, pa12; fma.rn.bf16x2 pq2, pa13, pa13, pq2; fma.rn.bf16x2 pq2, pa14, pa14, pq2; fma.rn.bf16x2 pq2, pa15, pa15, pq2; fma.rn.bf16x2 pq2, pa16, pa16, pq2; fma.rn.bf16x2 pq2, pa17, pa17, pq2;\n"
        "mul.rn.bf16x2 pq3, pa18, pa18; fma.rn.bf16x2 pq3, pa19, pa19, pq3; fma.rn.bf16x2 pq3, pa20, pa20, pq3; fma.rn.bf16x2 pq3, pa21, pa21, pq3; fma.rn.bf16x2 pq3, pa22, pa22, pq3; fma.rn.bf16x2 pq3, pa23, pa23, pq3;\n"
        "B0:\n"
        "wgmma.fence.sync.aligned;\n"
        "wgmma.mma_async.sync.aligned.m64n8k16.f32.bf16.bf16 {d0,d1,d2,d3}, {pa0,pa6,pa1,pa7}, %9, pf, 1, 1, 0;\n"
        "wgmma.mma_async.sync.aligned.m64n8k16.f32.bf16.bf16 {d0,d1,d2,d3}, {pa2,pa8,pa3,pa9}, %9, pt, 1, 1, 0;\n"
        "wgmma.mma_async.sync.aligned.m64n8k16.f32.bf16.bf16 {d0,d1,d2,d3}, {pa4,pa10,pa5,pa11}, %9, pt, 1, 1, 0;\n"
        "wgmma.mma_async.sync.aligned.m64n8k16.f32.bf16.bf16 {d0,d1,d2,d3}, {pa12,pa18,pa13,pa19}, %10, pt, 1, 1, 0;\n"
        "wgmma.mma_async.sync.aligned.m64n8k16.f32.bf16.bf16 {d0,d1,d2,d3}, {pa14,pa20,pa15,pa21}, %10, pt, 1, 1, 0;\n"
        "wgmma.mma_async.sync.aligned.m64n8k16.f32.bf16.bf16 {d0,d1,d2,d3}, {pa16,pa22,pa17,pa23}, %10, pt, 1, 1, 0;\n"
        "wgmma.mma_async.sync.aligned.m64n8k16.f32.bf16.bf16 {d0,d1,d2,d3}, {pq0,pq1,pq2,pq3}, %11, pt, 1, 1, 0;\n"
        "wgmma.commit_group.sync.aligned;\n"
        "fence.proxy.async.shared::cta;\n"
        "@pl mbarrier.arrive.shared::cta.b64 _, [t+231552];\n"
        "add.u32 ad, %7, so; ld.shared.f32 us, [ad+4];\n"
        "fma.rn.bf16x2 pb0, pv0, pw18, pc0; fma.rn.bf16x2 pb1, pv1, pw19, pc1; fma.rn.bf16x2 pb2, pv2, pw20, pc2; fma.rn.bf16x2 pb3, pv3, pw21, pc3; fma.rn.bf16x2 pb4, pv4, pw22, pc4; fma.rn.bf16x2 pb5, pv5, pw23, pc5;\n"
        "fma.rn.bf16x2 pb6, pv6, pw18, pc6; fma.rn.bf16x2 pb7, pv7, pw19, pc7; fma.rn.bf16x2 pb8, pv8, pw20, pc8; fma.rn.bf16x2 pb9, pv9, pw21, pc9; fma.rn.bf16x2 pb10, pv10, pw22, pc10; fma.rn.bf16x2 pb11, pv11, pw23, pc11;\n"
        "fma.rn.bf16x2 pb0, pv6, pw24, pb0; fma.rn.bf16x2 pb1, pv7, pw25, pb1; fma.rn.bf16x2 pb2, pv8, pw26, pb2; fma.rn.bf16x2 pb3, pv9, pw27, pb3; fma.rn.bf16x2 pb4, pv10, pw28, pb4; fma.rn.bf16x2 pb5, pv11, pw29, pb5;\n"
        "fma.rn.bf16x2 pb6, pv12, pw24, pb6; fma.rn.bf16x2 pb7, pv13, pw25, pb7; fma.rn.bf16x2 pb8, pv14, pw26, pb8; fma.rn.bf16x2 pb9, pv15, pw27, pb9; fma.rn.bf16x2 pb10, pv16, pw28, pb10; fma.rn.bf16x2 pb11, pv17, pw29, pb11;\n"
        "fma.rn.bf16x2 pb0, pv12, pw30, pb0; fma.rn.bf16x2 pb1, pv13, pw31, pb1; fma.rn.bf16x2 pb2, pv14, pw32, pb2; fma.rn.bf16x2 pb3, pv15, pw33, pb3; fma.rn.bf16x2 pb4, pv16, pw34, pb4; fma.rn.bf16x2 pb5, pv17, pw35, pb5;\n"
        "fma.rn.bf16x2 pb6, pv18, pw30, pb6; fma.rn.bf16x2 pb7, pv19, pw31, pb7; fma.rn.bf16x2 pb8, pv20, pw32, pb8; fma.rn.bf16x2 pb9, pv21, pw33, pb9; fma.rn.bf16x2 pb10, pv22, pw34, pb10; fma.rn.bf16x2 pb11, pv23, pw35, pb11;\n"
        "B1:\n"
        "fma.rn.bf16x2 pb12, pv12, pw18, pc12; fma.rn.bf16x2 pb13, pv13, pw19, pc13; fma.rn.bf16x2 pb14, pv14, pw20, pc14; fma.rn.bf16x2 pb15, pv15, pw21, pc15; fma.rn.bf16x2 pb16, pv16, pw22, pc16; fma.rn.bf16x2 pb17, pv17, pw23, pc17;\n"
        "fma.rn.bf16x2 pb18, pv18, pw18, pc18; fma.rn.bf16x2 pb19, pv19, pw19, pc19; fma.rn.bf16x2 pb20, pv20, pw20, pc20; fma.rn.bf16x2 pb21, pv21, pw21, pc21; fma.rn.bf16x2 pb22, pv22, pw22, pc22; fma.rn.bf16x2 pb23, pv23, pw23, pc23;\n"
        "fma.rn.bf16x2 pb12, pv18, pw24, pb12; fma.rn.bf16x2 pb13, pv19, pw25, pb13; fma.rn.bf16x2 pb14, pv20, pw26, pb14; fma.rn.bf16x2 pb15, pv21, pw27, pb15; fma.rn.bf16x2 pb16, pv22, pw28, pb16; fma.rn.bf16x2 pb17, pv23, pw29, pb17;\n"
        "fma.rn.bf16x2 pb18, pv24, pw24, pb18; fma.rn.bf16x2 pb19, pv25, pw25, pb19; fma.rn.bf16x2 pb20, pv26, pw26, pb20; fma.rn.bf16x2 pb21, pv27, pw27, pb21; fma.rn.bf16x2 pb22, pv28, pw28, pb22; fma.rn.bf16x2 pb23, pv29, pw29, pb23;\n"
        "fma.rn.bf16x2 pb12, pv24, pw30, pb12; fma.rn.bf16x2 pb13, pv25, pw31, pb13; fma.rn.bf16x2 pb14, pv26, pw32, pb14; fma.rn.bf16x2 pb15, pv27, pw33, pb15; fma.rn.bf16x2 pb16, pv28, pw34, pb16; fma.rn.bf16x2 pb17, pv29, pw35, pb17;\n"
        "fma.rn.bf16x2 pb18, pv30, pw30, pb18; fma.rn.bf16x2 pb19, pv31, pw31, pb19; fma.rn.bf16x2 pb20, pv32, pw32, pb20; fma.rn.bf16x2 pb21, pv33, pw33, pb21; fma.rn.bf16x2 pb22, pv34, pw34, pb22; fma.rn.bf16x2 pb23, pv35, pw35, pb23;\n"
        "C0:\n"
        "wgmma.wait_group.sync.aligned 0;\n"
        "selp.f32 s0, d2, d0, po; selp.f32 s1, d3, d1, po;\n"
        "shfl.sync.bfly.b32 f0, s0, 4, 0x1f, 0xffffffff; shfl.sync.bfly.b32 f1, s1, 4, 0x1f, 0xffffffff;\n"
        "fma.rn.bf16x2 pc0, pv0, pw0, ps1; fma.rn.bf16x2 pc1, pv1, pw1, ps1; fma.rn.bf16x2 pc2, pv2, pw2, ps1; fma.rn.bf16x2 pc3, pv3, pw3, ps1; fma.rn.bf16x2 pc4, pv4, pw4, ps1; fma.rn.bf16x2 pc5, pv5, pw5, ps1;\n"
        "fma.rn.bf16x2 pc6, pv6, pw0, ps3; fma.rn.bf16x2 pc7, pv7, pw1, ps3; fma.rn.bf16x2 pc8, pv8, pw2, ps3; fma.rn.bf16x2 pc9, pv9, pw3, ps3; fma.rn.bf16x2 pc10, pv10, pw4, ps3; fma.rn.bf16x2 pc11, pv11, pw5, ps3;\n"
        "fma.rn.bf16x2 pc12, pv12, pw0, ps5; fma.rn.bf16x2 pc13, pv13, pw1, ps5; fma.rn.bf16x2 pc14, pv14, pw2, ps5; fma.rn.bf16x2 pc15, pv15, pw3, ps5; fma.rn.bf16x2 pc16, pv16, pw4, ps5; fma.rn.bf16x2 pc17, pv17, pw5, ps5;\n"
        "fma.rn.bf16x2 pc18, pv18, pw0, ps7; fma.rn.bf16x2 pc19, pv19, pw1, ps7; fma.rn.bf16x2 pc20, pv20, pw2, ps7; fma.rn.bf16x2 pc21, pv21, pw3, ps7; fma.rn.bf16x2 pc22, pv22, pw4, ps7; fma.rn.bf16x2 pc23, pv23, pw5, ps7;\n"
        "fma.rn.bf16x2 pc0, pv6, pw6, pc0; fma.rn.bf16x2 pc1, pv7, pw7, pc1; fma.rn.bf16x2 pc2, pv8, pw8, pc2; fma.rn.bf16x2 pc3, pv9, pw9, pc3; fma.rn.bf16x2 pc4, pv10, pw10, pc4; fma.rn.bf16x2 pc5, pv11, pw11, pc5;\n"
        "fma.rn.bf16x2 pc6, pv12, pw6, pc6; fma.rn.bf16x2 pc7, pv13, pw7, pc7; fma.rn.bf16x2 pc8, pv14, pw8, pc8; fma.rn.bf16x2 pc9, pv15, pw9, pc9; fma.rn.bf16x2 pc10, pv16, pw10, pc10; fma.rn.bf16x2 pc11, pv17, pw11, pc11;\n"
        "fma.rn.bf16x2 pc12, pv18, pw6, pc12; fma.rn.bf16x2 pc13, pv19, pw7, pc13; fma.rn.bf16x2 pc14, pv20, pw8, pc14; fma.rn.bf16x2 pc15, pv21, pw9, pc15; fma.rn.bf16x2 pc16, pv22, pw10, pc16; fma.rn.bf16x2 pc17, pv23, pw11, pc17;\n"
        "fma.rn.bf16x2 pc18, pv24, pw6, pc18; fma.rn.bf16x2 pc19, pv25, pw7, pc19; fma.rn.bf16x2 pc20, pv26, pw8, pc20; fma.rn.bf16x2 pc21, pv27, pw9, pc21; fma.rn.bf16x2 pc22, pv28, pw10, pc22; fma.rn.bf16x2 pc23, pv29, pw11, pc23;\n"
        "fma.rn.bf16x2 pc0, pv12, pw12, pc0; fma.rn.bf16x2 pc1, pv13, pw13, pc1; fma.rn.bf16x2 pc2, pv14, pw14, pc2; fma.rn.bf16x2 pc3, pv15, pw15, pc3; fma.rn.bf16x2 pc4, pv16, pw16, pc4; fma.rn.bf16x2 pc5, pv17, pw17, pc5;\n"
        "fma.rn.bf16x2 pc6, pv18, pw12, pc6; fma.rn.bf16x2 pc7, pv19, pw13, pc7; fma.rn.bf16x2 pc8, pv20, pw14, pc8; fma.rn.bf16x2 pc9, pv21, pw15, pc9; fma.rn.bf16x2 pc10, pv22, pw16, pc10; fma.rn.bf16x2 pc11, pv23, pw17, pc11;\n"
        "fma.rn.bf16x2 pc12, pv24, pw12, pc12; fma.rn.bf16x2 pc13, pv25, pw13, pc13; fma.rn.bf16x2 pc14, pv26, pw14, pc14; fma.rn.bf16x2 pc15, pv27, pw15, pc15; fma.rn.bf16x2 pc16, pv28, pw16, pc16; fma.rn.bf16x2 pc17, pv29, pw17, pc17;\n"
        "fma.rn.bf16x2 pc18, pv30, pw12, pc18; fma.rn.bf16x2 pc19, pv31, pw13, pc19; fma.rn.bf16x2 pc20, pv32, pw14, pc20; fma.rn.bf16x2 pc21, pv33, pw15, pc21; fma.rn.bf16x2 pc22, pv34, pw16, pc22; fma.rn.bf16x2 pc23, pv35, pw17, pc23;\n"
        "add.f32 s0, s0, f0; add.f32 s1, s1, f1; mul.f32 s0, s0, 0fBC2AAAAB;\n"
        "neg.f32 f0, s0; fma.rn.f32 f0, f0, s0, %13; fma.rn.f32 f0, s1, 0f3C2AAAAB, f0; max.f32 f0, f0, %13;\n"
        "rsqrt.approx.ftz.f32 f0, f0; mul.f32 f0, f0, %14; cvt.rn.bf16x2.f32 tt, f0, 0f00000000; mov.b32 f0, tt;\n"
        "mul.f32 f1, s0, kq; mul.f32 f1, f1, f0; cvt.rn.bf16x2.f32 tt, f1, f0; add.f32 us, us, s0; cvt.rn.bf16x2.f32 mm, us, us;\n"
        "add.u32 ad, %7, so; st.shared.v2.b32 [ad], {tt, mm};\n"
        "add.u32 ad, %6, so; ld.shared.v4.b32 {ps0,ps1,ps2,ps3}, [ad]; ld.shared.v4.b32 {ps4,ps5,ps6,ps7}, [ad+16];\n"
        "mbarrier.try_wait.parity.shared::cta.b64 pw, [t+231272], 0;\n"
        "N0:\n"
        "@!pw bra.uni SPIN;\n"
        "BACK:\n"
        "add.u32 ad, %0, so; ld.shared.v4.b32 {pv0,pv1,pv2,pv3}, [ad+0];\n"
        "add.u32 ad, %1, so; ld.shared.v2.b32 {pv4,pv5}, [ad+0];\n"
        "add.u32 ad, %0, so; ld.shared.v4.b32 {pv6,pv7,pv8,pv9}, [ad+192];\n"
        "add.u32 ad, %1, so; ld.shared.v2.b32 {pv10,pv11}, [ad+192];\n"
        "mov.b32 {xl, xh}, ps0; mov.b32 rr, {xl, xl}; mov.b32 mm, {xh, xh}; fma.rn.bf16x2 pa0, pa0, rr, mm; fma.rn.bf16x2 pa1, pa1, rr, mm; fma.rn.bf16x2 pa2, pa2, rr, mm; fma.rn.bf16x2 pa3, pa3, rr, mm; fma.rn.bf16x2 pa4, pa4, rr, mm; fma.rn.bf16x2 pa5, pa5, rr, mm;\n"
        "and.b32 m0, pa0, 0x7fff7fff; and.b32 m1, pa1, 0x7fff7fff; and.b32 m2, pa2, 0x7fff7fff; and.b32 m3, pa3, 0x7fff7fff; and.b32 m4, pa4, 0x7fff7fff; and.b32 m5, pa5, 0x7fff7fff;\n"
        "mad.lo.u32 y0, m0, 7, pa0; mad.lo.u32 y1, m1, 7, pa1; mad.lo.u32 y2, m2, 7, pa2; mad.lo.u32 y3, m3, 7, pa3; mad.lo.u32 y4, m4, 7, pa4; mad.lo.u32 y5, m5, 7, pa5;\n"
        "add.u32 ad, %2, so; st.shared.v4.b32 [ad+0], {y0,y1,y2,y3};\n"
        "add.u32 ad, %4, so; st.shared.v2.b32 [ad+0], {y4,y5};\n"
        "N1:\n"
        "add.u32 ad, %0, so; ld.shared.v4.b32 {pv12,pv13,pv14,pv15}, [ad+384];\n"
        "add.u32 ad, %1, so; ld.shared.v2.b32 {pv16,pv17}, [ad+384];\n"
        "add.u32 ad, %0, so; ld.shared.v4.b32 {pv18,pv19,pv20,pv21}, [ad+576];\n"
        "add.u32 ad, %1, so; ld.shared.v2.b32 {pv22,pv23}, [ad+576];\n"
        "mov.b32 {xl, xh}, ps2; mov.b32 rr, {xl, xl}; mov.b32 mm, {xh, xh}; fma.rn.bf16x2 pa6, pa6, rr, mm; fma.rn.bf16x2 pa7, pa7, rr, mm; fma.rn.bf16x2 pa8, pa8, rr, mm; fma.rn.bf16x2 pa9, pa9, rr, mm; fma.rn.bf16x2 pa10, pa10, rr, mm; fma.rn.bf16x2 pa11, pa11, rr, mm;\n"
        "and.b32 m0, pa6, 0x7fff7fff; and.b32 m1, pa7, 0x7fff7fff; and.b32 m2, pa8, 0x7fff7fff; and.b32 m3, pa9, 0x7fff7fff; and.b32 m4, pa10, 0x7fff7fff; and.b32 m5, pa11, 0x7fff7fff;\n"
        "mad.lo.u32 y0, m0, 7, pa6; mad.lo.u32 y1, m1, 7, pa7; mad.lo.u32 y2, m2, 7, pa8; mad.lo.u32 y3, m3, 7, pa9; mad.lo.u32 y4, m4, 7, pa10; mad.lo.u32 y5, m5, 7, pa11;\n"
        "add.u32 ad, %3, so; st.shared.v4.b32 [ad+0], {y0,y1,y2,y3};\n"
        "add.u32 ad, %5, so; st.shared.v2.b32 [ad+0], {y4,y5};\n"
        "N2:\n"
        "add.u32 ad, %0, so; ld.shared.v4.b32 {pv24,pv25,pv26,pv27}, [ad+768];\n"
        "add.u32 ad, %1, so; ld.shared.v2.b32 {pv28,pv29}, [ad+768];\n"
        "mov.b32 {xl, xh}, ps4; mov.b32 rr, {xl, xl}; mov.b32 mm, {xh, xh}; fma.rn.bf16x2 pa12, pa12, rr, mm; fma.rn.bf16x2 pa13, pa13, rr, mm; fma.rn.bf16x2 pa14, pa14, rr, mm; fma.rn.bf16x2 pa15, pa15, rr, mm; fma.rn.bf16x2 pa16, pa16, rr, mm; fma.rn.bf16x2 pa17, pa17, rr, mm;\n"
        "and.b32 m0, pa12, 0x7fff7fff; and.b32 m1, pa13, 0x7fff7fff; and.b32 m2, pa14, 0x7fff7fff; and.b32 m3, pa15, 0x7fff7fff; and.b32 m4, pa16, 0x7fff7fff; and.b32 m5, pa17, 0x7fff7fff;\n"
        "mad.lo.u32 y0, m0, 7, pa12; mad.lo.u32 y1, m1, 7, pa13; mad.lo.u32 y2, m2, 7, pa14; mad.lo.u32 y3, m3, 7, pa15; mad.lo.u32 y4, m4, 7, pa16; mad.lo.u32 y5, m5, 7, pa17;\n"
        "add.u32 ad, %2, so; st.shared.v4.b32 [ad+2048], {y0,y1,y2,y3};\n"
        "add.u32 ad, %4, so; st.shared.v2.b32 [ad+1024], {y4,y5};\n"
        "N3:\n"
        "add.u32 ad, %0, so; ld.shared.v4.b32 {pv30,pv31,pv32,pv33}, [ad+960];\n"
        "add.u32 ad, %1, so; ld.shared.v2.b32 {pv34,pv35}, [ad+960];\n"
        "mov.b32 {xl, xh}, ps6; mov.b32 rr, {xl, xl}; mov.b32 mm, {xh, xh}; fma.rn.bf16x2 pa18, pa18, rr, mm; fma.rn.bf16x2 pa19, pa19, rr, mm; fma.rn.bf16x2 pa20, pa20, rr, mm; fma.rn.bf16x2 pa21, pa21, rr, mm; fma.rn.bf16x2 pa22, pa22, rr, mm; fma.rn.bf16x2 pa23, pa23, rr, mm;\n"
        "and.b32 m0, pa18, 0x7fff7fff; and.b32 m1, pa19, 0x7fff7fff; and.b32 m2, pa20, 0x7fff7fff; and.b32 m3, pa21, 0x7fff7fff; and.b32 m4, pa22, 0x7fff7fff; and.b32 m5, pa23, 0x7fff7fff;\n"
        "mad.lo.u32 y0, m0, 7, pa18; mad.lo.u32 y1, m1, 7, pa19; mad.lo.u32 y2, m2, 7, pa20; mad.lo.u32 y3, m3, 7, pa21; mad.lo.u32 y4, m4, 7, pa22; mad.lo.u32 y5, m5, 7, pa23;\n"
        "add.u32 ad, %3, so; st.shared.v4.b32 [ad+2048], {y0,y1,y2,y3};\n"
        "add.u32 ad, %5, so; st.shared.v2.b32 [ad+1024], {y4,y5};\n"
        "add.u32 so, so, 26624; setp.eq.u32 pr, so, 79872; selp.u32 so, 0, so, pr;\n"
        "add.u32 t, t, 8; setp.lt.u32 pe, t, 256;\n"
        "@pe bra.uni LOOP;\n"
        "bra.uni DONE;\n"
        "SPIN: mov.u32 cnt, 0;\n"
        "SPINL:\n"
        "mbarrier.try_wait.parity.shared::cta.b64 pw, [t+231272], 0;\n"
        "@pw bra.uni BACK;\n"
        "add.u32 cnt, cnt, 1; setp.lt.u32 pw, cnt, 0x100000;\n"
        "@pw bra.uni SPINL;\n"
        "trap;\n"
        "RARE:\n"
        "ld.volatile.shared.u32 tt, [%6];\n"
        "mov.b32 pa0, tt; mov.b32 pa1, tt; mov.b32 pa2, tt; mov.b32 pa3, tt; mov.b32 pa4, tt; mov.b32 pa5, tt; mov.b32 pa6, tt; mov.b32 pa7, tt; mov.b32 pa8, tt; mov.b32 pa9, tt; mov.b32 pa10, tt; mov.b32 pa11, tt;\n"
        "mov.b32 pa12, tt; mov.b32 pa13, tt; mov.b32 pa14, tt; mov.b32 pa15, tt; mov.b32 pa16, tt; mov.b32 pa17, tt; mov.b32 pa18, tt; mov.b32 pa19, tt; mov.b32 pa20, tt; mov.b32 pa21, tt; mov.b32 pa22, tt; mov.b32 pa23, tt;\n"
        "mov.b32 pb0, tt; mov.b32 pb1, tt; mov.b32 pb2, tt; mov.b32 pb3, tt; mov.b32 pb4, tt; mov.b32 pb5, tt; mov.b32 pb6, tt; mov.b32 pb7, tt; mov.b32 pb8, tt; mov.b32 pb9, tt; mov.b32 pb10, tt; mov.b32 pb11, tt;\n"
        "mov.b32 pb12, tt; mov.b32 pb13, tt; mov.b32 pb14, tt; mov.b32 pb15, tt; mov.b32 pb16, tt; mov.b32 pb17, tt; mov.b32 pb18, tt; mov.b32 pb19, tt; mov.b32 pb20, tt; mov.b32 pb21, tt; mov.b32 pb22, tt; mov.b32 pb23, tt;\n"
        "mov.b32 pc0, tt; mov.b32 pc1, tt; mov.b32 pc2, tt; mov.b32 pc3, tt; mov.b32 pc4, tt; mov.b32 pc5, tt; mov.b32 pc6, tt; mov.b32 pc7, tt; mov.b32 pc8, tt; mov.b32 pc9, tt; mov.b32 pc10, tt; mov.b32 pc11, tt;\n"
        "mov.b32 pc12, tt; mov.b32 pc13, tt; mov.b32 pc14, tt; mov.b32 pc15, tt; mov.b32 pc16, tt; mov.b32 pc17, tt; mov.b32 pc18, tt; mov.b32 pc19, tt; mov.b32 pc20, tt; mov.b32 pc21, tt; mov.b32 pc22, tt; mov.b32 pc23, tt;\n"
        "mov.b32 ps0, tt; mov.b32 ps1, tt; mov.b32 ps2, tt; mov.b32 ps3, tt; mov.b32 ps4, tt; mov.b32 ps5, tt; mov.b32 ps6, tt; mov.b32 ps7, tt; mov.b32 pq0, tt; mov.b32 pq1, tt; mov.b32 pq2, tt; mov.b32 pq3, tt;\n"
        "ld.volatile.shared.v2.b32 {pw1, pw0}, [%6]; xor.b32 tt, tt, pw1;\n"
        "ld.volatile.shared.v2.b32 {pw3, pw2}, [%6]; xor.b32 tt, tt, pw3;\n"
        "ld.volatile.shared.v2.b32 {pw5, pw4}, [%6]; xor.b32 tt, tt, pw5;\n"
        "ld.volatile.shared.v2.b32 {pw7, pw6}, [%6]; xor.b32 tt, tt, pw7;\n"
        "ld.volatile.shared.v2.b32 {pw9, pw8}, [%6]; xor.b32 tt, tt, pw9;\n"
        "ld.volatile.shared.v2.b32 {pw11, pw10}, [%6]; xor.b32 tt, tt, pw11;\n"
        "ld.volatile.shared.v2.b32 {pw13, pw12}, [%6]; xor.b32 tt, tt, pw13;\n"
        "ld.volatile.shared.v2.b32 {pw15, pw14}, [%6]; xor.b32 tt, tt, pw15;\n"
        "ld.volatile.shared.v2.b32 {pw17, pw16}, [%6]; xor.b32 tt, tt, pw17;\n"
        "ld.volatile.shared.v2.b32 {pw19, pw18}, [%6]; xor.b32 tt, tt, pw19;\n"
        "ld.volatile.shared.v2.b32 {pw21, pw20}, [%6]; xor.b32 tt, tt, pw21;\n"
        "ld.volatile.shared.v2.b32 {pw23, pw22}, [%6]; xor.b32 tt, tt, pw23;\n"
        "ld.volatile.shared.v2.b32 {pw25, pw24}, [%6]; xor.b32 tt, tt, pw25;\n"
        "ld.volatile.shared.v2.b32 {pw27, pw26}, [%6]; xor.b32 tt, tt, pw27;\n"
        "ld.volatile.shared.v2.b32 {pw29, pw28}, [%6]; xor.b32 tt, tt, pw29;\n"
        "ld.volatile.shared.v2.b32 {pw31, pw30}, [%6]; xor.b32 tt, tt, pw31;\n"
        "ld.volatile.shared.v2.b32 {pw33, pw32}, [%6]; xor.b32 tt, tt, pw33;\n"
        "ld.volatile.shared.v2.b32 {pw35, pw34}, [%6]; xor.b32 tt, tt, pw35;\n"
        "ld.volatile.shared.v2.b32 {pw37, pw36}, [%6]; xor.b32 tt, tt, pw37;\n"
        "ld.volatile.shared.v2.b32 {pw39, pw38}, [%6]; xor.b32 tt, tt, pw39;\n"
        "ld.volatile.shared.v2.b32 {pw41, pw40}, [%6]; xor.b32 tt, tt, pw41;\n"
        "ld.volatile.shared.v2.b32 {pw43, pw42}, [%6]; xor.b32 tt, tt, pw43;\n"
        "ld.volatile.shared.v2.b32 {pw45, pw44}, [%6]; xor.b32 tt, tt, pw45;\n"
        "ld.volatile.shared.v2.b32 {pw47, pw46}, [%6]; xor.b32 tt, tt, pw47;\n"
        "ld.volatile.shared.v2.b32 {pw49, pw48}, [%6]; xor.b32 tt, tt, pw49;\n"
        "ld.volatile.shared.v2.b32 {pw51, pw50}, [%6]; xor.b32 tt, tt, pw51;\n"
        "ld.volatile.shared.v2.b32 {pw53, pw52}, [%6]; xor.b32 tt, tt, pw53;\n"
        "mov.b32 us, tt; setp.ne.u32 pw, %15, 7;\n"
        "wgmma.fence.sync.aligned;\n"
        "setp.eq.u32 pr, %15, 1000; @pr bra.uni B0;\n"
        "setp.eq.u32 pr, %15, 1001; @pr bra.uni B1;\n"
        "setp.eq.u32 pr, %15, 1002; @pr bra.uni C0;\n"
        "setp.eq.u32 pr, %15, 1003; @pr bra.uni N0;\n"
        "setp.eq.u32 pr, %15, 1004; @pr bra.uni N1;\n"
        "setp.eq.u32 pr, %15, 1005; @pr bra.uni N2;\n"
        "setp.eq.u32 pr, %15, 1006; @pr bra.uni N3;\n"
        "trap;\n"
        "DONE:\n"
        ASM_TRC("t")
        "fence.proxy.async.shared::cta;\n"
        "@pl mbarrier.arrive.shared::cta.b64 _, [t+231552];\n"
        "}\n"
        :: "r"(sb + SM_X + c.xoff[0]), "r"(sb + SM_X + c.xoff[1]), "r"(sb + SM_Y1 + c.yoff[0][0]), "r"(sb + SM_Y1 + c.yoff[0][1]),
           "r"(sb + SM_Y1 + c.yoff[1][0]), "r"(sb + SM_Y1 + c.yoff[1][1]), "r"(c.stat), "r"(c.own), "r"(c.lane),
           "l"(prm.sel[0]), "l"(prm.sel[1]), "l"(prm.sel[2]), "r"(prm.ydesc), "f"(LN_EPS_SCALED), "f"(RSTD_SCALE), "r"(prm.w1desc)
        : "memory");
}

__device__ __forceinline__ void produce(const Producer& c, const Params& prm) {
    uint32_t B[24], C[24];
    uint32_t st[8];
    uint32_t v[6][6];
    uint32_t ws[6];
#pragma unroll
    for (int u = 0; u < 6; u++) {
        ws[u] = c.w[0][u];
#pragma unroll
        for (int t = 1; t < 9; t++) ws[u] = bf2_add(ws[u], c.w[t][u]);
    }
    SMARK(2);
#pragma unroll 1
    for (int i = loop_init<0>(), so = loop_init<0>();; i++, so += SLOT_BYTES) {
        mbar_wait_c<0>(sb + SM_GO + i * 8);
        SMARK(4 + i);
        load_x(v, c, sb + SM_X + so);
        if (i == 2) break;
        if (so == 0) {
            const uint32_t p = bf2_add(bf2_fma(v[2][2], ws[2], bf2_fma(v[2][1], ws[1], bf2_mul(v[2][0], ws[0]))),
                                       bf2_fma(v[2][5], ws[5], bf2_fma(v[2][4], ws[4], bf2_mul(v[2][3], ws[3]))));
            float e = quad_sum(bf_lo(p) + bf_hi(p));
            e = (e + __shfl_xor_sync(0xffffffffu, e, 4)) * (-1.0f / CH);
            st[1] = st[3] = st[5] = st[7] = pack_bf2(e, e);
#pragma unroll
            for (int k = 0; k < NX; k++) sts32(c.own + k * SLOT_BYTES + 4, st[1]);
        } else {
            conv_row<1, 1>(B, C, v, c);
        }
        conv_row<0, 0>(C, st, v, c);
        fence_async_smem();
        asm volatile("bar.arrive %0, 160;" ::"r"(6 + i) : "memory");
    }
    asm volatile(".reg .b32 pw<54>, pb<24>, pc<24>, pv<36>, ps<8>;");
    hand_over<0>(c, B, C, v);
    asm volatile("mov.b32 ps1, %0; mov.b32 ps3, %1; mov.b32 ps5, %2; mov.b32 ps7, %3;" ::"r"(st[1]), "r"(st[3]), "r"(st[5]), "r"(st[7]));
    SMARK(7);
    produce_tiles(c, prm);
    mbar_arrive_if(sb + SM_YFULL + ROWS_PER_CTA * 8, c.lane == 0);
}

struct Duty {
    const char* g;
    const char* zeros;
    long long step;
    uint32_t s, bytes;
    int end, zero;
};
__device__ __forceinline__ Duty make_duty(const Params& prm, int wg, int w) {
    const RowCopy rc = row_copy(prm);
    Duty d;
    d.g = (w == 2 ? rc.y0 : rc.x0 + (w == 0 ? rc.cut0 : w == 1 ? 32 * 192 : 192)) +
          (wg + (w == 2 ? 0 : w < 2 ? 2 * NX : 2 * NX + L2_AHEAD)) * rc.stride;
    d.step = NX * rc.stride;
    d.s = wg * SLOT_BYTES + (w == 2 ? sb + SM_Y1 : sb + SM_X + (w == 0 ? rc.cut0 : XHALF_B));
    d.bytes = w >= 2 ? TILE_BYTES : XHALF_BYTES - (w == 0 ? rc.cut0 : rc.cut1);
    d.end = w == 2 ? ROWS_PER_CTA : w < 2 ? STEPS + 1 - 2 * NX : rc.last + 1 - 2 * NX - L2_AHEAD;
    d.zero = rc.last + 1 - 2 * NX;
    d.zeros = rc.zeros;
    return d;
}

static_assert(sb + SM_BAR == 230800 && sb + SM_YFULL == 231560 && sb + SM_GO == 231248 && SLOT_BYTES == 26624 && sb + SM_GAMMA == 229248 &&
              SM_BETA == SM_GAMMA + 768 && SM_W2 == 73728 && sb + SM_BUF3 == 187392 && BAR_W2 == 9 && BAR_W1B == 10, "layout");
__device__ __forceinline__ void consume(float (&acc)[2][2], uint32_t w1t, uint32_t yd, uint32_t wd, uint32_t own_slot, const Duty& d,
                                        uint32_t role, uint32_t lane, const Params& prm) {
    asm volatile(
        "{\n"
        ".reg .b32 z<32>, w<44>, p, a<4>, lo<2>, hi<2>, t, g, q<4>, dl, dh, n, so, c, tt, cnt, f0, f1;\n"
        ".reg .b16 xl, xh, xr;\n"
        ".reg .b64 ds<6>, wd, gp, src;\n"
        ".reg .pred pt, pf, pr, pw, pl, pe;\n"
        "setp.ne.b32 pt, 1, 0; setp.ne.b32 pf, 0, 0; setp.eq.u32 pl, %15, 0;\n"
        "mov.b32 c, 0x40D940D9;\n"
        "ldmatrix.sync.aligned.m8n8.x4.trans.shared.b16 {w0,w1,w2,w3}, [%4+0];\n"
        "ldmatrix.sync.aligned.m8n8.x4.trans.shared.b16 {w4,w5,w6,w7}, [%4+2048];\n"
        "ldmatrix.sync.aligned.m8n8.x4.trans.shared.b16 {w8,w9,w10,w11}, [%4+4096];\n"
        "ldmatrix.sync.aligned.m8n8.x4.trans.shared.b16 {w12,w13,w14,w15}, [%4+6144];\n"
        "ldmatrix.sync.aligned.m8n8.x4.trans.shared.b16 {w16,w17,w18,w19}, [%4+8192];\n"
        "ldmatrix.sync.aligned.m8n8.x4.trans.shared.b16 {w20,w21,w22,w23}, [%4+10240];\n"
        "shl.b32 f0, w0, 16; and.b32 f1, w0, 0xffff0000; cvt.rn.f16x2.f32 w0, f1, f0; shl.b32 f0, w1, 16; and.b32 f1, w1, 0xffff0000; cvt.rn.f16x2.f32 w1, f1, f0; shl.b32 f0, w2, 16; and.b32 f1, w2, 0xffff0000; cvt.rn.f16x2.f32 w2, f1, f0; shl.b32 f0, w3, 16; and.b32 f1, w3, 0xffff0000; cvt.rn.f16x2.f32 w3, f1, f0;\n"
        "stmatrix.sync.aligned.m8n8.x4.trans.shared.b16 [%4+0], {w0,w1,w2,w3};\n"
        "shl.b32 f0, w4, 16; and.b32 f1, w4, 0xffff0000; cvt.rn.f16x2.f32 w4, f1, f0; shl.b32 f0, w5, 16; and.b32 f1, w5, 0xffff0000; cvt.rn.f16x2.f32 w5, f1, f0; shl.b32 f0, w6, 16; and.b32 f1, w6, 0xffff0000; cvt.rn.f16x2.f32 w6, f1, f0; shl.b32 f0, w7, 16; and.b32 f1, w7, 0xffff0000; cvt.rn.f16x2.f32 w7, f1, f0;\n"
        "stmatrix.sync.aligned.m8n8.x4.trans.shared.b16 [%4+2048], {w4,w5,w6,w7};\n"
        "shl.b32 f0, w8, 16; and.b32 f1, w8, 0xffff0000; cvt.rn.f16x2.f32 w8, f1, f0; shl.b32 f0, w9, 16; and.b32 f1, w9, 0xffff0000; cvt.rn.f16x2.f32 w9, f1, f0; shl.b32 f0, w10, 16; and.b32 f1, w10, 0xffff0000; cvt.rn.f16x2.f32 w10, f1, f0; shl.b32 f0, w11, 16; and.b32 f1, w11, 0xffff0000; cvt.rn.f16x2.f32 w11, f1, f0;\n"
        "stmatrix.sync.aligned.m8n8.x4.trans.shared.b16 [%4+4096], {w8,w9,w10,w11};\n"
        "shl.b32 f0, w12, 16; and.b32 f1, w12, 0xffff0000; cvt.rn.f16x2.f32 w12, f1, f0; shl.b32 f0, w13, 16; and.b32 f1, w13, 0xffff0000; cvt.rn.f16x2.f32 w13, f1, f0; shl.b32 f0, w14, 16; and.b32 f1, w14, 0xffff0000; cvt.rn.f16x2.f32 w14, f1, f0; shl.b32 f0, w15, 16; and.b32 f1, w15, 0xffff0000; cvt.rn.f16x2.f32 w15, f1, f0;\n"
        "stmatrix.sync.aligned.m8n8.x4.trans.shared.b16 [%4+6144], {w12,w13,w14,w15};\n"
        "shl.b32 f0, w16, 16; and.b32 f1, w16, 0xffff0000; cvt.rn.f16x2.f32 w16, f1, f0; shl.b32 f0, w17, 16; and.b32 f1, w17, 0xffff0000; cvt.rn.f16x2.f32 w17, f1, f0; shl.b32 f0, w18, 16; and.b32 f1, w18, 0xffff0000; cvt.rn.f16x2.f32 w18, f1, f0; shl.b32 f0, w19, 16; and.b32 f1, w19, 0xffff0000; cvt.rn.f16x2.f32 w19, f1, f0;\n"
        "stmatrix.sync.aligned.m8n8.x4.trans.shared.b16 [%4+8192], {w16,w17,w18,w19};\n"
        "shl.b32 f0, w20, 16; and.b32 f1, w20, 0xffff0000; cvt.rn.f16x2.f32 w20, f1, f0; shl.b32 f0, w21, 16; and.b32 f1, w21, 0xffff0000; cvt.rn.f16x2.f32 w21, f1, f0; shl.b32 f0, w22, 16; and.b32 f1, w22, 0xffff0000; cvt.rn.f16x2.f32 w22, f1, f0; shl.b32 f0, w23, 16; and.b32 f1, w23, 0xffff0000; cvt.rn.f16x2.f32 w23, f1, f0;\n"
        "stmatrix.sync.aligned.m8n8.x4.trans.shared.b16 [%4+10240], {w20,w21,w22,w23};\n"
        "mov.u32 tt, 230880; mbarrier.try_wait.parity.shared::cta.b64 pw, [tt], 0;\n"
        "@!pw bra.uni SPINW;\n"
        "BACKW:\n"
        "ldmatrix.sync.aligned.m8n8.x4.trans.shared.b16 {z0,z1,z2,z3}, [%4+22528];\n"
        "ldmatrix.sync.aligned.m8n8.x4.trans.shared.b16 {w24,w25,w26,w27}, [%4+12288];\n"
        "ldmatrix.sync.aligned.m8n8.x4.trans.shared.b16 {w28,w29,w30,w31}, [%4+14336];\n"
        "ldmatrix.sync.aligned.m8n8.x4.trans.shared.b16 {w32,w33,w34,w35}, [%4+16384];\n"
        "ldmatrix.sync.aligned.m8n8.x4.trans.shared.b16 {w36,w37,w38,w39}, [%4+18432];\n"
        "ldmatrix.sync.aligned.m8n8.x4.trans.shared.b16 {w40,w41,w42,w43}, [%4+20480];\n"
        "shl.b32 f0, z0, 16; and.b32 f1, z0, 0xffff0000; cvt.rn.f16x2.f32 z0, f1, f0; shl.b32 f0, z1, 16; and.b32 f1, z1, 0xffff0000; cvt.rn.f16x2.f32 z1, f1, f0; shl.b32 f0, z2, 16; and.b32 f1, z2, 0xffff0000; cvt.rn.f16x2.f32 z2, f1, f0; shl.b32 f0, z3, 16; and.b32 f1, z3, 0xffff0000; cvt.rn.f16x2.f32 z3, f1, f0;\n"
        "stmatrix.sync.aligned.m8n8.x4.trans.shared.b16 [%4+22528], {z0,z1,z2,z3};\n"
        "shl.b32 f0, w24, 16; and.b32 f1, w24, 0xffff0000; cvt.rn.f16x2.f32 w24, f1, f0; shl.b32 f0, w25, 16; and.b32 f1, w25, 0xffff0000; cvt.rn.f16x2.f32 w25, f1, f0; shl.b32 f0, w26, 16; and.b32 f1, w26, 0xffff0000; cvt.rn.f16x2.f32 w26, f1, f0; shl.b32 f0, w27, 16; and.b32 f1, w27, 0xffff0000; cvt.rn.f16x2.f32 w27, f1, f0;\n"
        "stmatrix.sync.aligned.m8n8.x4.trans.shared.b16 [%4+12288], {w24,w25,w26,w27};\n"
        "shl.b32 f0, w28, 16; and.b32 f1, w28, 0xffff0000; cvt.rn.f16x2.f32 w28, f1, f0; shl.b32 f0, w29, 16; and.b32 f1, w29, 0xffff0000; cvt.rn.f16x2.f32 w29, f1, f0; shl.b32 f0, w30, 16; and.b32 f1, w30, 0xffff0000; cvt.rn.f16x2.f32 w30, f1, f0; shl.b32 f0, w31, 16; and.b32 f1, w31, 0xffff0000; cvt.rn.f16x2.f32 w31, f1, f0;\n"
        "stmatrix.sync.aligned.m8n8.x4.trans.shared.b16 [%4+14336], {w28,w29,w30,w31};\n"
        "shl.b32 f0, w32, 16; and.b32 f1, w32, 0xffff0000; cvt.rn.f16x2.f32 w32, f1, f0; shl.b32 f0, w33, 16; and.b32 f1, w33, 0xffff0000; cvt.rn.f16x2.f32 w33, f1, f0; shl.b32 f0, w34, 16; and.b32 f1, w34, 0xffff0000; cvt.rn.f16x2.f32 w34, f1, f0; shl.b32 f0, w35, 16; and.b32 f1, w35, 0xffff0000; cvt.rn.f16x2.f32 w35, f1, f0;\n"
        "stmatrix.sync.aligned.m8n8.x4.trans.shared.b16 [%4+16384], {w32,w33,w34,w35};\n"
        "shl.b32 f0, w36, 16; and.b32 f1, w36, 0xffff0000; cvt.rn.f16x2.f32 w36, f1, f0; shl.b32 f0, w37, 16; and.b32 f1, w37, 0xffff0000; cvt.rn.f16x2.f32 w37, f1, f0; shl.b32 f0, w38, 16; and.b32 f1, w38, 0xffff0000; cvt.rn.f16x2.f32 w38, f1, f0; shl.b32 f0, w39, 16; and.b32 f1, w39, 0xffff0000; cvt.rn.f16x2.f32 w39, f1, f0;\n"
        "stmatrix.sync.aligned.m8n8.x4.trans.shared.b16 [%4+18432], {w36,w37,w38,w39};\n"
        "shl.b32 f0, w40, 16; and.b32 f1, w40, 0xffff0000; cvt.rn.f16x2.f32 w40, f1, f0; shl.b32 f0, w41, 16; and.b32 f1, w41, 0xffff0000; cvt.rn.f16x2.f32 w41, f1, f0; shl.b32 f0, w42, 16; and.b32 f1, w42, 0xffff0000; cvt.rn.f16x2.f32 w42, f1, f0; shl.b32 f0, w43, 16; and.b32 f1, w43, 0xffff0000; cvt.rn.f16x2.f32 w43, f1, f0;\n"
        "stmatrix.sync.aligned.m8n8.x4.trans.shared.b16 [%4+20480], {w40,w41,w42,w43};\n"
        "fence.proxy.async.shared::cta;\n"
        ASM_SMARK
        "mov.b32 p, 0; mov.b32 t, 0; mov.b32 g, 0; mov.b32 a0, 0; mov.b32 a1, 0; mov.b32 a2, 0; mov.b32 a3, 0; mov.b32 lo0, 0; mov.b32 lo1, 0; mov.b32 hi0, 0; mov.b32 hi1, 0; mov.b32 q0, 0; mov.b32 q1, 0; mov.b32 q2, 0; mov.b32 q3, 0;\n"
        "mov.b32 z16, 0; mov.b32 z17, 0; mov.b32 z18, 0; mov.b32 z19, 0; mov.b32 z20, 0; mov.b32 z21, 0; mov.b32 z22, 0; mov.b32 z23, 0; mov.b32 z24, 0; mov.b32 z25, 0; mov.b32 z26, 0; mov.b32 z27, 0; mov.b32 z28, 0; mov.b32 z29, 0; mov.b32 z30, 0; mov.b32 z31, 0;\n"
        "mov.f32 %0, 0f00000000; mov.f32 %1, 0f00000000; mov.f32 %2, 0f00000000; mov.f32 %3, 0f00000000;\n"
        "mov.u32 n, 0; mov.u32 so, 0; mov.b64 gp, %8; mov.b64 wd, {%6, 0x40000040};\n"
        "mov.b64 ds0, %20; add.s64 ds1, ds0, 2; add.s64 ds2, ds0, 4; add.s64 ds3, ds0, 6; mov.b64 ds4, %21; add.s64 ds5, ds4, 2;\n"
        "setp.eq.u32 pr, %7, 53248; setp.lt.and.u32 pr, %13, 2, pr;\n"
        "@!pr bra.uni ROW5;\n"
        "mbarrier.try_wait.parity.shared::cta.b64 pw, [n+231552], 0;\n"
        "@!pw bra.uni SPIN5;\n"
        "BACK5:\n"
        "sub.s64 src, gp, %16; mov.u32 tt, 231288;\n"
        "elect.sync _|pr, 0xffffffff;\n"
        "@pr mbarrier.arrive.expect_tx.shared::cta.b64 _, [tt], %10;\n"
        "@pr cp.async.bulk.shared::cluster.global.mbarrier::complete_tx::bytes [%9], [src], %10, [tt];\n"
        "ROW5:\n"
        "mbarrier.try_wait.parity.shared::cta.b64 pw, [n+231560], 0;\n"
        "@!pw bra.uni SPIN0;\n"
        "BACK0:\n"
        ASM_TS
        "wgmma.fence.sync.aligned;\n"
        "wgmma.mma_async.sync.aligned.m64n64k16.f16.f16.f16 {z0,z1,z2,z3,z4,z5,z6,z7,z8,z9,z10,z11,z12,z13,z14,z15}, {w0,w1,w2,w3}, ds0, pf, 1, 1, 0;\n"
        "wgmma.mma_async.sync.aligned.m64n64k16.f16.f16.f16 {z0,z1,z2,z3,z4,z5,z6,z7,z8,z9,z10,z11,z12,z13,z14,z15}, {w4,w5,w6,w7}, ds1, pt, 1, 1, 0;\n"
        "wgmma.mma_async.sync.aligned.m64n64k16.f16.f16.f16 {z0,z1,z2,z3,z4,z5,z6,z7,z8,z9,z10,z11,z12,z13,z14,z15}, {w8,w9,w10,w11}, ds2, pt, 1, 1, 0;\n"
        "wgmma.fence.sync.aligned;\n"
        "wgmma.mma_async.sync.aligned.m64n64k16.f16.f16.f16 {z0,z1,z2,z3,z4,z5,z6,z7,z8,z9,z10,z11,z12,z13,z14,z15}, {w12,w13,w14,w15}, ds3, pt, 1, 1, 0;\n"
        "wgmma.mma_async.sync.aligned.m64n64k16.f16.f16.f16 {z0,z1,z2,z3,z4,z5,z6,z7,z8,z9,z10,z11,z12,z13,z14,z15}, {w16,w17,w18,w19}, ds4, pt, 1, 1, 0;\n"
        "wgmma.mma_async.sync.aligned.m64n64k16.f16.f16.f16 {z0,z1,z2,z3,z4,z5,z6,z7,z8,z9,z10,z11,z12,z13,z14,z15}, {w20,w21,w22,w23}, ds5, pt, 1, 1, 0;\n"
        "wgmma.commit_group.sync.aligned;\n"
        "setp.eq.u32 pr, so, %7;\n"
        "@pr bra.uni DUTY;\n"
        "TOP:\n"
        ASM_TRC("n")
        "wgmma.wait_group.sync.aligned 0;\n"
        "mov.b32 {xl, xh}, a2; tanh.approx.f16 xr, xh; cvt.u32.u16 hi0, xr; mul.rn.f16x2 a3, z31, p; fma.rn.f16x2 p, z0, z0, c; fma.rn.f16x2 q3, g, g, q3; fma.rn.f16x2 g, z28, t, z28; prmt.b32 t, lo1, hi1, 0x5410; tanh.approx.f16 xr, xl; cvt.u32.u16 lo0, xr;\n"
        "B31:\n"
        "mov.b32 {xl, xh}, a3; tanh.approx.f16 xr, xh; cvt.u32.u16 hi1, xr; mul.rn.f16x2 a0, z0, p; fma.rn.f16x2 p, z1, z1, c; fma.rn.f16x2 q2, g, g, q2; fma.rn.f16x2 g, z29, t, z29; prmt.b32 t, lo0, hi0, 0x5410; tanh.approx.f16 xr, xl; cvt.u32.u16 lo1, xr;\n"
        "B0:\n"
        "mov.b32 {xl, xh}, a0; tanh.approx.f16 xr, xh; cvt.u32.u16 hi0, xr; mul.rn.f16x2 a1, z1, p; fma.rn.f16x2 p, z2, z2, c; fma.rn.f16x2 q3, g, g, q3; fma.rn.f16x2 g, z30, t, z30; prmt.b32 t, lo1, hi1, 0x5410; tanh.approx.f16 xr, xl; cvt.u32.u16 lo0, xr;\n"
        "B1:\n"
        "mov.b32 {xl, xh}, a1; tanh.approx.f16 xr, xh; cvt.u32.u16 hi1, xr; mul.rn.f16x2 a2, z2, p; fma.rn.f16x2 p, z3, z3, c; fma.rn.f16x2 q2, g, g, q2; fma.rn.f16x2 g, z31, t, z31; prmt.b32 t, lo0, hi0, 0x5410; tanh.approx.f16 xr, xl; cvt.u32.u16 lo1, xr;\n"
        "B2:\n"
        "wgmma.fence.sync.aligned;\n"
        "wgmma.mma_async.sync.aligned.m64n64k16.f16.f16.f16 {z16,z17,z18,z19,z20,z21,z22,z23,z24,z25,z26,z27,z28,z29,z30,z31}, {w24,w25,w26,w27}, ds0, pf, 1, 1, 0;\n"
        "wgmma.mma_async.sync.aligned.m64n64k16.f16.f16.f16 {z16,z17,z18,z19,z20,z21,z22,z23,z24,z25,z26,z27,z28,z29,z30,z31}, {w28,w29,w30,w31}, ds1, pt, 1, 1, 0;\n"
        "wgmma.mma_async.sync.aligned.m64n64k16.f16.f16.f16 {z16,z17,z18,z19,z20,z21,z22,z23,z24,z25,z26,z27,z28,z29,z30,z31}, {w32,w33,w34,w35}, ds2, pt, 1, 1, 0;\n"
        "mov.b32 {xl, xh}, a2; tanh.approx.f16 xr, xh; cvt.u32.u16 hi0, xr; mul.rn.f16x2 a3, z3, p; fma.rn.f16x2 p, z4, z4, c; fma.rn.f16x2 q3, g, g, q3; fma.rn.f16x2 g, z0, t, z0; prmt.b32 t, lo1, hi1, 0x5410; tanh.approx.f16 xr, xl; cvt.u32.u16 lo0, xr;\n"
        "B3:\n"
        "mov.b32 {xl, xh}, a3; tanh.approx.f16 xr, xh; cvt.u32.u16 hi1, xr; mul.rn.f16x2 a0, z4, p; fma.rn.f16x2 p, z5, z5, c; fma.rn.f16x2 q0, g, g, q0; fma.rn.f16x2 g, z1, t, z1; prmt.b32 t, lo0, hi0, 0x5410; tanh.approx.f16 xr, xl; cvt.u32.u16 lo1, xr;\n"
        "B4:\n"
        "mov.b32 {xl, xh}, a0; tanh.approx.f16 xr, xh; cvt.u32.u16 hi0, xr; mul.rn.f16x2 a1, z5, p; fma.rn.f16x2 p, z6, z6, c; fma.rn.f16x2 q1, g, g, q1; fma.rn.f16x2 g, z2, t, z2; prmt.b32 t, lo1, hi1, 0x5410; tanh.approx.f16 xr, xl; cvt.u32.u16 lo0, xr;\n"
        "B5:\n"
        "wgmma.fence.sync.aligned;\n"
        "wgmma.mma_async.sync.aligned.m64n64k16.f16.f16.f16 {z16,z17,z18,z19,z20,z21,z22,z23,z24,z25,z26,z27,z28,z29,z30,z31}, {w36,w37,w38,w39}, ds3, pt, 1, 1, 0;\n"
        "wgmma.mma_async.sync.aligned.m64n64k16.f16.f16.f16 {z16,z17,z18,z19,z20,z21,z22,z23,z24,z25,z26,z27,z28,z29,z30,z31}, {w40,w41,w42,w43}, ds4, pt, 1, 1, 0;\n"
        "wgmma.mma_async.sync.aligned.m64n64k16.f16.f16.f16 {z16,z17,z18,z19,z20,z21,z22,z23,z24,z25,z26,z27,z28,z29,z30,z31}, wd, ds5, pt, 1, 1, 1, 0;\n"
        "wgmma.commit_group.sync.aligned;\n"
        "mov.b32 {xl, xh}, a1; tanh.approx.f16 xr, xh; cvt.u32.u16 hi1, xr; mul.rn.f16x2 a2, z6, p; fma.rn.f16x2 p, z7, z7, c; fma.rn.f16x2 q0, g, g, q0; fma.rn.f16x2 g, z3, t, z3; prmt.b32 t, lo0, hi0, 0x5410; tanh.approx.f16 xr, xl; cvt.u32.u16 lo1, xr;\n"
        "B6:\n"
        "add.u32 so, so, 26624; setp.eq.u32 pr, so, 79872; selp.u32 so, 0, so, pr;\n"
        "mov.b32 {xl, xh}, a2; tanh.approx.f16 xr, xh; cvt.u32.u16 hi0, xr; mul.rn.f16x2 a3, z7, p; fma.rn.f16x2 p, z8, z8, c; fma.rn.f16x2 q1, g, g, q1; fma.rn.f16x2 g, z4, t, z4; prmt.b32 t, lo1, hi1, 0x5410; tanh.approx.f16 xr, xl; cvt.u32.u16 lo0, xr;\n"
        "B7:\n"
        "shr.u32 tt, so, 4;\n"
        "mov.b64 {dl, dh}, ds0; add.u32 dl, tt, 74816; mov.b64 ds0, {dl, dh}; mov.b64 {dl, dh}, ds1; add.u32 dl, tt, 74818; mov.b64 ds1, {dl, dh}; mov.b64 {dl, dh}, ds2; add.u32 dl, tt, 74820; mov.b64 ds2, {dl, dh};\n"
        "mov.b32 {xl, xh}, a3; tanh.approx.f16 xr, xh; cvt.u32.u16 hi1, xr; mul.rn.f16x2 a0, z8, p; fma.rn.f16x2 p, z9, z9, c; fma.rn.f16x2 q0, g, g, q0; fma.rn.f16x2 g, z5, t, z5; prmt.b32 t, lo0, hi0, 0x5410; tanh.approx.f16 xr, xl; cvt.u32.u16 lo1, xr;\n"
        "B8:\n"
        "shr.u32 tt, so, 4;\n"
        "mov.b64 {dl, dh}, ds3; add.u32 dl, tt, 74822; mov.b64 ds3, {dl, dh}; mov.b64 {dl, dh}, ds4; add.u32 dl, tt, 75328; mov.b64 ds4, {dl, dh}; mov.b64 {dl, dh}, ds5; add.u32 dl, tt, 75330; mov.b64 ds5, {dl, dh};\n"
        "mov.b32 {xl, xh}, a0; tanh.approx.f16 xr, xh; cvt.u32.u16 hi0, xr; mul.rn.f16x2 a1, z9, p; fma.rn.f16x2 p, z10, z10, c; fma.rn.f16x2 q1, g, g, q1; fma.rn.f16x2 g, z6, t, z6; prmt.b32 t, lo1, hi1, 0x5410; tanh.approx.f16 xr, xl; cvt.u32.u16 lo0, xr;\n"
        "B9:\n"
        "mov.b32 {xl, xh}, a1; tanh.approx.f16 xr, xh; cvt.u32.u16 hi1, xr; mul.rn.f16x2 a2, z10, p; fma.rn.f16x2 p, z11, z11, c; fma.rn.f16x2 q0, g, g, q0; fma.rn.f16x2 g, z7, t, z7; prmt.b32 t, lo0, hi0, 0x5410; tanh.approx.f16 xr, xl; cvt.u32.u16 lo1, xr;\n"
        "B10:\n"
        "mov.b32 {xl, xh}, a2; tanh.approx.f16 xr, xh; cvt.u32.u16 hi0, xr; mul.rn.f16x2 a3, z11, p; fma.rn.f16x2 p, z12, z12, c; fma.rn.f16x2 q1, g, g, q1; fma.rn.f16x2 g, z8, t, z8; prmt.b32 t, lo1, hi1, 0x5410; tanh.approx.f16 xr, xl; cvt.u32.u16 lo0, xr;\n"
        "B11:\n"
        "mov.b32 {xl, xh}, a3; tanh.approx.f16 xr, xh; cvt.u32.u16 hi1, xr; mul.rn.f16x2 a0, z12, p; fma.rn.f16x2 p, z13, z13, c; fma.rn.f16x2 q0, g, g, q0; fma.rn.f16x2 g, z9, t, z9; prmt.b32 t, lo0, hi0, 0x5410; tanh.approx.f16 xr, xl; cvt.u32.u16 lo1, xr;\n"
        "B12:\n"
        "mov.b32 {xl, xh}, a0; tanh.approx.f16 xr, xh; cvt.u32.u16 hi0, xr; mul.rn.f16x2 a1, z13, p; fma.rn.f16x2 p, z14, z14, c; fma.rn.f16x2 q1, g, g, q1; fma.rn.f16x2 g, z10, t, z10; prmt.b32 t, lo1, hi1, 0x5410; tanh.approx.f16 xr, xl; cvt.u32.u16 lo0, xr;\n"
        "B13:\n"
        "mov.b32 {xl, xh}, a1; tanh.approx.f16 xr, xh; cvt.u32.u16 hi1, xr; mul.rn.f16x2 a2, z14, p; fma.rn.f16x2 p, z15, z15, c; fma.rn.f16x2 q0, g, g, q0; fma.rn.f16x2 g, z11, t, z11; prmt.b32 t, lo0, hi0, 0x5410; tanh.approx.f16 xr, xl; cvt.u32.u16 lo1, xr;\n"
        "B14:\n"
        "wgmma.wait_group.sync.aligned 0;\n"
        "cp.async.bulk.wait_group.read 0;\n"
        "@pl mbarrier.arrive.shared::cta.b64 _, [n+231296];\n"
        "mov.b32 {xl, xh}, a2; tanh.approx.f16 xr, xh; cvt.u32.u16 hi0, xr; mul.rn.f16x2 a3, z15, p; fma.rn.f16x2 p, z16, z16, c; fma.rn.f16x2 q1, g, g, q1; fma.rn.f16x2 g, z12, t, z12; prmt.b32 t, lo1, hi1, 0x5410; tanh.approx.f16 xr, xl; cvt.u32.u16 lo0, xr;\n"
        "B15:\n"
        "mov.b32 {xl, xh}, a3; tanh.approx.f16 xr, xh; cvt.u32.u16 hi1, xr; mul.rn.f16x2 a0, z16, p; fma.rn.f16x2 p, z17, z17, c; fma.rn.f16x2 q0, g, g, q0; fma.rn.f16x2 g, z13, t, z13; prmt.b32 t, lo0, hi0, 0x5410; tanh.approx.f16 xr, xl; cvt.u32.u16 lo1, xr;\n"
        "B16:\n"
        "mbarrier.try_wait.parity.shared::cta.b64 pw, [n+231568], 0;\n"
        "mov.b32 {xl, xh}, a0; tanh.approx.f16 xr, xh; cvt.u32.u16 hi0, xr; mul.rn.f16x2 a1, z17, p; fma.rn.f16x2 p, z18, z18, c; fma.rn.f16x2 q1, g, g, q1; fma.rn.f16x2 g, z14, t, z14; prmt.b32 t, lo1, hi1, 0x5410; tanh.approx.f16 xr, xl; cvt.u32.u16 lo0, xr;\n"
        "B17:\n"
        "mov.b32 {xl, xh}, a1; tanh.approx.f16 xr, xh; cvt.u32.u16 hi1, xr; mul.rn.f16x2 a2, z18, p; fma.rn.f16x2 p, z19, z19, c; fma.rn.f16x2 q0, g, g, q0; fma.rn.f16x2 g, z15, t, z15; prmt.b32 t, lo0, hi0, 0x5410; tanh.approx.f16 xr, xl; cvt.u32.u16 lo1, xr;\n"
        "B18:\n"
        "@!pw bra.uni SPIN;\n"
        "BACK:\n"
        "wgmma.fence.sync.aligned;\n"
        "wgmma.mma_async.sync.aligned.m64n64k16.f16.f16.f16 {z0,z1,z2,z3,z4,z5,z6,z7,z8,z9,z10,z11,z12,z13,z14,z15}, {w0,w1,w2,w3}, ds0, pf, 1, 1, 0;\n"
        "wgmma.mma_async.sync.aligned.m64n64k16.f16.f16.f16 {z0,z1,z2,z3,z4,z5,z6,z7,z8,z9,z10,z11,z12,z13,z14,z15}, {w4,w5,w6,w7}, ds1, pt, 1, 1, 0;\n"
        "wgmma.mma_async.sync.aligned.m64n64k16.f16.f16.f16 {z0,z1,z2,z3,z4,z5,z6,z7,z8,z9,z10,z11,z12,z13,z14,z15}, {w8,w9,w10,w11}, ds2, pt, 1, 1, 0;\n"
        "mov.b32 {xl, xh}, a2; tanh.approx.f16 xr, xh; cvt.u32.u16 hi0, xr; mul.rn.f16x2 a3, z19, p; fma.rn.f16x2 p, z20, z20, c; fma.rn.f16x2 q1, g, g, q1; fma.rn.f16x2 g, z16, t, z16; prmt.b32 t, lo1, hi1, 0x5410; tanh.approx.f16 xr, xl; cvt.u32.u16 lo0, xr;\n"
        "B19:\n"
        "mov.b32 {xl, xh}, a3; tanh.approx.f16 xr, xh; cvt.u32.u16 hi1, xr; mul.rn.f16x2 a0, z20, p; fma.rn.f16x2 p, z21, z21, c; fma.rn.f16x2 q2, g, g, q2; fma.rn.f16x2 g, z17, t, z17; prmt.b32 t, lo0, hi0, 0x5410; tanh.approx.f16 xr, xl; cvt.u32.u16 lo1, xr;\n"
        "B20:\n"
        "mov.b32 {xl, xh}, a0; tanh.approx.f16 xr, xh; cvt.u32.u16 hi0, xr; mul.rn.f16x2 a1, z21, p; fma.rn.f16x2 p, z22, z22, c; fma.rn.f16x2 q3, g, g, q3; fma.rn.f16x2 g, z18, t, z18; prmt.b32 t, lo1, hi1, 0x5410; tanh.approx.f16 xr, xl; cvt.u32.u16 lo0, xr;\n"
        "B21:\n"
        "wgmma.fence.sync.aligned;\n"
        "wgmma.mma_async.sync.aligned.m64n64k16.f16.f16.f16 {z0,z1,z2,z3,z4,z5,z6,z7,z8,z9,z10,z11,z12,z13,z14,z15}, {w12,w13,w14,w15}, ds3, pt, 1, 1, 0;\n"
        "wgmma.mma_async.sync.aligned.m64n64k16.f16.f16.f16 {z0,z1,z2,z3,z4,z5,z6,z7,z8,z9,z10,z11,z12,z13,z14,z15}, {w16,w17,w18,w19}, ds4, pt, 1, 1, 0;\n"
        "wgmma.mma_async.sync.aligned.m64n64k16.f16.f16.f16 {z0,z1,z2,z3,z4,z5,z6,z7,z8,z9,z10,z11,z12,z13,z14,z15}, {w20,w21,w22,w23}, ds5, pt, 1, 1, 0;\n"
        "wgmma.commit_group.sync.aligned;\n"
        "mov.b32 {xl, xh}, a1; tanh.approx.f16 xr, xh; cvt.u32.u16 hi1, xr; mul.rn.f16x2 a2, z22, p; fma.rn.f16x2 p, z23, z23, c; fma.rn.f16x2 q2, g, g, q2; fma.rn.f16x2 g, z19, t, z19; prmt.b32 t, lo0, hi0, 0x5410; tanh.approx.f16 xr, xl; cvt.u32.u16 lo1, xr;\n"
        "B22:\n"
        "mov.b32 {xl, xh}, a2; tanh.approx.f16 xr, xh; cvt.u32.u16 hi0, xr; mul.rn.f16x2 a3, z23, p; fma.rn.f16x2 p, z24, z24, c; fma.rn.f16x2 q3, g, g, q3; fma.rn.f16x2 g, z20, t, z20; prmt.b32 t, lo1, hi1, 0x5410; tanh.approx.f16 xr, xl; cvt.u32.u16 lo0, xr;\n"
        "B23:\n"
        "mov.b32 {xl, xh}, a3; tanh.approx.f16 xr, xh; cvt.u32.u16 hi1, xr; mul.rn.f16x2 a0, z24, p; fma.rn.f16x2 p, z25, z25, c; fma.rn.f16x2 q2, g, g, q2; fma.rn.f16x2 g, z21, t, z21; prmt.b32 t, lo0, hi0, 0x5410; tanh.approx.f16 xr, xl; cvt.u32.u16 lo1, xr;\n"
        "B24:\n"
        "mov.b32 {xl, xh}, a0; tanh.approx.f16 xr, xh; cvt.u32.u16 hi0, xr; mul.rn.f16x2 a1, z25, p; fma.rn.f16x2 p, z26, z26, c; fma.rn.f16x2 q3, g, g, q3; fma.rn.f16x2 g, z22, t, z22; prmt.b32 t, lo1, hi1, 0x5410; tanh.approx.f16 xr, xl; cvt.u32.u16 lo0, xr;\n"
        "B25:\n"
        "mov.b32 {xl, xh}, a1; tanh.approx.f16 xr, xh; cvt.u32.u16 hi1, xr; mul.rn.f16x2 a2, z26, p; fma.rn.f16x2 p, z27, z27, c; fma.rn.f16x2 q2, g, g, q2; fma.rn.f16x2 g, z23, t, z23; prmt.b32 t, lo0, hi0, 0x5410; tanh.approx.f16 xr, xl; cvt.u32.u16 lo1, xr;\n"
        "B26:\n"
        "mov.b32 {xl, xh}, a2; tanh.approx.f16 xr, xh; cvt.u32.u16 hi0, xr; mul.rn.f16x2 a3, z27, p; fma.rn.f16x2 p, z28, z28, c; fma.rn.f16x2 q3, g, g, q3; fma.rn.f16x2 g, z24, t, z24; prmt.b32 t, lo1, hi1, 0x5410; tanh.approx.f16 xr, xl; cvt.u32.u16 lo0, xr;\n"
        "B27:\n"
        "add.u32 n, n, 8; setp.lt.u32 pe, n, 256; setp.ne.and.u32 pe, so, %7, pe;\n"
        "mov.b32 {xl, xh}, a3; tanh.approx.f16 xr, xh; cvt.u32.u16 hi1, xr; mul.rn.f16x2 a0, z28, p; fma.rn.f16x2 p, z29, z29, c; fma.rn.f16x2 q2, g, g, q2; fma.rn.f16x2 g, z25, t, z25; prmt.b32 t, lo0, hi0, 0x5410; tanh.approx.f16 xr, xl; cvt.u32.u16 lo1, xr;\n"
        "B28:\n"
        "mov.b32 {xl, xh}, a0; tanh.approx.f16 xr, xh; cvt.u32.u16 hi0, xr; mul.rn.f16x2 a1, z29, p; fma.rn.f16x2 p, z30, z30, c; fma.rn.f16x2 q3, g, g, q3; fma.rn.f16x2 g, z26, t, z26; prmt.b32 t, lo1, hi1, 0x5410; tanh.approx.f16 xr, xl; cvt.u32.u16 lo0, xr;\n"
        "B29:\n"
        "mov.b32 {xl, xh}, a1; tanh.approx.f16 xr, xh; cvt.u32.u16 hi1, xr; mul.rn.f16x2 a2, z30, p; fma.rn.f16x2 p, z31, z31, c; fma.rn.f16x2 q2, g, g, q2; fma.rn.f16x2 g, z27, t, z27; prmt.b32 t, lo0, hi0, 0x5410; tanh.approx.f16 xr, xl; cvt.u32.u16 lo1, xr;\n"
        "@pe bra.uni TOP;\n"
        "setp.lt.u32 pe, n, 256;\n"
        "@pe bra.uni DUTY;\n"
        "bra.uni DONE;\n"
        "SPINW: mov.u32 cnt, 0;\n"
        "SPINWL:\n"
        "mov.u32 tt, 230880; mbarrier.try_wait.parity.shared::cta.b64 pw, [tt], 0;\n"
        "@pw bra.uni BACKW;\n"
        "add.u32 cnt, cnt, 1; setp.lt.u32 pw, cnt, 0x100000;\n"
        "@pw bra.uni SPINWL;\n"
        "trap;\n"
        "SPIN5: mov.u32 cnt, 0;\n"
        "SPIN5L:\n"
        "mbarrier.try_wait.parity.shared::cta.b64 pw, [n+231552], 0;\n"
        "@pw bra.uni BACK5;\n"
        "add.u32 cnt, cnt, 1; setp.lt.u32 pw, cnt, 0x100000;\n"
        "@pw bra.uni SPIN5L;\n"
        "trap;\n"
        "SPIN0: mov.u32 cnt, 0;\n"
        "SPIN0L:\n"
        "mbarrier.try_wait.parity.shared::cta.b64 pw, [n+231560], 0;\n"
        "@pw bra.uni BACK0;\n"
        "add.u32 cnt, cnt, 1; setp.lt.u32 pw, cnt, 0x100000;\n"
        "@pw bra.uni SPIN0L;\n"
        "trap;\n"
        "SPIN: mov.u32 cnt, 0;\n"
        "SPINL:\n"
        "mbarrier.try_wait.parity.shared::cta.b64 pw, [n+231568], 0;\n"
        "@pw bra.uni BACK;\n"
        "add.u32 cnt, cnt, 1; setp.lt.u32 pw, cnt, 0x100000;\n"
        "@pw bra.uni SPINL;\n"
        "trap;\n"
        "DUTY:\n"
        "setp.ge.s32 pr, n, %11;\n"
        "@pr bra.uni FLUSH;\n"
        "setp.ge.u32 pr, %13, 2;\n"
        "@pr bra.uni ROLE2;\n"
        "setp.ge.s32 pr, n, %12; selp.b64 src, %14, gp, pr; add.u32 tt, n, 231296;\n"
        "elect.sync _|pr, 0xffffffff;\n"
        "@pr mbarrier.arrive.expect_tx.shared::cta.b64 _, [tt], %10;\n"
        "@pr cp.async.bulk.shared::cluster.global.mbarrier::complete_tx::bytes [%9], [src], %10, [tt];\n"
        "bra.uni FLUSH;\n"
        "ROLE2:\n"
        "setp.eq.u32 pr, %13, 3;\n"
        "@pr bra.uni ROLE3;\n"
        "setp.ne.s32 pr, n, 192;\n"
        "@pr bra.uni NOFLAG;\n"
        "cp.async.bulk.wait_group 0;\n"
        "mov.u32 tt, 230784; ld.shared.u32 tt, [tt]; add.u32 tt, tt, 1;\n"
        "@pl st.relaxed.gpu.global.u32 [%22], tt;\n"
        "NOFLAG:\n"
        "setp.ne.s32 pr, n, 248;\n"
        "@pr bra.uni PARK;\n"
        "cp.async.bulk.wait_group 0;\n"
        "sub.s64 src, gp, %16; mov.u32 tt, 230824; mov.u32 cnt, 187392;\n"
        "elect.sync _|pr, 0xffffffff;\n"
        "@pr mbarrier.arrive.expect_tx.shared::cta.b64 _, [tt], 12288;\n"
        "@pr cp.async.bulk.shared::cluster.global.mbarrier::complete_tx::bytes [cnt], [src], 12288, [tt];\n"
        "PARK:\n"
        "setp.ge.s32 pr, n, 232;\n"
        "@pr bra.uni FLUSH;\n"
        "elect.sync _|pr, 0xffffffff;\n"
        "@pr cp.async.bulk.global.shared::cta.bulk_group [gp], [%9], 12288;\n"
        "@pr cp.async.bulk.commit_group;\n"
        "bra.uni FLUSH;\n"
        "ROLE3:\n"
        "setp.ne.s32 pr, n, 64;\n"
        "@pr bra.uni AHEAD;\n"
        "mov.u32 tt, 230872;\n"
        "elect.sync _|pr, 0xffffffff;\n"
        "@pr mbarrier.arrive.expect_tx.shared::cta.b64 _, [tt], 75264;\n"
        "mov.u32 cnt, 229248; @pr cp.async.bulk.shared::cluster.global.mbarrier::complete_tx::bytes [cnt], [%18], 768, [tt];\n"
        "mov.u32 cnt, 230016; @pr cp.async.bulk.shared::cluster.global.mbarrier::complete_tx::bytes [cnt], [%19], 768, [tt];\n"
        "mov.u32 cnt, 74752; @pr cp.async.bulk.tensor.2d.shared::cluster.global.mbarrier::complete_tx::bytes [cnt], [%17, {0, 0}], [tt];\n"
        "mov.u32 cnt, 87040; @pr cp.async.bulk.tensor.2d.shared::cluster.global.mbarrier::complete_tx::bytes [cnt], [%17, {0, 192}], [tt];\n"
        "mov.u32 cnt, 99328; @pr cp.async.bulk.tensor.2d.shared::cluster.global.mbarrier::complete_tx::bytes [cnt], [%17, {32, 0}], [tt];\n"
        "mov.u32 cnt, 111616; @pr cp.async.bulk.tensor.2d.shared::cluster.global.mbarrier::complete_tx::bytes [cnt], [%17, {32, 192}], [tt];\n"
        "mov.u32 cnt, 123904; @pr cp.async.bulk.tensor.2d.shared::cluster.global.mbarrier::complete_tx::bytes [cnt], [%17, {64, 0}], [tt];\n"
        "mov.u32 cnt, 136192; @pr cp.async.bulk.tensor.2d.shared::cluster.global.mbarrier::complete_tx::bytes [cnt], [%17, {64, 192}], [tt];\n"
        "AHEAD:\n"
        "elect.sync _|pr, 0xffffffff;\n"
        "@pr cp.async.bulk.prefetch.L2.global [gp], 12288;\n"
        "FLUSH:\n"
        "add.s64 gp, gp, %16;\n"
        "mov.b32 {xl, xh}, q0; cvt.f32.f16 f0, xl; cvt.f32.f16 f1, xh; add.f32 f0, f0, f1; add.f32 %0, %0, f0; mov.b32 q0, 0;\n"
        "mov.b32 {xl, xh}, q1; cvt.f32.f16 f0, xl; cvt.f32.f16 f1, xh; add.f32 f0, f0, f1; add.f32 %1, %1, f0; mov.b32 q1, 0;\n"
        "mov.b32 {xl, xh}, q2; cvt.f32.f16 f0, xl; cvt.f32.f16 f1, xh; add.f32 f0, f0, f1; add.f32 %2, %2, f0; mov.b32 q2, 0;\n"
        "mov.b32 {xl, xh}, q3; cvt.f32.f16 f0, xl; cvt.f32.f16 f1, xh; add.f32 f0, f0, f1; add.f32 %3, %3, f0; mov.b32 q3, 0;\n"
        "setp.ne.u32 pr, %5, 0;\n"
        "@pr bra.uni TOP;\n"
        "wgmma.wait_group.sync.aligned 0;\n"
        "wgmma.fence.sync.aligned;\n"
        "ld.volatile.shared.v2.b32 {lo0, hi0}, [so]; xor.b32 f0, f0, lo0;\n"
        "ld.volatile.shared.v2.b32 {lo1, hi1}, [so]; xor.b32 f0, f0, lo1;\n"
        "ld.volatile.shared.v2.b32 {q1, a0}, [so]; xor.b32 f0, f0, q1;\n"
        "ld.volatile.shared.v2.b32 {q2, a1}, [so]; xor.b32 f0, f0, q2;\n"
        "ld.volatile.shared.v2.b32 {q3, a2}, [so]; xor.b32 f0, f0, q3;\n"
        "ld.volatile.shared.v2.b32 {q0, a3}, [so]; xor.b32 f0, f0, q0;\n"
        "ld.volatile.shared.v2.b32 {t, g}, [so]; xor.b32 f0, f0, t;\n"
        "ld.volatile.shared.v2.b32 {p, f1}, [so]; xor.b32 f0, f0, p;\n"
        "add.f32 %0, %0, f0;\n"
        "setp.eq.u32 pr, n, 1000; @pr bra.uni B31;\n"
        "setp.eq.u32 pr, n, 1001; @pr bra.uni B0;\n"
        "setp.eq.u32 pr, n, 1002; @pr bra.uni B1;\n"
        "setp.eq.u32 pr, n, 1003; @pr bra.uni B2;\n"
        "setp.eq.u32 pr, n, 1004; @pr bra.uni B3;\n"
        "setp.eq.u32 pr, n, 1005; @pr bra.uni B4;\n"
        "setp.eq.u32 pr, n, 1006; @pr bra.uni B5;\n"
        "setp.eq.u32 pr, n, 1007; @pr bra.uni B6;\n"
        "setp.eq.u32 pr, n, 1008; @pr bra.uni B7;\n"
        "setp.eq.u32 pr, n, 1009; @pr bra.uni B8;\n"
        "setp.eq.u32 pr, n, 1010; @pr bra.uni B9;\n"
        "setp.eq.u32 pr, n, 1011; @pr bra.uni B10;\n"
        "setp.eq.u32 pr, n, 1012; @pr bra.uni B11;\n"
        "setp.eq.u32 pr, n, 1013; @pr bra.uni B12;\n"
        "setp.eq.u32 pr, n, 1014; @pr bra.uni B13;\n"
        "setp.eq.u32 pr, n, 1015; @pr bra.uni B14;\n"
        "setp.eq.u32 pr, n, 1016; @pr bra.uni B15;\n"
        "setp.eq.u32 pr, n, 1017; @pr bra.uni B16;\n"
        "setp.eq.u32 pr, n, 1018; @pr bra.uni B17;\n"
        "setp.eq.u32 pr, n, 1019; @pr bra.uni B18;\n"
        "setp.eq.u32 pr, n, 1020; @pr bra.uni B19;\n"
        "setp.eq.u32 pr, n, 1021; @pr bra.uni B20;\n"
        "setp.eq.u32 pr, n, 1022; @pr bra.uni B21;\n"
        "setp.eq.u32 pr, n, 1023; @pr bra.uni B22;\n"
        "setp.eq.u32 pr, n, 1024; @pr bra.uni B23;\n"
        "setp.eq.u32 pr, n, 1025; @pr bra.uni B24;\n"
        "setp.eq.u32 pr, n, 1026; @pr bra.uni B25;\n"
        "setp.eq.u32 pr, n, 1027; @pr bra.uni B26;\n"
        "setp.eq.u32 pr, n, 1028; @pr bra.uni B27;\n"
        "setp.eq.u32 pr, n, 1029; @pr bra.uni B28;\n"
        "setp.eq.u32 pr, n, 1030; @pr bra.uni B29;\n"
        "setp.eq.u32 pr, n, 1031; @pr bra.uni TOP;\n"
        "trap;\n"
        "DONE:\n"
        ASM_TRC("n")
        "mov.b32 {xl, xh}, a2; tanh.approx.f16 xr, xh; cvt.u32.u16 hi0, xr; mul.rn.f16x2 a3, z31, p; fma.rn.f16x2 q3, g, g, q3; fma.rn.f16x2 g, z28, t, z28; prmt.b32 t, lo1, hi1, 0x5410; tanh.approx.f16 xr, xl; cvt.u32.u16 lo0, xr;\n"
        "mov.b32 {xl, xh}, a3; tanh.approx.f16 xr, xh; cvt.u32.u16 hi1, xr; fma.rn.f16x2 q2, g, g, q2; fma.rn.f16x2 g, z29, t, z29; prmt.b32 t, lo0, hi0, 0x5410; tanh.approx.f16 xr, xl; cvt.u32.u16 lo1, xr;\n"
        "fma.rn.f16x2 q3, g, g, q3; fma.rn.f16x2 g, z30, t, z30; prmt.b32 t, lo1, hi1, 0x5410;\n"
        "fma.rn.f16x2 q2, g, g, q2; fma.rn.f16x2 g, z31, t, z31;\n"
        "fma.rn.f16x2 q3, g, g, q3;\n"
        "mov.b32 {xl, xh}, q0; cvt.f32.f16 f0, xl; cvt.f32.f16 f1, xh; add.f32 f0, f0, f1; add.f32 %0, %0, f0; mov.b32 q0, 0;\n"
        "mov.b32 {xl, xh}, q1; cvt.f32.f16 f0, xl; cvt.f32.f16 f1, xh; add.f32 f0, f0, f1; add.f32 %1, %1, f0; mov.b32 q1, 0;\n"
        "mov.b32 {xl, xh}, q2; cvt.f32.f16 f0, xl; cvt.f32.f16 f1, xh; add.f32 f0, f0, f1; add.f32 %2, %2, f0; mov.b32 q2, 0;\n"
        "mov.b32 {xl, xh}, q3; cvt.f32.f16 f0, xl; cvt.f32.f16 f1, xh; add.f32 f0, f0, f1; add.f32 %3, %3, f0; mov.b32 q3, 0;\n"
        "wgmma.wait_group.sync.aligned 0;\n"
        "}\n"
        : "=f"(acc[0][0]), "=f"(acc[0][1]), "=f"(acc[1][0]), "=f"(acc[1][1])
        : "r"(w1t), "r"(yd), "r"(wd), "r"(own_slot), "l"(d.g), "r"(d.s), "r"(d.bytes), "r"(8 * d.end), "r"(8 * d.zero), "r"(role),
          "l"(d.zeros), "r"(lane), "l"(d.step), "l"(&prm.w2_map), "l"(prm.gamma), "l"(prm.beta), "l"(prm.ydesc64[0]), "l"(prm.ydesc64[1]),
          "l"(prm.g->parked + fresh_cta())
        : "memory");
}

template <int M>
__device__ __forceinline__ void gemm1_t(uint32_t (&d)[16], const uint32_t* wa, uint32_t yd, uint32_t wd) {
    wg_fence();
    wgmma_n64_h_set<0>(d, wa, desc<1024, 1>(yd, 0));
#pragma unroll
    for (int kk = 1; kk < 5; kk++)
        wgmma_n64_h_acc<0>(d, wa + kk * 4, kk < 4 ? desc<1024, 1>(yd, kk * 32) : desc<512, 2>(yd, 8192 + (kk - 4) * 32));
    wgmma_n64_h_acc_ss(d, desc<1024, 1>(wd, M * 12288), desc<512, 2>(yd, 8192 + 32));
    wg_commit();
}

__device__ __forceinline__ void gelu_sumsq_f(const uint32_t (&d)[16], float (&acc)[2]) {
#pragma unroll
    for (int r = 0; r < 16; r++) {
        float lo, hi;
        h2_unpack(gelu2(d[r]), lo, hi);
        acc[r & 1] = fmaf(lo, lo, acc[r & 1]);
        acc[r & 1] = fmaf(hi, hi, acc[r & 1]);
    }
}
__device__ __forceinline__ void load_w1t(uint32_t (&wa)[2][24], int wg, int w, int lane) {
#pragma unroll
    for (int m = 0; m < 2; m++)
#pragma unroll
        for (int kk = 0; kk < 5; kk++) {
            const int q = lane >> 3, c = 16 * kk + 8 * (q >> 1) + (lane & 7), ck = 2 * w + (q & 1);
            ldsm4_t(wa[m] + kk * 4, sb + SM_W1 + (2 * wg + m) * 12288 + c * 128 + ((ck ^ (c & 7)) * 16));
        }
}
__device__ __forceinline__ unsigned long long* acc_word(const Params& prm, uint32_t epoch, uint32_t e) {
    return &prm.g->acc[epoch & 1][(e >> 2) * 32 + (e & 3)];
}
__device__ __forceinline__ void publish_fast(const Params& prm, const float (&acc)[2][2], uint32_t epoch, int wg, int w, int lane) {
    const bool m = lane & 2, h = lane & 1;
    const float a = (m ? acc[1][0] : acc[0][0]) + __shfl_xor_sync(0xffffffffu, m ? acc[0][0] : acc[1][0], 2);
    const float b = (m ? acc[1][1] : acc[0][1]) + __shfl_xor_sync(0xffffffffu, m ? acc[0][1] : acc[1][1], 2);
    const float v = (h ? b : a) + __shfl_xor_sync(0xffffffffu, h ? a : b, 1);
    const unsigned long long q = (__float2ull_rn(fminf(v, ACC_LIMIT) * 0x1p16f) << 8) + 1;
    asm volatile("red.relaxed.gpu.global.add.u64 [%0], %1;"
                 ::"l"(acc_word(prm, epoch, 128 * wg + 32 * (lane & 2) + 16 * w + (lane >> 2) + 8 * (lane & 1))), "l"(q) : "memory");
}
__device__ __forceinline__ void collect_fast(const unsigned long long* word, uint32_t ctas, float (&ss)[3]) {
    unsigned long long v[3];
    asm volatile(
        "{\n.reg .pred p;\n.reg .u32 n, lo, hi;\n.reg .b64 w;\nmov.u32 n, 0;\n"
        "POLL:\nld.relaxed.gpu.global.u64 %0, [%3];\nld.relaxed.gpu.global.u64 %1, [%3+8192];\nld.relaxed.gpu.global.u64 %2, [%3+16384];\n"
        "and.b64 w, %0, %1;\nand.b64 w, w, %2;\nmov.b64 {lo, hi}, w;\nand.b32 lo, lo, 255;\n"
        "setp.eq.u32 p, lo, %4;\nvote.sync.all.pred p, p, 0xffffffff;\n@p bra.uni POLL_DONE;\n"
        "add.u32 n, n, 1;\nsetp.lt.u32 p, n, 0x400000;\n@p bra.uni POLL;\ntrap;\nPOLL_DONE:\n}\n"
        : "=&l"(v[0]), "=&l"(v[1]), "=&l"(v[2]) : "l"(word), "r"(ctas) : "memory");
#pragma unroll
    for (int k = 0; k < 3; k++) ss[k] = __ull2float_rn(v[k] >> 8) * 0x1p-16f;
}
__device__ __forceinline__ void publish_sums(const float (&acc)[2][2], float* sums, unsigned int* counter, int wg, int w, int lane) {
#pragma unroll
    for (int m = 0; m < 2; m++)
#pragma unroll
        for (int h = 0; h < 2; h++) {
            const float v = quad_sum(acc[m][h]);
            if ((lane & 3) == 0) atomicAdd(sums + 64 * (2 * wg + m) + 16 * w + (lane >> 2) + 8 * h, v);
        }
    named_sync(1, 384);
    if (fresh_tid() == 0) asm volatile("red.release.gpu.global.add.u32 [%0], 1;" ::"l"(counter) : "memory");
}
__device__ __forceinline__ void grid_wait(const unsigned int* counter, unsigned int target) {
    if (fresh_tid() == 0) {
        unsigned int v, spins = 0;
        do {
            asm volatile("ld.acquire.gpu.global.u32 %0, [%1];" : "=r"(v) : "l"(counter) : "memory");
            if (++spins > (1u << 22)) __trap();
        } while ((int)(v - target) < 0);
    }
    __syncthreads();
}

struct Pass2 {
    uint32_t wg;
    uint32_t off;
    int step;
    uint32_t xs;
    uint32_t a_offs, xs_offs, bias_addr;
    uint32_t w;
    int last;
    const void* park;
};

static_assert(BAR_Y2FULL == 0 && BAR_XSFULL == 4 && BAR_TURN == 11 && BAR_ROWS == 51 && BAR_STAT == 54 &&
              sb + SM_RED + RED_SCALE * 4 == 230792, "layout");
__device__ __forceinline__ bool pass2_tiles(const Pass2& c, const Params& prm, uint32_t round) {
    uint32_t retry;
    asm volatile(
        "{\n"
        ".reg .b32 qa<24>, qz<32>, o<24>, g<16>, p<2>, a<4>, lo<2>, hi<2>, h<2>, osc, v<8>, r<24>, t<2>;\n"
        ".reg .b32 n, off, c, tt, ad, cnt, ybar, xbar, tbar, tpar, id;\n"
        ".reg .b16 xl, xh, xr;\n"
        ".reg .f32 f0, f1;\n"
        ".reg .b64 w1d, w2d, dt, gp, gq, pol;\n"
        ".reg .pred pt, pf, pr, pw, pl, pm, pz, pn;\n"
        "setp.ne.b32 pt, 1, 0; setp.ne.b32 pf, 0, 0; setp.eq.u32 pl, %10, 0; setp.eq.u32 pz, %1, 0;\n"
        "mov.b32 c, 0x40D940D9;\n"
        "mov.b64 w1d, {%1, 0x40000040}; mov.b64 w2d, {%2, 0x80000020};\n"
        "mad.lo.u32 ybar, %3, 8, 230800; mad.lo.u32 xbar, %3, 8, 230832; add.u32 id, %3, 2;\n"
        "mad.lo.u32 tbar, %3, 64, 230888; setp.eq.u32 pr, %3, 0; selp.u32 tpar, 1, 0, pr; mov.u32 tt, %laneid; setp.eq.u32 pn, tt, 0;\n"
        "mov.u32 n, -1; add.u32 off, %4, %9; mov.pred pm, pt; createpolicy.fractional.L2::evict_first.b64 pol, 1.0;\n"
        "mbarrier.try_wait.parity.shared::cta.b64 pw, [ybar], 0;\n"
        "@!pw bra.uni SPINY0;\n"
        "BACKY0:\n"
        "and.b32 t0, %6, 0xffff; shr.u32 t1, %6, 16;\n"
        "xor.b32 ad, t0, 0; add.u32 ad, ad, %5; ldmatrix.sync.aligned.m8n8.x4.shared.b16 {qa0,qa1,qa2,qa3}, [ad];\n"
        "xor.b32 ad, t0, 32; add.u32 ad, ad, %5; ldmatrix.sync.aligned.m8n8.x4.shared.b16 {qa4,qa5,qa6,qa7}, [ad];\n"
        "xor.b32 ad, t0, 64; add.u32 ad, ad, %5; ldmatrix.sync.aligned.m8n8.x4.shared.b16 {qa8,qa9,qa10,qa11}, [ad];\n"
        "xor.b32 ad, t0, 96; add.u32 ad, ad, %5; ldmatrix.sync.aligned.m8n8.x4.shared.b16 {qa12,qa13,qa14,qa15}, [ad];\n"
        "xor.b32 ad, t1, 0; add.u32 ad, ad, %5; ldmatrix.sync.aligned.m8n8.x4.shared.b16 {qa16,qa17,qa18,qa19}, [ad];\n"
        "xor.b32 ad, t1, 32; add.u32 ad, ad, %5; ldmatrix.sync.aligned.m8n8.x4.shared.b16 {qa20,qa21,qa22,qa23}, [ad];\n"
        "wgmma.fence.sync.aligned;\n"
        "add.s64 dt, w1d, 0; wgmma.mma_async.sync.aligned.m64n64k16.f16.f16.f16 {qz0,qz1,qz2,qz3,qz4,qz5,qz6,qz7,qz8,qz9,qz10,qz11,qz12,qz13,qz14,qz15}, {qa0,qa1,qa2,qa3}, dt, pf, 1, 1, 1;\n"
        "add.s64 dt, w1d, 128; wgmma.mma_async.sync.aligned.m64n64k16.f16.f16.f16 {qz0,qz1,qz2,qz3,qz4,qz5,qz6,qz7,qz8,qz9,qz10,qz11,qz12,qz13,qz14,qz15}, {qa4,qa5,qa6,qa7}, dt, pt, 1, 1, 1;\n"
        "add.s64 dt, w1d, 256; wgmma.mma_async.sync.aligned.m64n64k16.f16.f16.f16 {qz0,qz1,qz2,qz3,qz4,qz5,qz6,qz7,qz8,qz9,qz10,qz11,qz12,qz13,qz14,qz15}, {qa8,qa9,qa10,qa11}, dt, pt, 1, 1, 1;\n"
        "add.s64 dt, w1d, 384; wgmma.mma_async.sync.aligned.m64n64k16.f16.f16.f16 {qz0,qz1,qz2,qz3,qz4,qz5,qz6,qz7,qz8,qz9,qz10,qz11,qz12,qz13,qz14,qz15}, {qa12,qa13,qa14,qa15}, dt, pt, 1, 1, 1;\n"
        "add.s64 dt, w1d, 512; wgmma.mma_async.sync.aligned.m64n64k16.f16.f16.f16 {qz0,qz1,qz2,qz3,qz4,qz5,qz6,qz7,qz8,qz9,qz10,qz11,qz12,qz13,qz14,qz15}, {qa16,qa17,qa18,qa19}, dt, pt, 1, 1, 1;\n"
        "add.s64 dt, w1d, 640; wgmma.mma_async.sync.aligned.m64n64k16.f16.f16.f16 {qz0,qz1,qz2,qz3,qz4,qz5,qz6,qz7,qz8,qz9,qz10,qz11,qz12,qz13,qz14,qz15}, {qa20,qa21,qa22,qa23}, dt, pt, 1, 1, 1;\n"
        "wgmma.commit_group.sync.aligned;\n"
        "mov.b32 g0, 0; mov.b32 g1, 0; mov.b32 g2, 0; mov.b32 g3, 0; mov.b32 g4, 0; mov.b32 g5, 0; mov.b32 g6, 0; mov.b32 g7, 0; mov.b32 g8, 0; mov.b32 g9, 0; mov.b32 g10, 0; mov.b32 g11, 0; mov.b32 g12, 0; mov.b32 g13, 0; mov.b32 g14, 0; mov.b32 g15, 0; mov.b32 o0, 0; mov.b32 o1, 0; mov.b32 o2, 0; mov.b32 o3, 0; mov.b32 o4, 0; mov.b32 o5, 0; mov.b32 o6, 0; mov.b32 o7, 0; mov.b32 o8, 0; mov.b32 o9, 0; mov.b32 o10, 0; mov.b32 o11, 0; mov.b32 o12, 0; mov.b32 o13, 0; mov.b32 o14, 0; mov.b32 o15, 0; mov.b32 o16, 0; mov.b32 o17, 0; mov.b32 o18, 0; mov.b32 o19, 0; mov.b32 o20, 0; mov.b32 o21, 0; mov.b32 o22, 0; mov.b32 o23, 0;\n"
        "mov.b32 osc, 0;\n"
        "wgmma.wait_group.sync.aligned 0;\n"
        "fma.rn.f16x2 p0, qz0, qz0, c;\n"
        "mul.rn.f16x2 a0, qz0, p0; fma.rn.f16x2 p1, qz1, qz1, c;\n"
        "mov.b32 {xl, xh}, a0; tanh.approx.f16 xr, xl; cvt.u32.u16 lo0, xr; tanh.approx.f16 xr, xh; cvt.u32.u16 hi0, xr; mul.rn.f16x2 a1, qz1, p1; fma.rn.f16x2 p0, qz2, qz2, c;\n"
        "mov.b32 {xl, xh}, a1; tanh.approx.f16 xr, xl; cvt.u32.u16 lo1, xr; tanh.approx.f16 xr, xh; cvt.u32.u16 hi1, xr; mul.rn.f16x2 a2, qz2, p0; fma.rn.f16x2 p1, qz3, qz3, c; prmt.b32 h0, lo0, hi0, 0x5410;\n"
        "mov.b32 {xl, xh}, a2; tanh.approx.f16 xr, xl; cvt.u32.u16 lo0, xr; tanh.approx.f16 xr, xh; cvt.u32.u16 hi0, xr; mul.rn.f16x2 a3, qz3, p1; fma.rn.f16x2 p0, qz4, qz4, c; fma.rn.f16x2 g0, qz0, h0, qz0; prmt.b32 h1, lo1, hi1, 0x5410;\n"
        "mov.b32 {xl, xh}, a3; tanh.approx.f16 xr, xl; cvt.u32.u16 lo1, xr; tanh.approx.f16 xr, xh; cvt.u32.u16 hi1, xr; mul.rn.f16x2 a0, qz4, p0; fma.rn.f16x2 p1, qz5, qz5, c; fma.rn.f16x2 g1, qz1, h1, qz1; prmt.b32 h0, lo0, hi0, 0x5410;\n"
        "mov.b32 {xl, xh}, a0; tanh.approx.f16 xr, xl; cvt.u32.u16 lo0, xr; tanh.approx.f16 xr, xh; cvt.u32.u16 hi0, xr; mul.rn.f16x2 a1, qz5, p1; fma.rn.f16x2 p0, qz6, qz6, c; fma.rn.f16x2 g2, qz2, h0, qz2; prmt.b32 h1, lo1, hi1, 0x5410;\n"
        "mov.b32 {xl, xh}, a1; tanh.approx.f16 xr, xl; cvt.u32.u16 lo1, xr; tanh.approx.f16 xr, xh; cvt.u32.u16 hi1, xr; mul.rn.f16x2 a2, qz6, p0; fma.rn.f16x2 p1, qz7, qz7, c; fma.rn.f16x2 g3, qz3, h1, qz3; prmt.b32 h0, lo0, hi0, 0x5410;\n"
        "LOOP:\n"
        "wgmma.fence.sync.aligned;\n"
        "add.s64 dt, w1d, 768; wgmma.mma_async.sync.aligned.m64n64k16.f16.f16.f16 {qz16,qz17,qz18,qz19,qz20,qz21,qz22,qz23,qz24,qz25,qz26,qz27,qz28,qz29,qz30,qz31}, {qa0,qa1,qa2,qa3}, dt, pf, 1, 1, 1;\n"
        "add.s64 dt, w1d, 896; wgmma.mma_async.sync.aligned.m64n64k16.f16.f16.f16 {qz16,qz17,qz18,qz19,qz20,qz21,qz22,qz23,qz24,qz25,qz26,qz27,qz28,qz29,qz30,qz31}, {qa4,qa5,qa6,qa7}, dt, pt, 1, 1, 1;\n"
        "add.s64 dt, w1d, 1024; wgmma.mma_async.sync.aligned.m64n64k16.f16.f16.f16 {qz16,qz17,qz18,qz19,qz20,qz21,qz22,qz23,qz24,qz25,qz26,qz27,qz28,qz29,qz30,qz31}, {qa8,qa9,qa10,qa11}, dt, pt, 1, 1, 1;\n"
        "add.s64 dt, w1d, 1152; wgmma.mma_async.sync.aligned.m64n64k16.f16.f16.f16 {qz16,qz17,qz18,qz19,qz20,qz21,qz22,qz23,qz24,qz25,qz26,qz27,qz28,qz29,qz30,qz31}, {qa12,qa13,qa14,qa15}, dt, pt, 1, 1, 1;\n"
        "add.s64 dt, w1d, 1280; wgmma.mma_async.sync.aligned.m64n64k16.f16.f16.f16 {qz16,qz17,qz18,qz19,qz20,qz21,qz22,qz23,qz24,qz25,qz26,qz27,qz28,qz29,qz30,qz31}, {qa16,qa17,qa18,qa19}, dt, pt, 1, 1, 1;\n"
        "add.s64 dt, w1d, 1408; wgmma.mma_async.sync.aligned.m64n64k16.f16.f16.f16 {qz16,qz17,qz18,qz19,qz20,qz21,qz22,qz23,qz24,qz25,qz26,qz27,qz28,qz29,qz30,qz31}, {qa20,qa21,qa22,qa23}, dt, pt, 1, 1, 1;\n"
        "setp.lt.s32 pr, n, 0;\n"
        "@pr bra.uni FIRST;\n"
        "and.b32 tt, n, 1; mbarrier.try_wait.parity.shared::cta.b64 pw, [xbar], tt;\n"
        "@!pw bra.uni SPINX;\n"
        "BACKX:\n"
        "and.b32 ad, %7, 0xffff; add.u32 ad, ad, %5; ld.shared.v4.b32 {v0,v1,v2,v3}, [ad+0];\n"
        "shr.u32 ad, %7, 16; add.u32 ad, ad, %5; ld.shared.v4.b32 {v4,v5,v6,v7}, [ad+0];\n"
        "mov.b32 {xl, xh}, o0; cvt.f32.f16 f0, xl; cvt.f32.f16 f1, xh; cvt.rn.bf16x2.f32 tt, f1, f0; fma.rn.bf16x2 v0, tt, osc, v0;\n"
        "mov.b32 {xl, xh}, o2; cvt.f32.f16 f0, xl; cvt.f32.f16 f1, xh; cvt.rn.bf16x2.f32 tt, f1, f0; fma.rn.bf16x2 v1, tt, osc, v1;\n"
        "mov.b32 {xl, xh}, o4; cvt.f32.f16 f0, xl; cvt.f32.f16 f1, xh; cvt.rn.bf16x2.f32 tt, f1, f0; fma.rn.bf16x2 v2, tt, osc, v2;\n"
        "mov.b32 {xl, xh}, o6; cvt.f32.f16 f0, xl; cvt.f32.f16 f1, xh; cvt.rn.bf16x2.f32 tt, f1, f0; fma.rn.bf16x2 v3, tt, osc, v3;\n"
        "and.b32 ad, %7, 0xffff; add.u32 ad, ad, %5; st.shared.v4.b32 [ad+0], {v0,v1,v2,v3};\n"
        "and.b32 ad, %7, 0xffff; add.u32 ad, ad, %5; ld.shared.v4.b32 {v0,v1,v2,v3}, [ad+64];\n"
        "mov.b32 {xl, xh}, o1; cvt.f32.f16 f0, xl; cvt.f32.f16 f1, xh; cvt.rn.bf16x2.f32 tt, f1, f0; fma.rn.bf16x2 v4, tt, osc, v4;\n"
        "mov.b32 {xl, xh}, o3; cvt.f32.f16 f0, xl; cvt.f32.f16 f1, xh; cvt.rn.bf16x2.f32 tt, f1, f0; fma.rn.bf16x2 v5, tt, osc, v5;\n"
        "mov.b32 {xl, xh}, o5; cvt.f32.f16 f0, xl; cvt.f32.f16 f1, xh; cvt.rn.bf16x2.f32 tt, f1, f0; fma.rn.bf16x2 v6, tt, osc, v6;\n"
        "mov.b32 {xl, xh}, o7; cvt.f32.f16 f0, xl; cvt.f32.f16 f1, xh; cvt.rn.bf16x2.f32 tt, f1, f0; fma.rn.bf16x2 v7, tt, osc, v7;\n"
        "shr.u32 ad, %7, 16; add.u32 ad, ad, %5; st.shared.v4.b32 [ad+0], {v4,v5,v6,v7};\n"
        "shr.u32 ad, %7, 16; add.u32 ad, ad, %5; ld.shared.v4.b32 {v4,v5,v6,v7}, [ad+64];\n"
        "ld.shared.v4.b32 {o0,o1,o2,o3}, [%8+0];\n"
        "ld.shared.v4.b32 {o4,o5,o6,o7}, [%8+64];\n"
        "mov.b32 {xl, xh}, o8; cvt.f32.f16 f0, xl; cvt.f32.f16 f1, xh; cvt.rn.bf16x2.f32 tt, f1, f0; fma.rn.bf16x2 v0, tt, osc, v0;\n"
        "mov.b32 {xl, xh}, o10; cvt.f32.f16 f0, xl; cvt.f32.f16 f1, xh; cvt.rn.bf16x2.f32 tt, f1, f0; fma.rn.bf16x2 v1, tt, osc, v1;\n"
        "mov.b32 {xl, xh}, o12; cvt.f32.f16 f0, xl; cvt.f32.f16 f1, xh; cvt.rn.bf16x2.f32 tt, f1, f0; fma.rn.bf16x2 v2, tt, osc, v2;\n"
        "mov.b32 {xl, xh}, o14; cvt.f32.f16 f0, xl; cvt.f32.f16 f1, xh; cvt.rn.bf16x2.f32 tt, f1, f0; fma.rn.bf16x2 v3, tt, osc, v3;\n"
        "and.b32 ad, %7, 0xffff; add.u32 ad, ad, %5; st.shared.v4.b32 [ad+64], {v0,v1,v2,v3};\n"
        "and.b32 ad, %7, 0xffff; add.u32 ad, ad, %5; ld.shared.v4.b32 {v0,v1,v2,v3}, [ad+128];\n"
        "mov.b32 {xl, xh}, o9; cvt.f32.f16 f0, xl; cvt.f32.f16 f1, xh; cvt.rn.bf16x2.f32 tt, f1, f0; fma.rn.bf16x2 v4, tt, osc, v4;\n"
        "mov.b32 {xl, xh}, o11; cvt.f32.f16 f0, xl; cvt.f32.f16 f1, xh; cvt.rn.bf16x2.f32 tt, f1, f0; fma.rn.bf16x2 v5, tt, osc, v5;\n"
        "mov.b32 {xl, xh}, o13; cvt.f32.f16 f0, xl; cvt.f32.f16 f1, xh; cvt.rn.bf16x2.f32 tt, f1, f0; fma.rn.bf16x2 v6, tt, osc, v6;\n"
        "mov.b32 {xl, xh}, o15; cvt.f32.f16 f0, xl; cvt.f32.f16 f1, xh; cvt.rn.bf16x2.f32 tt, f1, f0; fma.rn.bf16x2 v7, tt, osc, v7;\n"
        "shr.u32 ad, %7, 16; add.u32 ad, ad, %5; st.shared.v4.b32 [ad+64], {v4,v5,v6,v7};\n"
        "shr.u32 ad, %7, 16; add.u32 ad, ad, %5; ld.shared.v4.b32 {v4,v5,v6,v7}, [ad+128];\n"
        "ld.shared.v4.b32 {o8,o9,o10,o11}, [%8+128];\n"
        "ld.shared.v4.b32 {o12,o13,o14,o15}, [%8+192];\n"
        "mov.b32 {xl, xh}, o16; cvt.f32.f16 f0, xl; cvt.f32.f16 f1, xh; cvt.rn.bf16x2.f32 tt, f1, f0; fma.rn.bf16x2 v0, tt, osc, v0;\n"
        "mov.b32 {xl, xh}, o18; cvt.f32.f16 f0, xl; cvt.f32.f16 f1, xh; cvt.rn.bf16x2.f32 tt, f1, f0; fma.rn.bf16x2 v1, tt, osc, v1;\n"
        "mov.b32 {xl, xh}, o20; cvt.f32.f16 f0, xl; cvt.f32.f16 f1, xh; cvt.rn.bf16x2.f32 tt, f1, f0; fma.rn.bf16x2 v2, tt, osc, v2;\n"
        "mov.b32 {xl, xh}, o22; cvt.f32.f16 f0, xl; cvt.f32.f16 f1, xh; cvt.rn.bf16x2.f32 tt, f1, f0; fma.rn.bf16x2 v3, tt, osc, v3;\n"
        "and.b32 ad, %7, 0xffff; add.u32 ad, ad, %5; st.shared.v4.b32 [ad+128], {v0,v1,v2,v3};\n"
        "mov.b32 {xl, xh}, o17; cvt.f32.f16 f0, xl; cvt.f32.f16 f1, xh; cvt.rn.bf16x2.f32 tt, f1, f0; fma.rn.bf16x2 v4, tt, osc, v4;\n"
        "mov.b32 {xl, xh}, o19; cvt.f32.f16 f0, xl; cvt.f32.f16 f1, xh; cvt.rn.bf16x2.f32 tt, f1, f0; fma.rn.bf16x2 v5, tt, osc, v5;\n"
        "mov.b32 {xl, xh}, o21; cvt.f32.f16 f0, xl; cvt.f32.f16 f1, xh; cvt.rn.bf16x2.f32 tt, f1, f0; fma.rn.bf16x2 v6, tt, osc, v6;\n"
        "mov.b32 {xl, xh}, o23; cvt.f32.f16 f0, xl; cvt.f32.f16 f1, xh; cvt.rn.bf16x2.f32 tt, f1, f0; fma.rn.bf16x2 v7, tt, osc, v7;\n"
        "shr.u32 ad, %7, 16; add.u32 ad, ad, %5; st.shared.v4.b32 [ad+128], {v4,v5,v6,v7};\n"
        "ld.shared.v4.b32 {o16,o17,o18,o19}, [%8+256];\n"
        "ld.shared.v4.b32 {o20,o21,o22,o23}, [%8+320];\n"
        "FIRST:\n"
        "@pz bra.uni B7;\n"
        "mov.b32 {xl, xh}, a2; tanh.approx.f16 xr, xl; cvt.u32.u16 lo0, xr; tanh.approx.f16 xr, xh; cvt.u32.u16 hi0, xr; mul.rn.f16x2 a3, qz7, p1; fma.rn.f16x2 p0, qz8, qz8, c; fma.rn.f16x2 g4, qz4, h0, qz4; prmt.b32 h1, lo1, hi1, 0x5410;\n"
        "B7:\n"
        "fence.proxy.async.shared::cta;\n"
        "add.u32 tt, id, 4;\n"
        "@pl bra.uni STORE;\n"
        "bar.arrive tt, 128;\n"
        "STOREB:\n"
        ASM_MARK
        "add.s32 n, n, 1; sub.u32 off, off, %9; setp.lt.s32 pm, n, %14;\n"
        "@pz bra.uni B10;\n"
        "mov.b32 {xl, xh}, a3; tanh.approx.f16 xr, xl; cvt.u32.u16 lo1, xr; tanh.approx.f16 xr, xh; cvt.u32.u16 hi1, xr; mul.rn.f16x2 a0, qz8, p0; fma.rn.f16x2 p1, qz9, qz9, c; fma.rn.f16x2 g5, qz5, h1, qz5; prmt.b32 h0, lo0, hi0, 0x5410;\n"
        "mov.b32 {xl, xh}, a0; tanh.approx.f16 xr, xl; cvt.u32.u16 lo0, xr; tanh.approx.f16 xr, xh; cvt.u32.u16 hi0, xr; mul.rn.f16x2 a1, qz9, p1; fma.rn.f16x2 p0, qz10, qz10, c; fma.rn.f16x2 g6, qz6, h0, qz6; prmt.b32 h1, lo1, hi1, 0x5410;\n"
        "mov.b32 {xl, xh}, a1; tanh.approx.f16 xr, xl; cvt.u32.u16 lo1, xr; tanh.approx.f16 xr, xh; cvt.u32.u16 hi1, xr; mul.rn.f16x2 a2, qz10, p0; fma.rn.f16x2 p1, qz11, qz11, c; fma.rn.f16x2 g7, qz7, h1, qz7; prmt.b32 h0, lo0, hi0, 0x5410;\n"
        "B10:\n"
        "setp.eq.s32 pr, n, 0;\n"
        "@pr bra.uni SPINR;\n"
        "BACKW0:\n"
        "wgmma.fence.sync.aligned;\n"
        "add.s64 dt, w2d, 0; wgmma.mma_async.sync.aligned.m64n96k16.f16.f16.f16 {o0,o1,o2,o3,o4,o5,o6,o7,o8,o9,o10,o11,o12,o13,o14,o15,o16,o17,o18,o19,o20,o21,o22,o23}, {g0,g1,g2,g3}, dt, pt, 1, 1, 1;\n"
        "add.s64 dt, w2d, 64; wgmma.mma_async.sync.aligned.m64n96k16.f16.f16.f16 {o0,o1,o2,o3,o4,o5,o6,o7,o8,o9,o10,o11,o12,o13,o14,o15,o16,o17,o18,o19,o20,o21,o22,o23}, {g4,g5,g6,g7}, dt, pt, 1, 1, 1;\n"
        "wgmma.commit_group.sync.aligned;\n"
        "@pz bra.uni B14;\n"
        "mov.b32 {xl, xh}, a2; tanh.approx.f16 xr, xl; cvt.u32.u16 lo0, xr; tanh.approx.f16 xr, xh; cvt.u32.u16 hi0, xr; mul.rn.f16x2 a3, qz11, p1; fma.rn.f16x2 p0, qz12, qz12, c; fma.rn.f16x2 g8, qz8, h0, qz8; prmt.b32 h1, lo1, hi1, 0x5410;\n"
        "mov.b32 {xl, xh}, a3; tanh.approx.f16 xr, xl; cvt.u32.u16 lo1, xr; tanh.approx.f16 xr, xh; cvt.u32.u16 hi1, xr; mul.rn.f16x2 a0, qz12, p0; fma.rn.f16x2 p1, qz13, qz13, c; fma.rn.f16x2 g9, qz9, h1, qz9; prmt.b32 h0, lo0, hi0, 0x5410;\n"
        "mov.b32 {xl, xh}, a0; tanh.approx.f16 xr, xl; cvt.u32.u16 lo0, xr; tanh.approx.f16 xr, xh; cvt.u32.u16 hi0, xr; mul.rn.f16x2 a1, qz13, p1; fma.rn.f16x2 p0, qz14, qz14, c; fma.rn.f16x2 g10, qz10, h0, qz10; prmt.b32 h1, lo1, hi1, 0x5410;\n"
        "mov.b32 {xl, xh}, a1; tanh.approx.f16 xr, xl; cvt.u32.u16 lo1, xr; tanh.approx.f16 xr, xh; cvt.u32.u16 hi1, xr; mul.rn.f16x2 a2, qz14, p0; fma.rn.f16x2 p1, qz15, qz15, c; fma.rn.f16x2 g11, qz11, h1, qz11; prmt.b32 h0, lo0, hi0, 0x5410;\n"
        "B14:\n"
        "wgmma.wait_group.sync.aligned 0;\n"
        "mad.lo.u32 tt, n, 8, tbar; mbarrier.try_wait.parity.shared::cta.b64 pw, [tt], tpar;\n"
        "@!pw bra.uni SPINT;\n"
        "BACKT:\n"
        "wgmma.fence.sync.aligned;\n"
        "add.s64 dt, w2d, 128; wgmma.mma_async.sync.aligned.m64n96k16.f16.f16.f16 {o0,o1,o2,o3,o4,o5,o6,o7,o8,o9,o10,o11,o12,o13,o14,o15,o16,o17,o18,o19,o20,o21,o22,o23}, {g8,g9,g10,g11}, dt, pt, 1, 1, 1;\n"
        "wgmma.commit_group.sync.aligned;\n"
        "@pz bra.uni B18;\n"
        "mov.b32 {xl, xh}, a2; tanh.approx.f16 xr, xl; cvt.u32.u16 lo0, xr; tanh.approx.f16 xr, xh; cvt.u32.u16 hi0, xr; mul.rn.f16x2 a3, qz15, p1; fma.rn.f16x2 p0, qz16, qz16, c; fma.rn.f16x2 g12, qz12, h0, qz12; prmt.b32 h1, lo1, hi1, 0x5410;\n"
        "mov.b32 {xl, xh}, a3; tanh.approx.f16 xr, xl; cvt.u32.u16 lo1, xr; tanh.approx.f16 xr, xh; cvt.u32.u16 hi1, xr; mul.rn.f16x2 a0, qz16, p0; fma.rn.f16x2 p1, qz17, qz17, c; fma.rn.f16x2 g13, qz13, h1, qz13; prmt.b32 h0, lo0, hi0, 0x5410;\n"
        "mov.b32 {xl, xh}, a0; tanh.approx.f16 xr, xl; cvt.u32.u16 lo0, xr; tanh.approx.f16 xr, xh; cvt.u32.u16 hi0, xr; mul.rn.f16x2 a1, qz17, p1; fma.rn.f16x2 p0, qz18, qz18, c; fma.rn.f16x2 g14, qz14, h0, qz14; prmt.b32 h1, lo1, hi1, 0x5410;\n"
        "mov.b32 {xl, xh}, a1; tanh.approx.f16 xr, xl; cvt.u32.u16 lo1, xr; tanh.approx.f16 xr, xh; cvt.u32.u16 hi1, xr; mul.rn.f16x2 a2, qz18, p0; fma.rn.f16x2 p1, qz19, qz19, c; fma.rn.f16x2 g15, qz15, h1, qz15; prmt.b32 h0, lo0, hi0, 0x5410;\n"
        "B18:\n"
        "wgmma.fence.sync.aligned;\n"
        "add.s64 dt, w2d, 192; wgmma.mma_async.sync.aligned.m64n96k16.f16.f16.f16 {o0,o1,o2,o3,o4,o5,o6,o7,o8,o9,o10,o11,o12,o13,o14,o15,o16,o17,o18,o19,o20,o21,o22,o23}, {g12,g13,g14,g15}, dt, pt, 1, 1, 1;\n"
        "add.s64 dt, w1d, 1536; wgmma.mma_async.sync.aligned.m64n64k16.f16.f16.f16 {qz0,qz1,qz2,qz3,qz4,qz5,qz6,qz7,qz8,qz9,qz10,qz11,qz12,qz13,qz14,qz15}, {qa0,qa1,qa2,qa3}, dt, pf, 1, 1, 1;\n"
        "add.s64 dt, w1d, 1664; wgmma.mma_async.sync.aligned.m64n64k16.f16.f16.f16 {qz0,qz1,qz2,qz3,qz4,qz5,qz6,qz7,qz8,qz9,qz10,qz11,qz12,qz13,qz14,qz15}, {qa4,qa5,qa6,qa7}, dt, pt, 1, 1, 1;\n"
        "add.s64 dt, w1d, 1792; wgmma.mma_async.sync.aligned.m64n64k16.f16.f16.f16 {qz0,qz1,qz2,qz3,qz4,qz5,qz6,qz7,qz8,qz9,qz10,qz11,qz12,qz13,qz14,qz15}, {qa8,qa9,qa10,qa11}, dt, pt, 1, 1, 1;\n"
        "wgmma.commit_group.sync.aligned;\n"
        "@pl bra.uni YLOAD;\n"
        "YLOADB:\n"
        "@pz bra.uni B22;\n"
        "mov.b32 {xl, xh}, a2; tanh.approx.f16 xr, xl; cvt.u32.u16 lo0, xr; tanh.approx.f16 xr, xh; cvt.u32.u16 hi0, xr; mul.rn.f16x2 a3, qz19, p1; fma.rn.f16x2 p0, qz20, qz20, c; fma.rn.f16x2 g0, qz16, h0, qz16; prmt.b32 h1, lo1, hi1, 0x5410;\n"
        "mov.b32 {xl, xh}, a3; tanh.approx.f16 xr, xl; cvt.u32.u16 lo1, xr; tanh.approx.f16 xr, xh; cvt.u32.u16 hi1, xr; mul.rn.f16x2 a0, qz20, p0; fma.rn.f16x2 p1, qz21, qz21, c; fma.rn.f16x2 g1, qz17, h1, qz17; prmt.b32 h0, lo0, hi0, 0x5410;\n"
        "mov.b32 {xl, xh}, a0; tanh.approx.f16 xr, xl; cvt.u32.u16 lo0, xr; tanh.approx.f16 xr, xh; cvt.u32.u16 hi0, xr; mul.rn.f16x2 a1, qz21, p1; fma.rn.f16x2 p0, qz22, qz22, c; fma.rn.f16x2 g2, qz18, h0, qz18; prmt.b32 h1, lo1, hi1, 0x5410;\n"
        "mov.b32 {xl, xh}, a1; tanh.approx.f16 xr, xl; cvt.u32.u16 lo1, xr; tanh.approx.f16 xr, xh; cvt.u32.u16 hi1, xr; mul.rn.f16x2 a2, qz22, p0; fma.rn.f16x2 p1, qz23, qz23, c; fma.rn.f16x2 g3, qz19, h1, qz19; prmt.b32 h0, lo0, hi0, 0x5410;\n"
        "B22:\n"
        "wgmma.fence.sync.aligned;\n"
        "add.s64 dt, w1d, 1920; wgmma.mma_async.sync.aligned.m64n64k16.f16.f16.f16 {qz0,qz1,qz2,qz3,qz4,qz5,qz6,qz7,qz8,qz9,qz10,qz11,qz12,qz13,qz14,qz15}, {qa12,qa13,qa14,qa15}, dt, pt, 1, 1, 1;\n"
        "add.s64 dt, w1d, 2048; wgmma.mma_async.sync.aligned.m64n64k16.f16.f16.f16 {qz0,qz1,qz2,qz3,qz4,qz5,qz6,qz7,qz8,qz9,qz10,qz11,qz12,qz13,qz14,qz15}, {qa16,qa17,qa18,qa19}, dt, pt, 1, 1, 1;\n"
        "add.s64 dt, w1d, 2176; wgmma.mma_async.sync.aligned.m64n64k16.f16.f16.f16 {qz0,qz1,qz2,qz3,qz4,qz5,qz6,qz7,qz8,qz9,qz10,qz11,qz12,qz13,qz14,qz15}, {qa20,qa21,qa22,qa23}, dt, pt, 1, 1, 1;\n"
        "wgmma.commit_group.sync.aligned;\n"
        "@pz bra.uni B26;\n"
        "mov.b32 {xl, xh}, a2; tanh.approx.f16 xr, xl; cvt.u32.u16 lo0, xr; tanh.approx.f16 xr, xh; cvt.u32.u16 hi0, xr; mul.rn.f16x2 a3, qz23, p1; fma.rn.f16x2 p0, qz24, qz24, c; fma.rn.f16x2 g4, qz20, h0, qz20; prmt.b32 h1, lo1, hi1, 0x5410;\n"
        "mov.b32 {xl, xh}, a3; tanh.approx.f16 xr, xl; cvt.u32.u16 lo1, xr; tanh.approx.f16 xr, xh; cvt.u32.u16 hi1, xr; mul.rn.f16x2 a0, qz24, p0; fma.rn.f16x2 p1, qz25, qz25, c; fma.rn.f16x2 g5, qz21, h1, qz21; prmt.b32 h0, lo0, hi0, 0x5410;\n"
        "mov.b32 {xl, xh}, a0; tanh.approx.f16 xr, xl; cvt.u32.u16 lo0, xr; tanh.approx.f16 xr, xh; cvt.u32.u16 hi0, xr; mul.rn.f16x2 a1, qz25, p1; fma.rn.f16x2 p0, qz26, qz26, c; fma.rn.f16x2 g6, qz22, h0, qz22; prmt.b32 h1, lo1, hi1, 0x5410;\n"
        "mov.b32 {xl, xh}, a1; tanh.approx.f16 xr, xl; cvt.u32.u16 lo1, xr; tanh.approx.f16 xr, xh; cvt.u32.u16 hi1, xr; mul.rn.f16x2 a2, qz26, p0; fma.rn.f16x2 p1, qz27, qz27, c; fma.rn.f16x2 g7, qz23, h1, qz23; prmt.b32 h0, lo0, hi0, 0x5410;\n"
        "B26:\n"
        "wgmma.wait_group.sync.aligned 2;\n"
        "wgmma.fence.sync.aligned;\n"
        "add.s64 dt, w2d, 256; wgmma.mma_async.sync.aligned.m64n96k16.f16.f16.f16 {o0,o1,o2,o3,o4,o5,o6,o7,o8,o9,o10,o11,o12,o13,o14,o15,o16,o17,o18,o19,o20,o21,o22,o23}, {g0,g1,g2,g3}, dt, pt, 1, 1, 1;\n"
        "add.s64 dt, w2d, 320; wgmma.mma_async.sync.aligned.m64n96k16.f16.f16.f16 {o0,o1,o2,o3,o4,o5,o6,o7,o8,o9,o10,o11,o12,o13,o14,o15,o16,o17,o18,o19,o20,o21,o22,o23}, {g4,g5,g6,g7}, dt, pt, 1, 1, 1;\n"
        "wgmma.commit_group.sync.aligned;\n"
        "@pz bra.uni B30;\n"
        "mov.b32 {xl, xh}, a2; tanh.approx.f16 xr, xl; cvt.u32.u16 lo0, xr; tanh.approx.f16 xr, xh; cvt.u32.u16 hi0, xr; mul.rn.f16x2 a3, qz27, p1; fma.rn.f16x2 p0, qz28, qz28, c; fma.rn.f16x2 g8, qz24, h0, qz24; prmt.b32 h1, lo1, hi1, 0x5410;\n"
        "mov.b32 {xl, xh}, a3; tanh.approx.f16 xr, xl; cvt.u32.u16 lo1, xr; tanh.approx.f16 xr, xh; cvt.u32.u16 hi1, xr; mul.rn.f16x2 a0, qz28, p0; fma.rn.f16x2 p1, qz29, qz29, c; fma.rn.f16x2 g9, qz25, h1, qz25; prmt.b32 h0, lo0, hi0, 0x5410;\n"
        "mov.b32 {xl, xh}, a0; tanh.approx.f16 xr, xl; cvt.u32.u16 lo0, xr; tanh.approx.f16 xr, xh; cvt.u32.u16 hi0, xr; mul.rn.f16x2 a1, qz29, p1; fma.rn.f16x2 p0, qz30, qz30, c; fma.rn.f16x2 g10, qz26, h0, qz26; prmt.b32 h1, lo1, hi1, 0x5410;\n"
        "mov.b32 {xl, xh}, a1; tanh.approx.f16 xr, xl; cvt.u32.u16 lo1, xr; tanh.approx.f16 xr, xh; cvt.u32.u16 hi1, xr; mul.rn.f16x2 a2, qz30, p0; fma.rn.f16x2 p1, qz31, qz31, c; fma.rn.f16x2 g11, qz27, h1, qz27; prmt.b32 h0, lo0, hi0, 0x5410;\n"
        "B30:\n"
        "wgmma.wait_group.sync.aligned 1;\n"
        "wgmma.fence.sync.aligned;\n"
        "add.s64 dt, w2d, 384; wgmma.mma_async.sync.aligned.m64n96k16.f16.f16.f16 {o0,o1,o2,o3,o4,o5,o6,o7,o8,o9,o10,o11,o12,o13,o14,o15,o16,o17,o18,o19,o20,o21,o22,o23}, {g8,g9,g10,g11}, dt, pt, 1, 1, 1;\n"
        "wgmma.commit_group.sync.aligned;\n"
        "@pz bra.uni B34;\n"
        "mov.b32 {xl, xh}, a2; tanh.approx.f16 xr, xl; cvt.u32.u16 lo0, xr; tanh.approx.f16 xr, xh; cvt.u32.u16 hi0, xr; mul.rn.f16x2 a3, qz31, p1; fma.rn.f16x2 p0, qz0, qz0, c; fma.rn.f16x2 g12, qz28, h0, qz28; prmt.b32 h1, lo1, hi1, 0x5410;\n"
        "mov.b32 {xl, xh}, a3; tanh.approx.f16 xr, xl; cvt.u32.u16 lo1, xr; tanh.approx.f16 xr, xh; cvt.u32.u16 hi1, xr; mul.rn.f16x2 a0, qz0, p0; fma.rn.f16x2 p1, qz1, qz1, c; fma.rn.f16x2 g13, qz29, h1, qz29; prmt.b32 h0, lo0, hi0, 0x5410;\n"
        "mov.b32 {xl, xh}, a0; tanh.approx.f16 xr, xl; cvt.u32.u16 lo0, xr; tanh.approx.f16 xr, xh; cvt.u32.u16 hi0, xr; mul.rn.f16x2 a1, qz1, p1; fma.rn.f16x2 p0, qz2, qz2, c; fma.rn.f16x2 g14, qz30, h0, qz30; prmt.b32 h1, lo1, hi1, 0x5410;\n"
        "mov.b32 {xl, xh}, a1; tanh.approx.f16 xr, xl; cvt.u32.u16 lo1, xr; tanh.approx.f16 xr, xh; cvt.u32.u16 hi1, xr; mul.rn.f16x2 a2, qz2, p0; fma.rn.f16x2 p1, qz3, qz3, c; fma.rn.f16x2 g15, qz31, h1, qz31; prmt.b32 h0, lo0, hi0, 0x5410;\n"
        "B34:\n"
        "wgmma.wait_group.sync.aligned 1;\n"
        "wgmma.fence.sync.aligned;\n"
        "add.s64 dt, w2d, 448; wgmma.mma_async.sync.aligned.m64n96k16.f16.f16.f16 {o0,o1,o2,o3,o4,o5,o6,o7,o8,o9,o10,o11,o12,o13,o14,o15,o16,o17,o18,o19,o20,o21,o22,o23}, {g12,g13,g14,g15}, dt, pt, 1, 1, 1;\n"
        "add.s64 dt, w1d, 2304; wgmma.mma_async.sync.aligned.m64n64k16.f16.f16.f16 {qz16,qz17,qz18,qz19,qz20,qz21,qz22,qz23,qz24,qz25,qz26,qz27,qz28,qz29,qz30,qz31}, {qa0,qa1,qa2,qa3}, dt, pf, 1, 1, 1;\n"
        "add.s64 dt, w1d, 2432; wgmma.mma_async.sync.aligned.m64n64k16.f16.f16.f16 {qz16,qz17,qz18,qz19,qz20,qz21,qz22,qz23,qz24,qz25,qz26,qz27,qz28,qz29,qz30,qz31}, {qa4,qa5,qa6,qa7}, dt, pt, 1, 1, 1;\n"
        "add.s64 dt, w1d, 2560; wgmma.mma_async.sync.aligned.m64n64k16.f16.f16.f16 {qz16,qz17,qz18,qz19,qz20,qz21,qz22,qz23,qz24,qz25,qz26,qz27,qz28,qz29,qz30,qz31}, {qa8,qa9,qa10,qa11}, dt, pt, 1, 1, 1;\n"
        "wgmma.commit_group.sync.aligned;\n"
        "@pz bra.uni B38;\n"
        "mov.b32 {xl, xh}, a2; tanh.approx.f16 xr, xl; cvt.u32.u16 lo0, xr; tanh.approx.f16 xr, xh; cvt.u32.u16 hi0, xr; mul.rn.f16x2 a3, qz3, p1; fma.rn.f16x2 p0, qz4, qz4, c; fma.rn.f16x2 g0, qz0, h0, qz0; prmt.b32 h1, lo1, hi1, 0x5410;\n"
        "mov.b32 {xl, xh}, a3; tanh.approx.f16 xr, xl; cvt.u32.u16 lo1, xr; tanh.approx.f16 xr, xh; cvt.u32.u16 hi1, xr; mul.rn.f16x2 a0, qz4, p0; fma.rn.f16x2 p1, qz5, qz5, c; fma.rn.f16x2 g1, qz1, h1, qz1; prmt.b32 h0, lo0, hi0, 0x5410;\n"
        "mov.b32 {xl, xh}, a0; tanh.approx.f16 xr, xl; cvt.u32.u16 lo0, xr; tanh.approx.f16 xr, xh; cvt.u32.u16 hi0, xr; mul.rn.f16x2 a1, qz5, p1; fma.rn.f16x2 p0, qz6, qz6, c; fma.rn.f16x2 g2, qz2, h0, qz2; prmt.b32 h1, lo1, hi1, 0x5410;\n"
        "mov.b32 {xl, xh}, a1; tanh.approx.f16 xr, xl; cvt.u32.u16 lo1, xr; tanh.approx.f16 xr, xh; cvt.u32.u16 hi1, xr; mul.rn.f16x2 a2, qz6, p0; fma.rn.f16x2 p1, qz7, qz7, c; fma.rn.f16x2 g3, qz3, h1, qz3; prmt.b32 h0, lo0, hi0, 0x5410;\n"
        "B38:\n"
        "wgmma.fence.sync.aligned;\n"
        "add.s64 dt, w1d, 2688; wgmma.mma_async.sync.aligned.m64n64k16.f16.f16.f16 {qz16,qz17,qz18,qz19,qz20,qz21,qz22,qz23,qz24,qz25,qz26,qz27,qz28,qz29,qz30,qz31}, {qa12,qa13,qa14,qa15}, dt, pt, 1, 1, 1;\n"
        "add.s64 dt, w1d, 2816; wgmma.mma_async.sync.aligned.m64n64k16.f16.f16.f16 {qz16,qz17,qz18,qz19,qz20,qz21,qz22,qz23,qz24,qz25,qz26,qz27,qz28,qz29,qz30,qz31}, {qa16,qa17,qa18,qa19}, dt, pt, 1, 1, 1;\n"
        "add.s64 dt, w1d, 2944; wgmma.mma_async.sync.aligned.m64n64k16.f16.f16.f16 {qz16,qz17,qz18,qz19,qz20,qz21,qz22,qz23,qz24,qz25,qz26,qz27,qz28,qz29,qz30,qz31}, {qa20,qa21,qa22,qa23}, dt, pt, 1, 1, 1;\n"
        "wgmma.commit_group.sync.aligned;\n"
        "and.pred pr, pl, pm;\n"
        "@pr bra.uni XPF;\n"
        "XPFB:\n"
        "@pz bra.uni B42;\n"
        "mov.b32 {xl, xh}, a2; tanh.approx.f16 xr, xl; cvt.u32.u16 lo0, xr; tanh.approx.f16 xr, xh; cvt.u32.u16 hi0, xr; mul.rn.f16x2 a3, qz7, p1; fma.rn.f16x2 p0, qz8, qz8, c; fma.rn.f16x2 g4, qz4, h0, qz4; prmt.b32 h1, lo1, hi1, 0x5410;\n"
        "mov.b32 {xl, xh}, a3; tanh.approx.f16 xr, xl; cvt.u32.u16 lo1, xr; tanh.approx.f16 xr, xh; cvt.u32.u16 hi1, xr; mul.rn.f16x2 a0, qz8, p0; fma.rn.f16x2 p1, qz9, qz9, c; fma.rn.f16x2 g5, qz5, h1, qz5; prmt.b32 h0, lo0, hi0, 0x5410;\n"
        "mov.b32 {xl, xh}, a0; tanh.approx.f16 xr, xl; cvt.u32.u16 lo0, xr; tanh.approx.f16 xr, xh; cvt.u32.u16 hi0, xr; mul.rn.f16x2 a1, qz9, p1; fma.rn.f16x2 p0, qz10, qz10, c; fma.rn.f16x2 g6, qz6, h0, qz6; prmt.b32 h1, lo1, hi1, 0x5410;\n"
        "mov.b32 {xl, xh}, a1; tanh.approx.f16 xr, xl; cvt.u32.u16 lo1, xr; tanh.approx.f16 xr, xh; cvt.u32.u16 hi1, xr; mul.rn.f16x2 a2, qz10, p0; fma.rn.f16x2 p1, qz11, qz11, c; fma.rn.f16x2 g7, qz7, h1, qz7; prmt.b32 h0, lo0, hi0, 0x5410;\n"
        "B42:\n"
        "wgmma.wait_group.sync.aligned 2;\n"
        "setp.eq.s32 pr, n, 0;\n"
        "@pr bra.uni SPINW1;\n"
        "BACKW1:\n"
        "wgmma.fence.sync.aligned;\n"
        "add.s64 dt, w2d, 512; wgmma.mma_async.sync.aligned.m64n96k16.f16.f16.f16 {o0,o1,o2,o3,o4,o5,o6,o7,o8,o9,o10,o11,o12,o13,o14,o15,o16,o17,o18,o19,o20,o21,o22,o23}, {g0,g1,g2,g3}, dt, pt, 1, 1, 1;\n"
        "add.s64 dt, w2d, 576; wgmma.mma_async.sync.aligned.m64n96k16.f16.f16.f16 {o0,o1,o2,o3,o4,o5,o6,o7,o8,o9,o10,o11,o12,o13,o14,o15,o16,o17,o18,o19,o20,o21,o22,o23}, {g4,g5,g6,g7}, dt, pt, 1, 1, 1;\n"
        "wgmma.commit_group.sync.aligned;\n"
        "@pz bra.uni B46;\n"
        "mov.b32 {xl, xh}, a2; tanh.approx.f16 xr, xl; cvt.u32.u16 lo0, xr; tanh.approx.f16 xr, xh; cvt.u32.u16 hi0, xr; mul.rn.f16x2 a3, qz11, p1; fma.rn.f16x2 p0, qz12, qz12, c; fma.rn.f16x2 g8, qz8, h0, qz8; prmt.b32 h1, lo1, hi1, 0x5410;\n"
        "mov.b32 {xl, xh}, a3; tanh.approx.f16 xr, xl; cvt.u32.u16 lo1, xr; tanh.approx.f16 xr, xh; cvt.u32.u16 hi1, xr; mul.rn.f16x2 a0, qz12, p0; fma.rn.f16x2 p1, qz13, qz13, c; fma.rn.f16x2 g9, qz9, h1, qz9; prmt.b32 h0, lo0, hi0, 0x5410;\n"
        "mov.b32 {xl, xh}, a0; tanh.approx.f16 xr, xl; cvt.u32.u16 lo0, xr; tanh.approx.f16 xr, xh; cvt.u32.u16 hi0, xr; mul.rn.f16x2 a1, qz13, p1; fma.rn.f16x2 p0, qz14, qz14, c; fma.rn.f16x2 g10, qz10, h0, qz10; prmt.b32 h1, lo1, hi1, 0x5410;\n"
        "mov.b32 {xl, xh}, a1; tanh.approx.f16 xr, xl; cvt.u32.u16 lo1, xr; tanh.approx.f16 xr, xh; cvt.u32.u16 hi1, xr; mul.rn.f16x2 a2, qz14, p0; fma.rn.f16x2 p1, qz15, qz15, c; fma.rn.f16x2 g11, qz11, h1, qz11; prmt.b32 h0, lo0, hi0, 0x5410;\n"
        "B46:\n"
        "wgmma.wait_group.sync.aligned 1;\n"
        "wgmma.fence.sync.aligned;\n"
        "add.s64 dt, w2d, 640; wgmma.mma_async.sync.aligned.m64n96k16.f16.f16.f16 {o0,o1,o2,o3,o4,o5,o6,o7,o8,o9,o10,o11,o12,o13,o14,o15,o16,o17,o18,o19,o20,o21,o22,o23}, {g8,g9,g10,g11}, dt, pt, 1, 1, 1;\n"
        "wgmma.commit_group.sync.aligned;\n"
        "mad.lo.u32 tt, n, 8, tbar;\n"
        "@pn mbarrier.arrive.shared::cta.b64 _, [tt+64];\n"
        "@pz bra.uni B50;\n"
        "mov.b32 {xl, xh}, a2; tanh.approx.f16 xr, xl; cvt.u32.u16 lo0, xr; tanh.approx.f16 xr, xh; cvt.u32.u16 hi0, xr; mul.rn.f16x2 a3, qz15, p1; fma.rn.f16x2 p0, qz16, qz16, c; fma.rn.f16x2 g12, qz12, h0, qz12; prmt.b32 h1, lo1, hi1, 0x5410;\n"
        "mov.b32 {xl, xh}, a3; tanh.approx.f16 xr, xl; cvt.u32.u16 lo1, xr; tanh.approx.f16 xr, xh; cvt.u32.u16 hi1, xr; mul.rn.f16x2 a0, qz16, p0; fma.rn.f16x2 p1, qz17, qz17, c; fma.rn.f16x2 g13, qz13, h1, qz13; prmt.b32 h0, lo0, hi0, 0x5410;\n"
        "mov.b32 {xl, xh}, a0; tanh.approx.f16 xr, xl; cvt.u32.u16 lo0, xr; tanh.approx.f16 xr, xh; cvt.u32.u16 hi0, xr; mul.rn.f16x2 a1, qz17, p1; fma.rn.f16x2 p0, qz18, qz18, c; fma.rn.f16x2 g14, qz14, h0, qz14; prmt.b32 h1, lo1, hi1, 0x5410;\n"
        "mov.b32 {xl, xh}, a1; tanh.approx.f16 xr, xl; cvt.u32.u16 lo1, xr; tanh.approx.f16 xr, xh; cvt.u32.u16 hi1, xr; mul.rn.f16x2 a2, qz18, p0; fma.rn.f16x2 p1, qz19, qz19, c; fma.rn.f16x2 g15, qz15, h1, qz15; prmt.b32 h0, lo0, hi0, 0x5410;\n"
        "B50:\n"
        "wgmma.wait_group.sync.aligned 1;\n"
        "wgmma.fence.sync.aligned;\n"
        "add.s64 dt, w2d, 704; wgmma.mma_async.sync.aligned.m64n96k16.f16.f16.f16 {o0,o1,o2,o3,o4,o5,o6,o7,o8,o9,o10,o11,o12,o13,o14,o15,o16,o17,o18,o19,o20,o21,o22,o23}, {g12,g13,g14,g15}, dt, pt, 1, 1, 1;\n"
        "add.s64 dt, w1d, 3072; wgmma.mma_async.sync.aligned.m64n64k16.f16.f16.f16 {qz0,qz1,qz2,qz3,qz4,qz5,qz6,qz7,qz8,qz9,qz10,qz11,qz12,qz13,qz14,qz15}, {qa0,qa1,qa2,qa3}, dt, pf, 1, 1, 1;\n"
        "add.s64 dt, w1d, 3200; wgmma.mma_async.sync.aligned.m64n64k16.f16.f16.f16 {qz0,qz1,qz2,qz3,qz4,qz5,qz6,qz7,qz8,qz9,qz10,qz11,qz12,qz13,qz14,qz15}, {qa4,qa5,qa6,qa7}, dt, pt, 1, 1, 1;\n"
        "add.s64 dt, w1d, 3328; wgmma.mma_async.sync.aligned.m64n64k16.f16.f16.f16 {qz0,qz1,qz2,qz3,qz4,qz5,qz6,qz7,qz8,qz9,qz10,qz11,qz12,qz13,qz14,qz15}, {qa8,qa9,qa10,qa11}, dt, pt, 1, 1, 1;\n"
        "wgmma.commit_group.sync.aligned;\n"
        "@pz bra.uni B54;\n"
        "mov.b32 {xl, xh}, a2; tanh.approx.f16 xr, xl; cvt.u32.u16 lo0, xr; tanh.approx.f16 xr, xh; cvt.u32.u16 hi0, xr; mul.rn.f16x2 a3, qz19, p1; fma.rn.f16x2 p0, qz20, qz20, c; fma.rn.f16x2 g0, qz16, h0, qz16; prmt.b32 h1, lo1, hi1, 0x5410;\n"
        "mov.b32 {xl, xh}, a3; tanh.approx.f16 xr, xl; cvt.u32.u16 lo1, xr; tanh.approx.f16 xr, xh; cvt.u32.u16 hi1, xr; mul.rn.f16x2 a0, qz20, p0; fma.rn.f16x2 p1, qz21, qz21, c; fma.rn.f16x2 g1, qz17, h1, qz17; prmt.b32 h0, lo0, hi0, 0x5410;\n"
        "mov.b32 {xl, xh}, a0; tanh.approx.f16 xr, xl; cvt.u32.u16 lo0, xr; tanh.approx.f16 xr, xh; cvt.u32.u16 hi0, xr; mul.rn.f16x2 a1, qz21, p1; fma.rn.f16x2 p0, qz22, qz22, c; fma.rn.f16x2 g2, qz18, h0, qz18; prmt.b32 h1, lo1, hi1, 0x5410;\n"
        "mov.b32 {xl, xh}, a1; tanh.approx.f16 xr, xl; cvt.u32.u16 lo1, xr; tanh.approx.f16 xr, xh; cvt.u32.u16 hi1, xr; mul.rn.f16x2 a2, qz22, p0; fma.rn.f16x2 p1, qz23, qz23, c; fma.rn.f16x2 g3, qz19, h1, qz19; prmt.b32 h0, lo0, hi0, 0x5410;\n"
        "B54:\n"
        "wgmma.fence.sync.aligned;\n"
        "add.s64 dt, w1d, 3456; wgmma.mma_async.sync.aligned.m64n64k16.f16.f16.f16 {qz0,qz1,qz2,qz3,qz4,qz5,qz6,qz7,qz8,qz9,qz10,qz11,qz12,qz13,qz14,qz15}, {qa12,qa13,qa14,qa15}, dt, pt, 1, 1, 1;\n"
        "add.s64 dt, w1d, 3584; wgmma.mma_async.sync.aligned.m64n64k16.f16.f16.f16 {qz0,qz1,qz2,qz3,qz4,qz5,qz6,qz7,qz8,qz9,qz10,qz11,qz12,qz13,qz14,qz15}, {qa16,qa17,qa18,qa19}, dt, pt, 1, 1, 1;\n"
        "add.s64 dt, w1d, 3712; wgmma.mma_async.sync.aligned.m64n64k16.f16.f16.f16 {qz0,qz1,qz2,qz3,qz4,qz5,qz6,qz7,qz8,qz9,qz10,qz11,qz12,qz13,qz14,qz15}, {qa20,qa21,qa22,qa23}, dt, pt, 1, 1, 1;\n"
        "wgmma.commit_group.sync.aligned;\n"
        "@pz bra.uni B58;\n"
        "mov.b32 {xl, xh}, a2; tanh.approx.f16 xr, xl; cvt.u32.u16 lo0, xr; tanh.approx.f16 xr, xh; cvt.u32.u16 hi0, xr; mul.rn.f16x2 a3, qz23, p1; fma.rn.f16x2 p0, qz24, qz24, c; fma.rn.f16x2 g4, qz20, h0, qz20; prmt.b32 h1, lo1, hi1, 0x5410;\n"
        "mov.b32 {xl, xh}, a3; tanh.approx.f16 xr, xl; cvt.u32.u16 lo1, xr; tanh.approx.f16 xr, xh; cvt.u32.u16 hi1, xr; mul.rn.f16x2 a0, qz24, p0; fma.rn.f16x2 p1, qz25, qz25, c; fma.rn.f16x2 g5, qz21, h1, qz21; prmt.b32 h0, lo0, hi0, 0x5410;\n"
        "mov.b32 {xl, xh}, a0; tanh.approx.f16 xr, xl; cvt.u32.u16 lo0, xr; tanh.approx.f16 xr, xh; cvt.u32.u16 hi0, xr; mul.rn.f16x2 a1, qz25, p1; fma.rn.f16x2 p0, qz26, qz26, c; fma.rn.f16x2 g6, qz22, h0, qz22; prmt.b32 h1, lo1, hi1, 0x5410;\n"
        "mov.b32 {xl, xh}, a1; tanh.approx.f16 xr, xl; cvt.u32.u16 lo1, xr; tanh.approx.f16 xr, xh; cvt.u32.u16 hi1, xr; mul.rn.f16x2 a2, qz26, p0; fma.rn.f16x2 p1, qz27, qz27, c; fma.rn.f16x2 g7, qz23, h1, qz23; prmt.b32 h0, lo0, hi0, 0x5410;\n"
        "B58:\n"
        "wgmma.wait_group.sync.aligned 2;\n"
        "wgmma.fence.sync.aligned;\n"
        "add.s64 dt, w2d, 768; wgmma.mma_async.sync.aligned.m64n96k16.f16.f16.f16 {o0,o1,o2,o3,o4,o5,o6,o7,o8,o9,o10,o11,o12,o13,o14,o15,o16,o17,o18,o19,o20,o21,o22,o23}, {g0,g1,g2,g3}, dt, pt, 1, 1, 1;\n"
        "add.s64 dt, w2d, 832; wgmma.mma_async.sync.aligned.m64n96k16.f16.f16.f16 {o0,o1,o2,o3,o4,o5,o6,o7,o8,o9,o10,o11,o12,o13,o14,o15,o16,o17,o18,o19,o20,o21,o22,o23}, {g4,g5,g6,g7}, dt, pt, 1, 1, 1;\n"
        "wgmma.commit_group.sync.aligned;\n"
        "@pz bra.uni B62;\n"
        "mov.b32 {xl, xh}, a2; tanh.approx.f16 xr, xl; cvt.u32.u16 lo0, xr; tanh.approx.f16 xr, xh; cvt.u32.u16 hi0, xr; mul.rn.f16x2 a3, qz27, p1; fma.rn.f16x2 p0, qz28, qz28, c; fma.rn.f16x2 g8, qz24, h0, qz24; prmt.b32 h1, lo1, hi1, 0x5410;\n"
        "mov.b32 {xl, xh}, a3; tanh.approx.f16 xr, xl; cvt.u32.u16 lo1, xr; tanh.approx.f16 xr, xh; cvt.u32.u16 hi1, xr; mul.rn.f16x2 a0, qz28, p0; fma.rn.f16x2 p1, qz29, qz29, c; fma.rn.f16x2 g9, qz25, h1, qz25; prmt.b32 h0, lo0, hi0, 0x5410;\n"
        "mov.b32 {xl, xh}, a0; tanh.approx.f16 xr, xl; cvt.u32.u16 lo0, xr; tanh.approx.f16 xr, xh; cvt.u32.u16 hi0, xr; mul.rn.f16x2 a1, qz29, p1; fma.rn.f16x2 p0, qz30, qz30, c; fma.rn.f16x2 g10, qz26, h0, qz26; prmt.b32 h1, lo1, hi1, 0x5410;\n"
        "mov.b32 {xl, xh}, a1; tanh.approx.f16 xr, xl; cvt.u32.u16 lo1, xr; tanh.approx.f16 xr, xh; cvt.u32.u16 hi1, xr; mul.rn.f16x2 a2, qz30, p0; fma.rn.f16x2 p1, qz31, qz31, c; fma.rn.f16x2 g11, qz27, h1, qz27; prmt.b32 h0, lo0, hi0, 0x5410;\n"
        "B62:\n"
        "wgmma.wait_group.sync.aligned 1;\n"
        "wgmma.fence.sync.aligned;\n"
        "add.s64 dt, w2d, 896; wgmma.mma_async.sync.aligned.m64n96k16.f16.f16.f16 {o0,o1,o2,o3,o4,o5,o6,o7,o8,o9,o10,o11,o12,o13,o14,o15,o16,o17,o18,o19,o20,o21,o22,o23}, {g8,g9,g10,g11}, dt, pt, 1, 1, 1;\n"
        "wgmma.commit_group.sync.aligned;\n"
        "@pz bra.uni B66;\n"
        "mov.b32 {xl, xh}, a2; tanh.approx.f16 xr, xl; cvt.u32.u16 lo0, xr; tanh.approx.f16 xr, xh; cvt.u32.u16 hi0, xr; mul.rn.f16x2 a3, qz31, p1; fma.rn.f16x2 p0, qz0, qz0, c; fma.rn.f16x2 g12, qz28, h0, qz28; prmt.b32 h1, lo1, hi1, 0x5410;\n"
        "mov.b32 {xl, xh}, a3; tanh.approx.f16 xr, xl; cvt.u32.u16 lo1, xr; tanh.approx.f16 xr, xh; cvt.u32.u16 hi1, xr; mul.rn.f16x2 a0, qz0, p0; fma.rn.f16x2 p1, qz1, qz1, c; fma.rn.f16x2 g13, qz29, h1, qz29; prmt.b32 h0, lo0, hi0, 0x5410;\n"
        "mov.b32 {xl, xh}, a0; tanh.approx.f16 xr, xl; cvt.u32.u16 lo0, xr; tanh.approx.f16 xr, xh; cvt.u32.u16 hi0, xr; mul.rn.f16x2 a1, qz1, p1; fma.rn.f16x2 p0, qz2, qz2, c; fma.rn.f16x2 g14, qz30, h0, qz30; prmt.b32 h1, lo1, hi1, 0x5410;\n"
        "mov.b32 {xl, xh}, a1; tanh.approx.f16 xr, xl; cvt.u32.u16 lo1, xr; tanh.approx.f16 xr, xh; cvt.u32.u16 hi1, xr; mul.rn.f16x2 a2, qz2, p0; fma.rn.f16x2 p1, qz3, qz3, c; fma.rn.f16x2 g15, qz31, h1, qz31; prmt.b32 h0, lo0, hi0, 0x5410;\n"
        "B66:\n"
        "wgmma.wait_group.sync.aligned 1;\n"
        "wgmma.fence.sync.aligned;\n"
        "add.s64 dt, w2d, 960; wgmma.mma_async.sync.aligned.m64n96k16.f16.f16.f16 {o0,o1,o2,o3,o4,o5,o6,o7,o8,o9,o10,o11,o12,o13,o14,o15,o16,o17,o18,o19,o20,o21,o22,o23}, {g12,g13,g14,g15}, dt, pt, 1, 1, 1;\n"
        "add.s64 dt, w1d, 3840; wgmma.mma_async.sync.aligned.m64n64k16.f16.f16.f16 {qz16,qz17,qz18,qz19,qz20,qz21,qz22,qz23,qz24,qz25,qz26,qz27,qz28,qz29,qz30,qz31}, {qa0,qa1,qa2,qa3}, dt, pf, 1, 1, 1;\n"
        "add.s64 dt, w1d, 3968; wgmma.mma_async.sync.aligned.m64n64k16.f16.f16.f16 {qz16,qz17,qz18,qz19,qz20,qz21,qz22,qz23,qz24,qz25,qz26,qz27,qz28,qz29,qz30,qz31}, {qa4,qa5,qa6,qa7}, dt, pt, 1, 1, 1;\n"
        "add.s64 dt, w1d, 4096; wgmma.mma_async.sync.aligned.m64n64k16.f16.f16.f16 {qz16,qz17,qz18,qz19,qz20,qz21,qz22,qz23,qz24,qz25,qz26,qz27,qz28,qz29,qz30,qz31}, {qa8,qa9,qa10,qa11}, dt, pt, 1, 1, 1;\n"
        "wgmma.commit_group.sync.aligned;\n"
        "@pz bra.uni B70;\n"
        "mov.b32 {xl, xh}, a2; tanh.approx.f16 xr, xl; cvt.u32.u16 lo0, xr; tanh.approx.f16 xr, xh; cvt.u32.u16 hi0, xr; mul.rn.f16x2 a3, qz3, p1; fma.rn.f16x2 p0, qz4, qz4, c; fma.rn.f16x2 g0, qz0, h0, qz0; prmt.b32 h1, lo1, hi1, 0x5410;\n"
        "mov.b32 {xl, xh}, a3; tanh.approx.f16 xr, xl; cvt.u32.u16 lo1, xr; tanh.approx.f16 xr, xh; cvt.u32.u16 hi1, xr; mul.rn.f16x2 a0, qz4, p0; fma.rn.f16x2 p1, qz5, qz5, c; fma.rn.f16x2 g1, qz1, h1, qz1; prmt.b32 h0, lo0, hi0, 0x5410;\n"
        "mov.b32 {xl, xh}, a0; tanh.approx.f16 xr, xl; cvt.u32.u16 lo0, xr; tanh.approx.f16 xr, xh; cvt.u32.u16 hi0, xr; mul.rn.f16x2 a1, qz5, p1; fma.rn.f16x2 p0, qz6, qz6, c; fma.rn.f16x2 g2, qz2, h0, qz2; prmt.b32 h1, lo1, hi1, 0x5410;\n"
        "mov.b32 {xl, xh}, a1; tanh.approx.f16 xr, xl; cvt.u32.u16 lo1, xr; tanh.approx.f16 xr, xh; cvt.u32.u16 hi1, xr; mul.rn.f16x2 a2, qz6, p0; fma.rn.f16x2 p1, qz7, qz7, c; fma.rn.f16x2 g3, qz3, h1, qz3; prmt.b32 h0, lo0, hi0, 0x5410;\n"
        "B70:\n"
        "wgmma.fence.sync.aligned;\n"
        "add.s64 dt, w1d, 4224; wgmma.mma_async.sync.aligned.m64n64k16.f16.f16.f16 {qz16,qz17,qz18,qz19,qz20,qz21,qz22,qz23,qz24,qz25,qz26,qz27,qz28,qz29,qz30,qz31}, {qa12,qa13,qa14,qa15}, dt, pt, 1, 1, 1;\n"
        "add.s64 dt, w1d, 4352; wgmma.mma_async.sync.aligned.m64n64k16.f16.f16.f16 {qz16,qz17,qz18,qz19,qz20,qz21,qz22,qz23,qz24,qz25,qz26,qz27,qz28,qz29,qz30,qz31}, {qa16,qa17,qa18,qa19}, dt, pt, 1, 1, 1;\n"
        "add.s64 dt, w1d, 4480; wgmma.mma_async.sync.aligned.m64n64k16.f16.f16.f16 {qz16,qz17,qz18,qz19,qz20,qz21,qz22,qz23,qz24,qz25,qz26,qz27,qz28,qz29,qz30,qz31}, {qa20,qa21,qa22,qa23}, dt, pt, 1, 1, 1;\n"
        "wgmma.commit_group.sync.aligned;\n"
        "@pz bra.uni B74;\n"
        "mov.b32 {xl, xh}, a2; tanh.approx.f16 xr, xl; cvt.u32.u16 lo0, xr; tanh.approx.f16 xr, xh; cvt.u32.u16 hi0, xr; mul.rn.f16x2 a3, qz7, p1; fma.rn.f16x2 p0, qz8, qz8, c; fma.rn.f16x2 g4, qz4, h0, qz4; prmt.b32 h1, lo1, hi1, 0x5410;\n"
        "mov.b32 {xl, xh}, a3; tanh.approx.f16 xr, xl; cvt.u32.u16 lo1, xr; tanh.approx.f16 xr, xh; cvt.u32.u16 hi1, xr; mul.rn.f16x2 a0, qz8, p0; fma.rn.f16x2 p1, qz9, qz9, c; fma.rn.f16x2 g5, qz5, h1, qz5; prmt.b32 h0, lo0, hi0, 0x5410;\n"
        "mov.b32 {xl, xh}, a0; tanh.approx.f16 xr, xl; cvt.u32.u16 lo0, xr; tanh.approx.f16 xr, xh; cvt.u32.u16 hi0, xr; mul.rn.f16x2 a1, qz9, p1; fma.rn.f16x2 p0, qz10, qz10, c; fma.rn.f16x2 g6, qz6, h0, qz6; prmt.b32 h1, lo1, hi1, 0x5410;\n"
        "mov.b32 {xl, xh}, a1; tanh.approx.f16 xr, xl; cvt.u32.u16 lo1, xr; tanh.approx.f16 xr, xh; cvt.u32.u16 hi1, xr; mul.rn.f16x2 a2, qz10, p0; fma.rn.f16x2 p1, qz11, qz11, c; fma.rn.f16x2 g7, qz7, h1, qz7; prmt.b32 h0, lo0, hi0, 0x5410;\n"
        "B74:\n"
        "wgmma.wait_group.sync.aligned 2;\n"
        "setp.eq.s32 pr, n, 0;\n"
        "@pr bra.uni SPINW2;\n"
        "BACKW2:\n"
        "wgmma.fence.sync.aligned;\n"
        "add.s64 dt, w2d, 1024; wgmma.mma_async.sync.aligned.m64n96k16.f16.f16.f16 {o0,o1,o2,o3,o4,o5,o6,o7,o8,o9,o10,o11,o12,o13,o14,o15,o16,o17,o18,o19,o20,o21,o22,o23}, {g0,g1,g2,g3}, dt, pt, 1, 1, 1;\n"
        "add.s64 dt, w2d, 1088; wgmma.mma_async.sync.aligned.m64n96k16.f16.f16.f16 {o0,o1,o2,o3,o4,o5,o6,o7,o8,o9,o10,o11,o12,o13,o14,o15,o16,o17,o18,o19,o20,o21,o22,o23}, {g4,g5,g6,g7}, dt, pt, 1, 1, 1;\n"
        "wgmma.commit_group.sync.aligned;\n"
        "@pz bra.uni B78;\n"
        "mov.b32 {xl, xh}, a2; tanh.approx.f16 xr, xl; cvt.u32.u16 lo0, xr; tanh.approx.f16 xr, xh; cvt.u32.u16 hi0, xr; mul.rn.f16x2 a3, qz11, p1; fma.rn.f16x2 p0, qz12, qz12, c; fma.rn.f16x2 g8, qz8, h0, qz8; prmt.b32 h1, lo1, hi1, 0x5410;\n"
        "mov.b32 {xl, xh}, a3; tanh.approx.f16 xr, xl; cvt.u32.u16 lo1, xr; tanh.approx.f16 xr, xh; cvt.u32.u16 hi1, xr; mul.rn.f16x2 a0, qz12, p0; fma.rn.f16x2 p1, qz13, qz13, c; fma.rn.f16x2 g9, qz9, h1, qz9; prmt.b32 h0, lo0, hi0, 0x5410;\n"
        "mov.b32 {xl, xh}, a0; tanh.approx.f16 xr, xl; cvt.u32.u16 lo0, xr; tanh.approx.f16 xr, xh; cvt.u32.u16 hi0, xr; mul.rn.f16x2 a1, qz13, p1; fma.rn.f16x2 p0, qz14, qz14, c; fma.rn.f16x2 g10, qz10, h0, qz10; prmt.b32 h1, lo1, hi1, 0x5410;\n"
        "mov.b32 {xl, xh}, a1; tanh.approx.f16 xr, xl; cvt.u32.u16 lo1, xr; tanh.approx.f16 xr, xh; cvt.u32.u16 hi1, xr; mul.rn.f16x2 a2, qz14, p0; fma.rn.f16x2 p1, qz15, qz15, c; fma.rn.f16x2 g11, qz11, h1, qz11; prmt.b32 h0, lo0, hi0, 0x5410;\n"
        "B78:\n"
        "wgmma.wait_group.sync.aligned 1;\n"
        "@!pm bra.uni BACKY;\n"
        "add.u32 tt, n, 1; and.b32 tt, tt, 1; mbarrier.try_wait.parity.shared::cta.b64 pw, [ybar], tt;\n"
        "@!pw bra.uni SPINY;\n"
        "BACKY:\n"
        "@pz bra.uni B80;\n"
        "and.b32 ad, %6, 0xffff; xor.b32 ad, ad, 0; add.u32 ad, ad, %5; ldmatrix.sync.aligned.m8n8.x4.shared.b16 {qa0,qa1,qa2,qa3}, [ad];\n"
        "and.b32 ad, %6, 0xffff; xor.b32 ad, ad, 32; add.u32 ad, ad, %5; ldmatrix.sync.aligned.m8n8.x4.shared.b16 {qa4,qa5,qa6,qa7}, [ad];\n"
        "and.b32 ad, %6, 0xffff; xor.b32 ad, ad, 64; add.u32 ad, ad, %5; ldmatrix.sync.aligned.m8n8.x4.shared.b16 {qa8,qa9,qa10,qa11}, [ad];\n"
        "and.b32 ad, %6, 0xffff; xor.b32 ad, ad, 96; add.u32 ad, ad, %5; ldmatrix.sync.aligned.m8n8.x4.shared.b16 {qa12,qa13,qa14,qa15}, [ad];\n"
        "shr.u32 ad, %6, 16; xor.b32 ad, ad, 0; add.u32 ad, ad, %5; ldmatrix.sync.aligned.m8n8.x4.shared.b16 {qa16,qa17,qa18,qa19}, [ad];\n"
        "shr.u32 ad, %6, 16; xor.b32 ad, ad, 32; add.u32 ad, ad, %5; ldmatrix.sync.aligned.m8n8.x4.shared.b16 {qa20,qa21,qa22,qa23}, [ad];\n"
        "mov.b32 {xl, xh}, a2; tanh.approx.f16 xr, xl; cvt.u32.u16 lo0, xr; tanh.approx.f16 xr, xh; cvt.u32.u16 hi0, xr; mul.rn.f16x2 a3, qz15, p1; fma.rn.f16x2 p0, qz16, qz16, c; fma.rn.f16x2 g12, qz12, h0, qz12; prmt.b32 h1, lo1, hi1, 0x5410;\n"
        "mov.b32 {xl, xh}, a3; tanh.approx.f16 xr, xl; cvt.u32.u16 lo1, xr; tanh.approx.f16 xr, xh; cvt.u32.u16 hi1, xr; mul.rn.f16x2 a0, qz16, p0; fma.rn.f16x2 p1, qz17, qz17, c; fma.rn.f16x2 g13, qz13, h1, qz13; prmt.b32 h0, lo0, hi0, 0x5410;\n"
        "B80:\n"
        "@!pm bra.uni XLOADB;\n"
        "fence.proxy.async.shared::cta;\n"
        "add.u32 tt, id, 0;\n"
        "@pl bra.uni XLOAD;\n"
        "bar.arrive tt, 128;\n"
        "XLOADB:\n"
        "wgmma.fence.sync.aligned;\n"
        "add.s64 dt, w2d, 1152; wgmma.mma_async.sync.aligned.m64n96k16.f16.f16.f16 {o0,o1,o2,o3,o4,o5,o6,o7,o8,o9,o10,o11,o12,o13,o14,o15,o16,o17,o18,o19,o20,o21,o22,o23}, {g8,g9,g10,g11}, dt, pt, 1, 1, 1;\n"
        "wgmma.commit_group.sync.aligned;\n"
        "@pz bra.uni B82;\n"
        "mov.b32 {xl, xh}, a0; tanh.approx.f16 xr, xl; cvt.u32.u16 lo0, xr; tanh.approx.f16 xr, xh; cvt.u32.u16 hi0, xr; mul.rn.f16x2 a1, qz17, p1; fma.rn.f16x2 p0, qz18, qz18, c; fma.rn.f16x2 g14, qz14, h0, qz14; prmt.b32 h1, lo1, hi1, 0x5410;\n"
        "mov.b32 {xl, xh}, a1; tanh.approx.f16 xr, xl; cvt.u32.u16 lo1, xr; tanh.approx.f16 xr, xh; cvt.u32.u16 hi1, xr; mul.rn.f16x2 a2, qz18, p0; fma.rn.f16x2 p1, qz19, qz19, c; fma.rn.f16x2 g15, qz15, h1, qz15; prmt.b32 h0, lo0, hi0, 0x5410;\n"
        "B82:\n"
        "wgmma.wait_group.sync.aligned 1;\n"
        "@!pm bra.uni SKIP0;\n"
        "wgmma.fence.sync.aligned;\n"
        "add.s64 dt, w1d, 0; wgmma.mma_async.sync.aligned.m64n64k16.f16.f16.f16 {qz0,qz1,qz2,qz3,qz4,qz5,qz6,qz7,qz8,qz9,qz10,qz11,qz12,qz13,qz14,qz15}, {qa0,qa1,qa2,qa3}, dt, pf, 1, 1, 1;\n"
        "add.s64 dt, w1d, 128; wgmma.mma_async.sync.aligned.m64n64k16.f16.f16.f16 {qz0,qz1,qz2,qz3,qz4,qz5,qz6,qz7,qz8,qz9,qz10,qz11,qz12,qz13,qz14,qz15}, {qa4,qa5,qa6,qa7}, dt, pt, 1, 1, 1;\n"
        "add.s64 dt, w1d, 256; wgmma.mma_async.sync.aligned.m64n64k16.f16.f16.f16 {qz0,qz1,qz2,qz3,qz4,qz5,qz6,qz7,qz8,qz9,qz10,qz11,qz12,qz13,qz14,qz15}, {qa8,qa9,qa10,qa11}, dt, pt, 1, 1, 1;\n"
        "SKIP0:\n"
        "wgmma.fence.sync.aligned;\n"
        "add.s64 dt, w2d, 1216; wgmma.mma_async.sync.aligned.m64n96k16.f16.f16.f16 {o0,o1,o2,o3,o4,o5,o6,o7,o8,o9,o10,o11,o12,o13,o14,o15,o16,o17,o18,o19,o20,o21,o22,o23}, {g12,g13,g14,g15}, dt, pt, 1, 1, 1;\n"
        "wgmma.commit_group.sync.aligned;\n"
        "@pz bra.uni B86;\n"
        "mov.b32 {xl, xh}, a2; tanh.approx.f16 xr, xl; cvt.u32.u16 lo0, xr; tanh.approx.f16 xr, xh; cvt.u32.u16 hi0, xr; mul.rn.f16x2 a3, qz19, p1; fma.rn.f16x2 p0, qz20, qz20, c; fma.rn.f16x2 g0, qz16, h0, qz16; prmt.b32 h1, lo1, hi1, 0x5410;\n"
        "mov.b32 {xl, xh}, a3; tanh.approx.f16 xr, xl; cvt.u32.u16 lo1, xr; tanh.approx.f16 xr, xh; cvt.u32.u16 hi1, xr; mul.rn.f16x2 a0, qz20, p0; fma.rn.f16x2 p1, qz21, qz21, c; fma.rn.f16x2 g1, qz17, h1, qz17; prmt.b32 h0, lo0, hi0, 0x5410;\n"
        "mov.b32 {xl, xh}, a0; tanh.approx.f16 xr, xl; cvt.u32.u16 lo0, xr; tanh.approx.f16 xr, xh; cvt.u32.u16 hi0, xr; mul.rn.f16x2 a1, qz21, p1; fma.rn.f16x2 p0, qz22, qz22, c; fma.rn.f16x2 g2, qz18, h0, qz18; prmt.b32 h1, lo1, hi1, 0x5410;\n"
        "mov.b32 {xl, xh}, a1; tanh.approx.f16 xr, xl; cvt.u32.u16 lo1, xr; tanh.approx.f16 xr, xh; cvt.u32.u16 hi1, xr; mul.rn.f16x2 a2, qz22, p0; fma.rn.f16x2 p1, qz23, qz23, c; fma.rn.f16x2 g3, qz19, h1, qz19; prmt.b32 h0, lo0, hi0, 0x5410;\n"
        "B86:\n"
        "@!pm bra.uni SKIP1;\n"
        "wgmma.fence.sync.aligned;\n"
        "add.s64 dt, w1d, 384; wgmma.mma_async.sync.aligned.m64n64k16.f16.f16.f16 {qz0,qz1,qz2,qz3,qz4,qz5,qz6,qz7,qz8,qz9,qz10,qz11,qz12,qz13,qz14,qz15}, {qa12,qa13,qa14,qa15}, dt, pt, 1, 1, 1;\n"
        "add.s64 dt, w1d, 512; wgmma.mma_async.sync.aligned.m64n64k16.f16.f16.f16 {qz0,qz1,qz2,qz3,qz4,qz5,qz6,qz7,qz8,qz9,qz10,qz11,qz12,qz13,qz14,qz15}, {qa16,qa17,qa18,qa19}, dt, pt, 1, 1, 1;\n"
        "add.s64 dt, w1d, 640; wgmma.mma_async.sync.aligned.m64n64k16.f16.f16.f16 {qz0,qz1,qz2,qz3,qz4,qz5,qz6,qz7,qz8,qz9,qz10,qz11,qz12,qz13,qz14,qz15}, {qa20,qa21,qa22,qa23}, dt, pt, 1, 1, 1;\n"
        "SKIP1:\n"
        "@pz bra.uni B90;\n"
        "mov.b32 {xl, xh}, a2; tanh.approx.f16 xr, xl; cvt.u32.u16 lo0, xr; tanh.approx.f16 xr, xh; cvt.u32.u16 hi0, xr; mul.rn.f16x2 a3, qz23, p1; fma.rn.f16x2 p0, qz24, qz24, c; fma.rn.f16x2 g4, qz20, h0, qz20; prmt.b32 h1, lo1, hi1, 0x5410;\n"
        "mov.b32 {xl, xh}, a3; tanh.approx.f16 xr, xl; cvt.u32.u16 lo1, xr; tanh.approx.f16 xr, xh; cvt.u32.u16 hi1, xr; mul.rn.f16x2 a0, qz24, p0; fma.rn.f16x2 p1, qz25, qz25, c; fma.rn.f16x2 g5, qz21, h1, qz21; prmt.b32 h0, lo0, hi0, 0x5410;\n"
        "mov.b32 {xl, xh}, a0; tanh.approx.f16 xr, xl; cvt.u32.u16 lo0, xr; tanh.approx.f16 xr, xh; cvt.u32.u16 hi0, xr; mul.rn.f16x2 a1, qz25, p1; fma.rn.f16x2 p0, qz26, qz26, c; fma.rn.f16x2 g6, qz22, h0, qz22; prmt.b32 h1, lo1, hi1, 0x5410;\n"
        "mov.b32 {xl, xh}, a1; tanh.approx.f16 xr, xl; cvt.u32.u16 lo1, xr; tanh.approx.f16 xr, xh; cvt.u32.u16 hi1, xr; mul.rn.f16x2 a2, qz26, p0; fma.rn.f16x2 p1, qz27, qz27, c; fma.rn.f16x2 g7, qz23, h1, qz23; prmt.b32 h0, lo0, hi0, 0x5410;\n"
        "B90:\n"
        "wgmma.wait_group.sync.aligned 1;\n"
        "wgmma.fence.sync.aligned;\n"
        "add.s64 dt, w2d, 1280; wgmma.mma_async.sync.aligned.m64n96k16.f16.f16.f16 {o0,o1,o2,o3,o4,o5,o6,o7,o8,o9,o10,o11,o12,o13,o14,o15,o16,o17,o18,o19,o20,o21,o22,o23}, {g0,g1,g2,g3}, dt, pt, 1, 1, 1;\n"
        "add.s64 dt, w2d, 1344; wgmma.mma_async.sync.aligned.m64n96k16.f16.f16.f16 {o0,o1,o2,o3,o4,o5,o6,o7,o8,o9,o10,o11,o12,o13,o14,o15,o16,o17,o18,o19,o20,o21,o22,o23}, {g4,g5,g6,g7}, dt, pt, 1, 1, 1;\n"
        "wgmma.commit_group.sync.aligned;\n"
        "@pz bra.uni B94;\n"
        "mov.b32 {xl, xh}, a2; tanh.approx.f16 xr, xl; cvt.u32.u16 lo0, xr; tanh.approx.f16 xr, xh; cvt.u32.u16 hi0, xr; mul.rn.f16x2 a3, qz27, p1; fma.rn.f16x2 p0, qz28, qz28, c; fma.rn.f16x2 g8, qz24, h0, qz24; prmt.b32 h1, lo1, hi1, 0x5410;\n"
        "mov.b32 {xl, xh}, a3; tanh.approx.f16 xr, xl; cvt.u32.u16 lo1, xr; tanh.approx.f16 xr, xh; cvt.u32.u16 hi1, xr; mul.rn.f16x2 a0, qz28, p0; fma.rn.f16x2 p1, qz29, qz29, c; fma.rn.f16x2 g9, qz25, h1, qz25; prmt.b32 h0, lo0, hi0, 0x5410;\n"
        "mov.b32 {xl, xh}, a0; tanh.approx.f16 xr, xl; cvt.u32.u16 lo0, xr; tanh.approx.f16 xr, xh; cvt.u32.u16 hi0, xr; mul.rn.f16x2 a1, qz29, p1; fma.rn.f16x2 p0, qz30, qz30, c; fma.rn.f16x2 g10, qz26, h0, qz26; prmt.b32 h1, lo1, hi1, 0x5410;\n"
        "mov.b32 {xl, xh}, a1; tanh.approx.f16 xr, xl; cvt.u32.u16 lo1, xr; tanh.approx.f16 xr, xh; cvt.u32.u16 hi1, xr; mul.rn.f16x2 a2, qz30, p0; fma.rn.f16x2 p1, qz31, qz31, c; fma.rn.f16x2 g11, qz27, h1, qz27; prmt.b32 h0, lo0, hi0, 0x5410;\n"
        "B94:\n"
        "wgmma.wait_group.sync.aligned 0;\n"
        "wgmma.fence.sync.aligned;\n"
        "add.s64 dt, w2d, 1408; wgmma.mma_async.sync.aligned.m64n96k16.f16.f16.f16 {o0,o1,o2,o3,o4,o5,o6,o7,o8,o9,o10,o11,o12,o13,o14,o15,o16,o17,o18,o19,o20,o21,o22,o23}, {g8,g9,g10,g11}, dt, pt, 1, 1, 1;\n"
        "wgmma.commit_group.sync.aligned;\n"
        "@pz bra.uni B2;\n"
        "mov.b32 {xl, xh}, a2; tanh.approx.f16 xr, xl; cvt.u32.u16 lo0, xr; tanh.approx.f16 xr, xh; cvt.u32.u16 hi0, xr; mul.rn.f16x2 a3, qz31, p1; fma.rn.f16x2 p0, qz0, qz0, c; fma.rn.f16x2 g12, qz28, h0, qz28; prmt.b32 h1, lo1, hi1, 0x5410;\n"
        "mov.b32 {xl, xh}, a3; tanh.approx.f16 xr, xl; cvt.u32.u16 lo1, xr; tanh.approx.f16 xr, xh; cvt.u32.u16 hi1, xr; mul.rn.f16x2 a0, qz0, p0; fma.rn.f16x2 p1, qz1, qz1, c; fma.rn.f16x2 g13, qz29, h1, qz29; prmt.b32 h0, lo0, hi0, 0x5410;\n"
        "mov.b32 {xl, xh}, a0; tanh.approx.f16 xr, xl; cvt.u32.u16 lo0, xr; tanh.approx.f16 xr, xh; cvt.u32.u16 hi0, xr; mul.rn.f16x2 a1, qz1, p1; fma.rn.f16x2 p0, qz2, qz2, c; fma.rn.f16x2 g14, qz30, h0, qz30; prmt.b32 h1, lo1, hi1, 0x5410;\n"
        "mov.b32 {xl, xh}, a1; tanh.approx.f16 xr, xl; cvt.u32.u16 lo1, xr; tanh.approx.f16 xr, xh; cvt.u32.u16 hi1, xr; mul.rn.f16x2 a2, qz2, p0; fma.rn.f16x2 p1, qz3, qz3, c; fma.rn.f16x2 g15, qz31, h1, qz31; prmt.b32 h0, lo0, hi0, 0x5410;\n"
        "B2:\n"
        "wgmma.fence.sync.aligned;\n"
        "add.s64 dt, w2d, 1472; wgmma.mma_async.sync.aligned.m64n96k16.f16.f16.f16 {o0,o1,o2,o3,o4,o5,o6,o7,o8,o9,o10,o11,o12,o13,o14,o15,o16,o17,o18,o19,o20,o21,o22,o23}, {g12,g13,g14,g15}, dt, pt, 1, 1, 1;\n"
        "wgmma.commit_group.sync.aligned;\n"
        "@!pm bra.uni LAST;\n"
        "@pz bra.uni BE;\n"
        "mov.b32 {xl, xh}, a2; tanh.approx.f16 xr, xl; cvt.u32.u16 lo0, xr; tanh.approx.f16 xr, xh; cvt.u32.u16 hi0, xr; mul.rn.f16x2 a3, qz3, p1; fma.rn.f16x2 p0, qz4, qz4, c; fma.rn.f16x2 g0, qz0, h0, qz0; prmt.b32 h1, lo1, hi1, 0x5410;\n"
        "mov.b32 {xl, xh}, a3; tanh.approx.f16 xr, xl; cvt.u32.u16 lo1, xr; tanh.approx.f16 xr, xh; cvt.u32.u16 hi1, xr; mul.rn.f16x2 a0, qz4, p0; fma.rn.f16x2 p1, qz5, qz5, c; fma.rn.f16x2 g1, qz1, h1, qz1; prmt.b32 h0, lo0, hi0, 0x5410;\n"
        "mov.b32 {xl, xh}, a0; tanh.approx.f16 xr, xl; cvt.u32.u16 lo0, xr; tanh.approx.f16 xr, xh; cvt.u32.u16 hi0, xr; mul.rn.f16x2 a1, qz5, p1; fma.rn.f16x2 p0, qz6, qz6, c; fma.rn.f16x2 g2, qz2, h0, qz2; prmt.b32 h1, lo1, hi1, 0x5410;\n"
        "mov.b32 {xl, xh}, a1; tanh.approx.f16 xr, xl; cvt.u32.u16 lo1, xr; tanh.approx.f16 xr, xh; cvt.u32.u16 hi1, xr; mul.rn.f16x2 a2, qz6, p0; fma.rn.f16x2 p1, qz7, qz7, c; fma.rn.f16x2 g3, qz3, h1, qz3; prmt.b32 h0, lo0, hi0, 0x5410;\n"
        "BE:\n"
        "wgmma.wait_group.sync.aligned 0;\n"
        "bra.uni LOOP;\n"
        "STORE:\n"
        "bar.sync tt, 128;\n"
        "setp.lt.s32 pr, n, 0;\n"
        "@pr bra.uni STOREB;\n"
        "cvt.u64.u32 gp, off; add.s64 gp, gp, %12;\n"
        "elect.sync _|pr, 0xffffffff;\n"
        "@pr cp.async.bulk.global.shared::cta.bulk_group [gp], [%5], 12288;\n"
        "@pr cp.async.bulk.commit_group;\n"
        "bra.uni STOREB;\n"
        "YLOAD:\n"
        "cp.async.bulk.wait_group.read 0;\n"
        "@!pm bra.uni XLAST;\n"
        "sub.u32 ad, off, %9; cvt.u64.u32 gp, ad; add.s64 gp, gp, %12;\n"
        "elect.sync _|pr, 0xffffffff;\n"
        "@pr mbarrier.arrive.expect_tx.shared::cta.b64 _, [ybar], 12288;\n"
        "@pr cp.async.bulk.shared::cluster.global.mbarrier::complete_tx::bytes [%5], [gp], 12288, [ybar];\n"
        "bra.uni YLOADB;\n"
        "XLAST:\n"
        "cvt.u64.u32 gp, off; add.s64 gp, gp, %11;\n"
        "elect.sync _|pr, 0xffffffff;\n"
        "@pr mbarrier.arrive.expect_tx.shared::cta.b64 _, [xbar], 12288;\n"
        "@pr cp.async.bulk.shared::cluster.global.mbarrier::complete_tx::bytes.L2::cache_hint [%5], [gp], 12288, [xbar], pol;\n"
        "bra.uni YLOADB;\n"
        "XPF:\n"
        "elect.sync _|pr, 0xffffffff;\n"
        "cvt.u64.u32 gp, off; add.s64 gp, gp, %11;\n"
        "@pr cp.async.bulk.prefetch.L2.global.L2::cache_hint [gp], 12288, pol;\n"
        "bra.uni XPFB;\n"
        "XLOAD:\n"
        "bar.sync tt, 128;\n"
        "cvt.u64.u32 gp, off; add.s64 gp, gp, %11;\n"
        "elect.sync _|pr, 0xffffffff;\n"
        "@pr mbarrier.arrive.expect_tx.shared::cta.b64 _, [xbar], 12288;\n"
        "@pr cp.async.bulk.shared::cluster.global.mbarrier::complete_tx::bytes.L2::cache_hint [%5], [gp], 12288, [xbar], pol;\n"
        "bra.uni XLOADB;\n"
        "SPINY: mov.u32 cnt, 0;\n"
        "SPINYL:\n"
        "add.u32 tt, n, 1; and.b32 tt, tt, 1; mbarrier.try_wait.parity.shared::cta.b64 pw, [ybar], tt;\n"
        "@pw bra.uni BACKY;\n"
        "add.u32 cnt, cnt, 1; setp.lt.u32 pw, cnt, 0x100000;\n"
        "@pw bra.uni SPINYL;\n"
        "trap;\n"
        "SPINX: mov.u32 cnt, 0;\n"
        "SPINXL:\n"
        "and.b32 tt, n, 1; mbarrier.try_wait.parity.shared::cta.b64 pw, [xbar], tt;\n"
        "@pw bra.uni BACKX;\n"
        "add.u32 cnt, cnt, 1; setp.lt.u32 pw, cnt, 0x100000;\n"
        "@pw bra.uni SPINXL;\n"
        "trap;\n"
        "SPINT: mov.u32 cnt, 0;\n"
        "SPINTL:\n"
        "mad.lo.u32 tt, n, 8, tbar; mbarrier.try_wait.parity.shared::cta.b64 pw, [tt], tpar;\n"
        "@pw bra.uni BACKT;\n"
        "add.u32 cnt, cnt, 1; setp.lt.u32 pw, cnt, 0x100000;\n"
        "@pw bra.uni SPINTL;\n"
        "trap;\n"
        "SPINW0: mov.u32 cnt, 0;\n"
        "SPINW0L:\n"
        "mov.u32 tt, 231208; mbarrier.try_wait.parity.shared::cta.b64 pw, [tt], 0;\n"
        "@pw bra.uni BACKW0;\n"
        "add.u32 cnt, cnt, 1; setp.lt.u32 pw, cnt, 0x100000;\n"
        "@pw bra.uni SPINW0L;\n"
        "trap;\n"
        "SPINW1: mov.u32 cnt, 0;\n"
        "SPINW1L:\n"
        "mov.u32 tt, 231216; mbarrier.try_wait.parity.shared::cta.b64 pw, [tt], 0;\n"
        "@pw bra.uni BACKW1;\n"
        "add.u32 cnt, cnt, 1; setp.lt.u32 pw, cnt, 0x100000;\n"
        "@pw bra.uni SPINW1L;\n"
        "trap;\n"
        "SPINW2: mov.u32 cnt, 0;\n"
        "SPINW2L:\n"
        "mov.u32 tt, 231224; mbarrier.try_wait.parity.shared::cta.b64 pw, [tt], 0;\n"
        "@pw bra.uni BACKW2;\n"
        "add.u32 cnt, cnt, 1; setp.lt.u32 pw, cnt, 0x100000;\n"
        "@pw bra.uni SPINW2L;\n"
        "trap;\n"
        "SPINY0: mov.u32 cnt, 0;\n"
        "SPINY0L:\n"
        "mbarrier.try_wait.parity.shared::cta.b64 pw, [ybar], 0;\n"
        "@pw bra.uni BACKY0;\n"
        "add.u32 cnt, cnt, 1; setp.lt.u32 pw, cnt, 0x100000;\n"
        "@pw bra.uni SPINY0L;\n"
        "trap;\n"
        "SPINR: mov.u32 cnt, 0;\n"
        "SPINRL:\n"
        "mov.u32 tt, 231232; mbarrier.try_wait.parity.shared::cta.b64 pw, [tt], %13;\n"
        "@pw bra.uni BACKR;\n"
        "add.u32 cnt, cnt, 1; setp.lt.u32 pw, cnt, 0x100000;\n"
        "@pw bra.uni SPINRL;\n"
        "trap;\n"
        "BACKR:\n"
        "mov.u32 tt, 230792; ld.shared.v2.b32 {osc, tt}, [tt];\n"
        "setp.ne.u32 pr, tt, 0; vote.sync.any.pred pr, pr, 0xffffffff;\n"
        "@pr bra.uni RETRY;\n"
        "setp.eq.u32 pr, %3, 0;\n"
        "@pr bra.uni BACKB;\n"
        "SPINB: mov.u32 cnt, 0;\n"
        "SPINBL:\n"
        "mov.u32 tt, 231208; mbarrier.try_wait.parity.shared::cta.b64 pw, [tt], 0;\n"
        "@pw bra.uni BACKB;\n"
        "add.u32 cnt, cnt, 1; setp.lt.u32 pw, cnt, 0x100000;\n"
        "@pw bra.uni SPINBL;\n"
        "trap;\n"
        "BACKB:\n"
        "ld.shared.v4.b32 {o0,o1,o2,o3}, [%8+0];\n"
        "ld.shared.v4.b32 {o4,o5,o6,o7}, [%8+64];\n"
        "ld.shared.v4.b32 {o8,o9,o10,o11}, [%8+128];\n"
        "ld.shared.v4.b32 {o12,o13,o14,o15}, [%8+192];\n"
        "ld.shared.v4.b32 {o16,o17,o18,o19}, [%8+256];\n"
        "ld.shared.v4.b32 {o20,o21,o22,o23}, [%8+320];\n"
        "bra.uni SPINW0;\n"
        "RETRY:\n"
        "wgmma.fence.sync.aligned;\n"
        "wgmma.commit_group.sync.aligned;\n"
        "wgmma.wait_group.sync.aligned 0;\n"
        "mov.u32 %0, 1;\n"
        "bra.uni OUT;\n"
        "SPINL: mov.u32 cnt, 0;\n"
        "SPINLL:\n"
        "and.b32 tt, n, 1; mbarrier.try_wait.parity.shared::cta.b64 pw, [xbar], tt;\n"
        "@pw bra.uni BACKL;\n"
        "add.u32 cnt, cnt, 1; setp.lt.u32 pw, cnt, 0x100000;\n"
        "@pw bra.uni SPINLL;\n"
        "trap;\n"
        "LAST:\n"
        "and.b32 tt, n, 1; mbarrier.try_wait.parity.shared::cta.b64 pw, [xbar], tt;\n"
        "@!pw bra.uni SPINL;\n"
        "BACKL:\n"
        "and.b32 ad, %7, 0xffff; add.u32 ad, ad, %5; ld.shared.v4.b32 {r0,r1,r2,r3}, [ad+0];\n"
        "shr.u32 ad, %7, 16; add.u32 ad, ad, %5; ld.shared.v4.b32 {r4,r5,r6,r7}, [ad+0];\n"
        "and.b32 ad, %7, 0xffff; add.u32 ad, ad, %5; ld.shared.v4.b32 {r8,r9,r10,r11}, [ad+64];\n"
        "shr.u32 ad, %7, 16; add.u32 ad, ad, %5; ld.shared.v4.b32 {r12,r13,r14,r15}, [ad+64];\n"
        "and.b32 ad, %7, 0xffff; add.u32 ad, ad, %5; ld.shared.v4.b32 {r16,r17,r18,r19}, [ad+128];\n"
        "shr.u32 ad, %7, 16; add.u32 ad, ad, %5; ld.shared.v4.b32 {r20,r21,r22,r23}, [ad+128];\n"
        "wgmma.wait_group.sync.aligned 0;\n"
        "mov.b32 {xl, xh}, o0; cvt.f32.f16 f0, xl; cvt.f32.f16 f1, xh; cvt.rn.bf16x2.f32 tt, f1, f0; fma.rn.bf16x2 r0, tt, osc, r0;\n"
        "mov.b32 {xl, xh}, o2; cvt.f32.f16 f0, xl; cvt.f32.f16 f1, xh; cvt.rn.bf16x2.f32 tt, f1, f0; fma.rn.bf16x2 r1, tt, osc, r1;\n"
        "mov.b32 {xl, xh}, o4; cvt.f32.f16 f0, xl; cvt.f32.f16 f1, xh; cvt.rn.bf16x2.f32 tt, f1, f0; fma.rn.bf16x2 r2, tt, osc, r2;\n"
        "mov.b32 {xl, xh}, o6; cvt.f32.f16 f0, xl; cvt.f32.f16 f1, xh; cvt.rn.bf16x2.f32 tt, f1, f0; fma.rn.bf16x2 r3, tt, osc, r3;\n"
        "and.b32 ad, %7, 0xffff; add.u32 ad, ad, off; cvt.u64.u32 gp, ad; add.s64 gp, gp, %12; st.global.v4.b32 [gp+0], {r0,r1,r2,r3};\n"
        "mov.b32 {xl, xh}, o1; cvt.f32.f16 f0, xl; cvt.f32.f16 f1, xh; cvt.rn.bf16x2.f32 tt, f1, f0; fma.rn.bf16x2 r4, tt, osc, r4;\n"
        "mov.b32 {xl, xh}, o3; cvt.f32.f16 f0, xl; cvt.f32.f16 f1, xh; cvt.rn.bf16x2.f32 tt, f1, f0; fma.rn.bf16x2 r5, tt, osc, r5;\n"
        "mov.b32 {xl, xh}, o5; cvt.f32.f16 f0, xl; cvt.f32.f16 f1, xh; cvt.rn.bf16x2.f32 tt, f1, f0; fma.rn.bf16x2 r6, tt, osc, r6;\n"
        "mov.b32 {xl, xh}, o7; cvt.f32.f16 f0, xl; cvt.f32.f16 f1, xh; cvt.rn.bf16x2.f32 tt, f1, f0; fma.rn.bf16x2 r7, tt, osc, r7;\n"
        "shr.u32 ad, %7, 16; add.u32 ad, ad, off; cvt.u64.u32 gp, ad; add.s64 gp, gp, %12; st.global.v4.b32 [gp+0], {r4,r5,r6,r7};\n"
        "mov.b32 {xl, xh}, o8; cvt.f32.f16 f0, xl; cvt.f32.f16 f1, xh; cvt.rn.bf16x2.f32 tt, f1, f0; fma.rn.bf16x2 r8, tt, osc, r8;\n"
        "mov.b32 {xl, xh}, o10; cvt.f32.f16 f0, xl; cvt.f32.f16 f1, xh; cvt.rn.bf16x2.f32 tt, f1, f0; fma.rn.bf16x2 r9, tt, osc, r9;\n"
        "mov.b32 {xl, xh}, o12; cvt.f32.f16 f0, xl; cvt.f32.f16 f1, xh; cvt.rn.bf16x2.f32 tt, f1, f0; fma.rn.bf16x2 r10, tt, osc, r10;\n"
        "mov.b32 {xl, xh}, o14; cvt.f32.f16 f0, xl; cvt.f32.f16 f1, xh; cvt.rn.bf16x2.f32 tt, f1, f0; fma.rn.bf16x2 r11, tt, osc, r11;\n"
        "and.b32 ad, %7, 0xffff; add.u32 ad, ad, off; cvt.u64.u32 gp, ad; add.s64 gp, gp, %12; st.global.v4.b32 [gp+64], {r8,r9,r10,r11};\n"
        "mov.b32 {xl, xh}, o9; cvt.f32.f16 f0, xl; cvt.f32.f16 f1, xh; cvt.rn.bf16x2.f32 tt, f1, f0; fma.rn.bf16x2 r12, tt, osc, r12;\n"
        "mov.b32 {xl, xh}, o11; cvt.f32.f16 f0, xl; cvt.f32.f16 f1, xh; cvt.rn.bf16x2.f32 tt, f1, f0; fma.rn.bf16x2 r13, tt, osc, r13;\n"
        "mov.b32 {xl, xh}, o13; cvt.f32.f16 f0, xl; cvt.f32.f16 f1, xh; cvt.rn.bf16x2.f32 tt, f1, f0; fma.rn.bf16x2 r14, tt, osc, r14;\n"
        "mov.b32 {xl, xh}, o15; cvt.f32.f16 f0, xl; cvt.f32.f16 f1, xh; cvt.rn.bf16x2.f32 tt, f1, f0; fma.rn.bf16x2 r15, tt, osc, r15;\n"
        "shr.u32 ad, %7, 16; add.u32 ad, ad, off; cvt.u64.u32 gp, ad; add.s64 gp, gp, %12; st.global.v4.b32 [gp+64], {r12,r13,r14,r15};\n"
        "mov.b32 {xl, xh}, o16; cvt.f32.f16 f0, xl; cvt.f32.f16 f1, xh; cvt.rn.bf16x2.f32 tt, f1, f0; fma.rn.bf16x2 r16, tt, osc, r16;\n"
        "mov.b32 {xl, xh}, o18; cvt.f32.f16 f0, xl; cvt.f32.f16 f1, xh; cvt.rn.bf16x2.f32 tt, f1, f0; fma.rn.bf16x2 r17, tt, osc, r17;\n"
        "mov.b32 {xl, xh}, o20; cvt.f32.f16 f0, xl; cvt.f32.f16 f1, xh; cvt.rn.bf16x2.f32 tt, f1, f0; fma.rn.bf16x2 r18, tt, osc, r18;\n"
        "mov.b32 {xl, xh}, o22; cvt.f32.f16 f0, xl; cvt.f32.f16 f1, xh; cvt.rn.bf16x2.f32 tt, f1, f0; fma.rn.bf16x2 r19, tt, osc, r19;\n"
        "and.b32 ad, %7, 0xffff; add.u32 ad, ad, off; cvt.u64.u32 gp, ad; add.s64 gp, gp, %12; st.global.v4.b32 [gp+128], {r16,r17,r18,r19};\n"
        "mov.b32 {xl, xh}, o17; cvt.f32.f16 f0, xl; cvt.f32.f16 f1, xh; cvt.rn.bf16x2.f32 tt, f1, f0; fma.rn.bf16x2 r20, tt, osc, r20;\n"
        "mov.b32 {xl, xh}, o19; cvt.f32.f16 f0, xl; cvt.f32.f16 f1, xh; cvt.rn.bf16x2.f32 tt, f1, f0; fma.rn.bf16x2 r21, tt, osc, r21;\n"
        "mov.b32 {xl, xh}, o21; cvt.f32.f16 f0, xl; cvt.f32.f16 f1, xh; cvt.rn.bf16x2.f32 tt, f1, f0; fma.rn.bf16x2 r22, tt, osc, r22;\n"
        "mov.b32 {xl, xh}, o23; cvt.f32.f16 f0, xl; cvt.f32.f16 f1, xh; cvt.rn.bf16x2.f32 tt, f1, f0; fma.rn.bf16x2 r23, tt, osc, r23;\n"
        "shr.u32 ad, %7, 16; add.u32 ad, ad, off; cvt.u64.u32 gp, ad; add.s64 gp, gp, %12; st.global.v4.b32 [gp+128], {r20,r21,r22,r23};\n"
        ASM_MARK
        "mov.u32 %0, 0;\n"
        "OUT:\n"
        "}\n"
        : "=r"(retry)
        : "r"(prm.w1desc), "r"(prm.w2desc), "r"(c.wg), "r"(c.off), "r"(c.xs), "r"(c.a_offs), "r"(c.xs_offs), "r"(c.bias_addr),
          "r"(c.step), "r"(c.w), "l"(prm.x), "l"(prm.out), "r"(round), "r"(c.last), "l"(c.park)
        : "memory");
    return retry;
}
static_assert(BAR_Y2FULL == 0 && BAR_XSFULL == 4 && BAR_TURN == 11 && BAR_ROWS == 51 && BAR_STAT == 54 &&
              sb + SM_RED + RED_SCALE * 4 == 230792, "layout");
__device__ __forceinline__ bool helper_tiles(const Pass2& c, const Params& prm, uint32_t round) {
    uint32_t retry;
    asm volatile(
        "{\n"
        ".reg .b32 qa<24>, qz<32>, o<24>, g<16>, p<2>, a<4>, lo<2>, hi<2>, h<2>, osc, v<8>, r<24>, t<2>;\n"
        ".reg .b32 n, off, c, tt, ad, cnt, ybar, xbar, tbar, tpar, id;\n"
        ".reg .b16 xl, xh, xr;\n"
        ".reg .f32 f0, f1;\n"
        ".reg .b64 w1d, w2d, dt, gp, gq, pol;\n"
        ".reg .pred pt, pf, pr, pw, pl, pm, pz, pn;\n"
        "setp.ne.b32 pt, 1, 0; setp.ne.b32 pf, 0, 0; setp.eq.u32 pl, %10, 0; setp.eq.u32 pz, %1, 0;\n"
        "mov.b32 c, 0x40D940D9;\n"
        "mov.b64 w1d, {%1, 0x40000040}; mov.b64 w2d, {%2, 0x80000020};\n"
        "mad.lo.u32 ybar, %3, 8, 230800; mad.lo.u32 xbar, %3, 8, 230832; add.u32 id, %3, 2;\n"
        "mad.lo.u32 tbar, %3, 64, 230888; setp.eq.u32 pr, %3, 0; selp.u32 tpar, 1, 0, pr; mov.u32 tt, %laneid; setp.eq.u32 pn, tt, 0;\n"
        "mov.u32 n, -1; add.u32 off, %4, %9; mov.pred pm, pt; createpolicy.fractional.L2::evict_first.b64 pol, 1.0;\n"
        "mbarrier.try_wait.parity.shared::cta.b64 pw, [ybar], 0;\n"
        "@!pw bra.uni SPINY0;\n"
        "BACKY0:\n"
        "and.b32 t0, %6, 0xffff; shr.u32 t1, %6, 16;\n"
        "xor.b32 ad, t0, 0; add.u32 ad, ad, %5; ldmatrix.sync.aligned.m8n8.x4.shared.b16 {qa0,qa1,qa2,qa3}, [ad];\n"
        "xor.b32 ad, t0, 32; add.u32 ad, ad, %5; ldmatrix.sync.aligned.m8n8.x4.shared.b16 {qa4,qa5,qa6,qa7}, [ad];\n"
        "xor.b32 ad, t0, 64; add.u32 ad, ad, %5; ldmatrix.sync.aligned.m8n8.x4.shared.b16 {qa8,qa9,qa10,qa11}, [ad];\n"
        "xor.b32 ad, t0, 96; add.u32 ad, ad, %5; ldmatrix.sync.aligned.m8n8.x4.shared.b16 {qa12,qa13,qa14,qa15}, [ad];\n"
        "xor.b32 ad, t1, 0; add.u32 ad, ad, %5; ldmatrix.sync.aligned.m8n8.x4.shared.b16 {qa16,qa17,qa18,qa19}, [ad];\n"
        "xor.b32 ad, t1, 32; add.u32 ad, ad, %5; ldmatrix.sync.aligned.m8n8.x4.shared.b16 {qa20,qa21,qa22,qa23}, [ad];\n"
        "wgmma.fence.sync.aligned;\n"
        "add.s64 dt, w1d, 0; wgmma.mma_async.sync.aligned.m64n64k16.f16.f16.f16 {qz0,qz1,qz2,qz3,qz4,qz5,qz6,qz7,qz8,qz9,qz10,qz11,qz12,qz13,qz14,qz15}, {qa0,qa1,qa2,qa3}, dt, pf, 1, 1, 1;\n"
        "add.s64 dt, w1d, 128; wgmma.mma_async.sync.aligned.m64n64k16.f16.f16.f16 {qz0,qz1,qz2,qz3,qz4,qz5,qz6,qz7,qz8,qz9,qz10,qz11,qz12,qz13,qz14,qz15}, {qa4,qa5,qa6,qa7}, dt, pt, 1, 1, 1;\n"
        "add.s64 dt, w1d, 256; wgmma.mma_async.sync.aligned.m64n64k16.f16.f16.f16 {qz0,qz1,qz2,qz3,qz4,qz5,qz6,qz7,qz8,qz9,qz10,qz11,qz12,qz13,qz14,qz15}, {qa8,qa9,qa10,qa11}, dt, pt, 1, 1, 1;\n"
        "add.s64 dt, w1d, 384; wgmma.mma_async.sync.aligned.m64n64k16.f16.f16.f16 {qz0,qz1,qz2,qz3,qz4,qz5,qz6,qz7,qz8,qz9,qz10,qz11,qz12,qz13,qz14,qz15}, {qa12,qa13,qa14,qa15}, dt, pt, 1, 1, 1;\n"
        "add.s64 dt, w1d, 512; wgmma.mma_async.sync.aligned.m64n64k16.f16.f16.f16 {qz0,qz1,qz2,qz3,qz4,qz5,qz6,qz7,qz8,qz9,qz10,qz11,qz12,qz13,qz14,qz15}, {qa16,qa17,qa18,qa19}, dt, pt, 1, 1, 1;\n"
        "add.s64 dt, w1d, 640; wgmma.mma_async.sync.aligned.m64n64k16.f16.f16.f16 {qz0,qz1,qz2,qz3,qz4,qz5,qz6,qz7,qz8,qz9,qz10,qz11,qz12,qz13,qz14,qz15}, {qa20,qa21,qa22,qa23}, dt, pt, 1, 1, 1;\n"
        "wgmma.commit_group.sync.aligned;\n"
        "mov.b32 g0, 0; mov.b32 g1, 0; mov.b32 g2, 0; mov.b32 g3, 0; mov.b32 g4, 0; mov.b32 g5, 0; mov.b32 g6, 0; mov.b32 g7, 0; mov.b32 g8, 0; mov.b32 g9, 0; mov.b32 g10, 0; mov.b32 g11, 0; mov.b32 g12, 0; mov.b32 g13, 0; mov.b32 g14, 0; mov.b32 g15, 0; mov.b32 o0, 0; mov.b32 o1, 0; mov.b32 o2, 0; mov.b32 o3, 0; mov.b32 o4, 0; mov.b32 o5, 0; mov.b32 o6, 0; mov.b32 o7, 0; mov.b32 o8, 0; mov.b32 o9, 0; mov.b32 o10, 0; mov.b32 o11, 0; mov.b32 o12, 0; mov.b32 o13, 0; mov.b32 o14, 0; mov.b32 o15, 0; mov.b32 o16, 0; mov.b32 o17, 0; mov.b32 o18, 0; mov.b32 o19, 0; mov.b32 o20, 0; mov.b32 o21, 0; mov.b32 o22, 0; mov.b32 o23, 0;\n"
        "mov.b32 osc, 0;\n"
        "wgmma.wait_group.sync.aligned 0;\n"
        "fma.rn.f16x2 p0, qz0, qz0, c;\n"
        "mul.rn.f16x2 a0, qz0, p0; fma.rn.f16x2 p1, qz1, qz1, c;\n"
        "mov.b32 {xl, xh}, a0; tanh.approx.f16 xr, xl; cvt.u32.u16 lo0, xr; tanh.approx.f16 xr, xh; cvt.u32.u16 hi0, xr; mul.rn.f16x2 a1, qz1, p1; fma.rn.f16x2 p0, qz2, qz2, c;\n"
        "mov.b32 {xl, xh}, a1; tanh.approx.f16 xr, xl; cvt.u32.u16 lo1, xr; tanh.approx.f16 xr, xh; cvt.u32.u16 hi1, xr; mul.rn.f16x2 a2, qz2, p0; fma.rn.f16x2 p1, qz3, qz3, c; prmt.b32 h0, lo0, hi0, 0x5410;\n"
        "mov.b32 {xl, xh}, a2; tanh.approx.f16 xr, xl; cvt.u32.u16 lo0, xr; tanh.approx.f16 xr, xh; cvt.u32.u16 hi0, xr; mul.rn.f16x2 a3, qz3, p1; fma.rn.f16x2 p0, qz4, qz4, c; fma.rn.f16x2 g0, qz0, h0, qz0; prmt.b32 h1, lo1, hi1, 0x5410;\n"
        "mov.b32 {xl, xh}, a3; tanh.approx.f16 xr, xl; cvt.u32.u16 lo1, xr; tanh.approx.f16 xr, xh; cvt.u32.u16 hi1, xr; mul.rn.f16x2 a0, qz4, p0; fma.rn.f16x2 p1, qz5, qz5, c; fma.rn.f16x2 g1, qz1, h1, qz1; prmt.b32 h0, lo0, hi0, 0x5410;\n"
        "mov.b32 {xl, xh}, a0; tanh.approx.f16 xr, xl; cvt.u32.u16 lo0, xr; tanh.approx.f16 xr, xh; cvt.u32.u16 hi0, xr; mul.rn.f16x2 a1, qz5, p1; fma.rn.f16x2 p0, qz6, qz6, c; fma.rn.f16x2 g2, qz2, h0, qz2; prmt.b32 h1, lo1, hi1, 0x5410;\n"
        "mov.b32 {xl, xh}, a1; tanh.approx.f16 xr, xl; cvt.u32.u16 lo1, xr; tanh.approx.f16 xr, xh; cvt.u32.u16 hi1, xr; mul.rn.f16x2 a2, qz6, p0; fma.rn.f16x2 p1, qz7, qz7, c; fma.rn.f16x2 g3, qz3, h1, qz3; prmt.b32 h0, lo0, hi0, 0x5410;\n"
        "setp.ne.u64 pr, %15, 0;\n"
        "@pr bra.uni FAST;\n"
        "LOOP:\n"
        "wgmma.fence.sync.aligned;\n"
        "add.s64 dt, w1d, 768; wgmma.mma_async.sync.aligned.m64n64k16.f16.f16.f16 {qz16,qz17,qz18,qz19,qz20,qz21,qz22,qz23,qz24,qz25,qz26,qz27,qz28,qz29,qz30,qz31}, {qa0,qa1,qa2,qa3}, dt, pf, 1, 1, 1;\n"
        "add.s64 dt, w1d, 896; wgmma.mma_async.sync.aligned.m64n64k16.f16.f16.f16 {qz16,qz17,qz18,qz19,qz20,qz21,qz22,qz23,qz24,qz25,qz26,qz27,qz28,qz29,qz30,qz31}, {qa4,qa5,qa6,qa7}, dt, pt, 1, 1, 1;\n"
        "add.s64 dt, w1d, 1024; wgmma.mma_async.sync.aligned.m64n64k16.f16.f16.f16 {qz16,qz17,qz18,qz19,qz20,qz21,qz22,qz23,qz24,qz25,qz26,qz27,qz28,qz29,qz30,qz31}, {qa8,qa9,qa10,qa11}, dt, pt, 1, 1, 1;\n"
        "add.s64 dt, w1d, 1152; wgmma.mma_async.sync.aligned.m64n64k16.f16.f16.f16 {qz16,qz17,qz18,qz19,qz20,qz21,qz22,qz23,qz24,qz25,qz26,qz27,qz28,qz29,qz30,qz31}, {qa12,qa13,qa14,qa15}, dt, pt, 1, 1, 1;\n"
        "add.s64 dt, w1d, 1280; wgmma.mma_async.sync.aligned.m64n64k16.f16.f16.f16 {qz16,qz17,qz18,qz19,qz20,qz21,qz22,qz23,qz24,qz25,qz26,qz27,qz28,qz29,qz30,qz31}, {qa16,qa17,qa18,qa19}, dt, pt, 1, 1, 1;\n"
        "add.s64 dt, w1d, 1408; wgmma.mma_async.sync.aligned.m64n64k16.f16.f16.f16 {qz16,qz17,qz18,qz19,qz20,qz21,qz22,qz23,qz24,qz25,qz26,qz27,qz28,qz29,qz30,qz31}, {qa20,qa21,qa22,qa23}, dt, pt, 1, 1, 1;\n"
        "setp.lt.s32 pr, n, 0;\n"
        "@pr bra.uni FIRST;\n"
        "and.b32 tt, n, 1; mbarrier.try_wait.parity.shared::cta.b64 pw, [xbar], tt;\n"
        "@!pw bra.uni SPINX;\n"
        "BACKX:\n"
        "and.b32 ad, %7, 0xffff; add.u32 ad, ad, %5; ld.shared.v4.b32 {v0,v1,v2,v3}, [ad+0];\n"
        "shr.u32 ad, %7, 16; add.u32 ad, ad, %5; ld.shared.v4.b32 {v4,v5,v6,v7}, [ad+0];\n"
        "mov.b32 {xl, xh}, o0; cvt.f32.f16 f0, xl; cvt.f32.f16 f1, xh; cvt.rn.bf16x2.f32 tt, f1, f0; fma.rn.bf16x2 v0, tt, osc, v0;\n"
        "mov.b32 {xl, xh}, o2; cvt.f32.f16 f0, xl; cvt.f32.f16 f1, xh; cvt.rn.bf16x2.f32 tt, f1, f0; fma.rn.bf16x2 v1, tt, osc, v1;\n"
        "mov.b32 {xl, xh}, o4; cvt.f32.f16 f0, xl; cvt.f32.f16 f1, xh; cvt.rn.bf16x2.f32 tt, f1, f0; fma.rn.bf16x2 v2, tt, osc, v2;\n"
        "mov.b32 {xl, xh}, o6; cvt.f32.f16 f0, xl; cvt.f32.f16 f1, xh; cvt.rn.bf16x2.f32 tt, f1, f0; fma.rn.bf16x2 v3, tt, osc, v3;\n"
        "and.b32 ad, %7, 0xffff; add.u32 ad, ad, %5; st.shared.v4.b32 [ad+0], {v0,v1,v2,v3};\n"
        "and.b32 ad, %7, 0xffff; add.u32 ad, ad, %5; ld.shared.v4.b32 {v0,v1,v2,v3}, [ad+64];\n"
        "mov.b32 {xl, xh}, o1; cvt.f32.f16 f0, xl; cvt.f32.f16 f1, xh; cvt.rn.bf16x2.f32 tt, f1, f0; fma.rn.bf16x2 v4, tt, osc, v4;\n"
        "mov.b32 {xl, xh}, o3; cvt.f32.f16 f0, xl; cvt.f32.f16 f1, xh; cvt.rn.bf16x2.f32 tt, f1, f0; fma.rn.bf16x2 v5, tt, osc, v5;\n"
        "mov.b32 {xl, xh}, o5; cvt.f32.f16 f0, xl; cvt.f32.f16 f1, xh; cvt.rn.bf16x2.f32 tt, f1, f0; fma.rn.bf16x2 v6, tt, osc, v6;\n"
        "mov.b32 {xl, xh}, o7; cvt.f32.f16 f0, xl; cvt.f32.f16 f1, xh; cvt.rn.bf16x2.f32 tt, f1, f0; fma.rn.bf16x2 v7, tt, osc, v7;\n"
        "shr.u32 ad, %7, 16; add.u32 ad, ad, %5; st.shared.v4.b32 [ad+0], {v4,v5,v6,v7};\n"
        "shr.u32 ad, %7, 16; add.u32 ad, ad, %5; ld.shared.v4.b32 {v4,v5,v6,v7}, [ad+64];\n"
        "ld.shared.v4.b32 {o0,o1,o2,o3}, [%8+0];\n"
        "ld.shared.v4.b32 {o4,o5,o6,o7}, [%8+64];\n"
        "mov.b32 {xl, xh}, o8; cvt.f32.f16 f0, xl; cvt.f32.f16 f1, xh; cvt.rn.bf16x2.f32 tt, f1, f0; fma.rn.bf16x2 v0, tt, osc, v0;\n"
        "mov.b32 {xl, xh}, o10; cvt.f32.f16 f0, xl; cvt.f32.f16 f1, xh; cvt.rn.bf16x2.f32 tt, f1, f0; fma.rn.bf16x2 v1, tt, osc, v1;\n"
        "mov.b32 {xl, xh}, o12; cvt.f32.f16 f0, xl; cvt.f32.f16 f1, xh; cvt.rn.bf16x2.f32 tt, f1, f0; fma.rn.bf16x2 v2, tt, osc, v2;\n"
        "mov.b32 {xl, xh}, o14; cvt.f32.f16 f0, xl; cvt.f32.f16 f1, xh; cvt.rn.bf16x2.f32 tt, f1, f0; fma.rn.bf16x2 v3, tt, osc, v3;\n"
        "and.b32 ad, %7, 0xffff; add.u32 ad, ad, %5; st.shared.v4.b32 [ad+64], {v0,v1,v2,v3};\n"
        "and.b32 ad, %7, 0xffff; add.u32 ad, ad, %5; ld.shared.v4.b32 {v0,v1,v2,v3}, [ad+128];\n"
        "mov.b32 {xl, xh}, o9; cvt.f32.f16 f0, xl; cvt.f32.f16 f1, xh; cvt.rn.bf16x2.f32 tt, f1, f0; fma.rn.bf16x2 v4, tt, osc, v4;\n"
        "mov.b32 {xl, xh}, o11; cvt.f32.f16 f0, xl; cvt.f32.f16 f1, xh; cvt.rn.bf16x2.f32 tt, f1, f0; fma.rn.bf16x2 v5, tt, osc, v5;\n"
        "mov.b32 {xl, xh}, o13; cvt.f32.f16 f0, xl; cvt.f32.f16 f1, xh; cvt.rn.bf16x2.f32 tt, f1, f0; fma.rn.bf16x2 v6, tt, osc, v6;\n"
        "mov.b32 {xl, xh}, o15; cvt.f32.f16 f0, xl; cvt.f32.f16 f1, xh; cvt.rn.bf16x2.f32 tt, f1, f0; fma.rn.bf16x2 v7, tt, osc, v7;\n"
        "shr.u32 ad, %7, 16; add.u32 ad, ad, %5; st.shared.v4.b32 [ad+64], {v4,v5,v6,v7};\n"
        "shr.u32 ad, %7, 16; add.u32 ad, ad, %5; ld.shared.v4.b32 {v4,v5,v6,v7}, [ad+128];\n"
        "ld.shared.v4.b32 {o8,o9,o10,o11}, [%8+128];\n"
        "ld.shared.v4.b32 {o12,o13,o14,o15}, [%8+192];\n"
        "mov.b32 {xl, xh}, o16; cvt.f32.f16 f0, xl; cvt.f32.f16 f1, xh; cvt.rn.bf16x2.f32 tt, f1, f0; fma.rn.bf16x2 v0, tt, osc, v0;\n"
        "mov.b32 {xl, xh}, o18; cvt.f32.f16 f0, xl; cvt.f32.f16 f1, xh; cvt.rn.bf16x2.f32 tt, f1, f0; fma.rn.bf16x2 v1, tt, osc, v1;\n"
        "mov.b32 {xl, xh}, o20; cvt.f32.f16 f0, xl; cvt.f32.f16 f1, xh; cvt.rn.bf16x2.f32 tt, f1, f0; fma.rn.bf16x2 v2, tt, osc, v2;\n"
        "mov.b32 {xl, xh}, o22; cvt.f32.f16 f0, xl; cvt.f32.f16 f1, xh; cvt.rn.bf16x2.f32 tt, f1, f0; fma.rn.bf16x2 v3, tt, osc, v3;\n"
        "and.b32 ad, %7, 0xffff; add.u32 ad, ad, %5; st.shared.v4.b32 [ad+128], {v0,v1,v2,v3};\n"
        "mov.b32 {xl, xh}, o17; cvt.f32.f16 f0, xl; cvt.f32.f16 f1, xh; cvt.rn.bf16x2.f32 tt, f1, f0; fma.rn.bf16x2 v4, tt, osc, v4;\n"
        "mov.b32 {xl, xh}, o19; cvt.f32.f16 f0, xl; cvt.f32.f16 f1, xh; cvt.rn.bf16x2.f32 tt, f1, f0; fma.rn.bf16x2 v5, tt, osc, v5;\n"
        "mov.b32 {xl, xh}, o21; cvt.f32.f16 f0, xl; cvt.f32.f16 f1, xh; cvt.rn.bf16x2.f32 tt, f1, f0; fma.rn.bf16x2 v6, tt, osc, v6;\n"
        "mov.b32 {xl, xh}, o23; cvt.f32.f16 f0, xl; cvt.f32.f16 f1, xh; cvt.rn.bf16x2.f32 tt, f1, f0; fma.rn.bf16x2 v7, tt, osc, v7;\n"
        "shr.u32 ad, %7, 16; add.u32 ad, ad, %5; st.shared.v4.b32 [ad+128], {v4,v5,v6,v7};\n"
        "ld.shared.v4.b32 {o16,o17,o18,o19}, [%8+256];\n"
        "ld.shared.v4.b32 {o20,o21,o22,o23}, [%8+320];\n"
        "FIRST:\n"
        "@pz bra.uni B7;\n"
        "mov.b32 {xl, xh}, a2; tanh.approx.f16 xr, xl; cvt.u32.u16 lo0, xr; tanh.approx.f16 xr, xh; cvt.u32.u16 hi0, xr; mul.rn.f16x2 a3, qz7, p1; fma.rn.f16x2 p0, qz8, qz8, c; fma.rn.f16x2 g4, qz4, h0, qz4; prmt.b32 h1, lo1, hi1, 0x5410;\n"
        "B7:\n"
        "fence.proxy.async.shared::cta;\n"
        "add.u32 tt, id, 4;\n"
        "@pl bra.uni STORE;\n"
        "bar.arrive tt, 128;\n"
        "STOREB:\n"
        ASM_MARK
        "add.s32 n, n, 1; sub.u32 off, off, %9; setp.lt.s32 pm, n, %14;\n"
        "@pz bra.uni B10;\n"
        "mov.b32 {xl, xh}, a3; tanh.approx.f16 xr, xl; cvt.u32.u16 lo1, xr; tanh.approx.f16 xr, xh; cvt.u32.u16 hi1, xr; mul.rn.f16x2 a0, qz8, p0; fma.rn.f16x2 p1, qz9, qz9, c; fma.rn.f16x2 g5, qz5, h1, qz5; prmt.b32 h0, lo0, hi0, 0x5410;\n"
        "mov.b32 {xl, xh}, a0; tanh.approx.f16 xr, xl; cvt.u32.u16 lo0, xr; tanh.approx.f16 xr, xh; cvt.u32.u16 hi0, xr; mul.rn.f16x2 a1, qz9, p1; fma.rn.f16x2 p0, qz10, qz10, c; fma.rn.f16x2 g6, qz6, h0, qz6; prmt.b32 h1, lo1, hi1, 0x5410;\n"
        "mov.b32 {xl, xh}, a1; tanh.approx.f16 xr, xl; cvt.u32.u16 lo1, xr; tanh.approx.f16 xr, xh; cvt.u32.u16 hi1, xr; mul.rn.f16x2 a2, qz10, p0; fma.rn.f16x2 p1, qz11, qz11, c; fma.rn.f16x2 g7, qz7, h1, qz7; prmt.b32 h0, lo0, hi0, 0x5410;\n"
        "B10:\n"
        "setp.eq.s32 pr, n, 0;\n"
        "@pr bra.uni SPINR;\n"
        "BACKW0:\n"
        "wgmma.fence.sync.aligned;\n"
        "add.s64 dt, w2d, 0; wgmma.mma_async.sync.aligned.m64n96k16.f16.f16.f16 {o0,o1,o2,o3,o4,o5,o6,o7,o8,o9,o10,o11,o12,o13,o14,o15,o16,o17,o18,o19,o20,o21,o22,o23}, {g0,g1,g2,g3}, dt, pt, 1, 1, 1;\n"
        "add.s64 dt, w2d, 64; wgmma.mma_async.sync.aligned.m64n96k16.f16.f16.f16 {o0,o1,o2,o3,o4,o5,o6,o7,o8,o9,o10,o11,o12,o13,o14,o15,o16,o17,o18,o19,o20,o21,o22,o23}, {g4,g5,g6,g7}, dt, pt, 1, 1, 1;\n"
        "wgmma.commit_group.sync.aligned;\n"
        "@pz bra.uni B14;\n"
        "mov.b32 {xl, xh}, a2; tanh.approx.f16 xr, xl; cvt.u32.u16 lo0, xr; tanh.approx.f16 xr, xh; cvt.u32.u16 hi0, xr; mul.rn.f16x2 a3, qz11, p1; fma.rn.f16x2 p0, qz12, qz12, c; fma.rn.f16x2 g8, qz8, h0, qz8; prmt.b32 h1, lo1, hi1, 0x5410;\n"
        "mov.b32 {xl, xh}, a3; tanh.approx.f16 xr, xl; cvt.u32.u16 lo1, xr; tanh.approx.f16 xr, xh; cvt.u32.u16 hi1, xr; mul.rn.f16x2 a0, qz12, p0; fma.rn.f16x2 p1, qz13, qz13, c; fma.rn.f16x2 g9, qz9, h1, qz9; prmt.b32 h0, lo0, hi0, 0x5410;\n"
        "mov.b32 {xl, xh}, a0; tanh.approx.f16 xr, xl; cvt.u32.u16 lo0, xr; tanh.approx.f16 xr, xh; cvt.u32.u16 hi0, xr; mul.rn.f16x2 a1, qz13, p1; fma.rn.f16x2 p0, qz14, qz14, c; fma.rn.f16x2 g10, qz10, h0, qz10; prmt.b32 h1, lo1, hi1, 0x5410;\n"
        "mov.b32 {xl, xh}, a1; tanh.approx.f16 xr, xl; cvt.u32.u16 lo1, xr; tanh.approx.f16 xr, xh; cvt.u32.u16 hi1, xr; mul.rn.f16x2 a2, qz14, p0; fma.rn.f16x2 p1, qz15, qz15, c; fma.rn.f16x2 g11, qz11, h1, qz11; prmt.b32 h0, lo0, hi0, 0x5410;\n"
        "B14:\n"
        "wgmma.wait_group.sync.aligned 0;\n"
        "mad.lo.u32 tt, n, 8, tbar; mbarrier.try_wait.parity.shared::cta.b64 pw, [tt], tpar;\n"
        "@!pw bra.uni SPINT;\n"
        "BACKT:\n"
        "wgmma.fence.sync.aligned;\n"
        "add.s64 dt, w2d, 128; wgmma.mma_async.sync.aligned.m64n96k16.f16.f16.f16 {o0,o1,o2,o3,o4,o5,o6,o7,o8,o9,o10,o11,o12,o13,o14,o15,o16,o17,o18,o19,o20,o21,o22,o23}, {g8,g9,g10,g11}, dt, pt, 1, 1, 1;\n"
        "wgmma.commit_group.sync.aligned;\n"
        "@pz bra.uni B18;\n"
        "mov.b32 {xl, xh}, a2; tanh.approx.f16 xr, xl; cvt.u32.u16 lo0, xr; tanh.approx.f16 xr, xh; cvt.u32.u16 hi0, xr; mul.rn.f16x2 a3, qz15, p1; fma.rn.f16x2 p0, qz16, qz16, c; fma.rn.f16x2 g12, qz12, h0, qz12; prmt.b32 h1, lo1, hi1, 0x5410;\n"
        "mov.b32 {xl, xh}, a3; tanh.approx.f16 xr, xl; cvt.u32.u16 lo1, xr; tanh.approx.f16 xr, xh; cvt.u32.u16 hi1, xr; mul.rn.f16x2 a0, qz16, p0; fma.rn.f16x2 p1, qz17, qz17, c; fma.rn.f16x2 g13, qz13, h1, qz13; prmt.b32 h0, lo0, hi0, 0x5410;\n"
        "mov.b32 {xl, xh}, a0; tanh.approx.f16 xr, xl; cvt.u32.u16 lo0, xr; tanh.approx.f16 xr, xh; cvt.u32.u16 hi0, xr; mul.rn.f16x2 a1, qz17, p1; fma.rn.f16x2 p0, qz18, qz18, c; fma.rn.f16x2 g14, qz14, h0, qz14; prmt.b32 h1, lo1, hi1, 0x5410;\n"
        "mov.b32 {xl, xh}, a1; tanh.approx.f16 xr, xl; cvt.u32.u16 lo1, xr; tanh.approx.f16 xr, xh; cvt.u32.u16 hi1, xr; mul.rn.f16x2 a2, qz18, p0; fma.rn.f16x2 p1, qz19, qz19, c; fma.rn.f16x2 g15, qz15, h1, qz15; prmt.b32 h0, lo0, hi0, 0x5410;\n"
        "B18:\n"
        "wgmma.fence.sync.aligned;\n"
        "add.s64 dt, w2d, 192; wgmma.mma_async.sync.aligned.m64n96k16.f16.f16.f16 {o0,o1,o2,o3,o4,o5,o6,o7,o8,o9,o10,o11,o12,o13,o14,o15,o16,o17,o18,o19,o20,o21,o22,o23}, {g12,g13,g14,g15}, dt, pt, 1, 1, 1;\n"
        "add.s64 dt, w1d, 1536; wgmma.mma_async.sync.aligned.m64n64k16.f16.f16.f16 {qz0,qz1,qz2,qz3,qz4,qz5,qz6,qz7,qz8,qz9,qz10,qz11,qz12,qz13,qz14,qz15}, {qa0,qa1,qa2,qa3}, dt, pf, 1, 1, 1;\n"
        "add.s64 dt, w1d, 1664; wgmma.mma_async.sync.aligned.m64n64k16.f16.f16.f16 {qz0,qz1,qz2,qz3,qz4,qz5,qz6,qz7,qz8,qz9,qz10,qz11,qz12,qz13,qz14,qz15}, {qa4,qa5,qa6,qa7}, dt, pt, 1, 1, 1;\n"
        "add.s64 dt, w1d, 1792; wgmma.mma_async.sync.aligned.m64n64k16.f16.f16.f16 {qz0,qz1,qz2,qz3,qz4,qz5,qz6,qz7,qz8,qz9,qz10,qz11,qz12,qz13,qz14,qz15}, {qa8,qa9,qa10,qa11}, dt, pt, 1, 1, 1;\n"
        "wgmma.commit_group.sync.aligned;\n"
        "@pl bra.uni YLOAD;\n"
        "YLOADB:\n"
        "@pz bra.uni B22;\n"
        "mov.b32 {xl, xh}, a2; tanh.approx.f16 xr, xl; cvt.u32.u16 lo0, xr; tanh.approx.f16 xr, xh; cvt.u32.u16 hi0, xr; mul.rn.f16x2 a3, qz19, p1; fma.rn.f16x2 p0, qz20, qz20, c; fma.rn.f16x2 g0, qz16, h0, qz16; prmt.b32 h1, lo1, hi1, 0x5410;\n"
        "mov.b32 {xl, xh}, a3; tanh.approx.f16 xr, xl; cvt.u32.u16 lo1, xr; tanh.approx.f16 xr, xh; cvt.u32.u16 hi1, xr; mul.rn.f16x2 a0, qz20, p0; fma.rn.f16x2 p1, qz21, qz21, c; fma.rn.f16x2 g1, qz17, h1, qz17; prmt.b32 h0, lo0, hi0, 0x5410;\n"
        "mov.b32 {xl, xh}, a0; tanh.approx.f16 xr, xl; cvt.u32.u16 lo0, xr; tanh.approx.f16 xr, xh; cvt.u32.u16 hi0, xr; mul.rn.f16x2 a1, qz21, p1; fma.rn.f16x2 p0, qz22, qz22, c; fma.rn.f16x2 g2, qz18, h0, qz18; prmt.b32 h1, lo1, hi1, 0x5410;\n"
        "mov.b32 {xl, xh}, a1; tanh.approx.f16 xr, xl; cvt.u32.u16 lo1, xr; tanh.approx.f16 xr, xh; cvt.u32.u16 hi1, xr; mul.rn.f16x2 a2, qz22, p0; fma.rn.f16x2 p1, qz23, qz23, c; fma.rn.f16x2 g3, qz19, h1, qz19; prmt.b32 h0, lo0, hi0, 0x5410;\n"
        "B22:\n"
        "wgmma.fence.sync.aligned;\n"
        "add.s64 dt, w1d, 1920; wgmma.mma_async.sync.aligned.m64n64k16.f16.f16.f16 {qz0,qz1,qz2,qz3,qz4,qz5,qz6,qz7,qz8,qz9,qz10,qz11,qz12,qz13,qz14,qz15}, {qa12,qa13,qa14,qa15}, dt, pt, 1, 1, 1;\n"
        "add.s64 dt, w1d, 2048; wgmma.mma_async.sync.aligned.m64n64k16.f16.f16.f16 {qz0,qz1,qz2,qz3,qz4,qz5,qz6,qz7,qz8,qz9,qz10,qz11,qz12,qz13,qz14,qz15}, {qa16,qa17,qa18,qa19}, dt, pt, 1, 1, 1;\n"
        "add.s64 dt, w1d, 2176; wgmma.mma_async.sync.aligned.m64n64k16.f16.f16.f16 {qz0,qz1,qz2,qz3,qz4,qz5,qz6,qz7,qz8,qz9,qz10,qz11,qz12,qz13,qz14,qz15}, {qa20,qa21,qa22,qa23}, dt, pt, 1, 1, 1;\n"
        "wgmma.commit_group.sync.aligned;\n"
        "@pz bra.uni B26;\n"
        "mov.b32 {xl, xh}, a2; tanh.approx.f16 xr, xl; cvt.u32.u16 lo0, xr; tanh.approx.f16 xr, xh; cvt.u32.u16 hi0, xr; mul.rn.f16x2 a3, qz23, p1; fma.rn.f16x2 p0, qz24, qz24, c; fma.rn.f16x2 g4, qz20, h0, qz20; prmt.b32 h1, lo1, hi1, 0x5410;\n"
        "mov.b32 {xl, xh}, a3; tanh.approx.f16 xr, xl; cvt.u32.u16 lo1, xr; tanh.approx.f16 xr, xh; cvt.u32.u16 hi1, xr; mul.rn.f16x2 a0, qz24, p0; fma.rn.f16x2 p1, qz25, qz25, c; fma.rn.f16x2 g5, qz21, h1, qz21; prmt.b32 h0, lo0, hi0, 0x5410;\n"
        "mov.b32 {xl, xh}, a0; tanh.approx.f16 xr, xl; cvt.u32.u16 lo0, xr; tanh.approx.f16 xr, xh; cvt.u32.u16 hi0, xr; mul.rn.f16x2 a1, qz25, p1; fma.rn.f16x2 p0, qz26, qz26, c; fma.rn.f16x2 g6, qz22, h0, qz22; prmt.b32 h1, lo1, hi1, 0x5410;\n"
        "mov.b32 {xl, xh}, a1; tanh.approx.f16 xr, xl; cvt.u32.u16 lo1, xr; tanh.approx.f16 xr, xh; cvt.u32.u16 hi1, xr; mul.rn.f16x2 a2, qz26, p0; fma.rn.f16x2 p1, qz27, qz27, c; fma.rn.f16x2 g7, qz23, h1, qz23; prmt.b32 h0, lo0, hi0, 0x5410;\n"
        "B26:\n"
        "wgmma.wait_group.sync.aligned 2;\n"
        "wgmma.fence.sync.aligned;\n"
        "add.s64 dt, w2d, 256; wgmma.mma_async.sync.aligned.m64n96k16.f16.f16.f16 {o0,o1,o2,o3,o4,o5,o6,o7,o8,o9,o10,o11,o12,o13,o14,o15,o16,o17,o18,o19,o20,o21,o22,o23}, {g0,g1,g2,g3}, dt, pt, 1, 1, 1;\n"
        "add.s64 dt, w2d, 320; wgmma.mma_async.sync.aligned.m64n96k16.f16.f16.f16 {o0,o1,o2,o3,o4,o5,o6,o7,o8,o9,o10,o11,o12,o13,o14,o15,o16,o17,o18,o19,o20,o21,o22,o23}, {g4,g5,g6,g7}, dt, pt, 1, 1, 1;\n"
        "wgmma.commit_group.sync.aligned;\n"
        "@pz bra.uni B30;\n"
        "mov.b32 {xl, xh}, a2; tanh.approx.f16 xr, xl; cvt.u32.u16 lo0, xr; tanh.approx.f16 xr, xh; cvt.u32.u16 hi0, xr; mul.rn.f16x2 a3, qz27, p1; fma.rn.f16x2 p0, qz28, qz28, c; fma.rn.f16x2 g8, qz24, h0, qz24; prmt.b32 h1, lo1, hi1, 0x5410;\n"
        "mov.b32 {xl, xh}, a3; tanh.approx.f16 xr, xl; cvt.u32.u16 lo1, xr; tanh.approx.f16 xr, xh; cvt.u32.u16 hi1, xr; mul.rn.f16x2 a0, qz28, p0; fma.rn.f16x2 p1, qz29, qz29, c; fma.rn.f16x2 g9, qz25, h1, qz25; prmt.b32 h0, lo0, hi0, 0x5410;\n"
        "mov.b32 {xl, xh}, a0; tanh.approx.f16 xr, xl; cvt.u32.u16 lo0, xr; tanh.approx.f16 xr, xh; cvt.u32.u16 hi0, xr; mul.rn.f16x2 a1, qz29, p1; fma.rn.f16x2 p0, qz30, qz30, c; fma.rn.f16x2 g10, qz26, h0, qz26; prmt.b32 h1, lo1, hi1, 0x5410;\n"
        "mov.b32 {xl, xh}, a1; tanh.approx.f16 xr, xl; cvt.u32.u16 lo1, xr; tanh.approx.f16 xr, xh; cvt.u32.u16 hi1, xr; mul.rn.f16x2 a2, qz30, p0; fma.rn.f16x2 p1, qz31, qz31, c; fma.rn.f16x2 g11, qz27, h1, qz27; prmt.b32 h0, lo0, hi0, 0x5410;\n"
        "B30:\n"
        "wgmma.wait_group.sync.aligned 1;\n"
        "wgmma.fence.sync.aligned;\n"
        "add.s64 dt, w2d, 384; wgmma.mma_async.sync.aligned.m64n96k16.f16.f16.f16 {o0,o1,o2,o3,o4,o5,o6,o7,o8,o9,o10,o11,o12,o13,o14,o15,o16,o17,o18,o19,o20,o21,o22,o23}, {g8,g9,g10,g11}, dt, pt, 1, 1, 1;\n"
        "wgmma.commit_group.sync.aligned;\n"
        "@pz bra.uni B34;\n"
        "mov.b32 {xl, xh}, a2; tanh.approx.f16 xr, xl; cvt.u32.u16 lo0, xr; tanh.approx.f16 xr, xh; cvt.u32.u16 hi0, xr; mul.rn.f16x2 a3, qz31, p1; fma.rn.f16x2 p0, qz0, qz0, c; fma.rn.f16x2 g12, qz28, h0, qz28; prmt.b32 h1, lo1, hi1, 0x5410;\n"
        "mov.b32 {xl, xh}, a3; tanh.approx.f16 xr, xl; cvt.u32.u16 lo1, xr; tanh.approx.f16 xr, xh; cvt.u32.u16 hi1, xr; mul.rn.f16x2 a0, qz0, p0; fma.rn.f16x2 p1, qz1, qz1, c; fma.rn.f16x2 g13, qz29, h1, qz29; prmt.b32 h0, lo0, hi0, 0x5410;\n"
        "mov.b32 {xl, xh}, a0; tanh.approx.f16 xr, xl; cvt.u32.u16 lo0, xr; tanh.approx.f16 xr, xh; cvt.u32.u16 hi0, xr; mul.rn.f16x2 a1, qz1, p1; fma.rn.f16x2 p0, qz2, qz2, c; fma.rn.f16x2 g14, qz30, h0, qz30; prmt.b32 h1, lo1, hi1, 0x5410;\n"
        "mov.b32 {xl, xh}, a1; tanh.approx.f16 xr, xl; cvt.u32.u16 lo1, xr; tanh.approx.f16 xr, xh; cvt.u32.u16 hi1, xr; mul.rn.f16x2 a2, qz2, p0; fma.rn.f16x2 p1, qz3, qz3, c; fma.rn.f16x2 g15, qz31, h1, qz31; prmt.b32 h0, lo0, hi0, 0x5410;\n"
        "B34:\n"
        "wgmma.wait_group.sync.aligned 1;\n"
        "wgmma.fence.sync.aligned;\n"
        "add.s64 dt, w2d, 448; wgmma.mma_async.sync.aligned.m64n96k16.f16.f16.f16 {o0,o1,o2,o3,o4,o5,o6,o7,o8,o9,o10,o11,o12,o13,o14,o15,o16,o17,o18,o19,o20,o21,o22,o23}, {g12,g13,g14,g15}, dt, pt, 1, 1, 1;\n"
        "add.s64 dt, w1d, 2304; wgmma.mma_async.sync.aligned.m64n64k16.f16.f16.f16 {qz16,qz17,qz18,qz19,qz20,qz21,qz22,qz23,qz24,qz25,qz26,qz27,qz28,qz29,qz30,qz31}, {qa0,qa1,qa2,qa3}, dt, pf, 1, 1, 1;\n"
        "add.s64 dt, w1d, 2432; wgmma.mma_async.sync.aligned.m64n64k16.f16.f16.f16 {qz16,qz17,qz18,qz19,qz20,qz21,qz22,qz23,qz24,qz25,qz26,qz27,qz28,qz29,qz30,qz31}, {qa4,qa5,qa6,qa7}, dt, pt, 1, 1, 1;\n"
        "add.s64 dt, w1d, 2560; wgmma.mma_async.sync.aligned.m64n64k16.f16.f16.f16 {qz16,qz17,qz18,qz19,qz20,qz21,qz22,qz23,qz24,qz25,qz26,qz27,qz28,qz29,qz30,qz31}, {qa8,qa9,qa10,qa11}, dt, pt, 1, 1, 1;\n"
        "wgmma.commit_group.sync.aligned;\n"
        "@pz bra.uni B38;\n"
        "mov.b32 {xl, xh}, a2; tanh.approx.f16 xr, xl; cvt.u32.u16 lo0, xr; tanh.approx.f16 xr, xh; cvt.u32.u16 hi0, xr; mul.rn.f16x2 a3, qz3, p1; fma.rn.f16x2 p0, qz4, qz4, c; fma.rn.f16x2 g0, qz0, h0, qz0; prmt.b32 h1, lo1, hi1, 0x5410;\n"
        "mov.b32 {xl, xh}, a3; tanh.approx.f16 xr, xl; cvt.u32.u16 lo1, xr; tanh.approx.f16 xr, xh; cvt.u32.u16 hi1, xr; mul.rn.f16x2 a0, qz4, p0; fma.rn.f16x2 p1, qz5, qz5, c; fma.rn.f16x2 g1, qz1, h1, qz1; prmt.b32 h0, lo0, hi0, 0x5410;\n"
        "mov.b32 {xl, xh}, a0; tanh.approx.f16 xr, xl; cvt.u32.u16 lo0, xr; tanh.approx.f16 xr, xh; cvt.u32.u16 hi0, xr; mul.rn.f16x2 a1, qz5, p1; fma.rn.f16x2 p0, qz6, qz6, c; fma.rn.f16x2 g2, qz2, h0, qz2; prmt.b32 h1, lo1, hi1, 0x5410;\n"
        "mov.b32 {xl, xh}, a1; tanh.approx.f16 xr, xl; cvt.u32.u16 lo1, xr; tanh.approx.f16 xr, xh; cvt.u32.u16 hi1, xr; mul.rn.f16x2 a2, qz6, p0; fma.rn.f16x2 p1, qz7, qz7, c; fma.rn.f16x2 g3, qz3, h1, qz3; prmt.b32 h0, lo0, hi0, 0x5410;\n"
        "B38:\n"
        "wgmma.fence.sync.aligned;\n"
        "add.s64 dt, w1d, 2688; wgmma.mma_async.sync.aligned.m64n64k16.f16.f16.f16 {qz16,qz17,qz18,qz19,qz20,qz21,qz22,qz23,qz24,qz25,qz26,qz27,qz28,qz29,qz30,qz31}, {qa12,qa13,qa14,qa15}, dt, pt, 1, 1, 1;\n"
        "add.s64 dt, w1d, 2816; wgmma.mma_async.sync.aligned.m64n64k16.f16.f16.f16 {qz16,qz17,qz18,qz19,qz20,qz21,qz22,qz23,qz24,qz25,qz26,qz27,qz28,qz29,qz30,qz31}, {qa16,qa17,qa18,qa19}, dt, pt, 1, 1, 1;\n"
        "add.s64 dt, w1d, 2944; wgmma.mma_async.sync.aligned.m64n64k16.f16.f16.f16 {qz16,qz17,qz18,qz19,qz20,qz21,qz22,qz23,qz24,qz25,qz26,qz27,qz28,qz29,qz30,qz31}, {qa20,qa21,qa22,qa23}, dt, pt, 1, 1, 1;\n"
        "wgmma.commit_group.sync.aligned;\n"
        "and.pred pr, pl, pm;\n"
        "@pr bra.uni XPF;\n"
        "XPFB:\n"
        "@pz bra.uni B42;\n"
        "mov.b32 {xl, xh}, a2; tanh.approx.f16 xr, xl; cvt.u32.u16 lo0, xr; tanh.approx.f16 xr, xh; cvt.u32.u16 hi0, xr; mul.rn.f16x2 a3, qz7, p1; fma.rn.f16x2 p0, qz8, qz8, c; fma.rn.f16x2 g4, qz4, h0, qz4; prmt.b32 h1, lo1, hi1, 0x5410;\n"
        "mov.b32 {xl, xh}, a3; tanh.approx.f16 xr, xl; cvt.u32.u16 lo1, xr; tanh.approx.f16 xr, xh; cvt.u32.u16 hi1, xr; mul.rn.f16x2 a0, qz8, p0; fma.rn.f16x2 p1, qz9, qz9, c; fma.rn.f16x2 g5, qz5, h1, qz5; prmt.b32 h0, lo0, hi0, 0x5410;\n"
        "mov.b32 {xl, xh}, a0; tanh.approx.f16 xr, xl; cvt.u32.u16 lo0, xr; tanh.approx.f16 xr, xh; cvt.u32.u16 hi0, xr; mul.rn.f16x2 a1, qz9, p1; fma.rn.f16x2 p0, qz10, qz10, c; fma.rn.f16x2 g6, qz6, h0, qz6; prmt.b32 h1, lo1, hi1, 0x5410;\n"
        "mov.b32 {xl, xh}, a1; tanh.approx.f16 xr, xl; cvt.u32.u16 lo1, xr; tanh.approx.f16 xr, xh; cvt.u32.u16 hi1, xr; mul.rn.f16x2 a2, qz10, p0; fma.rn.f16x2 p1, qz11, qz11, c; fma.rn.f16x2 g7, qz7, h1, qz7; prmt.b32 h0, lo0, hi0, 0x5410;\n"
        "B42:\n"
        "wgmma.wait_group.sync.aligned 2;\n"
        "setp.eq.s32 pr, n, 0;\n"
        "@pr bra.uni SPINW1;\n"
        "BACKW1:\n"
        "wgmma.fence.sync.aligned;\n"
        "add.s64 dt, w2d, 512; wgmma.mma_async.sync.aligned.m64n96k16.f16.f16.f16 {o0,o1,o2,o3,o4,o5,o6,o7,o8,o9,o10,o11,o12,o13,o14,o15,o16,o17,o18,o19,o20,o21,o22,o23}, {g0,g1,g2,g3}, dt, pt, 1, 1, 1;\n"
        "add.s64 dt, w2d, 576; wgmma.mma_async.sync.aligned.m64n96k16.f16.f16.f16 {o0,o1,o2,o3,o4,o5,o6,o7,o8,o9,o10,o11,o12,o13,o14,o15,o16,o17,o18,o19,o20,o21,o22,o23}, {g4,g5,g6,g7}, dt, pt, 1, 1, 1;\n"
        "wgmma.commit_group.sync.aligned;\n"
        "@pz bra.uni B46;\n"
        "mov.b32 {xl, xh}, a2; tanh.approx.f16 xr, xl; cvt.u32.u16 lo0, xr; tanh.approx.f16 xr, xh; cvt.u32.u16 hi0, xr; mul.rn.f16x2 a3, qz11, p1; fma.rn.f16x2 p0, qz12, qz12, c; fma.rn.f16x2 g8, qz8, h0, qz8; prmt.b32 h1, lo1, hi1, 0x5410;\n"
        "mov.b32 {xl, xh}, a3; tanh.approx.f16 xr, xl; cvt.u32.u16 lo1, xr; tanh.approx.f16 xr, xh; cvt.u32.u16 hi1, xr; mul.rn.f16x2 a0, qz12, p0; fma.rn.f16x2 p1, qz13, qz13, c; fma.rn.f16x2 g9, qz9, h1, qz9; prmt.b32 h0, lo0, hi0, 0x5410;\n"
        "mov.b32 {xl, xh}, a0; tanh.approx.f16 xr, xl; cvt.u32.u16 lo0, xr; tanh.approx.f16 xr, xh; cvt.u32.u16 hi0, xr; mul.rn.f16x2 a1, qz13, p1; fma.rn.f16x2 p0, qz14, qz14, c; fma.rn.f16x2 g10, qz10, h0, qz10; prmt.b32 h1, lo1, hi1, 0x5410;\n"
        "mov.b32 {xl, xh}, a1; tanh.approx.f16 xr, xl; cvt.u32.u16 lo1, xr; tanh.approx.f16 xr, xh; cvt.u32.u16 hi1, xr; mul.rn.f16x2 a2, qz14, p0; fma.rn.f16x2 p1, qz15, qz15, c; fma.rn.f16x2 g11, qz11, h1, qz11; prmt.b32 h0, lo0, hi0, 0x5410;\n"
        "B46:\n"
        "wgmma.wait_group.sync.aligned 1;\n"
        "wgmma.fence.sync.aligned;\n"
        "add.s64 dt, w2d, 640; wgmma.mma_async.sync.aligned.m64n96k16.f16.f16.f16 {o0,o1,o2,o3,o4,o5,o6,o7,o8,o9,o10,o11,o12,o13,o14,o15,o16,o17,o18,o19,o20,o21,o22,o23}, {g8,g9,g10,g11}, dt, pt, 1, 1, 1;\n"
        "wgmma.commit_group.sync.aligned;\n"
        "mad.lo.u32 tt, n, 8, tbar;\n"
        "@pn mbarrier.arrive.shared::cta.b64 _, [tt+64];\n"
        "@pz bra.uni B50;\n"
        "mov.b32 {xl, xh}, a2; tanh.approx.f16 xr, xl; cvt.u32.u16 lo0, xr; tanh.approx.f16 xr, xh; cvt.u32.u16 hi0, xr; mul.rn.f16x2 a3, qz15, p1; fma.rn.f16x2 p0, qz16, qz16, c; fma.rn.f16x2 g12, qz12, h0, qz12; prmt.b32 h1, lo1, hi1, 0x5410;\n"
        "mov.b32 {xl, xh}, a3; tanh.approx.f16 xr, xl; cvt.u32.u16 lo1, xr; tanh.approx.f16 xr, xh; cvt.u32.u16 hi1, xr; mul.rn.f16x2 a0, qz16, p0; fma.rn.f16x2 p1, qz17, qz17, c; fma.rn.f16x2 g13, qz13, h1, qz13; prmt.b32 h0, lo0, hi0, 0x5410;\n"
        "mov.b32 {xl, xh}, a0; tanh.approx.f16 xr, xl; cvt.u32.u16 lo0, xr; tanh.approx.f16 xr, xh; cvt.u32.u16 hi0, xr; mul.rn.f16x2 a1, qz17, p1; fma.rn.f16x2 p0, qz18, qz18, c; fma.rn.f16x2 g14, qz14, h0, qz14; prmt.b32 h1, lo1, hi1, 0x5410;\n"
        "mov.b32 {xl, xh}, a1; tanh.approx.f16 xr, xl; cvt.u32.u16 lo1, xr; tanh.approx.f16 xr, xh; cvt.u32.u16 hi1, xr; mul.rn.f16x2 a2, qz18, p0; fma.rn.f16x2 p1, qz19, qz19, c; fma.rn.f16x2 g15, qz15, h1, qz15; prmt.b32 h0, lo0, hi0, 0x5410;\n"
        "B50:\n"
        "wgmma.wait_group.sync.aligned 1;\n"
        "wgmma.fence.sync.aligned;\n"
        "add.s64 dt, w2d, 704; wgmma.mma_async.sync.aligned.m64n96k16.f16.f16.f16 {o0,o1,o2,o3,o4,o5,o6,o7,o8,o9,o10,o11,o12,o13,o14,o15,o16,o17,o18,o19,o20,o21,o22,o23}, {g12,g13,g14,g15}, dt, pt, 1, 1, 1;\n"
        "add.s64 dt, w1d, 3072; wgmma.mma_async.sync.aligned.m64n64k16.f16.f16.f16 {qz0,qz1,qz2,qz3,qz4,qz5,qz6,qz7,qz8,qz9,qz10,qz11,qz12,qz13,qz14,qz15}, {qa0,qa1,qa2,qa3}, dt, pf, 1, 1, 1;\n"
        "add.s64 dt, w1d, 3200; wgmma.mma_async.sync.aligned.m64n64k16.f16.f16.f16 {qz0,qz1,qz2,qz3,qz4,qz5,qz6,qz7,qz8,qz9,qz10,qz11,qz12,qz13,qz14,qz15}, {qa4,qa5,qa6,qa7}, dt, pt, 1, 1, 1;\n"
        "add.s64 dt, w1d, 3328; wgmma.mma_async.sync.aligned.m64n64k16.f16.f16.f16 {qz0,qz1,qz2,qz3,qz4,qz5,qz6,qz7,qz8,qz9,qz10,qz11,qz12,qz13,qz14,qz15}, {qa8,qa9,qa10,qa11}, dt, pt, 1, 1, 1;\n"
        "wgmma.commit_group.sync.aligned;\n"
        "@pz bra.uni B54;\n"
        "mov.b32 {xl, xh}, a2; tanh.approx.f16 xr, xl; cvt.u32.u16 lo0, xr; tanh.approx.f16 xr, xh; cvt.u32.u16 hi0, xr; mul.rn.f16x2 a3, qz19, p1; fma.rn.f16x2 p0, qz20, qz20, c; fma.rn.f16x2 g0, qz16, h0, qz16; prmt.b32 h1, lo1, hi1, 0x5410;\n"
        "mov.b32 {xl, xh}, a3; tanh.approx.f16 xr, xl; cvt.u32.u16 lo1, xr; tanh.approx.f16 xr, xh; cvt.u32.u16 hi1, xr; mul.rn.f16x2 a0, qz20, p0; fma.rn.f16x2 p1, qz21, qz21, c; fma.rn.f16x2 g1, qz17, h1, qz17; prmt.b32 h0, lo0, hi0, 0x5410;\n"
        "mov.b32 {xl, xh}, a0; tanh.approx.f16 xr, xl; cvt.u32.u16 lo0, xr; tanh.approx.f16 xr, xh; cvt.u32.u16 hi0, xr; mul.rn.f16x2 a1, qz21, p1; fma.rn.f16x2 p0, qz22, qz22, c; fma.rn.f16x2 g2, qz18, h0, qz18; prmt.b32 h1, lo1, hi1, 0x5410;\n"
        "mov.b32 {xl, xh}, a1; tanh.approx.f16 xr, xl; cvt.u32.u16 lo1, xr; tanh.approx.f16 xr, xh; cvt.u32.u16 hi1, xr; mul.rn.f16x2 a2, qz22, p0; fma.rn.f16x2 p1, qz23, qz23, c; fma.rn.f16x2 g3, qz19, h1, qz19; prmt.b32 h0, lo0, hi0, 0x5410;\n"
        "B54:\n"
        "wgmma.fence.sync.aligned;\n"
        "add.s64 dt, w1d, 3456; wgmma.mma_async.sync.aligned.m64n64k16.f16.f16.f16 {qz0,qz1,qz2,qz3,qz4,qz5,qz6,qz7,qz8,qz9,qz10,qz11,qz12,qz13,qz14,qz15}, {qa12,qa13,qa14,qa15}, dt, pt, 1, 1, 1;\n"
        "add.s64 dt, w1d, 3584; wgmma.mma_async.sync.aligned.m64n64k16.f16.f16.f16 {qz0,qz1,qz2,qz3,qz4,qz5,qz6,qz7,qz8,qz9,qz10,qz11,qz12,qz13,qz14,qz15}, {qa16,qa17,qa18,qa19}, dt, pt, 1, 1, 1;\n"
        "add.s64 dt, w1d, 3712; wgmma.mma_async.sync.aligned.m64n64k16.f16.f16.f16 {qz0,qz1,qz2,qz3,qz4,qz5,qz6,qz7,qz8,qz9,qz10,qz11,qz12,qz13,qz14,qz15}, {qa20,qa21,qa22,qa23}, dt, pt, 1, 1, 1;\n"
        "wgmma.commit_group.sync.aligned;\n"
        "@pz bra.uni B58;\n"
        "mov.b32 {xl, xh}, a2; tanh.approx.f16 xr, xl; cvt.u32.u16 lo0, xr; tanh.approx.f16 xr, xh; cvt.u32.u16 hi0, xr; mul.rn.f16x2 a3, qz23, p1; fma.rn.f16x2 p0, qz24, qz24, c; fma.rn.f16x2 g4, qz20, h0, qz20; prmt.b32 h1, lo1, hi1, 0x5410;\n"
        "mov.b32 {xl, xh}, a3; tanh.approx.f16 xr, xl; cvt.u32.u16 lo1, xr; tanh.approx.f16 xr, xh; cvt.u32.u16 hi1, xr; mul.rn.f16x2 a0, qz24, p0; fma.rn.f16x2 p1, qz25, qz25, c; fma.rn.f16x2 g5, qz21, h1, qz21; prmt.b32 h0, lo0, hi0, 0x5410;\n"
        "mov.b32 {xl, xh}, a0; tanh.approx.f16 xr, xl; cvt.u32.u16 lo0, xr; tanh.approx.f16 xr, xh; cvt.u32.u16 hi0, xr; mul.rn.f16x2 a1, qz25, p1; fma.rn.f16x2 p0, qz26, qz26, c; fma.rn.f16x2 g6, qz22, h0, qz22; prmt.b32 h1, lo1, hi1, 0x5410;\n"
        "mov.b32 {xl, xh}, a1; tanh.approx.f16 xr, xl; cvt.u32.u16 lo1, xr; tanh.approx.f16 xr, xh; cvt.u32.u16 hi1, xr; mul.rn.f16x2 a2, qz26, p0; fma.rn.f16x2 p1, qz27, qz27, c; fma.rn.f16x2 g7, qz23, h1, qz23; prmt.b32 h0, lo0, hi0, 0x5410;\n"
        "B58:\n"
        "wgmma.wait_group.sync.aligned 2;\n"
        "wgmma.fence.sync.aligned;\n"
        "add.s64 dt, w2d, 768; wgmma.mma_async.sync.aligned.m64n96k16.f16.f16.f16 {o0,o1,o2,o3,o4,o5,o6,o7,o8,o9,o10,o11,o12,o13,o14,o15,o16,o17,o18,o19,o20,o21,o22,o23}, {g0,g1,g2,g3}, dt, pt, 1, 1, 1;\n"
        "add.s64 dt, w2d, 832; wgmma.mma_async.sync.aligned.m64n96k16.f16.f16.f16 {o0,o1,o2,o3,o4,o5,o6,o7,o8,o9,o10,o11,o12,o13,o14,o15,o16,o17,o18,o19,o20,o21,o22,o23}, {g4,g5,g6,g7}, dt, pt, 1, 1, 1;\n"
        "wgmma.commit_group.sync.aligned;\n"
        "@pz bra.uni B62;\n"
        "mov.b32 {xl, xh}, a2; tanh.approx.f16 xr, xl; cvt.u32.u16 lo0, xr; tanh.approx.f16 xr, xh; cvt.u32.u16 hi0, xr; mul.rn.f16x2 a3, qz27, p1; fma.rn.f16x2 p0, qz28, qz28, c; fma.rn.f16x2 g8, qz24, h0, qz24; prmt.b32 h1, lo1, hi1, 0x5410;\n"
        "mov.b32 {xl, xh}, a3; tanh.approx.f16 xr, xl; cvt.u32.u16 lo1, xr; tanh.approx.f16 xr, xh; cvt.u32.u16 hi1, xr; mul.rn.f16x2 a0, qz28, p0; fma.rn.f16x2 p1, qz29, qz29, c; fma.rn.f16x2 g9, qz25, h1, qz25; prmt.b32 h0, lo0, hi0, 0x5410;\n"
        "mov.b32 {xl, xh}, a0; tanh.approx.f16 xr, xl; cvt.u32.u16 lo0, xr; tanh.approx.f16 xr, xh; cvt.u32.u16 hi0, xr; mul.rn.f16x2 a1, qz29, p1; fma.rn.f16x2 p0, qz30, qz30, c; fma.rn.f16x2 g10, qz26, h0, qz26; prmt.b32 h1, lo1, hi1, 0x5410;\n"
        "mov.b32 {xl, xh}, a1; tanh.approx.f16 xr, xl; cvt.u32.u16 lo1, xr; tanh.approx.f16 xr, xh; cvt.u32.u16 hi1, xr; mul.rn.f16x2 a2, qz30, p0; fma.rn.f16x2 p1, qz31, qz31, c; fma.rn.f16x2 g11, qz27, h1, qz27; prmt.b32 h0, lo0, hi0, 0x5410;\n"
        "B62:\n"
        "wgmma.wait_group.sync.aligned 1;\n"
        "wgmma.fence.sync.aligned;\n"
        "add.s64 dt, w2d, 896; wgmma.mma_async.sync.aligned.m64n96k16.f16.f16.f16 {o0,o1,o2,o3,o4,o5,o6,o7,o8,o9,o10,o11,o12,o13,o14,o15,o16,o17,o18,o19,o20,o21,o22,o23}, {g8,g9,g10,g11}, dt, pt, 1, 1, 1;\n"
        "wgmma.commit_group.sync.aligned;\n"
        "@pz bra.uni B66;\n"
        "mov.b32 {xl, xh}, a2; tanh.approx.f16 xr, xl; cvt.u32.u16 lo0, xr; tanh.approx.f16 xr, xh; cvt.u32.u16 hi0, xr; mul.rn.f16x2 a3, qz31, p1; fma.rn.f16x2 p0, qz0, qz0, c; fma.rn.f16x2 g12, qz28, h0, qz28; prmt.b32 h1, lo1, hi1, 0x5410;\n"
        "mov.b32 {xl, xh}, a3; tanh.approx.f16 xr, xl; cvt.u32.u16 lo1, xr; tanh.approx.f16 xr, xh; cvt.u32.u16 hi1, xr; mul.rn.f16x2 a0, qz0, p0; fma.rn.f16x2 p1, qz1, qz1, c; fma.rn.f16x2 g13, qz29, h1, qz29; prmt.b32 h0, lo0, hi0, 0x5410;\n"
        "mov.b32 {xl, xh}, a0; tanh.approx.f16 xr, xl; cvt.u32.u16 lo0, xr; tanh.approx.f16 xr, xh; cvt.u32.u16 hi0, xr; mul.rn.f16x2 a1, qz1, p1; fma.rn.f16x2 p0, qz2, qz2, c; fma.rn.f16x2 g14, qz30, h0, qz30; prmt.b32 h1, lo1, hi1, 0x5410;\n"
        "mov.b32 {xl, xh}, a1; tanh.approx.f16 xr, xl; cvt.u32.u16 lo1, xr; tanh.approx.f16 xr, xh; cvt.u32.u16 hi1, xr; mul.rn.f16x2 a2, qz2, p0; fma.rn.f16x2 p1, qz3, qz3, c; fma.rn.f16x2 g15, qz31, h1, qz31; prmt.b32 h0, lo0, hi0, 0x5410;\n"
        "B66:\n"
        "wgmma.wait_group.sync.aligned 1;\n"
        "wgmma.fence.sync.aligned;\n"
        "add.s64 dt, w2d, 960; wgmma.mma_async.sync.aligned.m64n96k16.f16.f16.f16 {o0,o1,o2,o3,o4,o5,o6,o7,o8,o9,o10,o11,o12,o13,o14,o15,o16,o17,o18,o19,o20,o21,o22,o23}, {g12,g13,g14,g15}, dt, pt, 1, 1, 1;\n"
        "add.s64 dt, w1d, 3840; wgmma.mma_async.sync.aligned.m64n64k16.f16.f16.f16 {qz16,qz17,qz18,qz19,qz20,qz21,qz22,qz23,qz24,qz25,qz26,qz27,qz28,qz29,qz30,qz31}, {qa0,qa1,qa2,qa3}, dt, pf, 1, 1, 1;\n"
        "add.s64 dt, w1d, 3968; wgmma.mma_async.sync.aligned.m64n64k16.f16.f16.f16 {qz16,qz17,qz18,qz19,qz20,qz21,qz22,qz23,qz24,qz25,qz26,qz27,qz28,qz29,qz30,qz31}, {qa4,qa5,qa6,qa7}, dt, pt, 1, 1, 1;\n"
        "add.s64 dt, w1d, 4096; wgmma.mma_async.sync.aligned.m64n64k16.f16.f16.f16 {qz16,qz17,qz18,qz19,qz20,qz21,qz22,qz23,qz24,qz25,qz26,qz27,qz28,qz29,qz30,qz31}, {qa8,qa9,qa10,qa11}, dt, pt, 1, 1, 1;\n"
        "wgmma.commit_group.sync.aligned;\n"
        "@pz bra.uni B70;\n"
        "mov.b32 {xl, xh}, a2; tanh.approx.f16 xr, xl; cvt.u32.u16 lo0, xr; tanh.approx.f16 xr, xh; cvt.u32.u16 hi0, xr; mul.rn.f16x2 a3, qz3, p1; fma.rn.f16x2 p0, qz4, qz4, c; fma.rn.f16x2 g0, qz0, h0, qz0; prmt.b32 h1, lo1, hi1, 0x5410;\n"
        "mov.b32 {xl, xh}, a3; tanh.approx.f16 xr, xl; cvt.u32.u16 lo1, xr; tanh.approx.f16 xr, xh; cvt.u32.u16 hi1, xr; mul.rn.f16x2 a0, qz4, p0; fma.rn.f16x2 p1, qz5, qz5, c; fma.rn.f16x2 g1, qz1, h1, qz1; prmt.b32 h0, lo0, hi0, 0x5410;\n"
        "mov.b32 {xl, xh}, a0; tanh.approx.f16 xr, xl; cvt.u32.u16 lo0, xr; tanh.approx.f16 xr, xh; cvt.u32.u16 hi0, xr; mul.rn.f16x2 a1, qz5, p1; fma.rn.f16x2 p0, qz6, qz6, c; fma.rn.f16x2 g2, qz2, h0, qz2; prmt.b32 h1, lo1, hi1, 0x5410;\n"
        "mov.b32 {xl, xh}, a1; tanh.approx.f16 xr, xl; cvt.u32.u16 lo1, xr; tanh.approx.f16 xr, xh; cvt.u32.u16 hi1, xr; mul.rn.f16x2 a2, qz6, p0; fma.rn.f16x2 p1, qz7, qz7, c; fma.rn.f16x2 g3, qz3, h1, qz3; prmt.b32 h0, lo0, hi0, 0x5410;\n"
        "B70:\n"
        "wgmma.fence.sync.aligned;\n"
        "add.s64 dt, w1d, 4224; wgmma.mma_async.sync.aligned.m64n64k16.f16.f16.f16 {qz16,qz17,qz18,qz19,qz20,qz21,qz22,qz23,qz24,qz25,qz26,qz27,qz28,qz29,qz30,qz31}, {qa12,qa13,qa14,qa15}, dt, pt, 1, 1, 1;\n"
        "add.s64 dt, w1d, 4352; wgmma.mma_async.sync.aligned.m64n64k16.f16.f16.f16 {qz16,qz17,qz18,qz19,qz20,qz21,qz22,qz23,qz24,qz25,qz26,qz27,qz28,qz29,qz30,qz31}, {qa16,qa17,qa18,qa19}, dt, pt, 1, 1, 1;\n"
        "add.s64 dt, w1d, 4480; wgmma.mma_async.sync.aligned.m64n64k16.f16.f16.f16 {qz16,qz17,qz18,qz19,qz20,qz21,qz22,qz23,qz24,qz25,qz26,qz27,qz28,qz29,qz30,qz31}, {qa20,qa21,qa22,qa23}, dt, pt, 1, 1, 1;\n"
        "wgmma.commit_group.sync.aligned;\n"
        "@pz bra.uni B74;\n"
        "mov.b32 {xl, xh}, a2; tanh.approx.f16 xr, xl; cvt.u32.u16 lo0, xr; tanh.approx.f16 xr, xh; cvt.u32.u16 hi0, xr; mul.rn.f16x2 a3, qz7, p1; fma.rn.f16x2 p0, qz8, qz8, c; fma.rn.f16x2 g4, qz4, h0, qz4; prmt.b32 h1, lo1, hi1, 0x5410;\n"
        "mov.b32 {xl, xh}, a3; tanh.approx.f16 xr, xl; cvt.u32.u16 lo1, xr; tanh.approx.f16 xr, xh; cvt.u32.u16 hi1, xr; mul.rn.f16x2 a0, qz8, p0; fma.rn.f16x2 p1, qz9, qz9, c; fma.rn.f16x2 g5, qz5, h1, qz5; prmt.b32 h0, lo0, hi0, 0x5410;\n"
        "mov.b32 {xl, xh}, a0; tanh.approx.f16 xr, xl; cvt.u32.u16 lo0, xr; tanh.approx.f16 xr, xh; cvt.u32.u16 hi0, xr; mul.rn.f16x2 a1, qz9, p1; fma.rn.f16x2 p0, qz10, qz10, c; fma.rn.f16x2 g6, qz6, h0, qz6; prmt.b32 h1, lo1, hi1, 0x5410;\n"
        "mov.b32 {xl, xh}, a1; tanh.approx.f16 xr, xl; cvt.u32.u16 lo1, xr; tanh.approx.f16 xr, xh; cvt.u32.u16 hi1, xr; mul.rn.f16x2 a2, qz10, p0; fma.rn.f16x2 p1, qz11, qz11, c; fma.rn.f16x2 g7, qz7, h1, qz7; prmt.b32 h0, lo0, hi0, 0x5410;\n"
        "B74:\n"
        "wgmma.wait_group.sync.aligned 0;\n"
        "setp.eq.s32 pr, n, 0;\n"
        "@pr bra.uni SPINW2;\n"
        "BACKW2:\n"
        "wgmma.fence.sync.aligned;\n"
        "add.s64 dt, w2d, 1024; wgmma.mma_async.sync.aligned.m64n96k16.f16.f16.f16 {o0,o1,o2,o3,o4,o5,o6,o7,o8,o9,o10,o11,o12,o13,o14,o15,o16,o17,o18,o19,o20,o21,o22,o23}, {g0,g1,g2,g3}, dt, pt, 1, 1, 1;\n"
        "add.s64 dt, w2d, 1088; wgmma.mma_async.sync.aligned.m64n96k16.f16.f16.f16 {o0,o1,o2,o3,o4,o5,o6,o7,o8,o9,o10,o11,o12,o13,o14,o15,o16,o17,o18,o19,o20,o21,o22,o23}, {g4,g5,g6,g7}, dt, pt, 1, 1, 1;\n"
        "wgmma.commit_group.sync.aligned;\n"
        "@pz bra.uni B78;\n"
        "mov.b32 {xl, xh}, a2; tanh.approx.f16 xr, xl; cvt.u32.u16 lo0, xr; tanh.approx.f16 xr, xh; cvt.u32.u16 hi0, xr; mul.rn.f16x2 a3, qz11, p1; fma.rn.f16x2 p0, qz12, qz12, c; fma.rn.f16x2 g8, qz8, h0, qz8; prmt.b32 h1, lo1, hi1, 0x5410;\n"
        "mov.b32 {xl, xh}, a3; tanh.approx.f16 xr, xl; cvt.u32.u16 lo1, xr; tanh.approx.f16 xr, xh; cvt.u32.u16 hi1, xr; mul.rn.f16x2 a0, qz12, p0; fma.rn.f16x2 p1, qz13, qz13, c; fma.rn.f16x2 g9, qz9, h1, qz9; prmt.b32 h0, lo0, hi0, 0x5410;\n"
        "mov.b32 {xl, xh}, a0; tanh.approx.f16 xr, xl; cvt.u32.u16 lo0, xr; tanh.approx.f16 xr, xh; cvt.u32.u16 hi0, xr; mul.rn.f16x2 a1, qz13, p1; fma.rn.f16x2 p0, qz14, qz14, c; fma.rn.f16x2 g10, qz10, h0, qz10; prmt.b32 h1, lo1, hi1, 0x5410;\n"
        "mov.b32 {xl, xh}, a1; tanh.approx.f16 xr, xl; cvt.u32.u16 lo1, xr; tanh.approx.f16 xr, xh; cvt.u32.u16 hi1, xr; mul.rn.f16x2 a2, qz14, p0; fma.rn.f16x2 p1, qz15, qz15, c; fma.rn.f16x2 g11, qz11, h1, qz11; prmt.b32 h0, lo0, hi0, 0x5410;\n"
        "B78:\n"
        "@!pm bra.uni BACKY;\n"
        "add.u32 tt, n, 1; and.b32 tt, tt, 1; mbarrier.try_wait.parity.shared::cta.b64 pw, [ybar], tt;\n"
        "@!pw bra.uni SPINY;\n"
        "BACKY:\n"
        "@pz bra.uni B80;\n"
        "and.b32 ad, %6, 0xffff; xor.b32 ad, ad, 0; add.u32 ad, ad, %5; ldmatrix.sync.aligned.m8n8.x4.shared.b16 {qa0,qa1,qa2,qa3}, [ad];\n"
        "and.b32 ad, %6, 0xffff; xor.b32 ad, ad, 32; add.u32 ad, ad, %5; ldmatrix.sync.aligned.m8n8.x4.shared.b16 {qa4,qa5,qa6,qa7}, [ad];\n"
        "and.b32 ad, %6, 0xffff; xor.b32 ad, ad, 64; add.u32 ad, ad, %5; ldmatrix.sync.aligned.m8n8.x4.shared.b16 {qa8,qa9,qa10,qa11}, [ad];\n"
        "and.b32 ad, %6, 0xffff; xor.b32 ad, ad, 96; add.u32 ad, ad, %5; ldmatrix.sync.aligned.m8n8.x4.shared.b16 {qa12,qa13,qa14,qa15}, [ad];\n"
        "shr.u32 ad, %6, 16; xor.b32 ad, ad, 0; add.u32 ad, ad, %5; ldmatrix.sync.aligned.m8n8.x4.shared.b16 {qa16,qa17,qa18,qa19}, [ad];\n"
        "shr.u32 ad, %6, 16; xor.b32 ad, ad, 32; add.u32 ad, ad, %5; ldmatrix.sync.aligned.m8n8.x4.shared.b16 {qa20,qa21,qa22,qa23}, [ad];\n"
        "mov.b32 {xl, xh}, a2; tanh.approx.f16 xr, xl; cvt.u32.u16 lo0, xr; tanh.approx.f16 xr, xh; cvt.u32.u16 hi0, xr; mul.rn.f16x2 a3, qz15, p1; fma.rn.f16x2 p0, qz16, qz16, c; fma.rn.f16x2 g12, qz12, h0, qz12; prmt.b32 h1, lo1, hi1, 0x5410;\n"
        "mov.b32 {xl, xh}, a3; tanh.approx.f16 xr, xl; cvt.u32.u16 lo1, xr; tanh.approx.f16 xr, xh; cvt.u32.u16 hi1, xr; mul.rn.f16x2 a0, qz16, p0; fma.rn.f16x2 p1, qz17, qz17, c; fma.rn.f16x2 g13, qz13, h1, qz13; prmt.b32 h0, lo0, hi0, 0x5410;\n"
        "B80:\n"
        "@!pm bra.uni XLOADB;\n"
        "fence.proxy.async.shared::cta;\n"
        "add.u32 tt, id, 0;\n"
        "@pl bra.uni XLOAD;\n"
        "bar.arrive tt, 128;\n"
        "XLOADB:\n"
        "wgmma.fence.sync.aligned;\n"
        "add.s64 dt, w2d, 1152; wgmma.mma_async.sync.aligned.m64n96k16.f16.f16.f16 {o0,o1,o2,o3,o4,o5,o6,o7,o8,o9,o10,o11,o12,o13,o14,o15,o16,o17,o18,o19,o20,o21,o22,o23}, {g8,g9,g10,g11}, dt, pt, 1, 1, 1;\n"
        "wgmma.commit_group.sync.aligned;\n"
        "@pz bra.uni B82;\n"
        "mov.b32 {xl, xh}, a0; tanh.approx.f16 xr, xl; cvt.u32.u16 lo0, xr; tanh.approx.f16 xr, xh; cvt.u32.u16 hi0, xr; mul.rn.f16x2 a1, qz17, p1; fma.rn.f16x2 p0, qz18, qz18, c; fma.rn.f16x2 g14, qz14, h0, qz14; prmt.b32 h1, lo1, hi1, 0x5410;\n"
        "mov.b32 {xl, xh}, a1; tanh.approx.f16 xr, xl; cvt.u32.u16 lo1, xr; tanh.approx.f16 xr, xh; cvt.u32.u16 hi1, xr; mul.rn.f16x2 a2, qz18, p0; fma.rn.f16x2 p1, qz19, qz19, c; fma.rn.f16x2 g15, qz15, h1, qz15; prmt.b32 h0, lo0, hi0, 0x5410;\n"
        "B82:\n"
        "wgmma.wait_group.sync.aligned 1;\n"
        "@!pm bra.uni SKIP0;\n"
        "wgmma.fence.sync.aligned;\n"
        "add.s64 dt, w1d, 0; wgmma.mma_async.sync.aligned.m64n64k16.f16.f16.f16 {qz0,qz1,qz2,qz3,qz4,qz5,qz6,qz7,qz8,qz9,qz10,qz11,qz12,qz13,qz14,qz15}, {qa0,qa1,qa2,qa3}, dt, pf, 1, 1, 1;\n"
        "add.s64 dt, w1d, 128; wgmma.mma_async.sync.aligned.m64n64k16.f16.f16.f16 {qz0,qz1,qz2,qz3,qz4,qz5,qz6,qz7,qz8,qz9,qz10,qz11,qz12,qz13,qz14,qz15}, {qa4,qa5,qa6,qa7}, dt, pt, 1, 1, 1;\n"
        "add.s64 dt, w1d, 256; wgmma.mma_async.sync.aligned.m64n64k16.f16.f16.f16 {qz0,qz1,qz2,qz3,qz4,qz5,qz6,qz7,qz8,qz9,qz10,qz11,qz12,qz13,qz14,qz15}, {qa8,qa9,qa10,qa11}, dt, pt, 1, 1, 1;\n"
        "SKIP0:\n"
        "wgmma.fence.sync.aligned;\n"
        "add.s64 dt, w2d, 1216; wgmma.mma_async.sync.aligned.m64n96k16.f16.f16.f16 {o0,o1,o2,o3,o4,o5,o6,o7,o8,o9,o10,o11,o12,o13,o14,o15,o16,o17,o18,o19,o20,o21,o22,o23}, {g12,g13,g14,g15}, dt, pt, 1, 1, 1;\n"
        "wgmma.commit_group.sync.aligned;\n"
        "@pz bra.uni B86;\n"
        "mov.b32 {xl, xh}, a2; tanh.approx.f16 xr, xl; cvt.u32.u16 lo0, xr; tanh.approx.f16 xr, xh; cvt.u32.u16 hi0, xr; mul.rn.f16x2 a3, qz19, p1; fma.rn.f16x2 p0, qz20, qz20, c; fma.rn.f16x2 g0, qz16, h0, qz16; prmt.b32 h1, lo1, hi1, 0x5410;\n"
        "mov.b32 {xl, xh}, a3; tanh.approx.f16 xr, xl; cvt.u32.u16 lo1, xr; tanh.approx.f16 xr, xh; cvt.u32.u16 hi1, xr; mul.rn.f16x2 a0, qz20, p0; fma.rn.f16x2 p1, qz21, qz21, c; fma.rn.f16x2 g1, qz17, h1, qz17; prmt.b32 h0, lo0, hi0, 0x5410;\n"
        "mov.b32 {xl, xh}, a0; tanh.approx.f16 xr, xl; cvt.u32.u16 lo0, xr; tanh.approx.f16 xr, xh; cvt.u32.u16 hi0, xr; mul.rn.f16x2 a1, qz21, p1; fma.rn.f16x2 p0, qz22, qz22, c; fma.rn.f16x2 g2, qz18, h0, qz18; prmt.b32 h1, lo1, hi1, 0x5410;\n"
        "mov.b32 {xl, xh}, a1; tanh.approx.f16 xr, xl; cvt.u32.u16 lo1, xr; tanh.approx.f16 xr, xh; cvt.u32.u16 hi1, xr; mul.rn.f16x2 a2, qz22, p0; fma.rn.f16x2 p1, qz23, qz23, c; fma.rn.f16x2 g3, qz19, h1, qz19; prmt.b32 h0, lo0, hi0, 0x5410;\n"
        "B86:\n"
        "@!pm bra.uni SKIP1;\n"
        "wgmma.fence.sync.aligned;\n"
        "add.s64 dt, w1d, 384; wgmma.mma_async.sync.aligned.m64n64k16.f16.f16.f16 {qz0,qz1,qz2,qz3,qz4,qz5,qz6,qz7,qz8,qz9,qz10,qz11,qz12,qz13,qz14,qz15}, {qa12,qa13,qa14,qa15}, dt, pt, 1, 1, 1;\n"
        "add.s64 dt, w1d, 512; wgmma.mma_async.sync.aligned.m64n64k16.f16.f16.f16 {qz0,qz1,qz2,qz3,qz4,qz5,qz6,qz7,qz8,qz9,qz10,qz11,qz12,qz13,qz14,qz15}, {qa16,qa17,qa18,qa19}, dt, pt, 1, 1, 1;\n"
        "add.s64 dt, w1d, 640; wgmma.mma_async.sync.aligned.m64n64k16.f16.f16.f16 {qz0,qz1,qz2,qz3,qz4,qz5,qz6,qz7,qz8,qz9,qz10,qz11,qz12,qz13,qz14,qz15}, {qa20,qa21,qa22,qa23}, dt, pt, 1, 1, 1;\n"
        "SKIP1:\n"
        "@pz bra.uni B90;\n"
        "mov.b32 {xl, xh}, a2; tanh.approx.f16 xr, xl; cvt.u32.u16 lo0, xr; tanh.approx.f16 xr, xh; cvt.u32.u16 hi0, xr; mul.rn.f16x2 a3, qz23, p1; fma.rn.f16x2 p0, qz24, qz24, c; fma.rn.f16x2 g4, qz20, h0, qz20; prmt.b32 h1, lo1, hi1, 0x5410;\n"
        "mov.b32 {xl, xh}, a3; tanh.approx.f16 xr, xl; cvt.u32.u16 lo1, xr; tanh.approx.f16 xr, xh; cvt.u32.u16 hi1, xr; mul.rn.f16x2 a0, qz24, p0; fma.rn.f16x2 p1, qz25, qz25, c; fma.rn.f16x2 g5, qz21, h1, qz21; prmt.b32 h0, lo0, hi0, 0x5410;\n"
        "mov.b32 {xl, xh}, a0; tanh.approx.f16 xr, xl; cvt.u32.u16 lo0, xr; tanh.approx.f16 xr, xh; cvt.u32.u16 hi0, xr; mul.rn.f16x2 a1, qz25, p1; fma.rn.f16x2 p0, qz26, qz26, c; fma.rn.f16x2 g6, qz22, h0, qz22; prmt.b32 h1, lo1, hi1, 0x5410;\n"
        "mov.b32 {xl, xh}, a1; tanh.approx.f16 xr, xl; cvt.u32.u16 lo1, xr; tanh.approx.f16 xr, xh; cvt.u32.u16 hi1, xr; mul.rn.f16x2 a2, qz26, p0; fma.rn.f16x2 p1, qz27, qz27, c; fma.rn.f16x2 g7, qz23, h1, qz23; prmt.b32 h0, lo0, hi0, 0x5410;\n"
        "B90:\n"
        "wgmma.wait_group.sync.aligned 1;\n"
        "wgmma.fence.sync.aligned;\n"
        "add.s64 dt, w2d, 1280; wgmma.mma_async.sync.aligned.m64n96k16.f16.f16.f16 {o0,o1,o2,o3,o4,o5,o6,o7,o8,o9,o10,o11,o12,o13,o14,o15,o16,o17,o18,o19,o20,o21,o22,o23}, {g0,g1,g2,g3}, dt, pt, 1, 1, 1;\n"
        "add.s64 dt, w2d, 1344; wgmma.mma_async.sync.aligned.m64n96k16.f16.f16.f16 {o0,o1,o2,o3,o4,o5,o6,o7,o8,o9,o10,o11,o12,o13,o14,o15,o16,o17,o18,o19,o20,o21,o22,o23}, {g4,g5,g6,g7}, dt, pt, 1, 1, 1;\n"
        "wgmma.commit_group.sync.aligned;\n"
        "@pz bra.uni B94;\n"
        "mov.b32 {xl, xh}, a2; tanh.approx.f16 xr, xl; cvt.u32.u16 lo0, xr; tanh.approx.f16 xr, xh; cvt.u32.u16 hi0, xr; mul.rn.f16x2 a3, qz27, p1; fma.rn.f16x2 p0, qz28, qz28, c; fma.rn.f16x2 g8, qz24, h0, qz24; prmt.b32 h1, lo1, hi1, 0x5410;\n"
        "mov.b32 {xl, xh}, a3; tanh.approx.f16 xr, xl; cvt.u32.u16 lo1, xr; tanh.approx.f16 xr, xh; cvt.u32.u16 hi1, xr; mul.rn.f16x2 a0, qz28, p0; fma.rn.f16x2 p1, qz29, qz29, c; fma.rn.f16x2 g9, qz25, h1, qz25; prmt.b32 h0, lo0, hi0, 0x5410;\n"
        "mov.b32 {xl, xh}, a0; tanh.approx.f16 xr, xl; cvt.u32.u16 lo0, xr; tanh.approx.f16 xr, xh; cvt.u32.u16 hi0, xr; mul.rn.f16x2 a1, qz29, p1; fma.rn.f16x2 p0, qz30, qz30, c; fma.rn.f16x2 g10, qz26, h0, qz26; prmt.b32 h1, lo1, hi1, 0x5410;\n"
        "mov.b32 {xl, xh}, a1; tanh.approx.f16 xr, xl; cvt.u32.u16 lo1, xr; tanh.approx.f16 xr, xh; cvt.u32.u16 hi1, xr; mul.rn.f16x2 a2, qz30, p0; fma.rn.f16x2 p1, qz31, qz31, c; fma.rn.f16x2 g11, qz27, h1, qz27; prmt.b32 h0, lo0, hi0, 0x5410;\n"
        "B94:\n"
        "wgmma.wait_group.sync.aligned 0;\n"
        "wgmma.fence.sync.aligned;\n"
        "add.s64 dt, w2d, 1408; wgmma.mma_async.sync.aligned.m64n96k16.f16.f16.f16 {o0,o1,o2,o3,o4,o5,o6,o7,o8,o9,o10,o11,o12,o13,o14,o15,o16,o17,o18,o19,o20,o21,o22,o23}, {g8,g9,g10,g11}, dt, pt, 1, 1, 1;\n"
        "wgmma.commit_group.sync.aligned;\n"
        "@pz bra.uni B2;\n"
        "mov.b32 {xl, xh}, a2; tanh.approx.f16 xr, xl; cvt.u32.u16 lo0, xr; tanh.approx.f16 xr, xh; cvt.u32.u16 hi0, xr; mul.rn.f16x2 a3, qz31, p1; fma.rn.f16x2 p0, qz0, qz0, c; fma.rn.f16x2 g12, qz28, h0, qz28; prmt.b32 h1, lo1, hi1, 0x5410;\n"
        "mov.b32 {xl, xh}, a3; tanh.approx.f16 xr, xl; cvt.u32.u16 lo1, xr; tanh.approx.f16 xr, xh; cvt.u32.u16 hi1, xr; mul.rn.f16x2 a0, qz0, p0; fma.rn.f16x2 p1, qz1, qz1, c; fma.rn.f16x2 g13, qz29, h1, qz29; prmt.b32 h0, lo0, hi0, 0x5410;\n"
        "mov.b32 {xl, xh}, a0; tanh.approx.f16 xr, xl; cvt.u32.u16 lo0, xr; tanh.approx.f16 xr, xh; cvt.u32.u16 hi0, xr; mul.rn.f16x2 a1, qz1, p1; fma.rn.f16x2 p0, qz2, qz2, c; fma.rn.f16x2 g14, qz30, h0, qz30; prmt.b32 h1, lo1, hi1, 0x5410;\n"
        "mov.b32 {xl, xh}, a1; tanh.approx.f16 xr, xl; cvt.u32.u16 lo1, xr; tanh.approx.f16 xr, xh; cvt.u32.u16 hi1, xr; mul.rn.f16x2 a2, qz2, p0; fma.rn.f16x2 p1, qz3, qz3, c; fma.rn.f16x2 g15, qz31, h1, qz31; prmt.b32 h0, lo0, hi0, 0x5410;\n"
        "B2:\n"
        "wgmma.fence.sync.aligned;\n"
        "add.s64 dt, w2d, 1472; wgmma.mma_async.sync.aligned.m64n96k16.f16.f16.f16 {o0,o1,o2,o3,o4,o5,o6,o7,o8,o9,o10,o11,o12,o13,o14,o15,o16,o17,o18,o19,o20,o21,o22,o23}, {g12,g13,g14,g15}, dt, pt, 1, 1, 1;\n"
        "wgmma.commit_group.sync.aligned;\n"
        "@!pm bra.uni LAST;\n"
        "@pz bra.uni BE;\n"
        "mov.b32 {xl, xh}, a2; tanh.approx.f16 xr, xl; cvt.u32.u16 lo0, xr; tanh.approx.f16 xr, xh; cvt.u32.u16 hi0, xr; mul.rn.f16x2 a3, qz3, p1; fma.rn.f16x2 p0, qz4, qz4, c; fma.rn.f16x2 g0, qz0, h0, qz0; prmt.b32 h1, lo1, hi1, 0x5410;\n"
        "mov.b32 {xl, xh}, a3; tanh.approx.f16 xr, xl; cvt.u32.u16 lo1, xr; tanh.approx.f16 xr, xh; cvt.u32.u16 hi1, xr; mul.rn.f16x2 a0, qz4, p0; fma.rn.f16x2 p1, qz5, qz5, c; fma.rn.f16x2 g1, qz1, h1, qz1; prmt.b32 h0, lo0, hi0, 0x5410;\n"
        "mov.b32 {xl, xh}, a0; tanh.approx.f16 xr, xl; cvt.u32.u16 lo0, xr; tanh.approx.f16 xr, xh; cvt.u32.u16 hi0, xr; mul.rn.f16x2 a1, qz5, p1; fma.rn.f16x2 p0, qz6, qz6, c; fma.rn.f16x2 g2, qz2, h0, qz2; prmt.b32 h1, lo1, hi1, 0x5410;\n"
        "mov.b32 {xl, xh}, a1; tanh.approx.f16 xr, xl; cvt.u32.u16 lo1, xr; tanh.approx.f16 xr, xh; cvt.u32.u16 hi1, xr; mul.rn.f16x2 a2, qz6, p0; fma.rn.f16x2 p1, qz7, qz7, c; fma.rn.f16x2 g3, qz3, h1, qz3; prmt.b32 h0, lo0, hi0, 0x5410;\n"
        "BE:\n"
        "wgmma.wait_group.sync.aligned 0;\n"
        "bra.uni LOOP;\n"
        "STORE:\n"
        "bar.sync tt, 128;\n"
        "setp.lt.s32 pr, n, 0;\n"
        "@pr bra.uni STOREB;\n"
        "cvt.u64.u32 gp, off; add.s64 gp, gp, %12;\n"
        "elect.sync _|pr, 0xffffffff;\n"
        "@pr cp.async.bulk.global.shared::cta.bulk_group [gp], [%5], 12288;\n"
        "@pr cp.async.bulk.commit_group;\n"
        "bra.uni STOREB;\n"
        "YLOAD:\n"
        "cp.async.bulk.wait_group.read 0;\n"
        "@!pm bra.uni XLAST;\n"
        "sub.u32 ad, off, %9; cvt.u64.u32 gp, ad; add.s64 gp, gp, %12;\n"
        "elect.sync _|pr, 0xffffffff;\n"
        "@pr mbarrier.arrive.expect_tx.shared::cta.b64 _, [ybar], 12288;\n"
        "@pr cp.async.bulk.shared::cluster.global.mbarrier::complete_tx::bytes [%5], [gp], 12288, [ybar];\n"
        "bra.uni YLOADB;\n"
        "XLAST:\n"
        "cvt.u64.u32 gp, off; add.s64 gp, gp, %11;\n"
        "elect.sync _|pr, 0xffffffff;\n"
        "@pr mbarrier.arrive.expect_tx.shared::cta.b64 _, [xbar], 12288;\n"
        "@pr cp.async.bulk.shared::cluster.global.mbarrier::complete_tx::bytes.L2::cache_hint [%5], [gp], 12288, [xbar], pol;\n"
        "bra.uni YLOADB;\n"
        "XPF:\n"
        "elect.sync _|pr, 0xffffffff;\n"
        "cvt.u64.u32 gp, off; add.s64 gp, gp, %11;\n"
        "@pr cp.async.bulk.prefetch.L2.global.L2::cache_hint [gp], 12288, pol;\n"
        "bra.uni XPFB;\n"
        "XLOAD:\n"
        "bar.sync tt, 128;\n"
        "cvt.u64.u32 gp, off; add.s64 gp, gp, %11;\n"
        "elect.sync _|pr, 0xffffffff;\n"
        "@pr mbarrier.arrive.expect_tx.shared::cta.b64 _, [xbar], 12288;\n"
        "@pr cp.async.bulk.shared::cluster.global.mbarrier::complete_tx::bytes.L2::cache_hint [%5], [gp], 12288, [xbar], pol;\n"
        "bra.uni XLOADB;\n"
        "SPINY: mov.u32 cnt, 0;\n"
        "SPINYL:\n"
        "add.u32 tt, n, 1; and.b32 tt, tt, 1; mbarrier.try_wait.parity.shared::cta.b64 pw, [ybar], tt;\n"
        "@pw bra.uni BACKY;\n"
        "add.u32 cnt, cnt, 1; setp.lt.u32 pw, cnt, 0x100000;\n"
        "@pw bra.uni SPINYL;\n"
        "trap;\n"
        "SPINX: mov.u32 cnt, 0;\n"
        "SPINXL:\n"
        "and.b32 tt, n, 1; mbarrier.try_wait.parity.shared::cta.b64 pw, [xbar], tt;\n"
        "@pw bra.uni BACKX;\n"
        "add.u32 cnt, cnt, 1; setp.lt.u32 pw, cnt, 0x100000;\n"
        "@pw bra.uni SPINXL;\n"
        "trap;\n"
        "SPINT: mov.u32 cnt, 0;\n"
        "SPINTL:\n"
        "mad.lo.u32 tt, n, 8, tbar; mbarrier.try_wait.parity.shared::cta.b64 pw, [tt], tpar;\n"
        "@pw bra.uni BACKT;\n"
        "add.u32 cnt, cnt, 1; setp.lt.u32 pw, cnt, 0x100000;\n"
        "@pw bra.uni SPINTL;\n"
        "trap;\n"
        "SPINW0: mov.u32 cnt, 0;\n"
        "SPINW0L:\n"
        "mov.u32 tt, 231208; mbarrier.try_wait.parity.shared::cta.b64 pw, [tt], 0;\n"
        "@pw bra.uni BACKW0;\n"
        "add.u32 cnt, cnt, 1; setp.lt.u32 pw, cnt, 0x100000;\n"
        "@pw bra.uni SPINW0L;\n"
        "trap;\n"
        "SPINW1: mov.u32 cnt, 0;\n"
        "SPINW1L:\n"
        "mov.u32 tt, 231216; mbarrier.try_wait.parity.shared::cta.b64 pw, [tt], 0;\n"
        "@pw bra.uni BACKW1;\n"
        "add.u32 cnt, cnt, 1; setp.lt.u32 pw, cnt, 0x100000;\n"
        "@pw bra.uni SPINW1L;\n"
        "trap;\n"
        "SPINW2: mov.u32 cnt, 0;\n"
        "SPINW2L:\n"
        "mov.u32 tt, 231224; mbarrier.try_wait.parity.shared::cta.b64 pw, [tt], 0;\n"
        "@pw bra.uni BACKW2;\n"
        "add.u32 cnt, cnt, 1; setp.lt.u32 pw, cnt, 0x100000;\n"
        "@pw bra.uni SPINW2L;\n"
        "trap;\n"
        "SPINY0: mov.u32 cnt, 0;\n"
        "SPINY0L:\n"
        "mbarrier.try_wait.parity.shared::cta.b64 pw, [ybar], 0;\n"
        "@pw bra.uni BACKY0;\n"
        "add.u32 cnt, cnt, 1; setp.lt.u32 pw, cnt, 0x100000;\n"
        "@pw bra.uni SPINY0L;\n"
        "trap;\n"
        "SPINR: mov.u32 cnt, 0;\n"
        "SPINRL:\n"
        "mov.u32 tt, 231232; mbarrier.try_wait.parity.shared::cta.b64 pw, [tt], %13;\n"
        "@pw bra.uni BACKR;\n"
        "add.u32 cnt, cnt, 1; setp.lt.u32 pw, cnt, 0x100000;\n"
        "@pw bra.uni SPINRL;\n"
        "trap;\n"
        "BACKR:\n"
        "mov.u32 tt, 230792; ld.shared.v2.b32 {osc, tt}, [tt];\n"
        "setp.ne.u32 pr, tt, 0; vote.sync.any.pred pr, pr, 0xffffffff;\n"
        "@pr bra.uni RETRY;\n"
        "setp.eq.u32 pr, %3, 0;\n"
        "@pr bra.uni BACKB;\n"
        "SPINB: mov.u32 cnt, 0;\n"
        "SPINBL:\n"
        "mov.u32 tt, 231208; mbarrier.try_wait.parity.shared::cta.b64 pw, [tt], 0;\n"
        "@pw bra.uni BACKB;\n"
        "add.u32 cnt, cnt, 1; setp.lt.u32 pw, cnt, 0x100000;\n"
        "@pw bra.uni SPINBL;\n"
        "trap;\n"
        "BACKB:\n"
        "ld.shared.v4.b32 {o0,o1,o2,o3}, [%8+0];\n"
        "ld.shared.v4.b32 {o4,o5,o6,o7}, [%8+64];\n"
        "ld.shared.v4.b32 {o8,o9,o10,o11}, [%8+128];\n"
        "ld.shared.v4.b32 {o12,o13,o14,o15}, [%8+192];\n"
        "ld.shared.v4.b32 {o16,o17,o18,o19}, [%8+256];\n"
        "ld.shared.v4.b32 {o20,o21,o22,o23}, [%8+320];\n"
        "bra.uni SPINW0;\n"
        "RETRY:\n"
        "wgmma.fence.sync.aligned;\n"
        "wgmma.commit_group.sync.aligned;\n"
        "wgmma.wait_group.sync.aligned 0;\n"
        "mov.u32 %0, 1;\n"
        "bra.uni OUT;\n"
        "FAST:\n"
        "mov.u32 n, 0; mov.u32 off, %4;\n"
        "fence.proxy.async.shared::cta;\n"
        "add.u32 tt, id, 4; bar.sync tt, 128;\n"
        "wgmma.fence.sync.aligned;\n"
        "add.s64 dt, w1d, 768; wgmma.mma_async.sync.aligned.m64n64k16.f16.f16.f16 {qz16,qz17,qz18,qz19,qz20,qz21,qz22,qz23,qz24,qz25,qz26,qz27,qz28,qz29,qz30,qz31}, {qa0,qa1,qa2,qa3}, dt, pf, 1, 1, 1;\n"
        "add.s64 dt, w1d, 896; wgmma.mma_async.sync.aligned.m64n64k16.f16.f16.f16 {qz16,qz17,qz18,qz19,qz20,qz21,qz22,qz23,qz24,qz25,qz26,qz27,qz28,qz29,qz30,qz31}, {qa4,qa5,qa6,qa7}, dt, pt, 1, 1, 1;\n"
        "add.s64 dt, w1d, 1024; wgmma.mma_async.sync.aligned.m64n64k16.f16.f16.f16 {qz16,qz17,qz18,qz19,qz20,qz21,qz22,qz23,qz24,qz25,qz26,qz27,qz28,qz29,qz30,qz31}, {qa8,qa9,qa10,qa11}, dt, pt, 1, 1, 1;\n"
        "add.s64 dt, w1d, 1152; wgmma.mma_async.sync.aligned.m64n64k16.f16.f16.f16 {qz16,qz17,qz18,qz19,qz20,qz21,qz22,qz23,qz24,qz25,qz26,qz27,qz28,qz29,qz30,qz31}, {qa12,qa13,qa14,qa15}, dt, pt, 1, 1, 1;\n"
        "add.s64 dt, w1d, 1280; wgmma.mma_async.sync.aligned.m64n64k16.f16.f16.f16 {qz16,qz17,qz18,qz19,qz20,qz21,qz22,qz23,qz24,qz25,qz26,qz27,qz28,qz29,qz30,qz31}, {qa16,qa17,qa18,qa19}, dt, pt, 1, 1, 1;\n"
        "add.s64 dt, w1d, 1408; wgmma.mma_async.sync.aligned.m64n64k16.f16.f16.f16 {qz16,qz17,qz18,qz19,qz20,qz21,qz22,qz23,qz24,qz25,qz26,qz27,qz28,qz29,qz30,qz31}, {qa20,qa21,qa22,qa23}, dt, pt, 1, 1, 1;\n"
        "wgmma.commit_group.sync.aligned;\n"
        "@pz bra.uni L10;\n"
        "mov.u32 ad, %tid.x; and.b32 ad, ad, 127; mad.wide.u32 gq, ad, 16, %15; st.global.v4.b32 [gq+0], {g0,g1,g2,g3};\n"
        "mov.b32 {xl, xh}, a2; tanh.approx.f16 xr, xl; cvt.u32.u16 lo0, xr; tanh.approx.f16 xr, xh; cvt.u32.u16 hi0, xr; mul.rn.f16x2 a3, qz7, p1; fma.rn.f16x2 p0, qz8, qz8, c; fma.rn.f16x2 g4, qz4, h0, qz4; prmt.b32 h1, lo1, hi1, 0x5410;\n"
        "mov.b32 {xl, xh}, a3; tanh.approx.f16 xr, xl; cvt.u32.u16 lo1, xr; tanh.approx.f16 xr, xh; cvt.u32.u16 hi1, xr; mul.rn.f16x2 a0, qz8, p0; fma.rn.f16x2 p1, qz9, qz9, c; fma.rn.f16x2 g5, qz5, h1, qz5; prmt.b32 h0, lo0, hi0, 0x5410;\n"
        "mov.b32 {xl, xh}, a0; tanh.approx.f16 xr, xl; cvt.u32.u16 lo0, xr; tanh.approx.f16 xr, xh; cvt.u32.u16 hi0, xr; mul.rn.f16x2 a1, qz9, p1; fma.rn.f16x2 p0, qz10, qz10, c; fma.rn.f16x2 g6, qz6, h0, qz6; prmt.b32 h1, lo1, hi1, 0x5410;\n"
        "mov.b32 {xl, xh}, a1; tanh.approx.f16 xr, xl; cvt.u32.u16 lo1, xr; tanh.approx.f16 xr, xh; cvt.u32.u16 hi1, xr; mul.rn.f16x2 a2, qz10, p0; fma.rn.f16x2 p1, qz11, qz11, c; fma.rn.f16x2 g7, qz7, h1, qz7; prmt.b32 h0, lo0, hi0, 0x5410;\n"
        "L10:\n"
        "@pz bra.uni L14;\n"
        "mov.u32 ad, %tid.x; and.b32 ad, ad, 127; mad.wide.u32 gq, ad, 16, %15; st.global.v4.b32 [gq+2048], {g4,g5,g6,g7};\n"
        "mov.b32 {xl, xh}, a2; tanh.approx.f16 xr, xl; cvt.u32.u16 lo0, xr; tanh.approx.f16 xr, xh; cvt.u32.u16 hi0, xr; mul.rn.f16x2 a3, qz11, p1; fma.rn.f16x2 p0, qz12, qz12, c; fma.rn.f16x2 g8, qz8, h0, qz8; prmt.b32 h1, lo1, hi1, 0x5410;\n"
        "mov.b32 {xl, xh}, a3; tanh.approx.f16 xr, xl; cvt.u32.u16 lo1, xr; tanh.approx.f16 xr, xh; cvt.u32.u16 hi1, xr; mul.rn.f16x2 a0, qz12, p0; fma.rn.f16x2 p1, qz13, qz13, c; fma.rn.f16x2 g9, qz9, h1, qz9; prmt.b32 h0, lo0, hi0, 0x5410;\n"
        "mov.b32 {xl, xh}, a0; tanh.approx.f16 xr, xl; cvt.u32.u16 lo0, xr; tanh.approx.f16 xr, xh; cvt.u32.u16 hi0, xr; mul.rn.f16x2 a1, qz13, p1; fma.rn.f16x2 p0, qz14, qz14, c; fma.rn.f16x2 g10, qz10, h0, qz10; prmt.b32 h1, lo1, hi1, 0x5410;\n"
        "mov.b32 {xl, xh}, a1; tanh.approx.f16 xr, xl; cvt.u32.u16 lo1, xr; tanh.approx.f16 xr, xh; cvt.u32.u16 hi1, xr; mul.rn.f16x2 a2, qz14, p0; fma.rn.f16x2 p1, qz15, qz15, c; fma.rn.f16x2 g11, qz11, h1, qz11; prmt.b32 h0, lo0, hi0, 0x5410;\n"
        "L14:\n"
        "wgmma.wait_group.sync.aligned 0;\n"
        "@pz bra.uni L18;\n"
        "mov.u32 ad, %tid.x; and.b32 ad, ad, 127; mad.wide.u32 gq, ad, 16, %15; st.global.v4.b32 [gq+4096], {g8,g9,g10,g11};\n"
        "mov.b32 {xl, xh}, a2; tanh.approx.f16 xr, xl; cvt.u32.u16 lo0, xr; tanh.approx.f16 xr, xh; cvt.u32.u16 hi0, xr; mul.rn.f16x2 a3, qz15, p1; fma.rn.f16x2 p0, qz16, qz16, c; fma.rn.f16x2 g12, qz12, h0, qz12; prmt.b32 h1, lo1, hi1, 0x5410;\n"
        "mov.b32 {xl, xh}, a3; tanh.approx.f16 xr, xl; cvt.u32.u16 lo1, xr; tanh.approx.f16 xr, xh; cvt.u32.u16 hi1, xr; mul.rn.f16x2 a0, qz16, p0; fma.rn.f16x2 p1, qz17, qz17, c; fma.rn.f16x2 g13, qz13, h1, qz13; prmt.b32 h0, lo0, hi0, 0x5410;\n"
        "mov.b32 {xl, xh}, a0; tanh.approx.f16 xr, xl; cvt.u32.u16 lo0, xr; tanh.approx.f16 xr, xh; cvt.u32.u16 hi0, xr; mul.rn.f16x2 a1, qz17, p1; fma.rn.f16x2 p0, qz18, qz18, c; fma.rn.f16x2 g14, qz14, h0, qz14; prmt.b32 h1, lo1, hi1, 0x5410;\n"
        "mov.b32 {xl, xh}, a1; tanh.approx.f16 xr, xl; cvt.u32.u16 lo1, xr; tanh.approx.f16 xr, xh; cvt.u32.u16 hi1, xr; mul.rn.f16x2 a2, qz18, p0; fma.rn.f16x2 p1, qz19, qz19, c; fma.rn.f16x2 g15, qz15, h1, qz15; prmt.b32 h0, lo0, hi0, 0x5410;\n"
        "L18:\n"
        "wgmma.fence.sync.aligned;\n"
        "add.s64 dt, w1d, 1536; wgmma.mma_async.sync.aligned.m64n64k16.f16.f16.f16 {qz0,qz1,qz2,qz3,qz4,qz5,qz6,qz7,qz8,qz9,qz10,qz11,qz12,qz13,qz14,qz15}, {qa0,qa1,qa2,qa3}, dt, pf, 1, 1, 1;\n"
        "add.s64 dt, w1d, 1664; wgmma.mma_async.sync.aligned.m64n64k16.f16.f16.f16 {qz0,qz1,qz2,qz3,qz4,qz5,qz6,qz7,qz8,qz9,qz10,qz11,qz12,qz13,qz14,qz15}, {qa4,qa5,qa6,qa7}, dt, pt, 1, 1, 1;\n"
        "add.s64 dt, w1d, 1792; wgmma.mma_async.sync.aligned.m64n64k16.f16.f16.f16 {qz0,qz1,qz2,qz3,qz4,qz5,qz6,qz7,qz8,qz9,qz10,qz11,qz12,qz13,qz14,qz15}, {qa8,qa9,qa10,qa11}, dt, pt, 1, 1, 1;\n"
        "add.s64 dt, w1d, 1920; wgmma.mma_async.sync.aligned.m64n64k16.f16.f16.f16 {qz0,qz1,qz2,qz3,qz4,qz5,qz6,qz7,qz8,qz9,qz10,qz11,qz12,qz13,qz14,qz15}, {qa12,qa13,qa14,qa15}, dt, pt, 1, 1, 1;\n"
        "add.s64 dt, w1d, 2048; wgmma.mma_async.sync.aligned.m64n64k16.f16.f16.f16 {qz0,qz1,qz2,qz3,qz4,qz5,qz6,qz7,qz8,qz9,qz10,qz11,qz12,qz13,qz14,qz15}, {qa16,qa17,qa18,qa19}, dt, pt, 1, 1, 1;\n"
        "add.s64 dt, w1d, 2176; wgmma.mma_async.sync.aligned.m64n64k16.f16.f16.f16 {qz0,qz1,qz2,qz3,qz4,qz5,qz6,qz7,qz8,qz9,qz10,qz11,qz12,qz13,qz14,qz15}, {qa20,qa21,qa22,qa23}, dt, pt, 1, 1, 1;\n"
        "wgmma.commit_group.sync.aligned;\n"
        "@pz bra.uni L22;\n"
        "mov.u32 ad, %tid.x; and.b32 ad, ad, 127; mad.wide.u32 gq, ad, 16, %15; st.global.v4.b32 [gq+6144], {g12,g13,g14,g15};\n"
        "mov.b32 {xl, xh}, a2; tanh.approx.f16 xr, xl; cvt.u32.u16 lo0, xr; tanh.approx.f16 xr, xh; cvt.u32.u16 hi0, xr; mul.rn.f16x2 a3, qz19, p1; fma.rn.f16x2 p0, qz20, qz20, c; fma.rn.f16x2 g0, qz16, h0, qz16; prmt.b32 h1, lo1, hi1, 0x5410;\n"
        "mov.b32 {xl, xh}, a3; tanh.approx.f16 xr, xl; cvt.u32.u16 lo1, xr; tanh.approx.f16 xr, xh; cvt.u32.u16 hi1, xr; mul.rn.f16x2 a0, qz20, p0; fma.rn.f16x2 p1, qz21, qz21, c; fma.rn.f16x2 g1, qz17, h1, qz17; prmt.b32 h0, lo0, hi0, 0x5410;\n"
        "mov.b32 {xl, xh}, a0; tanh.approx.f16 xr, xl; cvt.u32.u16 lo0, xr; tanh.approx.f16 xr, xh; cvt.u32.u16 hi0, xr; mul.rn.f16x2 a1, qz21, p1; fma.rn.f16x2 p0, qz22, qz22, c; fma.rn.f16x2 g2, qz18, h0, qz18; prmt.b32 h1, lo1, hi1, 0x5410;\n"
        "mov.b32 {xl, xh}, a1; tanh.approx.f16 xr, xl; cvt.u32.u16 lo1, xr; tanh.approx.f16 xr, xh; cvt.u32.u16 hi1, xr; mul.rn.f16x2 a2, qz22, p0; fma.rn.f16x2 p1, qz23, qz23, c; fma.rn.f16x2 g3, qz19, h1, qz19; prmt.b32 h0, lo0, hi0, 0x5410;\n"
        "L22:\n"
        "@pz bra.uni L26;\n"
        "mov.u32 ad, %tid.x; and.b32 ad, ad, 127; mad.wide.u32 gq, ad, 16, %15; st.global.v4.b32 [gq+8192], {g0,g1,g2,g3};\n"
        "mov.b32 {xl, xh}, a2; tanh.approx.f16 xr, xl; cvt.u32.u16 lo0, xr; tanh.approx.f16 xr, xh; cvt.u32.u16 hi0, xr; mul.rn.f16x2 a3, qz23, p1; fma.rn.f16x2 p0, qz24, qz24, c; fma.rn.f16x2 g4, qz20, h0, qz20; prmt.b32 h1, lo1, hi1, 0x5410;\n"
        "mov.b32 {xl, xh}, a3; tanh.approx.f16 xr, xl; cvt.u32.u16 lo1, xr; tanh.approx.f16 xr, xh; cvt.u32.u16 hi1, xr; mul.rn.f16x2 a0, qz24, p0; fma.rn.f16x2 p1, qz25, qz25, c; fma.rn.f16x2 g5, qz21, h1, qz21; prmt.b32 h0, lo0, hi0, 0x5410;\n"
        "mov.b32 {xl, xh}, a0; tanh.approx.f16 xr, xl; cvt.u32.u16 lo0, xr; tanh.approx.f16 xr, xh; cvt.u32.u16 hi0, xr; mul.rn.f16x2 a1, qz25, p1; fma.rn.f16x2 p0, qz26, qz26, c; fma.rn.f16x2 g6, qz22, h0, qz22; prmt.b32 h1, lo1, hi1, 0x5410;\n"
        "mov.b32 {xl, xh}, a1; tanh.approx.f16 xr, xl; cvt.u32.u16 lo1, xr; tanh.approx.f16 xr, xh; cvt.u32.u16 hi1, xr; mul.rn.f16x2 a2, qz26, p0; fma.rn.f16x2 p1, qz27, qz27, c; fma.rn.f16x2 g7, qz23, h1, qz23; prmt.b32 h0, lo0, hi0, 0x5410;\n"
        "L26:\n"
        "@pz bra.uni L30;\n"
        "mov.u32 ad, %tid.x; and.b32 ad, ad, 127; mad.wide.u32 gq, ad, 16, %15; st.global.v4.b32 [gq+10240], {g4,g5,g6,g7};\n"
        "mov.b32 {xl, xh}, a2; tanh.approx.f16 xr, xl; cvt.u32.u16 lo0, xr; tanh.approx.f16 xr, xh; cvt.u32.u16 hi0, xr; mul.rn.f16x2 a3, qz27, p1; fma.rn.f16x2 p0, qz28, qz28, c; fma.rn.f16x2 g8, qz24, h0, qz24; prmt.b32 h1, lo1, hi1, 0x5410;\n"
        "mov.b32 {xl, xh}, a3; tanh.approx.f16 xr, xl; cvt.u32.u16 lo1, xr; tanh.approx.f16 xr, xh; cvt.u32.u16 hi1, xr; mul.rn.f16x2 a0, qz28, p0; fma.rn.f16x2 p1, qz29, qz29, c; fma.rn.f16x2 g9, qz25, h1, qz25; prmt.b32 h0, lo0, hi0, 0x5410;\n"
        "mov.b32 {xl, xh}, a0; tanh.approx.f16 xr, xl; cvt.u32.u16 lo0, xr; tanh.approx.f16 xr, xh; cvt.u32.u16 hi0, xr; mul.rn.f16x2 a1, qz29, p1; fma.rn.f16x2 p0, qz30, qz30, c; fma.rn.f16x2 g10, qz26, h0, qz26; prmt.b32 h1, lo1, hi1, 0x5410;\n"
        "mov.b32 {xl, xh}, a1; tanh.approx.f16 xr, xl; cvt.u32.u16 lo1, xr; tanh.approx.f16 xr, xh; cvt.u32.u16 hi1, xr; mul.rn.f16x2 a2, qz30, p0; fma.rn.f16x2 p1, qz31, qz31, c; fma.rn.f16x2 g11, qz27, h1, qz27; prmt.b32 h0, lo0, hi0, 0x5410;\n"
        "L30:\n"
        "wgmma.wait_group.sync.aligned 0;\n"
        "@pz bra.uni L34;\n"
        "mov.u32 ad, %tid.x; and.b32 ad, ad, 127; mad.wide.u32 gq, ad, 16, %15; st.global.v4.b32 [gq+12288], {g8,g9,g10,g11};\n"
        "mov.b32 {xl, xh}, a2; tanh.approx.f16 xr, xl; cvt.u32.u16 lo0, xr; tanh.approx.f16 xr, xh; cvt.u32.u16 hi0, xr; mul.rn.f16x2 a3, qz31, p1; fma.rn.f16x2 p0, qz0, qz0, c; fma.rn.f16x2 g12, qz28, h0, qz28; prmt.b32 h1, lo1, hi1, 0x5410;\n"
        "mov.b32 {xl, xh}, a3; tanh.approx.f16 xr, xl; cvt.u32.u16 lo1, xr; tanh.approx.f16 xr, xh; cvt.u32.u16 hi1, xr; mul.rn.f16x2 a0, qz0, p0; fma.rn.f16x2 p1, qz1, qz1, c; fma.rn.f16x2 g13, qz29, h1, qz29; prmt.b32 h0, lo0, hi0, 0x5410;\n"
        "mov.b32 {xl, xh}, a0; tanh.approx.f16 xr, xl; cvt.u32.u16 lo0, xr; tanh.approx.f16 xr, xh; cvt.u32.u16 hi0, xr; mul.rn.f16x2 a1, qz1, p1; fma.rn.f16x2 p0, qz2, qz2, c; fma.rn.f16x2 g14, qz30, h0, qz30; prmt.b32 h1, lo1, hi1, 0x5410;\n"
        "mov.b32 {xl, xh}, a1; tanh.approx.f16 xr, xl; cvt.u32.u16 lo1, xr; tanh.approx.f16 xr, xh; cvt.u32.u16 hi1, xr; mul.rn.f16x2 a2, qz2, p0; fma.rn.f16x2 p1, qz3, qz3, c; fma.rn.f16x2 g15, qz31, h1, qz31; prmt.b32 h0, lo0, hi0, 0x5410;\n"
        "L34:\n"
        "wgmma.fence.sync.aligned;\n"
        "add.s64 dt, w1d, 2304; wgmma.mma_async.sync.aligned.m64n64k16.f16.f16.f16 {qz16,qz17,qz18,qz19,qz20,qz21,qz22,qz23,qz24,qz25,qz26,qz27,qz28,qz29,qz30,qz31}, {qa0,qa1,qa2,qa3}, dt, pf, 1, 1, 1;\n"
        "add.s64 dt, w1d, 2432; wgmma.mma_async.sync.aligned.m64n64k16.f16.f16.f16 {qz16,qz17,qz18,qz19,qz20,qz21,qz22,qz23,qz24,qz25,qz26,qz27,qz28,qz29,qz30,qz31}, {qa4,qa5,qa6,qa7}, dt, pt, 1, 1, 1;\n"
        "add.s64 dt, w1d, 2560; wgmma.mma_async.sync.aligned.m64n64k16.f16.f16.f16 {qz16,qz17,qz18,qz19,qz20,qz21,qz22,qz23,qz24,qz25,qz26,qz27,qz28,qz29,qz30,qz31}, {qa8,qa9,qa10,qa11}, dt, pt, 1, 1, 1;\n"
        "add.s64 dt, w1d, 2688; wgmma.mma_async.sync.aligned.m64n64k16.f16.f16.f16 {qz16,qz17,qz18,qz19,qz20,qz21,qz22,qz23,qz24,qz25,qz26,qz27,qz28,qz29,qz30,qz31}, {qa12,qa13,qa14,qa15}, dt, pt, 1, 1, 1;\n"
        "add.s64 dt, w1d, 2816; wgmma.mma_async.sync.aligned.m64n64k16.f16.f16.f16 {qz16,qz17,qz18,qz19,qz20,qz21,qz22,qz23,qz24,qz25,qz26,qz27,qz28,qz29,qz30,qz31}, {qa16,qa17,qa18,qa19}, dt, pt, 1, 1, 1;\n"
        "add.s64 dt, w1d, 2944; wgmma.mma_async.sync.aligned.m64n64k16.f16.f16.f16 {qz16,qz17,qz18,qz19,qz20,qz21,qz22,qz23,qz24,qz25,qz26,qz27,qz28,qz29,qz30,qz31}, {qa20,qa21,qa22,qa23}, dt, pt, 1, 1, 1;\n"
        "wgmma.commit_group.sync.aligned;\n"
        "@pz bra.uni L38;\n"
        "mov.u32 ad, %tid.x; and.b32 ad, ad, 127; mad.wide.u32 gq, ad, 16, %15; st.global.v4.b32 [gq+14336], {g12,g13,g14,g15};\n"
        "mov.b32 {xl, xh}, a2; tanh.approx.f16 xr, xl; cvt.u32.u16 lo0, xr; tanh.approx.f16 xr, xh; cvt.u32.u16 hi0, xr; mul.rn.f16x2 a3, qz3, p1; fma.rn.f16x2 p0, qz4, qz4, c; fma.rn.f16x2 g0, qz0, h0, qz0; prmt.b32 h1, lo1, hi1, 0x5410;\n"
        "mov.b32 {xl, xh}, a3; tanh.approx.f16 xr, xl; cvt.u32.u16 lo1, xr; tanh.approx.f16 xr, xh; cvt.u32.u16 hi1, xr; mul.rn.f16x2 a0, qz4, p0; fma.rn.f16x2 p1, qz5, qz5, c; fma.rn.f16x2 g1, qz1, h1, qz1; prmt.b32 h0, lo0, hi0, 0x5410;\n"
        "mov.b32 {xl, xh}, a0; tanh.approx.f16 xr, xl; cvt.u32.u16 lo0, xr; tanh.approx.f16 xr, xh; cvt.u32.u16 hi0, xr; mul.rn.f16x2 a1, qz5, p1; fma.rn.f16x2 p0, qz6, qz6, c; fma.rn.f16x2 g2, qz2, h0, qz2; prmt.b32 h1, lo1, hi1, 0x5410;\n"
        "mov.b32 {xl, xh}, a1; tanh.approx.f16 xr, xl; cvt.u32.u16 lo1, xr; tanh.approx.f16 xr, xh; cvt.u32.u16 hi1, xr; mul.rn.f16x2 a2, qz6, p0; fma.rn.f16x2 p1, qz7, qz7, c; fma.rn.f16x2 g3, qz3, h1, qz3; prmt.b32 h0, lo0, hi0, 0x5410;\n"
        "L38:\n"
        "@pz bra.uni L42;\n"
        "mov.u32 ad, %tid.x; and.b32 ad, ad, 127; mad.wide.u32 gq, ad, 16, %15; st.global.v4.b32 [gq+16384], {g0,g1,g2,g3};\n"
        "mov.b32 {xl, xh}, a2; tanh.approx.f16 xr, xl; cvt.u32.u16 lo0, xr; tanh.approx.f16 xr, xh; cvt.u32.u16 hi0, xr; mul.rn.f16x2 a3, qz7, p1; fma.rn.f16x2 p0, qz8, qz8, c; fma.rn.f16x2 g4, qz4, h0, qz4; prmt.b32 h1, lo1, hi1, 0x5410;\n"
        "mov.b32 {xl, xh}, a3; tanh.approx.f16 xr, xl; cvt.u32.u16 lo1, xr; tanh.approx.f16 xr, xh; cvt.u32.u16 hi1, xr; mul.rn.f16x2 a0, qz8, p0; fma.rn.f16x2 p1, qz9, qz9, c; fma.rn.f16x2 g5, qz5, h1, qz5; prmt.b32 h0, lo0, hi0, 0x5410;\n"
        "mov.b32 {xl, xh}, a0; tanh.approx.f16 xr, xl; cvt.u32.u16 lo0, xr; tanh.approx.f16 xr, xh; cvt.u32.u16 hi0, xr; mul.rn.f16x2 a1, qz9, p1; fma.rn.f16x2 p0, qz10, qz10, c; fma.rn.f16x2 g6, qz6, h0, qz6; prmt.b32 h1, lo1, hi1, 0x5410;\n"
        "mov.b32 {xl, xh}, a1; tanh.approx.f16 xr, xl; cvt.u32.u16 lo1, xr; tanh.approx.f16 xr, xh; cvt.u32.u16 hi1, xr; mul.rn.f16x2 a2, qz10, p0; fma.rn.f16x2 p1, qz11, qz11, c; fma.rn.f16x2 g7, qz7, h1, qz7; prmt.b32 h0, lo0, hi0, 0x5410;\n"
        "L42:\n"
        "@pz bra.uni L46;\n"
        "mov.u32 ad, %tid.x; and.b32 ad, ad, 127; mad.wide.u32 gq, ad, 16, %15; st.global.v4.b32 [gq+18432], {g4,g5,g6,g7};\n"
        "mov.b32 {xl, xh}, a2; tanh.approx.f16 xr, xl; cvt.u32.u16 lo0, xr; tanh.approx.f16 xr, xh; cvt.u32.u16 hi0, xr; mul.rn.f16x2 a3, qz11, p1; fma.rn.f16x2 p0, qz12, qz12, c; fma.rn.f16x2 g8, qz8, h0, qz8; prmt.b32 h1, lo1, hi1, 0x5410;\n"
        "mov.b32 {xl, xh}, a3; tanh.approx.f16 xr, xl; cvt.u32.u16 lo1, xr; tanh.approx.f16 xr, xh; cvt.u32.u16 hi1, xr; mul.rn.f16x2 a0, qz12, p0; fma.rn.f16x2 p1, qz13, qz13, c; fma.rn.f16x2 g9, qz9, h1, qz9; prmt.b32 h0, lo0, hi0, 0x5410;\n"
        "mov.b32 {xl, xh}, a0; tanh.approx.f16 xr, xl; cvt.u32.u16 lo0, xr; tanh.approx.f16 xr, xh; cvt.u32.u16 hi0, xr; mul.rn.f16x2 a1, qz13, p1; fma.rn.f16x2 p0, qz14, qz14, c; fma.rn.f16x2 g10, qz10, h0, qz10; prmt.b32 h1, lo1, hi1, 0x5410;\n"
        "mov.b32 {xl, xh}, a1; tanh.approx.f16 xr, xl; cvt.u32.u16 lo1, xr; tanh.approx.f16 xr, xh; cvt.u32.u16 hi1, xr; mul.rn.f16x2 a2, qz14, p0; fma.rn.f16x2 p1, qz15, qz15, c; fma.rn.f16x2 g11, qz11, h1, qz11; prmt.b32 h0, lo0, hi0, 0x5410;\n"
        "L46:\n"
        "wgmma.wait_group.sync.aligned 0;\n"
        "@pz bra.uni L50;\n"
        "mov.u32 ad, %tid.x; and.b32 ad, ad, 127; mad.wide.u32 gq, ad, 16, %15; st.global.v4.b32 [gq+20480], {g8,g9,g10,g11};\n"
        "mov.b32 {xl, xh}, a2; tanh.approx.f16 xr, xl; cvt.u32.u16 lo0, xr; tanh.approx.f16 xr, xh; cvt.u32.u16 hi0, xr; mul.rn.f16x2 a3, qz15, p1; fma.rn.f16x2 p0, qz16, qz16, c; fma.rn.f16x2 g12, qz12, h0, qz12; prmt.b32 h1, lo1, hi1, 0x5410;\n"
        "mov.b32 {xl, xh}, a3; tanh.approx.f16 xr, xl; cvt.u32.u16 lo1, xr; tanh.approx.f16 xr, xh; cvt.u32.u16 hi1, xr; mul.rn.f16x2 a0, qz16, p0; fma.rn.f16x2 p1, qz17, qz17, c; fma.rn.f16x2 g13, qz13, h1, qz13; prmt.b32 h0, lo0, hi0, 0x5410;\n"
        "mov.b32 {xl, xh}, a0; tanh.approx.f16 xr, xl; cvt.u32.u16 lo0, xr; tanh.approx.f16 xr, xh; cvt.u32.u16 hi0, xr; mul.rn.f16x2 a1, qz17, p1; fma.rn.f16x2 p0, qz18, qz18, c; fma.rn.f16x2 g14, qz14, h0, qz14; prmt.b32 h1, lo1, hi1, 0x5410;\n"
        "mov.b32 {xl, xh}, a1; tanh.approx.f16 xr, xl; cvt.u32.u16 lo1, xr; tanh.approx.f16 xr, xh; cvt.u32.u16 hi1, xr; mul.rn.f16x2 a2, qz18, p0; fma.rn.f16x2 p1, qz19, qz19, c; fma.rn.f16x2 g15, qz15, h1, qz15; prmt.b32 h0, lo0, hi0, 0x5410;\n"
        "L50:\n"
        "wgmma.fence.sync.aligned;\n"
        "add.s64 dt, w1d, 3072; wgmma.mma_async.sync.aligned.m64n64k16.f16.f16.f16 {qz0,qz1,qz2,qz3,qz4,qz5,qz6,qz7,qz8,qz9,qz10,qz11,qz12,qz13,qz14,qz15}, {qa0,qa1,qa2,qa3}, dt, pf, 1, 1, 1;\n"
        "add.s64 dt, w1d, 3200; wgmma.mma_async.sync.aligned.m64n64k16.f16.f16.f16 {qz0,qz1,qz2,qz3,qz4,qz5,qz6,qz7,qz8,qz9,qz10,qz11,qz12,qz13,qz14,qz15}, {qa4,qa5,qa6,qa7}, dt, pt, 1, 1, 1;\n"
        "add.s64 dt, w1d, 3328; wgmma.mma_async.sync.aligned.m64n64k16.f16.f16.f16 {qz0,qz1,qz2,qz3,qz4,qz5,qz6,qz7,qz8,qz9,qz10,qz11,qz12,qz13,qz14,qz15}, {qa8,qa9,qa10,qa11}, dt, pt, 1, 1, 1;\n"
        "add.s64 dt, w1d, 3456; wgmma.mma_async.sync.aligned.m64n64k16.f16.f16.f16 {qz0,qz1,qz2,qz3,qz4,qz5,qz6,qz7,qz8,qz9,qz10,qz11,qz12,qz13,qz14,qz15}, {qa12,qa13,qa14,qa15}, dt, pt, 1, 1, 1;\n"
        "add.s64 dt, w1d, 3584; wgmma.mma_async.sync.aligned.m64n64k16.f16.f16.f16 {qz0,qz1,qz2,qz3,qz4,qz5,qz6,qz7,qz8,qz9,qz10,qz11,qz12,qz13,qz14,qz15}, {qa16,qa17,qa18,qa19}, dt, pt, 1, 1, 1;\n"
        "add.s64 dt, w1d, 3712; wgmma.mma_async.sync.aligned.m64n64k16.f16.f16.f16 {qz0,qz1,qz2,qz3,qz4,qz5,qz6,qz7,qz8,qz9,qz10,qz11,qz12,qz13,qz14,qz15}, {qa20,qa21,qa22,qa23}, dt, pt, 1, 1, 1;\n"
        "wgmma.commit_group.sync.aligned;\n"
        "@pz bra.uni L54;\n"
        "mov.u32 ad, %tid.x; and.b32 ad, ad, 127; mad.wide.u32 gq, ad, 16, %15; st.global.v4.b32 [gq+22528], {g12,g13,g14,g15};\n"
        "mov.b32 {xl, xh}, a2; tanh.approx.f16 xr, xl; cvt.u32.u16 lo0, xr; tanh.approx.f16 xr, xh; cvt.u32.u16 hi0, xr; mul.rn.f16x2 a3, qz19, p1; fma.rn.f16x2 p0, qz20, qz20, c; fma.rn.f16x2 g0, qz16, h0, qz16; prmt.b32 h1, lo1, hi1, 0x5410;\n"
        "mov.b32 {xl, xh}, a3; tanh.approx.f16 xr, xl; cvt.u32.u16 lo1, xr; tanh.approx.f16 xr, xh; cvt.u32.u16 hi1, xr; mul.rn.f16x2 a0, qz20, p0; fma.rn.f16x2 p1, qz21, qz21, c; fma.rn.f16x2 g1, qz17, h1, qz17; prmt.b32 h0, lo0, hi0, 0x5410;\n"
        "mov.b32 {xl, xh}, a0; tanh.approx.f16 xr, xl; cvt.u32.u16 lo0, xr; tanh.approx.f16 xr, xh; cvt.u32.u16 hi0, xr; mul.rn.f16x2 a1, qz21, p1; fma.rn.f16x2 p0, qz22, qz22, c; fma.rn.f16x2 g2, qz18, h0, qz18; prmt.b32 h1, lo1, hi1, 0x5410;\n"
        "mov.b32 {xl, xh}, a1; tanh.approx.f16 xr, xl; cvt.u32.u16 lo1, xr; tanh.approx.f16 xr, xh; cvt.u32.u16 hi1, xr; mul.rn.f16x2 a2, qz22, p0; fma.rn.f16x2 p1, qz23, qz23, c; fma.rn.f16x2 g3, qz19, h1, qz19; prmt.b32 h0, lo0, hi0, 0x5410;\n"
        "L54:\n"
        "@pz bra.uni L58;\n"
        "mov.u32 ad, %tid.x; and.b32 ad, ad, 127; mad.wide.u32 gq, ad, 16, %15; st.global.v4.b32 [gq+24576], {g0,g1,g2,g3};\n"
        "mov.b32 {xl, xh}, a2; tanh.approx.f16 xr, xl; cvt.u32.u16 lo0, xr; tanh.approx.f16 xr, xh; cvt.u32.u16 hi0, xr; mul.rn.f16x2 a3, qz23, p1; fma.rn.f16x2 p0, qz24, qz24, c; fma.rn.f16x2 g4, qz20, h0, qz20; prmt.b32 h1, lo1, hi1, 0x5410;\n"
        "mov.b32 {xl, xh}, a3; tanh.approx.f16 xr, xl; cvt.u32.u16 lo1, xr; tanh.approx.f16 xr, xh; cvt.u32.u16 hi1, xr; mul.rn.f16x2 a0, qz24, p0; fma.rn.f16x2 p1, qz25, qz25, c; fma.rn.f16x2 g5, qz21, h1, qz21; prmt.b32 h0, lo0, hi0, 0x5410;\n"
        "mov.b32 {xl, xh}, a0; tanh.approx.f16 xr, xl; cvt.u32.u16 lo0, xr; tanh.approx.f16 xr, xh; cvt.u32.u16 hi0, xr; mul.rn.f16x2 a1, qz25, p1; fma.rn.f16x2 p0, qz26, qz26, c; fma.rn.f16x2 g6, qz22, h0, qz22; prmt.b32 h1, lo1, hi1, 0x5410;\n"
        "mov.b32 {xl, xh}, a1; tanh.approx.f16 xr, xl; cvt.u32.u16 lo1, xr; tanh.approx.f16 xr, xh; cvt.u32.u16 hi1, xr; mul.rn.f16x2 a2, qz26, p0; fma.rn.f16x2 p1, qz27, qz27, c; fma.rn.f16x2 g7, qz23, h1, qz23; prmt.b32 h0, lo0, hi0, 0x5410;\n"
        "L58:\n"
        "@pz bra.uni L62;\n"
        "mov.u32 ad, %tid.x; and.b32 ad, ad, 127; mad.wide.u32 gq, ad, 16, %15; st.global.v4.b32 [gq+26624], {g4,g5,g6,g7};\n"
        "mov.b32 {xl, xh}, a2; tanh.approx.f16 xr, xl; cvt.u32.u16 lo0, xr; tanh.approx.f16 xr, xh; cvt.u32.u16 hi0, xr; mul.rn.f16x2 a3, qz27, p1; fma.rn.f16x2 p0, qz28, qz28, c; fma.rn.f16x2 g8, qz24, h0, qz24; prmt.b32 h1, lo1, hi1, 0x5410;\n"
        "mov.b32 {xl, xh}, a3; tanh.approx.f16 xr, xl; cvt.u32.u16 lo1, xr; tanh.approx.f16 xr, xh; cvt.u32.u16 hi1, xr; mul.rn.f16x2 a0, qz28, p0; fma.rn.f16x2 p1, qz29, qz29, c; fma.rn.f16x2 g9, qz25, h1, qz25; prmt.b32 h0, lo0, hi0, 0x5410;\n"
        "mov.b32 {xl, xh}, a0; tanh.approx.f16 xr, xl; cvt.u32.u16 lo0, xr; tanh.approx.f16 xr, xh; cvt.u32.u16 hi0, xr; mul.rn.f16x2 a1, qz29, p1; fma.rn.f16x2 p0, qz30, qz30, c; fma.rn.f16x2 g10, qz26, h0, qz26; prmt.b32 h1, lo1, hi1, 0x5410;\n"
        "mov.b32 {xl, xh}, a1; tanh.approx.f16 xr, xl; cvt.u32.u16 lo1, xr; tanh.approx.f16 xr, xh; cvt.u32.u16 hi1, xr; mul.rn.f16x2 a2, qz30, p0; fma.rn.f16x2 p1, qz31, qz31, c; fma.rn.f16x2 g11, qz27, h1, qz27; prmt.b32 h0, lo0, hi0, 0x5410;\n"
        "L62:\n"
        "wgmma.wait_group.sync.aligned 0;\n"
        "@pz bra.uni L66;\n"
        "mov.u32 ad, %tid.x; and.b32 ad, ad, 127; mad.wide.u32 gq, ad, 16, %15; st.global.v4.b32 [gq+28672], {g8,g9,g10,g11};\n"
        "mov.b32 {xl, xh}, a2; tanh.approx.f16 xr, xl; cvt.u32.u16 lo0, xr; tanh.approx.f16 xr, xh; cvt.u32.u16 hi0, xr; mul.rn.f16x2 a3, qz31, p1; fma.rn.f16x2 p0, qz0, qz0, c; fma.rn.f16x2 g12, qz28, h0, qz28; prmt.b32 h1, lo1, hi1, 0x5410;\n"
        "mov.b32 {xl, xh}, a3; tanh.approx.f16 xr, xl; cvt.u32.u16 lo1, xr; tanh.approx.f16 xr, xh; cvt.u32.u16 hi1, xr; mul.rn.f16x2 a0, qz0, p0; fma.rn.f16x2 p1, qz1, qz1, c; fma.rn.f16x2 g13, qz29, h1, qz29; prmt.b32 h0, lo0, hi0, 0x5410;\n"
        "mov.b32 {xl, xh}, a0; tanh.approx.f16 xr, xl; cvt.u32.u16 lo0, xr; tanh.approx.f16 xr, xh; cvt.u32.u16 hi0, xr; mul.rn.f16x2 a1, qz1, p1; fma.rn.f16x2 p0, qz2, qz2, c; fma.rn.f16x2 g14, qz30, h0, qz30; prmt.b32 h1, lo1, hi1, 0x5410;\n"
        "mov.b32 {xl, xh}, a1; tanh.approx.f16 xr, xl; cvt.u32.u16 lo1, xr; tanh.approx.f16 xr, xh; cvt.u32.u16 hi1, xr; mul.rn.f16x2 a2, qz2, p0; fma.rn.f16x2 p1, qz3, qz3, c; fma.rn.f16x2 g15, qz31, h1, qz31; prmt.b32 h0, lo0, hi0, 0x5410;\n"
        "L66:\n"
        "wgmma.fence.sync.aligned;\n"
        "add.s64 dt, w1d, 3840; wgmma.mma_async.sync.aligned.m64n64k16.f16.f16.f16 {qz16,qz17,qz18,qz19,qz20,qz21,qz22,qz23,qz24,qz25,qz26,qz27,qz28,qz29,qz30,qz31}, {qa0,qa1,qa2,qa3}, dt, pf, 1, 1, 1;\n"
        "add.s64 dt, w1d, 3968; wgmma.mma_async.sync.aligned.m64n64k16.f16.f16.f16 {qz16,qz17,qz18,qz19,qz20,qz21,qz22,qz23,qz24,qz25,qz26,qz27,qz28,qz29,qz30,qz31}, {qa4,qa5,qa6,qa7}, dt, pt, 1, 1, 1;\n"
        "add.s64 dt, w1d, 4096; wgmma.mma_async.sync.aligned.m64n64k16.f16.f16.f16 {qz16,qz17,qz18,qz19,qz20,qz21,qz22,qz23,qz24,qz25,qz26,qz27,qz28,qz29,qz30,qz31}, {qa8,qa9,qa10,qa11}, dt, pt, 1, 1, 1;\n"
        "add.s64 dt, w1d, 4224; wgmma.mma_async.sync.aligned.m64n64k16.f16.f16.f16 {qz16,qz17,qz18,qz19,qz20,qz21,qz22,qz23,qz24,qz25,qz26,qz27,qz28,qz29,qz30,qz31}, {qa12,qa13,qa14,qa15}, dt, pt, 1, 1, 1;\n"
        "add.s64 dt, w1d, 4352; wgmma.mma_async.sync.aligned.m64n64k16.f16.f16.f16 {qz16,qz17,qz18,qz19,qz20,qz21,qz22,qz23,qz24,qz25,qz26,qz27,qz28,qz29,qz30,qz31}, {qa16,qa17,qa18,qa19}, dt, pt, 1, 1, 1;\n"
        "add.s64 dt, w1d, 4480; wgmma.mma_async.sync.aligned.m64n64k16.f16.f16.f16 {qz16,qz17,qz18,qz19,qz20,qz21,qz22,qz23,qz24,qz25,qz26,qz27,qz28,qz29,qz30,qz31}, {qa20,qa21,qa22,qa23}, dt, pt, 1, 1, 1;\n"
        "wgmma.commit_group.sync.aligned;\n"
        "@pz bra.uni L70;\n"
        "mov.u32 ad, %tid.x; and.b32 ad, ad, 127; mad.wide.u32 gq, ad, 16, %15; st.global.v4.b32 [gq+30720], {g12,g13,g14,g15};\n"
        "mov.b32 {xl, xh}, a2; tanh.approx.f16 xr, xl; cvt.u32.u16 lo0, xr; tanh.approx.f16 xr, xh; cvt.u32.u16 hi0, xr; mul.rn.f16x2 a3, qz3, p1; fma.rn.f16x2 p0, qz4, qz4, c; fma.rn.f16x2 g0, qz0, h0, qz0; prmt.b32 h1, lo1, hi1, 0x5410;\n"
        "mov.b32 {xl, xh}, a3; tanh.approx.f16 xr, xl; cvt.u32.u16 lo1, xr; tanh.approx.f16 xr, xh; cvt.u32.u16 hi1, xr; mul.rn.f16x2 a0, qz4, p0; fma.rn.f16x2 p1, qz5, qz5, c; fma.rn.f16x2 g1, qz1, h1, qz1; prmt.b32 h0, lo0, hi0, 0x5410;\n"
        "mov.b32 {xl, xh}, a0; tanh.approx.f16 xr, xl; cvt.u32.u16 lo0, xr; tanh.approx.f16 xr, xh; cvt.u32.u16 hi0, xr; mul.rn.f16x2 a1, qz5, p1; fma.rn.f16x2 p0, qz6, qz6, c; fma.rn.f16x2 g2, qz2, h0, qz2; prmt.b32 h1, lo1, hi1, 0x5410;\n"
        "mov.b32 {xl, xh}, a1; tanh.approx.f16 xr, xl; cvt.u32.u16 lo1, xr; tanh.approx.f16 xr, xh; cvt.u32.u16 hi1, xr; mul.rn.f16x2 a2, qz6, p0; fma.rn.f16x2 p1, qz7, qz7, c; fma.rn.f16x2 g3, qz3, h1, qz3; prmt.b32 h0, lo0, hi0, 0x5410;\n"
        "L70:\n"
        "@pz bra.uni L74;\n"
        "mov.b32 {xl, xh}, a2; tanh.approx.f16 xr, xl; cvt.u32.u16 lo0, xr; tanh.approx.f16 xr, xh; cvt.u32.u16 hi0, xr; mul.rn.f16x2 a3, qz7, p1; fma.rn.f16x2 p0, qz8, qz8, c; fma.rn.f16x2 g4, qz4, h0, qz4; prmt.b32 h1, lo1, hi1, 0x5410;\n"
        "mov.b32 {xl, xh}, a3; tanh.approx.f16 xr, xl; cvt.u32.u16 lo1, xr; tanh.approx.f16 xr, xh; cvt.u32.u16 hi1, xr; mul.rn.f16x2 a0, qz8, p0; fma.rn.f16x2 p1, qz9, qz9, c; fma.rn.f16x2 g5, qz5, h1, qz5; prmt.b32 h0, lo0, hi0, 0x5410;\n"
        "mov.b32 {xl, xh}, a0; tanh.approx.f16 xr, xl; cvt.u32.u16 lo0, xr; tanh.approx.f16 xr, xh; cvt.u32.u16 hi0, xr; mul.rn.f16x2 a1, qz9, p1; fma.rn.f16x2 p0, qz10, qz10, c; fma.rn.f16x2 g6, qz6, h0, qz6; prmt.b32 h1, lo1, hi1, 0x5410;\n"
        "mov.b32 {xl, xh}, a1; tanh.approx.f16 xr, xl; cvt.u32.u16 lo1, xr; tanh.approx.f16 xr, xh; cvt.u32.u16 hi1, xr; mul.rn.f16x2 a2, qz10, p0; fma.rn.f16x2 p1, qz11, qz11, c; fma.rn.f16x2 g7, qz7, h1, qz7; prmt.b32 h0, lo0, hi0, 0x5410;\n"
        "L74:\n"
        "wgmma.wait_group.sync.aligned 0;\n"
        "mov.u32 ad, %tid.x; and.b32 ad, ad, 127; mad.wide.u32 gq, ad, 16, %15;\n"
        "ld.global.v4.b32 {qa0,qa1,qa2,qa3}, [gq+0];\n"
        "ld.global.v4.b32 {qa4,qa5,qa6,qa7}, [gq+2048];\n"
        "ld.global.v4.b32 {qa8,qa9,qa10,qa11}, [gq+4096];\n"
        "ld.global.v4.b32 {qa12,qa13,qa14,qa15}, [gq+6144];\n"
        "ld.global.v4.b32 {qa16,qa17,qa18,qa19}, [gq+8192];\n"
        "ld.global.v4.b32 {qa20,qa21,qa22,qa23}, [gq+10240];\n"
        "@!pl bra.uni FPREB;\n"
        "sub.u32 tt, off, %9; cvt.u64.u32 gp, tt; add.s64 gp, gp, %12;\n"
        "elect.sync _|pr, 0xffffffff;\n"
        "@pr cp.async.bulk.prefetch.L2.global [gp], 12288;\n"
        "cvt.u64.u32 gp, off; add.s64 gp, gp, %11;\n"
        "@pr cp.async.bulk.prefetch.L2.global [gp], 12288;\n"
        "FPREB:\n"
        "mov.u32 tt, 231232; mbarrier.try_wait.parity.shared::cta.b64 pw, [tt], %13;\n"
        "@!pw bra.uni SPINFR;\n"
        "BACKFR:\n"
        "mov.u32 tt, 230792; ld.shared.v2.b32 {osc, tt}, [tt];\n"
        "setp.ne.u32 pr, tt, 0; vote.sync.any.pred pr, pr, 0xffffffff;\n"
        "@pr bra.uni RETRY;\n"
        "@!pl bra.uni FLOADB;\n"
        "sub.u32 tt, off, %9; cvt.u64.u32 gp, tt; add.s64 gp, gp, %12;\n"
        "elect.sync _|pr, 0xffffffff;\n"
        "@pr mbarrier.arrive.expect_tx.shared::cta.b64 _, [ybar], 12288;\n"
        "@pr cp.async.bulk.shared::cluster.global.mbarrier::complete_tx::bytes [%5], [gp], 12288, [ybar];\n"
        "FLOADB:\n"
        "mad.lo.u32 tt, n, 8, tbar; mbarrier.try_wait.parity.shared::cta.b64 pw, [tt], tpar;\n"
        "@!pw bra.uni SPINFT;\n"
        "BACKFT:\n"
        "ld.shared.v4.b32 {o0,o1,o2,o3}, [%8+0];\n"
        "ld.shared.v4.b32 {o4,o5,o6,o7}, [%8+64];\n"
        "ld.shared.v4.b32 {o8,o9,o10,o11}, [%8+128];\n"
        "ld.shared.v4.b32 {o12,o13,o14,o15}, [%8+192];\n"
        "ld.shared.v4.b32 {o16,o17,o18,o19}, [%8+256];\n"
        "ld.shared.v4.b32 {o20,o21,o22,o23}, [%8+320];\n"
        "mov.u32 tt, 231208; mbarrier.try_wait.parity.shared::cta.b64 pw, [tt], 0;\n"
        "@!pw bra.uni SPINF0;\n"
        "BACKF0:\n"
        "wgmma.fence.sync.aligned;\n"
        "add.s64 dt, w2d, 0; wgmma.mma_async.sync.aligned.m64n96k16.f16.f16.f16 {o0,o1,o2,o3,o4,o5,o6,o7,o8,o9,o10,o11,o12,o13,o14,o15,o16,o17,o18,o19,o20,o21,o22,o23}, {qa0,qa1,qa2,qa3}, dt, pt, 1, 1, 1;\n"
        "wgmma.commit_group.sync.aligned;\n"
        "wgmma.fence.sync.aligned;\n"
        "add.s64 dt, w2d, 64; wgmma.mma_async.sync.aligned.m64n96k16.f16.f16.f16 {o0,o1,o2,o3,o4,o5,o6,o7,o8,o9,o10,o11,o12,o13,o14,o15,o16,o17,o18,o19,o20,o21,o22,o23}, {qa4,qa5,qa6,qa7}, dt, pt, 1, 1, 1;\n"
        "wgmma.commit_group.sync.aligned;\n"
        "wgmma.wait_group.sync.aligned 1;\n"
        "@pz bra.uni R1;\n"
        "mov.u32 ad, %tid.x; and.b32 ad, ad, 127; mad.wide.u32 gq, ad, 16, %15;\n"
        "ld.volatile.global.v4.b32 {qa0,qa1,qa2,qa3}, [gq+12288];\n"
        "R1:\n"
        "wgmma.fence.sync.aligned;\n"
        "add.s64 dt, w2d, 128; wgmma.mma_async.sync.aligned.m64n96k16.f16.f16.f16 {o0,o1,o2,o3,o4,o5,o6,o7,o8,o9,o10,o11,o12,o13,o14,o15,o16,o17,o18,o19,o20,o21,o22,o23}, {qa8,qa9,qa10,qa11}, dt, pt, 1, 1, 1;\n"
        "wgmma.commit_group.sync.aligned;\n"
        "wgmma.wait_group.sync.aligned 1;\n"
        "@pz bra.uni R2;\n"
        "mov.u32 ad, %tid.x; and.b32 ad, ad, 127; mad.wide.u32 gq, ad, 16, %15;\n"
        "ld.volatile.global.v4.b32 {qa4,qa5,qa6,qa7}, [gq+14336];\n"
        "R2:\n"
        "wgmma.fence.sync.aligned;\n"
        "add.s64 dt, w2d, 192; wgmma.mma_async.sync.aligned.m64n96k16.f16.f16.f16 {o0,o1,o2,o3,o4,o5,o6,o7,o8,o9,o10,o11,o12,o13,o14,o15,o16,o17,o18,o19,o20,o21,o22,o23}, {qa12,qa13,qa14,qa15}, dt, pt, 1, 1, 1;\n"
        "wgmma.commit_group.sync.aligned;\n"
        "wgmma.wait_group.sync.aligned 1;\n"
        "@pz bra.uni R3;\n"
        "mov.u32 ad, %tid.x; and.b32 ad, ad, 127; mad.wide.u32 gq, ad, 16, %15;\n"
        "ld.volatile.global.v4.b32 {qa8,qa9,qa10,qa11}, [gq+16384];\n"
        "R3:\n"
        "wgmma.fence.sync.aligned;\n"
        "add.s64 dt, w2d, 256; wgmma.mma_async.sync.aligned.m64n96k16.f16.f16.f16 {o0,o1,o2,o3,o4,o5,o6,o7,o8,o9,o10,o11,o12,o13,o14,o15,o16,o17,o18,o19,o20,o21,o22,o23}, {qa16,qa17,qa18,qa19}, dt, pt, 1, 1, 1;\n"
        "wgmma.commit_group.sync.aligned;\n"
        "wgmma.wait_group.sync.aligned 1;\n"
        "@pz bra.uni R4;\n"
        "mov.u32 ad, %tid.x; and.b32 ad, ad, 127; mad.wide.u32 gq, ad, 16, %15;\n"
        "ld.volatile.global.v4.b32 {qa12,qa13,qa14,qa15}, [gq+18432];\n"
        "R4:\n"
        "wgmma.fence.sync.aligned;\n"
        "add.s64 dt, w2d, 320; wgmma.mma_async.sync.aligned.m64n96k16.f16.f16.f16 {o0,o1,o2,o3,o4,o5,o6,o7,o8,o9,o10,o11,o12,o13,o14,o15,o16,o17,o18,o19,o20,o21,o22,o23}, {qa20,qa21,qa22,qa23}, dt, pt, 1, 1, 1;\n"
        "wgmma.commit_group.sync.aligned;\n"
        "wgmma.wait_group.sync.aligned 1;\n"
        "@pz bra.uni R5;\n"
        "mov.u32 ad, %tid.x; and.b32 ad, ad, 127; mad.wide.u32 gq, ad, 16, %15;\n"
        "ld.volatile.global.v4.b32 {qa16,qa17,qa18,qa19}, [gq+20480];\n"
        "R5:\n"
        "@pn mbarrier.arrive.shared::cta.b64 _, [tbar+64];\n"
        "wgmma.fence.sync.aligned;\n"
        "add.s64 dt, w2d, 384; wgmma.mma_async.sync.aligned.m64n96k16.f16.f16.f16 {o0,o1,o2,o3,o4,o5,o6,o7,o8,o9,o10,o11,o12,o13,o14,o15,o16,o17,o18,o19,o20,o21,o22,o23}, {qa0,qa1,qa2,qa3}, dt, pt, 1, 1, 1;\n"
        "wgmma.commit_group.sync.aligned;\n"
        "wgmma.wait_group.sync.aligned 1;\n"
        "@pz bra.uni R6;\n"
        "mov.u32 ad, %tid.x; and.b32 ad, ad, 127; mad.wide.u32 gq, ad, 16, %15;\n"
        "ld.volatile.global.v4.b32 {qa20,qa21,qa22,qa23}, [gq+22528];\n"
        "R6:\n"
        "wgmma.fence.sync.aligned;\n"
        "add.s64 dt, w2d, 448; wgmma.mma_async.sync.aligned.m64n96k16.f16.f16.f16 {o0,o1,o2,o3,o4,o5,o6,o7,o8,o9,o10,o11,o12,o13,o14,o15,o16,o17,o18,o19,o20,o21,o22,o23}, {qa4,qa5,qa6,qa7}, dt, pt, 1, 1, 1;\n"
        "wgmma.commit_group.sync.aligned;\n"
        "wgmma.wait_group.sync.aligned 1;\n"
        "@pz bra.uni R7;\n"
        "mov.u32 ad, %tid.x; and.b32 ad, ad, 127; mad.wide.u32 gq, ad, 16, %15;\n"
        "ld.volatile.global.v4.b32 {qa0,qa1,qa2,qa3}, [gq+24576];\n"
        "R7:\n"
        "mov.u32 tt, 231216; mbarrier.try_wait.parity.shared::cta.b64 pw, [tt], 0;\n"
        "@!pw bra.uni SPINF1;\n"
        "BACKF1:\n"
        "wgmma.fence.sync.aligned;\n"
        "add.s64 dt, w2d, 512; wgmma.mma_async.sync.aligned.m64n96k16.f16.f16.f16 {o0,o1,o2,o3,o4,o5,o6,o7,o8,o9,o10,o11,o12,o13,o14,o15,o16,o17,o18,o19,o20,o21,o22,o23}, {qa8,qa9,qa10,qa11}, dt, pt, 1, 1, 1;\n"
        "wgmma.commit_group.sync.aligned;\n"
        "wgmma.wait_group.sync.aligned 1;\n"
        "@pz bra.uni R8;\n"
        "mov.u32 ad, %tid.x; and.b32 ad, ad, 127; mad.wide.u32 gq, ad, 16, %15;\n"
        "ld.volatile.global.v4.b32 {qa4,qa5,qa6,qa7}, [gq+26624];\n"
        "R8:\n"
        "wgmma.fence.sync.aligned;\n"
        "add.s64 dt, w2d, 576; wgmma.mma_async.sync.aligned.m64n96k16.f16.f16.f16 {o0,o1,o2,o3,o4,o5,o6,o7,o8,o9,o10,o11,o12,o13,o14,o15,o16,o17,o18,o19,o20,o21,o22,o23}, {qa12,qa13,qa14,qa15}, dt, pt, 1, 1, 1;\n"
        "wgmma.commit_group.sync.aligned;\n"
        "wgmma.wait_group.sync.aligned 1;\n"
        "@pz bra.uni R9;\n"
        "mov.u32 ad, %tid.x; and.b32 ad, ad, 127; mad.wide.u32 gq, ad, 16, %15;\n"
        "ld.volatile.global.v4.b32 {qa8,qa9,qa10,qa11}, [gq+28672];\n"
        "R9:\n"
        "wgmma.fence.sync.aligned;\n"
        "add.s64 dt, w2d, 640; wgmma.mma_async.sync.aligned.m64n96k16.f16.f16.f16 {o0,o1,o2,o3,o4,o5,o6,o7,o8,o9,o10,o11,o12,o13,o14,o15,o16,o17,o18,o19,o20,o21,o22,o23}, {qa16,qa17,qa18,qa19}, dt, pt, 1, 1, 1;\n"
        "wgmma.commit_group.sync.aligned;\n"
        "wgmma.wait_group.sync.aligned 1;\n"
        "@pz bra.uni R10;\n"
        "mov.u32 ad, %tid.x; and.b32 ad, ad, 127; mad.wide.u32 gq, ad, 16, %15;\n"
        "ld.volatile.global.v4.b32 {qa12,qa13,qa14,qa15}, [gq+30720];\n"
        "R10:\n"
        "wgmma.fence.sync.aligned;\n"
        "add.s64 dt, w2d, 704; wgmma.mma_async.sync.aligned.m64n96k16.f16.f16.f16 {o0,o1,o2,o3,o4,o5,o6,o7,o8,o9,o10,o11,o12,o13,o14,o15,o16,o17,o18,o19,o20,o21,o22,o23}, {qa20,qa21,qa22,qa23}, dt, pt, 1, 1, 1;\n"
        "wgmma.commit_group.sync.aligned;\n"
        "wgmma.fence.sync.aligned;\n"
        "add.s64 dt, w2d, 768; wgmma.mma_async.sync.aligned.m64n96k16.f16.f16.f16 {o0,o1,o2,o3,o4,o5,o6,o7,o8,o9,o10,o11,o12,o13,o14,o15,o16,o17,o18,o19,o20,o21,o22,o23}, {qa0,qa1,qa2,qa3}, dt, pt, 1, 1, 1;\n"
        "wgmma.commit_group.sync.aligned;\n"
        "wgmma.fence.sync.aligned;\n"
        "add.s64 dt, w2d, 832; wgmma.mma_async.sync.aligned.m64n96k16.f16.f16.f16 {o0,o1,o2,o3,o4,o5,o6,o7,o8,o9,o10,o11,o12,o13,o14,o15,o16,o17,o18,o19,o20,o21,o22,o23}, {qa4,qa5,qa6,qa7}, dt, pt, 1, 1, 1;\n"
        "wgmma.commit_group.sync.aligned;\n"
        "wgmma.fence.sync.aligned;\n"
        "add.s64 dt, w2d, 896; wgmma.mma_async.sync.aligned.m64n96k16.f16.f16.f16 {o0,o1,o2,o3,o4,o5,o6,o7,o8,o9,o10,o11,o12,o13,o14,o15,o16,o17,o18,o19,o20,o21,o22,o23}, {qa8,qa9,qa10,qa11}, dt, pt, 1, 1, 1;\n"
        "wgmma.commit_group.sync.aligned;\n"
        "wgmma.fence.sync.aligned;\n"
        "add.s64 dt, w2d, 960; wgmma.mma_async.sync.aligned.m64n96k16.f16.f16.f16 {o0,o1,o2,o3,o4,o5,o6,o7,o8,o9,o10,o11,o12,o13,o14,o15,o16,o17,o18,o19,o20,o21,o22,o23}, {qa12,qa13,qa14,qa15}, dt, pt, 1, 1, 1;\n"
        "wgmma.commit_group.sync.aligned;\n"
        "bra.uni B74;\n"
        "SPINFR: mov.u32 cnt, 0;\n"
        "SPINFRL:\n"
        "mov.u32 tt, 231232; mbarrier.try_wait.parity.shared::cta.b64 pw, [tt], %13;\n"
        "@pw bra.uni BACKFR;\n"
        "add.u32 cnt, cnt, 1; setp.lt.u32 pw, cnt, 0x100000;\n"
        "@pw bra.uni SPINFRL;\n"
        "trap;\n"
        "SPINFT: mov.u32 cnt, 0;\n"
        "SPINFTL:\n"
        "mad.lo.u32 tt, n, 8, tbar; mbarrier.try_wait.parity.shared::cta.b64 pw, [tt], tpar;\n"
        "@pw bra.uni BACKFT;\n"
        "add.u32 cnt, cnt, 1; setp.lt.u32 pw, cnt, 0x100000;\n"
        "@pw bra.uni SPINFTL;\n"
        "trap;\n"
        "SPINF0: mov.u32 cnt, 0;\n"
        "SPINF0L:\n"
        "mov.u32 tt, 231208; mbarrier.try_wait.parity.shared::cta.b64 pw, [tt], 0;\n"
        "@pw bra.uni BACKF0;\n"
        "add.u32 cnt, cnt, 1; setp.lt.u32 pw, cnt, 0x100000;\n"
        "@pw bra.uni SPINF0L;\n"
        "trap;\n"
        "SPINF1: mov.u32 cnt, 0;\n"
        "SPINF1L:\n"
        "mov.u32 tt, 231216; mbarrier.try_wait.parity.shared::cta.b64 pw, [tt], 0;\n"
        "@pw bra.uni BACKF1;\n"
        "add.u32 cnt, cnt, 1; setp.lt.u32 pw, cnt, 0x100000;\n"
        "@pw bra.uni SPINF1L;\n"
        "trap;\n"
        "SPINL: mov.u32 cnt, 0;\n"
        "SPINLL:\n"
        "and.b32 tt, n, 1; mbarrier.try_wait.parity.shared::cta.b64 pw, [xbar], tt;\n"
        "@pw bra.uni BACKL;\n"
        "add.u32 cnt, cnt, 1; setp.lt.u32 pw, cnt, 0x100000;\n"
        "@pw bra.uni SPINLL;\n"
        "trap;\n"
        "LAST:\n"
        "and.b32 tt, n, 1; mbarrier.try_wait.parity.shared::cta.b64 pw, [xbar], tt;\n"
        "@!pw bra.uni SPINL;\n"
        "BACKL:\n"
        "and.b32 ad, %7, 0xffff; add.u32 ad, ad, %5; ld.shared.v4.b32 {r0,r1,r2,r3}, [ad+0];\n"
        "shr.u32 ad, %7, 16; add.u32 ad, ad, %5; ld.shared.v4.b32 {r4,r5,r6,r7}, [ad+0];\n"
        "and.b32 ad, %7, 0xffff; add.u32 ad, ad, %5; ld.shared.v4.b32 {r8,r9,r10,r11}, [ad+64];\n"
        "shr.u32 ad, %7, 16; add.u32 ad, ad, %5; ld.shared.v4.b32 {r12,r13,r14,r15}, [ad+64];\n"
        "and.b32 ad, %7, 0xffff; add.u32 ad, ad, %5; ld.shared.v4.b32 {r16,r17,r18,r19}, [ad+128];\n"
        "shr.u32 ad, %7, 16; add.u32 ad, ad, %5; ld.shared.v4.b32 {r20,r21,r22,r23}, [ad+128];\n"
        "wgmma.wait_group.sync.aligned 0;\n"
        "mov.b32 {xl, xh}, o0; cvt.f32.f16 f0, xl; cvt.f32.f16 f1, xh; cvt.rn.bf16x2.f32 tt, f1, f0; fma.rn.bf16x2 r0, tt, osc, r0;\n"
        "mov.b32 {xl, xh}, o2; cvt.f32.f16 f0, xl; cvt.f32.f16 f1, xh; cvt.rn.bf16x2.f32 tt, f1, f0; fma.rn.bf16x2 r1, tt, osc, r1;\n"
        "mov.b32 {xl, xh}, o4; cvt.f32.f16 f0, xl; cvt.f32.f16 f1, xh; cvt.rn.bf16x2.f32 tt, f1, f0; fma.rn.bf16x2 r2, tt, osc, r2;\n"
        "mov.b32 {xl, xh}, o6; cvt.f32.f16 f0, xl; cvt.f32.f16 f1, xh; cvt.rn.bf16x2.f32 tt, f1, f0; fma.rn.bf16x2 r3, tt, osc, r3;\n"
        "and.b32 ad, %7, 0xffff; add.u32 ad, ad, off; cvt.u64.u32 gp, ad; add.s64 gp, gp, %12; st.global.v4.b32 [gp+0], {r0,r1,r2,r3};\n"
        "mov.b32 {xl, xh}, o1; cvt.f32.f16 f0, xl; cvt.f32.f16 f1, xh; cvt.rn.bf16x2.f32 tt, f1, f0; fma.rn.bf16x2 r4, tt, osc, r4;\n"
        "mov.b32 {xl, xh}, o3; cvt.f32.f16 f0, xl; cvt.f32.f16 f1, xh; cvt.rn.bf16x2.f32 tt, f1, f0; fma.rn.bf16x2 r5, tt, osc, r5;\n"
        "mov.b32 {xl, xh}, o5; cvt.f32.f16 f0, xl; cvt.f32.f16 f1, xh; cvt.rn.bf16x2.f32 tt, f1, f0; fma.rn.bf16x2 r6, tt, osc, r6;\n"
        "mov.b32 {xl, xh}, o7; cvt.f32.f16 f0, xl; cvt.f32.f16 f1, xh; cvt.rn.bf16x2.f32 tt, f1, f0; fma.rn.bf16x2 r7, tt, osc, r7;\n"
        "shr.u32 ad, %7, 16; add.u32 ad, ad, off; cvt.u64.u32 gp, ad; add.s64 gp, gp, %12; st.global.v4.b32 [gp+0], {r4,r5,r6,r7};\n"
        "mov.b32 {xl, xh}, o8; cvt.f32.f16 f0, xl; cvt.f32.f16 f1, xh; cvt.rn.bf16x2.f32 tt, f1, f0; fma.rn.bf16x2 r8, tt, osc, r8;\n"
        "mov.b32 {xl, xh}, o10; cvt.f32.f16 f0, xl; cvt.f32.f16 f1, xh; cvt.rn.bf16x2.f32 tt, f1, f0; fma.rn.bf16x2 r9, tt, osc, r9;\n"
        "mov.b32 {xl, xh}, o12; cvt.f32.f16 f0, xl; cvt.f32.f16 f1, xh; cvt.rn.bf16x2.f32 tt, f1, f0; fma.rn.bf16x2 r10, tt, osc, r10;\n"
        "mov.b32 {xl, xh}, o14; cvt.f32.f16 f0, xl; cvt.f32.f16 f1, xh; cvt.rn.bf16x2.f32 tt, f1, f0; fma.rn.bf16x2 r11, tt, osc, r11;\n"
        "and.b32 ad, %7, 0xffff; add.u32 ad, ad, off; cvt.u64.u32 gp, ad; add.s64 gp, gp, %12; st.global.v4.b32 [gp+64], {r8,r9,r10,r11};\n"
        "mov.b32 {xl, xh}, o9; cvt.f32.f16 f0, xl; cvt.f32.f16 f1, xh; cvt.rn.bf16x2.f32 tt, f1, f0; fma.rn.bf16x2 r12, tt, osc, r12;\n"
        "mov.b32 {xl, xh}, o11; cvt.f32.f16 f0, xl; cvt.f32.f16 f1, xh; cvt.rn.bf16x2.f32 tt, f1, f0; fma.rn.bf16x2 r13, tt, osc, r13;\n"
        "mov.b32 {xl, xh}, o13; cvt.f32.f16 f0, xl; cvt.f32.f16 f1, xh; cvt.rn.bf16x2.f32 tt, f1, f0; fma.rn.bf16x2 r14, tt, osc, r14;\n"
        "mov.b32 {xl, xh}, o15; cvt.f32.f16 f0, xl; cvt.f32.f16 f1, xh; cvt.rn.bf16x2.f32 tt, f1, f0; fma.rn.bf16x2 r15, tt, osc, r15;\n"
        "shr.u32 ad, %7, 16; add.u32 ad, ad, off; cvt.u64.u32 gp, ad; add.s64 gp, gp, %12; st.global.v4.b32 [gp+64], {r12,r13,r14,r15};\n"
        "mov.b32 {xl, xh}, o16; cvt.f32.f16 f0, xl; cvt.f32.f16 f1, xh; cvt.rn.bf16x2.f32 tt, f1, f0; fma.rn.bf16x2 r16, tt, osc, r16;\n"
        "mov.b32 {xl, xh}, o18; cvt.f32.f16 f0, xl; cvt.f32.f16 f1, xh; cvt.rn.bf16x2.f32 tt, f1, f0; fma.rn.bf16x2 r17, tt, osc, r17;\n"
        "mov.b32 {xl, xh}, o20; cvt.f32.f16 f0, xl; cvt.f32.f16 f1, xh; cvt.rn.bf16x2.f32 tt, f1, f0; fma.rn.bf16x2 r18, tt, osc, r18;\n"
        "mov.b32 {xl, xh}, o22; cvt.f32.f16 f0, xl; cvt.f32.f16 f1, xh; cvt.rn.bf16x2.f32 tt, f1, f0; fma.rn.bf16x2 r19, tt, osc, r19;\n"
        "and.b32 ad, %7, 0xffff; add.u32 ad, ad, off; cvt.u64.u32 gp, ad; add.s64 gp, gp, %12; st.global.v4.b32 [gp+128], {r16,r17,r18,r19};\n"
        "mov.b32 {xl, xh}, o17; cvt.f32.f16 f0, xl; cvt.f32.f16 f1, xh; cvt.rn.bf16x2.f32 tt, f1, f0; fma.rn.bf16x2 r20, tt, osc, r20;\n"
        "mov.b32 {xl, xh}, o19; cvt.f32.f16 f0, xl; cvt.f32.f16 f1, xh; cvt.rn.bf16x2.f32 tt, f1, f0; fma.rn.bf16x2 r21, tt, osc, r21;\n"
        "mov.b32 {xl, xh}, o21; cvt.f32.f16 f0, xl; cvt.f32.f16 f1, xh; cvt.rn.bf16x2.f32 tt, f1, f0; fma.rn.bf16x2 r22, tt, osc, r22;\n"
        "mov.b32 {xl, xh}, o23; cvt.f32.f16 f0, xl; cvt.f32.f16 f1, xh; cvt.rn.bf16x2.f32 tt, f1, f0; fma.rn.bf16x2 r23, tt, osc, r23;\n"
        "shr.u32 ad, %7, 16; add.u32 ad, ad, off; cvt.u64.u32 gp, ad; add.s64 gp, gp, %12; st.global.v4.b32 [gp+128], {r20,r21,r22,r23};\n"
        ASM_MARK
        "mov.u32 %0, 0;\n"
        "OUT:\n"
        "}\n"
        : "=r"(retry)
        : "r"(prm.helper_desc[0]), "r"(prm.helper_desc[1]), "r"(c.wg), "r"(c.off), "r"(c.xs), "r"(c.a_offs), "r"(c.xs_offs), "r"(c.bias_addr),
          "r"(c.step), "r"(c.w), "l"(prm.x), "l"(prm.out), "r"(round), "r"(c.last), "l"(c.park)
        : "memory");
    return retry;
}

__device__ __forceinline__ float warp_sum(float v) {
#pragma unroll
    for (int s = 16; s >= 1; s >>= 1) v += __shfl_xor_sync(0xffffffffu, v, s);
    return v;
}
__device__ __forceinline__ float pow2f(int e) { return __uint_as_float((uint32_t)(e + 127) << 23); }
__device__ __forceinline__ int exponent_of(float v) { return (int)(__float_as_uint(v) >> 23) - 127; }
__device__ __forceinline__ float lds_bf16(uint32_t addr) {
    uint16_t v; asm volatile("ld.shared.u16 %0, [%1];" : "=h"(v) : "r"(addr) : "memory"); return bf_lo(v);
}

__device__ __forceinline__ void publish_bias(const Params& prm, uint32_t c, uint32_t tag) {
    const uint32_t lane = fresh_tid() & 31;
    const uint32_t col = sb + SM_W2 + (c >> 5) * 24576 + lane * 64 + ((((c >> 3) ^ (lane >> 1)) & 3) * 16) + (c & 7) * 2;
    float v = 0.0f;
#pragma unroll
    for (int k = 0; k < EX / 32; k++) v = fmaf(lds_bf16(col + k * 2048), lds_bf16(sb + SM_BETA + lane * 2 + k * 64), v);
    v = warp_sum(v);
    if (lane == 0)
        asm volatile("st.relaxed.gpu.global.u64 [%0], %1;" ::"l"(prm.g->bias + c), "l"((uint64_t)tag << 32 | __float_as_uint(v)) : "memory");
}
__device__ __forceinline__ void collect_bias(const Params& prm, uint32_t tag) {
    const uint32_t lane = fresh_tid() & 31;
    if (lane < 24) {
        const unsigned long long* src = prm.g->bias + 32 * (lane >> 3) + 8 * (lane & 3) + (lane & 4);
        uint32_t v[4], t[4], spins = 0;
        for (;;) {
#pragma unroll
            for (int k = 0; k < 4; k++)
                asm volatile("{\n.reg .b64 w;\nld.relaxed.gpu.global.u64 w, [%2];\nmov.b64 {%0, %1}, w;\n}\n"
                             : "=r"(v[k]), "=r"(t[k]) : "l"(src + k) : "memory");
            if (t[0] == tag && t[1] == tag && t[2] == tag && t[3] == tag) break;
            if (++spins > (1u << 22)) __trap();
        }
        sts128(sb + SM_BIAS + lane * 16, v[0], v[1], v[2], v[3]);
    }
    __syncwarp();
}
__device__ __forceinline__ float fetch_w2_row(uint32_t (&u)[12][4], uint32_t row, uint32_t sw) {
    uint32_t mx[4] = {};
#pragma unroll
    for (int a = 0; a < 3; a++)
#pragma unroll
        for (int k = 0; k < 4; k++) {
            asm volatile("ld.shared.v4.b32 {%0,%1,%2,%3}, [%4];"
                         : "=r"(u[a * 4][k]), "=r"(u[a * 4 + 1][k]), "=r"(u[a * 4 + 2][k]), "=r"(u[a * 4 + 3][k])
                         : "r"(row + a * 24576 + ((k * 16) ^ sw)) : "memory");
#pragma unroll
            for (int b = 0; b < 4; b++) asm("max.xorsign.abs.bf16x2 %0, %0, %1;" : "+r"(mx[b]) : "r"(u[a * 4 + b][k]));
        }
#pragma unroll
    for (int b = 1; b < 4; b++) asm("max.xorsign.abs.bf16x2 %0, %0, %1;" : "+r"(mx[0]) : "r"(mx[b]));
    return fmaxf(fabsf(bf_lo(mx[0])), fabsf(bf_hi(mx[0])));
}

template <bool FAST> __device__ __forceinline__ bool grn_stats(const float (&ss)[3], const float (&gm)[3], const float (&bt)[3],
                                                               const float (&top)[3], int e, float (&gx)[3], float& inv, int& eo) {
    float b0 = 0.0f, b1 = 0.0f;
    bool bad = false;
#pragma unroll
    for (int k = 0; k < 3; k++) {
        gx[k] = sqrt_fast(fmaf(ss[k], INV_2A * INV_2A, 1e-6f));
        const float rt = sqrt_fast(ss[k] + 1.0f) * INV_2A * top[k];
        b0 += fmaf(bt[k], top[k], rt);
        b1 += rt * fabsf(gm[k]) * gx[k];
        bad |= !(ss[k] >= 16.0f && ss[k] < ACC_LIMIT);
    }
    const float sum = gx[0] + gx[1] + gx[2];
    uint32_t r[4] = {FAST ? __reduce_add_sync(0xffffffffu, __float2uint_rn(sum * 128.0f)) : __float_as_uint(warp_sum(sum)),
                     __reduce_max_sync(0xffffffffu, __float_as_uint(b0)), __reduce_max_sync(0xffffffffu, __float_as_uint(b1)),
                     (uint32_t)__any_sync(0xffffffffu, bad)};
    if ((e & 31) == 0) sts128(sb + SM_SEL + (e >> 5) * 16, r[0], r[1], r[2], r[3]);
    MARK(6);
    named_sync(10, 128);
    lds128(r, sb + SM_SEL + (e & 3) * 16);
    if ((e & 31) >= 4) r[0] = 0;
    const float tot = FAST ? __uint2float_rn(__reduce_add_sync(0xffffffffu, r[0])) * (1.0f / 128) : warp_sum(__uint_as_float(r[0]));
    inv = __fdividef(1.0f, fmaf(tot, 1.0f / EX, 1e-6f));
    const float bound = fmaf(__uint_as_float(__reduce_max_sync(0xffffffffu, r[2])), inv,
                             __uint_as_float(__reduce_max_sync(0xffffffffu, r[1]))) * (EX / 3);
    eo = min(max(exponent_of(bound), -90), 126) - 14;
    return __any_sync(0xffffffffu, r[3]);
}

__device__ __forceinline__ const float* exact_sums(const Params& prm) {
    const int lane = fresh_tid() & 31, warp = fresh_warp(), wg = warp >> 2;
    const uint32_t epoch = lds32(sb + SM_RED + (RED_EPOCH + 1) * 4), bar = sb + SM_BAR + BAR_W1 * 8;
    if (wg < 3 && fresh_cta() < NUM_CTAS) {
        uint32_t wa[2][24], d[2][16];
        float acc[2][2] = {};
        const uint32_t wd = prm.w1desc + ((2 * wg * 12288 + 5 * 2048) >> 4);
        load_w1t(wa, wg, warp & 3, lane);
#pragma unroll 1
        for (int n = 0; n < ROWS_PER_CTA; n++) {
            const int slot = n - (ROWS_PER_CTA - NX);
            if (slot < 0) {
                if (warp == 0) {
                    expect_tx(bar, TILE_BYTES);
                    bulk_load(sb + SM_SPARE, (const char*)prm.out + (cta_tile0(fresh_cta()) + n * cta_stride(fresh_cta())), TILE_BYTES, bar);
                }
                mbar_wait(bar, (n + 1) & 1);
            }
            const uint32_t yd = prm.ydesc + ((slot < 0 ? SM_SPARE - SM_Y1 : slot * SLOT_BYTES) >> 4);
            gemm1_t<0>(d[0], wa[0], yd, wd);
            gemm1_t<1>(d[1], wa[1], yd, wd);
            wg_wait<0>();
            pin(d[0]); pin(d[1]);
            gelu_sumsq_f(d[0], acc[0]);
            gelu_sumsq_f(d[1], acc[1]);
            named_sync(1, 384);
        }
        publish_sums(acc, prm.g->sums[epoch & 1], &prm.g->count[1], wg, warp & 3, lane);
    }
    grid_wait(&prm.g->count[1], (epoch + 1) * NUM_CTAS);
    return prm.g->sums[epoch & 1];
}

__device__ __forceinline__ void scale_w2_row(uint32_t (&u)[12][4], uint32_t row, uint32_t sw, float sc, int eo, uint32_t bar) {
    const float dn = pow2f(-eo);
    if (eo > 6) {
        const uint32_t dn2 = pack_bf2(dn, dn);
#pragma unroll
        for (int k = 0; k < 48; k++) u[k >> 2][k & 3] = bf2_mul(u[k >> 2][k & 3], dn2);
    } else {
        sc *= dn;
    }
    const uint32_t s2 = pack_bf2(sc * 0x1p-112f, sc * 0x1p-112f);
#pragma unroll
    for (int k = 0; k < 12; k++) {
        uint32_t v[4];
#pragma unroll
        for (int b = 0; b < 4; b++) {
            v[b] = bf2_mul(u[k][b], s2);
            v[b] += (v[b] & 0x7fff7fffu) * 7u;
        }
        sts128(row + (k >> 2) * 24576 + (((k & 3) * 16) ^ sw), v[0], v[1], v[2], v[3]);
    }
    fence_async_smem();
    __syncwarp();
    mbar_arrive_if(bar, (fresh_tid() & 31) == 0);
}
template <bool FIRST> __device__ __forceinline__ void prepare_w2(const Params& prm, const float* exact) {
    const int e = fresh_tid() - EX, lane = e & 31, warp = fresh_warp();
    const uint32_t row = sb + SM_W2 + e * 64, sw = ((e >> 1) & 3) * 16;
    uint32_t u[2][12][4];
    float top[3], gm[3], bt[3], ss[3], gx[3], inv;
    mbar_wait_c<0>(sb + SM_BAR + BAR_W2 * 8);
    top[2] = fetch_w2_row(u[0], row + 16384, sw);
    top[0] = fetch_w2_row(u[0], row, sw);
    top[1] = fetch_w2_row(u[1], row + 8192, sw);
#pragma unroll
    for (int k = 0; k < 3; k++) {
        gm[k] = lds_bf16(sb + SM_GAMMA + e * 2 + k * 256);
        bt[k] = fabsf(lds_bf16(sb + SM_BETA + e * 2 + k * 256));
    }
    MARK(3);
    if (FIRST) {
        const uint32_t epoch = lds32(sb + SM_RED + RED_EPOCH * 4);
        named_sync(11, 512);
        if (warp == 12) collect_bias(prm, epoch + 1);
        MARK(4);
        collect_fast(acc_word(prm, epoch, e), prm.ctas, ss);
        if (e == 32 && fresh_cta() == 0) prm.g->count[0] = epoch + 1;
    } else {
#pragma unroll
        for (int k = 0; k < 3; k++) ss[k] = __ldcg(exact + e + 128 * k);
    }
    MARK(5);
    int eo;
    const bool redo = (grn_stats<FIRST>(ss, gm, bt, top, e, gx, inv, eo) || FORCE_EXACT) && FIRST;
    MARK(8);
    if (warp == 12) {
        const float up = pow2f(eo), dn = pow2f(-eo);
        if (lane == 24) sts64(sb + SM_RED + RED_SCALE * 4, pack_bf2(up, up), redo);
        if (lane < 24 && !redo) {
            uint32_t b[4];
            lds128(b, sb + SM_BIAS + lane * 16);
            const uint32_t p0 = pack_h2(__uint_as_float(b[0]) * dn, __uint_as_float(b[1]) * dn);
            const uint32_t p1 = pack_h2(__uint_as_float(b[2]) * dn, __uint_as_float(b[3]) * dn);
            sts128(sb + SM_BIAS + lane * 16, p0, p0, p1, p1);
        }
        __syncwarp();
        mbar_arrive_if(sb + SM_BAR + BAR_STAT * 8, lane == 0);
    }
    if (redo) return;
#pragma unroll
    for (int k = 0; k < 3; k++) gx[k] = fmaf(gm[k], gx[k] * inv, 1.0f) * INV_2A;
    scale_w2_row(u[0], row, sw, gx[0], eo, sb + SM_BAR + BAR_ROWS * 8);
    MARK(7);
    fetch_w2_row(u[0], row + 16384, sw);
    scale_w2_row(u[1], row + 8192, sw, gx[1], eo, sb + SM_BAR + (BAR_ROWS + 1) * 8);
    scale_w2_row(u[0], row + 16384, sw, gx[2], eo, sb + SM_BAR + (BAR_ROWS + 2) * 8);
    MARK(9);
    TS(4); TS(5);
}

__device__ __forceinline__ uint32_t helper_source(uint32_t h, uint32_t wg) { return 8 * (wg & 1) + 2 * h + (wg >> 1); }
__device__ __forceinline__ Pass2 pass2_setup(const Params& prm) {
    const int warp = fresh_warp(), wg = warp >> 2, w = warp & 3, lane = fresh_tid() & 31, arow = 16 * w + (lane & 15);
    Pass2 c;
    c.wg = wg;
    c.w = w;
    const uint32_t cta = fresh_cta();
    const bool helper = cta >= NUM_CTAS;
    c.off = helper ? cta_tile0(helper_source(cta - NUM_CTAS, wg)) : cta_tile0(cta) + (ROWS_PER_CTA - 1 - wg) * cta_stride(cta);
    c.step = helper ? -2 * ROWS_PER_CTA * ROW_BYTES : 4 * cta_stride(cta);
    c.last = wg == 3 && !helper && prm.ctas > NUM_CTAS ? 6 : 7;
    c.park = helper && wg < 3 ? prm.g->park[cta - NUM_CTAS][wg] : nullptr;
    c.xs = wg == 3 ? sb + SM_BUF3 : sb + SM_Y1 + (wg == 2 ? 2 : 1 - wg) * SLOT_BYTES;
    static_assert((ROWS_PER_CTA - 1) % NX == 1, "slot of the last tile");
    c.a_offs = (arow * 128 + (((lane >> 4) ^ (arow & 7)) * 16)) |
               (8192 + arow * 64 + (((lane >> 4) ^ ((arow >> 1) & 3)) * 16)) << 16;
    const int g = lane >> 2, px = 33 * (g & 1) + 4 * (g >> 1) + 16 * (w >> 1) + 2 * (w & 1);
    c.xs_offs = (px * 192 + (lane & 3) * 16) | ((px ^ 1) * 192 + (lane & 3) * 16) << 16;
    c.bias_addr = sb + SM_BIAS + (lane & 3) * 16;
    return c;
}

__device__ __forceinline__ void helper_start(const Params& prm) {
    const uint32_t tid = fresh_tid(), warp = fresh_warp(), lane = tid & 31;
    uint32_t cnt[2];
    asm volatile("ld.relaxed.gpu.global.v2.u32 {%0, %1}, [%2];" : "=r"(cnt[0]), "=r"(cnt[1]) : "l"(prm.g->count) : "memory");
    if (tid == 0) {
        sts64(sb + SM_RED + RED_EPOCH * 4, cnt[0], cnt[1] / NUM_CTAS);
#pragma unroll 1
        for (int k = 0; k < BAR_DW; k++) mbar_init(sb + SM_BAR + k * 8, k < BAR_TURN || k == BAR_STAT ? 1 : 4);
        fence_async_smem();
    }
    __syncthreads();
    if (tid < EX) asm volatile("red.relaxed.gpu.global.add.u64 [%0], 1;" ::"l"(acc_word(prm, cnt[0], tid)) : "memory");
    if (warp == 0) {
        expect_tx(sb + SM_BAR + BAR_W1 * 8, CH * EX * 2);
        expect_tx(sb + SM_BAR + BAR_W2 * 8, CH * EX * 2 + EX * 4);
#pragma unroll 1
        for (int q = loop_init<0>(); q < 6; q++) {
            tma_load_2d(sb + SM_W1 + q * 12288, &prm.w1_map, 64 * q, 0, sb + SM_BAR + BAR_W1 * 8);
            tma_load_2d(sb + SM_W2 + q * 12288, &prm.w2_map, 32 * (q >> 1), 192 * (q & 1), sb + SM_BAR + BAR_W2 * 8);
        }
        bulk_load(sb + SM_GAMMA, prm.gamma, EX * 2, sb + SM_BAR + BAR_W2 * 8);
        bulk_load(sb + SM_BETA, prm.beta, EX * 2, sb + SM_BAR + BAR_W2 * 8);
    }
    mbar_wait_c<0>(sb + SM_BAR + BAR_W1 * 8);
#pragma unroll 1
    for (uint32_t a = sb + SM_W1 + tid * 16; a < sb + SM_W2; a += 8192) {
        uint32_t v[4];
        lds128(v, a);
        sts128(a, pack_h2(bf_lo(v[0]), bf_hi(v[0])), pack_h2(bf_lo(v[1]), bf_hi(v[1])), pack_h2(bf_lo(v[2]), bf_hi(v[2])),
               pack_h2(bf_lo(v[3]), bf_hi(v[3])));
    }
    if (warp == 1) {
        const unsigned int* flag = prm.g->parked + helper_source(fresh_cta() - NUM_CTAS, lane & 3) + 16 * (lane >> 2);
        uint32_t v, spins = 0;
        do {
            __nanosleep(500);
            asm volatile("ld.acquire.gpu.global.u32 %0, [%1];" : "=r"(v) : "l"(flag) : "memory");
            if (++spins > (1u << 20)) __trap();
        } while (v != cnt[0] + 1);
    }
    asm volatile("fence.proxy.async;" ::: "memory");
    __syncthreads();
    asm volatile("fence.proxy.async;" ::: "memory");
    const Pass2 c = pass2_setup(prm);
    if (c.w == 0) {
        expect_tx(sb + SM_BAR + (BAR_Y2FULL + c.wg) * 8, TILE_BYTES);
        bulk_load(c.xs, (const char*)prm.out + c.off, TILE_BYTES, sb + SM_BAR + (BAR_Y2FULL + c.wg) * 8);
    }
    if (warp < 12) {
        asm volatile("bar.arrive 11, 512;" ::: "memory");
    } else {
        unsigned long long v;
        uint32_t spins = 0;
        do {
            __nanosleep(200);
            asm volatile("ld.relaxed.gpu.global.u64 %0, [%1];" : "=l"(v) : "l"(acc_word(prm, cnt[0], EX - 1)) : "memory");
            if (++spins > (1u << 20)) __trap();
        } while ((v & 255) <= HELPERS);
        __syncwarp();
    }
}

__global__ void __launch_bounds__(512, 1) convnext_kernel(const __grid_constant__ Params prm) {
    extern __shared__ __align__(1024) uint8_t smem[];
    if ((uint32_t)__cvta_generic_to_shared(smem) != sb) __trap();
    if (fresh_cta() < NUM_CTAS) {
        const uint32_t tid = fresh_tid(), warp = fresh_warp(), lane = tid & 31;
        if (warp == 0) {
            if (lane == 0) {
#pragma unroll
                for (int k = 0; k < NX; k++) mbar_init(sb + SM_GO + k * 8, 2);
                mbar_init(sb + SM_BAR + BAR_DW * 8, 1);
                mbar_init(sb + SM_BAR + BAR_W1 * 8, 1);
                mbar_init(sb + SM_BAR + BAR_W1B * 8, 1);
                fence_async_smem();
            }
            __syncwarp();
            expect_tx(sb + SM_BAR + BAR_DW * 8, 9 * CH * 2);
            bulk_load(sb + SM_Y1, prm.dw, 9 * CH * 2, sb + SM_BAR + BAR_DW * 8);
            const RowCopy rc = row_copy(prm);
#pragma unroll
            for (int k = 0; k < NX; k++) issue_row_load(rc, k, k);
            SMARK(4);
        }
        if (fresh_warp() == 15) {
            const uint32_t cta = fresh_cta();
            bulk_prefetch((const char*)prm.w1 + cta * (CH * EX * 2 / NUM_CTAS), CH * EX * 2 / NUM_CTAS);
            bulk_prefetch(prm.dw, 9 * CH * 2);
            bulk_prefetch((const char*)prm.x + (cta_tile0(cta) - cta_stride(cta)), TILE_BYTES);
        } else if (warp == 2) {
            if (lane < 2) asm volatile("prefetch.tensormap [%0];" ::"l"(&prm.w1_map + lane) : "memory");
        } else if (warp - 6u < 6) {
            if (lane == 0) {
#pragma unroll 1
                for (int k = NX + warp - 6; k < GO_COUNT + ROWS_PER_CTA + 2; k += 6)
                    mbar_init(sb + SM_GO + k * 8, k < 2 * NX ? 2 : k < GO_COUNT ? 14 : 4);
                fence_async_smem();
            }
        } else if (warp == 3) {
            const uint32_t one = (lane & 5) == ((lane & 8) >> 1) + (lane >> 4) ? 0x3f803f80u : 0u;
            sts128(sb + SM_SEL + lane * 16, one, one, one, one);
            fence_async_smem();
        } else if (tid - 128u < NX * 12 && ((fresh_cta() + 1) & 7) < 2) {
            const int k = tid - 128;
            sts128(sb + SM_X + (k / 12) * SLOT_BYTES + ((fresh_cta() & 7) == 0 ? 0 : XHALF_B + 33 * 192) + (k % 12) * 16, 0, 0, 0, 0);
        }
        __syncwarp();
        SMARK(3);
        named_sync(0, 512);
    }
    if (fresh_cta() >= NUM_CTAS) {
        helper_start(prm);
    } else if (fresh_warp() >= 12) {
        Producer pc;
        SMARK(0);
        asm volatile("setmaxnreg.inc.sync.aligned.u32 %0;" ::"n"(PRODUCER_REGS));
        SMARK(1);
        const int w = fresh_warp() & 3, lane = fresh_tid() & 31;
        const int j = lane & 7, hb = (lane >> 3) & 1, base = 4 * (2 * w + (lane >> 4));
        pc.lane = lane;
        pc.xoff[0] = hb * XHALF_B + base * 192 + j * 16;
        pc.xoff[1] = hb * XHALF_B + base * 192 + 128 + j * 8;
        const int grp = 4 * w + (lane >> 3);
#pragma unroll
        for (int o = 0; o < 2; o++) {
            const int row = (grp & 7) + 8 * (o ^ hb) + 32 * (grp >> 3);
            pc.yoff[0][o] = row * 128 + ((j ^ (row & 7)) * 16);
            pc.yoff[1][o] = 8192 + row * 64 + (((j >> 1) ^ ((row >> 1) & 3)) * 16) + (j & 1) * 8;
        }
        pc.stat = sb + SM_STAT + (8 * w + (lane >> 2)) * 32;
        pc.own = pc.stat + (lane & 3) * 8;
        const int dstep = fresh_cta() & 8 ? 3 * CH * 2 : -3 * CH * 2;
        mbar_wait_c<0>(sb + SM_BAR + BAR_DW * 8);
        SMARK(8);
#pragma unroll
        for (int tap = 0; tap < 9; tap++) {
            const uint32_t dw = sb + SM_Y1 + (3 + tap % 3) * CH * 2 + (tap / 3 - 1) * dstep;
            lds128(pc.w[tap], dw + j * 16);
            asm volatile("ld.shared.v2.b32 {%0,%1}, [%2];" : "=r"(pc.w[tap][4]), "=r"(pc.w[tap][5]) : "r"(dw + 128 + j * 8) : "memory");
        }
#pragma unroll
        for (int tap = 0; tap < 9; tap++)
#pragma unroll
            for (int u = 0; u < 6; u++) pc.w[tap][u] = bf2_mul(pc.w[tap][u], TAP_SCALE_BF2);
        produce(pc, prm);
        TS(9);
        asm volatile("setmaxnreg.dec.sync.aligned.u32 %0;" ::"n"(EVEN_REGS));
        if (fresh_warp() == 12) {
            mbar_wait_c<0>(sb + SM_BAR + BAR_W2 * 8);
            if (fresh_cta() < CH) publish_bias(prm, fresh_cta(), lds32(sb + SM_RED + RED_EPOCH * 4) + 1);
        }
    } else {
        asm volatile("setmaxnreg.dec.sync.aligned.u32 %0;" ::"n"(CONSUMER_REGS));
        {
            const int tid = fresh_tid(), warp = fresh_warp();
            if (warp == 1) {
#pragma unroll
                for (int h = 0; h < 2; h++) {
                    const uint32_t bar = sb + SM_BAR + (h ? BAR_W1B : BAR_W1) * 8;
                    expect_tx(bar, CH * EX);
#pragma unroll
                    for (int q = h; q < 6; q += 2) tma_load_2d(sb + SM_W1 + q * 12288, &prm.w1_map, 64 * q, 0, bar);
                }
            }
            uint32_t cnt[2];
            asm volatile("ld.relaxed.gpu.global.v2.u32 {%0, %1}, [%2];" : "=r"(cnt[0]), "=r"(cnt[1]) : "l"(prm.g->count) : "memory");
            SMARK(0);
            if (warp == 2) {
                const RowCopy rc = row_copy(prm);
#pragma unroll 1
                for (int i = loop_init<0>(); i < NX - 1; i++) {
                    named_sync(6 + i, 160);
                    issue_row_load(rc, i + NX, i);
                }
            }
            if (tid == 256) {
                sts64(sb + SM_RED + RED_EPOCH * 4, cnt[0], cnt[1] / NUM_CTAS);
#pragma unroll
                for (int k = 0; k < BAR_DW; k++)
                    if (k != BAR_W1 && k != BAR_W1B) mbar_init(sb + SM_BAR + k * 8, k < BAR_TURN || k == BAR_STAT ? 1 : 4);
#pragma unroll
                for (int k = 0; k < 3; k++) mbar_arrive_if(sb + SM_BAR + (BAR_Y2FULL + k) * 8, true);
            }
            if (fresh_cta() == 0) *acc_word(prm, cnt[0] + 1, tid) = 0;
            if (fresh_cta() == 1) prm.g->sums[~(cnt[1] / NUM_CTAS) & 1][tid] = 0.0f;
            __syncwarp();
            SMARK(1);
            mbar_wait_c<0>(sb + SM_BAR + BAR_W1 * 8);
            SMARK(2);
        }

        const int tid = fresh_tid(), lane = tid & 31, wg = fresh_warp() >> 2, w = fresh_warp() & 3;
        float acc[2][2];
        const int c = 8 * (lane >> 4) + (lane & 7), ck = 2 * w + ((lane >> 3) & 1);
        consume(acc, sb + SM_W1 + 2 * wg * 12288 + c * 128 + ((ck ^ (c & 7)) * 16), prm.ydesc,
                prm.w1desc + (((2 * wg + 1) * 12288 + 5 * 2048) >> 4), wg * SLOT_BYTES, make_duty(prm, wg, w), w, lane, prm);
        publish_fast(prm, acc, lds32(sb + SM_RED + RED_EPOCH * 4), wg, w, lane);
        MARK(0);
        bulk_wait_all();
        asm volatile("bar.arrive 11, 512;" ::: "memory");
        if (wg == 0) TS(3);
        asm volatile("setmaxnreg.inc.sync.aligned.u32 %0;" ::"n"(EVEN_REGS));
    }

    {
        MARK(1);
        if (fresh_warp() >= 12) prepare_w2<true>(prm, nullptr);

        if (fresh_cta() < NUM_CTAS ? pass2_tiles(pass2_setup(prm), prm, 0) : helper_tiles(pass2_setup(prm), prm, 0)) {
            const float* exact = exact_sums(prm);
            if (fresh_warp() >= 12) prepare_w2<false>(prm, exact);
            pass2_tiles(pass2_setup(prm), prm, 1);
        }
        bulk_wait_read<0>();
        MARK(13);
    }
}

}

extern "C" void kernel_launch(void* const* d_in, const int* in_sizes, int n_in, void* d_out, int out_size) {
    (void)in_sizes; (void)n_in; (void)out_size;
    typedef CUresult (*EncodeFn)(CUtensorMap*, CUtensorMapDataType, cuuint32_t, void*, const cuuint64_t*, const cuuint64_t*,
                                 const cuuint32_t*, const cuuint32_t*, CUtensorMapInterleave, CUtensorMapSwizzle,
                                 CUtensorMapL2promotion, CUtensorMapFloatOOBfill);
    void* fn = nullptr;
    cudaDriverEntryPointQueryResult status;
    cudaGetDriverEntryPoint("cuTensorMapEncodeTiled", &fn, cudaEnableDefault, &status);
    const EncodeFn encode = (EncodeFn)fn;
    const cuuint32_t ones[2] = {1, 1};

    Params p;
    {
        const cuuint64_t dims[2] = {EX, CH}, strides[1] = {EX * 2};
        const cuuint32_t box[2] = {64, CH};
        encode(&p.w1_map, CU_TENSOR_MAP_DATA_TYPE_BFLOAT16, 2, d_in[2], dims, strides, box, ones,
               CU_TENSOR_MAP_INTERLEAVE_NONE, CU_TENSOR_MAP_SWIZZLE_128B, CU_TENSOR_MAP_L2_PROMOTION_NONE,
               CU_TENSOR_MAP_FLOAT_OOB_FILL_NONE);
    }
    {
        const cuuint64_t dims[2] = {CH, EX}, strides[1] = {CH * 2};
        const cuuint32_t box[2] = {32, 192};
        encode(&p.w2_map, CU_TENSOR_MAP_DATA_TYPE_BFLOAT16, 2, d_in[3], dims, strides, box, ones,
               CU_TENSOR_MAP_INTERLEAVE_NONE, CU_TENSOR_MAP_SWIZZLE_64B, CU_TENSOR_MAP_L2_PROMOTION_NONE,
               CU_TENSOR_MAP_FLOAT_OOB_FILL_NONE);
    }
    p.x = (const __nv_bfloat16*)d_in[0];
    p.dw = (const __nv_bfloat16*)d_in[1];
    p.w1 = (const __nv_bfloat16*)d_in[2];
    p.gamma = (const __nv_bfloat16*)d_in[4];
    p.beta = (const __nv_bfloat16*)d_in[5];
    p.out = (__nv_bfloat16*)d_out;
    cudaGetSymbolAddress((void**)&p.g, g_scratch);
    p.w1desc = desc_lo(sb + SM_W1, 12288);
    p.w2desc = desc_lo(sb + SM_W2, 24576);
    p.helper_desc[0] = p.w1desc;
    p.helper_desc[1] = p.w2desc;
    p.ydesc = desc_lo(sb + SM_Y1, 16);
    p.ydesc64[0] = (0x40000040ull << 32) | p.ydesc;
    p.ydesc64[1] = (0x80000020ull << 32) | (p.ydesc + 512);
    for (int k = 0; k < 3; k++) p.sel[k] = (8ull << 32) | desc_lo(sb + SM_SEL + k * 128, k == 2 ? 128 : 0);
    constexpr int smem_bytes = SM_TOTAL;
    cudaFuncSetAttribute(convnext_kernel, cudaFuncAttributeMaxDynamicSharedMemorySize, smem_bytes);
    int device = 0, sms = 0;
    cudaGetDevice(&device);
    cudaDeviceGetAttribute(&sms, cudaDevAttrMultiProcessorCount, device);
    p.ctas = USE_HELPERS && sms >= NUM_CTAS + HELPERS ? NUM_CTAS + HELPERS : NUM_CTAS;
    convnext_kernel<<<p.ctas, 512, smem_bytes>>>(p);
}
```
